```python
import torch

def _softmax(x, axis=-1):
    return torch.softmax(x, dim=axis)

def _gelu(x):
    return torch.nn.functional.gelu(x, approximate='tanh')

def _silu(x):
    return torch.nn.functional.silu(x)

def _sigmoid(x):
    return torch.sigmoid(x)

def _layernorm(x, axis=-1, eps=1e-05):
    m = x.mean(dim=axis, keepdim=True)
    v = x.var(dim=axis, keepdim=True, unbiased=False)
    return (x - m) / torch.sqrt(v + eps)

def _scatter_add(tgt, idx, src, axis=0):
    return tgt.clone().index_add_(axis, idx, src)

def _segment_sum(src, seg, n):
    out = torch.zeros((n,) + src.shape[1:], dtype=src.dtype)
    return out.index_add_(0, seg, src)

def _pad(x, pw):
    flat = tuple((v for pair in reversed(pw) for v in pair))
    return torch.nn.functional.pad(x, flat)
kernel_name = 'interleave_layers__memory_aug_recurrent_mem_tr__linear_kernel_hedgehog__prompt'

def setup_inputs():

    _w = lambda a: (lambda t: t.to(torch.bfloat16) if t.is_floating_point() else t)(torch.as_tensor(a))

    def _A_setup():
        B, S, Dm = (1, 2048, 640)
        H, Dh = (32, 192)
        M, seg = (8, 32)
        seg = min(seg, S)
        S = S // seg * seg
        return {'x': _w((lambda *s: torch.randn(*s, dtype=torch.bfloat16) * 0.05)(B, S, Dm)), 'mem0': _w((lambda *s: torch.randn(*s, dtype=torch.bfloat16) * 0.8)(B, M, Dm)), 'Wq': _w((lambda *s: torch.randn(*s, dtype=torch.bfloat16) * 1.6)(Dm, H, Dh) * Dm ** (-0.5)), 'Wk': _w((lambda *s: torch.randn(*s, dtype=torch.bfloat16) * 1.6)(Dm, H, Dh) * Dm ** (-0.5)), 'Wv': _w((lambda *s: torch.randn(*s, dtype=torch.bfloat16) * 0.8)(Dm, H, Dh) * Dm ** (-0.5)), 'Wo': _w((lambda *s: torch.randn(*s, dtype=torch.bfloat16) * 0.8)(H, Dh, Dm) * (H * Dh) ** (-0.5)), 'seg_len': seg}
    _A_in = _A_setup()

    def _B_setup():
        B, S, D, H = (1, 2048, 640, 32)
        Dh = D // H
        return {'x': _w((lambda *s: torch.randn(*s, dtype=torch.bfloat16) * 0.05)(B, S, D)), 'wqkv': _w((lambda *s: torch.randn(*s, dtype=torch.bfloat16) * 0.4)(D, 3 * D)), 'w_phi': _w((lambda *s: torch.randn(*s, dtype=torch.bfloat16) * 0.4)(H, Dh, Dh) * Dh ** (-0.5)), 'wo': _w((lambda *s: torch.randn(*s, dtype=torch.bfloat16) * 0.05)(D, D))}
    _B_in = _B_setup()
    return {'A_x': _A_in['x'], 'A_mem0': _A_in['mem0'], 'A_Wq': _A_in['Wq'], 'A_Wk': _A_in['Wk'], 'A_Wv': _A_in['Wv'], 'A_Wo': _A_in['Wo'], 'A_seg_len': _A_in['seg_len'], 'B_x': _B_in['x'], 'B_wqkv': _B_in['wqkv'], 'B_w_phi': _B_in['w_phi'], 'B_wo': _B_in['wo']}

def reference(A_x, A_mem0, A_Wq, A_Wk, A_Wv, A_Wo, A_seg_len, B_x, B_wqkv, B_w_phi, B_wo):

    def _A_ref(x, mem0, Wq, Wk, Wv, Wo, seg_len):
        B, S, Dm = x.shape
        H, Dh = (Wq.shape[1], Wq.shape[2])
        M = mem0.shape[1]
        scale = Dh ** (-0.5)
        n_seg = S // seg_len
        L = M + seg_len
        idx = torch.arange(L)
        mask = (idx[:, None] < M) | (idx[:, None] >= idx[None, :])
        mem = mem0
        outs = []
        for s in range(n_seg):
            xs = x[:, s * seg_len:(s + 1) * seg_len, :].clone()
            h = torch.concatenate([mem, xs], axis=1)
            q = torch.einsum('btd,dhe->bhte', h, Wq)
            k = torch.einsum('btd,dhe->bhte', h, Wk)
            v = torch.einsum('btd,dhe->bhte', h, Wv)
            scores = torch.einsum('bhqe,bhke->bhqk', q, k) * scale
            scores = torch.where(mask[None, None], scores, -1000000000.0)
            p = _softmax(scores, axis=-1)
            o = torch.einsum('bhqk,bhke->bhqe', p, v)
            o = torch.einsum('bhte,hed->btd', o, Wo)
            mem = o[:, :M, :].clone()
            outs.append(o[:, M:, :])
        return torch.concatenate(outs, axis=1)

    def _B_ref(x, wqkv, w_phi, wo):
        B, S, D = x.shape
        H = 32
        Dh = D // H
        qkv = (lambda x, *d: x.permute(*d))((x @ wqkv).reshape(B, S, 3, H, Dh), 2, 0, 3, 1, 4)
        q, k, v = (qkv[0], qkv[1], qkv[2])
        pq = torch.einsum('bhsd,hdf->bhsf', q, w_phi)
        pk = torch.einsum('bhsd,hdf->bhsf', k, w_phi)
        phi_q = torch.concatenate([_softmax(pq, axis=-1), _softmax(-pq, axis=-1)], axis=-1)
        phi_k = torch.concatenate([_softmax(pk, axis=-1), _softmax(-pk, axis=-1)], axis=-1)
        kv = torch.einsum('bhsf,bhsd->bhfd', phi_k, v)
        z = torch.einsum('bhsf->bhf', phi_k)
        num = torch.einsum('bhqf,bhfd->bhqd', phi_q, kv)
        den = torch.einsum('bhqf,bhf->bhq', phi_q, z)[..., None] + 1e-06
        o = num / den
        return (lambda x, *d: x.permute(*d))(o, 0, 2, 1, 3).reshape(B, S, D) @ wo
    x = A_x
    x = x + _A_ref(_layernorm(x, axis=-1), A_mem0, A_Wq, A_Wk, A_Wv, A_Wo, A_seg_len)
    x = x + _B_ref(_layernorm(x, axis=-1), B_wqkv, B_w_phi, B_wo)
    x = x + _A_ref(_layernorm(x, axis=-1), A_mem0, A_Wq, A_Wk, A_Wv, A_Wo, A_seg_len)
    x = x + _B_ref(_layernorm(x, axis=-1), B_wqkv, B_w_phi, B_wo)
    return x
```

```cpp
#include <cuda_runtime.h>
#include <cuda.h>
#include <cuda_bf16.h>
#include <stdint.h>
#include <type_traits>

typedef __nv_bfloat16 bf16;

namespace cfg {
constexpr int S = 2048, DM = 640, H = 32, DH = 192, NSEG = 64, SEG = 32, NM = 8;
constexpr int HD = H * DH;
}

__device__ __forceinline__ uint32_t smem_u32(const void* p) { return (uint32_t)__cvta_generic_to_shared(p); }
__device__ __forceinline__ uint32_t mapa_u32(uint32_t a, uint32_t r) {
  uint32_t o; asm("mapa.shared::cluster.u32 %0, %1, %2;" : "=r"(o) : "r"(a), "r"(r)); return o;
}
__device__ __forceinline__ void mbar_init(uint32_t b, uint32_t c) {
  asm volatile("mbarrier.init.shared::cta.b64 [%0], %1;" :: "r"(b), "r"(c) : "memory");
}
__device__ __forceinline__ void mbar_expect_tx(uint32_t b, uint32_t bytes) {
  asm volatile("mbarrier.arrive.expect_tx.shared::cta.b64 _, [%0], %1;" :: "r"(b), "r"(bytes) : "memory");
}
__device__ __forceinline__ void mbar_arrive(uint32_t b) {
  asm volatile("mbarrier.arrive.shared::cta.b64 _, [%0];" :: "r"(b) : "memory");
}
__device__ __forceinline__ bool mbar_try(uint32_t b, uint32_t ph) {
  uint32_t p;
  asm volatile("{.reg .pred p; mbarrier.try_wait.parity.shared::cta.b64 p, [%1], %2; selp.u32 %0, 1, 0, p;}"
               : "=r"(p) : "r"(b), "r"(ph) : "memory");
  return p;
}
__device__ __forceinline__ bool mbar_try_cluster(uint32_t b, uint32_t ph) {
  uint32_t p;
  asm volatile("{.reg .pred p; mbarrier.try_wait.parity.acquire.cluster.shared::cta.b64 p, [%1], %2; selp.u32 %0, 1, 0, p;}"
               : "=r"(p) : "r"(b), "r"(ph) : "memory");
  return p;
}
#define SPIN_LIMIT (1 << 22)
__device__ __forceinline__ void mbar_wait(uint32_t b, uint32_t ph) {
  asm volatile("{\n.reg .pred p, q;\n.reg .u32 c;\nmov.u32 c, 0;\n"
               "W_%=:\nmbarrier.try_wait.parity.shared::cta.b64 p, [%0], %1;\n@p bra D_%=;\n"
               "add.u32 c, c, 1;\nsetp.lt.u32 q, c, %2;\n@q bra W_%=;\nD_%=:\n}"
               :: "r"(b), "r"(ph), "n"(SPIN_LIMIT) : "memory");
}
__device__ __forceinline__ void mbar_spin(uint32_t b, uint32_t ph) {
  asm volatile("{\n.reg .pred p, q;\n.reg .u32 c;\nmov.u32 c, 0;\n"
               "W_%=:\nmbarrier.test_wait.parity.shared::cta.b64 p, [%0], %1;\n@p bra D_%=;\n"
               "add.u32 c, c, 1;\nsetp.lt.u32 q, c, %2;\n@q bra W_%=;\nD_%=:\n}"
               :: "r"(b), "r"(ph), "n"(SPIN_LIMIT) : "memory");
}
#define PIN(x) asm volatile("" : "+r"(x))
__device__ __forceinline__ void mbar_wait_cluster(uint32_t b, uint32_t ph) {
  int s = 0;
  while (!mbar_try_cluster(b, ph)) { if (++s > SPIN_LIMIT) break; }
}
__device__ __forceinline__ void st_async_v2(uint32_t a, uint32_t x, uint32_t y, uint32_t mb) {
  asm volatile("st.async.weak.shared::cluster.mbarrier::complete_tx::bytes.v2.b32 [%0], {%1,%2}, [%3];"
               :: "r"(a), "r"(x), "r"(y), "r"(mb) : "memory");
}
__device__ __forceinline__ void st_async_v4(uint32_t a, uint32_t x, uint32_t y, uint32_t z, uint32_t w, uint32_t mb) {
  asm volatile("st.async.weak.shared::cluster.mbarrier::complete_tx::bytes.v4.b32 [%0], {%1,%2,%3,%4}, [%5];"
               :: "r"(a), "r"(x), "r"(y), "r"(z), "r"(w), "r"(mb) : "memory");
}
__device__ __forceinline__ void bulk_g2s(uint32_t dst, const void* src, uint32_t bytes, uint32_t mb) {
  asm volatile("cp.async.bulk.shared::cluster.global.mbarrier::complete_tx::bytes [%0], [%1], %2, [%3];"
               :: "r"(dst), "l"(src), "r"(bytes), "r"(mb) : "memory");
}
__device__ __forceinline__ void cp_async16(uint32_t dst, const void* src) {
  asm volatile("cp.async.cg.shared.global [%0], [%1], 16;" :: "r"(dst), "l"(src) : "memory");
}
__device__ __forceinline__ void cp_async_wait_all() { asm volatile("cp.async.wait_all;" ::: "memory"); }
__device__ __forceinline__ void fence_proxy_async() { asm volatile("fence.proxy.async.shared::cta;" ::: "memory"); }
__device__ __forceinline__ void bar_sync(int id, int n) { asm volatile("bar.sync %0, %1;" :: "r"(id), "r"(n) : "memory"); }
__device__ __forceinline__ void bar_arrive(int id, int n) { asm volatile("bar.arrive %0, %1;" :: "r"(id), "r"(n) : "memory"); }
__device__ __forceinline__ void cluster_sync_all() {
  asm volatile("barrier.cluster.arrive.release.aligned; barrier.cluster.wait.acquire.aligned;" ::: "memory");
}
__device__ __forceinline__ void ldsm_x4(uint32_t (&r)[4], uint32_t a) {
  asm volatile("ldmatrix.sync.aligned.m8n8.x4.shared.b16 {%0,%1,%2,%3}, [%4];"
               : "=r"(r[0]), "=r"(r[1]), "=r"(r[2]), "=r"(r[3]) : "r"(a) : "memory");
}
__device__ __forceinline__ void ldsm_x4_t(uint32_t (&r)[4], uint32_t a) {
  asm volatile("ldmatrix.sync.aligned.m8n8.x4.trans.shared.b16 {%0,%1,%2,%3}, [%4];"
               : "=r"(r[0]), "=r"(r[1]), "=r"(r[2]), "=r"(r[3]) : "r"(a) : "memory");
}
template <int IMM> __device__ __forceinline__ void ldsm_x4_i(uint32_t (&r)[4], uint32_t a) {
  asm volatile("ldmatrix.sync.aligned.m8n8.x4.shared.b16 {%0,%1,%2,%3}, [%4+%5];"
               : "=r"(r[0]), "=r"(r[1]), "=r"(r[2]), "=r"(r[3]) : "r"(a), "n"(IMM) : "memory");
}
template <int IMM> __device__ __forceinline__ void ldsm_x4_t_i(uint32_t (&r)[4], uint32_t a) {
  asm volatile("ldmatrix.sync.aligned.m8n8.x4.trans.shared.b16 {%0,%1,%2,%3}, [%4+%5];"
               : "=r"(r[0]), "=r"(r[1]), "=r"(r[2]), "=r"(r[3]) : "r"(a), "n"(IMM) : "memory");
}
template <int IMM> __device__ __forceinline__ uint4 lds128_i(uint32_t a) {
  uint4 v; asm volatile("ld.shared.v4.u32 {%0,%1,%2,%3}, [%4+%5];" : "=r"(v.x), "=r"(v.y), "=r"(v.z), "=r"(v.w) : "r"(a), "n"(IMM) : "memory"); return v;
}
template <int IMM> __device__ __forceinline__ uint2 lds64_i(uint32_t a) {
  uint2 v; asm volatile("ld.shared.v2.u32 {%0,%1}, [%2+%3];" : "=r"(v.x), "=r"(v.y) : "r"(a), "n"(IMM) : "memory"); return v;
}
template <int IMM> __device__ __forceinline__ void sts128_i(uint32_t a, uint32_t x, uint32_t y, uint32_t z, uint32_t w) {
  asm volatile("st.shared.v4.u32 [%0+%5], {%1,%2,%3,%4};" :: "r"(a), "r"(x), "r"(y), "r"(z), "r"(w), "n"(IMM) : "memory");
}
template <int IMM> __device__ __forceinline__ void sts64_i(uint32_t a, uint32_t x, uint32_t y) {
  asm volatile("st.shared.v2.u32 [%0+%3], {%1,%2};" :: "r"(a), "r"(x), "r"(y), "n"(IMM) : "memory");
}
template <int IMM> __device__ __forceinline__ void st_async_v2_i(uint32_t a, uint32_t x, uint32_t y, uint32_t mb) {
  asm volatile("st.async.weak.shared::cluster.mbarrier::complete_tx::bytes.v2.b32 [%0+%4], {%1,%2}, [%3];"
               :: "r"(a), "r"(x), "r"(y), "r"(mb), "n"(IMM) : "memory");
}
template <int IMM> __device__ __forceinline__ uint4 ld_relaxed_v4_i(const void* p) {
  uint4 v; asm volatile("ld.relaxed.gpu.global.v4.u32 {%0,%1,%2,%3}, [%4+%5];" : "=r"(v.x), "=r"(v.y), "=r"(v.z), "=r"(v.w) : "l"(p), "n"(IMM) : "memory"); return v;
}
template <int I, int N, class F> __device__ __forceinline__ void static_for(F&& f) {
  if constexpr (I < N) { f(std::integral_constant<int, I>{}); static_for<I + 1, N>(f); }
}
__device__ __forceinline__ uint32_t movm_t(uint32_t a) {
  uint32_t d; asm volatile("movmatrix.sync.aligned.m8n8.trans.b16 %0, %1;" : "=r"(d) : "r"(a)); return d;
}
__device__ __forceinline__ void mma16816(float (&d)[4], uint32_t a0, uint32_t a1, uint32_t a2, uint32_t a3, uint32_t b0, uint32_t b1) {
  asm volatile("mma.sync.aligned.m16n8k16.row.col.f32.bf16.bf16.f32 {%0,%1,%2,%3}, {%4,%5,%6,%7}, {%8,%9}, {%0,%1,%2,%3};"
               : "+f"(d[0]), "+f"(d[1]), "+f"(d[2]), "+f"(d[3]) : "r"(a0), "r"(a1), "r"(a2), "r"(a3), "r"(b0), "r"(b1));
}
__device__ __forceinline__ uint32_t pack_bf16(float lo, float hi) {
  uint32_t d; asm("cvt.rn.bf16x2.f32 %0, %1, %2;" : "=r"(d) : "f"(hi), "f"(lo)); return d;
}
__device__ __forceinline__ float bf_lo(uint32_t w) { return __uint_as_float(w << 16); }
__device__ __forceinline__ float bf_hi(uint32_t w) { return __uint_as_float(w & 0xffff0000u); }
__device__ __forceinline__ uint4 lds128(uint32_t a) {
  uint4 v; asm volatile("ld.shared.v4.u32 {%0,%1,%2,%3}, [%4];" : "=r"(v.x), "=r"(v.y), "=r"(v.z), "=r"(v.w) : "r"(a) : "memory"); return v;
}
__device__ __forceinline__ uint2 lds64(uint32_t a) {
  uint2 v; asm volatile("ld.shared.v2.u32 {%0,%1}, [%2];" : "=r"(v.x), "=r"(v.y) : "r"(a) : "memory"); return v;
}
__device__ __forceinline__ void sts128(uint32_t a, uint32_t x, uint32_t y, uint32_t z, uint32_t w) {
  asm volatile("st.shared.v4.u32 [%0], {%1,%2,%3,%4};" :: "r"(a), "r"(x), "r"(y), "r"(z), "r"(w) : "memory");
}
__device__ __forceinline__ void sts64(uint32_t a, uint32_t x, uint32_t y) {
  asm volatile("st.shared.v2.u32 [%0], {%1,%2};" :: "r"(a), "r"(x), "r"(y) : "memory");
}
__device__ __forceinline__ uint4 ld_relaxed_v4(const void* p) {
  uint4 v; asm volatile("ld.relaxed.gpu.global.v4.u32 {%0,%1,%2,%3}, [%4];" : "=r"(v.x), "=r"(v.y), "=r"(v.z), "=r"(v.w) : "l"(p) : "memory"); return v;
}
__device__ __forceinline__ uint32_t ld_relaxed_u32(const void* p) {
  uint32_t v; asm volatile("ld.relaxed.gpu.global.u32 %0, [%1];" : "=r"(v) : "l"(p) : "memory"); return v;
}
__device__ __forceinline__ void st_relaxed_v2(void* p, uint32_t a, uint32_t b) {
  asm volatile("st.relaxed.gpu.global.v2.u32 [%0], {%1,%2};" :: "l"(p), "r"(a), "r"(b) : "memory");
}
__device__ __forceinline__ void st_relaxed_u32(void* p, uint32_t v) {
  asm volatile("st.relaxed.gpu.global.u32 [%0], %1;" :: "l"(p), "r"(v) : "memory");
}
__device__ __forceinline__ uint32_t clk32() { uint32_t c; asm volatile("mov.u32 %0, %%clock;" : "=r"(c) :: "memory"); return c; }
__device__ __forceinline__ uint32_t clkdep(uint32_t v) {
  uint32_t c; asm volatile("{.reg .pred p; setp.eq.u32 p, %1, 0xdeadbeef; @p trap; mov.u32 %0, %%clock;}" : "=r"(c) : "r"(v) : "memory"); return c;
}
__device__ __forceinline__ void wgmma_fence() { asm volatile("wgmma.fence.sync.aligned;" ::: "memory"); }
__device__ __forceinline__ void wgmma_commit() { asm volatile("wgmma.commit_group.sync.aligned;" ::: "memory"); }
template <int N> __device__ __forceinline__ void wgmma_wait() { asm volatile("wgmma.wait_group.sync.aligned %0;" :: "n"(N) : "memory"); }
__device__ __forceinline__ void wgmma_n8_ss_ta(float (&d)[4], uint64_t da, uint64_t db, int acc) {
  asm volatile("{\n.reg .pred p;\nsetp.ne.b32 p, %6, 0;\n"
               "wgmma.mma_async.sync.aligned.m64n8k16.f32.bf16.bf16 {%0,%1,%2,%3}, %4, %5, p, 1, 1, 1, 0;\n}\n"
               : "+f"(d[0]), "+f"(d[1]), "+f"(d[2]), "+f"(d[3]) : "l"(da), "l"(db), "r"(acc));
}
__device__ __forceinline__ uint64_t make_desc(uint32_t saddr, uint32_t lbo_bytes, uint32_t sbo_bytes, uint32_t swz) {
  return (uint64_t)((saddr & 0x3FFFF) >> 4) | ((uint64_t)(lbo_bytes >> 4) << 16) | ((uint64_t)(sbo_bytes >> 4) << 32) | ((uint64_t)swz << 62);
}

__device__ __forceinline__ void tma_load_2d(uint32_t dst, const CUtensorMap* tm, int c0, int c1, uint32_t mb) {
  asm volatile("cp.async.bulk.tensor.2d.shared::cluster.global.mbarrier::complete_tx::bytes [%0], [%1, {%3, %4}], [%2];"
               :: "r"(dst), "l"(tm), "r"(mb), "r"(c0), "r"(c1) : "memory");
}
__device__ __forceinline__ void bulk_s2g(void* dst, uint32_t src, uint32_t bytes) {
  asm volatile("cp.async.bulk.global.shared::cta.bulk_group [%0], [%1], %2;" :: "l"(dst), "r"(src), "r"(bytes) : "memory");
}
__device__ __forceinline__ uint64_t policy_evict_first() {
  uint64_t p; asm volatile("createpolicy.fractional.L2::evict_first.b64 %0, 1.0;" : "=l"(p)); return p;
}
__device__ __forceinline__ void bulk_s2g_hint(void* dst, uint32_t src, uint32_t bytes, uint64_t pol) {
  asm volatile("cp.async.bulk.global.shared::cta.bulk_group.L2::cache_hint [%0], [%1], %2, %3;" :: "l"(dst), "r"(src), "r"(bytes), "l"(pol) : "memory");
}
__device__ __forceinline__ void bulk_commit() { asm volatile("cp.async.bulk.commit_group;" ::: "memory"); }
template <int N> __device__ __forceinline__ void bulk_wait_read() { asm volatile("cp.async.bulk.wait_group.read %0;" :: "n"(N) : "memory"); }
template <int N> __device__ __forceinline__ void bulk_wait() { asm volatile("cp.async.bulk.wait_group %0;" :: "n"(N) : "memory"); }
__device__ __forceinline__ void stsm_x4(uint32_t a, uint32_t r0, uint32_t r1, uint32_t r2, uint32_t r3) {
  asm volatile("stmatrix.sync.aligned.m8n8.x4.shared.b16 [%0], {%1,%2,%3,%4};" :: "r"(a), "r"(r0), "r"(r1), "r"(r2), "r"(r3) : "memory");
}
__device__ __forceinline__ void stsm_x2(uint32_t a, uint32_t r0, uint32_t r1) {
  asm volatile("stmatrix.sync.aligned.m8n8.x2.shared.b16 [%0], {%1,%2};" :: "r"(a), "r"(r0), "r"(r1) : "memory");
}
__device__ __forceinline__ void ldsm_x2(uint32_t (&r)[2], uint32_t a) {
  asm volatile("ldmatrix.sync.aligned.m8n8.x2.shared.b16 {%0,%1}, [%2];" : "=r"(r[0]), "=r"(r[1]) : "r"(a) : "memory");
}
__device__ __forceinline__ void ldsm_x2_t(uint32_t (&r)[2], uint32_t a) {
  asm volatile("ldmatrix.sync.aligned.m8n8.x2.trans.shared.b16 {%0,%1}, [%2];" : "=r"(r[0]), "=r"(r[1]) : "r"(a) : "memory");
}
__device__ __forceinline__ float bf16r(float x) { return __uint_as_float(pack_bf16(0.f, x) & 0xffff0000u); }
__device__ __forceinline__ void bf16r2(float& a, float& b) { const uint32_t w = pack_bf16(a, b); a = bf_lo(w); b = bf_hi(w); }
__device__ __forceinline__ float rcpf(float x) { float r; asm("rcp.approx.ftz.f32 %0, %1;" : "=f"(r) : "f"(x)); return r; }
__device__ __forceinline__ float ex2f(float x) { float e; asm("ex2.approx.ftz.f32 %0, %1;" : "=f"(e) : "f"(x)); return e; }
__device__ __forceinline__ void prefetch_tmap(const CUtensorMap* tm) { asm volatile("prefetch.tensormap [%0];" :: "l"(tm) : "memory"); }

#define TL_ACC(idx, t0)
#define TL_NOW() 0ull
#define TL2(idx)
#define TL_BEGIN(id)
#define TL_END(id)
template <int TA, int TB> __device__ __forceinline__ void wgmma_n192(float (&d)[96], uint64_t da, uint64_t db, int acc) {
  asm volatile("{\n.reg .pred p;\nsetp.ne.b32 p, %98, 0;\n"
    "wgmma.mma_async.sync.aligned.m64n192k16.f32.bf16.bf16 {%0, %1, %2, %3, %4, %5, %6, %7, %8, %9, %10, %11, %12, %13, %14, %15, %16, %17, %18, %19, %20, %21, %22, %23, %24, %25, %26, %27, %28, %29, %30, %31, %32, %33, %34, %35, %36, %37, %38, %39, %40, %41, %42, %43, %44, %45, %46, %47, %48, %49, %50, %51, %52, %53, %54, %55, %56, %57, %58, %59, %60, %61, %62, %63, %64, %65, %66, %67, %68, %69, %70, %71, %72, %73, %74, %75, %76, %77, %78, %79, %80, %81, %82, %83, %84, %85, %86, %87, %88, %89, %90, %91, %92, %93, %94, %95}, %96, %97, p, 1, 1, %99, %100;\n}\n"
    : "+f"(d[0]), "+f"(d[1]), "+f"(d[2]), "+f"(d[3]), "+f"(d[4]), "+f"(d[5]), "+f"(d[6]), "+f"(d[7]), "+f"(d[8]), "+f"(d[9]), "+f"(d[10]), "+f"(d[11]), "+f"(d[12]), "+f"(d[13]), "+f"(d[14]), "+f"(d[15]), "+f"(d[16]), "+f"(d[17]), "+f"(d[18]), "+f"(d[19]), "+f"(d[20]), "+f"(d[21]), "+f"(d[22]), "+f"(d[23]), "+f"(d[24]), "+f"(d[25]), "+f"(d[26]), "+f"(d[27]), "+f"(d[28]), "+f"(d[29]), "+f"(d[30]), "+f"(d[31]), "+f"(d[32]), "+f"(d[33]), "+f"(d[34]), "+f"(d[35]), "+f"(d[36]), "+f"(d[37]), "+f"(d[38]), "+f"(d[39]), "+f"(d[40]), "+f"(d[41]), "+f"(d[42]), "+f"(d[43]), "+f"(d[44]), "+f"(d[45]), "+f"(d[46]), "+f"(d[47]), "+f"(d[48]), "+f"(d[49]), "+f"(d[50]), "+f"(d[51]), "+f"(d[52]), "+f"(d[53]), "+f"(d[54]), "+f"(d[55]), "+f"(d[56]), "+f"(d[57]), "+f"(d[58]), "+f"(d[59]), "+f"(d[60]), "+f"(d[61]), "+f"(d[62]), "+f"(d[63]), "+f"(d[64]), "+f"(d[65]), "+f"(d[66]), "+f"(d[67]), "+f"(d[68]), "+f"(d[69]), "+f"(d[70]), "+f"(d[71]), "+f"(d[72]), "+f"(d[73]), "+f"(d[74]), "+f"(d[75]), "+f"(d[76]), "+f"(d[77]), "+f"(d[78]), "+f"(d[79]), "+f"(d[80]), "+f"(d[81]), "+f"(d[82]), "+f"(d[83]), "+f"(d[84]), "+f"(d[85]), "+f"(d[86]), "+f"(d[87]), "+f"(d[88]), "+f"(d[89]), "+f"(d[90]), "+f"(d[91]), "+f"(d[92]), "+f"(d[93]), "+f"(d[94]), "+f"(d[95])
    : "l"(da), "l"(db), "r"(acc), "n"(TA), "n"(TB));
}

template <int TA, int TB> __device__ __forceinline__ void wgmma_n256(float (&d)[128], uint64_t da, uint64_t db, int acc) {
  asm volatile("{\n.reg .pred p;\nsetp.ne.b32 p, %130, 0;\n"
    "wgmma.mma_async.sync.aligned.m64n256k16.f32.bf16.bf16 {%0, %1, %2, %3, %4, %5, %6, %7, %8, %9, %10, %11, %12, %13, %14, %15, %16, %17, %18, %19, %20, %21, %22, %23, %24, %25, %26, %27, %28, %29, %30, %31, %32, %33, %34, %35, %36, %37, %38, %39, %40, %41, %42, %43, %44, %45, %46, %47, %48, %49, %50, %51, %52, %53, %54, %55, %56, %57, %58, %59, %60, %61, %62, %63, %64, %65, %66, %67, %68, %69, %70, %71, %72, %73, %74, %75, %76, %77, %78, %79, %80, %81, %82, %83, %84, %85, %86, %87, %88, %89, %90, %91, %92, %93, %94, %95, %96, %97, %98, %99, %100, %101, %102, %103, %104, %105, %106, %107, %108, %109, %110, %111, %112, %113, %114, %115, %116, %117, %118, %119, %120, %121, %122, %123, %124, %125, %126, %127}, %128, %129, p, 1, 1, %131, %132;\n}\n"
    : "+f"(d[0]), "+f"(d[1]), "+f"(d[2]), "+f"(d[3]), "+f"(d[4]), "+f"(d[5]), "+f"(d[6]), "+f"(d[7]), "+f"(d[8]), "+f"(d[9]), "+f"(d[10]), "+f"(d[11]), "+f"(d[12]), "+f"(d[13]), "+f"(d[14]), "+f"(d[15]), "+f"(d[16]), "+f"(d[17]), "+f"(d[18]), "+f"(d[19]), "+f"(d[20]), "+f"(d[21]), "+f"(d[22]), "+f"(d[23]), "+f"(d[24]), "+f"(d[25]), "+f"(d[26]), "+f"(d[27]), "+f"(d[28]), "+f"(d[29]), "+f"(d[30]), "+f"(d[31]), "+f"(d[32]), "+f"(d[33]), "+f"(d[34]), "+f"(d[35]), "+f"(d[36]), "+f"(d[37]), "+f"(d[38]), "+f"(d[39]), "+f"(d[40]), "+f"(d[41]), "+f"(d[42]), "+f"(d[43]), "+f"(d[44]), "+f"(d[45]), "+f"(d[46]), "+f"(d[47]), "+f"(d[48]), "+f"(d[49]), "+f"(d[50]), "+f"(d[51]), "+f"(d[52]), "+f"(d[53]), "+f"(d[54]), "+f"(d[55]), "+f"(d[56]), "+f"(d[57]), "+f"(d[58]), "+f"(d[59]), "+f"(d[60]), "+f"(d[61]), "+f"(d[62]), "+f"(d[63]), "+f"(d[64]), "+f"(d[65]), "+f"(d[66]), "+f"(d[67]), "+f"(d[68]), "+f"(d[69]), "+f"(d[70]), "+f"(d[71]), "+f"(d[72]), "+f"(d[73]), "+f"(d[74]), "+f"(d[75]), "+f"(d[76]), "+f"(d[77]), "+f"(d[78]), "+f"(d[79]), "+f"(d[80]), "+f"(d[81]), "+f"(d[82]), "+f"(d[83]), "+f"(d[84]), "+f"(d[85]), "+f"(d[86]), "+f"(d[87]), "+f"(d[88]), "+f"(d[89]), "+f"(d[90]), "+f"(d[91]), "+f"(d[92]), "+f"(d[93]), "+f"(d[94]), "+f"(d[95]), "+f"(d[96]), "+f"(d[97]), "+f"(d[98]), "+f"(d[99]), "+f"(d[100]), "+f"(d[101]), "+f"(d[102]), "+f"(d[103]), "+f"(d[104]), "+f"(d[105]), "+f"(d[106]), "+f"(d[107]), "+f"(d[108]), "+f"(d[109]), "+f"(d[110]), "+f"(d[111]), "+f"(d[112]), "+f"(d[113]), "+f"(d[114]), "+f"(d[115]), "+f"(d[116]), "+f"(d[117]), "+f"(d[118]), "+f"(d[119]), "+f"(d[120]), "+f"(d[121]), "+f"(d[122]), "+f"(d[123]), "+f"(d[124]), "+f"(d[125]), "+f"(d[126]), "+f"(d[127])
    : "l"(da), "l"(db), "r"(acc), "n"(TA), "n"(TB));
}

template <int TA, int TB> __device__ __forceinline__ void wgmma_n64(float (&d)[32], uint64_t da, uint64_t db, int acc) {
  asm volatile("{\n.reg .pred p;\nsetp.ne.b32 p, %34, 0;\n"
    "wgmma.mma_async.sync.aligned.m64n64k16.f32.bf16.bf16 {%0, %1, %2, %3, %4, %5, %6, %7, %8, %9, %10, %11, %12, %13, %14, %15, %16, %17, %18, %19, %20, %21, %22, %23, %24, %25, %26, %27, %28, %29, %30, %31}, %32, %33, p, 1, 1, %35, %36;\n}\n"
    : "+f"(d[0]), "+f"(d[1]), "+f"(d[2]), "+f"(d[3]), "+f"(d[4]), "+f"(d[5]), "+f"(d[6]), "+f"(d[7]), "+f"(d[8]), "+f"(d[9]), "+f"(d[10]), "+f"(d[11]), "+f"(d[12]), "+f"(d[13]), "+f"(d[14]), "+f"(d[15]), "+f"(d[16]), "+f"(d[17]), "+f"(d[18]), "+f"(d[19]), "+f"(d[20]), "+f"(d[21]), "+f"(d[22]), "+f"(d[23]), "+f"(d[24]), "+f"(d[25]), "+f"(d[26]), "+f"(d[27]), "+f"(d[28]), "+f"(d[29]), "+f"(d[30]), "+f"(d[31])
    : "l"(da), "l"(db), "r"(acc), "n"(TA), "n"(TB));
}

template <int TA, int TB> __device__ __forceinline__ void wgmma_n80(float (&d)[40], uint64_t da, uint64_t db, int acc) {
  asm volatile("{\n.reg .pred p;\nsetp.ne.b32 p, %42, 0;\n"
    "wgmma.mma_async.sync.aligned.m64n80k16.f32.bf16.bf16 {%0, %1, %2, %3, %4, %5, %6, %7, %8, %9, %10, %11, %12, %13, %14, %15, %16, %17, %18, %19, %20, %21, %22, %23, %24, %25, %26, %27, %28, %29, %30, %31, %32, %33, %34, %35, %36, %37, %38, %39}, %40, %41, p, 1, 1, %43, %44;\n}\n"
    : "+f"(d[0]), "+f"(d[1]), "+f"(d[2]), "+f"(d[3]), "+f"(d[4]), "+f"(d[5]), "+f"(d[6]), "+f"(d[7]), "+f"(d[8]), "+f"(d[9]), "+f"(d[10]), "+f"(d[11]), "+f"(d[12]), "+f"(d[13]), "+f"(d[14]), "+f"(d[15]), "+f"(d[16]), "+f"(d[17]), "+f"(d[18]), "+f"(d[19]), "+f"(d[20]), "+f"(d[21]), "+f"(d[22]), "+f"(d[23]), "+f"(d[24]), "+f"(d[25]), "+f"(d[26]), "+f"(d[27]), "+f"(d[28]), "+f"(d[29]), "+f"(d[30]), "+f"(d[31]), "+f"(d[32]), "+f"(d[33]), "+f"(d[34]), "+f"(d[35]), "+f"(d[36]), "+f"(d[37]), "+f"(d[38]), "+f"(d[39])
    : "l"(da), "l"(db), "r"(acc), "n"(TA), "n"(TB));
}

template <int TA, int TB> __device__ __forceinline__ void wgmma_n144(float (&d)[72], uint64_t da, uint64_t db, int acc) {
  asm volatile("{\n.reg .pred p;\nsetp.ne.b32 p, %74, 0;\n"
    "wgmma.mma_async.sync.aligned.m64n144k16.f32.bf16.bf16 {%0, %1, %2, %3, %4, %5, %6, %7, %8, %9, %10, %11, %12, %13, %14, %15, %16, %17, %18, %19, %20, %21, %22, %23, %24, %25, %26, %27, %28, %29, %30, %31, %32, %33, %34, %35, %36, %37, %38, %39, %40, %41, %42, %43, %44, %45, %46, %47, %48, %49, %50, %51, %52, %53, %54, %55, %56, %57, %58, %59, %60, %61, %62, %63, %64, %65, %66, %67, %68, %69, %70, %71}, %72, %73, p, 1, 1, %75, %76;\n}\n"
    : "+f"(d[0]), "+f"(d[1]), "+f"(d[2]), "+f"(d[3]), "+f"(d[4]), "+f"(d[5]), "+f"(d[6]), "+f"(d[7]), "+f"(d[8]), "+f"(d[9]), "+f"(d[10]), "+f"(d[11]), "+f"(d[12]), "+f"(d[13]), "+f"(d[14]), "+f"(d[15]), "+f"(d[16]), "+f"(d[17]), "+f"(d[18]), "+f"(d[19]), "+f"(d[20]), "+f"(d[21]), "+f"(d[22]), "+f"(d[23]), "+f"(d[24]), "+f"(d[25]), "+f"(d[26]), "+f"(d[27]), "+f"(d[28]), "+f"(d[29]), "+f"(d[30]), "+f"(d[31]), "+f"(d[32]), "+f"(d[33]), "+f"(d[34]), "+f"(d[35]), "+f"(d[36]), "+f"(d[37]), "+f"(d[38]), "+f"(d[39]), "+f"(d[40]), "+f"(d[41]), "+f"(d[42]), "+f"(d[43]), "+f"(d[44]), "+f"(d[45]), "+f"(d[46]), "+f"(d[47]), "+f"(d[48]), "+f"(d[49]), "+f"(d[50]), "+f"(d[51]), "+f"(d[52]), "+f"(d[53]), "+f"(d[54]), "+f"(d[55]), "+f"(d[56]), "+f"(d[57]), "+f"(d[58]), "+f"(d[59]), "+f"(d[60]), "+f"(d[61]), "+f"(d[62]), "+f"(d[63]), "+f"(d[64]), "+f"(d[65]), "+f"(d[66]), "+f"(d[67]), "+f"(d[68]), "+f"(d[69]), "+f"(d[70]), "+f"(d[71])
    : "l"(da), "l"(db), "r"(acc), "n"(TA), "n"(TB));
}

template <int TA, int TB> __device__ __forceinline__ void wgmma_n128(float (&d)[64], uint64_t da, uint64_t db, int acc) {
  asm volatile("{\n.reg .pred p;\nsetp.ne.b32 p, %66, 0;\n"
    "wgmma.mma_async.sync.aligned.m64n128k16.f32.bf16.bf16 {%0, %1, %2, %3, %4, %5, %6, %7, %8, %9, %10, %11, %12, %13, %14, %15, %16, %17, %18, %19, %20, %21, %22, %23, %24, %25, %26, %27, %28, %29, %30, %31, %32, %33, %34, %35, %36, %37, %38, %39, %40, %41, %42, %43, %44, %45, %46, %47, %48, %49, %50, %51, %52, %53, %54, %55, %56, %57, %58, %59, %60, %61, %62, %63}, %64, %65, p, 1, 1, %67, %68;\n}\n"
    : "+f"(d[0]), "+f"(d[1]), "+f"(d[2]), "+f"(d[3]), "+f"(d[4]), "+f"(d[5]), "+f"(d[6]), "+f"(d[7]), "+f"(d[8]), "+f"(d[9]), "+f"(d[10]), "+f"(d[11]), "+f"(d[12]), "+f"(d[13]), "+f"(d[14]), "+f"(d[15]), "+f"(d[16]), "+f"(d[17]), "+f"(d[18]), "+f"(d[19]), "+f"(d[20]), "+f"(d[21]), "+f"(d[22]), "+f"(d[23]), "+f"(d[24]), "+f"(d[25]), "+f"(d[26]), "+f"(d[27]), "+f"(d[28]), "+f"(d[29]), "+f"(d[30]), "+f"(d[31]), "+f"(d[32]), "+f"(d[33]), "+f"(d[34]), "+f"(d[35]), "+f"(d[36]), "+f"(d[37]), "+f"(d[38]), "+f"(d[39]), "+f"(d[40]), "+f"(d[41]), "+f"(d[42]), "+f"(d[43]), "+f"(d[44]), "+f"(d[45]), "+f"(d[46]), "+f"(d[47]), "+f"(d[48]), "+f"(d[49]), "+f"(d[50]), "+f"(d[51]), "+f"(d[52]), "+f"(d[53]), "+f"(d[54]), "+f"(d[55]), "+f"(d[56]), "+f"(d[57]), "+f"(d[58]), "+f"(d[59]), "+f"(d[60]), "+f"(d[61]), "+f"(d[62]), "+f"(d[63])
    : "l"(da), "l"(db), "r"(acc), "n"(TA), "n"(TB));
}

template <int OFF16, int ACC> __device__ __forceinline__ void wgmma_rs_n32(float (&d)[16], uint32_t a0, uint32_t a1, uint32_t a2, uint32_t a3, uint32_t dlo) {
  asm volatile("{\n.reg .pred p;\n.reg .b32 t;\n.reg .b64 db;\nsetp.ne.b32 p, %22, 0;\nadd.u32 t, %20, %21;\nmov.b64 db, {t, 0x40000040};\n"
    "wgmma.mma_async.sync.aligned.m64n32k16.f32.bf16.bf16 {%0, %1, %2, %3, %4, %5, %6, %7, %8, %9, %10, %11, %12, %13, %14, %15}, {%16, %17, %18, %19}, db, p, 1, 1, 0;\n}\n"
    : "+f"(d[0]), "+f"(d[1]), "+f"(d[2]), "+f"(d[3]), "+f"(d[4]), "+f"(d[5]), "+f"(d[6]), "+f"(d[7]), "+f"(d[8]), "+f"(d[9]), "+f"(d[10]), "+f"(d[11]), "+f"(d[12]), "+f"(d[13]), "+f"(d[14]), "+f"(d[15])
    : "r"(a0), "r"(a1), "r"(a2), "r"(a3), "r"(dlo), "n"(OFF16), "n"(ACC));
}

constexpr uint32_t AR_ACC = 0;
constexpr uint32_t AR_TAB = 0x100000;
constexpr uint32_t AR_PROG = 0x101000;
constexpr uint32_t AR_CNT = 0x102000;
constexpr uint32_t AR_QUEUE = 0x103000;
constexpr uint32_t AR_SIZE = 0x104000;

struct ChainArgs {
  const bf16 *Wo, *mem0;
  const void* xh;
  bf16 *kx, *vx;
  bf16 *km, *vm;
  unsigned char* arena;
  uint32_t* dbg;
  int tl;
};

namespace ch {
constexpr int OFF_WQ = 0;
constexpr int OFF_X = 81920;
constexpr int OFF_KX = OFF_X + 40960;
constexpr int OFF_KM = OFF_KX + 4096, OFF_VM = OFF_KM + 1024;
constexpr int OFF_MEM = OFF_VM + 1024;
constexpr int OFF_WO = OFF_MEM + 10240;
constexpr int WOK = 8 * 896;
constexpr int OFF_VX = OFF_WO + 11 * WOK;
constexpr int OFF_O = OFF_WO + 86016;
constexpr int OFF_Q = OFF_O + 1024;
constexpr int OFF_S = OFF_O + 3072;
constexpr int OFF_SR = OFF_S + 1280;
constexpr int OFF_BAR = OFF_SR + 1536;
constexpr int SMEM = OFF_BAR + 128 + 1152;
static_assert(SMEM <= 232448, "smem");
constexpr int MB_S = OFF_BAR, MB_O = OFF_BAR + 8, MB_X = OFF_BAR + 16, MB_K = OFF_BAR + 24, MB_V = OFF_BAR + 32, MB_Q = OFF_BAR + 40, MB_R = OFF_BAR + 48;
constexpr int SC_IN = OFF_BAR + 64;
constexpr int SC_MX = OFF_S;
constexpr int SC_W = OFF_BAR + 96;
constexpr int WOS = 464;
enum { B_MEM0 = 1, B_QK, B_SL, B_V, B_O, B_RED, B_X, B_C, B_H, B_MEM1, B_A, B_G };
#define NQ1 6
#define NQ0 4
#define NP0 4
#define NWO 5
#define NWP 4
#define NB0 2
#define BBS 100
#define VSYNC 0
#define XPOS 0
#define XPD 300
#define WOF 0
#define XBYTES 36864
#define NRT 7
#define NRF 2
#define NPM0 2
#define NPM1 2
#define RSYNC 1
#define PFK 1
#define PA0 7
#define PA1 0
#define PB0 7
#define PB1 5
#define PQE 0
#define XT 30
constexpr int NR = NQ1 > NQ0 ? NQ1 : NQ0;
}

#define CHAIN_TIMING 0
#define TS(i)
#define TSV(i, v)
#define TS_SETUP()
#define POLL_DELAY 500
#define XN 40
#define PF0 8
#define PFS 3
#define XDELAY 0
#define NOKM 0
#define PUB_REL 1
template <int V> using IC = std::integral_constant<int, V>;
__device__ __forceinline__ uint32_t clk_v() { uint64_t c; asm volatile("mov.u64 %0, %%clock64;" : "=l"(c) :: "memory"); return (uint32_t)c; }
__device__ __forceinline__ int fresh(int x) { int y; asm volatile("shfl.sync.bfly.b32 %0, %1, 0, 0x1f, 0xffffffff;" : "=r"(y) : "r"(x)); return y; }
#define SFENCE2(x, d) asm volatile("{\n.reg .pred p;\nsetp.eq.u32 p, %0, 0x7fffffff;\n@p st.shared.u32 [%0], %1;\n}" :: "r"(x), "r"(d) : "memory")
#define SFENCE(x) asm volatile("{\n.reg .pred p;\nsetp.eq.u32 p, %0, 0x7fffffff;\n@p st.shared.u32 [%0], %0;\n}" :: "r"(x) : "memory")
template <int I> __device__ __forceinline__ void bbfence(uint32_t x) {
  asm volatile("{\n.reg .pred p;\nsetp.eq.u32 p, %0, %1;\nL_%=:\n@p st.volatile.shared.u32 [%0], %0;\n@p bra.uni L_%=;\n}" :: "r"(x), "n"(4 * I) : "memory");
}
__device__ __forceinline__ float uniform_f(float x) { return __uint_as_float(__reduce_max_sync(0xffffffffu, __float_as_uint(x))); }

__device__ __forceinline__ void mma16816h(float (&d)[4], const uint32_t (&a)[4], uint32_t b0, uint32_t b1) {
  asm volatile("mma.sync.aligned.m16n8k16.row.col.f32.f16.f16.f32 {%0,%1,%2,%3}, {%4,%5,%6,%7}, {%8,%9}, {%0,%1,%2,%3};"
               : "+f"(d[0]), "+f"(d[1]), "+f"(d[2]), "+f"(d[3]) : "r"(a[0]), "r"(a[1]), "r"(a[2]), "r"(a[3]), "r"(b0), "r"(b1));
}
__device__ __forceinline__ void mma1688(float (&d)[4], uint32_t a0, uint32_t a1, uint32_t b0) {
  asm volatile("mma.sync.aligned.m16n8k8.row.col.f32.bf16.bf16.f32 {%0,%1,%2,%3}, {%4,%5}, {%6}, {%0,%1,%2,%3};"
               : "+f"(d[0]), "+f"(d[1]), "+f"(d[2]), "+f"(d[3]) : "r"(a0), "r"(a1), "r"(b0));
}
template <int OFF16, int ACC> __device__ __forceinline__ void wgmma_rs32h(float (&d)[16], const uint32_t (&a)[4], uint32_t dlo) {
  asm volatile("{\n.reg .pred p;\n.reg .b32 t;\n.reg .b64 db;\nsetp.ne.b32 p, %22, 0;\nadd.u32 t, %20, %21;\nmov.b64 db, {t, 0x40000040};\n"
    "wgmma.mma_async.sync.aligned.m64n32k16.f32.f16.f16 {%0,%1,%2,%3,%4,%5,%6,%7,%8,%9,%10,%11,%12,%13,%14,%15}, {%16,%17,%18,%19}, db, p, 1, 1, 0;\n}\n"
    : "+f"(d[0]), "+f"(d[1]), "+f"(d[2]), "+f"(d[3]), "+f"(d[4]), "+f"(d[5]), "+f"(d[6]), "+f"(d[7]), "+f"(d[8]), "+f"(d[9]), "+f"(d[10]), "+f"(d[11]),
      "+f"(d[12]), "+f"(d[13]), "+f"(d[14]), "+f"(d[15])
    : "r"(a[0]), "r"(a[1]), "r"(a[2]), "r"(a[3]), "r"(dlo), "n"(OFF16), "n"(ACC));
}
template <int IMM> __device__ __forceinline__ void stsm_x4_t_i(uint32_t a, uint32_t r0, uint32_t r1, uint32_t r2, uint32_t r3) {
  asm volatile("stmatrix.sync.aligned.m8n8.x4.trans.shared.b16 [%0+%5], {%1,%2,%3,%4};" :: "r"(a), "r"(r0), "r"(r1), "r"(r2), "r"(r3), "n"(IMM) : "memory");
}
template <int IMM> __device__ __forceinline__ void stsm_x2_t_i(uint32_t a, uint32_t r0, uint32_t r1) {
  asm volatile("stmatrix.sync.aligned.m8n8.x2.trans.shared.b16 [%0+%3], {%1,%2};" :: "r"(a), "r"(r0), "r"(r1), "n"(IMM) : "memory");
}
template <int IMM> __device__ __forceinline__ void st_async_b32_i(uint32_t a, uint32_t x, uint32_t mb) {
  asm volatile("st.async.weak.shared::cluster.mbarrier::complete_tx::bytes.b32 [%0+%3], %1, [%2];" :: "r"(a), "r"(x), "r"(mb), "n"(IMM) : "memory");
}
template <int IMM> __device__ __forceinline__ void ld_relaxed_v4_if(uint4& v, const void* p, uint32_t c) {
  asm volatile("{\n.reg .pred p;\nsetp.ne.u32 p, %6, 0;\n@p ld.relaxed.gpu.global.v4.u32 {%0,%1,%2,%3}, [%4+%5];\n}"
               : "+r"(v.x), "+r"(v.y), "+r"(v.z), "+r"(v.w) : "l"(p), "n"(IMM), "r"(c) : "memory");
}
template <int IMM> __device__ __forceinline__ uint32_t lds32_i(uint32_t a) {
  uint32_t v; asm volatile("ld.shared.u32 %0, [%1+%2];" : "=r"(v) : "r"(a), "n"(IMM) : "memory"); return v;
}
__device__ __forceinline__ void sts32(uint32_t a, uint32_t v) { asm volatile("st.shared.u32 [%0], %1;" :: "r"(a), "r"(v) : "memory"); }
__device__ __forceinline__ uint32_t pack_f16(float lo, float hi) {
  uint32_t d; asm("cvt.rn.f16x2.f32 %0, %1, %2;" : "=r"(d) : "f"(hi), "f"(lo)); return d;
}
__device__ __forceinline__ uint32_t amax_bf2(uint32_t a, uint32_t b) { uint32_t d; asm("max.xorsign.abs.bf16x2 %0, %1, %2;" : "=r"(d) : "r"(a), "r"(b)); return d; }
__device__ __forceinline__ uint32_t amax_h2(uint32_t a, uint32_t b) { uint32_t d; asm("max.xorsign.abs.f16x2 %0, %1, %2;" : "=r"(d) : "r"(a), "r"(b)); return d; }
__device__ __forceinline__ uint32_t amax_fold(uint32_t m) { return __reduce_max_sync(0xffffffffu, max(m & 0x7fffu, (m >> 16) & 0x7fffu)); }
__device__ __forceinline__ int wscale_exp(uint32_t m) { return min(141 - (int)(m >> 7), 100); }
__device__ __forceinline__ float exp2i(int e) { return __uint_as_float((uint32_t)(e + 127) << 23); }
__device__ __forceinline__ uint32_t bf2_to_h2(uint32_t w, float sc) { return pack_f16(bf_lo(w) * sc, bf_hi(w) * sc); }
__device__ __forceinline__ void bf2_to_h2_inplace(uint32_t& w, uint32_t sc2) {
  asm volatile("{\n.reg .b32 t, lo, hi;\nmul.rn.bf16x2 t, %0, %1;\nshl.b32 lo, t, 16;\nand.b32 hi, t, 0xffff0000;\ncvt.rn.f16x2.f32 %0, hi, lo;\n}" : "+r"(w) : "r"(sc2));
}
__device__ __forceinline__ void prefetch_l2(const void* p, uint32_t bytes) { asm volatile("cp.async.bulk.prefetch.L2.global [%0], %1;" :: "l"(p), "r"(bytes) : "memory"); }
__device__ __forceinline__ void prefetch_tma_2d(const CUtensorMap* tm, int c0, int c1) {
  asm volatile("cp.async.bulk.prefetch.tensor.2d.L2.global [%0, {%1, %2}];" :: "l"(tm), "r"(c0), "r"(c1) : "memory");
}
__host__ __device__ constexpr uint32_t acc_voff(int v) { return v < 4 ? v * 1024u : (v == 4 ? 128u : 3072u + 128u); }
__device__ __forceinline__ int unit28(int i) { return i == 3 ? 54 : 14 * i; }
__device__ __forceinline__ int unit24(int i) { return i < 2 ? 48 - 6 * i : 56 + 6 * i; }
__device__ __forceinline__ uint32_t acc_step(int s) { return (s >> 1) * 32768 + (s & 1) * 512; }
__device__ __forceinline__ uint32_t acc_lane(int i, int lane) { return ((lane >> 3) & 1) * 256 + (lane >> 4) * 4096 + i * 8192 + (lane & 7) * 16; }

__global__ void __cluster_dims__(3, 1, 1) __launch_bounds__(384, 1) chain_kernel(const ChainArgs a, const __grid_constant__ CUtensorMap tmWq,
    const __grid_constant__ CUtensorMap tmWk, const __grid_constant__ CUtensorMap tmWv) {
  using namespace ch;
  extern __shared__ __align__(1024) unsigned char smem_raw[];
  const uint32_t sb = smem_u32(smem_raw);
  const int warp = __shfl_sync(0xffffffffu, (int)threadIdx.x >> 5, 0);
  const int lane = __shfl_sync(0xffffffffu, (int)threadIdx.x & 31, threadIdx.x & 31);
  const int cta = blockIdx.x, h = cta / 3, j = cta % 3;
  const int g = lane >> 2, q4 = lane & 3, r8 = lane & 7, m4 = lane >> 3;
  unsigned char* const arena = a.arena;
  if (sb & 1023u) __trap();
  asm volatile("griddepcontrol.launch_dependents;");
  TL_BEGIN(a.tl);
  if (threadIdx.x == 0) {
    mbar_init(sb + MB_S, 1); mbar_init(sb + MB_O, 1); mbar_init(sb + MB_X, 1);
    mbar_init(sb + MB_K, 1); mbar_init(sb + MB_V, 1); mbar_init(sb + MB_Q, 1); mbar_init(sb + MB_R, 1);
    sts32(sb + SC_W, 0); sts32(sb + SC_W + 4, 0); sts32(sb + SC_W + 8, 0); sts32(sb + SC_IN + 12, 0); sts32(sb + SC_IN + 20, 0);
    asm volatile("fence.mbarrier_init.release.cluster;" ::: "memory");
    mbar_expect_tx(sb + MB_S, 1280); mbar_expect_tx(sb + MB_O, 2048);
  }
  __syncthreads();
  const int col0 = j == 0 ? 0 : (j == 1 ? 224 : 432), rowb = j == 0 ? 448 : 416;
  const uint32_t d1 = mapa_u32(sb, (j + 1) % 3) - sb, d2 = mapa_u32(sb, (j + 2) % 3) - sb;

  if (warp >= 8) {
    asm volatile("setmaxnreg.dec.sync.aligned.u32 40;");
    const int hw = warp - 8, ht = hw * 32 + lane;
    const bool lead = ht == 0;
    auto stage_wo = [&](int half) {
      if (ht < 96) bulk_g2s(sb + OFF_X + ht * WOS, a.Wo + ((size_t)h * cfg::DH + (half * 96 + ht + 64 * j) % 192) * cfg::DM + col0, rowb, sb + MB_R);
    };
    auto stage_w = [&](const CUtensorMap* tm, uint32_t dst, uint32_t mb) {
      mbar_expect_tx(mb, 81920);
      for (int b = 0; b < 10; b++) tma_load_2d(dst + b * 8192, tm, h * cfg::DH + j * 64, b * 64, mb);
    };
    const unsigned char* xg = (const unsigned char*)a.xh;
    auto issue_x = [&](int s) { mbar_expect_tx(sb + MB_X, 40960); bulk_g2s(sb + OFF_X, xg + (size_t)s * 40960, 40960, sb + MB_X); };
    if (lead) { stage_w(&tmWk, sb + OFF_WQ, sb + MB_K); mbar_expect_tx(sb + MB_R, 96 * rowb); }
    if (ht == 32) stage_w(&tmWv, sb + OFF_WO, sb + MB_V);
    bar_sync(B_H, 128);
    stage_wo(0);
    if (ht == 64) for (int b = 0; b < 10; b++) prefetch_tma_2d(&tmWq, h * cfg::DH + j * 64, b * 64);
    if (ht < 96) prefetch_l2(a.Wo + ((size_t)h * cfg::DH + (96 + ht + 64 * j) % 192) * cfg::DM + col0, rowb);
    {
      uint4 v[5]; uint32_t m = 0;
#pragma unroll
      for (int i = 0; i < 5; i++) {
        const int c = ht + 128 * i;
        v[i] = *(const uint4*)(a.mem0 + (c & 7) * cfg::DM + (c >> 3) * 8);
        m = amax_bf2(amax_bf2(m, amax_bf2(v[i].x, v[i].y)), amax_bf2(v[i].z, v[i].w));
      }
      m = amax_fold(m);
      if (lane == 0) sts32(sb + SC_MX + hw * 4, m);
      bar_sync(B_H, 128);
      const uint4 mm = lds128(sb + SC_MX);
      const int se = max(wscale_exp(max(max(mm.x, mm.y), max(mm.z, mm.w))), -100);
      const float sc = exp2i(se);
#pragma unroll
      for (int i = 0; i < 5; i++) {
        const int c = ht + 128 * i, t = c & 7, chn = c >> 3;
        sts128(sb + OFF_MEM + chn * 128 + ((t ^ (2 * (chn & 3))) << 4), bf2_to_h2(v[i].x, sc), bf2_to_h2(v[i].y, sc), bf2_to_h2(v[i].z, sc), bf2_to_h2(v[i].w, sc));
      }
      if (lead) { sts32(sb + SC_IN, __float_as_uint(exp2i(-se))); sts32(sb + SC_IN + 4, 0x7800u); }
    }
    bar_sync(0, 384);
    if (lead) stage_w(&tmWq, sb + OFF_WQ, sb + MB_Q);
    bar_sync(0, 384);
    if (lead) mbar_expect_tx(sb + MB_R, 96 * rowb);
    bar_sync(B_H, 128);
    stage_wo(1);
    bar_sync(0, 384);
    if (lead) {
      issue_x(0);
      st_relaxed_u32(arena + AR_TAB + cta * 4, 0x80000000u | (lds32_i<SC_W>(sb) << 15) | lds32_i<SC_W + 4>(sb));
    }
    {
      uint32_t mv = 0, mo = 0;
      for (int i = 0; i < 3; i++) {
        uint32_t v; int spin = 0;
        while (((v = ld_relaxed_u32(arena + AR_TAB + (lane + 32 * i) * 4)) >> 31) == 0) { if (++spin > SPIN_LIMIT) break; }
        mv = max(mv, (v >> 15) & 0x7fffu); mo = max(mo, v & 0x7fffu);
      }
      __syncwarp();
      sts32(sb + SC_IN + 8 + (lane & 1) * 16, 15 - ((__reduce_max_sync(0xffffffffu, mv) >> 7) + (__reduce_max_sync(0xffffffffu, mo) >> 7) - 252 + 22));
    }
    cluster_sync_all();

    const int cb28 = unit28(hw), du = (unit24(hw) - cb28) * 128;
    int ln = lane;
    bar_sync(B_MEM0, 256); bar_sync(B_MEM1, 256);
#pragma unroll 1
    for (int s = 0; s < cfg::NSEG; s++) {
      TS_SETUP();
      const bool last = s == cfg::NSEG - 1;
      const size_t blk = (size_t)s * 96 + cta;
      if (ln == 0) {
        if (hw == 2 && !last) issue_x(s + 1);
        if (hw == 0) { fence_proxy_async(); bulk_s2g(a.kx + blk * 2048, sb + OFF_KX, 4096); bulk_s2g(a.vx + blk * 2048, sb + OFF_VX, 4096); bulk_commit(); }
      }
      __syncwarp();
      if (last) break;
      ln = fresh(ln);
      uint32_t kb0[4], kb1[4];
      { const uint32_t ka = sb + hw * 128 + (ln >> 3) * 512 + (ln & 7) * 16; ldsm_x4_i<OFF_KX>(kb0, ka); ldsm_x4_i<OFF_KX + 2048>(kb1, ka); }
      const uint32_t l16 = sb + ln * 16, s8 = sb + ln * 8, xs = s8 + hw * 256, xr = sb + ln * 4 + (hw >> 1) * 512 + (hw & 1) * 128;
      TS(1);
      bar_sync(B_QK, 384);
      {
        uint32_t q0[4], q1[4], q2[4], q3[4];
        float sa[4] = {0, 0, 0, 0}, sc2[4] = {0, 0, 0, 0};
        ldsm_x4_i<OFF_Q>(q0, l16); ldsm_x4_i<OFF_Q + 1024>(q2, l16); ldsm_x4_i<OFF_Q + 512>(q1, l16);
        bar_arrive(B_A, 288);
        ldsm_x4_i<OFF_Q + 1536>(q3, l16);
        mma16816(sa, q0[0], q0[1], q0[2], q0[3], kb0[0], kb0[1]);
        mma16816(sc2, q2[0], q2[1], q2[2], q2[3], kb1[0], kb1[1]);
        mma16816(sa, q1[0], q1[1], q1[2], q1[3], kb0[2], kb0[3]);
        mma16816(sc2, q3[0], q3[1], q3[2], q3[3], kb1[2], kb1[3]);
        const float x0 = (sa[0] + sa[2]) + (sc2[0] + sc2[2]), x1 = (sa[1] + sa[3]) + (sc2[1] + sc2[3]);
        const uint32_t xp = pack_bf16(x0, x1);
        st_async_b32_i<OFF_SR + 256>(xr + d1, xp, sb + MB_S + d1);
        st_async_b32_i<OFF_SR>(xr + d2, xp, sb + MB_S + d2);
        sts64_i<OFF_S>(xs, __float_as_uint(x0), __float_as_uint(x1));
      }
      TS(3);
      bar_sync(B_SL, 256);
      float t0[4], t1[4], t2[4] = {0, 0, 0, 0};
      float osc;
      {
        const uint4 si = lds128_i<SC_IN>(sb + 16 * (s & 1));
        { const uint2 x = lds64_i<OFF_S>(s8), y = lds64_i<OFF_S + 256>(s8); t0[0] = __uint_as_float(x.x); t0[1] = __uint_as_float(x.y); t0[2] = __uint_as_float(y.x); t0[3] = __uint_as_float(y.y); }
        { const uint2 x = lds64_i<OFF_S + 512>(s8), y = lds64_i<OFF_S + 768>(s8); t1[0] = __uint_as_float(x.x); t1[1] = __uint_as_float(x.y); t1[2] = __uint_as_float(y.x); t1[3] = __uint_as_float(y.y); }
        { const uint2 x = lds64_i<OFF_S + 1024>(s8); t2[0] = __uint_as_float(x.x); t2[1] = __uint_as_float(x.y); }
        const int em = (int)(si.y >> 10) - 14 + (int)(si.x >> 23) - 127;
        osc = exp2i(max(min((int)si.z - max(em, 1), 100), -100));
      }
      const uint32_t xo = sb + hw * 256 + (ln & 2) * 64 + (ln >> 2) * 16 + (ln & 1) * 8;
      const uint32_t eye = ((ln >> 3) == (ln & 3)) ? ((ln & 4) ? 0x3f800000u : 0x3f80u) : 0u;
      mbar_spin(sb + MB_S, s & 1);
      TS(4);
      uint32_t v0[4], v1[4], vm[2];
      {
        uint32_t r0[4], r1[4], r2[4];
        ldsm_x4_i<OFF_SR>(r0, l16); ldsm_x4_i<OFF_SR + 512>(r1, l16); ldsm_x4_i<OFF_SR + 1024>(r2, l16);
        mma16816(t0, r0[0], r0[1], r0[2], r0[3], eye, eye);
        mma16816(t1, r1[0], r1[1], r1[2], r1[3], eye, eye);
        mma16816(t2, r2[0], r2[1], r2[2], r2[3], eye, eye);
      }
      float sc[10] = {t0[0], t0[1], t0[2], t0[3], t1[0], t1[1], t1[2], t1[3], t2[0], t2[1]};
      const float cs = 0.07216878364870322f * 1.4426950408889634f;
      float mx = fmaxf(fmaxf(fmaxf(sc[0], sc[1]), fmaxf(sc[2], sc[3])), fmaxf(fmaxf(sc[4], sc[5]), fmaxf(sc[6], sc[7])));
      mx = fmaxf(mx, fmaxf(sc[8], sc[9]));
      {
        const float m1 = __shfl_xor_sync(0xffffffffu, mx, 1), m2 = __shfl_xor_sync(0xffffffffu, mx, 2), m3 = __shfl_xor_sync(0xffffffffu, mx, 3);
        SFENCE2(l16, __float_as_uint(mx));
        ldsm_x4_t_i<OFF_VX>(v0, l16 + hw * 1024); ldsm_x4_t_i<OFF_VX + 512>(v1, l16 + hw * 1024);
        bar_sync(B_V, 256);
        bar_arrive(B_G, 384);
        ldsm_x2_t(vm, l16 + hw * 256 + OFF_VM);
        mx = fmaxf(fmaxf(mx, m1), fmaxf(m2, m3));
      }
      const float mo = mx * cs;
#pragma unroll
      for (int i = 0; i < 10; i++) sc[i] = ex2f(fmaf(sc[i], cs, -mo));
      const uint32_t p0 = pack_bf16(sc[0], sc[1]), p1 = pack_bf16(sc[2], sc[3]), p2 = pack_bf16(sc[4], sc[5]), p3 = pack_bf16(sc[6], sc[7]), p4 = pack_bf16(sc[8], sc[9]);
      TS(5);
      float oa[4] = {0, 0, 0, 0}, ob[4] = {0, 0, 0, 0}, oc[4] = {0, 0, 0, 0}, od[4] = {0, 0, 0, 0}, rs[4] = {0, 0, 0, 0};
      const uint32_t ones = 0x3f803f80u;
      mma16816(rs, p0, p2, p1, p3, ones, ones);
      mma16816(oc, p0, p2, p1, p3, v0[2], v0[3]);
      mma16816(od, p0, p2, p1, p3, v1[2], v1[3]);
      mma16816(oa, p0, p2, p1, p3, v0[0], v0[1]);
      mma16816(ob, p0, p2, p1, p3, v1[0], v1[1]);
      mma1688(rs, p4, 0u, ones);
      mma1688(oa, p4, 0u, vm[0]);
      mma1688(ob, p4, 0u, vm[1]);
      const float inv = rcpf(rs[0] + rs[2]) * osc;
      {
        const uint32_t y0 = pack_bf16((oa[0] + oc[2]) * inv, (oa[1] + oc[3]) * inv), y1 = pack_bf16((ob[0] + od[2]) * inv, (ob[1] + od[3]) * inv);
        st_async_v2_i<OFF_O + 2048>(xo + d1, y0, y1, sb + MB_O + d1);
        st_async_v2_i<OFF_O + 1024>(xo + d2, y0, y1, sb + MB_O + d2);
        sts64_i<OFF_O>(xo, y0, y1);
      }
      bar_arrive(B_O, 384);
      TS(6);
      if (ln == 0) {
        if (hw == 0) {
          bulk_wait<0>();
          if ((s & 3) == 0 && s > 0) {
            asm volatile("st.release.gpu.global.u32 [%0], %1;" :: "l"(arena + (AR_PROG + (cta + ln) * 4)), "r"(s) : "memory");
          }
        }
        if (hw == 1) { fence_proxy_async(); bulk_s2g(a.km + blk * 512, sb + OFF_KM, 1024); bulk_s2g(a.vm + blk * 512, sb + OFF_VM, 1024); bulk_commit(); }
        if (hw == 3) { mbar_expect_tx(sb + MB_S, 1280); sts64_i<SC_IN>(sb + 16 * ((s + 1) & 1), 0x7f000000u - __float_as_uint(osc), 0u); }
      }
      __syncwarp();
      ln = fresh(ln);
      auto mslot = [&](int c) -> uint32_t { return sb + OFF_MEM + c * 128 + (((ln >> 2) ^ (2 * (c & 3))) << 4); };
      const int lq = ln & 3;
      const uint32_t ma = mslot(cb28 + lq), mb_ = mslot(cb28 + (lq >> 1)) + (lq & 1) * 8;
      const unsigned char* gp = arena + (AR_ACC + acc_lane(hw, ln) + acc_step(s));
      const bool odd = ln & 1;
      SFENCE(ma);
      bar_sync(B_RED, 384);
      SFENCE(mb_);
      const uint32_t tw = clk_v();
      TSV(7, tw);
      if (ln == 0) {
        if (hw == 3) mbar_expect_tx(sb + MB_O, 2048);
        if (hw == 1) bulk_wait<0>();
      }
      __syncwarp();
      while (clk_v() - tw < POLL_DELAY) {}
      TS(8);
      uint4 v[6];
      int spin = 0;
      const uint32_t cm = odd ? 0x5000u : 0u;
      do {
        static_for<0, 6>([&](auto I) { v[I.value] = ld_relaxed_v4_i<acc_voff(I.value)>(gp); });
      } while (__any_sync(0xffffffffu, (~((v[0].w & v[1].w & v[2].w) & (v[3].w & v[4].w & v[5].w)) & cm) != 0) && ++spin < SPIN_LIMIT);
      v[0].w = odd ? v[3].x : v[0].w; v[1].w = odd ? v[3].y : v[1].w; v[2].w = odd ? v[3].z : v[2].w; v[3].w = odd ? 0u : v[3].w;
      sts128_i<0>(ma, v[0].x, v[0].y, v[0].z, v[0].w);
      sts128_i<512>(ma, v[1].x, v[1].y, v[1].z, v[1].w);
      sts128_i<1024>(ma, v[2].x, v[2].y, v[2].z, v[2].w);
      sts128_i<0>(ma + du, v[4].x, v[4].y, v[4].z, v[5].z);
      sts64_i<512>(mb_ + du, v[5].x, v[5].y);
      if (!odd) sts128_i<1536>(mb_, v[3].x, v[3].y, v[3].z, v[3].w);
      TSV(11, spin);
      TS(10);
      bar_sync(B_MEM0, 256); bar_sync(B_MEM1, 256);
      uint32_t m = lds32_i<SC_IN + 12>(sb);
      uint32_t m2 = m;
      static_for<0, 3>([&](auto I) { m = amax_h2(amax_h2(amax_h2(amax_h2(m, v[I.value].x), v[I.value].y), v[I.value].z), v[I.value].w); });
      static_for<3, 6>([&](auto I) { m2 = amax_h2(amax_h2(amax_h2(m2, v[I.value].x), v[I.value].y), v[I.value].z); });
      m = amax_fold(amax_h2(amax_h2(m2, v[3].w), m));
      if (ln == 0) asm volatile("red.shared.max.u32 [%0], %1;" :: "r"(sb + SC_IN + 4 + 16 * ((s + 1) & 1)), "r"(m) : "memory");
    }
    bar_sync(B_RED, 384);
    if (hw == 0 && ln == 0) {
      const size_t blk = (size_t)(cfg::NSEG - 1) * 96 + cta;
      fence_proxy_async();
      bulk_s2g(a.km + blk * 512, sb + OFF_KM, 1024); bulk_s2g(a.vm + blk * 512, sb + OFF_VM, 1024); bulk_commit();
      bulk_wait<0>();
      asm volatile("st.release.gpu.global.u32 [%0], %1;" :: "l"(arena + AR_PROG + cta * 4), "r"(cfg::NSEG) : "memory");
    }
    __syncwarp();
    TL_END(a.tl);
    cluster_sync_all();
  } else {
    asm volatile("setmaxnreg.inc.sync.aligned.u32 232;");
    const int wi = warp & 3, hf = warp >> 2, tid = warp * 32 + lane;
    uint32_t w[40][4];
    uint32_t wqa;
    { const int mrow = r8 + ((lane >> 4) << 3), mch = 2 * wi + (m4 & 1); wqa = sb + mrow * 128 + ((mch ^ r8) << 4); }
    mbar_wait(sb + (hf ? MB_V : MB_K), 0);
    { const uint32_t wa = wqa + (hf ? OFF_WO : OFF_WQ); static_for<0, 40>([&](auto K) { ldsm_x4_t_i<K.value * 2048>(w[K.value], wa); }); }
    bar_sync(0, 384);
    float iw, iq;
    {
      uint32_t m = 0;
#pragma unroll
      for (int k = 0; k < 40; k++) m = amax_bf2(amax_bf2(m, amax_bf2(w[k][0], w[k][1])), amax_bf2(w[k][2], w[k][3]));
      m = amax_fold(m);
      if (hf && lane == 0) asm volatile("red.shared.max.u32 [%0], %1;" :: "r"(sb + SC_W), "r"(m) : "memory");
      const int e = wscale_exp(m);
      const uint32_t sc = (uint32_t)(e + 127) * 0x00800080u; iw = exp2i(-e);
#pragma unroll
      for (int k = 0; k < 40; k++) { bf2_to_h2_inplace(w[k][0], sc); bf2_to_h2_inplace(w[k][1], sc); bf2_to_h2_inplace(w[k][2], sc); bf2_to_h2_inplace(w[k][3], sc); }
    }
    const bool t28 = j == 0 || warp < 4;
    const int bi = j == 0 ? hf : (warp < 4 ? j + 1 : 2 * (j - 1) + ((warp - 4) >> 1)), bv = t28 ? wi : 4 + (warp & 1);
    uint32_t wo1 = sb + OFF_WO + warp * 896 + lane * 16, wo2;
    {
      const int cb = (t28 ? unit28(bi) : unit24(bi)) - col0 / 8;
      uint32_t cp[4];
#pragma unroll
      for (int wd = 0; wd < 4; wd++) {
        int c, p;
        if (bv < 3) { c = 4 * bv + q4; p = wd; }
        else if (bv == 3) { if (q4 & 1) { c = 4 * (wd % 3) + q4; p = 3; } else { c = 12 + (q4 >> 1); p = wd; } }
        else if (bv == 4) { c = q4; p = wd; }
        else { if (wd < 2) { c = 4 + (q4 >> 1); p = 2 * (q4 & 1) + wd; } else { c = q4; p = 3; } }
        cp[wd] = sb + OFF_X + ((g & 1) + (g & 2) * 4 + (g >> 2) * 2) * WOS + (cb + c) * 16 + p * 4;
      }
      const int cidx = (r8 & 1) + ((r8 >> 2) << 1);
      wo2 = sb + OFF_WO + warp * 896 + ((m4 & 1) ? 768 + (m4 >> 1) * 64 + cidx * 16 : 512 + (m4 >> 1) * 128 + r8 * 16);
      const bool dump = (m4 & 1) && (r8 & 2);
      uint32_t mo = 0;
      auto wo_half = [&](int half) {
#pragma unroll 2
        for (int kk = 0; kk < 6; kk++) {
          uint32_t x[4], y[4];
#pragma unroll
          for (int wd = 0; wd < 4; wd++) { x[wd] = lds32_i<0>(cp[wd] + kk * 16 * WOS); y[wd] = lds32_i<4 * WOS>(cp[wd] + kk * 16 * WOS); mo = amax_bf2(mo, amax_bf2(x[wd], y[wd])); }
          const uint32_t o = (half * 6 + kk) * WOK;
          stsm_x4_t_i<0>(wo1 + o, x[0], x[1], y[0], y[1]);
          stsm_x4_t_i<0>(dump ? sb + OFF_S + lane * 16 : wo2 + o, x[2], x[3], y[2], y[3]);
        }
      };
      mbar_wait(sb + MB_R, 0);
      wo_half(0);
      bar_sync(0, 384);
      mbar_wait(sb + MB_Q, 0);
      uint32_t m = 0;
#pragma unroll 4
      for (int i = 0; i < 20; i++) { const uint4 v = lds128(sb + OFF_WQ + (tid + 256 * i) * 16); m = amax_bf2(amax_bf2(m, amax_bf2(v.x, v.y)), amax_bf2(v.z, v.w)); }
      m = amax_fold(m);
      if (lane == 0) asm volatile("red.shared.max.u32 [%0], %1;" :: "r"(sb + SC_W + 8), "r"(m) : "memory");
      bar_sync(B_C, 256);
      const int e = wscale_exp(lds32_i<SC_W + 8>(sb));
      const float sc = exp2i(e); iq = uniform_f(exp2i(-e));
#pragma unroll 4
      for (int i = 0; i < 20; i++) {
        const uint32_t p = sb + OFF_WQ + (tid + 256 * i) * 16; const uint4 v = lds128(p);
        sts128(p, bf2_to_h2(v.x, sc), bf2_to_h2(v.y, sc), bf2_to_h2(v.z, sc), bf2_to_h2(v.w, sc));
      }
      mbar_wait(sb + MB_R, 1);
      wo_half(1);
      mo = amax_fold(mo);
      if (lane == 0) asm volatile("red.shared.max.u32 [%0], %1;" :: "r"(sb + SC_W + 4), "r"(mo) : "memory");
    }
    bar_sync(0, 384);
    auto run = [&](auto HF) {
    constexpr int hf = HF.value;
    uint32_t mema, sta, l16 = sb + lane * 16;
    uint32_t rq[hf ? NQ1 : NQ0][4];
    auto x_gemm = [&](uint32_t ph, [[maybe_unused]] uint32_t tsb) {
      float xa[16];
      const uint32_t dlo = (((sb + OFF_X) & 0x3FFFF) >> 4) | (1u << 16);
      constexpr int NP = hf ? NQ1 : NP0;
      if constexpr (hf) {
        static_for<PQE, NP>([&](auto K) { ldsm_x4_t_i<OFF_WQ + K.value * 2048>(rq[K.value], wqa); });
        bar_sync(B_X, 256);
      }
      wgmma_fence();
      static_for<0, 40>([&](auto K) {
        constexpr int k = K.value;
        wgmma_rs32h<((k >> 2) * 4096 + (k & 3) * 32) / 16, (k != 0)>(xa, w[k], dlo);
        if constexpr (!hf && k == PFK && NP > PQE) { SFENCE(wqa); static_for<PQE, NP>([&](auto K) { ldsm_x4_t_i<OFF_WQ + K.value * 2048>(rq[K.value], wqa); }); SFENCE(wqa); }
        if constexpr (!hf && k == XT) bar_arrive(B_X, 256);
      });
      {
        const int lr = (l16 >> 4) & 7, lm = (l16 >> 7) & 3;
        mema = l16 ^ (lm << 5);
        sta = sb + lr * 16 + (lm < 2 ? OFF_Q + wi * 512 + hf * 128 + lm * 256 : OFF_KM + wi * 256 + (lm - 2) * 128);
      }
      wgmma_commit();
      TS(9);
      wgmma_wait<0>();
      const uint32_t xs = l16 + wi * 1024 + hf * (OFF_VX - OFF_KX);
      stsm_x4_t_i<OFF_KX>(xs, pack_bf16(xa[0] * iw, xa[1] * iw), pack_bf16(xa[4] * iw, xa[5] * iw), pack_bf16(xa[8] * iw, xa[9] * iw), pack_bf16(xa[12] * iw, xa[13] * iw));
      stsm_x4_t_i<OFF_KX + 512>(xs, pack_bf16(xa[2] * iw, xa[3] * iw), pack_bf16(xa[6] * iw, xa[7] * iw), pack_bf16(xa[10] * iw, xa[11] * iw), pack_bf16(xa[14] * iw, xa[15] * iw));
    };
    auto wq_addr = [&](uint32_t l) -> uint32_t {
      const int lr = (l >> 4) & 7, lm = (l >> 7) & 3;
      return sb + hf * ((40 - NQ1) * 2048) + (lr + ((lm >> 1) << 3)) * 128 + (((2 * wi + (lm & 1)) ^ lr) << 4);
    };
    constexpr int NPM = hf ? NPM1 : NPM0;
    uint32_t u1[NPM][4], u2[NPM][4];
    static_for<0, NPM>([&](auto K) { ldsm_x4_i<(12 - NPM + K.value) * WOK>(u1[K.value], wo1); ldsm_x4_i<(12 - NPM + K.value) * WOK>(u2[K.value], wo2); });
    bar_sync(B_C, 256);
    wqa = wq_addr(l16);
    static_for<0, PQE>([&](auto K) { ldsm_x4_t_i<OFF_WQ + K.value * 2048>(rq[K.value], wqa); });
    mbar_spin(sb + MB_X, 0);
    x_gemm(0, sb + OFF_SR + 1152);
    cluster_sync_all();
    TL_END(a.tl + 1);
#pragma unroll 1
    for (int s = 0; s < cfg::NSEG; s++) {
      TS_SETUP();
      const bool last = s == cfg::NSEG - 1;
      bar_sync(hf ? B_MEM1 : B_MEM0, 256);
      const float sin_ = __uint_as_float(lds32_i<SC_IN>(sb + 16 * (s & 1)));
      constexpr int NPQ = (40 - NQ1) / 2;
      if constexpr (hf == 0) {
        float k0[4] = {0, 0, 0, 0}, k1[4] = {0, 0, 0, 0}, q0[4] = {0, 0, 0, 0}, q1[4] = {0, 0, 0, 0};
        constexpr auto pair_of = [](int t) { const int a = t * (20 - NPQ) / 20, b = (t + 1) * (20 - NPQ) / 20; return b > a ? NPQ + a : t - a; };
        uint32_t b[NB0][4];
        static_for<0, NB0>([&](auto T) { ldsm_x4_i<OFF_MEM + pair_of(T.value) * 512>(b[T.value], mema); });
        static_for<NP0, NQ0>([&](auto K) { ldsm_x4_t_i<OFF_WQ + K.value * 2048>(rq[K.value], wqa); });
        if (BBS < 100) bbfence<0>(mema);
        static_for<0, 20>([&](auto T) {
          constexpr int t = T.value, p = pair_of(t);
          uint32_t (&bb)[4] = b[t % NB0];
          if constexpr (p < NPQ) {
            mma16816h(q0, rq[(2 * p) % NQ0], bb[0], bb[1]);
            if constexpr (2 * p + NQ0 < 2 * NPQ) ldsm_x4_t_i<OFF_WQ + (2 * p + NQ0) * 2048>(rq[(2 * p) % NQ0], wqa);
          }
          mma16816h(k0, w[2 * p], bb[0], bb[1]);
          if constexpr (p < NPQ) {
            mma16816h(q1, rq[(2 * p + 1) % NQ0], bb[2], bb[3]);
            if constexpr (2 * p + 1 + NQ0 < 2 * NPQ) ldsm_x4_t_i<OFF_WQ + (2 * p + 1 + NQ0) * 2048>(rq[(2 * p + 1) % NQ0], wqa);
          }
          mma16816h(k1, w[2 * p + 1], bb[2], bb[3]);
          if constexpr (t + NB0 < 20) ldsm_x4_i<OFF_MEM + pair_of(t + NB0) * 512>(bb, mema);
          if constexpr (t < 20 - NB0 && (t % BBS) == BBS - 1) bbfence<t + 1>(mema);
        });
        const float sq = sin_ * iq, sk = sin_ * iw;
        stsm_x4_t_i<0>(sta, pack_bf16((q0[0] + q1[0]) * sq, (q0[1] + q1[1]) * sq), pack_bf16((q0[2] + q1[2]) * sq, (q0[3] + q1[3]) * sq),
                       pack_bf16((k0[0] + k1[0]) * sk, (k0[1] + k1[1]) * sk), pack_bf16((k0[2] + k1[2]) * sk, (k0[3] + k1[3]) * sk));
        TS(2);
        if (!last) {
          if (wi == 3) {
            const uint32_t s8 = sb + ((l16 & 511) >> 1), xr = sb + ((l16 & 511) >> 2);
            bar_sync(B_QK, 384);
            uint32_t a0[4], a1[4], a2[4], a3[4], kb0[4], kb1[4];
            ldsm_x4_i<OFF_Q>(a0, l16); ldsm_x4_i<OFF_KM>(kb0, l16); ldsm_x4_i<OFF_Q + 1024>(a2, l16); ldsm_x4_i<OFF_KM + 512>(kb1, l16);
            ldsm_x4_i<OFF_Q + 512>(a1, l16);
            bar_arrive(B_A, 288);
            ldsm_x4_i<OFF_Q + 1536>(a3, l16);
            float sa[4] = {0, 0, 0, 0}, sc2[4] = {0, 0, 0, 0};
            mma16816(sa, a0[0], a0[1], a0[2], a0[3], kb0[0], kb0[1]);
            mma16816(sc2, a2[0], a2[1], a2[2], a2[3], kb1[0], kb1[1]);
            mma16816(sa, a1[0], a1[1], a1[2], a1[3], kb0[2], kb0[3]);
            mma16816(sc2, a3[0], a3[1], a3[2], a3[3], kb1[2], kb1[3]);
            const float x0 = (sa[0] + sa[2]) + (sc2[0] + sc2[2]), x1 = (sa[1] + sa[3]) + (sc2[1] + sc2[3]);
            const uint32_t xp = pack_bf16(x0, x1);
            st_async_b32_i<OFF_SR + 1024 + 256>(xr + d1, xp, sb + MB_S + d1);
            st_async_b32_i<OFF_SR + 1024>(xr + d2, xp, sb + MB_S + d2);
            sts64_i<OFF_S + 1024>(s8, __float_as_uint(x0), __float_as_uint(x1));
          } else {
            bar_arrive(B_QK, 384);
          }
          bar_sync(B_SL, 256);
        }
      } else {
        float v0[4] = {0, 0, 0, 0}, v1[4] = {0, 0, 0, 0}, q0[4] = {0, 0, 0, 0}, q1[4] = {0, 0, 0, 0};
        uint32_t b[NQ1 / 2][4];
        static_for<0, NQ1 / 2>([&](auto T) { ldsm_x4_i<OFF_MEM + (NPQ + T.value) * 512>(b[T.value], mema); });
        static_for<0, NQ1 / 2>([&](auto T) {
          constexpr int t = T.value, p = NPQ + t;
          uint32_t (&bb)[4] = b[t];
          mma16816h(q0, rq[2 * t], bb[0], bb[1]);
          mma16816h(q1, rq[2 * t + 1], bb[2], bb[3]);
          mma16816h(v0, w[2 * p], bb[0], bb[1]);
          mma16816h(v1, w[2 * p + 1], bb[2], bb[3]);
        });
        const float sq = sin_ * iq, sv = sin_ * iw;
        stsm_x2_t_i<0>(sta, pack_bf16((q0[0] + q1[0]) * sq, (q0[1] + q1[1]) * sq), pack_bf16((q0[2] + q1[2]) * sq, (q0[3] + q1[3]) * sq));
        TS(2);
        if (!last) { bar_arrive(B_QK, 384); bar_sync(B_A, 288); }
        float v2[4] = {0, 0, 0, 0}, v3[4] = {0, 0, 0, 0};
        uint32_t c[4][4];
        static_for<0, 4>([&](auto T) { ldsm_x4_i<OFF_MEM + T.value * 512>(c[T.value], mema); });
        static_for<0, NPQ>([&](auto T) {
          constexpr int p = T.value;
          uint32_t (&bb)[4] = c[p & 3];
          if constexpr (p & 1) { mma16816h(v0, w[2 * p], bb[0], bb[1]); mma16816h(v1, w[2 * p + 1], bb[2], bb[3]); }
          else { mma16816h(v2, w[2 * p], bb[0], bb[1]); mma16816h(v3, w[2 * p + 1], bb[2], bb[3]); }
          if constexpr (p + 4 < NPQ) ldsm_x4_i<OFF_MEM + (p + 4) * 512>(bb, mema);
        });
        stsm_x2_t_i<OFF_VM>(l16 + wi * 256, pack_bf16(((v0[0] + v1[0]) + (v2[0] + v3[0])) * sv, ((v0[1] + v1[1]) + (v2[1] + v3[1])) * sv),
                            pack_bf16(((v0[2] + v1[2]) + (v2[2] + v3[2])) * sv, ((v0[3] + v1[3]) + (v2[3] + v3[3])) * sv));
        if (!last) bar_arrive(B_V, 256);
      }
      TS(3);
      if (last) break;
      {
        uint32_t t1[12][4], t2[12][4];
        const uint32_t o16 = l16;
        wo1 = l16 + (OFF_WO + warp * 896);
        wo2 = sb + OFF_WO + warp * 896 + ((l16 & 128) ? 768 + ((l16 & 256) >> 2) + (l16 & 16) + ((l16 & 64) >> 1) : 512 + ((l16 & 256) >> 1) + (l16 & 112));
        auto ldw = [&](auto K) { if constexpr (K.value < 12 - NPM) { ldsm_x4_i<K.value * WOK>(t1[K.value], wo1); ldsm_x4_i<K.value * WOK>(t2[K.value], wo2); } };
        constexpr int NR_ = NRT - NPM;
        constexpr int PB = (hf ? PB1 : PB0) < NR_ ? (hf ? PB1 : PB0) : NR_, PA = (hf ? PA1 : PA0) < PB ? (hf ? PA1 : PA0) : PB;
        static_for<0, PA>(ldw);
        mbar_spin(sb + MB_X, (s + 1) & 1);
        if constexpr (PB > PA) bar_sync(B_G, 384); else bar_arrive(B_G, 384);
        static_for<PA, PB>(ldw);
        float c0[4] = {0, 0, 0, 0}, c1[4] = {0, 0, 0, 0}, e0[4] = {0, 0, 0, 0}, e1[4] = {0, 0, 0, 0};
        uint32_t ob[6][4];
        auto kstep = [&](auto K) {
          constexpr int k = K.value;
          uint32_t (&bb)[4] = ob[k >> 1];
          uint32_t (&x)[4] = k < 12 - NPM ? t1[k] : u1[k < 12 - NPM ? 0 : k - (12 - NPM)];
          uint32_t (&y)[4] = k < 12 - NPM ? t2[k] : u2[k < 12 - NPM ? 0 : k - (12 - NPM)];
          if constexpr (k & 1) { mma16816(c1, x[0], x[1], x[2], x[3], bb[2], bb[3]); mma16816(e1, y[0], y[1], y[2], y[3], bb[2], bb[3]); }
          else { mma16816(c0, x[0], x[1], x[2], x[3], bb[0], bb[1]); mma16816(e0, y[0], y[1], y[2], y[3], bb[0], bb[1]); }
          if constexpr (k >= NRF) ldw(IC<k + NR_ - NRF>{});
        };
        auto ldo = [&](auto P) { ldsm_x4_i<OFF_O + P.value * 512>(ob[P.value], o16); };
        TS(4);
        bar_sync(B_O, 384);
        ldo(IC<0>{}); ldo(IC<1>{});
        SFENCE(o16);
        static_for<PB, NR_>(ldw);
        static_for<0, 4>(kstep);
        TS(5);
        mbar_spin(sb + MB_O, s & 1);
        TS(6);
        ldo(IC<2>{}); ldo(IC<NPM >= 2 ? 5 : 3>{});
        if (WOF) SFENCE(o16);
        kstep(IC<4>{});
        if constexpr (NPM < 2) { kstep(IC<5>{}); ldo(IC<4>{}); kstep(IC<6>{}); kstep(IC<7>{}); ldo(IC<5>{}); static_for<8, 12>(kstep); }
        else if constexpr (NPM >= 4) { kstep(IC<10>{}); kstep(IC<11>{}); ldo(IC<4>{}); kstep(IC<5>{}); ldo(IC<3>{}); kstep(IC<8>{}); kstep(IC<9>{}); kstep(IC<6>{}); kstep(IC<7>{}); }
        else { kstep(IC<5>{}); ldo(IC<3>{}); kstep(IC<11>{}); kstep(IC<10>{}); ldo(IC<4>{}); kstep(IC<6>{}); kstep(IC<7>{}); if constexpr (NPM == 3) { kstep(IC<9>{}); kstep(IC<8>{}); } else { kstep(IC<8>{}); kstep(IC<9>{}); } }
        l16 = fresh(l16);
        const int ln = (l16 >> 4) & 31;
        unsigned char* gr = arena + (AR_ACC + acc_lane(bi, ln) + acc_voff(bv) + acc_step(s));
        const bool cnt = (ln & 1) || !t28;
        wqa = wq_addr(l16);
        SFENCE(o16);
        static_for<0, PQE>([&](auto K) { ldsm_x4_t_i<OFF_WQ + K.value * 2048>(rq[K.value], wqa); });
        const uint32_t y0 = movm_t(pack_f16(c0[0] + c1[0], c0[1] + c1[1])), y1 = movm_t(pack_f16(c0[2] + c1[2], c0[3] + c1[3]));
        const uint32_t y2 = movm_t(pack_f16(e0[0] + e1[0], e0[1] + e1[1])), y3 = movm_t(pack_f16(e0[2] + e1[2], e0[3] + e1[3]));
        asm volatile("red.relaxed.gpu.global.add.noftz.v4.f16x2 [%0], {%1,%2,%3,%4};" :: "l"(gr), "r"(y0), "r"(y1), "r"(y2), "r"(cnt ? 0x3c00u : y3) : "memory");
        if constexpr (hf || RSYNC) bar_sync(B_RED, 384); else bar_arrive(B_RED, 384);
        TS(7);
      }
      x_gemm((s + 1) & 1, 0);
      TS(8);
    }
    };
    if (hf == 0) run(IC<0>{}); else run(IC<1>{});
    bar_arrive(B_RED, 384);
    cluster_sync_all();
  }
}
struct PrepArgs { const bf16 *wqkv, *wphi, *wo; bf16 *wb, *wot; };
constexpr int PREP_BLOCKS = 480;
__device__ __forceinline__ void prep_body(const int b, const bf16* __restrict__ wqkv, const bf16* __restrict__ wphi, const bf16* __restrict__ wo,
                                          bf16* __restrict__ wb, bf16* __restrict__ wot) {
  const int task = b * 8 + (threadIdx.x >> 5), lane = threadIdx.x & 31;
  if (task < 1920) {
    const int which = task / 640, h = (task / 20) % 32, k = (task % 20) * 32 + lane;
    const int row0 = 288 * (h >> 2) + 96 * which + 24 * (h & 3);
    const uint2* src = (const uint2*)(wqkv + (size_t)k * 1920 + which * 640 + h * 20);
    float w[20];
#pragma unroll
    for (int d = 0; d < 5; d++) { const uint2 t = __ldg(src + d); w[4 * d] = bf_lo(t.x); w[4 * d + 1] = bf_hi(t.x); w[4 * d + 2] = bf_lo(t.y); w[4 * d + 3] = bf_hi(t.y); }
    if (which < 2) {
      float a[20];
#pragma unroll
      for (int f = 0; f < 20; f++) a[f] = 0.f;
      const uint32_t* ph = (const uint32_t*)(wphi + h * 400);
#pragma unroll
      for (int d = 0; d < 20; d++)
#pragma unroll
        for (int f = 0; f < 10; f++) { const uint32_t t = __ldg(ph + d * 10 + f); a[2 * f] = fmaf(w[d], bf_lo(t), a[2 * f]); a[2 * f + 1] = fmaf(w[d], bf_hi(t), a[2 * f + 1]); }
#pragma unroll
      for (int f = 0; f < 20; f++) wb[(size_t)(row0 + f) * cfg::DM + k] = __float2bfloat16_rn(a[f]);
    } else {
#pragma unroll
      for (int d = 0; d < 20; d++) wb[(size_t)(row0 + d) * cfg::DM + k] = __float2bfloat16_rn(w[d]);
    }
#pragma unroll
    for (int f = 20; f < 24; f++) wb[(size_t)(row0 + f) * cfg::DM + k] = __float2bfloat16_rn(0.f);
  } else {
    const int t = task - 1920, n = (t % 20) * 32 + lane, kk0 = (t / 20) * 8, h = kk0 / 24, d0 = kk0 % 24;
    unsigned short v[8];
#pragma unroll
    for (int e = 0; e < 8; e++) v[e] = (d0 + e < 20) ? __ldg((const unsigned short*)wo + (size_t)(h * 20 + d0 + e) * cfg::DM + n) : (unsigned short)0;
    *(uint4*)(wot + (size_t)n * 768 + kk0) = make_uint4(v[0] | (v[1] << 16), v[2] | (v[3] << 16), v[4] | (v[5] << 16), v[6] | (v[7] << 16));
  }
}

#define OSPLIT(b) ((b) < 11 ? 1 : ((b) < 13 ? 2 : ((b) < 14 ? 4 : 8)))
__host__ __device__ constexpr int o_split(int b) { return OSPLIT(b); }

template <int NP>
__global__ void __launch_bounds__(256, NP > 0 ? 2 : 4) ln_kernel(const bf16* __restrict__ xin, const float* __restrict__ part, bf16* __restrict__ xout,
                                                 bf16* __restrict__ xn, uint2* __restrict__ xh, uint4* __restrict__ z0, int n0, uint4* __restrict__ z1, int n1, PrepArgs pa, int tl) {
  TL_BEGIN(tl);
  if (blockIdx.x >= 256) { prep_body(blockIdx.x - 256, pa.wqkv, pa.wphi, pa.wo, pa.wb, pa.wot); return; }
  const int warp = threadIdx.x >> 5, lane = threadIdx.x & 31;
  for (int i = blockIdx.x * 256 + threadIdx.x; i < n0; i += 256 * 256) z0[i] = make_uint4(0, 0, 0, 0);
  for (int i = blockIdx.x * 256 + threadIdx.x; i < n1; i += 256 * 256) z1[i] = make_uint4(0, 0, 0, 0);
  const int row = (255 - blockIdx.x) * 8 + warp;
  float v[20];
  uint2 xw[5];
#pragma unroll
  for (int i = 0; i < 5; i++) xw[i] = *(const uint2*)(xin + (size_t)row * cfg::DM + i * 128 + lane * 4);
  float4 a[5];
  if (NP > 0) {
    const float* pp = part + (size_t)row * cfg::DM + lane * 4;
#pragma unroll
    for (int i = 0; i < 5; i++) a[i] = make_float4(0, 0, 0, 0);
    const int np = o_split(row >> 7);
    if (np == 1) {
#pragma unroll
      for (int i = 0; i < 5; i++) a[i] = __ldcg((const float4*)(pp + i * 128));
    } else if (np == 2) {
      float4 t[5];
#pragma unroll
      for (int i = 0; i < 5; i++) { a[i] = __ldcg((const float4*)(pp + i * 128)); t[i] = __ldcg((const float4*)(pp + (size_t)cfg::S * cfg::DM + i * 128)); }
#pragma unroll
      for (int i = 0; i < 5; i++) { a[i].x += t[i].x; a[i].y += t[i].y; a[i].z += t[i].z; a[i].w += t[i].w; }
    } else {
      for (int p0 = 0; p0 < np; p0 += 4) {
        float4 t[4][5];
#pragma unroll
        for (int p = 0; p < 4; p++)
#pragma unroll
          for (int i = 0; i < 5; i++) t[p][i] = __ldcg((const float4*)(pp + (size_t)(p0 + p) * cfg::S * cfg::DM + i * 128));
#pragma unroll
        for (int p = 0; p < 4; p++)
#pragma unroll
          for (int i = 0; i < 5; i++) { a[i].x += t[p][i].x; a[i].y += t[p][i].y; a[i].z += t[p][i].z; a[i].w += t[p][i].w; }
      }
    }
  }
#pragma unroll
  for (int i = 0; i < 5; i++) {
    v[4 * i] = bf_lo(xw[i].x); v[4 * i + 1] = bf_hi(xw[i].x); v[4 * i + 2] = bf_lo(xw[i].y); v[4 * i + 3] = bf_hi(xw[i].y);
    if (NP > 0) {
      v[4 * i] = bf16r(v[4 * i] + bf16r(a[i].x)); v[4 * i + 1] = bf16r(v[4 * i + 1] + bf16r(a[i].y));
      v[4 * i + 2] = bf16r(v[4 * i + 2] + bf16r(a[i].z)); v[4 * i + 3] = bf16r(v[4 * i + 3] + bf16r(a[i].w));
      *(uint2*)(xout + (size_t)row * cfg::DM + i * 128 + lane * 4) = make_uint2(pack_bf16(v[4 * i], v[4 * i + 1]), pack_bf16(v[4 * i + 2], v[4 * i + 3]));
    }
  }
  float s = 0.f;
#pragma unroll
  for (int i = 0; i < 20; i++) s += v[i];
#pragma unroll
  for (int o = 16; o; o >>= 1) s += __shfl_xor_sync(0xffffffffu, s, o);
  const float mean = s * (1.f / cfg::DM);
  float q = 0.f;
#pragma unroll
  for (int i = 0; i < 20; i++) { const float d = v[i] - mean; q += d * d; }
#pragma unroll
  for (int o = 16; o; o >>= 1) q += __shfl_xor_sync(0xffffffffu, q, o);
  const float mb = bf16r(mean), var = bf16r(q * (1.f / cfg::DM));
  const float den = bf16r(sqrtf(bf16r(var + 1e-5f)));
#pragma unroll
  for (int i = 0; i < 5; i++) {
    float y[4];
#pragma unroll
    for (int e = 0; e < 4; e++) y[e] = __fdividef(bf16r(v[4 * i + e] - mb), den);
    const uint32_t w0 = pack_bf16(y[0], y[1]), w1 = pack_bf16(y[2], y[3]);
    *(uint2*)(xn + (size_t)row * cfg::DM + i * 128 + lane * 4) = make_uint2(w0, w1);
    if (NP == 0) xh[(((size_t)(row >> 5) * 10 + 2 * i + (lane >> 4)) * 32 + (row & 31)) * 16 + ((((lane >> 1) & 7) ^ (row & 7)) << 1) + (lane & 1)] =
        make_uint2(pack_f16(bf_lo(w0), bf_hi(w0)), pack_f16(bf_lo(w1), bf_hi(w1)));
  }
  TL_END(tl);
}

struct Pipe { uint32_t stage, phase; };
template <int NS> __device__ __forceinline__ void pipe_adv(Pipe& p) { if (++p.stage == NS) { p.stage = 0; p.phase ^= 1; } }
constexpr uint32_t SWZ128 = 1;
__device__ __forceinline__ uint64_t desc_kmajor(uint32_t a) { return make_desc(a, 16, 1024, SWZ128); }
__device__ __forceinline__ uint64_t desc_mnmajor(uint32_t a) { return make_desc(a, 8192, 1024, SWZ128); }

__device__ __forceinline__ uint32_t ld_acquire_u32(const void* p) {
  uint32_t v; asm volatile("ld.acquire.gpu.global.u32 %0, [%1];" : "=r"(v) : "l"(p) : "memory"); return v;
}
__device__ __forceinline__ void wait_ge(const void* p, uint32_t target) {
  int spin = 0;
  while (ld_acquire_u32(p) < target) { __nanosleep(64); if (++spin > (1 << 23)) break; }
}
__device__ __forceinline__ void fence_proxy_async_all() { asm volatile("fence.proxy.async;" ::: "memory"); }

namespace tr {
constexpr int NS = 4, STAGE = 16384 + 24576;
constexpr int SEGB = 15360;
constexpr int OFF_K = NS * STAGE;
constexpr int OFF_OST = OFF_K;
constexpr int OFF_BAR = OFF_K + 4 * SEGB;
constexpr int SMEM = OFF_BAR + 256;
static_assert(SMEM <= 232448, "smem");
constexpr int NQA = 32;
constexpr int o_items() { int n = 0; for (int b = 0; b < 16; b++) n += 4 * o_split(b); return n; }
constexpr int NITEMS = 16 * NQA + o_items();
enum { T_QA = 0, T_O = 1, T_END = 4 };
__device__ __forceinline__ void decode(int i, int& type, int& b, int& k) {
  if (i >= NITEMS) { type = T_END; b = 0; k = 0; return; }
  if (i < 2 * NQA) { type = T_QA; b = i / NQA; k = i % NQA; return; }
  i -= 2 * NQA;
  for (int q = 0; q < 16; q++) {
    const int no = 4 * o_split(q);
    if (i < no) { type = T_O; b = q; k = i; return; }
    i -= no;
    if (q + 2 < 16) { if (i < NQA) { type = T_QA; b = q + 2; k = i; return; } i -= NQA; }
  }
  type = T_END; b = 0; k = 0;
}
}

template <int BN> struct WG_N;
template <> struct WG_N<192> { static __device__ __forceinline__ void mma(float (&d)[96], uint64_t a, uint64_t b, int c) { wgmma_n192<0, 1>(d, a, b, c); } };
template <> struct WG_N<128> { static __device__ __forceinline__ void mma(float (&d)[64], uint64_t a, uint64_t b, int c) { wgmma_n128<0, 1>(d, a, b, c); } };
template <int BN>
__device__ __forceinline__ void tr_mainloop(float (&acc)[BN / 2], Pipe& p, uint32_t sb, uint32_t full, uint32_t empty, int nkb, int wg) {
  using namespace tr;
  uint32_t prev = 0;
#pragma unroll
  for (int i = 0; i < BN / 2; i++) acc[i] = 0.f;
  for (int kb = 0; kb < nkb; kb++) {
    mbar_wait(full + 8 * p.stage, p.phase);
    const uint32_t st = sb + p.stage * STAGE;
    wgmma_fence();
#pragma unroll
    for (int kk = 0; kk < 4; kk++) WG_N<BN>::mma(acc, desc_kmajor(st + wg * 8192 + kk * 32), desc_mnmajor(st + 16384 + kk * 2048), (kb | kk) != 0);
    wgmma_commit();
    if (kb > 0) { wgmma_wait<1>(); if ((threadIdx.x & 127) == 0) mbar_arrive(empty + 8 * prev); }
    prev = p.stage;
    pipe_adv<NS>(p);
  }
  wgmma_wait<0>();
  if ((threadIdx.x & 127) == 0) mbar_arrive(empty + 8 * prev);
}
template <int BN>
__device__ __forceinline__ void o_item(Pipe& p, uint32_t sb, uint32_t full, uint32_t empty, int nkb, float* __restrict__ dst, int wg, int wi, int lane) {
  float acc[BN / 2];
  tr_mainloop<BN>(acc, p, sb, full, empty, nkb, wg);
  float* p0 = dst + (size_t)(wg * 64 + wi * 16 + (lane >> 2)) * cfg::DM + (lane & 3) * 2;
#pragma unroll
  for (int v = 0; v < BN / 8; v++) {
    *(float2*)(p0 + 8 * v) = make_float2(acc[4 * v], acc[4 * v + 1]);
    *(float2*)(p0 + 8 * cfg::DM + 8 * v) = make_float2(acc[4 * v + 2], acc[4 * v + 3]);
  }
}

__global__ void __launch_bounds__(384, 1) trail_kernel(const __grid_constant__ CUtensorMap tmX, const __grid_constant__ CUtensorMap tmQ,
                                                       const __grid_constant__ CUtensorMap tmO, const __grid_constant__ CUtensorMap tmWo,
                                                       const bf16* __restrict__ kx, const bf16* __restrict__ vx,
                                                       const bf16* __restrict__ km, const bf16* __restrict__ vm, bf16* __restrict__ o,
                                                       float* __restrict__ part, unsigned char* __restrict__ arena, int tl) {
  using namespace tr;
  TL_BEGIN(tl);
  extern __shared__ __align__(1024) unsigned char smem_raw[];
  const uint32_t sb = smem_u32(smem_raw);
  const int warp = threadIdx.x >> 5, lane = threadIdx.x & 31;
  const uint32_t full = sb + OFF_BAR, empty = full + 8 * NS, barK = empty + 8 * NS, barKfree = barK + 8;
  const uint32_t mfull = barKfree + 8, mempty = mfull + 16, mbox = mempty + 16;
  if (threadIdx.x == 0) {
    for (int i = 0; i < NS; i++) { mbar_init(full + 8 * i, 1); mbar_init(empty + 8 * i, 2); }
    mbar_init(barK, 1); mbar_init(barKfree, 8);
    for (int i = 0; i < 2; i++) { mbar_init(mfull + 8 * i, 1); mbar_init(mempty + 8 * i, 8); }
    asm volatile("fence.mbarrier_init.release.cluster;" ::: "memory");
  }
  __syncthreads();
  if (warp >= 8) {
    asm volatile("setmaxnreg.dec.sync.aligned.u32 40;");
    if (warp == 8 && lane == 0) {
      Pipe p{0, 1}, mp{0, 1};
      uint32_t kph = 1;
      auto stage = [&](uint32_t bytes) -> uint32_t {
        mbar_wait(empty + 8 * p.stage, p.phase);
        mbar_expect_tx(full + 8 * p.stage, bytes);
        return sb + p.stage * STAGE;
      };
      while (true) {
        const int item = (int)atomicAdd((unsigned*)(arena + AR_QUEUE), 1u);
        int type, m, k;
        decode(item, type, m, k);
        mbar_wait(mempty + 8 * mp.stage, mp.phase);
        asm volatile("st.shared.u32 [%0], %1;" :: "r"(mbox + 4 * mp.stage), "r"(item) : "memory");
        mbar_arrive(mfull + 8 * mp.stage);
        pipe_adv<2>(mp);
        if (type == T_END) break;
        if (type == T_QA) {
          const CUtensorMap* tb = &tmQ;
          const int head = k & 31;
          auto ready = [&](bool block) -> bool {
            for (int jj = 0; jj < 3; jj++) {
              const void* f = arena + AR_PROG + (head * 3 + jj) * 4;
              if (block) wait_ge(f, 4 * m + 4); else if (ld_acquire_u32(f) < (uint32_t)(4 * m + 4)) return false;
            }
            return true;
          };
          auto load_k = [&]() {
            mbar_wait(barKfree, kph); kph ^= 1;
            fence_proxy_async_all();
            mbar_expect_tx(barK, 4 * SEGB);
            for (int sg = 0; sg < 4; sg++) {
              const size_t blk = (size_t)(m * 4 + sg) * 96 + head * 3;
              bulk_g2s(sb + OFF_K + sg * SEGB, kx + blk * 2048, 12288, barK);
              bulk_g2s(sb + OFF_K + sg * SEGB + 12288, km + blk * 512, 3072, barK);
            }
          };
          bool kdone = false;
          for (int kb = 0; kb < 10; kb++) {
            const uint32_t st = stage(16384 + 24576), fb = full + 8 * p.stage;
            tma_load_2d(st, &tmX, kb * 64, m * 128, fb);
#pragma unroll
            for (int b = 0; b < 3; b++) tma_load_2d(st + 16384 + b * 8192, tb, head * 192 + b * 64, kb * 64, fb);
            pipe_adv<NS>(p);
            if (!kdone && (kb == 2 || kb == 6) && ready(false)) { load_k(); kdone = true; }
          }
          if (type == T_QA) {
            if (!kdone) { ready(true); load_k(); }
            for (int hv = 0; hv < 2; hv++) {
              const uint32_t st = stage(2 * SEGB), fb = full + 8 * p.stage;
              for (int sg = 0; sg < 2; sg++) {
                const size_t blk = (size_t)(m * 4 + 2 * hv + sg) * 96 + head * 3;
                bulk_g2s(st + sg * SEGB, vx + blk * 2048, 12288, fb);
                bulk_g2s(st + sg * SEGB + 12288, vm + blk * 512, 3072, fb);
              }
              pipe_adv<NS>(p);
            }
          }
        } else {
          wait_ge(arena + AR_CNT + m * 4, NQA * 8);
          fence_proxy_async_all();
          const int nt = k & 3, ks = k >> 2, nkb = 96 / o_split(m), nb = nt < 2 ? 3 : 2, k0 = ks * nkb * 64, c0 = nt < 2 ? nt * 192 : 384 + (nt - 2) * 128;
          for (int kb = 0; kb < nkb; kb++) {
            const uint32_t st = stage(16384 + nb * 8192), fb = full + 8 * p.stage;
            tma_load_2d(st, &tmO, k0 + kb * 64, m * 128, fb);
            for (int b = 0; b < nb; b++) tma_load_2d(st + 16384 + b * 8192, &tmWo, c0 + b * 64, k0 + kb * 64, fb);
            pipe_adv<NS>(p);
          }
        }
      }
    }
    if (blockIdx.x == gridDim.x - 1 && warp == 8) asm volatile("griddepcontrol.wait;" ::: "memory");
    return;
  }
  asm volatile("setmaxnreg.inc.sync.aligned.u32 232;");
  const int wg = warp >> 2, wi = warp & 3;
  const int g = lane >> 2, q4 = lane & 3;
  Pipe p{0, 0}, mp{0, 0};
  uint32_t kph = 0;
  unsigned* pend = nullptr;
  auto publish = [&]() {
    if (pend) { __threadfence(); __syncwarp(); if (lane == 0) atomicAdd(pend, 1u); pend = nullptr; }
  };
  while (true) {
    int item;
    mbar_wait(mfull + 8 * mp.stage, mp.phase);
    asm volatile("ld.shared.u32 %0, [%1];" : "=r"(item) : "r"(mbox + 4 * mp.stage) : "memory");
    __syncwarp();
    if (lane == 0) mbar_arrive(mempty + 8 * mp.stage);
    pipe_adv<2>(mp);
    int type, m, k;
    decode(item, type, m, k);
    if (type != T_QA) publish();
    if (type == T_END) break;
    [[maybe_unused]] const unsigned long long ti0 = TL_NOW();
    if (type == T_O) {
      const int nt = k & 3, ks = k >> 2, nkb = 96 / o_split(m), c0 = nt < 2 ? nt * 192 : 384 + (nt - 2) * 128;
      float* dst = part + ((size_t)ks * cfg::S + m * 128) * cfg::DM + c0;
      if (nt >= 2) o_item<128>(p, sb, full, empty, nkb, dst, wg, wi, lane);
      else o_item<192>(p, sb, full, empty, nkb, dst, wg, wi, lane);
      TL_END(tl);
      TL2((tl >= 12 ? 128 : 0) + 64 + 16 + m);
      TL_ACC(40, ti0);
      continue;
    }
    float acc[96];
    tr_mainloop<192>(acc, p, sb, full, empty, 10, wg);
    publish();
    const int head = k & 31;
    TL_ACC(46, ti0);
    uint32_t qf[12][4];
#pragma unroll
    for (int k = 0; k < 12; k++) {
      qf[k][0] = pack_bf16(acc[8 * k], acc[8 * k + 1]); qf[k][1] = pack_bf16(acc[8 * k + 2], acc[8 * k + 3]);
      qf[k][2] = pack_bf16(acc[8 * k + 4], acc[8 * k + 5]); qf[k][3] = pack_bf16(acc[8 * k + 6], acc[8 * k + 7]);
    }
    const int sg = wg * 2 + (wi >> 1), half = wi & 1;
    const uint32_t kbase = sb + OFF_K + sg * SEGB;
    mbar_wait(barK, kph); kph ^= 1;
    float sc[5][4];
#pragma unroll
    for (int n = 0; n < 5; n++) { sc[n][0] = sc[n][1] = sc[n][2] = sc[n][3] = 0.f; }
    const int kr = lane & 7, kc = lane >> 3;
#pragma unroll
    for (int jj = 0; jj < 3; jj++) {
#pragma unroll
      for (int u = 0; u < 2; u++) {
        const int k0 = jj * 4 + u * 2;
#pragma unroll
        for (int n = 0; n < 4; n++) {
          if (n < 2 || half) {
            uint32_t b[4];
            ldsm_x4(b, kbase + jj * 4096 + (4 * u + kc) * 512 + n * 128 + kr * 16);
            mma16816(sc[n], qf[k0][0], qf[k0][1], qf[k0][2], qf[k0][3], b[0], b[1]);
            mma16816(sc[n], qf[k0 + 1][0], qf[k0 + 1][1], qf[k0 + 1][2], qf[k0 + 1][3], b[2], b[3]);
          }
        }
        uint32_t b[4];
        ldsm_x4(b, kbase + 12288 + jj * 1024 + (4 * u + kc) * 128 + kr * 16);
        mma16816(sc[4], qf[k0][0], qf[k0][1], qf[k0][2], qf[k0][3], b[0], b[1]);
        mma16816(sc[4], qf[k0 + 1][0], qf[k0 + 1][1], qf[k0 + 1][2], qf[k0 + 1][3], b[2], b[3]);
      }
    }
    const float cs = 0.07216878364870322f * 1.4426950408889634f;
    const int r0 = 16 * half + g, r1 = r0 + 8;
    float m0 = -INFINITY, m1 = -INFINITY;
#pragma unroll
    for (int n = 0; n < 5; n++) {
#pragma unroll
      for (int e = 0; e < 2; e++) {
        const int key = 8 * n + 2 * q4 + e;
        if (n < 4) { if (key > r0) sc[n][e] = -INFINITY; if (key > r1) sc[n][2 + e] = -INFINITY; }
        m0 = fmaxf(m0, sc[n][e]); m1 = fmaxf(m1, sc[n][2 + e]);
      }
    }
    m0 = fmaxf(m0, __shfl_xor_sync(0xffffffffu, m0, 1)); m0 = fmaxf(m0, __shfl_xor_sync(0xffffffffu, m0, 2));
    m1 = fmaxf(m1, __shfl_xor_sync(0xffffffffu, m1, 1)); m1 = fmaxf(m1, __shfl_xor_sync(0xffffffffu, m1, 2));
    float s0 = 0.f, s1 = 0.f;
#pragma unroll
    for (int n = 0; n < 5; n++) {
#pragma unroll
      for (int e = 0; e < 2; e++) {
        sc[n][e] = ex2f((sc[n][e] - m0) * cs); sc[n][2 + e] = ex2f((sc[n][2 + e] - m1) * cs);
        s0 += sc[n][e]; s1 += sc[n][2 + e];
      }
    }
    s0 += __shfl_xor_sync(0xffffffffu, s0, 1); s0 += __shfl_xor_sync(0xffffffffu, s0, 2);
    s1 += __shfl_xor_sync(0xffffffffu, s1, 1); s1 += __shfl_xor_sync(0xffffffffu, s1, 2);
    const float i0 = 1.f / s0, i1 = 1.f / s1;
    uint32_t pf[3][4];
#pragma unroll
    for (int k = 0; k < 2; k++) {
      pf[k][0] = pack_bf16(sc[2 * k][0] * i0, sc[2 * k][1] * i0); pf[k][1] = pack_bf16(sc[2 * k][2] * i1, sc[2 * k][3] * i1);
      pf[k][2] = pack_bf16(sc[2 * k + 1][0] * i0, sc[2 * k + 1][1] * i0); pf[k][3] = pack_bf16(sc[2 * k + 1][2] * i1, sc[2 * k + 1][3] * i1);
    }
    pf[2][0] = pack_bf16(sc[4][0] * i0, sc[4][1] * i0); pf[2][1] = pack_bf16(sc[4][2] * i1, sc[4][3] * i1); pf[2][2] = 0u; pf[2][3] = 0u;
    TL_ACC(52, ti0);
    const uint32_t sA = p.stage, phA = p.phase; pipe_adv<NS>(p);
    const uint32_t sB = p.stage, phB = p.phase; pipe_adv<NS>(p);
    mbar_wait(full + 8 * sA, phA);
    mbar_wait(full + 8 * sB, phB);
    if ((threadIdx.x & 127) == 0) mbar_arrive(empty + 8 * (wg == 0 ? sB : sA));
    bar_sync(3, 256);
    const uint32_t vbase = sb + (wg == 0 ? sA : sB) * STAGE + (wi >> 1) * SEGB;
    const uint32_t ost = sb + OFF_OST + warp * 6144;
    const int vr = (lane & 7) + (((lane >> 3) & 1) << 3), vc = lane >> 4;
    const int tok0 = m * 128 + wg * 64 + wi * 16;
    uint32_t ow[12][4];
#pragma unroll
    for (int jj = 0; jj < 3; jj++) {
#pragma unroll
      for (int c2 = 0; c2 < 4; c2++) {
        float oa[4] = {0, 0, 0, 0}, ob[4] = {0, 0, 0, 0};
        uint32_t b[4];
        const int ch = 2 * c2 + vc;
        ldsm_x4_t(b, vbase + jj * 4096 + ch * 512 + vr * 16);
        mma16816(oa, pf[0][0], pf[0][1], pf[0][2], pf[0][3], b[0], b[1]);
        mma16816(ob, pf[0][0], pf[0][1], pf[0][2], pf[0][3], b[2], b[3]);
        if (half) {
          uint32_t b2[4];
          ldsm_x4_t(b2, vbase + jj * 4096 + ch * 512 + 256 + vr * 16);
          mma16816(oa, pf[1][0], pf[1][1], pf[1][2], pf[1][3], b2[0], b2[1]);
          mma16816(ob, pf[1][0], pf[1][1], pf[1][2], pf[1][3], b2[2], b2[3]);
        }
        uint32_t bm[2];
        { const int r = lane & 7, c = 2 * c2 + ((lane >> 3) & 1); ldsm_x2_t(bm, vbase + 12288 + jj * 1024 + c * 128 + r * 16); }
        mma16816(oa, pf[2][0], pf[2][1], 0u, 0u, bm[0], 0u);
        mma16816(ob, pf[2][0], pf[2][1], 0u, 0u, bm[1], 0u);
        ow[jj * 4 + c2][0] = pack_bf16(oa[0], oa[1]); ow[jj * 4 + c2][1] = pack_bf16(oa[2], oa[3]);
        ow[jj * 4 + c2][2] = pack_bf16(ob[0], ob[1]); ow[jj * 4 + c2][3] = pack_bf16(ob[2], ob[3]);
      }
    }
    bar_sync(1 + wg, 128);
    if ((threadIdx.x & 127) == 0) mbar_arrive(empty + 8 * (wg == 0 ? sA : sB));
    {
      const int row = (lane & 7) + 8 * ((lane >> 3) & 1);
#pragma unroll
      for (int i = 0; i < 12; i++) {
        const int chunk = (i >> 2) * 8 + 2 * (i & 3) + (lane >> 4);
        stsm_x4(ost + row * 384 + (((chunk & ~7) | ((chunk & 7) ^ (row & 7))) << 4), ow[i][0], ow[i][1], ow[i][2], ow[i][3]);
      }
      __syncwarp();
      uint4 v[12];
#pragma unroll
      for (int i = 0; i < 12; i++) {
        const int c = lane + 32 * i, r = c / 24, chunk = c % 24;
        v[i] = lds128(ost + r * 384 + (((chunk & ~7) | ((chunk & 7) ^ (r & 7))) << 4));
      }
#pragma unroll
      for (int i = 0; i < 12; i++) {
        const int c = lane + 32 * i, r = c / 24, chunk = c % 24;
        *(uint4*)(o + (size_t)(tok0 + r) * cfg::HD + head * 192 + chunk * 8) = v[i];
      }
      __syncwarp();
    }
    if (lane == 0) mbar_arrive(barKfree);
    pend = (unsigned*)(arena + AR_CNT + m * 4);
    TL_END(tl + 1);
    TL2((tl >= 12 ? 128 : 0) + 64 + m);
    TL_ACC(50, ti0);
  }
}
namespace bf {
constexpr int NS = 4, STAGE = 16384 + 36864;
constexpr int PHI_STR = 112, PHI_HEAD = 128 * PHI_STR;
constexpr int V_STR = 48, V_HEAD = 128 * V_STR;
constexpr int OFF_PHI = 0, OFF_V = 4 * PHI_HEAD, OFF_X = OFF_V + 4 * V_HEAD;
constexpr int OFF_WOT = 100352;
constexpr int OFF_OST = 65536;
constexpr int ANS = 4;
constexpr int OFF_BAR = OFF_WOT + 12 * 10240;
constexpr int SMEM = OFF_BAR + 256;
static_assert(OFF_X + 4 * 36 * 128 <= OFF_WOT && NS * STAGE <= OFF_BAR && SMEM <= 232448, "smem");
}
__device__ __forceinline__ void hedgehog_features(const float (&x)[6], int q4, float (&pos)[6], float (&neg)[6]) {
  const bool v2 = q4 < 2;
  float mx = fmaxf(fmaxf(x[0], x[1]), fmaxf(x[2], x[3])), mn = fminf(fminf(x[0], x[1]), fminf(x[2], x[3]));
  if (v2) { mx = fmaxf(mx, fmaxf(x[4], x[5])); mn = fminf(mn, fminf(x[4], x[5])); }
  mx = fmaxf(mx, __shfl_xor_sync(0xffffffffu, mx, 1)); mn = fminf(mn, __shfl_xor_sync(0xffffffffu, mn, 1));
  mx = fmaxf(mx, __shfl_xor_sync(0xffffffffu, mx, 2)); mn = fminf(mn, __shfl_xor_sync(0xffffffffu, mn, 2));
  const float L = 1.4426950408889634f;
  float sp = 0.f, sn = 0.f;
#pragma unroll
  for (int i = 0; i < 6; i++) {
    const bool ok = i < 4 || v2;
    pos[i] = ok ? ex2f((x[i] - mx) * L) : 0.f;
    neg[i] = ok ? ex2f((mn - x[i]) * L) : 0.f;
    sp += pos[i]; sn += neg[i];
  }
  sp += __shfl_xor_sync(0xffffffffu, sp, 1); sn += __shfl_xor_sync(0xffffffffu, sn, 1);
  sp += __shfl_xor_sync(0xffffffffu, sp, 2); sn += __shfl_xor_sync(0xffffffffu, sn, 2);
  const float ip = rcpf(sp), in_ = rcpf(sn);
#pragma unroll
  for (int i = 0; i < 6; i++) { pos[i] *= ip; neg[i] *= in_; }
}

__global__ void __launch_bounds__(384, 1) blayer_kernel(const __grid_constant__ CUtensorMap tmA, const __grid_constant__ CUtensorMap tmB,
                                                        const __grid_constant__ CUtensorMap tmO, const __grid_constant__ CUtensorMap tmW,
                                                        float* __restrict__ kvacc, unsigned* __restrict__ cnt, bf16* __restrict__ o2,
                                                        const bf16* __restrict__ xin, bf16* __restrict__ xout, int tl) {
  using namespace bf;
  TL_BEGIN(tl);
  extern __shared__ __align__(1024) unsigned char smem_raw[];
  const uint32_t sb = smem_u32(smem_raw);
  const int warp = threadIdx.x >> 5, lane = threadIdx.x & 31;
  const uint32_t full = sb + OFF_BAR, empty = full + 8 * NS, full2 = empty + 8 * NS, empty2 = full2 + 8 * ANS, barW = empty2 + 8 * ANS, barGo = barW + 8;
  const int m = blockIdx.x & 15, u = blockIdx.x >> 4;
  unsigned* cntKV = cnt + u; unsigned* cntO = cnt + 8 + m;
  if (threadIdx.x == 0) {
    for (int i = 0; i < NS; i++) { mbar_init(full + 8 * i, 1); mbar_init(empty + 8 * i, 2); }
    for (int i = 0; i < ANS; i++) { mbar_init(full2 + 8 * i, 1); mbar_init(empty2 + 8 * i, 2); }
    mbar_init(barW, 1); mbar_init(barGo, 1);
    asm volatile("fence.mbarrier_init.release.cluster;" ::: "memory");
  }
  __syncthreads();
  if (warp >= 8) {
    asm volatile("setmaxnreg.dec.sync.aligned.u32 40;");
    if (warp == 8 && lane == 0) {
      prefetch_tmap(&tmO); prefetch_tmap(&tmW);
      Pipe p{0, 1};
      for (int kb = 0; kb < 10; kb++) {
        mbar_wait(empty + 8 * p.stage, p.phase);
        const uint32_t st = sb + p.stage * STAGE, fb = full + 8 * p.stage;
        mbar_expect_tx(fb, STAGE);
        tma_load_2d(st, &tmA, kb * 64, m * 128, fb);
        tma_load_2d(st + 16384, &tmB, kb * 64, u * 288, fb);
        tma_load_2d(st + 16384 + 18432, &tmB, kb * 64, u * 288 + 144, fb);
        pipe_adv<NS>(p);
      }
      for (int i = 0; i < NS; i++) { mbar_wait(empty + 8 * p.stage, p.phase); pipe_adv<NS>(p); }
      mbar_expect_tx(barW, 12 * 10240);
      for (int kb = 0; kb < 12; kb++) tma_load_2d(sb + OFF_WOT + kb * 10240, &tmW, kb * 64, u * 80, barW);
      mbar_wait(barGo, 0);
      wait_ge(cntO, 8);
      fence_proxy_async_all();
      Pipe q{0, 1};
      for (int kb = 0; kb < 12; kb++) {
        mbar_wait(empty2 + 8 * q.stage, q.phase);
        mbar_expect_tx(full2 + 8 * q.stage, 16384);
        tma_load_2d(sb + q.stage * 16384, &tmO, kb * 64, m * 128, full2 + 8 * q.stage);
        pipe_adv<ANS>(q);
      }
    }
    return;
  }
  asm volatile("setmaxnreg.inc.sync.aligned.u32 232;");
  const int wg = warp >> 2, wi = warp & 3;
  const int g = lane >> 2, q4 = lane & 3;
  float a0[72], a1[72];
  {
    Pipe p{0, 0};
    uint32_t prev = 0;
    for (int kb = 0; kb < 10; kb++) {
      mbar_wait(full + 8 * p.stage, p.phase);
      const uint32_t st = sb + p.stage * STAGE;
      wgmma_fence();
#pragma unroll
      for (int kk = 0; kk < 4; kk++) {
        const uint64_t da = desc_kmajor(st + wg * 8192 + kk * 32);
        wgmma_n144<0, 0>(a0, da, desc_kmajor(st + 16384 + kk * 32), (kb | kk) != 0);
        wgmma_n144<0, 0>(a1, da, desc_kmajor(st + 16384 + 18432 + kk * 32), (kb | kk) != 0);
      }
      wgmma_commit();
      if (kb > 0) { wgmma_wait<1>(); if ((threadIdx.x & 127) == 0) mbar_arrive(empty + 8 * prev); }
      prev = p.stage;
      pipe_adv<NS>(p);
    }
    wgmma_wait<0>();
    bar_sync(1, 256);
    if ((threadIdx.x & 127) == 0) mbar_arrive(empty + 8 * prev);
  }
  TL2((tl >= 12 ? 128 : 0) + 32 + 0);
  auto ACC = [&](auto V, auto E) -> float { constexpr int v = V.value, e = E.value; if constexpr (v < 18) return a0[4 * v + e]; else return a1[4 * (v - 18) + e]; };
  const int trow = wg * 64 + wi * 16;
  const int srow = (lane & 7) + 8 * ((lane >> 3) & 1);
  uint32_t qf[4][3][4];
  static_for<0, 4>([&](auto HH) {
    constexpr int hh = HH.value;
    float xa[6], xb[6], pa[6], na[6], pb[6], nb[6];
    static_for<0, 3>([&](auto T) {
      constexpr int t = T.value; using V = IC<3 * hh + t>;
      xa[2 * t] = ACC(V{}, IC<0>{}); xa[2 * t + 1] = ACC(V{}, IC<1>{}); xb[2 * t] = ACC(V{}, IC<2>{}); xb[2 * t + 1] = ACC(V{}, IC<3>{});
      bf16r2(xa[2 * t], xa[2 * t + 1]); bf16r2(xb[2 * t], xb[2 * t + 1]);
    });
    hedgehog_features(xa, q4, pa, na);
    hedgehog_features(xb, q4, pb, nb);
    qf[hh][0][0] = pack_bf16(pa[0], pa[1]); qf[hh][0][1] = pack_bf16(pb[0], pb[1]); qf[hh][0][2] = pack_bf16(pa[2], pa[3]); qf[hh][0][3] = pack_bf16(pb[2], pb[3]);
    qf[hh][1][0] = pack_bf16(pa[4], pa[5]); qf[hh][1][1] = pack_bf16(pb[4], pb[5]); qf[hh][1][2] = pack_bf16(na[0], na[1]); qf[hh][1][3] = pack_bf16(nb[0], nb[1]);
    qf[hh][2][0] = pack_bf16(na[2], na[3]); qf[hh][2][1] = pack_bf16(nb[2], nb[3]); qf[hh][2][2] = pack_bf16(na[4], na[5]); qf[hh][2][3] = pack_bf16(nb[4], nb[5]);
    static_for<0, 3>([&](auto T) {
      constexpr int t = T.value; using V = IC<12 + 3 * hh + t>;
      xa[2 * t] = ACC(V{}, IC<0>{}); xa[2 * t + 1] = ACC(V{}, IC<1>{}); xb[2 * t] = ACC(V{}, IC<2>{}); xb[2 * t + 1] = ACC(V{}, IC<3>{});
      bf16r2(xa[2 * t], xa[2 * t + 1]); bf16r2(xb[2 * t], xb[2 * t + 1]);
    });
    hedgehog_features(xa, q4, pa, na);
    hedgehog_features(xb, q4, pb, nb);
    const uint32_t ph = sb + OFF_PHI + hh * PHI_HEAD + (trow + srow) * PHI_STR + (lane >> 4) * 16;
    stsm_x4(ph, pack_bf16(pa[0], pa[1]), pack_bf16(pb[0], pb[1]), pack_bf16(pa[2], pa[3]), pack_bf16(pb[2], pb[3]));
    stsm_x4(ph + 32, pack_bf16(pa[4], pa[5]), pack_bf16(pb[4], pb[5]), pack_bf16(na[0], na[1]), pack_bf16(nb[0], nb[1]));
    stsm_x4(ph + 64, pack_bf16(na[2], na[3]), pack_bf16(nb[2], nb[3]), pack_bf16(na[4], na[5]), pack_bf16(nb[4], nb[5]));
    using V0 = IC<24 + 3 * hh>; using V1 = IC<24 + 3 * hh + 1>; using V2 = IC<24 + 3 * hh + 2>;
    float c0 = ACC(V2{}, IC<0>{}), c1 = ACC(V2{}, IC<1>{}), c2 = ACC(V2{}, IC<2>{}), c3 = ACC(V2{}, IC<3>{});
    if (q4 == 2) { c0 = 1.f; c1 = 0.f; c2 = 1.f; c3 = 0.f; }
    if (q4 == 3) { c0 = c1 = c2 = c3 = 0.f; }
    const uint32_t va = sb + OFF_V + hh * V_HEAD + (trow + srow) * V_STR;
    stsm_x4(va + (lane >> 4) * 16, pack_bf16(ACC(V0{}, IC<0>{}), ACC(V0{}, IC<1>{})), pack_bf16(ACC(V0{}, IC<2>{}), ACC(V0{}, IC<3>{})),
            pack_bf16(ACC(V1{}, IC<0>{}), ACC(V1{}, IC<1>{})), pack_bf16(ACC(V1{}, IC<2>{}), ACC(V1{}, IC<3>{})));
    stsm_x2(va + 32, pack_bf16(c0, c1), pack_bf16(c2, c3));
  });
  bar_sync(1, 256);
  TL2((tl >= 12 ? 128 : 0) + 32 + 1);
  {
    const int hh = warp >> 1, th = warp & 1;
    float d[3][3][4];
#pragma unroll
    for (int a = 0; a < 3; a++)
#pragma unroll
      for (int b = 0; b < 3; b++) { d[a][b][0] = d[a][b][1] = d[a][b][2] = d[a][b][3] = 0.f; }
#pragma unroll
    for (int ks = 0; ks < 4; ks++) {
      const int t0 = th * 64 + ks * 16;
      const uint32_t pa = sb + OFF_PHI + hh * PHI_HEAD + (t0 + (lane & 7) + 8 * (lane >> 4)) * PHI_STR + ((lane >> 3) & 1) * 16;
      const uint32_t pv = sb + OFF_V + hh * V_HEAD + (t0 + (lane & 7) + 8 * ((lane >> 3) & 1)) * V_STR;
      uint32_t b01[4], b2[2];
      ldsm_x4_t(b01, pv + (lane >> 4) * 16);
      ldsm_x2_t(b2, pv + 32);
#pragma unroll
      for (int a = 0; a < 3; a++) {
        uint32_t af[4];
        ldsm_x4_t(af, pa + a * 32);
        mma16816(d[a][0], af[0], af[1], af[2], af[3], b01[0], b01[1]);
        mma16816(d[a][1], af[0], af[1], af[2], af[3], b01[2], b01[3]);
        mma16816(d[a][2], af[0], af[1], af[2], af[3], b2[0], b2[1]);
      }
    }
    const uint32_t xa = sb + OFF_X + hh * (36 * 128) + lane * 4;
    if (th == 1) {
#pragma unroll
      for (int a = 0; a < 3; a++)
#pragma unroll
        for (int b = 0; b < 3; b++)
#pragma unroll
          for (int e = 0; e < 4; e++)
            asm volatile("st.shared.f32 [%0], %1;" :: "r"(xa + ((a * 3 + b) * 4 + e) * 128), "f"(d[a][b][e]) : "memory");
    }
    bar_sync(2 + hh, 64);
    if (th == 0) {
      float* dst = kvacc + (size_t)(u * 4 + hh) * (48 * 24);
#pragma unroll
      for (int a = 0; a < 3; a++)
#pragma unroll
        for (int b = 0; b < 3; b++) {
          float y[4];
#pragma unroll
          for (int e = 0; e < 4; e++) {
            float o;
            asm volatile("ld.shared.f32 %0, [%1];" : "=f"(o) : "r"(xa + ((a * 3 + b) * 4 + e) * 128) : "memory");
            y[e] = d[a][b][e] + o;
          }
          const int f0 = 16 * a + g, dd = 8 * b + 2 * q4;
          if (dd < 22) {
            asm volatile("red.relaxed.gpu.global.add.v2.f32 [%0], {%1,%2};" :: "l"(dst + f0 * 24 + dd), "f"(y[0]), "f"(y[1]) : "memory");
            asm volatile("red.relaxed.gpu.global.add.v2.f32 [%0], {%1,%2};" :: "l"(dst + (f0 + 8) * 24 + dd), "f"(y[2]), "f"(y[3]) : "memory");
          }
        }
      __threadfence();
    }
  }
  TL2((tl >= 12 ? 128 : 0) + 32 + 2);
  bar_sync(1, 256);
  if (threadIdx.x == 0) { __threadfence(); atomicAdd(cntKV, 1u); wait_ge(cntKV, 16); }
  bar_sync(1, 256);
  TL2((tl >= 12 ? 128 : 0) + 32 + 3);
  {
    float t[5][4];
#pragma unroll
    for (int it = 0; it < 5; it++) {
      const int i = min((int)threadIdx.x + 256 * it, 4 * 9 * 32 - 1);
      const int hh = i / 288, r = i % 288, tt = r >> 5, l = r & 31, ks = tt / 3, nt = tt % 3;
      const float* src = kvacc + (size_t)(u * 4 + hh) * (48 * 24) + (16 * ks + 2 * (l & 3)) * 24 + 8 * nt + (l >> 2);
      t[it][0] = __ldcg(src); t[it][1] = __ldcg(src + 24); t[it][2] = __ldcg(src + 8 * 24); t[it][3] = __ldcg(src + 9 * 24);
    }
#pragma unroll
    for (int it = 0; it < 5; it++) {
      const int i = threadIdx.x + 256 * it;
      if (i < 4 * 9 * 32) sts64(sb + OFF_X + i * 8, pack_bf16(t[it][0], t[it][1]), pack_bf16(t[it][2], t[it][3]));
    }
  }
  bar_sync(1, 256);
  {
    const uint32_t ost = sb + warp * 3072;
    uint32_t ow[4][6];
#pragma unroll
    for (int hh = 0; hh < 4; hh++) {
      float d[3][4];
#pragma unroll
      for (int n = 0; n < 3; n++) {
        d[n][0] = d[n][1] = d[n][2] = d[n][3] = 0.f;
        const uint32_t kb = sb + OFF_X + hh * 2304 + n * 256 + lane * 8;
        const uint2 k0 = lds64(kb), k1 = lds64(kb + 768), k2 = lds64(kb + 1536);
        mma16816(d[n], qf[hh][0][0], qf[hh][0][1], qf[hh][0][2], qf[hh][0][3], k0.x, k0.y);
        mma16816(d[n], qf[hh][1][0], qf[hh][1][1], qf[hh][1][2], qf[hh][1][3], k1.x, k1.y);
        mma16816(d[n], qf[hh][2][0], qf[hh][2][1], qf[hh][2][2], qf[hh][2][3], k2.x, k2.y);
      }
      const float da = bf16r(bf16r(__shfl_sync(0xffffffffu, d[2][0], (lane & ~3) | 2)) + 1e-6f);
      const float db = bf16r(bf16r(__shfl_sync(0xffffffffu, d[2][2], (lane & ~3) | 2)) + 1e-6f);
      float y[3][4];
#pragma unroll
      for (int n = 0; n < 3; n++) {
        bf16r2(d[n][0], d[n][1]); bf16r2(d[n][2], d[n][3]);
        y[n][0] = __fdividef(d[n][0], da); y[n][1] = __fdividef(d[n][1], da);
        y[n][2] = __fdividef(d[n][2], db); y[n][3] = __fdividef(d[n][3], db);
      }
      if (q4 >= 2) { y[2][0] = y[2][1] = y[2][2] = y[2][3] = 0.f; }
#pragma unroll
      for (int n = 0; n < 3; n++) { ow[hh][2 * n] = pack_bf16(y[n][0], y[n][1]); ow[hh][2 * n + 1] = pack_bf16(y[n][2], y[n][3]); }
    }
#pragma unroll
    for (int hh = 0; hh < 4; hh++) {
      const uint32_t ra = ost + srow * 192 + hh * 48;
      stsm_x4(ra + (lane >> 4) * 16, ow[hh][0], ow[hh][1], ow[hh][2], ow[hh][3]);
      stsm_x2(ra + 32, ow[hh][4], ow[hh][5]);
    }
    __syncwarp();
#pragma unroll
    for (int i = 0; i < 6; i++) {
      const int c = lane + 32 * i, row = c / 12, chunk = c % 12;
      const uint4 v = lds128(ost + row * 192 + chunk * 16);
      *(uint4*)(o2 + (size_t)(m * 128 + trow + row) * 768 + u * 96 + chunk * 8) = v;
    }
  }
  __threadfence();
  bar_sync(1, 256);
  if (threadIdx.x == 0) { atomicAdd(cntO, 1u); mbar_arrive(barGo); }
  TL2((tl >= 12 ? 128 : 0) + 32 + 4);
  float acc[40];
  uint4 xr[5];
#pragma unroll
  for (int i = 0; i < 5; i++) {
    const int c = lane + 32 * i;
    xr[i] = *(const uint4*)(xin + (size_t)(m * 128 + trow + c / 10) * cfg::DM + u * 80 + (c % 10) * 8);
  }
  mbar_wait(barW, 0);
  {
    Pipe p{0, 0};
    uint32_t prev = 0;
    for (int kb = 0; kb < 12; kb++) {
      mbar_wait(full2 + 8 * p.stage, p.phase);
      wgmma_fence();
#pragma unroll
      for (int kk = 0; kk < 4; kk++)
        wgmma_n80<0, 0>(acc, desc_kmajor(sb + p.stage * 16384 + wg * 8192 + kk * 32), desc_kmajor(sb + OFF_WOT + kb * 10240 + kk * 32), (kb | kk) != 0);
      wgmma_commit();
      if (kb > 0) { wgmma_wait<1>(); if ((threadIdx.x & 127) == 0) mbar_arrive(empty2 + 8 * prev); }
      prev = p.stage;
      pipe_adv<ANS>(p);
    }
    wgmma_wait<0>();
  }
  TL2((tl >= 12 ? 128 : 0) + 32 + 5);
  {
    const uint32_t ost = sb + OFF_OST + warp * 3072;
#pragma unroll
    for (int v = 0; v < 10; v += 2)
      stsm_x4(ost + srow * 176 + (v + (lane >> 4)) * 16, pack_bf16(acc[4 * v], acc[4 * v + 1]), pack_bf16(acc[4 * v + 2], acc[4 * v + 3]),
              pack_bf16(acc[4 * v + 4], acc[4 * v + 5]), pack_bf16(acc[4 * v + 6], acc[4 * v + 7]));
    __syncwarp();
#pragma unroll
    for (int i = 0; i < 5; i++) {
      const int c = lane + 32 * i, row = c / 10, chunk = c % 10;
      const uint4 y = lds128(ost + row * 176 + chunk * 16);
      const size_t off = (size_t)(m * 128 + trow + row) * cfg::DM + u * 80 + chunk * 8;
      const uint4 x = xr[i];
      *(uint4*)(xout + off) = make_uint4(pack_bf16(bf_lo(x.x) + bf_lo(y.x), bf_hi(x.x) + bf_hi(y.x)), pack_bf16(bf_lo(x.y) + bf_lo(y.y), bf_hi(x.y) + bf_hi(y.y)),
                                         pack_bf16(bf_lo(x.z) + bf_lo(y.z), bf_hi(x.z) + bf_hi(y.z)), pack_bf16(bf_lo(x.w) + bf_lo(y.w), bf_hi(x.w) + bf_hi(y.w)));
    }
  }
  TL_END(tl);
}
__device__ __align__(32768) unsigned char g_arena[AR_SIZE];
__device__ __align__(1024) uint2 g_xh[2048 * 160];
__device__ __align__(1024) bf16 g_kx[2048 * 6144], g_vx[2048 * 6144], g_o[2048 * 6144];
__device__ __align__(1024) bf16 g_km[64 * 8 * 6144], g_vm[64 * 8 * 6144];
__device__ __align__(1024) bf16 g_xn[2048 * 640], g_xa[2048 * 640], g_xb[2048 * 640];
__device__ __align__(1024) float g_part[8 * 2048 * 640];
__device__ __align__(1024) bf16 g_wb[2304 * 640], g_wot[640 * 768], g_pq[2048 * 768];
__device__ __align__(1024) float g_kvacc[32 * 48 * 24 + 64];

typedef CUresult (*EncodeFn)(CUtensorMap*, CUtensorMapDataType, cuuint32_t, void*, const cuuint64_t*, const cuuint64_t*, const cuuint32_t*,
                             const cuuint32_t*, CUtensorMapInterleave, CUtensorMapSwizzle, CUtensorMapL2promotion, CUtensorMapFloatOOBfill);
static EncodeFn g_encode = nullptr;
static CUtensorMap make_map(const void* p, uint64_t cols, uint64_t rows, uint32_t bc, uint32_t br) {
  CUtensorMap m;
  cuuint64_t dims[2] = {cols, rows}, strides[1] = {cols * 2};
  cuuint32_t box[2] = {bc, br}, es[2] = {1, 1};
  g_encode(&m, CU_TENSOR_MAP_DATA_TYPE_BFLOAT16, 2, const_cast<void*>(p), dims, strides, box, es, CU_TENSOR_MAP_INTERLEAVE_NONE,
           CU_TENSOR_MAP_SWIZZLE_128B, CU_TENSOR_MAP_L2_PROMOTION_L2_256B, CU_TENSOR_MAP_FLOAT_OOB_FILL_NONE);
  return m;
}
template <class T> static T* sym(const T& s) { void* p = nullptr; cudaGetSymbolAddress(&p, s); return (T*)p; }

struct Ptrs {
  unsigned char* arena; bf16 *kx, *vx, *o, *km, *vm, *xn, *xa, *xb, *wb, *wot, *pq; float *part, *kvacc; uint2* xh;
};

extern "C" void kernel_launch(void* const* d_in, const int* in_sizes, int n_in, void* d_out, int out_size) {
  const bf16* x = (const bf16*)d_in[0];
  const bf16* mem0 = (const bf16*)d_in[1];
  const bf16 *Wq = (const bf16*)d_in[2], *Wk = (const bf16*)d_in[3], *Wv = (const bf16*)d_in[4], *Wo = (const bf16*)d_in[5];
  const bf16 *wqkv = (const bf16*)d_in[8], *wphi = (const bf16*)d_in[9], *wo = (const bf16*)d_in[10];
  bf16* out = (bf16*)d_out;
  static Ptrs P; static bool init = false;
  if (!init) {
    void* fn = nullptr; cudaDriverEntryPointQueryResult qr;
    cudaGetDriverEntryPoint("cuTensorMapEncodeTiled", &fn, cudaEnableDefault, &qr);
    g_encode = (EncodeFn)fn;
    void* p;
    cudaGetSymbolAddress(&p, g_arena); P.arena = (unsigned char*)p;
    cudaGetSymbolAddress(&p, g_kx); P.kx = (bf16*)p;   cudaGetSymbolAddress(&p, g_vx); P.vx = (bf16*)p;
    cudaGetSymbolAddress(&p, g_o); P.o = (bf16*)p;     cudaGetSymbolAddress(&p, g_km); P.km = (bf16*)p;
    cudaGetSymbolAddress(&p, g_vm); P.vm = (bf16*)p;   cudaGetSymbolAddress(&p, g_xn); P.xn = (bf16*)p;
    cudaGetSymbolAddress(&p, g_xa); P.xa = (bf16*)p;   cudaGetSymbolAddress(&p, g_xb); P.xb = (bf16*)p;
    cudaGetSymbolAddress(&p, g_wb); P.wb = (bf16*)p;   cudaGetSymbolAddress(&p, g_wot); P.wot = (bf16*)p;
    cudaGetSymbolAddress(&p, g_pq); P.pq = (bf16*)p;   cudaGetSymbolAddress(&p, g_part); P.part = (float*)p;
    cudaGetSymbolAddress(&p, g_kvacc); P.kvacc = (float*)p;
    cudaGetSymbolAddress(&p, g_xh); P.xh = (uint2*)p;
    cudaFuncSetAttribute(chain_kernel, cudaFuncAttributeMaxDynamicSharedMemorySize, ch::SMEM);
    cudaFuncSetAttribute(trail_kernel, cudaFuncAttributeMaxDynamicSharedMemorySize, tr::SMEM);
    cudaFuncSetAttribute(blayer_kernel, cudaFuncAttributeMaxDynamicSharedMemorySize, bf::SMEM);
    init = true;
  }
  const CUtensorMap tmXn = make_map(P.xn, 640, 2048, 64, 128);
  const CUtensorMap tmWq = make_map(Wq, 6144, 640, 64, 64), tmWk = make_map(Wk, 6144, 640, 64, 64), tmWv = make_map(Wv, 6144, 640, 64, 64);
  const CUtensorMap tmO = make_map(P.o, 6144, 2048, 64, 128), tmWo = make_map(Wo, 640, 6144, 64, 64);
  const CUtensorMap tmWb = make_map(P.wb, 640, 2304, 64, 144), tmO2 = make_map(P.pq, 768, 2048, 64, 128), tmWot = make_map(P.wot, 768, 640, 64, 80);

  ChainArgs ca;
  ca.Wo = Wo; ca.xh = P.xh; ca.mem0 = mem0; ca.kx = P.kx; ca.vx = P.vx; ca.km = P.km; ca.vm = P.vm;
  ca.arena = P.arena; ca.dbg = nullptr; ca.tl = 0;
  uint4* zar = (uint4*)P.arena; const int nzar = AR_SIZE / 16;
  uint4* zkv = (uint4*)P.kvacc; const int nzkv = (32 * 48 * 24 + 64) / 4;

  const PrepArgs pa{wqkv, wphi, wo, P.wb, P.wot};
  const bf16* xcur = x;
  for (int layer = 0; layer < 2; layer++) {
    const int tl = layer * 12;
    ln_kernel<0><<<layer == 0 ? 256 + PREP_BLOCKS : 256, 256>>>(xcur, nullptr, nullptr, P.xn, P.xh, zar, nzar, nullptr, 0, pa, tl + 0);
    ca.tl = tl + 2;
    chain_kernel<<<96, 384, ch::SMEM>>>(ca, tmWq, tmWk, tmWv);
    {
      cudaLaunchConfig_t lc = {};
      lc.gridDim = dim3(132); lc.blockDim = dim3(384); lc.dynamicSmemBytes = tr::SMEM; lc.stream = cudaStreamPerThread;
      cudaLaunchAttribute at[1];
      at[0].id = cudaLaunchAttributeProgrammaticStreamSerialization; at[0].val.programmaticStreamSerializationAllowed = 1;
      lc.attrs = at; lc.numAttrs = 1;
      cudaLaunchKernelEx(&lc, trail_kernel, tmXn, tmWq, tmO, tmWo, (const bf16*)P.kx, (const bf16*)P.vx, (const bf16*)P.km, (const bf16*)P.vm, P.o, P.part, P.arena, tl + 4);
    }
    ln_kernel<4><<<256, 256>>>(xcur, P.part, P.xa, P.xn, nullptr, nullptr, 0, zkv, nzkv, pa, tl + 6);
    blayer_kernel<<<128, 384, bf::SMEM>>>(tmXn, tmWb, tmO2, tmWot, P.kvacc, (unsigned*)(P.kvacc + 32 * 48 * 24), P.pq, P.xa, layer == 0 ? P.xb : out, tl + 7);
    xcur = P.xb;
  }
}
```

```cpp
#include <cuda_runtime.h>
#include <cuda.h>
#include <cuda_bf16.h>
#include <stdint.h>
#include <type_traits>

typedef __nv_bfloat16 bf16;

namespace cfg {
constexpr int S = 2048, DM = 640, H = 32, DH = 192, NSEG = 64, SEG = 32, NM = 8;
constexpr int HD = H * DH;
}

__device__ __forceinline__ uint32_t smem_u32(const void* p) { return (uint32_t)__cvta_generic_to_shared(p); }
__device__ __forceinline__ uint32_t mapa_u32(uint32_t a, uint32_t r) {
  uint32_t o; asm("mapa.shared::cluster.u32 %0, %1, %2;" : "=r"(o) : "r"(a), "r"(r)); return o;
}
__device__ __forceinline__ void mbar_init(uint32_t b, uint32_t c) {
  asm volatile("mbarrier.init.shared::cta.b64 [%0], %1;" :: "r"(b), "r"(c) : "memory");
}
__device__ __forceinline__ void mbar_expect_tx(uint32_t b, uint32_t bytes) {
  asm volatile("mbarrier.arrive.expect_tx.shared::cta.b64 _, [%0], %1;" :: "r"(b), "r"(bytes) : "memory");
}
__device__ __forceinline__ void mbar_arrive(uint32_t b) {
  asm volatile("mbarrier.arrive.shared::cta.b64 _, [%0];" :: "r"(b) : "memory");
}
__device__ __forceinline__ bool mbar_try(uint32_t b, uint32_t ph) {
  uint32_t p;
  asm volatile("{.reg .pred p; mbarrier.try_wait.parity.shared::cta.b64 p, [%1], %2; selp.u32 %0, 1, 0, p;}"
               : "=r"(p) : "r"(b), "r"(ph) : "memory");
  return p;
}
__device__ __forceinline__ bool mbar_try_cluster(uint32_t b, uint32_t ph) {
  uint32_t p;
  asm volatile("{.reg .pred p; mbarrier.try_wait.parity.acquire.cluster.shared::cta.b64 p, [%1], %2; selp.u32 %0, 1, 0, p;}"
               : "=r"(p) : "r"(b), "r"(ph) : "memory");
  return p;
}
#define SPIN_LIMIT (1 << 22)
__device__ __forceinline__ void mbar_wait(uint32_t b, uint32_t ph) {
  asm volatile("{\n.reg .pred p, q;\n.reg .u32 c;\nmov.u32 c, 0;\n"
               "W_%=:\nmbarrier.try_wait.parity.shared::cta.b64 p, [%0], %1;\n@p bra D_%=;\n"
               "add.u32 c, c, 1;\nsetp.lt.u32 q, c, %2;\n@q bra W_%=;\nD_%=:\n}"
               :: "r"(b), "r"(ph), "n"(SPIN_LIMIT) : "memory");
}
__device__ __forceinline__ void mbar_spin(uint32_t b, uint32_t ph) {
  asm volatile("{\n.reg .pred p, q;\n.reg .u32 c;\nmov.u32 c, 0;\n"
               "W_%=:\nmbarrier.test_wait.parity.shared::cta.b64 p, [%0], %1;\n@p bra D_%=;\n"
               "add.u32 c, c, 1;\nsetp.lt.u32 q, c, %2;\n@q bra W_%=;\nD_%=:\n}"
               :: "r"(b), "r"(ph), "n"(SPIN_LIMIT) : "memory");
}
#define PIN(x) asm volatile("" : "+r"(x))
__device__ __forceinline__ void mbar_wait_cluster(uint32_t b, uint32_t ph) {
  int s = 0;
  while (!mbar_try_cluster(b, ph)) { if (++s > SPIN_LIMIT) break; }
}
__device__ __forceinline__ void st_async_v2(uint32_t a, uint32_t x, uint32_t y, uint32_t mb) {
  asm volatile("st.async.weak.shared::cluster.mbarrier::complete_tx::bytes.v2.b32 [%0], {%1,%2}, [%3];"
               :: "r"(a), "r"(x), "r"(y), "r"(mb) : "memory");
}
__device__ __forceinline__ void st_async_v4(uint32_t a, uint32_t x, uint32_t y, uint32_t z, uint32_t w, uint32_t mb) {
  asm volatile("st.async.weak.shared::cluster.mbarrier::complete_tx::bytes.v4.b32 [%0], {%1,%2,%3,%4}, [%5];"
               :: "r"(a), "r"(x), "r"(y), "r"(z), "r"(w), "r"(mb) : "memory");
}
__device__ __forceinline__ void bulk_g2s(uint32_t dst, const void* src, uint32_t bytes, uint32_t mb) {
  asm volatile("cp.async.bulk.shared::cluster.global.mbarrier::complete_tx::bytes [%0], [%1], %2, [%3];"
               :: "r"(dst), "l"(src), "r"(bytes), "r"(mb) : "memory");
}
__device__ __forceinline__ void cp_async16(uint32_t dst, const void* src) {
  asm volatile("cp.async.cg.shared.global [%0], [%1], 16;" :: "r"(dst), "l"(src) : "memory");
}
__device__ __forceinline__ void cp_async_wait_all() { asm volatile("cp.async.wait_all;" ::: "memory"); }
__device__ __forceinline__ void fence_proxy_async() { asm volatile("fence.proxy.async.shared::cta;" ::: "memory"); }
__device__ __forceinline__ void bar_sync(int id, int n) { asm volatile("bar.sync %0, %1;" :: "r"(id), "r"(n) : "memory"); }
__device__ __forceinline__ void bar_arrive(int id, int n) { asm volatile("bar.arrive %0, %1;" :: "r"(id), "r"(n) : "memory"); }
__device__ __forceinline__ void cluster_sync_all() {
  asm volatile("barrier.cluster.arrive.release.aligned; barrier.cluster.wait.acquire.aligned;" ::: "memory");
}
__device__ __forceinline__ void ldsm_x4(uint32_t (&r)[4], uint32_t a) {
  asm volatile("ldmatrix.sync.aligned.m8n8.x4.shared.b16 {%0,%1,%2,%3}, [%4];"
               : "=r"(r[0]), "=r"(r[1]), "=r"(r[2]), "=r"(r[3]) : "r"(a) : "memory");
}
__device__ __forceinline__ void ldsm_x4_t(uint32_t (&r)[4], uint32_t a) {
  asm volatile("ldmatrix.sync.aligned.m8n8.x4.trans.shared.b16 {%0,%1,%2,%3}, [%4];"
               : "=r"(r[0]), "=r"(r[1]), "=r"(r[2]), "=r"(r[3]) : "r"(a) : "memory");
}
template <int IMM> __device__ __forceinline__ void ldsm_x4_i(uint32_t (&r)[4], uint32_t a) {
  asm volatile("ldmatrix.sync.aligned.m8n8.x4.shared.b16 {%0,%1,%2,%3}, [%4+%5];"
               : "=r"(r[0]), "=r"(r[1]), "=r"(r[2]), "=r"(r[3]) : "r"(a), "n"(IMM) : "memory");
}
template <int IMM> __device__ __forceinline__ void ldsm_x4_t_i(uint32_t (&r)[4], uint32_t a) {
  asm volatile("ldmatrix.sync.aligned.m8n8.x4.trans.shared.b16 {%0,%1,%2,%3}, [%4+%5];"
               : "=r"(r[0]), "=r"(r[1]), "=r"(r[2]), "=r"(r[3]) : "r"(a), "n"(IMM) : "memory");
}
template <int IMM> __device__ __forceinline__ uint4 lds128_i(uint32_t a) {
  uint4 v; asm volatile("ld.shared.v4.u32 {%0,%1,%2,%3}, [%4+%5];" : "=r"(v.x), "=r"(v.y), "=r"(v.z), "=r"(v.w) : "r"(a), "n"(IMM) : "memory"); return v;
}
template <int IMM> __device__ __forceinline__ uint2 lds64_i(uint32_t a) {
  uint2 v; asm volatile("ld.shared.v2.u32 {%0,%1}, [%2+%3];" : "=r"(v.x), "=r"(v.y) : "r"(a), "n"(IMM) : "memory"); return v;
}
template <int IMM> __device__ __forceinline__ void sts128_i(uint32_t a, uint32_t x, uint32_t y, uint32_t z, uint32_t w) {
  asm volatile("st.shared.v4.u32 [%0+%5], {%1,%2,%3,%4};" :: "r"(a), "r"(x), "r"(y), "r"(z), "r"(w), "n"(IMM) : "memory");
}
template <int IMM> __device__ __forceinline__ void sts64_i(uint32_t a, uint32_t x, uint32_t y) {
  asm volatile("st.shared.v2.u32 [%0+%3], {%1,%2};" :: "r"(a), "r"(x), "r"(y), "n"(IMM) : "memory");
}
template <int IMM> __device__ __forceinline__ void st_async_v2_i(uint32_t a, uint32_t x, uint32_t y, uint32_t mb) {
  asm volatile("st.async.weak.shared::cluster.mbarrier::complete_tx::bytes.v2.b32 [%0+%4], {%1,%2}, [%3];"
               :: "r"(a), "r"(x), "r"(y), "r"(mb), "n"(IMM) : "memory");
}
template <int IMM> __device__ __forceinline__ uint4 ld_relaxed_v4_i(const void* p) {
  uint4 v; asm volatile("ld.relaxed.gpu.global.v4.u32 {%0,%1,%2,%3}, [%4+%5];" : "=r"(v.x), "=r"(v.y), "=r"(v.z), "=r"(v.w) : "l"(p), "n"(IMM) : "memory"); return v;
}
template <int I, int N, class F> __device__ __forceinline__ void static_for(F&& f) {
  if constexpr (I < N) { f(std::integral_constant<int, I>{}); static_for<I + 1, N>(f); }
}
__device__ __forceinline__ uint32_t movm_t(uint32_t a) {
  uint32_t d; asm volatile("movmatrix.sync.aligned.m8n8.trans.b16 %0, %1;" : "=r"(d) : "r"(a)); return d;
}
__device__ __forceinline__ void mma16816(float (&d)[4], uint32_t a0, uint32_t a1, uint32_t a2, uint32_t a3, uint32_t b0, uint32_t b1) {
  asm volatile("mma.sync.aligned.m16n8k16.row.col.f32.bf16.bf16.f32 {%0,%1,%2,%3}, {%4,%5,%6,%7}, {%8,%9}, {%0,%1,%2,%3};"
               : "+f"(d[0]), "+f"(d[1]), "+f"(d[2]), "+f"(d[3]) : "r"(a0), "r"(a1), "r"(a2), "r"(a3), "r"(b0), "r"(b1));
}
__device__ __forceinline__ uint32_t pack_bf16(float lo, float hi) {
  uint32_t d; asm("cvt.rn.bf16x2.f32 %0, %1, %2;" : "=r"(d) : "f"(hi), "f"(lo)); return d;
}
__device__ __forceinline__ float bf_lo(uint32_t w) { return __uint_as_float(w << 16); }
__device__ __forceinline__ float bf_hi(uint32_t w) { return __uint_as_float(w & 0xffff0000u); }
__device__ __forceinline__ uint4 lds128(uint32_t a) {
  uint4 v; asm volatile("ld.shared.v4.u32 {%0,%1,%2,%3}, [%4];" : "=r"(v.x), "=r"(v.y), "=r"(v.z), "=r"(v.w) : "r"(a) : "memory"); return v;
}
__device__ __forceinline__ uint2 lds64(uint32_t a) {
  uint2 v; asm volatile("ld.shared.v2.u32 {%0,%1}, [%2];" : "=r"(v.x), "=r"(v.y) : "r"(a) : "memory"); return v;
}
__device__ __forceinline__ void sts128(uint32_t a, uint32_t x, uint32_t y, uint32_t z, uint32_t w) {
  asm volatile("st.shared.v4.u32 [%0], {%1,%2,%3,%4};" :: "r"(a), "r"(x), "r"(y), "r"(z), "r"(w) : "memory");
}
__device__ __forceinline__ void sts64(uint32_t a, uint32_t x, uint32_t y) {
  asm volatile("st.shared.v2.u32 [%0], {%1,%2};" :: "r"(a), "r"(x), "r"(y) : "memory");
}
__device__ __forceinline__ uint4 ld_relaxed_v4(const void* p) {
  uint4 v; asm volatile("ld.relaxed.gpu.global.v4.u32 {%0,%1,%2,%3}, [%4];" : "=r"(v.x), "=r"(v.y), "=r"(v.z), "=r"(v.w) : "l"(p) : "memory"); return v;
}
__device__ __forceinline__ uint32_t ld_relaxed_u32(const void* p) {
  uint32_t v; asm volatile("ld.relaxed.gpu.global.u32 %0, [%1];" : "=r"(v) : "l"(p) : "memory"); return v;
}
__device__ __forceinline__ void st_relaxed_v2(void* p, uint32_t a, uint32_t b) {
  asm volatile("st.relaxed.gpu.global.v2.u32 [%0], {%1,%2};" :: "l"(p), "r"(a), "r"(b) : "memory");
}
__device__ __forceinline__ void st_relaxed_u32(void* p, uint32_t v) {
  asm volatile("st.relaxed.gpu.global.u32 [%0], %1;" :: "l"(p), "r"(v) : "memory");
}
__device__ __forceinline__ uint32_t clk32() { uint32_t c; asm volatile("mov.u32 %0, %%clock;" : "=r"(c) :: "memory"); return c; }
__device__ __forceinline__ uint32_t clkdep(uint32_t v) {
  uint32_t c; asm volatile("{.reg .pred p; setp.eq.u32 p, %1, 0xdeadbeef; @p trap; mov.u32 %0, %%clock;}" : "=r"(c) : "r"(v) : "memory"); return c;
}
__device__ __forceinline__ void wgmma_fence() { asm volatile("wgmma.fence.sync.aligned;" ::: "memory"); }
__device__ __forceinline__ void wgmma_commit() { asm volatile("wgmma.commit_group.sync.aligned;" ::: "memory"); }
template <int N> __device__ __forceinline__ void wgmma_wait() { asm volatile("wgmma.wait_group.sync.aligned %0;" :: "n"(N) : "memory"); }
__device__ __forceinline__ void wgmma_n8_ss_ta(float (&d)[4], uint64_t da, uint64_t db, int acc) {
  asm volatile("{\n.reg .pred p;\nsetp.ne.b32 p, %6, 0;\n"
               "wgmma.mma_async.sync.aligned.m64n8k16.f32.bf16.bf16 {%0,%1,%2,%3}, %4, %5, p, 1, 1, 1, 0;\n}\n"
               : "+f"(d[0]), "+f"(d[1]), "+f"(d[2]), "+f"(d[3]) : "l"(da), "l"(db), "r"(acc));
}
__device__ __forceinline__ uint64_t make_desc(uint32_t saddr, uint32_t lbo_bytes, uint32_t sbo_bytes, uint32_t swz) {
  return (uint64_t)((saddr & 0x3FFFF) >> 4) | ((uint64_t)(lbo_bytes >> 4) << 16) | ((uint64_t)(sbo_bytes >> 4) << 32) | ((uint64_t)swz << 62);
}

__device__ __forceinline__ void tma_load_2d(uint32_t dst, const CUtensorMap* tm, int c0, int c1, uint32_t mb) {
  asm volatile("cp.async.bulk.tensor.2d.shared::cluster.global.mbarrier::complete_tx::bytes [%0], [%1, {%3, %4}], [%2];"
               :: "r"(dst), "l"(tm), "r"(mb), "r"(c0), "r"(c1) : "memory");
}
__device__ __forceinline__ void bulk_s2g(void* dst, uint32_t src, uint32_t bytes) {
  asm volatile("cp.async.bulk.global.shared::cta.bulk_group [%0], [%1], %2;" :: "l"(dst), "r"(src), "r"(bytes) : "memory");
}
__device__ __forceinline__ uint64_t policy_evict_first() {
  uint64_t p; asm volatile("createpolicy.fractional.L2::evict_first.b64 %0, 1.0;" : "=l"(p)); return p;
}
__device__ __forceinline__ void bulk_s2g_hint(void* dst, uint32_t src, uint32_t bytes, uint64_t pol) {
  asm volatile("cp.async.bulk.global.shared::cta.bulk_group.L2::cache_hint [%0], [%1], %2, %3;" :: "l"(dst), "r"(src), "r"(bytes), "l"(pol) : "memory");
}
__device__ __forceinline__ void bulk_commit() { asm volatile("cp.async.bulk.commit_group;" ::: "memory"); }
template <int N> __device__ __forceinline__ void bulk_wait_read() { asm volatile("cp.async.bulk.wait_group.read %0;" :: "n"(N) : "memory"); }
template <int N> __device__ __forceinline__ void bulk_wait() { asm volatile("cp.async.bulk.wait_group %0;" :: "n"(N) : "memory"); }
__device__ __forceinline__ void stsm_x4(uint32_t a, uint32_t r0, uint32_t r1, uint32_t r2, uint32_t r3) {
  asm volatile("stmatrix.sync.aligned.m8n8.x4.shared.b16 [%0], {%1,%2,%3,%4};" :: "r"(a), "r"(r0), "r"(r1), "r"(r2), "r"(r3) : "memory");
}
__device__ __forceinline__ void stsm_x2(uint32_t a, uint32_t r0, uint32_t r1) {
  asm volatile("stmatrix.sync.aligned.m8n8.x2.shared.b16 [%0], {%1,%2};" :: "r"(a), "r"(r0), "r"(r1) : "memory");
}
__device__ __forceinline__ void ldsm_x2(uint32_t (&r)[2], uint32_t a) {
  asm volatile("ldmatrix.sync.aligned.m8n8.x2.shared.b16 {%0,%1}, [%2];" : "=r"(r[0]), "=r"(r[1]) : "r"(a) : "memory");
}
__device__ __forceinline__ void ldsm_x2_t(uint32_t (&r)[2], uint32_t a) {
  asm volatile("ldmatrix.sync.aligned.m8n8.x2.trans.shared.b16 {%0,%1}, [%2];" : "=r"(r[0]), "=r"(r[1]) : "r"(a) : "memory");
}
__device__ __forceinline__ float bf16r(float x) { return __uint_as_float(pack_bf16(0.f, x) & 0xffff0000u); }
__device__ __forceinline__ void bf16r2(float& a, float& b) { const uint32_t w = pack_bf16(a, b); a = bf_lo(w); b = bf_hi(w); }
__device__ __forceinline__ float rcpf(float x) { float r; asm("rcp.approx.ftz.f32 %0, %1;" : "=f"(r) : "f"(x)); return r; }
__device__ __forceinline__ float ex2f(float x) { float e; asm("ex2.approx.ftz.f32 %0, %1;" : "=f"(e) : "f"(x)); return e; }
__device__ __forceinline__ void prefetch_tmap(const CUtensorMap* tm) { asm volatile("prefetch.tensormap [%0];" :: "l"(tm) : "memory"); }

#define TL_ACC(idx, t0)
#define TL_NOW() 0ull
#define TL2(idx)
#define TL_BEGIN(id)
#define TL_END(id)
template <int TA, int TB> __device__ __forceinline__ void wgmma_n192(float (&d)[96], uint64_t da, uint64_t db, int acc) {
  asm volatile("{\n.reg .pred p;\nsetp.ne.b32 p, %98, 0;\n"
    "wgmma.mma_async.sync.aligned.m64n192k16.f32.bf16.bf16 {%0, %1, %2, %3, %4, %5, %6, %7, %8, %9, %10, %11, %12, %13, %14, %15, %16, %17, %18, %19, %20, %21, %22, %23, %24, %25, %26, %27, %28, %29, %30, %31, %32, %33, %34, %35, %36, %37, %38, %39, %40, %41, %42, %43, %44, %45, %46, %47, %48, %49, %50, %51, %52, %53, %54, %55, %56, %57, %58, %59, %60, %61, %62, %63, %64, %65, %66, %67, %68, %69, %70, %71, %72, %73, %74, %75, %76, %77, %78, %79, %80, %81, %82, %83, %84, %85, %86, %87, %88, %89, %90, %91, %92, %93, %94, %95}, %96, %97, p, 1, 1, %99, %100;\n}\n"
    : "+f"(d[0]), "+f"(d[1]), "+f"(d[2]), "+f"(d[3]), "+f"(d[4]), "+f"(d[5]), "+f"(d[6]), "+f"(d[7]), "+f"(d[8]), "+f"(d[9]), "+f"(d[10]), "+f"(d[11]), "+f"(d[12]), "+f"(d[13]), "+f"(d[14]), "+f"(d[15]), "+f"(d[16]), "+f"(d[17]), "+f"(d[18]), "+f"(d[19]), "+f"(d[20]), "+f"(d[21]), "+f"(d[22]), "+f"(d[23]), "+f"(d[24]), "+f"(d[25]), "+f"(d[26]), "+f"(d[27]), "+f"(d[28]), "+f"(d[29]), "+f"(d[30]), "+f"(d[31]), "+f"(d[32]), "+f"(d[33]), "+f"(d[34]), "+f"(d[35]), "+f"(d[36]), "+f"(d[37]), "+f"(d[38]), "+f"(d[39]), "+f"(d[40]), "+f"(d[41]), "+f"(d[42]), "+f"(d[43]), "+f"(d[44]), "+f"(d[45]), "+f"(d[46]), "+f"(d[47]), "+f"(d[48]), "+f"(d[49]), "+f"(d[50]), "+f"(d[51]), "+f"(d[52]), "+f"(d[53]), "+f"(d[54]), "+f"(d[55]), "+f"(d[56]), "+f"(d[57]), "+f"(d[58]), "+f"(d[59]), "+f"(d[60]), "+f"(d[61]), "+f"(d[62]), "+f"(d[63]), "+f"(d[64]), "+f"(d[65]), "+f"(d[66]), "+f"(d[67]), "+f"(d[68]), "+f"(d[69]), "+f"(d[70]), "+f"(d[71]), "+f"(d[72]), "+f"(d[73]), "+f"(d[74]), "+f"(d[75]), "+f"(d[76]), "+f"(d[77]), "+f"(d[78]), "+f"(d[79]), "+f"(d[80]), "+f"(d[81]), "+f"(d[82]), "+f"(d[83]), "+f"(d[84]), "+f"(d[85]), "+f"(d[86]), "+f"(d[87]), "+f"(d[88]), "+f"(d[89]), "+f"(d[90]), "+f"(d[91]), "+f"(d[92]), "+f"(d[93]), "+f"(d[94]), "+f"(d[95])
    : "l"(da), "l"(db), "r"(acc), "n"(TA), "n"(TB));
}

template <int TA, int TB> __device__ __forceinline__ void wgmma_n256(float (&d)[128], uint64_t da, uint64_t db, int acc) {
  asm volatile("{\n.reg .pred p;\nsetp.ne.b32 p, %130, 0;\n"
    "wgmma.mma_async.sync.aligned.m64n256k16.f32.bf16.bf16 {%0, %1, %2, %3, %4, %5, %6, %7, %8, %9, %10, %11, %12, %13, %14, %15, %16, %17, %18, %19, %20, %21, %22, %23, %24, %25, %26, %27, %28, %29, %30, %31, %32, %33, %34, %35, %36, %37, %38, %39, %40, %41, %42, %43, %44, %45, %46, %47, %48, %49, %50, %51, %52, %53, %54, %55, %56, %57, %58, %59, %60, %61, %62, %63, %64, %65, %66, %67, %68, %69, %70, %71, %72, %73, %74, %75, %76, %77, %78, %79, %80, %81, %82, %83, %84, %85, %86, %87, %88, %89, %90, %91, %92, %93, %94, %95, %96, %97, %98, %99, %100, %101, %102, %103, %104, %105, %106, %107, %108, %109, %110, %111, %112, %113, %114, %115, %116, %117, %118, %119, %120, %121, %122, %123, %124, %125, %126, %127}, %128, %129, p, 1, 1, %131, %132;\n}\n"
    : "+f"(d[0]), "+f"(d[1]), "+f"(d[2]), "+f"(d[3]), "+f"(d[4]), "+f"(d[5]), "+f"(d[6]), "+f"(d[7]), "+f"(d[8]), "+f"(d[9]), "+f"(d[10]), "+f"(d[11]), "+f"(d[12]), "+f"(d[13]), "+f"(d[14]), "+f"(d[15]), "+f"(d[16]), "+f"(d[17]), "+f"(d[18]), "+f"(d[19]), "+f"(d[20]), "+f"(d[21]), "+f"(d[22]), "+f"(d[23]), "+f"(d[24]), "+f"(d[25]), "+f"(d[26]), "+f"(d[27]), "+f"(d[28]), "+f"(d[29]), "+f"(d[30]), "+f"(d[31]), "+f"(d[32]), "+f"(d[33]), "+f"(d[34]), "+f"(d[35]), "+f"(d[36]), "+f"(d[37]), "+f"(d[38]), "+f"(d[39]), "+f"(d[40]), "+f"(d[41]), "+f"(d[42]), "+f"(d[43]), "+f"(d[44]), "+f"(d[45]), "+f"(d[46]), "+f"(d[47]), "+f"(d[48]), "+f"(d[49]), "+f"(d[50]), "+f"(d[51]), "+f"(d[52]), "+f"(d[53]), "+f"(d[54]), "+f"(d[55]), "+f"(d[56]), "+f"(d[57]), "+f"(d[58]), "+f"(d[59]), "+f"(d[60]), "+f"(d[61]), "+f"(d[62]), "+f"(d[63]), "+f"(d[64]), "+f"(d[65]), "+f"(d[66]), "+f"(d[67]), "+f"(d[68]), "+f"(d[69]), "+f"(d[70]), "+f"(d[71]), "+f"(d[72]), "+f"(d[73]), "+f"(d[74]), "+f"(d[75]), "+f"(d[76]), "+f"(d[77]), "+f"(d[78]), "+f"(d[79]), "+f"(d[80]), "+f"(d[81]), "+f"(d[82]), "+f"(d[83]), "+f"(d[84]), "+f"(d[85]), "+f"(d[86]), "+f"(d[87]), "+f"(d[88]), "+f"(d[89]), "+f"(d[90]), "+f"(d[91]), "+f"(d[92]), "+f"(d[93]), "+f"(d[94]), "+f"(d[95]), "+f"(d[96]), "+f"(d[97]), "+f"(d[98]), "+f"(d[99]), "+f"(d[100]), "+f"(d[101]), "+f"(d[102]), "+f"(d[103]), "+f"(d[104]), "+f"(d[105]), "+f"(d[106]), "+f"(d[107]), "+f"(d[108]), "+f"(d[109]), "+f"(d[110]), "+f"(d[111]), "+f"(d[112]), "+f"(d[113]), "+f"(d[114]), "+f"(d[115]), "+f"(d[116]), "+f"(d[117]), "+f"(d[118]), "+f"(d[119]), "+f"(d[120]), "+f"(d[121]), "+f"(d[122]), "+f"(d[123]), "+f"(d[124]), "+f"(d[125]), "+f"(d[126]), "+f"(d[127])
    : "l"(da), "l"(db), "r"(acc), "n"(TA), "n"(TB));
}

template <int TA, int TB> __device__ __forceinline__ void wgmma_n64(float (&d)[32], uint64_t da, uint64_t db, int acc) {
  asm volatile("{\n.reg .pred p;\nsetp.ne.b32 p, %34, 0;\n"
    "wgmma.mma_async.sync.aligned.m64n64k16.f32.bf16.bf16 {%0, %1, %2, %3, %4, %5, %6, %7, %8, %9, %10, %11, %12, %13, %14, %15, %16, %17, %18, %19, %20, %21, %22, %23, %24, %25, %26, %27, %28, %29, %30, %31}, %32, %33, p, 1, 1, %35, %36;\n}\n"
    : "+f"(d[0]), "+f"(d[1]), "+f"(d[2]), "+f"(d[3]), "+f"(d[4]), "+f"(d[5]), "+f"(d[6]), "+f"(d[7]), "+f"(d[8]), "+f"(d[9]), "+f"(d[10]), "+f"(d[11]), "+f"(d[12]), "+f"(d[13]), "+f"(d[14]), "+f"(d[15]), "+f"(d[16]), "+f"(d[17]), "+f"(d[18]), "+f"(d[19]), "+f"(d[20]), "+f"(d[21]), "+f"(d[22]), "+f"(d[23]), "+f"(d[24]), "+f"(d[25]), "+f"(d[26]), "+f"(d[27]), "+f"(d[28]), "+f"(d[29]), "+f"(d[30]), "+f"(d[31])
    : "l"(da), "l"(db), "r"(acc), "n"(TA), "n"(TB));
}

template <int TA, int TB> __device__ __forceinline__ void wgmma_n80(float (&d)[40], uint64_t da, uint64_t db, int acc) {
  asm volatile("{\n.reg .pred p;\nsetp.ne.b32 p, %42, 0;\n"
    "wgmma.mma_async.sync.aligned.m64n80k16.f32.bf16.bf16 {%0, %1, %2, %3, %4, %5, %6, %7, %8, %9, %10, %11, %12, %13, %14, %15, %16, %17, %18, %19, %20, %21, %22, %23, %24, %25, %26, %27, %28, %29, %30, %31, %32, %33, %34, %35, %36, %37, %38, %39}, %40, %41, p, 1, 1, %43, %44;\n}\n"
    : "+f"(d[0]), "+f"(d[1]), "+f"(d[2]), "+f"(d[3]), "+f"(d[4]), "+f"(d[5]), "+f"(d[6]), "+f"(d[7]), "+f"(d[8]), "+f"(d[9]), "+f"(d[10]), "+f"(d[11]), "+f"(d[12]), "+f"(d[13]), "+f"(d[14]), "+f"(d[15]), "+f"(d[16]), "+f"(d[17]), "+f"(d[18]), "+f"(d[19]), "+f"(d[20]), "+f"(d[21]), "+f"(d[22]), "+f"(d[23]), "+f"(d[24]), "+f"(d[25]), "+f"(d[26]), "+f"(d[27]), "+f"(d[28]), "+f"(d[29]), "+f"(d[30]), "+f"(d[31]), "+f"(d[32]), "+f"(d[33]), "+f"(d[34]), "+f"(d[35]), "+f"(d[36]), "+f"(d[37]), "+f"(d[38]), "+f"(d[39])
    : "l"(da), "l"(db), "r"(acc), "n"(TA), "n"(TB));
}

template <int TA, int TB> __device__ __forceinline__ void wgmma_n144(float (&d)[72], uint64_t da, uint64_t db, int acc) {
  asm volatile("{\n.reg .pred p;\nsetp.ne.b32 p, %74, 0;\n"
    "wgmma.mma_async.sync.aligned.m64n144k16.f32.bf16.bf16 {%0, %1, %2, %3, %4, %5, %6, %7, %8, %9, %10, %11, %12, %13, %14, %15, %16, %17, %18, %19, %20, %21, %22, %23, %24, %25, %26, %27, %28, %29, %30, %31, %32, %33, %34, %35, %36, %37, %38, %39, %40, %41, %42, %43, %44, %45, %46, %47, %48, %49, %50, %51, %52, %53, %54, %55, %56, %57, %58, %59, %60, %61, %62, %63, %64, %65, %66, %67, %68, %69, %70, %71}, %72, %73, p, 1, 1, %75, %76;\n}\n"
    : "+f"(d[0]), "+f"(d[1]), "+f"(d[2]), "+f"(d[3]), "+f"(d[4]), "+f"(d[5]), "+f"(d[6]), "+f"(d[7]), "+f"(d[8]), "+f"(d[9]), "+f"(d[10]), "+f"(d[11]), "+f"(d[12]), "+f"(d[13]), "+f"(d[14]), "+f"(d[15]), "+f"(d[16]), "+f"(d[17]), "+f"(d[18]), "+f"(d[19]), "+f"(d[20]), "+f"(d[21]), "+f"(d[22]), "+f"(d[23]), "+f"(d[24]), "+f"(d[25]), "+f"(d[26]), "+f"(d[27]), "+f"(d[28]), "+f"(d[29]), "+f"(d[30]), "+f"(d[31]), "+f"(d[32]), "+f"(d[33]), "+f"(d[34]), "+f"(d[35]), "+f"(d[36]), "+f"(d[37]), "+f"(d[38]), "+f"(d[39]), "+f"(d[40]), "+f"(d[41]), "+f"(d[42]), "+f"(d[43]), "+f"(d[44]), "+f"(d[45]), "+f"(d[46]), "+f"(d[47]), "+f"(d[48]), "+f"(d[49]), "+f"(d[50]), "+f"(d[51]), "+f"(d[52]), "+f"(d[53]), "+f"(d[54]), "+f"(d[55]), "+f"(d[56]), "+f"(d[57]), "+f"(d[58]), "+f"(d[59]), "+f"(d[60]), "+f"(d[61]), "+f"(d[62]), "+f"(d[63]), "+f"(d[64]), "+f"(d[65]), "+f"(d[66]), "+f"(d[67]), "+f"(d[68]), "+f"(d[69]), "+f"(d[70]), "+f"(d[71])
    : "l"(da), "l"(db), "r"(acc), "n"(TA), "n"(TB));
}

template <int TA, int TB> __device__ __forceinline__ void wgmma_n128(float (&d)[64], uint64_t da, uint64_t db, int acc) {
  asm volatile("{\n.reg .pred p;\nsetp.ne.b32 p, %66, 0;\n"
    "wgmma.mma_async.sync.aligned.m64n128k16.f32.bf16.bf16 {%0, %1, %2, %3, %4, %5, %6, %7, %8, %9, %10, %11, %12, %13, %14, %15, %16, %17, %18, %19, %20, %21, %22, %23, %24, %25, %26, %27, %28, %29, %30, %31, %32, %33, %34, %35, %36, %37, %38, %39, %40, %41, %42, %43, %44, %45, %46, %47, %48, %49, %50, %51, %52, %53, %54, %55, %56, %57, %58, %59, %60, %61, %62, %63}, %64, %65, p, 1, 1, %67, %68;\n}\n"
    : "+f"(d[0]), "+f"(d[1]), "+f"(d[2]), "+f"(d[3]), "+f"(d[4]), "+f"(d[5]), "+f"(d[6]), "+f"(d[7]), "+f"(d[8]), "+f"(d[9]), "+f"(d[10]), "+f"(d[11]), "+f"(d[12]), "+f"(d[13]), "+f"(d[14]), "+f"(d[15]), "+f"(d[16]), "+f"(d[17]), "+f"(d[18]), "+f"(d[19]), "+f"(d[20]), "+f"(d[21]), "+f"(d[22]), "+f"(d[23]), "+f"(d[24]), "+f"(d[25]), "+f"(d[26]), "+f"(d[27]), "+f"(d[28]), "+f"(d[29]), "+f"(d[30]), "+f"(d[31]), "+f"(d[32]), "+f"(d[33]), "+f"(d[34]), "+f"(d[35]), "+f"(d[36]), "+f"(d[37]), "+f"(d[38]), "+f"(d[39]), "+f"(d[40]), "+f"(d[41]), "+f"(d[42]), "+f"(d[43]), "+f"(d[44]), "+f"(d[45]), "+f"(d[46]), "+f"(d[47]), "+f"(d[48]), "+f"(d[49]), "+f"(d[50]), "+f"(d[51]), "+f"(d[52]), "+f"(d[53]), "+f"(d[54]), "+f"(d[55]), "+f"(d[56]), "+f"(d[57]), "+f"(d[58]), "+f"(d[59]), "+f"(d[60]), "+f"(d[61]), "+f"(d[62]), "+f"(d[63])
    : "l"(da), "l"(db), "r"(acc), "n"(TA), "n"(TB));
}

template <int OFF16, int ACC> __device__ __forceinline__ void wgmma_rs_n32(float (&d)[16], uint32_t a0, uint32_t a1, uint32_t a2, uint32_t a3, uint32_t dlo) {
  asm volatile("{\n.reg .pred p;\n.reg .b32 t;\n.reg .b64 db;\nsetp.ne.b32 p, %22, 0;\nadd.u32 t, %20, %21;\nmov.b64 db, {t, 0x40000040};\n"
    "wgmma.mma_async.sync.aligned.m64n32k16.f32.bf16.bf16 {%0, %1, %2, %3, %4, %5, %6, %7, %8, %9, %10, %11, %12, %13, %14, %15}, {%16, %17, %18, %19}, db, p, 1, 1, 0;\n}\n"
    : "+f"(d[0]), "+f"(d[1]), "+f"(d[2]), "+f"(d[3]), "+f"(d[4]), "+f"(d[5]), "+f"(d[6]), "+f"(d[7]), "+f"(d[8]), "+f"(d[9]), "+f"(d[10]), "+f"(d[11]), "+f"(d[12]), "+f"(d[13]), "+f"(d[14]), "+f"(d[15])
    : "r"(a0), "r"(a1), "r"(a2), "r"(a3), "r"(dlo), "n"(OFF16), "n"(ACC));
}

constexpr uint32_t AR_ACC = 0;
constexpr uint32_t AR_TAB = 0x100000;
constexpr uint32_t AR_PROG = 0x101000;
constexpr uint32_t AR_CNT = 0x102000;
constexpr uint32_t AR_QUEUE = 0x103000;
constexpr uint32_t AR_SIZE = 0x104000;

struct ChainArgs {
  const bf16* mem0;
  const uint2* xh;
  unsigned char *kg, *vg;
  unsigned char* arena;
  uint32_t* dbg;
  int tl;
};

namespace ch {
constexpr int OFF_WQ = 0;
constexpr int OFF_X = 81920;
constexpr int OFF_MEM = OFF_X + 40960;
constexpr int OFF_WO = OFF_MEM + 10240;
constexpr int WOK = 8 * 896;
constexpr int OFF_KV = OFF_WO + 10 * WOK;
constexpr int KVB = 5120;
constexpr int OFF_O = OFF_KV + 4 * KVB;
constexpr int OFF_Q = OFF_O + 1024;
constexpr int OFF_S = OFF_O + 3072;
constexpr int OFF_SR = OFF_S + 1280;
constexpr int OFF_BAR = OFF_SR + 1536;
constexpr int SMEM = OFF_BAR + 128 + 1152;
static_assert(SMEM <= 232448, "smem");
constexpr int MB_S = OFF_BAR, MB_O = OFF_BAR + 8, MB_X = OFF_BAR + 16;
constexpr int MB_K = OFF_SR + 1408, MB_V = MB_K + 16, MB_Q = MB_K + 32, MB_R = MB_K + 48;
constexpr int SC_IN = OFF_BAR + 64;
constexpr int SC_MX = OFF_S;
constexpr int SC_W = OFF_BAR + 96;
constexpr int WOS = 448;
enum { B_MEM0 = 1, B_QK, B_SL, B_V, B_O, B_RED, B_X, B_C, B_H, B_MEM1, B_A, B_G };
#define NQ1 6
#define NQ0 4
#define NP0 4
#define NWO 5
#define NWP 4
#define NB0 2
#define BBS 100
#define VSYNC 0
#define XPOS 0
#define XPD 300
#define WOF 0
#define XBYTES 36864
#define NRT 7
#define NRF 2
#define NPM0 2
#define NPM1 2
#define RSYNC 1
#define PFK 1
#define PA0 7
#define PA1 0
#define PB0 7
#define PB1 5
#define PQE 0
#define XT 30
static_assert(NPM0 >= 2 && NPM1 >= 2, "the K / V blocks live in the last two k-steps of Wo");
}

#define CHAIN_TIMING 0
#define TS(i)
#define TSV(i, v)
#define TS_SETUP()
#define POLL_DELAY 500
#define XN 40
#define PF0 8
#define PFS 3
#define XDELAY 0
#define NOKM 0
#define PUB_REL 1
template <int V> using IC = std::integral_constant<int, V>;
__device__ __forceinline__ uint32_t clk_v() { uint64_t c; asm volatile("mov.u64 %0, %%clock64;" : "=l"(c) :: "memory"); return (uint32_t)c; }
__device__ __forceinline__ int fresh(int x) { int y; asm volatile("shfl.sync.bfly.b32 %0, %1, 0, 0x1f, 0xffffffff;" : "=r"(y) : "r"(x)); return y; }
#define SFENCE2(x, d) asm volatile("{\n.reg .pred p;\nsetp.eq.u32 p, %0, 0x7fffffff;\n@p st.shared.u32 [%0], %1;\n}" :: "r"(x), "r"(d) : "memory")
#define SFENCE(x) asm volatile("{\n.reg .pred p;\nsetp.eq.u32 p, %0, 0x7fffffff;\n@p st.shared.u32 [%0], %0;\n}" :: "r"(x) : "memory")
template <int I> __device__ __forceinline__ void bbfence(uint32_t x) {
  asm volatile("{\n.reg .pred p;\nsetp.eq.u32 p, %0, %1;\nL_%=:\n@p st.volatile.shared.u32 [%0], %0;\n@p bra.uni L_%=;\n}" :: "r"(x), "n"(4 * I) : "memory");
}
__device__ __forceinline__ float uniform_f(float x) { return __uint_as_float(__reduce_max_sync(0xffffffffu, __float_as_uint(x))); }

__device__ __forceinline__ void mma16816h(float (&d)[4], const uint32_t (&a)[4], uint32_t b0, uint32_t b1) {
  asm volatile("mma.sync.aligned.m16n8k16.row.col.f32.f16.f16.f32 {%0,%1,%2,%3}, {%4,%5,%6,%7}, {%8,%9}, {%0,%1,%2,%3};"
               : "+f"(d[0]), "+f"(d[1]), "+f"(d[2]), "+f"(d[3]) : "r"(a[0]), "r"(a[1]), "r"(a[2]), "r"(a[3]), "r"(b0), "r"(b1));
}
__device__ __forceinline__ void mma1688(float (&d)[4], uint32_t a0, uint32_t a1, uint32_t b0) {
  asm volatile("mma.sync.aligned.m16n8k8.row.col.f32.bf16.bf16.f32 {%0,%1,%2,%3}, {%4,%5}, {%6}, {%0,%1,%2,%3};"
               : "+f"(d[0]), "+f"(d[1]), "+f"(d[2]), "+f"(d[3]) : "r"(a0), "r"(a1), "r"(b0));
}
template <int OFF16, int ACC> __device__ __forceinline__ void wgmma_rs32h(float (&d)[16], const uint32_t (&a)[4], uint32_t dlo) {
  asm volatile("{\n.reg .pred p;\n.reg .b32 t;\n.reg .b64 db;\nsetp.ne.b32 p, %22, 0;\nadd.u32 t, %20, %21;\nmov.b64 db, {t, 0x40000040};\n"
    "wgmma.mma_async.sync.aligned.m64n32k16.f32.f16.f16 {%0,%1,%2,%3,%4,%5,%6,%7,%8,%9,%10,%11,%12,%13,%14,%15}, {%16,%17,%18,%19}, db, p, 1, 1, 0;\n}\n"
    : "+f"(d[0]), "+f"(d[1]), "+f"(d[2]), "+f"(d[3]), "+f"(d[4]), "+f"(d[5]), "+f"(d[6]), "+f"(d[7]), "+f"(d[8]), "+f"(d[9]), "+f"(d[10]), "+f"(d[11]),
      "+f"(d[12]), "+f"(d[13]), "+f"(d[14]), "+f"(d[15])
    : "r"(a[0]), "r"(a[1]), "r"(a[2]), "r"(a[3]), "r"(dlo), "n"(OFF16), "n"(ACC));
}
template <int IMM> __device__ __forceinline__ void stsm_x4_t_i(uint32_t a, uint32_t r0, uint32_t r1, uint32_t r2, uint32_t r3) {
  asm volatile("stmatrix.sync.aligned.m8n8.x4.trans.shared.b16 [%0+%5], {%1,%2,%3,%4};" :: "r"(a), "r"(r0), "r"(r1), "r"(r2), "r"(r3), "n"(IMM) : "memory");
}
template <int IMM> __device__ __forceinline__ void stsm_x2_t_i(uint32_t a, uint32_t r0, uint32_t r1) {
  asm volatile("stmatrix.sync.aligned.m8n8.x2.trans.shared.b16 [%0+%3], {%1,%2};" :: "r"(a), "r"(r0), "r"(r1), "n"(IMM) : "memory");
}
template <int IMM> __device__ __forceinline__ void st_async_b32_i(uint32_t a, uint32_t x, uint32_t mb) {
  asm volatile("st.async.weak.shared::cluster.mbarrier::complete_tx::bytes.b32 [%0+%3], %1, [%2];" :: "r"(a), "r"(x), "r"(mb), "n"(IMM) : "memory");
}
template <int IMM> __device__ __forceinline__ void ld_relaxed_v4_if(uint4& v, const void* p, uint32_t c) {
  asm volatile("{\n.reg .pred p;\nsetp.ne.u32 p, %6, 0;\n@p ld.relaxed.gpu.global.v4.u32 {%0,%1,%2,%3}, [%4+%5];\n}"
               : "+r"(v.x), "+r"(v.y), "+r"(v.z), "+r"(v.w) : "l"(p), "n"(IMM), "r"(c) : "memory");
}
template <int IMM> __device__ __forceinline__ uint32_t lds32_i(uint32_t a) {
  uint32_t v; asm volatile("ld.shared.u32 %0, [%1+%2];" : "=r"(v) : "r"(a), "n"(IMM) : "memory"); return v;
}
__device__ __forceinline__ void sts32(uint32_t a, uint32_t v) { asm volatile("st.shared.u32 [%0], %1;" :: "r"(a), "r"(v) : "memory"); }
__device__ __forceinline__ uint32_t pack_f16(float lo, float hi) {
  uint32_t d; asm("cvt.rn.f16x2.f32 %0, %1, %2;" : "=r"(d) : "f"(hi), "f"(lo)); return d;
}
__device__ __forceinline__ uint32_t amax_bf2(uint32_t a, uint32_t b) { uint32_t d; asm("max.xorsign.abs.bf16x2 %0, %1, %2;" : "=r"(d) : "r"(a), "r"(b)); return d; }
__device__ __forceinline__ uint32_t amax_h2(uint32_t a, uint32_t b) { uint32_t d; asm("max.xorsign.abs.f16x2 %0, %1, %2;" : "=r"(d) : "r"(a), "r"(b)); return d; }
__device__ __forceinline__ uint32_t amax_fold(uint32_t m) { return __reduce_max_sync(0xffffffffu, max(m & 0x7fffu, (m >> 16) & 0x7fffu)); }
__device__ __forceinline__ int wscale_exp(uint32_t m) { return min(141 - (int)(m >> 7), 100); }
__device__ __forceinline__ float exp2i(int e) { return __uint_as_float((uint32_t)(e + 127) << 23); }
__device__ __forceinline__ uint32_t bf2_to_h2(uint32_t w, float sc) { return pack_f16(bf_lo(w) * sc, bf_hi(w) * sc); }
__device__ __forceinline__ void bf2_to_h2_inplace(uint32_t& w, uint32_t sc2) {
  asm volatile("{\n.reg .b32 t, lo, hi;\nmul.rn.bf16x2 t, %0, %1;\nshl.b32 lo, t, 16;\nand.b32 hi, t, 0xffff0000;\ncvt.rn.f16x2.f32 %0, hi, lo;\n}" : "+r"(w) : "r"(sc2));
}
__device__ __forceinline__ void prefetch_l2(const void* p, uint32_t bytes) { asm volatile("cp.async.bulk.prefetch.L2.global [%0], %1;" :: "l"(p), "r"(bytes) : "memory"); }
__device__ __forceinline__ void prefetch_tma_2d(const CUtensorMap* tm, int c0, int c1) {
  asm volatile("cp.async.bulk.prefetch.tensor.2d.L2.global [%0, {%1, %2}];" :: "l"(tm), "r"(c0), "r"(c1) : "memory");
}
__host__ __device__ constexpr uint32_t acc_voff(int v) { return v < 4 ? v * 1024u : (v == 4 ? 128u : 3072u + 128u); }
__device__ __forceinline__ int unit28(int i) { return i == 3 ? 54 : 14 * i; }
__device__ __forceinline__ int unit24(int i) { return i < 2 ? 48 - 6 * i : 56 + 6 * i; }
__device__ __forceinline__ uint32_t acc_step(int s) { return (s >> 1) * 32768 + (s & 1) * 512; }
__device__ __forceinline__ uint32_t acc_lane(int i, int lane) { return ((lane >> 3) & 1) * 256 + (lane >> 4) * 4096 + i * 8192 + (lane & 7) * 16; }

__device__ __forceinline__ uint32_t ld_acquire_u32(const void* p) {
  uint32_t v; asm volatile("ld.acquire.gpu.global.u32 %0, [%1];" : "=r"(v) : "l"(p) : "memory"); return v;
}
__device__ __forceinline__ void ln_row(const uint2 (&xw)[5], int row, int lane, bf16* __restrict__ xn, uint2* __restrict__ xh) {
  float v[20];
#pragma unroll
  for (int i = 0; i < 5; i++) { v[4 * i] = bf_lo(xw[i].x); v[4 * i + 1] = bf_hi(xw[i].x); v[4 * i + 2] = bf_lo(xw[i].y); v[4 * i + 3] = bf_hi(xw[i].y); }
  float s = 0.f;
#pragma unroll
  for (int i = 0; i < 20; i++) s += v[i];
#pragma unroll
  for (int o = 16; o; o >>= 1) s += __shfl_xor_sync(0xffffffffu, s, o);
  const float mean = s * (1.f / cfg::DM);
  float q = 0.f;
#pragma unroll
  for (int i = 0; i < 20; i++) { const float d = v[i] - mean; q += d * d; }
#pragma unroll
  for (int o = 16; o; o >>= 1) q += __shfl_xor_sync(0xffffffffu, q, o);
  const float mb = bf16r(mean), var = bf16r(q * (1.f / cfg::DM));
  const float den = bf16r(sqrtf(bf16r(var + 1e-5f)));
#pragma unroll
  for (int i = 0; i < 5; i++) {
    float y[4];
#pragma unroll
    for (int e = 0; e < 4; e++) y[e] = __fdividef(bf16r(v[4 * i + e] - mb), den);
    const uint32_t w0 = pack_bf16(y[0], y[1]), w1 = pack_bf16(y[2], y[3]);
    *(uint2*)(xn + (size_t)row * cfg::DM + i * 128 + lane * 4) = make_uint2(w0, w1);
    if (xh) xh[(((size_t)(row >> 5) * 10 + 2 * i + (lane >> 4)) * 32 + (row & 31)) * 16 + ((((lane >> 1) & 7) ^ (row & 7)) << 1) + (lane & 1)] =
        make_uint2(pack_f16(bf_lo(w0), bf_hi(w0)), pack_f16(bf_lo(w1), bf_hi(w1)));
  }
}

__global__ void __cluster_dims__(3, 1, 1) __launch_bounds__(384, 1) chain_kernel(const ChainArgs a, const __grid_constant__ CUtensorMap tmWq,
    const __grid_constant__ CUtensorMap tmWk, const __grid_constant__ CUtensorMap tmWv, const __grid_constant__ CUtensorMap tmWo) {
  using namespace ch;
  extern __shared__ __align__(1024) unsigned char smem_raw[];
  const uint32_t sb = smem_u32(smem_raw);
  const int warp = __shfl_sync(0xffffffffu, (int)threadIdx.x >> 5, 0);
  const int lane = __shfl_sync(0xffffffffu, (int)threadIdx.x & 31, threadIdx.x & 31);
  const int cta = blockIdx.x, h = cta / 3, j = cta % 3;
  const int g = lane >> 2, q4 = lane & 3, r8 = lane & 7, m4 = lane >> 3;
  unsigned char* const arena = a.arena;
  if (sb & 1023u) __trap();
  TL_BEGIN(a.tl);
  const int col0 = j == 0 ? 0 : (j == 1 ? 224 : 432);
  auto stage_w = [&](const CUtensorMap* tm, uint32_t dst, uint32_t mb, int half) {
    mbar_expect_tx(mb + 8 * half, 40960);
    tma_load_2d(dst + half * 40960, tm, h * cfg::DH + j * 64, half * 320, mb + 8 * half);
    tma_load_2d(dst + half * 40960 + 20480, tm, h * cfg::DH + j * 64, half * 320 + 160, mb + 8 * half);
  };
  if (threadIdx.x == 256) {
    for (int i = 0; i < 9; i++) mbar_init(sb + MB_K + 8 * i, 1);
    mbar_init(sb + MB_S, 1); mbar_init(sb + MB_O, 1); mbar_init(sb + MB_X, 1);
    asm volatile("fence.mbarrier_init.release.cluster;" ::: "memory");
    for (int i = 0; i < 2; i++) { stage_w(&tmWk, sb + OFF_WQ, sb + MB_K, i); stage_w(&tmWv, sb + OFF_WO, sb + MB_V, i); }
    sts32(sb + SC_W, 0); sts32(sb + SC_W + 4, 0); sts32(sb + SC_W + 8, 0); sts32(sb + SC_IN + 12, 0); sts32(sb + SC_IN + 20, 0);
    mbar_expect_tx(sb + MB_S, 1280); mbar_expect_tx(sb + MB_O, 2048);
  }
  __syncthreads();
  asm volatile("barrier.cluster.arrive.relaxed.aligned;" ::: "memory");
  const uint32_t d1 = mapa_u32(sb, (j + 1) % 3) - sb, d2 = mapa_u32(sb, (j + 2) % 3) - sb;

  if (warp >= 8) {
    asm volatile("setmaxnreg.dec.sync.aligned.u32 40;");
    const int hw = warp - 8, ht = hw * 32 + lane;
    const bool lead = ht == 0;
    auto stage_wo = [&](int i) {
      mbar_expect_tx(sb + MB_R + 8 * i, 64 * WOS);
      tma_load_2d(sb + OFF_WO + i * 64 * WOS, &tmWo, col0, h * cfg::DH + ((i + j) % 3) * 64, sb + MB_R + 8 * i);
    };
    const unsigned char* xg = (const unsigned char*)a.xh;
    auto issue_x = [&](int s) { mbar_expect_tx(sb + MB_X, 40960); bulk_g2s(sb + OFF_X, xg + (size_t)s * 40960, 40960, sb + MB_X); };
    uint4 v[5];
#pragma unroll
    for (int i = 0; i < 5; i++) { const int c = ht + 128 * i; v[i] = ld_relaxed_v4(a.mem0 + (c & 7) * cfg::DM + (c >> 3) * 8); }
    if (hw == 2) {
      asm volatile("griddepcontrol.wait;" ::: "memory");
      asm volatile("griddepcontrol.launch_dependents;" ::: "memory");
      if (lane == 0) issue_x(0);
    }
    if (hw == 0) {
      bar_sync(B_QK, 160); if (lane == 0) stage_w(&tmWq, sb + OFF_WQ, sb + MB_Q, 0);
      bar_sync(B_SL, 160); if (lane == 0) stage_w(&tmWq, sb + OFF_WQ, sb + MB_Q, 1);
    }
    if (hw == 1) {
      bar_sync(B_V, 160); if (lane == 0) stage_wo(0);
      bar_sync(B_O, 160); if (lane == 0) { stage_wo(1); stage_wo(2); }
    }
    __syncwarp();
    {
      uint32_t m = 0;
#pragma unroll
      for (int i = 0; i < 5; i++) {
        m = amax_bf2(amax_bf2(m, amax_bf2(v[i].x, v[i].y)), amax_bf2(v[i].z, v[i].w));
      }
      m = amax_fold(m);
      if (lane == 0) sts32(sb + SC_MX + hw * 4, m);
      bar_sync(B_H, 128);
      const uint4 mm = lds128(sb + SC_MX);
      const int se = max(wscale_exp(max(max(mm.x, mm.y), max(mm.z, mm.w))), -100);
      const float sc = exp2i(se);
#pragma unroll
      for (int i = 0; i < 5; i++) {
        const int c = ht + 128 * i, t = c & 7, chn = c >> 3;
        sts128(sb + OFF_MEM + chn * 128 + ((t ^ (2 * (chn & 3))) << 4), bf2_to_h2(v[i].x, sc), bf2_to_h2(v[i].y, sc), bf2_to_h2(v[i].z, sc), bf2_to_h2(v[i].w, sc));
      }
      if (lead) { sts32(sb + SC_IN, __float_as_uint(exp2i(-se))); sts32(sb + SC_IN + 4, 0x7800u); }
    }
    {
      const uint32_t p0 = sb + OFF_WQ + hw * 2048 + lane * 16;
      uint32_t m = 0;
#pragma unroll 1
      for (int i = 0; i < 10; i++) {
        if (i == 0 || i == 5) mbar_wait(sb + MB_Q + (i ? 8 : 0), 0);
        uint32_t r[4][4];
        static_for<0, 4>([&](auto K) { ldsm_x4_i<K.value * 512>(r[K.value], p0 + i * 8192); });
#pragma unroll
        for (int k = 0; k < 4; k++) m = amax_bf2(amax_bf2(m, amax_bf2(r[k][0], r[k][1])), amax_bf2(r[k][2], r[k][3]));
      }
      m = amax_fold(m);
      if (lane == 0) asm volatile("red.shared.max.u32 [%0], %1;" :: "r"(sb + SC_W + 8), "r"(m) : "memory");
      bar_sync(B_H, 128);
      const uint32_t sc = (uint32_t)(wscale_exp(lds32_i<SC_W + 8>(sb)) + 127) * 0x00800080u;
#pragma unroll 1
      for (int i = 0; i < 10; i++) {
        uint32_t r[4][4];
        static_for<0, 4>([&](auto K) { ldsm_x4_i<K.value * 512>(r[K.value], p0 + i * 8192); });
#pragma unroll
        for (int k = 0; k < 4; k++) {
          bf2_to_h2_inplace(r[k][0], sc); bf2_to_h2_inplace(r[k][1], sc); bf2_to_h2_inplace(r[k][2], sc); bf2_to_h2_inplace(r[k][3], sc);
          stsm_x4(p0 + i * 8192 + k * 512, r[k][0], r[k][1], r[k][2], r[k][3]);
        }
      }
    }
    bar_sync(0, 384);
    if (lead) st_relaxed_u32(arena + AR_TAB + cta * 4, 0x80000000u | (lds32_i<SC_W>(sb) << 15) | lds32_i<SC_W + 4>(sb));
    asm volatile("barrier.cluster.wait.aligned;" ::: "memory");
    bar_sync(B_MEM0, 256); bar_sync(B_MEM1, 256);
    {
      uint32_t v0, v1, v2; int spin = 0;
      do {
        v0 = ld_relaxed_u32(arena + AR_TAB + lane * 4); v1 = ld_relaxed_u32(arena + AR_TAB + 128 + lane * 4); v2 = ld_relaxed_u32(arena + AR_TAB + 256 + lane * 4);
      } while (__any_sync(0xffffffffu, ((v0 & v1 & v2) >> 31) == 0) && ++spin < SPIN_LIMIT);
      const uint32_t mv = (max(max(v0, v1), v2) >> 15) & 0x7fffu, mo = max(max(v0 & 0x7fffu, v1 & 0x7fffu), v2 & 0x7fffu);
      sts32(sb + SC_IN + 8 + (lane & 1) * 16, 15 - ((__reduce_max_sync(0xffffffffu, mv) >> 7) + (__reduce_max_sync(0xffffffffu, mo) >> 7) - 252 + 22));
    }

    auto store_kv = [&](int s) {
      const size_t o = ((size_t)s * 96 + cta) * KVB; const uint32_t src = sb + OFF_KV + (s & 1) * (2 * KVB);
      fence_proxy_async(); bulk_s2g(a.kg + o, src, KVB); bulk_s2g(a.vg + o, src + KVB, KVB); bulk_commit();
    };
    const int cb28 = unit28(hw), du = (unit24(hw) - cb28) * 128;
    int ln = lane;
#pragma unroll 1
    for (int s = 0; s < cfg::NSEG; s++) {
      TS_SETUP();
      const bool last = s == cfg::NSEG - 1;
      if (ln == 0) {
        if (hw == 2 && !last) issue_x(s + 1);
        if (hw == 0 && s > 0) store_kv(s - 1);
      }
      __syncwarp();
      if (last) break;
      const uint32_t kv = (s & 1) * (2 * KVB);
      ln = fresh(ln);
      uint32_t kb0[4], kb1[4];
      { const uint32_t ka = sb + kv + hw * 128 + (ln >> 3) * 640 + (ln & 7) * 16; ldsm_x4_i<OFF_KV>(kb0, ka); ldsm_x4_i<OFF_KV + 2560>(kb1, ka); }
      const uint32_t l16 = sb + ln * 16, s8 = sb + ln * 8, xs = s8 + hw * 256, xr = sb + ln * 4 + (hw >> 1) * 512 + (hw & 1) * 128;
      TS(1);
      bar_sync(B_QK, 384);
      {
        uint32_t q0[4], q1[4], q2[4], q3[4];
        float sa[4] = {0, 0, 0, 0}, sc2[4] = {0, 0, 0, 0};
        ldsm_x4_i<OFF_Q>(q0, l16); ldsm_x4_i<OFF_Q + 1024>(q2, l16); ldsm_x4_i<OFF_Q + 512>(q1, l16);
        bar_arrive(B_A, 288);
        ldsm_x4_i<OFF_Q + 1536>(q3, l16);
        mma16816(sa, q0[0], q0[1], q0[2], q0[3], kb0[0], kb0[1]);
        mma16816(sc2, q2[0], q2[1], q2[2], q2[3], kb1[0], kb1[1]);
        mma16816(sa, q1[0], q1[1], q1[2], q1[3], kb0[2], kb0[3]);
        mma16816(sc2, q3[0], q3[1], q3[2], q3[3], kb1[2], kb1[3]);
        const float x0 = (sa[0] + sa[2]) + (sc2[0] + sc2[2]), x1 = (sa[1] + sa[3]) + (sc2[1] + sc2[3]);
        const uint32_t xp = pack_bf16(x0, x1);
        st_async_b32_i<OFF_SR + 256>(xr + d1, xp, sb + MB_S + d1);
        st_async_b32_i<OFF_SR>(xr + d2, xp, sb + MB_S + d2);
        sts64_i<OFF_S>(xs, __float_as_uint(x0), __float_as_uint(x1));
      }
      TS(3);
      bar_sync(B_SL, 256);
      float t0[4], t1[4], t2[4] = {0, 0, 0, 0};
      float osc;
      {
        const uint4 si = lds128_i<SC_IN>(sb + 16 * (s & 1));
        { const uint2 x = lds64_i<OFF_S>(s8), y = lds64_i<OFF_S + 256>(s8); t0[0] = __uint_as_float(x.x); t0[1] = __uint_as_float(x.y); t0[2] = __uint_as_float(y.x); t0[3] = __uint_as_float(y.y); }
        { const uint2 x = lds64_i<OFF_S + 512>(s8), y = lds64_i<OFF_S + 768>(s8); t1[0] = __uint_as_float(x.x); t1[1] = __uint_as_float(x.y); t1[2] = __uint_as_float(y.x); t1[3] = __uint_as_float(y.y); }
        { const uint2 x = lds64_i<OFF_S + 1024>(s8); t2[0] = __uint_as_float(x.x); t2[1] = __uint_as_float(x.y); }
        const int em = (int)(si.y >> 10) - 14 + (int)(si.x >> 23) - 127;
        osc = exp2i(max(min((int)si.z - max(em, 1), 100), -100));
      }
      const uint32_t xo = sb + hw * 256 + (ln & 2) * 64 + (ln >> 2) * 16 + (ln & 1) * 8;
      const uint32_t eye = ((ln >> 3) == (ln & 3)) ? ((ln & 4) ? 0x3f800000u : 0x3f80u) : 0u;
      mbar_spin(sb + MB_S, s & 1);
      TS(4);
      uint32_t v0[4], v1[4], vm[2];
      {
        uint32_t r0[4], r1[4], r2[4];
        ldsm_x4_i<OFF_SR>(r0, l16); ldsm_x4_i<OFF_SR + 512>(r1, l16); ldsm_x4_i<OFF_SR + 1024>(r2, l16);
        mma16816(t0, r0[0], r0[1], r0[2], r0[3], eye, eye);
        mma16816(t1, r1[0], r1[1], r1[2], r1[3], eye, eye);
        mma16816(t2, r2[0], r2[1], r2[2], r2[3], eye, eye);
      }
      float sc[10] = {t0[0], t0[1], t0[2], t0[3], t1[0], t1[1], t1[2], t1[3], t2[0], t2[1]};
      const float cs = 0.07216878364870322f * 1.4426950408889634f;
      float mx = fmaxf(fmaxf(fmaxf(sc[0], sc[1]), fmaxf(sc[2], sc[3])), fmaxf(fmaxf(sc[4], sc[5]), fmaxf(sc[6], sc[7])));
      mx = fmaxf(mx, fmaxf(sc[8], sc[9]));
      {
        const float m1 = __shfl_xor_sync(0xffffffffu, mx, 1), m2 = __shfl_xor_sync(0xffffffffu, mx, 2), m3 = __shfl_xor_sync(0xffffffffu, mx, 3);
        SFENCE2(l16, __float_as_uint(mx));
        ldsm_x4_t_i<OFF_KV + KVB>(v0, l16 + (kv + hw * 1280)); ldsm_x4_t_i<OFF_KV + KVB + 640>(v1, l16 + (kv + hw * 1280));
        bar_sync(B_V, 256);
        bar_arrive(B_G, 384);
        ldsm_x2_t(vm, l16 + (ln & 8) * 64 + (kv + hw * 1280 + OFF_KV + KVB + 512));
        mx = fmaxf(fmaxf(mx, m1), fmaxf(m2, m3));
      }
      const float mo = mx * cs;
#pragma unroll
      for (int i = 0; i < 10; i++) sc[i] = ex2f(fmaf(sc[i], cs, -mo));
      const uint32_t p0 = pack_bf16(sc[0], sc[1]), p1 = pack_bf16(sc[2], sc[3]), p2 = pack_bf16(sc[4], sc[5]), p3 = pack_bf16(sc[6], sc[7]), p4 = pack_bf16(sc[8], sc[9]);
      TS(5);
      float oa[4] = {0, 0, 0, 0}, ob[4] = {0, 0, 0, 0}, oc[4] = {0, 0, 0, 0}, od[4] = {0, 0, 0, 0}, rs[4] = {0, 0, 0, 0};
      const uint32_t ones = 0x3f803f80u;
      mma16816(rs, p0, p2, p1, p3, ones, ones);
      mma16816(oc, p0, p2, p1, p3, v0[2], v0[3]);
      mma16816(od, p0, p2, p1, p3, v1[2], v1[3]);
      mma16816(oa, p0, p2, p1, p3, v0[0], v0[1]);
      mma16816(ob, p0, p2, p1, p3, v1[0], v1[1]);
      mma1688(rs, p4, 0u, ones);
      mma1688(oa, p4, 0u, vm[0]);
      mma1688(ob, p4, 0u, vm[1]);
      const float inv = rcpf(rs[0] + rs[2]) * osc;
      {
        const uint32_t y0 = pack_bf16((oa[0] + oc[2]) * inv, (oa[1] + oc[3]) * inv), y1 = pack_bf16((ob[0] + od[2]) * inv, (ob[1] + od[3]) * inv);
        st_async_v2_i<OFF_O + 2048>(xo + d1, y0, y1, sb + MB_O + d1);
        st_async_v2_i<OFF_O + 1024>(xo + d2, y0, y1, sb + MB_O + d2);
        sts64_i<OFF_O>(xo, y0, y1);
      }
      bar_arrive(B_O, 384);
      TS(6);
      if (ln == 0) {
        if (hw == 0) {
          bulk_wait<0>();
          if ((s & 3) == 0 && s > 0) {
            asm volatile("st.release.gpu.global.u32 [%0], %1;" :: "l"(arena + (AR_PROG + (cta + ln) * 4)), "r"(s) : "memory");
          }
        }
        if (hw == 3) { mbar_expect_tx(sb + MB_S, 1280); sts64_i<SC_IN>(sb + 16 * ((s + 1) & 1), 0x7f000000u - __float_as_uint(osc), 0u); }
      }
      __syncwarp();
      ln = fresh(ln);
      auto mslot = [&](int c) -> uint32_t { return sb + OFF_MEM + c * 128 + (((ln >> 2) ^ (2 * (c & 3))) << 4); };
      const int lq = ln & 3;
      const uint32_t ma = mslot(cb28 + lq), mb_ = mslot(cb28 + (lq >> 1)) + (lq & 1) * 8;
      const unsigned char* gp = arena + (AR_ACC + acc_lane(hw, ln) + acc_step(s));
      const bool odd = ln & 1;
      SFENCE(ma);
      bar_sync(B_RED, 384);
      SFENCE(mb_);
      const uint32_t tw = clk_v();
      TSV(7, tw);
      if (ln == 0 && hw == 3) mbar_expect_tx(sb + MB_O, 2048);
      __syncwarp();
      while (clk_v() - tw < POLL_DELAY) {}
      TS(8);
      uint4 v[6];
      int spin = 0;
      const uint32_t cm = odd ? 0x5000u : 0u;
      do {
        static_for<0, 6>([&](auto I) { v[I.value] = ld_relaxed_v4_i<acc_voff(I.value)>(gp); });
      } while (__any_sync(0xffffffffu, (~((v[0].w & v[1].w & v[2].w) & (v[3].w & v[4].w & v[5].w)) & cm) != 0) && ++spin < SPIN_LIMIT);
      v[0].w = odd ? v[3].x : v[0].w; v[1].w = odd ? v[3].y : v[1].w; v[2].w = odd ? v[3].z : v[2].w; v[3].w = odd ? 0u : v[3].w;
      sts128_i<0>(ma, v[0].x, v[0].y, v[0].z, v[0].w);
      sts128_i<512>(ma, v[1].x, v[1].y, v[1].z, v[1].w);
      sts128_i<1024>(ma, v[2].x, v[2].y, v[2].z, v[2].w);
      sts128_i<0>(ma + du, v[4].x, v[4].y, v[4].z, v[5].z);
      sts64_i<512>(mb_ + du, v[5].x, v[5].y);
      if (!odd) sts128_i<1536>(mb_, v[3].x, v[3].y, v[3].z, v[3].w);
      TSV(11, spin);
      TS(10);
      bar_sync(B_MEM0, 256); bar_sync(B_MEM1, 256);
      uint32_t m = lds32_i<SC_IN + 12>(sb);
      uint32_t m2 = m;
      static_for<0, 3>([&](auto I) { m = amax_h2(amax_h2(amax_h2(amax_h2(m, v[I.value].x), v[I.value].y), v[I.value].z), v[I.value].w); });
      static_for<3, 6>([&](auto I) { m2 = amax_h2(amax_h2(amax_h2(m2, v[I.value].x), v[I.value].y), v[I.value].z); });
      m = amax_fold(amax_h2(amax_h2(m2, v[3].w), m));
      if (ln == 0) asm volatile("red.shared.max.u32 [%0], %1;" :: "r"(sb + SC_IN + 4 + 16 * ((s + 1) & 1)), "r"(m) : "memory");
    }
    bar_sync(B_RED, 384);
    if (hw == 0 && ln == 0) {
      store_kv(cfg::NSEG - 1);
      bulk_wait<0>();
      asm volatile("st.release.gpu.global.u32 [%0], %1;" :: "l"(arena + AR_PROG + cta * 4), "r"(cfg::NSEG) : "memory");
    }
    __syncwarp();
    TL_END(a.tl);
    asm volatile("barrier.cluster.arrive.relaxed.aligned; barrier.cluster.wait.aligned;" ::: "memory");
  } else {
    asm volatile("setmaxnreg.inc.sync.aligned.u32 232;");
    const int wi = warp & 3, hf = warp >> 2, tid = warp * 32 + lane;
    uint32_t w[40][4];
    uint32_t wqa;
    { const int mrow = r8 + ((lane >> 4) << 3), mch = 2 * wi + (m4 & 1); wqa = sb + mrow * 128 + ((mch ^ r8) << 4); }
    {
      const uint32_t wa = wqa + (hf ? OFF_WO : OFF_WQ);
      mbar_wait(sb + (hf ? MB_V : MB_K), 0);
      static_for<0, 20>([&](auto K) { ldsm_x4_t_i<K.value * 2048>(w[K.value], wa); });
      bar_arrive(hf ? B_V : B_QK, 160);
      mbar_wait(sb + (hf ? MB_V : MB_K) + 8, 0);
      static_for<20, 40>([&](auto K) { ldsm_x4_t_i<K.value * 2048>(w[K.value], wa); });
      bar_arrive(hf ? B_O : B_SL, 160);
      SFENCE(wa);
    }
    float iw, iq;
    {
      uint32_t m = 0;
#pragma unroll
      for (int k = 0; k < 40; k++) m = amax_bf2(amax_bf2(m, amax_bf2(w[k][0], w[k][1])), amax_bf2(w[k][2], w[k][3]));
      m = amax_fold(m);
      if (hf && lane == 0) asm volatile("red.shared.max.u32 [%0], %1;" :: "r"(sb + SC_W), "r"(m) : "memory");
      const int e = wscale_exp(m);
      const uint32_t sc = (uint32_t)(e + 127) * 0x00800080u; iw = exp2i(-e);
#pragma unroll
      for (int k = 0; k < 40; k++) { bf2_to_h2_inplace(w[k][0], sc); bf2_to_h2_inplace(w[k][1], sc); bf2_to_h2_inplace(w[k][2], sc); bf2_to_h2_inplace(w[k][3], sc); }
    }
    uint32_t x0[8];
    {
      float xa[16];
      const uint32_t dlo = (((sb + OFF_X) & 0x3FFFF) >> 4) | (1u << 16);
      mbar_wait(sb + MB_X, 0);
      wgmma_fence();
      static_for<0, 40>([&](auto K) { constexpr int k = K.value; wgmma_rs32h<((k >> 2) * 4096 + (k & 3) * 32) / 16, (k != 0)>(xa, w[k], dlo); });
      wgmma_commit();
      wgmma_wait<0>();
#pragma unroll
      for (int i = 0; i < 8; i++) x0[i] = pack_bf16(xa[2 * i] * iw, xa[2 * i + 1] * iw);
    }
    const bool t28 = j == 0 || warp < 4;
    const int bi = j == 0 ? hf : (warp < 4 ? j + 1 : 2 * (j - 1) + ((warp - 4) >> 1)), bv = t28 ? wi : 4 + (warp & 1);
    uint32_t wo1 = sb + OFF_WO + warp * 896 + lane * 16, wo2;
    {
      const int cb = (t28 ? unit28(bi) : unit24(bi)) - col0 / 8;
      uint32_t cp[4];
#pragma unroll
      for (int wd = 0; wd < 4; wd++) {
        int c, p;
        if (bv < 3) { c = 4 * bv + q4; p = wd; }
        else if (bv == 3) { if (q4 & 1) { c = 4 * (wd % 3) + q4; p = 3; } else { c = 12 + (q4 >> 1); p = wd; } }
        else if (bv == 4) { c = q4; p = wd; }
        else { if (wd < 2) { c = 4 + (q4 >> 1); p = 2 * (q4 & 1) + wd; } else { c = q4; p = 3; } }
        cp[wd] = sb + OFF_WO + ((g & 1) + (g & 2) * 4 + (g >> 2) * 2) * WOS + (cb + c) * 16 + p * 4;
      }
      const int cidx = (r8 & 1) + ((r8 >> 2) << 1);
      wo2 = sb + OFF_WO + warp * 896 + ((m4 & 1) ? 768 + (m4 >> 1) * 64 + cidx * 16 : 512 + (m4 >> 1) * 128 + r8 * 16);
      const bool dump = (m4 & 1) && (r8 & 2);
      uint32_t mo = 0;
      const bool regular = bv < 3 || bv == 4;
#pragma unroll 1
      for (int i = 0; i < 3; i++) {
        uint32_t x[4][4], y[4][4];
        const uint32_t o = i * 4 * WOK;
        mbar_wait(sb + MB_R + 8 * i, 0);
        if (regular) {
          static_for<0, 4>([&](auto K) {
            constexpr int kk = K.value;
            const uint4 u = lds128_i<kk * WOK>(cp[0] + o), v = lds128_i<kk * WOK + 4 * WOS>(cp[0] + o);
            x[kk][0] = u.x; x[kk][1] = u.y; x[kk][2] = u.z; x[kk][3] = u.w; y[kk][0] = v.x; y[kk][1] = v.y; y[kk][2] = v.z; y[kk][3] = v.w;
          });
        } else {
          static_for<0, 4>([&](auto K) {
            constexpr int kk = K.value;
#pragma unroll
            for (int wd = 0; wd < 4; wd++) { x[kk][wd] = lds32_i<kk * WOK>(cp[wd] + o); y[kk][wd] = lds32_i<kk * WOK + 4 * WOS>(cp[wd] + o); }
          });
        }
        bar_sync(B_C, 256);
        static_for<0, 4>([&](auto K) {
          constexpr int kk = K.value;
#pragma unroll
          for (int wd = 0; wd < 4; wd++) mo = amax_bf2(mo, amax_bf2(x[kk][wd], y[kk][wd]));
          stsm_x4_t_i<kk * WOK>(wo1 + o, x[kk][0], x[kk][1], y[kk][0], y[kk][1]);
          stsm_x4_t_i<0>(dump ? sb + OFF_S + 512 + lane * 16 : wo2 + o + kk * WOK, x[kk][2], x[kk][3], y[kk][2], y[kk][3]);
        });
      }
      mo = amax_fold(mo);
      if (lane == 0) asm volatile("red.shared.max.u32 [%0], %1;" :: "r"(sb + SC_W + 4), "r"(mo) : "memory");
    }
    __syncwarp();
    auto run = [&](auto HF) {
    constexpr int hf = HF.value;
    uint32_t mema, sta, l16 = sb + lane * 16;
    uint32_t rq[hf ? NQ1 : NQ0][4];
    auto step_addr = [&](uint32_t kv) {
      const int lr = (l16 >> 4) & 7, lm = (l16 >> 7) & 3;
      mema = l16 ^ (lm << 5);
      sta = sb + lr * 16 + (lm < 2 ? OFF_Q + wi * 512 + hf * 128 + lm * 256 : OFF_KV + kv + 512 + (2 * wi + lm - 2) * 640);
    };
    auto x_gemm = [&](uint32_t ph, [[maybe_unused]] uint32_t tsb) {
      float xa[16];
      const uint32_t dlo = (((sb + OFF_X) & 0x3FFFF) >> 4) | (1u << 16);
      constexpr int NP = hf ? NQ1 : NP0;
      if constexpr (hf) {
        static_for<PQE, NP>([&](auto K) { ldsm_x4_t_i<OFF_WQ + K.value * 2048>(rq[K.value], wqa); });
        bar_sync(B_X, 256);
      }
      wgmma_fence();
      static_for<0, 40>([&](auto K) {
        constexpr int k = K.value;
        wgmma_rs32h<((k >> 2) * 4096 + (k & 3) * 32) / 16, (k != 0)>(xa, w[k], dlo);
        if constexpr (!hf && k == PFK && NP > PQE) { SFENCE(wqa); static_for<PQE, NP>([&](auto K) { ldsm_x4_t_i<OFF_WQ + K.value * 2048>(rq[K.value], wqa); }); SFENCE(wqa); }
        if constexpr (!hf && k == XT) bar_arrive(B_X, 256);
      });
      step_addr(ph * (2 * KVB));
      wgmma_commit();
      TS(9);
      wgmma_wait<0>();
      const uint32_t xs = l16 + (wi * 1280 + ph * (2 * KVB));
      stsm_x4_t_i<OFF_KV + hf * KVB>(xs, pack_bf16(xa[0] * iw, xa[1] * iw), pack_bf16(xa[4] * iw, xa[5] * iw), pack_bf16(xa[8] * iw, xa[9] * iw), pack_bf16(xa[12] * iw, xa[13] * iw));
      stsm_x4_t_i<OFF_KV + hf * KVB + 640>(xs, pack_bf16(xa[2] * iw, xa[3] * iw), pack_bf16(xa[6] * iw, xa[7] * iw), pack_bf16(xa[10] * iw, xa[11] * iw), pack_bf16(xa[14] * iw, xa[15] * iw));
    };
    auto wq_addr = [&](uint32_t l) -> uint32_t {
      const int lr = (l >> 4) & 7, lm = (l >> 7) & 3;
      return sb + hf * ((40 - NQ1) * 2048) + (lr + ((lm >> 1) << 3)) * 128 + (((2 * wi + (lm & 1)) ^ lr) << 4);
    };
    constexpr int NPM = hf ? NPM1 : NPM0;
    uint32_t u1[NPM][4], u2[NPM][4];
    static_for<0, NPM>([&](auto K) { ldsm_x4_i<(12 - NPM + K.value) * WOK>(u1[K.value], wo1); ldsm_x4_i<(12 - NPM + K.value) * WOK>(u2[K.value], wo2); });
    bar_sync(0, 384);
    iq = uniform_f(exp2i(-wscale_exp(lds32_i<SC_W + 8>(sb))));
    wqa = wq_addr(l16);
    static_for<0, (hf ? NQ1 : NP0)>([&](auto K) { ldsm_x4_t_i<OFF_WQ + K.value * 2048>(rq[K.value], wqa); });
    step_addr(0);
    stsm_x4_t_i<OFF_KV + hf * KVB>(l16 + wi * 1280, x0[0], x0[2], x0[4], x0[6]);
    stsm_x4_t_i<OFF_KV + hf * KVB + 640>(l16 + wi * 1280, x0[1], x0[3], x0[5], x0[7]);
    asm volatile("barrier.cluster.wait.aligned;" ::: "memory");
    TL_END(a.tl + 1);
#pragma unroll 1
    for (int s = 0; s < cfg::NSEG; s++) {
      TS_SETUP();
      const bool last = s == cfg::NSEG - 1;
      bar_sync(hf ? B_MEM1 : B_MEM0, 256);
      const float sin_ = __uint_as_float(lds32_i<SC_IN>(sb + 16 * (s & 1)));
      constexpr int NPQ = (40 - NQ1) / 2;
      if constexpr (hf == 0) {
        float k0[4] = {0, 0, 0, 0}, k1[4] = {0, 0, 0, 0}, q0[4] = {0, 0, 0, 0}, q1[4] = {0, 0, 0, 0};
        constexpr auto pair_of = [](int t) { const int a = t * (20 - NPQ) / 20, b = (t + 1) * (20 - NPQ) / 20; return b > a ? NPQ + a : t - a; };
        uint32_t b[NB0][4];
        static_for<0, NB0>([&](auto T) { ldsm_x4_i<OFF_MEM + pair_of(T.value) * 512>(b[T.value], mema); });
        static_for<NP0, NQ0>([&](auto K) { ldsm_x4_t_i<OFF_WQ + K.value * 2048>(rq[K.value], wqa); });
        if (BBS < 100) bbfence<0>(mema);
        static_for<0, 20>([&](auto T) {
          constexpr int t = T.value, p = pair_of(t);
          uint32_t (&bb)[4] = b[t % NB0];
          if constexpr (p < NPQ) {
            mma16816h(q0, rq[(2 * p) % NQ0], bb[0], bb[1]);
            if constexpr (2 * p + NQ0 < 2 * NPQ) ldsm_x4_t_i<OFF_WQ + (2 * p + NQ0) * 2048>(rq[(2 * p) % NQ0], wqa);
          }
          mma16816h(k0, w[2 * p], bb[0], bb[1]);
          if constexpr (p < NPQ) {
            mma16816h(q1, rq[(2 * p + 1) % NQ0], bb[2], bb[3]);
            if constexpr (2 * p + 1 + NQ0 < 2 * NPQ) ldsm_x4_t_i<OFF_WQ + (2 * p + 1 + NQ0) * 2048>(rq[(2 * p + 1) % NQ0], wqa);
          }
          mma16816h(k1, w[2 * p + 1], bb[2], bb[3]);
          if constexpr (t + NB0 < 20) ldsm_x4_i<OFF_MEM + pair_of(t + NB0) * 512>(bb, mema);
          if constexpr (t < 20 - NB0 && (t % BBS) == BBS - 1) bbfence<t + 1>(mema);
        });
        const float sq = sin_ * iq, sk = sin_ * iw;
        stsm_x4_t_i<0>(sta, pack_bf16((q0[0] + q1[0]) * sq, (q0[1] + q1[1]) * sq), pack_bf16((q0[2] + q1[2]) * sq, (q0[3] + q1[3]) * sq),
                       pack_bf16((k0[0] + k1[0]) * sk, (k0[1] + k1[1]) * sk), pack_bf16((k0[2] + k1[2]) * sk, (k0[3] + k1[3]) * sk));
        TS(2);
        if (!last) {
          if (wi == 3) {
            const uint32_t s8 = sb + ((l16 & 511) >> 1), xr = sb + ((l16 & 511) >> 2), ka = l16 + (l16 & 384) * 4 + (s & 1) * (2 * KVB);
            bar_sync(B_QK, 384);
            uint32_t a0[4], a1[4], a2[4], a3[4], kb0[4], kb1[4];
            ldsm_x4_i<OFF_Q>(a0, l16); ldsm_x4_i<OFF_KV + 512>(kb0, ka); ldsm_x4_i<OFF_Q + 1024>(a2, l16); ldsm_x4_i<OFF_KV + 512 + 2560>(kb1, ka);
            ldsm_x4_i<OFF_Q + 512>(a1, l16);
            bar_arrive(B_A, 288);
            ldsm_x4_i<OFF_Q + 1536>(a3, l16);
            float sa[4] = {0, 0, 0, 0}, sc2[4] = {0, 0, 0, 0};
            mma16816(sa, a0[0], a0[1], a0[2], a0[3], kb0[0], kb0[1]);
            mma16816(sc2, a2[0], a2[1], a2[2], a2[3], kb1[0], kb1[1]);
            mma16816(sa, a1[0], a1[1], a1[2], a1[3], kb0[2], kb0[3]);
            mma16816(sc2, a3[0], a3[1], a3[2], a3[3], kb1[2], kb1[3]);
            const float x0 = (sa[0] + sa[2]) + (sc2[0] + sc2[2]), x1 = (sa[1] + sa[3]) + (sc2[1] + sc2[3]);
            const uint32_t xp = pack_bf16(x0, x1);
            st_async_b32_i<OFF_SR + 1024 + 256>(xr + d1, xp, sb + MB_S + d1);
            st_async_b32_i<OFF_SR + 1024>(xr + d2, xp, sb + MB_S + d2);
            sts64_i<OFF_S + 1024>(s8, __float_as_uint(x0), __float_as_uint(x1));
          } else {
            bar_arrive(B_QK, 384);
          }
          bar_sync(B_SL, 256);
        }
      } else {
        float v0[4] = {0, 0, 0, 0}, v1[4] = {0, 0, 0, 0}, q0[4] = {0, 0, 0, 0}, q1[4] = {0, 0, 0, 0};
        uint32_t b[NQ1 / 2][4];
        static_for<0, NQ1 / 2>([&](auto T) { ldsm_x4_i<OFF_MEM + (NPQ + T.value) * 512>(b[T.value], mema); });
        static_for<0, NQ1 / 2>([&](auto T) {
          constexpr int t = T.value, p = NPQ + t;
          uint32_t (&bb)[4] = b[t];
          mma16816h(q0, rq[2 * t], bb[0], bb[1]);
          mma16816h(q1, rq[2 * t + 1], bb[2], bb[3]);
          mma16816h(v0, w[2 * p], bb[0], bb[1]);
          mma16816h(v1, w[2 * p + 1], bb[2], bb[3]);
        });
        const float sq = sin_ * iq, sv = sin_ * iw;
        stsm_x2_t_i<0>(sta, pack_bf16((q0[0] + q1[0]) * sq, (q0[1] + q1[1]) * sq), pack_bf16((q0[2] + q1[2]) * sq, (q0[3] + q1[3]) * sq));
        TS(2);
        if (!last) { bar_arrive(B_QK, 384); bar_sync(B_A, 288); }
        float v2[4] = {0, 0, 0, 0}, v3[4] = {0, 0, 0, 0};
        uint32_t c[4][4];
        static_for<0, 4>([&](auto T) { ldsm_x4_i<OFF_MEM + T.value * 512>(c[T.value], mema); });
        static_for<0, NPQ>([&](auto T) {
          constexpr int p = T.value;
          uint32_t (&bb)[4] = c[p & 3];
          if constexpr (p & 1) { mma16816h(v0, w[2 * p], bb[0], bb[1]); mma16816h(v1, w[2 * p + 1], bb[2], bb[3]); }
          else { mma16816h(v2, w[2 * p], bb[0], bb[1]); mma16816h(v3, w[2 * p + 1], bb[2], bb[3]); }
          if constexpr (p + 4 < NPQ) ldsm_x4_i<OFF_MEM + (p + 4) * 512>(bb, mema);
        });
        stsm_x2_t_i<OFF_KV + KVB + 512>(l16 + (l16 & 128) * 4 + (wi * 1280 + (s & 1) * (2 * KVB)), pack_bf16(((v0[0] + v1[0]) + (v2[0] + v3[0])) * sv, ((v0[1] + v1[1]) + (v2[1] + v3[1])) * sv),
                            pack_bf16(((v0[2] + v1[2]) + (v2[2] + v3[2])) * sv, ((v0[3] + v1[3]) + (v2[3] + v3[3])) * sv));
        if (!last) bar_arrive(B_V, 256);
      }
      TS(3);
      if (last) break;
      {
        uint32_t t1[12][4], t2[12][4];
        const uint32_t o16 = l16;
        wo1 = l16 + (OFF_WO + warp * 896);
        wo2 = sb + OFF_WO + warp * 896 + ((l16 & 128) ? 768 + ((l16 & 256) >> 2) + (l16 & 16) + ((l16 & 64) >> 1) : 512 + ((l16 & 256) >> 1) + (l16 & 112));
        auto ldw = [&](auto K) { if constexpr (K.value < 12 - NPM) { ldsm_x4_i<K.value * WOK>(t1[K.value], wo1); ldsm_x4_i<K.value * WOK>(t2[K.value], wo2); } };
        constexpr int NR_ = NRT - NPM;
        constexpr int PB = (hf ? PB1 : PB0) < NR_ ? (hf ? PB1 : PB0) : NR_, PA = (hf ? PA1 : PA0) < PB ? (hf ? PA1 : PA0) : PB;
        static_for<0, PA>(ldw);
        mbar_spin(sb + MB_X, (s + 1) & 1);
        if constexpr (PB > PA) bar_sync(B_G, 384); else bar_arrive(B_G, 384);
        static_for<PA, PB>(ldw);
        float c0[4] = {0, 0, 0, 0}, c1[4] = {0, 0, 0, 0}, e0[4] = {0, 0, 0, 0}, e1[4] = {0, 0, 0, 0};
        uint32_t ob[6][4];
        auto kstep = [&](auto K) {
          constexpr int k = K.value;
          uint32_t (&bb)[4] = ob[k >> 1];
          uint32_t (&x)[4] = k < 12 - NPM ? t1[k] : u1[k < 12 - NPM ? 0 : k - (12 - NPM)];
          uint32_t (&y)[4] = k < 12 - NPM ? t2[k] : u2[k < 12 - NPM ? 0 : k - (12 - NPM)];
          if constexpr (k & 1) { mma16816(c1, x[0], x[1], x[2], x[3], bb[2], bb[3]); mma16816(e1, y[0], y[1], y[2], y[3], bb[2], bb[3]); }
          else { mma16816(c0, x[0], x[1], x[2], x[3], bb[0], bb[1]); mma16816(e0, y[0], y[1], y[2], y[3], bb[0], bb[1]); }
          if constexpr (k >= NRF) ldw(IC<k + NR_ - NRF>{});
        };
        auto ldo = [&](auto P) { ldsm_x4_i<OFF_O + P.value * 512>(ob[P.value], o16); };
        TS(4);
        bar_sync(B_O, 384);
        ldo(IC<0>{}); ldo(IC<1>{});
        SFENCE(o16);
        static_for<PB, NR_>(ldw);
        static_for<0, 4>(kstep);
        TS(5);
        mbar_spin(sb + MB_O, s & 1);
        TS(6);
        ldo(IC<2>{}); ldo(IC<NPM >= 2 ? 5 : 3>{});
        if (WOF) SFENCE(o16);
        kstep(IC<4>{});
        if constexpr (NPM < 2) { kstep(IC<5>{}); ldo(IC<4>{}); kstep(IC<6>{}); kstep(IC<7>{}); ldo(IC<5>{}); static_for<8, 12>(kstep); }
        else if constexpr (NPM >= 4) { kstep(IC<10>{}); kstep(IC<11>{}); ldo(IC<4>{}); kstep(IC<5>{}); ldo(IC<3>{}); kstep(IC<8>{}); kstep(IC<9>{}); kstep(IC<6>{}); kstep(IC<7>{}); }
        else { kstep(IC<5>{}); ldo(IC<3>{}); kstep(IC<11>{}); kstep(IC<10>{}); ldo(IC<4>{}); kstep(IC<6>{}); kstep(IC<7>{}); if constexpr (NPM == 3) { kstep(IC<9>{}); kstep(IC<8>{}); } else { kstep(IC<8>{}); kstep(IC<9>{}); } }
        l16 = fresh(l16);
        const int ln = (l16 >> 4) & 31;
        unsigned char* gr = arena + (AR_ACC + acc_lane(bi, ln) + acc_voff(bv) + acc_step(s));
        const bool cnt = (ln & 1) || !t28;
        wqa = wq_addr(l16);
        SFENCE(o16);
        static_for<0, PQE>([&](auto K) { ldsm_x4_t_i<OFF_WQ + K.value * 2048>(rq[K.value], wqa); });
        const uint32_t y0 = movm_t(pack_f16(c0[0] + c1[0], c0[1] + c1[1])), y1 = movm_t(pack_f16(c0[2] + c1[2], c0[3] + c1[3]));
        const uint32_t y2 = movm_t(pack_f16(e0[0] + e1[0], e0[1] + e1[1])), y3 = movm_t(pack_f16(e0[2] + e1[2], e0[3] + e1[3]));
        asm volatile("red.relaxed.gpu.global.add.noftz.v4.f16x2 [%0], {%1,%2,%3,%4};" :: "l"(gr), "r"(y0), "r"(y1), "r"(y2), "r"(cnt ? 0x3c00u : y3) : "memory");
        if constexpr (hf || RSYNC) bar_sync(B_RED, 384); else bar_arrive(B_RED, 384);
        TS(7);
      }
      x_gemm((s + 1) & 1, 0);
      TS(8);
    }
    };
    if (hf == 0) run(IC<0>{}); else run(IC<1>{});
    bar_arrive(B_RED, 384);
    asm volatile("barrier.cluster.arrive.relaxed.aligned; barrier.cluster.wait.aligned;" ::: "memory");
  }
}
struct PrepArgs { const bf16 *wqkv, *wphi, *wo; bf16 *wb, *wot; };
constexpr int PREP_TASKS = 3840;
__device__ __forceinline__ void prep_body(const int b, const bf16* __restrict__ wqkv, const bf16* __restrict__ wphi, const bf16* __restrict__ wo,
                                          bf16* __restrict__ wb, bf16* __restrict__ wot) {
  const int task = b, lane = threadIdx.x & 31;
  if (task < 1920) {
    const int which = task / 640, h = (task / 20) % 32, k = (task % 20) * 32 + lane;
    const int row0 = 288 * (h >> 2) + 96 * which + 24 * (h & 3);
    const uint2* src = (const uint2*)(wqkv + (size_t)k * 1920 + which * 640 + h * 20);
    float w[20];
#pragma unroll
    for (int d = 0; d < 5; d++) { const uint2 t = __ldg(src + d); w[4 * d] = bf_lo(t.x); w[4 * d + 1] = bf_hi(t.x); w[4 * d + 2] = bf_lo(t.y); w[4 * d + 3] = bf_hi(t.y); }
    if (which < 2) {
      float a[20];
#pragma unroll
      for (int f = 0; f < 20; f++) a[f] = 0.f;
      const uint32_t* ph = (const uint32_t*)(wphi + h * 400);
#pragma unroll
      for (int d = 0; d < 20; d++)
#pragma unroll
        for (int f = 0; f < 10; f++) { const uint32_t t = __ldg(ph + d * 10 + f); a[2 * f] = fmaf(w[d], bf_lo(t), a[2 * f]); a[2 * f + 1] = fmaf(w[d], bf_hi(t), a[2 * f + 1]); }
#pragma unroll
      for (int f = 0; f < 20; f++) wb[(size_t)(row0 + f) * cfg::DM + k] = __float2bfloat16_rn(a[f]);
    } else {
#pragma unroll
      for (int d = 0; d < 20; d++) wb[(size_t)(row0 + d) * cfg::DM + k] = __float2bfloat16_rn(w[d]);
    }
#pragma unroll
    for (int f = 20; f < 24; f++) wb[(size_t)(row0 + f) * cfg::DM + k] = __float2bfloat16_rn(0.f);
  } else {
    const int t = task - 1920, n = (t % 20) * 32 + lane, kk0 = (t / 20) * 8, h = kk0 / 24, d0 = kk0 % 24;
    unsigned short v[8];
#pragma unroll
    for (int e = 0; e < 8; e++) v[e] = (d0 + e < 20) ? __ldg((const unsigned short*)wo + (size_t)(h * 20 + d0 + e) * cfg::DM + n) : (unsigned short)0;
    *(uint4*)(wot + (size_t)n * 768 + kk0) = make_uint4(v[0] | (v[1] << 16), v[2] | (v[3] << 16), v[4] | (v[5] << 16), v[6] | (v[7] << 16));
  }
}

#define OSPLIT(b) ((b) < 11 ? 1 : ((b) < 13 ? 2 : ((b) < 14 ? 4 : 8)))
__host__ __device__ constexpr int o_split(int b) { return OSPLIT(b); }

template <int NP>
__global__ void __launch_bounds__(256, NP > 0 ? 2 : 4) ln_kernel(const bf16* __restrict__ xin, const float* __restrict__ part, bf16* __restrict__ xout,
                                                 bf16* __restrict__ xn, uint2* __restrict__ xh, uint4* __restrict__ z0, int n0, uint4* __restrict__ z1, int n1, const bf16* pfa, const bf16* pfb, int npf, int tl) {
  asm volatile("griddepcontrol.wait;" ::: "memory");
  asm volatile("griddepcontrol.launch_dependents;" ::: "memory");
  TL_BEGIN(tl);
  const int warp = threadIdx.x >> 5, lane = threadIdx.x & 31;
  const int row = (255 - blockIdx.x) * 8 + warp;
  uint2 xw[5];
#pragma unroll
  for (int i = 0; i < 5; i++) xw[i] = *(const uint2*)(xin + (size_t)row * cfg::DM + i * 128 + lane * 4);
  for (int i = blockIdx.x * 256 + threadIdx.x; i < n0; i += 256 * 256) z0[i] = make_uint4(0, 0, 0, 0);
  for (int i = blockIdx.x * 256 + threadIdx.x; i < n1; i += 256 * 256) z1[i] = make_uint4(0, 0, 0, 0);
  float4 a[5];
  if (NP > 0) {
    const float* pp = part + (size_t)row * cfg::DM + lane * 4;
#pragma unroll
    for (int i = 0; i < 5; i++) a[i] = make_float4(0, 0, 0, 0);
    const int np = o_split(row >> 7);
    if (np == 1) {
#pragma unroll
      for (int i = 0; i < 5; i++) a[i] = __ldcg((const float4*)(pp + i * 128));
    } else if (np == 2) {
      float4 t[5];
#pragma unroll
      for (int i = 0; i < 5; i++) { a[i] = __ldcg((const float4*)(pp + i * 128)); t[i] = __ldcg((const float4*)(pp + (size_t)cfg::S * cfg::DM + i * 128)); }
#pragma unroll
      for (int i = 0; i < 5; i++) { a[i].x += t[i].x; a[i].y += t[i].y; a[i].z += t[i].z; a[i].w += t[i].w; }
    } else {
      for (int p0 = 0; p0 < np; p0 += 4) {
        float4 t[4][5];
#pragma unroll
        for (int p = 0; p < 4; p++)
#pragma unroll
          for (int i = 0; i < 5; i++) t[p][i] = __ldcg((const float4*)(pp + (size_t)(p0 + p) * cfg::S * cfg::DM + i * 128));
#pragma unroll
        for (int p = 0; p < 4; p++)
#pragma unroll
          for (int i = 0; i < 5; i++) { a[i].x += t[p][i].x; a[i].y += t[p][i].y; a[i].z += t[p][i].z; a[i].w += t[p][i].w; }
      }
    }
  }
  if (NP > 0) {
#pragma unroll
    for (int i = 0; i < 5; i++) {
      xw[i] = make_uint2(pack_bf16(bf_lo(xw[i].x) + bf16r(a[i].x), bf_hi(xw[i].x) + bf16r(a[i].y)), pack_bf16(bf_lo(xw[i].y) + bf16r(a[i].z), bf_hi(xw[i].y) + bf16r(a[i].w)));
      *(uint2*)(xout + (size_t)row * cfg::DM + i * 128 + lane * 4) = xw[i];
    }
  }
  if (npf && xw[4].y != 0x7fc17fc1u) {
    for (int i = 0; i < npf; i++) {
      const uint32_t l = (uint32_t)i * 32768u + (blockIdx.x * 256 + threadIdx.x) / 2;
      if (l < cfg::DM * cfg::HD / 64) asm volatile("prefetch.global.L2 [%0];" :: "l"(((threadIdx.x & 1) ? pfa : pfb) + (size_t)l * 64) : "memory");
    }
  }
  ln_row(xw, row, lane, xn, xh);
  TL_END(tl);
}

struct Pipe { uint32_t stage, phase; };
template <int NS> __device__ __forceinline__ void pipe_adv(Pipe& p) { if (++p.stage == NS) { p.stage = 0; p.phase ^= 1; } }
constexpr uint32_t SWZ128 = 1;
__device__ __forceinline__ uint64_t desc_kmajor(uint32_t a) { return make_desc(a, 16, 1024, SWZ128); }
__device__ __forceinline__ uint64_t desc_mnmajor(uint32_t a) { return make_desc(a, 8192, 1024, SWZ128); }

__device__ __forceinline__ void wait_ge(const void* p, uint32_t target) {
  int spin = 0;
  while (ld_acquire_u32(p) < target) { __nanosleep(64); if (++spin > (1 << 23)) break; }
}
__device__ __forceinline__ void fence_proxy_async_all() { asm volatile("fence.proxy.async;" ::: "memory"); }

namespace tr {
constexpr int NS = 4, STAGE = 16384 + 24576;
constexpr int SEGB = 15360;
constexpr int OFF_K = NS * STAGE;
constexpr int OFF_OST = OFF_K;
constexpr int OFF_BAR = OFF_K + 4 * SEGB;
constexpr int SMEM = OFF_BAR + 256;
static_assert(SMEM <= 232448, "smem");
constexpr int NQA = 32;
constexpr int o_items() { int n = 0; for (int b = 0; b < 16; b++) n += 4 * o_split(b); return n; }
constexpr int NITEMS = 16 * NQA + o_items();
enum { T_QA = 0, T_O = 1, T_END = 4 };
__device__ __forceinline__ void decode(int i, int& type, int& b, int& k) {
  if (i >= NITEMS) { type = T_END; b = 0; k = 0; return; }
  if (i < 2 * NQA) { type = T_QA; b = i / NQA; k = i % NQA; return; }
  i -= 2 * NQA;
  for (int q = 0; q < 16; q++) {
    const int no = 4 * o_split(q);
    if (i < no) { type = T_O; b = q; k = i; return; }
    i -= no;
    if (q + 2 < 16) { if (i < NQA) { type = T_QA; b = q + 2; k = i; return; } i -= NQA; }
  }
  type = T_END; b = 0; k = 0;
}
}

template <int BN> struct WG_N;
template <> struct WG_N<192> { static __device__ __forceinline__ void mma(float (&d)[96], uint64_t a, uint64_t b, int c) { wgmma_n192<0, 1>(d, a, b, c); } };
template <> struct WG_N<128> { static __device__ __forceinline__ void mma(float (&d)[64], uint64_t a, uint64_t b, int c) { wgmma_n128<0, 1>(d, a, b, c); } };
template <int BN>
__device__ __forceinline__ void tr_mainloop(float (&acc)[BN / 2], Pipe& p, uint32_t sb, uint32_t full, uint32_t empty, int nkb, int wg) {
  using namespace tr;
  uint32_t prev = 0;
#pragma unroll
  for (int i = 0; i < BN / 2; i++) acc[i] = 0.f;
  for (int kb = 0; kb < nkb; kb++) {
    mbar_wait(full + 8 * p.stage, p.phase);
    const uint32_t st = sb + p.stage * STAGE;
    wgmma_fence();
#pragma unroll
    for (int kk = 0; kk < 4; kk++) WG_N<BN>::mma(acc, desc_kmajor(st + wg * 8192 + kk * 32), desc_mnmajor(st + 16384 + kk * 2048), (kb | kk) != 0);
    wgmma_commit();
    if (kb > 0) { wgmma_wait<1>(); if ((threadIdx.x & 127) == 0) mbar_arrive(empty + 8 * prev); }
    prev = p.stage;
    pipe_adv<NS>(p);
  }
  wgmma_wait<0>();
  if ((threadIdx.x & 127) == 0) mbar_arrive(empty + 8 * prev);
}
template <int BN>
__device__ __forceinline__ void o_item(Pipe& p, uint32_t sb, uint32_t full, uint32_t empty, int nkb, float* __restrict__ dst, int wg, int wi, int lane) {
  float acc[BN / 2];
  tr_mainloop<BN>(acc, p, sb, full, empty, nkb, wg);
  float* p0 = dst + (size_t)(wg * 64 + wi * 16 + (lane >> 2)) * cfg::DM + (lane & 3) * 2;
#pragma unroll
  for (int v = 0; v < BN / 8; v++) {
    *(float2*)(p0 + 8 * v) = make_float2(acc[4 * v], acc[4 * v + 1]);
    *(float2*)(p0 + 8 * cfg::DM + 8 * v) = make_float2(acc[4 * v + 2], acc[4 * v + 3]);
  }
}

__global__ void __launch_bounds__(384, 1) trail_kernel(const __grid_constant__ CUtensorMap tmX, const __grid_constant__ CUtensorMap tmQ,
                                                       const __grid_constant__ CUtensorMap tmO, const __grid_constant__ CUtensorMap tmWo,
                                                       const unsigned char* __restrict__ kg, const unsigned char* __restrict__ vg, bf16* __restrict__ o,
                                                       float* __restrict__ part, unsigned char* __restrict__ arena, PrepArgs pa, int doprep, int tl) {
  using namespace tr;
  TL_BEGIN(tl);
  extern __shared__ __align__(1024) unsigned char smem_raw[];
  const uint32_t sb = smem_u32(smem_raw);
  const int warp = threadIdx.x >> 5, lane = threadIdx.x & 31;
  const uint32_t full = sb + OFF_BAR, empty = full + 8 * NS, barK = empty + 8 * NS, barKfree = barK + 8;
  const uint32_t mfull = barKfree + 8, mempty = mfull + 16, mbox = mempty + 16;
  if (threadIdx.x == 0) {
    for (int i = 0; i < NS; i++) { mbar_init(full + 8 * i, 1); mbar_init(empty + 8 * i, 2); }
    mbar_init(barK, 1); mbar_init(barKfree, 8);
    for (int i = 0; i < 2; i++) { mbar_init(mfull + 8 * i, 1); mbar_init(mempty + 8 * i, 8); }
    asm volatile("fence.mbarrier_init.release.cluster;" ::: "memory");
  }
  __syncthreads();
  if (warp >= 8) {
    asm volatile("setmaxnreg.dec.sync.aligned.u32 40;");
    if (warp == 8 && lane == 0) {
      Pipe p{0, 1}, mp{0, 1};
      uint32_t kph = 1;
      auto stage = [&](uint32_t bytes) -> uint32_t {
        mbar_wait(empty + 8 * p.stage, p.phase);
        mbar_expect_tx(full + 8 * p.stage, bytes);
        return sb + p.stage * STAGE;
      };
      while (true) {
        const int item = (int)atomicAdd((unsigned*)(arena + AR_QUEUE), 1u);
        int type, m, k;
        decode(item, type, m, k);
        mbar_wait(mempty + 8 * mp.stage, mp.phase);
        asm volatile("st.shared.u32 [%0], %1;" :: "r"(mbox + 4 * mp.stage), "r"(item) : "memory");
        mbar_arrive(mfull + 8 * mp.stage);
        pipe_adv<2>(mp);
        if (type == T_END) break;
        if (type == T_QA) {
          const CUtensorMap* tb = &tmQ;
          const int head = k & 31;
          auto ready = [&](bool block) -> bool {
            for (int jj = 0; jj < 3; jj++) {
              const void* f = arena + AR_PROG + (head * 3 + jj) * 4;
              if (block) wait_ge(f, 4 * m + 4); else if (ld_acquire_u32(f) < (uint32_t)(4 * m + 4)) return false;
            }
            return true;
          };
          auto load_k = [&]() {
            mbar_wait(barKfree, kph); kph ^= 1;
            fence_proxy_async_all();
            mbar_expect_tx(barK, 4 * SEGB);
            for (int sg = 0; sg < 4; sg++) {
              const size_t blk = (size_t)(m * 4 + sg) * 96 + head * 3;
              bulk_g2s(sb + OFF_K + sg * SEGB, kg + blk * 5120, SEGB, barK);
            }
          };
          bool kdone = false;
          for (int kb = 0; kb < 10; kb++) {
            const uint32_t st = stage(16384 + 24576), fb = full + 8 * p.stage;
            tma_load_2d(st, &tmX, kb * 64, m * 128, fb);
#pragma unroll
            for (int b = 0; b < 3; b++) tma_load_2d(st + 16384 + b * 8192, tb, head * 192 + b * 64, kb * 64, fb);
            pipe_adv<NS>(p);
            if (!kdone && (kb == 2 || kb == 6) && ready(false)) { load_k(); kdone = true; }
          }
          if (type == T_QA) {
            if (!kdone) { ready(true); load_k(); }
            for (int hv = 0; hv < 2; hv++) {
              const uint32_t st = stage(2 * SEGB), fb = full + 8 * p.stage;
              for (int sg = 0; sg < 2; sg++) {
                const size_t blk = (size_t)(m * 4 + 2 * hv + sg) * 96 + head * 3;
                bulk_g2s(st + sg * SEGB, vg + blk * 5120, SEGB, fb);
              }
              pipe_adv<NS>(p);
            }
          }
        } else {
          wait_ge(arena + AR_CNT + m * 4, NQA * 8);
          fence_proxy_async_all();
          const int nt = k & 3, ks = k >> 2, nkb = 96 / o_split(m), nb = nt < 2 ? 3 : 2, k0 = ks * nkb * 64, c0 = nt < 2 ? nt * 192 : 384 + (nt - 2) * 128;
          for (int kb = 0; kb < nkb; kb++) {
            const uint32_t st = stage(16384 + nb * 8192), fb = full + 8 * p.stage;
            tma_load_2d(st, &tmO, k0 + kb * 64, m * 128, fb);
            for (int b = 0; b < nb; b++) tma_load_2d(st + 16384 + b * 8192, &tmWo, c0 + b * 64, k0 + kb * 64, fb);
            pipe_adv<NS>(p);
          }
        }
      }
    }
    if (blockIdx.x == gridDim.x - 1 && warp == 8) asm volatile("griddepcontrol.wait;" ::: "memory");
    return;
  }
  asm volatile("setmaxnreg.inc.sync.aligned.u32 232;");
  const int wg = warp >> 2, wi = warp & 3;
  const int g = lane >> 2, q4 = lane & 3;
  if (doprep && blockIdx.x < 32) for (int t = blockIdx.x * 8 + warp; t < PREP_TASKS; t += 256) prep_body(t, pa.wqkv, pa.wphi, pa.wo, pa.wb, pa.wot);
  Pipe p{0, 0}, mp{0, 0};
  uint32_t kph = 0;
  unsigned* pend = nullptr;
  auto publish = [&]() {
    if (pend) { __threadfence(); __syncwarp(); if (lane == 0) atomicAdd(pend, 1u); pend = nullptr; }
  };
  while (true) {
    int item;
    mbar_wait(mfull + 8 * mp.stage, mp.phase);
    asm volatile("ld.shared.u32 %0, [%1];" : "=r"(item) : "r"(mbox + 4 * mp.stage) : "memory");
    __syncwarp();
    if (lane == 0) mbar_arrive(mempty + 8 * mp.stage);
    pipe_adv<2>(mp);
    int type, m, k;
    decode(item, type, m, k);
    if (type != T_QA) publish();
    if (type == T_END) break;
    [[maybe_unused]] const unsigned long long ti0 = TL_NOW();
    if (type == T_O) {
      const int nt = k & 3, ks = k >> 2, nkb = 96 / o_split(m), c0 = nt < 2 ? nt * 192 : 384 + (nt - 2) * 128;
      float* dst = part + ((size_t)ks * cfg::S + m * 128) * cfg::DM + c0;
      if (nt >= 2) o_item<128>(p, sb, full, empty, nkb, dst, wg, wi, lane);
      else o_item<192>(p, sb, full, empty, nkb, dst, wg, wi, lane);
      TL_END(tl);
      TL2((tl >= 12 ? 128 : 0) + 64 + 16 + m);
      TL_ACC(40, ti0);
      continue;
    }
    float acc[96];
    tr_mainloop<192>(acc, p, sb, full, empty, 10, wg);
    publish();
    const int head = k & 31;
    TL_ACC(46, ti0);
    uint32_t qf[12][4];
#pragma unroll
    for (int k = 0; k < 12; k++) {
      qf[k][0] = pack_bf16(acc[8 * k], acc[8 * k + 1]); qf[k][1] = pack_bf16(acc[8 * k + 2], acc[8 * k + 3]);
      qf[k][2] = pack_bf16(acc[8 * k + 4], acc[8 * k + 5]); qf[k][3] = pack_bf16(acc[8 * k + 6], acc[8 * k + 7]);
    }
    const int sg = wg * 2 + (wi >> 1), half = wi & 1;
    const uint32_t kbase = sb + OFF_K + sg * SEGB;
    mbar_wait(barK, kph); kph ^= 1;
    float sc[5][4];
#pragma unroll
    for (int n = 0; n < 5; n++) { sc[n][0] = sc[n][1] = sc[n][2] = sc[n][3] = 0.f; }
    const int kr = lane & 7, kc = lane >> 3;
#pragma unroll
    for (int jj = 0; jj < 3; jj++) {
#pragma unroll
      for (int u = 0; u < 2; u++) {
        const int k0 = jj * 4 + u * 2;
#pragma unroll
        for (int n = 0; n < 4; n++) {
          if (n < 2 || half) {
            uint32_t b[4];
            ldsm_x4(b, kbase + jj * 5120 + (4 * u + kc) * 640 + n * 128 + kr * 16);
            mma16816(sc[n], qf[k0][0], qf[k0][1], qf[k0][2], qf[k0][3], b[0], b[1]);
            mma16816(sc[n], qf[k0 + 1][0], qf[k0 + 1][1], qf[k0 + 1][2], qf[k0 + 1][3], b[2], b[3]);
          }
        }
        uint32_t b[4];
        ldsm_x4(b, kbase + jj * 5120 + (4 * u + kc) * 640 + 512 + kr * 16);
        mma16816(sc[4], qf[k0][0], qf[k0][1], qf[k0][2], qf[k0][3], b[0], b[1]);
        mma16816(sc[4], qf[k0 + 1][0], qf[k0 + 1][1], qf[k0 + 1][2], qf[k0 + 1][3], b[2], b[3]);
      }
    }
    const float cs = 0.07216878364870322f * 1.4426950408889634f;
    const int r0 = 16 * half + g, r1 = r0 + 8;
    float m0 = -INFINITY, m1 = -INFINITY;
#pragma unroll
    for (int n = 0; n < 5; n++) {
#pragma unroll
      for (int e = 0; e < 2; e++) {
        const int key = 8 * n + 2 * q4 + e;
        if (n < 4) { if (key > r0) sc[n][e] = -INFINITY; if (key > r1) sc[n][2 + e] = -INFINITY; }
        m0 = fmaxf(m0, sc[n][e]); m1 = fmaxf(m1, sc[n][2 + e]);
      }
    }
    m0 = fmaxf(m0, __shfl_xor_sync(0xffffffffu, m0, 1)); m0 = fmaxf(m0, __shfl_xor_sync(0xffffffffu, m0, 2));
    m1 = fmaxf(m1, __shfl_xor_sync(0xffffffffu, m1, 1)); m1 = fmaxf(m1, __shfl_xor_sync(0xffffffffu, m1, 2));
    float s0 = 0.f, s1 = 0.f;
#pragma unroll
    for (int n = 0; n < 5; n++) {
#pragma unroll
      for (int e = 0; e < 2; e++) {
        sc[n][e] = ex2f((sc[n][e] - m0) * cs); sc[n][2 + e] = ex2f((sc[n][2 + e] - m1) * cs);
        s0 += sc[n][e]; s1 += sc[n][2 + e];
      }
    }
    s0 += __shfl_xor_sync(0xffffffffu, s0, 1); s0 += __shfl_xor_sync(0xffffffffu, s0, 2);
    s1 += __shfl_xor_sync(0xffffffffu, s1, 1); s1 += __shfl_xor_sync(0xffffffffu, s1, 2);
    const float i0 = 1.f / s0, i1 = 1.f / s1;
    uint32_t pf[3][4];
#pragma unroll
    for (int k = 0; k < 2; k++) {
      pf[k][0] = pack_bf16(sc[2 * k][0] * i0, sc[2 * k][1] * i0); pf[k][1] = pack_bf16(sc[2 * k][2] * i1, sc[2 * k][3] * i1);
      pf[k][2] = pack_bf16(sc[2 * k + 1][0] * i0, sc[2 * k + 1][1] * i0); pf[k][3] = pack_bf16(sc[2 * k + 1][2] * i1, sc[2 * k + 1][3] * i1);
    }
    pf[2][0] = pack_bf16(sc[4][0] * i0, sc[4][1] * i0); pf[2][1] = pack_bf16(sc[4][2] * i1, sc[4][3] * i1); pf[2][2] = 0u; pf[2][3] = 0u;
    TL_ACC(52, ti0);
    const uint32_t sA = p.stage, phA = p.phase; pipe_adv<NS>(p);
    const uint32_t sB = p.stage, phB = p.phase; pipe_adv<NS>(p);
    mbar_wait(full + 8 * sA, phA);
    mbar_wait(full + 8 * sB, phB);
    if ((threadIdx.x & 127) == 0) mbar_arrive(empty + 8 * (wg == 0 ? sB : sA));
    bar_sync(3, 256);
    const uint32_t vbase = sb + (wg == 0 ? sA : sB) * STAGE + (wi >> 1) * SEGB;
    const uint32_t ost = sb + OFF_OST + warp * 6144;
    const int vr = (lane & 7) + (((lane >> 3) & 1) << 3), vc = lane >> 4;
    const int tok0 = m * 128 + wg * 64 + wi * 16;
    uint32_t ow[12][4];
#pragma unroll
    for (int jj = 0; jj < 3; jj++) {
#pragma unroll
      for (int c2 = 0; c2 < 4; c2++) {
        float oa[4] = {0, 0, 0, 0}, ob[4] = {0, 0, 0, 0};
        uint32_t b[4];
        const int ch = 2 * c2 + vc;
        ldsm_x4_t(b, vbase + jj * 5120 + ch * 640 + vr * 16);
        mma16816(oa, pf[0][0], pf[0][1], pf[0][2], pf[0][3], b[0], b[1]);
        mma16816(ob, pf[0][0], pf[0][1], pf[0][2], pf[0][3], b[2], b[3]);
        if (half) {
          uint32_t b2[4];
          ldsm_x4_t(b2, vbase + jj * 5120 + ch * 640 + 256 + vr * 16);
          mma16816(oa, pf[1][0], pf[1][1], pf[1][2], pf[1][3], b2[0], b2[1]);
          mma16816(ob, pf[1][0], pf[1][1], pf[1][2], pf[1][3], b2[2], b2[3]);
        }
        uint32_t bm[2];
        { const int r = lane & 7, c = 2 * c2 + ((lane >> 3) & 1); ldsm_x2_t(bm, vbase + jj * 5120 + c * 640 + 512 + r * 16); }
        mma16816(oa, pf[2][0], pf[2][1], 0u, 0u, bm[0], 0u);
        mma16816(ob, pf[2][0], pf[2][1], 0u, 0u, bm[1], 0u);
        ow[jj * 4 + c2][0] = pack_bf16(oa[0], oa[1]); ow[jj * 4 + c2][1] = pack_bf16(oa[2], oa[3]);
        ow[jj * 4 + c2][2] = pack_bf16(ob[0], ob[1]); ow[jj * 4 + c2][3] = pack_bf16(ob[2], ob[3]);
      }
    }
    bar_sync(1 + wg, 128);
    if ((threadIdx.x & 127) == 0) mbar_arrive(empty + 8 * (wg == 0 ? sA : sB));
    {
      const int row = (lane & 7) + 8 * ((lane >> 3) & 1);
#pragma unroll
      for (int i = 0; i < 12; i++) {
        const int chunk = (i >> 2) * 8 + 2 * (i & 3) + (lane >> 4);
        stsm_x4(ost + row * 384 + (((chunk & ~7) | ((chunk & 7) ^ (row & 7))) << 4), ow[i][0], ow[i][1], ow[i][2], ow[i][3]);
      }
      __syncwarp();
      uint4 v[12];
#pragma unroll
      for (int i = 0; i < 12; i++) {
        const int c = lane + 32 * i, r = c / 24, chunk = c % 24;
        v[i] = lds128(ost + r * 384 + (((chunk & ~7) | ((chunk & 7) ^ (r & 7))) << 4));
      }
#pragma unroll
      for (int i = 0; i < 12; i++) {
        const int c = lane + 32 * i, r = c / 24, chunk = c % 24;
        *(uint4*)(o + (size_t)(tok0 + r) * cfg::HD + head * 192 + chunk * 8) = v[i];
      }
      __syncwarp();
    }
    if (lane == 0) mbar_arrive(barKfree);
    pend = (unsigned*)(arena + AR_CNT + m * 4);
    TL_END(tl + 1);
    TL2((tl >= 12 ? 128 : 0) + 64 + m);
    TL_ACC(50, ti0);
  }
}
namespace bf {
constexpr int NS = 4, STAGE = 16384 + 36864;
constexpr int PHI_STR = 112, PHI_HEAD = 128 * PHI_STR;
constexpr int V_STR = 48, V_HEAD = 128 * V_STR;
constexpr int OFF_PHI = 0, OFF_V = 4 * PHI_HEAD, OFF_X = OFF_V + 4 * V_HEAD;
constexpr int OFF_WOT = 100352;
constexpr int OFF_OST = 65536;
constexpr int ANS = 4;
constexpr int OFF_BAR = OFF_WOT + 12 * 10240;
constexpr int SMEM = OFF_BAR + 256;
static_assert(OFF_X + 4 * 36 * 128 <= OFF_WOT && NS * STAGE <= OFF_BAR && SMEM <= 232448, "smem");
}
__device__ __forceinline__ void hedgehog_features(const float (&x)[6], int q4, float (&pos)[6], float (&neg)[6]) {
  const bool v2 = q4 < 2;
  float mx = fmaxf(fmaxf(x[0], x[1]), fmaxf(x[2], x[3])), mn = fminf(fminf(x[0], x[1]), fminf(x[2], x[3]));
  if (v2) { mx = fmaxf(mx, fmaxf(x[4], x[5])); mn = fminf(mn, fminf(x[4], x[5])); }
  mx = fmaxf(mx, __shfl_xor_sync(0xffffffffu, mx, 1)); mn = fminf(mn, __shfl_xor_sync(0xffffffffu, mn, 1));
  mx = fmaxf(mx, __shfl_xor_sync(0xffffffffu, mx, 2)); mn = fminf(mn, __shfl_xor_sync(0xffffffffu, mn, 2));
  const float L = 1.4426950408889634f;
  float sp = 0.f, sn = 0.f;
#pragma unroll
  for (int i = 0; i < 6; i++) {
    const bool ok = i < 4 || v2;
    pos[i] = ok ? ex2f((x[i] - mx) * L) : 0.f;
    neg[i] = ok ? ex2f((mn - x[i]) * L) : 0.f;
    sp += pos[i]; sn += neg[i];
  }
  sp += __shfl_xor_sync(0xffffffffu, sp, 1); sn += __shfl_xor_sync(0xffffffffu, sn, 1);
  sp += __shfl_xor_sync(0xffffffffu, sp, 2); sn += __shfl_xor_sync(0xffffffffu, sn, 2);
  const float ip = rcpf(sp), in_ = rcpf(sn);
#pragma unroll
  for (int i = 0; i < 6; i++) { pos[i] *= ip; neg[i] *= in_; }
}

__global__ void __launch_bounds__(384, 1) blayer_kernel(const __grid_constant__ CUtensorMap tmA, const __grid_constant__ CUtensorMap tmB,
                                                        const __grid_constant__ CUtensorMap tmO, const __grid_constant__ CUtensorMap tmW,
                                                        float* __restrict__ kvacc, unsigned* __restrict__ cnt, bf16* __restrict__ o2,
                                                        const bf16* __restrict__ xin, bf16* __restrict__ xout,
                                                        const bf16* pf0, const bf16* pf1, const bf16* pf2, const bf16* pf3, int tl) {
  using namespace bf;
  TL_BEGIN(tl);
  extern __shared__ __align__(1024) unsigned char smem_raw[];
  const uint32_t sb = smem_u32(smem_raw);
  const int warp = threadIdx.x >> 5, lane = threadIdx.x & 31;
  const uint32_t full = sb + OFF_BAR, empty = full + 8 * NS, full2 = empty + 8 * NS, empty2 = full2 + 8 * ANS, barW = empty2 + 8 * ANS, barGo = barW + 8;
  const int m = blockIdx.x & 15, u = blockIdx.x >> 4;
  unsigned* cntKV = cnt + u; unsigned* cntO = cnt + 8 + m;
  if (threadIdx.x == 0) {
    for (int i = 0; i < NS; i++) { mbar_init(full + 8 * i, 1); mbar_init(empty + 8 * i, 2); }
    for (int i = 0; i < ANS; i++) { mbar_init(full2 + 8 * i, 1); mbar_init(empty2 + 8 * i, 2); }
    mbar_init(barW, 1); mbar_init(barGo, 1);
    asm volatile("fence.mbarrier_init.release.cluster;" ::: "memory");
  }
  __syncthreads();
  asm volatile("griddepcontrol.wait;" ::: "memory");
  asm volatile("griddepcontrol.launch_dependents;" ::: "memory");
  if (warp >= 8) {
    asm volatile("setmaxnreg.dec.sync.aligned.u32 40;");
    if (warp == 8 && lane == 0) {
      prefetch_tmap(&tmO); prefetch_tmap(&tmW);
      Pipe p{0, 1};
      for (int kb = 0; kb < 10; kb++) {
        mbar_wait(empty + 8 * p.stage, p.phase);
        const uint32_t st = sb + p.stage * STAGE, fb = full + 8 * p.stage;
        mbar_expect_tx(fb, STAGE);
        tma_load_2d(st, &tmA, kb * 64, m * 128, fb);
        tma_load_2d(st + 16384, &tmB, kb * 64, u * 288, fb);
        tma_load_2d(st + 16384 + 18432, &tmB, kb * 64, u * 288 + 144, fb);
        pipe_adv<NS>(p);
      }
      if (pf0) {
        constexpr uint32_t PER = cfg::DM * cfg::HD * 2 / 128;
        prefetch_l2((const unsigned char*)pf0 + blockIdx.x * PER, PER); prefetch_l2((const unsigned char*)pf1 + blockIdx.x * PER, PER);
        if (pf2) { prefetch_l2((const unsigned char*)pf2 + blockIdx.x * PER, PER); prefetch_l2((const unsigned char*)pf3 + blockIdx.x * PER, PER); }
      }
      for (int i = 0; i < NS; i++) { mbar_wait(empty + 8 * p.stage, p.phase); pipe_adv<NS>(p); }
      mbar_expect_tx(barW, 12 * 10240);
      for (int kb = 0; kb < 12; kb++) tma_load_2d(sb + OFF_WOT + kb * 10240, &tmW, kb * 64, u * 80, barW);
      mbar_wait(barGo, 0);
      wait_ge(cntO, 8);
      fence_proxy_async_all();
      Pipe q{0, 1};
      for (int kb = 0; kb < 12; kb++) {
        mbar_wait(empty2 + 8 * q.stage, q.phase);
        mbar_expect_tx(full2 + 8 * q.stage, 16384);
        tma_load_2d(sb + q.stage * 16384, &tmO, kb * 64, m * 128, full2 + 8 * q.stage);
        pipe_adv<ANS>(q);
      }
    }
    return;
  }
  asm volatile("setmaxnreg.inc.sync.aligned.u32 232;");
  const int wg = warp >> 2, wi = warp & 3;
  const int g = lane >> 2, q4 = lane & 3;
  float a0[72], a1[72];
  {
    Pipe p{0, 0};
    uint32_t prev = 0;
    for (int kb = 0; kb < 10; kb++) {
      mbar_wait(full + 8 * p.stage, p.phase);
      const uint32_t st = sb + p.stage * STAGE;
      wgmma_fence();
#pragma unroll
      for (int kk = 0; kk < 4; kk++) {
        const uint64_t da = desc_kmajor(st + wg * 8192 + kk * 32);
        wgmma_n144<0, 0>(a0, da, desc_kmajor(st + 16384 + kk * 32), (kb | kk) != 0);
        wgmma_n144<0, 0>(a1, da, desc_kmajor(st + 16384 + 18432 + kk * 32), (kb | kk) != 0);
      }
      wgmma_commit();
      if (kb > 0) { wgmma_wait<1>(); if ((threadIdx.x & 127) == 0) mbar_arrive(empty + 8 * prev); }
      prev = p.stage;
      pipe_adv<NS>(p);
    }
    wgmma_wait<0>();
    bar_sync(1, 256);
    if ((threadIdx.x & 127) == 0) mbar_arrive(empty + 8 * prev);
  }
  TL2((tl >= 12 ? 128 : 0) + 32 + 0);
  auto ACC = [&](auto V, auto E) -> float { constexpr int v = V.value, e = E.value; if constexpr (v < 18) return a0[4 * v + e]; else return a1[4 * (v - 18) + e]; };
  const int trow = wg * 64 + wi * 16;
  const int srow = (lane & 7) + 8 * ((lane >> 3) & 1);
  uint32_t qf[4][3][4];
  static_for<0, 4>([&](auto HH) {
    constexpr int hh = HH.value;
    float xa[6], xb[6], pa[6], na[6], pb[6], nb[6];
    static_for<0, 3>([&](auto T) {
      constexpr int t = T.value; using V = IC<3 * hh + t>;
      xa[2 * t] = ACC(V{}, IC<0>{}); xa[2 * t + 1] = ACC(V{}, IC<1>{}); xb[2 * t] = ACC(V{}, IC<2>{}); xb[2 * t + 1] = ACC(V{}, IC<3>{});
      bf16r2(xa[2 * t], xa[2 * t + 1]); bf16r2(xb[2 * t], xb[2 * t + 1]);
    });
    hedgehog_features(xa, q4, pa, na);
    hedgehog_features(xb, q4, pb, nb);
    qf[hh][0][0] = pack_bf16(pa[0], pa[1]); qf[hh][0][1] = pack_bf16(pb[0], pb[1]); qf[hh][0][2] = pack_bf16(pa[2], pa[3]); qf[hh][0][3] = pack_bf16(pb[2], pb[3]);
    qf[hh][1][0] = pack_bf16(pa[4], pa[5]); qf[hh][1][1] = pack_bf16(pb[4], pb[5]); qf[hh][1][2] = pack_bf16(na[0], na[1]); qf[hh][1][3] = pack_bf16(nb[0], nb[1]);
    qf[hh][2][0] = pack_bf16(na[2], na[3]); qf[hh][2][1] = pack_bf16(nb[2], nb[3]); qf[hh][2][2] = pack_bf16(na[4], na[5]); qf[hh][2][3] = pack_bf16(nb[4], nb[5]);
    static_for<0, 3>([&](auto T) {
      constexpr int t = T.value; using V = IC<12 + 3 * hh + t>;
      xa[2 * t] = ACC(V{}, IC<0>{}); xa[2 * t + 1] = ACC(V{}, IC<1>{}); xb[2 * t] = ACC(V{}, IC<2>{}); xb[2 * t + 1] = ACC(V{}, IC<3>{});
      bf16r2(xa[2 * t], xa[2 * t + 1]); bf16r2(xb[2 * t], xb[2 * t + 1]);
    });
    hedgehog_features(xa, q4, pa, na);
    hedgehog_features(xb, q4, pb, nb);
    const uint32_t ph = sb + OFF_PHI + hh * PHI_HEAD + (trow + srow) * PHI_STR + (lane >> 4) * 16;
    stsm_x4(ph, pack_bf16(pa[0], pa[1]), pack_bf16(pb[0], pb[1]), pack_bf16(pa[2], pa[3]), pack_bf16(pb[2], pb[3]));
    stsm_x4(ph + 32, pack_bf16(pa[4], pa[5]), pack_bf16(pb[4], pb[5]), pack_bf16(na[0], na[1]), pack_bf16(nb[0], nb[1]));
    stsm_x4(ph + 64, pack_bf16(na[2], na[3]), pack_bf16(nb[2], nb[3]), pack_bf16(na[4], na[5]), pack_bf16(nb[4], nb[5]));
    using V0 = IC<24 + 3 * hh>; using V1 = IC<24 + 3 * hh + 1>; using V2 = IC<24 + 3 * hh + 2>;
    float c0 = ACC(V2{}, IC<0>{}), c1 = ACC(V2{}, IC<1>{}), c2 = ACC(V2{}, IC<2>{}), c3 = ACC(V2{}, IC<3>{});
    if (q4 == 2) { c0 = 1.f; c1 = 0.f; c2 = 1.f; c3 = 0.f; }
    if (q4 == 3) { c0 = c1 = c2 = c3 = 0.f; }
    const uint32_t va = sb + OFF_V + hh * V_HEAD + (trow + srow) * V_STR;
    stsm_x4(va + (lane >> 4) * 16, pack_bf16(ACC(V0{}, IC<0>{}), ACC(V0{}, IC<1>{})), pack_bf16(ACC(V0{}, IC<2>{}), ACC(V0{}, IC<3>{})),
            pack_bf16(ACC(V1{}, IC<0>{}), ACC(V1{}, IC<1>{})), pack_bf16(ACC(V1{}, IC<2>{}), ACC(V1{}, IC<3>{})));
    stsm_x2(va + 32, pack_bf16(c0, c1), pack_bf16(c2, c3));
  });
  bar_sync(1, 256);
  TL2((tl >= 12 ? 128 : 0) + 32 + 1);
  {
    const int hh = warp >> 1, th = warp & 1;
    float d[3][3][4];
#pragma unroll
    for (int a = 0; a < 3; a++)
#pragma unroll
      for (int b = 0; b < 3; b++) { d[a][b][0] = d[a][b][1] = d[a][b][2] = d[a][b][3] = 0.f; }
#pragma unroll
    for (int ks = 0; ks < 4; ks++) {
      const int t0 = th * 64 + ks * 16;
      const uint32_t pa = sb + OFF_PHI + hh * PHI_HEAD + (t0 + (lane & 7) + 8 * (lane >> 4)) * PHI_STR + ((lane >> 3) & 1) * 16;
      const uint32_t pv = sb + OFF_V + hh * V_HEAD + (t0 + (lane & 7) + 8 * ((lane >> 3) & 1)) * V_STR;
      uint32_t b01[4], b2[2];
      ldsm_x4_t(b01, pv + (lane >> 4) * 16);
      ldsm_x2_t(b2, pv + 32);
#pragma unroll
      for (int a = 0; a < 3; a++) {
        uint32_t af[4];
        ldsm_x4_t(af, pa + a * 32);
        mma16816(d[a][0], af[0], af[1], af[2], af[3], b01[0], b01[1]);
        mma16816(d[a][1], af[0], af[1], af[2], af[3], b01[2], b01[3]);
        mma16816(d[a][2], af[0], af[1], af[2], af[3], b2[0], b2[1]);
      }
    }
    const uint32_t xa = sb + OFF_X + hh * (36 * 128) + lane * 4;
    if (th == 1) {
#pragma unroll
      for (int a = 0; a < 3; a++)
#pragma unroll
        for (int b = 0; b < 3; b++)
#pragma unroll
          for (int e = 0; e < 4; e++)
            asm volatile("st.shared.f32 [%0], %1;" :: "r"(xa + ((a * 3 + b) * 4 + e) * 128), "f"(d[a][b][e]) : "memory");
    }
    bar_sync(2 + hh, 64);
    if (th == 0) {
      float* dst = kvacc + (size_t)(u * 4 + hh) * (48 * 24);
#pragma unroll
      for (int a = 0; a < 3; a++)
#pragma unroll
        for (int b = 0; b < 3; b++) {
          float y[4];
#pragma unroll
          for (int e = 0; e < 4; e++) {
            float o;
            asm volatile("ld.shared.f32 %0, [%1];" : "=f"(o) : "r"(xa + ((a * 3 + b) * 4 + e) * 128) : "memory");
            y[e] = d[a][b][e] + o;
          }
          const int f0 = 16 * a + g, dd = 8 * b + 2 * q4;
          if (dd < 22) {
            asm volatile("red.relaxed.gpu.global.add.v2.f32 [%0], {%1,%2};" :: "l"(dst + f0 * 24 + dd), "f"(y[0]), "f"(y[1]) : "memory");
            asm volatile("red.relaxed.gpu.global.add.v2.f32 [%0], {%1,%2};" :: "l"(dst + (f0 + 8) * 24 + dd), "f"(y[2]), "f"(y[3]) : "memory");
          }
        }
      __threadfence();
    }
  }
  TL2((tl >= 12 ? 128 : 0) + 32 + 2);
  bar_sync(1, 256);
  if (threadIdx.x == 0) { __threadfence(); atomicAdd(cntKV, 1u); wait_ge(cntKV, 16); }
  bar_sync(1, 256);
  TL2((tl >= 12 ? 128 : 0) + 32 + 3);
  {
    float t[5][4];
#pragma unroll
    for (int it = 0; it < 5; it++) {
      const int i = min((int)threadIdx.x + 256 * it, 4 * 9 * 32 - 1);
      const int hh = i / 288, r = i % 288, tt = r >> 5, l = r & 31, ks = tt / 3, nt = tt % 3;
      const float* src = kvacc + (size_t)(u * 4 + hh) * (48 * 24) + (16 * ks + 2 * (l & 3)) * 24 + 8 * nt + (l >> 2);
      t[it][0] = __ldcg(src); t[it][1] = __ldcg(src + 24); t[it][2] = __ldcg(src + 8 * 24); t[it][3] = __ldcg(src + 9 * 24);
    }
#pragma unroll
    for (int it = 0; it < 5; it++) {
      const int i = threadIdx.x + 256 * it;
      if (i < 4 * 9 * 32) sts64(sb + OFF_X + i * 8, pack_bf16(t[it][0], t[it][1]), pack_bf16(t[it][2], t[it][3]));
    }
  }
  bar_sync(1, 256);
  {
    const uint32_t ost = sb + warp * 3072;
    uint32_t ow[4][6];
#pragma unroll
    for (int hh = 0; hh < 4; hh++) {
      float d[3][4];
#pragma unroll
      for (int n = 0; n < 3; n++) {
        d[n][0] = d[n][1] = d[n][2] = d[n][3] = 0.f;
        const uint32_t kb = sb + OFF_X + hh * 2304 + n * 256 + lane * 8;
        const uint2 k0 = lds64(kb), k1 = lds64(kb + 768), k2 = lds64(kb + 1536);
        mma16816(d[n], qf[hh][0][0], qf[hh][0][1], qf[hh][0][2], qf[hh][0][3], k0.x, k0.y);
        mma16816(d[n], qf[hh][1][0], qf[hh][1][1], qf[hh][1][2], qf[hh][1][3], k1.x, k1.y);
        mma16816(d[n], qf[hh][2][0], qf[hh][2][1], qf[hh][2][2], qf[hh][2][3], k2.x, k2.y);
      }
      const float da = bf16r(bf16r(__shfl_sync(0xffffffffu, d[2][0], (lane & ~3) | 2)) + 1e-6f);
      const float db = bf16r(bf16r(__shfl_sync(0xffffffffu, d[2][2], (lane & ~3) | 2)) + 1e-6f);
      float y[3][4];
#pragma unroll
      for (int n = 0; n < 3; n++) {
        bf16r2(d[n][0], d[n][1]); bf16r2(d[n][2], d[n][3]);
        y[n][0] = __fdividef(d[n][0], da); y[n][1] = __fdividef(d[n][1], da);
        y[n][2] = __fdividef(d[n][2], db); y[n][3] = __fdividef(d[n][3], db);
      }
      if (q4 >= 2) { y[2][0] = y[2][1] = y[2][2] = y[2][3] = 0.f; }
#pragma unroll
      for (int n = 0; n < 3; n++) { ow[hh][2 * n] = pack_bf16(y[n][0], y[n][1]); ow[hh][2 * n + 1] = pack_bf16(y[n][2], y[n][3]); }
    }
#pragma unroll
    for (int hh = 0; hh < 4; hh++) {
      const uint32_t ra = ost + srow * 192 + hh * 48;
      stsm_x4(ra + (lane >> 4) * 16, ow[hh][0], ow[hh][1], ow[hh][2], ow[hh][3]);
      stsm_x2(ra + 32, ow[hh][4], ow[hh][5]);
    }
    __syncwarp();
#pragma unroll
    for (int i = 0; i < 6; i++) {
      const int c = lane + 32 * i, row = c / 12, chunk = c % 12;
      const uint4 v = lds128(ost + row * 192 + chunk * 16);
      *(uint4*)(o2 + (size_t)(m * 128 + trow + row) * 768 + u * 96 + chunk * 8) = v;
    }
  }
  __threadfence();
  bar_sync(1, 256);
  if (threadIdx.x == 0) { atomicAdd(cntO, 1u); mbar_arrive(barGo); }
  TL2((tl >= 12 ? 128 : 0) + 32 + 4);
  float acc[40];
  uint4 xr[5];
#pragma unroll
  for (int i = 0; i < 5; i++) {
    const int c = lane + 32 * i;
    xr[i] = *(const uint4*)(xin + (size_t)(m * 128 + trow + c / 10) * cfg::DM + u * 80 + (c % 10) * 8);
  }
  mbar_wait(barW, 0);
  {
    Pipe p{0, 0};
    uint32_t prev = 0;
    for (int kb = 0; kb < 12; kb++) {
      mbar_wait(full2 + 8 * p.stage, p.phase);
      wgmma_fence();
#pragma unroll
      for (int kk = 0; kk < 4; kk++)
        wgmma_n80<0, 0>(acc, desc_kmajor(sb + p.stage * 16384 + wg * 8192 + kk * 32), desc_kmajor(sb + OFF_WOT + kb * 10240 + kk * 32), (kb | kk) != 0);
      wgmma_commit();
      if (kb > 0) { wgmma_wait<1>(); if ((threadIdx.x & 127) == 0) mbar_arrive(empty2 + 8 * prev); }
      prev = p.stage;
      pipe_adv<ANS>(p);
    }
    wgmma_wait<0>();
  }
  TL2((tl >= 12 ? 128 : 0) + 32 + 5);
  {
    const uint32_t ost = sb + OFF_OST + warp * 3072;
#pragma unroll
    for (int v = 0; v < 10; v += 2)
      stsm_x4(ost + srow * 176 + (v + (lane >> 4)) * 16, pack_bf16(acc[4 * v], acc[4 * v + 1]), pack_bf16(acc[4 * v + 2], acc[4 * v + 3]),
              pack_bf16(acc[4 * v + 4], acc[4 * v + 5]), pack_bf16(acc[4 * v + 6], acc[4 * v + 7]));
    __syncwarp();
#pragma unroll
    for (int i = 0; i < 5; i++) {
      const int c = lane + 32 * i, row = c / 10, chunk = c % 10;
      const uint4 y = lds128(ost + row * 176 + chunk * 16);
      const size_t off = (size_t)(m * 128 + trow + row) * cfg::DM + u * 80 + chunk * 8;
      const uint4 x = xr[i];
      *(uint4*)(xout + off) = make_uint4(pack_bf16(bf_lo(x.x) + bf_lo(y.x), bf_hi(x.x) + bf_hi(y.x)), pack_bf16(bf_lo(x.y) + bf_lo(y.y), bf_hi(x.y) + bf_hi(y.y)),
                                         pack_bf16(bf_lo(x.z) + bf_lo(y.z), bf_hi(x.z) + bf_hi(y.z)), pack_bf16(bf_lo(x.w) + bf_lo(y.w), bf_hi(x.w) + bf_hi(y.w)));
    }
  }
  TL_END(tl);
}
__device__ __align__(32768) unsigned char g_arena[AR_SIZE];
__device__ __align__(1024) uint2 g_xh[2048 * 160];
__device__ __align__(1024) unsigned char g_k[64 * 96 * 5120], g_v[64 * 96 * 5120];
__device__ __align__(1024) bf16 g_o[2048 * 6144];
__device__ __align__(1024) bf16 g_xn[2048 * 640], g_xa[2048 * 640], g_xb[2048 * 640];
__device__ __align__(1024) float g_part[8 * 2048 * 640];
__device__ __align__(1024) bf16 g_wb[2304 * 640], g_wot[640 * 768], g_pq[2048 * 768];
__device__ __align__(1024) float g_kvacc[32 * 48 * 24 + 64];

typedef CUresult (*EncodeFn)(CUtensorMap*, CUtensorMapDataType, cuuint32_t, void*, const cuuint64_t*, const cuuint64_t*, const cuuint32_t*,
                             const cuuint32_t*, CUtensorMapInterleave, CUtensorMapSwizzle, CUtensorMapL2promotion, CUtensorMapFloatOOBfill);
static EncodeFn g_encode = nullptr;
static CUtensorMap make_map(const void* p, uint64_t cols, uint64_t rows, uint32_t bc, uint32_t br, bool swz = true) {
  CUtensorMap m;
  cuuint64_t dims[2] = {cols, rows}, strides[1] = {cols * 2};
  cuuint32_t box[2] = {bc, br}, es[2] = {1, 1};
  g_encode(&m, CU_TENSOR_MAP_DATA_TYPE_BFLOAT16, 2, const_cast<void*>(p), dims, strides, box, es, CU_TENSOR_MAP_INTERLEAVE_NONE,
           swz ? CU_TENSOR_MAP_SWIZZLE_128B : CU_TENSOR_MAP_SWIZZLE_NONE, CU_TENSOR_MAP_L2_PROMOTION_L2_256B, CU_TENSOR_MAP_FLOAT_OOB_FILL_NONE);
  return m;
}
template <class T> static T* sym(const T& s) { void* p = nullptr; cudaGetSymbolAddress(&p, s); return (T*)p; }

struct Ptrs {
  unsigned char *arena, *k, *v; bf16 *o, *xn, *xa, *xb, *wb, *wot, *pq; float *part, *kvacc; uint2* xh;
};

#define PDL_LN 0
#define PDL_CH 1
#define PDL_B 1
#define PF_A 1
#define PF_B 1
extern "C" void kernel_launch(void* const* d_in, const int* in_sizes, int n_in, void* d_out, int out_size) {
  const bf16* x = (const bf16*)d_in[0];
  const bf16* mem0 = (const bf16*)d_in[1];
  const bf16 *Wq = (const bf16*)d_in[2], *Wk = (const bf16*)d_in[3], *Wv = (const bf16*)d_in[4], *Wo = (const bf16*)d_in[5];
  const bf16 *wqkv = (const bf16*)d_in[8], *wphi = (const bf16*)d_in[9], *wo = (const bf16*)d_in[10];
  bf16* out = (bf16*)d_out;
  static Ptrs P; static bool init = false;
  if (!init) {
    void* fn = nullptr; cudaDriverEntryPointQueryResult qr;
    cudaGetDriverEntryPoint("cuTensorMapEncodeTiled", &fn, cudaEnableDefault, &qr);
    g_encode = (EncodeFn)fn;
    void* p;
    cudaGetSymbolAddress(&p, g_arena); P.arena = (unsigned char*)p;
    cudaGetSymbolAddress(&p, g_k); P.k = (unsigned char*)p;   cudaGetSymbolAddress(&p, g_v); P.v = (unsigned char*)p;
    cudaGetSymbolAddress(&p, g_o); P.o = (bf16*)p;
    cudaGetSymbolAddress(&p, g_xn); P.xn = (bf16*)p;
    cudaGetSymbolAddress(&p, g_xa); P.xa = (bf16*)p;   cudaGetSymbolAddress(&p, g_xb); P.xb = (bf16*)p;
    cudaGetSymbolAddress(&p, g_wb); P.wb = (bf16*)p;   cudaGetSymbolAddress(&p, g_wot); P.wot = (bf16*)p;
    cudaGetSymbolAddress(&p, g_pq); P.pq = (bf16*)p;   cudaGetSymbolAddress(&p, g_part); P.part = (float*)p;
    cudaGetSymbolAddress(&p, g_kvacc); P.kvacc = (float*)p;
    cudaGetSymbolAddress(&p, g_xh); P.xh = (uint2*)p;
    cudaFuncSetAttribute(chain_kernel, cudaFuncAttributeMaxDynamicSharedMemorySize, ch::SMEM);
    cudaFuncSetAttribute(trail_kernel, cudaFuncAttributeMaxDynamicSharedMemorySize, tr::SMEM);
    cudaFuncSetAttribute(blayer_kernel, cudaFuncAttributeMaxDynamicSharedMemorySize, bf::SMEM);
    init = true;
  }
  const CUtensorMap tmXn = make_map(P.xn, 640, 2048, 64, 128);
  const CUtensorMap tmWq = make_map(Wq, 6144, 640, 64, 64);
  const CUtensorMap tmCq = make_map(Wq, 6144, 640, 64, 160), tmCk = make_map(Wk, 6144, 640, 64, 160), tmCv = make_map(Wv, 6144, 640, 64, 160), tmCo = make_map(Wo, 640, 6144, 224, 64, false);
  const CUtensorMap tmO = make_map(P.o, 6144, 2048, 64, 128), tmWo = make_map(Wo, 640, 6144, 64, 64);
  const CUtensorMap tmWb = make_map(P.wb, 640, 2304, 64, 144), tmO2 = make_map(P.pq, 768, 2048, 64, 128), tmWot = make_map(P.wot, 768, 640, 64, 80);

  ChainArgs ca;
  ca.xh = P.xh; ca.mem0 = mem0; ca.kg = P.k; ca.vg = P.v;
  ca.arena = P.arena; ca.dbg = nullptr; ca.tl = 0;
  uint4* zar = (uint4*)P.arena; const int nzar = AR_SIZE / 16;
  uint4* zkv = (uint4*)P.kvacc; const int nzkv = (32 * 48 * 24 + 64) / 4;

  const PrepArgs pa{wqkv, wphi, wo, P.wb, P.wot};
  const bf16* xcur = x;
  cudaLaunchAttribute at[1];
  at[0].id = cudaLaunchAttributeProgrammaticStreamSerialization; at[0].val.programmaticStreamSerializationAllowed = 1;
  auto cfgof = [&](int grid, int block, int smem, bool pdl) {
    cudaLaunchConfig_t lc = {};
    lc.gridDim = dim3(grid); lc.blockDim = dim3(block); lc.dynamicSmemBytes = smem; lc.stream = cudaStreamPerThread;
    lc.attrs = at; lc.numAttrs = pdl ? 1 : 0;
    return lc;
  };
  for (int layer = 0; layer < 2; layer++) {
    const int tl = layer * 12;
    cudaLaunchConfig_t lc = cfgof(256, 256, 0, layer > 0 && PDL_LN);
    cudaLaunchKernelEx(&lc, ln_kernel<0>, xcur, (const float*)nullptr, (bf16*)nullptr, P.xn, P.xh, zar, nzar, (uint4*)nullptr, 0, Wk, Wv, layer == 0 ? PF_A : 0, tl + 0);
    ca.tl = tl + 2;
    lc = cfgof(96, 384, ch::SMEM, PDL_CH);
    cudaLaunchKernelEx(&lc, chain_kernel, ca, tmCq, tmCk, tmCv, tmCo);
    lc = cfgof(132, 384, tr::SMEM, true);
    cudaLaunchKernelEx(&lc, trail_kernel, tmXn, tmWq, tmO, tmWo, (const unsigned char*)P.k, (const unsigned char*)P.v, P.o, P.part, P.arena, pa, layer == 0 ? 1 : 0, tl + 4);
    lc = cfgof(256, 256, 0, false);
    cudaLaunchKernelEx(&lc, ln_kernel<4>, xcur, (const float*)P.part, P.xa, P.xn, (uint2*)nullptr, (uint4*)nullptr, 0, zkv, nzkv, Wk, Wv, 0, tl + 6);
    lc = cfgof(128, 384, bf::SMEM, PDL_B);
    cudaLaunchKernelEx(&lc, blayer_kernel, tmXn, tmWb, tmO2, tmWot, P.kvacc, (unsigned*)(P.kvacc + 32 * 48 * 24), P.pq, (const bf16*)P.xa, layer == 0 ? P.xb : out,
                       layer == 0 && PF_B ? Wk : nullptr, Wv, PF_B > 1 ? Wq : nullptr, Wo, tl + 7);
    xcur = P.xb;
  }
}
```

```cpp
#include <cuda_runtime.h>
#include <cuda.h>
#include <cuda_bf16.h>
#include <stdint.h>
#include <type_traits>

typedef __nv_bfloat16 bf16;

namespace cfg {
constexpr int S = 2048, DM = 640, H = 32, DH = 192, NSEG = 64, SEG = 32, NM = 8;
constexpr int HD = H * DH;
}

__device__ __forceinline__ uint32_t smem_u32(const void* p) { return (uint32_t)__cvta_generic_to_shared(p); }
__device__ __forceinline__ uint32_t mapa_u32(uint32_t a, uint32_t r) {
  uint32_t o; asm("mapa.shared::cluster.u32 %0, %1, %2;" : "=r"(o) : "r"(a), "r"(r)); return o;
}
__device__ __forceinline__ void mbar_init(uint32_t b, uint32_t c) {
  asm volatile("mbarrier.init.shared::cta.b64 [%0], %1;" :: "r"(b), "r"(c) : "memory");
}
__device__ __forceinline__ void mbar_expect_tx(uint32_t b, uint32_t bytes) {
  asm volatile("mbarrier.arrive.expect_tx.shared::cta.b64 _, [%0], %1;" :: "r"(b), "r"(bytes) : "memory");
}
__device__ __forceinline__ void mbar_arrive(uint32_t b) {
  asm volatile("mbarrier.arrive.shared::cta.b64 _, [%0];" :: "r"(b) : "memory");
}
__device__ __forceinline__ bool mbar_try(uint32_t b, uint32_t ph) {
  uint32_t p;
  asm volatile("{.reg .pred p; mbarrier.try_wait.parity.shared::cta.b64 p, [%1], %2; selp.u32 %0, 1, 0, p;}"
               : "=r"(p) : "r"(b), "r"(ph) : "memory");
  return p;
}
__device__ __forceinline__ bool mbar_try_cluster(uint32_t b, uint32_t ph) {
  uint32_t p;
  asm volatile("{.reg .pred p; mbarrier.try_wait.parity.acquire.cluster.shared::cta.b64 p, [%1], %2; selp.u32 %0, 1, 0, p;}"
               : "=r"(p) : "r"(b), "r"(ph) : "memory");
  return p;
}
#define SPIN_LIMIT (1 << 22)
__device__ __forceinline__ void mbar_wait(uint32_t b, uint32_t ph) {
  asm volatile("{\n.reg .pred p, q;\n.reg .u32 c;\nmov.u32 c, 0;\n"
               "W_%=:\nmbarrier.try_wait.parity.shared::cta.b64 p, [%0], %1;\n@p bra D_%=;\n"
               "add.u32 c, c, 1;\nsetp.lt.u32 q, c, %2;\n@q bra W_%=;\nD_%=:\n}"
               :: "r"(b), "r"(ph), "n"(SPIN_LIMIT) : "memory");
}
__device__ __forceinline__ void mbar_spin(uint32_t b, uint32_t ph) {
  asm volatile("{\n.reg .pred p, q;\n.reg .u32 c;\nmov.u32 c, 0;\n"
               "W_%=:\nmbarrier.test_wait.parity.shared::cta.b64 p, [%0], %1;\n@p bra D_%=;\n"
               "add.u32 c, c, 1;\nsetp.lt.u32 q, c, %2;\n@q bra W_%=;\nD_%=:\n}"
               :: "r"(b), "r"(ph), "n"(SPIN_LIMIT) : "memory");
}
#define PIN(x) asm volatile("" : "+r"(x))
__device__ __forceinline__ void mbar_wait_cluster(uint32_t b, uint32_t ph) {
  int s = 0;
  while (!mbar_try_cluster(b, ph)) { if (++s > SPIN_LIMIT) break; }
}
__device__ __forceinline__ void st_async_v2(uint32_t a, uint32_t x, uint32_t y, uint32_t mb) {
  asm volatile("st.async.weak.shared::cluster.mbarrier::complete_tx::bytes.v2.b32 [%0], {%1,%2}, [%3];"
               :: "r"(a), "r"(x), "r"(y), "r"(mb) : "memory");
}
__device__ __forceinline__ void st_async_v4(uint32_t a, uint32_t x, uint32_t y, uint32_t z, uint32_t w, uint32_t mb) {
  asm volatile("st.async.weak.shared::cluster.mbarrier::complete_tx::bytes.v4.b32 [%0], {%1,%2,%3,%4}, [%5];"
               :: "r"(a), "r"(x), "r"(y), "r"(z), "r"(w), "r"(mb) : "memory");
}
__device__ __forceinline__ void bulk_g2s(uint32_t dst, const void* src, uint32_t bytes, uint32_t mb) {
  asm volatile("cp.async.bulk.shared::cluster.global.mbarrier::complete_tx::bytes [%0], [%1], %2, [%3];"
               :: "r"(dst), "l"(src), "r"(bytes), "r"(mb) : "memory");
}
__device__ __forceinline__ void cp_async16(uint32_t dst, const void* src) {
  asm volatile("cp.async.cg.shared.global [%0], [%1], 16;" :: "r"(dst), "l"(src) : "memory");
}
__device__ __forceinline__ void cp_async_wait_all() { asm volatile("cp.async.wait_all;" ::: "memory"); }
__device__ __forceinline__ void fence_proxy_async() { asm volatile("fence.proxy.async.shared::cta;" ::: "memory"); }
__device__ __forceinline__ void bar_sync(int id, int n) { asm volatile("bar.sync %0, %1;" :: "r"(id), "r"(n) : "memory"); }
__device__ __forceinline__ void bar_arrive(int id, int n) { asm volatile("bar.arrive %0, %1;" :: "r"(id), "r"(n) : "memory"); }
__device__ __forceinline__ void cluster_sync_all() {
  asm volatile("barrier.cluster.arrive.release.aligned; barrier.cluster.wait.acquire.aligned;" ::: "memory");
}
__device__ __forceinline__ void ldsm_x4(uint32_t (&r)[4], uint32_t a) {
  asm volatile("ldmatrix.sync.aligned.m8n8.x4.shared.b16 {%0,%1,%2,%3}, [%4];"
               : "=r"(r[0]), "=r"(r[1]), "=r"(r[2]), "=r"(r[3]) : "r"(a) : "memory");
}
__device__ __forceinline__ void ldsm_x4_t(uint32_t (&r)[4], uint32_t a) {
  asm volatile("ldmatrix.sync.aligned.m8n8.x4.trans.shared.b16 {%0,%1,%2,%3}, [%4];"
               : "=r"(r[0]), "=r"(r[1]), "=r"(r[2]), "=r"(r[3]) : "r"(a) : "memory");
}
template <int IMM> __device__ __forceinline__ void ldsm_x4_i(uint32_t (&r)[4], uint32_t a) {
  asm volatile("ldmatrix.sync.aligned.m8n8.x4.shared.b16 {%0,%1,%2,%3}, [%4+%5];"
               : "=r"(r[0]), "=r"(r[1]), "=r"(r[2]), "=r"(r[3]) : "r"(a), "n"(IMM) : "memory");
}
template <int IMM> __device__ __forceinline__ void ldsm_x4_t_i(uint32_t (&r)[4], uint32_t a) {
  asm volatile("ldmatrix.sync.aligned.m8n8.x4.trans.shared.b16 {%0,%1,%2,%3}, [%4+%5];"
               : "=r"(r[0]), "=r"(r[1]), "=r"(r[2]), "=r"(r[3]) : "r"(a), "n"(IMM) : "memory");
}
template <int IMM> __device__ __forceinline__ uint4 lds128_i(uint32_t a) {
  uint4 v; asm volatile("ld.shared.v4.u32 {%0,%1,%2,%3}, [%4+%5];" : "=r"(v.x), "=r"(v.y), "=r"(v.z), "=r"(v.w) : "r"(a), "n"(IMM) : "memory"); return v;
}
template <int IMM> __device__ __forceinline__ uint2 lds64_i(uint32_t a) {
  uint2 v; asm volatile("ld.shared.v2.u32 {%0,%1}, [%2+%3];" : "=r"(v.x), "=r"(v.y) : "r"(a), "n"(IMM) : "memory"); return v;
}
template <int IMM> __device__ __forceinline__ void sts128_i(uint32_t a, uint32_t x, uint32_t y, uint32_t z, uint32_t w) {
  asm volatile("st.shared.v4.u32 [%0+%5], {%1,%2,%3,%4};" :: "r"(a), "r"(x), "r"(y), "r"(z), "r"(w), "n"(IMM) : "memory");
}
template <int IMM> __device__ __forceinline__ void sts64_i(uint32_t a, uint32_t x, uint32_t y) {
  asm volatile("st.shared.v2.u32 [%0+%3], {%1,%2};" :: "r"(a), "r"(x), "r"(y), "n"(IMM) : "memory");
}
template <int IMM> __device__ __forceinline__ void st_async_v2_i(uint32_t a, uint32_t x, uint32_t y, uint32_t mb) {
  asm volatile("st.async.weak.shared::cluster.mbarrier::complete_tx::bytes.v2.b32 [%0+%4], {%1,%2}, [%3];"
               :: "r"(a), "r"(x), "r"(y), "r"(mb), "n"(IMM) : "memory");
}
template <int IMM> __device__ __forceinline__ uint4 ld_relaxed_v4_i(const void* p) {
  uint4 v; asm volatile("ld.relaxed.gpu.global.v4.u32 {%0,%1,%2,%3}, [%4+%5];" : "=r"(v.x), "=r"(v.y), "=r"(v.z), "=r"(v.w) : "l"(p), "n"(IMM) : "memory"); return v;
}
template <int I, int N, class F> __device__ __forceinline__ void static_for(F&& f) {
  if constexpr (I < N) { f(std::integral_constant<int, I>{}); static_for<I + 1, N>(f); }
}
__device__ __forceinline__ uint32_t movm_t(uint32_t a) {
  uint32_t d; asm volatile("movmatrix.sync.aligned.m8n8.trans.b16 %0, %1;" : "=r"(d) : "r"(a)); return d;
}
__device__ __forceinline__ void mma16816(float (&d)[4], uint32_t a0, uint32_t a1, uint32_t a2, uint32_t a3, uint32_t b0, uint32_t b1) {
  asm volatile("mma.sync.aligned.m16n8k16.row.col.f32.bf16.bf16.f32 {%0,%1,%2,%3}, {%4,%5,%6,%7}, {%8,%9}, {%0,%1,%2,%3};"
               : "+f"(d[0]), "+f"(d[1]), "+f"(d[2]), "+f"(d[3]) : "r"(a0), "r"(a1), "r"(a2), "r"(a3), "r"(b0), "r"(b1));
}
__device__ __forceinline__ uint32_t pack_bf16(float lo, float hi) {
  uint32_t d; asm("cvt.rn.bf16x2.f32 %0, %1, %2;" : "=r"(d) : "f"(hi), "f"(lo)); return d;
}
__device__ __forceinline__ float bf_lo(uint32_t w) { return __uint_as_float(w << 16); }
__device__ __forceinline__ float bf_hi(uint32_t w) { return __uint_as_float(w & 0xffff0000u); }
__device__ __forceinline__ uint4 lds128(uint32_t a) {
  uint4 v; asm volatile("ld.shared.v4.u32 {%0,%1,%2,%3}, [%4];" : "=r"(v.x), "=r"(v.y), "=r"(v.z), "=r"(v.w) : "r"(a) : "memory"); return v;
}
__device__ __forceinline__ uint2 lds64(uint32_t a) {
  uint2 v; asm volatile("ld.shared.v2.u32 {%0,%1}, [%2];" : "=r"(v.x), "=r"(v.y) : "r"(a) : "memory"); return v;
}
__device__ __forceinline__ void sts128(uint32_t a, uint32_t x, uint32_t y, uint32_t z, uint32_t w) {
  asm volatile("st.shared.v4.u32 [%0], {%1,%2,%3,%4};" :: "r"(a), "r"(x), "r"(y), "r"(z), "r"(w) : "memory");
}
__device__ __forceinline__ void sts64(uint32_t a, uint32_t x, uint32_t y) {
  asm volatile("st.shared.v2.u32 [%0], {%1,%2};" :: "r"(a), "r"(x), "r"(y) : "memory");
}
__device__ __forceinline__ uint4 ld_relaxed_v4(const void* p) {
  uint4 v; asm volatile("ld.relaxed.gpu.global.v4.u32 {%0,%1,%2,%3}, [%4];" : "=r"(v.x), "=r"(v.y), "=r"(v.z), "=r"(v.w) : "l"(p) : "memory"); return v;
}
__device__ __forceinline__ uint32_t ld_relaxed_u32(const void* p) {
  uint32_t v; asm volatile("ld.relaxed.gpu.global.u32 %0, [%1];" : "=r"(v) : "l"(p) : "memory"); return v;
}
__device__ __forceinline__ void st_relaxed_v2(void* p, uint32_t a, uint32_t b) {
  asm volatile("st.relaxed.gpu.global.v2.u32 [%0], {%1,%2};" :: "l"(p), "r"(a), "r"(b) : "memory");
}
__device__ __forceinline__ void st_relaxed_u32(void* p, uint32_t v) {
  asm volatile("st.relaxed.gpu.global.u32 [%0], %1;" :: "l"(p), "r"(v) : "memory");
}
__device__ __forceinline__ uint32_t clk32() { uint32_t c; asm volatile("mov.u32 %0, %%clock;" : "=r"(c) :: "memory"); return c; }
__device__ __forceinline__ uint32_t clkdep(uint32_t v) {
  uint32_t c; asm volatile("{.reg .pred p; setp.eq.u32 p, %1, 0xdeadbeef; @p trap; mov.u32 %0, %%clock;}" : "=r"(c) : "r"(v) : "memory"); return c;
}
__device__ __forceinline__ void wgmma_fence() { asm volatile("wgmma.fence.sync.aligned;" ::: "memory"); }
__device__ __forceinline__ void wgmma_commit() { asm volatile("wgmma.commit_group.sync.aligned;" ::: "memory"); }
template <int N> __device__ __forceinline__ void wgmma_wait() { asm volatile("wgmma.wait_group.sync.aligned %0;" :: "n"(N) : "memory"); }
__device__ __forceinline__ void wgmma_n8_ss_ta(float (&d)[4], uint64_t da, uint64_t db, int acc) {
  asm volatile("{\n.reg .pred p;\nsetp.ne.b32 p, %6, 0;\n"
               "wgmma.mma_async.sync.aligned.m64n8k16.f32.bf16.bf16 {%0,%1,%2,%3}, %4, %5, p, 1, 1, 1, 0;\n}\n"
               : "+f"(d[0]), "+f"(d[1]), "+f"(d[2]), "+f"(d[3]) : "l"(da), "l"(db), "r"(acc));
}
__device__ __forceinline__ uint64_t make_desc(uint32_t saddr, uint32_t lbo_bytes, uint32_t sbo_bytes, uint32_t swz) {
  return (uint64_t)((saddr & 0x3FFFF) >> 4) | ((uint64_t)(lbo_bytes >> 4) << 16) | ((uint64_t)(sbo_bytes >> 4) << 32) | ((uint64_t)swz << 62);
}

__device__ __forceinline__ bool elect_one() {
  uint32_t p; asm volatile("{\n.reg .pred p;\nelect.sync _|p, 0xffffffff;\nselp.u32 %0, 1, 0, p;\n}" : "=r"(p)); return p;
}
__device__ __forceinline__ void tma_load_3d(uint32_t dst, const CUtensorMap* tm, int c0, int c1, int c2, uint32_t mb) {
  asm volatile("cp.async.bulk.tensor.3d.shared::cluster.global.mbarrier::complete_tx::bytes [%0], [%1, {%3, %4, %5}], [%2];"
               :: "r"(dst), "l"(tm), "r"(mb), "r"(c0), "r"(c1), "r"(c2) : "memory");
}
__device__ __forceinline__ void tma_load_2d(uint32_t dst, const CUtensorMap* tm, int c0, int c1, uint32_t mb) {
  asm volatile("cp.async.bulk.tensor.2d.shared::cluster.global.mbarrier::complete_tx::bytes [%0], [%1, {%3, %4}], [%2];"
               :: "r"(dst), "l"(tm), "r"(mb), "r"(c0), "r"(c1) : "memory");
}
__device__ __forceinline__ void bulk_s2g(void* dst, uint32_t src, uint32_t bytes) {
  asm volatile("cp.async.bulk.global.shared::cta.bulk_group [%0], [%1], %2;" :: "l"(dst), "r"(src), "r"(bytes) : "memory");
}
__device__ __forceinline__ uint64_t policy_evict_first() {
  uint64_t p; asm volatile("createpolicy.fractional.L2::evict_first.b64 %0, 1.0;" : "=l"(p)); return p;
}
__device__ __forceinline__ void bulk_s2g_hint(void* dst, uint32_t src, uint32_t bytes, uint64_t pol) {
  asm volatile("cp.async.bulk.global.shared::cta.bulk_group.L2::cache_hint [%0], [%1], %2, %3;" :: "l"(dst), "r"(src), "r"(bytes), "l"(pol) : "memory");
}
__device__ __forceinline__ void bulk_commit() { asm volatile("cp.async.bulk.commit_group;" ::: "memory"); }
template <int N> __device__ __forceinline__ void bulk_wait_read() { asm volatile("cp.async.bulk.wait_group.read %0;" :: "n"(N) : "memory"); }
template <int N> __device__ __forceinline__ void bulk_wait() { asm volatile("cp.async.bulk.wait_group %0;" :: "n"(N) : "memory"); }
__device__ __forceinline__ void stsm_x4(uint32_t a, uint32_t r0, uint32_t r1, uint32_t r2, uint32_t r3) {
  asm volatile("stmatrix.sync.aligned.m8n8.x4.shared.b16 [%0], {%1,%2,%3,%4};" :: "r"(a), "r"(r0), "r"(r1), "r"(r2), "r"(r3) : "memory");
}
__device__ __forceinline__ void stsm_x2(uint32_t a, uint32_t r0, uint32_t r1) {
  asm volatile("stmatrix.sync.aligned.m8n8.x2.shared.b16 [%0], {%1,%2};" :: "r"(a), "r"(r0), "r"(r1) : "memory");
}
__device__ __forceinline__ void ldsm_x2(uint32_t (&r)[2], uint32_t a) {
  asm volatile("ldmatrix.sync.aligned.m8n8.x2.shared.b16 {%0,%1}, [%2];" : "=r"(r[0]), "=r"(r[1]) : "r"(a) : "memory");
}
__device__ __forceinline__ void ldsm_x2_t(uint32_t (&r)[2], uint32_t a) {
  asm volatile("ldmatrix.sync.aligned.m8n8.x2.trans.shared.b16 {%0,%1}, [%2];" : "=r"(r[0]), "=r"(r[1]) : "r"(a) : "memory");
}
__device__ __forceinline__ float bf16r(float x) { return __uint_as_float(pack_bf16(0.f, x) & 0xffff0000u); }
__device__ __forceinline__ void bf16r2(float& a, float& b) { const uint32_t w = pack_bf16(a, b); a = bf_lo(w); b = bf_hi(w); }
__device__ __forceinline__ float rcpf(float x) { float r; asm("rcp.approx.ftz.f32 %0, %1;" : "=f"(r) : "f"(x)); return r; }
__device__ __forceinline__ float ex2f(float x) { float e; asm("ex2.approx.ftz.f32 %0, %1;" : "=f"(e) : "f"(x)); return e; }
__device__ __forceinline__ void prefetch_tmap(const CUtensorMap* tm) { asm volatile("prefetch.tensormap [%0];" :: "l"(tm) : "memory"); }

#define TL_ACC(idx, t0)
#define TL_NOW() 0ull
#define TL2(idx)
#define TL_BEGIN(id)
#define TL_END(id)
template <int TA, int TB> __device__ __forceinline__ void wgmma_n192(float (&d)[96], uint64_t da, uint64_t db, int acc) {
  asm volatile("{\n.reg .pred p;\nsetp.ne.b32 p, %98, 0;\n"
    "wgmma.mma_async.sync.aligned.m64n192k16.f32.bf16.bf16 {%0, %1, %2, %3, %4, %5, %6, %7, %8, %9, %10, %11, %12, %13, %14, %15, %16, %17, %18, %19, %20, %21, %22, %23, %24, %25, %26, %27, %28, %29, %30, %31, %32, %33, %34, %35, %36, %37, %38, %39, %40, %41, %42, %43, %44, %45, %46, %47, %48, %49, %50, %51, %52, %53, %54, %55, %56, %57, %58, %59, %60, %61, %62, %63, %64, %65, %66, %67, %68, %69, %70, %71, %72, %73, %74, %75, %76, %77, %78, %79, %80, %81, %82, %83, %84, %85, %86, %87, %88, %89, %90, %91, %92, %93, %94, %95}, %96, %97, p, 1, 1, %99, %100;\n}\n"
    : "+f"(d[0]), "+f"(d[1]), "+f"(d[2]), "+f"(d[3]), "+f"(d[4]), "+f"(d[5]), "+f"(d[6]), "+f"(d[7]), "+f"(d[8]), "+f"(d[9]), "+f"(d[10]), "+f"(d[11]), "+f"(d[12]), "+f"(d[13]), "+f"(d[14]), "+f"(d[15]), "+f"(d[16]), "+f"(d[17]), "+f"(d[18]), "+f"(d[19]), "+f"(d[20]), "+f"(d[21]), "+f"(d[22]), "+f"(d[23]), "+f"(d[24]), "+f"(d[25]), "+f"(d[26]), "+f"(d[27]), "+f"(d[28]), "+f"(d[29]), "+f"(d[30]), "+f"(d[31]), "+f"(d[32]), "+f"(d[33]), "+f"(d[34]), "+f"(d[35]), "+f"(d[36]), "+f"(d[37]), "+f"(d[38]), "+f"(d[39]), "+f"(d[40]), "+f"(d[41]), "+f"(d[42]), "+f"(d[43]), "+f"(d[44]), "+f"(d[45]), "+f"(d[46]), "+f"(d[47]), "+f"(d[48]), "+f"(d[49]), "+f"(d[50]), "+f"(d[51]), "+f"(d[52]), "+f"(d[53]), "+f"(d[54]), "+f"(d[55]), "+f"(d[56]), "+f"(d[57]), "+f"(d[58]), "+f"(d[59]), "+f"(d[60]), "+f"(d[61]), "+f"(d[62]), "+f"(d[63]), "+f"(d[64]), "+f"(d[65]), "+f"(d[66]), "+f"(d[67]), "+f"(d[68]), "+f"(d[69]), "+f"(d[70]), "+f"(d[71]), "+f"(d[72]), "+f"(d[73]), "+f"(d[74]), "+f"(d[75]), "+f"(d[76]), "+f"(d[77]), "+f"(d[78]), "+f"(d[79]), "+f"(d[80]), "+f"(d[81]), "+f"(d[82]), "+f"(d[83]), "+f"(d[84]), "+f"(d[85]), "+f"(d[86]), "+f"(d[87]), "+f"(d[88]), "+f"(d[89]), "+f"(d[90]), "+f"(d[91]), "+f"(d[92]), "+f"(d[93]), "+f"(d[94]), "+f"(d[95])
    : "l"(da), "l"(db), "r"(acc), "n"(TA), "n"(TB));
}

template <int TA, int TB> __device__ __forceinline__ void wgmma_n256(float (&d)[128], uint64_t da, uint64_t db, int acc) {
  asm volatile("{\n.reg .pred p;\nsetp.ne.b32 p, %130, 0;\n"
    "wgmma.mma_async.sync.aligned.m64n256k16.f32.bf16.bf16 {%0, %1, %2, %3, %4, %5, %6, %7, %8, %9, %10, %11, %12, %13, %14, %15, %16, %17, %18, %19, %20, %21, %22, %23, %24, %25, %26, %27, %28, %29, %30, %31, %32, %33, %34, %35, %36, %37, %38, %39, %40, %41, %42, %43, %44, %45, %46, %47, %48, %49, %50, %51, %52, %53, %54, %55, %56, %57, %58, %59, %60, %61, %62, %63, %64, %65, %66, %67, %68, %69, %70, %71, %72, %73, %74, %75, %76, %77, %78, %79, %80, %81, %82, %83, %84, %85, %86, %87, %88, %89, %90, %91, %92, %93, %94, %95, %96, %97, %98, %99, %100, %101, %102, %103, %104, %105, %106, %107, %108, %109, %110, %111, %112, %113, %114, %115, %116, %117, %118, %119, %120, %121, %122, %123, %124, %125, %126, %127}, %128, %129, p, 1, 1, %131, %132;\n}\n"
    : "+f"(d[0]), "+f"(d[1]), "+f"(d[2]), "+f"(d[3]), "+f"(d[4]), "+f"(d[5]), "+f"(d[6]), "+f"(d[7]), "+f"(d[8]), "+f"(d[9]), "+f"(d[10]), "+f"(d[11]), "+f"(d[12]), "+f"(d[13]), "+f"(d[14]), "+f"(d[15]), "+f"(d[16]), "+f"(d[17]), "+f"(d[18]), "+f"(d[19]), "+f"(d[20]), "+f"(d[21]), "+f"(d[22]), "+f"(d[23]), "+f"(d[24]), "+f"(d[25]), "+f"(d[26]), "+f"(d[27]), "+f"(d[28]), "+f"(d[29]), "+f"(d[30]), "+f"(d[31]), "+f"(d[32]), "+f"(d[33]), "+f"(d[34]), "+f"(d[35]), "+f"(d[36]), "+f"(d[37]), "+f"(d[38]), "+f"(d[39]), "+f"(d[40]), "+f"(d[41]), "+f"(d[42]), "+f"(d[43]), "+f"(d[44]), "+f"(d[45]), "+f"(d[46]), "+f"(d[47]), "+f"(d[48]), "+f"(d[49]), "+f"(d[50]), "+f"(d[51]), "+f"(d[52]), "+f"(d[53]), "+f"(d[54]), "+f"(d[55]), "+f"(d[56]), "+f"(d[57]), "+f"(d[58]), "+f"(d[59]), "+f"(d[60]), "+f"(d[61]), "+f"(d[62]), "+f"(d[63]), "+f"(d[64]), "+f"(d[65]), "+f"(d[66]), "+f"(d[67]), "+f"(d[68]), "+f"(d[69]), "+f"(d[70]), "+f"(d[71]), "+f"(d[72]), "+f"(d[73]), "+f"(d[74]), "+f"(d[75]), "+f"(d[76]), "+f"(d[77]), "+f"(d[78]), "+f"(d[79]), "+f"(d[80]), "+f"(d[81]), "+f"(d[82]), "+f"(d[83]), "+f"(d[84]), "+f"(d[85]), "+f"(d[86]), "+f"(d[87]), "+f"(d[88]), "+f"(d[89]), "+f"(d[90]), "+f"(d[91]), "+f"(d[92]), "+f"(d[93]), "+f"(d[94]), "+f"(d[95]), "+f"(d[96]), "+f"(d[97]), "+f"(d[98]), "+f"(d[99]), "+f"(d[100]), "+f"(d[101]), "+f"(d[102]), "+f"(d[103]), "+f"(d[104]), "+f"(d[105]), "+f"(d[106]), "+f"(d[107]), "+f"(d[108]), "+f"(d[109]), "+f"(d[110]), "+f"(d[111]), "+f"(d[112]), "+f"(d[113]), "+f"(d[114]), "+f"(d[115]), "+f"(d[116]), "+f"(d[117]), "+f"(d[118]), "+f"(d[119]), "+f"(d[120]), "+f"(d[121]), "+f"(d[122]), "+f"(d[123]), "+f"(d[124]), "+f"(d[125]), "+f"(d[126]), "+f"(d[127])
    : "l"(da), "l"(db), "r"(acc), "n"(TA), "n"(TB));
}

template <int TA, int TB> __device__ __forceinline__ void wgmma_n64(float (&d)[32], uint64_t da, uint64_t db, int acc) {
  asm volatile("{\n.reg .pred p;\nsetp.ne.b32 p, %34, 0;\n"
    "wgmma.mma_async.sync.aligned.m64n64k16.f32.bf16.bf16 {%0, %1, %2, %3, %4, %5, %6, %7, %8, %9, %10, %11, %12, %13, %14, %15, %16, %17, %18, %19, %20, %21, %22, %23, %24, %25, %26, %27, %28, %29, %30, %31}, %32, %33, p, 1, 1, %35, %36;\n}\n"
    : "+f"(d[0]), "+f"(d[1]), "+f"(d[2]), "+f"(d[3]), "+f"(d[4]), "+f"(d[5]), "+f"(d[6]), "+f"(d[7]), "+f"(d[8]), "+f"(d[9]), "+f"(d[10]), "+f"(d[11]), "+f"(d[12]), "+f"(d[13]), "+f"(d[14]), "+f"(d[15]), "+f"(d[16]), "+f"(d[17]), "+f"(d[18]), "+f"(d[19]), "+f"(d[20]), "+f"(d[21]), "+f"(d[22]), "+f"(d[23]), "+f"(d[24]), "+f"(d[25]), "+f"(d[26]), "+f"(d[27]), "+f"(d[28]), "+f"(d[29]), "+f"(d[30]), "+f"(d[31])
    : "l"(da), "l"(db), "r"(acc), "n"(TA), "n"(TB));
}

template <int TA, int TB> __device__ __forceinline__ void wgmma_n80(float (&d)[40], uint64_t da, uint64_t db, int acc) {
  asm volatile("{\n.reg .pred p;\nsetp.ne.b32 p, %42, 0;\n"
    "wgmma.mma_async.sync.aligned.m64n80k16.f32.bf16.bf16 {%0, %1, %2, %3, %4, %5, %6, %7, %8, %9, %10, %11, %12, %13, %14, %15, %16, %17, %18, %19, %20, %21, %22, %23, %24, %25, %26, %27, %28, %29, %30, %31, %32, %33, %34, %35, %36, %37, %38, %39}, %40, %41, p, 1, 1, %43, %44;\n}\n"
    : "+f"(d[0]), "+f"(d[1]), "+f"(d[2]), "+f"(d[3]), "+f"(d[4]), "+f"(d[5]), "+f"(d[6]), "+f"(d[7]), "+f"(d[8]), "+f"(d[9]), "+f"(d[10]), "+f"(d[11]), "+f"(d[12]), "+f"(d[13]), "+f"(d[14]), "+f"(d[15]), "+f"(d[16]), "+f"(d[17]), "+f"(d[18]), "+f"(d[19]), "+f"(d[20]), "+f"(d[21]), "+f"(d[22]), "+f"(d[23]), "+f"(d[24]), "+f"(d[25]), "+f"(d[26]), "+f"(d[27]), "+f"(d[28]), "+f"(d[29]), "+f"(d[30]), "+f"(d[31]), "+f"(d[32]), "+f"(d[33]), "+f"(d[34]), "+f"(d[35]), "+f"(d[36]), "+f"(d[37]), "+f"(d[38]), "+f"(d[39])
    : "l"(da), "l"(db), "r"(acc), "n"(TA), "n"(TB));
}

template <int TA, int TB> __device__ __forceinline__ void wgmma_n144(float (&d)[72], uint64_t da, uint64_t db, int acc) {
  asm volatile("{\n.reg .pred p;\nsetp.ne.b32 p, %74, 0;\n"
    "wgmma.mma_async.sync.aligned.m64n144k16.f32.bf16.bf16 {%0, %1, %2, %3, %4, %5, %6, %7, %8, %9, %10, %11, %12, %13, %14, %15, %16, %17, %18, %19, %20, %21, %22, %23, %24, %25, %26, %27, %28, %29, %30, %31, %32, %33, %34, %35, %36, %37, %38, %39, %40, %41, %42, %43, %44, %45, %46, %47, %48, %49, %50, %51, %52, %53, %54, %55, %56, %57, %58, %59, %60, %61, %62, %63, %64, %65, %66, %67, %68, %69, %70, %71}, %72, %73, p, 1, 1, %75, %76;\n}\n"
    : "+f"(d[0]), "+f"(d[1]), "+f"(d[2]), "+f"(d[3]), "+f"(d[4]), "+f"(d[5]), "+f"(d[6]), "+f"(d[7]), "+f"(d[8]), "+f"(d[9]), "+f"(d[10]), "+f"(d[11]), "+f"(d[12]), "+f"(d[13]), "+f"(d[14]), "+f"(d[15]), "+f"(d[16]), "+f"(d[17]), "+f"(d[18]), "+f"(d[19]), "+f"(d[20]), "+f"(d[21]), "+f"(d[22]), "+f"(d[23]), "+f"(d[24]), "+f"(d[25]), "+f"(d[26]), "+f"(d[27]), "+f"(d[28]), "+f"(d[29]), "+f"(d[30]), "+f"(d[31]), "+f"(d[32]), "+f"(d[33]), "+f"(d[34]), "+f"(d[35]), "+f"(d[36]), "+f"(d[37]), "+f"(d[38]), "+f"(d[39]), "+f"(d[40]), "+f"(d[41]), "+f"(d[42]), "+f"(d[43]), "+f"(d[44]), "+f"(d[45]), "+f"(d[46]), "+f"(d[47]), "+f"(d[48]), "+f"(d[49]), "+f"(d[50]), "+f"(d[51]), "+f"(d[52]), "+f"(d[53]), "+f"(d[54]), "+f"(d[55]), "+f"(d[56]), "+f"(d[57]), "+f"(d[58]), "+f"(d[59]), "+f"(d[60]), "+f"(d[61]), "+f"(d[62]), "+f"(d[63]), "+f"(d[64]), "+f"(d[65]), "+f"(d[66]), "+f"(d[67]), "+f"(d[68]), "+f"(d[69]), "+f"(d[70]), "+f"(d[71])
    : "l"(da), "l"(db), "r"(acc), "n"(TA), "n"(TB));
}

template <int TA, int TB> __device__ __forceinline__ void wgmma_n128(float (&d)[64], uint64_t da, uint64_t db, int acc) {
  asm volatile("{\n.reg .pred p;\nsetp.ne.b32 p, %66, 0;\n"
    "wgmma.mma_async.sync.aligned.m64n128k16.f32.bf16.bf16 {%0, %1, %2, %3, %4, %5, %6, %7, %8, %9, %10, %11, %12, %13, %14, %15, %16, %17, %18, %19, %20, %21, %22, %23, %24, %25, %26, %27, %28, %29, %30, %31, %32, %33, %34, %35, %36, %37, %38, %39, %40, %41, %42, %43, %44, %45, %46, %47, %48, %49, %50, %51, %52, %53, %54, %55, %56, %57, %58, %59, %60, %61, %62, %63}, %64, %65, p, 1, 1, %67, %68;\n}\n"
    : "+f"(d[0]), "+f"(d[1]), "+f"(d[2]), "+f"(d[3]), "+f"(d[4]), "+f"(d[5]), "+f"(d[6]), "+f"(d[7]), "+f"(d[8]), "+f"(d[9]), "+f"(d[10]), "+f"(d[11]), "+f"(d[12]), "+f"(d[13]), "+f"(d[14]), "+f"(d[15]), "+f"(d[16]), "+f"(d[17]), "+f"(d[18]), "+f"(d[19]), "+f"(d[20]), "+f"(d[21]), "+f"(d[22]), "+f"(d[23]), "+f"(d[24]), "+f"(d[25]), "+f"(d[26]), "+f"(d[27]), "+f"(d[28]), "+f"(d[29]), "+f"(d[30]), "+f"(d[31]), "+f"(d[32]), "+f"(d[33]), "+f"(d[34]), "+f"(d[35]), "+f"(d[36]), "+f"(d[37]), "+f"(d[38]), "+f"(d[39]), "+f"(d[40]), "+f"(d[41]), "+f"(d[42]), "+f"(d[43]), "+f"(d[44]), "+f"(d[45]), "+f"(d[46]), "+f"(d[47]), "+f"(d[48]), "+f"(d[49]), "+f"(d[50]), "+f"(d[51]), "+f"(d[52]), "+f"(d[53]), "+f"(d[54]), "+f"(d[55]), "+f"(d[56]), "+f"(d[57]), "+f"(d[58]), "+f"(d[59]), "+f"(d[60]), "+f"(d[61]), "+f"(d[62]), "+f"(d[63])
    : "l"(da), "l"(db), "r"(acc), "n"(TA), "n"(TB));
}

template <int TB> __device__ __forceinline__ void wgmma_rs_n40(float (&d)[20], uint32_t a0, uint32_t a1, uint32_t a2, uint32_t a3, uint64_t db, int acc) {
  asm volatile("{\n.reg .pred p;\nsetp.ne.b32 p, %25, 0;\n"
    "wgmma.mma_async.sync.aligned.m64n40k16.f32.bf16.bf16 {%0, %1, %2, %3, %4, %5, %6, %7, %8, %9, %10, %11, %12, %13, %14, %15, %16, %17, %18, %19}, {%20, %21, %22, %23}, %24, p, 1, 1, %26;\n}\n"
    : "+f"(d[0]), "+f"(d[1]), "+f"(d[2]), "+f"(d[3]), "+f"(d[4]), "+f"(d[5]), "+f"(d[6]), "+f"(d[7]), "+f"(d[8]), "+f"(d[9]), "+f"(d[10]), "+f"(d[11]), "+f"(d[12]), "+f"(d[13]), "+f"(d[14]), "+f"(d[15]), "+f"(d[16]), "+f"(d[17]), "+f"(d[18]), "+f"(d[19])
    : "r"(a0), "r"(a1), "r"(a2), "r"(a3), "l"(db), "r"(acc), "n"(TB));
}

template <int TB> __device__ __forceinline__ void wgmma_rs_n192(float (&d)[96], uint32_t a0, uint32_t a1, uint32_t a2, uint32_t a3, uint64_t db, int acc) {
  asm volatile("{\n.reg .pred p;\nsetp.ne.b32 p, %101, 0;\n"
    "wgmma.mma_async.sync.aligned.m64n192k16.f32.bf16.bf16 {%0, %1, %2, %3, %4, %5, %6, %7, %8, %9, %10, %11, %12, %13, %14, %15, %16, %17, %18, %19, %20, %21, %22, %23, %24, %25, %26, %27, %28, %29, %30, %31, %32, %33, %34, %35, %36, %37, %38, %39, %40, %41, %42, %43, %44, %45, %46, %47, %48, %49, %50, %51, %52, %53, %54, %55, %56, %57, %58, %59, %60, %61, %62, %63, %64, %65, %66, %67, %68, %69, %70, %71, %72, %73, %74, %75, %76, %77, %78, %79, %80, %81, %82, %83, %84, %85, %86, %87, %88, %89, %90, %91, %92, %93, %94, %95}, {%96, %97, %98, %99}, %100, p, 1, 1, %102;\n}\n"
    : "+f"(d[0]), "+f"(d[1]), "+f"(d[2]), "+f"(d[3]), "+f"(d[4]), "+f"(d[5]), "+f"(d[6]), "+f"(d[7]), "+f"(d[8]), "+f"(d[9]), "+f"(d[10]), "+f"(d[11]), "+f"(d[12]), "+f"(d[13]), "+f"(d[14]), "+f"(d[15]), "+f"(d[16]), "+f"(d[17]), "+f"(d[18]), "+f"(d[19]), "+f"(d[20]), "+f"(d[21]), "+f"(d[22]), "+f"(d[23]), "+f"(d[24]), "+f"(d[25]), "+f"(d[26]), "+f"(d[27]), "+f"(d[28]), "+f"(d[29]), "+f"(d[30]), "+f"(d[31]), "+f"(d[32]), "+f"(d[33]), "+f"(d[34]), "+f"(d[35]), "+f"(d[36]), "+f"(d[37]), "+f"(d[38]), "+f"(d[39]), "+f"(d[40]), "+f"(d[41]), "+f"(d[42]), "+f"(d[43]), "+f"(d[44]), "+f"(d[45]), "+f"(d[46]), "+f"(d[47]), "+f"(d[48]), "+f"(d[49]), "+f"(d[50]), "+f"(d[51]), "+f"(d[52]), "+f"(d[53]), "+f"(d[54]), "+f"(d[55]), "+f"(d[56]), "+f"(d[57]), "+f"(d[58]), "+f"(d[59]), "+f"(d[60]), "+f"(d[61]), "+f"(d[62]), "+f"(d[63]), "+f"(d[64]), "+f"(d[65]), "+f"(d[66]), "+f"(d[67]), "+f"(d[68]), "+f"(d[69]), "+f"(d[70]), "+f"(d[71]), "+f"(d[72]), "+f"(d[73]), "+f"(d[74]), "+f"(d[75]), "+f"(d[76]), "+f"(d[77]), "+f"(d[78]), "+f"(d[79]), "+f"(d[80]), "+f"(d[81]), "+f"(d[82]), "+f"(d[83]), "+f"(d[84]), "+f"(d[85]), "+f"(d[86]), "+f"(d[87]), "+f"(d[88]), "+f"(d[89]), "+f"(d[90]), "+f"(d[91]), "+f"(d[92]), "+f"(d[93]), "+f"(d[94]), "+f"(d[95])
    : "r"(a0), "r"(a1), "r"(a2), "r"(a3), "l"(db), "r"(acc), "n"(TB));
}
constexpr uint32_t AR_ACC = 0;
constexpr uint32_t AR_TAB = 0x100000;
constexpr uint32_t AR_PROG = 0x101000;
constexpr uint32_t AR_CNT = 0x102000;
constexpr uint32_t AR_QUEUE = 0x103000;
constexpr uint32_t AR_SIZE = 0x104000;

struct ChainArgs {
  const bf16* mem0;
  const uint2* xh;
  unsigned char *kg, *vg;
  unsigned char* arena;
  uint32_t* dbg;
  int tl;
};

namespace ch {
constexpr int OFF_WQ = 0;
constexpr int OFF_X = 81920;
constexpr int OFF_MEM = OFF_X + 40960;
constexpr int OFF_WO = OFF_MEM + 10240;
constexpr int WOK = 8 * 896;
constexpr int OFF_KV = OFF_WO + 10 * WOK;
constexpr int KVB = 5120;
constexpr int OFF_O = OFF_KV + 4 * KVB;
constexpr int OFF_Q = OFF_O + 1024;
constexpr int OFF_S = OFF_O + 3072;
constexpr int OFF_SR = OFF_S + 1280;
constexpr int OFF_BAR = OFF_SR + 1536;
constexpr int SMEM = OFF_BAR + 128 + 1152;
static_assert(SMEM <= 232448, "smem");
constexpr int MB_S = OFF_BAR, MB_O = OFF_BAR + 8, MB_X = OFF_BAR + 16;
constexpr int MB_K = OFF_SR + 1408, MB_V = MB_K + 16, MB_Q = MB_K + 32, MB_R = MB_K + 48;
constexpr int SC_IN = OFF_BAR + 64;
constexpr int SC_MX = OFF_S;
constexpr int SC_W = OFF_BAR + 96;
constexpr int WOS = 448;
enum { B_MEM0 = 1, B_QK, B_SL, B_V, B_O, B_RED, B_X, B_C, B_H, B_MEM1, B_A, B_G };
#define NQ1 6
#define NQ0 4
#define NP0 4
#define NWO 5
#define NWP 4
#define NB0 2
#define BBS 100
#define VSYNC 0
#define XPOS 0
#define XPD 300
#define WOF 0
#define XBYTES 36864
#define NRT 7
#define NRF 2
#define NPM0 2
#define NPM1 2
#define RSYNC 1
#define PFK 1
#define PA0 7
#define PA1 0
#define PB0 7
#define PB1 5
#define PQE 0
#define XT 30
static_assert(NPM0 >= 2 && NPM1 >= 2, "the K / V blocks live in the last two k-steps of Wo");
}

#define CHAIN_TIMING 0
#define TS(i)
#define TSV(i, v)
#define TS_SETUP()
#define POLL_DELAY 570
#define XN 40
#define PF0 8
#define PFS 3
#define XDELAY 0
#define NOKM 0
#define PFACC 1
#define PUB_REL 1
template <int V> using IC = std::integral_constant<int, V>;
__device__ __forceinline__ uint32_t clk_v() { uint64_t c; asm volatile("mov.u64 %0, %%clock64;" : "=l"(c) :: "memory"); return (uint32_t)c; }
__device__ __forceinline__ int fresh(int x) { int y; asm volatile("shfl.sync.bfly.b32 %0, %1, 0, 0x1f, 0xffffffff;" : "=r"(y) : "r"(x)); return y; }
#define SFENCE2(x, d) asm volatile("{\n.reg .pred p;\nsetp.eq.u32 p, %0, 0x7fffffff;\n@p st.shared.u32 [%0], %1;\n}" :: "r"(x), "r"(d) : "memory")
#define SFENCE(x) asm volatile("{\n.reg .pred p;\nsetp.eq.u32 p, %0, 0x7fffffff;\n@p st.shared.u32 [%0], %0;\n}" :: "r"(x) : "memory")
template <int I> __device__ __forceinline__ void bbfence(uint32_t x) {
  asm volatile("{\n.reg .pred p;\nsetp.eq.u32 p, %0, %1;\nL_%=:\n@p st.volatile.shared.u32 [%0], %0;\n@p bra.uni L_%=;\n}" :: "r"(x), "n"(4 * I) : "memory");
}
__device__ __forceinline__ float uniform_f(float x) { return __uint_as_float(__reduce_max_sync(0xffffffffu, __float_as_uint(x))); }

__device__ __forceinline__ void mma16816h(float (&d)[4], const uint32_t (&a)[4], uint32_t b0, uint32_t b1) {
  asm volatile("mma.sync.aligned.m16n8k16.row.col.f32.f16.f16.f32 {%0,%1,%2,%3}, {%4,%5,%6,%7}, {%8,%9}, {%0,%1,%2,%3};"
               : "+f"(d[0]), "+f"(d[1]), "+f"(d[2]), "+f"(d[3]) : "r"(a[0]), "r"(a[1]), "r"(a[2]), "r"(a[3]), "r"(b0), "r"(b1));
}
__device__ __forceinline__ void mma1688(float (&d)[4], uint32_t a0, uint32_t a1, uint32_t b0) {
  asm volatile("mma.sync.aligned.m16n8k8.row.col.f32.bf16.bf16.f32 {%0,%1,%2,%3}, {%4,%5}, {%6}, {%0,%1,%2,%3};"
               : "+f"(d[0]), "+f"(d[1]), "+f"(d[2]), "+f"(d[3]) : "r"(a0), "r"(a1), "r"(b0));
}
template <int OFF16, int ACC> __device__ __forceinline__ void wgmma_rs32h(float (&d)[16], const uint32_t (&a)[4], uint32_t dlo) {
  asm volatile("{\n.reg .pred p;\n.reg .b32 t;\n.reg .b64 db;\nsetp.ne.b32 p, %22, 0;\nadd.u32 t, %20, %21;\nmov.b64 db, {t, 0x40000040};\n"
    "wgmma.mma_async.sync.aligned.m64n32k16.f32.f16.f16 {%0,%1,%2,%3,%4,%5,%6,%7,%8,%9,%10,%11,%12,%13,%14,%15}, {%16,%17,%18,%19}, db, p, 1, 1, 0;\n}\n"
    : "+f"(d[0]), "+f"(d[1]), "+f"(d[2]), "+f"(d[3]), "+f"(d[4]), "+f"(d[5]), "+f"(d[6]), "+f"(d[7]), "+f"(d[8]), "+f"(d[9]), "+f"(d[10]), "+f"(d[11]),
      "+f"(d[12]), "+f"(d[13]), "+f"(d[14]), "+f"(d[15])
    : "r"(a[0]), "r"(a[1]), "r"(a[2]), "r"(a[3]), "r"(dlo), "n"(OFF16), "n"(ACC));
}
template <int IMM> __device__ __forceinline__ void stsm_x4_t_i(uint32_t a, uint32_t r0, uint32_t r1, uint32_t r2, uint32_t r3) {
  asm volatile("stmatrix.sync.aligned.m8n8.x4.trans.shared.b16 [%0+%5], {%1,%2,%3,%4};" :: "r"(a), "r"(r0), "r"(r1), "r"(r2), "r"(r3), "n"(IMM) : "memory");
}
template <int IMM> __device__ __forceinline__ void stsm_x2_t_i(uint32_t a, uint32_t r0, uint32_t r1) {
  asm volatile("stmatrix.sync.aligned.m8n8.x2.trans.shared.b16 [%0+%3], {%1,%2};" :: "r"(a), "r"(r0), "r"(r1), "n"(IMM) : "memory");
}
template <int IMM> __device__ __forceinline__ void st_async_b32_i(uint32_t a, uint32_t x, uint32_t mb) {
  asm volatile("st.async.weak.shared::cluster.mbarrier::complete_tx::bytes.b32 [%0+%3], %1, [%2];" :: "r"(a), "r"(x), "r"(mb), "n"(IMM) : "memory");
}
template <int IMM> __device__ __forceinline__ void ld_relaxed_v4_if(uint4& v, const void* p, uint32_t c) {
  asm volatile("{\n.reg .pred p;\nsetp.ne.u32 p, %6, 0;\n@p ld.relaxed.gpu.global.v4.u32 {%0,%1,%2,%3}, [%4+%5];\n}"
               : "+r"(v.x), "+r"(v.y), "+r"(v.z), "+r"(v.w) : "l"(p), "n"(IMM), "r"(c) : "memory");
}
template <int IMM> __device__ __forceinline__ uint32_t lds32_i(uint32_t a) {
  uint32_t v; asm volatile("ld.shared.u32 %0, [%1+%2];" : "=r"(v) : "r"(a), "n"(IMM) : "memory"); return v;
}
__device__ __forceinline__ void sts32(uint32_t a, uint32_t v) { asm volatile("st.shared.u32 [%0], %1;" :: "r"(a), "r"(v) : "memory"); }
__device__ __forceinline__ uint32_t pack_f16(float lo, float hi) {
  uint32_t d; asm("cvt.rn.f16x2.f32 %0, %1, %2;" : "=r"(d) : "f"(hi), "f"(lo)); return d;
}
__device__ __forceinline__ uint32_t amax_bf2(uint32_t a, uint32_t b) { uint32_t d; asm("max.xorsign.abs.bf16x2 %0, %1, %2;" : "=r"(d) : "r"(a), "r"(b)); return d; }
__device__ __forceinline__ uint32_t amax_h2(uint32_t a, uint32_t b) { uint32_t d; asm("max.xorsign.abs.f16x2 %0, %1, %2;" : "=r"(d) : "r"(a), "r"(b)); return d; }
__device__ __forceinline__ uint32_t amax_fold(uint32_t m) { return __reduce_max_sync(0xffffffffu, max(m & 0x7fffu, (m >> 16) & 0x7fffu)); }
__device__ __forceinline__ int wscale_exp(uint32_t m) { return min(141 - (int)(m >> 7), 100); }
__device__ __forceinline__ float exp2i(int e) { return __uint_as_float((uint32_t)(e + 127) << 23); }
__device__ __forceinline__ uint32_t bf2_to_h2(uint32_t w, float sc) { return pack_f16(bf_lo(w) * sc, bf_hi(w) * sc); }
__device__ __forceinline__ void bf2_to_h2_inplace(uint32_t& w, uint32_t sc2) {
  asm volatile("{\n.reg .b32 t, lo, hi;\nmul.rn.bf16x2 t, %0, %1;\nshl.b32 lo, t, 16;\nand.b32 hi, t, 0xffff0000;\ncvt.rn.f16x2.f32 %0, hi, lo;\n}" : "+r"(w) : "r"(sc2));
}
__device__ __forceinline__ void prefetch_l2(const void* p, uint32_t bytes) { asm volatile("cp.async.bulk.prefetch.L2.global [%0], %1;" :: "l"(p), "r"(bytes) : "memory"); }
__device__ __forceinline__ void prefetch_tma_2d(const CUtensorMap* tm, int c0, int c1) {
  asm volatile("cp.async.bulk.prefetch.tensor.2d.L2.global [%0, {%1, %2}];" :: "l"(tm), "r"(c0), "r"(c1) : "memory");
}
__host__ __device__ constexpr uint32_t acc_voff(int v) { return v < 4 ? v * 1024u : (v == 4 ? 128u : 3072u + 128u); }
__device__ __forceinline__ int unit28(int i) { return i == 3 ? 54 : 14 * i; }
__device__ __forceinline__ int unit24(int i) { return i < 2 ? 48 - 6 * i : 56 + 6 * i; }
__device__ __forceinline__ uint32_t acc_step(int s) { return (s >> 1) * 32768 + (s & 1) * 512; }
__device__ __forceinline__ uint32_t acc_lane(int i, int lane) { return ((lane >> 3) & 1) * 256 + (lane >> 4) * 4096 + i * 8192 + (lane & 7) * 16; }

__device__ __forceinline__ uint32_t ld_acquire_u32(const void* p) {
  uint32_t v; asm volatile("ld.acquire.gpu.global.u32 %0, [%1];" : "=r"(v) : "l"(p) : "memory"); return v;
}
__device__ __forceinline__ void ln_row(const uint2 (&xw)[5], int row, int lane, bf16* __restrict__ xn, uint2* __restrict__ xh) {
  float v[20];
#pragma unroll
  for (int i = 0; i < 5; i++) { v[4 * i] = bf_lo(xw[i].x); v[4 * i + 1] = bf_hi(xw[i].x); v[4 * i + 2] = bf_lo(xw[i].y); v[4 * i + 3] = bf_hi(xw[i].y); }
  float s = 0.f;
#pragma unroll
  for (int i = 0; i < 20; i++) s += v[i];
#pragma unroll
  for (int o = 16; o; o >>= 1) s += __shfl_xor_sync(0xffffffffu, s, o);
  const float mean = s * (1.f / cfg::DM);
  float q = 0.f;
#pragma unroll
  for (int i = 0; i < 20; i++) { const float d = v[i] - mean; q += d * d; }
#pragma unroll
  for (int o = 16; o; o >>= 1) q += __shfl_xor_sync(0xffffffffu, q, o);
  const float mb = bf16r(mean), var = bf16r(q * (1.f / cfg::DM));
  const float den = bf16r(sqrtf(bf16r(var + 1e-5f)));
#pragma unroll
  for (int i = 0; i < 5; i++) {
    float y[4];
#pragma unroll
    for (int e = 0; e < 4; e++) y[e] = __fdividef(bf16r(v[4 * i + e] - mb), den);
    const uint32_t w0 = pack_bf16(y[0], y[1]), w1 = pack_bf16(y[2], y[3]);
    *(uint2*)(xn + (size_t)row * cfg::DM + i * 128 + lane * 4) = make_uint2(w0, w1);
    if (xh) xh[(((size_t)(row >> 5) * 10 + 2 * i + (lane >> 4)) * 32 + (row & 31)) * 16 + ((((lane >> 1) & 7) ^ (row & 7)) << 1) + (lane & 1)] =
        make_uint2(pack_f16(bf_lo(w0), bf_hi(w0)), pack_f16(bf_lo(w1), bf_hi(w1)));
  }
}

__global__ void __cluster_dims__(3, 1, 1) __launch_bounds__(384, 1) chain_kernel(const ChainArgs a, const __grid_constant__ CUtensorMap tmWq,
    const __grid_constant__ CUtensorMap tmWk, const __grid_constant__ CUtensorMap tmWv, const __grid_constant__ CUtensorMap tmWo) {
  using namespace ch;
  extern __shared__ __align__(1024) unsigned char smem_raw[];
  const uint32_t sb = smem_u32(smem_raw);
  const int warp = __shfl_sync(0xffffffffu, (int)threadIdx.x >> 5, 0);
  const int lane = __shfl_sync(0xffffffffu, (int)threadIdx.x & 31, threadIdx.x & 31);
  const int cta = blockIdx.x, h = cta / 3, j = cta % 3;
  const int g = lane >> 2, q4 = lane & 3, r8 = lane & 7, m4 = lane >> 3;
  unsigned char* const arena = a.arena;
  if (sb & 1023u) __trap();
  TL_BEGIN(a.tl);
  const int col0 = j == 0 ? 0 : (j == 1 ? 224 : 432);
  auto stage_w = [&](const CUtensorMap* tm, uint32_t dst, uint32_t mb, int half) {
    mbar_expect_tx(mb + 8 * half, 40960);
    tma_load_2d(dst + half * 40960, tm, h * cfg::DH + j * 64, half * 320, mb + 8 * half);
    tma_load_2d(dst + half * 40960 + 20480, tm, h * cfg::DH + j * 64, half * 320 + 160, mb + 8 * half);
  };
  if (threadIdx.x == 256) {
    for (int i = 0; i < 9; i++) mbar_init(sb + MB_K + 8 * i, 1);
    mbar_init(sb + MB_S, 1); mbar_init(sb + MB_O, 1); mbar_init(sb + MB_X, 1);
    asm volatile("fence.mbarrier_init.release.cluster;" ::: "memory");
    for (int i = 0; i < 2; i++) { stage_w(&tmWk, sb + OFF_WQ, sb + MB_K, i); stage_w(&tmWv, sb + OFF_WO, sb + MB_V, i); }
    sts32(sb + SC_W, 0); sts32(sb + SC_W + 4, 0); sts32(sb + SC_W + 8, 0); sts32(sb + SC_IN + 12, 0); sts32(sb + SC_IN + 20, 0);
    mbar_expect_tx(sb + MB_S, 1280); mbar_expect_tx(sb + MB_O, 2048);
  }
  __syncthreads();
  asm volatile("barrier.cluster.arrive.relaxed.aligned;" ::: "memory");
  const uint32_t d1 = mapa_u32(sb, (j + 1) % 3) - sb, d2 = mapa_u32(sb, (j + 2) % 3) - sb;

  if (warp >= 8) {
    asm volatile("setmaxnreg.dec.sync.aligned.u32 40;");
    const int hw = warp - 8, ht = hw * 32 + lane;
    const bool lead = ht == 0;
    auto stage_wo = [&](int i) {
      mbar_expect_tx(sb + MB_R + 8 * i, 64 * WOS);
      tma_load_2d(sb + OFF_WO + i * 64 * WOS, &tmWo, col0, h * cfg::DH + ((i + j) % 3) * 64, sb + MB_R + 8 * i);
    };
    const unsigned char* xg = (const unsigned char*)a.xh;
    auto issue_x = [&](int s) { mbar_expect_tx(sb + MB_X, 40960); bulk_g2s(sb + OFF_X, xg + (size_t)s * 40960, 40960, sb + MB_X); };
    uint4 v[5];
#pragma unroll
    for (int i = 0; i < 5; i++) { const int c = ht + 128 * i; v[i] = ld_relaxed_v4(a.mem0 + (c & 7) * cfg::DM + (c >> 3) * 8); }
    if (hw == 2) {
      asm volatile("griddepcontrol.wait;" ::: "memory");
      asm volatile("griddepcontrol.launch_dependents;" ::: "memory");
      if (lane == 0) issue_x(0);
    }
    if (hw == 0) {
      bar_sync(B_QK, 160); if (lane == 0) stage_w(&tmWq, sb + OFF_WQ, sb + MB_Q, 0);
      bar_sync(B_SL, 160); if (lane == 0) stage_w(&tmWq, sb + OFF_WQ, sb + MB_Q, 1);
    }
    if (hw == 1) {
      bar_sync(B_V, 160); if (lane == 0) stage_wo(0);
      bar_sync(B_O, 160); if (lane == 0) { stage_wo(1); stage_wo(2); }
    }
    __syncwarp();
    {
      uint32_t m = 0;
#pragma unroll
      for (int i = 0; i < 5; i++) {
        m = amax_bf2(amax_bf2(m, amax_bf2(v[i].x, v[i].y)), amax_bf2(v[i].z, v[i].w));
      }
      m = amax_fold(m);
      if (lane == 0) sts32(sb + SC_MX + hw * 4, m);
      bar_sync(B_H, 128);
      const uint4 mm = lds128(sb + SC_MX);
      const int se = max(wscale_exp(max(max(mm.x, mm.y), max(mm.z, mm.w))), -100);
      const float sc = exp2i(se);
#pragma unroll
      for (int i = 0; i < 5; i++) {
        const int c = ht + 128 * i, t = c & 7, chn = c >> 3;
        sts128(sb + OFF_MEM + chn * 128 + ((t ^ (2 * (chn & 3))) << 4), bf2_to_h2(v[i].x, sc), bf2_to_h2(v[i].y, sc), bf2_to_h2(v[i].z, sc), bf2_to_h2(v[i].w, sc));
      }
      if (lead) { sts32(sb + SC_IN, __float_as_uint(exp2i(-se))); sts32(sb + SC_IN + 4, 0x7800u); }
    }
    {
      const uint32_t p0 = sb + OFF_WQ + hw * 2048 + lane * 16;
      uint32_t m = 0;
#pragma unroll 1
      for (int i = 0; i < 10; i++) {
        if (i == 0 || i == 5) mbar_wait(sb + MB_Q + (i ? 8 : 0), 0);
        uint32_t r[4][4];
        static_for<0, 4>([&](auto K) { ldsm_x4_i<K.value * 512>(r[K.value], p0 + i * 8192); });
#pragma unroll
        for (int k = 0; k < 4; k++) m = amax_bf2(amax_bf2(m, amax_bf2(r[k][0], r[k][1])), amax_bf2(r[k][2], r[k][3]));
      }
      m = amax_fold(m);
      if (lane == 0) asm volatile("red.shared.max.u32 [%0], %1;" :: "r"(sb + SC_W + 8), "r"(m) : "memory");
      bar_sync(B_H, 128);
      const uint32_t sc = (uint32_t)(wscale_exp(lds32_i<SC_W + 8>(sb)) + 127) * 0x00800080u;
#pragma unroll 1
      for (int i = 0; i < 10; i++) {
        uint32_t r[4][4];
        static_for<0, 4>([&](auto K) { ldsm_x4_i<K.value * 512>(r[K.value], p0 + i * 8192); });
#pragma unroll
        for (int k = 0; k < 4; k++) {
          bf2_to_h2_inplace(r[k][0], sc); bf2_to_h2_inplace(r[k][1], sc); bf2_to_h2_inplace(r[k][2], sc); bf2_to_h2_inplace(r[k][3], sc);
          stsm_x4(p0 + i * 8192 + k * 512, r[k][0], r[k][1], r[k][2], r[k][3]);
        }
      }
    }
    bar_sync(0, 384);
    if (lead) st_relaxed_u32(arena + AR_TAB + cta * 4, 0x80000000u | (lds32_i<SC_W>(sb) << 15) | lds32_i<SC_W + 4>(sb));
    asm volatile("barrier.cluster.wait.aligned;" ::: "memory");
    bar_sync(B_MEM0, 256); bar_sync(B_MEM1, 256);
    {
      uint32_t v0, v1, v2; int spin = 0;
      do {
        v0 = ld_relaxed_u32(arena + AR_TAB + lane * 4); v1 = ld_relaxed_u32(arena + AR_TAB + 128 + lane * 4); v2 = ld_relaxed_u32(arena + AR_TAB + 256 + lane * 4);
      } while (__any_sync(0xffffffffu, ((v0 & v1 & v2) >> 31) == 0) && ++spin < SPIN_LIMIT);
      const uint32_t mv = (max(max(v0, v1), v2) >> 15) & 0x7fffu, mo = max(max(v0 & 0x7fffu, v1 & 0x7fffu), v2 & 0x7fffu);
      sts32(sb + SC_IN + 8 + (lane & 1) * 16, 15 - ((__reduce_max_sync(0xffffffffu, mv) >> 7) + (__reduce_max_sync(0xffffffffu, mo) >> 7) - 252 + 22));
    }

    auto store_kv = [&](int s) {
      const size_t o = ((size_t)s * 96 + cta) * KVB; const uint32_t src = sb + OFF_KV + (s & 1) * (2 * KVB);
      fence_proxy_async(); bulk_s2g(a.kg + o, src, KVB); bulk_s2g(a.vg + o, src + KVB, KVB); bulk_commit();
    };
    const int cb28 = unit28(hw), du = (unit24(hw) - cb28) * 128;
    int ln = lane;
#pragma unroll 1
    for (int s = 0; s < cfg::NSEG; s++) {
      TS_SETUP();
      const bool last = s == cfg::NSEG - 1;
      if (ln == 0) {
        if (hw == 2 && !last) issue_x(s + 1);
        if (hw == 0 && s > 0) store_kv(s - 1);
        if (PFACC && hw == 1 && s + PFACC < cfg::NSEG - 1)
          asm volatile("prefetch.global.L2 [%0];" :: "l"(arena + (AR_ACC + acc_step(s + PFACC) + acc_lane(cta / 24, (cta & 3) * 8) + acc_voff((cta % 24) >> 2))) : "memory");
      }
      __syncwarp();
      if (last) break;
      const uint32_t kv = (s & 1) * (2 * KVB);
      ln = fresh(ln);
      uint32_t kb0[4], kb1[4];
      { const uint32_t ka = sb + kv + hw * 128 + (ln >> 3) * 640 + (ln & 7) * 16; ldsm_x4_i<OFF_KV>(kb0, ka); ldsm_x4_i<OFF_KV + 2560>(kb1, ka); }
      const uint32_t l16 = sb + ln * 16, s8 = sb + ln * 8, xs = s8 + hw * 256, xr = sb + ln * 4 + (hw >> 1) * 512 + (hw & 1) * 128;
      TS(1);
      bar_sync(B_QK, 384);
      {
        uint32_t q0[4], q1[4], q2[4], q3[4];
        float sa[4] = {0, 0, 0, 0}, sc2[4] = {0, 0, 0, 0};
        ldsm_x4_i<OFF_Q>(q0, l16); ldsm_x4_i<OFF_Q + 1024>(q2, l16); ldsm_x4_i<OFF_Q + 512>(q1, l16);
        bar_arrive(B_A, 288);
        ldsm_x4_i<OFF_Q + 1536>(q3, l16);
        mma16816(sa, q0[0], q0[1], q0[2], q0[3], kb0[0], kb0[1]);
        mma16816(sc2, q2[0], q2[1], q2[2], q2[3], kb1[0], kb1[1]);
        mma16816(sa, q1[0], q1[1], q1[2], q1[3], kb0[2], kb0[3]);
        mma16816(sc2, q3[0], q3[1], q3[2], q3[3], kb1[2], kb1[3]);
        const float x0 = (sa[0] + sa[2]) + (sc2[0] + sc2[2]), x1 = (sa[1] + sa[3]) + (sc2[1] + sc2[3]);
        const uint32_t xp = pack_bf16(x0, x1);
        st_async_b32_i<OFF_SR + 256>(xr + d1, xp, sb + MB_S + d1);
        st_async_b32_i<OFF_SR>(xr + d2, xp, sb + MB_S + d2);
        sts64_i<OFF_S>(xs, __float_as_uint(x0), __float_as_uint(x1));
      }
      TS(3);
      bar_sync(B_SL, 256);
      float t0[4], t1[4], t2[4] = {0, 0, 0, 0};
      float osc;
      {
        const uint4 si = lds128_i<SC_IN>(sb + 16 * (s & 1));
        { const uint2 x = lds64_i<OFF_S>(s8), y = lds64_i<OFF_S + 256>(s8); t0[0] = __uint_as_float(x.x); t0[1] = __uint_as_float(x.y); t0[2] = __uint_as_float(y.x); t0[3] = __uint_as_float(y.y); }
        { const uint2 x = lds64_i<OFF_S + 512>(s8), y = lds64_i<OFF_S + 768>(s8); t1[0] = __uint_as_float(x.x); t1[1] = __uint_as_float(x.y); t1[2] = __uint_as_float(y.x); t1[3] = __uint_as_float(y.y); }
        { const uint2 x = lds64_i<OFF_S + 1024>(s8); t2[0] = __uint_as_float(x.x); t2[1] = __uint_as_float(x.y); }
        const int em = (int)(si.y >> 10) - 14 + (int)(si.x >> 23) - 127;
        osc = exp2i(max(min((int)si.z - max(em, 1), 100), -100));
      }
      const uint32_t xo = sb + hw * 256 + (ln & 2) * 64 + (ln >> 2) * 16 + (ln & 1) * 8;
      const uint32_t eye = ((ln >> 3) == (ln & 3)) ? ((ln & 4) ? 0x3f800000u : 0x3f80u) : 0u;
      mbar_spin(sb + MB_S, s & 1);
      TS(4);
      uint32_t v0[4], v1[4], vm[2];
      {
        uint32_t r0[4], r1[4], r2[4];
        ldsm_x4_i<OFF_SR>(r0, l16); ldsm_x4_i<OFF_SR + 512>(r1, l16); ldsm_x4_i<OFF_SR + 1024>(r2, l16);
        mma16816(t0, r0[0], r0[1], r0[2], r0[3], eye, eye);
        mma16816(t1, r1[0], r1[1], r1[2], r1[3], eye, eye);
        mma16816(t2, r2[0], r2[1], r2[2], r2[3], eye, eye);
      }
      float sc[10] = {t0[0], t0[1], t0[2], t0[3], t1[0], t1[1], t1[2], t1[3], t2[0], t2[1]};
      const float cs = 0.07216878364870322f * 1.4426950408889634f;
      float mx = fmaxf(fmaxf(fmaxf(sc[0], sc[1]), fmaxf(sc[2], sc[3])), fmaxf(fmaxf(sc[4], sc[5]), fmaxf(sc[6], sc[7])));
      mx = fmaxf(mx, fmaxf(sc[8], sc[9]));
      {
        const float m1 = __shfl_xor_sync(0xffffffffu, mx, 1), m2 = __shfl_xor_sync(0xffffffffu, mx, 2), m3 = __shfl_xor_sync(0xffffffffu, mx, 3);
        SFENCE2(l16, __float_as_uint(mx));
        ldsm_x4_t_i<OFF_KV + KVB>(v0, l16 + (kv + hw * 1280)); ldsm_x4_t_i<OFF_KV + KVB + 640>(v1, l16 + (kv + hw * 1280));
        bar_sync(B_V, 256);
        bar_arrive(B_G, 384);
        ldsm_x2_t(vm, l16 + (ln & 8) * 64 + (kv + hw * 1280 + OFF_KV + KVB + 512));
        mx = fmaxf(fmaxf(mx, m1), fmaxf(m2, m3));
      }
      const float mo = mx * cs;
#pragma unroll
      for (int i = 0; i < 10; i++) sc[i] = ex2f(fmaf(sc[i], cs, -mo));
      const uint32_t p0 = pack_bf16(sc[0], sc[1]), p1 = pack_bf16(sc[2], sc[3]), p2 = pack_bf16(sc[4], sc[5]), p3 = pack_bf16(sc[6], sc[7]), p4 = pack_bf16(sc[8], sc[9]);
      TS(5);
      float oa[4] = {0, 0, 0, 0}, ob[4] = {0, 0, 0, 0}, oc[4] = {0, 0, 0, 0}, od[4] = {0, 0, 0, 0}, rs[4] = {0, 0, 0, 0};
      const uint32_t ones = 0x3f803f80u;
      mma16816(rs, p0, p2, p1, p3, ones, ones);
      mma16816(oc, p0, p2, p1, p3, v0[2], v0[3]);
      mma16816(od, p0, p2, p1, p3, v1[2], v1[3]);
      mma16816(oa, p0, p2, p1, p3, v0[0], v0[1]);
      mma16816(ob, p0, p2, p1, p3, v1[0], v1[1]);
      mma1688(rs, p4, 0u, ones);
      mma1688(oa, p4, 0u, vm[0]);
      mma1688(ob, p4, 0u, vm[1]);
      const float inv = rcpf(rs[0] + rs[2]) * osc;
      {
        const uint32_t y0 = pack_bf16((oa[0] + oc[2]) * inv, (oa[1] + oc[3]) * inv), y1 = pack_bf16((ob[0] + od[2]) * inv, (ob[1] + od[3]) * inv);
        st_async_v2_i<OFF_O + 2048>(xo + d1, y0, y1, sb + MB_O + d1);
        st_async_v2_i<OFF_O + 1024>(xo + d2, y0, y1, sb + MB_O + d2);
        sts64_i<OFF_O>(xo, y0, y1);
      }
      bar_arrive(B_O, 384);
      TS(6);
      if (ln == 0) {
        if (hw == 0) {
          bulk_wait<0>();
          if ((s & 3) == 0 && s > 0) {
            asm volatile("st.release.gpu.global.u32 [%0], %1;" :: "l"(arena + (AR_PROG + (cta + ln) * 4)), "r"(s) : "memory");
          }
        }
        if (hw == 3) { mbar_expect_tx(sb + MB_S, 1280); sts64_i<SC_IN>(sb + 16 * ((s + 1) & 1), 0x7f000000u - __float_as_uint(osc), 0u); }
      }
      __syncwarp();
      ln = fresh(ln);
      auto mslot = [&](int c) -> uint32_t { return sb + OFF_MEM + c * 128 + (((ln >> 2) ^ (2 * (c & 3))) << 4); };
      const int lq = ln & 3;
      const uint32_t ma = mslot(cb28 + lq), mb_ = mslot(cb28 + (lq >> 1)) + (lq & 1) * 8;
      const unsigned char* gp = arena + (AR_ACC + acc_lane(hw, ln) + acc_step(s));
      const bool odd = ln & 1;
      SFENCE(ma);
      bar_sync(B_RED, 384);
      SFENCE(mb_);
      const uint32_t tw = clk_v();
      TSV(7, tw);
      if (ln == 0 && hw == 3) mbar_expect_tx(sb + MB_O, 2048);
      __syncwarp();
      while (clk_v() - tw < POLL_DELAY) {}
      TS(8);
      uint4 v[6];
      int spin = 0;
      const uint32_t cm = odd ? 0x5000u : 0u;
      do {
        static_for<0, 6>([&](auto I) { v[I.value] = ld_relaxed_v4_i<acc_voff(I.value)>(gp); });
      } while (__any_sync(0xffffffffu, (~((v[0].w & v[1].w & v[2].w) & (v[3].w & v[4].w & v[5].w)) & cm) != 0) && ++spin < SPIN_LIMIT);
      v[0].w = odd ? v[3].x : v[0].w; v[1].w = odd ? v[3].y : v[1].w; v[2].w = odd ? v[3].z : v[2].w; v[3].w = odd ? 0u : v[3].w;
      sts128_i<0>(ma, v[0].x, v[0].y, v[0].z, v[0].w);
      sts128_i<512>(ma, v[1].x, v[1].y, v[1].z, v[1].w);
      sts128_i<1024>(ma, v[2].x, v[2].y, v[2].z, v[2].w);
      sts128_i<0>(ma + du, v[4].x, v[4].y, v[4].z, v[5].z);
      sts64_i<512>(mb_ + du, v[5].x, v[5].y);
      if (!odd) sts128_i<1536>(mb_, v[3].x, v[3].y, v[3].z, v[3].w);
      TSV(11, spin);
      TS(10);
      bar_sync(B_MEM0, 256); bar_sync(B_MEM1, 256);
      uint32_t m = lds32_i<SC_IN + 12>(sb);
      uint32_t m2 = m;
      static_for<0, 3>([&](auto I) { m = amax_h2(amax_h2(amax_h2(amax_h2(m, v[I.value].x), v[I.value].y), v[I.value].z), v[I.value].w); });
      static_for<3, 6>([&](auto I) { m2 = amax_h2(amax_h2(amax_h2(m2, v[I.value].x), v[I.value].y), v[I.value].z); });
      m = amax_fold(amax_h2(amax_h2(m2, v[3].w), m));
      if (ln == 0) asm volatile("red.shared.max.u32 [%0], %1;" :: "r"(sb + SC_IN + 4 + 16 * ((s + 1) & 1)), "r"(m) : "memory");
    }
    bar_sync(B_RED, 384);
    if (hw == 0 && ln == 0) {
      store_kv(cfg::NSEG - 1);
      bulk_wait<0>();
      asm volatile("st.release.gpu.global.u32 [%0], %1;" :: "l"(arena + AR_PROG + cta * 4), "r"(cfg::NSEG) : "memory");
    }
    __syncwarp();
    TL_END(a.tl);
    asm volatile("barrier.cluster.arrive.relaxed.aligned; barrier.cluster.wait.aligned;" ::: "memory");
  } else {
    asm volatile("setmaxnreg.inc.sync.aligned.u32 232;");
    const int wi = warp & 3, hf = warp >> 2, tid = warp * 32 + lane;
    uint32_t w[40][4];
    uint32_t wqa;
    { const int mrow = r8 + ((lane >> 4) << 3), mch = 2 * wi + (m4 & 1); wqa = sb + mrow * 128 + ((mch ^ r8) << 4); }
    {
      const uint32_t wa = wqa + (hf ? OFF_WO : OFF_WQ);
      mbar_wait(sb + (hf ? MB_V : MB_K), 0);
      static_for<0, 20>([&](auto K) { ldsm_x4_t_i<K.value * 2048>(w[K.value], wa); });
      bar_arrive(hf ? B_V : B_QK, 160);
      mbar_wait(sb + (hf ? MB_V : MB_K) + 8, 0);
      static_for<20, 40>([&](auto K) { ldsm_x4_t_i<K.value * 2048>(w[K.value], wa); });
      bar_arrive(hf ? B_O : B_SL, 160);
      SFENCE(wa);
    }
    float iw, iq;
    {
      uint32_t m = 0;
#pragma unroll
      for (int k = 0; k < 40; k++) m = amax_bf2(amax_bf2(m, amax_bf2(w[k][0], w[k][1])), amax_bf2(w[k][2], w[k][3]));
      m = amax_fold(m);
      if (hf && lane == 0) asm volatile("red.shared.max.u32 [%0], %1;" :: "r"(sb + SC_W), "r"(m) : "memory");
      const int e = wscale_exp(m);
      const uint32_t sc = (uint32_t)(e + 127) * 0x00800080u; iw = exp2i(-e);
#pragma unroll
      for (int k = 0; k < 40; k++) { bf2_to_h2_inplace(w[k][0], sc); bf2_to_h2_inplace(w[k][1], sc); bf2_to_h2_inplace(w[k][2], sc); bf2_to_h2_inplace(w[k][3], sc); }
    }
    uint32_t x0[8];
    {
      float xa[16];
      const uint32_t dlo = (((sb + OFF_X) & 0x3FFFF) >> 4) | (1u << 16);
      mbar_wait(sb + MB_X, 0);
      wgmma_fence();
      static_for<0, 40>([&](auto K) { constexpr int k = K.value; wgmma_rs32h<((k >> 2) * 4096 + (k & 3) * 32) / 16, (k != 0)>(xa, w[k], dlo); });
      wgmma_commit();
      wgmma_wait<0>();
#pragma unroll
      for (int i = 0; i < 8; i++) x0[i] = pack_bf16(xa[2 * i] * iw, xa[2 * i + 1] * iw);
    }
    const bool t28 = j == 0 || warp < 4;
    const int bi = j == 0 ? hf : (warp < 4 ? j + 1 : 2 * (j - 1) + ((warp - 4) >> 1)), bv = t28 ? wi : 4 + (warp & 1);
    uint32_t wo1 = sb + OFF_WO + warp * 896 + lane * 16, wo2;
    {
      const int cb = (t28 ? unit28(bi) : unit24(bi)) - col0 / 8;
      uint32_t cp[4];
#pragma unroll
      for (int wd = 0; wd < 4; wd++) {
        int c, p;
        if (bv < 3) { c = 4 * bv + q4; p = wd; }
        else if (bv == 3) { if (q4 & 1) { c = 4 * (wd % 3) + q4; p = 3; } else { c = 12 + (q4 >> 1); p = wd; } }
        else if (bv == 4) { c = q4; p = wd; }
        else { if (wd < 2) { c = 4 + (q4 >> 1); p = 2 * (q4 & 1) + wd; } else { c = q4; p = 3; } }
        cp[wd] = sb + OFF_WO + ((g & 1) + (g & 2) * 4 + (g >> 2) * 2) * WOS + (cb + c) * 16 + p * 4;
      }
      const int cidx = (r8 & 1) + ((r8 >> 2) << 1);
      wo2 = sb + OFF_WO + warp * 896 + ((m4 & 1) ? 768 + (m4 >> 1) * 64 + cidx * 16 : 512 + (m4 >> 1) * 128 + r8 * 16);
      const bool dump = (m4 & 1) && (r8 & 2);
      uint32_t mo = 0;
      const bool regular = bv < 3 || bv == 4;
#pragma unroll 1
      for (int i = 0; i < 3; i++) {
        uint32_t x[4][4], y[4][4];
        const uint32_t o = i * 4 * WOK;
        mbar_wait(sb + MB_R + 8 * i, 0);
        if (regular) {
          static_for<0, 4>([&](auto K) {
            constexpr int kk = K.value;
            const uint4 u = lds128_i<kk * WOK>(cp[0] + o), v = lds128_i<kk * WOK + 4 * WOS>(cp[0] + o);
            x[kk][0] = u.x; x[kk][1] = u.y; x[kk][2] = u.z; x[kk][3] = u.w; y[kk][0] = v.x; y[kk][1] = v.y; y[kk][2] = v.z; y[kk][3] = v.w;
          });
        } else {
          static_for<0, 4>([&](auto K) {
            constexpr int kk = K.value;
#pragma unroll
            for (int wd = 0; wd < 4; wd++) { x[kk][wd] = lds32_i<kk * WOK>(cp[wd] + o); y[kk][wd] = lds32_i<kk * WOK + 4 * WOS>(cp[wd] + o); }
          });
        }
        bar_sync(B_C, 256);
        static_for<0, 4>([&](auto K) {
          constexpr int kk = K.value;
#pragma unroll
          for (int wd = 0; wd < 4; wd++) mo = amax_bf2(mo, amax_bf2(x[kk][wd], y[kk][wd]));
          stsm_x4_t_i<kk * WOK>(wo1 + o, x[kk][0], x[kk][1], y[kk][0], y[kk][1]);
          stsm_x4_t_i<0>(dump ? sb + OFF_S + 512 + lane * 16 : wo2 + o + kk * WOK, x[kk][2], x[kk][3], y[kk][2], y[kk][3]);
        });
      }
      mo = amax_fold(mo);
      if (lane == 0) asm volatile("red.shared.max.u32 [%0], %1;" :: "r"(sb + SC_W + 4), "r"(mo) : "memory");
    }
    __syncwarp();
    auto run = [&](auto HF) {
    constexpr int hf = HF.value;
    uint32_t mema, sta, l16 = sb + lane * 16;
    uint32_t rq[hf ? NQ1 : NQ0][4];
    auto step_addr = [&](uint32_t kv) {
      const int lr = (l16 >> 4) & 7, lm = (l16 >> 7) & 3;
      mema = l16 ^ (lm << 5);
      sta = sb + lr * 16 + (lm < 2 ? OFF_Q + wi * 512 + hf * 128 + lm * 256 : OFF_KV + kv + 512 + (2 * wi + lm - 2) * 640);
    };
    auto x_gemm = [&](uint32_t ph, [[maybe_unused]] uint32_t tsb) {
      float xa[16];
      const uint32_t dlo = (((sb + OFF_X) & 0x3FFFF) >> 4) | (1u << 16);
      constexpr int NP = hf ? NQ1 : NP0;
      if constexpr (hf) {
        static_for<PQE, NP>([&](auto K) { ldsm_x4_t_i<OFF_WQ + K.value * 2048>(rq[K.value], wqa); });
        bar_sync(B_X, 256);
      }
      wgmma_fence();
      static_for<0, 40>([&](auto K) {
        constexpr int k = K.value;
        wgmma_rs32h<((k >> 2) * 4096 + (k & 3) * 32) / 16, (k != 0)>(xa, w[k], dlo);
        if constexpr (!hf && k == PFK && NP > PQE) { SFENCE(wqa); static_for<PQE, NP>([&](auto K) { ldsm_x4_t_i<OFF_WQ + K.value * 2048>(rq[K.value], wqa); }); SFENCE(wqa); }
        if constexpr (!hf && k == XT) bar_arrive(B_X, 256);
      });
      step_addr(ph * (2 * KVB));
      wgmma_commit();
      TS(9);
      wgmma_wait<0>();
      const uint32_t xs = l16 + (wi * 1280 + ph * (2 * KVB));
      stsm_x4_t_i<OFF_KV + hf * KVB>(xs, pack_bf16(xa[0] * iw, xa[1] * iw), pack_bf16(xa[4] * iw, xa[5] * iw), pack_bf16(xa[8] * iw, xa[9] * iw), pack_bf16(xa[12] * iw, xa[13] * iw));
      stsm_x4_t_i<OFF_KV + hf * KVB + 640>(xs, pack_bf16(xa[2] * iw, xa[3] * iw), pack_bf16(xa[6] * iw, xa[7] * iw), pack_bf16(xa[10] * iw, xa[11] * iw), pack_bf16(xa[14] * iw, xa[15] * iw));
    };
    auto wq_addr = [&](uint32_t l) -> uint32_t {
      const int lr = (l >> 4) & 7, lm = (l >> 7) & 3;
      return sb + hf * ((40 - NQ1) * 2048) + (lr + ((lm >> 1) << 3)) * 128 + (((2 * wi + (lm & 1)) ^ lr) << 4);
    };
    constexpr int NPM = hf ? NPM1 : NPM0;
    uint32_t u1[NPM][4], u2[NPM][4];
    static_for<0, NPM>([&](auto K) { ldsm_x4_i<(12 - NPM + K.value) * WOK>(u1[K.value], wo1); ldsm_x4_i<(12 - NPM + K.value) * WOK>(u2[K.value], wo2); });
    bar_sync(0, 384);
    iq = uniform_f(exp2i(-wscale_exp(lds32_i<SC_W + 8>(sb))));
    wqa = wq_addr(l16);
    static_for<0, (hf ? NQ1 : NP0)>([&](auto K) { ldsm_x4_t_i<OFF_WQ + K.value * 2048>(rq[K.value], wqa); });
    step_addr(0);
    stsm_x4_t_i<OFF_KV + hf * KVB>(l16 + wi * 1280, x0[0], x0[2], x0[4], x0[6]);
    stsm_x4_t_i<OFF_KV + hf * KVB + 640>(l16 + wi * 1280, x0[1], x0[3], x0[5], x0[7]);
    asm volatile("barrier.cluster.wait.aligned;" ::: "memory");
    TL_END(a.tl + 1);
#pragma unroll 1
    for (int s = 0; s < cfg::NSEG; s++) {
      TS_SETUP();
      const bool last = s == cfg::NSEG - 1;
      bar_sync(hf ? B_MEM1 : B_MEM0, 256);
      const float sin_ = __uint_as_float(lds32_i<SC_IN>(sb + 16 * (s & 1)));
      constexpr int NPQ = (40 - NQ1) / 2;
      if constexpr (hf == 0) {
        float k0[4] = {0, 0, 0, 0}, k1[4] = {0, 0, 0, 0}, q0[4] = {0, 0, 0, 0}, q1[4] = {0, 0, 0, 0};
        constexpr auto pair_of = [](int t) { const int a = t * (20 - NPQ) / 20, b = (t + 1) * (20 - NPQ) / 20; return b > a ? NPQ + a : t - a; };
        uint32_t b[NB0][4];
        static_for<0, NB0>([&](auto T) { ldsm_x4_i<OFF_MEM + pair_of(T.value) * 512>(b[T.value], mema); });
        static_for<NP0, NQ0>([&](auto K) { ldsm_x4_t_i<OFF_WQ + K.value * 2048>(rq[K.value], wqa); });
        if (BBS < 100) bbfence<0>(mema);
        static_for<0, 20>([&](auto T) {
          constexpr int t = T.value, p = pair_of(t);
          uint32_t (&bb)[4] = b[t % NB0];
          if constexpr (p < NPQ) {
            mma16816h(q0, rq[(2 * p) % NQ0], bb[0], bb[1]);
            if constexpr (2 * p + NQ0 < 2 * NPQ) ldsm_x4_t_i<OFF_WQ + (2 * p + NQ0) * 2048>(rq[(2 * p) % NQ0], wqa);
          }
          mma16816h(k0, w[2 * p], bb[0], bb[1]);
          if constexpr (p < NPQ) {
            mma16816h(q1, rq[(2 * p + 1) % NQ0], bb[2], bb[3]);
            if constexpr (2 * p + 1 + NQ0 < 2 * NPQ) ldsm_x4_t_i<OFF_WQ + (2 * p + 1 + NQ0) * 2048>(rq[(2 * p + 1) % NQ0], wqa);
          }
          mma16816h(k1, w[2 * p + 1], bb[2], bb[3]);
          if constexpr (t + NB0 < 20) ldsm_x4_i<OFF_MEM + pair_of(t + NB0) * 512>(bb, mema);
          if constexpr (t < 20 - NB0 && (t % BBS) == BBS - 1) bbfence<t + 1>(mema);
        });
        const float sq = sin_ * iq, sk = sin_ * iw;
        stsm_x4_t_i<0>(sta, pack_bf16((q0[0] + q1[0]) * sq, (q0[1] + q1[1]) * sq), pack_bf16((q0[2] + q1[2]) * sq, (q0[3] + q1[3]) * sq),
                       pack_bf16((k0[0] + k1[0]) * sk, (k0[1] + k1[1]) * sk), pack_bf16((k0[2] + k1[2]) * sk, (k0[3] + k1[3]) * sk));
        TS(2);
        if (!last) {
          if (wi == 3) {
            const uint32_t s8 = sb + ((l16 & 511) >> 1), xr = sb + ((l16 & 511) >> 2), ka = l16 + (l16 & 384) * 4 + (s & 1) * (2 * KVB);
            bar_sync(B_QK, 384);
            uint32_t a0[4], a1[4], a2[4], a3[4], kb0[4], kb1[4];
            ldsm_x4_i<OFF_Q>(a0, l16); ldsm_x4_i<OFF_KV + 512>(kb0, ka); ldsm_x4_i<OFF_Q + 1024>(a2, l16); ldsm_x4_i<OFF_KV + 512 + 2560>(kb1, ka);
            ldsm_x4_i<OFF_Q + 512>(a1, l16);
            bar_arrive(B_A, 288);
            ldsm_x4_i<OFF_Q + 1536>(a3, l16);
            float sa[4] = {0, 0, 0, 0}, sc2[4] = {0, 0, 0, 0};
            mma16816(sa, a0[0], a0[1], a0[2], a0[3], kb0[0], kb0[1]);
            mma16816(sc2, a2[0], a2[1], a2[2], a2[3], kb1[0], kb1[1]);
            mma16816(sa, a1[0], a1[1], a1[2], a1[3], kb0[2], kb0[3]);
            mma16816(sc2, a3[0], a3[1], a3[2], a3[3], kb1[2], kb1[3]);
            const float x0 = (sa[0] + sa[2]) + (sc2[0] + sc2[2]), x1 = (sa[1] + sa[3]) + (sc2[1] + sc2[3]);
            const uint32_t xp = pack_bf16(x0, x1);
            st_async_b32_i<OFF_SR + 1024 + 256>(xr + d1, xp, sb + MB_S + d1);
            st_async_b32_i<OFF_SR + 1024>(xr + d2, xp, sb + MB_S + d2);
            sts64_i<OFF_S + 1024>(s8, __float_as_uint(x0), __float_as_uint(x1));
          } else {
            bar_arrive(B_QK, 384);
          }
          bar_sync(B_SL, 256);
        }
      } else {
        float v0[4] = {0, 0, 0, 0}, v1[4] = {0, 0, 0, 0}, q0[4] = {0, 0, 0, 0}, q1[4] = {0, 0, 0, 0};
        uint32_t b[NQ1 / 2][4];
        static_for<0, NQ1 / 2>([&](auto T) { ldsm_x4_i<OFF_MEM + (NPQ + T.value) * 512>(b[T.value], mema); });
        static_for<0, NQ1 / 2>([&](auto T) {
          constexpr int t = T.value, p = NPQ + t;
          uint32_t (&bb)[4] = b[t];
          mma16816h(q0, rq[2 * t], bb[0], bb[1]);
          mma16816h(q1, rq[2 * t + 1], bb[2], bb[3]);
          mma16816h(v0, w[2 * p], bb[0], bb[1]);
          mma16816h(v1, w[2 * p + 1], bb[2], bb[3]);
        });
        const float sq = sin_ * iq, sv = sin_ * iw;
        stsm_x2_t_i<0>(sta, pack_bf16((q0[0] + q1[0]) * sq, (q0[1] + q1[1]) * sq), pack_bf16((q0[2] + q1[2]) * sq, (q0[3] + q1[3]) * sq));
        TS(2);
        if (!last) { bar_arrive(B_QK, 384); bar_sync(B_A, 288); }
        float v2[4] = {0, 0, 0, 0}, v3[4] = {0, 0, 0, 0};
        uint32_t c[4][4];
        static_for<0, 4>([&](auto T) { ldsm_x4_i<OFF_MEM + T.value * 512>(c[T.value], mema); });
        static_for<0, NPQ>([&](auto T) {
          constexpr int p = T.value;
          uint32_t (&bb)[4] = c[p & 3];
          if constexpr (p & 1) { mma16816h(v0, w[2 * p], bb[0], bb[1]); mma16816h(v1, w[2 * p + 1], bb[2], bb[3]); }
          else { mma16816h(v2, w[2 * p], bb[0], bb[1]); mma16816h(v3, w[2 * p + 1], bb[2], bb[3]); }
          if constexpr (p + 4 < NPQ) ldsm_x4_i<OFF_MEM + (p + 4) * 512>(bb, mema);
        });
        stsm_x2_t_i<OFF_KV + KVB + 512>(l16 + (l16 & 128) * 4 + (wi * 1280 + (s & 1) * (2 * KVB)), pack_bf16(((v0[0] + v1[0]) + (v2[0] + v3[0])) * sv, ((v0[1] + v1[1]) + (v2[1] + v3[1])) * sv),
                            pack_bf16(((v0[2] + v1[2]) + (v2[2] + v3[2])) * sv, ((v0[3] + v1[3]) + (v2[3] + v3[3])) * sv));
        if (!last) bar_arrive(B_V, 256);
      }
      TS(3);
      if (last) break;
      {
        uint32_t t1[12][4], t2[12][4];
        const uint32_t o16 = l16;
        wo1 = l16 + (OFF_WO + warp * 896);
        wo2 = sb + OFF_WO + warp * 896 + ((l16 & 128) ? 768 + ((l16 & 256) >> 2) + (l16 & 16) + ((l16 & 64) >> 1) : 512 + ((l16 & 256) >> 1) + (l16 & 112));
        auto ldw = [&](auto K) { if constexpr (K.value < 12 - NPM) { ldsm_x4_i<K.value * WOK>(t1[K.value], wo1); ldsm_x4_i<K.value * WOK>(t2[K.value], wo2); } };
        constexpr int NR_ = NRT - NPM;
        constexpr int PB = (hf ? PB1 : PB0) < NR_ ? (hf ? PB1 : PB0) : NR_, PA = (hf ? PA1 : PA0) < PB ? (hf ? PA1 : PA0) : PB;
        static_for<0, PA>(ldw);
        mbar_spin(sb + MB_X, (s + 1) & 1);
        if constexpr (PB > PA) bar_sync(B_G, 384); else bar_arrive(B_G, 384);
        static_for<PA, PB>(ldw);
        float c0[4] = {0, 0, 0, 0}, c1[4] = {0, 0, 0, 0}, e0[4] = {0, 0, 0, 0}, e1[4] = {0, 0, 0, 0};
        uint32_t ob[6][4];
        auto kstep = [&](auto K) {
          constexpr int k = K.value;
          uint32_t (&bb)[4] = ob[k >> 1];
          uint32_t (&x)[4] = k < 12 - NPM ? t1[k] : u1[k < 12 - NPM ? 0 : k - (12 - NPM)];
          uint32_t (&y)[4] = k < 12 - NPM ? t2[k] : u2[k < 12 - NPM ? 0 : k - (12 - NPM)];
          if constexpr (k & 1) { mma16816(c1, x[0], x[1], x[2], x[3], bb[2], bb[3]); mma16816(e1, y[0], y[1], y[2], y[3], bb[2], bb[3]); }
          else { mma16816(c0, x[0], x[1], x[2], x[3], bb[0], bb[1]); mma16816(e0, y[0], y[1], y[2], y[3], bb[0], bb[1]); }
          if constexpr (k >= NRF) ldw(IC<k + NR_ - NRF>{});
        };
        auto ldo = [&](auto P) { ldsm_x4_i<OFF_O + P.value * 512>(ob[P.value], o16); };
        TS(4);
        bar_sync(B_O, 384);
        ldo(IC<0>{}); ldo(IC<1>{});
        SFENCE(o16);
        static_for<PB, NR_>(ldw);
        static_for<0, 4>(kstep);
        TS(5);
        mbar_spin(sb + MB_O, s & 1);
        TS(6);
        ldo(IC<2>{}); ldo(IC<NPM >= 2 ? 5 : 3>{});
        if (WOF) SFENCE(o16);
        kstep(IC<4>{});
        if constexpr (NPM < 2) { kstep(IC<5>{}); ldo(IC<4>{}); kstep(IC<6>{}); kstep(IC<7>{}); ldo(IC<5>{}); static_for<8, 12>(kstep); }
        else if constexpr (NPM >= 4) { kstep(IC<10>{}); kstep(IC<11>{}); ldo(IC<4>{}); kstep(IC<5>{}); ldo(IC<3>{}); kstep(IC<8>{}); kstep(IC<9>{}); kstep(IC<6>{}); kstep(IC<7>{}); }
        else { kstep(IC<5>{}); ldo(IC<3>{}); kstep(IC<11>{}); kstep(IC<10>{}); ldo(IC<4>{}); kstep(IC<6>{}); kstep(IC<7>{}); if constexpr (NPM == 3) { kstep(IC<9>{}); kstep(IC<8>{}); } else { kstep(IC<8>{}); kstep(IC<9>{}); } }
        l16 = fresh(l16);
        const int ln = (l16 >> 4) & 31;
        unsigned char* gr = arena + (AR_ACC + acc_lane(bi, ln) + acc_voff(bv) + acc_step(s));
        const bool cnt = (ln & 1) || !t28;
        wqa = wq_addr(l16);
        SFENCE(o16);
        static_for<0, PQE>([&](auto K) { ldsm_x4_t_i<OFF_WQ + K.value * 2048>(rq[K.value], wqa); });
        const uint32_t y0 = movm_t(pack_f16(c0[0] + c1[0], c0[1] + c1[1])), y1 = movm_t(pack_f16(c0[2] + c1[2], c0[3] + c1[3]));
        const uint32_t y2 = movm_t(pack_f16(e0[0] + e1[0], e0[1] + e1[1])), y3 = movm_t(pack_f16(e0[2] + e1[2], e0[3] + e1[3]));
        asm volatile("red.relaxed.gpu.global.add.noftz.v4.f16x2 [%0], {%1,%2,%3,%4};" :: "l"(gr), "r"(y0), "r"(y1), "r"(y2), "r"(cnt ? 0x3c00u : y3) : "memory");
        if constexpr (hf || RSYNC) bar_sync(B_RED, 384); else bar_arrive(B_RED, 384);
        TS(7);
      }
      x_gemm((s + 1) & 1, 0);
      TS(8);
    }
    };
    if (hf == 0) run(IC<0>{}); else run(IC<1>{});
    bar_arrive(B_RED, 384);
    asm volatile("barrier.cluster.arrive.relaxed.aligned; barrier.cluster.wait.aligned;" ::: "memory");
  }
}
struct PrepArgs { const bf16 *wqkv, *wphi, *wo; bf16 *wb, *wot; };
constexpr int PREP_TASKS = 3840;
__device__ __forceinline__ void prep_body(const int b, const bf16* __restrict__ wqkv, const bf16* __restrict__ wphi, const bf16* __restrict__ wo,
                                          bf16* __restrict__ wb, bf16* __restrict__ wot) {
  const int task = b, lane = threadIdx.x & 31;
  if (task < 1920) {
    const int which = task / 640, h = (task / 20) % 32, k = (task % 20) * 32 + lane;
    const int row0 = 288 * (h >> 2) + 96 * which + 24 * (h & 3);
    const uint2* src = (const uint2*)(wqkv + (size_t)k * 1920 + which * 640 + h * 20);
    float w[20];
#pragma unroll
    for (int d = 0; d < 5; d++) { const uint2 t = __ldg(src + d); w[4 * d] = bf_lo(t.x); w[4 * d + 1] = bf_hi(t.x); w[4 * d + 2] = bf_lo(t.y); w[4 * d + 3] = bf_hi(t.y); }
    if (which < 2) {
      float a[20];
#pragma unroll
      for (int f = 0; f < 20; f++) a[f] = 0.f;
      const uint32_t* ph = (const uint32_t*)(wphi + h * 400);
#pragma unroll
      for (int d = 0; d < 20; d++)
#pragma unroll
        for (int f = 0; f < 10; f++) { const uint32_t t = __ldg(ph + d * 10 + f); a[2 * f] = fmaf(w[d], bf_lo(t), a[2 * f]); a[2 * f + 1] = fmaf(w[d], bf_hi(t), a[2 * f + 1]); }
#pragma unroll
      for (int f = 0; f < 20; f++) wb[(size_t)(row0 + f) * cfg::DM + k] = __float2bfloat16_rn(a[f]);
    } else {
#pragma unroll
      for (int d = 0; d < 20; d++) wb[(size_t)(row0 + d) * cfg::DM + k] = __float2bfloat16_rn(w[d]);
    }
#pragma unroll
    for (int f = 20; f < 24; f++) wb[(size_t)(row0 + f) * cfg::DM + k] = __float2bfloat16_rn(0.f);
  } else {
    const int t = task - 1920, n = (t % 20) * 32 + lane, kk0 = (t / 20) * 8, h = kk0 / 24, d0 = kk0 % 24;
    unsigned short v[8];
#pragma unroll
    for (int e = 0; e < 8; e++) v[e] = (d0 + e < 20) ? __ldg((const unsigned short*)wo + (size_t)(h * 20 + d0 + e) * cfg::DM + n) : (unsigned short)0;
    *(uint4*)(wot + (size_t)n * 768 + kk0) = make_uint4(v[0] | (v[1] << 16), v[2] | (v[3] << 16), v[4] | (v[5] << 16), v[6] | (v[7] << 16));
  }
}

__global__ void __launch_bounds__(256, 4) ln_kernel(const bf16* __restrict__ xin, bf16* __restrict__ xn, uint2* __restrict__ xh, uint4* __restrict__ z0, int n0,
                                                    uint4* __restrict__ z1, int n1, const bf16* pfa, const bf16* pfb, int npf, int tl) {
  asm volatile("griddepcontrol.wait;" ::: "memory");
  asm volatile("griddepcontrol.launch_dependents;" ::: "memory");
  TL_BEGIN(tl);
  const int warp = threadIdx.x >> 5, lane = threadIdx.x & 31;
  const int row = blockIdx.x * 8 + warp;
  uint2 xw[5];
#pragma unroll
  for (int i = 0; i < 5; i++) xw[i] = *(const uint2*)(xin + (size_t)row * cfg::DM + i * 128 + lane * 4);
  for (int i = blockIdx.x * 256 + threadIdx.x; i < n0; i += 256 * 256) z0[i] = make_uint4(0, 0, 0, 0);
  for (int i = blockIdx.x * 256 + threadIdx.x; i < n1; i += 256 * 256) z1[i] = make_uint4(0, 0, 0, 0);
  if (npf && xw[4].y != 0x7fc17fc1u) {
    for (int i = 0; i < npf; i++) {
      const uint32_t l = (uint32_t)i * 32768u + (blockIdx.x * 256 + threadIdx.x) / 2;
      if (l < cfg::DM * cfg::HD / 64) asm volatile("prefetch.global.L2 [%0];" :: "l"(((threadIdx.x & 1) ? pfa : pfb) + (size_t)l * 64) : "memory");
    }
  }
  ln_row(xw, row, lane, xn, xh);
  TL_END(tl);
}
struct Pipe { uint32_t stage, phase; };
template <int NS> __device__ __forceinline__ void pipe_adv(Pipe& p) { if (++p.stage == NS) { p.stage = 0; p.phase ^= 1; } }
constexpr uint32_t SWZ128 = 1;
__device__ __forceinline__ uint64_t desc_kmajor(uint32_t a) { return make_desc(a, 16, 1024, SWZ128); }
__device__ __forceinline__ uint64_t desc_mnmajor(uint32_t a) { return make_desc(a, 8192, 1024, SWZ128); }
__device__ __forceinline__ void wait_ge(const void* p, uint32_t target) {
  int spin = 0;
  while (ld_acquire_u32(p) < target) { __nanosleep(32); if (++spin > (1 << 23)) break; }
}
__device__ __forceinline__ void bulk_g2s_hint(uint32_t dst, const void* src, uint32_t bytes, uint32_t mb, uint64_t pol) {
  asm volatile("cp.async.bulk.shared::cluster.global.mbarrier::complete_tx::bytes.L2::cache_hint [%0], [%1], %2, [%3], %4;"
               :: "r"(dst), "l"(src), "r"(bytes), "r"(mb), "l"(pol) : "memory");
}
#define EF_KV 1
#define EF_O 1
__device__ __forceinline__ void fence_proxy_async_global() { asm volatile("fence.proxy.async.global;" ::: "memory"); }

namespace tr {
constexpr int NS = 4, STQ = 16384 + 24576, STO = 16384 + 40960;
constexpr int SEGB = 15360;
constexpr int OFF_K = NS * STQ;
constexpr int OFF_BAR = NS * STO;
constexpr int SMEM = OFF_BAR + 256;
static_assert(OFF_K + 4 * SEGB <= OFF_BAR && SMEM <= 232448, "smem");
enum { T_QA = 0, T_Q, T_A, T_OB, T_OS, T_L, T_END };
constexpr uint32_t C_QA = AR_CNT, C_O = AR_CNT + 64, C_Q = AR_CNT + 128;
struct Sched {
  uint16_t start[96];
  uint8_t type[96], blk[96];
  uint8_t ks[16];
  uint8_t wide[16];
  uint8_t lrows[16];
};
struct Args {
  const unsigned char *kg, *vg;
  unsigned char* o;
  uint4* qs;
  float* part;
  const bf16* xin;
  bf16 *xout, *xn;
  unsigned char* arena;
  int doprep, tl;
};
}

template <int N0, int N1>
__device__ __forceinline__ void tr_mainloop(float (&a0)[N0 / 2], float (&a1)[N1 ? N1 / 2 : 1], Pipe& p, uint32_t sb, uint32_t full, uint32_t empty, int nkb, int wg) {
  using namespace tr;
  constexpr uint32_t ST = N1 ? STO : STQ;
  uint32_t prev = 0;
#pragma unroll
  for (int i = 0; i < N0 / 2; i++) a0[i] = 0.f;
  if constexpr (N1 > 0) {
#pragma unroll
    for (int i = 0; i < N1 / 2; i++) a1[i] = 0.f;
  }
  for (int kb = 0; kb < nkb; kb++) {
    mbar_wait(full + 8 * p.stage, p.phase);
    const uint32_t st = sb + p.stage * ST;
    wgmma_fence();
#pragma unroll
    for (int kk = 0; kk < 4; kk++) {
      const uint64_t da = desc_kmajor(st + wg * 8192 + kk * 32);
      if constexpr (N0 == 192) wgmma_n192<0, 1>(a0, da, desc_mnmajor(st + 16384 + kk * 2048), (kb | kk) != 0);
      else wgmma_n128<0, 1>(a0, da, desc_mnmajor(st + 16384 + kk * 2048), (kb | kk) != 0);
      if constexpr (N1 > 0) wgmma_n128<0, 1>(a1, da, desc_mnmajor(st + 16384 + 24576 + kk * 2048), (kb | kk) != 0);
    }
    wgmma_commit();
    if (kb > 0) { wgmma_wait<1>(); if ((threadIdx.x & 127) == 0) mbar_arrive(empty + 8 * prev); }
    prev = p.stage;
    pipe_adv<NS>(p);
  }
  wgmma_wait<0>();
  if ((threadIdx.x & 127) == 0) mbar_arrive(empty + 8 * prev);
}
template <int N> __device__ __forceinline__ void store_part(const float (&acc)[N / 2], float* __restrict__ p0) {
#pragma unroll
  for (int v = 0; v < N / 8; v++) {
    *(float2*)(p0 + 8 * v) = make_float2(acc[4 * v], acc[4 * v + 1]);
    *(float2*)(p0 + 8 * cfg::DM + 8 * v) = make_float2(acc[4 * v + 2], acc[4 * v + 3]);
  }
}

__global__ void __launch_bounds__(384, 1) trail_kernel(const __grid_constant__ CUtensorMap tmX, const __grid_constant__ CUtensorMap tmQ,
                                                       const __grid_constant__ CUtensorMap tmWo5, const __grid_constant__ CUtensorMap tmWo2, const __grid_constant__ tr::Sched sc,
                                                       const __grid_constant__ tr::Args a, const __grid_constant__ PrepArgs pa) {
  using namespace tr;
  [[maybe_unused]] const int tl = a.tl;
  TL_BEGIN(tl);
  extern __shared__ __align__(1024) unsigned char smem_raw[];
  const uint32_t sb = smem_u32(smem_raw);
  const int warp = __shfl_sync(0xffffffffu, (int)threadIdx.x >> 5, 0), lane = threadIdx.x & 31;
  unsigned char* const arena = a.arena;
  const uint32_t full = sb + OFF_BAR, empty = full + 8 * NS, barK = empty + 8 * NS, barKfree = barK + 16, staged = barKfree + 16;
  const uint32_t mfull = staged + 32, mempty = mfull + 16, mbox = mempty + 16;
  if (threadIdx.x == 0) {
    for (int i = 0; i < NS; i++) { mbar_init(full + 8 * i, 1); mbar_init(empty + 8 * i, 2); }
    for (int i = 0; i < 2; i++) {
      mbar_init(barK + 8 * i, 1); mbar_init(barKfree + 8 * i, 1); mbar_init(staged + 16 * i, 4); mbar_init(staged + 16 * i + 8, 4);
      mbar_init(mfull + 8 * i, 1); mbar_init(mempty + 8 * i, 10);
    }
    asm volatile("fence.mbarrier_init.release.cluster;" ::: "memory");
  }
  __syncthreads();
  Pipe mp{0, 0};
  auto next_item = [&](int& type, int& m, int& k) {
    uint32_t it;
    mbar_wait(mfull + 8 * mp.stage, mp.phase);
    asm volatile("ld.shared.u32 %0, [%1];" : "=r"(it) : "r"(mbox + 4 * mp.stage) : "memory");
    type = it >> 16; m = (it >> 8) & 255; k = it & 255;
  };
  if (warp >= 8) {
    asm volatile("setmaxnreg.dec.sync.aligned.u32 40;");
    if (warp == 8) { if (elect_one()) {
      Pipe p{0, 1};
      mp.phase = 1;
      uint32_t kph = 1, wide = 0;
      int g = 0;
      const uint64_t ef = policy_evict_first();
      auto ld_kv = [&](uint32_t d, const void* s, uint32_t n, uint32_t mb) { if (EF_KV) bulk_g2s_hint(d, s, n, mb, ef); else bulk_g2s(d, s, n, mb); };
      auto ld_o = [&](uint32_t d, const void* s, uint32_t n, uint32_t mb) { if (EF_O) bulk_g2s_hint(d, s, n, mb, ef); else bulk_g2s(d, s, n, mb); };
      auto stage = [&](uint32_t bytes) -> uint32_t {
        mbar_wait(empty + 8 * p.stage, p.phase);
        mbar_expect_tx(full + 8 * p.stage, bytes);
        return sb + p.stage * (wide ? STO : STQ);
      };
      while (true) {
        const uint32_t item = atomicAdd((unsigned*)(arena + AR_QUEUE), 1u);
        while (item >= sc.start[g + 1] && sc.type[g] != T_END) g++;
        const int type = sc.type[g], m = sc.blk[g], k = item - sc.start[g];
        if (type == T_L) { wait_ge(arena + C_O + m * 4, sc.ks[m] * (sc.wide[m] ? 4 : 10)); }
        if (type == T_A) wait_ge(arena + C_Q + m * 4, 64);
        mbar_wait(mempty + 8 * mp.stage, mp.phase);
        asm volatile("st.shared.u32 [%0], %1;" :: "r"(mbox + 4 * mp.stage), "r"((type << 16) | (m << 8) | (k & 255)) : "memory");
        mbar_arrive(mfull + 8 * mp.stage);
        pipe_adv<2>(mp);
        if (type == T_END) break;
        if (type == T_L) continue;
        if (wide != (type == T_OB)) {
          for (uint32_t i = 0; i < NS; i++) mbar_wait(empty + 8 * i, i >= p.stage ? p.phase : p.phase ^ 1);
          mbar_wait(barKfree, kph); mbar_wait(barKfree + 8, kph);
          wide = type == T_OB;
        }
        if (type <= T_A) {
          auto ready = [&](bool block) -> bool {
            for (int jj = 0; jj < 3; jj++) {
              const void* f = arena + AR_PROG + (k * 3 + jj) * 4;
              if (block) wait_ge(f, 4 * m + 4); else if (ld_acquire_u32(f) < (uint32_t)(4 * m + 4)) return false;
            }
            return true;
          };
          const size_t blk = ((size_t)m * 4 * 96 + k * 3) * 5120;
          auto load_k = [&]() {
            fence_proxy_async_global();
            for (int w = 0; w < 2; w++) {
              mbar_wait(barKfree + 8 * w, kph);
              mbar_expect_tx(barK + 8 * w, 2 * SEGB);
              for (int sg = 2 * w; sg < 2 * w + 2; sg++) ld_kv(sb + OFF_K + sg * SEGB, a.kg + blk + (size_t)sg * (96 * 5120), SEGB, barK + 8 * w);
            }
            kph ^= 1;
          };
          bool kdone = type == T_Q;
          if (type != T_A)
            for (int kb = 0; kb < 10; kb++) {
              const uint32_t st = stage(STQ), fb = full + 8 * p.stage;
              tma_load_2d(st, &tmX, kb * 64, m * 128, fb);
              tma_load_3d(st + 16384, &tmQ, 0, kb * 64, k * 3, fb);
              pipe_adv<NS>(p);
              if (!kdone && kb == 6 && ready(false)) { load_k(); kdone = true; }
            }
          if (type != T_Q) {
            if (!kdone) { ready(true); load_k(); }
            for (int w = 0; w < 2; w++) {
              const uint32_t st = stage(2 * SEGB), fb = full + 8 * p.stage;
              for (int sg = 0; sg < 2; sg++) ld_kv(st + sg * SEGB, a.vg + blk + (size_t)(2 * w + sg) * (96 * 5120), SEGB, fb);
              pipe_adv<NS>(p);
            }
          }
        } else {
          const int nn = wide ? 2 : 5, nb = wide ? 5 : 2, nt = k % nn, nkb = 96 / sc.ks[m], k0 = (k / nn) * nkb;
          const Pipe p0 = p;
          for (int kb = 0; kb < nkb; kb++) {
            const uint32_t st = stage(16384 + nb * 8192), fb = full + 8 * p.stage;
            tma_load_3d(st + 16384, wide ? &tmWo5 : &tmWo2, 0, (k0 + kb) * 64, nt * nb, fb);
            if (kb >= NS) ld_o(st, a.o + ((size_t)m * 96 + k0 + kb) * 16384, 16384, fb);
            pipe_adv<NS>(p);
            if (kb == NS - 1 || (kb == nkb - 1 && nkb < NS)) {
              wait_ge(arena + C_QA + m * 4, 64);
              fence_proxy_async_global();
              Pipe q = p0;
              for (int i = 0; i <= kb; i++) { ld_o(sb + q.stage * (wide ? STO : STQ), a.o + ((size_t)m * 96 + k0 + i) * 16384, 16384, full + 8 * q.stage); pipe_adv<NS>(q); }
            }
          }
        }
      }
    } } else if (warp < 11) { if (elect_one()) {
      const int w = warp - 9;
      uint32_t sph = 0;
      [[maybe_unused]] int nlog = 0;
      while (true) {
        int type, m, k;
        next_item(type, m, k);
        const uint32_t slot = mp.stage;
        pipe_adv<2>(mp);
        if (type == T_END) break;
        mbar_wait(staged + 16 * w + 8 * slot, (sph >> slot) & 1); sph ^= 1u << slot;
        mbar_arrive(mempty + 8 * slot);
        if (type == T_L) continue;
        if (type == T_QA || type == T_A) {
          for (int jj = 0; jj < 3; jj++) bulk_s2g(a.o + ((size_t)m * 96 + k * 3 + jj) * 16384 + w * 8192, sb + OFF_K + w * 2 * SEGB + jj * 8192, 8192);
          bulk_commit();
          bulk_wait<0>();
          mbar_arrive(barKfree + 8 * w);
        }
        asm volatile("red.release.gpu.global.add.u32 [%0], 1;" :: "l"(arena + (type == T_Q ? C_Q : (type <= T_A ? C_QA : C_O)) + m * 4) : "memory");
      }
    } }
    if (blockIdx.x == gridDim.x - 1 && warp == 11) asm volatile("griddepcontrol.wait;" ::: "memory");
    return;
  }
  asm volatile("setmaxnreg.inc.sync.aligned.u32 232;");
  const int wg = warp >> 2, wi = warp & 3;
  const int g = lane >> 2, q4 = lane & 3;
  if (a.doprep && blockIdx.x < 32) for (int t = blockIdx.x * 8 + warp; t < PREP_TASKS; t += 256) prep_body(t, pa.wqkv, pa.wphi, pa.wo, pa.wb, pa.wot);
  Pipe p{0, 0};
  uint32_t kph = 0;
  while (true) {
    int type, m, k;
    next_item(type, m, k);
    __syncwarp();
    if (lane == 0) mbar_arrive(mempty + 8 * mp.stage);
    const uint32_t done = staged + 16 * wg + 8 * mp.stage;
    pipe_adv<2>(mp);
    if (type == T_END) break;
    if (type == T_L) {
      const int nr = sc.lrows[m], np = sc.ks[m];
      for (int r = 0; r < nr; r++) {
        const int row = m * 128 + (k * 8 + warp) * nr + r;
        uint2 xw[5]; float4 s[5];
        const float* pp = a.part + (size_t)row * cfg::DM + lane * 4;
#pragma unroll
        for (int i = 0; i < 5; i++) { xw[i] = __ldcg((const uint2*)(a.xin + (size_t)row * cfg::DM + i * 128 + lane * 4)); s[i] = make_float4(0, 0, 0, 0); }
        for (int p0 = 0; p0 < np; p0 += 6) {
          float4 t[6][5];
#pragma unroll
          for (int q = 0; q < 6; q++)
#pragma unroll
            for (int i = 0; i < 5; i++) t[q][i] = p0 + q < np ? __ldcg((const float4*)(pp + (size_t)(p0 + q) * cfg::S * cfg::DM + i * 128)) : make_float4(0, 0, 0, 0);
#pragma unroll
          for (int q = 0; q < 6; q++)
#pragma unroll
            for (int i = 0; i < 5; i++) { s[i].x += t[q][i].x; s[i].y += t[q][i].y; s[i].z += t[q][i].z; s[i].w += t[q][i].w; }
        }
#pragma unroll
        for (int i = 0; i < 5; i++) {
          xw[i] = make_uint2(pack_bf16(bf_lo(xw[i].x) + bf16r(s[i].x), bf_hi(xw[i].x) + bf16r(s[i].y)), pack_bf16(bf_lo(xw[i].y) + bf16r(s[i].z), bf_hi(xw[i].y) + bf16r(s[i].w)));
          *(uint2*)(a.xout + (size_t)row * cfg::DM + i * 128 + lane * 4) = xw[i];
        }
        ln_row(xw, row, lane, a.xn, nullptr);
      }
      __syncwarp();
      if (lane == 0) mbar_arrive(done);
      continue;
    }
    if (type >= T_OB) {
      const int nkb = 96 / sc.ks[m];
      float* dst = a.part + (size_t)(m * 128 + wg * 64 + wi * 16 + g) * cfg::DM + q4 * 2;
      if (type == T_OB) {
        float a0[96], a1[64];
        tr_mainloop<192, 128>(a0, a1, p, sb, full, empty, nkb, wg);
        dst += (size_t)(k >> 1) * cfg::S * cfg::DM + (k & 1) * 320;
        store_part<192>(a0, dst); store_part<128>(a1, dst + 192);
      } else {
        float a0[64], a1[1];
        tr_mainloop<128, 0>(a0, a1, p, sb, full, empty, nkb, wg);
        store_part<128>(a0, dst + (size_t)(k / 5) * cfg::S * cfg::DM + (k % 5) * 128);
      }
      __syncwarp();
      if (lane == 0) mbar_arrive(done);
      continue;
    }
    uint32_t qf[12][4];
    uint4* qp = a.qs + ((size_t)((m & 3) * 32 + k) * 12) * 256 + threadIdx.x;
    if (type != T_A) {
      float acc[96], a1[1];
      tr_mainloop<192, 0>(acc, a1, p, sb, full, empty, 10, wg);
#pragma unroll
      for (int i = 0; i < 12; i++) {
        qf[i][0] = pack_bf16(acc[8 * i], acc[8 * i + 1]); qf[i][1] = pack_bf16(acc[8 * i + 2], acc[8 * i + 3]);
        qf[i][2] = pack_bf16(acc[8 * i + 4], acc[8 * i + 5]); qf[i][3] = pack_bf16(acc[8 * i + 6], acc[8 * i + 7]);
      }
      if (type == T_Q) {
#pragma unroll
        for (int i = 0; i < 12; i++) qp[i * 256] = make_uint4(qf[i][0], qf[i][1], qf[i][2], qf[i][3]);
        __syncwarp();
        if (lane == 0) mbar_arrive(done);
        continue;
      }
    } else {
#pragma unroll
      for (int i = 0; i < 12; i++) { const uint4 v = __ldcg(qp + i * 256); qf[i][0] = v.x; qf[i][1] = v.y; qf[i][2] = v.z; qf[i][3] = v.w; }
    }
    const uint32_t kbase = sb + OFF_K + wg * 2 * SEGB;
    const bool second = wi >= 2;
    uint32_t pf[5][4];
    {
      float sa[20], sb2[20];
      mbar_wait(barK + 8 * wg, kph); kph ^= 1;
      wgmma_fence();
#pragma unroll
      for (int i = 0; i < 12; i++) {
        wgmma_rs_n40<0>(sa, qf[i][0], qf[i][1], qf[i][2], qf[i][3], make_desc(kbase + i * 1280, 640, 128, 0), i != 0);
        wgmma_rs_n40<0>(sb2, qf[i][0], qf[i][1], qf[i][2], qf[i][3], make_desc(kbase + SEGB + i * 1280, 640, 128, 0), i != 0);
      }
      wgmma_commit();
      wgmma_wait<0>();
      const float cs = 0.07216878364870322f * 1.4426950408889634f;
      const int r0 = 16 * (wi & 1) + g, r1 = r0 + 8;
      float m0 = -INFINITY, m1 = -INFINITY;
#pragma unroll
      for (int n = 0; n < 5; n++) {
#pragma unroll
        for (int e = 0; e < 2; e++) {
          const int key = 8 * n + 2 * q4 + e;
          float x = second ? sb2[4 * n + e] : sa[4 * n + e], y = second ? sb2[4 * n + 2 + e] : sa[4 * n + 2 + e];
          if (n < 4) { if (key > r0) x = -INFINITY; if (key > r1) y = -INFINITY; }
          sa[4 * n + e] = x; sa[4 * n + 2 + e] = y;
          m0 = fmaxf(m0, x); m1 = fmaxf(m1, y);
        }
      }
      m0 = fmaxf(m0, __shfl_xor_sync(0xffffffffu, m0, 1)); m1 = fmaxf(m1, __shfl_xor_sync(0xffffffffu, m1, 1));
      m0 = fmaxf(m0, __shfl_xor_sync(0xffffffffu, m0, 2)); m1 = fmaxf(m1, __shfl_xor_sync(0xffffffffu, m1, 2));
      float s0 = 0.f, s1 = 0.f;
#pragma unroll
      for (int n = 0; n < 5; n++) {
#pragma unroll
        for (int e = 0; e < 2; e++) {
          sa[4 * n + e] = ex2f((sa[4 * n + e] - m0) * cs); sa[4 * n + 2 + e] = ex2f((sa[4 * n + 2 + e] - m1) * cs);
          s0 += sa[4 * n + e]; s1 += sa[4 * n + 2 + e];
        }
      }
      s0 += __shfl_xor_sync(0xffffffffu, s0, 1); s1 += __shfl_xor_sync(0xffffffffu, s1, 1);
      s0 += __shfl_xor_sync(0xffffffffu, s0, 2); s1 += __shfl_xor_sync(0xffffffffu, s1, 2);
      const float i0 = rcpf(s0), i1 = rcpf(s1);
#pragma unroll
      for (int n = 0; n < 5; n++) {
        const uint32_t x = pack_bf16(sa[4 * n] * i0, sa[4 * n + 1] * i0), y = pack_bf16(sa[4 * n + 2] * i1, sa[4 * n + 3] * i1);
        if (n < 4) {
          pf[n >> 1][2 * (n & 1)] = second ? 0u : x; pf[n >> 1][2 * (n & 1) + 1] = second ? 0u : y;
          pf[2 + (n >> 1)][2 * (n & 1)] = second ? x : 0u; pf[2 + (n >> 1)][2 * (n & 1) + 1] = second ? y : 0u;
        } else {
          pf[4][0] = second ? 0u : x; pf[4][1] = second ? 0u : y; pf[4][2] = second ? x : 0u; pf[4][3] = second ? y : 0u;
        }
      }
    }
    {
      const uint32_t sA = p.stage, phA = p.phase; pipe_adv<NS>(p);
      const uint32_t sB = p.stage, phB = p.phase; pipe_adv<NS>(p);
      const uint32_t own = wg ? sB : sA;
      float o[96];
      mbar_wait(full + 8 * own, wg ? phB : phA);
      const uint32_t vbase = sb + own * STQ;
      wgmma_fence();
#pragma unroll
      for (int i = 0; i < 5; i++)
        wgmma_rs_n192<1>(o, pf[i][0], pf[i][1], pf[i][2], pf[i][3], i < 4 ? make_desc(vbase + (i >> 1) * SEGB + (i & 1) * 256, 128, 640, 0) : make_desc(vbase + 512, SEGB, 640, 0), i != 0);
      wgmma_commit();
      mbar_wait(full + 8 * (wg ? sA : sB), wg ? phA : phB);
      if ((threadIdx.x & 127) == 0) mbar_arrive(empty + 8 * (wg ? sA : sB));
      wgmma_wait<0>();
      if ((threadIdx.x & 127) == 0) mbar_arrive(empty + 8 * own);
      const int row = wi * 16 + (lane & 7) + 8 * ((lane >> 3) & 1);
#pragma unroll
      for (int v = 0; v < 24; v += 2)
        stsm_x4(kbase + (v >> 3) * 8192 + row * 128 + ((((v & 7) + (lane >> 4)) ^ (lane & 7)) << 4), pack_bf16(o[4 * v], o[4 * v + 1]), pack_bf16(o[4 * v + 2], o[4 * v + 3]),
                pack_bf16(o[4 * v + 4], o[4 * v + 5]), pack_bf16(o[4 * v + 6], o[4 * v + 7]));
      fence_proxy_async();
      __syncwarp();
      if (lane == 0) mbar_arrive(done);
    }
  }
}
namespace bf {
constexpr int NS = 4, STAGE = 16384 + 36864;
constexpr int PHI_STR = 112, PHI_HEAD = 128 * PHI_STR;
constexpr int V_STR = 48, V_HEAD = 128 * V_STR;
constexpr int OFF_PHI = 0, OFF_V = 4 * PHI_HEAD, OFF_X = OFF_V + 4 * V_HEAD;
constexpr int OFF_WOT = 100352;
constexpr int OFF_OST = 65536;
constexpr int ANS = 4;
constexpr int OFF_BAR = OFF_WOT + 12 * 10240;
constexpr int SMEM = OFF_BAR + 256;
static_assert(OFF_X + 4 * 36 * 128 <= OFF_WOT && NS * STAGE <= OFF_BAR && SMEM <= 232448, "smem");
}
__device__ __forceinline__ void hedgehog_features(const float (&x)[6], int q4, float (&pos)[6], float (&neg)[6]) {
  const bool v2 = q4 < 2;
  float mx = fmaxf(fmaxf(x[0], x[1]), fmaxf(x[2], x[3])), mn = fminf(fminf(x[0], x[1]), fminf(x[2], x[3]));
  if (v2) { mx = fmaxf(mx, fmaxf(x[4], x[5])); mn = fminf(mn, fminf(x[4], x[5])); }
  mx = fmaxf(mx, __shfl_xor_sync(0xffffffffu, mx, 1)); mn = fminf(mn, __shfl_xor_sync(0xffffffffu, mn, 1));
  mx = fmaxf(mx, __shfl_xor_sync(0xffffffffu, mx, 2)); mn = fminf(mn, __shfl_xor_sync(0xffffffffu, mn, 2));
  const float L = 1.4426950408889634f;
  float sp = 0.f, sn = 0.f;
#pragma unroll
  for (int i = 0; i < 6; i++) {
    const bool ok = i < 4 || v2;
    pos[i] = ok ? ex2f((x[i] - mx) * L) : 0.f;
    neg[i] = ok ? ex2f((mn - x[i]) * L) : 0.f;
    sp += pos[i]; sn += neg[i];
  }
  sp += __shfl_xor_sync(0xffffffffu, sp, 1); sn += __shfl_xor_sync(0xffffffffu, sn, 1);
  sp += __shfl_xor_sync(0xffffffffu, sp, 2); sn += __shfl_xor_sync(0xffffffffu, sn, 2);
  const float ip = rcpf(sp), in_ = rcpf(sn);
#pragma unroll
  for (int i = 0; i < 6; i++) { pos[i] *= ip; neg[i] *= in_; }
}

__global__ void __launch_bounds__(384, 1) blayer_kernel(const __grid_constant__ CUtensorMap tmA, const __grid_constant__ CUtensorMap tmB,
                                                        const __grid_constant__ CUtensorMap tmO, const __grid_constant__ CUtensorMap tmW,
                                                        float* __restrict__ kvacc, unsigned* __restrict__ cnt, bf16* __restrict__ o2,
                                                        const bf16* __restrict__ xin, bf16* __restrict__ xout,
                                                        const bf16* pf0, const bf16* pf1, const bf16* pf2, const bf16* pf3, int tl) {
  using namespace bf;
  TL_BEGIN(tl);
  extern __shared__ __align__(1024) unsigned char smem_raw[];
  const uint32_t sb = smem_u32(smem_raw);
  const int warp = __shfl_sync(0xffffffffu, (int)threadIdx.x >> 5, 0), lane = threadIdx.x & 31;
  const uint32_t full = sb + OFF_BAR, empty = full + 8 * NS, full2 = empty + 8 * NS, empty2 = full2 + 8 * ANS, barW = empty2 + 8 * ANS, barGo = barW + 8;
  const int m = blockIdx.x & 15, u = blockIdx.x >> 4;
  unsigned* cntKV = cnt + u; unsigned* cntO = cnt + 8 + m;
  if (threadIdx.x == 0) {
    for (int i = 0; i < NS; i++) { mbar_init(full + 8 * i, 1); mbar_init(empty + 8 * i, 2); }
    for (int i = 0; i < ANS; i++) { mbar_init(full2 + 8 * i, 1); mbar_init(empty2 + 8 * i, 2); }
    mbar_init(barW, 1); mbar_init(barGo, 1);
    asm volatile("fence.mbarrier_init.release.cluster;" ::: "memory");
  }
  __syncthreads();
  asm volatile("griddepcontrol.wait;" ::: "memory");
  asm volatile("griddepcontrol.launch_dependents;" ::: "memory");
  if (warp >= 8) {
    asm volatile("setmaxnreg.dec.sync.aligned.u32 40;");
    if (warp == 8 && elect_one()) {
      prefetch_tmap(&tmO); prefetch_tmap(&tmW);
      Pipe p{0, 1};
      for (int kb = 0; kb < 10; kb++) {
        mbar_wait(empty + 8 * p.stage, p.phase);
        const uint32_t st = sb + p.stage * STAGE, fb = full + 8 * p.stage;
        mbar_expect_tx(fb, STAGE);
        tma_load_2d(st, &tmA, kb * 64, m * 128, fb);
        tma_load_2d(st + 16384, &tmB, kb * 64, u * 288, fb);
        tma_load_2d(st + 16384 + 18432, &tmB, kb * 64, u * 288 + 144, fb);
        pipe_adv<NS>(p);
      }
      if (pf0) {
        constexpr uint32_t PER = cfg::DM * cfg::HD * 2 / 128;
        prefetch_l2((const unsigned char*)pf0 + blockIdx.x * PER, PER); prefetch_l2((const unsigned char*)pf1 + blockIdx.x * PER, PER);
        if (pf2) { prefetch_l2((const unsigned char*)pf2 + blockIdx.x * PER, PER); prefetch_l2((const unsigned char*)pf3 + blockIdx.x * PER, PER); }
      }
      for (int i = 0; i < NS; i++) { mbar_wait(empty + 8 * p.stage, p.phase); pipe_adv<NS>(p); }
      mbar_expect_tx(barW, 12 * 10240);
      for (int kb = 0; kb < 12; kb++) tma_load_2d(sb + OFF_WOT + kb * 10240, &tmW, kb * 64, u * 80, barW);
      mbar_wait(barGo, 0);
      wait_ge(cntO, 8);
      fence_proxy_async_global();
      Pipe q{0, 1};
      for (int kb = 0; kb < 12; kb++) {
        mbar_wait(empty2 + 8 * q.stage, q.phase);
        mbar_expect_tx(full2 + 8 * q.stage, 16384);
        tma_load_2d(sb + q.stage * 16384, &tmO, kb * 64, m * 128, full2 + 8 * q.stage);
        pipe_adv<ANS>(q);
      }
    }
    return;
  }
  asm volatile("setmaxnreg.inc.sync.aligned.u32 232;");
  const int wg = warp >> 2, wi = warp & 3;
  const int g = lane >> 2, q4 = lane & 3;
  float a0[72], a1[72];
  {
    Pipe p{0, 0};
    uint32_t prev = 0;
    for (int kb = 0; kb < 10; kb++) {
      mbar_wait(full + 8 * p.stage, p.phase);
      const uint32_t st = sb + p.stage * STAGE;
      wgmma_fence();
#pragma unroll
      for (int kk = 0; kk < 4; kk++) {
        const uint64_t da = desc_kmajor(st + wg * 8192 + kk * 32);
        wgmma_n144<0, 0>(a0, da, desc_kmajor(st + 16384 + kk * 32), (kb | kk) != 0);
        wgmma_n144<0, 0>(a1, da, desc_kmajor(st + 16384 + 18432 + kk * 32), (kb | kk) != 0);
      }
      wgmma_commit();
      if (kb > 0) { wgmma_wait<1>(); if ((threadIdx.x & 127) == 0) mbar_arrive(empty + 8 * prev); }
      prev = p.stage;
      pipe_adv<NS>(p);
    }
    wgmma_wait<0>();
    bar_sync(1, 256);
    if ((threadIdx.x & 127) == 0) mbar_arrive(empty + 8 * prev);
  }
  TL2((tl >= 12 ? 128 : 0) + 32 + 0);
  auto ACC = [&](auto V, auto E) -> float { constexpr int v = V.value, e = E.value; if constexpr (v < 18) return a0[4 * v + e]; else return a1[4 * (v - 18) + e]; };
  const int trow = wg * 64 + wi * 16;
  const int srow = (lane & 7) + 8 * ((lane >> 3) & 1);
  uint32_t qf[4][3][4];
  static_for<0, 4>([&](auto HH) {
    constexpr int hh = HH.value;
    float xa[6], xb[6], pa[6], na[6], pb[6], nb[6];
    static_for<0, 3>([&](auto T) {
      constexpr int t = T.value; using V = IC<3 * hh + t>;
      xa[2 * t] = ACC(V{}, IC<0>{}); xa[2 * t + 1] = ACC(V{}, IC<1>{}); xb[2 * t] = ACC(V{}, IC<2>{}); xb[2 * t + 1] = ACC(V{}, IC<3>{});
      bf16r2(xa[2 * t], xa[2 * t + 1]); bf16r2(xb[2 * t], xb[2 * t + 1]);
    });
    hedgehog_features(xa, q4, pa, na);
    hedgehog_features(xb, q4, pb, nb);
    qf[hh][0][0] = pack_bf16(pa[0], pa[1]); qf[hh][0][1] = pack_bf16(pb[0], pb[1]); qf[hh][0][2] = pack_bf16(pa[2], pa[3]); qf[hh][0][3] = pack_bf16(pb[2], pb[3]);
    qf[hh][1][0] = pack_bf16(pa[4], pa[5]); qf[hh][1][1] = pack_bf16(pb[4], pb[5]); qf[hh][1][2] = pack_bf16(na[0], na[1]); qf[hh][1][3] = pack_bf16(nb[0], nb[1]);
    qf[hh][2][0] = pack_bf16(na[2], na[3]); qf[hh][2][1] = pack_bf16(nb[2], nb[3]); qf[hh][2][2] = pack_bf16(na[4], na[5]); qf[hh][2][3] = pack_bf16(nb[4], nb[5]);
    static_for<0, 3>([&](auto T) {
      constexpr int t = T.value; using V = IC<12 + 3 * hh + t>;
      xa[2 * t] = ACC(V{}, IC<0>{}); xa[2 * t + 1] = ACC(V{}, IC<1>{}); xb[2 * t] = ACC(V{}, IC<2>{}); xb[2 * t + 1] = ACC(V{}, IC<3>{});
      bf16r2(xa[2 * t], xa[2 * t + 1]); bf16r2(xb[2 * t], xb[2 * t + 1]);
    });
    hedgehog_features(xa, q4, pa, na);
    hedgehog_features(xb, q4, pb, nb);
    const uint32_t ph = sb + OFF_PHI + hh * PHI_HEAD + (trow + srow) * PHI_STR + (lane >> 4) * 16;
    stsm_x4(ph, pack_bf16(pa[0], pa[1]), pack_bf16(pb[0], pb[1]), pack_bf16(pa[2], pa[3]), pack_bf16(pb[2], pb[3]));
    stsm_x4(ph + 32, pack_bf16(pa[4], pa[5]), pack_bf16(pb[4], pb[5]), pack_bf16(na[0], na[1]), pack_bf16(nb[0], nb[1]));
    stsm_x4(ph + 64, pack_bf16(na[2], na[3]), pack_bf16(nb[2], nb[3]), pack_bf16(na[4], na[5]), pack_bf16(nb[4], nb[5]));
    using V0 = IC<24 + 3 * hh>; using V1 = IC<24 + 3 * hh + 1>; using V2 = IC<24 + 3 * hh + 2>;
    float c0 = ACC(V2{}, IC<0>{}), c1 = ACC(V2{}, IC<1>{}), c2 = ACC(V2{}, IC<2>{}), c3 = ACC(V2{}, IC<3>{});
    if (q4 == 2) { c0 = 1.f; c1 = 0.f; c2 = 1.f; c3 = 0.f; }
    if (q4 == 3) { c0 = c1 = c2 = c3 = 0.f; }
    const uint32_t va = sb + OFF_V + hh * V_HEAD + (trow + srow) * V_STR;
    stsm_x4(va + (lane >> 4) * 16, pack_bf16(ACC(V0{}, IC<0>{}), ACC(V0{}, IC<1>{})), pack_bf16(ACC(V0{}, IC<2>{}), ACC(V0{}, IC<3>{})),
            pack_bf16(ACC(V1{}, IC<0>{}), ACC(V1{}, IC<1>{})), pack_bf16(ACC(V1{}, IC<2>{}), ACC(V1{}, IC<3>{})));
    stsm_x2(va + 32, pack_bf16(c0, c1), pack_bf16(c2, c3));
  });
  bar_sync(1, 256);
  TL2((tl >= 12 ? 128 : 0) + 32 + 1);
  {
    const int hh = warp >> 1, th = warp & 1;
    float d[3][3][4];
#pragma unroll
    for (int a = 0; a < 3; a++)
#pragma unroll
      for (int b = 0; b < 3; b++) { d[a][b][0] = d[a][b][1] = d[a][b][2] = d[a][b][3] = 0.f; }
#pragma unroll
    for (int ks = 0; ks < 4; ks++) {
      const int t0 = th * 64 + ks * 16;
      const uint32_t pa = sb + OFF_PHI + hh * PHI_HEAD + (t0 + (lane & 7) + 8 * (lane >> 4)) * PHI_STR + ((lane >> 3) & 1) * 16;
      const uint32_t pv = sb + OFF_V + hh * V_HEAD + (t0 + (lane & 7) + 8 * ((lane >> 3) & 1)) * V_STR;
      uint32_t b01[4], b2[2];
      ldsm_x4_t(b01, pv + (lane >> 4) * 16);
      ldsm_x2_t(b2, pv + 32);
#pragma unroll
      for (int a = 0; a < 3; a++) {
        uint32_t af[4];
        ldsm_x4_t(af, pa + a * 32);
        mma16816(d[a][0], af[0], af[1], af[2], af[3], b01[0], b01[1]);
        mma16816(d[a][1], af[0], af[1], af[2], af[3], b01[2], b01[3]);
        mma16816(d[a][2], af[0], af[1], af[2], af[3], b2[0], b2[1]);
      }
    }
    const uint32_t xa = sb + OFF_X + hh * (36 * 128) + lane * 4;
    if (th == 1) {
#pragma unroll
      for (int a = 0; a < 3; a++)
#pragma unroll
        for (int b = 0; b < 3; b++)
#pragma unroll
          for (int e = 0; e < 4; e++)
            asm volatile("st.shared.f32 [%0], %1;" :: "r"(xa + ((a * 3 + b) * 4 + e) * 128), "f"(d[a][b][e]) : "memory");
    }
    bar_sync(2 + hh, 64);
    if (th == 0) {
      float* dst = kvacc + (size_t)(u * 4 + hh) * (48 * 24);
#pragma unroll
      for (int a = 0; a < 3; a++)
#pragma unroll
        for (int b = 0; b < 3; b++) {
          float y[4];
#pragma unroll
          for (int e = 0; e < 4; e++) {
            float o;
            asm volatile("ld.shared.f32 %0, [%1];" : "=f"(o) : "r"(xa + ((a * 3 + b) * 4 + e) * 128) : "memory");
            y[e] = d[a][b][e] + o;
          }
          const int f0 = 16 * a + g, dd = 8 * b + 2 * q4;
          if (dd < 22) {
            asm volatile("red.relaxed.gpu.global.add.v2.f32 [%0], {%1,%2};" :: "l"(dst + f0 * 24 + dd), "f"(y[0]), "f"(y[1]) : "memory");
            asm volatile("red.relaxed.gpu.global.add.v2.f32 [%0], {%1,%2};" :: "l"(dst + (f0 + 8) * 24 + dd), "f"(y[2]), "f"(y[3]) : "memory");
          }
        }
      __threadfence();
    }
  }
  TL2((tl >= 12 ? 128 : 0) + 32 + 2);
  bar_sync(1, 256);
  if (threadIdx.x == 0) { __threadfence(); atomicAdd(cntKV, 1u); wait_ge(cntKV, 16); }
  bar_sync(1, 256);
  TL2((tl >= 12 ? 128 : 0) + 32 + 3);
  {
    float t[5][4];
#pragma unroll
    for (int it = 0; it < 5; it++) {
      const int i = min((int)threadIdx.x + 256 * it, 4 * 9 * 32 - 1);
      const int hh = i / 288, r = i % 288, tt = r >> 5, l = r & 31, ks = tt / 3, nt = tt % 3;
      const float* src = kvacc + (size_t)(u * 4 + hh) * (48 * 24) + (16 * ks + 2 * (l & 3)) * 24 + 8 * nt + (l >> 2);
      t[it][0] = __ldcg(src); t[it][1] = __ldcg(src + 24); t[it][2] = __ldcg(src + 8 * 24); t[it][3] = __ldcg(src + 9 * 24);
    }
#pragma unroll
    for (int it = 0; it < 5; it++) {
      const int i = threadIdx.x + 256 * it;
      if (i < 4 * 9 * 32) sts64(sb + OFF_X + i * 8, pack_bf16(t[it][0], t[it][1]), pack_bf16(t[it][2], t[it][3]));
    }
  }
  bar_sync(1, 256);
  {
    const uint32_t ost = sb + warp * 3072;
    uint32_t ow[4][6];
#pragma unroll
    for (int hh = 0; hh < 4; hh++) {
      float d[3][4];
#pragma unroll
      for (int n = 0; n < 3; n++) {
        d[n][0] = d[n][1] = d[n][2] = d[n][3] = 0.f;
        const uint32_t kb = sb + OFF_X + hh * 2304 + n * 256 + lane * 8;
        const uint2 k0 = lds64(kb), k1 = lds64(kb + 768), k2 = lds64(kb + 1536);
        mma16816(d[n], qf[hh][0][0], qf[hh][0][1], qf[hh][0][2], qf[hh][0][3], k0.x, k0.y);
        mma16816(d[n], qf[hh][1][0], qf[hh][1][1], qf[hh][1][2], qf[hh][1][3], k1.x, k1.y);
        mma16816(d[n], qf[hh][2][0], qf[hh][2][1], qf[hh][2][2], qf[hh][2][3], k2.x, k2.y);
      }
      const float da = bf16r(bf16r(__shfl_sync(0xffffffffu, d[2][0], (lane & ~3) | 2)) + 1e-6f);
      const float db = bf16r(bf16r(__shfl_sync(0xffffffffu, d[2][2], (lane & ~3) | 2)) + 1e-6f);
      float y[3][4];
#pragma unroll
      for (int n = 0; n < 3; n++) {
        bf16r2(d[n][0], d[n][1]); bf16r2(d[n][2], d[n][3]);
        y[n][0] = __fdividef(d[n][0], da); y[n][1] = __fdividef(d[n][1], da);
        y[n][2] = __fdividef(d[n][2], db); y[n][3] = __fdividef(d[n][3], db);
      }
      if (q4 >= 2) { y[2][0] = y[2][1] = y[2][2] = y[2][3] = 0.f; }
#pragma unroll
      for (int n = 0; n < 3; n++) { ow[hh][2 * n] = pack_bf16(y[n][0], y[n][1]); ow[hh][2 * n + 1] = pack_bf16(y[n][2], y[n][3]); }
    }
#pragma unroll
    for (int hh = 0; hh < 4; hh++) {
      const uint32_t ra = ost + srow * 192 + hh * 48;
      stsm_x4(ra + (lane >> 4) * 16, ow[hh][0], ow[hh][1], ow[hh][2], ow[hh][3]);
      stsm_x2(ra + 32, ow[hh][4], ow[hh][5]);
    }
    __syncwarp();
#pragma unroll
    for (int i = 0; i < 6; i++) {
      const int c = lane + 32 * i, row = c / 12, chunk = c % 12;
      const uint4 v = lds128(ost + row * 192 + chunk * 16);
      *(uint4*)(o2 + (size_t)(m * 128 + trow + row) * 768 + u * 96 + chunk * 8) = v;
    }
  }
  __threadfence();
  bar_sync(1, 256);
  if (threadIdx.x == 0) { atomicAdd(cntO, 1u); mbar_arrive(barGo); }
  TL2((tl >= 12 ? 128 : 0) + 32 + 4);
  float acc[40];
  uint4 xr[5];
#pragma unroll
  for (int i = 0; i < 5; i++) {
    const int c = lane + 32 * i;
    xr[i] = *(const uint4*)(xin + (size_t)(m * 128 + trow + c / 10) * cfg::DM + u * 80 + (c % 10) * 8);
  }
  mbar_wait(barW, 0);
  {
    Pipe p{0, 0};
    uint32_t prev = 0;
    for (int kb = 0; kb < 12; kb++) {
      mbar_wait(full2 + 8 * p.stage, p.phase);
      wgmma_fence();
#pragma unroll
      for (int kk = 0; kk < 4; kk++)
        wgmma_n80<0, 0>(acc, desc_kmajor(sb + p.stage * 16384 + wg * 8192 + kk * 32), desc_kmajor(sb + OFF_WOT + kb * 10240 + kk * 32), (kb | kk) != 0);
      wgmma_commit();
      if (kb > 0) { wgmma_wait<1>(); if ((threadIdx.x & 127) == 0) mbar_arrive(empty2 + 8 * prev); }
      prev = p.stage;
      pipe_adv<ANS>(p);
    }
    wgmma_wait<0>();
  }
  TL2((tl >= 12 ? 128 : 0) + 32 + 5);
  {
    const uint32_t ost = sb + OFF_OST + warp * 3072;
#pragma unroll
    for (int v = 0; v < 10; v += 2)
      stsm_x4(ost + srow * 176 + (v + (lane >> 4)) * 16, pack_bf16(acc[4 * v], acc[4 * v + 1]), pack_bf16(acc[4 * v + 2], acc[4 * v + 3]),
              pack_bf16(acc[4 * v + 4], acc[4 * v + 5]), pack_bf16(acc[4 * v + 6], acc[4 * v + 7]));
    __syncwarp();
#pragma unroll
    for (int i = 0; i < 5; i++) {
      const int c = lane + 32 * i, row = c / 10, chunk = c % 10;
      const uint4 y = lds128(ost + row * 176 + chunk * 16);
      const size_t off = (size_t)(m * 128 + trow + row) * cfg::DM + u * 80 + chunk * 8;
      const uint4 x = xr[i];
      *(uint4*)(xout + off) = make_uint4(pack_bf16(bf_lo(x.x) + bf_lo(y.x), bf_hi(x.x) + bf_hi(y.x)), pack_bf16(bf_lo(x.y) + bf_lo(y.y), bf_hi(x.y) + bf_hi(y.y)),
                                         pack_bf16(bf_lo(x.z) + bf_lo(y.z), bf_hi(x.z) + bf_hi(y.z)), pack_bf16(bf_lo(x.w) + bf_lo(y.w), bf_hi(x.w) + bf_hi(y.w)));
    }
  }
  TL_END(tl);
}
__device__ __align__(32768) unsigned char g_arena[AR_SIZE];
__device__ __align__(1024) uint2 g_xh[2048 * 160];
__device__ __align__(1024) unsigned char g_k[64 * 96 * 5120], g_v[64 * 96 * 5120];
__device__ __align__(1024) bf16 g_o[2048 * 6144];
__device__ __align__(1024) uint4 g_qs[4 * 32 * 12 * 256];
__device__ __align__(1024) bf16 g_xn[2048 * 640], g_xn2[2048 * 640], g_xa[2048 * 640], g_xb[2048 * 640];
__device__ __align__(1024) float g_part[24 * 2048 * 640];
__device__ __align__(1024) bf16 g_wb[2304 * 640], g_wot[640 * 768], g_pq[2048 * 768];
__device__ __align__(1024) float g_kvacc[32 * 48 * 24 + 64];

typedef CUresult (*EncodeFn)(CUtensorMap*, CUtensorMapDataType, cuuint32_t, void*, const cuuint64_t*, const cuuint64_t*, const cuuint32_t*,
                             const cuuint32_t*, CUtensorMapInterleave, CUtensorMapSwizzle, CUtensorMapL2promotion, CUtensorMapFloatOOBfill);
static EncodeFn g_encode = nullptr;
static CUtensorMap make_map(const void* p, uint64_t cols, uint64_t rows, uint32_t bc, uint32_t br, bool swz = true) {
  CUtensorMap m;
  cuuint64_t dims[2] = {cols, rows}, strides[1] = {cols * 2};
  cuuint32_t box[2] = {bc, br}, es[2] = {1, 1};
  g_encode(&m, CU_TENSOR_MAP_DATA_TYPE_BFLOAT16, 2, const_cast<void*>(p), dims, strides, box, es, CU_TENSOR_MAP_INTERLEAVE_NONE,
           swz ? CU_TENSOR_MAP_SWIZZLE_128B : CU_TENSOR_MAP_SWIZZLE_NONE, CU_TENSOR_MAP_L2_PROMOTION_L2_256B, CU_TENSOR_MAP_FLOAT_OOB_FILL_NONE);
  return m;
}
static CUtensorMap make_map3(const void* p, uint64_t cols, uint64_t rows, uint32_t nb) {
  CUtensorMap m;
  cuuint64_t dims[3] = {64, rows, cols / 64}, strides[2] = {cols * 2, 128};
  cuuint32_t box[3] = {64, 64, nb}, es[3] = {1, 1, 1};
  g_encode(&m, CU_TENSOR_MAP_DATA_TYPE_BFLOAT16, 3, const_cast<void*>(p), dims, strides, box, es, CU_TENSOR_MAP_INTERLEAVE_NONE,
           CU_TENSOR_MAP_SWIZZLE_128B, CU_TENSOR_MAP_L2_PROMOTION_L2_256B, CU_TENSOR_MAP_FLOAT_OOB_FILL_NONE);
  return m;
}
template <class T> static T* sym(const T& s) { void* p = nullptr; cudaGetSymbolAddress(&p, s); return (T*)p; }

struct Ptrs {
  unsigned char *arena, *k, *v; bf16 *o, *xn, *xa, *xb, *wb, *wot, *pq; float *part, *kvacc; uint2* xh; uint4* qs; bf16* xn2;
};

#define NQPRE 3
#define NQLATE 1
#define QFIRST 0
#define KSPLIT {2, 2, 2, 2, 2, 2, 2, 2, 2, 2, 2, 3, 4, 6, 12, 24}
#define NWIDE 14
#define LLAG 4
static tr::Sched make_sched(int layer) {
  using namespace tr;
  Sched s = {};
  const int ks[16] = KSPLIT;
  int g = 0, n = 0;
  auto add = [&](int type, int b, int cnt) { s.start[g] = (uint16_t)n; s.type[g] = (uint8_t)type; s.blk[g] = (uint8_t)b; g++; n += cnt; };
  for (int b = 0; b < 16; b++) { s.ks[b] = (uint8_t)ks[b]; s.wide[b] = b < NWIDE; s.lrows[b] = b < 11 ? 4 : 1; }
  auto qa = [&](int b) { add(b >= 16 - NQPRE ? T_A : T_QA, b, 32); };
  auto op = [&](int b) { add(s.wide[b] ? T_OB : T_OS, b, ks[b] * (s.wide[b] ? 2 : 5)); };
  auto ln = [&](int b) { add(T_L, b, 16 / s.lrows[b]); };
  for (int b = 16 - NQPRE; b < 16 - NQLATE; b++) add(T_Q, b, 32);
  qa(0);
  for (int b = 16 - NQLATE; b < 16; b++) add(T_Q, b, 32);
  int nl = 0;
  for (int b = 0; b < 16; b++) {
    if (b + 1 < 16 && b + 1 >= QFIRST) qa(b + 1);
    op(b);
    if (b + 1 < 16 && b + 1 < QFIRST) qa(b + 1);
    if (b >= LLAG && b < 14) ln(nl++);
  }
  while (nl < 16) ln(nl++);
  add(T_END, 0, 0);
  s.start[g] = 0xffff;
  return s;
}
#define TRAIL_GRID 132
#define PDL_LN 0
#define PDL_CH 1
#define PDL_B 0
#define PF_A 1
#define PF_B 1
extern "C" void kernel_launch(void* const* d_in, const int* in_sizes, int n_in, void* d_out, int out_size) {
  const bf16* x = (const bf16*)d_in[0];
  const bf16* mem0 = (const bf16*)d_in[1];
  const bf16 *Wq = (const bf16*)d_in[2], *Wk = (const bf16*)d_in[3], *Wv = (const bf16*)d_in[4], *Wo = (const bf16*)d_in[5];
  const bf16 *wqkv = (const bf16*)d_in[8], *wphi = (const bf16*)d_in[9], *wo = (const bf16*)d_in[10];
  bf16* out = (bf16*)d_out;
  static Ptrs P; static bool init = false;
  if (!init) {
    void* fn = nullptr; cudaDriverEntryPointQueryResult qr;
    cudaGetDriverEntryPoint("cuTensorMapEncodeTiled", &fn, cudaEnableDefault, &qr);
    g_encode = (EncodeFn)fn;
    void* p;
    cudaGetSymbolAddress(&p, g_arena); P.arena = (unsigned char*)p;
    cudaGetSymbolAddress(&p, g_k); P.k = (unsigned char*)p;   cudaGetSymbolAddress(&p, g_v); P.v = (unsigned char*)p;
    cudaGetSymbolAddress(&p, g_o); P.o = (bf16*)p;
    cudaGetSymbolAddress(&p, g_xn); P.xn = (bf16*)p;
    cudaGetSymbolAddress(&p, g_xa); P.xa = (bf16*)p;   cudaGetSymbolAddress(&p, g_xb); P.xb = (bf16*)p;
    cudaGetSymbolAddress(&p, g_wb); P.wb = (bf16*)p;   cudaGetSymbolAddress(&p, g_wot); P.wot = (bf16*)p;
    cudaGetSymbolAddress(&p, g_pq); P.pq = (bf16*)p;   cudaGetSymbolAddress(&p, g_part); P.part = (float*)p;
    cudaGetSymbolAddress(&p, g_kvacc); P.kvacc = (float*)p;
    cudaGetSymbolAddress(&p, g_xh); P.xh = (uint2*)p;
    cudaGetSymbolAddress(&p, g_qs); P.qs = (uint4*)p;
    cudaGetSymbolAddress(&p, g_xn2); P.xn2 = (bf16*)p;
    cudaFuncSetAttribute(chain_kernel, cudaFuncAttributeMaxDynamicSharedMemorySize, ch::SMEM);
    cudaFuncSetAttribute(trail_kernel, cudaFuncAttributeMaxDynamicSharedMemorySize, tr::SMEM);
    cudaFuncSetAttribute(blayer_kernel, cudaFuncAttributeMaxDynamicSharedMemorySize, bf::SMEM);
    init = true;
  }
  const CUtensorMap tmXn = make_map(P.xn, 640, 2048, 64, 128), tmXn2 = make_map(P.xn2, 640, 2048, 64, 128);
  const CUtensorMap tmWq = make_map3(Wq, 6144, 640, 3);
  const CUtensorMap tmCq = make_map(Wq, 6144, 640, 64, 160), tmCk = make_map(Wk, 6144, 640, 64, 160), tmCv = make_map(Wv, 6144, 640, 64, 160), tmCo = make_map(Wo, 640, 6144, 224, 64, false);
  const CUtensorMap tmWo5 = make_map3(Wo, 640, 6144, 5), tmWo2 = make_map3(Wo, 640, 6144, 2);
  const CUtensorMap tmWb = make_map(P.wb, 640, 2304, 64, 144), tmO2 = make_map(P.pq, 768, 2048, 64, 128), tmWot = make_map(P.wot, 768, 640, 64, 80);

  ChainArgs ca;
  ca.xh = P.xh; ca.mem0 = mem0; ca.kg = P.k; ca.vg = P.v;
  ca.arena = P.arena; ca.dbg = nullptr; ca.tl = 0;
  uint4* zar = (uint4*)P.arena; const int nzar = AR_SIZE / 16;
  uint4* zkv = (uint4*)P.kvacc; const int nzkv = (32 * 48 * 24 + 64) / 4;

  const PrepArgs pa{wqkv, wphi, wo, P.wb, P.wot};
  const bf16* xcur = x;
  cudaLaunchAttribute at[1];
  at[0].id = cudaLaunchAttributeProgrammaticStreamSerialization; at[0].val.programmaticStreamSerializationAllowed = 1;
  auto cfgof = [&](int grid, int block, int smem, bool pdl) {
    cudaLaunchConfig_t lc = {};
    lc.gridDim = dim3(grid); lc.blockDim = dim3(block); lc.dynamicSmemBytes = smem; lc.stream = cudaStreamPerThread;
    lc.attrs = at; lc.numAttrs = pdl ? 1 : 0;
    return lc;
  };
  for (int layer = 0; layer < 2; layer++) {
    const int tl = layer * 12;
    cudaLaunchConfig_t lc = cfgof(256, 256, 0, layer > 0 && PDL_LN);
    cudaLaunchKernelEx(&lc, ln_kernel, xcur, P.xn, P.xh, zar, nzar, zkv, nzkv, Wk, Wv, layer == 0 ? PF_A : 0, tl + 0);
    ca.tl = tl + 2;
    lc = cfgof(96, 384, ch::SMEM, PDL_CH);
    cudaLaunchKernelEx(&lc, chain_kernel, ca, tmCq, tmCk, tmCv, tmCo);
    lc = cfgof(TRAIL_GRID, 384, tr::SMEM, true);
    const tr::Args ta{P.k, P.v, (unsigned char*)P.o, P.qs, P.part, xcur, P.xa, P.xn2, P.arena, layer == 0 ? 1 : 0, tl + 4};
    cudaLaunchKernelEx(&lc, trail_kernel, tmXn, tmWq, tmWo5, tmWo2, make_sched(layer), ta, pa);
    lc = cfgof(128, 384, bf::SMEM, PDL_B);
    cudaLaunchKernelEx(&lc, blayer_kernel, tmXn2, tmWb, tmO2, tmWot, P.kvacc, (unsigned*)(P.kvacc + 32 * 48 * 24), P.pq, (const bf16*)P.xa, layer == 0 ? P.xb : out,
                       layer == 0 && PF_B ? Wk : nullptr, Wv, PF_B > 1 ? Wq : nullptr, Wo, tl + 7);
    xcur = P.xb;
  }
}
```

```cpp
#include <cuda_runtime.h>
#include <cuda.h>
#include <cuda_bf16.h>
#include <stdint.h>
#include <type_traits>

typedef __nv_bfloat16 bf16;

namespace cfg {
constexpr int S = 2048, DM = 640, H = 32, DH = 192, NSEG = 64, SEG = 32, NM = 8;
constexpr int HD = H * DH;
}

__device__ __forceinline__ uint32_t smem_u32(const void* p) { return (uint32_t)__cvta_generic_to_shared(p); }
__device__ __forceinline__ uint32_t mapa_u32(uint32_t a, uint32_t r) {
  uint32_t o; asm("mapa.shared::cluster.u32 %0, %1, %2;" : "=r"(o) : "r"(a), "r"(r)); return o;
}
__device__ __forceinline__ void mbar_init(uint32_t b, uint32_t c) {
  asm volatile("mbarrier.init.shared::cta.b64 [%0], %1;" :: "r"(b), "r"(c) : "memory");
}
__device__ __forceinline__ void mbar_expect_tx(uint32_t b, uint32_t bytes) {
  asm volatile("mbarrier.arrive.expect_tx.shared::cta.b64 _, [%0], %1;" :: "r"(b), "r"(bytes) : "memory");
}
__device__ __forceinline__ void mbar_arrive(uint32_t b) {
  asm volatile("mbarrier.arrive.shared::cta.b64 _, [%0];" :: "r"(b) : "memory");
}
__device__ __forceinline__ void mbar_arrive_if(bool c, uint32_t b) {
  asm volatile("{\n.reg .pred p;\nsetp.ne.u32 p, %1, 0;\n@p mbarrier.arrive.shared::cta.b64 _, [%0];\n}" :: "r"(b), "r"((uint32_t)c) : "memory");
}
__device__ __forceinline__ bool mbar_try(uint32_t b, uint32_t ph) {
  uint32_t p;
  asm volatile("{.reg .pred p; mbarrier.try_wait.parity.shared::cta.b64 p, [%1], %2; selp.u32 %0, 1, 0, p;}"
               : "=r"(p) : "r"(b), "r"(ph) : "memory");
  return p;
}
__device__ __forceinline__ bool mbar_try_cluster(uint32_t b, uint32_t ph) {
  uint32_t p;
  asm volatile("{.reg .pred p; mbarrier.try_wait.parity.acquire.cluster.shared::cta.b64 p, [%1], %2; selp.u32 %0, 1, 0, p;}"
               : "=r"(p) : "r"(b), "r"(ph) : "memory");
  return p;
}
#define SPIN_LIMIT (1 << 22)
__device__ __forceinline__ void mbar_wait(uint32_t b, uint32_t ph) {
  asm volatile("{\n.reg .pred p, q;\n.reg .u32 c;\nmov.u32 c, 0;\n"
               "W_%=:\nmbarrier.try_wait.parity.shared::cta.b64 p, [%0], %1;\n@p bra.uni D_%=;\n"
               "add.u32 c, c, 1;\nsetp.lt.u32 q, c, %2;\n@q bra.uni W_%=;\nD_%=:\n}"
               :: "r"(b), "r"(ph), "n"(SPIN_LIMIT) : "memory");
}
__device__ __forceinline__ void mbar_spin(uint32_t b, uint32_t ph) {
  asm volatile("{\n.reg .pred p, q;\n.reg .u32 c;\nmov.u32 c, 0;\n"
               "W_%=:\nmbarrier.test_wait.parity.shared::cta.b64 p, [%0], %1;\n@p bra D_%=;\n"
               "add.u32 c, c, 1;\nsetp.lt.u32 q, c, %2;\n@q bra W_%=;\nD_%=:\n}"
               :: "r"(b), "r"(ph), "n"(SPIN_LIMIT) : "memory");
}
#define PIN(x) asm volatile("" : "+r"(x))
__device__ __forceinline__ void mbar_wait_cluster(uint32_t b, uint32_t ph) {
  int s = 0;
  while (!mbar_try_cluster(b, ph)) { if (++s > SPIN_LIMIT) break; }
}
__device__ __forceinline__ void st_async_v2(uint32_t a, uint32_t x, uint32_t y, uint32_t mb) {
  asm volatile("st.async.weak.shared::cluster.mbarrier::complete_tx::bytes.v2.b32 [%0], {%1,%2}, [%3];"
               :: "r"(a), "r"(x), "r"(y), "r"(mb) : "memory");
}
__device__ __forceinline__ void st_async_v4(uint32_t a, uint32_t x, uint32_t y, uint32_t z, uint32_t w, uint32_t mb) {
  asm volatile("st.async.weak.shared::cluster.mbarrier::complete_tx::bytes.v4.b32 [%0], {%1,%2,%3,%4}, [%5];"
               :: "r"(a), "r"(x), "r"(y), "r"(z), "r"(w), "r"(mb) : "memory");
}
__device__ __forceinline__ void bulk_g2s(uint32_t dst, const void* src, uint32_t bytes, uint32_t mb) {
  asm volatile("cp.async.bulk.shared::cluster.global.mbarrier::complete_tx::bytes [%0], [%1], %2, [%3];"
               :: "r"(dst), "l"(src), "r"(bytes), "r"(mb) : "memory");
}
__device__ __forceinline__ void cp_async16(uint32_t dst, const void* src) {
  asm volatile("cp.async.cg.shared.global [%0], [%1], 16;" :: "r"(dst), "l"(src) : "memory");
}
__device__ __forceinline__ void cp_async_wait_all() { asm volatile("cp.async.wait_all;" ::: "memory"); }
__device__ __forceinline__ void fence_proxy_async() { asm volatile("fence.proxy.async.shared::cta;" ::: "memory"); }
__device__ __forceinline__ void bar_sync(int id, int n) { asm volatile("bar.sync %0, %1;" :: "r"(id), "r"(n) : "memory"); }
__device__ __forceinline__ void bar_arrive(int id, int n) { asm volatile("bar.arrive %0, %1;" :: "r"(id), "r"(n) : "memory"); }
__device__ __forceinline__ void cluster_sync_all() {
  asm volatile("barrier.cluster.arrive.release.aligned; barrier.cluster.wait.acquire.aligned;" ::: "memory");
}
__device__ __forceinline__ void ldsm_x4(uint32_t (&r)[4], uint32_t a) {
  asm volatile("ldmatrix.sync.aligned.m8n8.x4.shared.b16 {%0,%1,%2,%3}, [%4];"
               : "=r"(r[0]), "=r"(r[1]), "=r"(r[2]), "=r"(r[3]) : "r"(a) : "memory");
}
__device__ __forceinline__ void ldsm_x4_t(uint32_t (&r)[4], uint32_t a) {
  asm volatile("ldmatrix.sync.aligned.m8n8.x4.trans.shared.b16 {%0,%1,%2,%3}, [%4];"
               : "=r"(r[0]), "=r"(r[1]), "=r"(r[2]), "=r"(r[3]) : "r"(a) : "memory");
}
template <int IMM> __device__ __forceinline__ void ldsm_x4_i(uint32_t (&r)[4], uint32_t a) {
  asm volatile("ldmatrix.sync.aligned.m8n8.x4.shared.b16 {%0,%1,%2,%3}, [%4+%5];"
               : "=r"(r[0]), "=r"(r[1]), "=r"(r[2]), "=r"(r[3]) : "r"(a), "n"(IMM) : "memory");
}
template <int IMM> __device__ __forceinline__ void ldsm_x4_t_i(uint32_t (&r)[4], uint32_t a) {
  asm volatile("ldmatrix.sync.aligned.m8n8.x4.trans.shared.b16 {%0,%1,%2,%3}, [%4+%5];"
               : "=r"(r[0]), "=r"(r[1]), "=r"(r[2]), "=r"(r[3]) : "r"(a), "n"(IMM) : "memory");
}
template <int IMM> __device__ __forceinline__ uint4 lds128_i(uint32_t a) {
  uint4 v; asm volatile("ld.shared.v4.u32 {%0,%1,%2,%3}, [%4+%5];" : "=r"(v.x), "=r"(v.y), "=r"(v.z), "=r"(v.w) : "r"(a), "n"(IMM) : "memory"); return v;
}
template <int IMM> __device__ __forceinline__ uint2 lds64_i(uint32_t a) {
  uint2 v; asm volatile("ld.shared.v2.u32 {%0,%1}, [%2+%3];" : "=r"(v.x), "=r"(v.y) : "r"(a), "n"(IMM) : "memory"); return v;
}
template <int IMM> __device__ __forceinline__ void sts128_i(uint32_t a, uint32_t x, uint32_t y, uint32_t z, uint32_t w) {
  asm volatile("st.shared.v4.u32 [%0+%5], {%1,%2,%3,%4};" :: "r"(a), "r"(x), "r"(y), "r"(z), "r"(w), "n"(IMM) : "memory");
}
template <int IMM> __device__ __forceinline__ void sts64_i(uint32_t a, uint32_t x, uint32_t y) {
  asm volatile("st.shared.v2.u32 [%0+%3], {%1,%2};" :: "r"(a), "r"(x), "r"(y), "n"(IMM) : "memory");
}
template <int IMM> __device__ __forceinline__ void st_async_v2_i(uint32_t a, uint32_t x, uint32_t y, uint32_t mb) {
  asm volatile("st.async.weak.shared::cluster.mbarrier::complete_tx::bytes.v2.b32 [%0+%4], {%1,%2}, [%3];"
               :: "r"(a), "r"(x), "r"(y), "r"(mb), "n"(IMM) : "memory");
}
template <int IMM> __device__ __forceinline__ uint4 ld_relaxed_v4_i(const void* p) {
  uint4 v; asm volatile("ld.relaxed.gpu.global.v4.u32 {%0,%1,%2,%3}, [%4+%5];" : "=r"(v.x), "=r"(v.y), "=r"(v.z), "=r"(v.w) : "l"(p), "n"(IMM) : "memory"); return v;
}
template <int I, int N, class F> __device__ __forceinline__ void static_for(F&& f) {
  if constexpr (I < N) { f(std::integral_constant<int, I>{}); static_for<I + 1, N>(f); }
}
__device__ __forceinline__ uint32_t movm_t(uint32_t a) {
  uint32_t d; asm volatile("movmatrix.sync.aligned.m8n8.trans.b16 %0, %1;" : "=r"(d) : "r"(a)); return d;
}
__device__ __forceinline__ void mma16816(float (&d)[4], uint32_t a0, uint32_t a1, uint32_t a2, uint32_t a3, uint32_t b0, uint32_t b1) {
  asm volatile("mma.sync.aligned.m16n8k16.row.col.f32.bf16.bf16.f32 {%0,%1,%2,%3}, {%4,%5,%6,%7}, {%8,%9}, {%0,%1,%2,%3};"
               : "+f"(d[0]), "+f"(d[1]), "+f"(d[2]), "+f"(d[3]) : "r"(a0), "r"(a1), "r"(a2), "r"(a3), "r"(b0), "r"(b1));
}
__device__ __forceinline__ uint32_t pack_bf16(float lo, float hi) {
  uint32_t d; asm("cvt.rn.bf16x2.f32 %0, %1, %2;" : "=r"(d) : "f"(hi), "f"(lo)); return d;
}
__device__ __forceinline__ float bf_lo(uint32_t w) { return __uint_as_float(w << 16); }
__device__ __forceinline__ float bf_hi(uint32_t w) { return __uint_as_float(w & 0xffff0000u); }
__device__ __forceinline__ uint4 lds128(uint32_t a) {
  uint4 v; asm volatile("ld.shared.v4.u32 {%0,%1,%2,%3}, [%4];" : "=r"(v.x), "=r"(v.y), "=r"(v.z), "=r"(v.w) : "r"(a) : "memory"); return v;
}
__device__ __forceinline__ uint2 lds64(uint32_t a) {
  uint2 v; asm volatile("ld.shared.v2.u32 {%0,%1}, [%2];" : "=r"(v.x), "=r"(v.y) : "r"(a) : "memory"); return v;
}
__device__ __forceinline__ void sts128(uint32_t a, uint32_t x, uint32_t y, uint32_t z, uint32_t w) {
  asm volatile("st.shared.v4.u32 [%0], {%1,%2,%3,%4};" :: "r"(a), "r"(x), "r"(y), "r"(z), "r"(w) : "memory");
}
__device__ __forceinline__ void sts64(uint32_t a, uint32_t x, uint32_t y) {
  asm volatile("st.shared.v2.u32 [%0], {%1,%2};" :: "r"(a), "r"(x), "r"(y) : "memory");
}
__device__ __forceinline__ uint4 ld_relaxed_v4(const void* p) {
  uint4 v; asm volatile("ld.relaxed.gpu.global.v4.u32 {%0,%1,%2,%3}, [%4];" : "=r"(v.x), "=r"(v.y), "=r"(v.z), "=r"(v.w) : "l"(p) : "memory"); return v;
}
__device__ __forceinline__ uint32_t ld_relaxed_u32(const void* p) {
  uint32_t v; asm volatile("ld.relaxed.gpu.global.u32 %0, [%1];" : "=r"(v) : "l"(p) : "memory"); return v;
}
__device__ __forceinline__ void st_relaxed_v2(void* p, uint32_t a, uint32_t b) {
  asm volatile("st.relaxed.gpu.global.v2.u32 [%0], {%1,%2};" :: "l"(p), "r"(a), "r"(b) : "memory");
}
__device__ __forceinline__ void st_relaxed_u32(void* p, uint32_t v) {
  asm volatile("st.relaxed.gpu.global.u32 [%0], %1;" :: "l"(p), "r"(v) : "memory");
}
__device__ __forceinline__ uint32_t clk32() { uint32_t c; asm volatile("mov.u32 %0, %%clock;" : "=r"(c) :: "memory"); return c; }
__device__ __forceinline__ uint32_t clkdep(uint32_t v) {
  uint32_t c; asm volatile("{.reg .pred p; setp.eq.u32 p, %1, 0xdeadbeef; @p trap; mov.u32 %0, %%clock;}" : "=r"(c) : "r"(v) : "memory"); return c;
}
__device__ __forceinline__ void wgmma_fence() { asm volatile("wgmma.fence.sync.aligned;" ::: "memory"); }
__device__ __forceinline__ void wgmma_commit() { asm volatile("wgmma.commit_group.sync.aligned;" ::: "memory"); }
template <int N> __device__ __forceinline__ void wgmma_wait() { asm volatile("wgmma.wait_group.sync.aligned %0;" :: "n"(N) : "memory"); }
__device__ __forceinline__ void wgmma_n8_ss_ta(float (&d)[4], uint64_t da, uint64_t db, int acc) {
  asm volatile("{\n.reg .pred p;\nsetp.ne.b32 p, %6, 0;\n"
               "wgmma.mma_async.sync.aligned.m64n8k16.f32.bf16.bf16 {%0,%1,%2,%3}, %4, %5, p, 1, 1, 1, 0;\n}\n"
               : "+f"(d[0]), "+f"(d[1]), "+f"(d[2]), "+f"(d[3]) : "l"(da), "l"(db), "r"(acc));
}
__device__ __forceinline__ uint64_t make_desc(uint32_t saddr, uint32_t lbo_bytes, uint32_t sbo_bytes, uint32_t swz) {
  return (uint64_t)((saddr & 0x3FFFF) >> 4) | ((uint64_t)(lbo_bytes >> 4) << 16) | ((uint64_t)(sbo_bytes >> 4) << 32) | ((uint64_t)swz << 62);
}

__device__ __forceinline__ bool elect_one() {
  uint32_t p; asm volatile("{\n.reg .pred p;\nelect.sync _|p, 0xffffffff;\nselp.u32 %0, 1, 0, p;\n}" : "=r"(p)); return p;
}
__device__ __forceinline__ void tma_load_3d(uint32_t dst, const CUtensorMap* tm, int c0, int c1, int c2, uint32_t mb) {
  asm volatile("cp.async.bulk.tensor.3d.shared::cluster.global.mbarrier::complete_tx::bytes [%0], [%1, {%3, %4, %5}], [%2];"
               :: "r"(dst), "l"(tm), "r"(mb), "r"(c0), "r"(c1), "r"(c2) : "memory");
}
__device__ __forceinline__ void tma_load_2d(uint32_t dst, const CUtensorMap* tm, int c0, int c1, uint32_t mb) {
  asm volatile("cp.async.bulk.tensor.2d.shared::cluster.global.mbarrier::complete_tx::bytes [%0], [%1, {%3, %4}], [%2];"
               :: "r"(dst), "l"(tm), "r"(mb), "r"(c0), "r"(c1) : "memory");
}
__device__ __forceinline__ void bulk_s2g(void* dst, uint32_t src, uint32_t bytes) {
  asm volatile("cp.async.bulk.global.shared::cta.bulk_group [%0], [%1], %2;" :: "l"(dst), "r"(src), "r"(bytes) : "memory");
}
__device__ __forceinline__ uint64_t policy_evict_first() {
  uint64_t p; asm volatile("createpolicy.fractional.L2::evict_first.b64 %0, 1.0;" : "=l"(p)); return p;
}
__device__ __forceinline__ void bulk_s2g_hint(void* dst, uint32_t src, uint32_t bytes, uint64_t pol) {
  asm volatile("cp.async.bulk.global.shared::cta.bulk_group.L2::cache_hint [%0], [%1], %2, %3;" :: "l"(dst), "r"(src), "r"(bytes), "l"(pol) : "memory");
}
__device__ __forceinline__ void bulk_commit() { asm volatile("cp.async.bulk.commit_group;" ::: "memory"); }
template <int N> __device__ __forceinline__ void bulk_wait_read() { asm volatile("cp.async.bulk.wait_group.read %0;" :: "n"(N) : "memory"); }
template <int N> __device__ __forceinline__ void bulk_wait() { asm volatile("cp.async.bulk.wait_group %0;" :: "n"(N) : "memory"); }
__device__ __forceinline__ void stsm_x4(uint32_t a, uint32_t r0, uint32_t r1, uint32_t r2, uint32_t r3) {
  asm volatile("stmatrix.sync.aligned.m8n8.x4.shared.b16 [%0], {%1,%2,%3,%4};" :: "r"(a), "r"(r0), "r"(r1), "r"(r2), "r"(r3) : "memory");
}
__device__ __forceinline__ void stsm_x2(uint32_t a, uint32_t r0, uint32_t r1) {
  asm volatile("stmatrix.sync.aligned.m8n8.x2.shared.b16 [%0], {%1,%2};" :: "r"(a), "r"(r0), "r"(r1) : "memory");
}
__device__ __forceinline__ void ldsm_x2(uint32_t (&r)[2], uint32_t a) {
  asm volatile("ldmatrix.sync.aligned.m8n8.x2.shared.b16 {%0,%1}, [%2];" : "=r"(r[0]), "=r"(r[1]) : "r"(a) : "memory");
}
__device__ __forceinline__ void ldsm_x2_t(uint32_t (&r)[2], uint32_t a) {
  asm volatile("ldmatrix.sync.aligned.m8n8.x2.trans.shared.b16 {%0,%1}, [%2];" : "=r"(r[0]), "=r"(r[1]) : "r"(a) : "memory");
}
__device__ __forceinline__ float bf16r(float x) { return __uint_as_float(pack_bf16(0.f, x) & 0xffff0000u); }
__device__ __forceinline__ void bf16r2(float& a, float& b) { const uint32_t w = pack_bf16(a, b); a = bf_lo(w); b = bf_hi(w); }
__device__ __forceinline__ float rcpf(float x) { float r; asm("rcp.approx.ftz.f32 %0, %1;" : "=f"(r) : "f"(x)); return r; }
__device__ __forceinline__ float ex2f(float x) { float e; asm("ex2.approx.ftz.f32 %0, %1;" : "=f"(e) : "f"(x)); return e; }
__device__ __forceinline__ void prefetch_tmap(const CUtensorMap* tm) { asm volatile("prefetch.tensormap [%0];" :: "l"(tm) : "memory"); }

#define TL_ACC(idx, t0)
#define TL_NOW() 0ull
#define TL2(idx)
#define TL_BEGIN(id)
#define TL_END(id)
template <int TA, int TB> __device__ __forceinline__ void wgmma_n192(float (&d)[96], uint64_t da, uint64_t db, int acc) {
  asm volatile("{\n.reg .pred p;\nsetp.ne.b32 p, %98, 0;\n"
    "wgmma.mma_async.sync.aligned.m64n192k16.f32.bf16.bf16 {%0, %1, %2, %3, %4, %5, %6, %7, %8, %9, %10, %11, %12, %13, %14, %15, %16, %17, %18, %19, %20, %21, %22, %23, %24, %25, %26, %27, %28, %29, %30, %31, %32, %33, %34, %35, %36, %37, %38, %39, %40, %41, %42, %43, %44, %45, %46, %47, %48, %49, %50, %51, %52, %53, %54, %55, %56, %57, %58, %59, %60, %61, %62, %63, %64, %65, %66, %67, %68, %69, %70, %71, %72, %73, %74, %75, %76, %77, %78, %79, %80, %81, %82, %83, %84, %85, %86, %87, %88, %89, %90, %91, %92, %93, %94, %95}, %96, %97, p, 1, 1, %99, %100;\n}\n"
    : "+f"(d[0]), "+f"(d[1]), "+f"(d[2]), "+f"(d[3]), "+f"(d[4]), "+f"(d[5]), "+f"(d[6]), "+f"(d[7]), "+f"(d[8]), "+f"(d[9]), "+f"(d[10]), "+f"(d[11]), "+f"(d[12]), "+f"(d[13]), "+f"(d[14]), "+f"(d[15]), "+f"(d[16]), "+f"(d[17]), "+f"(d[18]), "+f"(d[19]), "+f"(d[20]), "+f"(d[21]), "+f"(d[22]), "+f"(d[23]), "+f"(d[24]), "+f"(d[25]), "+f"(d[26]), "+f"(d[27]), "+f"(d[28]), "+f"(d[29]), "+f"(d[30]), "+f"(d[31]), "+f"(d[32]), "+f"(d[33]), "+f"(d[34]), "+f"(d[35]), "+f"(d[36]), "+f"(d[37]), "+f"(d[38]), "+f"(d[39]), "+f"(d[40]), "+f"(d[41]), "+f"(d[42]), "+f"(d[43]), "+f"(d[44]), "+f"(d[45]), "+f"(d[46]), "+f"(d[47]), "+f"(d[48]), "+f"(d[49]), "+f"(d[50]), "+f"(d[51]), "+f"(d[52]), "+f"(d[53]), "+f"(d[54]), "+f"(d[55]), "+f"(d[56]), "+f"(d[57]), "+f"(d[58]), "+f"(d[59]), "+f"(d[60]), "+f"(d[61]), "+f"(d[62]), "+f"(d[63]), "+f"(d[64]), "+f"(d[65]), "+f"(d[66]), "+f"(d[67]), "+f"(d[68]), "+f"(d[69]), "+f"(d[70]), "+f"(d[71]), "+f"(d[72]), "+f"(d[73]), "+f"(d[74]), "+f"(d[75]), "+f"(d[76]), "+f"(d[77]), "+f"(d[78]), "+f"(d[79]), "+f"(d[80]), "+f"(d[81]), "+f"(d[82]), "+f"(d[83]), "+f"(d[84]), "+f"(d[85]), "+f"(d[86]), "+f"(d[87]), "+f"(d[88]), "+f"(d[89]), "+f"(d[90]), "+f"(d[91]), "+f"(d[92]), "+f"(d[93]), "+f"(d[94]), "+f"(d[95])
    : "l"(da), "l"(db), "r"(acc), "n"(TA), "n"(TB));
}

template <int TA, int TB> __device__ __forceinline__ void wgmma_n256(float (&d)[128], uint64_t da, uint64_t db, int acc) {
  asm volatile("{\n.reg .pred p;\nsetp.ne.b32 p, %130, 0;\n"
    "wgmma.mma_async.sync.aligned.m64n256k16.f32.bf16.bf16 {%0, %1, %2, %3, %4, %5, %6, %7, %8, %9, %10, %11, %12, %13, %14, %15, %16, %17, %18, %19, %20, %21, %22, %23, %24, %25, %26, %27, %28, %29, %30, %31, %32, %33, %34, %35, %36, %37, %38, %39, %40, %41, %42, %43, %44, %45, %46, %47, %48, %49, %50, %51, %52, %53, %54, %55, %56, %57, %58, %59, %60, %61, %62, %63, %64, %65, %66, %67, %68, %69, %70, %71, %72, %73, %74, %75, %76, %77, %78, %79, %80, %81, %82, %83, %84, %85, %86, %87, %88, %89, %90, %91, %92, %93, %94, %95, %96, %97, %98, %99, %100, %101, %102, %103, %104, %105, %106, %107, %108, %109, %110, %111, %112, %113, %114, %115, %116, %117, %118, %119, %120, %121, %122, %123, %124, %125, %126, %127}, %128, %129, p, 1, 1, %131, %132;\n}\n"
    : "+f"(d[0]), "+f"(d[1]), "+f"(d[2]), "+f"(d[3]), "+f"(d[4]), "+f"(d[5]), "+f"(d[6]), "+f"(d[7]), "+f"(d[8]), "+f"(d[9]), "+f"(d[10]), "+f"(d[11]), "+f"(d[12]), "+f"(d[13]), "+f"(d[14]), "+f"(d[15]), "+f"(d[16]), "+f"(d[17]), "+f"(d[18]), "+f"(d[19]), "+f"(d[20]), "+f"(d[21]), "+f"(d[22]), "+f"(d[23]), "+f"(d[24]), "+f"(d[25]), "+f"(d[26]), "+f"(d[27]), "+f"(d[28]), "+f"(d[29]), "+f"(d[30]), "+f"(d[31]), "+f"(d[32]), "+f"(d[33]), "+f"(d[34]), "+f"(d[35]), "+f"(d[36]), "+f"(d[37]), "+f"(d[38]), "+f"(d[39]), "+f"(d[40]), "+f"(d[41]), "+f"(d[42]), "+f"(d[43]), "+f"(d[44]), "+f"(d[45]), "+f"(d[46]), "+f"(d[47]), "+f"(d[48]), "+f"(d[49]), "+f"(d[50]), "+f"(d[51]), "+f"(d[52]), "+f"(d[53]), "+f"(d[54]), "+f"(d[55]), "+f"(d[56]), "+f"(d[57]), "+f"(d[58]), "+f"(d[59]), "+f"(d[60]), "+f"(d[61]), "+f"(d[62]), "+f"(d[63]), "+f"(d[64]), "+f"(d[65]), "+f"(d[66]), "+f"(d[67]), "+f"(d[68]), "+f"(d[69]), "+f"(d[70]), "+f"(d[71]), "+f"(d[72]), "+f"(d[73]), "+f"(d[74]), "+f"(d[75]), "+f"(d[76]), "+f"(d[77]), "+f"(d[78]), "+f"(d[79]), "+f"(d[80]), "+f"(d[81]), "+f"(d[82]), "+f"(d[83]), "+f"(d[84]), "+f"(d[85]), "+f"(d[86]), "+f"(d[87]), "+f"(d[88]), "+f"(d[89]), "+f"(d[90]), "+f"(d[91]), "+f"(d[92]), "+f"(d[93]), "+f"(d[94]), "+f"(d[95]), "+f"(d[96]), "+f"(d[97]), "+f"(d[98]), "+f"(d[99]), "+f"(d[100]), "+f"(d[101]), "+f"(d[102]), "+f"(d[103]), "+f"(d[104]), "+f"(d[105]), "+f"(d[106]), "+f"(d[107]), "+f"(d[108]), "+f"(d[109]), "+f"(d[110]), "+f"(d[111]), "+f"(d[112]), "+f"(d[113]), "+f"(d[114]), "+f"(d[115]), "+f"(d[116]), "+f"(d[117]), "+f"(d[118]), "+f"(d[119]), "+f"(d[120]), "+f"(d[121]), "+f"(d[122]), "+f"(d[123]), "+f"(d[124]), "+f"(d[125]), "+f"(d[126]), "+f"(d[127])
    : "l"(da), "l"(db), "r"(acc), "n"(TA), "n"(TB));
}

template <int TA, int TB> __device__ __forceinline__ void wgmma_n64(float (&d)[32], uint64_t da, uint64_t db, int acc) {
  asm volatile("{\n.reg .pred p;\nsetp.ne.b32 p, %34, 0;\n"
    "wgmma.mma_async.sync.aligned.m64n64k16.f32.bf16.bf16 {%0, %1, %2, %3, %4, %5, %6, %7, %8, %9, %10, %11, %12, %13, %14, %15, %16, %17, %18, %19, %20, %21, %22, %23, %24, %25, %26, %27, %28, %29, %30, %31}, %32, %33, p, 1, 1, %35, %36;\n}\n"
    : "+f"(d[0]), "+f"(d[1]), "+f"(d[2]), "+f"(d[3]), "+f"(d[4]), "+f"(d[5]), "+f"(d[6]), "+f"(d[7]), "+f"(d[8]), "+f"(d[9]), "+f"(d[10]), "+f"(d[11]), "+f"(d[12]), "+f"(d[13]), "+f"(d[14]), "+f"(d[15]), "+f"(d[16]), "+f"(d[17]), "+f"(d[18]), "+f"(d[19]), "+f"(d[20]), "+f"(d[21]), "+f"(d[22]), "+f"(d[23]), "+f"(d[24]), "+f"(d[25]), "+f"(d[26]), "+f"(d[27]), "+f"(d[28]), "+f"(d[29]), "+f"(d[30]), "+f"(d[31])
    : "l"(da), "l"(db), "r"(acc), "n"(TA), "n"(TB));
}

template <int TA, int TB> __device__ __forceinline__ void wgmma_n80(float (&d)[40], uint64_t da, uint64_t db, int acc) {
  asm volatile("{\n.reg .pred p;\nsetp.ne.b32 p, %42, 0;\n"
    "wgmma.mma_async.sync.aligned.m64n80k16.f32.bf16.bf16 {%0, %1, %2, %3, %4, %5, %6, %7, %8, %9, %10, %11, %12, %13, %14, %15, %16, %17, %18, %19, %20, %21, %22, %23, %24, %25, %26, %27, %28, %29, %30, %31, %32, %33, %34, %35, %36, %37, %38, %39}, %40, %41, p, 1, 1, %43, %44;\n}\n"
    : "+f"(d[0]), "+f"(d[1]), "+f"(d[2]), "+f"(d[3]), "+f"(d[4]), "+f"(d[5]), "+f"(d[6]), "+f"(d[7]), "+f"(d[8]), "+f"(d[9]), "+f"(d[10]), "+f"(d[11]), "+f"(d[12]), "+f"(d[13]), "+f"(d[14]), "+f"(d[15]), "+f"(d[16]), "+f"(d[17]), "+f"(d[18]), "+f"(d[19]), "+f"(d[20]), "+f"(d[21]), "+f"(d[22]), "+f"(d[23]), "+f"(d[24]), "+f"(d[25]), "+f"(d[26]), "+f"(d[27]), "+f"(d[28]), "+f"(d[29]), "+f"(d[30]), "+f"(d[31]), "+f"(d[32]), "+f"(d[33]), "+f"(d[34]), "+f"(d[35]), "+f"(d[36]), "+f"(d[37]), "+f"(d[38]), "+f"(d[39])
    : "l"(da), "l"(db), "r"(acc), "n"(TA), "n"(TB));
}

template <int TA, int TB> __device__ __forceinline__ void wgmma_n144(float (&d)[72], uint64_t da, uint64_t db, int acc) {
  asm volatile("{\n.reg .pred p;\nsetp.ne.b32 p, %74, 0;\n"
    "wgmma.mma_async.sync.aligned.m64n144k16.f32.bf16.bf16 {%0, %1, %2, %3, %4, %5, %6, %7, %8, %9, %10, %11, %12, %13, %14, %15, %16, %17, %18, %19, %20, %21, %22, %23, %24, %25, %26, %27, %28, %29, %30, %31, %32, %33, %34, %35, %36, %37, %38, %39, %40, %41, %42, %43, %44, %45, %46, %47, %48, %49, %50, %51, %52, %53, %54, %55, %56, %57, %58, %59, %60, %61, %62, %63, %64, %65, %66, %67, %68, %69, %70, %71}, %72, %73, p, 1, 1, %75, %76;\n}\n"
    : "+f"(d[0]), "+f"(d[1]), "+f"(d[2]), "+f"(d[3]), "+f"(d[4]), "+f"(d[5]), "+f"(d[6]), "+f"(d[7]), "+f"(d[8]), "+f"(d[9]), "+f"(d[10]), "+f"(d[11]), "+f"(d[12]), "+f"(d[13]), "+f"(d[14]), "+f"(d[15]), "+f"(d[16]), "+f"(d[17]), "+f"(d[18]), "+f"(d[19]), "+f"(d[20]), "+f"(d[21]), "+f"(d[22]), "+f"(d[23]), "+f"(d[24]), "+f"(d[25]), "+f"(d[26]), "+f"(d[27]), "+f"(d[28]), "+f"(d[29]), "+f"(d[30]), "+f"(d[31]), "+f"(d[32]), "+f"(d[33]), "+f"(d[34]), "+f"(d[35]), "+f"(d[36]), "+f"(d[37]), "+f"(d[38]), "+f"(d[39]), "+f"(d[40]), "+f"(d[41]), "+f"(d[42]), "+f"(d[43]), "+f"(d[44]), "+f"(d[45]), "+f"(d[46]), "+f"(d[47]), "+f"(d[48]), "+f"(d[49]), "+f"(d[50]), "+f"(d[51]), "+f"(d[52]), "+f"(d[53]), "+f"(d[54]), "+f"(d[55]), "+f"(d[56]), "+f"(d[57]), "+f"(d[58]), "+f"(d[59]), "+f"(d[60]), "+f"(d[61]), "+f"(d[62]), "+f"(d[63]), "+f"(d[64]), "+f"(d[65]), "+f"(d[66]), "+f"(d[67]), "+f"(d[68]), "+f"(d[69]), "+f"(d[70]), "+f"(d[71])
    : "l"(da), "l"(db), "r"(acc), "n"(TA), "n"(TB));
}

template <int TA, int TB> __device__ __forceinline__ void wgmma_n128(float (&d)[64], uint64_t da, uint64_t db, int acc) {
  asm volatile("{\n.reg .pred p;\nsetp.ne.b32 p, %66, 0;\n"
    "wgmma.mma_async.sync.aligned.m64n128k16.f32.bf16.bf16 {%0, %1, %2, %3, %4, %5, %6, %7, %8, %9, %10, %11, %12, %13, %14, %15, %16, %17, %18, %19, %20, %21, %22, %23, %24, %25, %26, %27, %28, %29, %30, %31, %32, %33, %34, %35, %36, %37, %38, %39, %40, %41, %42, %43, %44, %45, %46, %47, %48, %49, %50, %51, %52, %53, %54, %55, %56, %57, %58, %59, %60, %61, %62, %63}, %64, %65, p, 1, 1, %67, %68;\n}\n"
    : "+f"(d[0]), "+f"(d[1]), "+f"(d[2]), "+f"(d[3]), "+f"(d[4]), "+f"(d[5]), "+f"(d[6]), "+f"(d[7]), "+f"(d[8]), "+f"(d[9]), "+f"(d[10]), "+f"(d[11]), "+f"(d[12]), "+f"(d[13]), "+f"(d[14]), "+f"(d[15]), "+f"(d[16]), "+f"(d[17]), "+f"(d[18]), "+f"(d[19]), "+f"(d[20]), "+f"(d[21]), "+f"(d[22]), "+f"(d[23]), "+f"(d[24]), "+f"(d[25]), "+f"(d[26]), "+f"(d[27]), "+f"(d[28]), "+f"(d[29]), "+f"(d[30]), "+f"(d[31]), "+f"(d[32]), "+f"(d[33]), "+f"(d[34]), "+f"(d[35]), "+f"(d[36]), "+f"(d[37]), "+f"(d[38]), "+f"(d[39]), "+f"(d[40]), "+f"(d[41]), "+f"(d[42]), "+f"(d[43]), "+f"(d[44]), "+f"(d[45]), "+f"(d[46]), "+f"(d[47]), "+f"(d[48]), "+f"(d[49]), "+f"(d[50]), "+f"(d[51]), "+f"(d[52]), "+f"(d[53]), "+f"(d[54]), "+f"(d[55]), "+f"(d[56]), "+f"(d[57]), "+f"(d[58]), "+f"(d[59]), "+f"(d[60]), "+f"(d[61]), "+f"(d[62]), "+f"(d[63])
    : "l"(da), "l"(db), "r"(acc), "n"(TA), "n"(TB));
}

template <int TB> __device__ __forceinline__ void wgmma_rs_n40(float (&d)[20], uint32_t a0, uint32_t a1, uint32_t a2, uint32_t a3, uint64_t db, int acc) {
  asm volatile("{\n.reg .pred p;\nsetp.ne.b32 p, %25, 0;\n"
    "wgmma.mma_async.sync.aligned.m64n40k16.f32.bf16.bf16 {%0, %1, %2, %3, %4, %5, %6, %7, %8, %9, %10, %11, %12, %13, %14, %15, %16, %17, %18, %19}, {%20, %21, %22, %23}, %24, p, 1, 1, %26;\n}\n"
    : "+f"(d[0]), "+f"(d[1]), "+f"(d[2]), "+f"(d[3]), "+f"(d[4]), "+f"(d[5]), "+f"(d[6]), "+f"(d[7]), "+f"(d[8]), "+f"(d[9]), "+f"(d[10]), "+f"(d[11]), "+f"(d[12]), "+f"(d[13]), "+f"(d[14]), "+f"(d[15]), "+f"(d[16]), "+f"(d[17]), "+f"(d[18]), "+f"(d[19])
    : "r"(a0), "r"(a1), "r"(a2), "r"(a3), "l"(db), "r"(acc), "n"(TB));
}

template <int TB> __device__ __forceinline__ void wgmma_rs_n192(float (&d)[96], uint32_t a0, uint32_t a1, uint32_t a2, uint32_t a3, uint64_t db, int acc) {
  asm volatile("{\n.reg .pred p;\nsetp.ne.b32 p, %101, 0;\n"
    "wgmma.mma_async.sync.aligned.m64n192k16.f32.bf16.bf16 {%0, %1, %2, %3, %4, %5, %6, %7, %8, %9, %10, %11, %12, %13, %14, %15, %16, %17, %18, %19, %20, %21, %22, %23, %24, %25, %26, %27, %28, %29, %30, %31, %32, %33, %34, %35, %36, %37, %38, %39, %40, %41, %42, %43, %44, %45, %46, %47, %48, %49, %50, %51, %52, %53, %54, %55, %56, %57, %58, %59, %60, %61, %62, %63, %64, %65, %66, %67, %68, %69, %70, %71, %72, %73, %74, %75, %76, %77, %78, %79, %80, %81, %82, %83, %84, %85, %86, %87, %88, %89, %90, %91, %92, %93, %94, %95}, {%96, %97, %98, %99}, %100, p, 1, 1, %102;\n}\n"
    : "+f"(d[0]), "+f"(d[1]), "+f"(d[2]), "+f"(d[3]), "+f"(d[4]), "+f"(d[5]), "+f"(d[6]), "+f"(d[7]), "+f"(d[8]), "+f"(d[9]), "+f"(d[10]), "+f"(d[11]), "+f"(d[12]), "+f"(d[13]), "+f"(d[14]), "+f"(d[15]), "+f"(d[16]), "+f"(d[17]), "+f"(d[18]), "+f"(d[19]), "+f"(d[20]), "+f"(d[21]), "+f"(d[22]), "+f"(d[23]), "+f"(d[24]), "+f"(d[25]), "+f"(d[26]), "+f"(d[27]), "+f"(d[28]), "+f"(d[29]), "+f"(d[30]), "+f"(d[31]), "+f"(d[32]), "+f"(d[33]), "+f"(d[34]), "+f"(d[35]), "+f"(d[36]), "+f"(d[37]), "+f"(d[38]), "+f"(d[39]), "+f"(d[40]), "+f"(d[41]), "+f"(d[42]), "+f"(d[43]), "+f"(d[44]), "+f"(d[45]), "+f"(d[46]), "+f"(d[47]), "+f"(d[48]), "+f"(d[49]), "+f"(d[50]), "+f"(d[51]), "+f"(d[52]), "+f"(d[53]), "+f"(d[54]), "+f"(d[55]), "+f"(d[56]), "+f"(d[57]), "+f"(d[58]), "+f"(d[59]), "+f"(d[60]), "+f"(d[61]), "+f"(d[62]), "+f"(d[63]), "+f"(d[64]), "+f"(d[65]), "+f"(d[66]), "+f"(d[67]), "+f"(d[68]), "+f"(d[69]), "+f"(d[70]), "+f"(d[71]), "+f"(d[72]), "+f"(d[73]), "+f"(d[74]), "+f"(d[75]), "+f"(d[76]), "+f"(d[77]), "+f"(d[78]), "+f"(d[79]), "+f"(d[80]), "+f"(d[81]), "+f"(d[82]), "+f"(d[83]), "+f"(d[84]), "+f"(d[85]), "+f"(d[86]), "+f"(d[87]), "+f"(d[88]), "+f"(d[89]), "+f"(d[90]), "+f"(d[91]), "+f"(d[92]), "+f"(d[93]), "+f"(d[94]), "+f"(d[95])
    : "r"(a0), "r"(a1), "r"(a2), "r"(a3), "l"(db), "r"(acc), "n"(TB));
}
constexpr uint32_t AR_ACC = 0;
constexpr uint32_t AR_TAB = 0x100000;
constexpr uint32_t AR_PROG = 0x101000;
constexpr uint32_t AR_CNT = 0x102000;
constexpr uint32_t AR_QUEUE = 0x103000;
constexpr uint32_t AR_SIZE = 0x104000;

struct ChainArgs {
  const bf16* mem0;
  const uint2* xh;
  unsigned char *kg, *vg;
  unsigned char* arena;
  uint32_t* dbg;
  int tl;
};

namespace ch {
constexpr int OFF_WQ = 0;
constexpr int OFF_X = 81920;
constexpr int OFF_MEM = OFF_X + 40960;
constexpr int OFF_WO = OFF_MEM + 10240;
constexpr int WOK = 8 * 896;
constexpr int OFF_KV = OFF_WO + 10 * WOK;
constexpr int KVB = 5120;
constexpr int OFF_O = OFF_KV + 4 * KVB;
constexpr int OFF_Q = OFF_O + 1024;
constexpr int OFF_S = OFF_O + 3072;
constexpr int OFF_SR = OFF_S + 1280;
constexpr int OFF_BAR = OFF_SR + 1536;
constexpr int SMEM = OFF_BAR + 128 + 1152;
static_assert(SMEM <= 232448, "smem");
constexpr int MB_S = OFF_BAR, MB_O = OFF_BAR + 8, MB_X = OFF_BAR + 16;
constexpr int MB_K = OFF_SR + 1408, MB_V = MB_K + 16, MB_Q = MB_K + 32, MB_R = MB_K + 48;
constexpr int SC_IN = OFF_BAR + 64;
constexpr int SC_MX = OFF_S;
constexpr int SC_W = OFF_BAR + 96;
constexpr int WOS = 448;
enum { B_MEM0 = 1, B_QK, B_SL, B_V, B_O, B_RED, B_X, B_C, B_H, B_MEM1, B_A, B_G };
#define NQ1 6
#define NQ0 4
#define NP0 4
#define NWO 5
#define NWP 4
#define NB0 2
#define BBS 100
#define VSYNC 0
#define XPOS 0
#define XPD 300
#define WOF 0
#define XBYTES 36864
#define NRT 7
#define NRF 2
#define NPM0 2
#define NPM1 2
#define RSYNC 1
#define PFK 1
#define PA0 7
#define PA1 0
#define PB0 7
#define PB1 5
#define PQE 0
#define XT 30
static_assert(NPM0 >= 2 && NPM1 >= 2, "the K / V blocks live in the last two k-steps of Wo");
}

#define CHAIN_TIMING 0
#define TS(i)
#define TSV(i, v)
#define TS_SETUP()
#define POLL_DELAY 570
#define XN 40
#define PF0 8
#define PFS 3
#define XDELAY 0
#define NOKM 0
#define PFACC 1
#define PUB_REL 1
template <int V> using IC = std::integral_constant<int, V>;
__device__ __forceinline__ uint32_t clk_v() { uint64_t c; asm volatile("mov.u64 %0, %%clock64;" : "=l"(c) :: "memory"); return (uint32_t)c; }
__device__ __forceinline__ int fresh(int x) { int y; asm volatile("shfl.sync.bfly.b32 %0, %1, 0, 0x1f, 0xffffffff;" : "=r"(y) : "r"(x)); return y; }
#define SFENCE2(x, d) asm volatile("{\n.reg .pred p;\nsetp.eq.u32 p, %0, 0x7fffffff;\n@p st.shared.u32 [%0], %1;\n}" :: "r"(x), "r"(d) : "memory")
#define SFENCE(x) asm volatile("{\n.reg .pred p;\nsetp.eq.u32 p, %0, 0x7fffffff;\n@p st.shared.u32 [%0], %0;\n}" :: "r"(x) : "memory")
template <int I> __device__ __forceinline__ void bbfence(uint32_t x) {
  asm volatile("{\n.reg .pred p;\nsetp.eq.u32 p, %0, %1;\nL_%=:\n@p st.volatile.shared.u32 [%0], %0;\n@p bra.uni L_%=;\n}" :: "r"(x), "n"(4 * I) : "memory");
}
__device__ __forceinline__ float uniform_f(float x) { return __uint_as_float(__reduce_max_sync(0xffffffffu, __float_as_uint(x))); }

__device__ __forceinline__ void mma16816h(float (&d)[4], const uint32_t (&a)[4], uint32_t b0, uint32_t b1) {
  asm volatile("mma.sync.aligned.m16n8k16.row.col.f32.f16.f16.f32 {%0,%1,%2,%3}, {%4,%5,%6,%7}, {%8,%9}, {%0,%1,%2,%3};"
               : "+f"(d[0]), "+f"(d[1]), "+f"(d[2]), "+f"(d[3]) : "r"(a[0]), "r"(a[1]), "r"(a[2]), "r"(a[3]), "r"(b0), "r"(b1));
}
__device__ __forceinline__ void mma1688(float (&d)[4], uint32_t a0, uint32_t a1, uint32_t b0) {
  asm volatile("mma.sync.aligned.m16n8k8.row.col.f32.bf16.bf16.f32 {%0,%1,%2,%3}, {%4,%5}, {%6}, {%0,%1,%2,%3};"
               : "+f"(d[0]), "+f"(d[1]), "+f"(d[2]), "+f"(d[3]) : "r"(a0), "r"(a1), "r"(b0));
}
template <int OFF16, int ACC> __device__ __forceinline__ void wgmma_rs32h(float (&d)[16], const uint32_t (&a)[4], uint32_t dlo) {
  asm volatile("{\n.reg .pred p;\n.reg .b32 t;\n.reg .b64 db;\nsetp.ne.b32 p, %22, 0;\nadd.u32 t, %20, %21;\nmov.b64 db, {t, 0x40000040};\n"
    "wgmma.mma_async.sync.aligned.m64n32k16.f32.f16.f16 {%0,%1,%2,%3,%4,%5,%6,%7,%8,%9,%10,%11,%12,%13,%14,%15}, {%16,%17,%18,%19}, db, p, 1, 1, 0;\n}\n"
    : "+f"(d[0]), "+f"(d[1]), "+f"(d[2]), "+f"(d[3]), "+f"(d[4]), "+f"(d[5]), "+f"(d[6]), "+f"(d[7]), "+f"(d[8]), "+f"(d[9]), "+f"(d[10]), "+f"(d[11]),
      "+f"(d[12]), "+f"(d[13]), "+f"(d[14]), "+f"(d[15])
    : "r"(a[0]), "r"(a[1]), "r"(a[2]), "r"(a[3]), "r"(dlo), "n"(OFF16), "n"(ACC));
}
template <int IMM> __device__ __forceinline__ void stsm_x4_t_i(uint32_t a, uint32_t r0, uint32_t r1, uint32_t r2, uint32_t r3) {
  asm volatile("stmatrix.sync.aligned.m8n8.x4.trans.shared.b16 [%0+%5], {%1,%2,%3,%4};" :: "r"(a), "r"(r0), "r"(r1), "r"(r2), "r"(r3), "n"(IMM) : "memory");
}
template <int IMM> __device__ __forceinline__ void stsm_x2_t_i(uint32_t a, uint32_t r0, uint32_t r1) {
  asm volatile("stmatrix.sync.aligned.m8n8.x2.trans.shared.b16 [%0+%3], {%1,%2};" :: "r"(a), "r"(r0), "r"(r1), "n"(IMM) : "memory");
}
template <int IMM> __device__ __forceinline__ void st_async_b32_i(uint32_t a, uint32_t x, uint32_t mb) {
  asm volatile("st.async.weak.shared::cluster.mbarrier::complete_tx::bytes.b32 [%0+%3], %1, [%2];" :: "r"(a), "r"(x), "r"(mb), "n"(IMM) : "memory");
}
template <int IMM> __device__ __forceinline__ void ld_relaxed_v4_if(uint4& v, const void* p, uint32_t c) {
  asm volatile("{\n.reg .pred p;\nsetp.ne.u32 p, %6, 0;\n@p ld.relaxed.gpu.global.v4.u32 {%0,%1,%2,%3}, [%4+%5];\n}"
               : "+r"(v.x), "+r"(v.y), "+r"(v.z), "+r"(v.w) : "l"(p), "n"(IMM), "r"(c) : "memory");
}
template <int IMM> __device__ __forceinline__ uint32_t lds32_i(uint32_t a) {
  uint32_t v; asm volatile("ld.shared.u32 %0, [%1+%2];" : "=r"(v) : "r"(a), "n"(IMM) : "memory"); return v;
}
__device__ __forceinline__ void sts32(uint32_t a, uint32_t v) { asm volatile("st.shared.u32 [%0], %1;" :: "r"(a), "r"(v) : "memory"); }
__device__ __forceinline__ uint32_t pack_f16(float lo, float hi) {
  uint32_t d; asm("cvt.rn.f16x2.f32 %0, %1, %2;" : "=r"(d) : "f"(hi), "f"(lo)); return d;
}
__device__ __forceinline__ uint32_t amax_bf2(uint32_t a, uint32_t b) { uint32_t d; asm("max.xorsign.abs.bf16x2 %0, %1, %2;" : "=r"(d) : "r"(a), "r"(b)); return d; }
__device__ __forceinline__ uint32_t amax_h2(uint32_t a, uint32_t b) { uint32_t d; asm("max.xorsign.abs.f16x2 %0, %1, %2;" : "=r"(d) : "r"(a), "r"(b)); return d; }
__device__ __forceinline__ uint32_t amax_fold(uint32_t m) { return __reduce_max_sync(0xffffffffu, max(m & 0x7fffu, (m >> 16) & 0x7fffu)); }
__device__ __forceinline__ int wscale_exp(uint32_t m) { return min(141 - (int)(m >> 7), 100); }
__device__ __forceinline__ float exp2i(int e) { return __uint_as_float((uint32_t)(e + 127) << 23); }
__device__ __forceinline__ uint32_t bf2_to_h2(uint32_t w, float sc) { return pack_f16(bf_lo(w) * sc, bf_hi(w) * sc); }
__device__ __forceinline__ void bf2_to_h2_inplace(uint32_t& w, uint32_t sc2) {
  asm volatile("{\n.reg .b32 t, lo, hi;\nmul.rn.bf16x2 t, %0, %1;\nshl.b32 lo, t, 16;\nand.b32 hi, t, 0xffff0000;\ncvt.rn.f16x2.f32 %0, hi, lo;\n}" : "+r"(w) : "r"(sc2));
}
__device__ __forceinline__ void prefetch_l2(const void* p, uint32_t bytes) { asm volatile("cp.async.bulk.prefetch.L2.global [%0], %1;" :: "l"(p), "r"(bytes) : "memory"); }
__device__ __forceinline__ void prefetch_tma_2d(const CUtensorMap* tm, int c0, int c1) {
  asm volatile("cp.async.bulk.prefetch.tensor.2d.L2.global [%0, {%1, %2}];" :: "l"(tm), "r"(c0), "r"(c1) : "memory");
}
__host__ __device__ constexpr uint32_t acc_voff(int v) { return v < 4 ? v * 1024u : (v == 4 ? 128u : 3072u + 128u); }
__device__ __forceinline__ int unit28(int i) { return i == 3 ? 54 : 14 * i; }
__device__ __forceinline__ int unit24(int i) { return i < 2 ? 48 - 6 * i : 56 + 6 * i; }
__device__ __forceinline__ uint32_t acc_step(int s) { return (s >> 1) * 32768 + (s & 1) * 512; }
__device__ __forceinline__ uint32_t acc_lane(int i, int lane) { return ((lane >> 3) & 1) * 256 + (lane >> 4) * 4096 + i * 8192 + (lane & 7) * 16; }

__device__ __forceinline__ uint32_t ld_acquire_u32(const void* p) {
  uint32_t v; asm volatile("ld.acquire.gpu.global.u32 %0, [%1];" : "=r"(v) : "l"(p) : "memory"); return v;
}
template <int R> __device__ __forceinline__ void ln_rows(const uint2 (&xw)[R][5], int row0, int lane, bf16* __restrict__ xn, uint2* __restrict__ xh) {
  float v[R][20], s[R], q[R];
#pragma unroll
  for (int r = 0; r < R; r++) {
    s[r] = 0.f; q[r] = 0.f;
#pragma unroll
    for (int i = 0; i < 5; i++) { v[r][4 * i] = bf_lo(xw[r][i].x); v[r][4 * i + 1] = bf_hi(xw[r][i].x); v[r][4 * i + 2] = bf_lo(xw[r][i].y); v[r][4 * i + 3] = bf_hi(xw[r][i].y); }
#pragma unroll
    for (int i = 0; i < 5; i++) s[r] += (v[r][4 * i] + v[r][4 * i + 1]) + (v[r][4 * i + 2] + v[r][4 * i + 3]);
  }
#pragma unroll
  for (int o = 16; o; o >>= 1)
#pragma unroll
    for (int r = 0; r < R; r++) s[r] += __shfl_xor_sync(0xffffffffu, s[r], o);
#pragma unroll
  for (int r = 0; r < R; r++) {
    s[r] *= 1.f / cfg::DM;
#pragma unroll
    for (int i = 0; i < 10; i++) { const float d = v[r][2 * i] - s[r], e = v[r][2 * i + 1] - s[r]; q[r] += d * d + e * e; }
  }
#pragma unroll
  for (int o = 16; o; o >>= 1)
#pragma unroll
    for (int r = 0; r < R; r++) q[r] += __shfl_xor_sync(0xffffffffu, q[r], o);
#pragma unroll
  for (int r = 0; r < R; r++) {
    const int row = row0 + r;
    const float mb = bf16r(s[r]), var = bf16r(q[r] * (1.f / cfg::DM));
    const float den = bf16r(sqrtf(bf16r(var + 1e-5f)));
#pragma unroll
    for (int i = 0; i < 5; i++) {
      float y[4];
#pragma unroll
      for (int e = 0; e < 4; e++) y[e] = __fdividef(bf16r(v[r][4 * i + e] - mb), den);
      const uint32_t w0 = pack_bf16(y[0], y[1]), w1 = pack_bf16(y[2], y[3]);
      *(uint2*)(xn + (size_t)row * cfg::DM + i * 128 + lane * 4) = make_uint2(w0, w1);
      if (xh) xh[(((size_t)(row >> 5) * 10 + 2 * i + (lane >> 4)) * 32 + (row & 31)) * 16 + ((((lane >> 1) & 7) ^ (row & 7)) << 1) + (lane & 1)] =
          make_uint2(pack_f16(bf_lo(w0), bf_hi(w0)), pack_f16(bf_lo(w1), bf_hi(w1)));
    }
  }
}

__global__ void __cluster_dims__(3, 1, 1) __launch_bounds__(384, 1) chain_kernel(const ChainArgs a, const __grid_constant__ CUtensorMap tmWq,
    const __grid_constant__ CUtensorMap tmWk, const __grid_constant__ CUtensorMap tmWv, const __grid_constant__ CUtensorMap tmWo) {
  using namespace ch;
  extern __shared__ __align__(1024) unsigned char smem_raw[];
  const uint32_t sb = smem_u32(smem_raw);
  const int warp = __shfl_sync(0xffffffffu, (int)threadIdx.x >> 5, 0);
  const int lane = __shfl_sync(0xffffffffu, (int)threadIdx.x & 31, threadIdx.x & 31);
  const int cta = blockIdx.x, h = cta / 3, j = cta % 3;
  const int g = lane >> 2, q4 = lane & 3, r8 = lane & 7, m4 = lane >> 3;
  unsigned char* const arena = a.arena;
  if (sb & 1023u) __trap();
  TL_BEGIN(a.tl);
  const int col0 = j == 0 ? 0 : (j == 1 ? 224 : 432);
  auto stage_w = [&](const CUtensorMap* tm, uint32_t dst, uint32_t mb, int half) {
    mbar_expect_tx(mb + 8 * half, 40960);
    tma_load_2d(dst + half * 40960, tm, h * cfg::DH + j * 64, half * 320, mb + 8 * half);
    tma_load_2d(dst + half * 40960 + 20480, tm, h * cfg::DH + j * 64, half * 320 + 160, mb + 8 * half);
  };
  if (threadIdx.x == 256) {
    for (int i = 0; i < 9; i++) mbar_init(sb + MB_K + 8 * i, 1);
    mbar_init(sb + MB_S, 1); mbar_init(sb + MB_O, 1); mbar_init(sb + MB_X, 1);
    asm volatile("fence.mbarrier_init.release.cluster;" ::: "memory");
    for (int i = 0; i < 2; i++) { stage_w(&tmWk, sb + OFF_WQ, sb + MB_K, i); stage_w(&tmWv, sb + OFF_WO, sb + MB_V, i); }
    sts32(sb + SC_W, 0); sts32(sb + SC_W + 4, 0); sts32(sb + SC_W + 8, 0); sts32(sb + SC_IN + 12, 0); sts32(sb + SC_IN + 20, 0);
    mbar_expect_tx(sb + MB_S, 1280); mbar_expect_tx(sb + MB_O, 2048);
  }
  __syncthreads();
  asm volatile("barrier.cluster.arrive.relaxed.aligned;" ::: "memory");
  const uint32_t d1 = mapa_u32(sb, (j + 1) % 3) - sb, d2 = mapa_u32(sb, (j + 2) % 3) - sb;

  if (warp >= 8) {
    asm volatile("setmaxnreg.dec.sync.aligned.u32 40;");
    const int hw = warp - 8, ht = hw * 32 + lane;
    const bool lead = ht == 0;
    auto stage_wo = [&](int i) {
      mbar_expect_tx(sb + MB_R + 8 * i, 64 * WOS);
      tma_load_2d(sb + OFF_WO + i * 64 * WOS, &tmWo, col0, h * cfg::DH + ((i + j) % 3) * 64, sb + MB_R + 8 * i);
    };
    const unsigned char* xg = (const unsigned char*)a.xh;
    auto issue_x = [&](int s) { mbar_expect_tx(sb + MB_X, 40960); bulk_g2s(sb + OFF_X, xg + (size_t)s * 40960, 40960, sb + MB_X); };
    uint4 v[5];
#pragma unroll
    for (int i = 0; i < 5; i++) { const int c = ht + 128 * i; v[i] = ld_relaxed_v4(a.mem0 + (c & 7) * cfg::DM + (c >> 3) * 8); }
    if (hw == 2) {
      asm volatile("griddepcontrol.wait;" ::: "memory");
      asm volatile("griddepcontrol.launch_dependents;" ::: "memory");
      if (lane == 0) issue_x(0);
    }
    if (hw == 0) {
      bar_sync(B_QK, 160); if (lane == 0) stage_w(&tmWq, sb + OFF_WQ, sb + MB_Q, 0);
      bar_sync(B_SL, 160); if (lane == 0) stage_w(&tmWq, sb + OFF_WQ, sb + MB_Q, 1);
    }
    if (hw == 1) {
      bar_sync(B_V, 160); if (lane == 0) stage_wo(0);
      bar_sync(B_O, 160); if (lane == 0) { stage_wo(1); stage_wo(2); }
    }
    __syncwarp();
    {
      uint32_t m = 0;
#pragma unroll
      for (int i = 0; i < 5; i++) {
        m = amax_bf2(amax_bf2(m, amax_bf2(v[i].x, v[i].y)), amax_bf2(v[i].z, v[i].w));
      }
      m = amax_fold(m);
      if (lane == 0) sts32(sb + SC_MX + hw * 4, m);
      bar_sync(B_H, 128);
      const uint4 mm = lds128(sb + SC_MX);
      const int se = max(wscale_exp(max(max(mm.x, mm.y), max(mm.z, mm.w))), -100);
      const float sc = exp2i(se);
#pragma unroll
      for (int i = 0; i < 5; i++) {
        const int c = ht + 128 * i, t = c & 7, chn = c >> 3;
        sts128(sb + OFF_MEM + chn * 128 + ((t ^ (2 * (chn & 3))) << 4), bf2_to_h2(v[i].x, sc), bf2_to_h2(v[i].y, sc), bf2_to_h2(v[i].z, sc), bf2_to_h2(v[i].w, sc));
      }
      if (lead) { sts32(sb + SC_IN, __float_as_uint(exp2i(-se))); sts32(sb + SC_IN + 4, 0x7800u); }
    }
    {
      const uint32_t p0 = sb + OFF_WQ + hw * 2048 + lane * 16;
      uint32_t m = 0;
#pragma unroll 1
      for (int i = 0; i < 10; i++) {
        if (i == 0 || i == 5) mbar_wait(sb + MB_Q + (i ? 8 : 0), 0);
        uint32_t r[4][4];
        static_for<0, 4>([&](auto K) { ldsm_x4_i<K.value * 512>(r[K.value], p0 + i * 8192); });
#pragma unroll
        for (int k = 0; k < 4; k++) m = amax_bf2(amax_bf2(m, amax_bf2(r[k][0], r[k][1])), amax_bf2(r[k][2], r[k][3]));
      }
      m = amax_fold(m);
      if (lane == 0) asm volatile("red.shared.max.u32 [%0], %1;" :: "r"(sb + SC_W + 8), "r"(m) : "memory");
      bar_sync(B_H, 128);
      const uint32_t sc = (uint32_t)(wscale_exp(lds32_i<SC_W + 8>(sb)) + 127) * 0x00800080u;
#pragma unroll 1
      for (int i = 0; i < 10; i++) {
        uint32_t r[4][4];
        static_for<0, 4>([&](auto K) { ldsm_x4_i<K.value * 512>(r[K.value], p0 + i * 8192); });
#pragma unroll
        for (int k = 0; k < 4; k++) {
          bf2_to_h2_inplace(r[k][0], sc); bf2_to_h2_inplace(r[k][1], sc); bf2_to_h2_inplace(r[k][2], sc); bf2_to_h2_inplace(r[k][3], sc);
          stsm_x4(p0 + i * 8192 + k * 512, r[k][0], r[k][1], r[k][2], r[k][3]);
        }
      }
    }
    bar_sync(0, 384);
    if (lead) st_relaxed_u32(arena + AR_TAB + cta * 4, 0x80000000u | (lds32_i<SC_W>(sb) << 15) | lds32_i<SC_W + 4>(sb));
    asm volatile("barrier.cluster.wait.aligned;" ::: "memory");
    bar_sync(B_MEM0, 256); bar_sync(B_MEM1, 256);
    {
      uint32_t v0, v1, v2; int spin = 0;
      do {
        v0 = ld_relaxed_u32(arena + AR_TAB + lane * 4); v1 = ld_relaxed_u32(arena + AR_TAB + 128 + lane * 4); v2 = ld_relaxed_u32(arena + AR_TAB + 256 + lane * 4);
      } while (__any_sync(0xffffffffu, ((v0 & v1 & v2) >> 31) == 0) && ++spin < SPIN_LIMIT);
      const uint32_t mv = (max(max(v0, v1), v2) >> 15) & 0x7fffu, mo = max(max(v0 & 0x7fffu, v1 & 0x7fffu), v2 & 0x7fffu);
      sts32(sb + SC_IN + 8 + (lane & 1) * 16, 15 - ((__reduce_max_sync(0xffffffffu, mv) >> 7) + (__reduce_max_sync(0xffffffffu, mo) >> 7) - 252 + 22));
    }

    auto store_kv = [&](int s) {
      const size_t o = ((size_t)s * 96 + cta) * KVB; const uint32_t src = sb + OFF_KV + (s & 1) * (2 * KVB);
      fence_proxy_async(); bulk_s2g(a.kg + o, src, KVB); bulk_s2g(a.vg + o, src + KVB, KVB); bulk_commit();
    };
    const int cb28 = unit28(hw), du = (unit24(hw) - cb28) * 128;
    int ln = lane;
#pragma unroll 1
    for (int s = 0; s < cfg::NSEG; s++) {
      TS_SETUP();
      const bool last = s == cfg::NSEG - 1;
      if (ln == 0) {
        if (hw == 2 && !last) issue_x(s + 1);
        if (hw == 0 && s > 0) store_kv(s - 1);
        if (PFACC && hw == 1 && s + PFACC < cfg::NSEG - 1)
          asm volatile("prefetch.global.L2 [%0];" :: "l"(arena + (AR_ACC + acc_step(s + PFACC) + acc_lane(cta / 24, (cta & 3) * 8) + acc_voff((cta % 24) >> 2))) : "memory");
      }
      __syncwarp();
      if (last) break;
      const uint32_t kv = (s & 1) * (2 * KVB);
      ln = fresh(ln);
      uint32_t kb0[4], kb1[4];
      { const uint32_t ka = sb + kv + hw * 128 + (ln >> 3) * 640 + (ln & 7) * 16; ldsm_x4_i<OFF_KV>(kb0, ka); ldsm_x4_i<OFF_KV + 2560>(kb1, ka); }
      const uint32_t l16 = sb + ln * 16, s8 = sb + ln * 8, xs = s8 + hw * 256, xr = sb + ln * 4 + (hw >> 1) * 512 + (hw & 1) * 128;
      TS(1);
      bar_sync(B_QK, 384);
      {
        uint32_t q0[4], q1[4], q2[4], q3[4];
        float sa[4] = {0, 0, 0, 0}, sc2[4] = {0, 0, 0, 0};
        ldsm_x4_i<OFF_Q>(q0, l16); ldsm_x4_i<OFF_Q + 1024>(q2, l16); ldsm_x4_i<OFF_Q + 512>(q1, l16);
        bar_arrive(B_A, 288);
        ldsm_x4_i<OFF_Q + 1536>(q3, l16);
        mma16816(sa, q0[0], q0[1], q0[2], q0[3], kb0[0], kb0[1]);
        mma16816(sc2, q2[0], q2[1], q2[2], q2[3], kb1[0], kb1[1]);
        mma16816(sa, q1[0], q1[1], q1[2], q1[3], kb0[2], kb0[3]);
        mma16816(sc2, q3[0], q3[1], q3[2], q3[3], kb1[2], kb1[3]);
        const float x0 = (sa[0] + sa[2]) + (sc2[0] + sc2[2]), x1 = (sa[1] + sa[3]) + (sc2[1] + sc2[3]);
        const uint32_t xp = pack_bf16(x0, x1);
        st_async_b32_i<OFF_SR + 256>(xr + d1, xp, sb + MB_S + d1);
        st_async_b32_i<OFF_SR>(xr + d2, xp, sb + MB_S + d2);
        sts64_i<OFF_S>(xs, __float_as_uint(x0), __float_as_uint(x1));
      }
      TS(3);
      bar_sync(B_SL, 256);
      float t0[4], t1[4], t2[4] = {0, 0, 0, 0};
      float osc;
      {
        const uint4 si = lds128_i<SC_IN>(sb + 16 * (s & 1));
        { const uint2 x = lds64_i<OFF_S>(s8), y = lds64_i<OFF_S + 256>(s8); t0[0] = __uint_as_float(x.x); t0[1] = __uint_as_float(x.y); t0[2] = __uint_as_float(y.x); t0[3] = __uint_as_float(y.y); }
        { const uint2 x = lds64_i<OFF_S + 512>(s8), y = lds64_i<OFF_S + 768>(s8); t1[0] = __uint_as_float(x.x); t1[1] = __uint_as_float(x.y); t1[2] = __uint_as_float(y.x); t1[3] = __uint_as_float(y.y); }
        { const uint2 x = lds64_i<OFF_S + 1024>(s8); t2[0] = __uint_as_float(x.x); t2[1] = __uint_as_float(x.y); }
        const int em = (int)(si.y >> 10) - 14 + (int)(si.x >> 23) - 127;
        osc = exp2i(max(min((int)si.z - max(em, 1), 100), -100));
      }
      const uint32_t xo = sb + hw * 256 + (ln & 2) * 64 + (ln >> 2) * 16 + (ln & 1) * 8;
      const uint32_t eye = ((ln >> 3) == (ln & 3)) ? ((ln & 4) ? 0x3f800000u : 0x3f80u) : 0u;
      mbar_spin(sb + MB_S, s & 1);
      TS(4);
      uint32_t v0[4], v1[4], vm[2];
      {
        uint32_t r0[4], r1[4], r2[4];
        ldsm_x4_i<OFF_SR>(r0, l16); ldsm_x4_i<OFF_SR + 512>(r1, l16); ldsm_x4_i<OFF_SR + 1024>(r2, l16);
        mma16816(t0, r0[0], r0[1], r0[2], r0[3], eye, eye);
        mma16816(t1, r1[0], r1[1], r1[2], r1[3], eye, eye);
        mma16816(t2, r2[0], r2[1], r2[2], r2[3], eye, eye);
      }
      float sc[10] = {t0[0], t0[1], t0[2], t0[3], t1[0], t1[1], t1[2], t1[3], t2[0], t2[1]};
      const float cs = 0.07216878364870322f * 1.4426950408889634f;
      float mx = fmaxf(fmaxf(fmaxf(sc[0], sc[1]), fmaxf(sc[2], sc[3])), fmaxf(fmaxf(sc[4], sc[5]), fmaxf(sc[6], sc[7])));
      mx = fmaxf(mx, fmaxf(sc[8], sc[9]));
      {
        const float m1 = __shfl_xor_sync(0xffffffffu, mx, 1), m2 = __shfl_xor_sync(0xffffffffu, mx, 2), m3 = __shfl_xor_sync(0xffffffffu, mx, 3);
        SFENCE2(l16, __float_as_uint(mx));
        ldsm_x4_t_i<OFF_KV + KVB>(v0, l16 + (kv + hw * 1280)); ldsm_x4_t_i<OFF_KV + KVB + 640>(v1, l16 + (kv + hw * 1280));
        bar_sync(B_V, 256);
        bar_arrive(B_G, 384);
        ldsm_x2_t(vm, l16 + (ln & 8) * 64 + (kv + hw * 1280 + OFF_KV + KVB + 512));
        mx = fmaxf(fmaxf(mx, m1), fmaxf(m2, m3));
      }
      const float mo = mx * cs;
#pragma unroll
      for (int i = 0; i < 10; i++) sc[i] = ex2f(fmaf(sc[i], cs, -mo));
      const uint32_t p0 = pack_bf16(sc[0], sc[1]), p1 = pack_bf16(sc[2], sc[3]), p2 = pack_bf16(sc[4], sc[5]), p3 = pack_bf16(sc[6], sc[7]), p4 = pack_bf16(sc[8], sc[9]);
      TS(5);
      float oa[4] = {0, 0, 0, 0}, ob[4] = {0, 0, 0, 0}, oc[4] = {0, 0, 0, 0}, od[4] = {0, 0, 0, 0}, rs[4] = {0, 0, 0, 0};
      const uint32_t ones = 0x3f803f80u;
      mma16816(rs, p0, p2, p1, p3, ones, ones);
      mma16816(oc, p0, p2, p1, p3, v0[2], v0[3]);
      mma16816(od, p0, p2, p1, p3, v1[2], v1[3]);
      mma16816(oa, p0, p2, p1, p3, v0[0], v0[1]);
      mma16816(ob, p0, p2, p1, p3, v1[0], v1[1]);
      mma1688(rs, p4, 0u, ones);
      mma1688(oa, p4, 0u, vm[0]);
      mma1688(ob, p4, 0u, vm[1]);
      const float inv = rcpf(rs[0] + rs[2]) * osc;
      {
        const uint32_t y0 = pack_bf16((oa[0] + oc[2]) * inv, (oa[1] + oc[3]) * inv), y1 = pack_bf16((ob[0] + od[2]) * inv, (ob[1] + od[3]) * inv);
        st_async_v2_i<OFF_O + 2048>(xo + d1, y0, y1, sb + MB_O + d1);
        st_async_v2_i<OFF_O + 1024>(xo + d2, y0, y1, sb + MB_O + d2);
        sts64_i<OFF_O>(xo, y0, y1);
      }
      bar_arrive(B_O, 384);
      TS(6);
      if (ln == 0) {
        if (hw == 0) {
          bulk_wait<0>();
          if ((s & 3) == 0 && s > 0) {
            asm volatile("st.release.gpu.global.u32 [%0], %1;" :: "l"(arena + (AR_PROG + (cta + ln) * 4)), "r"(s) : "memory");
          }
        }
        if (hw == 3) { mbar_expect_tx(sb + MB_S, 1280); sts64_i<SC_IN>(sb + 16 * ((s + 1) & 1), 0x7f000000u - __float_as_uint(osc), 0u); }
      }
      __syncwarp();
      ln = fresh(ln);
      auto mslot = [&](int c) -> uint32_t { return sb + OFF_MEM + c * 128 + (((ln >> 2) ^ (2 * (c & 3))) << 4); };
      const int lq = ln & 3;
      const uint32_t ma = mslot(cb28 + lq), mb_ = mslot(cb28 + (lq >> 1)) + (lq & 1) * 8;
      const unsigned char* gp = arena + (AR_ACC + acc_lane(hw, ln) + acc_step(s));
      const bool odd = ln & 1;
      SFENCE(ma);
      bar_sync(B_RED, 384);
      SFENCE(mb_);
      const uint32_t tw = clk_v();
      TSV(7, tw);
      if (ln == 0 && hw == 3) mbar_expect_tx(sb + MB_O, 2048);
      __syncwarp();
      while (clk_v() - tw < POLL_DELAY) {}
      TS(8);
      uint4 v[6];
      int spin = 0;
      const uint32_t cm = odd ? 0x5000u : 0u;
      do {
        static_for<0, 6>([&](auto I) { v[I.value] = ld_relaxed_v4_i<acc_voff(I.value)>(gp); });
      } while (__any_sync(0xffffffffu, (~((v[0].w & v[1].w & v[2].w) & (v[3].w & v[4].w & v[5].w)) & cm) != 0) && ++spin < SPIN_LIMIT);
      v[0].w = odd ? v[3].x : v[0].w; v[1].w = odd ? v[3].y : v[1].w; v[2].w = odd ? v[3].z : v[2].w; v[3].w = odd ? 0u : v[3].w;
      sts128_i<0>(ma, v[0].x, v[0].y, v[0].z, v[0].w);
      sts128_i<512>(ma, v[1].x, v[1].y, v[1].z, v[1].w);
      sts128_i<1024>(ma, v[2].x, v[2].y, v[2].z, v[2].w);
      sts128_i<0>(ma + du, v[4].x, v[4].y, v[4].z, v[5].z);
      sts64_i<512>(mb_ + du, v[5].x, v[5].y);
      if (!odd) sts128_i<1536>(mb_, v[3].x, v[3].y, v[3].z, v[3].w);
      TSV(11, spin);
      TS(10);
      bar_sync(B_MEM0, 256); bar_sync(B_MEM1, 256);
      uint32_t m = lds32_i<SC_IN + 12>(sb);
      uint32_t m2 = m;
      static_for<0, 3>([&](auto I) { m = amax_h2(amax_h2(amax_h2(amax_h2(m, v[I.value].x), v[I.value].y), v[I.value].z), v[I.value].w); });
      static_for<3, 6>([&](auto I) { m2 = amax_h2(amax_h2(amax_h2(m2, v[I.value].x), v[I.value].y), v[I.value].z); });
      m = amax_fold(amax_h2(amax_h2(m2, v[3].w), m));
      if (ln == 0) asm volatile("red.shared.max.u32 [%0], %1;" :: "r"(sb + SC_IN + 4 + 16 * ((s + 1) & 1)), "r"(m) : "memory");
    }
    bar_sync(B_RED, 384);
    if (hw == 0 && ln == 0) {
      store_kv(cfg::NSEG - 1);
      bulk_wait<0>();
      asm volatile("st.release.gpu.global.u32 [%0], %1;" :: "l"(arena + AR_PROG + cta * 4), "r"(cfg::NSEG) : "memory");
    }
    __syncwarp();
    TL_END(a.tl);
    asm volatile("barrier.cluster.arrive.relaxed.aligned; barrier.cluster.wait.aligned;" ::: "memory");
  } else {
    asm volatile("setmaxnreg.inc.sync.aligned.u32 232;");
    const int wi = warp & 3, hf = warp >> 2, tid = warp * 32 + lane;
    uint32_t w[40][4];
    uint32_t wqa;
    { const int mrow = r8 + ((lane >> 4) << 3), mch = 2 * wi + (m4 & 1); wqa = sb + mrow * 128 + ((mch ^ r8) << 4); }
    {
      const uint32_t wa = wqa + (hf ? OFF_WO : OFF_WQ);
      mbar_wait(sb + (hf ? MB_V : MB_K), 0);
      static_for<0, 20>([&](auto K) { ldsm_x4_t_i<K.value * 2048>(w[K.value], wa); });
      bar_arrive(hf ? B_V : B_QK, 160);
      mbar_wait(sb + (hf ? MB_V : MB_K) + 8, 0);
      static_for<20, 40>([&](auto K) { ldsm_x4_t_i<K.value * 2048>(w[K.value], wa); });
      bar_arrive(hf ? B_O : B_SL, 160);
      SFENCE(wa);
    }
    float iw, iq;
    {
      uint32_t m = 0;
#pragma unroll
      for (int k = 0; k < 40; k++) m = amax_bf2(amax_bf2(m, amax_bf2(w[k][0], w[k][1])), amax_bf2(w[k][2], w[k][3]));
      m = amax_fold(m);
      if (hf && lane == 0) asm volatile("red.shared.max.u32 [%0], %1;" :: "r"(sb + SC_W), "r"(m) : "memory");
      const int e = wscale_exp(m);
      const uint32_t sc = (uint32_t)(e + 127) * 0x00800080u; iw = exp2i(-e);
#pragma unroll
      for (int k = 0; k < 40; k++) { bf2_to_h2_inplace(w[k][0], sc); bf2_to_h2_inplace(w[k][1], sc); bf2_to_h2_inplace(w[k][2], sc); bf2_to_h2_inplace(w[k][3], sc); }
    }
    uint32_t x0[8];
    {
      float xa[16];
      const uint32_t dlo = (((sb + OFF_X) & 0x3FFFF) >> 4) | (1u << 16);
      mbar_wait(sb + MB_X, 0);
      wgmma_fence();
      static_for<0, 40>([&](auto K) { constexpr int k = K.value; wgmma_rs32h<((k >> 2) * 4096 + (k & 3) * 32) / 16, (k != 0)>(xa, w[k], dlo); });
      wgmma_commit();
      wgmma_wait<0>();
#pragma unroll
      for (int i = 0; i < 8; i++) x0[i] = pack_bf16(xa[2 * i] * iw, xa[2 * i + 1] * iw);
    }
    const bool t28 = j == 0 || warp < 4;
    const int bi = j == 0 ? hf : (warp < 4 ? j + 1 : 2 * (j - 1) + ((warp - 4) >> 1)), bv = t28 ? wi : 4 + (warp & 1);
    uint32_t wo1 = sb + OFF_WO + warp * 896 + lane * 16, wo2;
    {
      const int cb = (t28 ? unit28(bi) : unit24(bi)) - col0 / 8;
      uint32_t cp[4];
#pragma unroll
      for (int wd = 0; wd < 4; wd++) {
        int c, p;
        if (bv < 3) { c = 4 * bv + q4; p = wd; }
        else if (bv == 3) { if (q4 & 1) { c = 4 * (wd % 3) + q4; p = 3; } else { c = 12 + (q4 >> 1); p = wd; } }
        else if (bv == 4) { c = q4; p = wd; }
        else { if (wd < 2) { c = 4 + (q4 >> 1); p = 2 * (q4 & 1) + wd; } else { c = q4; p = 3; } }
        cp[wd] = sb + OFF_WO + ((g & 1) + (g & 2) * 4 + (g >> 2) * 2) * WOS + (cb + c) * 16 + p * 4;
      }
      const int cidx = (r8 & 1) + ((r8 >> 2) << 1);
      wo2 = sb + OFF_WO + warp * 896 + ((m4 & 1) ? 768 + (m4 >> 1) * 64 + cidx * 16 : 512 + (m4 >> 1) * 128 + r8 * 16);
      const bool dump = (m4 & 1) && (r8 & 2);
      uint32_t mo = 0;
      const bool regular = bv < 3 || bv == 4;
#pragma unroll 1
      for (int i = 0; i < 3; i++) {
        uint32_t x[4][4], y[4][4];
        const uint32_t o = i * 4 * WOK;
        mbar_wait(sb + MB_R + 8 * i, 0);
        if (regular) {
          static_for<0, 4>([&](auto K) {
            constexpr int kk = K.value;
            const uint4 u = lds128_i<kk * WOK>(cp[0] + o), v = lds128_i<kk * WOK + 4 * WOS>(cp[0] + o);
            x[kk][0] = u.x; x[kk][1] = u.y; x[kk][2] = u.z; x[kk][3] = u.w; y[kk][0] = v.x; y[kk][1] = v.y; y[kk][2] = v.z; y[kk][3] = v.w;
          });
        } else {
          static_for<0, 4>([&](auto K) {
            constexpr int kk = K.value;
#pragma unroll
            for (int wd = 0; wd < 4; wd++) { x[kk][wd] = lds32_i<kk * WOK>(cp[wd] + o); y[kk][wd] = lds32_i<kk * WOK + 4 * WOS>(cp[wd] + o); }
          });
        }
        bar_sync(B_C, 256);
        static_for<0, 4>([&](auto K) {
          constexpr int kk = K.value;
#pragma unroll
          for (int wd = 0; wd < 4; wd++) mo = amax_bf2(mo, amax_bf2(x[kk][wd], y[kk][wd]));
          stsm_x4_t_i<kk * WOK>(wo1 + o, x[kk][0], x[kk][1], y[kk][0], y[kk][1]);
          stsm_x4_t_i<0>(dump ? sb + OFF_S + 512 + lane * 16 : wo2 + o + kk * WOK, x[kk][2], x[kk][3], y[kk][2], y[kk][3]);
        });
      }
      mo = amax_fold(mo);
      if (lane == 0) asm volatile("red.shared.max.u32 [%0], %1;" :: "r"(sb + SC_W + 4), "r"(mo) : "memory");
    }
    __syncwarp();
    auto run = [&](auto HF) {
    constexpr int hf = HF.value;
    uint32_t mema, sta, l16 = sb + lane * 16;
    uint32_t rq[hf ? NQ1 : NQ0][4];
    auto step_addr = [&](uint32_t kv) {
      const int lr = (l16 >> 4) & 7, lm = (l16 >> 7) & 3;
      mema = l16 ^ (lm << 5);
      sta = sb + lr * 16 + (lm < 2 ? OFF_Q + wi * 512 + hf * 128 + lm * 256 : OFF_KV + kv + 512 + (2 * wi + lm - 2) * 640);
    };
    auto x_gemm = [&](uint32_t ph, [[maybe_unused]] uint32_t tsb) {
      float xa[16];
      const uint32_t dlo = (((sb + OFF_X) & 0x3FFFF) >> 4) | (1u << 16);
      constexpr int NP = hf ? NQ1 : NP0;
      if constexpr (hf) {
        static_for<PQE, NP>([&](auto K) { ldsm_x4_t_i<OFF_WQ + K.value * 2048>(rq[K.value], wqa); });
        bar_sync(B_X, 256);
      }
      wgmma_fence();
      static_for<0, 40>([&](auto K) {
        constexpr int k = K.value;
        wgmma_rs32h<((k >> 2) * 4096 + (k & 3) * 32) / 16, (k != 0)>(xa, w[k], dlo);
        if constexpr (!hf && k == PFK && NP > PQE) { SFENCE(wqa); static_for<PQE, NP>([&](auto K) { ldsm_x4_t_i<OFF_WQ + K.value * 2048>(rq[K.value], wqa); }); SFENCE(wqa); }
        if constexpr (!hf && k == XT) bar_arrive(B_X, 256);
      });
      step_addr(ph * (2 * KVB));
      wgmma_commit();
      TS(9);
      wgmma_wait<0>();
      const uint32_t xs = l16 + (wi * 1280 + ph * (2 * KVB));
      stsm_x4_t_i<OFF_KV + hf * KVB>(xs, pack_bf16(xa[0] * iw, xa[1] * iw), pack_bf16(xa[4] * iw, xa[5] * iw), pack_bf16(xa[8] * iw, xa[9] * iw), pack_bf16(xa[12] * iw, xa[13] * iw));
      stsm_x4_t_i<OFF_KV + hf * KVB + 640>(xs, pack_bf16(xa[2] * iw, xa[3] * iw), pack_bf16(xa[6] * iw, xa[7] * iw), pack_bf16(xa[10] * iw, xa[11] * iw), pack_bf16(xa[14] * iw, xa[15] * iw));
    };
    auto wq_addr = [&](uint32_t l) -> uint32_t {
      const int lr = (l >> 4) & 7, lm = (l >> 7) & 3;
      return sb + hf * ((40 - NQ1) * 2048) + (lr + ((lm >> 1) << 3)) * 128 + (((2 * wi + (lm & 1)) ^ lr) << 4);
    };
    constexpr int NPM = hf ? NPM1 : NPM0;
    uint32_t u1[NPM][4], u2[NPM][4];
    static_for<0, NPM>([&](auto K) { ldsm_x4_i<(12 - NPM + K.value) * WOK>(u1[K.value], wo1); ldsm_x4_i<(12 - NPM + K.value) * WOK>(u2[K.value], wo2); });
    bar_sync(0, 384);
    iq = uniform_f(exp2i(-wscale_exp(lds32_i<SC_W + 8>(sb))));
    wqa = wq_addr(l16);
    static_for<0, (hf ? NQ1 : NP0)>([&](auto K) { ldsm_x4_t_i<OFF_WQ + K.value * 2048>(rq[K.value], wqa); });
    step_addr(0);
    stsm_x4_t_i<OFF_KV + hf * KVB>(l16 + wi * 1280, x0[0], x0[2], x0[4], x0[6]);
    stsm_x4_t_i<OFF_KV + hf * KVB + 640>(l16 + wi * 1280, x0[1], x0[3], x0[5], x0[7]);
    asm volatile("barrier.cluster.wait.aligned;" ::: "memory");
    TL_END(a.tl + 1);
#pragma unroll 1
    for (int s = 0; s < cfg::NSEG; s++) {
      TS_SETUP();
      const bool last = s == cfg::NSEG - 1;
      bar_sync(hf ? B_MEM1 : B_MEM0, 256);
      const float sin_ = __uint_as_float(lds32_i<SC_IN>(sb + 16 * (s & 1)));
      constexpr int NPQ = (40 - NQ1) / 2;
      if constexpr (hf == 0) {
        float k0[4] = {0, 0, 0, 0}, k1[4] = {0, 0, 0, 0}, q0[4] = {0, 0, 0, 0}, q1[4] = {0, 0, 0, 0};
        constexpr auto pair_of = [](int t) { const int a = t * (20 - NPQ) / 20, b = (t + 1) * (20 - NPQ) / 20; return b > a ? NPQ + a : t - a; };
        uint32_t b[NB0][4];
        static_for<0, NB0>([&](auto T) { ldsm_x4_i<OFF_MEM + pair_of(T.value) * 512>(b[T.value], mema); });
        static_for<NP0, NQ0>([&](auto K) { ldsm_x4_t_i<OFF_WQ + K.value * 2048>(rq[K.value], wqa); });
        if (BBS < 100) bbfence<0>(mema);
        static_for<0, 20>([&](auto T) {
          constexpr int t = T.value, p = pair_of(t);
          uint32_t (&bb)[4] = b[t % NB0];
          if constexpr (p < NPQ) {
            mma16816h(q0, rq[(2 * p) % NQ0], bb[0], bb[1]);
            if constexpr (2 * p + NQ0 < 2 * NPQ) ldsm_x4_t_i<OFF_WQ + (2 * p + NQ0) * 2048>(rq[(2 * p) % NQ0], wqa);
          }
          mma16816h(k0, w[2 * p], bb[0], bb[1]);
          if constexpr (p < NPQ) {
            mma16816h(q1, rq[(2 * p + 1) % NQ0], bb[2], bb[3]);
            if constexpr (2 * p + 1 + NQ0 < 2 * NPQ) ldsm_x4_t_i<OFF_WQ + (2 * p + 1 + NQ0) * 2048>(rq[(2 * p + 1) % NQ0], wqa);
          }
          mma16816h(k1, w[2 * p + 1], bb[2], bb[3]);
          if constexpr (t + NB0 < 20) ldsm_x4_i<OFF_MEM + pair_of(t + NB0) * 512>(bb, mema);
          if constexpr (t < 20 - NB0 && (t % BBS) == BBS - 1) bbfence<t + 1>(mema);
        });
        const float sq = sin_ * iq, sk = sin_ * iw;
        stsm_x4_t_i<0>(sta, pack_bf16((q0[0] + q1[0]) * sq, (q0[1] + q1[1]) * sq), pack_bf16((q0[2] + q1[2]) * sq, (q0[3] + q1[3]) * sq),
                       pack_bf16((k0[0] + k1[0]) * sk, (k0[1] + k1[1]) * sk), pack_bf16((k0[2] + k1[2]) * sk, (k0[3] + k1[3]) * sk));
        TS(2);
        if (!last) {
          if (wi == 3) {
            const uint32_t s8 = sb + ((l16 & 511) >> 1), xr = sb + ((l16 & 511) >> 2), ka = l16 + (l16 & 384) * 4 + (s & 1) * (2 * KVB);
            bar_sync(B_QK, 384);
            uint32_t a0[4], a1[4], a2[4], a3[4], kb0[4], kb1[4];
            ldsm_x4_i<OFF_Q>(a0, l16); ldsm_x4_i<OFF_KV + 512>(kb0, ka); ldsm_x4_i<OFF_Q + 1024>(a2, l16); ldsm_x4_i<OFF_KV + 512 + 2560>(kb1, ka);
            ldsm_x4_i<OFF_Q + 512>(a1, l16);
            bar_arrive(B_A, 288);
            ldsm_x4_i<OFF_Q + 1536>(a3, l16);
            float sa[4] = {0, 0, 0, 0}, sc2[4] = {0, 0, 0, 0};
            mma16816(sa, a0[0], a0[1], a0[2], a0[3], kb0[0], kb0[1]);
            mma16816(sc2, a2[0], a2[1], a2[2], a2[3], kb1[0], kb1[1]);
            mma16816(sa, a1[0], a1[1], a1[2], a1[3], kb0[2], kb0[3]);
            mma16816(sc2, a3[0], a3[1], a3[2], a3[3], kb1[2], kb1[3]);
            const float x0 = (sa[0] + sa[2]) + (sc2[0] + sc2[2]), x1 = (sa[1] + sa[3]) + (sc2[1] + sc2[3]);
            const uint32_t xp = pack_bf16(x0, x1);
            st_async_b32_i<OFF_SR + 1024 + 256>(xr + d1, xp, sb + MB_S + d1);
            st_async_b32_i<OFF_SR + 1024>(xr + d2, xp, sb + MB_S + d2);
            sts64_i<OFF_S + 1024>(s8, __float_as_uint(x0), __float_as_uint(x1));
          } else {
            bar_arrive(B_QK, 384);
          }
          bar_sync(B_SL, 256);
        }
      } else {
        float v0[4] = {0, 0, 0, 0}, v1[4] = {0, 0, 0, 0}, q0[4] = {0, 0, 0, 0}, q1[4] = {0, 0, 0, 0};
        uint32_t b[NQ1 / 2][4];
        static_for<0, NQ1 / 2>([&](auto T) { ldsm_x4_i<OFF_MEM + (NPQ + T.value) * 512>(b[T.value], mema); });
        static_for<0, NQ1 / 2>([&](auto T) {
          constexpr int t = T.value, p = NPQ + t;
          uint32_t (&bb)[4] = b[t];
          mma16816h(q0, rq[2 * t], bb[0], bb[1]);
          mma16816h(q1, rq[2 * t + 1], bb[2], bb[3]);
          mma16816h(v0, w[2 * p], bb[0], bb[1]);
          mma16816h(v1, w[2 * p + 1], bb[2], bb[3]);
        });
        const float sq = sin_ * iq, sv = sin_ * iw;
        stsm_x2_t_i<0>(sta, pack_bf16((q0[0] + q1[0]) * sq, (q0[1] + q1[1]) * sq), pack_bf16((q0[2] + q1[2]) * sq, (q0[3] + q1[3]) * sq));
        TS(2);
        if (!last) { bar_arrive(B_QK, 384); bar_sync(B_A, 288); }
        float v2[4] = {0, 0, 0, 0}, v3[4] = {0, 0, 0, 0};
        uint32_t c[4][4];
        static_for<0, 4>([&](auto T) { ldsm_x4_i<OFF_MEM + T.value * 512>(c[T.value], mema); });
        static_for<0, NPQ>([&](auto T) {
          constexpr int p = T.value;
          uint32_t (&bb)[4] = c[p & 3];
          if constexpr (p & 1) { mma16816h(v0, w[2 * p], bb[0], bb[1]); mma16816h(v1, w[2 * p + 1], bb[2], bb[3]); }
          else { mma16816h(v2, w[2 * p], bb[0], bb[1]); mma16816h(v3, w[2 * p + 1], bb[2], bb[3]); }
          if constexpr (p + 4 < NPQ) ldsm_x4_i<OFF_MEM + (p + 4) * 512>(bb, mema);
        });
        stsm_x2_t_i<OFF_KV + KVB + 512>(l16 + (l16 & 128) * 4 + (wi * 1280 + (s & 1) * (2 * KVB)), pack_bf16(((v0[0] + v1[0]) + (v2[0] + v3[0])) * sv, ((v0[1] + v1[1]) + (v2[1] + v3[1])) * sv),
                            pack_bf16(((v0[2] + v1[2]) + (v2[2] + v3[2])) * sv, ((v0[3] + v1[3]) + (v2[3] + v3[3])) * sv));
        if (!last) bar_arrive(B_V, 256);
      }
      TS(3);
      if (last) break;
      {
        uint32_t t1[12][4], t2[12][4];
        const uint32_t o16 = l16;
        wo1 = l16 + (OFF_WO + warp * 896);
        wo2 = sb + OFF_WO + warp * 896 + ((l16 & 128) ? 768 + ((l16 & 256) >> 2) + (l16 & 16) + ((l16 & 64) >> 1) : 512 + ((l16 & 256) >> 1) + (l16 & 112));
        auto ldw = [&](auto K) { if constexpr (K.value < 12 - NPM) { ldsm_x4_i<K.value * WOK>(t1[K.value], wo1); ldsm_x4_i<K.value * WOK>(t2[K.value], wo2); } };
        constexpr int NR_ = NRT - NPM;
        constexpr int PB = (hf ? PB1 : PB0) < NR_ ? (hf ? PB1 : PB0) : NR_, PA = (hf ? PA1 : PA0) < PB ? (hf ? PA1 : PA0) : PB;
        static_for<0, PA>(ldw);
        mbar_spin(sb + MB_X, (s + 1) & 1);
        if constexpr (PB > PA) bar_sync(B_G, 384); else bar_arrive(B_G, 384);
        static_for<PA, PB>(ldw);
        float c0[4] = {0, 0, 0, 0}, c1[4] = {0, 0, 0, 0}, e0[4] = {0, 0, 0, 0}, e1[4] = {0, 0, 0, 0};
        uint32_t ob[6][4];
        auto kstep = [&](auto K) {
          constexpr int k = K.value;
          uint32_t (&bb)[4] = ob[k >> 1];
          uint32_t (&x)[4] = k < 12 - NPM ? t1[k] : u1[k < 12 - NPM ? 0 : k - (12 - NPM)];
          uint32_t (&y)[4] = k < 12 - NPM ? t2[k] : u2[k < 12 - NPM ? 0 : k - (12 - NPM)];
          if constexpr (k & 1) { mma16816(c1, x[0], x[1], x[2], x[3], bb[2], bb[3]); mma16816(e1, y[0], y[1], y[2], y[3], bb[2], bb[3]); }
          else { mma16816(c0, x[0], x[1], x[2], x[3], bb[0], bb[1]); mma16816(e0, y[0], y[1], y[2], y[3], bb[0], bb[1]); }
          if constexpr (k >= NRF) ldw(IC<k + NR_ - NRF>{});
        };
        auto ldo = [&](auto P) { ldsm_x4_i<OFF_O + P.value * 512>(ob[P.value], o16); };
        TS(4);
        bar_sync(B_O, 384);
        ldo(IC<0>{}); ldo(IC<1>{});
        SFENCE(o16);
        static_for<PB, NR_>(ldw);
        static_for<0, 4>(kstep);
        TS(5);
        mbar_spin(sb + MB_O, s & 1);
        TS(6);
        ldo(IC<2>{}); ldo(IC<NPM >= 2 ? 5 : 3>{});
        if (WOF) SFENCE(o16);
        kstep(IC<4>{});
        if constexpr (NPM < 2) { kstep(IC<5>{}); ldo(IC<4>{}); kstep(IC<6>{}); kstep(IC<7>{}); ldo(IC<5>{}); static_for<8, 12>(kstep); }
        else if constexpr (NPM >= 4) { kstep(IC<10>{}); kstep(IC<11>{}); ldo(IC<4>{}); kstep(IC<5>{}); ldo(IC<3>{}); kstep(IC<8>{}); kstep(IC<9>{}); kstep(IC<6>{}); kstep(IC<7>{}); }
        else { kstep(IC<5>{}); ldo(IC<3>{}); kstep(IC<11>{}); kstep(IC<10>{}); ldo(IC<4>{}); kstep(IC<6>{}); kstep(IC<7>{}); if constexpr (NPM == 3) { kstep(IC<9>{}); kstep(IC<8>{}); } else { kstep(IC<8>{}); kstep(IC<9>{}); } }
        l16 = fresh(l16);
        const int ln = (l16 >> 4) & 31;
        unsigned char* gr = arena + (AR_ACC + acc_lane(bi, ln) + acc_voff(bv) + acc_step(s));
        const bool cnt = (ln & 1) || !t28;
        wqa = wq_addr(l16);
        SFENCE(o16);
        static_for<0, PQE>([&](auto K) { ldsm_x4_t_i<OFF_WQ + K.value * 2048>(rq[K.value], wqa); });
        const uint32_t y0 = movm_t(pack_f16(c0[0] + c1[0], c0[1] + c1[1])), y1 = movm_t(pack_f16(c0[2] + c1[2], c0[3] + c1[3]));
        const uint32_t y2 = movm_t(pack_f16(e0[0] + e1[0], e0[1] + e1[1])), y3 = movm_t(pack_f16(e0[2] + e1[2], e0[3] + e1[3]));
        asm volatile("red.relaxed.gpu.global.add.noftz.v4.f16x2 [%0], {%1,%2,%3,%4};" :: "l"(gr), "r"(y0), "r"(y1), "r"(y2), "r"(cnt ? 0x3c00u : y3) : "memory");
        if constexpr (hf || RSYNC) bar_sync(B_RED, 384); else bar_arrive(B_RED, 384);
        TS(7);
      }
      x_gemm((s + 1) & 1, 0);
      TS(8);
    }
    };
    if (hf == 0) run(IC<0>{}); else run(IC<1>{});
    bar_arrive(B_RED, 384);
    asm volatile("barrier.cluster.arrive.relaxed.aligned; barrier.cluster.wait.aligned;" ::: "memory");
  }
}
struct PrepArgs { const bf16 *wqkv, *wphi, *wo; bf16 *wb, *wot; };
constexpr int PREP_TASKS = 3840;
__device__ __forceinline__ void prep_body(const int b, const bf16* __restrict__ wqkv, const bf16* __restrict__ wphi, const bf16* __restrict__ wo,
                                          bf16* __restrict__ wb, bf16* __restrict__ wot) {
  const int task = b, lane = threadIdx.x & 31;
  if (task < 1920) {
    const int which = task / 640, h = (task / 20) % 32, k = (task % 20) * 32 + lane;
    const int row0 = 288 * (h >> 2) + 96 * which + 24 * (h & 3);
    const uint2* src = (const uint2*)(wqkv + (size_t)k * 1920 + which * 640 + h * 20);
    float w[20];
#pragma unroll
    for (int d = 0; d < 5; d++) { const uint2 t = __ldg(src + d); w[4 * d] = bf_lo(t.x); w[4 * d + 1] = bf_hi(t.x); w[4 * d + 2] = bf_lo(t.y); w[4 * d + 3] = bf_hi(t.y); }
    if (which < 2) {
      float a[20];
#pragma unroll
      for (int f = 0; f < 20; f++) a[f] = 0.f;
      const uint32_t* ph = (const uint32_t*)(wphi + h * 400);
#pragma unroll
      for (int d = 0; d < 20; d++)
#pragma unroll
        for (int f = 0; f < 10; f++) { const uint32_t t = __ldg(ph + d * 10 + f); a[2 * f] = fmaf(w[d], bf_lo(t), a[2 * f]); a[2 * f + 1] = fmaf(w[d], bf_hi(t), a[2 * f + 1]); }
#pragma unroll
      for (int f = 0; f < 20; f++) wb[(size_t)(row0 + f) * cfg::DM + k] = __float2bfloat16_rn(a[f]);
    } else {
#pragma unroll
      for (int d = 0; d < 20; d++) wb[(size_t)(row0 + d) * cfg::DM + k] = __float2bfloat16_rn(w[d]);
    }
#pragma unroll
    for (int f = 20; f < 24; f++) wb[(size_t)(row0 + f) * cfg::DM + k] = __float2bfloat16_rn(0.f);
  } else {
    const int t = task - 1920, n = (t % 20) * 32 + lane, kk0 = (t / 20) * 8, h = kk0 / 24, d0 = kk0 % 24;
    unsigned short v[8];
#pragma unroll
    for (int e = 0; e < 8; e++) v[e] = (d0 + e < 20) ? __ldg((const unsigned short*)wo + (size_t)(h * 20 + d0 + e) * cfg::DM + n) : (unsigned short)0;
    *(uint4*)(wot + (size_t)n * 768 + kk0) = make_uint4(v[0] | (v[1] << 16), v[2] | (v[3] << 16), v[4] | (v[5] << 16), v[6] | (v[7] << 16));
  }
}

__global__ void __launch_bounds__(256, 4) ln_kernel(const bf16* __restrict__ xin, bf16* __restrict__ xn, uint2* __restrict__ xh, uint4* __restrict__ z0, int n0,
                                                    uint4* __restrict__ z1, int n1, const bf16* pfa, const bf16* pfb, int npf, int tl) {
  asm volatile("griddepcontrol.wait;" ::: "memory");
  asm volatile("griddepcontrol.launch_dependents;" ::: "memory");
  TL_BEGIN(tl);
  const int warp = threadIdx.x >> 5, lane = threadIdx.x & 31;
  const int row = blockIdx.x * 8 + warp;
  uint2 xw[1][5];
#pragma unroll
  for (int i = 0; i < 5; i++) xw[0][i] = *(const uint2*)(xin + (size_t)row * cfg::DM + i * 128 + lane * 4);
  for (int i = blockIdx.x * 256 + threadIdx.x; i < n0; i += 256 * 256) z0[i] = make_uint4(0, 0, 0, 0);
  for (int i = blockIdx.x * 256 + threadIdx.x; i < n1; i += 256 * 256) z1[i] = make_uint4(0, 0, 0, 0);
  if (npf && xw[0][4].y != 0x7fc17fc1u) {
    for (int i = 0; i < npf; i++) {
      const uint32_t l = (uint32_t)i * 32768u + (blockIdx.x * 256 + threadIdx.x) / 2;
      if (l < cfg::DM * cfg::HD / 64) asm volatile("prefetch.global.L2 [%0];" :: "l"(((threadIdx.x & 1) ? pfa : pfb) + (size_t)l * 64) : "memory");
    }
  }
  ln_rows<1>(xw, row, lane, xn, xh);
  TL_END(tl);
}
struct Pipe { uint32_t stage, phase; };
template <int NS> __device__ __forceinline__ void pipe_adv(Pipe& p) { if (++p.stage == NS) { p.stage = 0; p.phase ^= 1; } }
constexpr uint32_t SWZ128 = 1;
__device__ __forceinline__ uint64_t desc_kmajor(uint32_t a) { return make_desc(a, 16, 1024, SWZ128); }
__device__ __forceinline__ uint64_t desc_mnmajor(uint32_t a) { return make_desc(a, 8192, 1024, SWZ128); }
__device__ __forceinline__ void wait_ge(const void* p, uint32_t target) {
  int spin = 0;
  while (ld_acquire_u32(p) < target) { __nanosleep(32); if (++spin > (1 << 23)) break; }
}
__device__ __forceinline__ void bulk_g2s_hint(uint32_t dst, const void* src, uint32_t bytes, uint32_t mb, uint64_t pol) {
  asm volatile("cp.async.bulk.shared::cluster.global.mbarrier::complete_tx::bytes.L2::cache_hint [%0], [%1], %2, [%3], %4;"
               :: "r"(dst), "l"(src), "r"(bytes), "r"(mb), "l"(pol) : "memory");
}
#define STAG 1
#define EF_KV 1
#define EF_O 1
__device__ __forceinline__ void fence_proxy_async_global() { asm volatile("fence.proxy.async.global;" ::: "memory"); }

namespace tr {
constexpr int NS = 4, STQ = 16384 + 24576, STO = 16384 + 40960;
constexpr int SEGB = 15360;
constexpr int OFF_K = NS * STQ;
constexpr int OFF_BAR = NS * STO;
constexpr int SMEM = OFF_BAR + 256;
static_assert(OFF_K + 4 * SEGB <= OFF_BAR && SMEM <= 232448, "smem");
enum { T_QA = 0, T_Q, T_A, T_OB, T_OS, T_L, T_END };
constexpr uint32_t C_QA = AR_CNT, C_O = AR_CNT + 64, C_Q = AR_CNT + 128;
struct Sched {
  uint16_t start[96];
  uint8_t type[96], blk[96];
  uint8_t ks[16];
  uint8_t wide[16];
  uint8_t lrows[16];
};
struct Args {
  const unsigned char *kg, *vg;
  unsigned char* o;
  uint4* qs;
  unsigned char* part;
  const bf16* xin;
  bf16 *xout, *xn;
  unsigned char* arena;
  int doprep, tl;
};
}

template <int N0, int N1>
__device__ __forceinline__ void tr_mainloop(float (&a0)[N0 / 2], float (&a1)[N1 ? N1 / 2 : 1], Pipe& p, uint32_t sb, uint32_t full, uint32_t empty, int nkb, int wg) {
  using namespace tr;
  constexpr uint32_t ST = N1 ? STO : STQ;
  uint32_t prev = 0;
#pragma unroll
  for (int i = 0; i < N0 / 2; i++) a0[i] = 0.f;
  if constexpr (N1 > 0) {
#pragma unroll
    for (int i = 0; i < N1 / 2; i++) a1[i] = 0.f;
  }
  for (int kb = 0; kb < nkb; kb++) {
    mbar_wait(full + 8 * p.stage, p.phase);
    const uint32_t st = sb + p.stage * ST;
    wgmma_fence();
#pragma unroll
    for (int kk = 0; kk < 4; kk++) {
      const uint64_t da = desc_kmajor(st + wg * 8192 + kk * 32);
      if constexpr (N0 == 192) wgmma_n192<0, 1>(a0, da, desc_mnmajor(st + 16384 + kk * 2048), (kb | kk) != 0);
      else wgmma_n128<0, 1>(a0, da, desc_mnmajor(st + 16384 + kk * 2048), (kb | kk) != 0);
      if constexpr (N1 > 0) wgmma_n128<0, 1>(a1, da, desc_mnmajor(st + 16384 + 24576 + kk * 2048), (kb | kk) != 0);
    }
    wgmma_commit();
    if (kb > 0) { wgmma_wait<1>(); mbar_arrive_if((threadIdx.x & 127) == 0, empty + 8 * prev); }
    prev = p.stage;
    pipe_adv<NS>(p);
  }
  wgmma_wait<0>();
  mbar_arrive_if((threadIdx.x & 127) == 0, empty + 8 * prev);
}
template <int N> __device__ __forceinline__ void stage_tiles(const float (&o)[N / 2], uint32_t base, int wi, int lane) {
  const uint32_t ra = base + (wi * 16 + (lane & 7) + 8 * ((lane >> 3) & 1)) * 128;
#pragma unroll
  for (int v = 0; v < N / 8; v += 2)
    stsm_x4(ra + (v >> 3) * 8192 + ((((v & 7) + (lane >> 4)) ^ (lane & 7)) << 4), pack_bf16(o[4 * v], o[4 * v + 1]), pack_bf16(o[4 * v + 2], o[4 * v + 3]),
            pack_bf16(o[4 * v + 4], o[4 * v + 5]), pack_bf16(o[4 * v + 6], o[4 * v + 7]));
}
template <int R, int NP> __device__ __forceinline__ void l_rows(const tr::Args& a, int row0, int np, int lane) {
  uint2 xw[R][5]; float s[R][20];
#pragma unroll
  for (int r = 0; r < R; r++)
#pragma unroll
    for (int i = 0; i < 5; i++) {
      xw[r][i] = __ldcg((const uint2*)(a.xin + (size_t)(row0 + r) * cfg::DM + i * 128 + lane * 4));
      s[r][4 * i] = s[r][4 * i + 1] = s[r][4 * i + 2] = s[r][4 * i + 3] = 0.f;
    }
  for (int p0 = 0; p0 < np; p0 += NP) {
    uint2 t[R][NP][5];
#pragma unroll
    for (int r = 0; r < R; r++) {
      const int row = row0 + r;
      const unsigned char* pp = a.part + (size_t)(row >> 6) * 81920 + (lane >> 4) * 8192 + (row & 63) * 128 + ((((lane >> 1) & 7) ^ (row & 7)) << 4) + (lane & 1) * 8;
#pragma unroll
      for (int q = 0; q < NP; q++)
#pragma unroll
        for (int i = 0; i < 5; i++) t[r][q][i] = p0 + q < np ? __ldcg((const uint2*)(pp + (size_t)(p0 + q) * (32 * 81920) + i * 16384)) : make_uint2(0, 0);
    }
#pragma unroll
    for (int r = 0; r < R; r++)
#pragma unroll
      for (int q = 0; q < NP; q++)
#pragma unroll
        for (int i = 0; i < 5; i++) { s[r][4 * i] += bf_lo(t[r][q][i].x); s[r][4 * i + 1] += bf_hi(t[r][q][i].x); s[r][4 * i + 2] += bf_lo(t[r][q][i].y); s[r][4 * i + 3] += bf_hi(t[r][q][i].y); }
  }
#pragma unroll
  for (int r = 0; r < R; r++) {
#pragma unroll
    for (int i = 0; i < 5; i++) {
      xw[r][i] = make_uint2(pack_bf16(bf_lo(xw[r][i].x) + bf16r(s[r][4 * i]), bf_hi(xw[r][i].x) + bf16r(s[r][4 * i + 1])),
                            pack_bf16(bf_lo(xw[r][i].y) + bf16r(s[r][4 * i + 2]), bf_hi(xw[r][i].y) + bf16r(s[r][4 * i + 3])));
      *(uint2*)(a.xout + (size_t)(row0 + r) * cfg::DM + i * 128 + lane * 4) = xw[r][i];
    }
  }
  ln_rows<R>(xw, row0, lane, a.xn, nullptr);
}

__global__ void __launch_bounds__(384, 1) trail_kernel(const __grid_constant__ CUtensorMap tmX, const __grid_constant__ CUtensorMap tmQ,
                                                       const __grid_constant__ CUtensorMap tmWo5, const __grid_constant__ CUtensorMap tmWo2, const __grid_constant__ tr::Sched sc,
                                                       const __grid_constant__ tr::Args a, const __grid_constant__ PrepArgs pa) {
  using namespace tr;
  [[maybe_unused]] const int tl = a.tl;
  TL_BEGIN(tl);
  extern __shared__ __align__(1024) unsigned char smem_raw[];
  const uint32_t sb = smem_u32(smem_raw);
  const int warp = __shfl_sync(0xffffffffu, (int)threadIdx.x >> 5, 0), lane = threadIdx.x & 31;
  unsigned char* const arena = a.arena;
  const uint32_t full = sb + OFF_BAR, empty = full + 8 * NS, barK = empty + 8 * NS, barKfree = barK + 16, staged = barKfree + 16;
  const uint32_t kvrdy = staged + 32, mfull = kvrdy + 8, mempty = mfull + 16, mbox = mempty + 16;
  if (threadIdx.x == 0) {
    for (int i = 0; i < NS; i++) { mbar_init(full + 8 * i, 1); mbar_init(empty + 8 * i, 2); }
    for (int i = 0; i < 2; i++) {
      mbar_init(barK + 8 * i, 1); mbar_init(barKfree + 8 * i, 1); mbar_init(staged + 16 * i, 4); mbar_init(staged + 16 * i + 8, 4);
      mbar_init(mfull + 8 * i, 1); mbar_init(mempty + 8 * i, 11);
    }
    mbar_init(kvrdy, 1);
    asm volatile("fence.mbarrier_init.release.cluster;" ::: "memory");
  }
  __syncthreads();
  Pipe mp{0, 0};
  auto next_item = [&]() -> uint32_t {
    uint32_t it;
    mbar_wait(mfull + 8 * mp.stage, mp.phase);
    asm volatile("ld.shared.u32 %0, [%1];" : "=r"(it) : "r"(mbox + 4 * mp.stage) : "memory");
    return it;
  };
  if (warp >= 8) {
    asm volatile("setmaxnreg.dec.sync.aligned.u32 40;");
    if (warp == 8) { if (elect_one()) {
      Pipe p{0, 1};
      mp.phase = 1;
      uint32_t kph = 1, wide = 0;
      int g = 0;
      const uint64_t ef = policy_evict_first();
      auto ld_kv = [&](uint32_t d, const void* s, uint32_t n, uint32_t mb) { if (EF_KV) bulk_g2s_hint(d, s, n, mb, ef); else bulk_g2s(d, s, n, mb); };
      auto ld_o = [&](uint32_t d, const void* s, uint32_t n, uint32_t mb) { if (EF_O) bulk_g2s_hint(d, s, n, mb, ef); else bulk_g2s(d, s, n, mb); };
      auto stage = [&](uint32_t bytes) -> uint32_t {
        mbar_wait(empty + 8 * p.stage, p.phase);
        mbar_expect_tx(full + 8 * p.stage, bytes);
        return sb + p.stage * (wide ? STO : STQ);
      };
      auto fetch = [&]() -> uint32_t { uint32_t v; asm volatile("atom.relaxed.gpu.global.add.u32 %0, [%1], 1;" : "=r"(v) : "l"(arena + AR_QUEUE) : "memory"); return v; };
      uint32_t next = fetch();
      while (true) {
        const uint32_t item = next;
        while (item >= sc.start[g + 1] && sc.type[g] != T_END) g++;
        const int type = sc.type[g], m = sc.blk[g], k = item - sc.start[g];
        if (type == T_L) { wait_ge(arena + C_O + m * 4, sc.ks[m] * (sc.wide[m] ? 4 : 10)); }
        if (type == T_A) wait_ge(arena + C_Q + m * 4, 64);
        if (type < T_L && wide != (type == T_OB)) {
          for (uint32_t i = 0; i < NS; i++) mbar_wait(empty + 8 * i, i >= p.stage ? p.phase : p.phase ^ 1);
          mbar_wait(barKfree, kph); mbar_wait(barKfree + 8, kph);
          wide = type == T_OB;
        }
        mbar_wait(mempty + 8 * mp.stage, mp.phase);
        asm volatile("st.shared.u32 [%0], %1;" :: "r"(mbox + 4 * mp.stage), "r"((p.stage << 24) | (type << 16) | (m << 8) | (k & 255)) : "memory");
        mbar_arrive(mfull + 8 * mp.stage);
        pipe_adv<2>(mp);
        if (type == T_END) break;
        if (type == T_L) { next = fetch(); continue; }
        if (type <= T_A) {
          if (type != T_A)
#pragma unroll 1
            for (int kb = 0; kb < 10; kb++) {
              const uint32_t st = stage(STQ), fb = full + 8 * p.stage;
              tma_load_2d(st, &tmX, kb * 64, m * 128, fb);
              tma_load_3d(st + 16384, &tmQ, 0, kb * 64, k * 3, fb);
              pipe_adv<NS>(p);
              if (type == T_Q && kb == 8) next = fetch();
            }
          if (type != T_Q) {
            const size_t blk = ((size_t)m * 4 * 96 + k * 3) * 5120;
            kph ^= 1;
            mbar_wait(kvrdy, kph);
            next = fetch();
            fence_proxy_async_global();
#pragma unroll 1
            for (int w = type == T_A ? 0 : 2; w < 4; w++) {
              const uint32_t st = stage(2 * SEGB), fb = full + 8 * p.stage;
              for (int sg = 0; sg < 2; sg++) ld_kv(st + sg * SEGB, (w < 2 ? a.kg : a.vg) + blk + (size_t)(2 * (w & 1) + sg) * (96 * 5120), SEGB, fb);
              pipe_adv<NS>(p);
            }
          }
        } else {
          const int nn = wide ? 2 : 5, nb = wide ? 5 : 2, nt = k % nn, nkb = 96 / sc.ks[m], k0 = (k / nn) * nkb;
          const Pipe p0 = p;
          for (int kb = 0; kb < nkb; kb++) {
            const uint32_t st = stage(16384 + nb * 8192), fb = full + 8 * p.stage;
            tma_load_3d(st + 16384, wide ? &tmWo5 : &tmWo2, 0, (k0 + kb) * 64, nt * nb, fb);
            if (kb >= NS) ld_o(st, a.o + ((size_t)m * 96 + k0 + kb) * 16384, 16384, fb);
            pipe_adv<NS>(p);
            if (kb == NS - 1 || (kb == nkb - 1 && nkb < NS)) {
              wait_ge(arena + C_QA + m * 4, 64);
              fence_proxy_async_global();
              Pipe q = p0;
#pragma unroll 1
              for (int i = 0; i <= kb; i++) { ld_o(sb + q.stage * (wide ? STO : STQ), a.o + ((size_t)m * 96 + k0 + i) * 16384, 16384, full + 8 * q.stage); pipe_adv<NS>(q); }
            }
          }
          next = fetch();
          for (int w = 0; w < 2; w++) { mbar_wait(empty + 8 * p.stage, p.phase); mbar_arrive(full + 8 * p.stage); pipe_adv<NS>(p); }
        }
      }
    } } else if (warp < 11) { if (elect_one()) {
      const int w = warp - 9;
      uint32_t sph = 0;
      [[maybe_unused]] int nlog = 0;
      while (true) {
        const uint32_t it = next_item();
        const int type = (it >> 16) & 255, m = (it >> 8) & 255, k = it & 255;
        const uint32_t slot = mp.stage;
        pipe_adv<2>(mp);
        if (type == T_END) break;
        mbar_wait(staged + 16 * w + 8 * slot, (sph >> slot) & 1); sph ^= 1u << slot;
        mbar_arrive(mempty + 8 * slot);
        if (type == T_L) continue;
        if (type == T_QA || type == T_A) {
          for (int jj = 0; jj < 3; jj++) bulk_s2g(a.o + ((size_t)m * 96 + k * 3 + jj) * 16384 + w * 8192, sb + OFF_K + w * 2 * SEGB + jj * 8192, 8192);
          bulk_commit();
          bulk_wait<0>();
          mbar_arrive(barKfree + 8 * w);
        } else if (type >= T_OB) {
          const bool wide = type == T_OB;
          const int nn = wide ? 2 : 5, nb = wide ? 5 : 2;
          const uint32_t own = ((it >> 24) + 96 / sc.ks[m] + w) % NS;
          bulk_s2g(a.part + ((size_t)((k / nn) * 32 + m * 2 + w) * 10 + (k % nn) * nb) * 8192, sb + own * (wide ? STO : STQ), nb * 8192);
          bulk_commit();
          bulk_wait<0>();
          mbar_arrive(empty + 8 * own);
        }
        asm volatile("red.release.gpu.global.add.u32 [%0], 1;" :: "l"(arena + (type == T_Q ? C_Q : (type <= T_A ? C_QA : C_O)) + m * 4) : "memory");
      }
    } } else if (elect_one()) {
      const uint64_t ef = policy_evict_first();
      uint32_t kph = 1;
      while (true) {
        const uint32_t it = next_item();
        const int type = (it >> 16) & 255, m = (it >> 8) & 255, k = it & 255;
        const uint32_t slot = mp.stage;
        pipe_adv<2>(mp);
        if (type == T_END) break;
        if (type == T_QA || type == T_A) {
          for (int jj = 0; jj < 3; jj++) wait_ge(arena + AR_PROG + (k * 3 + jj) * 4, 4 * m + 4);
          mbar_arrive(kvrdy);
          fence_proxy_async_global();
          const unsigned char* src = a.kg + ((size_t)m * 4 * 96 + k * 3) * 5120;
#pragma unroll 1
          for (int w = 0; w < 2; w++) {
            mbar_wait(barKfree + 8 * w, kph);
            if (type == T_A) { mbar_arrive(barK + 8 * w); continue; }
            mbar_expect_tx(barK + 8 * w, 2 * SEGB);
            for (int sg = 2 * w; sg < 2 * w + 2; sg++) bulk_g2s_hint(sb + OFF_K + sg * SEGB, src + (size_t)sg * (96 * 5120), SEGB, barK + 8 * w, ef);
          }
          kph ^= 1;
        }
        mbar_arrive(mempty + 8 * slot);
      }
    }
    __syncwarp();
    if (blockIdx.x == gridDim.x - 1 && warp == 11) asm volatile("griddepcontrol.wait;" ::: "memory");
    return;
  }
  asm volatile("setmaxnreg.inc.sync.aligned.u32 232;");
  const int wg = warp >> 2, wi = warp & 3;
  const int g = lane >> 2, q4 = lane & 3;
  if (a.doprep && blockIdx.x < 32) for (int t = blockIdx.x * 8 + warp; t < PREP_TASKS; t += 256) prep_body(t, pa.wqkv, pa.wphi, pa.wo, pa.wb, pa.wot);
  bar_sync(2, 256);
  Pipe p{0, 0};
  uint32_t kph = 0;
  auto own_slot = [&]() -> uint32_t {
    const uint32_t sA = p.stage, phA = p.phase; pipe_adv<NS>(p);
    const uint32_t sB = p.stage, phB = p.phase; pipe_adv<NS>(p);
    mbar_wait(full + 8 * sA, phA); mbar_wait(full + 8 * sB, phB);
    mbar_arrive_if((threadIdx.x & 127) == 0, empty + 8 * (wg ? sA : sB));
    return wg ? sB : sA;
  };
  while (true) {
    const uint32_t it = __shfl_sync(0xffffffffu, next_item(), 0);
    const int type = (it >> 16) & 255, m = (it >> 8) & 255, k = it & 255;
    mbar_arrive_if(lane == 0, mempty + 8 * mp.stage);
    const uint32_t done = staged + 16 * wg + 8 * mp.stage;
    pipe_adv<2>(mp);
    if (type == T_END) break;
    if (type == T_L) {
      const int nr = sc.lrows[m], np = sc.ks[m], row0 = m * 128 + (k * 8 + warp) * nr;
      if (nr == 1) l_rows<1, 12>(a, row0, np, lane);
      else for (int r = 0; r < nr; r += 2) l_rows<2, 4>(a, row0 + r, np, lane);
      __syncwarp();
      mbar_arrive_if(lane == 0, done);
      continue;
    }
    if (type >= T_OB) {
      const int nkb = 96 / sc.ks[m];
      if (type == T_OB) {
        float a0[96], a1[64];
        tr_mainloop<192, 128>(a0, a1, p, sb, full, empty, nkb, wg);
        const uint32_t st = sb + own_slot() * STO;
        stage_tiles<192>(a0, st, wi, lane); stage_tiles<128>(a1, st + 24576, wi, lane);
      } else {
        float a0[64], a1[1];
        tr_mainloop<128, 0>(a0, a1, p, sb, full, empty, nkb, wg);
        stage_tiles<128>(a0, sb + own_slot() * STQ, wi, lane);
      }
      fence_proxy_async();
      __syncwarp();
      mbar_arrive_if(lane == 0, done);
      continue;
    }
    uint32_t qf[12][4];
    uint4* qp = a.qs + ((size_t)((m & 3) * 32 + k) * 12) * 256 + threadIdx.x;
    if (type != T_A) {
      float acc[96], a1[1];
      tr_mainloop<192, 0>(acc, a1, p, sb, full, empty, 10, wg);
#pragma unroll
      for (int i = 0; i < 12; i++) {
        qf[i][0] = pack_bf16(acc[8 * i], acc[8 * i + 1]); qf[i][1] = pack_bf16(acc[8 * i + 2], acc[8 * i + 3]);
        qf[i][2] = pack_bf16(acc[8 * i + 4], acc[8 * i + 5]); qf[i][3] = pack_bf16(acc[8 * i + 6], acc[8 * i + 7]);
      }
      if (type == T_Q) {
#pragma unroll
        for (int i = 0; i < 12; i++) qp[i * 256] = make_uint4(qf[i][0], qf[i][1], qf[i][2], qf[i][3]);
        __syncwarp();
        mbar_arrive_if(lane == 0, done);
        continue;
      }
    } else {
#pragma unroll
      for (int i = 0; i < 12; i++) { const uint4 v = __ldcg(qp + i * 256); qf[i][0] = v.x; qf[i][1] = v.y; qf[i][2] = v.z; qf[i][3] = v.w; }
    }
    const uint32_t ost = sb + OFF_K + wg * 2 * SEGB;
    const bool second = wi >= 2;
    uint32_t pf[5][4];
    {
      float sa[20], sb2[20];
      uint32_t kbase = ost, kslot = 0;
      if (type == T_A) { kslot = own_slot(); kbase = sb + kslot * STQ; } else mbar_wait(barK + 8 * wg, kph);
      if (STAG && wg) bar_sync(1, 256);
      wgmma_fence();
#pragma unroll
      for (int i = 0; i < 12; i++) {
        wgmma_rs_n40<0>(sa, qf[i][0], qf[i][1], qf[i][2], qf[i][3], make_desc(kbase + i * 1280, 640, 128, 0), i != 0);
        wgmma_rs_n40<0>(sb2, qf[i][0], qf[i][1], qf[i][2], qf[i][3], make_desc(kbase + SEGB + i * 1280, 640, 128, 0), i != 0);
      }
      wgmma_commit();
      wgmma_wait<0>();
      if (STAG && !wg) bar_arrive(1, 256);
      mbar_arrive_if(type == T_A && (threadIdx.x & 127) == 0, empty + 8 * kslot);
      const float cs = 0.07216878364870322f * 1.4426950408889634f;
      const int r0 = 16 * (wi & 1) + g, r1 = r0 + 8;
      float m0 = -INFINITY, m1 = -INFINITY;
#pragma unroll
      for (int n = 0; n < 5; n++) {
#pragma unroll
        for (int e = 0; e < 2; e++) {
          const int key = 8 * n + 2 * q4 + e;
          float x = second ? sb2[4 * n + e] : sa[4 * n + e], y = second ? sb2[4 * n + 2 + e] : sa[4 * n + 2 + e];
          if (n < 4) { if (key > r0) x = -INFINITY; if (key > r1) y = -INFINITY; }
          sa[4 * n + e] = x; sa[4 * n + 2 + e] = y;
          m0 = fmaxf(m0, x); m1 = fmaxf(m1, y);
        }
      }
      m0 = fmaxf(m0, __shfl_xor_sync(0xffffffffu, m0, 1)); m1 = fmaxf(m1, __shfl_xor_sync(0xffffffffu, m1, 1));
      m0 = fmaxf(m0, __shfl_xor_sync(0xffffffffu, m0, 2)); m1 = fmaxf(m1, __shfl_xor_sync(0xffffffffu, m1, 2));
      float s0 = 0.f, s1 = 0.f;
#pragma unroll
      for (int n = 0; n < 5; n++) {
#pragma unroll
        for (int e = 0; e < 2; e++) {
          sa[4 * n + e] = ex2f((sa[4 * n + e] - m0) * cs); sa[4 * n + 2 + e] = ex2f((sa[4 * n + 2 + e] - m1) * cs);
          s0 += sa[4 * n + e]; s1 += sa[4 * n + 2 + e];
        }
      }
      s0 += __shfl_xor_sync(0xffffffffu, s0, 1); s1 += __shfl_xor_sync(0xffffffffu, s1, 1);
      s0 += __shfl_xor_sync(0xffffffffu, s0, 2); s1 += __shfl_xor_sync(0xffffffffu, s1, 2);
      const float i0 = rcpf(s0), i1 = rcpf(s1);
#pragma unroll
      for (int n = 0; n < 5; n++) {
        const uint32_t x = pack_bf16(sa[4 * n] * i0, sa[4 * n + 1] * i0), y = pack_bf16(sa[4 * n + 2] * i1, sa[4 * n + 3] * i1);
        if (n < 4) {
          pf[n >> 1][2 * (n & 1)] = second ? 0u : x; pf[n >> 1][2 * (n & 1) + 1] = second ? 0u : y;
          pf[2 + (n >> 1)][2 * (n & 1)] = second ? x : 0u; pf[2 + (n >> 1)][2 * (n & 1) + 1] = second ? y : 0u;
        } else {
          pf[4][0] = second ? 0u : x; pf[4][1] = second ? 0u : y; pf[4][2] = second ? x : 0u; pf[4][3] = second ? y : 0u;
        }
      }
    }
    {
      float o[96];
#pragma unroll
      for (int i = 0; i < 5; i++) { PIN(pf[i][0]); PIN(pf[i][1]); PIN(pf[i][2]); PIN(pf[i][3]); }
      const uint32_t own = own_slot(), vbase = sb + own * STQ;
      wgmma_fence();
#pragma unroll
      for (int i = 0; i < 5; i++)
        wgmma_rs_n192<1>(o, pf[i][0], pf[i][1], pf[i][2], pf[i][3], i < 4 ? make_desc(vbase + (i >> 1) * SEGB + (i & 1) * 256, 128, 640, 0) : make_desc(vbase + 512, SEGB, 640, 0), i != 0);
      wgmma_commit();
      if (type == T_A) mbar_wait(barK + 8 * wg, kph);
      kph ^= 1;
      wgmma_wait<0>();
      mbar_arrive_if((threadIdx.x & 127) == 0, empty + 8 * own);
      stage_tiles<192>(o, ost, wi, lane);
      fence_proxy_async();
      __syncwarp();
      mbar_arrive_if(lane == 0, done);
    }
  }
}
namespace bf {
constexpr int NS = 4, STAGE = 16384 + 36864;
constexpr int PHI_STR = 112, PHI_HEAD = 128 * PHI_STR;
constexpr int V_STR = 48, V_HEAD = 128 * V_STR;
constexpr int OFF_PHI = 0, OFF_V = 4 * PHI_HEAD, OFF_X = OFF_V + 4 * V_HEAD;
constexpr int OFF_WOT = 100352;
constexpr int OFF_OST = 65536;
constexpr int ANS = 4;
constexpr int OFF_BAR = OFF_WOT + 12 * 10240;
constexpr int SMEM = OFF_BAR + 256;
static_assert(OFF_X + 4 * 36 * 128 <= OFF_WOT && NS * STAGE <= OFF_BAR && SMEM <= 232448, "smem");
}
__device__ __forceinline__ void hedgehog_features(const float (&x)[6], int q4, float (&pos)[6], float (&neg)[6]) {
  const bool v2 = q4 < 2;
  float mx = fmaxf(fmaxf(x[0], x[1]), fmaxf(x[2], x[3])), mn = fminf(fminf(x[0], x[1]), fminf(x[2], x[3]));
  if (v2) { mx = fmaxf(mx, fmaxf(x[4], x[5])); mn = fminf(mn, fminf(x[4], x[5])); }
  mx = fmaxf(mx, __shfl_xor_sync(0xffffffffu, mx, 1)); mn = fminf(mn, __shfl_xor_sync(0xffffffffu, mn, 1));
  mx = fmaxf(mx, __shfl_xor_sync(0xffffffffu, mx, 2)); mn = fminf(mn, __shfl_xor_sync(0xffffffffu, mn, 2));
  const float L = 1.4426950408889634f;
  float sp = 0.f, sn = 0.f;
#pragma unroll
  for (int i = 0; i < 6; i++) {
    const bool ok = i < 4 || v2;
    pos[i] = ok ? ex2f((x[i] - mx) * L) : 0.f;
    neg[i] = ok ? ex2f((mn - x[i]) * L) : 0.f;
    sp += pos[i]; sn += neg[i];
  }
  sp += __shfl_xor_sync(0xffffffffu, sp, 1); sn += __shfl_xor_sync(0xffffffffu, sn, 1);
  sp += __shfl_xor_sync(0xffffffffu, sp, 2); sn += __shfl_xor_sync(0xffffffffu, sn, 2);
  const float ip = rcpf(sp), in_ = rcpf(sn);
#pragma unroll
  for (int i = 0; i < 6; i++) { pos[i] *= ip; neg[i] *= in_; }
}

__global__ void __launch_bounds__(384, 1) blayer_kernel(const __grid_constant__ CUtensorMap tmA, const __grid_constant__ CUtensorMap tmB,
                                                        const __grid_constant__ CUtensorMap tmO, const __grid_constant__ CUtensorMap tmW,
                                                        float* __restrict__ kvacc, unsigned* __restrict__ cnt, bf16* __restrict__ o2,
                                                        const bf16* __restrict__ xin, bf16* __restrict__ xout,
                                                        const bf16* pf0, const bf16* pf1, const bf16* pf2, const bf16* pf3, int tl) {
  using namespace bf;
  TL_BEGIN(tl);
  extern __shared__ __align__(1024) unsigned char smem_raw[];
  const uint32_t sb = smem_u32(smem_raw);
  const int warp = __shfl_sync(0xffffffffu, (int)threadIdx.x >> 5, 0), lane = threadIdx.x & 31;
  const uint32_t full = sb + OFF_BAR, empty = full + 8 * NS, full2 = empty + 8 * NS, empty2 = full2 + 8 * ANS, barW = empty2 + 8 * ANS, barGo = barW + 8;
  const int m = blockIdx.x & 15, u = blockIdx.x >> 4;
  unsigned* cntKV = cnt + u; unsigned* cntO = cnt + 8 + m;
  if (threadIdx.x == 0) {
    for (int i = 0; i < NS; i++) { mbar_init(full + 8 * i, 1); mbar_init(empty + 8 * i, 2); }
    for (int i = 0; i < ANS; i++) { mbar_init(full2 + 8 * i, 1); mbar_init(empty2 + 8 * i, 2); }
    mbar_init(barW, 1); mbar_init(barGo, 1);
    asm volatile("fence.mbarrier_init.release.cluster;" ::: "memory");
  }
  __syncthreads();
  asm volatile("griddepcontrol.wait;" ::: "memory");
  asm volatile("griddepcontrol.launch_dependents;" ::: "memory");
  if (warp >= 8) {
    asm volatile("setmaxnreg.dec.sync.aligned.u32 40;");
    if (warp == 8 && elect_one()) {
      prefetch_tmap(&tmO); prefetch_tmap(&tmW);
      Pipe p{0, 1};
      for (int kb = 0; kb < 10; kb++) {
        mbar_wait(empty + 8 * p.stage, p.phase);
        const uint32_t st = sb + p.stage * STAGE, fb = full + 8 * p.stage;
        mbar_expect_tx(fb, STAGE);
        tma_load_2d(st, &tmA, kb * 64, m * 128, fb);
        tma_load_2d(st + 16384, &tmB, kb * 64, u * 288, fb);
        tma_load_2d(st + 16384 + 18432, &tmB, kb * 64, u * 288 + 144, fb);
        pipe_adv<NS>(p);
      }
      if (pf0) {
        constexpr uint32_t PER = cfg::DM * cfg::HD * 2 / 128;
        prefetch_l2((const unsigned char*)pf0 + blockIdx.x * PER, PER); prefetch_l2((const unsigned char*)pf1 + blockIdx.x * PER, PER);
        if (pf2) { prefetch_l2((const unsigned char*)pf2 + blockIdx.x * PER, PER); prefetch_l2((const unsigned char*)pf3 + blockIdx.x * PER, PER); }
      }
      for (int i = 0; i < NS; i++) { mbar_wait(empty + 8 * p.stage, p.phase); pipe_adv<NS>(p); }
      mbar_expect_tx(barW, 12 * 10240);
      for (int kb = 0; kb < 12; kb++) tma_load_2d(sb + OFF_WOT + kb * 10240, &tmW, kb * 64, u * 80, barW);
      mbar_wait(barGo, 0);
      wait_ge(cntO, 8);
      fence_proxy_async_global();
      Pipe q{0, 1};
      for (int kb = 0; kb < 12; kb++) {
        mbar_wait(empty2 + 8 * q.stage, q.phase);
        mbar_expect_tx(full2 + 8 * q.stage, 16384);
        tma_load_2d(sb + q.stage * 16384, &tmO, kb * 64, m * 128, full2 + 8 * q.stage);
        pipe_adv<ANS>(q);
      }
    }
    return;
  }
  asm volatile("setmaxnreg.inc.sync.aligned.u32 232;");
  const int wg = warp >> 2, wi = warp & 3;
  const int g = lane >> 2, q4 = lane & 3;
  float a0[72], a1[72];
  {
    Pipe p{0, 0};
    uint32_t prev = 0;
    for (int kb = 0; kb < 10; kb++) {
      mbar_wait(full + 8 * p.stage, p.phase);
      const uint32_t st = sb + p.stage * STAGE;
      wgmma_fence();
#pragma unroll
      for (int kk = 0; kk < 4; kk++) {
        const uint64_t da = desc_kmajor(st + wg * 8192 + kk * 32);
        wgmma_n144<0, 0>(a0, da, desc_kmajor(st + 16384 + kk * 32), (kb | kk) != 0);
        wgmma_n144<0, 0>(a1, da, desc_kmajor(st + 16384 + 18432 + kk * 32), (kb | kk) != 0);
      }
      wgmma_commit();
      if (kb > 0) { wgmma_wait<1>(); if ((threadIdx.x & 127) == 0) mbar_arrive(empty + 8 * prev); }
      prev = p.stage;
      pipe_adv<NS>(p);
    }
    wgmma_wait<0>();
    bar_sync(1, 256);
    if ((threadIdx.x & 127) == 0) mbar_arrive(empty + 8 * prev);
  }
  TL2((tl >= 12 ? 128 : 0) + 32 + 0);
  auto ACC = [&](auto V, auto E) -> float { constexpr int v = V.value, e = E.value; if constexpr (v < 18) return a0[4 * v + e]; else return a1[4 * (v - 18) + e]; };
  const int trow = wg * 64 + wi * 16;
  const int srow = (lane & 7) + 8 * ((lane >> 3) & 1);
  uint32_t qf[4][3][4];
  static_for<0, 4>([&](auto HH) {
    constexpr int hh = HH.value;
    float xa[6], xb[6], pa[6], na[6], pb[6], nb[6];
    static_for<0, 3>([&](auto T) {
      constexpr int t = T.value; using V = IC<3 * hh + t>;
      xa[2 * t] = ACC(V{}, IC<0>{}); xa[2 * t + 1] = ACC(V{}, IC<1>{}); xb[2 * t] = ACC(V{}, IC<2>{}); xb[2 * t + 1] = ACC(V{}, IC<3>{});
      bf16r2(xa[2 * t], xa[2 * t + 1]); bf16r2(xb[2 * t], xb[2 * t + 1]);
    });
    hedgehog_features(xa, q4, pa, na);
    hedgehog_features(xb, q4, pb, nb);
    qf[hh][0][0] = pack_bf16(pa[0], pa[1]); qf[hh][0][1] = pack_bf16(pb[0], pb[1]); qf[hh][0][2] = pack_bf16(pa[2], pa[3]); qf[hh][0][3] = pack_bf16(pb[2], pb[3]);
    qf[hh][1][0] = pack_bf16(pa[4], pa[5]); qf[hh][1][1] = pack_bf16(pb[4], pb[5]); qf[hh][1][2] = pack_bf16(na[0], na[1]); qf[hh][1][3] = pack_bf16(nb[0], nb[1]);
    qf[hh][2][0] = pack_bf16(na[2], na[3]); qf[hh][2][1] = pack_bf16(nb[2], nb[3]); qf[hh][2][2] = pack_bf16(na[4], na[5]); qf[hh][2][3] = pack_bf16(nb[4], nb[5]);
    static_for<0, 3>([&](auto T) {
      constexpr int t = T.value; using V = IC<12 + 3 * hh + t>;
      xa[2 * t] = ACC(V{}, IC<0>{}); xa[2 * t + 1] = ACC(V{}, IC<1>{}); xb[2 * t] = ACC(V{}, IC<2>{}); xb[2 * t + 1] = ACC(V{}, IC<3>{});
      bf16r2(xa[2 * t], xa[2 * t + 1]); bf16r2(xb[2 * t], xb[2 * t + 1]);
    });
    hedgehog_features(xa, q4, pa, na);
    hedgehog_features(xb, q4, pb, nb);
    const uint32_t ph = sb + OFF_PHI + hh * PHI_HEAD + (trow + srow) * PHI_STR + (lane >> 4) * 16;
    stsm_x4(ph, pack_bf16(pa[0], pa[1]), pack_bf16(pb[0], pb[1]), pack_bf16(pa[2], pa[3]), pack_bf16(pb[2], pb[3]));
    stsm_x4(ph + 32, pack_bf16(pa[4], pa[5]), pack_bf16(pb[4], pb[5]), pack_bf16(na[0], na[1]), pack_bf16(nb[0], nb[1]));
    stsm_x4(ph + 64, pack_bf16(na[2], na[3]), pack_bf16(nb[2], nb[3]), pack_bf16(na[4], na[5]), pack_bf16(nb[4], nb[5]));
    using V0 = IC<24 + 3 * hh>; using V1 = IC<24 + 3 * hh + 1>; using V2 = IC<24 + 3 * hh + 2>;
    float c0 = ACC(V2{}, IC<0>{}), c1 = ACC(V2{}, IC<1>{}), c2 = ACC(V2{}, IC<2>{}), c3 = ACC(V2{}, IC<3>{});
    if (q4 == 2) { c0 = 1.f; c1 = 0.f; c2 = 1.f; c3 = 0.f; }
    if (q4 == 3) { c0 = c1 = c2 = c3 = 0.f; }
    const uint32_t va = sb + OFF_V + hh * V_HEAD + (trow + srow) * V_STR;
    stsm_x4(va + (lane >> 4) * 16, pack_bf16(ACC(V0{}, IC<0>{}), ACC(V0{}, IC<1>{})), pack_bf16(ACC(V0{}, IC<2>{}), ACC(V0{}, IC<3>{})),
            pack_bf16(ACC(V1{}, IC<0>{}), ACC(V1{}, IC<1>{})), pack_bf16(ACC(V1{}, IC<2>{}), ACC(V1{}, IC<3>{})));
    stsm_x2(va + 32, pack_bf16(c0, c1), pack_bf16(c2, c3));
  });
  bar_sync(1, 256);
  TL2((tl >= 12 ? 128 : 0) + 32 + 1);
  {
    const int hh = warp >> 1, th = warp & 1;
    float d[3][3][4];
#pragma unroll
    for (int a = 0; a < 3; a++)
#pragma unroll
      for (int b = 0; b < 3; b++) { d[a][b][0] = d[a][b][1] = d[a][b][2] = d[a][b][3] = 0.f; }
#pragma unroll
    for (int ks = 0; ks < 4; ks++) {
      const int t0 = th * 64 + ks * 16;
      const uint32_t pa = sb + OFF_PHI + hh * PHI_HEAD + (t0 + (lane & 7) + 8 * (lane >> 4)) * PHI_STR + ((lane >> 3) & 1) * 16;
      const uint32_t pv = sb + OFF_V + hh * V_HEAD + (t0 + (lane & 7) + 8 * ((lane >> 3) & 1)) * V_STR;
      uint32_t b01[4], b2[2];
      ldsm_x4_t(b01, pv + (lane >> 4) * 16);
      ldsm_x2_t(b2, pv + 32);
#pragma unroll
      for (int a = 0; a < 3; a++) {
        uint32_t af[4];
        ldsm_x4_t(af, pa + a * 32);
        mma16816(d[a][0], af[0], af[1], af[2], af[3], b01[0], b01[1]);
        mma16816(d[a][1], af[0], af[1], af[2], af[3], b01[2], b01[3]);
        mma16816(d[a][2], af[0], af[1], af[2], af[3], b2[0], b2[1]);
      }
    }
    const uint32_t xa = sb + OFF_X + hh * (36 * 128) + lane * 4;
    if (th == 1) {
#pragma unroll
      for (int a = 0; a < 3; a++)
#pragma unroll
        for (int b = 0; b < 3; b++)
#pragma unroll
          for (int e = 0; e < 4; e++)
            asm volatile("st.shared.f32 [%0], %1;" :: "r"(xa + ((a * 3 + b) * 4 + e) * 128), "f"(d[a][b][e]) : "memory");
    }
    bar_sync(2 + hh, 64);
    if (th == 0) {
      float* dst = kvacc + (size_t)(u * 4 + hh) * (48 * 24);
#pragma unroll
      for (int a = 0; a < 3; a++)
#pragma unroll
        for (int b = 0; b < 3; b++) {
          float y[4];
#pragma unroll
          for (int e = 0; e < 4; e++) {
            float o;
            asm volatile("ld.shared.f32 %0, [%1];" : "=f"(o) : "r"(xa + ((a * 3 + b) * 4 + e) * 128) : "memory");
            y[e] = d[a][b][e] + o;
          }
          const int f0 = 16 * a + g, dd = 8 * b + 2 * q4;
          if (dd < 22) {
            asm volatile("red.relaxed.gpu.global.add.v2.f32 [%0], {%1,%2};" :: "l"(dst + f0 * 24 + dd), "f"(y[0]), "f"(y[1]) : "memory");
            asm volatile("red.relaxed.gpu.global.add.v2.f32 [%0], {%1,%2};" :: "l"(dst + (f0 + 8) * 24 + dd), "f"(y[2]), "f"(y[3]) : "memory");
          }
        }
      __threadfence();
    }
  }
  TL2((tl >= 12 ? 128 : 0) + 32 + 2);
  bar_sync(1, 256);
  if (threadIdx.x == 0) { __threadfence(); atomicAdd(cntKV, 1u); wait_ge(cntKV, 16); }
  bar_sync(1, 256);
  TL2((tl >= 12 ? 128 : 0) + 32 + 3);
  {
    float t[5][4];
#pragma unroll
    for (int it = 0; it < 5; it++) {
      const int i = min((int)threadIdx.x + 256 * it, 4 * 9 * 32 - 1);
      const int hh = i / 288, r = i % 288, tt = r >> 5, l = r & 31, ks = tt / 3, nt = tt % 3;
      const float* src = kvacc + (size_t)(u * 4 + hh) * (48 * 24) + (16 * ks + 2 * (l & 3)) * 24 + 8 * nt + (l >> 2);
      t[it][0] = __ldcg(src); t[it][1] = __ldcg(src + 24); t[it][2] = __ldcg(src + 8 * 24); t[it][3] = __ldcg(src + 9 * 24);
    }
#pragma unroll
    for (int it = 0; it < 5; it++) {
      const int i = threadIdx.x + 256 * it;
      if (i < 4 * 9 * 32) sts64(sb + OFF_X + i * 8, pack_bf16(t[it][0], t[it][1]), pack_bf16(t[it][2], t[it][3]));
    }
  }
  bar_sync(1, 256);
  {
    const uint32_t ost = sb + warp * 3072;
    uint32_t ow[4][6];
#pragma unroll
    for (int hh = 0; hh < 4; hh++) {
      float d[3][4];
#pragma unroll
      for (int n = 0; n < 3; n++) {
        d[n][0] = d[n][1] = d[n][2] = d[n][3] = 0.f;
        const uint32_t kb = sb + OFF_X + hh * 2304 + n * 256 + lane * 8;
        const uint2 k0 = lds64(kb), k1 = lds64(kb + 768), k2 = lds64(kb + 1536);
        mma16816(d[n], qf[hh][0][0], qf[hh][0][1], qf[hh][0][2], qf[hh][0][3], k0.x, k0.y);
        mma16816(d[n], qf[hh][1][0], qf[hh][1][1], qf[hh][1][2], qf[hh][1][3], k1.x, k1.y);
        mma16816(d[n], qf[hh][2][0], qf[hh][2][1], qf[hh][2][2], qf[hh][2][3], k2.x, k2.y);
      }
      const float da = bf16r(bf16r(__shfl_sync(0xffffffffu, d[2][0], (lane & ~3) | 2)) + 1e-6f);
      const float db = bf16r(bf16r(__shfl_sync(0xffffffffu, d[2][2], (lane & ~3) | 2)) + 1e-6f);
      float y[3][4];
#pragma unroll
      for (int n = 0; n < 3; n++) {
        bf16r2(d[n][0], d[n][1]); bf16r2(d[n][2], d[n][3]);
        y[n][0] = __fdividef(d[n][0], da); y[n][1] = __fdividef(d[n][1], da);
        y[n][2] = __fdividef(d[n][2], db); y[n][3] = __fdividef(d[n][3], db);
      }
      if (q4 >= 2) { y[2][0] = y[2][1] = y[2][2] = y[2][3] = 0.f; }
#pragma unroll
      for (int n = 0; n < 3; n++) { ow[hh][2 * n] = pack_bf16(y[n][0], y[n][1]); ow[hh][2 * n + 1] = pack_bf16(y[n][2], y[n][3]); }
    }
#pragma unroll
    for (int hh = 0; hh < 4; hh++) {
      const uint32_t ra = ost + srow * 192 + hh * 48;
      stsm_x4(ra + (lane >> 4) * 16, ow[hh][0], ow[hh][1], ow[hh][2], ow[hh][3]);
      stsm_x2(ra + 32, ow[hh][4], ow[hh][5]);
    }
    __syncwarp();
#pragma unroll
    for (int i = 0; i < 6; i++) {
      const int c = lane + 32 * i, row = c / 12, chunk = c % 12;
      const uint4 v = lds128(ost + row * 192 + chunk * 16);
      *(uint4*)(o2 + (size_t)(m * 128 + trow + row) * 768 + u * 96 + chunk * 8) = v;
    }
  }
  __threadfence();
  bar_sync(1, 256);
  if (threadIdx.x == 0) { atomicAdd(cntO, 1u); mbar_arrive(barGo); }
  TL2((tl >= 12 ? 128 : 0) + 32 + 4);
  float acc[40];
  uint4 xr[5];
#pragma unroll
  for (int i = 0; i < 5; i++) {
    const int c = lane + 32 * i;
    xr[i] = *(const uint4*)(xin + (size_t)(m * 128 + trow + c / 10) * cfg::DM + u * 80 + (c % 10) * 8);
  }
  mbar_wait(barW, 0);
  {
    Pipe p{0, 0};
    uint32_t prev = 0;
    for (int kb = 0; kb < 12; kb++) {
      mbar_wait(full2 + 8 * p.stage, p.phase);
      wgmma_fence();
#pragma unroll
      for (int kk = 0; kk < 4; kk++)
        wgmma_n80<0, 0>(acc, desc_kmajor(sb + p.stage * 16384 + wg * 8192 + kk * 32), desc_kmajor(sb + OFF_WOT + kb * 10240 + kk * 32), (kb | kk) != 0);
      wgmma_commit();
      if (kb > 0) { wgmma_wait<1>(); if ((threadIdx.x & 127) == 0) mbar_arrive(empty2 + 8 * prev); }
      prev = p.stage;
      pipe_adv<ANS>(p);
    }
    wgmma_wait<0>();
  }
  TL2((tl >= 12 ? 128 : 0) + 32 + 5);
  {
    const uint32_t ost = sb + OFF_OST + warp * 3072;
#pragma unroll
    for (int v = 0; v < 10; v += 2)
      stsm_x4(ost + srow * 176 + (v + (lane >> 4)) * 16, pack_bf16(acc[4 * v], acc[4 * v + 1]), pack_bf16(acc[4 * v + 2], acc[4 * v + 3]),
              pack_bf16(acc[4 * v + 4], acc[4 * v + 5]), pack_bf16(acc[4 * v + 6], acc[4 * v + 7]));
    __syncwarp();
#pragma unroll
    for (int i = 0; i < 5; i++) {
      const int c = lane + 32 * i, row = c / 10, chunk = c % 10;
      const uint4 y = lds128(ost + row * 176 + chunk * 16);
      const size_t off = (size_t)(m * 128 + trow + row) * cfg::DM + u * 80 + chunk * 8;
      const uint4 x = xr[i];
      *(uint4*)(xout + off) = make_uint4(pack_bf16(bf_lo(x.x) + bf_lo(y.x), bf_hi(x.x) + bf_hi(y.x)), pack_bf16(bf_lo(x.y) + bf_lo(y.y), bf_hi(x.y) + bf_hi(y.y)),
                                         pack_bf16(bf_lo(x.z) + bf_lo(y.z), bf_hi(x.z) + bf_hi(y.z)), pack_bf16(bf_lo(x.w) + bf_lo(y.w), bf_hi(x.w) + bf_hi(y.w)));
    }
  }
  TL_END(tl);
}
__device__ __align__(32768) unsigned char g_arena[AR_SIZE];
__device__ __align__(1024) uint2 g_xh[2048 * 160];
__device__ __align__(1024) unsigned char g_k[64 * 96 * 5120], g_v[64 * 96 * 5120];
__device__ __align__(1024) bf16 g_o[2048 * 6144];
__device__ __align__(1024) uint4 g_qs[4 * 32 * 12 * 256];
__device__ __align__(1024) bf16 g_xn[2048 * 640], g_xn2[2048 * 640], g_xa[2048 * 640], g_xb[2048 * 640];
__device__ __align__(1024) bf16 g_part[24 * 2048 * 640];
__device__ __align__(1024) bf16 g_wb[2304 * 640], g_wot[640 * 768], g_pq[2048 * 768];
__device__ __align__(1024) float g_kvacc[32 * 48 * 24 + 64];

typedef CUresult (*EncodeFn)(CUtensorMap*, CUtensorMapDataType, cuuint32_t, void*, const cuuint64_t*, const cuuint64_t*, const cuuint32_t*,
                             const cuuint32_t*, CUtensorMapInterleave, CUtensorMapSwizzle, CUtensorMapL2promotion, CUtensorMapFloatOOBfill);
static EncodeFn g_encode = nullptr;
static CUtensorMap make_map(const void* p, uint64_t cols, uint64_t rows, uint32_t bc, uint32_t br, bool swz = true) {
  CUtensorMap m;
  cuuint64_t dims[2] = {cols, rows}, strides[1] = {cols * 2};
  cuuint32_t box[2] = {bc, br}, es[2] = {1, 1};
  g_encode(&m, CU_TENSOR_MAP_DATA_TYPE_BFLOAT16, 2, const_cast<void*>(p), dims, strides, box, es, CU_TENSOR_MAP_INTERLEAVE_NONE,
           swz ? CU_TENSOR_MAP_SWIZZLE_128B : CU_TENSOR_MAP_SWIZZLE_NONE, CU_TENSOR_MAP_L2_PROMOTION_L2_256B, CU_TENSOR_MAP_FLOAT_OOB_FILL_NONE);
  return m;
}
static CUtensorMap make_map3(const void* p, uint64_t cols, uint64_t rows, uint32_t nb) {
  CUtensorMap m;
  cuuint64_t dims[3] = {64, rows, cols / 64}, strides[2] = {cols * 2, 128};
  cuuint32_t box[3] = {64, 64, nb}, es[3] = {1, 1, 1};
  g_encode(&m, CU_TENSOR_MAP_DATA_TYPE_BFLOAT16, 3, const_cast<void*>(p), dims, strides, box, es, CU_TENSOR_MAP_INTERLEAVE_NONE,
           CU_TENSOR_MAP_SWIZZLE_128B, CU_TENSOR_MAP_L2_PROMOTION_L2_256B, CU_TENSOR_MAP_FLOAT_OOB_FILL_NONE);
  return m;
}
template <class T> static T* sym(const T& s) { void* p = nullptr; cudaGetSymbolAddress(&p, s); return (T*)p; }

struct Ptrs {
  unsigned char *arena, *k, *v; bf16 *o, *xn, *xa, *xb, *wb, *wot, *pq; float *part, *kvacc; uint2* xh; uint4* qs; bf16* xn2;
};

#define NQPRE 3
#define NQLATE 1
#define QFIRST 0
#define KSPLIT {2, 2, 2, 2, 2, 2, 2, 2, 2, 2, 2, 3, 4, 6, 12, 24}
#define NWIDE 14
#define LFINE 11
#define LLAG 4
static tr::Sched make_sched(int layer) {
  using namespace tr;
  Sched s = {};
  const int ks[16] = KSPLIT;
  int g = 0, n = 0;
  auto add = [&](int type, int b, int cnt) { s.start[g] = (uint16_t)n; s.type[g] = (uint8_t)type; s.blk[g] = (uint8_t)b; g++; n += cnt; };
  for (int b = 0; b < 16; b++) { s.ks[b] = (uint8_t)ks[b]; s.wide[b] = b < NWIDE; s.lrows[b] = b < LFINE ? 4 : (ks[b] <= 4 ? 2 : 1); }
  auto qa = [&](int b) { add(b >= 16 - NQPRE ? T_A : T_QA, b, 32); };
  auto op = [&](int b) { add(s.wide[b] ? T_OB : T_OS, b, ks[b] * (s.wide[b] ? 2 : 5)); };
  auto ln = [&](int b) { add(T_L, b, 16 / s.lrows[b]); };
  for (int b = 16 - NQPRE; b < 16 - NQLATE; b++) add(T_Q, b, 32);
  qa(0);
  for (int b = 16 - NQLATE; b < 16; b++) add(T_Q, b, 32);
  int nl = 0;
  for (int b = 0; b < 16; b++) {
    if (b + 1 < 16 && b + 1 >= QFIRST) qa(b + 1);
    op(b);
    if (b + 1 < 16 && b + 1 < QFIRST) qa(b + 1);
    if (b >= LLAG && b < 14) ln(nl++);
  }
  while (nl < 16) ln(nl++);
  add(T_END, 0, 0);
  s.start[g] = 0xffff;
  return s;
}
#define TRAIL_GRID 132
#define PDL_LN 0
#define PDL_CH 1
#define PDL_B 0
#define PF_A 1
#define PF_B 1
extern "C" void kernel_launch(void* const* d_in, const int* in_sizes, int n_in, void* d_out, int out_size) {
  const bf16* x = (const bf16*)d_in[0];
  const bf16* mem0 = (const bf16*)d_in[1];
  const bf16 *Wq = (const bf16*)d_in[2], *Wk = (const bf16*)d_in[3], *Wv = (const bf16*)d_in[4], *Wo = (const bf16*)d_in[5];
  const bf16 *wqkv = (const bf16*)d_in[8], *wphi = (const bf16*)d_in[9], *wo = (const bf16*)d_in[10];
  bf16* out = (bf16*)d_out;
  static Ptrs P; static bool init = false;
  if (!init) {
    void* fn = nullptr; cudaDriverEntryPointQueryResult qr;
    cudaGetDriverEntryPoint("cuTensorMapEncodeTiled", &fn, cudaEnableDefault, &qr);
    g_encode = (EncodeFn)fn;
    void* p;
    cudaGetSymbolAddress(&p, g_arena); P.arena = (unsigned char*)p;
    cudaGetSymbolAddress(&p, g_k); P.k = (unsigned char*)p;   cudaGetSymbolAddress(&p, g_v); P.v = (unsigned char*)p;
    cudaGetSymbolAddress(&p, g_o); P.o = (bf16*)p;
    cudaGetSymbolAddress(&p, g_xn); P.xn = (bf16*)p;
    cudaGetSymbolAddress(&p, g_xa); P.xa = (bf16*)p;   cudaGetSymbolAddress(&p, g_xb); P.xb = (bf16*)p;
    cudaGetSymbolAddress(&p, g_wb); P.wb = (bf16*)p;   cudaGetSymbolAddress(&p, g_wot); P.wot = (bf16*)p;
    cudaGetSymbolAddress(&p, g_pq); P.pq = (bf16*)p;   cudaGetSymbolAddress(&p, g_part); P.part = (float*)p;
    cudaGetSymbolAddress(&p, g_kvacc); P.kvacc = (float*)p;
    cudaGetSymbolAddress(&p, g_xh); P.xh = (uint2*)p;
    cudaGetSymbolAddress(&p, g_qs); P.qs = (uint4*)p;
    cudaGetSymbolAddress(&p, g_xn2); P.xn2 = (bf16*)p;
    cudaFuncSetAttribute(chain_kernel, cudaFuncAttributeMaxDynamicSharedMemorySize, ch::SMEM);
    cudaFuncSetAttribute(trail_kernel, cudaFuncAttributeMaxDynamicSharedMemorySize, tr::SMEM);
    cudaFuncSetAttribute(blayer_kernel, cudaFuncAttributeMaxDynamicSharedMemorySize, bf::SMEM);
    init = true;
  }
  const CUtensorMap tmXn = make_map(P.xn, 640, 2048, 64, 128), tmXn2 = make_map(P.xn2, 640, 2048, 64, 128);
  const CUtensorMap tmWq = make_map3(Wq, 6144, 640, 3);
  const CUtensorMap tmCq = make_map(Wq, 6144, 640, 64, 160), tmCk = make_map(Wk, 6144, 640, 64, 160), tmCv = make_map(Wv, 6144, 640, 64, 160), tmCo = make_map(Wo, 640, 6144, 224, 64, false);
  const CUtensorMap tmWo5 = make_map3(Wo, 640, 6144, 5), tmWo2 = make_map3(Wo, 640, 6144, 2);
  const CUtensorMap tmWb = make_map(P.wb, 640, 2304, 64, 144), tmO2 = make_map(P.pq, 768, 2048, 64, 128), tmWot = make_map(P.wot, 768, 640, 64, 80);

  ChainArgs ca;
  ca.xh = P.xh; ca.mem0 = mem0; ca.kg = P.k; ca.vg = P.v;
  ca.arena = P.arena; ca.dbg = nullptr; ca.tl = 0;
  uint4* zar = (uint4*)P.arena; const int nzar = AR_SIZE / 16;
  uint4* zkv = (uint4*)P.kvacc; const int nzkv = (32 * 48 * 24 + 64) / 4;

  const PrepArgs pa{wqkv, wphi, wo, P.wb, P.wot};
  const bf16* xcur = x;
  cudaLaunchAttribute at[1];
  at[0].id = cudaLaunchAttributeProgrammaticStreamSerialization; at[0].val.programmaticStreamSerializationAllowed = 1;
  auto cfgof = [&](int grid, int block, int smem, bool pdl) {
    cudaLaunchConfig_t lc = {};
    lc.gridDim = dim3(grid); lc.blockDim = dim3(block); lc.dynamicSmemBytes = smem; lc.stream = cudaStreamPerThread;
    lc.attrs = at; lc.numAttrs = pdl ? 1 : 0;
    return lc;
  };
  for (int layer = 0; layer < 2; layer++) {
    const int tl = layer * 12;
    cudaLaunchConfig_t lc = cfgof(256, 256, 0, layer > 0 && PDL_LN);
    cudaLaunchKernelEx(&lc, ln_kernel, xcur, P.xn, P.xh, zar, nzar, zkv, nzkv, Wk, Wv, layer == 0 ? PF_A : 0, tl + 0);
    ca.tl = tl + 2;
    lc = cfgof(96, 384, ch::SMEM, PDL_CH);
    cudaLaunchKernelEx(&lc, chain_kernel, ca, tmCq, tmCk, tmCv, tmCo);
    lc = cfgof(TRAIL_GRID, 384, tr::SMEM, true);
    const tr::Args ta{P.k, P.v, (unsigned char*)P.o, P.qs, (unsigned char*)P.part, xcur, P.xa, P.xn2, P.arena, layer == 0 ? 1 : 0, tl + 4};
    cudaLaunchKernelEx(&lc, trail_kernel, tmXn, tmWq, tmWo5, tmWo2, make_sched(layer), ta, pa);
    lc = cfgof(128, 384, bf::SMEM, PDL_B);
    cudaLaunchKernelEx(&lc, blayer_kernel, tmXn2, tmWb, tmO2, tmWot, P.kvacc, (unsigned*)(P.kvacc + 32 * 48 * 24), P.pq, (const bf16*)P.xa, layer == 0 ? P.xb : out,
                       layer == 0 && PF_B ? Wk : nullptr, Wv, PF_B > 1 ? Wq : nullptr, Wo, tl + 7);
    xcur = P.xb;
  }
}
```

```cpp
#include <cuda_runtime.h>
#include <cuda.h>
#include <cuda_bf16.h>
#include <stdint.h>
#include <stdlib.h>
#include <type_traits>

typedef __nv_bfloat16 bf16;

namespace cfg {
constexpr int S = 2048, DM = 640, H = 32, DH = 192, NSEG = 64, SEG = 32, NM = 8;
constexpr int HD = H * DH;
}

__device__ __forceinline__ uint32_t smem_u32(const void* p) { return (uint32_t)__cvta_generic_to_shared(p); }
__device__ __forceinline__ uint32_t mapa_u32(uint32_t a, uint32_t r) {
  uint32_t o; asm("mapa.shared::cluster.u32 %0, %1, %2;" : "=r"(o) : "r"(a), "r"(r)); return o;
}
__device__ __forceinline__ void mbar_init(uint32_t b, uint32_t c) {
  asm volatile("mbarrier.init.shared::cta.b64 [%0], %1;" :: "r"(b), "r"(c) : "memory");
}
__device__ __forceinline__ void mbar_expect_tx(uint32_t b, uint32_t bytes) {
  asm volatile("mbarrier.arrive.expect_tx.shared::cta.b64 _, [%0], %1;" :: "r"(b), "r"(bytes) : "memory");
}
__device__ __forceinline__ void mbar_arrive(uint32_t b) {
  asm volatile("mbarrier.arrive.shared::cta.b64 _, [%0];" :: "r"(b) : "memory");
}
__device__ __forceinline__ void mbar_arrive_if(bool c, uint32_t b) {
  asm volatile("{\n.reg .pred p;\nsetp.ne.u32 p, %1, 0;\n@p mbarrier.arrive.shared::cta.b64 _, [%0];\n}" :: "r"(b), "r"((uint32_t)c) : "memory");
}
__device__ __forceinline__ bool mbar_try(uint32_t b, uint32_t ph) {
  uint32_t p;
  asm volatile("{.reg .pred p; mbarrier.try_wait.parity.shared::cta.b64 p, [%1], %2; selp.u32 %0, 1, 0, p;}"
               : "=r"(p) : "r"(b), "r"(ph) : "memory");
  return p;
}
__device__ __forceinline__ bool mbar_try_cluster(uint32_t b, uint32_t ph) {
  uint32_t p;
  asm volatile("{.reg .pred p; mbarrier.try_wait.parity.acquire.cluster.shared::cta.b64 p, [%1], %2; selp.u32 %0, 1, 0, p;}"
               : "=r"(p) : "r"(b), "r"(ph) : "memory");
  return p;
}
#ifndef SPIN_LIMIT
#define SPIN_LIMIT (1 << 22)
#endif
__device__ __forceinline__ void mbar_wait(uint32_t b, uint32_t ph) {
  asm volatile("{\n.reg .pred p, q;\n.reg .u32 c;\nmov.u32 c, 0;\n"
               "W_%=:\nmbarrier.try_wait.parity.shared::cta.b64 p, [%0], %1;\n@p bra.uni D_%=;\n"
               "add.u32 c, c, 1;\nsetp.lt.u32 q, c, %2;\n@q bra.uni W_%=;\nD_%=:\n}"
               :: "r"(b), "r"(ph), "n"(SPIN_LIMIT) : "memory");
}
__device__ __forceinline__ void mbar_spin(uint32_t b, uint32_t ph) {
  asm volatile("{\n.reg .pred p, q;\n.reg .u32 c;\nmov.u32 c, 0;\n"
               "W_%=:\nmbarrier.test_wait.parity.shared::cta.b64 p, [%0], %1;\n@p bra D_%=;\n"
               "add.u32 c, c, 1;\nsetp.lt.u32 q, c, %2;\n@q bra W_%=;\nD_%=:\n}"
               :: "r"(b), "r"(ph), "n"(SPIN_LIMIT) : "memory");
}
#define PIN(x) asm volatile("" : "+r"(x))
__device__ __forceinline__ void mbar_wait_cluster(uint32_t b, uint32_t ph) {
  int s = 0;
  while (!mbar_try_cluster(b, ph)) { if (++s > SPIN_LIMIT) break; }
}
__device__ __forceinline__ void st_async_v2(uint32_t a, uint32_t x, uint32_t y, uint32_t mb) {
  asm volatile("st.async.weak.shared::cluster.mbarrier::complete_tx::bytes.v2.b32 [%0], {%1,%2}, [%3];"
               :: "r"(a), "r"(x), "r"(y), "r"(mb) : "memory");
}
__device__ __forceinline__ void st_async_v4(uint32_t a, uint32_t x, uint32_t y, uint32_t z, uint32_t w, uint32_t mb) {
  asm volatile("st.async.weak.shared::cluster.mbarrier::complete_tx::bytes.v4.b32 [%0], {%1,%2,%3,%4}, [%5];"
               :: "r"(a), "r"(x), "r"(y), "r"(z), "r"(w), "r"(mb) : "memory");
}
__device__ __forceinline__ void bulk_g2s(uint32_t dst, const void* src, uint32_t bytes, uint32_t mb) {
  asm volatile("cp.async.bulk.shared::cluster.global.mbarrier::complete_tx::bytes [%0], [%1], %2, [%3];"
               :: "r"(dst), "l"(src), "r"(bytes), "r"(mb) : "memory");
}
__device__ __forceinline__ void cp_async16(uint32_t dst, const void* src) {
  asm volatile("cp.async.cg.shared.global [%0], [%1], 16;" :: "r"(dst), "l"(src) : "memory");
}
__device__ __forceinline__ void cp_async_wait_all() { asm volatile("cp.async.wait_all;" ::: "memory"); }
__device__ __forceinline__ void fence_proxy_async() { asm volatile("fence.proxy.async.shared::cta;" ::: "memory"); }
__device__ __forceinline__ void bar_sync(int id, int n) { asm volatile("bar.sync %0, %1;" :: "r"(id), "r"(n) : "memory"); }
__device__ __forceinline__ void bar_arrive(int id, int n) { asm volatile("bar.arrive %0, %1;" :: "r"(id), "r"(n) : "memory"); }
__device__ __forceinline__ void cluster_sync_all() {
  asm volatile("barrier.cluster.arrive.release.aligned; barrier.cluster.wait.acquire.aligned;" ::: "memory");
}
__device__ __forceinline__ void ldsm_x4(uint32_t (&r)[4], uint32_t a) {
  asm volatile("ldmatrix.sync.aligned.m8n8.x4.shared.b16 {%0,%1,%2,%3}, [%4];"
               : "=r"(r[0]), "=r"(r[1]), "=r"(r[2]), "=r"(r[3]) : "r"(a) : "memory");
}
__device__ __forceinline__ void ldsm_x4_t(uint32_t (&r)[4], uint32_t a) {
  asm volatile("ldmatrix.sync.aligned.m8n8.x4.trans.shared.b16 {%0,%1,%2,%3}, [%4];"
               : "=r"(r[0]), "=r"(r[1]), "=r"(r[2]), "=r"(r[3]) : "r"(a) : "memory");
}
template <int IMM> __device__ __forceinline__ void ldsm_x4_i(uint32_t (&r)[4], uint32_t a) {
  asm volatile("ldmatrix.sync.aligned.m8n8.x4.shared.b16 {%0,%1,%2,%3}, [%4+%5];"
               : "=r"(r[0]), "=r"(r[1]), "=r"(r[2]), "=r"(r[3]) : "r"(a), "n"(IMM) : "memory");
}
template <int IMM> __device__ __forceinline__ void ldsm_x4_t_i(uint32_t (&r)[4], uint32_t a) {
  asm volatile("ldmatrix.sync.aligned.m8n8.x4.trans.shared.b16 {%0,%1,%2,%3}, [%4+%5];"
               : "=r"(r[0]), "=r"(r[1]), "=r"(r[2]), "=r"(r[3]) : "r"(a), "n"(IMM) : "memory");
}
template <int IMM> __device__ __forceinline__ uint4 lds128_i(uint32_t a) {
  uint4 v; asm volatile("ld.shared.v4.u32 {%0,%1,%2,%3}, [%4+%5];" : "=r"(v.x), "=r"(v.y), "=r"(v.z), "=r"(v.w) : "r"(a), "n"(IMM) : "memory"); return v;
}
template <int IMM> __device__ __forceinline__ uint2 lds64_i(uint32_t a) {
  uint2 v; asm volatile("ld.shared.v2.u32 {%0,%1}, [%2+%3];" : "=r"(v.x), "=r"(v.y) : "r"(a), "n"(IMM) : "memory"); return v;
}
template <int IMM> __device__ __forceinline__ void sts128_i(uint32_t a, uint32_t x, uint32_t y, uint32_t z, uint32_t w) {
  asm volatile("st.shared.v4.u32 [%0+%5], {%1,%2,%3,%4};" :: "r"(a), "r"(x), "r"(y), "r"(z), "r"(w), "n"(IMM) : "memory");
}
template <int IMM> __device__ __forceinline__ void sts64_i(uint32_t a, uint32_t x, uint32_t y) {
  asm volatile("st.shared.v2.u32 [%0+%3], {%1,%2};" :: "r"(a), "r"(x), "r"(y), "n"(IMM) : "memory");
}
template <int IMM> __device__ __forceinline__ void st_async_v2_i(uint32_t a, uint32_t x, uint32_t y, uint32_t mb) {
  asm volatile("st.async.weak.shared::cluster.mbarrier::complete_tx::bytes.v2.b32 [%0+%4], {%1,%2}, [%3];"
               :: "r"(a), "r"(x), "r"(y), "r"(mb), "n"(IMM) : "memory");
}
template <int IMM> __device__ __forceinline__ uint4 ld_relaxed_v4_i(const void* p) {
  uint4 v; asm volatile("ld.relaxed.gpu.global.v4.u32 {%0,%1,%2,%3}, [%4+%5];" : "=r"(v.x), "=r"(v.y), "=r"(v.z), "=r"(v.w) : "l"(p), "n"(IMM) : "memory"); return v;
}
template <int I, int N, class F> __device__ __forceinline__ void static_for(F&& f) {
  if constexpr (I < N) { f(std::integral_constant<int, I>{}); static_for<I + 1, N>(f); }
}
__device__ __forceinline__ uint32_t movm_t(uint32_t a) {
  uint32_t d; asm volatile("movmatrix.sync.aligned.m8n8.trans.b16 %0, %1;" : "=r"(d) : "r"(a)); return d;
}
__device__ __forceinline__ void mma16816(float (&d)[4], uint32_t a0, uint32_t a1, uint32_t a2, uint32_t a3, uint32_t b0, uint32_t b1) {
  asm volatile("mma.sync.aligned.m16n8k16.row.col.f32.bf16.bf16.f32 {%0,%1,%2,%3}, {%4,%5,%6,%7}, {%8,%9}, {%0,%1,%2,%3};"
               : "+f"(d[0]), "+f"(d[1]), "+f"(d[2]), "+f"(d[3]) : "r"(a0), "r"(a1), "r"(a2), "r"(a3), "r"(b0), "r"(b1));
}
__device__ __forceinline__ uint32_t pack_bf16(float lo, float hi) {
  uint32_t d; asm("cvt.rn.bf16x2.f32 %0, %1, %2;" : "=r"(d) : "f"(hi), "f"(lo)); return d;
}
__device__ __forceinline__ float bf_lo(uint32_t w) { return __uint_as_float(w << 16); }
__device__ __forceinline__ float bf_hi(uint32_t w) { return __uint_as_float(w & 0xffff0000u); }
__device__ __forceinline__ uint4 lds128(uint32_t a) {
  uint4 v; asm volatile("ld.shared.v4.u32 {%0,%1,%2,%3}, [%4];" : "=r"(v.x), "=r"(v.y), "=r"(v.z), "=r"(v.w) : "r"(a) : "memory"); return v;
}
__device__ __forceinline__ uint2 lds64(uint32_t a) {
  uint2 v; asm volatile("ld.shared.v2.u32 {%0,%1}, [%2];" : "=r"(v.x), "=r"(v.y) : "r"(a) : "memory"); return v;
}
__device__ __forceinline__ void sts128(uint32_t a, uint32_t x, uint32_t y, uint32_t z, uint32_t w) {
  asm volatile("st.shared.v4.u32 [%0], {%1,%2,%3,%4};" :: "r"(a), "r"(x), "r"(y), "r"(z), "r"(w) : "memory");
}
__device__ __forceinline__ void sts64(uint32_t a, uint32_t x, uint32_t y) {
  asm volatile("st.shared.v2.u32 [%0], {%1,%2};" :: "r"(a), "r"(x), "r"(y) : "memory");
}
__device__ __forceinline__ uint4 ld_relaxed_v4(const void* p) {
  uint4 v; asm volatile("ld.relaxed.gpu.global.v4.u32 {%0,%1,%2,%3}, [%4];" : "=r"(v.x), "=r"(v.y), "=r"(v.z), "=r"(v.w) : "l"(p) : "memory"); return v;
}
__device__ __forceinline__ uint32_t ld_relaxed_u32(const void* p) {
  uint32_t v; asm volatile("ld.relaxed.gpu.global.u32 %0, [%1];" : "=r"(v) : "l"(p) : "memory"); return v;
}
__device__ __forceinline__ void st_relaxed_v2(void* p, uint32_t a, uint32_t b) {
  asm volatile("st.relaxed.gpu.global.v2.u32 [%0], {%1,%2};" :: "l"(p), "r"(a), "r"(b) : "memory");
}
__device__ __forceinline__ void st_relaxed_u32(void* p, uint32_t v) {
  asm volatile("st.relaxed.gpu.global.u32 [%0], %1;" :: "l"(p), "r"(v) : "memory");
}
__device__ __forceinline__ uint32_t clk32() { uint32_t c; asm volatile("mov.u32 %0, %%clock;" : "=r"(c) :: "memory"); return c; }
__device__ __forceinline__ uint32_t clkdep(uint32_t v) {
  uint32_t c; asm volatile("{.reg .pred p; setp.eq.u32 p, %1, 0xdeadbeef; @p trap; mov.u32 %0, %%clock;}" : "=r"(c) : "r"(v) : "memory"); return c;
}
__device__ __forceinline__ void wgmma_fence() { asm volatile("wgmma.fence.sync.aligned;" ::: "memory"); }
__device__ __forceinline__ void wgmma_commit() { asm volatile("wgmma.commit_group.sync.aligned;" ::: "memory"); }
template <int N> __device__ __forceinline__ void wgmma_wait() { asm volatile("wgmma.wait_group.sync.aligned %0;" :: "n"(N) : "memory"); }
__device__ __forceinline__ void wgmma_n8_ss_ta(float (&d)[4], uint64_t da, uint64_t db, int acc) {
  asm volatile("{\n.reg .pred p;\nsetp.ne.b32 p, %6, 0;\n"
               "wgmma.mma_async.sync.aligned.m64n8k16.f32.bf16.bf16 {%0,%1,%2,%3}, %4, %5, p, 1, 1, 1, 0;\n}\n"
               : "+f"(d[0]), "+f"(d[1]), "+f"(d[2]), "+f"(d[3]) : "l"(da), "l"(db), "r"(acc));
}
__device__ __forceinline__ uint64_t make_desc(uint32_t saddr, uint32_t lbo_bytes, uint32_t sbo_bytes, uint32_t swz) {
  return (uint64_t)((saddr & 0x3FFFF) >> 4) | ((uint64_t)(lbo_bytes >> 4) << 16) | ((uint64_t)(sbo_bytes >> 4) << 32) | ((uint64_t)swz << 62);
}


__device__ __forceinline__ bool elect_one() {
  uint32_t p; asm volatile("{\n.reg .pred p;\nelect.sync _|p, 0xffffffff;\nselp.u32 %0, 1, 0, p;\n}" : "=r"(p)); return p;
}
__device__ __forceinline__ void tma_load_3d(uint32_t dst, const CUtensorMap* tm, int c0, int c1, int c2, uint32_t mb) {
  asm volatile("cp.async.bulk.tensor.3d.shared::cluster.global.mbarrier::complete_tx::bytes [%0], [%1, {%3, %4, %5}], [%2];"
               :: "r"(dst), "l"(tm), "r"(mb), "r"(c0), "r"(c1), "r"(c2) : "memory");
}
__device__ __forceinline__ void tma_load_2d(uint32_t dst, const CUtensorMap* tm, int c0, int c1, uint32_t mb) {
  asm volatile("cp.async.bulk.tensor.2d.shared::cluster.global.mbarrier::complete_tx::bytes [%0], [%1, {%3, %4}], [%2];"
               :: "r"(dst), "l"(tm), "r"(mb), "r"(c0), "r"(c1) : "memory");
}
__device__ __forceinline__ void bulk_s2g(void* dst, uint32_t src, uint32_t bytes) {
  asm volatile("cp.async.bulk.global.shared::cta.bulk_group [%0], [%1], %2;" :: "l"(dst), "r"(src), "r"(bytes) : "memory");
}
__device__ __forceinline__ uint64_t policy_evict_first() {
  uint64_t p; asm volatile("createpolicy.fractional.L2::evict_first.b64 %0, 1.0;" : "=l"(p)); return p;
}
__device__ __forceinline__ void bulk_s2g_hint(void* dst, uint32_t src, uint32_t bytes, uint64_t pol) {
  asm volatile("cp.async.bulk.global.shared::cta.bulk_group.L2::cache_hint [%0], [%1], %2, %3;" :: "l"(dst), "r"(src), "r"(bytes), "l"(pol) : "memory");
}
__device__ __forceinline__ void bulk_commit() { asm volatile("cp.async.bulk.commit_group;" ::: "memory"); }
template <int N> __device__ __forceinline__ void bulk_wait_read() { asm volatile("cp.async.bulk.wait_group.read %0;" :: "n"(N) : "memory"); }
template <int N> __device__ __forceinline__ void bulk_wait() { asm volatile("cp.async.bulk.wait_group %0;" :: "n"(N) : "memory"); }
__device__ __forceinline__ void stsm_x4(uint32_t a, uint32_t r0, uint32_t r1, uint32_t r2, uint32_t r3) {
  asm volatile("stmatrix.sync.aligned.m8n8.x4.shared.b16 [%0], {%1,%2,%3,%4};" :: "r"(a), "r"(r0), "r"(r1), "r"(r2), "r"(r3) : "memory");
}
__device__ __forceinline__ void stsm_x2(uint32_t a, uint32_t r0, uint32_t r1) {
  asm volatile("stmatrix.sync.aligned.m8n8.x2.shared.b16 [%0], {%1,%2};" :: "r"(a), "r"(r0), "r"(r1) : "memory");
}
__device__ __forceinline__ void ldsm_x2(uint32_t (&r)[2], uint32_t a) {
  asm volatile("ldmatrix.sync.aligned.m8n8.x2.shared.b16 {%0,%1}, [%2];" : "=r"(r[0]), "=r"(r[1]) : "r"(a) : "memory");
}
__device__ __forceinline__ void ldsm_x2_t(uint32_t (&r)[2], uint32_t a) {
  asm volatile("ldmatrix.sync.aligned.m8n8.x2.trans.shared.b16 {%0,%1}, [%2];" : "=r"(r[0]), "=r"(r[1]) : "r"(a) : "memory");
}
__device__ __forceinline__ float bf16r(float x) { return __uint_as_float(pack_bf16(0.f, x) & 0xffff0000u); }
__device__ __forceinline__ void bf16r2(float& a, float& b) { const uint32_t w = pack_bf16(a, b); a = bf_lo(w); b = bf_hi(w); }
__device__ __forceinline__ float rcpf(float x) { float r; asm("rcp.approx.ftz.f32 %0, %1;" : "=f"(r) : "f"(x)); return r; }
__device__ __forceinline__ float ex2f(float x) { float e; asm("ex2.approx.ftz.f32 %0, %1;" : "=f"(e) : "f"(x)); return e; }
__device__ __forceinline__ void prefetch_tmap(const CUtensorMap* tm) { asm volatile("prefetch.tensormap [%0];" :: "l"(tm) : "memory"); }

#ifdef TIMELINE
__device__ unsigned long long g_tl[2 * 64];
__device__ unsigned long long g_log[2 * 132 * 64 * 2 + 2];
__device__ unsigned long long g_tl2[4 * 64];
__device__ __forceinline__ unsigned long long gtime() { unsigned long long t; asm volatile("mov.u64 %0, %%globaltimer;" : "=l"(t)); return t; }
#define TL_BEGIN(id) do { if (threadIdx.x == 0) atomicMin(&g_tl[2 * (id)], gtime()); } while (0)
#define TL_END(id) do { if ((threadIdx.x & 31) == 0) atomicMax(&g_tl[2 * (id) + 1], gtime()); } while (0)
#define TL_ACC(idx, t0) do { if (threadIdx.x == 0 && m >= 4 && m < 11) { atomicAdd(&g_tl2[idx], gtime() - (t0)); atomicAdd(&g_tl2[(idx) + 1], 1ull); } } while (0)
#define TL_NOW() gtime()
#define TL2(idx) do { if (threadIdx.x == 0) atomicMax(&g_tl2[idx], gtime()); } while (0)
#else
#define TL_ACC(idx, t0)
#define TL_NOW() 0ull
#define TL2(idx)
#define TL_BEGIN(id)
#define TL_END(id)
#endif
template <int TA, int TB> __device__ __forceinline__ void wgmma_n192(float (&d)[96], uint64_t da, uint64_t db, int acc) {
  asm volatile("{\n.reg .pred p;\nsetp.ne.b32 p, %98, 0;\n"
    "wgmma.mma_async.sync.aligned.m64n192k16.f32.bf16.bf16 {%0, %1, %2, %3, %4, %5, %6, %7, %8, %9, %10, %11, %12, %13, %14, %15, %16, %17, %18, %19, %20, %21, %22, %23, %24, %25, %26, %27, %28, %29, %30, %31, %32, %33, %34, %35, %36, %37, %38, %39, %40, %41, %42, %43, %44, %45, %46, %47, %48, %49, %50, %51, %52, %53, %54, %55, %56, %57, %58, %59, %60, %61, %62, %63, %64, %65, %66, %67, %68, %69, %70, %71, %72, %73, %74, %75, %76, %77, %78, %79, %80, %81, %82, %83, %84, %85, %86, %87, %88, %89, %90, %91, %92, %93, %94, %95}, %96, %97, p, 1, 1, %99, %100;\n}\n"
    : "+f"(d[0]), "+f"(d[1]), "+f"(d[2]), "+f"(d[3]), "+f"(d[4]), "+f"(d[5]), "+f"(d[6]), "+f"(d[7]), "+f"(d[8]), "+f"(d[9]), "+f"(d[10]), "+f"(d[11]), "+f"(d[12]), "+f"(d[13]), "+f"(d[14]), "+f"(d[15]), "+f"(d[16]), "+f"(d[17]), "+f"(d[18]), "+f"(d[19]), "+f"(d[20]), "+f"(d[21]), "+f"(d[22]), "+f"(d[23]), "+f"(d[24]), "+f"(d[25]), "+f"(d[26]), "+f"(d[27]), "+f"(d[28]), "+f"(d[29]), "+f"(d[30]), "+f"(d[31]), "+f"(d[32]), "+f"(d[33]), "+f"(d[34]), "+f"(d[35]), "+f"(d[36]), "+f"(d[37]), "+f"(d[38]), "+f"(d[39]), "+f"(d[40]), "+f"(d[41]), "+f"(d[42]), "+f"(d[43]), "+f"(d[44]), "+f"(d[45]), "+f"(d[46]), "+f"(d[47]), "+f"(d[48]), "+f"(d[49]), "+f"(d[50]), "+f"(d[51]), "+f"(d[52]), "+f"(d[53]), "+f"(d[54]), "+f"(d[55]), "+f"(d[56]), "+f"(d[57]), "+f"(d[58]), "+f"(d[59]), "+f"(d[60]), "+f"(d[61]), "+f"(d[62]), "+f"(d[63]), "+f"(d[64]), "+f"(d[65]), "+f"(d[66]), "+f"(d[67]), "+f"(d[68]), "+f"(d[69]), "+f"(d[70]), "+f"(d[71]), "+f"(d[72]), "+f"(d[73]), "+f"(d[74]), "+f"(d[75]), "+f"(d[76]), "+f"(d[77]), "+f"(d[78]), "+f"(d[79]), "+f"(d[80]), "+f"(d[81]), "+f"(d[82]), "+f"(d[83]), "+f"(d[84]), "+f"(d[85]), "+f"(d[86]), "+f"(d[87]), "+f"(d[88]), "+f"(d[89]), "+f"(d[90]), "+f"(d[91]), "+f"(d[92]), "+f"(d[93]), "+f"(d[94]), "+f"(d[95])
    : "l"(da), "l"(db), "r"(acc), "n"(TA), "n"(TB));
}

template <int TA, int TB> __device__ __forceinline__ void wgmma_n256(float (&d)[128], uint64_t da, uint64_t db, int acc) {
  asm volatile("{\n.reg .pred p;\nsetp.ne.b32 p, %130, 0;\n"
    "wgmma.mma_async.sync.aligned.m64n256k16.f32.bf16.bf16 {%0, %1, %2, %3, %4, %5, %6, %7, %8, %9, %10, %11, %12, %13, %14, %15, %16, %17, %18, %19, %20, %21, %22, %23, %24, %25, %26, %27, %28, %29, %30, %31, %32, %33, %34, %35, %36, %37, %38, %39, %40, %41, %42, %43, %44, %45, %46, %47, %48, %49, %50, %51, %52, %53, %54, %55, %56, %57, %58, %59, %60, %61, %62, %63, %64, %65, %66, %67, %68, %69, %70, %71, %72, %73, %74, %75, %76, %77, %78, %79, %80, %81, %82, %83, %84, %85, %86, %87, %88, %89, %90, %91, %92, %93, %94, %95, %96, %97, %98, %99, %100, %101, %102, %103, %104, %105, %106, %107, %108, %109, %110, %111, %112, %113, %114, %115, %116, %117, %118, %119, %120, %121, %122, %123, %124, %125, %126, %127}, %128, %129, p, 1, 1, %131, %132;\n}\n"
    : "+f"(d[0]), "+f"(d[1]), "+f"(d[2]), "+f"(d[3]), "+f"(d[4]), "+f"(d[5]), "+f"(d[6]), "+f"(d[7]), "+f"(d[8]), "+f"(d[9]), "+f"(d[10]), "+f"(d[11]), "+f"(d[12]), "+f"(d[13]), "+f"(d[14]), "+f"(d[15]), "+f"(d[16]), "+f"(d[17]), "+f"(d[18]), "+f"(d[19]), "+f"(d[20]), "+f"(d[21]), "+f"(d[22]), "+f"(d[23]), "+f"(d[24]), "+f"(d[25]), "+f"(d[26]), "+f"(d[27]), "+f"(d[28]), "+f"(d[29]), "+f"(d[30]), "+f"(d[31]), "+f"(d[32]), "+f"(d[33]), "+f"(d[34]), "+f"(d[35]), "+f"(d[36]), "+f"(d[37]), "+f"(d[38]), "+f"(d[39]), "+f"(d[40]), "+f"(d[41]), "+f"(d[42]), "+f"(d[43]), "+f"(d[44]), "+f"(d[45]), "+f"(d[46]), "+f"(d[47]), "+f"(d[48]), "+f"(d[49]), "+f"(d[50]), "+f"(d[51]), "+f"(d[52]), "+f"(d[53]), "+f"(d[54]), "+f"(d[55]), "+f"(d[56]), "+f"(d[57]), "+f"(d[58]), "+f"(d[59]), "+f"(d[60]), "+f"(d[61]), "+f"(d[62]), "+f"(d[63]), "+f"(d[64]), "+f"(d[65]), "+f"(d[66]), "+f"(d[67]), "+f"(d[68]), "+f"(d[69]), "+f"(d[70]), "+f"(d[71]), "+f"(d[72]), "+f"(d[73]), "+f"(d[74]), "+f"(d[75]), "+f"(d[76]), "+f"(d[77]), "+f"(d[78]), "+f"(d[79]), "+f"(d[80]), "+f"(d[81]), "+f"(d[82]), "+f"(d[83]), "+f"(d[84]), "+f"(d[85]), "+f"(d[86]), "+f"(d[87]), "+f"(d[88]), "+f"(d[89]), "+f"(d[90]), "+f"(d[91]), "+f"(d[92]), "+f"(d[93]), "+f"(d[94]), "+f"(d[95]), "+f"(d[96]), "+f"(d[97]), "+f"(d[98]), "+f"(d[99]), "+f"(d[100]), "+f"(d[101]), "+f"(d[102]), "+f"(d[103]), "+f"(d[104]), "+f"(d[105]), "+f"(d[106]), "+f"(d[107]), "+f"(d[108]), "+f"(d[109]), "+f"(d[110]), "+f"(d[111]), "+f"(d[112]), "+f"(d[113]), "+f"(d[114]), "+f"(d[115]), "+f"(d[116]), "+f"(d[117]), "+f"(d[118]), "+f"(d[119]), "+f"(d[120]), "+f"(d[121]), "+f"(d[122]), "+f"(d[123]), "+f"(d[124]), "+f"(d[125]), "+f"(d[126]), "+f"(d[127])
    : "l"(da), "l"(db), "r"(acc), "n"(TA), "n"(TB));
}

template <int TA, int TB> __device__ __forceinline__ void wgmma_n64(float (&d)[32], uint64_t da, uint64_t db, int acc) {
  asm volatile("{\n.reg .pred p;\nsetp.ne.b32 p, %34, 0;\n"
    "wgmma.mma_async.sync.aligned.m64n64k16.f32.bf16.bf16 {%0, %1, %2, %3, %4, %5, %6, %7, %8, %9, %10, %11, %12, %13, %14, %15, %16, %17, %18, %19, %20, %21, %22, %23, %24, %25, %26, %27, %28, %29, %30, %31}, %32, %33, p, 1, 1, %35, %36;\n}\n"
    : "+f"(d[0]), "+f"(d[1]), "+f"(d[2]), "+f"(d[3]), "+f"(d[4]), "+f"(d[5]), "+f"(d[6]), "+f"(d[7]), "+f"(d[8]), "+f"(d[9]), "+f"(d[10]), "+f"(d[11]), "+f"(d[12]), "+f"(d[13]), "+f"(d[14]), "+f"(d[15]), "+f"(d[16]), "+f"(d[17]), "+f"(d[18]), "+f"(d[19]), "+f"(d[20]), "+f"(d[21]), "+f"(d[22]), "+f"(d[23]), "+f"(d[24]), "+f"(d[25]), "+f"(d[26]), "+f"(d[27]), "+f"(d[28]), "+f"(d[29]), "+f"(d[30]), "+f"(d[31])
    : "l"(da), "l"(db), "r"(acc), "n"(TA), "n"(TB));
}

template <int TA, int TB> __device__ __forceinline__ void wgmma_n80(float (&d)[40], uint64_t da, uint64_t db, int acc) {
  asm volatile("{\n.reg .pred p;\nsetp.ne.b32 p, %42, 0;\n"
    "wgmma.mma_async.sync.aligned.m64n80k16.f32.bf16.bf16 {%0, %1, %2, %3, %4, %5, %6, %7, %8, %9, %10, %11, %12, %13, %14, %15, %16, %17, %18, %19, %20, %21, %22, %23, %24, %25, %26, %27, %28, %29, %30, %31, %32, %33, %34, %35, %36, %37, %38, %39}, %40, %41, p, 1, 1, %43, %44;\n}\n"
    : "+f"(d[0]), "+f"(d[1]), "+f"(d[2]), "+f"(d[3]), "+f"(d[4]), "+f"(d[5]), "+f"(d[6]), "+f"(d[7]), "+f"(d[8]), "+f"(d[9]), "+f"(d[10]), "+f"(d[11]), "+f"(d[12]), "+f"(d[13]), "+f"(d[14]), "+f"(d[15]), "+f"(d[16]), "+f"(d[17]), "+f"(d[18]), "+f"(d[19]), "+f"(d[20]), "+f"(d[21]), "+f"(d[22]), "+f"(d[23]), "+f"(d[24]), "+f"(d[25]), "+f"(d[26]), "+f"(d[27]), "+f"(d[28]), "+f"(d[29]), "+f"(d[30]), "+f"(d[31]), "+f"(d[32]), "+f"(d[33]), "+f"(d[34]), "+f"(d[35]), "+f"(d[36]), "+f"(d[37]), "+f"(d[38]), "+f"(d[39])
    : "l"(da), "l"(db), "r"(acc), "n"(TA), "n"(TB));
}

template <int TA, int TB> __device__ __forceinline__ void wgmma_n144(float (&d)[72], uint64_t da, uint64_t db, int acc) {
  asm volatile("{\n.reg .pred p;\nsetp.ne.b32 p, %74, 0;\n"
    "wgmma.mma_async.sync.aligned.m64n144k16.f32.bf16.bf16 {%0, %1, %2, %3, %4, %5, %6, %7, %8, %9, %10, %11, %12, %13, %14, %15, %16, %17, %18, %19, %20, %21, %22, %23, %24, %25, %26, %27, %28, %29, %30, %31, %32, %33, %34, %35, %36, %37, %38, %39, %40, %41, %42, %43, %44, %45, %46, %47, %48, %49, %50, %51, %52, %53, %54, %55, %56, %57, %58, %59, %60, %61, %62, %63, %64, %65, %66, %67, %68, %69, %70, %71}, %72, %73, p, 1, 1, %75, %76;\n}\n"
    : "+f"(d[0]), "+f"(d[1]), "+f"(d[2]), "+f"(d[3]), "+f"(d[4]), "+f"(d[5]), "+f"(d[6]), "+f"(d[7]), "+f"(d[8]), "+f"(d[9]), "+f"(d[10]), "+f"(d[11]), "+f"(d[12]), "+f"(d[13]), "+f"(d[14]), "+f"(d[15]), "+f"(d[16]), "+f"(d[17]), "+f"(d[18]), "+f"(d[19]), "+f"(d[20]), "+f"(d[21]), "+f"(d[22]), "+f"(d[23]), "+f"(d[24]), "+f"(d[25]), "+f"(d[26]), "+f"(d[27]), "+f"(d[28]), "+f"(d[29]), "+f"(d[30]), "+f"(d[31]), "+f"(d[32]), "+f"(d[33]), "+f"(d[34]), "+f"(d[35]), "+f"(d[36]), "+f"(d[37]), "+f"(d[38]), "+f"(d[39]), "+f"(d[40]), "+f"(d[41]), "+f"(d[42]), "+f"(d[43]), "+f"(d[44]), "+f"(d[45]), "+f"(d[46]), "+f"(d[47]), "+f"(d[48]), "+f"(d[49]), "+f"(d[50]), "+f"(d[51]), "+f"(d[52]), "+f"(d[53]), "+f"(d[54]), "+f"(d[55]), "+f"(d[56]), "+f"(d[57]), "+f"(d[58]), "+f"(d[59]), "+f"(d[60]), "+f"(d[61]), "+f"(d[62]), "+f"(d[63]), "+f"(d[64]), "+f"(d[65]), "+f"(d[66]), "+f"(d[67]), "+f"(d[68]), "+f"(d[69]), "+f"(d[70]), "+f"(d[71])
    : "l"(da), "l"(db), "r"(acc), "n"(TA), "n"(TB));
}

template <int TA, int TB> __device__ __forceinline__ void wgmma_n128(float (&d)[64], uint64_t da, uint64_t db, int acc) {
  asm volatile("{\n.reg .pred p;\nsetp.ne.b32 p, %66, 0;\n"
    "wgmma.mma_async.sync.aligned.m64n128k16.f32.bf16.bf16 {%0, %1, %2, %3, %4, %5, %6, %7, %8, %9, %10, %11, %12, %13, %14, %15, %16, %17, %18, %19, %20, %21, %22, %23, %24, %25, %26, %27, %28, %29, %30, %31, %32, %33, %34, %35, %36, %37, %38, %39, %40, %41, %42, %43, %44, %45, %46, %47, %48, %49, %50, %51, %52, %53, %54, %55, %56, %57, %58, %59, %60, %61, %62, %63}, %64, %65, p, 1, 1, %67, %68;\n}\n"
    : "+f"(d[0]), "+f"(d[1]), "+f"(d[2]), "+f"(d[3]), "+f"(d[4]), "+f"(d[5]), "+f"(d[6]), "+f"(d[7]), "+f"(d[8]), "+f"(d[9]), "+f"(d[10]), "+f"(d[11]), "+f"(d[12]), "+f"(d[13]), "+f"(d[14]), "+f"(d[15]), "+f"(d[16]), "+f"(d[17]), "+f"(d[18]), "+f"(d[19]), "+f"(d[20]), "+f"(d[21]), "+f"(d[22]), "+f"(d[23]), "+f"(d[24]), "+f"(d[25]), "+f"(d[26]), "+f"(d[27]), "+f"(d[28]), "+f"(d[29]), "+f"(d[30]), "+f"(d[31]), "+f"(d[32]), "+f"(d[33]), "+f"(d[34]), "+f"(d[35]), "+f"(d[36]), "+f"(d[37]), "+f"(d[38]), "+f"(d[39]), "+f"(d[40]), "+f"(d[41]), "+f"(d[42]), "+f"(d[43]), "+f"(d[44]), "+f"(d[45]), "+f"(d[46]), "+f"(d[47]), "+f"(d[48]), "+f"(d[49]), "+f"(d[50]), "+f"(d[51]), "+f"(d[52]), "+f"(d[53]), "+f"(d[54]), "+f"(d[55]), "+f"(d[56]), "+f"(d[57]), "+f"(d[58]), "+f"(d[59]), "+f"(d[60]), "+f"(d[61]), "+f"(d[62]), "+f"(d[63])
    : "l"(da), "l"(db), "r"(acc), "n"(TA), "n"(TB));
}

template <int TB> __device__ __forceinline__ void wgmma_rs_n40(float (&d)[20], uint32_t a0, uint32_t a1, uint32_t a2, uint32_t a3, uint64_t db, int acc) {
  asm volatile("{\n.reg .pred p;\nsetp.ne.b32 p, %25, 0;\n"
    "wgmma.mma_async.sync.aligned.m64n40k16.f32.bf16.bf16 {%0, %1, %2, %3, %4, %5, %6, %7, %8, %9, %10, %11, %12, %13, %14, %15, %16, %17, %18, %19}, {%20, %21, %22, %23}, %24, p, 1, 1, %26;\n}\n"
    : "+f"(d[0]), "+f"(d[1]), "+f"(d[2]), "+f"(d[3]), "+f"(d[4]), "+f"(d[5]), "+f"(d[6]), "+f"(d[7]), "+f"(d[8]), "+f"(d[9]), "+f"(d[10]), "+f"(d[11]), "+f"(d[12]), "+f"(d[13]), "+f"(d[14]), "+f"(d[15]), "+f"(d[16]), "+f"(d[17]), "+f"(d[18]), "+f"(d[19])
    : "r"(a0), "r"(a1), "r"(a2), "r"(a3), "l"(db), "r"(acc), "n"(TB));
}

template <int TB> __device__ __forceinline__ void wgmma_rs_n192(float (&d)[96], uint32_t a0, uint32_t a1, uint32_t a2, uint32_t a3, uint64_t db, int acc) {
  asm volatile("{\n.reg .pred p;\nsetp.ne.b32 p, %101, 0;\n"
    "wgmma.mma_async.sync.aligned.m64n192k16.f32.bf16.bf16 {%0, %1, %2, %3, %4, %5, %6, %7, %8, %9, %10, %11, %12, %13, %14, %15, %16, %17, %18, %19, %20, %21, %22, %23, %24, %25, %26, %27, %28, %29, %30, %31, %32, %33, %34, %35, %36, %37, %38, %39, %40, %41, %42, %43, %44, %45, %46, %47, %48, %49, %50, %51, %52, %53, %54, %55, %56, %57, %58, %59, %60, %61, %62, %63, %64, %65, %66, %67, %68, %69, %70, %71, %72, %73, %74, %75, %76, %77, %78, %79, %80, %81, %82, %83, %84, %85, %86, %87, %88, %89, %90, %91, %92, %93, %94, %95}, {%96, %97, %98, %99}, %100, p, 1, 1, %102;\n}\n"
    : "+f"(d[0]), "+f"(d[1]), "+f"(d[2]), "+f"(d[3]), "+f"(d[4]), "+f"(d[5]), "+f"(d[6]), "+f"(d[7]), "+f"(d[8]), "+f"(d[9]), "+f"(d[10]), "+f"(d[11]), "+f"(d[12]), "+f"(d[13]), "+f"(d[14]), "+f"(d[15]), "+f"(d[16]), "+f"(d[17]), "+f"(d[18]), "+f"(d[19]), "+f"(d[20]), "+f"(d[21]), "+f"(d[22]), "+f"(d[23]), "+f"(d[24]), "+f"(d[25]), "+f"(d[26]), "+f"(d[27]), "+f"(d[28]), "+f"(d[29]), "+f"(d[30]), "+f"(d[31]), "+f"(d[32]), "+f"(d[33]), "+f"(d[34]), "+f"(d[35]), "+f"(d[36]), "+f"(d[37]), "+f"(d[38]), "+f"(d[39]), "+f"(d[40]), "+f"(d[41]), "+f"(d[42]), "+f"(d[43]), "+f"(d[44]), "+f"(d[45]), "+f"(d[46]), "+f"(d[47]), "+f"(d[48]), "+f"(d[49]), "+f"(d[50]), "+f"(d[51]), "+f"(d[52]), "+f"(d[53]), "+f"(d[54]), "+f"(d[55]), "+f"(d[56]), "+f"(d[57]), "+f"(d[58]), "+f"(d[59]), "+f"(d[60]), "+f"(d[61]), "+f"(d[62]), "+f"(d[63]), "+f"(d[64]), "+f"(d[65]), "+f"(d[66]), "+f"(d[67]), "+f"(d[68]), "+f"(d[69]), "+f"(d[70]), "+f"(d[71]), "+f"(d[72]), "+f"(d[73]), "+f"(d[74]), "+f"(d[75]), "+f"(d[76]), "+f"(d[77]), "+f"(d[78]), "+f"(d[79]), "+f"(d[80]), "+f"(d[81]), "+f"(d[82]), "+f"(d[83]), "+f"(d[84]), "+f"(d[85]), "+f"(d[86]), "+f"(d[87]), "+f"(d[88]), "+f"(d[89]), "+f"(d[90]), "+f"(d[91]), "+f"(d[92]), "+f"(d[93]), "+f"(d[94]), "+f"(d[95])
    : "r"(a0), "r"(a1), "r"(a2), "r"(a3), "l"(db), "r"(acc), "n"(TB));
}
constexpr uint32_t AR_ACC = 0;
constexpr uint32_t AR_TAB = 0x100000;
constexpr uint32_t AR_PROG = 0x101000;
#ifndef PROG_STRIDE
#define PROG_STRIDE 128
#endif
constexpr uint32_t AR_CNT = 0x108000;
constexpr uint32_t AR_QUEUE = 0x109000;
constexpr uint32_t AR_SIZE = 0x10a000;

struct ChainArgs {
  const bf16* mem0;
  const uint2* xh;
  unsigned char *kg, *vg;
  unsigned char* arena;
  uint32_t* dbg;
  uint32_t delay;
  int tl;
};

namespace ch {
constexpr int OFF_WQ = 0;
constexpr int OFF_X = 81920;
constexpr int OFF_MEM = OFF_X + 40960;
constexpr int OFF_WO = OFF_MEM + 10240;
constexpr int WOK = 8 * 896;
constexpr int OFF_KV = OFF_WO + 10 * WOK;
constexpr int KVB = 5120;
constexpr int OFF_O = OFF_KV + 4 * KVB;
constexpr int OFF_Q = OFF_O + 1024;
constexpr int OFF_S = OFF_O + 3072;
constexpr int OFF_SR = OFF_S + 1280;
constexpr int OFF_BAR = OFF_SR + 1536;
constexpr int SMEM = OFF_BAR + 128 + 1152;
static_assert(SMEM <= 232448, "smem");
constexpr int MB_S = OFF_BAR, MB_O = OFF_BAR + 8, MB_X = OFF_BAR + 16;
constexpr int MB_K = OFF_SR + 1408, MB_V = MB_K + 16, MB_Q = MB_K + 32, MB_R = MB_K + 48;
constexpr int SC_IN = OFF_BAR + 64;
constexpr int SC_MX = OFF_S;
constexpr int SC_W = OFF_BAR + 96;
constexpr int WOS = 448;
enum { B_MEM0 = 1, B_QK, B_SL, B_V, B_O, B_RED, B_X, B_C, B_H, B_MEM1, B_A, B_G };
#ifndef NQ1
#define NQ1 6
#endif
#ifndef NQ0
#define NQ0 4
#endif
#ifndef NP0
#define NP0 4
#endif
#ifndef NWO
#define NWO 5
#endif
#ifndef NWP
#define NWP 4
#endif
#ifndef NB0
#define NB0 2
#endif
#ifndef BBS
#define BBS 100
#endif
#ifndef VSYNC
#define VSYNC 0
#endif
#ifndef XPOS
#define XPOS 0
#endif
#ifndef XPD
#define XPD 300
#endif
#ifndef WOF
#define WOF 0
#endif
#ifndef XBYTES
#define XBYTES 36864
#endif
#ifndef NRT
#define NRT 7
#endif
#ifndef NRF
#define NRF 2
#endif
#ifndef NPM0
#define NPM0 2
#endif
#ifndef NPM1
#define NPM1 2
#endif
#ifndef RSYNC
#define RSYNC 1
#endif
#ifndef PFK
#define PFK 1
#endif
#ifndef PA0
#define PA0 7
#endif
#ifndef PA1
#define PA1 0
#endif
#ifndef PB0
#define PB0 7
#endif
#ifndef PB1
#define PB1 5
#endif
#ifndef PQE
#define PQE 0
#endif
#ifndef XT
#define XT 30
#endif
static_assert(NPM0 >= 2 && NPM1 >= 2, "the K / V blocks live in the last two k-steps of Wo");
}

#ifndef CHAIN_TIMING
#define CHAIN_TIMING 0
#endif
#if CHAIN_TIMING
#ifndef TR0
#define TR0 41
#endif
#ifndef TSMASK
#define TSMASK 0xffff
#endif
#define TSV(i, v) do { if ((TSMASK >> (i)) & 1) asm volatile("st.shared.u32 [%0+%1], %2;" :: "r"(tsb), "n"((i) * 4), "r"(v) : "memory"); } while (0)
#define TS(i) TSV(i, clk32())
#define TS_SETUP() const uint32_t tsb = sb + ((s == TR0 || s == TR0 + 1) ? OFF_BAR + 128 + ((s - TR0) * 12 + warp) * 48 : OFF_SR + 1152)
#else
#define TS(i)
#define TSV(i, v)
#define TS_SETUP()
#endif
#ifndef POLL_DELAY
#define POLL_DELAY 590
#endif
#ifndef XN
#define XN 40
#endif
#ifndef PF0
#define PF0 8
#endif
#ifndef PFS
#define PFS 3
#endif
#ifndef XDELAY
#define XDELAY 0
#endif
#ifndef NOKM
#define NOKM 0
#endif
#ifndef PFACC
#define PFACC 1
#endif
template <int V> using IC = std::integral_constant<int, V>;
__device__ __forceinline__ uint32_t clk_v() { uint64_t c; asm volatile("mov.u64 %0, %%clock64;" : "=l"(c) :: "memory"); return (uint32_t)c; }
__device__ __forceinline__ int fresh(int x) { int y; asm volatile("shfl.sync.bfly.b32 %0, %1, 0, 0x1f, 0xffffffff;" : "=r"(y) : "r"(x)); return y; }
#define SFENCE2(x, d) asm volatile("{\n.reg .pred p;\nsetp.eq.u32 p, %0, 0x7fffffff;\n@p st.shared.u32 [%0], %1;\n}" :: "r"(x), "r"(d) : "memory")
#define SFENCE(x) asm volatile("{\n.reg .pred p;\nsetp.eq.u32 p, %0, 0x7fffffff;\n@p st.shared.u32 [%0], %0;\n}" :: "r"(x) : "memory")
template <int I> __device__ __forceinline__ void bbfence(uint32_t x) {
  asm volatile("{\n.reg .pred p;\nsetp.eq.u32 p, %0, %1;\nL_%=:\n@p st.volatile.shared.u32 [%0], %0;\n@p bra.uni L_%=;\n}" :: "r"(x), "n"(4 * I) : "memory");
}
__device__ __forceinline__ float uniform_f(float x) { return __uint_as_float(__reduce_max_sync(0xffffffffu, __float_as_uint(x))); }

__device__ __forceinline__ void mma16816h(float (&d)[4], const uint32_t (&a)[4], uint32_t b0, uint32_t b1) {
  asm volatile("mma.sync.aligned.m16n8k16.row.col.f32.f16.f16.f32 {%0,%1,%2,%3}, {%4,%5,%6,%7}, {%8,%9}, {%0,%1,%2,%3};"
               : "+f"(d[0]), "+f"(d[1]), "+f"(d[2]), "+f"(d[3]) : "r"(a[0]), "r"(a[1]), "r"(a[2]), "r"(a[3]), "r"(b0), "r"(b1));
}
__device__ __forceinline__ void mma1688(float (&d)[4], uint32_t a0, uint32_t a1, uint32_t b0) {
  asm volatile("mma.sync.aligned.m16n8k8.row.col.f32.bf16.bf16.f32 {%0,%1,%2,%3}, {%4,%5}, {%6}, {%0,%1,%2,%3};"
               : "+f"(d[0]), "+f"(d[1]), "+f"(d[2]), "+f"(d[3]) : "r"(a0), "r"(a1), "r"(b0));
}
template <int OFF16, int ACC> __device__ __forceinline__ void wgmma_rs32h(float (&d)[16], const uint32_t (&a)[4], uint32_t dlo) {
  asm volatile("{\n.reg .pred p;\n.reg .b32 t;\n.reg .b64 db;\nsetp.ne.b32 p, %22, 0;\nadd.u32 t, %20, %21;\nmov.b64 db, {t, 0x40000040};\n"
    "wgmma.mma_async.sync.aligned.m64n32k16.f32.f16.f16 {%0,%1,%2,%3,%4,%5,%6,%7,%8,%9,%10,%11,%12,%13,%14,%15}, {%16,%17,%18,%19}, db, p, 1, 1, 0;\n}\n"
    : "+f"(d[0]), "+f"(d[1]), "+f"(d[2]), "+f"(d[3]), "+f"(d[4]), "+f"(d[5]), "+f"(d[6]), "+f"(d[7]), "+f"(d[8]), "+f"(d[9]), "+f"(d[10]), "+f"(d[11]),
      "+f"(d[12]), "+f"(d[13]), "+f"(d[14]), "+f"(d[15])
    : "r"(a[0]), "r"(a[1]), "r"(a[2]), "r"(a[3]), "r"(dlo), "n"(OFF16), "n"(ACC));
}
template <int IMM> __device__ __forceinline__ void stsm_x4_t_i(uint32_t a, uint32_t r0, uint32_t r1, uint32_t r2, uint32_t r3) {
  asm volatile("stmatrix.sync.aligned.m8n8.x4.trans.shared.b16 [%0+%5], {%1,%2,%3,%4};" :: "r"(a), "r"(r0), "r"(r1), "r"(r2), "r"(r3), "n"(IMM) : "memory");
}
template <int IMM> __device__ __forceinline__ void stsm_x2_t_i(uint32_t a, uint32_t r0, uint32_t r1) {
  asm volatile("stmatrix.sync.aligned.m8n8.x2.trans.shared.b16 [%0+%3], {%1,%2};" :: "r"(a), "r"(r0), "r"(r1), "n"(IMM) : "memory");
}
template <int IMM> __device__ __forceinline__ void st_async_b32_i(uint32_t a, uint32_t x, uint32_t mb) {
  asm volatile("st.async.weak.shared::cluster.mbarrier::complete_tx::bytes.b32 [%0+%3], %1, [%2];" :: "r"(a), "r"(x), "r"(mb), "n"(IMM) : "memory");
}
template <int IMM> __device__ __forceinline__ void ld_relaxed_v4_if(uint4& v, const void* p, uint32_t c) {
  asm volatile("{\n.reg .pred p;\nsetp.ne.u32 p, %6, 0;\n@p ld.relaxed.gpu.global.v4.u32 {%0,%1,%2,%3}, [%4+%5];\n}"
               : "+r"(v.x), "+r"(v.y), "+r"(v.z), "+r"(v.w) : "l"(p), "n"(IMM), "r"(c) : "memory");
}
template <int IMM> __device__ __forceinline__ uint32_t lds32_i(uint32_t a) {
  uint32_t v; asm volatile("ld.shared.u32 %0, [%1+%2];" : "=r"(v) : "r"(a), "n"(IMM) : "memory"); return v;
}
__device__ __forceinline__ void sts32(uint32_t a, uint32_t v) { asm volatile("st.shared.u32 [%0], %1;" :: "r"(a), "r"(v) : "memory"); }
__device__ __forceinline__ uint32_t pack_f16(float lo, float hi) {
  uint32_t d; asm("cvt.rn.f16x2.f32 %0, %1, %2;" : "=r"(d) : "f"(hi), "f"(lo)); return d;
}
__device__ __forceinline__ uint32_t amax_bf2(uint32_t a, uint32_t b) { uint32_t d; asm("max.xorsign.abs.bf16x2 %0, %1, %2;" : "=r"(d) : "r"(a), "r"(b)); return d; }
__device__ __forceinline__ uint32_t amax_h2(uint32_t a, uint32_t b) { uint32_t d; asm("max.xorsign.abs.f16x2 %0, %1, %2;" : "=r"(d) : "r"(a), "r"(b)); return d; }
__device__ __forceinline__ uint32_t amax_fold(uint32_t m) { return __reduce_max_sync(0xffffffffu, max(m & 0x7fffu, (m >> 16) & 0x7fffu)); }
__device__ __forceinline__ int wscale_exp(uint32_t m) { return min(141 - (int)(m >> 7), 100); }
__device__ __forceinline__ float exp2i(int e) { return __uint_as_float((uint32_t)(e + 127) << 23); }
__device__ __forceinline__ uint32_t bf2_to_h2(uint32_t w, float sc) { return pack_f16(bf_lo(w) * sc, bf_hi(w) * sc); }
__device__ __forceinline__ void bf2_to_h2_inplace(uint32_t& w, uint32_t sc2) {
  asm volatile("{\n.reg .b32 t, lo, hi;\nmul.rn.bf16x2 t, %0, %1;\nshl.b32 lo, t, 16;\nand.b32 hi, t, 0xffff0000;\ncvt.rn.f16x2.f32 %0, hi, lo;\n}" : "+r"(w) : "r"(sc2));
}
__device__ __forceinline__ void prefetch_l2(const void* p, uint32_t bytes) { asm volatile("cp.async.bulk.prefetch.L2.global [%0], %1;" :: "l"(p), "r"(bytes) : "memory"); }
__device__ __forceinline__ void prefetch_tma_2d(const CUtensorMap* tm, int c0, int c1) {
  asm volatile("cp.async.bulk.prefetch.tensor.2d.L2.global [%0, {%1, %2}];" :: "l"(tm), "r"(c0), "r"(c1) : "memory");
}
__host__ __device__ constexpr uint32_t acc_voff(int v) { return v < 4 ? v * 1024u : (v == 4 ? 128u : 3072u + 128u); }
__device__ __forceinline__ int unit28(int i) { return i == 3 ? 54 : 14 * i; }
__device__ __forceinline__ int unit24(int i) { return i < 2 ? 48 - 6 * i : 56 + 6 * i; }
__device__ __forceinline__ uint32_t acc_step(int s) { return (s >> 1) * 32768 + (s & 1) * 512; }
__device__ __forceinline__ uint32_t acc_lane(int i, int lane) { return ((lane >> 3) & 1) * 256 + (lane >> 4) * 4096 + i * 8192 + (lane & 7) * 16; }

__device__ __forceinline__ uint32_t ld_acquire_u32(const void* p) {
  uint32_t v; asm volatile("ld.acquire.gpu.global.u32 %0, [%1];" : "=r"(v) : "l"(p) : "memory"); return v;
}
template <int R> __device__ __forceinline__ void ln_rows(const uint2 (&xw)[R][5], int row0, int lane, bf16* __restrict__ xn, uint2* __restrict__ xh) {
  float v[R][20], s[R], q[R];
#pragma unroll
  for (int r = 0; r < R; r++) {
    s[r] = 0.f; q[r] = 0.f;
#pragma unroll
    for (int i = 0; i < 5; i++) { v[r][4 * i] = bf_lo(xw[r][i].x); v[r][4 * i + 1] = bf_hi(xw[r][i].x); v[r][4 * i + 2] = bf_lo(xw[r][i].y); v[r][4 * i + 3] = bf_hi(xw[r][i].y); }
#pragma unroll
    for (int i = 0; i < 5; i++) s[r] += (v[r][4 * i] + v[r][4 * i + 1]) + (v[r][4 * i + 2] + v[r][4 * i + 3]);
  }
#pragma unroll
  for (int o = 16; o; o >>= 1)
#pragma unroll
    for (int r = 0; r < R; r++) s[r] += __shfl_xor_sync(0xffffffffu, s[r], o);
#pragma unroll
  for (int r = 0; r < R; r++) {
    s[r] *= 1.f / cfg::DM;
#pragma unroll
    for (int i = 0; i < 10; i++) { const float d = v[r][2 * i] - s[r], e = v[r][2 * i + 1] - s[r]; q[r] += d * d + e * e; }
  }
#pragma unroll
  for (int o = 16; o; o >>= 1)
#pragma unroll
    for (int r = 0; r < R; r++) q[r] += __shfl_xor_sync(0xffffffffu, q[r], o);
#pragma unroll
  for (int r = 0; r < R; r++) {
    const int row = row0 + r;
    const float mb = bf16r(s[r]), var = bf16r(q[r] * (1.f / cfg::DM));
    const float den = bf16r(sqrtf(bf16r(var + 1e-5f)));
#pragma unroll
    for (int i = 0; i < 5; i++) {
      float y[4];
#pragma unroll
      for (int e = 0; e < 4; e++) y[e] = __fdividef(bf16r(v[r][4 * i + e] - mb), den);
      const uint32_t w0 = pack_bf16(y[0], y[1]), w1 = pack_bf16(y[2], y[3]);
      *(uint2*)(xn + (size_t)row * cfg::DM + i * 128 + lane * 4) = make_uint2(w0, w1);
      if (xh) xh[(((size_t)(row >> 5) * 10 + 2 * i + (lane >> 4)) * 32 + (row & 31)) * 16 + ((((lane >> 1) & 7) ^ (row & 7)) << 1) + (lane & 1)] =
          make_uint2(pack_f16(bf_lo(w0), bf_hi(w0)), pack_f16(bf_lo(w1), bf_hi(w1)));
    }
  }
}

__global__ void __cluster_dims__(3, 1, 1) __launch_bounds__(384, 1) chain_kernel(const ChainArgs a, const __grid_constant__ CUtensorMap tmWq,
    const __grid_constant__ CUtensorMap tmWk, const __grid_constant__ CUtensorMap tmWv, const __grid_constant__ CUtensorMap tmWo) {
  using namespace ch;
  extern __shared__ __align__(1024) unsigned char smem_raw[];
  const uint32_t sb = smem_u32(smem_raw);
  const int warp = __shfl_sync(0xffffffffu, (int)threadIdx.x >> 5, 0);
  const int lane = __shfl_sync(0xffffffffu, (int)threadIdx.x & 31, threadIdx.x & 31);
  const int cta = blockIdx.x, h = cta / 3, j = cta % 3;
  const int g = lane >> 2, q4 = lane & 3, r8 = lane & 7, m4 = lane >> 3;
  unsigned char* const arena = a.arena;
  if (sb & 1023u) __trap();
  TL_BEGIN(a.tl);
  const int col0 = j == 0 ? 0 : (j == 1 ? 224 : 432);
  auto stage_w = [&](const CUtensorMap* tm, uint32_t dst, uint32_t mb, int half) {
    mbar_expect_tx(mb + 8 * half, 40960);
    tma_load_2d(dst + half * 40960, tm, h * cfg::DH + j * 64, half * 320, mb + 8 * half);
    tma_load_2d(dst + half * 40960 + 20480, tm, h * cfg::DH + j * 64, half * 320 + 160, mb + 8 * half);
  };
  if (threadIdx.x == 256) {
    for (int i = 0; i < 9; i++) mbar_init(sb + MB_K + 8 * i, 1);
    mbar_init(sb + MB_S, 1); mbar_init(sb + MB_O, 1); mbar_init(sb + MB_X, 1);
    asm volatile("fence.mbarrier_init.release.cluster;" ::: "memory");
    for (int i = 0; i < 2; i++) { stage_w(&tmWk, sb + OFF_WQ, sb + MB_K, i); stage_w(&tmWv, sb + OFF_WO, sb + MB_V, i); }
    sts32(sb + SC_W, 0); sts32(sb + SC_W + 4, 0); sts32(sb + SC_W + 8, 0); sts32(sb + SC_IN + 12, 0); sts32(sb + SC_IN + 20, 0);
    mbar_expect_tx(sb + MB_S, 1280); mbar_expect_tx(sb + MB_O, 2048);
  }
  __syncthreads();
  asm volatile("barrier.cluster.arrive.relaxed.aligned;" ::: "memory");
  const uint32_t d1 = mapa_u32(sb, (j + 1) % 3) - sb, d2 = mapa_u32(sb, (j + 2) % 3) - sb;

  if (warp >= 8) {
    asm volatile("setmaxnreg.dec.sync.aligned.u32 40;");
    const int hw = warp - 8, ht = hw * 32 + lane;
    const bool lead = ht == 0;
    auto stage_wo = [&](int i) {
      mbar_expect_tx(sb + MB_R + 8 * i, 64 * WOS);
      tma_load_2d(sb + OFF_WO + i * 64 * WOS, &tmWo, col0, h * cfg::DH + ((i + j) % 3) * 64, sb + MB_R + 8 * i);
    };
    const unsigned char* xg = (const unsigned char*)a.xh;
    auto issue_x = [&](int s) { mbar_expect_tx(sb + MB_X, 40960); bulk_g2s(sb + OFF_X, xg + (size_t)s * 40960, 40960, sb + MB_X); };
    uint4 v[5];
#pragma unroll
    for (int i = 0; i < 5; i++) { const int c = ht + 128 * i; v[i] = ld_relaxed_v4(a.mem0 + (c & 7) * cfg::DM + (c >> 3) * 8); }
    if (hw == 2) {
      asm volatile("griddepcontrol.wait;" ::: "memory");
      asm volatile("griddepcontrol.launch_dependents;" ::: "memory");
      if (lane == 0) issue_x(0);
    }
    if (hw == 0) {
      bar_sync(B_QK, 160); if (lane == 0) stage_w(&tmWq, sb + OFF_WQ, sb + MB_Q, 0);
      bar_sync(B_SL, 160); if (lane == 0) stage_w(&tmWq, sb + OFF_WQ, sb + MB_Q, 1);
    }
    if (hw == 1) {
      bar_sync(B_V, 160); if (lane == 0) stage_wo(0);
      bar_sync(B_O, 160); if (lane == 0) { stage_wo(1); stage_wo(2); }
    }
    __syncwarp();
    {
      uint32_t m = 0;
#pragma unroll
      for (int i = 0; i < 5; i++) {
        m = amax_bf2(amax_bf2(m, amax_bf2(v[i].x, v[i].y)), amax_bf2(v[i].z, v[i].w));
      }
      m = amax_fold(m);
      if (lane == 0) sts32(sb + SC_MX + hw * 4, m);
      bar_sync(B_H, 128);
      const uint4 mm = lds128(sb + SC_MX);
      const int se = max(wscale_exp(max(max(mm.x, mm.y), max(mm.z, mm.w))), -100);
      const float sc = exp2i(se);
#pragma unroll
      for (int i = 0; i < 5; i++) {
        const int c = ht + 128 * i, t = c & 7, chn = c >> 3;
        sts128(sb + OFF_MEM + chn * 128 + ((t ^ (2 * (chn & 3))) << 4), bf2_to_h2(v[i].x, sc), bf2_to_h2(v[i].y, sc), bf2_to_h2(v[i].z, sc), bf2_to_h2(v[i].w, sc));
      }
      if (lead) { sts32(sb + SC_IN, __float_as_uint(exp2i(-se))); sts32(sb + SC_IN + 4, 0x7800u); }
    }
    {
      const uint32_t p0 = sb + OFF_WQ + hw * 2048 + lane * 16;
      uint32_t m = 0;
#pragma unroll 1
      for (int i = 0; i < 10; i++) {
        if (i == 0 || i == 5) mbar_wait(sb + MB_Q + (i ? 8 : 0), 0);
        uint32_t r[4][4];
        static_for<0, 4>([&](auto K) { ldsm_x4_i<K.value * 512>(r[K.value], p0 + i * 8192); });
#pragma unroll
        for (int k = 0; k < 4; k++) m = amax_bf2(amax_bf2(m, amax_bf2(r[k][0], r[k][1])), amax_bf2(r[k][2], r[k][3]));
      }
      m = amax_fold(m);
      if (lane == 0) asm volatile("red.shared.max.u32 [%0], %1;" :: "r"(sb + SC_W + 8), "r"(m) : "memory");
      bar_sync(B_H, 128);
      const uint32_t sc = (uint32_t)(wscale_exp(lds32_i<SC_W + 8>(sb)) + 127) * 0x00800080u;
#pragma unroll 1
      for (int i = 0; i < 10; i++) {
        uint32_t r[4][4];
        static_for<0, 4>([&](auto K) { ldsm_x4_i<K.value * 512>(r[K.value], p0 + i * 8192); });
#pragma unroll
        for (int k = 0; k < 4; k++) {
          bf2_to_h2_inplace(r[k][0], sc); bf2_to_h2_inplace(r[k][1], sc); bf2_to_h2_inplace(r[k][2], sc); bf2_to_h2_inplace(r[k][3], sc);
          stsm_x4(p0 + i * 8192 + k * 512, r[k][0], r[k][1], r[k][2], r[k][3]);
        }
      }
    }
    bar_sync(0, 384);
    if (lead) st_relaxed_u32(arena + AR_TAB + cta * 4, 0x80000000u | (lds32_i<SC_W>(sb) << 15) | lds32_i<SC_W + 4>(sb));
    asm volatile("barrier.cluster.wait.aligned;" ::: "memory");
    bar_sync(B_MEM0, 256); bar_sync(B_MEM1, 256);
    {
      uint32_t v0, v1, v2; int spin = 0;
      do {
        v0 = ld_relaxed_u32(arena + AR_TAB + lane * 4); v1 = ld_relaxed_u32(arena + AR_TAB + 128 + lane * 4); v2 = ld_relaxed_u32(arena + AR_TAB + 256 + lane * 4);
      } while (__any_sync(0xffffffffu, ((v0 & v1 & v2) >> 31) == 0) && ++spin < SPIN_LIMIT);
      const uint32_t mv = (max(max(v0, v1), v2) >> 15) & 0x7fffu, mo = max(max(v0 & 0x7fffu, v1 & 0x7fffu), v2 & 0x7fffu);
      sts32(sb + SC_IN + 8 + (lane & 1) * 16, 15 - ((__reduce_max_sync(0xffffffffu, mv) >> 7) + (__reduce_max_sync(0xffffffffu, mo) >> 7) - 252 + 22));
    }

    auto store_kv = [&](int s) {
      const size_t o = ((size_t)s * 96 + cta) * KVB; const uint32_t src = sb + OFF_KV + (s & 1) * (2 * KVB);
      fence_proxy_async(); bulk_s2g(a.kg + o, src, KVB); bulk_s2g(a.vg + o, src + KVB, KVB); bulk_commit();
    };
    const int cb28 = unit28(hw), du = (unit24(hw) - cb28) * 128;
    int ln = lane;
#ifdef TIMELINE
    if (cta == 0 && lead) { g_tl2[(a.tl >= 12) * 128 + 0] = clock64(); g_tl2[(a.tl >= 12) * 128 + 1] = gtime(); }
#endif
#pragma unroll 1
    for (int s = 0; s < cfg::NSEG; s++) {
      TS_SETUP();
      const bool last = s == cfg::NSEG - 1;
      if (ln == 0) {
        if (hw == 2 && !last) issue_x(s + 1);
        if (hw == 0 && s > 0) store_kv(s - 1);
        if (PFACC && hw == 1 && s + PFACC < cfg::NSEG - 1)
          asm volatile("prefetch.global.L2 [%0];" :: "l"(arena + (AR_ACC + acc_step(s + PFACC) + acc_lane(cta / 24, (cta & 3) * 8) + acc_voff((cta % 24) >> 2))) : "memory");
      }
      __syncwarp();
      if (last) break;
      const uint32_t kv = (s & 1) * (2 * KVB);
      ln = fresh(ln);
      uint32_t kb0[4], kb1[4];
      { const uint32_t ka = sb + kv + hw * 128 + (ln >> 3) * 640 + (ln & 7) * 16; ldsm_x4_i<OFF_KV>(kb0, ka); ldsm_x4_i<OFF_KV + 2560>(kb1, ka); }
      const uint32_t l16 = sb + ln * 16, s8 = sb + ln * 8, xs = s8 + hw * 256, xr = sb + ln * 4 + (hw >> 1) * 512 + (hw & 1) * 128;
      TS(1);
      bar_sync(B_QK, 384);
      {
        uint32_t q0[4], q1[4], q2[4], q3[4];
        float sa[4] = {0, 0, 0, 0}, sc2[4] = {0, 0, 0, 0};
        ldsm_x4_i<OFF_Q>(q0, l16); ldsm_x4_i<OFF_Q + 1024>(q2, l16); ldsm_x4_i<OFF_Q + 512>(q1, l16);
        bar_arrive(B_A, 288);
        ldsm_x4_i<OFF_Q + 1536>(q3, l16);
        mma16816(sa, q0[0], q0[1], q0[2], q0[3], kb0[0], kb0[1]);
        mma16816(sc2, q2[0], q2[1], q2[2], q2[3], kb1[0], kb1[1]);
        mma16816(sa, q1[0], q1[1], q1[2], q1[3], kb0[2], kb0[3]);
        mma16816(sc2, q3[0], q3[1], q3[2], q3[3], kb1[2], kb1[3]);
        const float x0 = (sa[0] + sa[2]) + (sc2[0] + sc2[2]), x1 = (sa[1] + sa[3]) + (sc2[1] + sc2[3]);
        const uint32_t xp = pack_bf16(x0, x1);
        st_async_b32_i<OFF_SR + 256>(xr + d1, xp, sb + MB_S + d1);
        st_async_b32_i<OFF_SR>(xr + d2, xp, sb + MB_S + d2);
        sts64_i<OFF_S>(xs, __float_as_uint(x0), __float_as_uint(x1));
      }
      TS(3);
      bar_sync(B_SL, 256);
      float t0[4], t1[4], t2[4] = {0, 0, 0, 0};
      float osc;
      {
        const uint4 si = lds128_i<SC_IN>(sb + 16 * (s & 1));
        { const uint2 x = lds64_i<OFF_S>(s8), y = lds64_i<OFF_S + 256>(s8); t0[0] = __uint_as_float(x.x); t0[1] = __uint_as_float(x.y); t0[2] = __uint_as_float(y.x); t0[3] = __uint_as_float(y.y); }
        { const uint2 x = lds64_i<OFF_S + 512>(s8), y = lds64_i<OFF_S + 768>(s8); t1[0] = __uint_as_float(x.x); t1[1] = __uint_as_float(x.y); t1[2] = __uint_as_float(y.x); t1[3] = __uint_as_float(y.y); }
        { const uint2 x = lds64_i<OFF_S + 1024>(s8); t2[0] = __uint_as_float(x.x); t2[1] = __uint_as_float(x.y); }
        const int em = (int)(si.y >> 10) - 14 + (int)(si.x >> 23) - 127;
        osc = exp2i(max(min((int)si.z - max(em, 1), 100), -100));
      }
      const uint32_t xo = sb + hw * 256 + (ln & 2) * 64 + (ln >> 2) * 16 + (ln & 1) * 8;
      const uint32_t eye = ((ln >> 3) == (ln & 3)) ? ((ln & 4) ? 0x3f800000u : 0x3f80u) : 0u;
      mbar_spin(sb + MB_S, s & 1);
      TS(4);
      uint32_t v0[4], v1[4], vm[2];
      {
        uint32_t r0[4], r1[4], r2[4];
        ldsm_x4_i<OFF_SR>(r0, l16); ldsm_x4_i<OFF_SR + 512>(r1, l16); ldsm_x4_i<OFF_SR + 1024>(r2, l16);
        mma16816(t0, r0[0], r0[1], r0[2], r0[3], eye, eye);
        mma16816(t1, r1[0], r1[1], r1[2], r1[3], eye, eye);
        mma16816(t2, r2[0], r2[1], r2[2], r2[3], eye, eye);
      }
      float sc[10] = {t0[0], t0[1], t0[2], t0[3], t1[0], t1[1], t1[2], t1[3], t2[0], t2[1]};
      const float cs = 0.07216878364870322f * 1.4426950408889634f;
      float mx = fmaxf(fmaxf(fmaxf(sc[0], sc[1]), fmaxf(sc[2], sc[3])), fmaxf(fmaxf(sc[4], sc[5]), fmaxf(sc[6], sc[7])));
      mx = fmaxf(mx, fmaxf(sc[8], sc[9]));
      {
        const float m1 = __shfl_xor_sync(0xffffffffu, mx, 1), m2 = __shfl_xor_sync(0xffffffffu, mx, 2), m3 = __shfl_xor_sync(0xffffffffu, mx, 3);
        SFENCE2(l16, __float_as_uint(mx));
        ldsm_x4_t_i<OFF_KV + KVB>(v0, l16 + (kv + hw * 1280)); ldsm_x4_t_i<OFF_KV + KVB + 640>(v1, l16 + (kv + hw * 1280));
        bar_sync(B_V, 256);
        bar_arrive(B_G, 384);
        ldsm_x2_t(vm, l16 + (ln & 8) * 64 + (kv + hw * 1280 + OFF_KV + KVB + 512));
        mx = fmaxf(fmaxf(mx, m1), fmaxf(m2, m3));
      }
      const float mo = mx * cs;
#pragma unroll
      for (int i = 0; i < 10; i++) sc[i] = ex2f(fmaf(sc[i], cs, -mo));
      const uint32_t p0 = pack_bf16(sc[0], sc[1]), p1 = pack_bf16(sc[2], sc[3]), p2 = pack_bf16(sc[4], sc[5]), p3 = pack_bf16(sc[6], sc[7]), p4 = pack_bf16(sc[8], sc[9]);
      TS(5);
      float oa[4] = {0, 0, 0, 0}, ob[4] = {0, 0, 0, 0}, oc[4] = {0, 0, 0, 0}, od[4] = {0, 0, 0, 0}, rs[4] = {0, 0, 0, 0};
      const uint32_t ones = 0x3f803f80u;
      mma16816(rs, p0, p2, p1, p3, ones, ones);
      mma16816(oc, p0, p2, p1, p3, v0[2], v0[3]);
      mma16816(od, p0, p2, p1, p3, v1[2], v1[3]);
      mma16816(oa, p0, p2, p1, p3, v0[0], v0[1]);
      mma16816(ob, p0, p2, p1, p3, v1[0], v1[1]);
      mma1688(rs, p4, 0u, ones);
      mma1688(oa, p4, 0u, vm[0]);
      mma1688(ob, p4, 0u, vm[1]);
      const float inv = rcpf(rs[0] + rs[2]) * osc;
      {
        const uint32_t y0 = pack_bf16((oa[0] + oc[2]) * inv, (oa[1] + oc[3]) * inv), y1 = pack_bf16((ob[0] + od[2]) * inv, (ob[1] + od[3]) * inv);
        st_async_v2_i<OFF_O + 2048>(xo + d1, y0, y1, sb + MB_O + d1);
        st_async_v2_i<OFF_O + 1024>(xo + d2, y0, y1, sb + MB_O + d2);
        sts64_i<OFF_O>(xo, y0, y1);
      }
      bar_arrive(B_O, 384);
      TS(6);
      if (ln == 0) {
        if (hw == 0) {
          bulk_wait<0>();
          if ((s & 3) == 0 && s > 0) {
            st_relaxed_u32(arena + (AR_PROG + (cta + ln) * PROG_STRIDE), s);
          }
        }
        if (hw == 3) { mbar_expect_tx(sb + MB_S, 1280); sts64_i<SC_IN>(sb + 16 * ((s + 1) & 1), 0x7f000000u - __float_as_uint(osc), 0u); }
      }
      __syncwarp();
      ln = fresh(ln);
      auto mslot = [&](int c) -> uint32_t { return sb + OFF_MEM + c * 128 + (((ln >> 2) ^ (2 * (c & 3))) << 4); };
      const int lq = ln & 3;
      const uint32_t ma = mslot(cb28 + lq), mb_ = mslot(cb28 + (lq >> 1)) + (lq & 1) * 8;
      const unsigned char* gp = arena + (AR_ACC + acc_lane(hw, ln) + acc_step(s));
      const bool odd = ln & 1;
      SFENCE(ma);
      bar_sync(B_RED, 384);
      SFENCE(mb_);
      const uint32_t tw = clk_v();
      TSV(7, tw);
      if (ln == 0 && hw == 3) mbar_expect_tx(sb + MB_O, 2048);
      __syncwarp();
      while (clk_v() - tw < a.delay) {}
      TS(8);
      uint4 v[6];
      int spin = 0;
      const uint32_t cm = odd ? 0x5000u : 0u;
      do {
        static_for<0, 6>([&](auto I) { v[I.value] = ld_relaxed_v4_i<acc_voff(I.value)>(gp); });
      } while (__any_sync(0xffffffffu, (~((v[0].w & v[1].w & v[2].w) & (v[3].w & v[4].w & v[5].w)) & cm) != 0) && ++spin < SPIN_LIMIT);
      v[0].w = odd ? v[3].x : v[0].w; v[1].w = odd ? v[3].y : v[1].w; v[2].w = odd ? v[3].z : v[2].w; v[3].w = odd ? 0u : v[3].w;
      sts128_i<0>(ma, v[0].x, v[0].y, v[0].z, v[0].w);
      sts128_i<512>(ma, v[1].x, v[1].y, v[1].z, v[1].w);
      sts128_i<1024>(ma, v[2].x, v[2].y, v[2].z, v[2].w);
      sts128_i<0>(ma + du, v[4].x, v[4].y, v[4].z, v[5].z);
      sts64_i<512>(mb_ + du, v[5].x, v[5].y);
      if (!odd) sts128_i<1536>(mb_, v[3].x, v[3].y, v[3].z, v[3].w);
      TSV(11, spin);
#ifdef TIMELINE
      if (spin && ln == 0) atomicAdd(&g_tl2[(a.tl >= 12) * 128 + 4], 1ull);
#endif
      TS(10);
      bar_sync(B_MEM0, 256); bar_sync(B_MEM1, 256);
      uint32_t m = lds32_i<SC_IN + 12>(sb);
      uint32_t m2 = m;
      static_for<0, 3>([&](auto I) { m = amax_h2(amax_h2(amax_h2(amax_h2(m, v[I.value].x), v[I.value].y), v[I.value].z), v[I.value].w); });
      static_for<3, 6>([&](auto I) { m2 = amax_h2(amax_h2(amax_h2(m2, v[I.value].x), v[I.value].y), v[I.value].z); });
      m = amax_fold(amax_h2(amax_h2(m2, v[3].w), m));
      if (ln == 0) asm volatile("red.shared.max.u32 [%0], %1;" :: "r"(sb + SC_IN + 4 + 16 * ((s + 1) & 1)), "r"(m) : "memory");
    }
    bar_sync(B_RED, 384);
    if (hw == 0 && ln == 0) {
      store_kv(cfg::NSEG - 1);
      bulk_wait<0>();
      st_relaxed_u32(arena + AR_PROG + cta * PROG_STRIDE, cfg::NSEG);
    }
    __syncwarp();
#ifdef TIMELINE
    if (cta == 0 && hw == 0 && ln == 0) { g_tl2[(a.tl >= 12) * 128 + 2] = clock64(); g_tl2[(a.tl >= 12) * 128 + 3] = gtime(); }
#endif
    TL_END(a.tl);
    asm volatile("barrier.cluster.arrive.relaxed.aligned; barrier.cluster.wait.aligned;" ::: "memory");
  } else {
    asm volatile("setmaxnreg.inc.sync.aligned.u32 232;");
    const int wi = warp & 3, hf = warp >> 2, tid = warp * 32 + lane;
    uint32_t w[40][4];
    uint32_t wqa;
    { const int mrow = r8 + ((lane >> 4) << 3), mch = 2 * wi + (m4 & 1); wqa = sb + mrow * 128 + ((mch ^ r8) << 4); }
    {
      const uint32_t wa = wqa + (hf ? OFF_WO : OFF_WQ);
      mbar_wait(sb + (hf ? MB_V : MB_K), 0);
      static_for<0, 20>([&](auto K) { ldsm_x4_t_i<K.value * 2048>(w[K.value], wa); });
      bar_arrive(hf ? B_V : B_QK, 160);
      mbar_wait(sb + (hf ? MB_V : MB_K) + 8, 0);
      static_for<20, 40>([&](auto K) { ldsm_x4_t_i<K.value * 2048>(w[K.value], wa); });
      bar_arrive(hf ? B_O : B_SL, 160);
      SFENCE(wa);
    }
    float iw, iq;
    {
      uint32_t m = 0;
#pragma unroll
      for (int k = 0; k < 40; k++) m = amax_bf2(amax_bf2(m, amax_bf2(w[k][0], w[k][1])), amax_bf2(w[k][2], w[k][3]));
      m = amax_fold(m);
      if (hf && lane == 0) asm volatile("red.shared.max.u32 [%0], %1;" :: "r"(sb + SC_W), "r"(m) : "memory");
      const int e = wscale_exp(m);
      const uint32_t sc = (uint32_t)(e + 127) * 0x00800080u; iw = exp2i(-e);
#pragma unroll
      for (int k = 0; k < 40; k++) { bf2_to_h2_inplace(w[k][0], sc); bf2_to_h2_inplace(w[k][1], sc); bf2_to_h2_inplace(w[k][2], sc); bf2_to_h2_inplace(w[k][3], sc); }
    }
    uint32_t x0[8];
    {
      float xa[16];
      const uint32_t dlo = (((sb + OFF_X) & 0x3FFFF) >> 4) | (1u << 16);
      mbar_wait(sb + MB_X, 0);
      wgmma_fence();
      static_for<0, 40>([&](auto K) { constexpr int k = K.value; wgmma_rs32h<((k >> 2) * 4096 + (k & 3) * 32) / 16, (k != 0)>(xa, w[k], dlo); });
      wgmma_commit();
      wgmma_wait<0>();
#pragma unroll
      for (int i = 0; i < 8; i++) x0[i] = pack_bf16(xa[2 * i] * iw, xa[2 * i + 1] * iw);
    }
    const bool t28 = j == 0 || warp < 4;
    const int bi = j == 0 ? hf : (warp < 4 ? j + 1 : 2 * (j - 1) + ((warp - 4) >> 1)), bv = t28 ? wi : 4 + (warp & 1);
    uint32_t wo1 = sb + OFF_WO + warp * 896 + lane * 16, wo2;
    {
      const int cb = (t28 ? unit28(bi) : unit24(bi)) - col0 / 8;
      uint32_t cp[4];
#pragma unroll
      for (int wd = 0; wd < 4; wd++) {
        int c, p;
        if (bv < 3) { c = 4 * bv + q4; p = wd; }
        else if (bv == 3) { if (q4 & 1) { c = 4 * (wd % 3) + q4; p = 3; } else { c = 12 + (q4 >> 1); p = wd; } }
        else if (bv == 4) { c = q4; p = wd; }
        else { if (wd < 2) { c = 4 + (q4 >> 1); p = 2 * (q4 & 1) + wd; } else { c = q4; p = 3; } }
        cp[wd] = sb + OFF_WO + ((g & 1) + (g & 2) * 4 + (g >> 2) * 2) * WOS + (cb + c) * 16 + p * 4;
      }
      const int cidx = (r8 & 1) + ((r8 >> 2) << 1);
      wo2 = sb + OFF_WO + warp * 896 + ((m4 & 1) ? 768 + (m4 >> 1) * 64 + cidx * 16 : 512 + (m4 >> 1) * 128 + r8 * 16);
      const bool dump = (m4 & 1) && (r8 & 2);
      uint32_t mo = 0;
      const bool regular = bv < 3 || bv == 4;
#pragma unroll 1
      for (int i = 0; i < 3; i++) {
        uint32_t x[4][4], y[4][4];
        const uint32_t o = i * 4 * WOK;
        mbar_wait(sb + MB_R + 8 * i, 0);
        if (regular) {
          static_for<0, 4>([&](auto K) {
            constexpr int kk = K.value;
            const uint4 u = lds128_i<kk * WOK>(cp[0] + o), v = lds128_i<kk * WOK + 4 * WOS>(cp[0] + o);
            x[kk][0] = u.x; x[kk][1] = u.y; x[kk][2] = u.z; x[kk][3] = u.w; y[kk][0] = v.x; y[kk][1] = v.y; y[kk][2] = v.z; y[kk][3] = v.w;
          });
        } else {
          static_for<0, 4>([&](auto K) {
            constexpr int kk = K.value;
#pragma unroll
            for (int wd = 0; wd < 4; wd++) { x[kk][wd] = lds32_i<kk * WOK>(cp[wd] + o); y[kk][wd] = lds32_i<kk * WOK + 4 * WOS>(cp[wd] + o); }
          });
        }
        bar_sync(B_C, 256);
        static_for<0, 4>([&](auto K) {
          constexpr int kk = K.value;
#pragma unroll
          for (int wd = 0; wd < 4; wd++) mo = amax_bf2(mo, amax_bf2(x[kk][wd], y[kk][wd]));
          stsm_x4_t_i<kk * WOK>(wo1 + o, x[kk][0], x[kk][1], y[kk][0], y[kk][1]);
          stsm_x4_t_i<0>(dump ? sb + OFF_S + 512 + lane * 16 : wo2 + o + kk * WOK, x[kk][2], x[kk][3], y[kk][2], y[kk][3]);
        });
      }
      mo = amax_fold(mo);
      if (lane == 0) asm volatile("red.shared.max.u32 [%0], %1;" :: "r"(sb + SC_W + 4), "r"(mo) : "memory");
    }
    __syncwarp();
    auto run = [&](auto HF) {
    constexpr int hf = HF.value;
    uint32_t mema, sta, l16 = sb + lane * 16;
    uint32_t rq[hf ? NQ1 : NQ0][4];
    auto step_addr = [&](uint32_t kv) {
      const int lr = (l16 >> 4) & 7, lm = (l16 >> 7) & 3;
      mema = l16 ^ (lm << 5);
      sta = sb + lr * 16 + (lm < 2 ? OFF_Q + wi * 512 + hf * 128 + lm * 256 : OFF_KV + kv + 512 + (2 * wi + lm - 2) * 640);
    };
    auto x_gemm = [&](uint32_t ph, [[maybe_unused]] uint32_t tsb) {
      float xa[16];
      const uint32_t dlo = (((sb + OFF_X) & 0x3FFFF) >> 4) | (1u << 16);
      constexpr int NP = hf ? NQ1 : NP0;
      if constexpr (hf) {
        static_for<PQE, NP>([&](auto K) { ldsm_x4_t_i<OFF_WQ + K.value * 2048>(rq[K.value], wqa); });
        bar_sync(B_X, 256);
      }
      wgmma_fence();
      static_for<0, 40>([&](auto K) {
        constexpr int k = K.value;
        wgmma_rs32h<((k >> 2) * 4096 + (k & 3) * 32) / 16, (k != 0)>(xa, w[k], dlo);
        if constexpr (!hf && k == PFK && NP > PQE) { SFENCE(wqa); static_for<PQE, NP>([&](auto K) { ldsm_x4_t_i<OFF_WQ + K.value * 2048>(rq[K.value], wqa); }); SFENCE(wqa); }
        if constexpr (!hf && k == XT) bar_arrive(B_X, 256);
      });
      step_addr(ph * (2 * KVB));
      wgmma_commit();
      TS(9);
      wgmma_wait<0>();
      const uint32_t xs = l16 + (wi * 1280 + ph * (2 * KVB));
      stsm_x4_t_i<OFF_KV + hf * KVB>(xs, pack_bf16(xa[0] * iw, xa[1] * iw), pack_bf16(xa[4] * iw, xa[5] * iw), pack_bf16(xa[8] * iw, xa[9] * iw), pack_bf16(xa[12] * iw, xa[13] * iw));
      stsm_x4_t_i<OFF_KV + hf * KVB + 640>(xs, pack_bf16(xa[2] * iw, xa[3] * iw), pack_bf16(xa[6] * iw, xa[7] * iw), pack_bf16(xa[10] * iw, xa[11] * iw), pack_bf16(xa[14] * iw, xa[15] * iw));
    };
    auto wq_addr = [&](uint32_t l) -> uint32_t {
      const int lr = (l >> 4) & 7, lm = (l >> 7) & 3;
      return sb + hf * ((40 - NQ1) * 2048) + (lr + ((lm >> 1) << 3)) * 128 + (((2 * wi + (lm & 1)) ^ lr) << 4);
    };
    constexpr int NPM = hf ? NPM1 : NPM0;
    uint32_t u1[NPM][4], u2[NPM][4];
    static_for<0, NPM>([&](auto K) { ldsm_x4_i<(12 - NPM + K.value) * WOK>(u1[K.value], wo1); ldsm_x4_i<(12 - NPM + K.value) * WOK>(u2[K.value], wo2); });
    bar_sync(0, 384);
    iq = uniform_f(exp2i(-wscale_exp(lds32_i<SC_W + 8>(sb))));
    wqa = wq_addr(l16);
    static_for<0, (hf ? NQ1 : NP0)>([&](auto K) { ldsm_x4_t_i<OFF_WQ + K.value * 2048>(rq[K.value], wqa); });
    step_addr(0);
    stsm_x4_t_i<OFF_KV + hf * KVB>(l16 + wi * 1280, x0[0], x0[2], x0[4], x0[6]);
    stsm_x4_t_i<OFF_KV + hf * KVB + 640>(l16 + wi * 1280, x0[1], x0[3], x0[5], x0[7]);
    asm volatile("barrier.cluster.wait.aligned;" ::: "memory");
    TL_END(a.tl + 1);
#pragma unroll 1
    for (int s = 0; s < cfg::NSEG; s++) {
      TS_SETUP();
      const bool last = s == cfg::NSEG - 1;
#if CHAIN_TIMING
      if (tid == 0 && (s & 7) == 0) a.dbg[96 * 288 + cta * 8 + (s >> 3)] = clk32();
#endif
      bar_sync(hf ? B_MEM1 : B_MEM0, 256);
      const float sin_ = __uint_as_float(lds32_i<SC_IN>(sb + 16 * (s & 1)));
      constexpr int NPQ = (40 - NQ1) / 2;
      if constexpr (hf == 0) {
        float k0[4] = {0, 0, 0, 0}, k1[4] = {0, 0, 0, 0}, q0[4] = {0, 0, 0, 0}, q1[4] = {0, 0, 0, 0};
        constexpr auto pair_of = [](int t) { const int a = t * (20 - NPQ) / 20, b = (t + 1) * (20 - NPQ) / 20; return b > a ? NPQ + a : t - a; };
        uint32_t b[NB0][4];
        static_for<0, NB0>([&](auto T) { ldsm_x4_i<OFF_MEM + pair_of(T.value) * 512>(b[T.value], mema); });
        static_for<NP0, NQ0>([&](auto K) { ldsm_x4_t_i<OFF_WQ + K.value * 2048>(rq[K.value], wqa); });
        if (BBS < 100) bbfence<0>(mema);
        static_for<0, 20>([&](auto T) {
          constexpr int t = T.value, p = pair_of(t);
          uint32_t (&bb)[4] = b[t % NB0];
          if constexpr (p < NPQ) {
            mma16816h(q0, rq[(2 * p) % NQ0], bb[0], bb[1]);
            if constexpr (2 * p + NQ0 < 2 * NPQ) ldsm_x4_t_i<OFF_WQ + (2 * p + NQ0) * 2048>(rq[(2 * p) % NQ0], wqa);
          }
          mma16816h(k0, w[2 * p], bb[0], bb[1]);
          if constexpr (p < NPQ) {
            mma16816h(q1, rq[(2 * p + 1) % NQ0], bb[2], bb[3]);
            if constexpr (2 * p + 1 + NQ0 < 2 * NPQ) ldsm_x4_t_i<OFF_WQ + (2 * p + 1 + NQ0) * 2048>(rq[(2 * p + 1) % NQ0], wqa);
          }
          mma16816h(k1, w[2 * p + 1], bb[2], bb[3]);
          if constexpr (t + NB0 < 20) ldsm_x4_i<OFF_MEM + pair_of(t + NB0) * 512>(bb, mema);
          if constexpr (t < 20 - NB0 && (t % BBS) == BBS - 1) bbfence<t + 1>(mema);
        });
        const float sq = sin_ * iq, sk = sin_ * iw;
        stsm_x4_t_i<0>(sta, pack_bf16((q0[0] + q1[0]) * sq, (q0[1] + q1[1]) * sq), pack_bf16((q0[2] + q1[2]) * sq, (q0[3] + q1[3]) * sq),
                       pack_bf16((k0[0] + k1[0]) * sk, (k0[1] + k1[1]) * sk), pack_bf16((k0[2] + k1[2]) * sk, (k0[3] + k1[3]) * sk));
        TS(2);
        if (!last) {
          if (wi == 3) {
            const uint32_t s8 = sb + ((l16 & 511) >> 1), xr = sb + ((l16 & 511) >> 2), ka = l16 + (l16 & 384) * 4 + (s & 1) * (2 * KVB);
            bar_sync(B_QK, 384);
            uint32_t a0[4], a1[4], a2[4], a3[4], kb0[4], kb1[4];
            ldsm_x4_i<OFF_Q>(a0, l16); ldsm_x4_i<OFF_KV + 512>(kb0, ka); ldsm_x4_i<OFF_Q + 1024>(a2, l16); ldsm_x4_i<OFF_KV + 512 + 2560>(kb1, ka);
            ldsm_x4_i<OFF_Q + 512>(a1, l16);
            bar_arrive(B_A, 288);
            ldsm_x4_i<OFF_Q + 1536>(a3, l16);
            float sa[4] = {0, 0, 0, 0}, sc2[4] = {0, 0, 0, 0};
            mma16816(sa, a0[0], a0[1], a0[2], a0[3], kb0[0], kb0[1]);
            mma16816(sc2, a2[0], a2[1], a2[2], a2[3], kb1[0], kb1[1]);
            mma16816(sa, a1[0], a1[1], a1[2], a1[3], kb0[2], kb0[3]);
            mma16816(sc2, a3[0], a3[1], a3[2], a3[3], kb1[2], kb1[3]);
            const float x0 = (sa[0] + sa[2]) + (sc2[0] + sc2[2]), x1 = (sa[1] + sa[3]) + (sc2[1] + sc2[3]);
            const uint32_t xp = pack_bf16(x0, x1);
            st_async_b32_i<OFF_SR + 1024 + 256>(xr + d1, xp, sb + MB_S + d1);
            st_async_b32_i<OFF_SR + 1024>(xr + d2, xp, sb + MB_S + d2);
            sts64_i<OFF_S + 1024>(s8, __float_as_uint(x0), __float_as_uint(x1));
          } else {
            bar_arrive(B_QK, 384);
          }
          bar_sync(B_SL, 256);
        }
      } else {
        float v0[4] = {0, 0, 0, 0}, v1[4] = {0, 0, 0, 0}, q0[4] = {0, 0, 0, 0}, q1[4] = {0, 0, 0, 0};
        uint32_t b[NQ1 / 2][4];
        static_for<0, NQ1 / 2>([&](auto T) { ldsm_x4_i<OFF_MEM + (NPQ + T.value) * 512>(b[T.value], mema); });
        static_for<0, NQ1 / 2>([&](auto T) {
          constexpr int t = T.value, p = NPQ + t;
          uint32_t (&bb)[4] = b[t];
          mma16816h(q0, rq[2 * t], bb[0], bb[1]);
          mma16816h(q1, rq[2 * t + 1], bb[2], bb[3]);
          mma16816h(v0, w[2 * p], bb[0], bb[1]);
          mma16816h(v1, w[2 * p + 1], bb[2], bb[3]);
        });
        const float sq = sin_ * iq, sv = sin_ * iw;
        stsm_x2_t_i<0>(sta, pack_bf16((q0[0] + q1[0]) * sq, (q0[1] + q1[1]) * sq), pack_bf16((q0[2] + q1[2]) * sq, (q0[3] + q1[3]) * sq));
        TS(2);
        if (!last) { bar_arrive(B_QK, 384); bar_sync(B_A, 288); }
        float v2[4] = {0, 0, 0, 0}, v3[4] = {0, 0, 0, 0};
        uint32_t c[4][4];
        static_for<0, 4>([&](auto T) { ldsm_x4_i<OFF_MEM + T.value * 512>(c[T.value], mema); });
        static_for<0, NPQ>([&](auto T) {
          constexpr int p = T.value;
          uint32_t (&bb)[4] = c[p & 3];
          if constexpr (p & 1) { mma16816h(v0, w[2 * p], bb[0], bb[1]); mma16816h(v1, w[2 * p + 1], bb[2], bb[3]); }
          else { mma16816h(v2, w[2 * p], bb[0], bb[1]); mma16816h(v3, w[2 * p + 1], bb[2], bb[3]); }
          if constexpr (p + 4 < NPQ) ldsm_x4_i<OFF_MEM + (p + 4) * 512>(bb, mema);
        });
        stsm_x2_t_i<OFF_KV + KVB + 512>(l16 + (l16 & 128) * 4 + (wi * 1280 + (s & 1) * (2 * KVB)), pack_bf16(((v0[0] + v1[0]) + (v2[0] + v3[0])) * sv, ((v0[1] + v1[1]) + (v2[1] + v3[1])) * sv),
                            pack_bf16(((v0[2] + v1[2]) + (v2[2] + v3[2])) * sv, ((v0[3] + v1[3]) + (v2[3] + v3[3])) * sv));
        if (!last) bar_arrive(B_V, 256);
      }
      TS(3);
      if (last) break;
      {
        uint32_t t1[12][4], t2[12][4];
        const uint32_t o16 = l16;
        wo1 = l16 + (OFF_WO + warp * 896);
        wo2 = sb + OFF_WO + warp * 896 + ((l16 & 128) ? 768 + ((l16 & 256) >> 2) + (l16 & 16) + ((l16 & 64) >> 1) : 512 + ((l16 & 256) >> 1) + (l16 & 112));
        auto ldw = [&](auto K) { if constexpr (K.value < 12 - NPM) { ldsm_x4_i<K.value * WOK>(t1[K.value], wo1); ldsm_x4_i<K.value * WOK>(t2[K.value], wo2); } };
        constexpr int NR_ = NRT - NPM;
        constexpr int PB = (hf ? PB1 : PB0) < NR_ ? (hf ? PB1 : PB0) : NR_, PA = (hf ? PA1 : PA0) < PB ? (hf ? PA1 : PA0) : PB;
        static_for<0, PA>(ldw);
        mbar_spin(sb + MB_X, (s + 1) & 1);
        if constexpr (PB > PA) bar_sync(B_G, 384); else bar_arrive(B_G, 384);
        static_for<PA, PB>(ldw);
        float c0[4] = {0, 0, 0, 0}, c1[4] = {0, 0, 0, 0}, e0[4] = {0, 0, 0, 0}, e1[4] = {0, 0, 0, 0};
        uint32_t ob[6][4];
        auto kstep = [&](auto K) {
          constexpr int k = K.value;
          uint32_t (&bb)[4] = ob[k >> 1];
          uint32_t (&x)[4] = k < 12 - NPM ? t1[k] : u1[k < 12 - NPM ? 0 : k - (12 - NPM)];
          uint32_t (&y)[4] = k < 12 - NPM ? t2[k] : u2[k < 12 - NPM ? 0 : k - (12 - NPM)];
          if constexpr (k & 1) { mma16816(c1, x[0], x[1], x[2], x[3], bb[2], bb[3]); mma16816(e1, y[0], y[1], y[2], y[3], bb[2], bb[3]); }
          else { mma16816(c0, x[0], x[1], x[2], x[3], bb[0], bb[1]); mma16816(e0, y[0], y[1], y[2], y[3], bb[0], bb[1]); }
          if constexpr (k >= NRF) ldw(IC<k + NR_ - NRF>{});
        };
        auto ldo = [&](auto P) { ldsm_x4_i<OFF_O + P.value * 512>(ob[P.value], o16); };
        TS(4);
        bar_sync(B_O, 384);
        ldo(IC<0>{}); ldo(IC<1>{});
        SFENCE(o16);
        static_for<PB, NR_>(ldw);
        static_for<0, 4>(kstep);
        TS(5);
        mbar_spin(sb + MB_O, s & 1);
        TS(6);
        ldo(IC<2>{}); ldo(IC<NPM >= 2 ? 5 : 3>{});
        if (WOF) SFENCE(o16);
        kstep(IC<4>{});
        if constexpr (NPM < 2) { kstep(IC<5>{}); ldo(IC<4>{}); kstep(IC<6>{}); kstep(IC<7>{}); ldo(IC<5>{}); static_for<8, 12>(kstep); }
        else if constexpr (NPM >= 4) { kstep(IC<10>{}); kstep(IC<11>{}); ldo(IC<4>{}); kstep(IC<5>{}); ldo(IC<3>{}); kstep(IC<8>{}); kstep(IC<9>{}); kstep(IC<6>{}); kstep(IC<7>{}); }
        else { kstep(IC<5>{}); ldo(IC<3>{}); kstep(IC<11>{}); kstep(IC<10>{}); ldo(IC<4>{}); kstep(IC<6>{}); kstep(IC<7>{}); if constexpr (NPM == 3) { kstep(IC<9>{}); kstep(IC<8>{}); } else { kstep(IC<8>{}); kstep(IC<9>{}); } }
        l16 = fresh(l16);
        const int ln = (l16 >> 4) & 31;
        unsigned char* gr = arena + (AR_ACC + acc_lane(bi, ln) + acc_voff(bv) + acc_step(s));
        const bool cnt = (ln & 1) || !t28;
        wqa = wq_addr(l16);
        SFENCE(o16);
        static_for<0, PQE>([&](auto K) { ldsm_x4_t_i<OFF_WQ + K.value * 2048>(rq[K.value], wqa); });
        const uint32_t y0 = movm_t(pack_f16(c0[0] + c1[0], c0[1] + c1[1])), y1 = movm_t(pack_f16(c0[2] + c1[2], c0[3] + c1[3]));
        const uint32_t y2 = movm_t(pack_f16(e0[0] + e1[0], e0[1] + e1[1])), y3 = movm_t(pack_f16(e0[2] + e1[2], e0[3] + e1[3]));
        asm volatile("red.relaxed.gpu.global.add.noftz.v4.f16x2 [%0], {%1,%2,%3,%4};" :: "l"(gr), "r"(y0), "r"(y1), "r"(y2), "r"(cnt ? 0x3c00u : y3) : "memory");
        bar_arrive(B_RED, 384);
        bar_sync(B_C, 256);
        TS(7);
      }
#if CHAIN_TIMING
      x_gemm((s + 1) & 1, tsb);
#else
      x_gemm((s + 1) & 1, 0);
#endif
      TS(8);
    }
    };
    if (hf == 0) run(IC<0>{}); else run(IC<1>{});
    bar_arrive(B_RED, 384);
#if CHAIN_TIMING
    for (int i = tid; i < 288; i += 256) a.dbg[cta * 288 + i] = lds32_i<OFF_BAR + 128>(sb + i * 4);
#endif
    asm volatile("barrier.cluster.arrive.relaxed.aligned; barrier.cluster.wait.aligned;" ::: "memory");
  }
}
struct PrepArgs { const bf16 *wqkv, *wphi, *wo; bf16 *wb, *wot; };
constexpr int PREP_TASKS = 3840;
__device__ __forceinline__ void prep_body(const int b, const bf16* __restrict__ wqkv, const bf16* __restrict__ wphi, const bf16* __restrict__ wo,
                                          bf16* __restrict__ wb, bf16* __restrict__ wot) {
  const int task = b, lane = threadIdx.x & 31;
  if (task < 1920) {
    const int which = task / 640, h = (task / 20) % 32, k = (task % 20) * 32 + lane;
    const int row0 = 288 * (h >> 2) + 96 * which + 24 * (h & 3);
    const uint2* src = (const uint2*)(wqkv + (size_t)k * 1920 + which * 640 + h * 20);
    float w[20];
#pragma unroll
    for (int d = 0; d < 5; d++) { const uint2 t = __ldg(src + d); w[4 * d] = bf_lo(t.x); w[4 * d + 1] = bf_hi(t.x); w[4 * d + 2] = bf_lo(t.y); w[4 * d + 3] = bf_hi(t.y); }
    if (which < 2) {
      float a[20];
#pragma unroll
      for (int f = 0; f < 20; f++) a[f] = 0.f;
      const uint32_t* ph = (const uint32_t*)(wphi + h * 400);
#pragma unroll
      for (int d = 0; d < 20; d++)
#pragma unroll
        for (int f = 0; f < 10; f++) { const uint32_t t = __ldg(ph + d * 10 + f); a[2 * f] = fmaf(w[d], bf_lo(t), a[2 * f]); a[2 * f + 1] = fmaf(w[d], bf_hi(t), a[2 * f + 1]); }
#pragma unroll
      for (int f = 0; f < 20; f++) wb[(size_t)(row0 + f) * cfg::DM + k] = __float2bfloat16_rn(a[f]);
    } else {
#pragma unroll
      for (int d = 0; d < 20; d++) wb[(size_t)(row0 + d) * cfg::DM + k] = __float2bfloat16_rn(w[d]);
    }
#pragma unroll
    for (int f = 20; f < 24; f++) wb[(size_t)(row0 + f) * cfg::DM + k] = __float2bfloat16_rn(0.f);
  } else {
    const int t = task - 1920, n = (t % 20) * 32 + lane, kk0 = (t / 20) * 8, h = kk0 / 24, d0 = kk0 % 24;
    unsigned short v[8];
#pragma unroll
    for (int e = 0; e < 8; e++) v[e] = (d0 + e < 20) ? __ldg((const unsigned short*)wo + (size_t)(h * 20 + d0 + e) * cfg::DM + n) : (unsigned short)0;
    *(uint4*)(wot + (size_t)n * 768 + kk0) = make_uint4(v[0] | (v[1] << 16), v[2] | (v[3] << 16), v[4] | (v[5] << 16), v[6] | (v[7] << 16));
  }
}

__global__ void __launch_bounds__(256, 4) ln_kernel(const bf16* __restrict__ xin, bf16* __restrict__ xn, uint2* __restrict__ xh, uint4* __restrict__ z0, int n0,
                                                    uint4* __restrict__ z1, int n1, const bf16* pfa, const bf16* pfb, int npf, int tl) {
  asm volatile("griddepcontrol.wait;" ::: "memory");
  asm volatile("griddepcontrol.launch_dependents;" ::: "memory");
  TL_BEGIN(tl);
  const int warp = threadIdx.x >> 5, lane = threadIdx.x & 31;
  const int row = blockIdx.x * 8 + warp;
  uint2 xw[1][5];
#pragma unroll
  for (int i = 0; i < 5; i++) xw[0][i] = *(const uint2*)(xin + (size_t)row * cfg::DM + i * 128 + lane * 4);
  for (int i = blockIdx.x * 256 + threadIdx.x; i < n0; i += 256 * 256) z0[i] = make_uint4(0, 0, 0, 0);
  for (int i = blockIdx.x * 256 + threadIdx.x; i < n1; i += 256 * 256) z1[i] = make_uint4(0, 0, 0, 0);
  if (npf && xw[0][4].y != 0x7fc17fc1u) {
    for (int i = 0; i < npf; i++) {
      const uint32_t l = (uint32_t)i * 32768u + (blockIdx.x * 256 + threadIdx.x) / 2;
      if (l < cfg::DM * cfg::HD / 64) asm volatile("prefetch.global.L2 [%0];" :: "l"(((threadIdx.x & 1) ? pfa : pfb) + (size_t)l * 64) : "memory");
    }
  }
  ln_rows<1>(xw, row, lane, xn, xh);
  TL_END(tl);
}
struct Pipe { uint32_t stage, phase; };
template <int NS> __device__ __forceinline__ void pipe_adv(Pipe& p) { if (++p.stage == NS) { p.stage = 0; p.phase ^= 1; } }
constexpr uint32_t SWZ128 = 1;
__device__ __forceinline__ uint64_t desc_kmajor(uint32_t a) { return make_desc(a, 16, 1024, SWZ128); }
__device__ __forceinline__ uint64_t desc_mnmajor(uint32_t a) { return make_desc(a, 8192, 1024, SWZ128); }
__device__ __forceinline__ void wait_ge(const void* p, uint32_t target, uint32_t ns = 32) {
  int spin = 0;
  while (ld_acquire_u32(p) < target) { __nanosleep(ns); if (++spin > (1 << 21)) break; }
}
__device__ __forceinline__ void bulk_g2s_hint(uint32_t dst, const void* src, uint32_t bytes, uint32_t mb, uint64_t pol) {
  asm volatile("cp.async.bulk.shared::cluster.global.mbarrier::complete_tx::bytes.L2::cache_hint [%0], [%1], %2, [%3], %4;"
               :: "r"(dst), "l"(src), "r"(bytes), "r"(mb), "l"(pol) : "memory");
}
#ifndef LNP
#define LNP 6
#endif
#ifndef STAG
#define STAG 1
#endif
#ifndef EF_KV
#define EF_KV 1
#endif
#ifndef EF_O
#define EF_O 1
#endif
__device__ __forceinline__ void fence_proxy_async_global() { asm volatile("fence.proxy.async.global;" ::: "memory"); }

namespace tr {
constexpr int NS = 4, STQ = 16384 + 24576, STO = 16384 + 40960;
constexpr int SEGB = 15360;
constexpr int OFF_K = NS * STQ;
constexpr int OFF_BAR = NS * STO;
constexpr int SMEM = OFF_BAR + 256;
static_assert(OFF_K + 4 * SEGB <= OFF_BAR && SMEM <= 232448, "smem");
enum { T_QA = 0, T_Q, T_A, T_OB, T_OS, T_L, T_END };
constexpr uint32_t C_QA = AR_CNT, C_O = AR_CNT + 64, C_Q = AR_CNT + 128;
struct Sched {
  uint16_t start[96];
  uint8_t type[96], blk[96], first[96];
  uint8_t ks[16];
  uint8_t wide[16];
  uint8_t lrows[16];
};
struct Args {
  const unsigned char *kg, *vg;
  unsigned char* o;
  uint4* qs;
  unsigned char* part;
  const bf16* xin;
  bf16 *xout, *xn;
  unsigned char* arena;
  int doprep, tl;
  uint32_t nap, nap2;
};
}

template <int N0, int N1>
__device__ __forceinline__ void tr_mainloop(float (&a0)[N0 / 2], float (&a1)[N1 ? N1 / 2 : 1], Pipe& p, uint32_t sb, uint32_t full, uint32_t empty, int nkb, int wg) {
  using namespace tr;
  constexpr uint32_t ST = N1 ? STO : STQ;
  uint32_t prev = 0;
#pragma unroll
  for (int i = 0; i < N0 / 2; i++) a0[i] = 0.f;
  if constexpr (N1 > 0) {
#pragma unroll
    for (int i = 0; i < N1 / 2; i++) a1[i] = 0.f;
  }
#pragma unroll 1
  for (int kb = 0; kb < nkb; kb++) {
    mbar_wait(full + 8 * p.stage, p.phase);
    const uint32_t st = sb + p.stage * ST;
    wgmma_fence();
#pragma unroll
    for (int kk = 0; kk < 4; kk++) {
      const uint64_t da = desc_kmajor(st + wg * 8192 + kk * 32);
      if constexpr (N0 == 192) wgmma_n192<0, 1>(a0, da, desc_mnmajor(st + 16384 + kk * 2048), (kb | kk) != 0);
      else wgmma_n128<0, 1>(a0, da, desc_mnmajor(st + 16384 + kk * 2048), (kb | kk) != 0);
      if constexpr (N1 > 0) wgmma_n128<0, 1>(a1, da, desc_mnmajor(st + 16384 + 24576 + kk * 2048), (kb | kk) != 0);
    }
    wgmma_commit();
    if (kb > 0) { wgmma_wait<1>(); mbar_arrive_if((threadIdx.x & 127) == 0, empty + 8 * prev); }
    prev = p.stage;
    pipe_adv<NS>(p);
  }
  wgmma_wait<0>();
  mbar_arrive_if((threadIdx.x & 127) == 0, empty + 8 * prev);
}
template <int N> __device__ __forceinline__ void stage_tiles(const float (&o)[N / 2], uint32_t base, int wi, int lane) {
  const uint32_t ra = base + (wi * 16 + (lane & 7) + 8 * ((lane >> 3) & 1)) * 128;
#pragma unroll
  for (int v = 0; v < N / 8; v += 2)
    stsm_x4(ra + (v >> 3) * 8192 + ((((v & 7) + (lane >> 4)) ^ (lane & 7)) << 4), pack_bf16(o[4 * v], o[4 * v + 1]), pack_bf16(o[4 * v + 2], o[4 * v + 3]),
            pack_bf16(o[4 * v + 4], o[4 * v + 5]), pack_bf16(o[4 * v + 6], o[4 * v + 7]));
}
template <int NP> __device__ __forceinline__ void l_row(const tr::Args& a, int row, int np, int lane) {
  uint2 xw[1][5]; float s[20];
#pragma unroll
  for (int i = 0; i < 5; i++) {
    xw[0][i] = __ldcg((const uint2*)(a.xin + (size_t)row * cfg::DM + i * 128 + lane * 4));
    s[4 * i] = s[4 * i + 1] = s[4 * i + 2] = s[4 * i + 3] = 0.f;
  }
  const unsigned char* pp = a.part + (size_t)(row >> 6) * 81920 + (lane >> 4) * 8192 + (row & 63) * 128 + ((((lane >> 1) & 7) ^ (row & 7)) << 4) + (lane & 1) * 8;
#pragma unroll 1
  for (int p0 = 0; p0 < np; p0 += NP) {
    uint2 t[NP][5];
    static_for<0, NP>([&](auto Q) {
      static_for<0, 5>([&](auto I) {
        asm volatile("{\n.reg .pred p;\nsetp.ne.u32 p, %3, 0;\nmov.b32 %0, 0;\nmov.b32 %1, 0;\n@p ld.global.cg.v2.u32 {%0,%1}, [%2+%4];\n}"
                     : "=r"(t[Q.value][I.value].x), "=r"(t[Q.value][I.value].y) : "l"(pp), "r"((uint32_t)(p0 + Q.value < np)), "n"(I.value * 16384) : "memory");
      });
      pp += 32 * 81920;
    });
#pragma unroll
    for (int q = 0; q < NP; q++)
#pragma unroll
      for (int i = 0; i < 5; i++) { s[4 * i] += bf_lo(t[q][i].x); s[4 * i + 1] += bf_hi(t[q][i].x); s[4 * i + 2] += bf_lo(t[q][i].y); s[4 * i + 3] += bf_hi(t[q][i].y); }
  }
#pragma unroll
  for (int i = 0; i < 5; i++) {
    xw[0][i] = make_uint2(pack_bf16(bf_lo(xw[0][i].x) + bf16r(s[4 * i]), bf_hi(xw[0][i].x) + bf16r(s[4 * i + 1])),
                          pack_bf16(bf_lo(xw[0][i].y) + bf16r(s[4 * i + 2]), bf_hi(xw[0][i].y) + bf16r(s[4 * i + 3])));
    *(uint2*)(a.xout + (size_t)row * cfg::DM + i * 128 + lane * 4) = xw[0][i];
  }
  ln_rows<1>(xw, row, lane, a.xn, nullptr);
}

__global__ void __launch_bounds__(384, 1) trail_kernel(const __grid_constant__ CUtensorMap tmX, const __grid_constant__ CUtensorMap tmQ,
                                                       const __grid_constant__ CUtensorMap tmWo5, const __grid_constant__ CUtensorMap tmWo2, const __grid_constant__ tr::Sched sc,
                                                       const __grid_constant__ tr::Args a, const __grid_constant__ PrepArgs pa) {
  using namespace tr;
  [[maybe_unused]] const int tl = a.tl;
  TL_BEGIN(tl);
  extern __shared__ __align__(1024) unsigned char smem_raw[];
  const uint32_t sb = smem_u32(smem_raw);
  const int warp = __shfl_sync(0xffffffffu, (int)threadIdx.x >> 5, 0), lane = threadIdx.x & 31;
  unsigned char* const arena = a.arena;
  const uint32_t full = sb + OFF_BAR, empty = full + 8 * NS, barK = empty + 8 * NS, barKfree = barK + 16, staged = barKfree + 16;
  const uint32_t kvrdy = staged + 32, mfull = kvrdy + 8, mempty = mfull + 16, mbox = mempty + 16;
  if (threadIdx.x == 0) {
    for (int i = 0; i < NS; i++) { mbar_init(full + 8 * i, 1); mbar_init(empty + 8 * i, 2); }
    for (int i = 0; i < 2; i++) {
      mbar_init(barK + 8 * i, 1); mbar_init(barKfree + 8 * i, 1); mbar_init(staged + 16 * i, 4); mbar_init(staged + 16 * i + 8, 4);
      mbar_init(mfull + 8 * i, 1); mbar_init(mempty + 8 * i, 11);
    }
    mbar_init(kvrdy, 1);
    asm volatile("fence.mbarrier_init.release.cluster;" ::: "memory");
  }
  __syncthreads();
  Pipe mp{0, 0};
  auto next_item = [&]() -> uint32_t {
    uint32_t it;
    mbar_wait(mfull + 8 * mp.stage, mp.phase);
    asm volatile("ld.shared.u32 %0, [%1];" : "=r"(it) : "r"(mbox + 4 * mp.stage) : "memory");
    return it;
  };
  if (warp >= 8) {
    asm volatile("setmaxnreg.dec.sync.aligned.u32 40;");
    if (warp == 8) { if (elect_one()) {
      Pipe p{0, 1};
      mp.phase = 1;
      uint32_t kph = 1, wide = 0;
      int g = 0;
      const uint64_t ef = policy_evict_first();
      auto ld_kv = [&](uint32_t d, const void* s, uint32_t n, uint32_t mb) { if (EF_KV) bulk_g2s_hint(d, s, n, mb, ef); else bulk_g2s(d, s, n, mb); };
      auto ld_o = [&](uint32_t d, const void* s, uint32_t n, uint32_t mb) { if (EF_O) bulk_g2s_hint(d, s, n, mb, ef); else bulk_g2s(d, s, n, mb); };
      auto stage = [&](uint32_t bytes) -> uint32_t {
        mbar_wait(empty + 8 * p.stage, p.phase);
        mbar_expect_tx(full + 8 * p.stage, bytes);
        return sb + p.stage * (wide ? STO : STQ);
      };
      auto fetch = [&]() -> uint32_t { uint32_t v; asm volatile("atom.relaxed.gpu.global.add.u32 %0, [%1], 1;" : "=r"(v) : "l"(arena + AR_QUEUE) : "memory"); return v; };
      uint32_t next = fetch();
      while (true) {
        const uint32_t item = next;
        while (item >= sc.start[g + 1] && sc.type[g] != T_END) g++;
        const int type = sc.type[g], m = sc.blk[g], k = item - sc.start[g] + sc.first[g];
        if (type == T_L) { wait_ge(arena + C_O + m * 4, sc.ks[m] * (sc.wide[m] ? 4 : 10), m < 13 ? a.nap : 32); }
        if (type == T_A) wait_ge(arena + C_Q + m * 4, 64);
        if (type < T_L && wide != (type == T_OB)) {
          for (uint32_t i = 0; i < NS; i++) mbar_wait(empty + 8 * i, i >= p.stage ? p.phase : p.phase ^ 1);
          mbar_wait(barKfree, kph); mbar_wait(barKfree + 8, kph);
          wide = type == T_OB;
        }
        mbar_wait(mempty + 8 * mp.stage, mp.phase);
        asm volatile("st.shared.u32 [%0], %1;" :: "r"(mbox + 4 * mp.stage), "r"((p.stage << 24) | (type << 16) | (m << 8) | (k & 255)) : "memory");
        mbar_arrive(mfull + 8 * mp.stage);
        pipe_adv<2>(mp);
        if (type == T_END) break;
        if (type == T_L) { next = fetch(); continue; }
        if (type <= T_A) {
          if (type != T_A)
#pragma unroll 1
            for (int kb = 0; kb < 10; kb++) {
              const uint32_t st = stage(STQ), fb = full + 8 * p.stage;
              tma_load_2d(st, &tmX, kb * 64, m * 128, fb);
              tma_load_3d(st + 16384, &tmQ, 0, kb * 64, k * 3, fb);
              pipe_adv<NS>(p);
              if (type == T_Q && kb == 8) next = fetch();
            }
          if (type != T_Q) {
            const size_t blk = ((size_t)m * 4 * 96 + k * 3) * 5120;
            kph ^= 1;
            mbar_wait(kvrdy, kph);
            next = fetch();
            fence_proxy_async_global();
#pragma unroll 1
            for (int w = type == T_A ? 0 : 2; w < 4; w++) {
              const uint32_t st = stage(2 * SEGB), fb = full + 8 * p.stage;
              for (int sg = 0; sg < 2; sg++) ld_kv(st + sg * SEGB, (w < 2 ? a.kg : a.vg) + blk + (size_t)(2 * (w & 1) + sg) * (96 * 5120), SEGB, fb);
              pipe_adv<NS>(p);
            }
          }
        } else {
          const int nn = wide ? 2 : 5, nb = wide ? 5 : 2, nt = k % nn, nkb = 96 / sc.ks[m], k0 = (k / nn) * nkb;
          const Pipe p0 = p;
          for (int kb = 0; kb < nkb; kb++) {
            const uint32_t st = stage(16384 + nb * 8192), fb = full + 8 * p.stage;
            tma_load_3d(st + 16384, wide ? &tmWo5 : &tmWo2, 0, (k0 + kb) * 64, nt * nb, fb);
            if (kb >= NS) ld_o(st, a.o + ((size_t)m * 96 + k0 + kb) * 16384, 16384, fb);
            pipe_adv<NS>(p);
            if (kb == NS - 1 || (kb == nkb - 1 && nkb < NS)) {
              wait_ge(arena + C_QA + m * 4, 64, m < 14 ? a.nap : 32);
              fence_proxy_async_global();
              Pipe q = p0;
#pragma unroll 1
              for (int i = 0; i <= kb; i++) { ld_o(sb + q.stage * (wide ? STO : STQ), a.o + ((size_t)m * 96 + k0 + i) * 16384, 16384, full + 8 * q.stage); pipe_adv<NS>(q); }
            }
          }
          next = fetch();
          for (int w = 0; w < 2; w++) { mbar_wait(empty + 8 * p.stage, p.phase); mbar_arrive(full + 8 * p.stage); pipe_adv<NS>(p); }
        }
      }
    } } else if (warp < 11) { if (elect_one()) {
      const int w = warp - 9;
      uint32_t sph = 0;
      [[maybe_unused]] int nlog = 0;
#ifdef TIMELINE
      if (w == 0) { unsigned long long* lg = g_log + (((tl >= 12) * 132 + blockIdx.x) * 64 + nlog++) * 2; lg[0] = T_END << 16; lg[1] = gtime(); lg[2] = ~0ull; }
#endif
      while (true) {
        const uint32_t it = next_item();
        const int type = (it >> 16) & 255, m = (it >> 8) & 255, k = it & 255;
        const uint32_t slot = mp.stage;
        pipe_adv<2>(mp);
        if (type == T_END) break;
        mbar_wait(staged + 16 * w + 8 * slot, (sph >> slot) & 1); sph ^= 1u << slot;
        mbar_arrive(mempty + 8 * slot);
#ifdef TIMELINE
        if (w == 0 && nlog < 63) { unsigned long long* lg = g_log + (((tl >= 12) * 132 + blockIdx.x) * 64 + nlog++) * 2; lg[0] = (type << 16) | (m << 8) | k; lg[1] = gtime(); lg[2] = ~0ull; }
#endif
        if (type == T_L) continue;
        if (type == T_QA || type == T_A) {
          for (int jj = 0; jj < 3; jj++) bulk_s2g(a.o + ((size_t)m * 96 + k * 3 + jj) * 16384 + w * 8192, sb + OFF_K + w * 2 * SEGB + jj * 8192, 8192);
          bulk_commit();
          bulk_wait<0>();
          mbar_arrive(barKfree + 8 * w);
        } else if (type >= T_OB) {
          const bool wide = type == T_OB;
          const int nn = wide ? 2 : 5, nb = wide ? 5 : 2;
          const uint32_t own = ((it >> 24) + 96 / sc.ks[m] + w) % NS;
          bulk_s2g(a.part + ((size_t)((k / nn) * 32 + m * 2 + w) * 10 + (k % nn) * nb) * 8192, sb + own * (wide ? STO : STQ), nb * 8192);
          bulk_commit();
          bulk_wait<0>();
          mbar_arrive(empty + 8 * own);
        }
        if (type == T_Q) __threadfence();
        asm volatile("red.relaxed.gpu.global.add.u32 [%0], 1;" :: "l"(arena + (type == T_Q ? C_Q : (type <= T_A ? C_QA : C_O)) + m * 4) : "memory");
      }
    } } else if (elect_one()) {
      const uint64_t ef = policy_evict_first();
      uint32_t kph = 1;
      while (true) {
        const uint32_t it = next_item();
        const int type = (it >> 16) & 255, m = (it >> 8) & 255, k = it & 255;
        const uint32_t slot = mp.stage;
        pipe_adv<2>(mp);
        if (type == T_END) break;
        if (type == T_QA || type == T_A) {
          for (int jj = 0; jj < 3; jj++) wait_ge(arena + AR_PROG + (k * 3 + jj) * PROG_STRIDE, 4 * m + 4, m < 15 ? a.nap : a.nap2);
          mbar_arrive(kvrdy);
          fence_proxy_async_global();
          const unsigned char* src = a.kg + ((size_t)m * 4 * 96 + k * 3) * 5120;
#pragma unroll 1
          for (int w = 0; w < 2; w++) {
            mbar_wait(barKfree + 8 * w, kph);
            if (type == T_A) { mbar_arrive(barK + 8 * w); continue; }
            mbar_expect_tx(barK + 8 * w, 2 * SEGB);
            for (int sg = 2 * w; sg < 2 * w + 2; sg++) bulk_g2s_hint(sb + OFF_K + sg * SEGB, src + (size_t)sg * (96 * 5120), SEGB, barK + 8 * w, ef);
          }
          kph ^= 1;
        }
        mbar_arrive(mempty + 8 * slot);
      }
      if (blockIdx.x == gridDim.x - 1) asm volatile("griddepcontrol.wait;" ::: "memory");
    }
    return;
  }
  asm volatile("setmaxnreg.inc.sync.aligned.u32 232;");
  const int wg = warp >> 2, wi = warp & 3;
  const int g = lane >> 2, q4 = lane & 3;
  if (a.doprep && blockIdx.x < 32) for (int t = blockIdx.x * 8 + warp; t < PREP_TASKS; t += 256) prep_body(t, pa.wqkv, pa.wphi, pa.wo, pa.wb, pa.wot);
  bar_sync(2, 256);
  Pipe p{0, 0};
  uint32_t kph = 0;
  auto own_slot = [&]() -> uint32_t {
    const uint32_t sA = p.stage, phA = p.phase; pipe_adv<NS>(p);
    const uint32_t sB = p.stage, phB = p.phase; pipe_adv<NS>(p);
    mbar_wait(full + 8 * sA, phA); mbar_wait(full + 8 * sB, phB);
    mbar_arrive_if((threadIdx.x & 127) == 0, empty + 8 * (wg ? sA : sB));
    return wg ? sB : sA;
  };
  while (true) {
    const uint32_t it = __shfl_sync(0xffffffffu, next_item(), 0);
    const int type = (it >> 16) & 255, m = (it >> 8) & 255, k = it & 255;
    mbar_arrive_if(lane == 0, mempty + 8 * mp.stage);
    const uint32_t done = staged + 16 * wg + 8 * mp.stage;
    pipe_adv<2>(mp);
    if (type == T_END) break;
    if (type == T_L) {
      const int nr = sc.lrows[m], np = sc.ks[m], row0 = m * 128 + (k * 8 + warp) * nr;
#pragma unroll 1
      for (int r = 0; r < nr; r++) l_row<LNP>(a, row0 + r, np, lane);
      __syncwarp();
      mbar_arrive_if(lane == 0, done);
      continue;
    }
    if (type >= T_OB) {
      const int nkb = 96 / sc.ks[m];
      if (type == T_OB) {
        float a0[96], a1[64];
        tr_mainloop<192, 128>(a0, a1, p, sb, full, empty, nkb, wg);
        const uint32_t st = sb + own_slot() * STO;
        stage_tiles<192>(a0, st, wi, lane); stage_tiles<128>(a1, st + 24576, wi, lane);
      } else {
        float a0[64], a1[1];
        tr_mainloop<128, 0>(a0, a1, p, sb, full, empty, nkb, wg);
        stage_tiles<128>(a0, sb + own_slot() * STQ, wi, lane);
      }
      fence_proxy_async();
      __syncwarp();
      mbar_arrive_if(lane == 0, done);
      continue;
    }
    uint32_t qf[12][4];
    uint4* qp = a.qs + ((size_t)((m & 7) * 32 + k) * 12) * 256 + threadIdx.x;
    if (type != T_A) {
      float acc[96], a1[1];
      tr_mainloop<192, 0>(acc, a1, p, sb, full, empty, 10, wg);
#pragma unroll
      for (int i = 0; i < 12; i++) {
        qf[i][0] = pack_bf16(acc[8 * i], acc[8 * i + 1]); qf[i][1] = pack_bf16(acc[8 * i + 2], acc[8 * i + 3]);
        qf[i][2] = pack_bf16(acc[8 * i + 4], acc[8 * i + 5]); qf[i][3] = pack_bf16(acc[8 * i + 6], acc[8 * i + 7]);
      }
      if (type == T_Q) {
#pragma unroll
        for (int i = 0; i < 12; i++) qp[i * 256] = make_uint4(qf[i][0], qf[i][1], qf[i][2], qf[i][3]);
        __syncwarp();
        mbar_arrive_if(lane == 0, done);
        continue;
      }
    } else {
#pragma unroll
      for (int i = 0; i < 12; i++) { const uint4 v = __ldcg(qp + i * 256); qf[i][0] = v.x; qf[i][1] = v.y; qf[i][2] = v.z; qf[i][3] = v.w; }
    }
    const uint32_t ost = sb + OFF_K + wg * 2 * SEGB;
    const bool second = wi >= 2;
    uint32_t pf[5][4];
    {
      float sa[20], sb2[20];
      uint32_t kbase = ost, kslot = 0;
      if (type == T_A) { kslot = own_slot(); kbase = sb + kslot * STQ; } else mbar_wait(barK + 8 * wg, kph);
      if (STAG && wg) bar_sync(1, 256);
      wgmma_fence();
#pragma unroll
      for (int i = 0; i < 12; i++) {
        wgmma_rs_n40<0>(sa, qf[i][0], qf[i][1], qf[i][2], qf[i][3], make_desc(kbase + i * 1280, 640, 128, 0), i != 0);
        wgmma_rs_n40<0>(sb2, qf[i][0], qf[i][1], qf[i][2], qf[i][3], make_desc(kbase + SEGB + i * 1280, 640, 128, 0), i != 0);
      }
      wgmma_commit();
      wgmma_wait<0>();
      if (STAG && !wg) bar_arrive(1, 256);
      mbar_arrive_if(type == T_A && (threadIdx.x & 127) == 0, empty + 8 * kslot);
      const float cs = 0.07216878364870322f * 1.4426950408889634f;
      const int r0 = 16 * (wi & 1) + g, r1 = r0 + 8;
      float m0 = -INFINITY, m1 = -INFINITY;
#pragma unroll
      for (int n = 0; n < 5; n++) {
#pragma unroll
        for (int e = 0; e < 2; e++) {
          const int key = 8 * n + 2 * q4 + e;
          float x = second ? sb2[4 * n + e] : sa[4 * n + e], y = second ? sb2[4 * n + 2 + e] : sa[4 * n + 2 + e];
          if (n < 4) { if (key > r0) x = -INFINITY; if (key > r1) y = -INFINITY; }
          sa[4 * n + e] = x; sa[4 * n + 2 + e] = y;
          m0 = fmaxf(m0, x); m1 = fmaxf(m1, y);
        }
      }
      m0 = fmaxf(m0, __shfl_xor_sync(0xffffffffu, m0, 1)); m1 = fmaxf(m1, __shfl_xor_sync(0xffffffffu, m1, 1));
      m0 = fmaxf(m0, __shfl_xor_sync(0xffffffffu, m0, 2)); m1 = fmaxf(m1, __shfl_xor_sync(0xffffffffu, m1, 2));
      float s0 = 0.f, s1 = 0.f;
#pragma unroll
      for (int n = 0; n < 5; n++) {
#pragma unroll
        for (int e = 0; e < 2; e++) {
          sa[4 * n + e] = ex2f((sa[4 * n + e] - m0) * cs); sa[4 * n + 2 + e] = ex2f((sa[4 * n + 2 + e] - m1) * cs);
          s0 += sa[4 * n + e]; s1 += sa[4 * n + 2 + e];
        }
      }
      s0 += __shfl_xor_sync(0xffffffffu, s0, 1); s1 += __shfl_xor_sync(0xffffffffu, s1, 1);
      s0 += __shfl_xor_sync(0xffffffffu, s0, 2); s1 += __shfl_xor_sync(0xffffffffu, s1, 2);
      const float i0 = rcpf(s0), i1 = rcpf(s1);
#pragma unroll
      for (int n = 0; n < 5; n++) {
        const uint32_t x = pack_bf16(sa[4 * n] * i0, sa[4 * n + 1] * i0), y = pack_bf16(sa[4 * n + 2] * i1, sa[4 * n + 3] * i1);
        if (n < 4) {
          pf[n >> 1][2 * (n & 1)] = second ? 0u : x; pf[n >> 1][2 * (n & 1) + 1] = second ? 0u : y;
          pf[2 + (n >> 1)][2 * (n & 1)] = second ? x : 0u; pf[2 + (n >> 1)][2 * (n & 1) + 1] = second ? y : 0u;
        } else {
          pf[4][0] = second ? 0u : x; pf[4][1] = second ? 0u : y; pf[4][2] = second ? x : 0u; pf[4][3] = second ? y : 0u;
        }
      }
    }
    {
      float o[96];
#pragma unroll
      for (int i = 0; i < 5; i++) { PIN(pf[i][0]); PIN(pf[i][1]); PIN(pf[i][2]); PIN(pf[i][3]); }
      const uint32_t own = own_slot(), vbase = sb + own * STQ;
      wgmma_fence();
#pragma unroll
      for (int i = 0; i < 5; i++)
        wgmma_rs_n192<1>(o, pf[i][0], pf[i][1], pf[i][2], pf[i][3], i < 4 ? make_desc(vbase + (i >> 1) * SEGB + (i & 1) * 256, 128, 640, 0) : make_desc(vbase + 512, SEGB, 640, 0), i != 0);
      wgmma_commit();
      if (type == T_A) mbar_wait(barK + 8 * wg, kph);
      kph ^= 1;
      wgmma_wait<0>();
      mbar_arrive_if((threadIdx.x & 127) == 0, empty + 8 * own);
      stage_tiles<192>(o, ost, wi, lane);
      fence_proxy_async();
      __syncwarp();
      mbar_arrive_if(lane == 0, done);
    }
  }
}
namespace bf {
constexpr int NS = 4, STAGE = 16384 + 36864;
constexpr int PHI_STR = 112, PHI_HEAD = 128 * PHI_STR;
constexpr int V_STR = 48, V_HEAD = 128 * V_STR;
constexpr int OFF_PHI = 0, OFF_V = 4 * PHI_HEAD, OFF_X = OFF_V + 4 * V_HEAD;
constexpr int OFF_WOT = 100352;
constexpr int OFF_OST = 65536;
constexpr int ANS = 4;
constexpr int OFF_BAR = OFF_WOT + 12 * 10240;
constexpr int SMEM = OFF_BAR + 256;
static_assert(OFF_X + 4 * 36 * 128 <= OFF_WOT && NS * STAGE <= OFF_BAR && SMEM <= 232448, "smem");
}
__device__ __forceinline__ void hedgehog_features(const float (&x)[6], int q4, float (&pos)[6], float (&neg)[6]) {
  const bool v2 = q4 < 2;
  float mx = fmaxf(fmaxf(x[0], x[1]), fmaxf(x[2], x[3])), mn = fminf(fminf(x[0], x[1]), fminf(x[2], x[3]));
  if (v2) { mx = fmaxf(mx, fmaxf(x[4], x[5])); mn = fminf(mn, fminf(x[4], x[5])); }
  mx = fmaxf(mx, __shfl_xor_sync(0xffffffffu, mx, 1)); mn = fminf(mn, __shfl_xor_sync(0xffffffffu, mn, 1));
  mx = fmaxf(mx, __shfl_xor_sync(0xffffffffu, mx, 2)); mn = fminf(mn, __shfl_xor_sync(0xffffffffu, mn, 2));
  const float L = 1.4426950408889634f;
  float sp = 0.f, sn = 0.f;
#pragma unroll
  for (int i = 0; i < 6; i++) {
    const bool ok = i < 4 || v2;
    pos[i] = ok ? ex2f((x[i] - mx) * L) : 0.f;
    neg[i] = ok ? ex2f((mn - x[i]) * L) : 0.f;
    sp += pos[i]; sn += neg[i];
  }
  sp += __shfl_xor_sync(0xffffffffu, sp, 1); sn += __shfl_xor_sync(0xffffffffu, sn, 1);
  sp += __shfl_xor_sync(0xffffffffu, sp, 2); sn += __shfl_xor_sync(0xffffffffu, sn, 2);
  const float ip = rcpf(sp), in_ = rcpf(sn);
#pragma unroll
  for (int i = 0; i < 6; i++) { pos[i] *= ip; neg[i] *= in_; }
}


__global__ void __launch_bounds__(384, 1) blayer_kernel(const __grid_constant__ CUtensorMap tmA, const __grid_constant__ CUtensorMap tmB,
                                                        const __grid_constant__ CUtensorMap tmO, const __grid_constant__ CUtensorMap tmW,
                                                        float* __restrict__ kvacc, unsigned* __restrict__ cnt, bf16* __restrict__ o2,
                                                        const bf16* __restrict__ xin, bf16* __restrict__ xout,
                                                        const bf16* pf0, const bf16* pf1, const bf16* pf2, const bf16* pf3, int tl) {
  using namespace bf;
  TL_BEGIN(tl);
  extern __shared__ __align__(1024) unsigned char smem_raw[];
  const uint32_t sb = smem_u32(smem_raw);
  const int warp = __shfl_sync(0xffffffffu, (int)threadIdx.x >> 5, 0), lane = threadIdx.x & 31;
  const uint32_t full = sb + OFF_BAR, empty = full + 8 * NS, full2 = empty + 8 * NS, empty2 = full2 + 8 * ANS, barW = empty2 + 8 * ANS, barGo = barW + 8;
  const int m = blockIdx.x & 15, u = blockIdx.x >> 4;
  unsigned* cntKV = cnt + u; unsigned* cntO = cnt + 8 + m;
  if (threadIdx.x == 0) {
    for (int i = 0; i < NS; i++) { mbar_init(full + 8 * i, 1); mbar_init(empty + 8 * i, 2); }
    for (int i = 0; i < ANS; i++) { mbar_init(full2 + 8 * i, 1); mbar_init(empty2 + 8 * i, 2); }
    mbar_init(barW, 1); mbar_init(barGo, 1);
    asm volatile("fence.mbarrier_init.release.cluster;" ::: "memory");
  }
  __syncthreads();
  asm volatile("griddepcontrol.wait;" ::: "memory");
  asm volatile("griddepcontrol.launch_dependents;" ::: "memory");
  if (warp >= 8) {
    asm volatile("setmaxnreg.dec.sync.aligned.u32 40;");
    if (warp == 8 && elect_one()) {
      prefetch_tmap(&tmO); prefetch_tmap(&tmW);
      Pipe p{0, 1};
      for (int kb = 0; kb < 10; kb++) {
        mbar_wait(empty + 8 * p.stage, p.phase);
        const uint32_t st = sb + p.stage * STAGE, fb = full + 8 * p.stage;
        mbar_expect_tx(fb, STAGE);
        tma_load_2d(st, &tmA, kb * 64, m * 128, fb);
        tma_load_2d(st + 16384, &tmB, kb * 64, u * 288, fb);
        tma_load_2d(st + 16384 + 18432, &tmB, kb * 64, u * 288 + 144, fb);
        pipe_adv<NS>(p);
      }
      if (pf0) {
        constexpr uint32_t PER = cfg::DM * cfg::HD * 2 / 128;
        prefetch_l2((const unsigned char*)pf0 + blockIdx.x * PER, PER); prefetch_l2((const unsigned char*)pf1 + blockIdx.x * PER, PER);
        if (pf2) { prefetch_l2((const unsigned char*)pf2 + blockIdx.x * PER, PER); prefetch_l2((const unsigned char*)pf3 + blockIdx.x * PER, PER); }
      }
      for (int i = 0; i < NS; i++) { mbar_wait(empty + 8 * p.stage, p.phase); pipe_adv<NS>(p); }
      mbar_expect_tx(barW, 12 * 10240);
      for (int kb = 0; kb < 12; kb++) tma_load_2d(sb + OFF_WOT + kb * 10240, &tmW, kb * 64, u * 80, barW);
      mbar_wait(barGo, 0);
      wait_ge(cntO, 8);
      fence_proxy_async_global();
      Pipe q{0, 1};
      for (int kb = 0; kb < 12; kb++) {
        mbar_wait(empty2 + 8 * q.stage, q.phase);
        mbar_expect_tx(full2 + 8 * q.stage, 16384);
        tma_load_2d(sb + q.stage * 16384, &tmO, kb * 64, m * 128, full2 + 8 * q.stage);
        pipe_adv<ANS>(q);
      }
    }
    return;
  }
  asm volatile("setmaxnreg.inc.sync.aligned.u32 232;");
  const int wg = warp >> 2, wi = warp & 3;
  const int g = lane >> 2, q4 = lane & 3;
  float a0[72], a1[72];
  {
    Pipe p{0, 0};
    uint32_t prev = 0;
    for (int kb = 0; kb < 10; kb++) {
      mbar_wait(full + 8 * p.stage, p.phase);
      const uint32_t st = sb + p.stage * STAGE;
      wgmma_fence();
#pragma unroll
      for (int kk = 0; kk < 4; kk++) {
        const uint64_t da = desc_kmajor(st + wg * 8192 + kk * 32);
        wgmma_n144<0, 0>(a0, da, desc_kmajor(st + 16384 + kk * 32), (kb | kk) != 0);
        wgmma_n144<0, 0>(a1, da, desc_kmajor(st + 16384 + 18432 + kk * 32), (kb | kk) != 0);
      }
      wgmma_commit();
      if (kb > 0) { wgmma_wait<1>(); if ((threadIdx.x & 127) == 0) mbar_arrive(empty + 8 * prev); }
      prev = p.stage;
      pipe_adv<NS>(p);
    }
    wgmma_wait<0>();
    bar_sync(1, 256);
    if ((threadIdx.x & 127) == 0) mbar_arrive(empty + 8 * prev);
  }
  TL2((tl >= 12 ? 128 : 0) + 32 + 0);
  auto ACC = [&](auto V, auto E) -> float { constexpr int v = V.value, e = E.value; if constexpr (v < 18) return a0[4 * v + e]; else return a1[4 * (v - 18) + e]; };
  const int trow = wg * 64 + wi * 16;
  const int srow = (lane & 7) + 8 * ((lane >> 3) & 1);
  uint32_t qf[4][3][4];
  static_for<0, 4>([&](auto HH) {
    constexpr int hh = HH.value;
    float xa[6], xb[6], pa[6], na[6], pb[6], nb[6];
    static_for<0, 3>([&](auto T) {
      constexpr int t = T.value; using V = IC<3 * hh + t>;
      xa[2 * t] = ACC(V{}, IC<0>{}); xa[2 * t + 1] = ACC(V{}, IC<1>{}); xb[2 * t] = ACC(V{}, IC<2>{}); xb[2 * t + 1] = ACC(V{}, IC<3>{});
      bf16r2(xa[2 * t], xa[2 * t + 1]); bf16r2(xb[2 * t], xb[2 * t + 1]);
    });
    hedgehog_features(xa, q4, pa, na);
    hedgehog_features(xb, q4, pb, nb);
    qf[hh][0][0] = pack_bf16(pa[0], pa[1]); qf[hh][0][1] = pack_bf16(pb[0], pb[1]); qf[hh][0][2] = pack_bf16(pa[2], pa[3]); qf[hh][0][3] = pack_bf16(pb[2], pb[3]);
    qf[hh][1][0] = pack_bf16(pa[4], pa[5]); qf[hh][1][1] = pack_bf16(pb[4], pb[5]); qf[hh][1][2] = pack_bf16(na[0], na[1]); qf[hh][1][3] = pack_bf16(nb[0], nb[1]);
    qf[hh][2][0] = pack_bf16(na[2], na[3]); qf[hh][2][1] = pack_bf16(nb[2], nb[3]); qf[hh][2][2] = pack_bf16(na[4], na[5]); qf[hh][2][3] = pack_bf16(nb[4], nb[5]);
    static_for<0, 3>([&](auto T) {
      constexpr int t = T.value; using V = IC<12 + 3 * hh + t>;
      xa[2 * t] = ACC(V{}, IC<0>{}); xa[2 * t + 1] = ACC(V{}, IC<1>{}); xb[2 * t] = ACC(V{}, IC<2>{}); xb[2 * t + 1] = ACC(V{}, IC<3>{});
      bf16r2(xa[2 * t], xa[2 * t + 1]); bf16r2(xb[2 * t], xb[2 * t + 1]);
    });
    hedgehog_features(xa, q4, pa, na);
    hedgehog_features(xb, q4, pb, nb);
    const uint32_t ph = sb + OFF_PHI + hh * PHI_HEAD + (trow + srow) * PHI_STR + (lane >> 4) * 16;
    stsm_x4(ph, pack_bf16(pa[0], pa[1]), pack_bf16(pb[0], pb[1]), pack_bf16(pa[2], pa[3]), pack_bf16(pb[2], pb[3]));
    stsm_x4(ph + 32, pack_bf16(pa[4], pa[5]), pack_bf16(pb[4], pb[5]), pack_bf16(na[0], na[1]), pack_bf16(nb[0], nb[1]));
    stsm_x4(ph + 64, pack_bf16(na[2], na[3]), pack_bf16(nb[2], nb[3]), pack_bf16(na[4], na[5]), pack_bf16(nb[4], nb[5]));
    using V0 = IC<24 + 3 * hh>; using V1 = IC<24 + 3 * hh + 1>; using V2 = IC<24 + 3 * hh + 2>;
    float c0 = ACC(V2{}, IC<0>{}), c1 = ACC(V2{}, IC<1>{}), c2 = ACC(V2{}, IC<2>{}), c3 = ACC(V2{}, IC<3>{});
    if (q4 == 2) { c0 = 1.f; c1 = 0.f; c2 = 1.f; c3 = 0.f; }
    if (q4 == 3) { c0 = c1 = c2 = c3 = 0.f; }
    const uint32_t va = sb + OFF_V + hh * V_HEAD + (trow + srow) * V_STR;
    stsm_x4(va + (lane >> 4) * 16, pack_bf16(ACC(V0{}, IC<0>{}), ACC(V0{}, IC<1>{})), pack_bf16(ACC(V0{}, IC<2>{}), ACC(V0{}, IC<3>{})),
            pack_bf16(ACC(V1{}, IC<0>{}), ACC(V1{}, IC<1>{})), pack_bf16(ACC(V1{}, IC<2>{}), ACC(V1{}, IC<3>{})));
    stsm_x2(va + 32, pack_bf16(c0, c1), pack_bf16(c2, c3));
  });
  bar_sync(1, 256);
  TL2((tl >= 12 ? 128 : 0) + 32 + 1);
  {
    const int hh = warp >> 1, th = warp & 1;
    float d[3][3][4];
#pragma unroll
    for (int a = 0; a < 3; a++)
#pragma unroll
      for (int b = 0; b < 3; b++) { d[a][b][0] = d[a][b][1] = d[a][b][2] = d[a][b][3] = 0.f; }
#pragma unroll
    for (int ks = 0; ks < 4; ks++) {
      const int t0 = th * 64 + ks * 16;
      const uint32_t pa = sb + OFF_PHI + hh * PHI_HEAD + (t0 + (lane & 7) + 8 * (lane >> 4)) * PHI_STR + ((lane >> 3) & 1) * 16;
      const uint32_t pv = sb + OFF_V + hh * V_HEAD + (t0 + (lane & 7) + 8 * ((lane >> 3) & 1)) * V_STR;
      uint32_t b01[4], b2[2];
      ldsm_x4_t(b01, pv + (lane >> 4) * 16);
      ldsm_x2_t(b2, pv + 32);
#pragma unroll
      for (int a = 0; a < 3; a++) {
        uint32_t af[4];
        ldsm_x4_t(af, pa + a * 32);
        mma16816(d[a][0], af[0], af[1], af[2], af[3], b01[0], b01[1]);
        mma16816(d[a][1], af[0], af[1], af[2], af[3], b01[2], b01[3]);
        mma16816(d[a][2], af[0], af[1], af[2], af[3], b2[0], b2[1]);
      }
    }
    const uint32_t xa = sb + OFF_X + hh * (36 * 128) + lane * 4;
    if (th == 1) {
#pragma unroll
      for (int a = 0; a < 3; a++)
#pragma unroll
        for (int b = 0; b < 3; b++)
#pragma unroll
          for (int e = 0; e < 4; e++)
            asm volatile("st.shared.f32 [%0], %1;" :: "r"(xa + ((a * 3 + b) * 4 + e) * 128), "f"(d[a][b][e]) : "memory");
    }
    bar_sync(2 + hh, 64);
    if (th == 0) {
      float* dst = kvacc + (size_t)(u * 4 + hh) * (48 * 24);
#pragma unroll
      for (int a = 0; a < 3; a++)
#pragma unroll
        for (int b = 0; b < 3; b++) {
          float y[4];
#pragma unroll
          for (int e = 0; e < 4; e++) {
            float o;
            asm volatile("ld.shared.f32 %0, [%1];" : "=f"(o) : "r"(xa + ((a * 3 + b) * 4 + e) * 128) : "memory");
            y[e] = d[a][b][e] + o;
          }
          const int f0 = 16 * a + g, dd = 8 * b + 2 * q4;
          if (dd < 22) {
            asm volatile("red.relaxed.gpu.global.add.v2.f32 [%0], {%1,%2};" :: "l"(dst + f0 * 24 + dd), "f"(y[0]), "f"(y[1]) : "memory");
            asm volatile("red.relaxed.gpu.global.add.v2.f32 [%0], {%1,%2};" :: "l"(dst + (f0 + 8) * 24 + dd), "f"(y[2]), "f"(y[3]) : "memory");
          }
        }
      __threadfence();
    }
  }
  TL2((tl >= 12 ? 128 : 0) + 32 + 2);
  bar_sync(1, 256);
  if (threadIdx.x == 0) { __threadfence(); atomicAdd(cntKV, 1u); wait_ge(cntKV, 16); }
  bar_sync(1, 256);
  TL2((tl >= 12 ? 128 : 0) + 32 + 3);
  {
    float t[5][4];
#pragma unroll
    for (int it = 0; it < 5; it++) {
      const int i = min((int)threadIdx.x + 256 * it, 4 * 9 * 32 - 1);
      const int hh = i / 288, r = i % 288, tt = r >> 5, l = r & 31, ks = tt / 3, nt = tt % 3;
      const float* src = kvacc + (size_t)(u * 4 + hh) * (48 * 24) + (16 * ks + 2 * (l & 3)) * 24 + 8 * nt + (l >> 2);
      t[it][0] = __ldcg(src); t[it][1] = __ldcg(src + 24); t[it][2] = __ldcg(src + 8 * 24); t[it][3] = __ldcg(src + 9 * 24);
    }
#pragma unroll
    for (int it = 0; it < 5; it++) {
      const int i = threadIdx.x + 256 * it;
      if (i < 4 * 9 * 32) sts64(sb + OFF_X + i * 8, pack_bf16(t[it][0], t[it][1]), pack_bf16(t[it][2], t[it][3]));
    }
  }
  bar_sync(1, 256);
  {
    const uint32_t ost = sb + warp * 3072;
    uint32_t ow[4][6];
#pragma unroll
    for (int hh = 0; hh < 4; hh++) {
      float d[3][4];
#pragma unroll
      for (int n = 0; n < 3; n++) {
        d[n][0] = d[n][1] = d[n][2] = d[n][3] = 0.f;
        const uint32_t kb = sb + OFF_X + hh * 2304 + n * 256 + lane * 8;
        const uint2 k0 = lds64(kb), k1 = lds64(kb + 768), k2 = lds64(kb + 1536);
        mma16816(d[n], qf[hh][0][0], qf[hh][0][1], qf[hh][0][2], qf[hh][0][3], k0.x, k0.y);
        mma16816(d[n], qf[hh][1][0], qf[hh][1][1], qf[hh][1][2], qf[hh][1][3], k1.x, k1.y);
        mma16816(d[n], qf[hh][2][0], qf[hh][2][1], qf[hh][2][2], qf[hh][2][3], k2.x, k2.y);
      }
      const float da = bf16r(bf16r(__shfl_sync(0xffffffffu, d[2][0], (lane & ~3) | 2)) + 1e-6f);
      const float db = bf16r(bf16r(__shfl_sync(0xffffffffu, d[2][2], (lane & ~3) | 2)) + 1e-6f);
      float y[3][4];
#pragma unroll
      for (int n = 0; n < 3; n++) {
        bf16r2(d[n][0], d[n][1]); bf16r2(d[n][2], d[n][3]);
        y[n][0] = __fdividef(d[n][0], da); y[n][1] = __fdividef(d[n][1], da);
        y[n][2] = __fdividef(d[n][2], db); y[n][3] = __fdividef(d[n][3], db);
      }
      if (q4 >= 2) { y[2][0] = y[2][1] = y[2][2] = y[2][3] = 0.f; }
#pragma unroll
      for (int n = 0; n < 3; n++) { ow[hh][2 * n] = pack_bf16(y[n][0], y[n][1]); ow[hh][2 * n + 1] = pack_bf16(y[n][2], y[n][3]); }
    }
#pragma unroll
    for (int hh = 0; hh < 4; hh++) {
      const uint32_t ra = ost + srow * 192 + hh * 48;
      stsm_x4(ra + (lane >> 4) * 16, ow[hh][0], ow[hh][1], ow[hh][2], ow[hh][3]);
      stsm_x2(ra + 32, ow[hh][4], ow[hh][5]);
    }
    __syncwarp();
#pragma unroll
    for (int i = 0; i < 6; i++) {
      const int c = lane + 32 * i, row = c / 12, chunk = c % 12;
      const uint4 v = lds128(ost + row * 192 + chunk * 16);
      *(uint4*)(o2 + (size_t)(m * 128 + trow + row) * 768 + u * 96 + chunk * 8) = v;
    }
  }
  __threadfence();
  bar_sync(1, 256);
  if (threadIdx.x == 0) { atomicAdd(cntO, 1u); mbar_arrive(barGo); }
  TL2((tl >= 12 ? 128 : 0) + 32 + 4);
  float acc[40];
  uint4 xr[5];
#pragma unroll
  for (int i = 0; i < 5; i++) {
    const int c = lane + 32 * i;
    xr[i] = *(const uint4*)(xin + (size_t)(m * 128 + trow + c / 10) * cfg::DM + u * 80 + (c % 10) * 8);
  }
  mbar_wait(barW, 0);
  {
    Pipe p{0, 0};
    uint32_t prev = 0;
    for (int kb = 0; kb < 12; kb++) {
      mbar_wait(full2 + 8 * p.stage, p.phase);
      wgmma_fence();
#pragma unroll
      for (int kk = 0; kk < 4; kk++)
        wgmma_n80<0, 0>(acc, desc_kmajor(sb + p.stage * 16384 + wg * 8192 + kk * 32), desc_kmajor(sb + OFF_WOT + kb * 10240 + kk * 32), (kb | kk) != 0);
      wgmma_commit();
      if (kb > 0) { wgmma_wait<1>(); if ((threadIdx.x & 127) == 0) mbar_arrive(empty2 + 8 * prev); }
      prev = p.stage;
      pipe_adv<ANS>(p);
    }
    wgmma_wait<0>();
  }
  TL2((tl >= 12 ? 128 : 0) + 32 + 5);
  {
    const uint32_t ost = sb + OFF_OST + warp * 3072;
#pragma unroll
    for (int v = 0; v < 10; v += 2)
      stsm_x4(ost + srow * 176 + (v + (lane >> 4)) * 16, pack_bf16(acc[4 * v], acc[4 * v + 1]), pack_bf16(acc[4 * v + 2], acc[4 * v + 3]),
              pack_bf16(acc[4 * v + 4], acc[4 * v + 5]), pack_bf16(acc[4 * v + 6], acc[4 * v + 7]));
    __syncwarp();
#pragma unroll
    for (int i = 0; i < 5; i++) {
      const int c = lane + 32 * i, row = c / 10, chunk = c % 10;
      const uint4 y = lds128(ost + row * 176 + chunk * 16);
      const size_t off = (size_t)(m * 128 + trow + row) * cfg::DM + u * 80 + chunk * 8;
      const uint4 x = xr[i];
      *(uint4*)(xout + off) = make_uint4(pack_bf16(bf_lo(x.x) + bf_lo(y.x), bf_hi(x.x) + bf_hi(y.x)), pack_bf16(bf_lo(x.y) + bf_lo(y.y), bf_hi(x.y) + bf_hi(y.y)),
                                         pack_bf16(bf_lo(x.z) + bf_lo(y.z), bf_hi(x.z) + bf_hi(y.z)), pack_bf16(bf_lo(x.w) + bf_lo(y.w), bf_hi(x.w) + bf_hi(y.w)));
    }
  }
  TL_END(tl);
}
__device__ __align__(32768) unsigned char g_arena[AR_SIZE];
__device__ __align__(1024) uint2 g_xh[2048 * 160];
__device__ __align__(1024) unsigned char g_k[64 * 96 * 5120], g_v[64 * 96 * 5120];
__device__ __align__(1024) bf16 g_o[2048 * 6144];
__device__ __align__(1024) uint4 g_qs[8 * 32 * 12 * 256];
__device__ __align__(1024) bf16 g_xn[2048 * 640], g_xn2[2048 * 640], g_xa[2048 * 640], g_xb[2048 * 640];
__device__ __align__(1024) bf16 g_part[24 * 2048 * 640];
__device__ __align__(1024) bf16 g_wb[2304 * 640], g_wot[640 * 768], g_pq[2048 * 768];
__device__ __align__(1024) float g_kvacc[32 * 48 * 24 + 64];

typedef CUresult (*EncodeFn)(CUtensorMap*, CUtensorMapDataType, cuuint32_t, void*, const cuuint64_t*, const cuuint64_t*, const cuuint32_t*,
                             const cuuint32_t*, CUtensorMapInterleave, CUtensorMapSwizzle, CUtensorMapL2promotion, CUtensorMapFloatOOBfill);
static EncodeFn g_encode = nullptr;
static CUtensorMap make_map(const void* p, uint64_t cols, uint64_t rows, uint32_t bc, uint32_t br, bool swz = true) {
  CUtensorMap m;
  cuuint64_t dims[2] = {cols, rows}, strides[1] = {cols * 2};
  cuuint32_t box[2] = {bc, br}, es[2] = {1, 1};
  g_encode(&m, CU_TENSOR_MAP_DATA_TYPE_BFLOAT16, 2, const_cast<void*>(p), dims, strides, box, es, CU_TENSOR_MAP_INTERLEAVE_NONE,
           swz ? CU_TENSOR_MAP_SWIZZLE_128B : CU_TENSOR_MAP_SWIZZLE_NONE, CU_TENSOR_MAP_L2_PROMOTION_L2_256B, CU_TENSOR_MAP_FLOAT_OOB_FILL_NONE);
  return m;
}
static CUtensorMap make_map3(const void* p, uint64_t cols, uint64_t rows, uint32_t nb) {
  CUtensorMap m;
  cuuint64_t dims[3] = {64, rows, cols / 64}, strides[2] = {cols * 2, 128};
  cuuint32_t box[3] = {64, 64, nb}, es[3] = {1, 1, 1};
  g_encode(&m, CU_TENSOR_MAP_DATA_TYPE_BFLOAT16, 3, const_cast<void*>(p), dims, strides, box, es, CU_TENSOR_MAP_INTERLEAVE_NONE,
           CU_TENSOR_MAP_SWIZZLE_128B, CU_TENSOR_MAP_L2_PROMOTION_L2_256B, CU_TENSOR_MAP_FLOAT_OOB_FILL_NONE);
  return m;
}
template <class T> static T* sym(const T& s) { void* p = nullptr; cudaGetSymbolAddress(&p, s); return (T*)p; }

struct Ptrs {
  unsigned char *arena, *k, *v; bf16 *o, *xn, *xa, *xb, *wb, *wot, *pq; float *part, *kvacc; uint2* xh; uint4* qs; bf16* xn2;
};

static tr::Sched make_sched(const char* str, const int* ks, const int* lr) {
  using namespace tr;
  Sched s = {};
  int g = 0, n = 0;
  for (int b = 0; b < 16; b++) { s.ks[b] = (uint8_t)abs(ks[b]); s.wide[b] = ks[b] > 0; s.lrows[b] = (uint8_t)lr[b]; }
  for (const char* p = str; *p;) {
    if (*p == ' ') { p++; continue; }
    const char c = *p++;
    char* e;
    const int b = (int)strtol(p, &e, 10); p = e;
    int first = 0, cnt = c == 'o' ? s.ks[b] * (s.wide[b] ? 2 : 5) : (c == 'l' ? 16 / lr[b] : 32);
    if (*p == '.') { first = (int)strtol(p + 1, &e, 10); cnt = (int)strtol(e + 1, &e, 10); p = e; }
    s.start[g] = (uint16_t)n; s.first[g] = (uint8_t)first; s.blk[g] = (uint8_t)b;
    s.type[g] = c == 'a' ? T_QA : (c == 'q' ? T_Q : (c == 't' ? T_A : (c == 'l' ? T_L : (s.wide[b] ? T_OB : T_OS))));
    g++; n += cnt;
  }
  s.start[g] = (uint16_t)n; s.type[g] = T_END; s.start[g + 1] = 0xffff;
  return s;
}
static tr::Sched sched_of(int layer) {
  const char* str = "q13 q14 a0 q15 a1 o0 a2 o1 a3 o2 a4 o3 a5 o4 l0 a6 o5 l1 a7 o6 l2 a8 o7 l3 a9 o8 l4 a10 o9 l5 a11 o10 l6 a12 o11 l7 t13 o12 l8 o13 l9 t14 t15 o14 l10 l11 o15 l12 l13 l14 l15";
  int ks[16] = {2, 2, 2, 2, 2, 2, 2, 2, 2, 2, 2, 3, 4, 6, -12, -12}, lr[16] = {4, 4, 4, 4, 4, 4, 4, 4, 4, 4, 4, 1, 1, 1, 1, 1};
#ifdef TUNE
  if (getenv("SCHED")) str = getenv("SCHED");
  if (layer == 0 && getenv("SCHED0")) str = getenv("SCHED0");
  if (const char* p = getenv("KS")) for (int b = 0; b < 16; b++) { char* e; ks[b] = (int)strtol(p, &e, 10); p = e; }
  if (const char* p = getenv("LR")) for (int b = 0; b < 16; b++) { char* e; lr[b] = (int)strtol(p, &e, 10); p = e; }
#endif
  return make_sched(str, ks, lr);
}
#ifndef TRAIL_GRID
#define TRAIL_GRID 132
#endif
#ifndef PDL_LN
#define PDL_LN 0
#endif
#ifndef PDL_CH
#define PDL_CH 1
#endif
#ifndef PDL_B
#define PDL_B 0
#endif
#ifndef PF_A
#define PF_A 1
#endif
#ifndef PF_B
#define PF_B 1
#endif
extern "C" void kernel_launch(void* const* d_in, const int* in_sizes, int n_in, void* d_out, int out_size) {
  const bf16* x = (const bf16*)d_in[0];
  const bf16* mem0 = (const bf16*)d_in[1];
  const bf16 *Wq = (const bf16*)d_in[2], *Wk = (const bf16*)d_in[3], *Wv = (const bf16*)d_in[4], *Wo = (const bf16*)d_in[5];
  const bf16 *wqkv = (const bf16*)d_in[8], *wphi = (const bf16*)d_in[9], *wo = (const bf16*)d_in[10];
  bf16* out = (bf16*)d_out;
  static Ptrs P; static bool init = false;
  if (!init) {
    void* fn = nullptr; cudaDriverEntryPointQueryResult qr;
    cudaGetDriverEntryPoint("cuTensorMapEncodeTiled", &fn, cudaEnableDefault, &qr);
    g_encode = (EncodeFn)fn;
    void* p;
    cudaGetSymbolAddress(&p, g_arena); P.arena = (unsigned char*)p;
    cudaGetSymbolAddress(&p, g_k); P.k = (unsigned char*)p;   cudaGetSymbolAddress(&p, g_v); P.v = (unsigned char*)p;
    cudaGetSymbolAddress(&p, g_o); P.o = (bf16*)p;
    cudaGetSymbolAddress(&p, g_xn); P.xn = (bf16*)p;
    cudaGetSymbolAddress(&p, g_xa); P.xa = (bf16*)p;   cudaGetSymbolAddress(&p, g_xb); P.xb = (bf16*)p;
    cudaGetSymbolAddress(&p, g_wb); P.wb = (bf16*)p;   cudaGetSymbolAddress(&p, g_wot); P.wot = (bf16*)p;
    cudaGetSymbolAddress(&p, g_pq); P.pq = (bf16*)p;   cudaGetSymbolAddress(&p, g_part); P.part = (float*)p;
    cudaGetSymbolAddress(&p, g_kvacc); P.kvacc = (float*)p;
    cudaGetSymbolAddress(&p, g_xh); P.xh = (uint2*)p;
    cudaGetSymbolAddress(&p, g_qs); P.qs = (uint4*)p;
    cudaGetSymbolAddress(&p, g_xn2); P.xn2 = (bf16*)p;
    cudaFuncSetAttribute(chain_kernel, cudaFuncAttributeMaxDynamicSharedMemorySize, ch::SMEM);
    cudaFuncSetAttribute(trail_kernel, cudaFuncAttributeMaxDynamicSharedMemorySize, tr::SMEM);
    cudaFuncSetAttribute(blayer_kernel, cudaFuncAttributeMaxDynamicSharedMemorySize, bf::SMEM);
    init = true;
  }
  const CUtensorMap tmXn = make_map(P.xn, 640, 2048, 64, 128), tmXn2 = make_map(P.xn2, 640, 2048, 64, 128);
  const CUtensorMap tmWq = make_map3(Wq, 6144, 640, 3);
  const CUtensorMap tmCq = make_map(Wq, 6144, 640, 64, 160), tmCk = make_map(Wk, 6144, 640, 64, 160), tmCv = make_map(Wv, 6144, 640, 64, 160), tmCo = make_map(Wo, 640, 6144, 224, 64, false);
  const CUtensorMap tmWo5 = make_map3(Wo, 640, 6144, 5), tmWo2 = make_map3(Wo, 640, 6144, 2);
  const CUtensorMap tmWb = make_map(P.wb, 640, 2304, 64, 144), tmO2 = make_map(P.pq, 768, 2048, 64, 128), tmWot = make_map(P.wot, 768, 640, 64, 80);

  ChainArgs ca;
  ca.xh = P.xh; ca.mem0 = mem0; ca.kg = P.k; ca.vg = P.v;
  ca.arena = P.arena; ca.dbg = nullptr; ca.delay = POLL_DELAY;
#ifdef TUNE
  if (getenv("PD")) ca.delay = atoi(getenv("PD"));
#endif
  ca.tl = 0;
  uint4* zar = (uint4*)P.arena; const int nzar = AR_SIZE / 16;
  uint4* zkv = (uint4*)P.kvacc; const int nzkv = (32 * 48 * 24 + 64) / 4;

  const PrepArgs pa{wqkv, wphi, wo, P.wb, P.wot};
  const bf16* xcur = x;
  cudaLaunchAttribute at[1];
  at[0].id = cudaLaunchAttributeProgrammaticStreamSerialization; at[0].val.programmaticStreamSerializationAllowed = 1;
  auto cfgof = [&](int grid, int block, int smem, bool pdl) {
    cudaLaunchConfig_t lc = {};
    lc.gridDim = dim3(grid); lc.blockDim = dim3(block); lc.dynamicSmemBytes = smem; lc.stream = cudaStreamPerThread;
    lc.attrs = at; lc.numAttrs = pdl ? 1 : 0;
    return lc;
  };
  for (int layer = 0; layer < 2; layer++) {
    const int tl = layer * 12;
    cudaLaunchConfig_t lc = cfgof(256, 256, 0, layer > 0 && PDL_LN);
    cudaLaunchKernelEx(&lc, ln_kernel, xcur, P.xn, P.xh, zar, nzar, zkv, nzkv, Wk, Wv, layer == 0 ? PF_A : 0, tl + 0);
    ca.tl = tl + 2;
    lc = cfgof(96, 384, ch::SMEM, PDL_CH);
    cudaLaunchKernelEx(&lc, chain_kernel, ca, tmCq, tmCk, tmCv, tmCo);
    lc = cfgof(TRAIL_GRID, 384, tr::SMEM, true);
    tr::Args ta{P.k, P.v, (unsigned char*)P.o, P.qs, (unsigned char*)P.part, xcur, P.xa, P.xn2, P.arena, layer == 0 ? 1 : 0, tl + 4, 500, 100};
#ifdef TUNE
    if (getenv("NAP")) ta.nap = atoi(getenv("NAP"));
    if (getenv("NAP2")) ta.nap2 = atoi(getenv("NAP2"));
#endif
    cudaLaunchKernelEx(&lc, trail_kernel, tmXn, tmWq, tmWo5, tmWo2, sched_of(layer), ta, pa);
    lc = cfgof(128, 384, bf::SMEM, PDL_B);
    cudaLaunchKernelEx(&lc, blayer_kernel, tmXn2, tmWb, tmO2, tmWot, P.kvacc, (unsigned*)(P.kvacc + 32 * 48 * 24), P.pq, (const bf16*)P.xa, layer == 0 ? P.xb : out,
                       layer == 0 && PF_B ? Wk : nullptr, Wv, PF_B > 1 ? Wq : nullptr, Wo, tl + 7);
    xcur = P.xb;
  }
}
```

```cpp
#include <cuda_runtime.h>
#include <cuda.h>
#include <cuda_bf16.h>
#include <stdint.h>
#include <stdlib.h>
#include <type_traits>

typedef __nv_bfloat16 bf16;

namespace cfg {
constexpr int S = 2048, DM = 640, H = 32, DH = 192, NSEG = 64, SEG = 32, NM = 8;
constexpr int HD = H * DH;
}

__device__ __forceinline__ uint32_t smem_u32(const void* p) { return (uint32_t)__cvta_generic_to_shared(p); }
__device__ __forceinline__ uint32_t mapa_u32(uint32_t a, uint32_t r) {
  uint32_t o; asm("mapa.shared::cluster.u32 %0, %1, %2;" : "=r"(o) : "r"(a), "r"(r)); return o;
}
__device__ __forceinline__ void mbar_init(uint32_t b, uint32_t c) {
  asm volatile("mbarrier.init.shared::cta.b64 [%0], %1;" :: "r"(b), "r"(c) : "memory");
}
__device__ __forceinline__ void mbar_expect_tx(uint32_t b, uint32_t bytes) {
  asm volatile("mbarrier.arrive.expect_tx.shared::cta.b64 _, [%0], %1;" :: "r"(b), "r"(bytes) : "memory");
}
__device__ __forceinline__ void mbar_arrive(uint32_t b) {
  asm volatile("mbarrier.arrive.shared::cta.b64 _, [%0];" :: "r"(b) : "memory");
}
__device__ __forceinline__ void mbar_arrive_if(bool c, uint32_t b) {
  asm volatile("{\n.reg .pred p;\nsetp.ne.u32 p, %1, 0;\n@p mbarrier.arrive.shared::cta.b64 _, [%0];\n}" :: "r"(b), "r"((uint32_t)c) : "memory");
}
__device__ __forceinline__ bool mbar_try(uint32_t b, uint32_t ph) {
  uint32_t p;
  asm volatile("{.reg .pred p; mbarrier.try_wait.parity.shared::cta.b64 p, [%1], %2; selp.u32 %0, 1, 0, p;}"
               : "=r"(p) : "r"(b), "r"(ph) : "memory");
  return p;
}
__device__ __forceinline__ bool mbar_try_cluster(uint32_t b, uint32_t ph) {
  uint32_t p;
  asm volatile("{.reg .pred p; mbarrier.try_wait.parity.acquire.cluster.shared::cta.b64 p, [%1], %2; selp.u32 %0, 1, 0, p;}"
               : "=r"(p) : "r"(b), "r"(ph) : "memory");
  return p;
}
#ifndef SPIN_LIMIT
#define SPIN_LIMIT (1 << 22)
#endif
__device__ __forceinline__ void mbar_wait(uint32_t b, uint32_t ph) {
  asm volatile("{\n.reg .pred p, q;\n.reg .u32 c;\nmov.u32 c, 0;\n"
               "W_%=:\nmbarrier.try_wait.parity.shared::cta.b64 p, [%0], %1;\n@p bra.uni D_%=;\n"
               "add.u32 c, c, 1;\nsetp.lt.u32 q, c, %2;\n@q bra.uni W_%=;\nD_%=:\n}"
               :: "r"(b), "r"(ph), "n"(SPIN_LIMIT) : "memory");
}
__device__ __forceinline__ void mbar_spin(uint32_t b, uint32_t ph) {
  asm volatile("{\n.reg .pred p, q;\n.reg .u32 c;\nmov.u32 c, 0;\n"
               "W_%=:\nmbarrier.test_wait.parity.shared::cta.b64 p, [%0], %1;\n@p bra D_%=;\n"
               "add.u32 c, c, 1;\nsetp.lt.u32 q, c, %2;\n@q bra W_%=;\nD_%=:\n}"
               :: "r"(b), "r"(ph), "n"(SPIN_LIMIT) : "memory");
}
#define PIN(x) asm volatile("" : "+r"(x))
__device__ __forceinline__ void mbar_wait_cluster(uint32_t b, uint32_t ph) {
  int s = 0;
  while (!mbar_try_cluster(b, ph)) { if (++s > SPIN_LIMIT) break; }
}
__device__ __forceinline__ void st_async_v2(uint32_t a, uint32_t x, uint32_t y, uint32_t mb) {
  asm volatile("st.async.weak.shared::cluster.mbarrier::complete_tx::bytes.v2.b32 [%0], {%1,%2}, [%3];"
               :: "r"(a), "r"(x), "r"(y), "r"(mb) : "memory");
}
__device__ __forceinline__ void st_async_v4(uint32_t a, uint32_t x, uint32_t y, uint32_t z, uint32_t w, uint32_t mb) {
  asm volatile("st.async.weak.shared::cluster.mbarrier::complete_tx::bytes.v4.b32 [%0], {%1,%2,%3,%4}, [%5];"
               :: "r"(a), "r"(x), "r"(y), "r"(z), "r"(w), "r"(mb) : "memory");
}
__device__ __forceinline__ void bulk_g2s(uint32_t dst, const void* src, uint32_t bytes, uint32_t mb) {
  asm volatile("cp.async.bulk.shared::cluster.global.mbarrier::complete_tx::bytes [%0], [%1], %2, [%3];"
               :: "r"(dst), "l"(src), "r"(bytes), "r"(mb) : "memory");
}
__device__ __forceinline__ void cp_async16(uint32_t dst, const void* src) {
  asm volatile("cp.async.cg.shared.global [%0], [%1], 16;" :: "r"(dst), "l"(src) : "memory");
}
__device__ __forceinline__ void cp_async_wait_all() { asm volatile("cp.async.wait_all;" ::: "memory"); }
__device__ __forceinline__ void fence_proxy_async() { asm volatile("fence.proxy.async.shared::cta;" ::: "memory"); }
__device__ __forceinline__ void bar_sync(int id, int n) { asm volatile("bar.sync %0, %1;" :: "r"(id), "r"(n) : "memory"); }
__device__ __forceinline__ void bar_arrive(int id, int n) { asm volatile("bar.arrive %0, %1;" :: "r"(id), "r"(n) : "memory"); }
__device__ __forceinline__ void cluster_sync_all() {
  asm volatile("barrier.cluster.arrive.release.aligned; barrier.cluster.wait.acquire.aligned;" ::: "memory");
}
__device__ __forceinline__ void ldsm_x4(uint32_t (&r)[4], uint32_t a) {
  asm volatile("ldmatrix.sync.aligned.m8n8.x4.shared.b16 {%0,%1,%2,%3}, [%4];"
               : "=r"(r[0]), "=r"(r[1]), "=r"(r[2]), "=r"(r[3]) : "r"(a) : "memory");
}
__device__ __forceinline__ void ldsm_x4_t(uint32_t (&r)[4], uint32_t a) {
  asm volatile("ldmatrix.sync.aligned.m8n8.x4.trans.shared.b16 {%0,%1,%2,%3}, [%4];"
               : "=r"(r[0]), "=r"(r[1]), "=r"(r[2]), "=r"(r[3]) : "r"(a) : "memory");
}
template <int IMM> __device__ __forceinline__ void ldsm_x4_i(uint32_t (&r)[4], uint32_t a) {
  asm volatile("ldmatrix.sync.aligned.m8n8.x4.shared.b16 {%0,%1,%2,%3}, [%4+%5];"
               : "=r"(r[0]), "=r"(r[1]), "=r"(r[2]), "=r"(r[3]) : "r"(a), "n"(IMM) : "memory");
}
template <int IMM> __device__ __forceinline__ void ldsm_x4_t_i(uint32_t (&r)[4], uint32_t a) {
  asm volatile("ldmatrix.sync.aligned.m8n8.x4.trans.shared.b16 {%0,%1,%2,%3}, [%4+%5];"
               : "=r"(r[0]), "=r"(r[1]), "=r"(r[2]), "=r"(r[3]) : "r"(a), "n"(IMM) : "memory");
}
template <int IMM> __device__ __forceinline__ uint4 lds128_i(uint32_t a) {
  uint4 v; asm volatile("ld.shared.v4.u32 {%0,%1,%2,%3}, [%4+%5];" : "=r"(v.x), "=r"(v.y), "=r"(v.z), "=r"(v.w) : "r"(a), "n"(IMM) : "memory"); return v;
}
template <int IMM> __device__ __forceinline__ uint2 lds64_i(uint32_t a) {
  uint2 v; asm volatile("ld.shared.v2.u32 {%0,%1}, [%2+%3];" : "=r"(v.x), "=r"(v.y) : "r"(a), "n"(IMM) : "memory"); return v;
}
template <int IMM> __device__ __forceinline__ void sts128_i(uint32_t a, uint32_t x, uint32_t y, uint32_t z, uint32_t w) {
  asm volatile("st.shared.v4.u32 [%0+%5], {%1,%2,%3,%4};" :: "r"(a), "r"(x), "r"(y), "r"(z), "r"(w), "n"(IMM) : "memory");
}
template <int IMM> __device__ __forceinline__ void sts64_i(uint32_t a, uint32_t x, uint32_t y) {
  asm volatile("st.shared.v2.u32 [%0+%3], {%1,%2};" :: "r"(a), "r"(x), "r"(y), "n"(IMM) : "memory");
}
template <int IMM> __device__ __forceinline__ void st_async_v2_i(uint32_t a, uint32_t x, uint32_t y, uint32_t mb) {
  asm volatile("st.async.weak.shared::cluster.mbarrier::complete_tx::bytes.v2.b32 [%0+%4], {%1,%2}, [%3];"
               :: "r"(a), "r"(x), "r"(y), "r"(mb), "n"(IMM) : "memory");
}
template <int IMM> __device__ __forceinline__ uint4 ld_relaxed_v4_i(const void* p) {
  uint4 v; asm volatile("ld.relaxed.gpu.global.v4.u32 {%0,%1,%2,%3}, [%4+%5];" : "=r"(v.x), "=r"(v.y), "=r"(v.z), "=r"(v.w) : "l"(p), "n"(IMM) : "memory"); return v;
}
template <int I, int N, class F> __device__ __forceinline__ void static_for(F&& f) {
  if constexpr (I < N) { f(std::integral_constant<int, I>{}); static_for<I + 1, N>(f); }
}
__device__ __forceinline__ uint32_t movm_t(uint32_t a) {
  uint32_t d; asm volatile("movmatrix.sync.aligned.m8n8.trans.b16 %0, %1;" : "=r"(d) : "r"(a)); return d;
}
__device__ __forceinline__ void mma16816(float (&d)[4], uint32_t a0, uint32_t a1, uint32_t a2, uint32_t a3, uint32_t b0, uint32_t b1) {
  asm volatile("mma.sync.aligned.m16n8k16.row.col.f32.bf16.bf16.f32 {%0,%1,%2,%3}, {%4,%5,%6,%7}, {%8,%9}, {%0,%1,%2,%3};"
               : "+f"(d[0]), "+f"(d[1]), "+f"(d[2]), "+f"(d[3]) : "r"(a0), "r"(a1), "r"(a2), "r"(a3), "r"(b0), "r"(b1));
}
__device__ __forceinline__ uint32_t pack_bf16(float lo, float hi) {
  uint32_t d; asm("cvt.rn.bf16x2.f32 %0, %1, %2;" : "=r"(d) : "f"(hi), "f"(lo)); return d;
}
__device__ __forceinline__ float bf_lo(uint32_t w) { return __uint_as_float(w << 16); }
__device__ __forceinline__ float bf_hi(uint32_t w) { return __uint_as_float(w & 0xffff0000u); }
__device__ __forceinline__ uint4 lds128(uint32_t a) {
  uint4 v; asm volatile("ld.shared.v4.u32 {%0,%1,%2,%3}, [%4];" : "=r"(v.x), "=r"(v.y), "=r"(v.z), "=r"(v.w) : "r"(a) : "memory"); return v;
}
__device__ __forceinline__ uint2 lds64(uint32_t a) {
  uint2 v; asm volatile("ld.shared.v2.u32 {%0,%1}, [%2];" : "=r"(v.x), "=r"(v.y) : "r"(a) : "memory"); return v;
}
__device__ __forceinline__ void sts128(uint32_t a, uint32_t x, uint32_t y, uint32_t z, uint32_t w) {
  asm volatile("st.shared.v4.u32 [%0], {%1,%2,%3,%4};" :: "r"(a), "r"(x), "r"(y), "r"(z), "r"(w) : "memory");
}
__device__ __forceinline__ void sts64(uint32_t a, uint32_t x, uint32_t y) {
  asm volatile("st.shared.v2.u32 [%0], {%1,%2};" :: "r"(a), "r"(x), "r"(y) : "memory");
}
__device__ __forceinline__ uint4 ld_relaxed_v4(const void* p) {
  uint4 v; asm volatile("ld.relaxed.gpu.global.v4.u32 {%0,%1,%2,%3}, [%4];" : "=r"(v.x), "=r"(v.y), "=r"(v.z), "=r"(v.w) : "l"(p) : "memory"); return v;
}
__device__ __forceinline__ uint32_t ld_relaxed_u32(const void* p) {
  uint32_t v; asm volatile("ld.relaxed.gpu.global.u32 %0, [%1];" : "=r"(v) : "l"(p) : "memory"); return v;
}
__device__ __forceinline__ void st_relaxed_v2(void* p, uint32_t a, uint32_t b) {
  asm volatile("st.relaxed.gpu.global.v2.u32 [%0], {%1,%2};" :: "l"(p), "r"(a), "r"(b) : "memory");
}
__device__ __forceinline__ void st_relaxed_u32(void* p, uint32_t v) {
  asm volatile("st.relaxed.gpu.global.u32 [%0], %1;" :: "l"(p), "r"(v) : "memory");
}
__device__ __forceinline__ uint32_t clk32() { uint32_t c; asm volatile("mov.u32 %0, %%clock;" : "=r"(c) :: "memory"); return c; }
__device__ __forceinline__ uint32_t clkdep(uint32_t v) {
  uint32_t c; asm volatile("{.reg .pred p; setp.eq.u32 p, %1, 0xdeadbeef; @p trap; mov.u32 %0, %%clock;}" : "=r"(c) : "r"(v) : "memory"); return c;
}
__device__ __forceinline__ void wgmma_fence() { asm volatile("wgmma.fence.sync.aligned;" ::: "memory"); }
__device__ __forceinline__ void wgmma_commit() { asm volatile("wgmma.commit_group.sync.aligned;" ::: "memory"); }
template <int N> __device__ __forceinline__ void wgmma_wait() { asm volatile("wgmma.wait_group.sync.aligned %0;" :: "n"(N) : "memory"); }
__device__ __forceinline__ void wgmma_n8_ss_ta(float (&d)[4], uint64_t da, uint64_t db, int acc) {
  asm volatile("{\n.reg .pred p;\nsetp.ne.b32 p, %6, 0;\n"
               "wgmma.mma_async.sync.aligned.m64n8k16.f32.bf16.bf16 {%0,%1,%2,%3}, %4, %5, p, 1, 1, 1, 0;\n}\n"
               : "+f"(d[0]), "+f"(d[1]), "+f"(d[2]), "+f"(d[3]) : "l"(da), "l"(db), "r"(acc));
}
__device__ __forceinline__ uint64_t make_desc(uint32_t saddr, uint32_t lbo_bytes, uint32_t sbo_bytes, uint32_t swz) {
  return (uint64_t)((saddr & 0x3FFFF) >> 4) | ((uint64_t)(lbo_bytes >> 4) << 16) | ((uint64_t)(sbo_bytes >> 4) << 32) | ((uint64_t)swz << 62);
}


__device__ __forceinline__ bool elect_one() {
  uint32_t p; asm volatile("{\n.reg .pred p;\nelect.sync _|p, 0xffffffff;\nselp.u32 %0, 1, 0, p;\n}" : "=r"(p)); return p;
}
__device__ __forceinline__ void tma_load_3d(uint32_t dst, const CUtensorMap* tm, int c0, int c1, int c2, uint32_t mb) {
  asm volatile("cp.async.bulk.tensor.3d.shared::cluster.global.mbarrier::complete_tx::bytes [%0], [%1, {%3, %4, %5}], [%2];"
               :: "r"(dst), "l"(tm), "r"(mb), "r"(c0), "r"(c1), "r"(c2) : "memory");
}
__device__ __forceinline__ void tma_load_2d(uint32_t dst, const CUtensorMap* tm, int c0, int c1, uint32_t mb) {
  asm volatile("cp.async.bulk.tensor.2d.shared::cluster.global.mbarrier::complete_tx::bytes [%0], [%1, {%3, %4}], [%2];"
               :: "r"(dst), "l"(tm), "r"(mb), "r"(c0), "r"(c1) : "memory");
}
__device__ __forceinline__ void bulk_s2g(void* dst, uint32_t src, uint32_t bytes) {
  asm volatile("cp.async.bulk.global.shared::cta.bulk_group [%0], [%1], %2;" :: "l"(dst), "r"(src), "r"(bytes) : "memory");
}
__device__ __forceinline__ uint64_t policy_evict_first() {
  uint64_t p; asm volatile("createpolicy.fractional.L2::evict_first.b64 %0, 1.0;" : "=l"(p)); return p;
}
__device__ __forceinline__ void bulk_s2g_hint(void* dst, uint32_t src, uint32_t bytes, uint64_t pol) {
  asm volatile("cp.async.bulk.global.shared::cta.bulk_group.L2::cache_hint [%0], [%1], %2, %3;" :: "l"(dst), "r"(src), "r"(bytes), "l"(pol) : "memory");
}
__device__ __forceinline__ void bulk_commit() { asm volatile("cp.async.bulk.commit_group;" ::: "memory"); }
template <int N> __device__ __forceinline__ void bulk_wait_read() { asm volatile("cp.async.bulk.wait_group.read %0;" :: "n"(N) : "memory"); }
template <int N> __device__ __forceinline__ void bulk_wait() { asm volatile("cp.async.bulk.wait_group %0;" :: "n"(N) : "memory"); }
__device__ __forceinline__ void stsm_x4(uint32_t a, uint32_t r0, uint32_t r1, uint32_t r2, uint32_t r3) {
  asm volatile("stmatrix.sync.aligned.m8n8.x4.shared.b16 [%0], {%1,%2,%3,%4};" :: "r"(a), "r"(r0), "r"(r1), "r"(r2), "r"(r3) : "memory");
}
__device__ __forceinline__ void stsm_x2(uint32_t a, uint32_t r0, uint32_t r1) {
  asm volatile("stmatrix.sync.aligned.m8n8.x2.shared.b16 [%0], {%1,%2};" :: "r"(a), "r"(r0), "r"(r1) : "memory");
}
__device__ __forceinline__ void ldsm_x2(uint32_t (&r)[2], uint32_t a) {
  asm volatile("ldmatrix.sync.aligned.m8n8.x2.shared.b16 {%0,%1}, [%2];" : "=r"(r[0]), "=r"(r[1]) : "r"(a) : "memory");
}
__device__ __forceinline__ void ldsm_x2_t(uint32_t (&r)[2], uint32_t a) {
  asm volatile("ldmatrix.sync.aligned.m8n8.x2.trans.shared.b16 {%0,%1}, [%2];" : "=r"(r[0]), "=r"(r[1]) : "r"(a) : "memory");
}
__device__ __forceinline__ float bf16r(float x) { return __uint_as_float(pack_bf16(0.f, x) & 0xffff0000u); }
__device__ __forceinline__ void bf16r2(float& a, float& b) { const uint32_t w = pack_bf16(a, b); a = bf_lo(w); b = bf_hi(w); }
__device__ __forceinline__ float rcpf(float x) { float r; asm("rcp.approx.ftz.f32 %0, %1;" : "=f"(r) : "f"(x)); return r; }
__device__ __forceinline__ float ex2f(float x) { float e; asm("ex2.approx.ftz.f32 %0, %1;" : "=f"(e) : "f"(x)); return e; }
__device__ __forceinline__ void prefetch_tmap(const CUtensorMap* tm) { asm volatile("prefetch.tensormap [%0];" :: "l"(tm) : "memory"); }

#ifdef TIMELINE
__device__ unsigned long long g_tl[2 * 64];
__device__ unsigned long long g_log[2 * 132 * 64 * 2 + 2];
__device__ unsigned long long g_tl2[4 * 64];
__device__ __forceinline__ unsigned long long gtime() { unsigned long long t; asm volatile("mov.u64 %0, %%globaltimer;" : "=l"(t)); return t; }
#define TL_BEGIN(id) do { if (threadIdx.x == 0) atomicMin(&g_tl[2 * (id)], gtime()); } while (0)
#define TL_END(id) do { if ((threadIdx.x & 31) == 0) atomicMax(&g_tl[2 * (id) + 1], gtime()); } while (0)
#define TL_ACC(idx, t0) do { if (threadIdx.x == 0 && m >= 4 && m < 11) { atomicAdd(&g_tl2[idx], gtime() - (t0)); atomicAdd(&g_tl2[(idx) + 1], 1ull); } } while (0)
#define TL_NOW() gtime()
#define TL2(idx) asm volatile("{\n.reg .pred p;\nsetp.eq.u32 p, %2, 0;\n@p red.relaxed.gpu.global.max.u64 [%0], %1;\n}" :: "l"(&g_tl2[idx]), "l"(gtime()), "r"(threadIdx.x) : "memory")
#define TL_BEGIN0(id) atomicMin(&g_tl[2 * (id)], gtime())
#else
#define TL_ACC(idx, t0)
#define TL_NOW() 0ull
#define TL2(idx)
#define TL_BEGIN0(id)
#define TL_BEGIN(id)
#define TL_END(id)
#endif
template <int TA, int TB> __device__ __forceinline__ void wgmma_n24(float (&d)[12], uint64_t da, uint64_t db, int acc) {
  asm volatile("{\n.reg .pred p;\nsetp.ne.b32 p, %14, 0;\n"
    "wgmma.mma_async.sync.aligned.m64n24k16.f32.bf16.bf16 {%0, %1, %2, %3, %4, %5, %6, %7, %8, %9, %10, %11}, %12, %13, p, 1, 1, %15, %16;\n}\n"
    : "+f"(d[0]), "+f"(d[1]), "+f"(d[2]), "+f"(d[3]), "+f"(d[4]), "+f"(d[5]), "+f"(d[6]), "+f"(d[7]), "+f"(d[8]), "+f"(d[9]), "+f"(d[10]), "+f"(d[11])
    : "l"(da), "l"(db), "r"(acc), "n"(TA), "n"(TB));
}

template <int TA, int TB> __device__ __forceinline__ void wgmma_n80(float (&d)[40], uint64_t da, uint64_t db, int acc) {
  asm volatile("{\n.reg .pred p;\nsetp.ne.b32 p, %42, 0;\n"
    "wgmma.mma_async.sync.aligned.m64n80k16.f32.bf16.bf16 {%0, %1, %2, %3, %4, %5, %6, %7, %8, %9, %10, %11, %12, %13, %14, %15, %16, %17, %18, %19, %20, %21, %22, %23, %24, %25, %26, %27, %28, %29, %30, %31, %32, %33, %34, %35, %36, %37, %38, %39}, %40, %41, p, 1, 1, %43, %44;\n}\n"
    : "+f"(d[0]), "+f"(d[1]), "+f"(d[2]), "+f"(d[3]), "+f"(d[4]), "+f"(d[5]), "+f"(d[6]), "+f"(d[7]), "+f"(d[8]), "+f"(d[9]), "+f"(d[10]), "+f"(d[11]), "+f"(d[12]), "+f"(d[13]), "+f"(d[14]), "+f"(d[15]), "+f"(d[16]), "+f"(d[17]), "+f"(d[18]), "+f"(d[19]), "+f"(d[20]), "+f"(d[21]), "+f"(d[22]), "+f"(d[23]), "+f"(d[24]), "+f"(d[25]), "+f"(d[26]), "+f"(d[27]), "+f"(d[28]), "+f"(d[29]), "+f"(d[30]), "+f"(d[31]), "+f"(d[32]), "+f"(d[33]), "+f"(d[34]), "+f"(d[35]), "+f"(d[36]), "+f"(d[37]), "+f"(d[38]), "+f"(d[39])
    : "l"(da), "l"(db), "r"(acc), "n"(TA), "n"(TB));
}

template <int TA, int TB> __device__ __forceinline__ void wgmma_n128(float (&d)[64], uint64_t da, uint64_t db, int acc) {
  asm volatile("{\n.reg .pred p;\nsetp.ne.b32 p, %66, 0;\n"
    "wgmma.mma_async.sync.aligned.m64n128k16.f32.bf16.bf16 {%0, %1, %2, %3, %4, %5, %6, %7, %8, %9, %10, %11, %12, %13, %14, %15, %16, %17, %18, %19, %20, %21, %22, %23, %24, %25, %26, %27, %28, %29, %30, %31, %32, %33, %34, %35, %36, %37, %38, %39, %40, %41, %42, %43, %44, %45, %46, %47, %48, %49, %50, %51, %52, %53, %54, %55, %56, %57, %58, %59, %60, %61, %62, %63}, %64, %65, p, 1, 1, %67, %68;\n}\n"
    : "+f"(d[0]), "+f"(d[1]), "+f"(d[2]), "+f"(d[3]), "+f"(d[4]), "+f"(d[5]), "+f"(d[6]), "+f"(d[7]), "+f"(d[8]), "+f"(d[9]), "+f"(d[10]), "+f"(d[11]), "+f"(d[12]), "+f"(d[13]), "+f"(d[14]), "+f"(d[15]), "+f"(d[16]), "+f"(d[17]), "+f"(d[18]), "+f"(d[19]), "+f"(d[20]), "+f"(d[21]), "+f"(d[22]), "+f"(d[23]), "+f"(d[24]), "+f"(d[25]), "+f"(d[26]), "+f"(d[27]), "+f"(d[28]), "+f"(d[29]), "+f"(d[30]), "+f"(d[31]), "+f"(d[32]), "+f"(d[33]), "+f"(d[34]), "+f"(d[35]), "+f"(d[36]), "+f"(d[37]), "+f"(d[38]), "+f"(d[39]), "+f"(d[40]), "+f"(d[41]), "+f"(d[42]), "+f"(d[43]), "+f"(d[44]), "+f"(d[45]), "+f"(d[46]), "+f"(d[47]), "+f"(d[48]), "+f"(d[49]), "+f"(d[50]), "+f"(d[51]), "+f"(d[52]), "+f"(d[53]), "+f"(d[54]), "+f"(d[55]), "+f"(d[56]), "+f"(d[57]), "+f"(d[58]), "+f"(d[59]), "+f"(d[60]), "+f"(d[61]), "+f"(d[62]), "+f"(d[63])
    : "l"(da), "l"(db), "r"(acc), "n"(TA), "n"(TB));
}

template <int TA, int TB> __device__ __forceinline__ void wgmma_n192(float (&d)[96], uint64_t da, uint64_t db, int acc) {
  asm volatile("{\n.reg .pred p;\nsetp.ne.b32 p, %98, 0;\n"
    "wgmma.mma_async.sync.aligned.m64n192k16.f32.bf16.bf16 {%0, %1, %2, %3, %4, %5, %6, %7, %8, %9, %10, %11, %12, %13, %14, %15, %16, %17, %18, %19, %20, %21, %22, %23, %24, %25, %26, %27, %28, %29, %30, %31, %32, %33, %34, %35, %36, %37, %38, %39, %40, %41, %42, %43, %44, %45, %46, %47, %48, %49, %50, %51, %52, %53, %54, %55, %56, %57, %58, %59, %60, %61, %62, %63, %64, %65, %66, %67, %68, %69, %70, %71, %72, %73, %74, %75, %76, %77, %78, %79, %80, %81, %82, %83, %84, %85, %86, %87, %88, %89, %90, %91, %92, %93, %94, %95}, %96, %97, p, 1, 1, %99, %100;\n}\n"
    : "+f"(d[0]), "+f"(d[1]), "+f"(d[2]), "+f"(d[3]), "+f"(d[4]), "+f"(d[5]), "+f"(d[6]), "+f"(d[7]), "+f"(d[8]), "+f"(d[9]), "+f"(d[10]), "+f"(d[11]), "+f"(d[12]), "+f"(d[13]), "+f"(d[14]), "+f"(d[15]), "+f"(d[16]), "+f"(d[17]), "+f"(d[18]), "+f"(d[19]), "+f"(d[20]), "+f"(d[21]), "+f"(d[22]), "+f"(d[23]), "+f"(d[24]), "+f"(d[25]), "+f"(d[26]), "+f"(d[27]), "+f"(d[28]), "+f"(d[29]), "+f"(d[30]), "+f"(d[31]), "+f"(d[32]), "+f"(d[33]), "+f"(d[34]), "+f"(d[35]), "+f"(d[36]), "+f"(d[37]), "+f"(d[38]), "+f"(d[39]), "+f"(d[40]), "+f"(d[41]), "+f"(d[42]), "+f"(d[43]), "+f"(d[44]), "+f"(d[45]), "+f"(d[46]), "+f"(d[47]), "+f"(d[48]), "+f"(d[49]), "+f"(d[50]), "+f"(d[51]), "+f"(d[52]), "+f"(d[53]), "+f"(d[54]), "+f"(d[55]), "+f"(d[56]), "+f"(d[57]), "+f"(d[58]), "+f"(d[59]), "+f"(d[60]), "+f"(d[61]), "+f"(d[62]), "+f"(d[63]), "+f"(d[64]), "+f"(d[65]), "+f"(d[66]), "+f"(d[67]), "+f"(d[68]), "+f"(d[69]), "+f"(d[70]), "+f"(d[71]), "+f"(d[72]), "+f"(d[73]), "+f"(d[74]), "+f"(d[75]), "+f"(d[76]), "+f"(d[77]), "+f"(d[78]), "+f"(d[79]), "+f"(d[80]), "+f"(d[81]), "+f"(d[82]), "+f"(d[83]), "+f"(d[84]), "+f"(d[85]), "+f"(d[86]), "+f"(d[87]), "+f"(d[88]), "+f"(d[89]), "+f"(d[90]), "+f"(d[91]), "+f"(d[92]), "+f"(d[93]), "+f"(d[94]), "+f"(d[95])
    : "l"(da), "l"(db), "r"(acc), "n"(TA), "n"(TB));
}

template <int TA, int TB> __device__ __forceinline__ void wgmma_n256(float (&d)[128], uint64_t da, uint64_t db, int acc) {
  asm volatile("{\n.reg .pred p;\nsetp.ne.b32 p, %130, 0;\n"
    "wgmma.mma_async.sync.aligned.m64n256k16.f32.bf16.bf16 {%0, %1, %2, %3, %4, %5, %6, %7, %8, %9, %10, %11, %12, %13, %14, %15, %16, %17, %18, %19, %20, %21, %22, %23, %24, %25, %26, %27, %28, %29, %30, %31, %32, %33, %34, %35, %36, %37, %38, %39, %40, %41, %42, %43, %44, %45, %46, %47, %48, %49, %50, %51, %52, %53, %54, %55, %56, %57, %58, %59, %60, %61, %62, %63, %64, %65, %66, %67, %68, %69, %70, %71, %72, %73, %74, %75, %76, %77, %78, %79, %80, %81, %82, %83, %84, %85, %86, %87, %88, %89, %90, %91, %92, %93, %94, %95, %96, %97, %98, %99, %100, %101, %102, %103, %104, %105, %106, %107, %108, %109, %110, %111, %112, %113, %114, %115, %116, %117, %118, %119, %120, %121, %122, %123, %124, %125, %126, %127}, %128, %129, p, 1, 1, %131, %132;\n}\n"
    : "+f"(d[0]), "+f"(d[1]), "+f"(d[2]), "+f"(d[3]), "+f"(d[4]), "+f"(d[5]), "+f"(d[6]), "+f"(d[7]), "+f"(d[8]), "+f"(d[9]), "+f"(d[10]), "+f"(d[11]), "+f"(d[12]), "+f"(d[13]), "+f"(d[14]), "+f"(d[15]), "+f"(d[16]), "+f"(d[17]), "+f"(d[18]), "+f"(d[19]), "+f"(d[20]), "+f"(d[21]), "+f"(d[22]), "+f"(d[23]), "+f"(d[24]), "+f"(d[25]), "+f"(d[26]), "+f"(d[27]), "+f"(d[28]), "+f"(d[29]), "+f"(d[30]), "+f"(d[31]), "+f"(d[32]), "+f"(d[33]), "+f"(d[34]), "+f"(d[35]), "+f"(d[36]), "+f"(d[37]), "+f"(d[38]), "+f"(d[39]), "+f"(d[40]), "+f"(d[41]), "+f"(d[42]), "+f"(d[43]), "+f"(d[44]), "+f"(d[45]), "+f"(d[46]), "+f"(d[47]), "+f"(d[48]), "+f"(d[49]), "+f"(d[50]), "+f"(d[51]), "+f"(d[52]), "+f"(d[53]), "+f"(d[54]), "+f"(d[55]), "+f"(d[56]), "+f"(d[57]), "+f"(d[58]), "+f"(d[59]), "+f"(d[60]), "+f"(d[61]), "+f"(d[62]), "+f"(d[63]), "+f"(d[64]), "+f"(d[65]), "+f"(d[66]), "+f"(d[67]), "+f"(d[68]), "+f"(d[69]), "+f"(d[70]), "+f"(d[71]), "+f"(d[72]), "+f"(d[73]), "+f"(d[74]), "+f"(d[75]), "+f"(d[76]), "+f"(d[77]), "+f"(d[78]), "+f"(d[79]), "+f"(d[80]), "+f"(d[81]), "+f"(d[82]), "+f"(d[83]), "+f"(d[84]), "+f"(d[85]), "+f"(d[86]), "+f"(d[87]), "+f"(d[88]), "+f"(d[89]), "+f"(d[90]), "+f"(d[91]), "+f"(d[92]), "+f"(d[93]), "+f"(d[94]), "+f"(d[95]), "+f"(d[96]), "+f"(d[97]), "+f"(d[98]), "+f"(d[99]), "+f"(d[100]), "+f"(d[101]), "+f"(d[102]), "+f"(d[103]), "+f"(d[104]), "+f"(d[105]), "+f"(d[106]), "+f"(d[107]), "+f"(d[108]), "+f"(d[109]), "+f"(d[110]), "+f"(d[111]), "+f"(d[112]), "+f"(d[113]), "+f"(d[114]), "+f"(d[115]), "+f"(d[116]), "+f"(d[117]), "+f"(d[118]), "+f"(d[119]), "+f"(d[120]), "+f"(d[121]), "+f"(d[122]), "+f"(d[123]), "+f"(d[124]), "+f"(d[125]), "+f"(d[126]), "+f"(d[127])
    : "l"(da), "l"(db), "r"(acc), "n"(TA), "n"(TB));
}

template <int TB> __device__ __forceinline__ void wgmma_rs_n24(float (&d)[12], uint32_t a0, uint32_t a1, uint32_t a2, uint32_t a3, uint64_t db, int acc) {
  asm volatile("{\n.reg .pred p;\nsetp.ne.b32 p, %17, 0;\n"
    "wgmma.mma_async.sync.aligned.m64n24k16.f32.bf16.bf16 {%0, %1, %2, %3, %4, %5, %6, %7, %8, %9, %10, %11}, {%12, %13, %14, %15}, %16, p, 1, 1, %18;\n}\n"
    : "+f"(d[0]), "+f"(d[1]), "+f"(d[2]), "+f"(d[3]), "+f"(d[4]), "+f"(d[5]), "+f"(d[6]), "+f"(d[7]), "+f"(d[8]), "+f"(d[9]), "+f"(d[10]), "+f"(d[11])
    : "r"(a0), "r"(a1), "r"(a2), "r"(a3), "l"(db), "r"(acc), "n"(TB));
}

template <int TB> __device__ __forceinline__ void wgmma_rs_n40(float (&d)[20], uint32_t a0, uint32_t a1, uint32_t a2, uint32_t a3, uint64_t db, int acc) {
  asm volatile("{\n.reg .pred p;\nsetp.ne.b32 p, %25, 0;\n"
    "wgmma.mma_async.sync.aligned.m64n40k16.f32.bf16.bf16 {%0, %1, %2, %3, %4, %5, %6, %7, %8, %9, %10, %11, %12, %13, %14, %15, %16, %17, %18, %19}, {%20, %21, %22, %23}, %24, p, 1, 1, %26;\n}\n"
    : "+f"(d[0]), "+f"(d[1]), "+f"(d[2]), "+f"(d[3]), "+f"(d[4]), "+f"(d[5]), "+f"(d[6]), "+f"(d[7]), "+f"(d[8]), "+f"(d[9]), "+f"(d[10]), "+f"(d[11]), "+f"(d[12]), "+f"(d[13]), "+f"(d[14]), "+f"(d[15]), "+f"(d[16]), "+f"(d[17]), "+f"(d[18]), "+f"(d[19])
    : "r"(a0), "r"(a1), "r"(a2), "r"(a3), "l"(db), "r"(acc), "n"(TB));
}

template <int TB> __device__ __forceinline__ void wgmma_rs_n192(float (&d)[96], uint32_t a0, uint32_t a1, uint32_t a2, uint32_t a3, uint64_t db, int acc) {
  asm volatile("{\n.reg .pred p;\nsetp.ne.b32 p, %101, 0;\n"
    "wgmma.mma_async.sync.aligned.m64n192k16.f32.bf16.bf16 {%0, %1, %2, %3, %4, %5, %6, %7, %8, %9, %10, %11, %12, %13, %14, %15, %16, %17, %18, %19, %20, %21, %22, %23, %24, %25, %26, %27, %28, %29, %30, %31, %32, %33, %34, %35, %36, %37, %38, %39, %40, %41, %42, %43, %44, %45, %46, %47, %48, %49, %50, %51, %52, %53, %54, %55, %56, %57, %58, %59, %60, %61, %62, %63, %64, %65, %66, %67, %68, %69, %70, %71, %72, %73, %74, %75, %76, %77, %78, %79, %80, %81, %82, %83, %84, %85, %86, %87, %88, %89, %90, %91, %92, %93, %94, %95}, {%96, %97, %98, %99}, %100, p, 1, 1, %102;\n}\n"
    : "+f"(d[0]), "+f"(d[1]), "+f"(d[2]), "+f"(d[3]), "+f"(d[4]), "+f"(d[5]), "+f"(d[6]), "+f"(d[7]), "+f"(d[8]), "+f"(d[9]), "+f"(d[10]), "+f"(d[11]), "+f"(d[12]), "+f"(d[13]), "+f"(d[14]), "+f"(d[15]), "+f"(d[16]), "+f"(d[17]), "+f"(d[18]), "+f"(d[19]), "+f"(d[20]), "+f"(d[21]), "+f"(d[22]), "+f"(d[23]), "+f"(d[24]), "+f"(d[25]), "+f"(d[26]), "+f"(d[27]), "+f"(d[28]), "+f"(d[29]), "+f"(d[30]), "+f"(d[31]), "+f"(d[32]), "+f"(d[33]), "+f"(d[34]), "+f"(d[35]), "+f"(d[36]), "+f"(d[37]), "+f"(d[38]), "+f"(d[39]), "+f"(d[40]), "+f"(d[41]), "+f"(d[42]), "+f"(d[43]), "+f"(d[44]), "+f"(d[45]), "+f"(d[46]), "+f"(d[47]), "+f"(d[48]), "+f"(d[49]), "+f"(d[50]), "+f"(d[51]), "+f"(d[52]), "+f"(d[53]), "+f"(d[54]), "+f"(d[55]), "+f"(d[56]), "+f"(d[57]), "+f"(d[58]), "+f"(d[59]), "+f"(d[60]), "+f"(d[61]), "+f"(d[62]), "+f"(d[63]), "+f"(d[64]), "+f"(d[65]), "+f"(d[66]), "+f"(d[67]), "+f"(d[68]), "+f"(d[69]), "+f"(d[70]), "+f"(d[71]), "+f"(d[72]), "+f"(d[73]), "+f"(d[74]), "+f"(d[75]), "+f"(d[76]), "+f"(d[77]), "+f"(d[78]), "+f"(d[79]), "+f"(d[80]), "+f"(d[81]), "+f"(d[82]), "+f"(d[83]), "+f"(d[84]), "+f"(d[85]), "+f"(d[86]), "+f"(d[87]), "+f"(d[88]), "+f"(d[89]), "+f"(d[90]), "+f"(d[91]), "+f"(d[92]), "+f"(d[93]), "+f"(d[94]), "+f"(d[95])
    : "r"(a0), "r"(a1), "r"(a2), "r"(a3), "l"(db), "r"(acc), "n"(TB));
}
constexpr uint32_t AR_ACC = 0;
constexpr uint32_t AR_TAB = 0x100000;
constexpr uint32_t AR_PROG = 0x101000;
#ifndef PROG_STRIDE
#define PROG_STRIDE 128
#endif
constexpr uint32_t AR_CNT = 0x108000;
constexpr uint32_t AR_QUEUE = 0x109000;
constexpr uint32_t AR_SIZE = 0x10a000;

struct ChainArgs {
  const bf16* mem0;
  const uint2* xh;
  unsigned char *kg, *vg;
  unsigned char* arena;
  uint32_t* dbg;
  uint32_t delay;
  int tl;
};

namespace ch {
constexpr int OFF_WQ = 0;
constexpr int OFF_X = 81920;
constexpr int OFF_MEM = OFF_X + 40960;
constexpr int OFF_WO = OFF_MEM + 10240;
constexpr int WOK = 8 * 896;
constexpr int OFF_KV = OFF_WO + 10 * WOK;
constexpr int KVB = 5120;
constexpr int OFF_O = OFF_KV + 4 * KVB;
constexpr int OFF_Q = OFF_O + 1024;
constexpr int OFF_S = OFF_O + 3072;
constexpr int OFF_SR = OFF_S + 1280;
constexpr int OFF_BAR = OFF_SR + 1536;
constexpr int SMEM = OFF_BAR + 128 + 1152;
static_assert(SMEM <= 232448, "smem");
constexpr int MB_S = OFF_BAR, MB_O = OFF_BAR + 8, MB_X = OFF_BAR + 16;
constexpr int MB_K = OFF_SR + 1408, MB_V = MB_K + 16, MB_Q = MB_K + 32, MB_R = MB_K + 48;
constexpr int SC_IN = OFF_BAR + 64;
constexpr int SC_MX = OFF_S;
constexpr int SC_W = OFF_BAR + 96;
constexpr int WOS = 448;
enum { B_MEM0 = 1, B_QK, B_SL, B_V, B_O, B_RED, B_X, B_C, B_H, B_MEM1, B_A, B_G };
#ifndef NQ1
#define NQ1 6
#endif
#ifndef NQ0
#define NQ0 4
#endif
#ifndef NP0
#define NP0 4
#endif
#ifndef NWO
#define NWO 5
#endif
#ifndef NWP
#define NWP 4
#endif
#ifndef NB0
#define NB0 2
#endif
#ifndef BBS
#define BBS 100
#endif
#ifndef VSYNC
#define VSYNC 0
#endif
#ifndef XPOS
#define XPOS 0
#endif
#ifndef XPD
#define XPD 300
#endif
#ifndef WOF
#define WOF 0
#endif
#ifndef XBYTES
#define XBYTES 36864
#endif
#ifndef NRT
#define NRT 7
#endif
#ifndef NRF
#define NRF 2
#endif
#ifndef NPM0
#define NPM0 2
#endif
#ifndef NPM1
#define NPM1 2
#endif
#ifndef RSYNC
#define RSYNC 1
#endif
#ifndef PFK
#define PFK 1
#endif
#ifndef PA0
#define PA0 7
#endif
#ifndef PA1
#define PA1 0
#endif
#ifndef PB0
#define PB0 7
#endif
#ifndef PB1
#define PB1 5
#endif
#ifndef PQE
#define PQE 0
#endif
#ifndef XT
#define XT 30
#endif
static_assert(NPM0 >= 2 && NPM1 >= 2, "the K / V blocks live in the last two k-steps of Wo");
}

#ifndef CHAIN_TIMING
#define CHAIN_TIMING 0
#endif
#if CHAIN_TIMING
#ifndef TR0
#define TR0 41
#endif
#ifndef TSMASK
#define TSMASK 0xffff
#endif
#define TSV(i, v) do { if ((TSMASK >> (i)) & 1) asm volatile("st.shared.u32 [%0+%1], %2;" :: "r"(tsb), "n"((i) * 4), "r"(v) : "memory"); } while (0)
#define TS(i) TSV(i, clk32())
#define TS_SETUP() const uint32_t tsb = sb + ((s == TR0 || s == TR0 + 1) ? OFF_BAR + 128 + ((s - TR0) * 12 + warp) * 48 : OFF_SR + 1152)
#else
#define TS(i)
#define TSV(i, v)
#define TS_SETUP()
#endif
#ifndef POLL_DELAY
#define POLL_DELAY 590
#endif
#ifndef XN
#define XN 40
#endif
#ifndef PF0
#define PF0 8
#endif
#ifndef PFS
#define PFS 3
#endif
#ifndef XDELAY
#define XDELAY 0
#endif
#ifndef NOKM
#define NOKM 0
#endif
#ifndef PFACC
#define PFACC 1
#endif
template <int V> using IC = std::integral_constant<int, V>;
__device__ __forceinline__ uint32_t clk_v() { uint64_t c; asm volatile("mov.u64 %0, %%clock64;" : "=l"(c) :: "memory"); return (uint32_t)c; }
__device__ __forceinline__ int fresh(int x) { int y; asm volatile("shfl.sync.bfly.b32 %0, %1, 0, 0x1f, 0xffffffff;" : "=r"(y) : "r"(x)); return y; }
#define SFENCE2(x, d) asm volatile("{\n.reg .pred p;\nsetp.eq.u32 p, %0, 0x7fffffff;\n@p st.shared.u32 [%0], %1;\n}" :: "r"(x), "r"(d) : "memory")
#define SFENCE(x) asm volatile("{\n.reg .pred p;\nsetp.eq.u32 p, %0, 0x7fffffff;\n@p st.shared.u32 [%0], %0;\n}" :: "r"(x) : "memory")
template <int I> __device__ __forceinline__ void bbfence(uint32_t x) {
  asm volatile("{\n.reg .pred p;\nsetp.eq.u32 p, %0, %1;\nL_%=:\n@p st.volatile.shared.u32 [%0], %0;\n@p bra.uni L_%=;\n}" :: "r"(x), "n"(4 * I) : "memory");
}
__device__ __forceinline__ float uniform_f(float x) { return __uint_as_float(__reduce_max_sync(0xffffffffu, __float_as_uint(x))); }

__device__ __forceinline__ void mma16816h(float (&d)[4], const uint32_t (&a)[4], uint32_t b0, uint32_t b1) {
  asm volatile("mma.sync.aligned.m16n8k16.row.col.f32.f16.f16.f32 {%0,%1,%2,%3}, {%4,%5,%6,%7}, {%8,%9}, {%0,%1,%2,%3};"
               : "+f"(d[0]), "+f"(d[1]), "+f"(d[2]), "+f"(d[3]) : "r"(a[0]), "r"(a[1]), "r"(a[2]), "r"(a[3]), "r"(b0), "r"(b1));
}
__device__ __forceinline__ void mma1688(float (&d)[4], uint32_t a0, uint32_t a1, uint32_t b0) {
  asm volatile("mma.sync.aligned.m16n8k8.row.col.f32.bf16.bf16.f32 {%0,%1,%2,%3}, {%4,%5}, {%6}, {%0,%1,%2,%3};"
               : "+f"(d[0]), "+f"(d[1]), "+f"(d[2]), "+f"(d[3]) : "r"(a0), "r"(a1), "r"(b0));
}
template <int OFF16, int ACC> __device__ __forceinline__ void wgmma_rs32h(float (&d)[16], const uint32_t (&a)[4], uint32_t dlo) {
  asm volatile("{\n.reg .pred p;\n.reg .b32 t;\n.reg .b64 db;\nsetp.ne.b32 p, %22, 0;\nadd.u32 t, %20, %21;\nmov.b64 db, {t, 0x40000040};\n"
    "wgmma.mma_async.sync.aligned.m64n32k16.f32.f16.f16 {%0,%1,%2,%3,%4,%5,%6,%7,%8,%9,%10,%11,%12,%13,%14,%15}, {%16,%17,%18,%19}, db, p, 1, 1, 0;\n}\n"
    : "+f"(d[0]), "+f"(d[1]), "+f"(d[2]), "+f"(d[3]), "+f"(d[4]), "+f"(d[5]), "+f"(d[6]), "+f"(d[7]), "+f"(d[8]), "+f"(d[9]), "+f"(d[10]), "+f"(d[11]),
      "+f"(d[12]), "+f"(d[13]), "+f"(d[14]), "+f"(d[15])
    : "r"(a[0]), "r"(a[1]), "r"(a[2]), "r"(a[3]), "r"(dlo), "n"(OFF16), "n"(ACC));
}
template <int IMM> __device__ __forceinline__ void stsm_x4_t_i(uint32_t a, uint32_t r0, uint32_t r1, uint32_t r2, uint32_t r3) {
  asm volatile("stmatrix.sync.aligned.m8n8.x4.trans.shared.b16 [%0+%5], {%1,%2,%3,%4};" :: "r"(a), "r"(r0), "r"(r1), "r"(r2), "r"(r3), "n"(IMM) : "memory");
}
template <int IMM> __device__ __forceinline__ void stsm_x2_t_i(uint32_t a, uint32_t r0, uint32_t r1) {
  asm volatile("stmatrix.sync.aligned.m8n8.x2.trans.shared.b16 [%0+%3], {%1,%2};" :: "r"(a), "r"(r0), "r"(r1), "n"(IMM) : "memory");
}
template <int IMM> __device__ __forceinline__ void st_async_b32_i(uint32_t a, uint32_t x, uint32_t mb) {
  asm volatile("st.async.weak.shared::cluster.mbarrier::complete_tx::bytes.b32 [%0+%3], %1, [%2];" :: "r"(a), "r"(x), "r"(mb), "n"(IMM) : "memory");
}
template <int IMM> __device__ __forceinline__ void ld_relaxed_v4_if(uint4& v, const void* p, uint32_t c) {
  asm volatile("{\n.reg .pred p;\nsetp.ne.u32 p, %6, 0;\n@p ld.relaxed.gpu.global.v4.u32 {%0,%1,%2,%3}, [%4+%5];\n}"
               : "+r"(v.x), "+r"(v.y), "+r"(v.z), "+r"(v.w) : "l"(p), "n"(IMM), "r"(c) : "memory");
}
template <int IMM> __device__ __forceinline__ uint32_t lds32_i(uint32_t a) {
  uint32_t v; asm volatile("ld.shared.u32 %0, [%1+%2];" : "=r"(v) : "r"(a), "n"(IMM) : "memory"); return v;
}
__device__ __forceinline__ void sts32(uint32_t a, uint32_t v) { asm volatile("st.shared.u32 [%0], %1;" :: "r"(a), "r"(v) : "memory"); }
__device__ __forceinline__ uint32_t pack_f16(float lo, float hi) {
  uint32_t d; asm("cvt.rn.f16x2.f32 %0, %1, %2;" : "=r"(d) : "f"(hi), "f"(lo)); return d;
}
__device__ __forceinline__ uint32_t amax_bf2(uint32_t a, uint32_t b) { uint32_t d; asm("max.xorsign.abs.bf16x2 %0, %1, %2;" : "=r"(d) : "r"(a), "r"(b)); return d; }
__device__ __forceinline__ uint32_t amax_h2(uint32_t a, uint32_t b) { uint32_t d; asm("max.xorsign.abs.f16x2 %0, %1, %2;" : "=r"(d) : "r"(a), "r"(b)); return d; }
__device__ __forceinline__ uint32_t amax_fold(uint32_t m) { return __reduce_max_sync(0xffffffffu, max(m & 0x7fffu, (m >> 16) & 0x7fffu)); }
__device__ __forceinline__ int wscale_exp(uint32_t m) { return min(141 - (int)(m >> 7), 100); }
__device__ __forceinline__ float exp2i(int e) { return __uint_as_float((uint32_t)(e + 127) << 23); }
__device__ __forceinline__ uint32_t bf2_to_h2(uint32_t w, float sc) { return pack_f16(bf_lo(w) * sc, bf_hi(w) * sc); }
__device__ __forceinline__ void bf2_to_h2_inplace(uint32_t& w, uint32_t sc2) {
  asm volatile("{\n.reg .b32 t, lo, hi;\nmul.rn.bf16x2 t, %0, %1;\nshl.b32 lo, t, 16;\nand.b32 hi, t, 0xffff0000;\ncvt.rn.f16x2.f32 %0, hi, lo;\n}" : "+r"(w) : "r"(sc2));
}
__device__ __forceinline__ void prefetch_l2(const void* p, uint32_t bytes) { asm volatile("cp.async.bulk.prefetch.L2.global [%0], %1;" :: "l"(p), "r"(bytes) : "memory"); }
__device__ __forceinline__ void prefetch_tma_2d(const CUtensorMap* tm, int c0, int c1) {
  asm volatile("cp.async.bulk.prefetch.tensor.2d.L2.global [%0, {%1, %2}];" :: "l"(tm), "r"(c0), "r"(c1) : "memory");
}
__host__ __device__ constexpr uint32_t acc_voff(int v) { return v < 4 ? v * 1024u : (v == 4 ? 128u : 3072u + 128u); }
__device__ __forceinline__ int unit28(int i) { return i == 3 ? 54 : 14 * i; }
__device__ __forceinline__ int unit24(int i) { return i < 2 ? 48 - 6 * i : 56 + 6 * i; }
__device__ __forceinline__ uint32_t acc_step(int s) { return (s >> 1) * 32768 + (s & 1) * 512; }
__device__ __forceinline__ uint32_t acc_lane(int i, int lane) { return ((lane >> 3) & 1) * 256 + (lane >> 4) * 4096 + i * 8192 + (lane & 7) * 16; }

__device__ __forceinline__ uint32_t ld_acquire_u32(const void* p) {
  uint32_t v; asm volatile("ld.acquire.gpu.global.u32 %0, [%1];" : "=r"(v) : "l"(p) : "memory"); return v;
}
template <int R> __device__ __forceinline__ void ln_rows(const uint2 (&xw)[R][5], int row0, int lane, bf16* __restrict__ xn, uint2* __restrict__ xh) {
  float v[R][20], s[R], q[R];
#pragma unroll
  for (int r = 0; r < R; r++) {
    s[r] = 0.f; q[r] = 0.f;
#pragma unroll
    for (int i = 0; i < 5; i++) { v[r][4 * i] = bf_lo(xw[r][i].x); v[r][4 * i + 1] = bf_hi(xw[r][i].x); v[r][4 * i + 2] = bf_lo(xw[r][i].y); v[r][4 * i + 3] = bf_hi(xw[r][i].y); }
#pragma unroll
    for (int i = 0; i < 5; i++) s[r] += (v[r][4 * i] + v[r][4 * i + 1]) + (v[r][4 * i + 2] + v[r][4 * i + 3]);
  }
#pragma unroll
  for (int o = 16; o; o >>= 1)
#pragma unroll
    for (int r = 0; r < R; r++) s[r] += __shfl_xor_sync(0xffffffffu, s[r], o);
#pragma unroll
  for (int r = 0; r < R; r++) {
    s[r] *= 1.f / cfg::DM;
#pragma unroll
    for (int i = 0; i < 10; i++) { const float d = v[r][2 * i] - s[r], e = v[r][2 * i + 1] - s[r]; q[r] += d * d + e * e; }
  }
#pragma unroll
  for (int o = 16; o; o >>= 1)
#pragma unroll
    for (int r = 0; r < R; r++) q[r] += __shfl_xor_sync(0xffffffffu, q[r], o);
#pragma unroll
  for (int r = 0; r < R; r++) {
    const int row = row0 + r;
    const float mb = bf16r(s[r]), var = bf16r(q[r] * (1.f / cfg::DM));
    const float den = bf16r(sqrtf(bf16r(var + 1e-5f)));
#pragma unroll
    for (int i = 0; i < 5; i++) {
      float y[4];
#pragma unroll
      for (int e = 0; e < 4; e++) y[e] = __fdividef(bf16r(v[r][4 * i + e] - mb), den);
      const uint32_t w0 = pack_bf16(y[0], y[1]), w1 = pack_bf16(y[2], y[3]);
      *(uint2*)(xn + (size_t)row * cfg::DM + i * 128 + lane * 4) = make_uint2(w0, w1);
      if (xh) xh[(((size_t)(row >> 5) * 10 + 2 * i + (lane >> 4)) * 32 + (row & 31)) * 16 + ((((lane >> 1) & 7) ^ (row & 7)) << 1) + (lane & 1)] =
          make_uint2(pack_f16(bf_lo(w0), bf_hi(w0)), pack_f16(bf_lo(w1), bf_hi(w1)));
    }
  }
}

__global__ void __cluster_dims__(3, 1, 1) __launch_bounds__(384, 1) chain_kernel(const ChainArgs a, const __grid_constant__ CUtensorMap tmWq,
    const __grid_constant__ CUtensorMap tmWk, const __grid_constant__ CUtensorMap tmWv, const __grid_constant__ CUtensorMap tmWo) {
  using namespace ch;
  extern __shared__ __align__(1024) unsigned char smem_raw[];
  const uint32_t sb = smem_u32(smem_raw);
  const int warp = __shfl_sync(0xffffffffu, (int)threadIdx.x >> 5, 0);
  const int lane = __shfl_sync(0xffffffffu, (int)threadIdx.x & 31, threadIdx.x & 31);
  const int cta = blockIdx.x, h = cta / 3, j = cta % 3;
  const int g = lane >> 2, q4 = lane & 3, r8 = lane & 7, m4 = lane >> 3;
  unsigned char* const arena = a.arena;
  if (sb & 1023u) __trap();
  TL_BEGIN(a.tl);
  const int col0 = j == 0 ? 0 : (j == 1 ? 224 : 432);
  auto stage_w = [&](const CUtensorMap* tm, uint32_t dst, uint32_t mb, int half) {
    mbar_expect_tx(mb + 8 * half, 40960);
    tma_load_2d(dst + half * 40960, tm, h * cfg::DH + j * 64, half * 320, mb + 8 * half);
    tma_load_2d(dst + half * 40960 + 20480, tm, h * cfg::DH + j * 64, half * 320 + 160, mb + 8 * half);
  };
  if (threadIdx.x == 256) {
    for (int i = 0; i < 9; i++) mbar_init(sb + MB_K + 8 * i, 1);
    mbar_init(sb + MB_S, 1); mbar_init(sb + MB_O, 1); mbar_init(sb + MB_X, 1);
    asm volatile("fence.mbarrier_init.release.cluster;" ::: "memory");
    for (int i = 0; i < 2; i++) { stage_w(&tmWk, sb + OFF_WQ, sb + MB_K, i); stage_w(&tmWv, sb + OFF_WO, sb + MB_V, i); }
    sts32(sb + SC_W, 0); sts32(sb + SC_W + 4, 0); sts32(sb + SC_W + 8, 0); sts32(sb + SC_IN + 12, 0); sts32(sb + SC_IN + 20, 0);
    mbar_expect_tx(sb + MB_S, 1280); mbar_expect_tx(sb + MB_O, 2048);
  }
  __syncthreads();
  asm volatile("barrier.cluster.arrive.relaxed.aligned;" ::: "memory");
  const uint32_t d1 = mapa_u32(sb, (j + 1) % 3) - sb, d2 = mapa_u32(sb, (j + 2) % 3) - sb;

  if (warp >= 8) {
    asm volatile("setmaxnreg.dec.sync.aligned.u32 40;");
    const int hw = warp - 8, ht = hw * 32 + lane;
    const bool lead = ht == 0;
    auto stage_wo = [&](int i) {
      mbar_expect_tx(sb + MB_R + 8 * i, 64 * WOS);
      tma_load_2d(sb + OFF_WO + i * 64 * WOS, &tmWo, col0, h * cfg::DH + ((i + j) % 3) * 64, sb + MB_R + 8 * i);
    };
    const unsigned char* xg = (const unsigned char*)a.xh;
    auto issue_x = [&](int s) { mbar_expect_tx(sb + MB_X, 40960); bulk_g2s(sb + OFF_X, xg + (size_t)s * 40960, 40960, sb + MB_X); };
    uint4 v[5];
#pragma unroll
    for (int i = 0; i < 5; i++) { const int c = ht + 128 * i; v[i] = ld_relaxed_v4(a.mem0 + (c & 7) * cfg::DM + (c >> 3) * 8); }
    if (hw == 2) {
      asm volatile("griddepcontrol.wait;" ::: "memory");
      asm volatile("griddepcontrol.launch_dependents;" ::: "memory");
      if (lane == 0) issue_x(0);
    }
    if (hw == 0) {
      bar_sync(B_QK, 160); if (lane == 0) stage_w(&tmWq, sb + OFF_WQ, sb + MB_Q, 0);
      bar_sync(B_SL, 160); if (lane == 0) stage_w(&tmWq, sb + OFF_WQ, sb + MB_Q, 1);
    }
    if (hw == 1) {
      bar_sync(B_V, 160); if (lane == 0) stage_wo(0);
      bar_sync(B_O, 160); if (lane == 0) { stage_wo(1); stage_wo(2); }
    }
    __syncwarp();
    {
      uint32_t m = 0;
#pragma unroll
      for (int i = 0; i < 5; i++) {
        m = amax_bf2(amax_bf2(m, amax_bf2(v[i].x, v[i].y)), amax_bf2(v[i].z, v[i].w));
      }
      m = amax_fold(m);
      if (lane == 0) sts32(sb + SC_MX + hw * 4, m);
      bar_sync(B_H, 128);
      const uint4 mm = lds128(sb + SC_MX);
      const int se = max(wscale_exp(max(max(mm.x, mm.y), max(mm.z, mm.w))), -100);
      const float sc = exp2i(se);
#pragma unroll
      for (int i = 0; i < 5; i++) {
        const int c = ht + 128 * i, t = c & 7, chn = c >> 3;
        sts128(sb + OFF_MEM + chn * 128 + ((t ^ (2 * (chn & 3))) << 4), bf2_to_h2(v[i].x, sc), bf2_to_h2(v[i].y, sc), bf2_to_h2(v[i].z, sc), bf2_to_h2(v[i].w, sc));
      }
      if (lead) { sts32(sb + SC_IN, __float_as_uint(exp2i(-se))); sts32(sb + SC_IN + 4, 0x7800u); }
    }
    {
      const uint32_t p0 = sb + OFF_WQ + hw * 2048 + lane * 16;
      uint32_t m = 0;
#pragma unroll 1
      for (int i = 0; i < 10; i++) {
        if (i == 0 || i == 5) mbar_wait(sb + MB_Q + (i ? 8 : 0), 0);
        uint32_t r[4][4];
        static_for<0, 4>([&](auto K) { ldsm_x4_i<K.value * 512>(r[K.value], p0 + i * 8192); });
#pragma unroll
        for (int k = 0; k < 4; k++) m = amax_bf2(amax_bf2(m, amax_bf2(r[k][0], r[k][1])), amax_bf2(r[k][2], r[k][3]));
      }
      m = amax_fold(m);
      if (lane == 0) asm volatile("red.shared.max.u32 [%0], %1;" :: "r"(sb + SC_W + 8), "r"(m) : "memory");
      bar_sync(B_H, 128);
      const uint32_t sc = (uint32_t)(wscale_exp(lds32_i<SC_W + 8>(sb)) + 127) * 0x00800080u;
#pragma unroll 1
      for (int i = 0; i < 10; i++) {
        uint32_t r[4][4];
        static_for<0, 4>([&](auto K) { ldsm_x4_i<K.value * 512>(r[K.value], p0 + i * 8192); });
#pragma unroll
        for (int k = 0; k < 4; k++) {
          bf2_to_h2_inplace(r[k][0], sc); bf2_to_h2_inplace(r[k][1], sc); bf2_to_h2_inplace(r[k][2], sc); bf2_to_h2_inplace(r[k][3], sc);
          stsm_x4(p0 + i * 8192 + k * 512, r[k][0], r[k][1], r[k][2], r[k][3]);
        }
      }
    }
    bar_sync(0, 384);
    if (lead) st_relaxed_u32(arena + AR_TAB + cta * 4, 0x80000000u | (lds32_i<SC_W>(sb) << 15) | lds32_i<SC_W + 4>(sb));
    asm volatile("barrier.cluster.wait.aligned;" ::: "memory");
    bar_sync(B_MEM0, 256); bar_sync(B_MEM1, 256);
    {
      uint32_t v0, v1, v2; int spin = 0;
      do {
        v0 = ld_relaxed_u32(arena + AR_TAB + lane * 4); v1 = ld_relaxed_u32(arena + AR_TAB + 128 + lane * 4); v2 = ld_relaxed_u32(arena + AR_TAB + 256 + lane * 4);
      } while (__any_sync(0xffffffffu, ((v0 & v1 & v2) >> 31) == 0) && ++spin < SPIN_LIMIT);
      const uint32_t mv = (max(max(v0, v1), v2) >> 15) & 0x7fffu, mo = max(max(v0 & 0x7fffu, v1 & 0x7fffu), v2 & 0x7fffu);
      sts32(sb + SC_IN + 8 + (lane & 1) * 16, 15 - ((__reduce_max_sync(0xffffffffu, mv) >> 7) + (__reduce_max_sync(0xffffffffu, mo) >> 7) - 252 + 22));
    }

    auto store_kv = [&](int s) {
      const size_t o = ((size_t)s * 96 + cta) * KVB; const uint32_t src = sb + OFF_KV + (s & 1) * (2 * KVB);
      fence_proxy_async(); bulk_s2g(a.kg + o, src, KVB); bulk_s2g(a.vg + o, src + KVB, KVB); bulk_commit();
    };
    const int cb28 = unit28(hw), du = (unit24(hw) - cb28) * 128;
    int ln = lane;
#ifdef TIMELINE
    if (cta == 0 && lead) { g_tl2[(a.tl >= 12) * 128 + 0] = clock64(); g_tl2[(a.tl >= 12) * 128 + 1] = gtime(); }
#endif
#pragma unroll 1
    for (int s = 0; s < cfg::NSEG; s++) {
      TS_SETUP();
      const bool last = s == cfg::NSEG - 1;
      if (ln == 0) {
        if (hw == 2 && !last) issue_x(s + 1);
        if (hw == 0 && s > 0) store_kv(s - 1);
        if (PFACC && hw == 1 && s + PFACC < cfg::NSEG - 1)
          asm volatile("prefetch.global.L2 [%0];" :: "l"(arena + (AR_ACC + acc_step(s + PFACC) + acc_lane(cta / 24, (cta & 3) * 8) + acc_voff((cta % 24) >> 2))) : "memory");
      }
      __syncwarp();
      if (last) break;
      const uint32_t kv = (s & 1) * (2 * KVB);
      ln = fresh(ln);
      uint32_t kb0[4], kb1[4];
      { const uint32_t ka = sb + kv + hw * 128 + (ln >> 3) * 640 + (ln & 7) * 16; ldsm_x4_i<OFF_KV>(kb0, ka); ldsm_x4_i<OFF_KV + 2560>(kb1, ka); }
      const uint32_t l16 = sb + ln * 16, s8 = sb + ln * 8, xs = s8 + hw * 256, xr = sb + ln * 4 + (hw >> 1) * 512 + (hw & 1) * 128;
      TS(1);
      bar_sync(B_QK, 384);
      {
        uint32_t q0[4], q1[4], q2[4], q3[4];
        float sa[4] = {0, 0, 0, 0}, sc2[4] = {0, 0, 0, 0};
        ldsm_x4_i<OFF_Q>(q0, l16); ldsm_x4_i<OFF_Q + 1024>(q2, l16); ldsm_x4_i<OFF_Q + 512>(q1, l16);
        bar_arrive(B_A, 288);
        ldsm_x4_i<OFF_Q + 1536>(q3, l16);
        mma16816(sa, q0[0], q0[1], q0[2], q0[3], kb0[0], kb0[1]);
        mma16816(sc2, q2[0], q2[1], q2[2], q2[3], kb1[0], kb1[1]);
        mma16816(sa, q1[0], q1[1], q1[2], q1[3], kb0[2], kb0[3]);
        mma16816(sc2, q3[0], q3[1], q3[2], q3[3], kb1[2], kb1[3]);
        const float x0 = (sa[0] + sa[2]) + (sc2[0] + sc2[2]), x1 = (sa[1] + sa[3]) + (sc2[1] + sc2[3]);
        const uint32_t xp = pack_bf16(x0, x1);
        st_async_b32_i<OFF_SR + 256>(xr + d1, xp, sb + MB_S + d1);
        st_async_b32_i<OFF_SR>(xr + d2, xp, sb + MB_S + d2);
        sts64_i<OFF_S>(xs, __float_as_uint(x0), __float_as_uint(x1));
      }
      TS(3);
      bar_sync(B_SL, 256);
      float t0[4], t1[4], t2[4] = {0, 0, 0, 0};
      float osc;
      {
        const uint4 si = lds128_i<SC_IN>(sb + 16 * (s & 1));
        { const uint2 x = lds64_i<OFF_S>(s8), y = lds64_i<OFF_S + 256>(s8); t0[0] = __uint_as_float(x.x); t0[1] = __uint_as_float(x.y); t0[2] = __uint_as_float(y.x); t0[3] = __uint_as_float(y.y); }
        { const uint2 x = lds64_i<OFF_S + 512>(s8), y = lds64_i<OFF_S + 768>(s8); t1[0] = __uint_as_float(x.x); t1[1] = __uint_as_float(x.y); t1[2] = __uint_as_float(y.x); t1[3] = __uint_as_float(y.y); }
        { const uint2 x = lds64_i<OFF_S + 1024>(s8); t2[0] = __uint_as_float(x.x); t2[1] = __uint_as_float(x.y); }
        const int em = (int)(si.y >> 10) - 14 + (int)(si.x >> 23) - 127;
        osc = exp2i(max(min((int)si.z - max(em, 1), 100), -100));
      }
      const uint32_t xo = sb + hw * 256 + (ln & 2) * 64 + (ln >> 2) * 16 + (ln & 1) * 8;
      const uint32_t eye = ((ln >> 3) == (ln & 3)) ? ((ln & 4) ? 0x3f800000u : 0x3f80u) : 0u;
      mbar_spin(sb + MB_S, s & 1);
      TS(4);
      uint32_t v0[4], v1[4], vm[2];
      {
        uint32_t r0[4], r1[4], r2[4];
        ldsm_x4_i<OFF_SR>(r0, l16); ldsm_x4_i<OFF_SR + 512>(r1, l16); ldsm_x4_i<OFF_SR + 1024>(r2, l16);
        mma16816(t0, r0[0], r0[1], r0[2], r0[3], eye, eye);
        mma16816(t1, r1[0], r1[1], r1[2], r1[3], eye, eye);
        mma16816(t2, r2[0], r2[1], r2[2], r2[3], eye, eye);
      }
      float sc[10] = {t0[0], t0[1], t0[2], t0[3], t1[0], t1[1], t1[2], t1[3], t2[0], t2[1]};
      const float cs = 0.07216878364870322f * 1.4426950408889634f;
      float mx = fmaxf(fmaxf(fmaxf(sc[0], sc[1]), fmaxf(sc[2], sc[3])), fmaxf(fmaxf(sc[4], sc[5]), fmaxf(sc[6], sc[7])));
      mx = fmaxf(mx, fmaxf(sc[8], sc[9]));
      {
        const float m1 = __shfl_xor_sync(0xffffffffu, mx, 1), m2 = __shfl_xor_sync(0xffffffffu, mx, 2), m3 = __shfl_xor_sync(0xffffffffu, mx, 3);
        SFENCE2(l16, __float_as_uint(mx));
        ldsm_x4_t_i<OFF_KV + KVB>(v0, l16 + (kv + hw * 1280)); ldsm_x4_t_i<OFF_KV + KVB + 640>(v1, l16 + (kv + hw * 1280));
        bar_sync(B_V, 256);
        bar_arrive(B_G, 384);
        ldsm_x2_t(vm, l16 + (ln & 8) * 64 + (kv + hw * 1280 + OFF_KV + KVB + 512));
        mx = fmaxf(fmaxf(mx, m1), fmaxf(m2, m3));
      }
      const float mo = mx * cs;
#pragma unroll
      for (int i = 0; i < 10; i++) sc[i] = ex2f(fmaf(sc[i], cs, -mo));
      const uint32_t p0 = pack_bf16(sc[0], sc[1]), p1 = pack_bf16(sc[2], sc[3]), p2 = pack_bf16(sc[4], sc[5]), p3 = pack_bf16(sc[6], sc[7]), p4 = pack_bf16(sc[8], sc[9]);
      TS(5);
      float oa[4] = {0, 0, 0, 0}, ob[4] = {0, 0, 0, 0}, oc[4] = {0, 0, 0, 0}, od[4] = {0, 0, 0, 0}, rs[4] = {0, 0, 0, 0};
      const uint32_t ones = 0x3f803f80u;
      mma16816(rs, p0, p2, p1, p3, ones, ones);
      mma16816(oc, p0, p2, p1, p3, v0[2], v0[3]);
      mma16816(od, p0, p2, p1, p3, v1[2], v1[3]);
      mma16816(oa, p0, p2, p1, p3, v0[0], v0[1]);
      mma16816(ob, p0, p2, p1, p3, v1[0], v1[1]);
      mma1688(rs, p4, 0u, ones);
      mma1688(oa, p4, 0u, vm[0]);
      mma1688(ob, p4, 0u, vm[1]);
      const float inv = rcpf(rs[0] + rs[2]) * osc;
      {
        const uint32_t y0 = pack_bf16((oa[0] + oc[2]) * inv, (oa[1] + oc[3]) * inv), y1 = pack_bf16((ob[0] + od[2]) * inv, (ob[1] + od[3]) * inv);
        st_async_v2_i<OFF_O + 2048>(xo + d1, y0, y1, sb + MB_O + d1);
        st_async_v2_i<OFF_O + 1024>(xo + d2, y0, y1, sb + MB_O + d2);
        sts64_i<OFF_O>(xo, y0, y1);
      }
      bar_arrive(B_O, 384);
      TS(6);
      if (ln == 0) {
        if (hw == 0) {
          bulk_wait<0>();
          if ((s & 3) == 0 && s > 0) {
            st_relaxed_u32(arena + (AR_PROG + (cta + ln) * PROG_STRIDE), s);
          }
        }
        if (hw == 3) { mbar_expect_tx(sb + MB_S, 1280); sts64_i<SC_IN>(sb + 16 * ((s + 1) & 1), 0x7f000000u - __float_as_uint(osc), 0u); }
      }
      __syncwarp();
      ln = fresh(ln);
      auto mslot = [&](int c) -> uint32_t { return sb + OFF_MEM + c * 128 + (((ln >> 2) ^ (2 * (c & 3))) << 4); };
      const int lq = ln & 3;
      const uint32_t ma = mslot(cb28 + lq), mb_ = mslot(cb28 + (lq >> 1)) + (lq & 1) * 8;
      const unsigned char* gp = arena + (AR_ACC + acc_lane(hw, ln) + acc_step(s));
      const bool odd = ln & 1;
      SFENCE(ma);
      bar_sync(B_RED, 384);
      SFENCE(mb_);
      const uint32_t tw = clk_v();
      TSV(7, tw);
      if (ln == 0 && hw == 3) mbar_expect_tx(sb + MB_O, 2048);
      __syncwarp();
      while (clk_v() - tw < a.delay) {}
      TS(8);
      uint4 v[6];
      int spin = 0;
      const uint32_t cm = odd ? 0x5000u : 0u;
      do {
        static_for<0, 6>([&](auto I) { v[I.value] = ld_relaxed_v4_i<acc_voff(I.value)>(gp); });
      } while (__any_sync(0xffffffffu, (~((v[0].w & v[1].w & v[2].w) & (v[3].w & v[4].w & v[5].w)) & cm) != 0) && ++spin < SPIN_LIMIT);
      v[0].w = odd ? v[3].x : v[0].w; v[1].w = odd ? v[3].y : v[1].w; v[2].w = odd ? v[3].z : v[2].w; v[3].w = odd ? 0u : v[3].w;
      sts128_i<0>(ma, v[0].x, v[0].y, v[0].z, v[0].w);
      sts128_i<512>(ma, v[1].x, v[1].y, v[1].z, v[1].w);
      sts128_i<1024>(ma, v[2].x, v[2].y, v[2].z, v[2].w);
      sts128_i<0>(ma + du, v[4].x, v[4].y, v[4].z, v[5].z);
      sts64_i<512>(mb_ + du, v[5].x, v[5].y);
      if (!odd) sts128_i<1536>(mb_, v[3].x, v[3].y, v[3].z, v[3].w);
      TSV(11, spin);
#ifdef TIMELINE
      if (spin && ln == 0) atomicAdd(&g_tl2[(a.tl >= 12) * 128 + 4], 1ull);
#endif
      TS(10);
      bar_sync(B_MEM0, 256); bar_sync(B_MEM1, 256);
      uint32_t m = lds32_i<SC_IN + 12>(sb);
      uint32_t m2 = m;
      static_for<0, 3>([&](auto I) { m = amax_h2(amax_h2(amax_h2(amax_h2(m, v[I.value].x), v[I.value].y), v[I.value].z), v[I.value].w); });
      static_for<3, 6>([&](auto I) { m2 = amax_h2(amax_h2(amax_h2(m2, v[I.value].x), v[I.value].y), v[I.value].z); });
      m = amax_fold(amax_h2(amax_h2(m2, v[3].w), m));
      if (ln == 0) asm volatile("red.shared.max.u32 [%0], %1;" :: "r"(sb + SC_IN + 4 + 16 * ((s + 1) & 1)), "r"(m) : "memory");
    }
    bar_sync(B_RED, 384);
    if (hw == 0 && ln == 0) {
      store_kv(cfg::NSEG - 1);
      bulk_wait<0>();
      st_relaxed_u32(arena + AR_PROG + cta * PROG_STRIDE, cfg::NSEG);
    }
    __syncwarp();
#ifdef TIMELINE
    if (cta == 0 && hw == 0 && ln == 0) { g_tl2[(a.tl >= 12) * 128 + 2] = clock64(); g_tl2[(a.tl >= 12) * 128 + 3] = gtime(); }
#endif
    TL_END(a.tl);
    asm volatile("barrier.cluster.arrive.relaxed.aligned; barrier.cluster.wait.aligned;" ::: "memory");
  } else {
    asm volatile("setmaxnreg.inc.sync.aligned.u32 232;");
    const int wi = warp & 3, hf = warp >> 2, tid = warp * 32 + lane;
    uint32_t w[40][4];
    uint32_t wqa;
    { const int mrow = r8 + ((lane >> 4) << 3), mch = 2 * wi + (m4 & 1); wqa = sb + mrow * 128 + ((mch ^ r8) << 4); }
    {
      const uint32_t wa = wqa + (hf ? OFF_WO : OFF_WQ);
      mbar_wait(sb + (hf ? MB_V : MB_K), 0);
      static_for<0, 20>([&](auto K) { ldsm_x4_t_i<K.value * 2048>(w[K.value], wa); });
      bar_arrive(hf ? B_V : B_QK, 160);
      mbar_wait(sb + (hf ? MB_V : MB_K) + 8, 0);
      static_for<20, 40>([&](auto K) { ldsm_x4_t_i<K.value * 2048>(w[K.value], wa); });
      bar_arrive(hf ? B_O : B_SL, 160);
      SFENCE(wa);
    }
    float iw, iq;
    {
      uint32_t m = 0;
#pragma unroll
      for (int k = 0; k < 40; k++) m = amax_bf2(amax_bf2(m, amax_bf2(w[k][0], w[k][1])), amax_bf2(w[k][2], w[k][3]));
      m = amax_fold(m);
      if (hf && lane == 0) asm volatile("red.shared.max.u32 [%0], %1;" :: "r"(sb + SC_W), "r"(m) : "memory");
      const int e = wscale_exp(m);
      const uint32_t sc = (uint32_t)(e + 127) * 0x00800080u; iw = exp2i(-e);
#pragma unroll
      for (int k = 0; k < 40; k++) { bf2_to_h2_inplace(w[k][0], sc); bf2_to_h2_inplace(w[k][1], sc); bf2_to_h2_inplace(w[k][2], sc); bf2_to_h2_inplace(w[k][3], sc); }
    }
    uint32_t x0[8];
    {
      float xa[16];
      const uint32_t dlo = (((sb + OFF_X) & 0x3FFFF) >> 4) | (1u << 16);
      mbar_wait(sb + MB_X, 0);
      wgmma_fence();
      static_for<0, 40>([&](auto K) { constexpr int k = K.value; wgmma_rs32h<((k >> 2) * 4096 + (k & 3) * 32) / 16, (k != 0)>(xa, w[k], dlo); });
      wgmma_commit();
      wgmma_wait<0>();
#pragma unroll
      for (int i = 0; i < 8; i++) x0[i] = pack_bf16(xa[2 * i] * iw, xa[2 * i + 1] * iw);
    }
    const bool t28 = j == 0 || warp < 4;
    const int bi = j == 0 ? hf : (warp < 4 ? j + 1 : 2 * (j - 1) + ((warp - 4) >> 1)), bv = t28 ? wi : 4 + (warp & 1);
    uint32_t wo1 = sb + OFF_WO + warp * 896 + lane * 16, wo2;
    {
      const int cb = (t28 ? unit28(bi) : unit24(bi)) - col0 / 8;
      uint32_t cp[4];
#pragma unroll
      for (int wd = 0; wd < 4; wd++) {
        int c, p;
        if (bv < 3) { c = 4 * bv + q4; p = wd; }
        else if (bv == 3) { if (q4 & 1) { c = 4 * (wd % 3) + q4; p = 3; } else { c = 12 + (q4 >> 1); p = wd; } }
        else if (bv == 4) { c = q4; p = wd; }
        else { if (wd < 2) { c = 4 + (q4 >> 1); p = 2 * (q4 & 1) + wd; } else { c = q4; p = 3; } }
        cp[wd] = sb + OFF_WO + ((g & 1) + (g & 2) * 4 + (g >> 2) * 2) * WOS + (cb + c) * 16 + p * 4;
      }
      const int cidx = (r8 & 1) + ((r8 >> 2) << 1);
      wo2 = sb + OFF_WO + warp * 896 + ((m4 & 1) ? 768 + (m4 >> 1) * 64 + cidx * 16 : 512 + (m4 >> 1) * 128 + r8 * 16);
      const bool dump = (m4 & 1) && (r8 & 2);
      uint32_t mo = 0;
      const bool regular = bv < 3 || bv == 4;
#pragma unroll 1
      for (int i = 0; i < 3; i++) {
        uint32_t x[4][4], y[4][4];
        const uint32_t o = i * 4 * WOK;
        mbar_wait(sb + MB_R + 8 * i, 0);
        if (regular) {
          static_for<0, 4>([&](auto K) {
            constexpr int kk = K.value;
            const uint4 u = lds128_i<kk * WOK>(cp[0] + o), v = lds128_i<kk * WOK + 4 * WOS>(cp[0] + o);
            x[kk][0] = u.x; x[kk][1] = u.y; x[kk][2] = u.z; x[kk][3] = u.w; y[kk][0] = v.x; y[kk][1] = v.y; y[kk][2] = v.z; y[kk][3] = v.w;
          });
        } else {
          static_for<0, 4>([&](auto K) {
            constexpr int kk = K.value;
#pragma unroll
            for (int wd = 0; wd < 4; wd++) { x[kk][wd] = lds32_i<kk * WOK>(cp[wd] + o); y[kk][wd] = lds32_i<kk * WOK + 4 * WOS>(cp[wd] + o); }
          });
        }
        bar_sync(B_C, 256);
        static_for<0, 4>([&](auto K) {
          constexpr int kk = K.value;
#pragma unroll
          for (int wd = 0; wd < 4; wd++) mo = amax_bf2(mo, amax_bf2(x[kk][wd], y[kk][wd]));
          stsm_x4_t_i<kk * WOK>(wo1 + o, x[kk][0], x[kk][1], y[kk][0], y[kk][1]);
          stsm_x4_t_i<0>(dump ? sb + OFF_S + 512 + lane * 16 : wo2 + o + kk * WOK, x[kk][2], x[kk][3], y[kk][2], y[kk][3]);
        });
      }
      mo = amax_fold(mo);
      if (lane == 0) asm volatile("red.shared.max.u32 [%0], %1;" :: "r"(sb + SC_W + 4), "r"(mo) : "memory");
    }
    __syncwarp();
    auto run = [&](auto HF) {
    constexpr int hf = HF.value;
    uint32_t mema, sta, l16 = sb + lane * 16;
    uint32_t rq[hf ? NQ1 : NQ0][4];
    auto step_addr = [&](uint32_t kv) {
      const int lr = (l16 >> 4) & 7, lm = (l16 >> 7) & 3;
      mema = l16 ^ (lm << 5);
      sta = sb + lr * 16 + (lm < 2 ? OFF_Q + wi * 512 + hf * 128 + lm * 256 : OFF_KV + kv + 512 + (2 * wi + lm - 2) * 640);
    };
    auto x_gemm = [&](uint32_t ph, [[maybe_unused]] uint32_t tsb) {
      float xa[16];
      const uint32_t dlo = (((sb + OFF_X) & 0x3FFFF) >> 4) | (1u << 16);
      constexpr int NP = hf ? NQ1 : NP0;
      if constexpr (hf) {
        static_for<PQE, NP>([&](auto K) { ldsm_x4_t_i<OFF_WQ + K.value * 2048>(rq[K.value], wqa); });
        bar_sync(B_X, 256);
      }
      wgmma_fence();
      static_for<0, 40>([&](auto K) {
        constexpr int k = K.value;
        wgmma_rs32h<((k >> 2) * 4096 + (k & 3) * 32) / 16, (k != 0)>(xa, w[k], dlo);
        if constexpr (!hf && k == PFK && NP > PQE) { SFENCE(wqa); static_for<PQE, NP>([&](auto K) { ldsm_x4_t_i<OFF_WQ + K.value * 2048>(rq[K.value], wqa); }); SFENCE(wqa); }
        if constexpr (!hf && k == XT) bar_arrive(B_X, 256);
      });
      step_addr(ph * (2 * KVB));
      wgmma_commit();
      TS(9);
      wgmma_wait<0>();
      const uint32_t xs = l16 + (wi * 1280 + ph * (2 * KVB));
      stsm_x4_t_i<OFF_KV + hf * KVB>(xs, pack_bf16(xa[0] * iw, xa[1] * iw), pack_bf16(xa[4] * iw, xa[5] * iw), pack_bf16(xa[8] * iw, xa[9] * iw), pack_bf16(xa[12] * iw, xa[13] * iw));
      stsm_x4_t_i<OFF_KV + hf * KVB + 640>(xs, pack_bf16(xa[2] * iw, xa[3] * iw), pack_bf16(xa[6] * iw, xa[7] * iw), pack_bf16(xa[10] * iw, xa[11] * iw), pack_bf16(xa[14] * iw, xa[15] * iw));
    };
    auto wq_addr = [&](uint32_t l) -> uint32_t {
      const int lr = (l >> 4) & 7, lm = (l >> 7) & 3;
      return sb + hf * ((40 - NQ1) * 2048) + (lr + ((lm >> 1) << 3)) * 128 + (((2 * wi + (lm & 1)) ^ lr) << 4);
    };
    constexpr int NPM = hf ? NPM1 : NPM0;
    uint32_t u1[NPM][4], u2[NPM][4];
    static_for<0, NPM>([&](auto K) { ldsm_x4_i<(12 - NPM + K.value) * WOK>(u1[K.value], wo1); ldsm_x4_i<(12 - NPM + K.value) * WOK>(u2[K.value], wo2); });
    bar_sync(0, 384);
    iq = uniform_f(exp2i(-wscale_exp(lds32_i<SC_W + 8>(sb))));
    wqa = wq_addr(l16);
    static_for<0, (hf ? NQ1 : NP0)>([&](auto K) { ldsm_x4_t_i<OFF_WQ + K.value * 2048>(rq[K.value], wqa); });
    step_addr(0);
    stsm_x4_t_i<OFF_KV + hf * KVB>(l16 + wi * 1280, x0[0], x0[2], x0[4], x0[6]);
    stsm_x4_t_i<OFF_KV + hf * KVB + 640>(l16 + wi * 1280, x0[1], x0[3], x0[5], x0[7]);
    asm volatile("barrier.cluster.wait.aligned;" ::: "memory");
    TL_END(a.tl + 1);
#pragma unroll 1
    for (int s = 0; s < cfg::NSEG; s++) {
      TS_SETUP();
      const bool last = s == cfg::NSEG - 1;
#if CHAIN_TIMING
      if (tid == 0 && (s & 7) == 0) a.dbg[96 * 288 + cta * 8 + (s >> 3)] = clk32();
#endif
      bar_sync(hf ? B_MEM1 : B_MEM0, 256);
      const float sin_ = __uint_as_float(lds32_i<SC_IN>(sb + 16 * (s & 1)));
      constexpr int NPQ = (40 - NQ1) / 2;
      if constexpr (hf == 0) {
        float k0[4] = {0, 0, 0, 0}, k1[4] = {0, 0, 0, 0}, q0[4] = {0, 0, 0, 0}, q1[4] = {0, 0, 0, 0};
        constexpr auto pair_of = [](int t) { const int a = t * (20 - NPQ) / 20, b = (t + 1) * (20 - NPQ) / 20; return b > a ? NPQ + a : t - a; };
        uint32_t b[NB0][4];
        static_for<0, NB0>([&](auto T) { ldsm_x4_i<OFF_MEM + pair_of(T.value) * 512>(b[T.value], mema); });
        static_for<NP0, NQ0>([&](auto K) { ldsm_x4_t_i<OFF_WQ + K.value * 2048>(rq[K.value], wqa); });
        if (BBS < 100) bbfence<0>(mema);
        static_for<0, 20>([&](auto T) {
          constexpr int t = T.value, p = pair_of(t);
          uint32_t (&bb)[4] = b[t % NB0];
          if constexpr (p < NPQ) {
            mma16816h(q0, rq[(2 * p) % NQ0], bb[0], bb[1]);
            if constexpr (2 * p + NQ0 < 2 * NPQ) ldsm_x4_t_i<OFF_WQ + (2 * p + NQ0) * 2048>(rq[(2 * p) % NQ0], wqa);
          }
          mma16816h(k0, w[2 * p], bb[0], bb[1]);
          if constexpr (p < NPQ) {
            mma16816h(q1, rq[(2 * p + 1) % NQ0], bb[2], bb[3]);
            if constexpr (2 * p + 1 + NQ0 < 2 * NPQ) ldsm_x4_t_i<OFF_WQ + (2 * p + 1 + NQ0) * 2048>(rq[(2 * p + 1) % NQ0], wqa);
          }
          mma16816h(k1, w[2 * p + 1], bb[2], bb[3]);
          if constexpr (t + NB0 < 20) ldsm_x4_i<OFF_MEM + pair_of(t + NB0) * 512>(bb, mema);
          if constexpr (t < 20 - NB0 && (t % BBS) == BBS - 1) bbfence<t + 1>(mema);
        });
        const float sq = sin_ * iq, sk = sin_ * iw;
        stsm_x4_t_i<0>(sta, pack_bf16((q0[0] + q1[0]) * sq, (q0[1] + q1[1]) * sq), pack_bf16((q0[2] + q1[2]) * sq, (q0[3] + q1[3]) * sq),
                       pack_bf16((k0[0] + k1[0]) * sk, (k0[1] + k1[1]) * sk), pack_bf16((k0[2] + k1[2]) * sk, (k0[3] + k1[3]) * sk));
        TS(2);
        if (!last) {
          if (wi == 3) {
            const uint32_t s8 = sb + ((l16 & 511) >> 1), xr = sb + ((l16 & 511) >> 2), ka = l16 + (l16 & 384) * 4 + (s & 1) * (2 * KVB);
            bar_sync(B_QK, 384);
            uint32_t a0[4], a1[4], a2[4], a3[4], kb0[4], kb1[4];
            ldsm_x4_i<OFF_Q>(a0, l16); ldsm_x4_i<OFF_KV + 512>(kb0, ka); ldsm_x4_i<OFF_Q + 1024>(a2, l16); ldsm_x4_i<OFF_KV + 512 + 2560>(kb1, ka);
            ldsm_x4_i<OFF_Q + 512>(a1, l16);
            bar_arrive(B_A, 288);
            ldsm_x4_i<OFF_Q + 1536>(a3, l16);
            float sa[4] = {0, 0, 0, 0}, sc2[4] = {0, 0, 0, 0};
            mma16816(sa, a0[0], a0[1], a0[2], a0[3], kb0[0], kb0[1]);
            mma16816(sc2, a2[0], a2[1], a2[2], a2[3], kb1[0], kb1[1]);
            mma16816(sa, a1[0], a1[1], a1[2], a1[3], kb0[2], kb0[3]);
            mma16816(sc2, a3[0], a3[1], a3[2], a3[3], kb1[2], kb1[3]);
            const float x0 = (sa[0] + sa[2]) + (sc2[0] + sc2[2]), x1 = (sa[1] + sa[3]) + (sc2[1] + sc2[3]);
            const uint32_t xp = pack_bf16(x0, x1);
            st_async_b32_i<OFF_SR + 1024 + 256>(xr + d1, xp, sb + MB_S + d1);
            st_async_b32_i<OFF_SR + 1024>(xr + d2, xp, sb + MB_S + d2);
            sts64_i<OFF_S + 1024>(s8, __float_as_uint(x0), __float_as_uint(x1));
          } else {
            bar_arrive(B_QK, 384);
          }
          bar_sync(B_SL, 256);
        }
      } else {
        float v0[4] = {0, 0, 0, 0}, v1[4] = {0, 0, 0, 0}, q0[4] = {0, 0, 0, 0}, q1[4] = {0, 0, 0, 0};
        uint32_t b[NQ1 / 2][4];
        static_for<0, NQ1 / 2>([&](auto T) { ldsm_x4_i<OFF_MEM + (NPQ + T.value) * 512>(b[T.value], mema); });
        static_for<0, NQ1 / 2>([&](auto T) {
          constexpr int t = T.value, p = NPQ + t;
          uint32_t (&bb)[4] = b[t];
          mma16816h(q0, rq[2 * t], bb[0], bb[1]);
          mma16816h(q1, rq[2 * t + 1], bb[2], bb[3]);
          mma16816h(v0, w[2 * p], bb[0], bb[1]);
          mma16816h(v1, w[2 * p + 1], bb[2], bb[3]);
        });
        const float sq = sin_ * iq, sv = sin_ * iw;
        stsm_x2_t_i<0>(sta, pack_bf16((q0[0] + q1[0]) * sq, (q0[1] + q1[1]) * sq), pack_bf16((q0[2] + q1[2]) * sq, (q0[3] + q1[3]) * sq));
        TS(2);
        if (!last) { bar_arrive(B_QK, 384); bar_sync(B_A, 288); }
        float v2[4] = {0, 0, 0, 0}, v3[4] = {0, 0, 0, 0};
        uint32_t c[4][4];
        static_for<0, 4>([&](auto T) { ldsm_x4_i<OFF_MEM + T.value * 512>(c[T.value], mema); });
        static_for<0, NPQ>([&](auto T) {
          constexpr int p = T.value;
          uint32_t (&bb)[4] = c[p & 3];
          if constexpr (p & 1) { mma16816h(v0, w[2 * p], bb[0], bb[1]); mma16816h(v1, w[2 * p + 1], bb[2], bb[3]); }
          else { mma16816h(v2, w[2 * p], bb[0], bb[1]); mma16816h(v3, w[2 * p + 1], bb[2], bb[3]); }
          if constexpr (p + 4 < NPQ) ldsm_x4_i<OFF_MEM + (p + 4) * 512>(bb, mema);
        });
        stsm_x2_t_i<OFF_KV + KVB + 512>(l16 + (l16 & 128) * 4 + (wi * 1280 + (s & 1) * (2 * KVB)), pack_bf16(((v0[0] + v1[0]) + (v2[0] + v3[0])) * sv, ((v0[1] + v1[1]) + (v2[1] + v3[1])) * sv),
                            pack_bf16(((v0[2] + v1[2]) + (v2[2] + v3[2])) * sv, ((v0[3] + v1[3]) + (v2[3] + v3[3])) * sv));
        if (!last) bar_arrive(B_V, 256);
      }
      TS(3);
      if (last) break;
      {
        uint32_t t1[12][4], t2[12][4];
        const uint32_t o16 = l16;
        wo1 = l16 + (OFF_WO + warp * 896);
        wo2 = sb + OFF_WO + warp * 896 + ((l16 & 128) ? 768 + ((l16 & 256) >> 2) + (l16 & 16) + ((l16 & 64) >> 1) : 512 + ((l16 & 256) >> 1) + (l16 & 112));
        auto ldw = [&](auto K) { if constexpr (K.value < 12 - NPM) { ldsm_x4_i<K.value * WOK>(t1[K.value], wo1); ldsm_x4_i<K.value * WOK>(t2[K.value], wo2); } };
        constexpr int NR_ = NRT - NPM;
        constexpr int PB = (hf ? PB1 : PB0) < NR_ ? (hf ? PB1 : PB0) : NR_, PA = (hf ? PA1 : PA0) < PB ? (hf ? PA1 : PA0) : PB;
        static_for<0, PA>(ldw);
        mbar_spin(sb + MB_X, (s + 1) & 1);
        if constexpr (PB > PA) bar_sync(B_G, 384); else bar_arrive(B_G, 384);
        static_for<PA, PB>(ldw);
        float c0[4] = {0, 0, 0, 0}, c1[4] = {0, 0, 0, 0}, e0[4] = {0, 0, 0, 0}, e1[4] = {0, 0, 0, 0};
        uint32_t ob[6][4];
        auto kstep = [&](auto K) {
          constexpr int k = K.value;
          uint32_t (&bb)[4] = ob[k >> 1];
          uint32_t (&x)[4] = k < 12 - NPM ? t1[k] : u1[k < 12 - NPM ? 0 : k - (12 - NPM)];
          uint32_t (&y)[4] = k < 12 - NPM ? t2[k] : u2[k < 12 - NPM ? 0 : k - (12 - NPM)];
          if constexpr (k & 1) { mma16816(c1, x[0], x[1], x[2], x[3], bb[2], bb[3]); mma16816(e1, y[0], y[1], y[2], y[3], bb[2], bb[3]); }
          else { mma16816(c0, x[0], x[1], x[2], x[3], bb[0], bb[1]); mma16816(e0, y[0], y[1], y[2], y[3], bb[0], bb[1]); }
          if constexpr (k >= NRF) ldw(IC<k + NR_ - NRF>{});
        };
        auto ldo = [&](auto P) { ldsm_x4_i<OFF_O + P.value * 512>(ob[P.value], o16); };
        TS(4);
        bar_sync(B_O, 384);
        ldo(IC<0>{}); ldo(IC<1>{});
        SFENCE(o16);
        static_for<PB, NR_>(ldw);
        static_for<0, 4>(kstep);
        TS(5);
        mbar_spin(sb + MB_O, s & 1);
        TS(6);
        ldo(IC<2>{}); ldo(IC<NPM >= 2 ? 5 : 3>{});
        if (WOF) SFENCE(o16);
        kstep(IC<4>{});
        if constexpr (NPM < 2) { kstep(IC<5>{}); ldo(IC<4>{}); kstep(IC<6>{}); kstep(IC<7>{}); ldo(IC<5>{}); static_for<8, 12>(kstep); }
        else if constexpr (NPM >= 4) { kstep(IC<10>{}); kstep(IC<11>{}); ldo(IC<4>{}); kstep(IC<5>{}); ldo(IC<3>{}); kstep(IC<8>{}); kstep(IC<9>{}); kstep(IC<6>{}); kstep(IC<7>{}); }
        else { kstep(IC<5>{}); ldo(IC<3>{}); kstep(IC<11>{}); kstep(IC<10>{}); ldo(IC<4>{}); kstep(IC<6>{}); kstep(IC<7>{}); if constexpr (NPM == 3) { kstep(IC<9>{}); kstep(IC<8>{}); } else { kstep(IC<8>{}); kstep(IC<9>{}); } }
        l16 = fresh(l16);
        const int ln = (l16 >> 4) & 31;
        unsigned char* gr = arena + (AR_ACC + acc_lane(bi, ln) + acc_voff(bv) + acc_step(s));
        const bool cnt = (ln & 1) || !t28;
        wqa = wq_addr(l16);
        SFENCE(o16);
        static_for<0, PQE>([&](auto K) { ldsm_x4_t_i<OFF_WQ + K.value * 2048>(rq[K.value], wqa); });
        const uint32_t y0 = movm_t(pack_f16(c0[0] + c1[0], c0[1] + c1[1])), y1 = movm_t(pack_f16(c0[2] + c1[2], c0[3] + c1[3]));
        const uint32_t y2 = movm_t(pack_f16(e0[0] + e1[0], e0[1] + e1[1])), y3 = movm_t(pack_f16(e0[2] + e1[2], e0[3] + e1[3]));
        asm volatile("red.relaxed.gpu.global.add.noftz.v4.f16x2 [%0], {%1,%2,%3,%4};" :: "l"(gr), "r"(y0), "r"(y1), "r"(y2), "r"(cnt ? 0x3c00u : y3) : "memory");
        bar_arrive(B_RED, 384);
        bar_sync(B_C, 256);
        TS(7);
      }
#if CHAIN_TIMING
      x_gemm((s + 1) & 1, tsb);
#else
      x_gemm((s + 1) & 1, 0);
#endif
      TS(8);
    }
    };
    if (hf == 0) run(IC<0>{}); else run(IC<1>{});
    bar_arrive(B_RED, 384);
#if CHAIN_TIMING
    for (int i = tid; i < 288; i += 256) a.dbg[cta * 288 + i] = lds32_i<OFF_BAR + 128>(sb + i * 4);
#endif
    asm volatile("barrier.cluster.arrive.relaxed.aligned; barrier.cluster.wait.aligned;" ::: "memory");
  }
}
struct PrepArgs { const bf16 *wqkv, *wphi, *wo; unsigned char *wb, *wot; };
__device__ __forceinline__ void prep_body(const int cta, const PrepArgs& pa) {
  const int tid = threadIdx.x, lane = tid & 31, warp = tid >> 5, g = lane >> 2, q = lane & 3;
  const int pair = cta >> 1, which = cta & 1;
  uint32_t af[5][2][6];
#pragma unroll
  for (int i = 0; i < 5; i++)
#pragma unroll
    for (int hh = 0; hh < 2; hh++) {
      const uint32_t* r0 = (const uint32_t*)(pa.wqkv + (size_t)((warp * 5 + i) * 16 + g) * 1920 + which * 640 + (2 * pair + hh) * 20) + q;
      const uint32_t* r1 = r0 + 8 * 960;
      af[i][hh][0] = __ldg(r0); af[i][hh][1] = __ldg(r1); af[i][hh][2] = __ldg(r0 + 4); af[i][hh][3] = __ldg(r1 + 4);
      af[i][hh][4] = q < 2 ? __ldg(r0 + 8) : 0u; af[i][hh][5] = q < 2 ? __ldg(r1 + 8) : 0u;
    }
  uint32_t bfr[2][3][3];
#pragma unroll
  for (int hh = 0; hh < 2; hh++)
#pragma unroll
    for (int t = 0; t < 3; t++) {
      const bool on = t < 2 || (g & 1) == hh;
      const unsigned short* ph = (const unsigned short*)pa.wphi + (2 * pair + hh) * 400 + (t < 2 ? 8 * t + g : 16 + (g >> 1)) + 2 * q * 20;
#pragma unroll
      for (int r = 0; r < 3; r++) bfr[hh][t][r] = (on && (r < 2 || q < 2)) ? (uint32_t)__ldg(ph + r * 160) | ((uint32_t)__ldg(ph + r * 160 + 20) << 16) : 0u;
    }
  const int gt = cta * 256 + tid;
#pragma unroll 3
  for (int i = gt; i < 640 * 32; i += 8192) {
    const int k = (i & 7) + (i >> 8) * 8, h = (i >> 3) & 31;
    const uint2* src = (const uint2*)(pa.wqkv + (size_t)k * 1920 + 1280 + h * 20);
    const uint2 a = __ldg(src), b = __ldg(src + 1), c = __ldg(src + 2), d = __ldg(src + 3), e = __ldg(src + 4);
    uint4* dst = (uint4*)(pa.wb + ((size_t)((h >> 2) * 80 + (k >> 3)) * 32 + 20 + 3 * (h & 3)) * 128 + (k & 7) * 16);
    dst[0] = make_uint4(a.x, a.y, b.x, b.y); dst[8] = make_uint4(c.x, c.y, d.x, d.y);
    dst[16] = (h & 1) ? make_uint4(0, 0, e.x, e.y) : make_uint4(e.x, e.y, 0, 0);
  }
#pragma unroll 7
  for (int i = gt; i < 640 * 80; i += 8192) {
    const int r = i & 7, c = (i >> 3) % 80, kg = i / 640, c5 = kg % 5;
    const int row = (kg / 5) * 40 + (c5 < 2 ? 8 * c5 + r : (c5 == 2 ? 16 + (r & 3) + (r >> 2) * 20 : 20 + 8 * (c5 - 3) + r));
    *(uint4*)(pa.wot + ((size_t)((c / 10) * 80 + kg) * 10 + c % 10) * 128 + r * 16) = __ldg((const uint4*)(pa.wo + (size_t)row * cfg::DM + c * 8));
  }
#pragma unroll
  for (int i = 0; i < 5; i++) {
    uint32_t* dst = (uint32_t*)(pa.wb + ((size_t)((pair >> 1) * 80 + (warp * 5 + i) * 2) * 32 + which * 10 + (pair & 1) * 5) * 128) + lane;
#pragma unroll
    for (int t = 0; t < 5; t++) {
      float d[4] = {0, 0, 0, 0};
#pragma unroll
      for (int hh = 0; hh < 2; hh++)
        if (t == 2 || (t > 2) == (hh == 1)) {
          const int tt = t < 3 ? t : t - 3;
          mma16816(d, af[i][hh][0], af[i][hh][1], af[i][hh][2], af[i][hh][3], bfr[hh][tt][0], bfr[hh][tt][1]);
          mma1688(d, af[i][hh][4], af[i][hh][5], bfr[hh][tt][2]);
        }
      dst[t * 32] = pack_bf16(d[0], d[1]); dst[1024 + t * 32] = pack_bf16(d[2], d[3]);
    }
  }
}

__global__ void __launch_bounds__(256, 4) ln_kernel(const bf16* __restrict__ xin, bf16* __restrict__ xn, uint2* __restrict__ xh, uint4* __restrict__ z0, int n0,
                                                    uint4* __restrict__ z1, int n1, const bf16* pfa, const bf16* pfb, int npf, int tl) {
  asm volatile("griddepcontrol.wait;" ::: "memory");
  asm volatile("griddepcontrol.launch_dependents;" ::: "memory");
  TL_BEGIN(tl);
  const int warp = threadIdx.x >> 5, lane = threadIdx.x & 31;
  const int row = blockIdx.x * 8 + warp;
  uint2 xw[1][5];
#pragma unroll
  for (int i = 0; i < 5; i++) xw[0][i] = *(const uint2*)(xin + (size_t)row * cfg::DM + i * 128 + lane * 4);
  for (int i = blockIdx.x * 256 + threadIdx.x; i < n0; i += 256 * 256) z0[i] = make_uint4(0, 0, 0, 0);
  for (int i = blockIdx.x * 256 + threadIdx.x; i < n1; i += 256 * 256) z1[i] = make_uint4(0, 0, 0, 0);
  if (npf && xw[0][4].y != 0x7fc17fc1u) {
    for (int i = 0; i < npf; i++) {
      const uint32_t l = (uint32_t)i * 32768u + (blockIdx.x * 256 + threadIdx.x) / 2;
      if (l < cfg::DM * cfg::HD / 64) asm volatile("prefetch.global.L2 [%0];" :: "l"(((threadIdx.x & 1) ? pfa : pfb) + (size_t)l * 64) : "memory");
    }
  }
  ln_rows<1>(xw, row, lane, xn, xh);
  TL_END(tl);
}
struct Pipe { uint32_t stage, phase; };
template <int NS> __device__ __forceinline__ void pipe_adv(Pipe& p) { if (++p.stage == NS) { p.stage = 0; p.phase ^= 1; } }
constexpr uint32_t SWZ128 = 1;
__device__ __forceinline__ uint64_t desc_kmajor(uint32_t a) { return make_desc(a, 16, 1024, SWZ128); }
__device__ __forceinline__ uint64_t desc_mnmajor(uint32_t a) { return make_desc(a, 8192, 1024, SWZ128); }
__device__ __forceinline__ void wait_ge(const void* p, uint32_t target, uint32_t ns = 32) {
  int spin = 0;
  while (ld_acquire_u32(p) < target) { __nanosleep(ns); if (++spin > (1 << 21)) break; }
}
__device__ __forceinline__ void bulk_g2s_hint(uint32_t dst, const void* src, uint32_t bytes, uint32_t mb, uint64_t pol) {
  asm volatile("cp.async.bulk.shared::cluster.global.mbarrier::complete_tx::bytes.L2::cache_hint [%0], [%1], %2, [%3], %4;"
               :: "r"(dst), "l"(src), "r"(bytes), "r"(mb), "l"(pol) : "memory");
}
#ifndef PF_WB
#define PF_WB 1
#endif
#ifndef LNP
#define LNP 6
#endif
#ifndef STAG
#define STAG 1
#endif
#ifndef EF_KV
#define EF_KV 1
#endif
#ifndef EF_O
#define EF_O 1
#endif
__device__ __forceinline__ void fence_proxy_async_global() { asm volatile("fence.proxy.async.global;" ::: "memory"); }

namespace tr {
constexpr int NS = 4, STQ = 16384 + 24576, STO = 16384 + 40960;
constexpr int SEGB = 15360;
constexpr int OFF_K = NS * STQ;
constexpr int OFF_BAR = NS * STO;
constexpr int SMEM = OFF_BAR + 256;
static_assert(OFF_K + 4 * SEGB <= OFF_BAR && SMEM <= 232448, "smem");
enum { T_QA = 0, T_Q, T_A, T_OB, T_OS, T_L, T_END };
constexpr uint32_t C_QA = AR_CNT, C_O = AR_CNT + 64, C_Q = AR_CNT + 128;
struct Sched {
  uint16_t start[96];
  uint8_t type[96], blk[96], first[96];
  uint8_t ks[16];
  uint8_t wide[16];
  uint8_t lrows[16];
};
struct Args {
  const unsigned char *kg, *vg;
  unsigned char* o;
  uint4* qs;
  unsigned char* part;
  const bf16* xin;
  bf16 *xout, *xn;
  unsigned char* arena;
  int doprep, tl;
  uint32_t nap, nap2;
};
}

template <int N0, int N1>
__device__ __forceinline__ void tr_mainloop(float (&a0)[N0 / 2], float (&a1)[N1 ? N1 / 2 : 1], Pipe& p, uint32_t sb, uint32_t full, uint32_t empty, int nkb, int wg) {
  using namespace tr;
  constexpr uint32_t ST = N1 ? STO : STQ;
  uint32_t prev = 0;
#pragma unroll
  for (int i = 0; i < N0 / 2; i++) a0[i] = 0.f;
  if constexpr (N1 > 0) {
#pragma unroll
    for (int i = 0; i < N1 / 2; i++) a1[i] = 0.f;
  }
#pragma unroll 1
  for (int kb = 0; kb < nkb; kb++) {
    mbar_wait(full + 8 * p.stage, p.phase);
    const uint32_t st = sb + p.stage * ST;
    wgmma_fence();
#pragma unroll
    for (int kk = 0; kk < 4; kk++) {
      const uint64_t da = desc_kmajor(st + wg * 8192 + kk * 32);
      if constexpr (N0 == 192) wgmma_n192<0, 1>(a0, da, desc_mnmajor(st + 16384 + kk * 2048), (kb | kk) != 0);
      else wgmma_n128<0, 1>(a0, da, desc_mnmajor(st + 16384 + kk * 2048), (kb | kk) != 0);
      if constexpr (N1 > 0) wgmma_n128<0, 1>(a1, da, desc_mnmajor(st + 16384 + 24576 + kk * 2048), (kb | kk) != 0);
    }
    wgmma_commit();
    if (kb > 0) { wgmma_wait<1>(); mbar_arrive_if((threadIdx.x & 127) == 0, empty + 8 * prev); }
    prev = p.stage;
    pipe_adv<NS>(p);
  }
  wgmma_wait<0>();
  mbar_arrive_if((threadIdx.x & 127) == 0, empty + 8 * prev);
}
template <int N> __device__ __forceinline__ void stage_tiles(const float (&o)[N / 2], uint32_t base, int wi, int lane) {
  const uint32_t ra = base + (wi * 16 + (lane & 7) + 8 * ((lane >> 3) & 1)) * 128;
#pragma unroll
  for (int v = 0; v < N / 8; v += 2)
    stsm_x4(ra + (v >> 3) * 8192 + ((((v & 7) + (lane >> 4)) ^ (lane & 7)) << 4), pack_bf16(o[4 * v], o[4 * v + 1]), pack_bf16(o[4 * v + 2], o[4 * v + 3]),
            pack_bf16(o[4 * v + 4], o[4 * v + 5]), pack_bf16(o[4 * v + 6], o[4 * v + 7]));
}
template <int NP> __device__ __forceinline__ void l_row(const tr::Args& a, int row, int np, int lane) {
  uint2 xw[1][5]; float s[20];
#pragma unroll
  for (int i = 0; i < 5; i++) {
    xw[0][i] = __ldcg((const uint2*)(a.xin + (size_t)row * cfg::DM + i * 128 + lane * 4));
    s[4 * i] = s[4 * i + 1] = s[4 * i + 2] = s[4 * i + 3] = 0.f;
  }
  const unsigned char* pp = a.part + (size_t)(row >> 6) * 81920 + (lane >> 4) * 8192 + (row & 63) * 128 + ((((lane >> 1) & 7) ^ (row & 7)) << 4) + (lane & 1) * 8;
#pragma unroll 1
  for (int p0 = 0; p0 < np; p0 += NP) {
    uint2 t[NP][5];
    static_for<0, NP>([&](auto Q) {
      static_for<0, 5>([&](auto I) {
        asm volatile("{\n.reg .pred p;\nsetp.ne.u32 p, %3, 0;\nmov.b32 %0, 0;\nmov.b32 %1, 0;\n@p ld.global.cg.v2.u32 {%0,%1}, [%2+%4];\n}"
                     : "=r"(t[Q.value][I.value].x), "=r"(t[Q.value][I.value].y) : "l"(pp), "r"((uint32_t)(p0 + Q.value < np)), "n"(I.value * 16384) : "memory");
      });
      pp += 32 * 81920;
    });
#pragma unroll
    for (int q = 0; q < NP; q++)
#pragma unroll
      for (int i = 0; i < 5; i++) { s[4 * i] += bf_lo(t[q][i].x); s[4 * i + 1] += bf_hi(t[q][i].x); s[4 * i + 2] += bf_lo(t[q][i].y); s[4 * i + 3] += bf_hi(t[q][i].y); }
  }
#pragma unroll
  for (int i = 0; i < 5; i++) {
    xw[0][i] = make_uint2(pack_bf16(bf_lo(xw[0][i].x) + bf16r(s[4 * i]), bf_hi(xw[0][i].x) + bf16r(s[4 * i + 1])),
                          pack_bf16(bf_lo(xw[0][i].y) + bf16r(s[4 * i + 2]), bf_hi(xw[0][i].y) + bf16r(s[4 * i + 3])));
    *(uint2*)(a.xout + (size_t)row * cfg::DM + i * 128 + lane * 4) = xw[0][i];
  }
  ln_rows<1>(xw, row, lane, a.xn, nullptr);
}

__global__ void __launch_bounds__(384, 1) trail_kernel(const __grid_constant__ CUtensorMap tmX, const __grid_constant__ CUtensorMap tmQ,
                                                       const __grid_constant__ CUtensorMap tmWo5, const __grid_constant__ CUtensorMap tmWo2, const __grid_constant__ tr::Sched sc,
                                                       const __grid_constant__ tr::Args a, const __grid_constant__ PrepArgs pa) {
  using namespace tr;
  [[maybe_unused]] const int tl = a.tl;
  TL_BEGIN(tl);
  extern __shared__ __align__(1024) unsigned char smem_raw[];
  const uint32_t sb = smem_u32(smem_raw);
  const int warp = __shfl_sync(0xffffffffu, (int)threadIdx.x >> 5, 0), lane = threadIdx.x & 31;
  unsigned char* const arena = a.arena;
  const uint32_t full = sb + OFF_BAR, empty = full + 8 * NS, barK = empty + 8 * NS, barKfree = barK + 16, staged = barKfree + 16;
  const uint32_t kvrdy = staged + 32, mfull = kvrdy + 8, mempty = mfull + 16, mbox = mempty + 16;
  if (threadIdx.x == 0) {
    for (int i = 0; i < NS; i++) { mbar_init(full + 8 * i, 1); mbar_init(empty + 8 * i, 2); }
    for (int i = 0; i < 2; i++) {
      mbar_init(barK + 8 * i, 1); mbar_init(barKfree + 8 * i, 1); mbar_init(staged + 16 * i, 4); mbar_init(staged + 16 * i + 8, 4);
      mbar_init(mfull + 8 * i, 1); mbar_init(mempty + 8 * i, 11);
    }
    mbar_init(kvrdy, 1);
    asm volatile("fence.mbarrier_init.release.cluster;" ::: "memory");
  }
  __syncthreads();
  Pipe mp{0, 0};
  auto next_item = [&]() -> uint32_t {
    uint32_t it;
    mbar_wait(mfull + 8 * mp.stage, mp.phase);
    asm volatile("ld.shared.u32 %0, [%1];" : "=r"(it) : "r"(mbox + 4 * mp.stage) : "memory");
    return it;
  };
  if (warp >= 8) {
    asm volatile("setmaxnreg.dec.sync.aligned.u32 40;");
    if (warp == 8) { if (elect_one()) {
      Pipe p{0, 1};
      mp.phase = 1;
      uint32_t kph = 1, wide = 0;
      int g = 0;
      const uint64_t ef = policy_evict_first();
      auto ld_kv = [&](uint32_t d, const void* s, uint32_t n, uint32_t mb) { if (EF_KV) bulk_g2s_hint(d, s, n, mb, ef); else bulk_g2s(d, s, n, mb); };
      auto ld_o = [&](uint32_t d, const void* s, uint32_t n, uint32_t mb) { if (EF_O) bulk_g2s_hint(d, s, n, mb, ef); else bulk_g2s(d, s, n, mb); };
      auto stage = [&](uint32_t bytes) -> uint32_t {
        mbar_wait(empty + 8 * p.stage, p.phase);
        mbar_expect_tx(full + 8 * p.stage, bytes);
        return sb + p.stage * (wide ? STO : STQ);
      };
      auto fetch = [&]() -> uint32_t { uint32_t v; asm volatile("atom.relaxed.gpu.global.add.u32 %0, [%1], 1;" : "=r"(v) : "l"(arena + AR_QUEUE) : "memory"); return v; };
      uint32_t next = fetch();
      while (true) {
        const uint32_t item = next;
        while (item >= sc.start[g + 1] && sc.type[g] != T_END) g++;
        const int type = sc.type[g], m = sc.blk[g], k = item - sc.start[g] + sc.first[g];
        if (type == T_L) { wait_ge(arena + C_O + m * 4, sc.ks[m] * (sc.wide[m] ? 4 : 10), m < 13 ? a.nap : 32); }
        if (type == T_A) wait_ge(arena + C_Q + m * 4, 64);
        if (type < T_L && wide != (type == T_OB)) {
          for (uint32_t i = 0; i < NS; i++) mbar_wait(empty + 8 * i, i >= p.stage ? p.phase : p.phase ^ 1);
          mbar_wait(barKfree, kph); mbar_wait(barKfree + 8, kph);
          wide = type == T_OB;
        }
        mbar_wait(mempty + 8 * mp.stage, mp.phase);
        asm volatile("st.shared.u32 [%0], %1;" :: "r"(mbox + 4 * mp.stage), "r"((p.stage << 24) | (type << 16) | (m << 8) | (k & 255)) : "memory");
        mbar_arrive(mfull + 8 * mp.stage);
        pipe_adv<2>(mp);
        if (type == T_END) break;
        if (type == T_L) { next = fetch(); continue; }
        if (type <= T_A) {
          if (type != T_A)
#pragma unroll 1
            for (int kb = 0; kb < 10; kb++) {
              const uint32_t st = stage(STQ), fb = full + 8 * p.stage;
              tma_load_2d(st, &tmX, kb * 64, m * 128, fb);
              tma_load_3d(st + 16384, &tmQ, 0, kb * 64, k * 3, fb);
              pipe_adv<NS>(p);
              if (type == T_Q && kb == 8) next = fetch();
            }
          if (type != T_Q) {
            const size_t blk = ((size_t)m * 4 * 96 + k * 3) * 5120;
            kph ^= 1;
            mbar_wait(kvrdy, kph);
            next = fetch();
            fence_proxy_async_global();
#pragma unroll 1
            for (int w = type == T_A ? 0 : 2; w < 4; w++) {
              const uint32_t st = stage(2 * SEGB), fb = full + 8 * p.stage;
              for (int sg = 0; sg < 2; sg++) ld_kv(st + sg * SEGB, (w < 2 ? a.kg : a.vg) + blk + (size_t)(2 * (w & 1) + sg) * (96 * 5120), SEGB, fb);
              pipe_adv<NS>(p);
            }
          }
        } else {
          const int nn = wide ? 2 : 5, nb = wide ? 5 : 2, nt = k % nn, nkb = 96 / sc.ks[m], k0 = (k / nn) * nkb;
          const Pipe p0 = p;
          for (int kb = 0; kb < nkb; kb++) {
            const uint32_t st = stage(16384 + nb * 8192), fb = full + 8 * p.stage;
            tma_load_3d(st + 16384, wide ? &tmWo5 : &tmWo2, 0, (k0 + kb) * 64, nt * nb, fb);
            if (kb >= NS) ld_o(st, a.o + ((size_t)m * 96 + k0 + kb) * 16384, 16384, fb);
            pipe_adv<NS>(p);
            if (kb == NS - 1 || (kb == nkb - 1 && nkb < NS)) {
              wait_ge(arena + C_QA + m * 4, 64, m < 14 ? a.nap : 32);
              fence_proxy_async_global();
              Pipe q = p0;
#pragma unroll 1
              for (int i = 0; i <= kb; i++) { ld_o(sb + q.stage * (wide ? STO : STQ), a.o + ((size_t)m * 96 + k0 + i) * 16384, 16384, full + 8 * q.stage); pipe_adv<NS>(q); }
            }
          }
          next = fetch();
          for (int w = 0; w < 2; w++) { mbar_wait(empty + 8 * p.stage, p.phase); mbar_arrive(full + 8 * p.stage); pipe_adv<NS>(p); }
        }
      }
    } } else if (warp < 11) { if (elect_one()) {
      const int w = warp - 9;
      uint32_t sph = 0;
      [[maybe_unused]] int nlog = 0;
#ifdef TIMELINE
      if (w == 0) { unsigned long long* lg = g_log + (((tl >= 12) * 132 + blockIdx.x) * 64 + nlog++) * 2; lg[0] = T_END << 16; lg[1] = gtime(); lg[2] = ~0ull; }
#endif
      while (true) {
        const uint32_t it = next_item();
        const int type = (it >> 16) & 255, m = (it >> 8) & 255, k = it & 255;
        const uint32_t slot = mp.stage;
        pipe_adv<2>(mp);
        if (type == T_END) break;
        mbar_wait(staged + 16 * w + 8 * slot, (sph >> slot) & 1); sph ^= 1u << slot;
        mbar_arrive(mempty + 8 * slot);
#ifdef TIMELINE
        if (w == 0 && nlog < 63) { unsigned long long* lg = g_log + (((tl >= 12) * 132 + blockIdx.x) * 64 + nlog++) * 2; lg[0] = (type << 16) | (m << 8) | k; lg[1] = gtime(); lg[2] = ~0ull; }
#endif
        if (type == T_L) continue;
        if (type == T_QA || type == T_A) {
          for (int jj = 0; jj < 3; jj++) bulk_s2g(a.o + ((size_t)m * 96 + k * 3 + jj) * 16384 + w * 8192, sb + OFF_K + w * 2 * SEGB + jj * 8192, 8192);
          bulk_commit();
          bulk_wait<0>();
          mbar_arrive(barKfree + 8 * w);
        } else if (type >= T_OB) {
          const bool wide = type == T_OB;
          const int nn = wide ? 2 : 5, nb = wide ? 5 : 2;
          const uint32_t own = ((it >> 24) + 96 / sc.ks[m] + w) % NS;
          bulk_s2g(a.part + ((size_t)((k / nn) * 32 + m * 2 + w) * 10 + (k % nn) * nb) * 8192, sb + own * (wide ? STO : STQ), nb * 8192);
          bulk_commit();
          bulk_wait<0>();
          mbar_arrive(empty + 8 * own);
        }
        if (type == T_Q) __threadfence();
        asm volatile("red.relaxed.gpu.global.add.u32 [%0], 1;" :: "l"(arena + (type == T_Q ? C_Q : (type <= T_A ? C_QA : C_O)) + m * 4) : "memory");
      }
    } } else if (elect_one()) {
      const uint64_t ef = policy_evict_first();
      uint32_t kph = 1;
      if (PF_WB && blockIdx.x >= 52) { prefetch_l2(pa.wb + (blockIdx.x - 52) * 32768, 32768); prefetch_l2(pa.wot + (blockIdx.x - 52) * 10240, 10240); }
      while (true) {
        const uint32_t it = next_item();
        const int type = (it >> 16) & 255, m = (it >> 8) & 255, k = it & 255;
        const uint32_t slot = mp.stage;
        pipe_adv<2>(mp);
        if (type == T_END) break;
        if (type == T_QA || type == T_A) {
          for (int jj = 0; jj < 3; jj++) wait_ge(arena + AR_PROG + (k * 3 + jj) * PROG_STRIDE, 4 * m + 4, m < 15 ? a.nap : a.nap2);
          mbar_arrive(kvrdy);
          fence_proxy_async_global();
          const unsigned char* src = a.kg + ((size_t)m * 4 * 96 + k * 3) * 5120;
#pragma unroll 1
          for (int w = 0; w < 2; w++) {
            mbar_wait(barKfree + 8 * w, kph);
            if (type == T_A) { mbar_arrive(barK + 8 * w); continue; }
            mbar_expect_tx(barK + 8 * w, 2 * SEGB);
            for (int sg = 2 * w; sg < 2 * w + 2; sg++) bulk_g2s_hint(sb + OFF_K + sg * SEGB, src + (size_t)sg * (96 * 5120), SEGB, barK + 8 * w, ef);
          }
          kph ^= 1;
        }
        mbar_arrive(mempty + 8 * slot);
      }
      if (blockIdx.x == gridDim.x - 1) asm volatile("griddepcontrol.wait;" ::: "memory");
    }
    return;
  }
  asm volatile("setmaxnreg.inc.sync.aligned.u32 232;");
  const int wg = warp >> 2, wi = warp & 3;
  const int g = lane >> 2, q4 = lane & 3;
  if (a.doprep && blockIdx.x < 32) { prep_body(blockIdx.x, pa); __threadfence(); }
  bar_sync(2, 256);
  asm volatile("griddepcontrol.launch_dependents;" ::: "memory");
  Pipe p{0, 0};
  uint32_t kph = 0;
  auto own_slot = [&]() -> uint32_t {
    const uint32_t sA = p.stage, phA = p.phase; pipe_adv<NS>(p);
    const uint32_t sB = p.stage, phB = p.phase; pipe_adv<NS>(p);
    mbar_wait(full + 8 * sA, phA); mbar_wait(full + 8 * sB, phB);
    mbar_arrive_if((threadIdx.x & 127) == 0, empty + 8 * (wg ? sA : sB));
    return wg ? sB : sA;
  };
  while (true) {
    const uint32_t it = __shfl_sync(0xffffffffu, next_item(), 0);
    const int type = (it >> 16) & 255, m = (it >> 8) & 255, k = it & 255;
    mbar_arrive_if(lane == 0, mempty + 8 * mp.stage);
    const uint32_t done = staged + 16 * wg + 8 * mp.stage;
    pipe_adv<2>(mp);
    if (type == T_END) break;
    if (type == T_L) {
      const int nr = sc.lrows[m], np = sc.ks[m], row0 = m * 128 + (k * 8 + warp) * nr;
#pragma unroll 1
      for (int r = 0; r < nr; r++) l_row<LNP>(a, row0 + r, np, lane);
      __syncwarp();
      mbar_arrive_if(lane == 0, done);
      continue;
    }
    if (type >= T_OB) {
      const int nkb = 96 / sc.ks[m];
      if (type == T_OB) {
        float a0[96], a1[64];
        tr_mainloop<192, 128>(a0, a1, p, sb, full, empty, nkb, wg);
        const uint32_t st = sb + own_slot() * STO;
        stage_tiles<192>(a0, st, wi, lane); stage_tiles<128>(a1, st + 24576, wi, lane);
      } else {
        float a0[64], a1[1];
        tr_mainloop<128, 0>(a0, a1, p, sb, full, empty, nkb, wg);
        stage_tiles<128>(a0, sb + own_slot() * STQ, wi, lane);
      }
      fence_proxy_async();
      __syncwarp();
      mbar_arrive_if(lane == 0, done);
      continue;
    }
    uint32_t qf[12][4];
    uint4* qp = a.qs + ((size_t)((m & 7) * 32 + k) * 12) * 256 + threadIdx.x;
    if (type != T_A) {
      float acc[96], a1[1];
      tr_mainloop<192, 0>(acc, a1, p, sb, full, empty, 10, wg);
#pragma unroll
      for (int i = 0; i < 12; i++) {
        qf[i][0] = pack_bf16(acc[8 * i], acc[8 * i + 1]); qf[i][1] = pack_bf16(acc[8 * i + 2], acc[8 * i + 3]);
        qf[i][2] = pack_bf16(acc[8 * i + 4], acc[8 * i + 5]); qf[i][3] = pack_bf16(acc[8 * i + 6], acc[8 * i + 7]);
      }
      if (type == T_Q) {
#pragma unroll
        for (int i = 0; i < 12; i++) qp[i * 256] = make_uint4(qf[i][0], qf[i][1], qf[i][2], qf[i][3]);
        __syncwarp();
        mbar_arrive_if(lane == 0, done);
        continue;
      }
    } else {
#pragma unroll
      for (int i = 0; i < 12; i++) { const uint4 v = __ldcg(qp + i * 256); qf[i][0] = v.x; qf[i][1] = v.y; qf[i][2] = v.z; qf[i][3] = v.w; }
    }
    const uint32_t ost = sb + OFF_K + wg * 2 * SEGB;
    const bool second = wi >= 2;
    uint32_t pf[5][4];
    {
      float sa[20], sb2[20];
      uint32_t kbase = ost, kslot = 0;
      if (type == T_A) { kslot = own_slot(); kbase = sb + kslot * STQ; } else mbar_wait(barK + 8 * wg, kph);
      if (STAG && wg) bar_sync(1, 256);
      wgmma_fence();
#pragma unroll
      for (int i = 0; i < 12; i++) {
        wgmma_rs_n40<0>(sa, qf[i][0], qf[i][1], qf[i][2], qf[i][3], make_desc(kbase + i * 1280, 640, 128, 0), i != 0);
        wgmma_rs_n40<0>(sb2, qf[i][0], qf[i][1], qf[i][2], qf[i][3], make_desc(kbase + SEGB + i * 1280, 640, 128, 0), i != 0);
      }
      wgmma_commit();
      wgmma_wait<0>();
      if (STAG && !wg) bar_arrive(1, 256);
      mbar_arrive_if(type == T_A && (threadIdx.x & 127) == 0, empty + 8 * kslot);
      const float cs = 0.07216878364870322f * 1.4426950408889634f;
      const int r0 = 16 * (wi & 1) + g, r1 = r0 + 8;
      float m0 = -INFINITY, m1 = -INFINITY;
#pragma unroll
      for (int n = 0; n < 5; n++) {
#pragma unroll
        for (int e = 0; e < 2; e++) {
          const int key = 8 * n + 2 * q4 + e;
          float x = second ? sb2[4 * n + e] : sa[4 * n + e], y = second ? sb2[4 * n + 2 + e] : sa[4 * n + 2 + e];
          if (n < 4) { if (key > r0) x = -INFINITY; if (key > r1) y = -INFINITY; }
          sa[4 * n + e] = x; sa[4 * n + 2 + e] = y;
          m0 = fmaxf(m0, x); m1 = fmaxf(m1, y);
        }
      }
      m0 = fmaxf(m0, __shfl_xor_sync(0xffffffffu, m0, 1)); m1 = fmaxf(m1, __shfl_xor_sync(0xffffffffu, m1, 1));
      m0 = fmaxf(m0, __shfl_xor_sync(0xffffffffu, m0, 2)); m1 = fmaxf(m1, __shfl_xor_sync(0xffffffffu, m1, 2));
      float s0 = 0.f, s1 = 0.f;
#pragma unroll
      for (int n = 0; n < 5; n++) {
#pragma unroll
        for (int e = 0; e < 2; e++) {
          sa[4 * n + e] = ex2f((sa[4 * n + e] - m0) * cs); sa[4 * n + 2 + e] = ex2f((sa[4 * n + 2 + e] - m1) * cs);
          s0 += sa[4 * n + e]; s1 += sa[4 * n + 2 + e];
        }
      }
      s0 += __shfl_xor_sync(0xffffffffu, s0, 1); s1 += __shfl_xor_sync(0xffffffffu, s1, 1);
      s0 += __shfl_xor_sync(0xffffffffu, s0, 2); s1 += __shfl_xor_sync(0xffffffffu, s1, 2);
      const float i0 = rcpf(s0), i1 = rcpf(s1);
#pragma unroll
      for (int n = 0; n < 5; n++) {
        const uint32_t x = pack_bf16(sa[4 * n] * i0, sa[4 * n + 1] * i0), y = pack_bf16(sa[4 * n + 2] * i1, sa[4 * n + 3] * i1);
        if (n < 4) {
          pf[n >> 1][2 * (n & 1)] = second ? 0u : x; pf[n >> 1][2 * (n & 1) + 1] = second ? 0u : y;
          pf[2 + (n >> 1)][2 * (n & 1)] = second ? x : 0u; pf[2 + (n >> 1)][2 * (n & 1) + 1] = second ? y : 0u;
        } else {
          pf[4][0] = second ? 0u : x; pf[4][1] = second ? 0u : y; pf[4][2] = second ? x : 0u; pf[4][3] = second ? y : 0u;
        }
      }
    }
    {
      float o[96];
#pragma unroll
      for (int i = 0; i < 5; i++) { PIN(pf[i][0]); PIN(pf[i][1]); PIN(pf[i][2]); PIN(pf[i][3]); }
      const uint32_t own = own_slot(), vbase = sb + own * STQ;
      wgmma_fence();
#pragma unroll
      for (int i = 0; i < 5; i++)
        wgmma_rs_n192<1>(o, pf[i][0], pf[i][1], pf[i][2], pf[i][3], i < 4 ? make_desc(vbase + (i >> 1) * SEGB + (i & 1) * 256, 128, 640, 0) : make_desc(vbase + 512, SEGB, 640, 0), i != 0);
      wgmma_commit();
      if (type == T_A) mbar_wait(barK + 8 * wg, kph);
      kph ^= 1;
      wgmma_wait<0>();
      mbar_arrive_if((threadIdx.x & 127) == 0, empty + 8 * own);
      stage_tiles<192>(o, ost, wi, lane);
      fence_proxy_async();
      __syncwarp();
      mbar_arrive_if(lane == 0, done);
    }
  }
}
namespace bf {
constexpr int NS = 4, STAGE = 16384 + 32768;
constexpr int PIECE = 20480;
constexpr int OFF_PHI = 0, OFF_V = 40960, OFF_KV = 65536;
constexpr int OFF_OST = 5 * PIECE;
constexpr int OFF_WOT = 6 * PIECE;
constexpr int OFF_BAR = OFF_WOT + 102400;
constexpr int SMEM = OFF_BAR + 256;
static_assert(NS * STAGE <= OFF_BAR && SMEM <= 232448, "smem");
constexpr int KVACC = 32 * 5 * 1024;
struct Args {
  const unsigned char *wb, *wot;
  unsigned char *kvacc, *o2;
  const bf16* xin;
  bf16* xout;
  const bf16 *pf0, *pf1;
  int tl;
};
}
__device__ __forceinline__ void hedgehog_features(float (&x)[2][5], uint32_t (&w)[2][5]) {
  const float L = 1.4426950408889634f;
  float mx[2], mn[2], sp[2], sn[2], pos[2][5], neg[2][5];
#pragma unroll
  for (int r = 0; r < 2; r++) {
    mx[r] = fmaxf(fmaxf(fmaxf(x[r][0], x[r][1]), fmaxf(x[r][2], x[r][3])), x[r][4]);
    mn[r] = fminf(fminf(fminf(x[r][0], x[r][1]), fminf(x[r][2], x[r][3])), x[r][4]);
  }
#pragma unroll
  for (int o = 1; o < 4; o <<= 1)
#pragma unroll
    for (int r = 0; r < 2; r++) {
      const uint32_t t = __shfl_xor_sync(0xffffffffu, __byte_perm(__float_as_uint(mn[r]), __float_as_uint(mx[r]), 0x7632), o);
      mx[r] = fmaxf(mx[r], bf_hi(t)); mn[r] = fminf(mn[r], bf_lo(t));
    }
#pragma unroll
  for (int r = 0; r < 2; r++) {
#pragma unroll
    for (int i = 0; i < 5; i++) { pos[r][i] = ex2f((x[r][i] - mx[r]) * L); neg[r][i] = ex2f((mn[r] - x[r][i]) * L); }
    sp[r] = ((pos[r][0] + pos[r][1]) + (pos[r][2] + pos[r][3])) + pos[r][4];
    sn[r] = ((neg[r][0] + neg[r][1]) + (neg[r][2] + neg[r][3])) + neg[r][4];
  }
#pragma unroll
  for (int o = 1; o < 4; o <<= 1)
#pragma unroll
    for (int r = 0; r < 2; r++) { sp[r] += __shfl_xor_sync(0xffffffffu, sp[r], o); sn[r] += __shfl_xor_sync(0xffffffffu, sn[r], o); }
#pragma unroll
  for (int r = 0; r < 2; r++) {
    const float ip = rcpf(sp[r]), in_ = rcpf(sn[r]);
    w[r][0] = pack_bf16(pos[r][0] * ip, pos[r][1] * ip); w[r][1] = pack_bf16(pos[r][2] * ip, pos[r][3] * ip);
    w[r][2] = pack_bf16(neg[r][0] * in_, neg[r][1] * in_); w[r][3] = pack_bf16(neg[r][2] * in_, neg[r][3] * in_);
    w[r][4] = pack_bf16(pos[r][4] * ip, neg[r][4] * in_);
  }
}
__device__ __forceinline__ void bulk_g2s_mc(uint32_t dst, const void* src, uint32_t bytes, uint32_t mb) {
  asm volatile("cp.async.bulk.shared::cluster.global.mbarrier::complete_tx::bytes.multicast::cluster [%0], [%1], %2, [%3], %4;"
               :: "r"(dst), "l"(src), "r"(bytes), "r"(mb), "h"((unsigned short)3) : "memory");
}
__device__ __forceinline__ void mbar_arrive_remote_if(bool c, uint32_t b) {
  asm volatile("{\n.reg .pred p;\nsetp.ne.u32 p, %1, 0;\n@p mbarrier.arrive.release.cluster.shared::cluster.b64 _, [%0];\n}" :: "r"(b), "r"((uint32_t)c) : "memory");
}

__global__ void __cluster_dims__(2, 1, 1) __launch_bounds__(384, 1) blayer_kernel(const __grid_constant__ CUtensorMap tmA, const __grid_constant__ bf::Args a) {
  using namespace bf;
  [[maybe_unused]] const int tl = a.tl;
  extern __shared__ __align__(1024) unsigned char smem_raw[];
  const uint32_t sb = smem_u32(smem_raw);
  const int warp = __shfl_sync(0xffffffffu, (int)threadIdx.x >> 5, 0), lane = threadIdx.x & 31;
  const uint32_t full = sb + OFF_BAR, empty = full + 8 * NS, full2 = empty + 8 * NS, empty2 = full2 + 64, barW = empty2 + 16, drained = barW + 8, staged = drained + 8, freeb = staged + 8;
  const int rank = blockIdx.x & 1, u = (blockIdx.x >> 1) & 7, mp = blockIdx.x >> 4;
  const int m = 2 * mp + rank;
  const int m2 = 2 * mp + (u & 1), ns = (u & ~1) + rank;
  const uint32_t dpeer = mapa_u32(sb, rank ^ 1) - sb;
  unsigned* cntO = (unsigned*)(a.kvacc + KVACC);
  if (threadIdx.x == 0) {
    for (int i = 0; i < NS; i++) { mbar_init(full + 8 * i, 1); mbar_init(empty + 8 * i, 4); }
    for (int i = 0; i < 8; i++) mbar_init(full2 + 8 * i, 1);
    mbar_init(empty2, 2); mbar_init(empty2 + 8, 2);
    mbar_init(barW, 1); mbar_init(drained, 1); mbar_init(staged, 8); mbar_init(freeb, 2);
    asm volatile("fence.mbarrier_init.release.cluster;" ::: "memory");
  }
  __syncthreads();
  asm volatile("barrier.cluster.arrive.relaxed.aligned; barrier.cluster.wait.aligned;" ::: "memory");
  if (warp >= 8) {
    asm volatile("setmaxnreg.dec.sync.aligned.u32 40;");
    if (warp == 8) { if (elect_one()) {
      const unsigned char* wsrc = a.wb + (size_t)u * 327680 + rank * 16384;
      asm volatile("fence.proxy.async.global;" ::: "memory");
      for (int kb = 0; kb < NS; kb++) {
        mbar_expect_tx(full + 8 * kb, STAGE);
        bulk_g2s_mc(sb + kb * STAGE + 16384 + rank * 16384, wsrc + kb * 32768, 16384, full + 8 * kb);
      }
      asm volatile("griddepcontrol.wait;" ::: "memory");
      TL_BEGIN0(tl);
      for (int kb = 0; kb < NS; kb++) tma_load_2d(sb + kb * STAGE, &tmA, kb * 64, m * 128, full + 8 * kb);
      if (m == 0) prefetch_l2(a.kvacc + u * (KVACC / 8), KVACC / 8);
#pragma unroll 1
      for (int kb = NS; kb < 10; kb++) {
        const uint32_t s = kb & 3, st = sb + s * STAGE, fb = full + 8 * s;
        mbar_wait_cluster(empty + 8 * s, ((kb >> 2) - 1) & 1);
        mbar_expect_tx(fb, STAGE);
        tma_load_2d(st, &tmA, kb * 64, m * 128, fb);
        bulk_g2s_mc(st + 16384 + rank * 16384, wsrc + kb * 32768, 16384, fb);
      }
      for (int i = 0; i < 6; i++) mbar_expect_tx(full2 + 8 * i, PIECE);
      mbar_wait(drained, 0);
      mbar_expect_tx(barW, 102400);
      bulk_g2s(sb + OFF_WOT, a.wot + (size_t)ns * 102400, 102400, barW);
      if (a.pf0) {
        constexpr uint32_t PER = cfg::DM * cfg::HD * 2 / 128;
        prefetch_l2((const unsigned char*)a.pf0 + blockIdx.x * PER, PER); prefetch_l2((const unsigned char*)a.pf1 + blockIdx.x * PER, PER);
      }
      mbar_wait(staged, 0);
      bulk_s2g(a.o2 + (size_t)(m * 8 + u) * PIECE, sb + OFF_OST, PIECE);
      bulk_commit();
      bulk_wait<0>();
      asm volatile("red.relaxed.gpu.global.add.u32 [%0], 1;" :: "l"(cntO + m) : "memory");
      mbar_arrive(freeb); mbar_arrive_remote_if(true, freeb + dpeer);
      wait_ge(cntO + m2, 8, 20);
      mbar_wait_cluster(freeb, 0);
      fence_proxy_async_global();
      const unsigned char* osrc = a.o2 + (size_t)m2 * 8 * PIECE;
      for (int i = 0; i < 6; i++) bulk_g2s_mc(sb + i * PIECE + rank * (PIECE / 2), osrc + i * PIECE + rank * (PIECE / 2), PIECE / 2, full2 + 8 * i);
      for (int i = 0; i < 2; i++) {
        mbar_wait(empty2 + 8 * i, 0);
        mbar_expect_tx(full2 + 8 * (6 + i), PIECE);
        bulk_g2s(sb + i * PIECE, osrc + (6 + i) * PIECE, PIECE, full2 + 8 * (6 + i));
      }
    } }
    return;
  }
  asm volatile("setmaxnreg.inc.sync.aligned.u32 232;");
  const int wg = warp >> 2, wi = warp & 3;
  const int q4 = lane & 3;
  const bool lead = (threadIdx.x & 127) == 0;
  float acc[128];
  {
#pragma unroll 1
    for (int kb = 0; kb < 10; kb++) {
      const uint32_t s = kb & 3, st = sb + s * STAGE;
      mbar_wait(full + 8 * s, (kb >> 2) & 1);
      wgmma_fence();
#pragma unroll
      for (int kk = 0; kk < 4; kk++) wgmma_n256<0, 1>(acc, desc_kmajor(st + wg * 8192 + kk * 32), make_desc(st + 16384 + kk * 8192, 4096, 128, 0), (kb | kk) != 0);
      wgmma_commit();
      if (kb > 0 && kb < 7) { wgmma_wait<1>(); const uint32_t e = empty + 8 * ((kb - 1) & 3); mbar_arrive_if(lead, e); mbar_arrive_remote_if(lead, e + dpeer); }
    }
    wgmma_wait<0>();
    bar_sync(1, 256);
    mbar_arrive_if(threadIdx.x == 0, drained);
  }
  TL2((tl >= 12 ? 128 : 0) + 32 + 0);
  const uint32_t srow = (wg * 64 + wi * 16 + (lane & 15)) * 16 + (lane >> 4) * 2048;
  auto features = [&](auto T0, auto HH, uint32_t (&w)[2][5]) {
    constexpr int t = T0.value + 5 * (HH.value >> 1), o = (HH.value & 1) ? 3 : 0, e = HH.value & 1;
    float x[2][5];
#pragma unroll
    for (int r = 0; r < 2; r++) {
      x[r][0] = acc[4 * (t + o) + 2 * r]; x[r][1] = acc[4 * (t + o) + 2 * r + 1]; x[r][2] = acc[4 * (t + o + 1) + 2 * r]; x[r][3] = acc[4 * (t + o + 1) + 2 * r + 1];
      bf16r2(x[r][0], x[r][1]); bf16r2(x[r][2], x[r][3]);
    }
    x[0][4] = acc[4 * (t + 2) + e]; x[1][4] = acc[4 * (t + 2) + 2 + e];
    bf16r2(x[0][4], x[1][4]);
    hedgehog_features(x, w);
  };
  static_for<0, 4>([&](auto HH) {
    constexpr int hh = HH.value, t = 20 + 3 * hh;
    const uint32_t one = q4 == ((hh & 1) ? 0 : 2) ? 0x3f80u : 0u;
    const uint32_t va = sb + OFF_V + hh * 6144 + srow;
    stsm_x4(va, pack_bf16(acc[4 * t], acc[4 * t + 1]), pack_bf16(acc[4 * t + 2], acc[4 * t + 3]), pack_bf16(acc[4 * t + 4], acc[4 * t + 5]), pack_bf16(acc[4 * t + 6], acc[4 * t + 7]));
    const bool pad = (q4 >= 2) != (hh & 1);
    stsm_x2(va + 4096, pad ? one : pack_bf16(acc[4 * t + 8], acc[4 * t + 9]), pad ? one : pack_bf16(acc[4 * t + 10], acc[4 * t + 11]));
    uint32_t w[2][5];
    features(IC<10>{}, HH, w);
    const uint32_t pa = sb + OFF_PHI + hh * 10240 + srow;
    stsm_x4(pa, w[0][0], w[1][0], w[0][1], w[1][1]);
    stsm_x4(pa + 4096, w[0][2], w[1][2], w[0][3], w[1][3]);
    stsm_x2(pa + 8192, w[0][4], w[1][4]);
  });
  fence_proxy_async();
  bar_sync(1, 256);
  TL2((tl >= 12 ? 128 : 0) + 32 + 1);
  {
    float d0[12], d1[12];
    const uint32_t pa = sb + OFF_PHI + wg * 20480, pv = sb + OFF_V + wg * 12288;
    wgmma_fence();
#pragma unroll
    for (int k = 0; k < 8; k++) {
      wgmma_n24<1, 1>(d0, make_desc(pa + k * 256, 128, 2048, 0), make_desc(pv + k * 256, 128, 2048, 0), k != 0);
      wgmma_n24<1, 1>(d1, make_desc(pa + 10240 + k * 256, 128, 2048, 0), make_desc(pv + 6144 + k * 256, 128, 2048, 0), k != 0);
    }
    wgmma_commit();
    wgmma_wait<0>();
    unsigned char* dst = a.kvacc + ((u * 4 + wg * 2) * 5 + 2 * wi) * 1024 + lane * 16;
    auto red4 = [&](bool on, unsigned char* p, float x, float y, float z) {
      asm volatile("{\n.reg .pred p;\nsetp.ne.u32 p, %4, 0;\n@p red.relaxed.gpu.global.add.v4.f32 [%0], {%1,%2,%3,%5};\n}" :: "l"(p), "f"(x), "f"(y), "f"(z), "r"((uint32_t)on), "f"(1.f) : "memory");
    };
    red4(wi < 3, dst, d0[0], d0[1], d0[4]); red4(wi < 3, dst + 512, d0[5], d0[8], d0[9]);
    red4(wi < 3, dst + 5120, d1[0], d1[1], d1[4]); red4(wi < 3, dst + 5632, d1[5], d1[8], d1[9]);
    red4(wi < 2, dst + 1024, d0[2], d0[3], d0[6]); red4(wi < 2, dst + 1536, d0[7], d0[10], d0[11]);
    red4(wi < 2, dst + 6144, d1[2], d1[3], d1[6]); red4(wi < 2, dst + 6656, d1[7], d1[10], d1[11]);
  }
  TL2((tl >= 12 ? 128 : 0) + 32 + 2);
  uint32_t qf[4][2][5];
  static_for<0, 4>([&](auto HH) { features(IC<0>{}, HH, qf[HH.value]); });
  uint4 xr[5];
#pragma unroll
  for (int i = 0; i < 5; i++) {
    const int c = lane + 32 * i;
    xr[i] = __ldcg((const uint4*)(a.xin + (size_t)(m2 * 128 + wg * 64 + wi * 16 + c / 10) * cfg::DM + ns * 80 + (c % 10) * 8));
  }
  {
    const unsigned char* src = a.kvacc + (u * 20 + warp) * 1024 + lane * 16;
    uint4 v[6];
    int spin = 0;
    while (true) {
      v[0] = ld_relaxed_v4_i<0>(src); v[1] = ld_relaxed_v4_i<512>(src); v[2] = ld_relaxed_v4_i<8192>(src); v[3] = ld_relaxed_v4_i<8704>(src);
      v[4] = ld_relaxed_v4_i<0>(src + (wg ? 0 : 16384)); v[5] = ld_relaxed_v4_i<512>(src + (wg ? 0 : 16384));
      const uint32_t c = (v[0].w & v[1].w & v[2].w) & (v[3].w & v[4].w & v[5].w);
      if (!__any_sync(0xffffffffu, (c & 0x41800000u) != 0x41800000u) || ++spin >= SPIN_LIMIT) break;
      __nanosleep(100);
    }
    const uint32_t kd = sb + OFF_KV + warp * 384 + lane * 4;
#pragma unroll
    for (int i = 0; i < 3; i++)
      if (i < 2 || wg == 0) {
        sts32(kd + i * 3072, pack_bf16(__uint_as_float(v[2 * i].x), __uint_as_float(v[2 * i].y)));
        sts32(kd + i * 3072 + 128, pack_bf16(__uint_as_float(v[2 * i].z), __uint_as_float(v[2 * i + 1].x)));
        sts32(kd + i * 3072 + 256, pack_bf16(__uint_as_float(v[2 * i + 1].y), __uint_as_float(v[2 * i + 1].z)));
      }
  }
  fence_proxy_async();
  bar_sync(1, 256);
  TL2((tl >= 12 ? 128 : 0) + 32 + 3);
  {
    float d[4][12];
    uint32_t zero = 0; PIN(zero);
#pragma unroll
    for (int hh = 0; hh < 4; hh++)
#pragma unroll
      for (int i = 0; i < 5; i++) { PIN(qf[hh][0][i]); PIN(qf[hh][1][i]); }
    wgmma_fence();
#pragma unroll
    for (int hh = 0; hh < 4; hh++) {
      const uint32_t kb = sb + OFF_KV + hh * 1920;
      wgmma_rs_n24<1>(d[hh], qf[hh][0][0], qf[hh][1][0], qf[hh][0][1], qf[hh][1][1], make_desc(kb, 384, 128, 0), 0);
      wgmma_rs_n24<1>(d[hh], qf[hh][0][2], qf[hh][1][2], qf[hh][0][3], qf[hh][1][3], make_desc(kb + 768, 384, 128, 0), 1);
      wgmma_rs_n24<1>(d[hh], qf[hh][0][4], qf[hh][1][4], zero, zero, make_desc(kb + 1536, 0, 128, 0), 1);
    }
    wgmma_commit();
    wgmma_wait<0>();
    uint32_t ow[4][6];
#pragma unroll
    for (int hh = 0; hh < 4; hh++) {
      const int zl = (lane & ~3) | ((hh & 1) ? 0 : 2);
      const float da = bf16r(bf16r(__shfl_sync(0xffffffffu, d[hh][8], zl)) + 1e-6f), db = bf16r(bf16r(__shfl_sync(0xffffffffu, d[hh][10], zl)) + 1e-6f);
#pragma unroll
      for (int n = 0; n < 3; n++) {
        bf16r2(d[hh][4 * n], d[hh][4 * n + 1]); bf16r2(d[hh][4 * n + 2], d[hh][4 * n + 3]);
        ow[hh][2 * n] = pack_bf16(__fdividef(d[hh][4 * n], da), __fdividef(d[hh][4 * n + 1], da));
        ow[hh][2 * n + 1] = pack_bf16(__fdividef(d[hh][4 * n + 2], db), __fdividef(d[hh][4 * n + 3], db));
      }
    }
#pragma unroll
    for (int p = 0; p < 2; p++) {
      const uint32_t oa = sb + OFF_OST + p * 10240 + srow;
      stsm_x4(oa, ow[2 * p][0], ow[2 * p][1], ow[2 * p][2], ow[2 * p][3]);
      stsm_x2(oa + 4096, q4 < 2 ? ow[2 * p][4] : ow[2 * p + 1][4], q4 < 2 ? ow[2 * p][5] : ow[2 * p + 1][5]);
      stsm_x4(oa + 6144, ow[2 * p + 1][0], ow[2 * p + 1][1], ow[2 * p + 1][2], ow[2 * p + 1][3]);
    }
    fence_proxy_async();
    __syncwarp();
    mbar_arrive_if(lane == 0, staged);
  }
  TL2((tl >= 12 ? 128 : 0) + 32 + 4);
  float c2[40];
  mbar_wait(barW, 0);
#pragma unroll 1
  for (int i = 0; i < 8; i++) {
    mbar_wait(full2 + 8 * i, 0);
    const uint32_t st = sb + (i < 6 ? i : i - 6) * PIECE + wg * 1024, wo = sb + OFF_WOT + i * 12800;
    wgmma_fence();
#pragma unroll
    for (int kk = 0; kk < 5; kk++) wgmma_n80<0, 1>(c2, make_desc(st + kk * 4096, 2048, 128, 0), make_desc(wo + kk * 2560, 1280, 128, 0), (i | kk) != 0);
    wgmma_commit();
    if (i == 1 || i == 2) { wgmma_wait<1>(); mbar_arrive_if(lead, empty2 + 8 * (i - 1)); }
  }
  wgmma_wait<0>();
  TL2((tl >= 12 ? 128 : 0) + 32 + 5);
  {
    bar_sync(1, 256);
    const uint32_t ost = sb + 2 * PIECE + warp * 3072;
#pragma unroll
    for (int v = 0; v < 10; v += 2)
      stsm_x4(ost + (lane & 15) * 176 + (v + (lane >> 4)) * 16, pack_bf16(c2[4 * v], c2[4 * v + 1]), pack_bf16(c2[4 * v + 2], c2[4 * v + 3]),
              pack_bf16(c2[4 * v + 4], c2[4 * v + 5]), pack_bf16(c2[4 * v + 6], c2[4 * v + 7]));
    __syncwarp();
#pragma unroll
    for (int i = 0; i < 5; i++) {
      const int c = lane + 32 * i, row = c / 10, chunk = c % 10;
      const uint4 y = lds128(ost + row * 176 + chunk * 16);
      const size_t off = (size_t)(m2 * 128 + wg * 64 + wi * 16 + row) * cfg::DM + ns * 80 + chunk * 8;
      const uint4 x = xr[i];
      *(uint4*)(a.xout + off) = make_uint4(pack_bf16(bf_lo(x.x) + bf_lo(y.x), bf_hi(x.x) + bf_hi(y.x)), pack_bf16(bf_lo(x.y) + bf_lo(y.y), bf_hi(x.y) + bf_hi(y.y)),
                                           pack_bf16(bf_lo(x.z) + bf_lo(y.z), bf_hi(x.z) + bf_hi(y.z)), pack_bf16(bf_lo(x.w) + bf_lo(y.w), bf_hi(x.w) + bf_hi(y.w)));
    }
  }
  TL_END(tl);
}
__device__ __align__(32768) unsigned char g_arena[AR_SIZE];
__device__ __align__(1024) uint2 g_xh[2048 * 160];
__device__ __align__(1024) unsigned char g_k[64 * 96 * 5120], g_v[64 * 96 * 5120];
__device__ __align__(1024) bf16 g_o[2048 * 6144];
__device__ __align__(1024) uint4 g_qs[8 * 32 * 12 * 256];
__device__ __align__(1024) bf16 g_xn[2048 * 640], g_xn2[2048 * 640], g_xa[2048 * 640], g_xb[2048 * 640];
__device__ __align__(1024) bf16 g_part[24 * 2048 * 640];
__device__ __align__(1024) bf16 g_wb[2048 * 640], g_wot[640 * 640], g_pq[2048 * 640];
__device__ __align__(1024) float g_kvacc[bf::KVACC / 4 + 64];

typedef CUresult (*EncodeFn)(CUtensorMap*, CUtensorMapDataType, cuuint32_t, void*, const cuuint64_t*, const cuuint64_t*, const cuuint32_t*,
                             const cuuint32_t*, CUtensorMapInterleave, CUtensorMapSwizzle, CUtensorMapL2promotion, CUtensorMapFloatOOBfill);
static EncodeFn g_encode = nullptr;
static CUtensorMap make_map(const void* p, uint64_t cols, uint64_t rows, uint32_t bc, uint32_t br, bool swz = true) {
  CUtensorMap m;
  cuuint64_t dims[2] = {cols, rows}, strides[1] = {cols * 2};
  cuuint32_t box[2] = {bc, br}, es[2] = {1, 1};
  g_encode(&m, CU_TENSOR_MAP_DATA_TYPE_BFLOAT16, 2, const_cast<void*>(p), dims, strides, box, es, CU_TENSOR_MAP_INTERLEAVE_NONE,
           swz ? CU_TENSOR_MAP_SWIZZLE_128B : CU_TENSOR_MAP_SWIZZLE_NONE, CU_TENSOR_MAP_L2_PROMOTION_L2_256B, CU_TENSOR_MAP_FLOAT_OOB_FILL_NONE);
  return m;
}
static CUtensorMap make_map3(const void* p, uint64_t cols, uint64_t rows, uint32_t nb) {
  CUtensorMap m;
  cuuint64_t dims[3] = {64, rows, cols / 64}, strides[2] = {cols * 2, 128};
  cuuint32_t box[3] = {64, 64, nb}, es[3] = {1, 1, 1};
  g_encode(&m, CU_TENSOR_MAP_DATA_TYPE_BFLOAT16, 3, const_cast<void*>(p), dims, strides, box, es, CU_TENSOR_MAP_INTERLEAVE_NONE,
           CU_TENSOR_MAP_SWIZZLE_128B, CU_TENSOR_MAP_L2_PROMOTION_L2_256B, CU_TENSOR_MAP_FLOAT_OOB_FILL_NONE);
  return m;
}
template <class T> static T* sym(const T& s) { void* p = nullptr; cudaGetSymbolAddress(&p, s); return (T*)p; }

struct Ptrs {
  unsigned char *arena, *k, *v; bf16 *o, *xn, *xa, *xb, *wb, *wot, *pq; float *part, *kvacc; uint2* xh; uint4* qs; bf16* xn2;
};

static tr::Sched make_sched(const char* str, const int* ks, const int* lr) {
  using namespace tr;
  Sched s = {};
  int g = 0, n = 0;
  for (int b = 0; b < 16; b++) { s.ks[b] = (uint8_t)abs(ks[b]); s.wide[b] = ks[b] > 0; s.lrows[b] = (uint8_t)lr[b]; }
  for (const char* p = str; *p;) {
    if (*p == ' ') { p++; continue; }
    const char c = *p++;
    char* e;
    const int b = (int)strtol(p, &e, 10); p = e;
    int first = 0, cnt = c == 'o' ? s.ks[b] * (s.wide[b] ? 2 : 5) : (c == 'l' ? 16 / lr[b] : 32);
    if (*p == '.') { first = (int)strtol(p + 1, &e, 10); cnt = (int)strtol(e + 1, &e, 10); p = e; }
    s.start[g] = (uint16_t)n; s.first[g] = (uint8_t)first; s.blk[g] = (uint8_t)b;
    s.type[g] = c == 'a' ? T_QA : (c == 'q' ? T_Q : (c == 't' ? T_A : (c == 'l' ? T_L : (s.wide[b] ? T_OB : T_OS))));
    g++; n += cnt;
  }
  s.start[g] = (uint16_t)n; s.type[g] = T_END; s.start[g + 1] = 0xffff;
  return s;
}
static tr::Sched sched_of(int layer) {
  const char* str = "q13 q14 a0 q15 a1 o0 a2 o1 a3 o2 a4 o3 a5 o4 l0 a6 o5 l1 a7 o6 l2 a8 o7 l3 a9 o8 l4 a10 o9 l5 a11 o10 l6 a12 o11 l7 t13 o12 l8 o13 l9 t14 t15 o14 l10 l11 o15 l12 l13 l14 l15";
  int ks[16] = {2, 2, 2, 2, 2, 2, 2, 2, 2, 2, 2, 3, 4, 6, -12, -12}, lr[16] = {4, 4, 4, 4, 4, 4, 4, 4, 4, 4, 4, 1, 1, 1, 1, 1};
#ifdef TUNE
  if (getenv("SCHED")) str = getenv("SCHED");
  if (layer == 0 && getenv("SCHED0")) str = getenv("SCHED0");
  if (const char* p = getenv("KS")) for (int b = 0; b < 16; b++) { char* e; ks[b] = (int)strtol(p, &e, 10); p = e; }
  if (const char* p = getenv("LR")) for (int b = 0; b < 16; b++) { char* e; lr[b] = (int)strtol(p, &e, 10); p = e; }
#endif
  return make_sched(str, ks, lr);
}
#ifndef TRAIL_GRID
#define TRAIL_GRID 132
#endif
#ifndef PDL_LN
#define PDL_LN 0
#endif
#ifndef PDL_CH
#define PDL_CH 1
#endif
#ifndef PDL_B
#define PDL_B 1
#endif
#ifndef PF_A
#define PF_A 1
#endif
#ifndef PF_B
#define PF_B 0
#endif
extern "C" void kernel_launch(void* const* d_in, const int* in_sizes, int n_in, void* d_out, int out_size) {
  const bf16* x = (const bf16*)d_in[0];
  const bf16* mem0 = (const bf16*)d_in[1];
  const bf16 *Wq = (const bf16*)d_in[2], *Wk = (const bf16*)d_in[3], *Wv = (const bf16*)d_in[4], *Wo = (const bf16*)d_in[5];
  const bf16 *wqkv = (const bf16*)d_in[8], *wphi = (const bf16*)d_in[9], *wo = (const bf16*)d_in[10];
  bf16* out = (bf16*)d_out;
  static Ptrs P; static bool init = false;
  if (!init) {
    void* fn = nullptr; cudaDriverEntryPointQueryResult qr;
    cudaGetDriverEntryPoint("cuTensorMapEncodeTiled", &fn, cudaEnableDefault, &qr);
    g_encode = (EncodeFn)fn;
    void* p;
    cudaGetSymbolAddress(&p, g_arena); P.arena = (unsigned char*)p;
    cudaGetSymbolAddress(&p, g_k); P.k = (unsigned char*)p;   cudaGetSymbolAddress(&p, g_v); P.v = (unsigned char*)p;
    cudaGetSymbolAddress(&p, g_o); P.o = (bf16*)p;
    cudaGetSymbolAddress(&p, g_xn); P.xn = (bf16*)p;
    cudaGetSymbolAddress(&p, g_xa); P.xa = (bf16*)p;   cudaGetSymbolAddress(&p, g_xb); P.xb = (bf16*)p;
    cudaGetSymbolAddress(&p, g_wb); P.wb = (bf16*)p;   cudaGetSymbolAddress(&p, g_wot); P.wot = (bf16*)p;
    cudaGetSymbolAddress(&p, g_pq); P.pq = (bf16*)p;   cudaGetSymbolAddress(&p, g_part); P.part = (float*)p;
    cudaGetSymbolAddress(&p, g_kvacc); P.kvacc = (float*)p;
    cudaGetSymbolAddress(&p, g_xh); P.xh = (uint2*)p;
    cudaGetSymbolAddress(&p, g_qs); P.qs = (uint4*)p;
    cudaGetSymbolAddress(&p, g_xn2); P.xn2 = (bf16*)p;
    cudaFuncSetAttribute(chain_kernel, cudaFuncAttributeMaxDynamicSharedMemorySize, ch::SMEM);
    cudaFuncSetAttribute(trail_kernel, cudaFuncAttributeMaxDynamicSharedMemorySize, tr::SMEM);
    cudaFuncSetAttribute(blayer_kernel, cudaFuncAttributeMaxDynamicSharedMemorySize, bf::SMEM);
    init = true;
  }
  const CUtensorMap tmXn = make_map(P.xn, 640, 2048, 64, 128), tmXn2 = make_map(P.xn2, 640, 2048, 64, 128);
  const CUtensorMap tmWq = make_map3(Wq, 6144, 640, 3);
  const CUtensorMap tmCq = make_map(Wq, 6144, 640, 64, 160), tmCk = make_map(Wk, 6144, 640, 64, 160), tmCv = make_map(Wv, 6144, 640, 64, 160), tmCo = make_map(Wo, 640, 6144, 224, 64, false);
  const CUtensorMap tmWo5 = make_map3(Wo, 640, 6144, 5), tmWo2 = make_map3(Wo, 640, 6144, 2);

  ChainArgs ca;
  ca.xh = P.xh; ca.mem0 = mem0; ca.kg = P.k; ca.vg = P.v;
  ca.arena = P.arena; ca.dbg = nullptr; ca.delay = POLL_DELAY;
#ifdef TUNE
  if (getenv("PD")) ca.delay = atoi(getenv("PD"));
#endif
  ca.tl = 0;
  uint4* zar = (uint4*)P.arena; const int nzar = AR_SIZE / 16;
  uint4* zkv = (uint4*)P.kvacc; const int nzkv = (bf::KVACC / 4 + 64) / 4;

  const PrepArgs pa{wqkv, wphi, wo, (unsigned char*)P.wb, (unsigned char*)P.wot};
  const bf16* xcur = x;
  cudaLaunchAttribute at[1];
  at[0].id = cudaLaunchAttributeProgrammaticStreamSerialization; at[0].val.programmaticStreamSerializationAllowed = 1;
  auto cfgof = [&](int grid, int block, int smem, bool pdl) {
    cudaLaunchConfig_t lc = {};
    lc.gridDim = dim3(grid); lc.blockDim = dim3(block); lc.dynamicSmemBytes = smem; lc.stream = cudaStreamPerThread;
    lc.attrs = at; lc.numAttrs = pdl ? 1 : 0;
    return lc;
  };
  for (int layer = 0; layer < 2; layer++) {
    const int tl = layer * 12;
    cudaLaunchConfig_t lc = cfgof(256, 256, 0, layer > 0 && PDL_LN);
    cudaLaunchKernelEx(&lc, ln_kernel, xcur, P.xn, P.xh, zar, nzar, zkv, nzkv, Wk, Wv, layer == 0 ? PF_A : 0, tl + 0);
    ca.tl = tl + 2;
    lc = cfgof(96, 384, ch::SMEM, PDL_CH);
    cudaLaunchKernelEx(&lc, chain_kernel, ca, tmCq, tmCk, tmCv, tmCo);
    lc = cfgof(TRAIL_GRID, 384, tr::SMEM, true);
    tr::Args ta{P.k, P.v, (unsigned char*)P.o, P.qs, (unsigned char*)P.part, xcur, P.xa, P.xn2, P.arena, layer == 0 ? 1 : 0, tl + 4, 500, 100};
#ifdef TUNE
    if (getenv("NAP")) ta.nap = atoi(getenv("NAP"));
    if (getenv("NAP2")) ta.nap2 = atoi(getenv("NAP2"));
#endif
    cudaLaunchKernelEx(&lc, trail_kernel, tmXn, tmWq, tmWo5, tmWo2, sched_of(layer), ta, pa);
    lc = cfgof(128, 384, bf::SMEM, PDL_B);
    const bf::Args ba{(const unsigned char*)P.wb, (const unsigned char*)P.wot, (unsigned char*)P.kvacc, (unsigned char*)P.pq, P.xa, layer == 0 ? P.xb : out,
                      layer == 0 && PF_B ? Wk : nullptr, Wv, tl + 7};
    cudaLaunchKernelEx(&lc, blayer_kernel, tmXn2, ba);
    xcur = P.xb;
  }
}
```

```cpp
#include <cuda_runtime.h>
#include <cuda.h>
#include <cuda_bf16.h>
#include <stdint.h>
#include <stdlib.h>
#include <type_traits>

typedef __nv_bfloat16 bf16;

namespace cfg {
constexpr int S = 2048, DM = 640, H = 32, DH = 192, NSEG = 64, SEG = 32, NM = 8;
constexpr int HD = H * DH;
}

__device__ __forceinline__ uint32_t smem_u32(const void* p) { return (uint32_t)__cvta_generic_to_shared(p); }
__device__ __forceinline__ uint32_t mapa_u32(uint32_t a, uint32_t r) {
  uint32_t o; asm("mapa.shared::cluster.u32 %0, %1, %2;" : "=r"(o) : "r"(a), "r"(r)); return o;
}
__device__ __forceinline__ void mbar_init(uint32_t b, uint32_t c) {
  asm volatile("mbarrier.init.shared::cta.b64 [%0], %1;" :: "r"(b), "r"(c) : "memory");
}
__device__ __forceinline__ void mbar_expect_tx(uint32_t b, uint32_t bytes) {
  asm volatile("mbarrier.arrive.expect_tx.shared::cta.b64 _, [%0], %1;" :: "r"(b), "r"(bytes) : "memory");
}
__device__ __forceinline__ void mbar_arrive(uint32_t b) {
  asm volatile("mbarrier.arrive.shared::cta.b64 _, [%0];" :: "r"(b) : "memory");
}
__device__ __forceinline__ void mbar_arrive_if(bool c, uint32_t b) {
  asm volatile("{\n.reg .pred p;\nsetp.ne.u32 p, %1, 0;\n@p mbarrier.arrive.shared::cta.b64 _, [%0];\n}" :: "r"(b), "r"((uint32_t)c) : "memory");
}
__device__ __forceinline__ bool mbar_try(uint32_t b, uint32_t ph) {
  uint32_t p;
  asm volatile("{.reg .pred p; mbarrier.try_wait.parity.shared::cta.b64 p, [%1], %2; selp.u32 %0, 1, 0, p;}"
               : "=r"(p) : "r"(b), "r"(ph) : "memory");
  return p;
}
__device__ __forceinline__ bool mbar_try_cluster(uint32_t b, uint32_t ph) {
  uint32_t p;
  asm volatile("{.reg .pred p; mbarrier.try_wait.parity.acquire.cluster.shared::cta.b64 p, [%1], %2; selp.u32 %0, 1, 0, p;}"
               : "=r"(p) : "r"(b), "r"(ph) : "memory");
  return p;
}
#ifndef SPIN_LIMIT
#define SPIN_LIMIT (1 << 22)
#endif
__device__ __forceinline__ void mbar_wait(uint32_t b, uint32_t ph) {
  asm volatile("{\n.reg .pred p, q;\n.reg .u32 c;\nmov.u32 c, 0;\n"
               "W_%=:\nmbarrier.try_wait.parity.shared::cta.b64 p, [%0], %1;\n@p bra.uni D_%=;\n"
               "add.u32 c, c, 1;\nsetp.lt.u32 q, c, %2;\n@q bra.uni W_%=;\nD_%=:\n}"
               :: "r"(b), "r"(ph), "n"(SPIN_LIMIT) : "memory");
}
__device__ __forceinline__ void mbar_spin(uint32_t b, uint32_t ph) {
  asm volatile("{\n.reg .pred p, q;\n.reg .u32 c;\nmov.u32 c, 0;\n"
               "W_%=:\nmbarrier.test_wait.parity.shared::cta.b64 p, [%0], %1;\n@p bra D_%=;\n"
               "add.u32 c, c, 1;\nsetp.lt.u32 q, c, %2;\n@q bra W_%=;\nD_%=:\n}"
               :: "r"(b), "r"(ph), "n"(SPIN_LIMIT) : "memory");
}
#define PIN(x) asm volatile("" : "+r"(x))
__device__ __forceinline__ void mbar_wait_cluster(uint32_t b, uint32_t ph) {
  int s = 0;
  while (!mbar_try_cluster(b, ph)) { if (++s > SPIN_LIMIT) break; }
}
__device__ __forceinline__ void st_async_v2(uint32_t a, uint32_t x, uint32_t y, uint32_t mb) {
  asm volatile("st.async.weak.shared::cluster.mbarrier::complete_tx::bytes.v2.b32 [%0], {%1,%2}, [%3];"
               :: "r"(a), "r"(x), "r"(y), "r"(mb) : "memory");
}
__device__ __forceinline__ void st_async_v4(uint32_t a, uint32_t x, uint32_t y, uint32_t z, uint32_t w, uint32_t mb) {
  asm volatile("st.async.weak.shared::cluster.mbarrier::complete_tx::bytes.v4.b32 [%0], {%1,%2,%3,%4}, [%5];"
               :: "r"(a), "r"(x), "r"(y), "r"(z), "r"(w), "r"(mb) : "memory");
}
__device__ __forceinline__ void bulk_g2s(uint32_t dst, const void* src, uint32_t bytes, uint32_t mb) {
  asm volatile("cp.async.bulk.shared::cluster.global.mbarrier::complete_tx::bytes [%0], [%1], %2, [%3];"
               :: "r"(dst), "l"(src), "r"(bytes), "r"(mb) : "memory");
}
__device__ __forceinline__ void cp_async16(uint32_t dst, const void* src) {
  asm volatile("cp.async.cg.shared.global [%0], [%1], 16;" :: "r"(dst), "l"(src) : "memory");
}
__device__ __forceinline__ void cp_async_wait_all() { asm volatile("cp.async.wait_all;" ::: "memory"); }
__device__ __forceinline__ void fence_proxy_async() { asm volatile("fence.proxy.async.shared::cta;" ::: "memory"); }
__device__ __forceinline__ void bar_sync(int id, int n) { asm volatile("bar.sync %0, %1;" :: "r"(id), "r"(n) : "memory"); }
__device__ __forceinline__ void bar_arrive(int id, int n) { asm volatile("bar.arrive %0, %1;" :: "r"(id), "r"(n) : "memory"); }
__device__ __forceinline__ void cluster_sync_all() {
  asm volatile("barrier.cluster.arrive.release.aligned; barrier.cluster.wait.acquire.aligned;" ::: "memory");
}
__device__ __forceinline__ void ldsm_x4(uint32_t (&r)[4], uint32_t a) {
  asm volatile("ldmatrix.sync.aligned.m8n8.x4.shared.b16 {%0,%1,%2,%3}, [%4];"
               : "=r"(r[0]), "=r"(r[1]), "=r"(r[2]), "=r"(r[3]) : "r"(a) : "memory");
}
__device__ __forceinline__ void ldsm_x4_t(uint32_t (&r)[4], uint32_t a) {
  asm volatile("ldmatrix.sync.aligned.m8n8.x4.trans.shared.b16 {%0,%1,%2,%3}, [%4];"
               : "=r"(r[0]), "=r"(r[1]), "=r"(r[2]), "=r"(r[3]) : "r"(a) : "memory");
}
template <int IMM> __device__ __forceinline__ void ldsm_x4_i(uint32_t (&r)[4], uint32_t a) {
  asm volatile("ldmatrix.sync.aligned.m8n8.x4.shared.b16 {%0,%1,%2,%3}, [%4+%5];"
               : "=r"(r[0]), "=r"(r[1]), "=r"(r[2]), "=r"(r[3]) : "r"(a), "n"(IMM) : "memory");
}
template <int IMM> __device__ __forceinline__ void ldsm_x4_t_i(uint32_t (&r)[4], uint32_t a) {
  asm volatile("ldmatrix.sync.aligned.m8n8.x4.trans.shared.b16 {%0,%1,%2,%3}, [%4+%5];"
               : "=r"(r[0]), "=r"(r[1]), "=r"(r[2]), "=r"(r[3]) : "r"(a), "n"(IMM) : "memory");
}
template <int IMM> __device__ __forceinline__ uint4 lds128_i(uint32_t a) {
  uint4 v; asm volatile("ld.shared.v4.u32 {%0,%1,%2,%3}, [%4+%5];" : "=r"(v.x), "=r"(v.y), "=r"(v.z), "=r"(v.w) : "r"(a), "n"(IMM) : "memory"); return v;
}
template <int IMM> __device__ __forceinline__ uint2 lds64_i(uint32_t a) {
  uint2 v; asm volatile("ld.shared.v2.u32 {%0,%1}, [%2+%3];" : "=r"(v.x), "=r"(v.y) : "r"(a), "n"(IMM) : "memory"); return v;
}
template <int IMM> __device__ __forceinline__ void sts128_i(uint32_t a, uint32_t x, uint32_t y, uint32_t z, uint32_t w) {
  asm volatile("st.shared.v4.u32 [%0+%5], {%1,%2,%3,%4};" :: "r"(a), "r"(x), "r"(y), "r"(z), "r"(w), "n"(IMM) : "memory");
}
template <int IMM> __device__ __forceinline__ void sts64_i(uint32_t a, uint32_t x, uint32_t y) {
  asm volatile("st.shared.v2.u32 [%0+%3], {%1,%2};" :: "r"(a), "r"(x), "r"(y), "n"(IMM) : "memory");
}
template <int IMM> __device__ __forceinline__ void st_async_v2_i(uint32_t a, uint32_t x, uint32_t y, uint32_t mb) {
  asm volatile("st.async.weak.shared::cluster.mbarrier::complete_tx::bytes.v2.b32 [%0+%4], {%1,%2}, [%3];"
               :: "r"(a), "r"(x), "r"(y), "r"(mb), "n"(IMM) : "memory");
}
template <int IMM> __device__ __forceinline__ uint4 ld_relaxed_v4_i(const void* p) {
  uint4 v; asm volatile("ld.relaxed.gpu.global.v4.u32 {%0,%1,%2,%3}, [%4+%5];" : "=r"(v.x), "=r"(v.y), "=r"(v.z), "=r"(v.w) : "l"(p), "n"(IMM) : "memory"); return v;
}
template <int I, int N, class F> __device__ __forceinline__ void static_for(F&& f) {
  if constexpr (I < N) { f(std::integral_constant<int, I>{}); static_for<I + 1, N>(f); }
}
__device__ __forceinline__ uint32_t movm_t(uint32_t a) {
  uint32_t d; asm volatile("movmatrix.sync.aligned.m8n8.trans.b16 %0, %1;" : "=r"(d) : "r"(a)); return d;
}
__device__ __forceinline__ void mma16816(float (&d)[4], uint32_t a0, uint32_t a1, uint32_t a2, uint32_t a3, uint32_t b0, uint32_t b1) {
  asm volatile("mma.sync.aligned.m16n8k16.row.col.f32.bf16.bf16.f32 {%0,%1,%2,%3}, {%4,%5,%6,%7}, {%8,%9}, {%0,%1,%2,%3};"
               : "+f"(d[0]), "+f"(d[1]), "+f"(d[2]), "+f"(d[3]) : "r"(a0), "r"(a1), "r"(a2), "r"(a3), "r"(b0), "r"(b1));
}
__device__ __forceinline__ uint32_t pack_bf16(float lo, float hi) {
  uint32_t d; asm("cvt.rn.bf16x2.f32 %0, %1, %2;" : "=r"(d) : "f"(hi), "f"(lo)); return d;
}
__device__ __forceinline__ float bf_lo(uint32_t w) { return __uint_as_float(w << 16); }
__device__ __forceinline__ float bf_hi(uint32_t w) { return __uint_as_float(w & 0xffff0000u); }
__device__ __forceinline__ uint4 lds128(uint32_t a) {
  uint4 v; asm volatile("ld.shared.v4.u32 {%0,%1,%2,%3}, [%4];" : "=r"(v.x), "=r"(v.y), "=r"(v.z), "=r"(v.w) : "r"(a) : "memory"); return v;
}
__device__ __forceinline__ uint2 lds64(uint32_t a) {
  uint2 v; asm volatile("ld.shared.v2.u32 {%0,%1}, [%2];" : "=r"(v.x), "=r"(v.y) : "r"(a) : "memory"); return v;
}
__device__ __forceinline__ void sts128(uint32_t a, uint32_t x, uint32_t y, uint32_t z, uint32_t w) {
  asm volatile("st.shared.v4.u32 [%0], {%1,%2,%3,%4};" :: "r"(a), "r"(x), "r"(y), "r"(z), "r"(w) : "memory");
}
__device__ __forceinline__ void sts64(uint32_t a, uint32_t x, uint32_t y) {
  asm volatile("st.shared.v2.u32 [%0], {%1,%2};" :: "r"(a), "r"(x), "r"(y) : "memory");
}
__device__ __forceinline__ uint4 ld_relaxed_v4(const void* p) {
  uint4 v; asm volatile("ld.relaxed.gpu.global.v4.u32 {%0,%1,%2,%3}, [%4];" : "=r"(v.x), "=r"(v.y), "=r"(v.z), "=r"(v.w) : "l"(p) : "memory"); return v;
}
__device__ __forceinline__ uint32_t ld_relaxed_u32(const void* p) {
  uint32_t v; asm volatile("ld.relaxed.gpu.global.u32 %0, [%1];" : "=r"(v) : "l"(p) : "memory"); return v;
}
__device__ __forceinline__ void st_relaxed_v2(void* p, uint32_t a, uint32_t b) {
  asm volatile("st.relaxed.gpu.global.v2.u32 [%0], {%1,%2};" :: "l"(p), "r"(a), "r"(b) : "memory");
}
__device__ __forceinline__ void st_relaxed_u32(void* p, uint32_t v) {
  asm volatile("st.relaxed.gpu.global.u32 [%0], %1;" :: "l"(p), "r"(v) : "memory");
}
__device__ __forceinline__ uint32_t clk32() { uint32_t c; asm volatile("mov.u32 %0, %%clock;" : "=r"(c) :: "memory"); return c; }
__device__ __forceinline__ uint32_t clkdep(uint32_t v) {
  uint32_t c; asm volatile("{.reg .pred p; setp.eq.u32 p, %1, 0xdeadbeef; @p trap; mov.u32 %0, %%clock;}" : "=r"(c) : "r"(v) : "memory"); return c;
}
__device__ __forceinline__ void wgmma_fence() { asm volatile("wgmma.fence.sync.aligned;" ::: "memory"); }
__device__ __forceinline__ void wgmma_commit() { asm volatile("wgmma.commit_group.sync.aligned;" ::: "memory"); }
template <int N> __device__ __forceinline__ void wgmma_wait() { asm volatile("wgmma.wait_group.sync.aligned %0;" :: "n"(N) : "memory"); }
__device__ __forceinline__ void wgmma_n8_ss_ta(float (&d)[4], uint64_t da, uint64_t db, int acc) {
  asm volatile("{\n.reg .pred p;\nsetp.ne.b32 p, %6, 0;\n"
               "wgmma.mma_async.sync.aligned.m64n8k16.f32.bf16.bf16 {%0,%1,%2,%3}, %4, %5, p, 1, 1, 1, 0;\n}\n"
               : "+f"(d[0]), "+f"(d[1]), "+f"(d[2]), "+f"(d[3]) : "l"(da), "l"(db), "r"(acc));
}
__device__ __forceinline__ uint64_t make_desc(uint32_t saddr, uint32_t lbo_bytes, uint32_t sbo_bytes, uint32_t swz) {
  return (uint64_t)((saddr & 0x3FFFF) >> 4) | ((uint64_t)(lbo_bytes >> 4) << 16) | ((uint64_t)(sbo_bytes >> 4) << 32) | ((uint64_t)swz << 62);
}


__device__ __forceinline__ bool elect_one() {
  uint32_t p; asm volatile("{\n.reg .pred p;\nelect.sync _|p, 0xffffffff;\nselp.u32 %0, 1, 0, p;\n}" : "=r"(p)); return p;
}
__device__ __forceinline__ void tma_load_3d(uint32_t dst, const CUtensorMap* tm, int c0, int c1, int c2, uint32_t mb) {
  asm volatile("cp.async.bulk.tensor.3d.shared::cluster.global.mbarrier::complete_tx::bytes [%0], [%1, {%3, %4, %5}], [%2];"
               :: "r"(dst), "l"(tm), "r"(mb), "r"(c0), "r"(c1), "r"(c2) : "memory");
}
__device__ __forceinline__ void tma_load_2d(uint32_t dst, const CUtensorMap* tm, int c0, int c1, uint32_t mb) {
  asm volatile("cp.async.bulk.tensor.2d.shared::cluster.global.mbarrier::complete_tx::bytes [%0], [%1, {%3, %4}], [%2];"
               :: "r"(dst), "l"(tm), "r"(mb), "r"(c0), "r"(c1) : "memory");
}
__device__ __forceinline__ void bulk_s2g(void* dst, uint32_t src, uint32_t bytes) {
  asm volatile("cp.async.bulk.global.shared::cta.bulk_group [%0], [%1], %2;" :: "l"(dst), "r"(src), "r"(bytes) : "memory");
}
__device__ __forceinline__ uint64_t policy_evict_first() {
  uint64_t p; asm volatile("createpolicy.fractional.L2::evict_first.b64 %0, 1.0;" : "=l"(p)); return p;
}
__device__ __forceinline__ void bulk_s2g_hint(void* dst, uint32_t src, uint32_t bytes, uint64_t pol) {
  asm volatile("cp.async.bulk.global.shared::cta.bulk_group.L2::cache_hint [%0], [%1], %2, %3;" :: "l"(dst), "r"(src), "r"(bytes), "l"(pol) : "memory");
}
__device__ __forceinline__ void bulk_commit() { asm volatile("cp.async.bulk.commit_group;" ::: "memory"); }
template <int N> __device__ __forceinline__ void bulk_wait_read() { asm volatile("cp.async.bulk.wait_group.read %0;" :: "n"(N) : "memory"); }
template <int N> __device__ __forceinline__ void bulk_wait() { asm volatile("cp.async.bulk.wait_group %0;" :: "n"(N) : "memory"); }
__device__ __forceinline__ void stsm_x4(uint32_t a, uint32_t r0, uint32_t r1, uint32_t r2, uint32_t r3) {
  asm volatile("stmatrix.sync.aligned.m8n8.x4.shared.b16 [%0], {%1,%2,%3,%4};" :: "r"(a), "r"(r0), "r"(r1), "r"(r2), "r"(r3) : "memory");
}
__device__ __forceinline__ void stsm_x2(uint32_t a, uint32_t r0, uint32_t r1) {
  asm volatile("stmatrix.sync.aligned.m8n8.x2.shared.b16 [%0], {%1,%2};" :: "r"(a), "r"(r0), "r"(r1) : "memory");
}
__device__ __forceinline__ void ldsm_x2(uint32_t (&r)[2], uint32_t a) {
  asm volatile("ldmatrix.sync.aligned.m8n8.x2.shared.b16 {%0,%1}, [%2];" : "=r"(r[0]), "=r"(r[1]) : "r"(a) : "memory");
}
__device__ __forceinline__ void ldsm_x2_t(uint32_t (&r)[2], uint32_t a) {
  asm volatile("ldmatrix.sync.aligned.m8n8.x2.trans.shared.b16 {%0,%1}, [%2];" : "=r"(r[0]), "=r"(r[1]) : "r"(a) : "memory");
}
__device__ __forceinline__ float bf16r(float x) { return __uint_as_float(pack_bf16(0.f, x) & 0xffff0000u); }
__device__ __forceinline__ void bf16r2(float& a, float& b) { const uint32_t w = pack_bf16(a, b); a = bf_lo(w); b = bf_hi(w); }
__device__ __forceinline__ float rcpf(float x) { float r; asm("rcp.approx.ftz.f32 %0, %1;" : "=f"(r) : "f"(x)); return r; }
__device__ __forceinline__ float ex2f(float x) { float e; asm("ex2.approx.ftz.f32 %0, %1;" : "=f"(e) : "f"(x)); return e; }
__device__ __forceinline__ void prefetch_tmap(const CUtensorMap* tm) { asm volatile("prefetch.tensormap [%0];" :: "l"(tm) : "memory"); }

#ifdef TIMELINE
__device__ unsigned long long g_tl[2 * 64];
__device__ unsigned long long g_log[2 * 132 * 64 * 2 + 2];
__device__ unsigned long long g_tl2[4 * 64];
__device__ __forceinline__ unsigned long long gtime() { unsigned long long t; asm volatile("mov.u64 %0, %%globaltimer;" : "=l"(t)); return t; }
#define TL_BEGIN(id) do { if (threadIdx.x == 0) atomicMin(&g_tl[2 * (id)], gtime()); } while (0)
#define TL_END(id) do { if ((threadIdx.x & 31) == 0) atomicMax(&g_tl[2 * (id) + 1], gtime()); } while (0)
#define TL_ACC(idx, t0) do { if (threadIdx.x == 0 && m >= 4 && m < 11) { atomicAdd(&g_tl2[idx], gtime() - (t0)); atomicAdd(&g_tl2[(idx) + 1], 1ull); } } while (0)
#define TL_NOW() gtime()
#define TL2(idx) asm volatile("{\n.reg .pred p;\nsetp.eq.u32 p, %2, 0;\n@p red.relaxed.gpu.global.max.u64 [%0], %1;\n}" :: "l"(&g_tl2[idx]), "l"(gtime()), "r"(threadIdx.x) : "memory")
#define TL_BEGIN0(id) atomicMin(&g_tl[2 * (id)], gtime())
#else
#define TL_ACC(idx, t0)
#define TL_NOW() 0ull
#define TL2(idx)
#define TL_BEGIN0(id)
#define TL_BEGIN(id)
#define TL_END(id)
#endif
template <int TA, int TB> __device__ __forceinline__ void wgmma_n24(float (&d)[12], uint64_t da, uint64_t db, int acc) {
  asm volatile("{\n.reg .pred p;\nsetp.ne.b32 p, %14, 0;\n"
    "wgmma.mma_async.sync.aligned.m64n24k16.f32.bf16.bf16 {%0, %1, %2, %3, %4, %5, %6, %7, %8, %9, %10, %11}, %12, %13, p, 1, 1, %15, %16;\n}\n"
    : "+f"(d[0]), "+f"(d[1]), "+f"(d[2]), "+f"(d[3]), "+f"(d[4]), "+f"(d[5]), "+f"(d[6]), "+f"(d[7]), "+f"(d[8]), "+f"(d[9]), "+f"(d[10]), "+f"(d[11])
    : "l"(da), "l"(db), "r"(acc), "n"(TA), "n"(TB));
}

template <int TA, int TB> __device__ __forceinline__ void wgmma_n80(float (&d)[40], uint64_t da, uint64_t db, int acc) {
  asm volatile("{\n.reg .pred p;\nsetp.ne.b32 p, %42, 0;\n"
    "wgmma.mma_async.sync.aligned.m64n80k16.f32.bf16.bf16 {%0, %1, %2, %3, %4, %5, %6, %7, %8, %9, %10, %11, %12, %13, %14, %15, %16, %17, %18, %19, %20, %21, %22, %23, %24, %25, %26, %27, %28, %29, %30, %31, %32, %33, %34, %35, %36, %37, %38, %39}, %40, %41, p, 1, 1, %43, %44;\n}\n"
    : "+f"(d[0]), "+f"(d[1]), "+f"(d[2]), "+f"(d[3]), "+f"(d[4]), "+f"(d[5]), "+f"(d[6]), "+f"(d[7]), "+f"(d[8]), "+f"(d[9]), "+f"(d[10]), "+f"(d[11]), "+f"(d[12]), "+f"(d[13]), "+f"(d[14]), "+f"(d[15]), "+f"(d[16]), "+f"(d[17]), "+f"(d[18]), "+f"(d[19]), "+f"(d[20]), "+f"(d[21]), "+f"(d[22]), "+f"(d[23]), "+f"(d[24]), "+f"(d[25]), "+f"(d[26]), "+f"(d[27]), "+f"(d[28]), "+f"(d[29]), "+f"(d[30]), "+f"(d[31]), "+f"(d[32]), "+f"(d[33]), "+f"(d[34]), "+f"(d[35]), "+f"(d[36]), "+f"(d[37]), "+f"(d[38]), "+f"(d[39])
    : "l"(da), "l"(db), "r"(acc), "n"(TA), "n"(TB));
}

template <int TA, int TB> __device__ __forceinline__ void wgmma_n128(float (&d)[64], uint64_t da, uint64_t db, int acc) {
  asm volatile("{\n.reg .pred p;\nsetp.ne.b32 p, %66, 0;\n"
    "wgmma.mma_async.sync.aligned.m64n128k16.f32.bf16.bf16 {%0, %1, %2, %3, %4, %5, %6, %7, %8, %9, %10, %11, %12, %13, %14, %15, %16, %17, %18, %19, %20, %21, %22, %23, %24, %25, %26, %27, %28, %29, %30, %31, %32, %33, %34, %35, %36, %37, %38, %39, %40, %41, %42, %43, %44, %45, %46, %47, %48, %49, %50, %51, %52, %53, %54, %55, %56, %57, %58, %59, %60, %61, %62, %63}, %64, %65, p, 1, 1, %67, %68;\n}\n"
    : "+f"(d[0]), "+f"(d[1]), "+f"(d[2]), "+f"(d[3]), "+f"(d[4]), "+f"(d[5]), "+f"(d[6]), "+f"(d[7]), "+f"(d[8]), "+f"(d[9]), "+f"(d[10]), "+f"(d[11]), "+f"(d[12]), "+f"(d[13]), "+f"(d[14]), "+f"(d[15]), "+f"(d[16]), "+f"(d[17]), "+f"(d[18]), "+f"(d[19]), "+f"(d[20]), "+f"(d[21]), "+f"(d[22]), "+f"(d[23]), "+f"(d[24]), "+f"(d[25]), "+f"(d[26]), "+f"(d[27]), "+f"(d[28]), "+f"(d[29]), "+f"(d[30]), "+f"(d[31]), "+f"(d[32]), "+f"(d[33]), "+f"(d[34]), "+f"(d[35]), "+f"(d[36]), "+f"(d[37]), "+f"(d[38]), "+f"(d[39]), "+f"(d[40]), "+f"(d[41]), "+f"(d[42]), "+f"(d[43]), "+f"(d[44]), "+f"(d[45]), "+f"(d[46]), "+f"(d[47]), "+f"(d[48]), "+f"(d[49]), "+f"(d[50]), "+f"(d[51]), "+f"(d[52]), "+f"(d[53]), "+f"(d[54]), "+f"(d[55]), "+f"(d[56]), "+f"(d[57]), "+f"(d[58]), "+f"(d[59]), "+f"(d[60]), "+f"(d[61]), "+f"(d[62]), "+f"(d[63])
    : "l"(da), "l"(db), "r"(acc), "n"(TA), "n"(TB));
}

template <int TA, int TB> __device__ __forceinline__ void wgmma_n192(float (&d)[96], uint64_t da, uint64_t db, int acc) {
  asm volatile("{\n.reg .pred p;\nsetp.ne.b32 p, %98, 0;\n"
    "wgmma.mma_async.sync.aligned.m64n192k16.f32.bf16.bf16 {%0, %1, %2, %3, %4, %5, %6, %7, %8, %9, %10, %11, %12, %13, %14, %15, %16, %17, %18, %19, %20, %21, %22, %23, %24, %25, %26, %27, %28, %29, %30, %31, %32, %33, %34, %35, %36, %37, %38, %39, %40, %41, %42, %43, %44, %45, %46, %47, %48, %49, %50, %51, %52, %53, %54, %55, %56, %57, %58, %59, %60, %61, %62, %63, %64, %65, %66, %67, %68, %69, %70, %71, %72, %73, %74, %75, %76, %77, %78, %79, %80, %81, %82, %83, %84, %85, %86, %87, %88, %89, %90, %91, %92, %93, %94, %95}, %96, %97, p, 1, 1, %99, %100;\n}\n"
    : "+f"(d[0]), "+f"(d[1]), "+f"(d[2]), "+f"(d[3]), "+f"(d[4]), "+f"(d[5]), "+f"(d[6]), "+f"(d[7]), "+f"(d[8]), "+f"(d[9]), "+f"(d[10]), "+f"(d[11]), "+f"(d[12]), "+f"(d[13]), "+f"(d[14]), "+f"(d[15]), "+f"(d[16]), "+f"(d[17]), "+f"(d[18]), "+f"(d[19]), "+f"(d[20]), "+f"(d[21]), "+f"(d[22]), "+f"(d[23]), "+f"(d[24]), "+f"(d[25]), "+f"(d[26]), "+f"(d[27]), "+f"(d[28]), "+f"(d[29]), "+f"(d[30]), "+f"(d[31]), "+f"(d[32]), "+f"(d[33]), "+f"(d[34]), "+f"(d[35]), "+f"(d[36]), "+f"(d[37]), "+f"(d[38]), "+f"(d[39]), "+f"(d[40]), "+f"(d[41]), "+f"(d[42]), "+f"(d[43]), "+f"(d[44]), "+f"(d[45]), "+f"(d[46]), "+f"(d[47]), "+f"(d[48]), "+f"(d[49]), "+f"(d[50]), "+f"(d[51]), "+f"(d[52]), "+f"(d[53]), "+f"(d[54]), "+f"(d[55]), "+f"(d[56]), "+f"(d[57]), "+f"(d[58]), "+f"(d[59]), "+f"(d[60]), "+f"(d[61]), "+f"(d[62]), "+f"(d[63]), "+f"(d[64]), "+f"(d[65]), "+f"(d[66]), "+f"(d[67]), "+f"(d[68]), "+f"(d[69]), "+f"(d[70]), "+f"(d[71]), "+f"(d[72]), "+f"(d[73]), "+f"(d[74]), "+f"(d[75]), "+f"(d[76]), "+f"(d[77]), "+f"(d[78]), "+f"(d[79]), "+f"(d[80]), "+f"(d[81]), "+f"(d[82]), "+f"(d[83]), "+f"(d[84]), "+f"(d[85]), "+f"(d[86]), "+f"(d[87]), "+f"(d[88]), "+f"(d[89]), "+f"(d[90]), "+f"(d[91]), "+f"(d[92]), "+f"(d[93]), "+f"(d[94]), "+f"(d[95])
    : "l"(da), "l"(db), "r"(acc), "n"(TA), "n"(TB));
}

template <int TA, int TB> __device__ __forceinline__ void wgmma_n256(float (&d)[128], uint64_t da, uint64_t db, int acc) {
  asm volatile("{\n.reg .pred p;\nsetp.ne.b32 p, %130, 0;\n"
    "wgmma.mma_async.sync.aligned.m64n256k16.f32.bf16.bf16 {%0, %1, %2, %3, %4, %5, %6, %7, %8, %9, %10, %11, %12, %13, %14, %15, %16, %17, %18, %19, %20, %21, %22, %23, %24, %25, %26, %27, %28, %29, %30, %31, %32, %33, %34, %35, %36, %37, %38, %39, %40, %41, %42, %43, %44, %45, %46, %47, %48, %49, %50, %51, %52, %53, %54, %55, %56, %57, %58, %59, %60, %61, %62, %63, %64, %65, %66, %67, %68, %69, %70, %71, %72, %73, %74, %75, %76, %77, %78, %79, %80, %81, %82, %83, %84, %85, %86, %87, %88, %89, %90, %91, %92, %93, %94, %95, %96, %97, %98, %99, %100, %101, %102, %103, %104, %105, %106, %107, %108, %109, %110, %111, %112, %113, %114, %115, %116, %117, %118, %119, %120, %121, %122, %123, %124, %125, %126, %127}, %128, %129, p, 1, 1, %131, %132;\n}\n"
    : "+f"(d[0]), "+f"(d[1]), "+f"(d[2]), "+f"(d[3]), "+f"(d[4]), "+f"(d[5]), "+f"(d[6]), "+f"(d[7]), "+f"(d[8]), "+f"(d[9]), "+f"(d[10]), "+f"(d[11]), "+f"(d[12]), "+f"(d[13]), "+f"(d[14]), "+f"(d[15]), "+f"(d[16]), "+f"(d[17]), "+f"(d[18]), "+f"(d[19]), "+f"(d[20]), "+f"(d[21]), "+f"(d[22]), "+f"(d[23]), "+f"(d[24]), "+f"(d[25]), "+f"(d[26]), "+f"(d[27]), "+f"(d[28]), "+f"(d[29]), "+f"(d[30]), "+f"(d[31]), "+f"(d[32]), "+f"(d[33]), "+f"(d[34]), "+f"(d[35]), "+f"(d[36]), "+f"(d[37]), "+f"(d[38]), "+f"(d[39]), "+f"(d[40]), "+f"(d[41]), "+f"(d[42]), "+f"(d[43]), "+f"(d[44]), "+f"(d[45]), "+f"(d[46]), "+f"(d[47]), "+f"(d[48]), "+f"(d[49]), "+f"(d[50]), "+f"(d[51]), "+f"(d[52]), "+f"(d[53]), "+f"(d[54]), "+f"(d[55]), "+f"(d[56]), "+f"(d[57]), "+f"(d[58]), "+f"(d[59]), "+f"(d[60]), "+f"(d[61]), "+f"(d[62]), "+f"(d[63]), "+f"(d[64]), "+f"(d[65]), "+f"(d[66]), "+f"(d[67]), "+f"(d[68]), "+f"(d[69]), "+f"(d[70]), "+f"(d[71]), "+f"(d[72]), "+f"(d[73]), "+f"(d[74]), "+f"(d[75]), "+f"(d[76]), "+f"(d[77]), "+f"(d[78]), "+f"(d[79]), "+f"(d[80]), "+f"(d[81]), "+f"(d[82]), "+f"(d[83]), "+f"(d[84]), "+f"(d[85]), "+f"(d[86]), "+f"(d[87]), "+f"(d[88]), "+f"(d[89]), "+f"(d[90]), "+f"(d[91]), "+f"(d[92]), "+f"(d[93]), "+f"(d[94]), "+f"(d[95]), "+f"(d[96]), "+f"(d[97]), "+f"(d[98]), "+f"(d[99]), "+f"(d[100]), "+f"(d[101]), "+f"(d[102]), "+f"(d[103]), "+f"(d[104]), "+f"(d[105]), "+f"(d[106]), "+f"(d[107]), "+f"(d[108]), "+f"(d[109]), "+f"(d[110]), "+f"(d[111]), "+f"(d[112]), "+f"(d[113]), "+f"(d[114]), "+f"(d[115]), "+f"(d[116]), "+f"(d[117]), "+f"(d[118]), "+f"(d[119]), "+f"(d[120]), "+f"(d[121]), "+f"(d[122]), "+f"(d[123]), "+f"(d[124]), "+f"(d[125]), "+f"(d[126]), "+f"(d[127])
    : "l"(da), "l"(db), "r"(acc), "n"(TA), "n"(TB));
}

template <int TB> __device__ __forceinline__ void wgmma_rs_n24(float (&d)[12], uint32_t a0, uint32_t a1, uint32_t a2, uint32_t a3, uint64_t db, int acc) {
  asm volatile("{\n.reg .pred p;\nsetp.ne.b32 p, %17, 0;\n"
    "wgmma.mma_async.sync.aligned.m64n24k16.f32.bf16.bf16 {%0, %1, %2, %3, %4, %5, %6, %7, %8, %9, %10, %11}, {%12, %13, %14, %15}, %16, p, 1, 1, %18;\n}\n"
    : "+f"(d[0]), "+f"(d[1]), "+f"(d[2]), "+f"(d[3]), "+f"(d[4]), "+f"(d[5]), "+f"(d[6]), "+f"(d[7]), "+f"(d[8]), "+f"(d[9]), "+f"(d[10]), "+f"(d[11])
    : "r"(a0), "r"(a1), "r"(a2), "r"(a3), "l"(db), "r"(acc), "n"(TB));
}

template <int TB> __device__ __forceinline__ void wgmma_rs_n40(float (&d)[20], uint32_t a0, uint32_t a1, uint32_t a2, uint32_t a3, uint64_t db, int acc) {
  asm volatile("{\n.reg .pred p;\nsetp.ne.b32 p, %25, 0;\n"
    "wgmma.mma_async.sync.aligned.m64n40k16.f32.bf16.bf16 {%0, %1, %2, %3, %4, %5, %6, %7, %8, %9, %10, %11, %12, %13, %14, %15, %16, %17, %18, %19}, {%20, %21, %22, %23}, %24, p, 1, 1, %26;\n}\n"
    : "+f"(d[0]), "+f"(d[1]), "+f"(d[2]), "+f"(d[3]), "+f"(d[4]), "+f"(d[5]), "+f"(d[6]), "+f"(d[7]), "+f"(d[8]), "+f"(d[9]), "+f"(d[10]), "+f"(d[11]), "+f"(d[12]), "+f"(d[13]), "+f"(d[14]), "+f"(d[15]), "+f"(d[16]), "+f"(d[17]), "+f"(d[18]), "+f"(d[19])
    : "r"(a0), "r"(a1), "r"(a2), "r"(a3), "l"(db), "r"(acc), "n"(TB));
}

template <int TB> __device__ __forceinline__ void wgmma_rs_n192(float (&d)[96], uint32_t a0, uint32_t a1, uint32_t a2, uint32_t a3, uint64_t db, int acc) {
  asm volatile("{\n.reg .pred p;\nsetp.ne.b32 p, %101, 0;\n"
    "wgmma.mma_async.sync.aligned.m64n192k16.f32.bf16.bf16 {%0, %1, %2, %3, %4, %5, %6, %7, %8, %9, %10, %11, %12, %13, %14, %15, %16, %17, %18, %19, %20, %21, %22, %23, %24, %25, %26, %27, %28, %29, %30, %31, %32, %33, %34, %35, %36, %37, %38, %39, %40, %41, %42, %43, %44, %45, %46, %47, %48, %49, %50, %51, %52, %53, %54, %55, %56, %57, %58, %59, %60, %61, %62, %63, %64, %65, %66, %67, %68, %69, %70, %71, %72, %73, %74, %75, %76, %77, %78, %79, %80, %81, %82, %83, %84, %85, %86, %87, %88, %89, %90, %91, %92, %93, %94, %95}, {%96, %97, %98, %99}, %100, p, 1, 1, %102;\n}\n"
    : "+f"(d[0]), "+f"(d[1]), "+f"(d[2]), "+f"(d[3]), "+f"(d[4]), "+f"(d[5]), "+f"(d[6]), "+f"(d[7]), "+f"(d[8]), "+f"(d[9]), "+f"(d[10]), "+f"(d[11]), "+f"(d[12]), "+f"(d[13]), "+f"(d[14]), "+f"(d[15]), "+f"(d[16]), "+f"(d[17]), "+f"(d[18]), "+f"(d[19]), "+f"(d[20]), "+f"(d[21]), "+f"(d[22]), "+f"(d[23]), "+f"(d[24]), "+f"(d[25]), "+f"(d[26]), "+f"(d[27]), "+f"(d[28]), "+f"(d[29]), "+f"(d[30]), "+f"(d[31]), "+f"(d[32]), "+f"(d[33]), "+f"(d[34]), "+f"(d[35]), "+f"(d[36]), "+f"(d[37]), "+f"(d[38]), "+f"(d[39]), "+f"(d[40]), "+f"(d[41]), "+f"(d[42]), "+f"(d[43]), "+f"(d[44]), "+f"(d[45]), "+f"(d[46]), "+f"(d[47]), "+f"(d[48]), "+f"(d[49]), "+f"(d[50]), "+f"(d[51]), "+f"(d[52]), "+f"(d[53]), "+f"(d[54]), "+f"(d[55]), "+f"(d[56]), "+f"(d[57]), "+f"(d[58]), "+f"(d[59]), "+f"(d[60]), "+f"(d[61]), "+f"(d[62]), "+f"(d[63]), "+f"(d[64]), "+f"(d[65]), "+f"(d[66]), "+f"(d[67]), "+f"(d[68]), "+f"(d[69]), "+f"(d[70]), "+f"(d[71]), "+f"(d[72]), "+f"(d[73]), "+f"(d[74]), "+f"(d[75]), "+f"(d[76]), "+f"(d[77]), "+f"(d[78]), "+f"(d[79]), "+f"(d[80]), "+f"(d[81]), "+f"(d[82]), "+f"(d[83]), "+f"(d[84]), "+f"(d[85]), "+f"(d[86]), "+f"(d[87]), "+f"(d[88]), "+f"(d[89]), "+f"(d[90]), "+f"(d[91]), "+f"(d[92]), "+f"(d[93]), "+f"(d[94]), "+f"(d[95])
    : "r"(a0), "r"(a1), "r"(a2), "r"(a3), "l"(db), "r"(acc), "n"(TB));
}
constexpr uint32_t AR_ACC = 0;
constexpr uint32_t AR_TAB = 0x100000;
constexpr uint32_t AR_PROG = 0x101000;
__host__ __device__ constexpr uint32_t prog_off(int h, int j) { return AR_PROG + h * 128 + j * 4; }
constexpr uint32_t AR_CNT = 0x108000;
constexpr uint32_t AR_QUEUE = 0x109000;
constexpr uint32_t AR_SIZE = 0x10a000;

struct ChainArgs {
  const bf16* mem0;
  const uint2* xh;
  unsigned char *kg, *vg;
  unsigned char* arena;
  uint32_t* dbg;
  uint32_t delay;
  int pfw, margin;
  int tl;
};

namespace ch {
constexpr int OFF_WQ = 0;
constexpr int OFF_X = 81920;
constexpr int OFF_MEM = OFF_X + 40960;
constexpr int OFF_WO = OFF_MEM + 10240;
constexpr int WOK = 8 * 896;
constexpr int OFF_KV = OFF_WO + 10 * WOK;
constexpr int KVB = 5120;
constexpr int OFF_O = OFF_KV + 4 * KVB;
constexpr int OFF_Q = OFF_O + 1024;
constexpr int OFF_S = OFF_O + 3072;
constexpr int OFF_SR = OFF_S + 1280;
constexpr int OFF_BAR = OFF_SR + 1536;
constexpr int SMEM = OFF_BAR + 128 + 1152;
static_assert(SMEM <= 232448, "smem");
constexpr int MB_S = OFF_BAR, MB_O = OFF_BAR + 8, MB_X = OFF_BAR + 16;
constexpr int MB_K = OFF_SR + 1408, MB_V = MB_K + 16, MB_Q = MB_K + 32, MB_R = MB_K + 48;
constexpr int SC_IN = OFF_BAR + 64;
constexpr int SC_MX = OFF_S;
constexpr int SC_W = OFF_BAR + 96;
constexpr int WOS = 448;
enum { B_MEM0 = 1, B_QK, B_SL, B_V, B_O, B_RED, B_X, B_C, B_H, B_MEM1, B_A, B_G };
#ifndef NQ1
#define NQ1 6
#endif
#ifndef NQ0
#define NQ0 4
#endif
#ifndef NP0
#define NP0 4
#endif
#ifndef NWO
#define NWO 5
#endif
#ifndef NWP
#define NWP 4
#endif
#ifndef NB0
#define NB0 2
#endif
#ifndef BBS
#define BBS 100
#endif
#ifndef VSYNC
#define VSYNC 0
#endif
#ifndef XPOS
#define XPOS 0
#endif
#ifndef XPD
#define XPD 300
#endif
#ifndef WOF
#define WOF 0
#endif
#ifndef XBYTES
#define XBYTES 36864
#endif
#ifndef NRT
#define NRT 7
#endif
#ifndef NRF
#define NRF 2
#endif
#ifndef NPM0
#define NPM0 2
#endif
#ifndef NPM1
#define NPM1 2
#endif
#ifndef RSYNC
#define RSYNC 1
#endif
#ifndef PFK
#define PFK 1
#endif
#ifndef PA0
#define PA0 7
#endif
#ifndef PA1
#define PA1 0
#endif
#ifndef PB0
#define PB0 7
#endif
#ifndef PB1
#define PB1 5
#endif
#ifndef PQE
#define PQE 0
#endif
#ifndef XT
#define XT 30
#endif
static_assert(NPM0 >= 2 && NPM1 >= 2, "the K / V blocks live in the last two k-steps of Wo");
}

#ifndef CHAIN_TIMING
#define CHAIN_TIMING 0
#endif
#if CHAIN_TIMING
#ifndef TR0
#define TR0 41
#endif
#ifndef TSMASK
#define TSMASK 0xffff
#endif
#define TSV(i, v) do { if ((TSMASK >> (i)) & 1) asm volatile("st.shared.u32 [%0+%1], %2;" :: "r"(tsb), "n"((i) * 4), "r"(v) : "memory"); } while (0)
#define TS(i) TSV(i, clk32())
#define TS_SETUP() const uint32_t tsb = sb + ((s == TR0 || s == TR0 + 1) ? OFF_BAR + 128 + ((s - TR0) * 12 + warp) * 48 : OFF_SR + 1152)
#else
#define TS(i)
#define TSV(i, v)
#define TS_SETUP()
#endif
#ifndef POLL_DELAY
#define POLL_DELAY 590
#endif
#ifndef XN
#define XN 40
#endif
#ifndef PF0
#define PF0 8
#endif
#ifndef PFS
#define PFS 3
#endif
#ifndef XDELAY
#define XDELAY 0
#endif
#ifndef NOKM
#define NOKM 0
#endif
#ifndef EARLYTRIG
#define EARLYTRIG 0
#endif
#ifndef HINT
#define HINT 0
#endif
#ifndef PFX
#define PFX 3
#endif
#ifndef PFACC
#define PFACC 1
#endif
template <int V> using IC = std::integral_constant<int, V>;
__device__ __forceinline__ uint32_t clk_v() { uint64_t c; asm volatile("mov.u64 %0, %%clock64;" : "=l"(c) :: "memory"); return (uint32_t)c; }
__device__ __forceinline__ int fresh(int x) { int y; asm volatile("shfl.sync.bfly.b32 %0, %1, 0, 0x1f, 0xffffffff;" : "=r"(y) : "r"(x)); return y; }
#define SFENCE2(x, d) asm volatile("{\n.reg .pred p;\nsetp.eq.u32 p, %0, 0x7fffffff;\n@p st.shared.u32 [%0], %1;\n}" :: "r"(x), "r"(d) : "memory")
#define SFENCE(x) asm volatile("{\n.reg .pred p;\nsetp.eq.u32 p, %0, 0x7fffffff;\n@p st.shared.u32 [%0], %0;\n}" :: "r"(x) : "memory")
template <int I> __device__ __forceinline__ void bbfence(uint32_t x) {
  asm volatile("{\n.reg .pred p;\nsetp.eq.u32 p, %0, %1;\nL_%=:\n@p st.volatile.shared.u32 [%0], %0;\n@p bra.uni L_%=;\n}" :: "r"(x), "n"(4 * I) : "memory");
}
__device__ __forceinline__ float uniform_f(float x) { return __uint_as_float(__reduce_max_sync(0xffffffffu, __float_as_uint(x))); }

__device__ __forceinline__ void mma16816h(float (&d)[4], const uint32_t (&a)[4], uint32_t b0, uint32_t b1) {
  asm volatile("mma.sync.aligned.m16n8k16.row.col.f32.f16.f16.f32 {%0,%1,%2,%3}, {%4,%5,%6,%7}, {%8,%9}, {%0,%1,%2,%3};"
               : "+f"(d[0]), "+f"(d[1]), "+f"(d[2]), "+f"(d[3]) : "r"(a[0]), "r"(a[1]), "r"(a[2]), "r"(a[3]), "r"(b0), "r"(b1));
}
__device__ __forceinline__ void mma1688(float (&d)[4], uint32_t a0, uint32_t a1, uint32_t b0) {
  asm volatile("mma.sync.aligned.m16n8k8.row.col.f32.bf16.bf16.f32 {%0,%1,%2,%3}, {%4,%5}, {%6}, {%0,%1,%2,%3};"
               : "+f"(d[0]), "+f"(d[1]), "+f"(d[2]), "+f"(d[3]) : "r"(a0), "r"(a1), "r"(b0));
}
template <int OFF16, int ACC> __device__ __forceinline__ void wgmma_rs32h(float (&d)[16], const uint32_t (&a)[4], uint32_t dlo) {
  asm volatile("{\n.reg .pred p;\n.reg .b32 t;\n.reg .b64 db;\nsetp.ne.b32 p, %22, 0;\nadd.u32 t, %20, %21;\nmov.b64 db, {t, 0x40000040};\n"
    "wgmma.mma_async.sync.aligned.m64n32k16.f32.f16.f16 {%0,%1,%2,%3,%4,%5,%6,%7,%8,%9,%10,%11,%12,%13,%14,%15}, {%16,%17,%18,%19}, db, p, 1, 1, 0;\n}\n"
    : "+f"(d[0]), "+f"(d[1]), "+f"(d[2]), "+f"(d[3]), "+f"(d[4]), "+f"(d[5]), "+f"(d[6]), "+f"(d[7]), "+f"(d[8]), "+f"(d[9]), "+f"(d[10]), "+f"(d[11]),
      "+f"(d[12]), "+f"(d[13]), "+f"(d[14]), "+f"(d[15])
    : "r"(a[0]), "r"(a[1]), "r"(a[2]), "r"(a[3]), "r"(dlo), "n"(OFF16), "n"(ACC));
}
template <int IMM> __device__ __forceinline__ void stsm_x4_t_i(uint32_t a, uint32_t r0, uint32_t r1, uint32_t r2, uint32_t r3) {
  asm volatile("stmatrix.sync.aligned.m8n8.x4.trans.shared.b16 [%0+%5], {%1,%2,%3,%4};" :: "r"(a), "r"(r0), "r"(r1), "r"(r2), "r"(r3), "n"(IMM) : "memory");
}
template <int IMM> __device__ __forceinline__ void stsm_x2_t_i(uint32_t a, uint32_t r0, uint32_t r1) {
  asm volatile("stmatrix.sync.aligned.m8n8.x2.trans.shared.b16 [%0+%3], {%1,%2};" :: "r"(a), "r"(r0), "r"(r1), "n"(IMM) : "memory");
}
template <int IMM> __device__ __forceinline__ void st_async_b32_i(uint32_t a, uint32_t x, uint32_t mb) {
  asm volatile("st.async.weak.shared::cluster.mbarrier::complete_tx::bytes.b32 [%0+%3], %1, [%2];" :: "r"(a), "r"(x), "r"(mb), "n"(IMM) : "memory");
}
template <int IMM> __device__ __forceinline__ void ld_relaxed_v4_if(uint4& v, const void* p, uint32_t c) {
  asm volatile("{\n.reg .pred p;\nsetp.ne.u32 p, %6, 0;\n@p ld.relaxed.gpu.global.v4.u32 {%0,%1,%2,%3}, [%4+%5];\n}"
               : "+r"(v.x), "+r"(v.y), "+r"(v.z), "+r"(v.w) : "l"(p), "n"(IMM), "r"(c) : "memory");
}
template <int IMM> __device__ __forceinline__ uint32_t lds32_i(uint32_t a) {
  uint32_t v; asm volatile("ld.shared.u32 %0, [%1+%2];" : "=r"(v) : "r"(a), "n"(IMM) : "memory"); return v;
}
__device__ __forceinline__ void sts32(uint32_t a, uint32_t v) { asm volatile("st.shared.u32 [%0], %1;" :: "r"(a), "r"(v) : "memory"); }
__device__ __forceinline__ uint32_t pack_f16(float lo, float hi) {
  uint32_t d; asm("cvt.rn.f16x2.f32 %0, %1, %2;" : "=r"(d) : "f"(hi), "f"(lo)); return d;
}
__device__ __forceinline__ uint32_t amax_bf2(uint32_t a, uint32_t b) { uint32_t d; asm("max.xorsign.abs.bf16x2 %0, %1, %2;" : "=r"(d) : "r"(a), "r"(b)); return d; }
__device__ __forceinline__ uint32_t amax_h2(uint32_t a, uint32_t b) { uint32_t d; asm("max.xorsign.abs.f16x2 %0, %1, %2;" : "=r"(d) : "r"(a), "r"(b)); return d; }
__device__ __forceinline__ uint32_t amax_fold(uint32_t m) { return __reduce_max_sync(0xffffffffu, max(m & 0x7fffu, (m >> 16) & 0x7fffu)); }
__device__ __forceinline__ int wscale_exp(uint32_t m) { return min(141 - (int)(m >> 7), 100); }
__device__ __forceinline__ float exp2i(int e) { return __uint_as_float((uint32_t)(e + 127) << 23); }
__device__ __forceinline__ uint32_t bf2_to_h2(uint32_t w, float sc) { return pack_f16(bf_lo(w) * sc, bf_hi(w) * sc); }
__device__ __forceinline__ void bf2_to_h2_inplace(uint32_t& w, uint32_t sc2) {
  asm volatile("{\n.reg .b32 t, lo, hi;\nmul.rn.bf16x2 t, %0, %1;\nshl.b32 lo, t, 16;\nand.b32 hi, t, 0xffff0000;\ncvt.rn.f16x2.f32 %0, hi, lo;\n}" : "+r"(w) : "r"(sc2));
}
__device__ __forceinline__ void prefetch_l2(const void* p, uint32_t bytes) { asm volatile("cp.async.bulk.prefetch.L2.global [%0], %1;" :: "l"(p), "r"(bytes) : "memory"); }
__device__ __forceinline__ void prefetch_tma_2d(const CUtensorMap* tm, int c0, int c1) {
  asm volatile("cp.async.bulk.prefetch.tensor.2d.L2.global [%0, {%1, %2}];" :: "l"(tm), "r"(c0), "r"(c1) : "memory");
}
__host__ __device__ constexpr uint32_t acc_voff(int v) { return v < 4 ? v * 1024u : (v == 4 ? 128u : 3072u + 128u); }
__device__ __forceinline__ int unit28(int i) { return i == 3 ? 54 : 14 * i; }
__device__ __forceinline__ int unit24(int i) { return i < 2 ? 48 - 6 * i : 56 + 6 * i; }
__host__ __device__ constexpr uint32_t hint_off(int j) { return 1024 + 128 + j * 8192; }
__device__ __forceinline__ uint32_t acc_step(int s) { return (s >> 1) * 32768 + (s & 1) * 512; }
__device__ __forceinline__ uint32_t acc_lane(int i, int lane) { return ((lane >> 3) & 1) * 256 + (lane >> 4) * 4096 + i * 8192 + (lane & 7) * 16; }

__device__ __forceinline__ uint32_t ld_acquire_u32(const void* p) {
  uint32_t v; asm volatile("ld.acquire.gpu.global.u32 %0, [%1];" : "=r"(v) : "l"(p) : "memory"); return v;
}
template <int R> __device__ __forceinline__ void ln_rows(const uint2 (&xw)[R][5], int row0, int lane, bf16* __restrict__ xn, uint2* __restrict__ xh) {
  float v[R][20], s[R], q[R];
#pragma unroll
  for (int r = 0; r < R; r++) {
    s[r] = 0.f; q[r] = 0.f;
#pragma unroll
    for (int i = 0; i < 5; i++) { v[r][4 * i] = bf_lo(xw[r][i].x); v[r][4 * i + 1] = bf_hi(xw[r][i].x); v[r][4 * i + 2] = bf_lo(xw[r][i].y); v[r][4 * i + 3] = bf_hi(xw[r][i].y); }
#pragma unroll
    for (int i = 0; i < 5; i++) s[r] += (v[r][4 * i] + v[r][4 * i + 1]) + (v[r][4 * i + 2] + v[r][4 * i + 3]);
  }
#pragma unroll
  for (int o = 16; o; o >>= 1)
#pragma unroll
    for (int r = 0; r < R; r++) s[r] += __shfl_xor_sync(0xffffffffu, s[r], o);
#pragma unroll
  for (int r = 0; r < R; r++) {
    s[r] *= 1.f / cfg::DM;
#pragma unroll
    for (int i = 0; i < 10; i++) { const float d = v[r][2 * i] - s[r], e = v[r][2 * i + 1] - s[r]; q[r] += d * d + e * e; }
  }
#pragma unroll
  for (int o = 16; o; o >>= 1)
#pragma unroll
    for (int r = 0; r < R; r++) q[r] += __shfl_xor_sync(0xffffffffu, q[r], o);
#pragma unroll
  for (int r = 0; r < R; r++) {
    const int row = row0 + r;
    const float mb = bf16r(s[r]), var = bf16r(q[r] * (1.f / cfg::DM));
    float sd; asm("sqrt.approx.f32 %0, %1;" : "=f"(sd) : "f"(bf16r(var + 1e-5f)));
    const float inv = rcpf(bf16r(sd));
#pragma unroll
    for (int i = 0; i < 5; i++) {
      float y[4];
#pragma unroll
      for (int e = 0; e < 4; e++) y[e] = v[r][4 * i + e] - mb;
      bf16r2(y[0], y[1]); bf16r2(y[2], y[3]);
      const uint32_t w0 = pack_bf16(y[0] * inv, y[1] * inv), w1 = pack_bf16(y[2] * inv, y[3] * inv);
      *(uint2*)(xn + (size_t)row * cfg::DM + i * 128 + lane * 4) = make_uint2(w0, w1);
      if (xh) xh[(((size_t)(row >> 5) * 10 + 2 * i + (lane >> 4)) * 32 + (row & 31)) * 16 + ((((lane >> 1) & 7) ^ (row & 7)) << 1) + (lane & 1)] =
          make_uint2(pack_f16(bf_lo(w0), bf_hi(w0)), pack_f16(bf_lo(w1), bf_hi(w1)));
    }
  }
}

__global__ void __cluster_dims__(3, 1, 1) __launch_bounds__(384, 1) chain_kernel(const ChainArgs a, const __grid_constant__ CUtensorMap tmWq,
    const __grid_constant__ CUtensorMap tmWk, const __grid_constant__ CUtensorMap tmWv, const __grid_constant__ CUtensorMap tmWo) {
  using namespace ch;
  extern __shared__ __align__(1024) unsigned char smem_raw[];
  const uint32_t sb = smem_u32(smem_raw);
  const int warp = __shfl_sync(0xffffffffu, (int)threadIdx.x >> 5, 0);
  const int lane = __shfl_sync(0xffffffffu, (int)threadIdx.x & 31, threadIdx.x & 31);
  const int cta = blockIdx.x, h = cta / 3, j = cta % 3;
  const int g = lane >> 2, q4 = lane & 3, r8 = lane & 7, m4 = lane >> 3;
  unsigned char* const arena = a.arena;
  if (sb & 1023u) __trap();
  TL_BEGIN(a.tl);
  const int col0 = j == 0 ? 0 : (j == 1 ? 224 : 432);
  auto stage_w = [&](const CUtensorMap* tm, uint32_t dst, uint32_t mb, int half) {
    mbar_expect_tx(mb + 8 * half, 40960);
    tma_load_2d(dst + half * 40960, tm, h * cfg::DH + j * 64, half * 320, mb + 8 * half);
    tma_load_2d(dst + half * 40960 + 20480, tm, h * cfg::DH + j * 64, half * 320 + 160, mb + 8 * half);
  };
  if (threadIdx.x == 256) {
    for (int i = 0; i < 9; i++) mbar_init(sb + MB_K + 8 * i, 1);
    mbar_init(sb + MB_S, 1); mbar_init(sb + MB_O, 1); mbar_init(sb + MB_X, 1);
    asm volatile("fence.mbarrier_init.release.cluster;" ::: "memory");
    if (EARLYTRIG) {
      asm volatile("griddepcontrol.wait;" ::: "memory");
      asm volatile("griddepcontrol.launch_dependents;" ::: "memory");
    }
    for (int i = 0; i < 2; i++) { stage_w(&tmWk, sb + OFF_WQ, sb + MB_K, i); stage_w(&tmWv, sb + OFF_WO, sb + MB_V, i); }
    sts32(sb + SC_W, 0); sts32(sb + SC_W + 4, 0); sts32(sb + SC_W + 8, 0); sts32(sb + SC_IN + 12, 0); sts32(sb + SC_IN + 20, 0);
    mbar_expect_tx(sb + MB_S, 1280); mbar_expect_tx(sb + MB_O, 2048);
  }
  __syncthreads();
  asm volatile("barrier.cluster.arrive.relaxed.aligned;" ::: "memory");
  const uint32_t d1 = mapa_u32(sb, (j + 1) % 3) - sb, d2 = mapa_u32(sb, (j + 2) % 3) - sb;

  if (warp >= 8) {
    asm volatile("setmaxnreg.dec.sync.aligned.u32 40;");
    const int hw = warp - 8, ht = hw * 32 + lane;
    const bool lead = ht == 0;
    auto stage_wo = [&](int i) {
      mbar_expect_tx(sb + MB_R + 8 * i, 64 * WOS);
      tma_load_2d(sb + OFF_WO + i * 64 * WOS, &tmWo, col0, h * cfg::DH + ((i + j) % 3) * 64, sb + MB_R + 8 * i);
    };
    const unsigned char* xg = (const unsigned char*)a.xh;
    auto issue_x = [&](int s) { mbar_expect_tx(sb + MB_X, 40960); bulk_g2s(sb + OFF_X, xg + (size_t)s * 40960, 40960, sb + MB_X); };
    uint4 v[5];
#pragma unroll
    for (int i = 0; i < 5; i++) { const int c = ht + 128 * i; v[i] = ld_relaxed_v4(a.mem0 + (c & 7) * cfg::DM + (c >> 3) * 8); }
    if (hw == 2) {
      asm volatile("griddepcontrol.wait;" ::: "memory");
      asm volatile("griddepcontrol.launch_dependents;" ::: "memory");
      if (lane == 0) issue_x(0);
    }
    if (hw == 0) {
      bar_sync(B_QK, 160); if (lane == 0) stage_w(&tmWq, sb + OFF_WQ, sb + MB_Q, 0);
      bar_sync(B_SL, 160); if (lane == 0) stage_w(&tmWq, sb + OFF_WQ, sb + MB_Q, 1);
    }
    if (hw == 1) {
      bar_sync(B_V, 160); if (lane == 0) stage_wo(0);
      bar_sync(B_O, 160); if (lane == 0) { stage_wo(1); stage_wo(2); }
    }
    __syncwarp();
    {
      uint32_t m = 0;
#pragma unroll
      for (int i = 0; i < 5; i++) {
        m = amax_bf2(amax_bf2(m, amax_bf2(v[i].x, v[i].y)), amax_bf2(v[i].z, v[i].w));
      }
      m = amax_fold(m);
      if (lane == 0) sts32(sb + SC_MX + hw * 4, m);
      bar_sync(B_H, 128);
      const uint4 mm = lds128(sb + SC_MX);
      const int se = max(wscale_exp(max(max(mm.x, mm.y), max(mm.z, mm.w))), -100);
      const float sc = exp2i(se);
#pragma unroll
      for (int i = 0; i < 5; i++) {
        const int c = ht + 128 * i, t = c & 7, chn = c >> 3;
        sts128(sb + OFF_MEM + chn * 128 + ((t ^ (2 * (chn & 3))) << 4), bf2_to_h2(v[i].x, sc), bf2_to_h2(v[i].y, sc), bf2_to_h2(v[i].z, sc), bf2_to_h2(v[i].w, sc));
      }
      if (lead) { sts32(sb + SC_IN, __float_as_uint(exp2i(-se))); sts32(sb + SC_IN + 4, 0x7800u); }
    }
    {
      const uint32_t p0 = sb + OFF_WQ + hw * 2048 + lane * 16;
      uint32_t m = 0;
#pragma unroll 1
      for (int i = 0; i < 10; i++) {
        if (i == 0 || i == 5) mbar_wait(sb + MB_Q + (i ? 8 : 0), 0);
        uint32_t r[4][4];
        static_for<0, 4>([&](auto K) { ldsm_x4_i<K.value * 512>(r[K.value], p0 + i * 8192); });
#pragma unroll
        for (int k = 0; k < 4; k++) m = amax_bf2(amax_bf2(m, amax_bf2(r[k][0], r[k][1])), amax_bf2(r[k][2], r[k][3]));
      }
      m = amax_fold(m);
      if (lane == 0) asm volatile("red.shared.max.u32 [%0], %1;" :: "r"(sb + SC_W + 8), "r"(m) : "memory");
      bar_sync(B_H, 128);
      const uint32_t sc = (uint32_t)(wscale_exp(lds32_i<SC_W + 8>(sb)) + 127) * 0x00800080u;
#pragma unroll 1
      for (int i = 0; i < 10; i++) {
        uint32_t r[4][4];
        static_for<0, 4>([&](auto K) { ldsm_x4_i<K.value * 512>(r[K.value], p0 + i * 8192); });
#pragma unroll
        for (int k = 0; k < 4; k++) {
          bf2_to_h2_inplace(r[k][0], sc); bf2_to_h2_inplace(r[k][1], sc); bf2_to_h2_inplace(r[k][2], sc); bf2_to_h2_inplace(r[k][3], sc);
          stsm_x4(p0 + i * 8192 + k * 512, r[k][0], r[k][1], r[k][2], r[k][3]);
        }
      }
    }
    bar_sync(0, 384);
    if (lead) st_relaxed_u32(arena + AR_TAB + cta * 4, 0x80000000u | (lds32_i<SC_W>(sb) << 15) | lds32_i<SC_W + 4>(sb));
    asm volatile("barrier.cluster.wait.aligned;" ::: "memory");
    bar_sync(B_MEM0, 256); bar_sync(B_MEM1, 256);
    {
      uint32_t v0, v1, v2; int spin = 0;
      do {
        v0 = ld_relaxed_u32(arena + AR_TAB + lane * 4); v1 = ld_relaxed_u32(arena + AR_TAB + 128 + lane * 4); v2 = ld_relaxed_u32(arena + AR_TAB + 256 + lane * 4);
      } while (__any_sync(0xffffffffu, ((v0 & v1 & v2) >> 31) == 0) && ++spin < SPIN_LIMIT);
      const uint32_t mv = (max(max(v0, v1), v2) >> 15) & 0x7fffu, mo = max(max(v0 & 0x7fffu, v1 & 0x7fffu), v2 & 0x7fffu);
      sts32(sb + SC_IN + 8 + (lane & 1) * 16, 15 - ((__reduce_max_sync(0xffffffffu, mv) >> 7) + (__reduce_max_sync(0xffffffffu, mo) >> 7) - 252 + 22));
    }

    auto store_kv = [&](int s) {
      const size_t o = ((size_t)s * 96 + cta) * KVB; const uint32_t src = sb + OFF_KV + (s & 1) * (2 * KVB);
      fence_proxy_async(); bulk_s2g(a.kg + o, src, KVB); bulk_s2g(a.vg + o, src + KVB, KVB); bulk_commit();
    };
    const int cb28 = unit28(hw), du = (unit24(hw) - cb28) * 128;
    int ln = lane;
    uint32_t hist = 0;
    auto stamp = [&](int s) {
      asm volatile("{\n.reg .pred p;\n.reg .u32 t;\nsetp.eq.u32 p, %1, 32;\nmov.u32 t, %%globaltimer_lo;\nor.b32 t, t, 1;\n@p st.relaxed.gpu.global.u32 [%0], t;\n}"
                   :: "l"(arena + (AR_ACC + acc_step(s) + hint_off(j) + h * 4)), "r"(hw * 32 + ln) : "memory");
    };
    if (HINT) stamp(0);
#ifdef TIMELINE
    if (cta == 0 && lead) { g_tl2[(a.tl >= 12) * 128 + 0] = clock64(); g_tl2[(a.tl >= 12) * 128 + 1] = gtime(); }
#endif
#pragma unroll 1
    for (int s = 0; s < cfg::NSEG; s++) {
      TS_SETUP();
      const bool last = s == cfg::NSEG - 1;
      if (ln == 0) {
        if (hw == 2 && !last) issue_x(s + 1);
        if (hw == 0 && s > 0) store_kv(s - 1);
        if (PFX && hw == 3 && cta < 80 && s + PFX < cfg::NSEG) prefetch_l2(xg + (size_t)(s + PFX) * 40960 + cta * 512, 512);
        if (hw == 3 && s >= a.pfw && s < a.pfw + 8) prefetch_tma_2d((s - a.pfw) & 1 ? &tmWv : &tmWk, h * cfg::DH + j * 64, ((s - a.pfw) >> 1) * 160);
        if (PFACC && hw == 1 && s + PFACC < cfg::NSEG - 1)
          asm volatile("prefetch.global.L2 [%0];" :: "l"(arena + (AR_ACC + acc_step(s + PFACC) + acc_lane(cta / 24, (cta & 3) * 8) + acc_voff((cta % 24) >> 2))) : "memory");
        if (HINT && hw == 1 && cta < 3 && s + 1 < cfg::NSEG - 1) asm volatile("prefetch.global.L2 [%0];" :: "l"(arena + (AR_ACC + acc_step(s + 1) + hint_off(j))) : "memory");
      }
      __syncwarp();
      if (last) break;
      const uint32_t kv = (s & 1) * (2 * KVB);
      ln = fresh(ln);
      uint32_t kb0[4], kb1[4];
      { const uint32_t ka = sb + kv + hw * 128 + (ln >> 3) * 640 + (ln & 7) * 16; ldsm_x4_i<OFF_KV>(kb0, ka); ldsm_x4_i<OFF_KV + 2560>(kb1, ka); }
      const uint32_t l16 = sb + ln * 16, s8 = sb + ln * 8, xs = s8 + hw * 256, xr = sb + ln * 4 + (hw >> 1) * 512 + (hw & 1) * 128;
      TS(1);
      bar_sync(B_QK, 384);
      {
        uint32_t q0[4], q1[4], q2[4], q3[4];
        float sa[4] = {0, 0, 0, 0}, sc2[4] = {0, 0, 0, 0};
        ldsm_x4_i<OFF_Q>(q0, l16); ldsm_x4_i<OFF_Q + 1024>(q2, l16); ldsm_x4_i<OFF_Q + 512>(q1, l16);
        bar_arrive(B_A, 288);
        ldsm_x4_i<OFF_Q + 1536>(q3, l16);
        mma16816(sa, q0[0], q0[1], q0[2], q0[3], kb0[0], kb0[1]);
        mma16816(sc2, q2[0], q2[1], q2[2], q2[3], kb1[0], kb1[1]);
        mma16816(sa, q1[0], q1[1], q1[2], q1[3], kb0[2], kb0[3]);
        mma16816(sc2, q3[0], q3[1], q3[2], q3[3], kb1[2], kb1[3]);
        const float x0 = (sa[0] + sa[2]) + (sc2[0] + sc2[2]), x1 = (sa[1] + sa[3]) + (sc2[1] + sc2[3]);
        const uint32_t xp = pack_bf16(x0, x1);
        st_async_b32_i<OFF_SR + 256>(xr + d1, xp, sb + MB_S + d1);
        st_async_b32_i<OFF_SR>(xr + d2, xp, sb + MB_S + d2);
        sts64_i<OFF_S>(xs, __float_as_uint(x0), __float_as_uint(x1));
      }
      TS(3);
      bar_sync(B_SL, 256);
      float t0[4], t1[4], t2[4] = {0, 0, 0, 0};
      float osc;
      {
        const uint4 si = lds128_i<SC_IN>(sb + 16 * (s & 1));
        { const uint2 x = lds64_i<OFF_S>(s8), y = lds64_i<OFF_S + 256>(s8); t0[0] = __uint_as_float(x.x); t0[1] = __uint_as_float(x.y); t0[2] = __uint_as_float(y.x); t0[3] = __uint_as_float(y.y); }
        { const uint2 x = lds64_i<OFF_S + 512>(s8), y = lds64_i<OFF_S + 768>(s8); t1[0] = __uint_as_float(x.x); t1[1] = __uint_as_float(x.y); t1[2] = __uint_as_float(y.x); t1[3] = __uint_as_float(y.y); }
        { const uint2 x = lds64_i<OFF_S + 1024>(s8); t2[0] = __uint_as_float(x.x); t2[1] = __uint_as_float(x.y); }
        const int em = (int)(si.y >> 10) - 14 + (int)(si.x >> 23) - 127;
        osc = exp2i(max(min((int)si.z - max(em, 1), 100), -100));
      }
      const uint32_t xo = sb + hw * 256 + (ln & 2) * 64 + (ln >> 2) * 16 + (ln & 1) * 8;
      const uint32_t eye = ((ln >> 3) == (ln & 3)) ? ((ln & 4) ? 0x3f800000u : 0x3f80u) : 0u;
      mbar_spin(sb + MB_S, s & 1);
      TS(4);
      uint32_t v0[4], v1[4], vm[2];
      {
        uint32_t r0[4], r1[4], r2[4];
        ldsm_x4_i<OFF_SR>(r0, l16); ldsm_x4_i<OFF_SR + 512>(r1, l16); ldsm_x4_i<OFF_SR + 1024>(r2, l16);
        mma16816(t0, r0[0], r0[1], r0[2], r0[3], eye, eye);
        mma16816(t1, r1[0], r1[1], r1[2], r1[3], eye, eye);
        mma16816(t2, r2[0], r2[1], r2[2], r2[3], eye, eye);
      }
      float sc[10] = {t0[0], t0[1], t0[2], t0[3], t1[0], t1[1], t1[2], t1[3], t2[0], t2[1]};
      const float cs = 0.07216878364870322f * 1.4426950408889634f;
      float mx = fmaxf(fmaxf(fmaxf(sc[0], sc[1]), fmaxf(sc[2], sc[3])), fmaxf(fmaxf(sc[4], sc[5]), fmaxf(sc[6], sc[7])));
      mx = fmaxf(mx, fmaxf(sc[8], sc[9]));
      {
        const float m1 = __shfl_xor_sync(0xffffffffu, mx, 1), m2 = __shfl_xor_sync(0xffffffffu, mx, 2), m3 = __shfl_xor_sync(0xffffffffu, mx, 3);
        SFENCE2(l16, __float_as_uint(mx));
        ldsm_x4_t_i<OFF_KV + KVB>(v0, l16 + (kv + hw * 1280)); ldsm_x4_t_i<OFF_KV + KVB + 640>(v1, l16 + (kv + hw * 1280));
        bar_sync(B_V, 256);
        bar_arrive(B_G, 384);
        ldsm_x2_t(vm, l16 + (ln & 8) * 64 + (kv + hw * 1280 + OFF_KV + KVB + 512));
        mx = fmaxf(fmaxf(mx, m1), fmaxf(m2, m3));
      }
      const float mo = mx * cs;
#pragma unroll
      for (int i = 0; i < 10; i++) sc[i] = ex2f(fmaf(sc[i], cs, -mo));
      const uint32_t p0 = pack_bf16(sc[0], sc[1]), p1 = pack_bf16(sc[2], sc[3]), p2 = pack_bf16(sc[4], sc[5]), p3 = pack_bf16(sc[6], sc[7]), p4 = pack_bf16(sc[8], sc[9]);
      TS(5);
      float oa[4] = {0, 0, 0, 0}, ob[4] = {0, 0, 0, 0}, oc[4] = {0, 0, 0, 0}, od[4] = {0, 0, 0, 0}, rs[4] = {0, 0, 0, 0};
      const uint32_t ones = 0x3f803f80u;
      mma16816(rs, p0, p2, p1, p3, ones, ones);
      mma16816(oc, p0, p2, p1, p3, v0[2], v0[3]);
      mma16816(od, p0, p2, p1, p3, v1[2], v1[3]);
      mma16816(oa, p0, p2, p1, p3, v0[0], v0[1]);
      mma16816(ob, p0, p2, p1, p3, v1[0], v1[1]);
      mma1688(rs, p4, 0u, ones);
      mma1688(oa, p4, 0u, vm[0]);
      mma1688(ob, p4, 0u, vm[1]);
      const float inv = rcpf(rs[0] + rs[2]) * osc;
      {
        const uint32_t y0 = pack_bf16((oa[0] + oc[2]) * inv, (oa[1] + oc[3]) * inv), y1 = pack_bf16((ob[0] + od[2]) * inv, (ob[1] + od[3]) * inv);
        st_async_v2_i<OFF_O + 2048>(xo + d1, y0, y1, sb + MB_O + d1);
        st_async_v2_i<OFF_O + 1024>(xo + d2, y0, y1, sb + MB_O + d2);
        sts64_i<OFF_O>(xo, y0, y1);
      }
      bar_arrive(B_O, 384);
      TS(6);
      if (ln == 0) {
        if (hw == 0) {
          bulk_wait<0>();
          if ((s & 3) == 0 && s > 0) {
            st_relaxed_u32(arena + (prog_off(h, j) + ln), s);
          }
        }
        if (hw == 3) { mbar_expect_tx(sb + MB_S, 1280); sts64_i<SC_IN>(sb + 16 * ((s + 1) & 1), 0x7f000000u - __float_as_uint(osc), 0u); }
      }
      __syncwarp();
      ln = fresh(ln);
      auto mslot = [&](int c) -> uint32_t { return sb + OFF_MEM + c * 128 + (((ln >> 2) ^ (2 * (c & 3))) << 4); };
      const int lq = ln & 3;
      const uint32_t ma = mslot(cb28 + lq), mb_ = mslot(cb28 + (lq >> 1)) + (lq & 1) * 8;
      const unsigned char* gp = arena + (AR_ACC + acc_lane(hw, ln) + acc_step(s));
      const bool odd = ln & 1;
      uint32_t delay = a.delay + ((hist & 2) ? a.margin : 0);
      if (HINT) {
        const unsigned char* hp = arena + (AR_ACC + acc_step(s) + ln * 4);
        const uint32_t t0 = ld_relaxed_u32(hp + hint_off(0)), t1 = ld_relaxed_u32(hp + hint_off(1)), t2 = ld_relaxed_u32(hp + hint_off(2));
        const uint32_t r = __shfl_sync(0xffffffffu, t0, h);
        const int t = (t0 & t1 & t2 & 1u) ? max(max((int)(t0 - r), (int)(t1 - r)), (int)(t2 - r)) : 1000;
        delay += min(max(__reduce_max_sync(0xffffffffu, t) - __shfl_sync(0xffffffffu, t, h) - a.margin, 0), 1000) * 7 / 4;
      }
      SFENCE(ma);
      bar_sync(B_RED, 384);
      SFENCE(mb_);
      const uint32_t tw = clk_v();
      TSV(7, tw);
      if (ln == 0 && hw == 3) mbar_expect_tx(sb + MB_O, 2048);
      __syncwarp();
      while (clk_v() - tw < delay) {}
      TS(8);
      uint4 v[6];
      int spin = 0;
      const uint32_t cm = odd ? 0x5000u : 0u;
      do {
        static_for<0, 6>([&](auto I) { v[I.value] = ld_relaxed_v4_i<acc_voff(I.value)>(gp); });
      } while (__any_sync(0xffffffffu, (~((v[0].w & v[1].w & v[2].w) & (v[3].w & v[4].w & v[5].w)) & cm) != 0) && ++spin < SPIN_LIMIT);
      v[0].w = odd ? v[3].x : v[0].w; v[1].w = odd ? v[3].y : v[1].w; v[2].w = odd ? v[3].z : v[2].w; v[3].w = odd ? 0u : v[3].w;
      sts128_i<0>(ma, v[0].x, v[0].y, v[0].z, v[0].w);
      sts128_i<512>(ma, v[1].x, v[1].y, v[1].z, v[1].w);
      sts128_i<1024>(ma, v[2].x, v[2].y, v[2].z, v[2].w);
      sts128_i<0>(ma + du, v[4].x, v[4].y, v[4].z, v[5].z);
      sts64_i<512>(mb_ + du, v[5].x, v[5].y);
      if (!odd) sts128_i<1536>(mb_, v[3].x, v[3].y, v[3].z, v[3].w);
      hist = hist * 2 + (spin != 0);
      TSV(11, spin);
#ifdef TIMELINE
      if (spin && ln == 0) atomicAdd(&g_tl2[(a.tl >= 12) * 128 + 4], 1ull);
#endif
      TS(10);
      bar_sync(B_MEM0, 256); bar_sync(B_MEM1, 256);
      uint32_t m = lds32_i<SC_IN + 12>(sb);
      if (HINT) stamp(s + 1);
      uint32_t m2 = m;
      static_for<0, 3>([&](auto I) { m = amax_h2(amax_h2(amax_h2(amax_h2(m, v[I.value].x), v[I.value].y), v[I.value].z), v[I.value].w); });
      static_for<3, 6>([&](auto I) { m2 = amax_h2(amax_h2(amax_h2(m2, v[I.value].x), v[I.value].y), v[I.value].z); });
      m = amax_fold(amax_h2(amax_h2(m2, v[3].w), m));
      if (ln == 0) asm volatile("red.shared.max.u32 [%0], %1;" :: "r"(sb + SC_IN + 4 + 16 * ((s + 1) & 1)), "r"(m) : "memory");
    }
    bar_sync(B_RED, 384);
    if (hw == 0 && ln == 0) {
      store_kv(cfg::NSEG - 1);
      bulk_wait<0>();
      st_relaxed_u32(arena + prog_off(h, j), cfg::NSEG);
    }
    __syncwarp();
#ifdef TIMELINE
    if (cta == 0 && hw == 0 && ln == 0) { g_tl2[(a.tl >= 12) * 128 + 2] = clock64(); g_tl2[(a.tl >= 12) * 128 + 3] = gtime(); }
#endif
    TL_END(a.tl);
    asm volatile("barrier.cluster.arrive.relaxed.aligned; barrier.cluster.wait.aligned;" ::: "memory");
  } else {
    asm volatile("setmaxnreg.inc.sync.aligned.u32 232;");
    const int wi = warp & 3, hf = warp >> 2, tid = warp * 32 + lane;
    uint32_t w[40][4];
    uint32_t wqa;
    { const int mrow = r8 + ((lane >> 4) << 3), mch = 2 * wi + (m4 & 1); wqa = sb + mrow * 128 + ((mch ^ r8) << 4); }
    {
      const uint32_t wa = wqa + (hf ? OFF_WO : OFF_WQ);
      mbar_wait(sb + (hf ? MB_V : MB_K), 0);
      static_for<0, 20>([&](auto K) { ldsm_x4_t_i<K.value * 2048>(w[K.value], wa); });
      bar_arrive(hf ? B_V : B_QK, 160);
      mbar_wait(sb + (hf ? MB_V : MB_K) + 8, 0);
      static_for<20, 40>([&](auto K) { ldsm_x4_t_i<K.value * 2048>(w[K.value], wa); });
      bar_arrive(hf ? B_O : B_SL, 160);
      SFENCE(wa);
    }
    float iw, iq;
    {
      uint32_t m = 0;
#pragma unroll
      for (int k = 0; k < 40; k++) m = amax_bf2(amax_bf2(m, amax_bf2(w[k][0], w[k][1])), amax_bf2(w[k][2], w[k][3]));
      m = amax_fold(m);
      if (hf && lane == 0) asm volatile("red.shared.max.u32 [%0], %1;" :: "r"(sb + SC_W), "r"(m) : "memory");
      const int e = wscale_exp(m);
      const uint32_t sc = (uint32_t)(e + 127) * 0x00800080u; iw = exp2i(-e);
#pragma unroll
      for (int k = 0; k < 40; k++) { bf2_to_h2_inplace(w[k][0], sc); bf2_to_h2_inplace(w[k][1], sc); bf2_to_h2_inplace(w[k][2], sc); bf2_to_h2_inplace(w[k][3], sc); }
    }
    uint32_t x0[8];
    {
      float xa[16];
      const uint32_t dlo = (((sb + OFF_X) & 0x3FFFF) >> 4) | (1u << 16);
      mbar_wait(sb + MB_X, 0);
      wgmma_fence();
      static_for<0, 40>([&](auto K) { constexpr int k = K.value; wgmma_rs32h<((k >> 2) * 4096 + (k & 3) * 32) / 16, (k != 0)>(xa, w[k], dlo); });
      wgmma_commit();
      wgmma_wait<0>();
#pragma unroll
      for (int i = 0; i < 8; i++) x0[i] = pack_bf16(xa[2 * i] * iw, xa[2 * i + 1] * iw);
    }
    const bool t28 = j == 0 || warp < 4;
    const int bi = j == 0 ? hf : (warp < 4 ? j + 1 : 2 * (j - 1) + ((warp - 4) >> 1)), bv = t28 ? wi : 4 + (warp & 1);
    uint32_t wo1 = sb + OFF_WO + warp * 896 + lane * 16, wo2;
    {
      const int cb = (t28 ? unit28(bi) : unit24(bi)) - col0 / 8;
      uint32_t cp[4];
#pragma unroll
      for (int wd = 0; wd < 4; wd++) {
        int c, p;
        if (bv < 3) { c = 4 * bv + q4; p = wd; }
        else if (bv == 3) { if (q4 & 1) { c = 4 * (wd % 3) + q4; p = 3; } else { c = 12 + (q4 >> 1); p = wd; } }
        else if (bv == 4) { c = q4; p = wd; }
        else { if (wd < 2) { c = 4 + (q4 >> 1); p = 2 * (q4 & 1) + wd; } else { c = q4; p = 3; } }
        cp[wd] = sb + OFF_WO + ((g & 1) + (g & 2) * 4 + (g >> 2) * 2) * WOS + (cb + c) * 16 + p * 4;
      }
      const int cidx = (r8 & 1) + ((r8 >> 2) << 1);
      wo2 = sb + OFF_WO + warp * 896 + ((m4 & 1) ? 768 + (m4 >> 1) * 64 + cidx * 16 : 512 + (m4 >> 1) * 128 + r8 * 16);
      const bool dump = (m4 & 1) && (r8 & 2);
      uint32_t mo = 0;
      const bool regular = bv < 3 || bv == 4;
#pragma unroll 1
      for (int i = 0; i < 3; i++) {
        uint32_t x[4][4], y[4][4];
        const uint32_t o = i * 4 * WOK;
        mbar_wait(sb + MB_R + 8 * i, 0);
        if (regular) {
          static_for<0, 4>([&](auto K) {
            constexpr int kk = K.value;
            const uint4 u = lds128_i<kk * WOK>(cp[0] + o), v = lds128_i<kk * WOK + 4 * WOS>(cp[0] + o);
            x[kk][0] = u.x; x[kk][1] = u.y; x[kk][2] = u.z; x[kk][3] = u.w; y[kk][0] = v.x; y[kk][1] = v.y; y[kk][2] = v.z; y[kk][3] = v.w;
          });
        } else {
          static_for<0, 4>([&](auto K) {
            constexpr int kk = K.value;
#pragma unroll
            for (int wd = 0; wd < 4; wd++) { x[kk][wd] = lds32_i<kk * WOK>(cp[wd] + o); y[kk][wd] = lds32_i<kk * WOK + 4 * WOS>(cp[wd] + o); }
          });
        }
        bar_sync(B_C, 256);
        static_for<0, 4>([&](auto K) {
          constexpr int kk = K.value;
#pragma unroll
          for (int wd = 0; wd < 4; wd++) mo = amax_bf2(mo, amax_bf2(x[kk][wd], y[kk][wd]));
          stsm_x4_t_i<kk * WOK>(wo1 + o, x[kk][0], x[kk][1], y[kk][0], y[kk][1]);
          stsm_x4_t_i<0>(dump ? sb + OFF_S + 512 + lane * 16 : wo2 + o + kk * WOK, x[kk][2], x[kk][3], y[kk][2], y[kk][3]);
        });
      }
      mo = amax_fold(mo);
      if (lane == 0) asm volatile("red.shared.max.u32 [%0], %1;" :: "r"(sb + SC_W + 4), "r"(mo) : "memory");
    }
    __syncwarp();
    auto run = [&](auto HF) {
    constexpr int hf = HF.value;
    uint32_t mema, sta, l16 = sb + lane * 16;
    uint32_t rq[hf ? NQ1 : NQ0][4];
    auto step_addr = [&](uint32_t kv) {
      const int lr = (l16 >> 4) & 7, lm = (l16 >> 7) & 3;
      mema = l16 ^ (lm << 5);
      sta = sb + lr * 16 + (lm < 2 ? OFF_Q + wi * 512 + hf * 128 + lm * 256 : OFF_KV + kv + 512 + (2 * wi + lm - 2) * 640);
    };
    auto x_gemm = [&](uint32_t ph, [[maybe_unused]] uint32_t tsb) {
      float xa[16];
      const uint32_t dlo = (((sb + OFF_X) & 0x3FFFF) >> 4) | (1u << 16);
      constexpr int NP = hf ? NQ1 : NP0;
      if constexpr (hf) {
        static_for<PQE, NP>([&](auto K) { ldsm_x4_t_i<OFF_WQ + K.value * 2048>(rq[K.value], wqa); });
        bar_sync(B_X, 256);
      }
      wgmma_fence();
      static_for<0, 40>([&](auto K) {
        constexpr int k = K.value;
        wgmma_rs32h<((k >> 2) * 4096 + (k & 3) * 32) / 16, (k != 0)>(xa, w[k], dlo);
        if constexpr (!hf && k == PFK && NP > PQE) { SFENCE(wqa); static_for<PQE, NP>([&](auto K) { ldsm_x4_t_i<OFF_WQ + K.value * 2048>(rq[K.value], wqa); }); SFENCE(wqa); }
        if constexpr (!hf && k == XT) bar_arrive(B_X, 256);
      });
      step_addr(ph * (2 * KVB));
      wgmma_commit();
      TS(9);
      wgmma_wait<0>();
      const uint32_t xs = l16 + (wi * 1280 + ph * (2 * KVB));
      stsm_x4_t_i<OFF_KV + hf * KVB>(xs, pack_bf16(xa[0] * iw, xa[1] * iw), pack_bf16(xa[4] * iw, xa[5] * iw), pack_bf16(xa[8] * iw, xa[9] * iw), pack_bf16(xa[12] * iw, xa[13] * iw));
      stsm_x4_t_i<OFF_KV + hf * KVB + 640>(xs, pack_bf16(xa[2] * iw, xa[3] * iw), pack_bf16(xa[6] * iw, xa[7] * iw), pack_bf16(xa[10] * iw, xa[11] * iw), pack_bf16(xa[14] * iw, xa[15] * iw));
    };
    auto wq_addr = [&](uint32_t l) -> uint32_t {
      const int lr = (l >> 4) & 7, lm = (l >> 7) & 3;
      return sb + hf * ((40 - NQ1) * 2048) + (lr + ((lm >> 1) << 3)) * 128 + (((2 * wi + (lm & 1)) ^ lr) << 4);
    };
    constexpr int NPM = hf ? NPM1 : NPM0;
    uint32_t u1[NPM][4], u2[NPM][4];
    static_for<0, NPM>([&](auto K) { ldsm_x4_i<(12 - NPM + K.value) * WOK>(u1[K.value], wo1); ldsm_x4_i<(12 - NPM + K.value) * WOK>(u2[K.value], wo2); });
    bar_sync(0, 384);
    iq = uniform_f(exp2i(-wscale_exp(lds32_i<SC_W + 8>(sb))));
    wqa = wq_addr(l16);
    static_for<0, (hf ? NQ1 : NP0)>([&](auto K) { ldsm_x4_t_i<OFF_WQ + K.value * 2048>(rq[K.value], wqa); });
    step_addr(0);
    stsm_x4_t_i<OFF_KV + hf * KVB>(l16 + wi * 1280, x0[0], x0[2], x0[4], x0[6]);
    stsm_x4_t_i<OFF_KV + hf * KVB + 640>(l16 + wi * 1280, x0[1], x0[3], x0[5], x0[7]);
    asm volatile("barrier.cluster.wait.aligned;" ::: "memory");
    TL_END(a.tl + 1);
#pragma unroll 1
    for (int s = 0; s < cfg::NSEG; s++) {
      TS_SETUP();
      const bool last = s == cfg::NSEG - 1;
#if CHAIN_TIMING
      if (tid == 0 && (s & 7) == 0) a.dbg[96 * 288 + cta * 8 + (s >> 3)] = clk32();
#endif
      bar_sync(hf ? B_MEM1 : B_MEM0, 256);
      const float sin_ = __uint_as_float(lds32_i<SC_IN>(sb + 16 * (s & 1)));
      constexpr int NPQ = (40 - NQ1) / 2;
      if constexpr (hf == 0) {
        float k0[4] = {0, 0, 0, 0}, k1[4] = {0, 0, 0, 0}, q0[4] = {0, 0, 0, 0}, q1[4] = {0, 0, 0, 0};
        constexpr auto pair_of = [](int t) { const int a = t * (20 - NPQ) / 20, b = (t + 1) * (20 - NPQ) / 20; return b > a ? NPQ + a : t - a; };
        uint32_t b[NB0][4];
        static_for<0, NB0>([&](auto T) { ldsm_x4_i<OFF_MEM + pair_of(T.value) * 512>(b[T.value], mema); });
        static_for<NP0, NQ0>([&](auto K) { ldsm_x4_t_i<OFF_WQ + K.value * 2048>(rq[K.value], wqa); });
        if (BBS < 100) bbfence<0>(mema);
        static_for<0, 20>([&](auto T) {
          constexpr int t = T.value, p = pair_of(t);
          uint32_t (&bb)[4] = b[t % NB0];
          if constexpr (p < NPQ) {
            mma16816h(q0, rq[(2 * p) % NQ0], bb[0], bb[1]);
            if constexpr (2 * p + NQ0 < 2 * NPQ) ldsm_x4_t_i<OFF_WQ + (2 * p + NQ0) * 2048>(rq[(2 * p) % NQ0], wqa);
          }
          mma16816h(k0, w[2 * p], bb[0], bb[1]);
          if constexpr (p < NPQ) {
            mma16816h(q1, rq[(2 * p + 1) % NQ0], bb[2], bb[3]);
            if constexpr (2 * p + 1 + NQ0 < 2 * NPQ) ldsm_x4_t_i<OFF_WQ + (2 * p + 1 + NQ0) * 2048>(rq[(2 * p + 1) % NQ0], wqa);
          }
          mma16816h(k1, w[2 * p + 1], bb[2], bb[3]);
          if constexpr (t + NB0 < 20) ldsm_x4_i<OFF_MEM + pair_of(t + NB0) * 512>(bb, mema);
          if constexpr (t < 20 - NB0 && (t % BBS) == BBS - 1) bbfence<t + 1>(mema);
        });
        const float sq = sin_ * iq, sk = sin_ * iw;
        stsm_x4_t_i<0>(sta, pack_bf16((q0[0] + q1[0]) * sq, (q0[1] + q1[1]) * sq), pack_bf16((q0[2] + q1[2]) * sq, (q0[3] + q1[3]) * sq),
                       pack_bf16((k0[0] + k1[0]) * sk, (k0[1] + k1[1]) * sk), pack_bf16((k0[2] + k1[2]) * sk, (k0[3] + k1[3]) * sk));
        TS(2);
        if (!last) {
          if (wi == 3) {
            const uint32_t s8 = sb + ((l16 & 511) >> 1), xr = sb + ((l16 & 511) >> 2), ka = l16 + (l16 & 384) * 4 + (s & 1) * (2 * KVB);
            bar_sync(B_QK, 384);
            uint32_t a0[4], a1[4], a2[4], a3[4], kb0[4], kb1[4];
            ldsm_x4_i<OFF_Q>(a0, l16); ldsm_x4_i<OFF_KV + 512>(kb0, ka); ldsm_x4_i<OFF_Q + 1024>(a2, l16); ldsm_x4_i<OFF_KV + 512 + 2560>(kb1, ka);
            ldsm_x4_i<OFF_Q + 512>(a1, l16);
            bar_arrive(B_A, 288);
            ldsm_x4_i<OFF_Q + 1536>(a3, l16);
            float sa[4] = {0, 0, 0, 0}, sc2[4] = {0, 0, 0, 0};
            mma16816(sa, a0[0], a0[1], a0[2], a0[3], kb0[0], kb0[1]);
            mma16816(sc2, a2[0], a2[1], a2[2], a2[3], kb1[0], kb1[1]);
            mma16816(sa, a1[0], a1[1], a1[2], a1[3], kb0[2], kb0[3]);
            mma16816(sc2, a3[0], a3[1], a3[2], a3[3], kb1[2], kb1[3]);
            const float x0 = (sa[0] + sa[2]) + (sc2[0] + sc2[2]), x1 = (sa[1] + sa[3]) + (sc2[1] + sc2[3]);
            const uint32_t xp = pack_bf16(x0, x1);
            st_async_b32_i<OFF_SR + 1024 + 256>(xr + d1, xp, sb + MB_S + d1);
            st_async_b32_i<OFF_SR + 1024>(xr + d2, xp, sb + MB_S + d2);
            sts64_i<OFF_S + 1024>(s8, __float_as_uint(x0), __float_as_uint(x1));
          } else {
            bar_arrive(B_QK, 384);
          }
          bar_sync(B_SL, 256);
        }
      } else {
        float v0[4] = {0, 0, 0, 0}, v1[4] = {0, 0, 0, 0}, q0[4] = {0, 0, 0, 0}, q1[4] = {0, 0, 0, 0};
        uint32_t b[NQ1 / 2][4];
        static_for<0, NQ1 / 2>([&](auto T) { ldsm_x4_i<OFF_MEM + (NPQ + T.value) * 512>(b[T.value], mema); });
        static_for<0, NQ1 / 2>([&](auto T) {
          constexpr int t = T.value, p = NPQ + t;
          uint32_t (&bb)[4] = b[t];
          mma16816h(q0, rq[2 * t], bb[0], bb[1]);
          mma16816h(q1, rq[2 * t + 1], bb[2], bb[3]);
          mma16816h(v0, w[2 * p], bb[0], bb[1]);
          mma16816h(v1, w[2 * p + 1], bb[2], bb[3]);
        });
        const float sq = sin_ * iq, sv = sin_ * iw;
        stsm_x2_t_i<0>(sta, pack_bf16((q0[0] + q1[0]) * sq, (q0[1] + q1[1]) * sq), pack_bf16((q0[2] + q1[2]) * sq, (q0[3] + q1[3]) * sq));
        TS(2);
        if (!last) { bar_arrive(B_QK, 384); bar_sync(B_A, 288); }
        float v2[4] = {0, 0, 0, 0}, v3[4] = {0, 0, 0, 0};
        uint32_t c[4][4];
        static_for<0, 4>([&](auto T) { ldsm_x4_i<OFF_MEM + T.value * 512>(c[T.value], mema); });
        static_for<0, NPQ>([&](auto T) {
          constexpr int p = T.value;
          uint32_t (&bb)[4] = c[p & 3];
          if constexpr (p & 1) { mma16816h(v0, w[2 * p], bb[0], bb[1]); mma16816h(v1, w[2 * p + 1], bb[2], bb[3]); }
          else { mma16816h(v2, w[2 * p], bb[0], bb[1]); mma16816h(v3, w[2 * p + 1], bb[2], bb[3]); }
          if constexpr (p + 4 < NPQ) ldsm_x4_i<OFF_MEM + (p + 4) * 512>(bb, mema);
        });
        stsm_x2_t_i<OFF_KV + KVB + 512>(l16 + (l16 & 128) * 4 + (wi * 1280 + (s & 1) * (2 * KVB)), pack_bf16(((v0[0] + v1[0]) + (v2[0] + v3[0])) * sv, ((v0[1] + v1[1]) + (v2[1] + v3[1])) * sv),
                            pack_bf16(((v0[2] + v1[2]) + (v2[2] + v3[2])) * sv, ((v0[3] + v1[3]) + (v2[3] + v3[3])) * sv));
        if (!last) bar_arrive(B_V, 256);
      }
      TS(3);
      if (last) break;
      {
        uint32_t t1[12][4], t2[12][4];
        const uint32_t o16 = l16;
        wo1 = l16 + (OFF_WO + warp * 896);
        wo2 = sb + OFF_WO + warp * 896 + ((l16 & 128) ? 768 + ((l16 & 256) >> 2) + (l16 & 16) + ((l16 & 64) >> 1) : 512 + ((l16 & 256) >> 1) + (l16 & 112));
        auto ldw = [&](auto K) { if constexpr (K.value < 12 - NPM) { ldsm_x4_i<K.value * WOK>(t1[K.value], wo1); ldsm_x4_i<K.value * WOK>(t2[K.value], wo2); } };
        constexpr int NR_ = NRT - NPM;
        constexpr int PB = (hf ? PB1 : PB0) < NR_ ? (hf ? PB1 : PB0) : NR_, PA = (hf ? PA1 : PA0) < PB ? (hf ? PA1 : PA0) : PB;
        static_for<0, PA>(ldw);
        mbar_spin(sb + MB_X, (s + 1) & 1);
        if constexpr (PB > PA) bar_sync(B_G, 384); else bar_arrive(B_G, 384);
        static_for<PA, PB>(ldw);
        float c0[4] = {0, 0, 0, 0}, c1[4] = {0, 0, 0, 0}, e0[4] = {0, 0, 0, 0}, e1[4] = {0, 0, 0, 0};
        uint32_t ob[6][4];
        auto kstep = [&](auto K) {
          constexpr int k = K.value;
          uint32_t (&bb)[4] = ob[k >> 1];
          uint32_t (&x)[4] = k < 12 - NPM ? t1[k] : u1[k < 12 - NPM ? 0 : k - (12 - NPM)];
          uint32_t (&y)[4] = k < 12 - NPM ? t2[k] : u2[k < 12 - NPM ? 0 : k - (12 - NPM)];
          if constexpr (k & 1) { mma16816(c1, x[0], x[1], x[2], x[3], bb[2], bb[3]); mma16816(e1, y[0], y[1], y[2], y[3], bb[2], bb[3]); }
          else { mma16816(c0, x[0], x[1], x[2], x[3], bb[0], bb[1]); mma16816(e0, y[0], y[1], y[2], y[3], bb[0], bb[1]); }
          if constexpr (k >= NRF) ldw(IC<k + NR_ - NRF>{});
        };
        auto ldo = [&](auto P) { ldsm_x4_i<OFF_O + P.value * 512>(ob[P.value], o16); };
        TS(4);
        bar_sync(B_O, 384);
        ldo(IC<0>{}); ldo(IC<1>{});
        SFENCE(o16);
        static_for<PB, NR_>(ldw);
        static_for<0, 4>(kstep);
        TS(5);
        mbar_spin(sb + MB_O, s & 1);
        TS(6);
        ldo(IC<2>{}); ldo(IC<NPM >= 2 ? 5 : 3>{});
        if (WOF) SFENCE(o16);
        kstep(IC<4>{});
        if constexpr (NPM < 2) { kstep(IC<5>{}); ldo(IC<4>{}); kstep(IC<6>{}); kstep(IC<7>{}); ldo(IC<5>{}); static_for<8, 12>(kstep); }
        else if constexpr (NPM >= 4) { kstep(IC<10>{}); kstep(IC<11>{}); ldo(IC<4>{}); kstep(IC<5>{}); ldo(IC<3>{}); kstep(IC<8>{}); kstep(IC<9>{}); kstep(IC<6>{}); kstep(IC<7>{}); }
        else { kstep(IC<5>{}); ldo(IC<3>{}); kstep(IC<11>{}); kstep(IC<10>{}); ldo(IC<4>{}); kstep(IC<6>{}); kstep(IC<7>{}); if constexpr (NPM == 3) { kstep(IC<9>{}); kstep(IC<8>{}); } else { kstep(IC<8>{}); kstep(IC<9>{}); } }
        l16 = fresh(l16);
        const int ln = (l16 >> 4) & 31;
        unsigned char* gr = arena + (AR_ACC + acc_lane(bi, ln) + acc_voff(bv) + acc_step(s));
        const bool cnt = (ln & 1) || !t28;
        wqa = wq_addr(l16);
        SFENCE(o16);
        static_for<0, PQE>([&](auto K) { ldsm_x4_t_i<OFF_WQ + K.value * 2048>(rq[K.value], wqa); });
        const uint32_t y0 = movm_t(pack_f16(c0[0] + c1[0], c0[1] + c1[1])), y1 = movm_t(pack_f16(c0[2] + c1[2], c0[3] + c1[3]));
        const uint32_t y2 = movm_t(pack_f16(e0[0] + e1[0], e0[1] + e1[1])), y3 = movm_t(pack_f16(e0[2] + e1[2], e0[3] + e1[3]));
        asm volatile("red.relaxed.gpu.global.add.noftz.v4.f16x2 [%0], {%1,%2,%3,%4};" :: "l"(gr), "r"(y0), "r"(y1), "r"(y2), "r"(cnt ? 0x3c00u : y3) : "memory");
        bar_arrive(B_RED, 384);
        bar_sync(B_C, 256);
        TS(7);
      }
#if CHAIN_TIMING
      x_gemm((s + 1) & 1, tsb);
#else
      x_gemm((s + 1) & 1, 0);
#endif
      TS(8);
    }
    };
    if (hf == 0) run(IC<0>{}); else run(IC<1>{});
    bar_arrive(B_RED, 384);
#if CHAIN_TIMING
    for (int i = tid; i < 288; i += 256) a.dbg[cta * 288 + i] = lds32_i<OFF_BAR + 128>(sb + i * 4);
#endif
    asm volatile("barrier.cluster.arrive.relaxed.aligned; barrier.cluster.wait.aligned;" ::: "memory");
  }
}
struct PrepArgs { const bf16 *wqkv, *wphi, *wo; unsigned char *wb, *wot; };
__device__ __forceinline__ void prep_body(const int cta, const PrepArgs& pa) {
  const int tid = threadIdx.x, lane = tid & 31, warp = tid >> 5, g = lane >> 2, q = lane & 3;
  const int pair = cta >> 1, which = cta & 1;
  uint32_t af[5][2][6];
#pragma unroll
  for (int i = 0; i < 5; i++)
#pragma unroll
    for (int hh = 0; hh < 2; hh++) {
      const uint32_t* r0 = (const uint32_t*)(pa.wqkv + (size_t)((warp * 5 + i) * 16 + g) * 1920 + which * 640 + (2 * pair + hh) * 20) + q;
      const uint32_t* r1 = r0 + 8 * 960;
      af[i][hh][0] = __ldg(r0); af[i][hh][1] = __ldg(r1); af[i][hh][2] = __ldg(r0 + 4); af[i][hh][3] = __ldg(r1 + 4);
      af[i][hh][4] = q < 2 ? __ldg(r0 + 8) : 0u; af[i][hh][5] = q < 2 ? __ldg(r1 + 8) : 0u;
    }
  uint32_t bfr[2][3][3];
#pragma unroll
  for (int hh = 0; hh < 2; hh++)
#pragma unroll
    for (int t = 0; t < 3; t++) {
      const bool on = t < 2 || (g & 1) == hh;
      const unsigned short* ph = (const unsigned short*)pa.wphi + (2 * pair + hh) * 400 + (t < 2 ? 8 * t + g : 16 + (g >> 1)) + 2 * q * 20;
#pragma unroll
      for (int r = 0; r < 3; r++) bfr[hh][t][r] = (on && (r < 2 || q < 2)) ? (uint32_t)__ldg(ph + r * 160) | ((uint32_t)__ldg(ph + r * 160 + 20) << 16) : 0u;
    }
  const int gt = cta * 256 + tid;
#pragma unroll 3
  for (int i = gt; i < 640 * 32; i += 8192) {
    const int k = (i & 7) + (i >> 8) * 8, h = (i >> 3) & 31;
    const uint2* src = (const uint2*)(pa.wqkv + (size_t)k * 1920 + 1280 + h * 20);
    const uint2 a = __ldg(src), b = __ldg(src + 1), c = __ldg(src + 2), d = __ldg(src + 3), e = __ldg(src + 4);
    uint4* dst = (uint4*)(pa.wb + ((size_t)((h >> 2) * 80 + (k >> 3)) * 32 + 20 + 3 * (h & 3)) * 128 + (k & 7) * 16);
    dst[0] = make_uint4(a.x, a.y, b.x, b.y); dst[8] = make_uint4(c.x, c.y, d.x, d.y);
    dst[16] = (h & 1) ? make_uint4(0, 0, e.x, e.y) : make_uint4(e.x, e.y, 0, 0);
  }
#pragma unroll 7
  for (int i = gt; i < 640 * 80; i += 8192) {
    const int r = i & 7, c = (i >> 3) % 80, kg = i / 640, c5 = kg % 5;
    const int row = (kg / 5) * 40 + (c5 < 2 ? 8 * c5 + r : (c5 == 2 ? 16 + (r & 3) + (r >> 2) * 20 : 20 + 8 * (c5 - 3) + r));
    *(uint4*)(pa.wot + ((size_t)((c / 10) * 80 + kg) * 10 + c % 10) * 128 + r * 16) = __ldg((const uint4*)(pa.wo + (size_t)row * cfg::DM + c * 8));
  }
#pragma unroll
  for (int i = 0; i < 5; i++) {
    uint32_t* dst = (uint32_t*)(pa.wb + ((size_t)((pair >> 1) * 80 + (warp * 5 + i) * 2) * 32 + which * 10 + (pair & 1) * 5) * 128) + lane;
#pragma unroll
    for (int t = 0; t < 5; t++) {
      float d[4] = {0, 0, 0, 0};
#pragma unroll
      for (int hh = 0; hh < 2; hh++)
        if (t == 2 || (t > 2) == (hh == 1)) {
          const int tt = t < 3 ? t : t - 3;
          mma16816(d, af[i][hh][0], af[i][hh][1], af[i][hh][2], af[i][hh][3], bfr[hh][tt][0], bfr[hh][tt][1]);
          mma1688(d, af[i][hh][4], af[i][hh][5], bfr[hh][tt][2]);
        }
      dst[t * 32] = pack_bf16(d[0], d[1]); dst[1024 + t * 32] = pack_bf16(d[2], d[3]);
    }
  }
}

__global__ void __launch_bounds__(256, 4) ln_kernel(const bf16* __restrict__ xin, bf16* __restrict__ xn, uint2* __restrict__ xh, uint4* __restrict__ z0, int n0,
                                                    uint4* __restrict__ z1, int n1, const bf16* pfa, const bf16* pfb, int npf, int tl) {
  asm volatile("griddepcontrol.wait;" ::: "memory");
  asm volatile("griddepcontrol.launch_dependents;" ::: "memory");
  TL_BEGIN(tl);
  const int warp = threadIdx.x >> 5, lane = threadIdx.x & 31;
  const int row = blockIdx.x * 8 + warp;
  uint2 xw[1][5];
#pragma unroll
  for (int i = 0; i < 5; i++) xw[0][i] = *(const uint2*)(xin + (size_t)row * cfg::DM + i * 128 + lane * 4);
  for (int i = blockIdx.x * 256 + threadIdx.x; i < n0; i += 256 * 256) z0[i] = make_uint4(0, 0, 0, 0);
  for (int i = blockIdx.x * 256 + threadIdx.x; i < n1; i += 256 * 256) z1[i] = make_uint4(0, 0, 0, 0);
  if (npf && xw[0][4].y != 0x7fc17fc1u) {
    for (int i = 0; i < npf; i++) {
      const uint32_t l = (uint32_t)i * 32768u + (blockIdx.x * 256 + threadIdx.x) / 2;
      if (l < cfg::DM * cfg::HD / 64) asm volatile("prefetch.global.L2 [%0];" :: "l"(((threadIdx.x & 1) ? pfa : pfb) + (size_t)l * 64) : "memory");
    }
  }
  ln_rows<1>(xw, row, lane, xn, xh);
  TL_END(tl);
}
struct Pipe { uint32_t stage, phase; };
template <int NS> __device__ __forceinline__ void pipe_adv(Pipe& p) { if (++p.stage == NS) { p.stage = 0; p.phase ^= 1; } }
constexpr uint32_t SWZ128 = 1;
__device__ __forceinline__ uint64_t desc_kmajor(uint32_t a) { return make_desc(a, 16, 1024, SWZ128); }
__device__ __forceinline__ uint64_t desc_mnmajor(uint32_t a) { return make_desc(a, 8192, 1024, SWZ128); }
__device__ __forceinline__ void wait_ge(const void* p, uint32_t target, uint32_t ns = 32) {
  int spin = 0;
  while (ld_acquire_u32(p) < target) { __nanosleep(ns); if (++spin > (1 << 21)) break; }
}
__device__ __forceinline__ void bulk_g2s_hint(uint32_t dst, const void* src, uint32_t bytes, uint32_t mb, uint64_t pol) {
  asm volatile("cp.async.bulk.shared::cluster.global.mbarrier::complete_tx::bytes.L2::cache_hint [%0], [%1], %2, [%3], %4;"
               :: "r"(dst), "l"(src), "r"(bytes), "r"(mb), "l"(pol) : "memory");
}
#ifndef PF_WB
#define PF_WB 2
#endif
#ifndef PF_XN
#define PF_XN 1
#endif
#ifndef LNP
#define LNP 4
#endif
#ifndef STAG
#define STAG 1
#endif
#ifndef EF_KV
#define EF_KV 1
#endif
#ifndef EF_O
#define EF_O 1
#endif
__device__ __forceinline__ void fence_proxy_async_global() { asm volatile("fence.proxy.async.global;" ::: "memory"); }

namespace tr {
constexpr int NS = 4, STQ = 16384 + 24576, STO = 16384 + 40960;
constexpr int SEGB = 15360;
constexpr int OFF_K = NS * STQ;
constexpr int OFF_BAR = NS * STO;
constexpr int SMEM = OFF_BAR + 256;
static_assert(OFF_K + 4 * SEGB <= OFF_BAR && SMEM <= 232448, "smem");
enum { T_QA = 0, T_Q, T_A, T_OB, T_OS, T_L, T_END };
constexpr uint32_t C_QA = AR_CNT, C_O = AR_CNT + 64, C_Q = AR_CNT + 128;
constexpr int MAXITEMS = 1200;
struct Sched {
  uint8_t ks[16];
  uint8_t wide[16];
  uint8_t lrows[16];
  uint32_t n;
  uint16_t item[MAXITEMS];
};
struct Args {
  const unsigned char *kg, *vg;
  unsigned char* o;
  uint4* qs;
  unsigned char* part;
  const bf16 *xin, *xq;
  bf16 *xout, *xn;
  unsigned char* arena;
  int doprep, tl;
  uint32_t nap, nap2;
  int lwait;
};
}

template <int N0, int N1>
__device__ __forceinline__ void tr_mainloop(float (&a0)[N0 / 2], float (&a1)[N1 ? N1 / 2 : 1], Pipe& p, uint32_t sb, uint32_t full, uint32_t empty, int nkb, int wg) {
  using namespace tr;
  constexpr uint32_t ST = N1 ? STO : STQ;
  uint32_t prev = 0;
#pragma unroll
  for (int i = 0; i < N0 / 2; i++) a0[i] = 0.f;
  if constexpr (N1 > 0) {
#pragma unroll
    for (int i = 0; i < N1 / 2; i++) a1[i] = 0.f;
  }
#pragma unroll 1
  for (int kb = 0; kb < nkb; kb++) {
    mbar_wait(full + 8 * p.stage, p.phase);
    const uint32_t st = sb + p.stage * ST;
    wgmma_fence();
#pragma unroll
    for (int kk = 0; kk < 4; kk++) {
      const uint64_t da = desc_kmajor(st + wg * 8192 + kk * 32);
      if constexpr (N0 == 192) wgmma_n192<0, 1>(a0, da, desc_mnmajor(st + 16384 + kk * 2048), (kb | kk) != 0);
      else wgmma_n128<0, 1>(a0, da, desc_mnmajor(st + 16384 + kk * 2048), (kb | kk) != 0);
      if constexpr (N1 > 0) wgmma_n128<0, 1>(a1, da, desc_mnmajor(st + 16384 + 24576 + kk * 2048), (kb | kk) != 0);
    }
    wgmma_commit();
    if (kb > 0) { wgmma_wait<1>(); mbar_arrive_if((threadIdx.x & 127) == 0, empty + 8 * prev); }
    prev = p.stage;
    pipe_adv<NS>(p);
  }
  wgmma_wait<0>();
  mbar_arrive_if((threadIdx.x & 127) == 0, empty + 8 * prev);
}
template <int N> __device__ __forceinline__ void stage_tiles(const float (&o)[N / 2], uint32_t base, int wi, int lane) {
  const uint32_t ra = base + (wi * 16 + (lane & 7) + 8 * ((lane >> 3) & 1)) * 128;
#pragma unroll
  for (int v = 0; v < N / 8; v += 2)
    stsm_x4(ra + (v >> 3) * 8192 + ((((v & 7) + (lane >> 4)) ^ (lane & 7)) << 4), pack_bf16(o[4 * v], o[4 * v + 1]), pack_bf16(o[4 * v + 2], o[4 * v + 3]),
            pack_bf16(o[4 * v + 4], o[4 * v + 5]), pack_bf16(o[4 * v + 6], o[4 * v + 7]));
}
template <int R, int NP> __device__ __forceinline__ void l_rows(const tr::Args& a, int row0, int np, int lane) {
  uint2 xw[R][5]; float s[R][20];
  const unsigned char* pp[R];
#pragma unroll
  for (int r = 0; r < R; r++) {
    const int row = row0 + r;
#pragma unroll
    for (int i = 0; i < 5; i++) {
      xw[r][i] = __ldcg((const uint2*)(a.xin + (size_t)row * cfg::DM + i * 128 + lane * 4));
      s[r][4 * i] = s[r][4 * i + 1] = s[r][4 * i + 2] = s[r][4 * i + 3] = 0.f;
    }
    pp[r] = a.part + (size_t)(row >> 6) * 81920 + (lane >> 4) * 8192 + (row & 63) * 128 + ((((lane >> 1) & 7) ^ (row & 7)) << 4) + (lane & 1) * 8;
  }
#pragma unroll 1
  for (int p0 = 0; p0 < np; p0 += NP) {
    uint2 t[R][NP][5];
    static_for<0, R * NP>([&](auto Q) {
      constexpr int r = Q.value / NP, q = Q.value % NP;
      static_for<0, 5>([&](auto I) {
        asm volatile("{\n.reg .pred p;\nsetp.ne.u32 p, %3, 0;\nmov.b32 %0, 0;\nmov.b32 %1, 0;\n@p ld.global.cg.v2.u32 {%0,%1}, [%2+%4];\n}"
                     : "=r"(t[r][q][I.value].x), "=r"(t[r][q][I.value].y) : "l"(pp[r]), "r"((uint32_t)(p0 + q < np)), "n"(I.value * 16384) : "memory");
      });
      pp[r] += 32 * 81920;
    });
#pragma unroll
    for (int r = 0; r < R; r++)
#pragma unroll
      for (int q = 0; q < NP; q++)
#pragma unroll
        for (int i = 0; i < 5; i++) { s[r][4 * i] += bf_lo(t[r][q][i].x); s[r][4 * i + 1] += bf_hi(t[r][q][i].x); s[r][4 * i + 2] += bf_lo(t[r][q][i].y); s[r][4 * i + 3] += bf_hi(t[r][q][i].y); }
  }
#pragma unroll
  for (int r = 0; r < R; r++)
#pragma unroll
    for (int i = 0; i < 5; i++) {
      bf16r2(s[r][4 * i], s[r][4 * i + 1]); bf16r2(s[r][4 * i + 2], s[r][4 * i + 3]);
      xw[r][i] = make_uint2(pack_bf16(bf_lo(xw[r][i].x) + s[r][4 * i], bf_hi(xw[r][i].x) + s[r][4 * i + 1]), pack_bf16(bf_lo(xw[r][i].y) + s[r][4 * i + 2], bf_hi(xw[r][i].y) + s[r][4 * i + 3]));
      *(uint2*)(a.xout + (size_t)(row0 + r) * cfg::DM + i * 128 + lane * 4) = xw[r][i];
    }
  ln_rows<R>(xw, row0, lane, a.xn, nullptr);
}

__global__ void __launch_bounds__(384, 1) trail_kernel(const __grid_constant__ CUtensorMap tmX, const __grid_constant__ CUtensorMap tmQ,
                                                       const __grid_constant__ CUtensorMap tmWo5, const __grid_constant__ CUtensorMap tmWo2, const __grid_constant__ tr::Sched sc,
                                                       const __grid_constant__ tr::Args a, const __grid_constant__ PrepArgs pa) {
  using namespace tr;
  [[maybe_unused]] const int tl = a.tl;
  TL_BEGIN(tl);
  extern __shared__ __align__(1024) unsigned char smem_raw[];
  const uint32_t sb = smem_u32(smem_raw);
  const int warp = __shfl_sync(0xffffffffu, (int)threadIdx.x >> 5, 0), lane = threadIdx.x & 31;
  unsigned char* const arena = a.arena;
  const uint32_t full = sb + OFF_BAR, empty = full + 8 * NS, barK = empty + 8 * NS, barKfree = barK + 16, staged = barKfree + 16;
  const uint32_t kvrdy = staged + 32, mfull = kvrdy + 8, mempty = mfull + 16, mbox = mempty + 16;
  uint32_t first = 0;
  if (threadIdx.x == 256) asm volatile("atom.relaxed.gpu.global.add.u32 %0, [%1], 1;" : "=r"(first) : "l"(arena + AR_QUEUE) : "memory");
  if (threadIdx.x == 0) {
    for (int i = 0; i < NS; i++) { mbar_init(full + 8 * i, 1); mbar_init(empty + 8 * i, 2); }
    for (int i = 0; i < 2; i++) {
      mbar_init(barK + 8 * i, 1); mbar_init(barKfree + 8 * i, 1); mbar_init(staged + 16 * i, 4); mbar_init(staged + 16 * i + 8, 4);
      mbar_init(mfull + 8 * i, 1); mbar_init(mempty + 8 * i, 11);
    }
    mbar_init(kvrdy, 1);
    asm volatile("fence.mbarrier_init.release.cluster;" ::: "memory");
  }
  __syncthreads();
  Pipe mp{0, 0};
  auto next_item = [&]() -> uint32_t {
    uint32_t it;
    mbar_wait(mfull + 8 * mp.stage, mp.phase);
    asm volatile("ld.shared.u32 %0, [%1];" : "=r"(it) : "r"(mbox + 4 * mp.stage) : "memory");
    return it;
  };
  if (warp >= 8) {
    asm volatile("setmaxnreg.dec.sync.aligned.u32 40;");
    if (warp == 8) { first = __shfl_sync(0xffffffffu, first, 0); if (elect_one()) {
      Pipe p{0, 1};
      mp.phase = 1;
      uint32_t kph = 1, wide = 0, qdone = 0;
      const uint64_t ef = policy_evict_first();
      auto ld_kv = [&](uint32_t d, const void* s, uint32_t n, uint32_t mb) { if (EF_KV) bulk_g2s_hint(d, s, n, mb, ef); else bulk_g2s(d, s, n, mb); };
      auto ld_o = [&](uint32_t d, const void* s, uint32_t n, uint32_t mb) { if (EF_O) bulk_g2s_hint(d, s, n, mb, ef); else bulk_g2s(d, s, n, mb); };
      auto stage = [&](uint32_t bytes) -> uint32_t {
        mbar_wait(empty + 8 * p.stage, p.phase);
        mbar_expect_tx(full + 8 * p.stage, bytes);
        return sb + p.stage * (wide ? STO : STQ);
      };
      auto fetch = [&]() -> uint32_t { uint32_t v; asm volatile("atom.relaxed.gpu.global.add.u32 %0, [%1], 1;" : "=r"(v) : "l"(arena + AR_QUEUE) : "memory"); return v; };
      uint32_t next = first;
      while (true) {
        const uint32_t item = next;
        const uint32_t code = sc.item[min(item, sc.n)];
        const int type = code >> 11, m = (code >> 7) & 15, k = code & 127;
        if (type == T_L) {
          prefetch_l2(a.xin + (size_t)(m * 128 + k * 8 * sc.lrows[m]) * cfg::DM, sc.lrows[m] * 8 * 1280);
          wait_ge(arena + C_O + m * 4, sc.ks[m] * (sc.wide[m] ? 4 : 10), m < 13 ? a.nap : 32);
        }
        if (type == T_A && !((qdone >> m) & 1)) { wait_ge(arena + C_Q + m * 4, 64); qdone |= 1u << m; }
        if (type < T_L && wide != (type == T_OB)) {
          for (uint32_t i = 0; i < NS; i++) mbar_wait(empty + 8 * i, i >= p.stage ? p.phase : p.phase ^ 1);
          mbar_wait(barKfree, kph); mbar_wait(barKfree + 8, kph);
          wide = type == T_OB;
        }
        mbar_wait(mempty + 8 * mp.stage, mp.phase);
        asm volatile("st.shared.u32 [%0], %1;" :: "r"(mbox + 4 * mp.stage), "r"((p.stage << 24) | (type << 16) | (m << 8) | (k & 255)) : "memory");
        mbar_arrive(mfull + 8 * mp.stage);
        pipe_adv<2>(mp);
        if (type == T_END) break;
        if (type == T_L) {
          if (m >= a.lwait) mbar_wait(mempty + 8 * (mp.stage ^ 1), mp.stage ? mp.phase ^ 1 : mp.phase);
          next = fetch(); continue;
        }
        if (type <= T_A) {
          if (type != T_A)
#pragma unroll 1
            for (int kb = 0; kb < 10; kb++) {
              const uint32_t st = stage(STQ), fb = full + 8 * p.stage;
              tma_load_2d(st, &tmX, kb * 64, m * 128, fb);
              tma_load_3d(st + 16384, &tmQ, 0, kb * 64, k * 3, fb);
              pipe_adv<NS>(p);
              if (type == T_Q && kb == 8) next = fetch();
            }
          if (type != T_Q) {
            const size_t blk = ((size_t)m * 4 * 96 + k * 3) * 5120;
            kph ^= 1;
            mbar_wait(kvrdy, kph);
            next = fetch();
            fence_proxy_async_global();
#pragma unroll 1
            for (int w = type == T_A ? 0 : 2; w < 4; w++) {
              const uint32_t st = stage(2 * SEGB), fb = full + 8 * p.stage;
              for (int sg = 0; sg < 2; sg++) ld_kv(st + sg * SEGB, (w < 2 ? a.kg : a.vg) + blk + (size_t)(2 * (w & 1) + sg) * (96 * 5120), SEGB, fb);
              pipe_adv<NS>(p);
            }
          }
        } else {
          const int nn = wide ? 2 : 5, nb = wide ? 5 : 2, nt = k % nn, nkb = 96 / sc.ks[m], k0 = (k / nn) * nkb;
          const Pipe p0 = p;
          for (int kb = 0; kb < nkb; kb++) {
            const uint32_t st = stage(16384 + nb * 8192), fb = full + 8 * p.stage;
            tma_load_3d(st + 16384, wide ? &tmWo5 : &tmWo2, 0, (k0 + kb) * 64, nt * nb, fb);
            if (kb >= NS) ld_o(st, a.o + ((size_t)m * 96 + k0 + kb) * 16384, 16384, fb);
            pipe_adv<NS>(p);
            if (kb == NS - 1 || (kb == nkb - 1 && nkb < NS)) {
              wait_ge(arena + C_QA + m * 4, 64, m < 14 ? a.nap : 32);
              fence_proxy_async_global();
              Pipe q = p0;
#pragma unroll 1
              for (int i = 0; i <= kb; i++) { ld_o(sb + q.stage * (wide ? STO : STQ), a.o + ((size_t)m * 96 + k0 + i) * 16384, 16384, full + 8 * q.stage); pipe_adv<NS>(q); }
            }
          }
          next = fetch();
          for (int w = 0; w < 2; w++) { mbar_wait(empty + 8 * p.stage, p.phase); mbar_arrive(full + 8 * p.stage); pipe_adv<NS>(p); }
        }
      }
    } } else if (warp < 11) { if (elect_one()) {
      const int w = warp - 9;
      uint32_t sph = 0;
      [[maybe_unused]] int nlog = 0;
#ifdef TIMELINE
      if (w == 0) { unsigned long long* lg = g_log + (((tl >= 12) * 132 + blockIdx.x) * 64 + nlog++) * 2; lg[0] = T_END << 16; lg[1] = gtime(); lg[2] = ~0ull; }
#endif
      while (true) {
        const uint32_t it = next_item();
        const int type = (it >> 16) & 255, m = (it >> 8) & 255, k = it & 255;
        const uint32_t slot = mp.stage;
        pipe_adv<2>(mp);
        if (type == T_END) break;
        mbar_wait(staged + 16 * w + 8 * slot, (sph >> slot) & 1); sph ^= 1u << slot;
        mbar_arrive(mempty + 8 * slot);
#ifdef TIMELINE
        if (w == 0 && nlog < 63) { unsigned long long* lg = g_log + (((tl >= 12) * 132 + blockIdx.x) * 64 + nlog++) * 2; lg[0] = (type << 16) | (m << 8) | k; lg[1] = gtime(); lg[2] = ~0ull; }
#endif
        if (type == T_L) continue;
        if (type == T_QA || type == T_A) {
          for (int jj = 0; jj < 3; jj++) bulk_s2g(a.o + ((size_t)m * 96 + k * 3 + jj) * 16384 + w * 8192, sb + OFF_K + w * 2 * SEGB + jj * 8192, 8192);
          bulk_commit();
          bulk_wait<0>();
          mbar_arrive(barKfree + 8 * w);
        } else if (type >= T_OB) {
          const bool wide = type == T_OB;
          const int nn = wide ? 2 : 5, nb = wide ? 5 : 2;
          const uint32_t own = ((it >> 24) + 96 / sc.ks[m] + w) % NS;
          bulk_s2g(a.part + ((size_t)((k / nn) * 32 + m * 2 + w) * 10 + (k % nn) * nb) * 8192, sb + own * (wide ? STO : STQ), nb * 8192);
          bulk_commit();
          bulk_wait<0>();
          mbar_arrive(empty + 8 * own);
        }
        if (type == T_Q) __threadfence();
        asm volatile("red.relaxed.gpu.global.add.u32 [%0], 1;" :: "l"(arena + (type == T_Q ? C_Q : (type <= T_A ? C_QA : C_O)) + m * 4) : "memory");
      }
    } } else if (elect_one()) {
      const uint64_t ef = policy_evict_first();
      uint32_t kph = 1;
      if (PF_WB && blockIdx.x >= 52) { prefetch_l2(pa.wb + (blockIdx.x - 52) * 32768, 32768); prefetch_l2(pa.wot + (blockIdx.x - 52) * 10240, 10240); }
      if (PF_WB > 1 && blockIdx.x >= 52) { prefetch_l2(a.xn + (blockIdx.x - 52) * 8192, 16384); prefetch_l2(a.xout + (blockIdx.x - 52) * 8192, 16384); }
      while (true) {
        const uint32_t it = next_item();
        const int type = (it >> 16) & 255, m = (it >> 8) & 255, k = it & 255;
        const uint32_t slot = mp.stage;
        pipe_adv<2>(mp);
        if (type == T_END) break;
        if (PF_XN && type == T_QA && m < 15) prefetch_l2(a.xq + ((m + 1) * 128 + k * 4) * cfg::DM, 5120);
        if (type == T_QA || type == T_A) {
          for (int spin = 0; spin < (1 << 21); spin++) {
            const uint4 f = ld_relaxed_v4(arena + prog_off(k, 0));
            if (min(min(f.x, f.y), f.z) >= (uint32_t)(4 * m + 4)) break;
            __nanosleep(m < 15 ? a.nap : a.nap2);
          }
          mbar_arrive(kvrdy);
          fence_proxy_async_global();
          const unsigned char* src = a.kg + ((size_t)m * 4 * 96 + k * 3) * 5120;
#pragma unroll 1
          for (int w = 0; w < 2; w++) {
            mbar_wait(barKfree + 8 * w, kph);
            if (type == T_A) { mbar_arrive(barK + 8 * w); continue; }
            mbar_expect_tx(barK + 8 * w, 2 * SEGB);
            for (int sg = 2 * w; sg < 2 * w + 2; sg++) bulk_g2s_hint(sb + OFF_K + sg * SEGB, src + (size_t)sg * (96 * 5120), SEGB, barK + 8 * w, ef);
          }
          kph ^= 1;
        }
        mbar_arrive(mempty + 8 * slot);
      }
      if (blockIdx.x == gridDim.x - 1) asm volatile("griddepcontrol.wait;" ::: "memory");
    }
    return;
  }
  asm volatile("setmaxnreg.inc.sync.aligned.u32 232;");
  const int wg = warp >> 2, wi = warp & 3;
  const int g = lane >> 2, q4 = lane & 3;
  if (a.doprep && blockIdx.x < 32) { prep_body(blockIdx.x, pa); __threadfence(); }
  bar_sync(2, 256);
  asm volatile("griddepcontrol.launch_dependents;" ::: "memory");
  Pipe p{0, 0};
  uint32_t kph = 0;
  auto own_slot = [&]() -> uint32_t {
    const uint32_t sA = p.stage, phA = p.phase; pipe_adv<NS>(p);
    const uint32_t sB = p.stage, phB = p.phase; pipe_adv<NS>(p);
    mbar_wait(full + 8 * sA, phA); mbar_wait(full + 8 * sB, phB);
    mbar_arrive_if((threadIdx.x & 127) == 0, empty + 8 * (wg ? sA : sB));
    return wg ? sB : sA;
  };
  while (true) {
    const uint32_t it = __shfl_sync(0xffffffffu, next_item(), 0);
    const int type = (it >> 16) & 255, m = (it >> 8) & 255, k = it & 255;
    mbar_arrive_if(lane == 0, mempty + 8 * mp.stage);
    const uint32_t done = staged + 16 * wg + 8 * mp.stage;
    pipe_adv<2>(mp);
    if (type == T_END) break;
    if (type == T_L) {
      const int nr = sc.lrows[m], np = sc.ks[m], row0 = m * 128 + (k * 8 + warp) * nr;
#pragma unroll 1
      for (int r = 0; r < nr; r++) l_rows<1, LNP>(a, row0 + r, np, lane);
      __syncwarp();
      mbar_arrive_if(lane == 0, done);
      continue;
    }
    if (type >= T_OB) {
      const int nkb = 96 / sc.ks[m];
      if (type == T_OB) {
        float a0[96], a1[64];
        tr_mainloop<192, 128>(a0, a1, p, sb, full, empty, nkb, wg);
        const uint32_t st = sb + own_slot() * STO;
        stage_tiles<192>(a0, st, wi, lane); stage_tiles<128>(a1, st + 24576, wi, lane);
      } else {
        float a0[64], a1[1];
        tr_mainloop<128, 0>(a0, a1, p, sb, full, empty, nkb, wg);
        stage_tiles<128>(a0, sb + own_slot() * STQ, wi, lane);
      }
      fence_proxy_async();
      __syncwarp();
      mbar_arrive_if(lane == 0, done);
      continue;
    }
    uint32_t qf[12][4];
    uint4* qp = a.qs + ((size_t)((m & 7) * 32 + k) * 12) * 256 + threadIdx.x;
    if (type != T_A) {
      float acc[96], a1[1];
      tr_mainloop<192, 0>(acc, a1, p, sb, full, empty, 10, wg);
#pragma unroll
      for (int i = 0; i < 12; i++) {
        qf[i][0] = pack_bf16(acc[8 * i], acc[8 * i + 1]); qf[i][1] = pack_bf16(acc[8 * i + 2], acc[8 * i + 3]);
        qf[i][2] = pack_bf16(acc[8 * i + 4], acc[8 * i + 5]); qf[i][3] = pack_bf16(acc[8 * i + 6], acc[8 * i + 7]);
      }
      if (type == T_Q) {
#pragma unroll
        for (int i = 0; i < 12; i++) qp[i * 256] = make_uint4(qf[i][0], qf[i][1], qf[i][2], qf[i][3]);
        __syncwarp();
        mbar_arrive_if(lane == 0, done);
        continue;
      }
    } else {
#pragma unroll
      for (int i = 0; i < 12; i++) { const uint4 v = __ldcg(qp + i * 256); qf[i][0] = v.x; qf[i][1] = v.y; qf[i][2] = v.z; qf[i][3] = v.w; }
    }
    const uint32_t ost = sb + OFF_K + wg * 2 * SEGB;
    const bool second = wi >= 2;
    uint32_t pf[5][4];
    {
      float sa[20], sb2[20];
      uint32_t kbase = ost, kslot = 0;
      if (type == T_A) { kslot = own_slot(); kbase = sb + kslot * STQ; } else mbar_wait(barK + 8 * wg, kph);
      if (STAG && wg) bar_sync(1, 256);
      wgmma_fence();
#pragma unroll
      for (int i = 0; i < 12; i++) {
        wgmma_rs_n40<0>(sa, qf[i][0], qf[i][1], qf[i][2], qf[i][3], make_desc(kbase + i * 1280, 640, 128, 0), i != 0);
        wgmma_rs_n40<0>(sb2, qf[i][0], qf[i][1], qf[i][2], qf[i][3], make_desc(kbase + SEGB + i * 1280, 640, 128, 0), i != 0);
      }
      wgmma_commit();
      wgmma_wait<0>();
      if (STAG && !wg) bar_arrive(1, 256);
      mbar_arrive_if(type == T_A && (threadIdx.x & 127) == 0, empty + 8 * kslot);
      const float cs = 0.07216878364870322f * 1.4426950408889634f;
      const int r0 = 16 * (wi & 1) + g, r1 = r0 + 8;
      float m0 = -INFINITY, m1 = -INFINITY;
#pragma unroll
      for (int n = 0; n < 5; n++) {
#pragma unroll
        for (int e = 0; e < 2; e++) {
          const int key = 8 * n + 2 * q4 + e;
          float x = second ? sb2[4 * n + e] : sa[4 * n + e], y = second ? sb2[4 * n + 2 + e] : sa[4 * n + 2 + e];
          if (n < 4) { if (key > r0) x = -INFINITY; if (key > r1) y = -INFINITY; }
          sa[4 * n + e] = x; sa[4 * n + 2 + e] = y;
          m0 = fmaxf(m0, x); m1 = fmaxf(m1, y);
        }
      }
      m0 = fmaxf(m0, __shfl_xor_sync(0xffffffffu, m0, 1)); m1 = fmaxf(m1, __shfl_xor_sync(0xffffffffu, m1, 1));
      m0 = fmaxf(m0, __shfl_xor_sync(0xffffffffu, m0, 2)); m1 = fmaxf(m1, __shfl_xor_sync(0xffffffffu, m1, 2));
      float s0 = 0.f, s1 = 0.f;
#pragma unroll
      for (int n = 0; n < 5; n++) {
#pragma unroll
        for (int e = 0; e < 2; e++) {
          sa[4 * n + e] = ex2f((sa[4 * n + e] - m0) * cs); sa[4 * n + 2 + e] = ex2f((sa[4 * n + 2 + e] - m1) * cs);
          s0 += sa[4 * n + e]; s1 += sa[4 * n + 2 + e];
        }
      }
      s0 += __shfl_xor_sync(0xffffffffu, s0, 1); s1 += __shfl_xor_sync(0xffffffffu, s1, 1);
      s0 += __shfl_xor_sync(0xffffffffu, s0, 2); s1 += __shfl_xor_sync(0xffffffffu, s1, 2);
      const float i0 = rcpf(s0), i1 = rcpf(s1);
#pragma unroll
      for (int n = 0; n < 5; n++) {
        const uint32_t x = pack_bf16(sa[4 * n] * i0, sa[4 * n + 1] * i0), y = pack_bf16(sa[4 * n + 2] * i1, sa[4 * n + 3] * i1);
        if (n < 4) {
          pf[n >> 1][2 * (n & 1)] = second ? 0u : x; pf[n >> 1][2 * (n & 1) + 1] = second ? 0u : y;
          pf[2 + (n >> 1)][2 * (n & 1)] = second ? x : 0u; pf[2 + (n >> 1)][2 * (n & 1) + 1] = second ? y : 0u;
        } else {
          pf[4][0] = second ? 0u : x; pf[4][1] = second ? 0u : y; pf[4][2] = second ? x : 0u; pf[4][3] = second ? y : 0u;
        }
      }
    }
    {
      float o[96];
#pragma unroll
      for (int i = 0; i < 5; i++) { PIN(pf[i][0]); PIN(pf[i][1]); PIN(pf[i][2]); PIN(pf[i][3]); }
      const uint32_t own = own_slot(), vbase = sb + own * STQ;
      wgmma_fence();
#pragma unroll
      for (int i = 0; i < 5; i++)
        wgmma_rs_n192<1>(o, pf[i][0], pf[i][1], pf[i][2], pf[i][3], i < 4 ? make_desc(vbase + (i >> 1) * SEGB + (i & 1) * 256, 128, 640, 0) : make_desc(vbase + 512, SEGB, 640, 0), i != 0);
      wgmma_commit();
      if (type == T_A) mbar_wait(barK + 8 * wg, kph);
      kph ^= 1;
      wgmma_wait<0>();
      mbar_arrive_if((threadIdx.x & 127) == 0, empty + 8 * own);
      stage_tiles<192>(o, ost, wi, lane);
      fence_proxy_async();
      __syncwarp();
      mbar_arrive_if(lane == 0, done);
    }
  }
}
namespace bf {
constexpr int NS = 4, STAGE = 16384 + 32768;
constexpr int PIECE = 20480;
constexpr int OFF_PHI = 0, OFF_V = 40960, OFF_KV = 65536;
constexpr int OFF_OST = 5 * PIECE;
constexpr int OFF_WOT = 6 * PIECE;
constexpr int OFF_BAR = OFF_WOT + 102400;
constexpr int SMEM = OFF_BAR + 256;
static_assert(NS * STAGE <= OFF_BAR && SMEM <= 232448, "smem");
constexpr int KVACC = 32 * 5 * 1024;
struct Args {
  const unsigned char *wb, *wot;
  unsigned char *kvacc, *o2;
  const bf16* xin;
  bf16* xout;
  const bf16 *pf0, *pf1;
  int tl;
};
}
__device__ __forceinline__ void hedgehog_features(float (&x)[2][5], uint32_t (&w)[2][5]) {
  const float L = 1.4426950408889634f;
  float mx[2], mn[2], sp[2], sn[2], pos[2][5], neg[2][5];
#pragma unroll
  for (int r = 0; r < 2; r++) {
    mx[r] = fmaxf(fmaxf(fmaxf(x[r][0], x[r][1]), fmaxf(x[r][2], x[r][3])), x[r][4]);
    mn[r] = fminf(fminf(fminf(x[r][0], x[r][1]), fminf(x[r][2], x[r][3])), x[r][4]);
  }
#pragma unroll
  for (int o = 1; o < 4; o <<= 1)
#pragma unroll
    for (int r = 0; r < 2; r++) {
      const uint32_t t = __shfl_xor_sync(0xffffffffu, __byte_perm(__float_as_uint(mn[r]), __float_as_uint(mx[r]), 0x7632), o);
      mx[r] = fmaxf(mx[r], bf_hi(t)); mn[r] = fminf(mn[r], bf_lo(t));
    }
#pragma unroll
  for (int r = 0; r < 2; r++) {
#pragma unroll
    for (int i = 0; i < 5; i++) { pos[r][i] = ex2f((x[r][i] - mx[r]) * L); neg[r][i] = ex2f((mn[r] - x[r][i]) * L); }
    sp[r] = ((pos[r][0] + pos[r][1]) + (pos[r][2] + pos[r][3])) + pos[r][4];
    sn[r] = ((neg[r][0] + neg[r][1]) + (neg[r][2] + neg[r][3])) + neg[r][4];
  }
#pragma unroll
  for (int o = 1; o < 4; o <<= 1)
#pragma unroll
    for (int r = 0; r < 2; r++) { sp[r] += __shfl_xor_sync(0xffffffffu, sp[r], o); sn[r] += __shfl_xor_sync(0xffffffffu, sn[r], o); }
#pragma unroll
  for (int r = 0; r < 2; r++) {
    const float ip = rcpf(sp[r]), in_ = rcpf(sn[r]);
    w[r][0] = pack_bf16(pos[r][0] * ip, pos[r][1] * ip); w[r][1] = pack_bf16(pos[r][2] * ip, pos[r][3] * ip);
    w[r][2] = pack_bf16(neg[r][0] * in_, neg[r][1] * in_); w[r][3] = pack_bf16(neg[r][2] * in_, neg[r][3] * in_);
    w[r][4] = pack_bf16(pos[r][4] * ip, neg[r][4] * in_);
  }
}
__device__ __forceinline__ void bulk_g2s_mc(uint32_t dst, const void* src, uint32_t bytes, uint32_t mb) {
  asm volatile("cp.async.bulk.shared::cluster.global.mbarrier::complete_tx::bytes.multicast::cluster [%0], [%1], %2, [%3], %4;"
               :: "r"(dst), "l"(src), "r"(bytes), "r"(mb), "h"((unsigned short)3) : "memory");
}
__device__ __forceinline__ void mbar_arrive_remote_if(bool c, uint32_t b) {
  asm volatile("{\n.reg .pred p;\nsetp.ne.u32 p, %1, 0;\n@p mbarrier.arrive.shared::cluster.b64 _, [%0];\n}" :: "r"(b), "r"((uint32_t)c) : "memory");
}

__global__ void __cluster_dims__(2, 1, 1) __launch_bounds__(384, 1) blayer_kernel(const __grid_constant__ CUtensorMap tmA, const __grid_constant__ bf::Args a) {
  using namespace bf;
  [[maybe_unused]] const int tl = a.tl;
  extern __shared__ __align__(1024) unsigned char smem_raw[];
  const uint32_t sb = smem_u32(smem_raw);
  const int warp = __shfl_sync(0xffffffffu, (int)threadIdx.x >> 5, 0), lane = threadIdx.x & 31;
  const uint32_t full = sb + OFF_BAR, empty = full + 8 * NS, full2 = empty + 8 * NS, empty2 = full2 + 64, barW = empty2 + 16, drained = barW + 8, staged = drained + 8, freeb = staged + 8;
  const int rank = blockIdx.x & 1, u = (blockIdx.x >> 1) & 7, mp = blockIdx.x >> 4;
  const int m = 2 * mp + rank;
  const int m2 = 2 * mp + (u & 1), ns = (u & ~1) + rank;
  const uint32_t dpeer = mapa_u32(sb, rank ^ 1) - sb;
  unsigned* cntO = (unsigned*)(a.kvacc + KVACC);
  if (threadIdx.x == 0) {
    for (int i = 0; i < NS; i++) { mbar_init(full + 8 * i, 1); mbar_init(empty + 8 * i, 4); }
    for (int i = 0; i < 8; i++) mbar_init(full2 + 8 * i, 1);
    mbar_init(empty2, 2); mbar_init(empty2 + 8, 2);
    mbar_init(barW, 1); mbar_init(drained, 1); mbar_init(staged, 8); mbar_init(freeb, 2);
    asm volatile("fence.mbarrier_init.release.cluster;" ::: "memory");
  }
  __syncthreads();
  asm volatile("barrier.cluster.arrive.relaxed.aligned; barrier.cluster.wait.aligned;" ::: "memory");
  if (warp >= 8) {
    asm volatile("setmaxnreg.dec.sync.aligned.u32 40;");
    if (warp == 8) { if (elect_one()) {
      const unsigned char* wsrc = a.wb + (size_t)u * 327680 + rank * 16384;
      asm volatile("fence.proxy.async.global;" ::: "memory");
      for (int kb = 0; kb < NS; kb++) {
        mbar_expect_tx(full + 8 * kb, STAGE);
        bulk_g2s_mc(sb + kb * STAGE + 16384 + rank * 16384, wsrc + kb * 32768, 16384, full + 8 * kb);
      }
      asm volatile("griddepcontrol.wait;" ::: "memory");
      TL_BEGIN0(tl);
      for (int kb = 0; kb < NS; kb++) tma_load_2d(sb + kb * STAGE, &tmA, kb * 64, m * 128, full + 8 * kb);
      if (a.pf0) {
        constexpr uint32_t PER = cfg::DM * cfg::HD * 2 / 128;
        prefetch_l2((const unsigned char*)a.pf0 + blockIdx.x * PER, PER); prefetch_l2((const unsigned char*)a.pf1 + blockIdx.x * PER, PER);
      }
      if (m == 0) prefetch_l2(a.kvacc + u * (KVACC / 8), KVACC / 8);
#pragma unroll 1
      for (int kb = NS; kb < 10; kb++) {
        const uint32_t s = kb & 3, st = sb + s * STAGE, fb = full + 8 * s;
        mbar_wait(empty + 8 * s, ((kb >> 2) - 1) & 1);
        mbar_expect_tx(fb, STAGE);
        tma_load_2d(st, &tmA, kb * 64, m * 128, fb);
        bulk_g2s_mc(st + 16384 + rank * 16384, wsrc + kb * 32768, 16384, fb);
      }
      for (int i = 0; i < 6; i++) mbar_expect_tx(full2 + 8 * i, PIECE);
      mbar_wait(drained, 0);
      mbar_expect_tx(barW, 102400);
      bulk_g2s(sb + OFF_WOT, a.wot + (size_t)ns * 102400, 102400, barW);
      mbar_wait(staged, 0);
      bulk_s2g(a.o2 + (size_t)(m * 8 + u) * PIECE, sb + OFF_OST, PIECE);
      bulk_commit();
      bulk_wait<0>();
      asm volatile("red.relaxed.gpu.global.add.u32 [%0], 1;" :: "l"(cntO + m) : "memory");
      mbar_arrive(freeb); mbar_arrive_remote_if(true, freeb + dpeer);
      wait_ge(cntO + m2, 8, 20);
      mbar_wait(freeb, 0);
      fence_proxy_async_global();
      const unsigned char* osrc = a.o2 + (size_t)m2 * 8 * PIECE;
      for (int i = 0; i < 6; i++) bulk_g2s_mc(sb + i * PIECE + rank * (PIECE / 2), osrc + i * PIECE + rank * (PIECE / 2), PIECE / 2, full2 + 8 * i);
      for (int i = 0; i < 2; i++) {
        mbar_wait(empty2 + 8 * i, 0);
        mbar_expect_tx(full2 + 8 * (6 + i), PIECE);
        bulk_g2s(sb + i * PIECE, osrc + (6 + i) * PIECE, PIECE, full2 + 8 * (6 + i));
      }
    } }
    return;
  }
  asm volatile("setmaxnreg.inc.sync.aligned.u32 232;");
  const int wg = warp >> 2, wi = warp & 3;
  const int q4 = lane & 3;
  const bool lead = (threadIdx.x & 127) == 0;
  float acc[128];
  {
#pragma unroll 1
    for (int kb = 0; kb < 10; kb++) {
      const uint32_t s = kb & 3, st = sb + s * STAGE;
      mbar_wait(full + 8 * s, (kb >> 2) & 1);
      wgmma_fence();
#pragma unroll
      for (int kk = 0; kk < 4; kk++) wgmma_n256<0, 1>(acc, desc_kmajor(st + wg * 8192 + kk * 32), make_desc(st + 16384 + kk * 8192, 4096, 128, 0), (kb | kk) != 0);
      wgmma_commit();
      if (kb > 0 && kb < 7) { wgmma_wait<1>(); const uint32_t e = empty + 8 * ((kb - 1) & 3); mbar_arrive_if(lead, e); mbar_arrive_remote_if(lead, e + dpeer); }
    }
    wgmma_wait<0>();
    bar_sync(1, 256);
    mbar_arrive_if(threadIdx.x == 0, drained);
  }
  TL2((tl >= 12 ? 128 : 0) + 32 + 0);
  const uint32_t srow = (wg * 64 + wi * 16 + (lane & 15)) * 16 + (lane >> 4) * 2048;
  auto features = [&](auto T0, auto HH, uint32_t (&w)[2][5]) {
    constexpr int t = T0.value + 5 * (HH.value >> 1), o = (HH.value & 1) ? 3 : 0, e = HH.value & 1;
    float x[2][5];
#pragma unroll
    for (int r = 0; r < 2; r++) {
      x[r][0] = acc[4 * (t + o) + 2 * r]; x[r][1] = acc[4 * (t + o) + 2 * r + 1]; x[r][2] = acc[4 * (t + o + 1) + 2 * r]; x[r][3] = acc[4 * (t + o + 1) + 2 * r + 1];
      bf16r2(x[r][0], x[r][1]); bf16r2(x[r][2], x[r][3]);
    }
    x[0][4] = acc[4 * (t + 2) + e]; x[1][4] = acc[4 * (t + 2) + 2 + e];
    bf16r2(x[0][4], x[1][4]);
    hedgehog_features(x, w);
  };
  static_for<0, 4>([&](auto HH) {
    constexpr int hh = HH.value, t = 20 + 3 * hh;
    const uint32_t one = q4 == ((hh & 1) ? 0 : 2) ? 0x3f80u : 0u;
    const uint32_t va = sb + OFF_V + hh * 6144 + srow;
    stsm_x4(va, pack_bf16(acc[4 * t], acc[4 * t + 1]), pack_bf16(acc[4 * t + 2], acc[4 * t + 3]), pack_bf16(acc[4 * t + 4], acc[4 * t + 5]), pack_bf16(acc[4 * t + 6], acc[4 * t + 7]));
    const bool pad = (q4 >= 2) != (hh & 1);
    stsm_x2(va + 4096, pad ? one : pack_bf16(acc[4 * t + 8], acc[4 * t + 9]), pad ? one : pack_bf16(acc[4 * t + 10], acc[4 * t + 11]));
    uint32_t w[2][5];
    features(IC<10>{}, HH, w);
    const uint32_t pa = sb + OFF_PHI + hh * 10240 + srow;
    stsm_x4(pa, w[0][0], w[1][0], w[0][1], w[1][1]);
    stsm_x4(pa + 4096, w[0][2], w[1][2], w[0][3], w[1][3]);
    stsm_x2(pa + 8192, w[0][4], w[1][4]);
  });
  fence_proxy_async();
  bar_sync(1, 256);
  TL2((tl >= 12 ? 128 : 0) + 32 + 1);
  {
    float d0[12], d1[12];
    const uint32_t pa = sb + OFF_PHI + wg * 20480, pv = sb + OFF_V + wg * 12288;
    wgmma_fence();
#pragma unroll
    for (int k = 0; k < 8; k++) {
      wgmma_n24<1, 1>(d0, make_desc(pa + k * 256, 128, 2048, 0), make_desc(pv + k * 256, 128, 2048, 0), k != 0);
      wgmma_n24<1, 1>(d1, make_desc(pa + 10240 + k * 256, 128, 2048, 0), make_desc(pv + 6144 + k * 256, 128, 2048, 0), k != 0);
    }
    wgmma_commit();
    wgmma_wait<0>();
    unsigned char* dst = a.kvacc + ((u * 4 + wg * 2) * 5 + 2 * wi) * 1024 + lane * 16;
    auto red4 = [&](bool on, unsigned char* p, float x, float y, float z) {
      asm volatile("{\n.reg .pred p;\nsetp.ne.u32 p, %4, 0;\n@p red.relaxed.gpu.global.add.v4.f32 [%0], {%1,%2,%3,%5};\n}" :: "l"(p), "f"(x), "f"(y), "f"(z), "r"((uint32_t)on), "f"(1.f) : "memory");
    };
    red4(wi < 3, dst, d0[0], d0[1], d0[4]); red4(wi < 3, dst + 512, d0[5], d0[8], d0[9]);
    red4(wi < 3, dst + 5120, d1[0], d1[1], d1[4]); red4(wi < 3, dst + 5632, d1[5], d1[8], d1[9]);
    red4(wi < 2, dst + 1024, d0[2], d0[3], d0[6]); red4(wi < 2, dst + 1536, d0[7], d0[10], d0[11]);
    red4(wi < 2, dst + 6144, d1[2], d1[3], d1[6]); red4(wi < 2, dst + 6656, d1[7], d1[10], d1[11]);
  }
  TL2((tl >= 12 ? 128 : 0) + 32 + 2);
  uint32_t qf[4][2][5];
  static_for<0, 4>([&](auto HH) { features(IC<0>{}, HH, qf[HH.value]); });
  uint4 xr[5];
#pragma unroll
  for (int i = 0; i < 5; i++) {
    const int c = lane + 32 * i;
    xr[i] = __ldcg((const uint4*)(a.xin + (size_t)(m2 * 128 + wg * 64 + wi * 16 + c / 10) * cfg::DM + ns * 80 + (c % 10) * 8));
  }
  {
    const unsigned char* src = a.kvacc + (u * 20 + warp) * 1024 + lane * 16;
    uint4 v[6];
    int spin = 0;
    while (true) {
      v[0] = ld_relaxed_v4_i<0>(src); v[1] = ld_relaxed_v4_i<512>(src); v[2] = ld_relaxed_v4_i<8192>(src); v[3] = ld_relaxed_v4_i<8704>(src);
      v[4] = ld_relaxed_v4_i<0>(src + (wg ? 0 : 16384)); v[5] = ld_relaxed_v4_i<512>(src + (wg ? 0 : 16384));
      const uint32_t c = (v[0].w & v[1].w & v[2].w) & (v[3].w & v[4].w & v[5].w);
      if (!__any_sync(0xffffffffu, (c & 0x41800000u) != 0x41800000u) || ++spin >= SPIN_LIMIT) break;
      __nanosleep(100);
    }
    const uint32_t kd = sb + OFF_KV + warp * 384 + lane * 4;
#pragma unroll
    for (int i = 0; i < 3; i++)
      if (i < 2 || wg == 0) {
        sts32(kd + i * 3072, pack_bf16(__uint_as_float(v[2 * i].x), __uint_as_float(v[2 * i].y)));
        sts32(kd + i * 3072 + 128, pack_bf16(__uint_as_float(v[2 * i].z), __uint_as_float(v[2 * i + 1].x)));
        sts32(kd + i * 3072 + 256, pack_bf16(__uint_as_float(v[2 * i + 1].y), __uint_as_float(v[2 * i + 1].z)));
      }
  }
  fence_proxy_async();
  bar_sync(1, 256);
  TL2((tl >= 12 ? 128 : 0) + 32 + 3);
  {
    float d[4][12];
    uint32_t zero = 0; PIN(zero);
#pragma unroll
    for (int hh = 0; hh < 4; hh++)
#pragma unroll
      for (int i = 0; i < 5; i++) { PIN(qf[hh][0][i]); PIN(qf[hh][1][i]); }
    wgmma_fence();
#pragma unroll
    for (int hh = 0; hh < 4; hh++) {
      const uint32_t kb = sb + OFF_KV + hh * 1920;
      wgmma_rs_n24<1>(d[hh], qf[hh][0][0], qf[hh][1][0], qf[hh][0][1], qf[hh][1][1], make_desc(kb, 384, 128, 0), 0);
      wgmma_rs_n24<1>(d[hh], qf[hh][0][2], qf[hh][1][2], qf[hh][0][3], qf[hh][1][3], make_desc(kb + 768, 384, 128, 0), 1);
      wgmma_rs_n24<1>(d[hh], qf[hh][0][4], qf[hh][1][4], zero, zero, make_desc(kb + 1536, 0, 128, 0), 1);
    }
    wgmma_commit();
    wgmma_wait<0>();
    uint32_t ow[4][6];
#pragma unroll
    for (int hh = 0; hh < 4; hh++) {
      const int zl = (lane & ~3) | ((hh & 1) ? 0 : 2);
      const float da = bf16r(bf16r(__shfl_sync(0xffffffffu, d[hh][8], zl)) + 1e-6f), db = bf16r(bf16r(__shfl_sync(0xffffffffu, d[hh][10], zl)) + 1e-6f);
#pragma unroll
      for (int n = 0; n < 3; n++) {
        bf16r2(d[hh][4 * n], d[hh][4 * n + 1]); bf16r2(d[hh][4 * n + 2], d[hh][4 * n + 3]);
        ow[hh][2 * n] = pack_bf16(__fdividef(d[hh][4 * n], da), __fdividef(d[hh][4 * n + 1], da));
        ow[hh][2 * n + 1] = pack_bf16(__fdividef(d[hh][4 * n + 2], db), __fdividef(d[hh][4 * n + 3], db));
      }
    }
#pragma unroll
    for (int p = 0; p < 2; p++) {
      const uint32_t oa = sb + OFF_OST + p * 10240 + srow;
      stsm_x4(oa, ow[2 * p][0], ow[2 * p][1], ow[2 * p][2], ow[2 * p][3]);
      stsm_x2(oa + 4096, q4 < 2 ? ow[2 * p][4] : ow[2 * p + 1][4], q4 < 2 ? ow[2 * p][5] : ow[2 * p + 1][5]);
      stsm_x4(oa + 6144, ow[2 * p + 1][0], ow[2 * p + 1][1], ow[2 * p + 1][2], ow[2 * p + 1][3]);
    }
    fence_proxy_async();
    __syncwarp();
    mbar_arrive_if(lane == 0, staged);
  }
  TL2((tl >= 12 ? 128 : 0) + 32 + 4);
  float c2[40];
  mbar_wait(barW, 0);
#pragma unroll 1
  for (int i = 0; i < 8; i++) {
    mbar_wait(full2 + 8 * i, 0);
    const uint32_t st = sb + (i < 6 ? i : i - 6) * PIECE + wg * 1024, wo = sb + OFF_WOT + i * 12800;
    wgmma_fence();
#pragma unroll
    for (int kk = 0; kk < 5; kk++) wgmma_n80<0, 1>(c2, make_desc(st + kk * 4096, 2048, 128, 0), make_desc(wo + kk * 2560, 1280, 128, 0), (i | kk) != 0);
    wgmma_commit();
    if (i == 1 || i == 2) { wgmma_wait<1>(); mbar_arrive_if(lead, empty2 + 8 * (i - 1)); }
  }
  wgmma_wait<0>();
  TL2((tl >= 12 ? 128 : 0) + 32 + 5);
  {
    bar_sync(1, 256);
    const uint32_t ost = sb + 2 * PIECE + warp * 3072;
#pragma unroll
    for (int v = 0; v < 10; v += 2)
      stsm_x4(ost + (lane & 15) * 176 + (v + (lane >> 4)) * 16, pack_bf16(c2[4 * v], c2[4 * v + 1]), pack_bf16(c2[4 * v + 2], c2[4 * v + 3]),
              pack_bf16(c2[4 * v + 4], c2[4 * v + 5]), pack_bf16(c2[4 * v + 6], c2[4 * v + 7]));
    __syncwarp();
#pragma unroll
    for (int i = 0; i < 5; i++) {
      const int c = lane + 32 * i, row = c / 10, chunk = c % 10;
      const uint4 y = lds128(ost + row * 176 + chunk * 16);
      const size_t off = (size_t)(m2 * 128 + wg * 64 + wi * 16 + row) * cfg::DM + ns * 80 + chunk * 8;
      const uint4 x = xr[i];
      *(uint4*)(a.xout + off) = make_uint4(pack_bf16(bf_lo(x.x) + bf_lo(y.x), bf_hi(x.x) + bf_hi(y.x)), pack_bf16(bf_lo(x.y) + bf_lo(y.y), bf_hi(x.y) + bf_hi(y.y)),
                                           pack_bf16(bf_lo(x.z) + bf_lo(y.z), bf_hi(x.z) + bf_hi(y.z)), pack_bf16(bf_lo(x.w) + bf_lo(y.w), bf_hi(x.w) + bf_hi(y.w)));
    }
  }
  TL_END(tl);
}
__device__ __align__(32768) unsigned char g_arena[AR_SIZE];
__device__ __align__(1024) uint2 g_xh[2048 * 160];
__device__ __align__(1024) unsigned char g_k[64 * 96 * 5120], g_v[64 * 96 * 5120];
__device__ __align__(1024) bf16 g_o[2048 * 6144];
__device__ __align__(1024) uint4 g_qs[8 * 32 * 12 * 256];
__device__ __align__(1024) bf16 g_xn[2048 * 640], g_xn2[2048 * 640], g_xa[2048 * 640], g_xb[2048 * 640];
__device__ __align__(1024) bf16 g_part[24 * 2048 * 640];
__device__ __align__(1024) bf16 g_wb[2048 * 640], g_wot[640 * 640], g_pq[2048 * 640];
__device__ __align__(1024) float g_kvacc[bf::KVACC / 4 + 64];

typedef CUresult (*EncodeFn)(CUtensorMap*, CUtensorMapDataType, cuuint32_t, void*, const cuuint64_t*, const cuuint64_t*, const cuuint32_t*,
                             const cuuint32_t*, CUtensorMapInterleave, CUtensorMapSwizzle, CUtensorMapL2promotion, CUtensorMapFloatOOBfill);
static EncodeFn g_encode = nullptr;
static CUtensorMap make_map(const void* p, uint64_t cols, uint64_t rows, uint32_t bc, uint32_t br, bool swz = true) {
  CUtensorMap m;
  cuuint64_t dims[2] = {cols, rows}, strides[1] = {cols * 2};
  cuuint32_t box[2] = {bc, br}, es[2] = {1, 1};
  g_encode(&m, CU_TENSOR_MAP_DATA_TYPE_BFLOAT16, 2, const_cast<void*>(p), dims, strides, box, es, CU_TENSOR_MAP_INTERLEAVE_NONE,
           swz ? CU_TENSOR_MAP_SWIZZLE_128B : CU_TENSOR_MAP_SWIZZLE_NONE, CU_TENSOR_MAP_L2_PROMOTION_L2_256B, CU_TENSOR_MAP_FLOAT_OOB_FILL_NONE);
  return m;
}
static CUtensorMap make_map3(const void* p, uint64_t cols, uint64_t rows, uint32_t nb) {
  CUtensorMap m;
  cuuint64_t dims[3] = {64, rows, cols / 64}, strides[2] = {cols * 2, 128};
  cuuint32_t box[3] = {64, 64, nb}, es[3] = {1, 1, 1};
  g_encode(&m, CU_TENSOR_MAP_DATA_TYPE_BFLOAT16, 3, const_cast<void*>(p), dims, strides, box, es, CU_TENSOR_MAP_INTERLEAVE_NONE,
           CU_TENSOR_MAP_SWIZZLE_128B, CU_TENSOR_MAP_L2_PROMOTION_L2_256B, CU_TENSOR_MAP_FLOAT_OOB_FILL_NONE);
  return m;
}
template <class T> static T* sym(const T& s) { void* p = nullptr; cudaGetSymbolAddress(&p, s); return (T*)p; }

struct Ptrs {
  unsigned char *arena, *k, *v; bf16 *o, *xn, *xa, *xb, *wb, *wot, *pq; float *part, *kvacc; uint2* xh; uint4* qs; bf16* xn2;
};

static tr::Sched make_sched(const char* str, const int* ks, const int* lr) {
  using namespace tr;
  Sched s = {};
  int n = 0;
  for (int b = 0; b < 16; b++) { s.ks[b] = (uint8_t)abs(ks[b]); s.wide[b] = ks[b] > 0; s.lrows[b] = (uint8_t)lr[b]; }
  for (const char* p = str; *p;) {
    if (*p == ' ') { p++; continue; }
    const char c = *p++;
    char* e;
    const int b = (int)strtol(p, &e, 10); p = e;
    int first = 0, cnt = c == 'o' ? s.ks[b] * (s.wide[b] ? 2 : 5) : (c == 'l' ? 16 / lr[b] : 32);
    if (*p == '.') { first = (int)strtol(p + 1, &e, 10); cnt = (int)strtol(e + 1, &e, 10); p = e; }
    const int type = c == 'a' ? T_QA : (c == 'q' ? T_Q : (c == 't' ? T_A : (c == 'l' ? T_L : (s.wide[b] ? T_OB : T_OS))));
    for (int i = 0; i < cnt && n < MAXITEMS - 1; i++) s.item[n++] = (uint16_t)((type << 11) | (b << 7) | (first + i));
  }
  s.n = n; s.item[n] = T_END << 11;
  return s;
}
static tr::Sched sched_of(int layer) {
  const char* str = "q13 q14 a0 q15 a1 o0 a2 o1 a3 o2 a4 o3 a5 o4 l0 a6 o5 l1 a7 o6 l2 a8 o7 l3 a9 o8 l4 a10 o9 l5 a11 o10 l6 a12 o11 l7 t13 o12 t14 t15 o13 o14 l8 l9 l10 l11 o15 l12 l13 l14 l15";
  int ks[16] = {2, 2, 2, 2, 2, 2, 2, 2, 2, 2, 3, 4, 6, -8, -8, -12}, lr[16] = {4, 4, 4, 4, 4, 4, 4, 4, 2, 1, 1, 1, 1, 1, 1, 1};
#ifdef TUNE
  if (getenv("SCHED")) str = getenv("SCHED");
  if (layer == 0 && getenv("SCHED0")) str = getenv("SCHED0");
  if (const char* p = getenv("KS")) for (int b = 0; b < 16; b++) { char* e; ks[b] = (int)strtol(p, &e, 10); p = e; }
  if (const char* p = getenv("LR")) for (int b = 0; b < 16; b++) { char* e; lr[b] = (int)strtol(p, &e, 10); p = e; }
#endif
  return make_sched(str, ks, lr);
}
#ifndef TRAIL_GRID
#define TRAIL_GRID 132
#endif
#ifndef PDL_LN
#define PDL_LN 0
#endif
#ifndef PDL_CH
#define PDL_CH 1
#endif
#ifndef PDL_B
#define PDL_B 1
#endif
#ifndef PFW
#define PFW 100
#endif
#ifndef PF_A
#define PF_A 1
#endif
#ifndef PF_B
#define PF_B 0
#endif
extern "C" void kernel_launch(void* const* d_in, const int* in_sizes, int n_in, void* d_out, int out_size) {
  const bf16* x = (const bf16*)d_in[0];
  const bf16* mem0 = (const bf16*)d_in[1];
  const bf16 *Wq = (const bf16*)d_in[2], *Wk = (const bf16*)d_in[3], *Wv = (const bf16*)d_in[4], *Wo = (const bf16*)d_in[5];
  const bf16 *wqkv = (const bf16*)d_in[8], *wphi = (const bf16*)d_in[9], *wo = (const bf16*)d_in[10];
  bf16* out = (bf16*)d_out;
  static Ptrs P; static bool init = false;
  if (!init) {
    void* fn = nullptr; cudaDriverEntryPointQueryResult qr;
    cudaGetDriverEntryPoint("cuTensorMapEncodeTiled", &fn, cudaEnableDefault, &qr);
    g_encode = (EncodeFn)fn;
    void* p;
    cudaGetSymbolAddress(&p, g_arena); P.arena = (unsigned char*)p;
    cudaGetSymbolAddress(&p, g_k); P.k = (unsigned char*)p;   cudaGetSymbolAddress(&p, g_v); P.v = (unsigned char*)p;
    cudaGetSymbolAddress(&p, g_o); P.o = (bf16*)p;
    cudaGetSymbolAddress(&p, g_xn); P.xn = (bf16*)p;
    cudaGetSymbolAddress(&p, g_xa); P.xa = (bf16*)p;   cudaGetSymbolAddress(&p, g_xb); P.xb = (bf16*)p;
    cudaGetSymbolAddress(&p, g_wb); P.wb = (bf16*)p;   cudaGetSymbolAddress(&p, g_wot); P.wot = (bf16*)p;
    cudaGetSymbolAddress(&p, g_pq); P.pq = (bf16*)p;   cudaGetSymbolAddress(&p, g_part); P.part = (float*)p;
    cudaGetSymbolAddress(&p, g_kvacc); P.kvacc = (float*)p;
    cudaGetSymbolAddress(&p, g_xh); P.xh = (uint2*)p;
    cudaGetSymbolAddress(&p, g_qs); P.qs = (uint4*)p;
    cudaGetSymbolAddress(&p, g_xn2); P.xn2 = (bf16*)p;
    cudaFuncSetAttribute(chain_kernel, cudaFuncAttributeMaxDynamicSharedMemorySize, ch::SMEM);
    cudaFuncSetAttribute(trail_kernel, cudaFuncAttributeMaxDynamicSharedMemorySize, tr::SMEM);
    cudaFuncSetAttribute(blayer_kernel, cudaFuncAttributeMaxDynamicSharedMemorySize, bf::SMEM);
    init = true;
  }
  const CUtensorMap tmXn = make_map(P.xn, 640, 2048, 64, 128), tmXn2 = make_map(P.xn2, 640, 2048, 64, 128);
  const CUtensorMap tmWq = make_map3(Wq, 6144, 640, 3);
  const CUtensorMap tmCq = make_map(Wq, 6144, 640, 64, 160), tmCk = make_map(Wk, 6144, 640, 64, 160), tmCv = make_map(Wv, 6144, 640, 64, 160), tmCo = make_map(Wo, 640, 6144, 224, 64, false);
  const CUtensorMap tmWo5 = make_map3(Wo, 640, 6144, 5), tmWo2 = make_map3(Wo, 640, 6144, 2);

  ChainArgs ca;
  ca.xh = P.xh; ca.mem0 = mem0; ca.kg = P.k; ca.vg = P.v;
  ca.arena = P.arena; ca.dbg = nullptr; ca.delay = POLL_DELAY; ca.margin = 150;
#ifdef TUNE
  if (getenv("MG")) ca.margin = atoi(getenv("MG"));
  if (getenv("PD")) ca.delay = atoi(getenv("PD"));
#endif
  ca.tl = 0;
  uint4* zar = (uint4*)P.arena; const int nzar = AR_SIZE / 16;
  uint4* zkv = (uint4*)P.kvacc; const int nzkv = (bf::KVACC / 4 + 64) / 4;

  const PrepArgs pa{wqkv, wphi, wo, (unsigned char*)P.wb, (unsigned char*)P.wot};
  const bf16* xcur = x;
  cudaLaunchAttribute at[1];
  at[0].id = cudaLaunchAttributeProgrammaticStreamSerialization; at[0].val.programmaticStreamSerializationAllowed = 1;
  auto cfgof = [&](int grid, int block, int smem, bool pdl) {
    cudaLaunchConfig_t lc = {};
    lc.gridDim = dim3(grid); lc.blockDim = dim3(block); lc.dynamicSmemBytes = smem; lc.stream = cudaStreamPerThread;
    lc.attrs = at; lc.numAttrs = pdl ? 1 : 0;
    return lc;
  };
  for (int layer = 0; layer < 2; layer++) {
    const int tl = layer * 12;
    cudaLaunchConfig_t lc = cfgof(256, 256, 0, layer > 0 && PDL_LN);
    cudaLaunchKernelEx(&lc, ln_kernel, xcur, P.xn, P.xh, zar, nzar, zkv, nzkv, Wk, Wv, layer == 0 ? PF_A : 0, tl + 0);
    ca.tl = tl + 2; ca.pfw = layer == 0 ? PFW : 100;
#ifdef TUNE
    if (getenv("PFW") && layer == 0) ca.pfw = atoi(getenv("PFW"));
#endif
    lc = cfgof(96, 384, ch::SMEM, PDL_CH);
    cudaLaunchKernelEx(&lc, chain_kernel, ca, tmCq, tmCk, tmCv, tmCo);
    lc = cfgof(TRAIL_GRID, 384, tr::SMEM, true);
    tr::Args ta{P.k, P.v, (unsigned char*)P.o, P.qs, (unsigned char*)P.part, xcur, P.xn, P.xa, P.xn2, P.arena, layer == 0 ? 1 : 0, tl + 4, 500, 100, 8};
#ifdef TUNE
    if (getenv("NAP")) ta.nap = atoi(getenv("NAP"));
    if (getenv("LW")) ta.lwait = atoi(getenv("LW"));
    if (getenv("NAP2")) ta.nap2 = atoi(getenv("NAP2"));
#endif
    cudaLaunchKernelEx(&lc, trail_kernel, tmXn, tmWq, tmWo5, tmWo2, sched_of(layer), ta, pa);
    lc = cfgof(128, 384, bf::SMEM, PDL_B);
    bf::Args ba{(const unsigned char*)P.wb, (const unsigned char*)P.wot, (unsigned char*)P.kvacc, (unsigned char*)P.pq, P.xa, layer == 0 ? P.xb : out,
                      layer == 0 && PF_B ? Wk : nullptr, Wv, tl + 7};
#ifdef TUNE
    if (getenv("PFB")) ba.pf0 = layer == 0 && atoi(getenv("PFB")) ? Wk : nullptr;
#endif
    cudaLaunchKernelEx(&lc, blayer_kernel, tmXn2, ba);
    xcur = P.xb;
  }
}
```

```cpp
#include <cuda_runtime.h>
#include <cuda.h>
#include <cuda_bf16.h>
#include <stdint.h>
#include <stdlib.h>
#include <type_traits>

typedef __nv_bfloat16 bf16;

namespace cfg {
constexpr int S = 2048, DM = 640, H = 32, DH = 192, NSEG = 64, SEG = 32, NM = 8;
constexpr int HD = H * DH;
}

__device__ __forceinline__ uint32_t smem_u32(const void* p) { return (uint32_t)__cvta_generic_to_shared(p); }
__device__ __forceinline__ uint32_t mapa_u32(uint32_t a, uint32_t r) {
  uint32_t o; asm("mapa.shared::cluster.u32 %0, %1, %2;" : "=r"(o) : "r"(a), "r"(r)); return o;
}
__device__ __forceinline__ void mbar_init(uint32_t b, uint32_t c) {
  asm volatile("mbarrier.init.shared::cta.b64 [%0], %1;" :: "r"(b), "r"(c) : "memory");
}
__device__ __forceinline__ void mbar_expect_tx(uint32_t b, uint32_t bytes) {
  asm volatile("mbarrier.arrive.expect_tx.shared::cta.b64 _, [%0], %1;" :: "r"(b), "r"(bytes) : "memory");
}
__device__ __forceinline__ void mbar_arrive(uint32_t b) {
  asm volatile("mbarrier.arrive.shared::cta.b64 _, [%0];" :: "r"(b) : "memory");
}
__device__ __forceinline__ void mbar_arrive_if(bool c, uint32_t b) {
  asm volatile("{\n.reg .pred p;\nsetp.ne.u32 p, %1, 0;\n@p mbarrier.arrive.shared::cta.b64 _, [%0];\n}" :: "r"(b), "r"((uint32_t)c) : "memory");
}
__device__ __forceinline__ bool mbar_try(uint32_t b, uint32_t ph) {
  uint32_t p;
  asm volatile("{.reg .pred p; mbarrier.try_wait.parity.shared::cta.b64 p, [%1], %2; selp.u32 %0, 1, 0, p;}"
               : "=r"(p) : "r"(b), "r"(ph) : "memory");
  return p;
}
__device__ __forceinline__ bool mbar_try_cluster(uint32_t b, uint32_t ph) {
  uint32_t p;
  asm volatile("{.reg .pred p; mbarrier.try_wait.parity.acquire.cluster.shared::cta.b64 p, [%1], %2; selp.u32 %0, 1, 0, p;}"
               : "=r"(p) : "r"(b), "r"(ph) : "memory");
  return p;
}
#ifndef SPIN_LIMIT
#define SPIN_LIMIT (1 << 22)
#endif
__device__ __forceinline__ void mbar_wait(uint32_t b, uint32_t ph) {
  asm volatile("{\n.reg .pred p, q;\n.reg .u32 c;\nmov.u32 c, 0;\n"
               "W_%=:\nmbarrier.try_wait.parity.shared::cta.b64 p, [%0], %1;\n@p bra.uni D_%=;\n"
               "add.u32 c, c, 1;\nsetp.lt.u32 q, c, %2;\n@q bra.uni W_%=;\nD_%=:\n}"
               :: "r"(b), "r"(ph), "n"(SPIN_LIMIT) : "memory");
}
__device__ __forceinline__ void mbar_spin(uint32_t b, uint32_t ph) {
  asm volatile("{\n.reg .pred p, q;\n.reg .u32 c;\nmov.u32 c, 0;\n"
               "W_%=:\nmbarrier.test_wait.parity.shared::cta.b64 p, [%0], %1;\n@p bra D_%=;\n"
               "add.u32 c, c, 1;\nsetp.lt.u32 q, c, %2;\n@q bra W_%=;\nD_%=:\n}"
               :: "r"(b), "r"(ph), "n"(SPIN_LIMIT) : "memory");
}
#define PIN(x) asm volatile("" : "+r"(x))
__device__ __forceinline__ void mbar_wait_cluster(uint32_t b, uint32_t ph) {
  int s = 0;
  while (!mbar_try_cluster(b, ph)) { if (++s > SPIN_LIMIT) break; }
}
__device__ __forceinline__ void st_async_v2(uint32_t a, uint32_t x, uint32_t y, uint32_t mb) {
  asm volatile("st.async.weak.shared::cluster.mbarrier::complete_tx::bytes.v2.b32 [%0], {%1,%2}, [%3];"
               :: "r"(a), "r"(x), "r"(y), "r"(mb) : "memory");
}
__device__ __forceinline__ void st_async_v4(uint32_t a, uint32_t x, uint32_t y, uint32_t z, uint32_t w, uint32_t mb) {
  asm volatile("st.async.weak.shared::cluster.mbarrier::complete_tx::bytes.v4.b32 [%0], {%1,%2,%3,%4}, [%5];"
               :: "r"(a), "r"(x), "r"(y), "r"(z), "r"(w), "r"(mb) : "memory");
}
__device__ __forceinline__ void bulk_g2s(uint32_t dst, const void* src, uint32_t bytes, uint32_t mb) {
  asm volatile("cp.async.bulk.shared::cluster.global.mbarrier::complete_tx::bytes [%0], [%1], %2, [%3];"
               :: "r"(dst), "l"(src), "r"(bytes), "r"(mb) : "memory");
}
__device__ __forceinline__ void cp_async16(uint32_t dst, const void* src) {
  asm volatile("cp.async.cg.shared.global [%0], [%1], 16;" :: "r"(dst), "l"(src) : "memory");
}
__device__ __forceinline__ void cp_async_wait_all() { asm volatile("cp.async.wait_all;" ::: "memory"); }
__device__ __forceinline__ void fence_proxy_async() { asm volatile("fence.proxy.async.shared::cta;" ::: "memory"); }
__device__ __forceinline__ void bar_sync(int id, int n) { asm volatile("bar.sync %0, %1;" :: "r"(id), "r"(n) : "memory"); }
__device__ __forceinline__ void bar_arrive(int id, int n) { asm volatile("bar.arrive %0, %1;" :: "r"(id), "r"(n) : "memory"); }
__device__ __forceinline__ void cluster_sync_all() {
  asm volatile("barrier.cluster.arrive.release.aligned; barrier.cluster.wait.acquire.aligned;" ::: "memory");
}
__device__ __forceinline__ void ldsm_x4(uint32_t (&r)[4], uint32_t a) {
  asm volatile("ldmatrix.sync.aligned.m8n8.x4.shared.b16 {%0,%1,%2,%3}, [%4];"
               : "=r"(r[0]), "=r"(r[1]), "=r"(r[2]), "=r"(r[3]) : "r"(a) : "memory");
}
__device__ __forceinline__ void ldsm_x4_t(uint32_t (&r)[4], uint32_t a) {
  asm volatile("ldmatrix.sync.aligned.m8n8.x4.trans.shared.b16 {%0,%1,%2,%3}, [%4];"
               : "=r"(r[0]), "=r"(r[1]), "=r"(r[2]), "=r"(r[3]) : "r"(a) : "memory");
}
template <int IMM> __device__ __forceinline__ void ldsm_x4_i(uint32_t (&r)[4], uint32_t a) {
  asm volatile("ldmatrix.sync.aligned.m8n8.x4.shared.b16 {%0,%1,%2,%3}, [%4+%5];"
               : "=r"(r[0]), "=r"(r[1]), "=r"(r[2]), "=r"(r[3]) : "r"(a), "n"(IMM) : "memory");
}
template <int IMM> __device__ __forceinline__ void ldsm_x4_t_i(uint32_t (&r)[4], uint32_t a) {
  asm volatile("ldmatrix.sync.aligned.m8n8.x4.trans.shared.b16 {%0,%1,%2,%3}, [%4+%5];"
               : "=r"(r[0]), "=r"(r[1]), "=r"(r[2]), "=r"(r[3]) : "r"(a), "n"(IMM) : "memory");
}
template <int IMM> __device__ __forceinline__ uint4 lds128_i(uint32_t a) {
  uint4 v; asm volatile("ld.shared.v4.u32 {%0,%1,%2,%3}, [%4+%5];" : "=r"(v.x), "=r"(v.y), "=r"(v.z), "=r"(v.w) : "r"(a), "n"(IMM) : "memory"); return v;
}
template <int IMM> __device__ __forceinline__ uint2 lds64_i(uint32_t a) {
  uint2 v; asm volatile("ld.shared.v2.u32 {%0,%1}, [%2+%3];" : "=r"(v.x), "=r"(v.y) : "r"(a), "n"(IMM) : "memory"); return v;
}
template <int IMM> __device__ __forceinline__ void sts128_i(uint32_t a, uint32_t x, uint32_t y, uint32_t z, uint32_t w) {
  asm volatile("st.shared.v4.u32 [%0+%5], {%1,%2,%3,%4};" :: "r"(a), "r"(x), "r"(y), "r"(z), "r"(w), "n"(IMM) : "memory");
}
template <int IMM> __device__ __forceinline__ void sts64_i(uint32_t a, uint32_t x, uint32_t y) {
  asm volatile("st.shared.v2.u32 [%0+%3], {%1,%2};" :: "r"(a), "r"(x), "r"(y), "n"(IMM) : "memory");
}
template <int IMM> __device__ __forceinline__ void st_async_v2_i(uint32_t a, uint32_t x, uint32_t y, uint32_t mb) {
  asm volatile("st.async.weak.shared::cluster.mbarrier::complete_tx::bytes.v2.b32 [%0+%4], {%1,%2}, [%3];"
               :: "r"(a), "r"(x), "r"(y), "r"(mb), "n"(IMM) : "memory");
}
template <int IMM> __device__ __forceinline__ uint4 ld_relaxed_v4_i(const void* p) {
  uint4 v; asm volatile("ld.relaxed.gpu.global.v4.u32 {%0,%1,%2,%3}, [%4+%5];" : "=r"(v.x), "=r"(v.y), "=r"(v.z), "=r"(v.w) : "l"(p), "n"(IMM) : "memory"); return v;
}
template <int I, int N, class F> __device__ __forceinline__ void static_for(F&& f) {
  if constexpr (I < N) { f(std::integral_constant<int, I>{}); static_for<I + 1, N>(f); }
}
__device__ __forceinline__ uint32_t movm_t(uint32_t a) {
  uint32_t d; asm volatile("movmatrix.sync.aligned.m8n8.trans.b16 %0, %1;" : "=r"(d) : "r"(a)); return d;
}
__device__ __forceinline__ void mma16816(float (&d)[4], uint32_t a0, uint32_t a1, uint32_t a2, uint32_t a3, uint32_t b0, uint32_t b1) {
  asm volatile("mma.sync.aligned.m16n8k16.row.col.f32.bf16.bf16.f32 {%0,%1,%2,%3}, {%4,%5,%6,%7}, {%8,%9}, {%0,%1,%2,%3};"
               : "+f"(d[0]), "+f"(d[1]), "+f"(d[2]), "+f"(d[3]) : "r"(a0), "r"(a1), "r"(a2), "r"(a3), "r"(b0), "r"(b1));
}
__device__ __forceinline__ uint32_t pack_bf16(float lo, float hi) {
  uint32_t d; asm("cvt.rn.bf16x2.f32 %0, %1, %2;" : "=r"(d) : "f"(hi), "f"(lo)); return d;
}
__device__ __forceinline__ float bf_lo(uint32_t w) { return __uint_as_float(w << 16); }
__device__ __forceinline__ float bf_hi(uint32_t w) { return __uint_as_float(w & 0xffff0000u); }
__device__ __forceinline__ uint4 lds128(uint32_t a) {
  uint4 v; asm volatile("ld.shared.v4.u32 {%0,%1,%2,%3}, [%4];" : "=r"(v.x), "=r"(v.y), "=r"(v.z), "=r"(v.w) : "r"(a) : "memory"); return v;
}
__device__ __forceinline__ uint2 lds64(uint32_t a) {
  uint2 v; asm volatile("ld.shared.v2.u32 {%0,%1}, [%2];" : "=r"(v.x), "=r"(v.y) : "r"(a) : "memory"); return v;
}
__device__ __forceinline__ void sts128(uint32_t a, uint32_t x, uint32_t y, uint32_t z, uint32_t w) {
  asm volatile("st.shared.v4.u32 [%0], {%1,%2,%3,%4};" :: "r"(a), "r"(x), "r"(y), "r"(z), "r"(w) : "memory");
}
__device__ __forceinline__ void sts64(uint32_t a, uint32_t x, uint32_t y) {
  asm volatile("st.shared.v2.u32 [%0], {%1,%2};" :: "r"(a), "r"(x), "r"(y) : "memory");
}
__device__ __forceinline__ uint4 ld_relaxed_v4(const void* p) {
  uint4 v; asm volatile("ld.relaxed.gpu.global.v4.u32 {%0,%1,%2,%3}, [%4];" : "=r"(v.x), "=r"(v.y), "=r"(v.z), "=r"(v.w) : "l"(p) : "memory"); return v;
}
__device__ __forceinline__ uint32_t ld_relaxed_u32(const void* p) {
  uint32_t v; asm volatile("ld.relaxed.gpu.global.u32 %0, [%1];" : "=r"(v) : "l"(p) : "memory"); return v;
}
__device__ __forceinline__ void st_relaxed_v2(void* p, uint32_t a, uint32_t b) {
  asm volatile("st.relaxed.gpu.global.v2.u32 [%0], {%1,%2};" :: "l"(p), "r"(a), "r"(b) : "memory");
}
__device__ __forceinline__ void st_relaxed_u32(void* p, uint32_t v) {
  asm volatile("st.relaxed.gpu.global.u32 [%0], %1;" :: "l"(p), "r"(v) : "memory");
}
__device__ __forceinline__ uint32_t clk32() { uint32_t c; asm volatile("mov.u32 %0, %%clock;" : "=r"(c) :: "memory"); return c; }
__device__ __forceinline__ uint32_t clkdep(uint32_t v) {
  uint32_t c; asm volatile("{.reg .pred p; setp.eq.u32 p, %1, 0xdeadbeef; @p trap; mov.u32 %0, %%clock;}" : "=r"(c) : "r"(v) : "memory"); return c;
}
__device__ __forceinline__ void wgmma_fence() { asm volatile("wgmma.fence.sync.aligned;" ::: "memory"); }
__device__ __forceinline__ void wgmma_commit() { asm volatile("wgmma.commit_group.sync.aligned;" ::: "memory"); }
template <int N> __device__ __forceinline__ void wgmma_wait() { asm volatile("wgmma.wait_group.sync.aligned %0;" :: "n"(N) : "memory"); }
__device__ __forceinline__ void wgmma_n8_ss_ta(float (&d)[4], uint64_t da, uint64_t db, int acc) {
  asm volatile("{\n.reg .pred p;\nsetp.ne.b32 p, %6, 0;\n"
               "wgmma.mma_async.sync.aligned.m64n8k16.f32.bf16.bf16 {%0,%1,%2,%3}, %4, %5, p, 1, 1, 1, 0;\n}\n"
               : "+f"(d[0]), "+f"(d[1]), "+f"(d[2]), "+f"(d[3]) : "l"(da), "l"(db), "r"(acc));
}
__device__ __forceinline__ uint64_t make_desc(uint32_t saddr, uint32_t lbo_bytes, uint32_t sbo_bytes, uint32_t swz) {
  return (uint64_t)((saddr & 0x3FFFF) >> 4) | ((uint64_t)(lbo_bytes >> 4) << 16) | ((uint64_t)(sbo_bytes >> 4) << 32) | ((uint64_t)swz << 62);
}


__device__ __forceinline__ bool elect_one() {
  uint32_t p; asm volatile("{\n.reg .pred p;\nelect.sync _|p, 0xffffffff;\nselp.u32 %0, 1, 0, p;\n}" : "=r"(p)); return p;
}
__device__ __forceinline__ void tma_load_3d(uint32_t dst, const CUtensorMap* tm, int c0, int c1, int c2, uint32_t mb) {
  asm volatile("cp.async.bulk.tensor.3d.shared::cluster.global.mbarrier::complete_tx::bytes [%0], [%1, {%3, %4, %5}], [%2];"
               :: "r"(dst), "l"(tm), "r"(mb), "r"(c0), "r"(c1), "r"(c2) : "memory");
}
__device__ __forceinline__ void tma_load_2d(uint32_t dst, const CUtensorMap* tm, int c0, int c1, uint32_t mb) {
  asm volatile("cp.async.bulk.tensor.2d.shared::cluster.global.mbarrier::complete_tx::bytes [%0], [%1, {%3, %4}], [%2];"
               :: "r"(dst), "l"(tm), "r"(mb), "r"(c0), "r"(c1) : "memory");
}
__device__ __forceinline__ void bulk_s2g(void* dst, uint32_t src, uint32_t bytes) {
  asm volatile("cp.async.bulk.global.shared::cta.bulk_group [%0], [%1], %2;" :: "l"(dst), "r"(src), "r"(bytes) : "memory");
}
__device__ __forceinline__ uint64_t policy_evict_first() {
  uint64_t p; asm volatile("createpolicy.fractional.L2::evict_first.b64 %0, 1.0;" : "=l"(p)); return p;
}
__device__ __forceinline__ void bulk_s2g_hint(void* dst, uint32_t src, uint32_t bytes, uint64_t pol) {
  asm volatile("cp.async.bulk.global.shared::cta.bulk_group.L2::cache_hint [%0], [%1], %2, %3;" :: "l"(dst), "r"(src), "r"(bytes), "l"(pol) : "memory");
}
__device__ __forceinline__ void bulk_commit() { asm volatile("cp.async.bulk.commit_group;" ::: "memory"); }
template <int N> __device__ __forceinline__ void bulk_wait_read() { asm volatile("cp.async.bulk.wait_group.read %0;" :: "n"(N) : "memory"); }
template <int N> __device__ __forceinline__ void bulk_wait() { asm volatile("cp.async.bulk.wait_group %0;" :: "n"(N) : "memory"); }
__device__ __forceinline__ void stsm_x4(uint32_t a, uint32_t r0, uint32_t r1, uint32_t r2, uint32_t r3) {
  asm volatile("stmatrix.sync.aligned.m8n8.x4.shared.b16 [%0], {%1,%2,%3,%4};" :: "r"(a), "r"(r0), "r"(r1), "r"(r2), "r"(r3) : "memory");
}
__device__ __forceinline__ void stsm_x2(uint32_t a, uint32_t r0, uint32_t r1) {
  asm volatile("stmatrix.sync.aligned.m8n8.x2.shared.b16 [%0], {%1,%2};" :: "r"(a), "r"(r0), "r"(r1) : "memory");
}
__device__ __forceinline__ void ldsm_x2(uint32_t (&r)[2], uint32_t a) {
  asm volatile("ldmatrix.sync.aligned.m8n8.x2.shared.b16 {%0,%1}, [%2];" : "=r"(r[0]), "=r"(r[1]) : "r"(a) : "memory");
}
__device__ __forceinline__ void ldsm_x2_t(uint32_t (&r)[2], uint32_t a) {
  asm volatile("ldmatrix.sync.aligned.m8n8.x2.trans.shared.b16 {%0,%1}, [%2];" : "=r"(r[0]), "=r"(r[1]) : "r"(a) : "memory");
}
__device__ __forceinline__ float bf16r(float x) { return __uint_as_float(pack_bf16(0.f, x) & 0xffff0000u); }
__device__ __forceinline__ void bf16r2(float& a, float& b) { const uint32_t w = pack_bf16(a, b); a = bf_lo(w); b = bf_hi(w); }
__device__ __forceinline__ float rcpf(float x) { float r; asm("rcp.approx.ftz.f32 %0, %1;" : "=f"(r) : "f"(x)); return r; }
__device__ __forceinline__ float ex2f(float x) { float e; asm("ex2.approx.ftz.f32 %0, %1;" : "=f"(e) : "f"(x)); return e; }
__device__ __forceinline__ void prefetch_tmap(const CUtensorMap* tm) { asm volatile("prefetch.tensormap [%0];" :: "l"(tm) : "memory"); }

#ifdef TIMELINE
__device__ unsigned long long g_tl[2 * 64];
__device__ unsigned long long g_log[2 * 132 * 64 * 2 + 2];
__device__ unsigned long long g_tl2[4 * 64];
__device__ __forceinline__ unsigned long long gtime() { unsigned long long t; asm volatile("mov.u64 %0, %%globaltimer;" : "=l"(t)); return t; }
#define TL_BEGIN(id) do { if (threadIdx.x == 0) atomicMin(&g_tl[2 * (id)], gtime()); } while (0)
#define TL_END(id) do { if ((threadIdx.x & 31) == 0) atomicMax(&g_tl[2 * (id) + 1], gtime()); } while (0)
#define TL_ACC(idx, t0) do { if (threadIdx.x == 0 && m >= 4 && m < 11) { atomicAdd(&g_tl2[idx], gtime() - (t0)); atomicAdd(&g_tl2[(idx) + 1], 1ull); } } while (0)
#define TL_NOW() gtime()
#define TL2(idx) asm volatile("{\n.reg .pred p;\nsetp.eq.u32 p, %2, 0;\n@p red.relaxed.gpu.global.max.u64 [%0], %1;\n}" :: "l"(&g_tl2[idx]), "l"(gtime()), "r"(threadIdx.x) : "memory")
#define TLW(idx) asm volatile("{\n.reg .pred p;\nsetp.eq.u32 p, %2, 0;\n@p red.relaxed.gpu.global.max.u64 [%0], %1;\n@p red.relaxed.gpu.global.add.u64 [%0+128], %1;\n}" :: "l"(&g_tl2[idx]), "l"(gtime() - g_tl0), "r"(threadIdx.x & 31) : "memory")
#define TL_BEGIN0(id) atomicMin(&g_tl[2 * (id)], gtime())
#else
#define TL_ACC(idx, t0)
#define TL_NOW() 0ull
#define TL2(idx)
#define TL_BEGIN0(id)
#define TLW(idx)
#define TL_BEGIN(id)
#define TL_END(id)
#endif
template <int TA, int TB> __device__ __forceinline__ void wgmma_n24(float (&d)[12], uint64_t da, uint64_t db, int acc) {
  asm volatile("{\n.reg .pred p;\nsetp.ne.b32 p, %14, 0;\n"
    "wgmma.mma_async.sync.aligned.m64n24k16.f32.bf16.bf16 {%0, %1, %2, %3, %4, %5, %6, %7, %8, %9, %10, %11}, %12, %13, p, 1, 1, %15, %16;\n}\n"
    : "+f"(d[0]), "+f"(d[1]), "+f"(d[2]), "+f"(d[3]), "+f"(d[4]), "+f"(d[5]), "+f"(d[6]), "+f"(d[7]), "+f"(d[8]), "+f"(d[9]), "+f"(d[10]), "+f"(d[11])
    : "l"(da), "l"(db), "r"(acc), "n"(TA), "n"(TB));
}

template <int TA, int TB> __device__ __forceinline__ void wgmma_n80(float (&d)[40], uint64_t da, uint64_t db, int acc) {
  asm volatile("{\n.reg .pred p;\nsetp.ne.b32 p, %42, 0;\n"
    "wgmma.mma_async.sync.aligned.m64n80k16.f32.bf16.bf16 {%0, %1, %2, %3, %4, %5, %6, %7, %8, %9, %10, %11, %12, %13, %14, %15, %16, %17, %18, %19, %20, %21, %22, %23, %24, %25, %26, %27, %28, %29, %30, %31, %32, %33, %34, %35, %36, %37, %38, %39}, %40, %41, p, 1, 1, %43, %44;\n}\n"
    : "+f"(d[0]), "+f"(d[1]), "+f"(d[2]), "+f"(d[3]), "+f"(d[4]), "+f"(d[5]), "+f"(d[6]), "+f"(d[7]), "+f"(d[8]), "+f"(d[9]), "+f"(d[10]), "+f"(d[11]), "+f"(d[12]), "+f"(d[13]), "+f"(d[14]), "+f"(d[15]), "+f"(d[16]), "+f"(d[17]), "+f"(d[18]), "+f"(d[19]), "+f"(d[20]), "+f"(d[21]), "+f"(d[22]), "+f"(d[23]), "+f"(d[24]), "+f"(d[25]), "+f"(d[26]), "+f"(d[27]), "+f"(d[28]), "+f"(d[29]), "+f"(d[30]), "+f"(d[31]), "+f"(d[32]), "+f"(d[33]), "+f"(d[34]), "+f"(d[35]), "+f"(d[36]), "+f"(d[37]), "+f"(d[38]), "+f"(d[39])
    : "l"(da), "l"(db), "r"(acc), "n"(TA), "n"(TB));
}

template <int TA, int TB> __device__ __forceinline__ void wgmma_n128(float (&d)[64], uint64_t da, uint64_t db, int acc) {
  asm volatile("{\n.reg .pred p;\nsetp.ne.b32 p, %66, 0;\n"
    "wgmma.mma_async.sync.aligned.m64n128k16.f32.bf16.bf16 {%0, %1, %2, %3, %4, %5, %6, %7, %8, %9, %10, %11, %12, %13, %14, %15, %16, %17, %18, %19, %20, %21, %22, %23, %24, %25, %26, %27, %28, %29, %30, %31, %32, %33, %34, %35, %36, %37, %38, %39, %40, %41, %42, %43, %44, %45, %46, %47, %48, %49, %50, %51, %52, %53, %54, %55, %56, %57, %58, %59, %60, %61, %62, %63}, %64, %65, p, 1, 1, %67, %68;\n}\n"
    : "+f"(d[0]), "+f"(d[1]), "+f"(d[2]), "+f"(d[3]), "+f"(d[4]), "+f"(d[5]), "+f"(d[6]), "+f"(d[7]), "+f"(d[8]), "+f"(d[9]), "+f"(d[10]), "+f"(d[11]), "+f"(d[12]), "+f"(d[13]), "+f"(d[14]), "+f"(d[15]), "+f"(d[16]), "+f"(d[17]), "+f"(d[18]), "+f"(d[19]), "+f"(d[20]), "+f"(d[21]), "+f"(d[22]), "+f"(d[23]), "+f"(d[24]), "+f"(d[25]), "+f"(d[26]), "+f"(d[27]), "+f"(d[28]), "+f"(d[29]), "+f"(d[30]), "+f"(d[31]), "+f"(d[32]), "+f"(d[33]), "+f"(d[34]), "+f"(d[35]), "+f"(d[36]), "+f"(d[37]), "+f"(d[38]), "+f"(d[39]), "+f"(d[40]), "+f"(d[41]), "+f"(d[42]), "+f"(d[43]), "+f"(d[44]), "+f"(d[45]), "+f"(d[46]), "+f"(d[47]), "+f"(d[48]), "+f"(d[49]), "+f"(d[50]), "+f"(d[51]), "+f"(d[52]), "+f"(d[53]), "+f"(d[54]), "+f"(d[55]), "+f"(d[56]), "+f"(d[57]), "+f"(d[58]), "+f"(d[59]), "+f"(d[60]), "+f"(d[61]), "+f"(d[62]), "+f"(d[63])
    : "l"(da), "l"(db), "r"(acc), "n"(TA), "n"(TB));
}

template <int TA, int TB> __device__ __forceinline__ void wgmma_n192(float (&d)[96], uint64_t da, uint64_t db, int acc) {
  asm volatile("{\n.reg .pred p;\nsetp.ne.b32 p, %98, 0;\n"
    "wgmma.mma_async.sync.aligned.m64n192k16.f32.bf16.bf16 {%0, %1, %2, %3, %4, %5, %6, %7, %8, %9, %10, %11, %12, %13, %14, %15, %16, %17, %18, %19, %20, %21, %22, %23, %24, %25, %26, %27, %28, %29, %30, %31, %32, %33, %34, %35, %36, %37, %38, %39, %40, %41, %42, %43, %44, %45, %46, %47, %48, %49, %50, %51, %52, %53, %54, %55, %56, %57, %58, %59, %60, %61, %62, %63, %64, %65, %66, %67, %68, %69, %70, %71, %72, %73, %74, %75, %76, %77, %78, %79, %80, %81, %82, %83, %84, %85, %86, %87, %88, %89, %90, %91, %92, %93, %94, %95}, %96, %97, p, 1, 1, %99, %100;\n}\n"
    : "+f"(d[0]), "+f"(d[1]), "+f"(d[2]), "+f"(d[3]), "+f"(d[4]), "+f"(d[5]), "+f"(d[6]), "+f"(d[7]), "+f"(d[8]), "+f"(d[9]), "+f"(d[10]), "+f"(d[11]), "+f"(d[12]), "+f"(d[13]), "+f"(d[14]), "+f"(d[15]), "+f"(d[16]), "+f"(d[17]), "+f"(d[18]), "+f"(d[19]), "+f"(d[20]), "+f"(d[21]), "+f"(d[22]), "+f"(d[23]), "+f"(d[24]), "+f"(d[25]), "+f"(d[26]), "+f"(d[27]), "+f"(d[28]), "+f"(d[29]), "+f"(d[30]), "+f"(d[31]), "+f"(d[32]), "+f"(d[33]), "+f"(d[34]), "+f"(d[35]), "+f"(d[36]), "+f"(d[37]), "+f"(d[38]), "+f"(d[39]), "+f"(d[40]), "+f"(d[41]), "+f"(d[42]), "+f"(d[43]), "+f"(d[44]), "+f"(d[45]), "+f"(d[46]), "+f"(d[47]), "+f"(d[48]), "+f"(d[49]), "+f"(d[50]), "+f"(d[51]), "+f"(d[52]), "+f"(d[53]), "+f"(d[54]), "+f"(d[55]), "+f"(d[56]), "+f"(d[57]), "+f"(d[58]), "+f"(d[59]), "+f"(d[60]), "+f"(d[61]), "+f"(d[62]), "+f"(d[63]), "+f"(d[64]), "+f"(d[65]), "+f"(d[66]), "+f"(d[67]), "+f"(d[68]), "+f"(d[69]), "+f"(d[70]), "+f"(d[71]), "+f"(d[72]), "+f"(d[73]), "+f"(d[74]), "+f"(d[75]), "+f"(d[76]), "+f"(d[77]), "+f"(d[78]), "+f"(d[79]), "+f"(d[80]), "+f"(d[81]), "+f"(d[82]), "+f"(d[83]), "+f"(d[84]), "+f"(d[85]), "+f"(d[86]), "+f"(d[87]), "+f"(d[88]), "+f"(d[89]), "+f"(d[90]), "+f"(d[91]), "+f"(d[92]), "+f"(d[93]), "+f"(d[94]), "+f"(d[95])
    : "l"(da), "l"(db), "r"(acc), "n"(TA), "n"(TB));
}

template <int TA, int TB> __device__ __forceinline__ void wgmma_n256(float (&d)[128], uint64_t da, uint64_t db, int acc) {
  asm volatile("{\n.reg .pred p;\nsetp.ne.b32 p, %130, 0;\n"
    "wgmma.mma_async.sync.aligned.m64n256k16.f32.bf16.bf16 {%0, %1, %2, %3, %4, %5, %6, %7, %8, %9, %10, %11, %12, %13, %14, %15, %16, %17, %18, %19, %20, %21, %22, %23, %24, %25, %26, %27, %28, %29, %30, %31, %32, %33, %34, %35, %36, %37, %38, %39, %40, %41, %42, %43, %44, %45, %46, %47, %48, %49, %50, %51, %52, %53, %54, %55, %56, %57, %58, %59, %60, %61, %62, %63, %64, %65, %66, %67, %68, %69, %70, %71, %72, %73, %74, %75, %76, %77, %78, %79, %80, %81, %82, %83, %84, %85, %86, %87, %88, %89, %90, %91, %92, %93, %94, %95, %96, %97, %98, %99, %100, %101, %102, %103, %104, %105, %106, %107, %108, %109, %110, %111, %112, %113, %114, %115, %116, %117, %118, %119, %120, %121, %122, %123, %124, %125, %126, %127}, %128, %129, p, 1, 1, %131, %132;\n}\n"
    : "+f"(d[0]), "+f"(d[1]), "+f"(d[2]), "+f"(d[3]), "+f"(d[4]), "+f"(d[5]), "+f"(d[6]), "+f"(d[7]), "+f"(d[8]), "+f"(d[9]), "+f"(d[10]), "+f"(d[11]), "+f"(d[12]), "+f"(d[13]), "+f"(d[14]), "+f"(d[15]), "+f"(d[16]), "+f"(d[17]), "+f"(d[18]), "+f"(d[19]), "+f"(d[20]), "+f"(d[21]), "+f"(d[22]), "+f"(d[23]), "+f"(d[24]), "+f"(d[25]), "+f"(d[26]), "+f"(d[27]), "+f"(d[28]), "+f"(d[29]), "+f"(d[30]), "+f"(d[31]), "+f"(d[32]), "+f"(d[33]), "+f"(d[34]), "+f"(d[35]), "+f"(d[36]), "+f"(d[37]), "+f"(d[38]), "+f"(d[39]), "+f"(d[40]), "+f"(d[41]), "+f"(d[42]), "+f"(d[43]), "+f"(d[44]), "+f"(d[45]), "+f"(d[46]), "+f"(d[47]), "+f"(d[48]), "+f"(d[49]), "+f"(d[50]), "+f"(d[51]), "+f"(d[52]), "+f"(d[53]), "+f"(d[54]), "+f"(d[55]), "+f"(d[56]), "+f"(d[57]), "+f"(d[58]), "+f"(d[59]), "+f"(d[60]), "+f"(d[61]), "+f"(d[62]), "+f"(d[63]), "+f"(d[64]), "+f"(d[65]), "+f"(d[66]), "+f"(d[67]), "+f"(d[68]), "+f"(d[69]), "+f"(d[70]), "+f"(d[71]), "+f"(d[72]), "+f"(d[73]), "+f"(d[74]), "+f"(d[75]), "+f"(d[76]), "+f"(d[77]), "+f"(d[78]), "+f"(d[79]), "+f"(d[80]), "+f"(d[81]), "+f"(d[82]), "+f"(d[83]), "+f"(d[84]), "+f"(d[85]), "+f"(d[86]), "+f"(d[87]), "+f"(d[88]), "+f"(d[89]), "+f"(d[90]), "+f"(d[91]), "+f"(d[92]), "+f"(d[93]), "+f"(d[94]), "+f"(d[95]), "+f"(d[96]), "+f"(d[97]), "+f"(d[98]), "+f"(d[99]), "+f"(d[100]), "+f"(d[101]), "+f"(d[102]), "+f"(d[103]), "+f"(d[104]), "+f"(d[105]), "+f"(d[106]), "+f"(d[107]), "+f"(d[108]), "+f"(d[109]), "+f"(d[110]), "+f"(d[111]), "+f"(d[112]), "+f"(d[113]), "+f"(d[114]), "+f"(d[115]), "+f"(d[116]), "+f"(d[117]), "+f"(d[118]), "+f"(d[119]), "+f"(d[120]), "+f"(d[121]), "+f"(d[122]), "+f"(d[123]), "+f"(d[124]), "+f"(d[125]), "+f"(d[126]), "+f"(d[127])
    : "l"(da), "l"(db), "r"(acc), "n"(TA), "n"(TB));
}

template <int TB> __device__ __forceinline__ void wgmma_rs_n24(float (&d)[12], uint32_t a0, uint32_t a1, uint32_t a2, uint32_t a3, uint64_t db, int acc) {
  asm volatile("{\n.reg .pred p;\nsetp.ne.b32 p, %17, 0;\n"
    "wgmma.mma_async.sync.aligned.m64n24k16.f32.bf16.bf16 {%0, %1, %2, %3, %4, %5, %6, %7, %8, %9, %10, %11}, {%12, %13, %14, %15}, %16, p, 1, 1, %18;\n}\n"
    : "+f"(d[0]), "+f"(d[1]), "+f"(d[2]), "+f"(d[3]), "+f"(d[4]), "+f"(d[5]), "+f"(d[6]), "+f"(d[7]), "+f"(d[8]), "+f"(d[9]), "+f"(d[10]), "+f"(d[11])
    : "r"(a0), "r"(a1), "r"(a2), "r"(a3), "l"(db), "r"(acc), "n"(TB));
}

template <int TB> __device__ __forceinline__ void wgmma_rs_n40(float (&d)[20], uint32_t a0, uint32_t a1, uint32_t a2, uint32_t a3, uint64_t db, int acc) {
  asm volatile("{\n.reg .pred p;\nsetp.ne.b32 p, %25, 0;\n"
    "wgmma.mma_async.sync.aligned.m64n40k16.f32.bf16.bf16 {%0, %1, %2, %3, %4, %5, %6, %7, %8, %9, %10, %11, %12, %13, %14, %15, %16, %17, %18, %19}, {%20, %21, %22, %23}, %24, p, 1, 1, %26;\n}\n"
    : "+f"(d[0]), "+f"(d[1]), "+f"(d[2]), "+f"(d[3]), "+f"(d[4]), "+f"(d[5]), "+f"(d[6]), "+f"(d[7]), "+f"(d[8]), "+f"(d[9]), "+f"(d[10]), "+f"(d[11]), "+f"(d[12]), "+f"(d[13]), "+f"(d[14]), "+f"(d[15]), "+f"(d[16]), "+f"(d[17]), "+f"(d[18]), "+f"(d[19])
    : "r"(a0), "r"(a1), "r"(a2), "r"(a3), "l"(db), "r"(acc), "n"(TB));
}

template <int TB> __device__ __forceinline__ void wgmma_rs_n192(float (&d)[96], uint32_t a0, uint32_t a1, uint32_t a2, uint32_t a3, uint64_t db, int acc) {
  asm volatile("{\n.reg .pred p;\nsetp.ne.b32 p, %101, 0;\n"
    "wgmma.mma_async.sync.aligned.m64n192k16.f32.bf16.bf16 {%0, %1, %2, %3, %4, %5, %6, %7, %8, %9, %10, %11, %12, %13, %14, %15, %16, %17, %18, %19, %20, %21, %22, %23, %24, %25, %26, %27, %28, %29, %30, %31, %32, %33, %34, %35, %36, %37, %38, %39, %40, %41, %42, %43, %44, %45, %46, %47, %48, %49, %50, %51, %52, %53, %54, %55, %56, %57, %58, %59, %60, %61, %62, %63, %64, %65, %66, %67, %68, %69, %70, %71, %72, %73, %74, %75, %76, %77, %78, %79, %80, %81, %82, %83, %84, %85, %86, %87, %88, %89, %90, %91, %92, %93, %94, %95}, {%96, %97, %98, %99}, %100, p, 1, 1, %102;\n}\n"
    : "+f"(d[0]), "+f"(d[1]), "+f"(d[2]), "+f"(d[3]), "+f"(d[4]), "+f"(d[5]), "+f"(d[6]), "+f"(d[7]), "+f"(d[8]), "+f"(d[9]), "+f"(d[10]), "+f"(d[11]), "+f"(d[12]), "+f"(d[13]), "+f"(d[14]), "+f"(d[15]), "+f"(d[16]), "+f"(d[17]), "+f"(d[18]), "+f"(d[19]), "+f"(d[20]), "+f"(d[21]), "+f"(d[22]), "+f"(d[23]), "+f"(d[24]), "+f"(d[25]), "+f"(d[26]), "+f"(d[27]), "+f"(d[28]), "+f"(d[29]), "+f"(d[30]), "+f"(d[31]), "+f"(d[32]), "+f"(d[33]), "+f"(d[34]), "+f"(d[35]), "+f"(d[36]), "+f"(d[37]), "+f"(d[38]), "+f"(d[39]), "+f"(d[40]), "+f"(d[41]), "+f"(d[42]), "+f"(d[43]), "+f"(d[44]), "+f"(d[45]), "+f"(d[46]), "+f"(d[47]), "+f"(d[48]), "+f"(d[49]), "+f"(d[50]), "+f"(d[51]), "+f"(d[52]), "+f"(d[53]), "+f"(d[54]), "+f"(d[55]), "+f"(d[56]), "+f"(d[57]), "+f"(d[58]), "+f"(d[59]), "+f"(d[60]), "+f"(d[61]), "+f"(d[62]), "+f"(d[63]), "+f"(d[64]), "+f"(d[65]), "+f"(d[66]), "+f"(d[67]), "+f"(d[68]), "+f"(d[69]), "+f"(d[70]), "+f"(d[71]), "+f"(d[72]), "+f"(d[73]), "+f"(d[74]), "+f"(d[75]), "+f"(d[76]), "+f"(d[77]), "+f"(d[78]), "+f"(d[79]), "+f"(d[80]), "+f"(d[81]), "+f"(d[82]), "+f"(d[83]), "+f"(d[84]), "+f"(d[85]), "+f"(d[86]), "+f"(d[87]), "+f"(d[88]), "+f"(d[89]), "+f"(d[90]), "+f"(d[91]), "+f"(d[92]), "+f"(d[93]), "+f"(d[94]), "+f"(d[95])
    : "r"(a0), "r"(a1), "r"(a2), "r"(a3), "l"(db), "r"(acc), "n"(TB));
}
constexpr uint32_t AR_ACC = 0;
constexpr uint32_t AR_TAB = 0x100000;
constexpr uint32_t AR_PROG = 0x101000;
__host__ __device__ constexpr uint32_t prog_off(int h, int j) { return AR_PROG + h * 128 + j * 4; }
constexpr uint32_t AR_CNT = 0x108000;
constexpr uint32_t AR_QUEUE = 0x109000;
constexpr uint32_t AR_SIZE = 0x10a000;

struct ChainArgs {
  const bf16* mem0;
  const uint2* xh;
  unsigned char *kg, *vg;
  unsigned char* arena;
  unsigned* go;
  uint32_t* dbg;
  uint32_t delay;
  int pfw, margin;
  int tl;
};

namespace ch {
constexpr int OFF_WQ = 0;
constexpr int OFF_X = 81920;
constexpr int OFF_MEM = OFF_X + 40960;
constexpr int OFF_WO = OFF_MEM + 10240;
constexpr int WOK = 8 * 896;
constexpr int OFF_KV = OFF_WO + 10 * WOK;
constexpr int KVB = 5120;
constexpr int OFF_O = OFF_KV + 4 * KVB;
constexpr int OFF_Q = OFF_O + 1024;
constexpr int OFF_S = OFF_O + 3072;
constexpr int OFF_SR = OFF_S + 1280;
constexpr int OFF_BAR = OFF_SR + 1536;
constexpr int SMEM = OFF_BAR + 128 + 1152;
static_assert(SMEM <= 232448, "smem");
constexpr int MB_S = OFF_BAR, MB_O = OFF_BAR + 8, MB_X = OFF_BAR + 16;
constexpr int MB_K = OFF_SR + 1408, MB_V = MB_K + 16, MB_Q = MB_K + 32, MB_R = MB_K + 48;
constexpr int SC_IN = OFF_BAR + 64;
constexpr int SC_MX = OFF_S;
constexpr int SC_W = OFF_BAR + 96;
constexpr int WOS = 448;
enum { B_MEM0 = 1, B_QK, B_SL, B_V, B_O, B_RED, B_X, B_C, B_H, B_MEM1, B_A, B_G };
#ifndef NQ1
#define NQ1 6
#endif
#ifndef NQ0
#define NQ0 4
#endif
#ifndef NP0
#define NP0 4
#endif
#ifndef NWO
#define NWO 5
#endif
#ifndef NWP
#define NWP 4
#endif
#ifndef NB0
#define NB0 2
#endif
#ifndef BBS
#define BBS 100
#endif
#ifndef VSYNC
#define VSYNC 0
#endif
#ifndef XPOS
#define XPOS 0
#endif
#ifndef XPD
#define XPD 300
#endif
#ifndef WOF
#define WOF 0
#endif
#ifndef XBYTES
#define XBYTES 36864
#endif
#ifndef NRT
#define NRT 7
#endif
#ifndef NRF
#define NRF 2
#endif
#ifndef NPM0
#define NPM0 2
#endif
#ifndef NPM1
#define NPM1 2
#endif
#ifndef RSYNC
#define RSYNC 1
#endif
#ifndef PFK
#define PFK 1
#endif
#ifndef PA0
#define PA0 7
#endif
#ifndef PA1
#define PA1 0
#endif
#ifndef PB0
#define PB0 7
#endif
#ifndef PB1
#define PB1 5
#endif
#ifndef PQE
#define PQE 0
#endif
#ifndef XT
#define XT 30
#endif
static_assert(NPM0 >= 2 && NPM1 >= 2, "the K / V blocks live in the last two k-steps of Wo");
}

#ifndef CHAIN_TIMING
#define CHAIN_TIMING 0
#endif
#if CHAIN_TIMING
#ifndef TR0
#define TR0 41
#endif
#ifndef TSMASK
#define TSMASK 0xffff
#endif
#define TSV(i, v) do { if ((TSMASK >> (i)) & 1) asm volatile("st.shared.u32 [%0+%1], %2;" :: "r"(tsb), "n"((i) * 4), "r"(v) : "memory"); } while (0)
#define TS(i) TSV(i, clk32())
#define TS_SETUP() const uint32_t tsb = sb + ((s == TR0 || s == TR0 + 1) ? OFF_BAR + 128 + ((s - TR0) * 12 + warp) * 48 : OFF_SR + 1152)
#else
#define TS(i)
#define TSV(i, v)
#define TS_SETUP()
#endif
#ifndef POLL_DELAY
#define POLL_DELAY 590
#endif
#ifndef XN
#define XN 40
#endif
#ifndef PF0
#define PF0 8
#endif
#ifndef PFS
#define PFS 3
#endif
#ifndef XDELAY
#define XDELAY 0
#endif
#ifndef NOKM
#define NOKM 0
#endif
#ifndef HINT
#define HINT 0
#endif
#ifndef PFX
#define PFX 3
#endif
#ifndef KVRING
#define KVRING 16
#endif
#ifndef ORING
#define ORING 16
#endif
#ifndef PUBLATE
#define PUBLATE 1
#endif
#ifndef PFACC
#define PFACC 1
#endif
template <int V> using IC = std::integral_constant<int, V>;
__device__ __forceinline__ uint32_t clk_v() { uint64_t c; asm volatile("mov.u64 %0, %%clock64;" : "=l"(c) :: "memory"); return (uint32_t)c; }
__device__ __forceinline__ int fresh(int x) { int y; asm volatile("shfl.sync.bfly.b32 %0, %1, 0, 0x1f, 0xffffffff;" : "=r"(y) : "r"(x)); return y; }
#define SFENCE2(x, d) asm volatile("{\n.reg .pred p;\nsetp.eq.u32 p, %0, 0x7fffffff;\n@p st.shared.u32 [%0], %1;\n}" :: "r"(x), "r"(d) : "memory")
#define SFENCE(x) asm volatile("{\n.reg .pred p;\nsetp.eq.u32 p, %0, 0x7fffffff;\n@p st.shared.u32 [%0], %0;\n}" :: "r"(x) : "memory")
template <int I> __device__ __forceinline__ void bbfence(uint32_t x) {
  asm volatile("{\n.reg .pred p;\nsetp.eq.u32 p, %0, %1;\nL_%=:\n@p st.volatile.shared.u32 [%0], %0;\n@p bra.uni L_%=;\n}" :: "r"(x), "n"(4 * I) : "memory");
}
__device__ __forceinline__ float uniform_f(float x) { return __uint_as_float(__reduce_max_sync(0xffffffffu, __float_as_uint(x))); }

__device__ __forceinline__ void mma16816h(float (&d)[4], const uint32_t (&a)[4], uint32_t b0, uint32_t b1) {
  asm volatile("mma.sync.aligned.m16n8k16.row.col.f32.f16.f16.f32 {%0,%1,%2,%3}, {%4,%5,%6,%7}, {%8,%9}, {%0,%1,%2,%3};"
               : "+f"(d[0]), "+f"(d[1]), "+f"(d[2]), "+f"(d[3]) : "r"(a[0]), "r"(a[1]), "r"(a[2]), "r"(a[3]), "r"(b0), "r"(b1));
}
__device__ __forceinline__ void mma1688(float (&d)[4], uint32_t a0, uint32_t a1, uint32_t b0) {
  asm volatile("mma.sync.aligned.m16n8k8.row.col.f32.bf16.bf16.f32 {%0,%1,%2,%3}, {%4,%5}, {%6}, {%0,%1,%2,%3};"
               : "+f"(d[0]), "+f"(d[1]), "+f"(d[2]), "+f"(d[3]) : "r"(a0), "r"(a1), "r"(b0));
}
template <int OFF16, int ACC> __device__ __forceinline__ void wgmma_rs32h(float (&d)[16], const uint32_t (&a)[4], uint32_t dlo) {
  asm volatile("{\n.reg .pred p;\n.reg .b32 t;\n.reg .b64 db;\nsetp.ne.b32 p, %22, 0;\nadd.u32 t, %20, %21;\nmov.b64 db, {t, 0x40000040};\n"
    "wgmma.mma_async.sync.aligned.m64n32k16.f32.f16.f16 {%0,%1,%2,%3,%4,%5,%6,%7,%8,%9,%10,%11,%12,%13,%14,%15}, {%16,%17,%18,%19}, db, p, 1, 1, 0;\n}\n"
    : "+f"(d[0]), "+f"(d[1]), "+f"(d[2]), "+f"(d[3]), "+f"(d[4]), "+f"(d[5]), "+f"(d[6]), "+f"(d[7]), "+f"(d[8]), "+f"(d[9]), "+f"(d[10]), "+f"(d[11]),
      "+f"(d[12]), "+f"(d[13]), "+f"(d[14]), "+f"(d[15])
    : "r"(a[0]), "r"(a[1]), "r"(a[2]), "r"(a[3]), "r"(dlo), "n"(OFF16), "n"(ACC));
}
template <int IMM> __device__ __forceinline__ void stsm_x4_t_i(uint32_t a, uint32_t r0, uint32_t r1, uint32_t r2, uint32_t r3) {
  asm volatile("stmatrix.sync.aligned.m8n8.x4.trans.shared.b16 [%0+%5], {%1,%2,%3,%4};" :: "r"(a), "r"(r0), "r"(r1), "r"(r2), "r"(r3), "n"(IMM) : "memory");
}
template <int IMM> __device__ __forceinline__ void stsm_x2_t_i(uint32_t a, uint32_t r0, uint32_t r1) {
  asm volatile("stmatrix.sync.aligned.m8n8.x2.trans.shared.b16 [%0+%3], {%1,%2};" :: "r"(a), "r"(r0), "r"(r1), "n"(IMM) : "memory");
}
template <int IMM> __device__ __forceinline__ void st_async_b32_i(uint32_t a, uint32_t x, uint32_t mb) {
  asm volatile("st.async.weak.shared::cluster.mbarrier::complete_tx::bytes.b32 [%0+%3], %1, [%2];" :: "r"(a), "r"(x), "r"(mb), "n"(IMM) : "memory");
}
template <int IMM> __device__ __forceinline__ void ld_relaxed_v4_if(uint4& v, const void* p, uint32_t c) {
  asm volatile("{\n.reg .pred p;\nsetp.ne.u32 p, %6, 0;\n@p ld.relaxed.gpu.global.v4.u32 {%0,%1,%2,%3}, [%4+%5];\n}"
               : "+r"(v.x), "+r"(v.y), "+r"(v.z), "+r"(v.w) : "l"(p), "n"(IMM), "r"(c) : "memory");
}
template <int IMM> __device__ __forceinline__ uint32_t lds32_i(uint32_t a) {
  uint32_t v; asm volatile("ld.shared.u32 %0, [%1+%2];" : "=r"(v) : "r"(a), "n"(IMM) : "memory"); return v;
}
__device__ __forceinline__ void sts32(uint32_t a, uint32_t v) { asm volatile("st.shared.u32 [%0], %1;" :: "r"(a), "r"(v) : "memory"); }
__device__ __forceinline__ uint32_t pack_f16(float lo, float hi) {
  uint32_t d; asm("cvt.rn.f16x2.f32 %0, %1, %2;" : "=r"(d) : "f"(hi), "f"(lo)); return d;
}
__device__ __forceinline__ uint32_t amax_bf2(uint32_t a, uint32_t b) { uint32_t d; asm("max.xorsign.abs.bf16x2 %0, %1, %2;" : "=r"(d) : "r"(a), "r"(b)); return d; }
__device__ __forceinline__ uint32_t amax_h2(uint32_t a, uint32_t b) { uint32_t d; asm("max.xorsign.abs.f16x2 %0, %1, %2;" : "=r"(d) : "r"(a), "r"(b)); return d; }
__device__ __forceinline__ uint32_t amax_fold(uint32_t m) { return __reduce_max_sync(0xffffffffu, max(m & 0x7fffu, (m >> 16) & 0x7fffu)); }
__device__ __forceinline__ int wscale_exp(uint32_t m) { return min(141 - (int)(m >> 7), 100); }
__device__ __forceinline__ float exp2i(int e) { return __uint_as_float((uint32_t)(e + 127) << 23); }
__device__ __forceinline__ uint32_t bf2_to_h2(uint32_t w, float sc) { return pack_f16(bf_lo(w) * sc, bf_hi(w) * sc); }
__device__ __forceinline__ void bf2_to_h2_inplace(uint32_t& w, uint32_t sc2) {
  asm volatile("{\n.reg .b32 t, lo, hi;\nmul.rn.bf16x2 t, %0, %1;\nshl.b32 lo, t, 16;\nand.b32 hi, t, 0xffff0000;\ncvt.rn.f16x2.f32 %0, hi, lo;\n}" : "+r"(w) : "r"(sc2));
}
__device__ __forceinline__ void prefetch_l2(const void* p, uint32_t bytes) { asm volatile("cp.async.bulk.prefetch.L2.global [%0], %1;" :: "l"(p), "r"(bytes) : "memory"); }
__device__ __forceinline__ void prefetch_tma_2d(const CUtensorMap* tm, int c0, int c1) {
  asm volatile("cp.async.bulk.prefetch.tensor.2d.L2.global [%0, {%1, %2}];" :: "l"(tm), "r"(c0), "r"(c1) : "memory");
}
__host__ __device__ constexpr uint32_t acc_voff(int v) { return v < 4 ? v * 1024u : (v == 4 ? 128u : 3072u + 128u); }
__device__ __forceinline__ int unit28(int i) { return i == 3 ? 54 : 14 * i; }
__device__ __forceinline__ int unit24(int i) { return i < 2 ? 48 - 6 * i : 56 + 6 * i; }
__host__ __device__ constexpr uint32_t hint_off(int j) { return 1024 + 128 + j * 8192; }
__device__ __forceinline__ uint32_t acc_step(int s) { return (s >> 1) * 32768 + (s & 1) * 512; }
__device__ __forceinline__ uint32_t acc_lane(int i, int lane) { return ((lane >> 3) & 1) * 256 + (lane >> 4) * 4096 + i * 8192 + (lane & 7) * 16; }

__device__ __forceinline__ uint32_t ld_acquire_u32(const void* p) {
  uint32_t v; asm volatile("ld.acquire.gpu.global.u32 %0, [%1];" : "=r"(v) : "l"(p) : "memory"); return v;
}
template <int R> __device__ __forceinline__ void ln_rows(const uint2 (&xw)[R][5], int row0, int lane, bf16* __restrict__ xn, uint2* __restrict__ xh) {
  float v[R][20], s[R], q[R];
#pragma unroll
  for (int r = 0; r < R; r++) {
    s[r] = 0.f; q[r] = 0.f;
#pragma unroll
    for (int i = 0; i < 5; i++) { v[r][4 * i] = bf_lo(xw[r][i].x); v[r][4 * i + 1] = bf_hi(xw[r][i].x); v[r][4 * i + 2] = bf_lo(xw[r][i].y); v[r][4 * i + 3] = bf_hi(xw[r][i].y); }
#pragma unroll
    for (int i = 0; i < 5; i++) s[r] += (v[r][4 * i] + v[r][4 * i + 1]) + (v[r][4 * i + 2] + v[r][4 * i + 3]);
  }
#pragma unroll
  for (int o = 16; o; o >>= 1)
#pragma unroll
    for (int r = 0; r < R; r++) s[r] += __shfl_xor_sync(0xffffffffu, s[r], o);
#pragma unroll
  for (int r = 0; r < R; r++) {
    s[r] *= 1.f / cfg::DM;
#pragma unroll
    for (int i = 0; i < 10; i++) { const float d = v[r][2 * i] - s[r], e = v[r][2 * i + 1] - s[r]; q[r] += d * d + e * e; }
  }
#pragma unroll
  for (int o = 16; o; o >>= 1)
#pragma unroll
    for (int r = 0; r < R; r++) q[r] += __shfl_xor_sync(0xffffffffu, q[r], o);
#pragma unroll
  for (int r = 0; r < R; r++) {
    const int row = row0 + r;
    const float mb = bf16r(s[r]), var = bf16r(q[r] * (1.f / cfg::DM));
    float sd; asm("sqrt.approx.f32 %0, %1;" : "=f"(sd) : "f"(bf16r(var + 1e-5f)));
    const float inv = rcpf(bf16r(sd));
#pragma unroll
    for (int i = 0; i < 5; i++) {
      float y[4];
#pragma unroll
      for (int e = 0; e < 4; e++) y[e] = v[r][4 * i + e] - mb;
      bf16r2(y[0], y[1]); bf16r2(y[2], y[3]);
      const uint32_t w0 = pack_bf16(y[0] * inv, y[1] * inv), w1 = pack_bf16(y[2] * inv, y[3] * inv);
      *(uint2*)(xn + (size_t)row * cfg::DM + i * 128 + lane * 4) = make_uint2(w0, w1);
      if (xh) xh[(((size_t)(row >> 5) * 10 + 2 * i + (lane >> 4)) * 32 + (row & 31)) * 16 + ((((lane >> 1) & 7) ^ (row & 7)) << 1) + (lane & 1)] =
          make_uint2(pack_f16(bf_lo(w0), bf_hi(w0)), pack_f16(bf_lo(w1), bf_hi(w1)));
    }
  }
}

__global__ void __cluster_dims__(3, 1, 1) __launch_bounds__(384, 1) chain_kernel(const ChainArgs a, const __grid_constant__ CUtensorMap tmWq,
    const __grid_constant__ CUtensorMap tmWk, const __grid_constant__ CUtensorMap tmWv, const __grid_constant__ CUtensorMap tmWo) {
  using namespace ch;
  extern __shared__ __align__(1024) unsigned char smem_raw[];
  const uint32_t sb = smem_u32(smem_raw);
  const int warp = __shfl_sync(0xffffffffu, (int)threadIdx.x >> 5, 0);
  const int lane = __shfl_sync(0xffffffffu, (int)threadIdx.x & 31, threadIdx.x & 31);
  const int cta = blockIdx.x, h = cta / 3, j = cta % 3;
  const int g = lane >> 2, q4 = lane & 3, r8 = lane & 7, m4 = lane >> 3;
  unsigned char* const arena = a.arena;
  if (sb & 1023u) __trap();
  asm volatile("griddepcontrol.launch_dependents;");
  TL_BEGIN(a.tl);
#ifdef TIMELINE
  const unsigned long long g_tl0 = gtime();
#define PT(i) TLW((a.tl >= 12) * 128 + 64 + (i))
#else
#define PT(i)
#endif
  const int col0 = j == 0 ? 0 : (j == 1 ? 224 : 432);
  auto stage_w = [&](const CUtensorMap* tm, uint32_t dst, uint32_t mb, int half) {
    mbar_expect_tx(mb + 8 * half, 40960);
    tma_load_2d(dst + half * 40960, tm, h * cfg::DH + j * 64, half * 320, mb + 8 * half);
    tma_load_2d(dst + half * 40960 + 20480, tm, h * cfg::DH + j * 64, half * 320 + 160, mb + 8 * half);
  };
  if (threadIdx.x == 256) {
    for (int i = 0; i < 9; i++) mbar_init(sb + MB_K + 8 * i, 1);
    mbar_init(sb + MB_S, 1); mbar_init(sb + MB_O, 1); mbar_init(sb + MB_X, 1);
    asm volatile("fence.mbarrier_init.release.cluster;" ::: "memory");
    for (int i = 0; i < 2; i++) { stage_w(&tmWk, sb + OFF_WQ, sb + MB_K, i); stage_w(&tmWv, sb + OFF_WO, sb + MB_V, i); }
    sts32(sb + SC_W, 0); sts32(sb + SC_W + 4, 0); sts32(sb + SC_W + 8, 0); sts32(sb + SC_IN + 12, 0); sts32(sb + SC_IN + 20, 0);
    mbar_expect_tx(sb + MB_S, 1280); mbar_expect_tx(sb + MB_O, 2048);
  }
  __syncthreads();
  asm volatile("barrier.cluster.arrive.relaxed.aligned;" ::: "memory");
  const uint32_t d1 = mapa_u32(sb, (j + 1) % 3) - sb, d2 = mapa_u32(sb, (j + 2) % 3) - sb;

  if (warp >= 8) {
    asm volatile("setmaxnreg.dec.sync.aligned.u32 40;");
    const int hw = warp - 8, ht = hw * 32 + lane;
    const bool lead = ht == 0;
    auto stage_wo = [&](int i) {
      mbar_expect_tx(sb + MB_R + 8 * i, 64 * WOS);
      tma_load_2d(sb + OFF_WO + i * 64 * WOS, &tmWo, col0, h * cfg::DH + ((i + j) % 3) * 64, sb + MB_R + 8 * i);
    };
    const unsigned char* xg = (const unsigned char*)a.xh;
    auto issue_x = [&](int s) { mbar_expect_tx(sb + MB_X, 40960); bulk_g2s(sb + OFF_X, xg + (size_t)s * 40960, 40960, sb + MB_X); };
    uint4 v[5];
#pragma unroll
    for (int i = 0; i < 5; i++) { const int c = ht + 128 * i; v[i] = ld_relaxed_v4(a.mem0 + (c & 7) * cfg::DM + (c >> 3) * 8); }
    if (hw == 2) {
      asm volatile("griddepcontrol.wait;" ::: "memory");
      if (lane == 0) { if (cta == 0) st_relaxed_u32(a.go, 1); issue_x(0); }
      PT(0);
    }
    if (hw == 0) {
      bar_sync(B_QK, 160); if (lane == 0) stage_w(&tmWq, sb + OFF_WQ, sb + MB_Q, 0);
      bar_sync(B_SL, 160); if (lane == 0) stage_w(&tmWq, sb + OFF_WQ, sb + MB_Q, 1);
    }
    if (hw == 1) {
      bar_sync(B_V, 160); if (lane == 0) stage_wo(0);
      bar_sync(B_O, 160); if (lane == 0) { stage_wo(1); stage_wo(2); }
    }
    __syncwarp();
    {
      uint32_t m = 0;
#pragma unroll
      for (int i = 0; i < 5; i++) {
        m = amax_bf2(amax_bf2(m, amax_bf2(v[i].x, v[i].y)), amax_bf2(v[i].z, v[i].w));
      }
      m = amax_fold(m);
      if (lane == 0) sts32(sb + SC_MX + hw * 4, m);
      bar_sync(B_H, 128);
      const uint4 mm = lds128(sb + SC_MX);
      const int se = max(wscale_exp(max(max(mm.x, mm.y), max(mm.z, mm.w))), -100);
      const float sc = exp2i(se);
#pragma unroll
      for (int i = 0; i < 5; i++) {
        const int c = ht + 128 * i, t = c & 7, chn = c >> 3;
        sts128(sb + OFF_MEM + chn * 128 + ((t ^ (2 * (chn & 3))) << 4), bf2_to_h2(v[i].x, sc), bf2_to_h2(v[i].y, sc), bf2_to_h2(v[i].z, sc), bf2_to_h2(v[i].w, sc));
      }
      if (lead) { sts32(sb + SC_IN, __float_as_uint(exp2i(-se))); sts32(sb + SC_IN + 4, 0x7800u); }
    }
    if (hw == 0) PT(11);
    {
      const uint32_t p0 = sb + OFF_WQ + hw * 2048 + lane * 16;
      uint32_t m = 0;
#pragma unroll 1
      for (int i = 0; i < 10; i++) {
        if (i == 0 || i == 5) mbar_wait(sb + MB_Q + (i ? 8 : 0), 0);
        uint32_t r[4][4];
        static_for<0, 4>([&](auto K) { ldsm_x4_i<K.value * 512>(r[K.value], p0 + i * 8192); });
#pragma unroll
        for (int k = 0; k < 4; k++) m = amax_bf2(amax_bf2(m, amax_bf2(r[k][0], r[k][1])), amax_bf2(r[k][2], r[k][3]));
      }
      if (hw == 0) PT(9);
      m = amax_fold(m);
      if (lane == 0) asm volatile("red.shared.max.u32 [%0], %1;" :: "r"(sb + SC_W + 8), "r"(m) : "memory");
      bar_sync(B_H, 128);
      const uint32_t sc = (uint32_t)(wscale_exp(lds32_i<SC_W + 8>(sb)) + 127) * 0x00800080u;
#pragma unroll 1
      for (int i = 0; i < 10; i++) {
        uint32_t r[4][4];
        static_for<0, 4>([&](auto K) { ldsm_x4_i<K.value * 512>(r[K.value], p0 + i * 8192); });
#pragma unroll
        for (int k = 0; k < 4; k++) {
          bf2_to_h2_inplace(r[k][0], sc); bf2_to_h2_inplace(r[k][1], sc); bf2_to_h2_inplace(r[k][2], sc); bf2_to_h2_inplace(r[k][3], sc);
          stsm_x4(p0 + i * 8192 + k * 512, r[k][0], r[k][1], r[k][2], r[k][3]);
        }
      }
    }
    if (hw == 0) PT(10);
    bar_sync(0, 384);
    if (lead) st_relaxed_u32(arena + AR_TAB + cta * 4, 0x80000000u | (lds32_i<SC_W>(sb) << 15) | lds32_i<SC_W + 4>(sb));
    asm volatile("barrier.cluster.wait.aligned;" ::: "memory");
    bar_sync(B_MEM0, 256); bar_sync(B_MEM1, 256);
    {
      uint32_t v0, v1, v2; int spin = 0;
      do {
        v0 = ld_relaxed_u32(arena + AR_TAB + lane * 4); v1 = ld_relaxed_u32(arena + AR_TAB + 128 + lane * 4); v2 = ld_relaxed_u32(arena + AR_TAB + 256 + lane * 4);
      } while (__any_sync(0xffffffffu, ((v0 & v1 & v2) >> 31) == 0) && ++spin < SPIN_LIMIT);
      const uint32_t mv = (max(max(v0, v1), v2) >> 15) & 0x7fffu, mo = max(max(v0 & 0x7fffu, v1 & 0x7fffu), v2 & 0x7fffu);
      sts32(sb + SC_IN + 8 + (lane & 1) * 16, 15 - ((__reduce_max_sync(0xffffffffu, mv) >> 7) + (__reduce_max_sync(0xffffffffu, mo) >> 7) - 252 + 22));
    }

    auto store_kv = [&](int s) {
      const size_t o = ((size_t)(s % (4 * KVRING)) * 96 + cta) * KVB; const uint32_t src = sb + OFF_KV + (s & 1) * (2 * KVB);
      fence_proxy_async(); bulk_s2g(a.kg + o, src, KVB); bulk_s2g(a.vg + o, src + KVB, KVB); bulk_commit();
    };
    const int cb28 = unit28(hw), du = (unit24(hw) - cb28) * 128;
    int ln = lane;
    uint32_t hist = 0;
    auto stamp = [&](int s) {
      asm volatile("{\n.reg .pred p;\n.reg .u32 t;\nsetp.eq.u32 p, %1, 32;\nmov.u32 t, %%globaltimer_lo;\nor.b32 t, t, 1;\n@p st.relaxed.gpu.global.u32 [%0], t;\n}"
                   :: "l"(arena + (AR_ACC + acc_step(s) + hint_off(j) + h * 4)), "r"(hw * 32 + ln) : "memory");
    };
    if (HINT) stamp(0);
#ifdef TIMELINE
    if (cta == 0 && lead) { g_tl2[(a.tl >= 12) * 128 + 0] = clock64(); g_tl2[(a.tl >= 12) * 128 + 1] = gtime(); }
#endif
#pragma unroll 1
    for (int s = 0; s < cfg::NSEG; s++) {
      TS_SETUP();
      const bool last = s == cfg::NSEG - 1;
      if (ln == 0) {
        if (hw == 2 && !last) issue_x(s + 1);
        if (PUBLATE && hw == 0 && (s & 3) == 1 && s > 1) st_relaxed_u32(arena + (prog_off(h, j) + ln), s - 1);
        if (hw == 0 && s > 0) store_kv(s - 1);
        if (PFX && hw == 3 && cta < 80 && s + PFX < cfg::NSEG) prefetch_l2(xg + (size_t)(s + PFX) * 40960 + cta * 512, 512);
        if (hw == 3 && s >= a.pfw && s < a.pfw + 8) prefetch_tma_2d((s - a.pfw) & 1 ? &tmWv : &tmWk, h * cfg::DH + j * 64, ((s - a.pfw) >> 1) * 160);
        if (PFACC && hw == 1 && s + PFACC < cfg::NSEG - 1)
          asm volatile("prefetch.global.L2 [%0];" :: "l"(arena + (AR_ACC + acc_step(s + PFACC) + acc_lane(cta / 24, (cta & 3) * 8) + acc_voff((cta % 24) >> 2))) : "memory");
        if (HINT && hw == 1 && cta < 3 && s + 1 < cfg::NSEG - 1) asm volatile("prefetch.global.L2 [%0];" :: "l"(arena + (AR_ACC + acc_step(s + 1) + hint_off(j))) : "memory");
      }
      __syncwarp();
      if (last) break;
      const uint32_t kv = (s & 1) * (2 * KVB);
      ln = fresh(ln);
      uint32_t kb0[4], kb1[4];
      { const uint32_t ka = sb + kv + hw * 128 + (ln >> 3) * 640 + (ln & 7) * 16; ldsm_x4_i<OFF_KV>(kb0, ka); ldsm_x4_i<OFF_KV + 2560>(kb1, ka); }
      const uint32_t l16 = sb + ln * 16, s8 = sb + ln * 8, xs = s8 + hw * 256, xr = sb + ln * 4 + (hw >> 1) * 512 + (hw & 1) * 128;
      TS(1);
      bar_sync(B_QK, 384);
      {
        uint32_t q0[4], q1[4], q2[4], q3[4];
        float sa[4] = {0, 0, 0, 0}, sc2[4] = {0, 0, 0, 0};
        ldsm_x4_i<OFF_Q>(q0, l16); ldsm_x4_i<OFF_Q + 1024>(q2, l16); ldsm_x4_i<OFF_Q + 512>(q1, l16);
        bar_arrive(B_A, 288);
        ldsm_x4_i<OFF_Q + 1536>(q3, l16);
        mma16816(sa, q0[0], q0[1], q0[2], q0[3], kb0[0], kb0[1]);
        mma16816(sc2, q2[0], q2[1], q2[2], q2[3], kb1[0], kb1[1]);
        mma16816(sa, q1[0], q1[1], q1[2], q1[3], kb0[2], kb0[3]);
        mma16816(sc2, q3[0], q3[1], q3[2], q3[3], kb1[2], kb1[3]);
        const float x0 = (sa[0] + sa[2]) + (sc2[0] + sc2[2]), x1 = (sa[1] + sa[3]) + (sc2[1] + sc2[3]);
        const uint32_t xp = pack_bf16(x0, x1);
        st_async_b32_i<OFF_SR + 256>(xr + d1, xp, sb + MB_S + d1);
        st_async_b32_i<OFF_SR>(xr + d2, xp, sb + MB_S + d2);
        sts64_i<OFF_S>(xs, __float_as_uint(x0), __float_as_uint(x1));
      }
      TS(3);
      bar_sync(B_SL, 256);
      float t0[4], t1[4], t2[4] = {0, 0, 0, 0};
      float osc;
      {
        const uint4 si = lds128_i<SC_IN>(sb + 16 * (s & 1));
        { const uint2 x = lds64_i<OFF_S>(s8), y = lds64_i<OFF_S + 256>(s8); t0[0] = __uint_as_float(x.x); t0[1] = __uint_as_float(x.y); t0[2] = __uint_as_float(y.x); t0[3] = __uint_as_float(y.y); }
        { const uint2 x = lds64_i<OFF_S + 512>(s8), y = lds64_i<OFF_S + 768>(s8); t1[0] = __uint_as_float(x.x); t1[1] = __uint_as_float(x.y); t1[2] = __uint_as_float(y.x); t1[3] = __uint_as_float(y.y); }
        { const uint2 x = lds64_i<OFF_S + 1024>(s8); t2[0] = __uint_as_float(x.x); t2[1] = __uint_as_float(x.y); }
        const int em = (int)(si.y >> 10) - 14 + (int)(si.x >> 23) - 127;
        osc = exp2i(max(min((int)si.z - max(em, 1), 100), -100));
      }
      const uint32_t xo = sb + hw * 256 + (ln & 2) * 64 + (ln >> 2) * 16 + (ln & 1) * 8;
      const uint32_t eye = ((ln >> 3) == (ln & 3)) ? ((ln & 4) ? 0x3f800000u : 0x3f80u) : 0u;
      mbar_spin(sb + MB_S, s & 1);
      TS(4);
      uint32_t v0[4], v1[4], vm[2];
      {
        uint32_t r0[4], r1[4], r2[4];
        ldsm_x4_i<OFF_SR>(r0, l16); ldsm_x4_i<OFF_SR + 512>(r1, l16); ldsm_x4_i<OFF_SR + 1024>(r2, l16);
        mma16816(t0, r0[0], r0[1], r0[2], r0[3], eye, eye);
        mma16816(t1, r1[0], r1[1], r1[2], r1[3], eye, eye);
        mma16816(t2, r2[0], r2[1], r2[2], r2[3], eye, eye);
      }
      float sc[10] = {t0[0], t0[1], t0[2], t0[3], t1[0], t1[1], t1[2], t1[3], t2[0], t2[1]};
      const float cs = 0.07216878364870322f * 1.4426950408889634f;
      float mx = fmaxf(fmaxf(fmaxf(sc[0], sc[1]), fmaxf(sc[2], sc[3])), fmaxf(fmaxf(sc[4], sc[5]), fmaxf(sc[6], sc[7])));
      mx = fmaxf(mx, fmaxf(sc[8], sc[9]));
      {
        const float m1 = __shfl_xor_sync(0xffffffffu, mx, 1), m2 = __shfl_xor_sync(0xffffffffu, mx, 2), m3 = __shfl_xor_sync(0xffffffffu, mx, 3);
        SFENCE2(l16, __float_as_uint(mx));
        ldsm_x4_t_i<OFF_KV + KVB>(v0, l16 + (kv + hw * 1280)); ldsm_x4_t_i<OFF_KV + KVB + 640>(v1, l16 + (kv + hw * 1280));
        bar_sync(B_V, 256);
        bar_arrive(B_G, 384);
        ldsm_x2_t(vm, l16 + (ln & 8) * 64 + (kv + hw * 1280 + OFF_KV + KVB + 512));
        mx = fmaxf(fmaxf(mx, m1), fmaxf(m2, m3));
      }
      const float mo = mx * cs;
#pragma unroll
      for (int i = 0; i < 10; i++) sc[i] = ex2f(fmaf(sc[i], cs, -mo));
      const uint32_t p0 = pack_bf16(sc[0], sc[1]), p1 = pack_bf16(sc[2], sc[3]), p2 = pack_bf16(sc[4], sc[5]), p3 = pack_bf16(sc[6], sc[7]), p4 = pack_bf16(sc[8], sc[9]);
      TS(5);
      float oa[4] = {0, 0, 0, 0}, ob[4] = {0, 0, 0, 0}, oc[4] = {0, 0, 0, 0}, od[4] = {0, 0, 0, 0}, rs[4] = {0, 0, 0, 0};
      const uint32_t ones = 0x3f803f80u;
      mma16816(rs, p0, p2, p1, p3, ones, ones);
      mma16816(oc, p0, p2, p1, p3, v0[2], v0[3]);
      mma16816(od, p0, p2, p1, p3, v1[2], v1[3]);
      mma16816(oa, p0, p2, p1, p3, v0[0], v0[1]);
      mma16816(ob, p0, p2, p1, p3, v1[0], v1[1]);
      mma1688(rs, p4, 0u, ones);
      mma1688(oa, p4, 0u, vm[0]);
      mma1688(ob, p4, 0u, vm[1]);
      const float inv = rcpf(rs[0] + rs[2]) * osc;
      {
        const uint32_t y0 = pack_bf16((oa[0] + oc[2]) * inv, (oa[1] + oc[3]) * inv), y1 = pack_bf16((ob[0] + od[2]) * inv, (ob[1] + od[3]) * inv);
        st_async_v2_i<OFF_O + 2048>(xo + d1, y0, y1, sb + MB_O + d1);
        st_async_v2_i<OFF_O + 1024>(xo + d2, y0, y1, sb + MB_O + d2);
        sts64_i<OFF_O>(xo, y0, y1);
      }
      bar_arrive(B_O, 384);
      TS(6);
      if (ln == 0) {
        if (hw == 0) {
          bulk_wait<0>();
          if (!PUBLATE && (s & 3) == 0 && s > 0) st_relaxed_u32(arena + (prog_off(h, j) + ln), s);
        }
        if (hw == 3) { mbar_expect_tx(sb + MB_S, 1280); sts64_i<SC_IN>(sb + 16 * ((s + 1) & 1), 0x7f000000u - __float_as_uint(osc), 0u); }
      }
      __syncwarp();
      ln = fresh(ln);
      auto mslot = [&](int c) -> uint32_t { return sb + OFF_MEM + c * 128 + (((ln >> 2) ^ (2 * (c & 3))) << 4); };
      const int lq = ln & 3;
      const uint32_t ma = mslot(cb28 + lq), mb_ = mslot(cb28 + (lq >> 1)) + (lq & 1) * 8;
      const unsigned char* gp = arena + (AR_ACC + acc_lane(hw, ln) + acc_step(s));
      const bool odd = ln & 1;
      uint32_t delay = a.delay + ((hist & 2) ? a.margin : 0);
      if (HINT) {
        const unsigned char* hp = arena + (AR_ACC + acc_step(s) + ln * 4);
        const uint32_t t0 = ld_relaxed_u32(hp + hint_off(0)), t1 = ld_relaxed_u32(hp + hint_off(1)), t2 = ld_relaxed_u32(hp + hint_off(2));
        const uint32_t r = __shfl_sync(0xffffffffu, t0, h);
        const int t = (t0 & t1 & t2 & 1u) ? max(max((int)(t0 - r), (int)(t1 - r)), (int)(t2 - r)) : 1000;
        delay += min(max(__reduce_max_sync(0xffffffffu, t) - __shfl_sync(0xffffffffu, t, h) - a.margin, 0), 1000) * 7 / 4;
      }
      SFENCE(ma);
      bar_sync(B_RED, 384);
      SFENCE(mb_);
      const uint32_t tw = clk_v();
      TSV(7, tw);
      if (ln == 0 && hw == 3) mbar_expect_tx(sb + MB_O, 2048);
      __syncwarp();
      while (clk_v() - tw < delay) {}
      TS(8);
      uint4 v[6];
      int spin = 0;
      const uint32_t cm = odd ? 0x5000u : 0u;
      do {
        static_for<0, 6>([&](auto I) { v[I.value] = ld_relaxed_v4_i<acc_voff(I.value)>(gp); });
      } while (__any_sync(0xffffffffu, (~((v[0].w & v[1].w & v[2].w) & (v[3].w & v[4].w & v[5].w)) & cm) != 0) && ++spin < SPIN_LIMIT);
      v[0].w = odd ? v[3].x : v[0].w; v[1].w = odd ? v[3].y : v[1].w; v[2].w = odd ? v[3].z : v[2].w; v[3].w = odd ? 0u : v[3].w;
      sts128_i<0>(ma, v[0].x, v[0].y, v[0].z, v[0].w);
      sts128_i<512>(ma, v[1].x, v[1].y, v[1].z, v[1].w);
      sts128_i<1024>(ma, v[2].x, v[2].y, v[2].z, v[2].w);
      sts128_i<0>(ma + du, v[4].x, v[4].y, v[4].z, v[5].z);
      sts64_i<512>(mb_ + du, v[5].x, v[5].y);
      if (!odd) sts128_i<1536>(mb_, v[3].x, v[3].y, v[3].z, v[3].w);
      hist = hist * 2 + (spin != 0);
      TSV(11, spin);
#ifdef TIMELINE
      if (spin && ln == 0) atomicAdd(&g_tl2[(a.tl >= 12) * 128 + 4], 1ull);
#endif
      TS(10);
      bar_sync(B_MEM0, 256); bar_sync(B_MEM1, 256);
      uint32_t m = lds32_i<SC_IN + 12>(sb);
      if (HINT) stamp(s + 1);
      uint32_t m2 = m;
      static_for<0, 3>([&](auto I) { m = amax_h2(amax_h2(amax_h2(amax_h2(m, v[I.value].x), v[I.value].y), v[I.value].z), v[I.value].w); });
      static_for<3, 6>([&](auto I) { m2 = amax_h2(amax_h2(amax_h2(m2, v[I.value].x), v[I.value].y), v[I.value].z); });
      m = amax_fold(amax_h2(amax_h2(m2, v[3].w), m));
      if (ln == 0) asm volatile("red.shared.max.u32 [%0], %1;" :: "r"(sb + SC_IN + 4 + 16 * ((s + 1) & 1)), "r"(m) : "memory");
    }
    bar_sync(B_RED, 384);
    if (hw == 0 && ln == 0) {
      store_kv(cfg::NSEG - 1);
      bulk_wait<0>();
      st_relaxed_u32(arena + prog_off(h, j), cfg::NSEG);
    }
    __syncwarp();
#ifdef TIMELINE
    if (cta == 0 && hw == 0 && ln == 0) { g_tl2[(a.tl >= 12) * 128 + 2] = clock64(); g_tl2[(a.tl >= 12) * 128 + 3] = gtime(); }
#endif
    TL_END(a.tl);
    asm volatile("barrier.cluster.arrive.relaxed.aligned; barrier.cluster.wait.aligned;" ::: "memory");
  } else {
    asm volatile("setmaxnreg.inc.sync.aligned.u32 232;");
    const int wi = warp & 3, hf = warp >> 2, tid = warp * 32 + lane;
    uint32_t w[40][4];
    uint32_t wqa;
    { const int mrow = r8 + ((lane >> 4) << 3), mch = 2 * wi + (m4 & 1); wqa = sb + mrow * 128 + ((mch ^ r8) << 4); }
    {
      const uint32_t wa = wqa + (hf ? OFF_WO : OFF_WQ);
      mbar_wait(sb + (hf ? MB_V : MB_K), 0);
      static_for<0, 20>([&](auto K) { ldsm_x4_t_i<K.value * 2048>(w[K.value], wa); });
      if (warp == 0) PT(1);
      bar_arrive(hf ? B_V : B_QK, 160);
      mbar_wait(sb + (hf ? MB_V : MB_K) + 8, 0);
      static_for<20, 40>([&](auto K) { ldsm_x4_t_i<K.value * 2048>(w[K.value], wa); });
      if (warp == 4) PT(2);
      bar_arrive(hf ? B_O : B_SL, 160);
      SFENCE(wa);
    }
    float iw, iq;
    {
      uint32_t m = 0;
#pragma unroll
      for (int k = 0; k < 40; k++) m = amax_bf2(amax_bf2(m, amax_bf2(w[k][0], w[k][1])), amax_bf2(w[k][2], w[k][3]));
      m = amax_fold(m);
      if (hf && lane == 0) asm volatile("red.shared.max.u32 [%0], %1;" :: "r"(sb + SC_W), "r"(m) : "memory");
      const int e = wscale_exp(m);
      const uint32_t sc = (uint32_t)(e + 127) * 0x00800080u; iw = exp2i(-e);
#pragma unroll
      for (int k = 0; k < 40; k++) { bf2_to_h2_inplace(w[k][0], sc); bf2_to_h2_inplace(w[k][1], sc); bf2_to_h2_inplace(w[k][2], sc); bf2_to_h2_inplace(w[k][3], sc); }
    }
    uint32_t x0[8];
    {
      float xa[16];
      const uint32_t dlo = (((sb + OFF_X) & 0x3FFFF) >> 4) | (1u << 16);
      if (warp == 0) PT(3);
      mbar_wait(sb + MB_X, 0);
      if (warp == 0) PT(4);
      wgmma_fence();
      static_for<0, 40>([&](auto K) { constexpr int k = K.value; wgmma_rs32h<((k >> 2) * 4096 + (k & 3) * 32) / 16, (k != 0)>(xa, w[k], dlo); });
      wgmma_commit();
      wgmma_wait<0>();
#pragma unroll
      for (int i = 0; i < 8; i++) x0[i] = pack_bf16(xa[2 * i] * iw, xa[2 * i + 1] * iw);
    }
    const bool t28 = j == 0 || warp < 4;
    const int bi = j == 0 ? hf : (warp < 4 ? j + 1 : 2 * (j - 1) + ((warp - 4) >> 1)), bv = t28 ? wi : 4 + (warp & 1);
    uint32_t wo1 = sb + OFF_WO + warp * 896 + lane * 16, wo2;
    {
      const int cb = (t28 ? unit28(bi) : unit24(bi)) - col0 / 8;
      uint32_t cp[4];
#pragma unroll
      for (int wd = 0; wd < 4; wd++) {
        int c, p;
        if (bv < 3) { c = 4 * bv + q4; p = wd; }
        else if (bv == 3) { if (q4 & 1) { c = 4 * (wd % 3) + q4; p = 3; } else { c = 12 + (q4 >> 1); p = wd; } }
        else if (bv == 4) { c = q4; p = wd; }
        else { if (wd < 2) { c = 4 + (q4 >> 1); p = 2 * (q4 & 1) + wd; } else { c = q4; p = 3; } }
        cp[wd] = sb + OFF_WO + ((g & 1) + (g & 2) * 4 + (g >> 2) * 2) * WOS + (cb + c) * 16 + p * 4;
      }
      const int cidx = (r8 & 1) + ((r8 >> 2) << 1);
      wo2 = sb + OFF_WO + warp * 896 + ((m4 & 1) ? 768 + (m4 >> 1) * 64 + cidx * 16 : 512 + (m4 >> 1) * 128 + r8 * 16);
      const bool dump = (m4 & 1) && (r8 & 2);
      uint32_t mo = 0;
      const bool regular = bv < 3 || bv == 4;
#pragma unroll 1
      for (int i = 0; i < 3; i++) {
        uint32_t x[4][4], y[4][4];
        const uint32_t o = i * 4 * WOK;
        mbar_wait(sb + MB_R + 8 * i, 0);
        if (warp == 0) PT(5 + i);
        if (regular) {
          static_for<0, 4>([&](auto K) {
            constexpr int kk = K.value;
            const uint4 u = lds128_i<kk * WOK>(cp[0] + o), v = lds128_i<kk * WOK + 4 * WOS>(cp[0] + o);
            x[kk][0] = u.x; x[kk][1] = u.y; x[kk][2] = u.z; x[kk][3] = u.w; y[kk][0] = v.x; y[kk][1] = v.y; y[kk][2] = v.z; y[kk][3] = v.w;
          });
        } else {
          static_for<0, 4>([&](auto K) {
            constexpr int kk = K.value;
#pragma unroll
            for (int wd = 0; wd < 4; wd++) { x[kk][wd] = lds32_i<kk * WOK>(cp[wd] + o); y[kk][wd] = lds32_i<kk * WOK + 4 * WOS>(cp[wd] + o); }
          });
        }
        bar_sync(B_C, 256);
        static_for<0, 4>([&](auto K) {
          constexpr int kk = K.value;
#pragma unroll
          for (int wd = 0; wd < 4; wd++) mo = amax_bf2(mo, amax_bf2(x[kk][wd], y[kk][wd]));
          stsm_x4_t_i<kk * WOK>(wo1 + o, x[kk][0], x[kk][1], y[kk][0], y[kk][1]);
          stsm_x4_t_i<0>(dump ? sb + OFF_S + 512 + lane * 16 : wo2 + o + kk * WOK, x[kk][2], x[kk][3], y[kk][2], y[kk][3]);
        });
      }
      if (warp == 0) PT(8);
      mo = amax_fold(mo);
      if (lane == 0) asm volatile("red.shared.max.u32 [%0], %1;" :: "r"(sb + SC_W + 4), "r"(mo) : "memory");
    }
    __syncwarp();
    auto run = [&](auto HF) {
    constexpr int hf = HF.value;
    uint32_t mema, sta, l16 = sb + lane * 16;
    uint32_t rq[hf ? NQ1 : NQ0][4];
    auto step_addr = [&](uint32_t kv) {
      const int lr = (l16 >> 4) & 7, lm = (l16 >> 7) & 3;
      mema = l16 ^ (lm << 5);
      sta = sb + lr * 16 + (lm < 2 ? OFF_Q + wi * 512 + hf * 128 + lm * 256 : OFF_KV + kv + 512 + (2 * wi + lm - 2) * 640);
    };
    auto x_gemm = [&](uint32_t ph, [[maybe_unused]] uint32_t tsb) {
      float xa[16];
      const uint32_t dlo = (((sb + OFF_X) & 0x3FFFF) >> 4) | (1u << 16);
      constexpr int NP = hf ? NQ1 : NP0;
      if constexpr (hf) {
        static_for<PQE, NP>([&](auto K) { ldsm_x4_t_i<OFF_WQ + K.value * 2048>(rq[K.value], wqa); });
        bar_sync(B_X, 256);
      }
      wgmma_fence();
      static_for<0, 40>([&](auto K) {
        constexpr int k = K.value;
        wgmma_rs32h<((k >> 2) * 4096 + (k & 3) * 32) / 16, (k != 0)>(xa, w[k], dlo);
        if constexpr (!hf && k == PFK && NP > PQE) { SFENCE(wqa); static_for<PQE, NP>([&](auto K) { ldsm_x4_t_i<OFF_WQ + K.value * 2048>(rq[K.value], wqa); }); SFENCE(wqa); }
        if constexpr (!hf && k == XT) bar_arrive(B_X, 256);
      });
      step_addr(ph * (2 * KVB));
      wgmma_commit();
      TS(9);
      wgmma_wait<0>();
      const uint32_t xs = l16 + (wi * 1280 + ph * (2 * KVB));
      stsm_x4_t_i<OFF_KV + hf * KVB>(xs, pack_bf16(xa[0] * iw, xa[1] * iw), pack_bf16(xa[4] * iw, xa[5] * iw), pack_bf16(xa[8] * iw, xa[9] * iw), pack_bf16(xa[12] * iw, xa[13] * iw));
      stsm_x4_t_i<OFF_KV + hf * KVB + 640>(xs, pack_bf16(xa[2] * iw, xa[3] * iw), pack_bf16(xa[6] * iw, xa[7] * iw), pack_bf16(xa[10] * iw, xa[11] * iw), pack_bf16(xa[14] * iw, xa[15] * iw));
    };
    auto wq_addr = [&](uint32_t l) -> uint32_t {
      const int lr = (l >> 4) & 7, lm = (l >> 7) & 3;
      return sb + hf * ((40 - NQ1) * 2048) + (lr + ((lm >> 1) << 3)) * 128 + (((2 * wi + (lm & 1)) ^ lr) << 4);
    };
    constexpr int NPM = hf ? NPM1 : NPM0;
    uint32_t u1[NPM][4], u2[NPM][4];
    static_for<0, NPM>([&](auto K) { ldsm_x4_i<(12 - NPM + K.value) * WOK>(u1[K.value], wo1); ldsm_x4_i<(12 - NPM + K.value) * WOK>(u2[K.value], wo2); });
    bar_sync(0, 384);
    iq = uniform_f(exp2i(-wscale_exp(lds32_i<SC_W + 8>(sb))));
    wqa = wq_addr(l16);
    static_for<0, (hf ? NQ1 : NP0)>([&](auto K) { ldsm_x4_t_i<OFF_WQ + K.value * 2048>(rq[K.value], wqa); });
    step_addr(0);
    stsm_x4_t_i<OFF_KV + hf * KVB>(l16 + wi * 1280, x0[0], x0[2], x0[4], x0[6]);
    stsm_x4_t_i<OFF_KV + hf * KVB + 640>(l16 + wi * 1280, x0[1], x0[3], x0[5], x0[7]);
    asm volatile("barrier.cluster.wait.aligned;" ::: "memory");
    TL_END(a.tl + 1);
#pragma unroll 1
    for (int s = 0; s < cfg::NSEG; s++) {
      TS_SETUP();
      const bool last = s == cfg::NSEG - 1;
#if CHAIN_TIMING
      if (tid == 0 && (s & 7) == 0) a.dbg[96 * 288 + cta * 8 + (s >> 3)] = clk32();
#endif
      bar_sync(hf ? B_MEM1 : B_MEM0, 256);
      const float sin_ = __uint_as_float(lds32_i<SC_IN>(sb + 16 * (s & 1)));
      constexpr int NPQ = (40 - NQ1) / 2;
      if constexpr (hf == 0) {
        float k0[4] = {0, 0, 0, 0}, k1[4] = {0, 0, 0, 0}, q0[4] = {0, 0, 0, 0}, q1[4] = {0, 0, 0, 0};
        constexpr auto pair_of = [](int t) { const int a = t * (20 - NPQ) / 20, b = (t + 1) * (20 - NPQ) / 20; return b > a ? NPQ + a : t - a; };
        uint32_t b[NB0][4];
        static_for<0, NB0>([&](auto T) { ldsm_x4_i<OFF_MEM + pair_of(T.value) * 512>(b[T.value], mema); });
        static_for<NP0, NQ0>([&](auto K) { ldsm_x4_t_i<OFF_WQ + K.value * 2048>(rq[K.value], wqa); });
        if (BBS < 100) bbfence<0>(mema);
        static_for<0, 20>([&](auto T) {
          constexpr int t = T.value, p = pair_of(t);
          uint32_t (&bb)[4] = b[t % NB0];
          if constexpr (p < NPQ) {
            mma16816h(q0, rq[(2 * p) % NQ0], bb[0], bb[1]);
            if constexpr (2 * p + NQ0 < 2 * NPQ) ldsm_x4_t_i<OFF_WQ + (2 * p + NQ0) * 2048>(rq[(2 * p) % NQ0], wqa);
          }
          mma16816h(k0, w[2 * p], bb[0], bb[1]);
          if constexpr (p < NPQ) {
            mma16816h(q1, rq[(2 * p + 1) % NQ0], bb[2], bb[3]);
            if constexpr (2 * p + 1 + NQ0 < 2 * NPQ) ldsm_x4_t_i<OFF_WQ + (2 * p + 1 + NQ0) * 2048>(rq[(2 * p + 1) % NQ0], wqa);
          }
          mma16816h(k1, w[2 * p + 1], bb[2], bb[3]);
          if constexpr (t + NB0 < 20) ldsm_x4_i<OFF_MEM + pair_of(t + NB0) * 512>(bb, mema);
          if constexpr (t < 20 - NB0 && (t % BBS) == BBS - 1) bbfence<t + 1>(mema);
        });
        const float sq = sin_ * iq, sk = sin_ * iw;
        stsm_x4_t_i<0>(sta, pack_bf16((q0[0] + q1[0]) * sq, (q0[1] + q1[1]) * sq), pack_bf16((q0[2] + q1[2]) * sq, (q0[3] + q1[3]) * sq),
                       pack_bf16((k0[0] + k1[0]) * sk, (k0[1] + k1[1]) * sk), pack_bf16((k0[2] + k1[2]) * sk, (k0[3] + k1[3]) * sk));
        TS(2);
        if (!last) {
          if (wi == 3) {
            const uint32_t s8 = sb + ((l16 & 511) >> 1), xr = sb + ((l16 & 511) >> 2), ka = l16 + (l16 & 384) * 4 + (s & 1) * (2 * KVB);
            bar_sync(B_QK, 384);
            uint32_t a0[4], a1[4], a2[4], a3[4], kb0[4], kb1[4];
            ldsm_x4_i<OFF_Q>(a0, l16); ldsm_x4_i<OFF_KV + 512>(kb0, ka); ldsm_x4_i<OFF_Q + 1024>(a2, l16); ldsm_x4_i<OFF_KV + 512 + 2560>(kb1, ka);
            ldsm_x4_i<OFF_Q + 512>(a1, l16);
            bar_arrive(B_A, 288);
            ldsm_x4_i<OFF_Q + 1536>(a3, l16);
            float sa[4] = {0, 0, 0, 0}, sc2[4] = {0, 0, 0, 0};
            mma16816(sa, a0[0], a0[1], a0[2], a0[3], kb0[0], kb0[1]);
            mma16816(sc2, a2[0], a2[1], a2[2], a2[3], kb1[0], kb1[1]);
            mma16816(sa, a1[0], a1[1], a1[2], a1[3], kb0[2], kb0[3]);
            mma16816(sc2, a3[0], a3[1], a3[2], a3[3], kb1[2], kb1[3]);
            const float x0 = (sa[0] + sa[2]) + (sc2[0] + sc2[2]), x1 = (sa[1] + sa[3]) + (sc2[1] + sc2[3]);
            const uint32_t xp = pack_bf16(x0, x1);
            st_async_b32_i<OFF_SR + 1024 + 256>(xr + d1, xp, sb + MB_S + d1);
            st_async_b32_i<OFF_SR + 1024>(xr + d2, xp, sb + MB_S + d2);
            sts64_i<OFF_S + 1024>(s8, __float_as_uint(x0), __float_as_uint(x1));
          } else {
            bar_arrive(B_QK, 384);
          }
          bar_sync(B_SL, 256);
        }
      } else {
        float v0[4] = {0, 0, 0, 0}, v1[4] = {0, 0, 0, 0}, q0[4] = {0, 0, 0, 0}, q1[4] = {0, 0, 0, 0};
        uint32_t b[NQ1 / 2][4];
        static_for<0, NQ1 / 2>([&](auto T) { ldsm_x4_i<OFF_MEM + (NPQ + T.value) * 512>(b[T.value], mema); });
        static_for<0, NQ1 / 2>([&](auto T) {
          constexpr int t = T.value, p = NPQ + t;
          uint32_t (&bb)[4] = b[t];
          mma16816h(q0, rq[2 * t], bb[0], bb[1]);
          mma16816h(q1, rq[2 * t + 1], bb[2], bb[3]);
          mma16816h(v0, w[2 * p], bb[0], bb[1]);
          mma16816h(v1, w[2 * p + 1], bb[2], bb[3]);
        });
        const float sq = sin_ * iq, sv = sin_ * iw;
        stsm_x2_t_i<0>(sta, pack_bf16((q0[0] + q1[0]) * sq, (q0[1] + q1[1]) * sq), pack_bf16((q0[2] + q1[2]) * sq, (q0[3] + q1[3]) * sq));
        TS(2);
        if (!last) { bar_arrive(B_QK, 384); bar_sync(B_A, 288); }
        float v2[4] = {0, 0, 0, 0}, v3[4] = {0, 0, 0, 0};
        uint32_t c[4][4];
        static_for<0, 4>([&](auto T) { ldsm_x4_i<OFF_MEM + T.value * 512>(c[T.value], mema); });
        static_for<0, NPQ>([&](auto T) {
          constexpr int p = T.value;
          uint32_t (&bb)[4] = c[p & 3];
          if constexpr (p & 1) { mma16816h(v0, w[2 * p], bb[0], bb[1]); mma16816h(v1, w[2 * p + 1], bb[2], bb[3]); }
          else { mma16816h(v2, w[2 * p], bb[0], bb[1]); mma16816h(v3, w[2 * p + 1], bb[2], bb[3]); }
          if constexpr (p + 4 < NPQ) ldsm_x4_i<OFF_MEM + (p + 4) * 512>(bb, mema);
        });
        stsm_x2_t_i<OFF_KV + KVB + 512>(l16 + (l16 & 128) * 4 + (wi * 1280 + (s & 1) * (2 * KVB)), pack_bf16(((v0[0] + v1[0]) + (v2[0] + v3[0])) * sv, ((v0[1] + v1[1]) + (v2[1] + v3[1])) * sv),
                            pack_bf16(((v0[2] + v1[2]) + (v2[2] + v3[2])) * sv, ((v0[3] + v1[3]) + (v2[3] + v3[3])) * sv));
        if (!last) bar_arrive(B_V, 256);
      }
      TS(3);
      if (last) break;
      {
        uint32_t t1[12][4], t2[12][4];
        const uint32_t o16 = l16;
        wo1 = l16 + (OFF_WO + warp * 896);
        wo2 = sb + OFF_WO + warp * 896 + ((l16 & 128) ? 768 + ((l16 & 256) >> 2) + (l16 & 16) + ((l16 & 64) >> 1) : 512 + ((l16 & 256) >> 1) + (l16 & 112));
        auto ldw = [&](auto K) { if constexpr (K.value < 12 - NPM) { ldsm_x4_i<K.value * WOK>(t1[K.value], wo1); ldsm_x4_i<K.value * WOK>(t2[K.value], wo2); } };
        constexpr int NR_ = NRT - NPM;
        constexpr int PB = (hf ? PB1 : PB0) < NR_ ? (hf ? PB1 : PB0) : NR_, PA = (hf ? PA1 : PA0) < PB ? (hf ? PA1 : PA0) : PB;
        static_for<0, PA>(ldw);
        mbar_spin(sb + MB_X, (s + 1) & 1);
        if constexpr (PB > PA) bar_sync(B_G, 384); else bar_arrive(B_G, 384);
        static_for<PA, PB>(ldw);
        float c0[4] = {0, 0, 0, 0}, c1[4] = {0, 0, 0, 0}, e0[4] = {0, 0, 0, 0}, e1[4] = {0, 0, 0, 0};
        uint32_t ob[6][4];
        auto kstep = [&](auto K) {
          constexpr int k = K.value;
          uint32_t (&bb)[4] = ob[k >> 1];
          uint32_t (&x)[4] = k < 12 - NPM ? t1[k] : u1[k < 12 - NPM ? 0 : k - (12 - NPM)];
          uint32_t (&y)[4] = k < 12 - NPM ? t2[k] : u2[k < 12 - NPM ? 0 : k - (12 - NPM)];
          if constexpr (k & 1) { mma16816(c1, x[0], x[1], x[2], x[3], bb[2], bb[3]); mma16816(e1, y[0], y[1], y[2], y[3], bb[2], bb[3]); }
          else { mma16816(c0, x[0], x[1], x[2], x[3], bb[0], bb[1]); mma16816(e0, y[0], y[1], y[2], y[3], bb[0], bb[1]); }
          if constexpr (k >= NRF) ldw(IC<k + NR_ - NRF>{});
        };
        auto ldo = [&](auto P) { ldsm_x4_i<OFF_O + P.value * 512>(ob[P.value], o16); };
        TS(4);
        bar_sync(B_O, 384);
        ldo(IC<0>{}); ldo(IC<1>{});
        SFENCE(o16);
        static_for<PB, NR_>(ldw);
        static_for<0, 4>(kstep);
        TS(5);
        mbar_spin(sb + MB_O, s & 1);
        TS(6);
        ldo(IC<2>{}); ldo(IC<NPM >= 2 ? 5 : 3>{});
        if (WOF) SFENCE(o16);
        kstep(IC<4>{});
        if constexpr (NPM < 2) { kstep(IC<5>{}); ldo(IC<4>{}); kstep(IC<6>{}); kstep(IC<7>{}); ldo(IC<5>{}); static_for<8, 12>(kstep); }
        else if constexpr (NPM >= 4) { kstep(IC<10>{}); kstep(IC<11>{}); ldo(IC<4>{}); kstep(IC<5>{}); ldo(IC<3>{}); kstep(IC<8>{}); kstep(IC<9>{}); kstep(IC<6>{}); kstep(IC<7>{}); }
        else { kstep(IC<5>{}); ldo(IC<3>{}); kstep(IC<11>{}); kstep(IC<10>{}); ldo(IC<4>{}); kstep(IC<6>{}); kstep(IC<7>{}); if constexpr (NPM == 3) { kstep(IC<9>{}); kstep(IC<8>{}); } else { kstep(IC<8>{}); kstep(IC<9>{}); } }
        l16 = fresh(l16);
        const int ln = (l16 >> 4) & 31;
        unsigned char* gr = arena + (AR_ACC + acc_lane(bi, ln) + acc_voff(bv) + acc_step(s));
        const bool cnt = (ln & 1) || !t28;
        wqa = wq_addr(l16);
        SFENCE(o16);
        static_for<0, PQE>([&](auto K) { ldsm_x4_t_i<OFF_WQ + K.value * 2048>(rq[K.value], wqa); });
        const uint32_t y0 = movm_t(pack_f16(c0[0] + c1[0], c0[1] + c1[1])), y1 = movm_t(pack_f16(c0[2] + c1[2], c0[3] + c1[3]));
        const uint32_t y2 = movm_t(pack_f16(e0[0] + e1[0], e0[1] + e1[1])), y3 = movm_t(pack_f16(e0[2] + e1[2], e0[3] + e1[3]));
        asm volatile("red.relaxed.gpu.global.add.noftz.v4.f16x2 [%0], {%1,%2,%3,%4};" :: "l"(gr), "r"(y0), "r"(y1), "r"(y2), "r"(cnt ? 0x3c00u : y3) : "memory");
        bar_arrive(B_RED, 384);
        bar_sync(B_C, 256);
        TS(7);
      }
#if CHAIN_TIMING
      x_gemm((s + 1) & 1, tsb);
#else
      x_gemm((s + 1) & 1, 0);
#endif
      TS(8);
    }
    };
    if (hf == 0) run(IC<0>{}); else run(IC<1>{});
    bar_arrive(B_RED, 384);
#if CHAIN_TIMING
    for (int i = tid; i < 288; i += 256) a.dbg[cta * 288 + i] = lds32_i<OFF_BAR + 128>(sb + i * 4);
#endif
    asm volatile("barrier.cluster.arrive.relaxed.aligned; barrier.cluster.wait.aligned;" ::: "memory");
  }
}
struct PrepArgs { const bf16 *wqkv, *wphi, *wo; unsigned char *wb, *wot; };
__device__ __forceinline__ void prep_body(const int cta, const PrepArgs& pa) {
  const int tid = threadIdx.x, lane = tid & 31, warp = tid >> 5, g = lane >> 2, q = lane & 3;
  const int pair = cta >> 1, which = cta & 1;
  uint32_t af[5][2][6];
#pragma unroll
  for (int i = 0; i < 5; i++)
#pragma unroll
    for (int hh = 0; hh < 2; hh++) {
      const uint32_t* r0 = (const uint32_t*)(pa.wqkv + (size_t)((warp * 5 + i) * 16 + g) * 1920 + which * 640 + (2 * pair + hh) * 20) + q;
      const uint32_t* r1 = r0 + 8 * 960;
      af[i][hh][0] = __ldg(r0); af[i][hh][1] = __ldg(r1); af[i][hh][2] = __ldg(r0 + 4); af[i][hh][3] = __ldg(r1 + 4);
      af[i][hh][4] = q < 2 ? __ldg(r0 + 8) : 0u; af[i][hh][5] = q < 2 ? __ldg(r1 + 8) : 0u;
    }
  uint32_t bfr[2][3][3];
#pragma unroll
  for (int hh = 0; hh < 2; hh++)
#pragma unroll
    for (int t = 0; t < 3; t++) {
      const bool on = t < 2 || (g & 1) == hh;
      const unsigned short* ph = (const unsigned short*)pa.wphi + (2 * pair + hh) * 400 + (t < 2 ? 8 * t + g : 16 + (g >> 1)) + 2 * q * 20;
#pragma unroll
      for (int r = 0; r < 3; r++) bfr[hh][t][r] = (on && (r < 2 || q < 2)) ? (uint32_t)__ldg(ph + r * 160) | ((uint32_t)__ldg(ph + r * 160 + 20) << 16) : 0u;
    }
  const int gt = cta * 256 + tid;
#pragma unroll 3
  for (int i = gt; i < 640 * 32; i += 8192) {
    const int k = (i & 7) + (i >> 8) * 8, h = (i >> 3) & 31;
    const uint2* src = (const uint2*)(pa.wqkv + (size_t)k * 1920 + 1280 + h * 20);
    const uint2 a = __ldg(src), b = __ldg(src + 1), c = __ldg(src + 2), d = __ldg(src + 3), e = __ldg(src + 4);
    uint4* dst = (uint4*)(pa.wb + ((size_t)((h >> 2) * 80 + (k >> 3)) * 32 + 20 + 3 * (h & 3)) * 128 + (k & 7) * 16);
    dst[0] = make_uint4(a.x, a.y, b.x, b.y); dst[8] = make_uint4(c.x, c.y, d.x, d.y);
    dst[16] = (h & 1) ? make_uint4(0, 0, e.x, e.y) : make_uint4(e.x, e.y, 0, 0);
  }
#pragma unroll 7
  for (int i = gt; i < 640 * 80; i += 8192) {
    const int r = i & 7, c = (i >> 3) % 80, kg = i / 640, c5 = kg % 5;
    const int row = (kg / 5) * 40 + (c5 < 2 ? 8 * c5 + r : (c5 == 2 ? 16 + (r & 3) + (r >> 2) * 20 : 20 + 8 * (c5 - 3) + r));
    *(uint4*)(pa.wot + ((size_t)((c / 10) * 80 + kg) * 10 + c % 10) * 128 + r * 16) = __ldg((const uint4*)(pa.wo + (size_t)row * cfg::DM + c * 8));
  }
#pragma unroll
  for (int i = 0; i < 5; i++) {
    uint32_t* dst = (uint32_t*)(pa.wb + ((size_t)((pair >> 1) * 80 + (warp * 5 + i) * 2) * 32 + which * 10 + (pair & 1) * 5) * 128) + lane;
#pragma unroll
    for (int t = 0; t < 5; t++) {
      float d[4] = {0, 0, 0, 0};
#pragma unroll
      for (int hh = 0; hh < 2; hh++)
        if (t == 2 || (t > 2) == (hh == 1)) {
          const int tt = t < 3 ? t : t - 3;
          mma16816(d, af[i][hh][0], af[i][hh][1], af[i][hh][2], af[i][hh][3], bfr[hh][tt][0], bfr[hh][tt][1]);
          mma1688(d, af[i][hh][4], af[i][hh][5], bfr[hh][tt][2]);
        }
      dst[t * 32] = pack_bf16(d[0], d[1]); dst[1024 + t * 32] = pack_bf16(d[2], d[3]);
    }
  }
}

__global__ void __launch_bounds__(256, 4) ln_kernel(const bf16* __restrict__ xin, bf16* __restrict__ xn, uint2* __restrict__ xh, uint4* __restrict__ z0, int n0,
                                                    uint4* __restrict__ z1, int n1, const bf16* pfa, const bf16* pfb, int npf, int tl) {
  asm volatile("griddepcontrol.wait;" ::: "memory");
  asm volatile("griddepcontrol.launch_dependents;" ::: "memory");
  TL_BEGIN(tl);
  const int warp = threadIdx.x >> 5, lane = threadIdx.x & 31;
  const int row = blockIdx.x * 8 + warp;
  uint2 xw[1][5];
#pragma unroll
  for (int i = 0; i < 5; i++) xw[0][i] = *(const uint2*)(xin + (size_t)row * cfg::DM + i * 128 + lane * 4);
  for (int i = blockIdx.x * 256 + threadIdx.x; i < n0; i += 256 * 256) z0[i] = make_uint4(0, 0, 0, 0);
  for (int i = blockIdx.x * 256 + threadIdx.x; i < n1; i += 256 * 256) z1[i] = make_uint4(0, 0, 0, 0);
  if (npf && xw[0][4].y != 0x7fc17fc1u) {
    for (int i = 0; i < npf; i++) {
      const uint32_t l = (uint32_t)i * 32768u + (blockIdx.x * 256 + threadIdx.x) / 2;
      if (l < cfg::DM * cfg::HD / 64) asm volatile("prefetch.global.L2 [%0];" :: "l"(((threadIdx.x & 1) ? pfa : pfb) + (size_t)l * 64) : "memory");
    }
  }
  ln_rows<1>(xw, row, lane, xn, xh);
  TL_END(tl);
}
struct Pipe { uint32_t stage, phase; };
template <int NS> __device__ __forceinline__ void pipe_adv(Pipe& p) { if (++p.stage == NS) { p.stage = 0; p.phase ^= 1; } }
constexpr uint32_t SWZ128 = 1;
__device__ __forceinline__ uint64_t desc_kmajor(uint32_t a) { return make_desc(a, 16, 1024, SWZ128); }
__device__ __forceinline__ uint64_t desc_mnmajor(uint32_t a) { return make_desc(a, 8192, 1024, SWZ128); }
__device__ __forceinline__ void wait_ge(const void* p, uint32_t target, uint32_t ns = 32) {
  int spin = 0;
  while (ld_acquire_u32(p) < target) { __nanosleep(ns); if (++spin > (1 << 21)) break; }
}
__device__ __forceinline__ void bulk_g2s_hint(uint32_t dst, const void* src, uint32_t bytes, uint32_t mb, uint64_t pol) {
  asm volatile("cp.async.bulk.shared::cluster.global.mbarrier::complete_tx::bytes.L2::cache_hint [%0], [%1], %2, [%3], %4;"
               :: "r"(dst), "l"(src), "r"(bytes), "r"(mb), "l"(pol) : "memory");
}
#ifndef PF_WB
#define PF_WB 2
#endif
#ifndef PF_XN
#define PF_XN 1
#endif
#ifndef STAG
#define STAG 1
#endif
#ifndef EF_KV
#define EF_KV 1
#endif
#ifndef EF_O
#define EF_O 1
#endif
__device__ __forceinline__ void fence_proxy_async_global() { asm volatile("fence.proxy.async.global;" ::: "memory"); }

namespace tr {
constexpr int NS = 4, STQ = 16384 + 24576, STO = 16384 + 40960;
constexpr int SEGB = 15360;
constexpr int OFF_K = NS * STQ;
constexpr int OFF_BAR = NS * STO;
constexpr int SMEM = OFF_BAR + 256;
static_assert(OFF_K + 4 * SEGB <= OFF_BAR && SMEM <= 232448, "smem");
enum { T_QA = 0, T_Q, T_A, T_OB, T_OS, T_L, T_END, T_P };
constexpr uint32_t C_QA = AR_CNT, C_O = AR_CNT + 64, C_Q = AR_CNT + 128, C_P = AR_CNT + 192;
constexpr int MAXITEMS = 1200;
struct Sched {
  uint8_t ks[16];
  uint8_t wide[16];
  uint8_t lrows[16];
  uint32_t n;
  uint16_t item[MAXITEMS];
};
struct Args {
  const unsigned char *kg, *vg;
  unsigned char* o;
  uint4* qs;
  unsigned char* part;
  const bf16 *xin, *xq;
  bf16 *xout, *xn;
  unsigned char* arena;
  const unsigned* go;
  int tl;
  uint32_t nap, nap2;
};
}

template <int N0, int N1>
__device__ __forceinline__ void tr_mainloop(float (&a0)[N0 / 2], float (&a1)[N1 ? N1 / 2 : 1], Pipe& p, uint32_t sb, uint32_t full, uint32_t empty, int nkb, int wg) {
  using namespace tr;
  constexpr uint32_t ST = N1 ? STO : STQ;
  uint32_t prev = 0;
#pragma unroll
  for (int i = 0; i < N0 / 2; i++) a0[i] = 0.f;
  if constexpr (N1 > 0) {
#pragma unroll
    for (int i = 0; i < N1 / 2; i++) a1[i] = 0.f;
  }
#pragma unroll 1
  for (int kb = 0; kb < nkb; kb++) {
    mbar_wait(full + 8 * p.stage, p.phase);
    const uint32_t st = sb + p.stage * ST;
    wgmma_fence();
#pragma unroll
    for (int kk = 0; kk < 4; kk++) {
      const uint64_t da = desc_kmajor(st + wg * 8192 + kk * 32);
      if constexpr (N0 == 192) wgmma_n192<0, 1>(a0, da, desc_mnmajor(st + 16384 + kk * 2048), (kb | kk) != 0);
      else wgmma_n128<0, 1>(a0, da, desc_mnmajor(st + 16384 + kk * 2048), (kb | kk) != 0);
      if constexpr (N1 > 0) wgmma_n128<0, 1>(a1, da, desc_mnmajor(st + 16384 + 24576 + kk * 2048), (kb | kk) != 0);
    }
    wgmma_commit();
    if (kb > 0) { wgmma_wait<1>(); mbar_arrive_if((threadIdx.x & 127) == 0, empty + 8 * prev); }
    prev = p.stage;
    pipe_adv<NS>(p);
  }
  wgmma_wait<0>();
  mbar_arrive_if((threadIdx.x & 127) == 0, empty + 8 * prev);
}
template <int N> __device__ __forceinline__ void stage_tiles(const float (&o)[N / 2], uint32_t base, int wi, int lane) {
  const uint32_t ra = base + (wi * 16 + (lane & 7) + 8 * ((lane >> 3) & 1)) * 128;
#pragma unroll
  for (int v = 0; v < N / 8; v += 2)
    stsm_x4(ra + (v >> 3) * 8192 + ((((v & 7) + (lane >> 4)) ^ (lane & 7)) << 4), pack_bf16(o[4 * v], o[4 * v + 1]), pack_bf16(o[4 * v + 2], o[4 * v + 3]),
            pack_bf16(o[4 * v + 4], o[4 * v + 5]), pack_bf16(o[4 * v + 6], o[4 * v + 7]));
}
__global__ void __launch_bounds__(384, 1) trail_kernel(const __grid_constant__ CUtensorMap tmX, const __grid_constant__ CUtensorMap tmQ,
                                                       const __grid_constant__ CUtensorMap tmWo5, const __grid_constant__ CUtensorMap tmWo2,
                                                       const __grid_constant__ CUtensorMap tmP, const __grid_constant__ tr::Sched sc,
                                                       const __grid_constant__ tr::Args a, const __grid_constant__ PrepArgs pa) {
  using namespace tr;
  [[maybe_unused]] const int tl = a.tl;
  TL_BEGIN(tl);
  extern __shared__ __align__(1024) unsigned char smem_raw[];
  const uint32_t sb = smem_u32(smem_raw);
  const int warp = __shfl_sync(0xffffffffu, (int)threadIdx.x >> 5, 0), lane = threadIdx.x & 31;
  unsigned char* const arena = a.arena;
  const uint32_t full = sb + OFF_BAR, empty = full + 8 * NS, barK = empty + 8 * NS, barKfree = barK + 16, staged = barKfree + 16;
  const uint32_t kvrdy = staged + 32, mfull = kvrdy + 8, mempty = mfull + 16, mbox = mempty + 16;
  uint32_t go = 0;
  if (threadIdx.x == 256) go = ld_acquire_u32(a.go);
  if (threadIdx.x == 0) {
    for (int i = 0; i < NS; i++) { mbar_init(full + 8 * i, 1); mbar_init(empty + 8 * i, 2); }
    for (int i = 0; i < 2; i++) {
      mbar_init(barK + 8 * i, 1); mbar_init(barKfree + 8 * i, 1); mbar_init(staged + 16 * i, 4); mbar_init(staged + 16 * i + 8, 4);
      mbar_init(mfull + 8 * i, 1); mbar_init(mempty + 8 * i, 11);
    }
    mbar_init(kvrdy, 1);
    asm volatile("fence.mbarrier_init.release.cluster;" ::: "memory");
  }
  __syncthreads();
  Pipe mp{0, 0};
  auto next_item = [&]() -> uint32_t {
    uint32_t it;
    mbar_wait(mfull + 8 * mp.stage, mp.phase);
    asm volatile("ld.shared.u32 %0, [%1];" : "=r"(it) : "r"(mbox + 4 * mp.stage) : "memory");
    return it;
  };
  if (warp >= 8) {
    asm volatile("setmaxnreg.dec.sync.aligned.u32 40;");
    if (warp == 8) { go = __shfl_sync(0xffffffffu, go, 0); if (elect_one()) {
      Pipe p{0, 1};
      mp.phase = 1;
      uint32_t kph = 1, rph = 0, wide = 0, qdone = 0;
      prefetch_tmap(&tmX); prefetch_tmap(&tmQ); prefetch_tmap(&tmWo5); prefetch_tmap(&tmWo2); prefetch_tmap(&tmP);
      const uint64_t ef = policy_evict_first();
      auto ld_kv = [&](uint32_t d, const void* s, uint32_t n, uint32_t mb) { if (EF_KV) bulk_g2s_hint(d, s, n, mb, ef); else bulk_g2s(d, s, n, mb); };
      auto ld_o = [&](uint32_t d, const void* s, uint32_t n, uint32_t mb) { if (EF_O) bulk_g2s_hint(d, s, n, mb, ef); else bulk_g2s(d, s, n, mb); };
      auto stage = [&](uint32_t bytes) -> uint32_t {
        mbar_wait(empty + 8 * p.stage, p.phase);
        mbar_expect_tx(full + 8 * p.stage, bytes);
        return sb + p.stage * (wide ? STO : STQ);
      };
      auto fetch = [&]() -> uint32_t { uint32_t v; asm volatile("atom.relaxed.gpu.global.add.u32 %0, [%1], 1;" : "=r"(v) : "l"(arena + AR_QUEUE) : "memory"); return v; };
      if (!go) wait_ge(a.go, 1, 200);
      fence_proxy_async_global();
      uint32_t next = fetch();
      while (true) {
        const uint32_t item = next;
        const uint32_t code = sc.item[min(item, sc.n)];
        const int type = code >> 11, m = (code >> 7) & 15, k = code & 127;
        if (type == T_A && !((qdone >> m) & 1)) { wait_ge(arena + C_Q + m * 4, 64); qdone |= 1u << m; }
        if (type == T_OB && !wide) for (uint32_t i = 0; i < NS; i++) mbar_wait(empty + 8 * i, i >= p.stage ? p.phase : p.phase ^ 1);
        wide = type == T_OB;
        mbar_wait(mempty + 8 * mp.stage, mp.phase);
        asm volatile("st.shared.u32 [%0], %1;" :: "r"(mbox + 4 * mp.stage), "r"((p.stage << 24) | (type << 16) | (m << 8) | (k & 255)) : "memory");
        mbar_arrive(mfull + 8 * mp.stage);
        pipe_adv<2>(mp);
        if (type == T_END) break;
        if (type == T_P) { next = fetch(); continue; }
        if (type == T_L) {
          const int nr = sc.lrows[m], np = sc.ks[m];
          prefetch_l2(a.xin + (size_t)(m * 128 + k * 8 * nr) * cfg::DM, nr * 10240);
          wait_ge(arena + C_O + m * 4, np * (sc.wide[m] ? 4 : 10), m < 13 ? a.nap : 32);
          fence_proxy_async_global();
#pragma unroll 1
          for (int r = 0; r < nr; r++) {
            const int rg = m * 16 + k * nr + r;
#pragma unroll 1
            for (int q0 = 0; q0 <= np; q0 += 4) {
              const int n = min(4, np + 1 - q0);
              const uint32_t st = stage(n * 10240), fb = full + 8 * p.stage;
#pragma unroll 1
              for (int q = q0; q < q0 + n; q++) {
                if (q == 0) bulk_g2s(st, a.xin + (size_t)rg * 8 * cfg::DM, 10240, fb);
                else tma_load_3d(st + (q - q0) * 10240, &tmP, 0, rg & 7, ((q - 1) * 32 + (rg >> 3)) * 10, fb);
              }
              pipe_adv<NS>(p);
            }
          }
          next = fetch(); continue;
        }
        if (type <= T_A) {
          if (type != T_A)
#pragma unroll 1
            for (int kb = 0; kb < 10; kb++) {
              const uint32_t st = stage(STQ), fb = full + 8 * p.stage;
              tma_load_2d(st, &tmX, kb * 64, m * 128, fb);
              tma_load_3d(st + 16384, &tmQ, 0, kb * 64, k * 3, fb);
              pipe_adv<NS>(p);
              if (type == T_Q && kb == 8) next = fetch();
            }
          if (type != T_Q) {
            const size_t blk = ((size_t)(m % KVRING) * 4 * 96 + k * 3) * 5120;
            kph ^= 1;
            mbar_wait(kvrdy, rph); rph ^= 1;
            next = fetch();
            fence_proxy_async_global();
#pragma unroll 1
            for (int w = type == T_A ? 0 : 2; w < 4; w++) {
              const uint32_t st = stage(2 * SEGB), fb = full + 8 * p.stage;
              for (int sg = 0; sg < 2; sg++) ld_kv(st + sg * SEGB, (w < 2 ? a.kg : a.vg) + blk + (size_t)(2 * (w & 1) + sg) * (96 * 5120), SEGB, fb);
              pipe_adv<NS>(p);
            }
          }
        } else {
          const int nn = wide ? 2 : 5, nb = wide ? 5 : 2, nt = k % nn, nkb = 96 / sc.ks[m], k0 = (k / nn) * nkb;
          const Pipe p0 = p;
          for (int kb = 0; kb < nkb; kb++) {
            if (wide && kb < NS && p.stage >= 2) { mbar_wait(barKfree, kph); mbar_wait(barKfree + 8, kph); }
            const uint32_t st = stage(16384 + nb * 8192), fb = full + 8 * p.stage;
            tma_load_3d(st + 16384, wide ? &tmWo5 : &tmWo2, 0, (k0 + kb) * 64, nt * nb, fb);
            if (kb >= NS) ld_o(st, a.o + ((size_t)(m % ORING) * 96 + k0 + kb) * 16384, 16384, fb);
            pipe_adv<NS>(p);
            if (kb == NS - 1 || (kb == nkb - 1 && nkb < NS)) {
              wait_ge(arena + C_QA + m * 4, 64, m < 14 ? a.nap : 32);
              fence_proxy_async_global();
              Pipe q = p0;
#pragma unroll 1
              for (int i = 0; i <= kb; i++) { ld_o(sb + q.stage * (wide ? STO : STQ), a.o + ((size_t)(m % ORING) * 96 + k0 + i) * 16384, 16384, full + 8 * q.stage); pipe_adv<NS>(q); }
            }
          }
          next = fetch();
          for (int w = wide ? -(int)((2 - p.stage) & 3) : 0; w < 2; w++) { mbar_wait(empty + 8 * p.stage, p.phase); mbar_arrive(full + 8 * p.stage); pipe_adv<NS>(p); }
          kph ^= wide;
        }
      }
    } } else if (warp < 11) { if (elect_one()) {
      const int w = warp - 9;
      uint32_t sph = 0;
      [[maybe_unused]] int nlog = 0;
#ifdef TIMELINE
      if (w == 0) { unsigned long long* lg = g_log + (((tl >= 12) * 132 + blockIdx.x) * 64 + nlog++) * 2; lg[0] = T_END << 16; lg[1] = gtime(); lg[2] = ~0ull; }
#endif
      while (true) {
        const uint32_t it = next_item();
        const int type = (it >> 16) & 255, m = (it >> 8) & 255, k = it & 255;
        const uint32_t slot = mp.stage;
        pipe_adv<2>(mp);
        if (type == T_END) break;
        mbar_wait(staged + 16 * w + 8 * slot, (sph >> slot) & 1); sph ^= 1u << slot;
        mbar_arrive(mempty + 8 * slot);
#ifdef TIMELINE
        if (w == 0 && nlog < 63) { unsigned long long* lg = g_log + (((tl >= 12) * 132 + blockIdx.x) * 64 + nlog++) * 2; lg[0] = (type << 16) | (m << 8) | k; lg[1] = gtime(); lg[2] = ~0ull; }
#endif
        if (type == T_L) continue;
        if (type == T_QA || type == T_A) {
          for (int jj = 0; jj < 3; jj++) bulk_s2g(a.o + ((size_t)(m % ORING) * 96 + k * 3 + jj) * 16384 + w * 8192, sb + OFF_K + w * 2 * SEGB + jj * 8192, 8192);
          bulk_commit();
          bulk_wait<0>();
          mbar_arrive(barKfree + 8 * w);
        } else if (type == T_OB || type == T_OS) {
          const bool wide = type == T_OB;
          const int nn = wide ? 2 : 5, nb = wide ? 5 : 2;
          const uint32_t own = wide ? 2 + w : ((it >> 24) + 96 / sc.ks[m] + w) % NS;
          bulk_s2g(a.part + ((size_t)((k / nn) * 32 + m * 2 + w) * 10 + (k % nn) * nb) * 8192, sb + own * (wide ? STO : STQ), nb * 8192);
          bulk_commit();
          bulk_wait<0>();
          mbar_arrive(empty + 8 * own);
          if (wide && w) { mbar_arrive(barKfree); mbar_arrive(barKfree + 8); }
        }
        if (type == T_Q || type == T_P) __threadfence();
        asm volatile("red.relaxed.gpu.global.add.u32 [%0], 1;" :: "l"(arena + (type == T_Q ? C_Q : (type <= T_A ? C_QA : (type == T_P ? C_P : C_O))) + m * 4) : "memory");
      }
    } } else if (elect_one()) {
      const uint64_t ef = policy_evict_first();
      uint32_t kph = 1;
      if (PF_WB && blockIdx.x >= 52) { prefetch_l2(pa.wb + (blockIdx.x - 52) * 32768, 32768); prefetch_l2(pa.wot + (blockIdx.x - 52) * 10240, 10240); }
      if (PF_WB > 1 && blockIdx.x >= 52) { prefetch_l2(a.xn + (blockIdx.x - 52) * 8192, 16384); prefetch_l2(a.xout + (blockIdx.x - 52) * 8192, 16384); }
      while (true) {
        const uint32_t it = next_item();
        const int type = (it >> 16) & 255, m = (it >> 8) & 255, k = it & 255;
        const uint32_t slot = mp.stage;
        pipe_adv<2>(mp);
        if (type == T_END) break;
        if (PF_XN && type == T_QA && m < 15) prefetch_l2(a.xq + ((m + 1) * 128 + k * 4) * cfg::DM, 5120);
        if (type == T_QA || type == T_A) {
          for (int spin = 0; spin < (1 << 21); spin++) {
            const uint4 f = ld_relaxed_v4(arena + prog_off(k, 0));
            if (min(min(f.x, f.y), f.z) >= (uint32_t)(4 * m + 4)) break;
            __nanosleep(m < 15 ? a.nap : a.nap2);
          }
          mbar_arrive(kvrdy);
          fence_proxy_async_global();
          const unsigned char* src = a.kg + ((size_t)(m % KVRING) * 4 * 96 + k * 3) * 5120;
#pragma unroll 1
          for (int w = 0; w < 2; w++) {
            mbar_wait(barKfree + 8 * w, kph);
            if (type == T_A) { mbar_arrive(barK + 8 * w); continue; }
            mbar_expect_tx(barK + 8 * w, 2 * SEGB);
            for (int sg = 2 * w; sg < 2 * w + 2; sg++) { if (EF_KV) bulk_g2s_hint(sb + OFF_K + sg * SEGB, src + (size_t)sg * (96 * 5120), SEGB, barK + 8 * w, ef); else bulk_g2s(sb + OFF_K + sg * SEGB, src + (size_t)sg * (96 * 5120), SEGB, barK + 8 * w); }
          }
          kph ^= 1;
        } else if (type == T_OB) {
          mbar_wait(barKfree, kph); mbar_wait(barKfree + 8, kph);
          kph ^= 1;
        }
        mbar_arrive(mempty + 8 * slot);
      }
      if (blockIdx.x == gridDim.x - 1) asm volatile("griddepcontrol.wait;" ::: "memory");
    }
    return;
  }
  asm volatile("setmaxnreg.inc.sync.aligned.u32 232;");
  const int wg = warp >> 2, wi = warp & 3;
  const int g = lane >> 2, q4 = lane & 3;
  asm volatile("griddepcontrol.launch_dependents;" ::: "memory");
  Pipe p{0, 0};
  uint32_t kph = 0;
  auto own_slot = [&]() -> uint32_t {
    const uint32_t sA = p.stage, phA = p.phase; pipe_adv<NS>(p);
    const uint32_t sB = p.stage, phB = p.phase; pipe_adv<NS>(p);
    mbar_wait(full + 8 * sA, phA); mbar_wait(full + 8 * sB, phB);
    mbar_arrive_if((threadIdx.x & 127) == 0, empty + 8 * (wg ? sA : sB));
    return wg ? sB : sA;
  };
  while (true) {
    const uint32_t it = __shfl_sync(0xffffffffu, next_item(), 0);
    const int type = (it >> 16) & 255, m = (it >> 8) & 255, k = it & 255;
    mbar_arrive_if(lane == 0, mempty + 8 * mp.stage);
    const uint32_t done = staged + 16 * wg + 8 * mp.stage;
    pipe_adv<2>(mp);
    if (type == T_END) break;
    if (type == T_P) {
      prep_body(k, pa);
      __syncwarp();
      mbar_arrive_if(lane == 0, done);
      continue;
    }
    if (type == T_L) {
      const int nr = sc.lrows[m], np = sc.ks[m];
      const uint32_t po = (lane >> 4) * 1024 + warp * 128 + ((((lane >> 1) & 7) ^ warp) << 4) + (lane & 1) * 8;
#pragma unroll 1
      for (int r = 0; r < nr; r++) {
        uint2 xw[1][5]; float s[20];
#pragma unroll
        for (int i = 0; i < 20; i++) s[i] = 0.f;
#pragma unroll 1
        for (int q0 = 0; q0 <= np; q0 += 4) {
          const uint32_t st = sb + p.stage * STQ;
          mbar_wait(full + 8 * p.stage, p.phase);
          if (q0 == 0) static_for<0, 5>([&](auto I) { xw[0][I.value] = lds64_i<I.value * 256>(st + warp * 1280 + lane * 8); });
#pragma unroll 1
          for (int q = q0 ? 0 : 1; q < min(4, np + 1 - q0); q++)
            static_for<0, 5>([&](auto I) {
              constexpr int i = I.value;
              const uint2 t = lds64_i<i * 2048>(st + q * 10240 + po);
              s[4 * i] += bf_lo(t.x); s[4 * i + 1] += bf_hi(t.x); s[4 * i + 2] += bf_lo(t.y); s[4 * i + 3] += bf_hi(t.y);
            });
          bar_sync(3 + wg, 128);
          mbar_arrive_if((threadIdx.x & 127) == 0, empty + 8 * p.stage);
          pipe_adv<NS>(p);
        }
        const int row = (m * 16 + k * nr + r) * 8 + warp;
#pragma unroll
        for (int i = 0; i < 5; i++) {
          bf16r2(s[4 * i], s[4 * i + 1]); bf16r2(s[4 * i + 2], s[4 * i + 3]);
          xw[0][i] = make_uint2(pack_bf16(bf_lo(xw[0][i].x) + s[4 * i], bf_hi(xw[0][i].x) + s[4 * i + 1]), pack_bf16(bf_lo(xw[0][i].y) + s[4 * i + 2], bf_hi(xw[0][i].y) + s[4 * i + 3]));
          *(uint2*)(a.xout + (size_t)row * cfg::DM + i * 128 + lane * 4) = xw[0][i];
        }
        ln_rows<1>(xw, row, lane, a.xn, nullptr);
      }
      __syncwarp();
      mbar_arrive_if(lane == 0, done);
      continue;
    }
    if (type >= T_OB) {
      const int nkb = 96 / sc.ks[m];
      if (type == T_OB) {
        float a0[96], a1[64];
        tr_mainloop<192, 128>(a0, a1, p, sb, full, empty, nkb, wg);
        while (p.stage != 2) { mbar_wait(full + 8 * p.stage, p.phase); mbar_arrive_if((threadIdx.x & 127) == 0, empty + 8 * p.stage); pipe_adv<NS>(p); }
        const uint32_t st = sb + own_slot() * STO;
        stage_tiles<192>(a0, st, wi, lane); stage_tiles<128>(a1, st + 24576, wi, lane);
      } else {
        float a0[64], a1[1];
        tr_mainloop<128, 0>(a0, a1, p, sb, full, empty, nkb, wg);
        stage_tiles<128>(a0, sb + own_slot() * STQ, wi, lane);
      }
      fence_proxy_async();
      __syncwarp();
      mbar_arrive_if(lane == 0, done);
      continue;
    }
    uint32_t qf[12][4];
    uint4* qp = a.qs + ((size_t)((m & 7) * 32 + k) * 12) * 256 + threadIdx.x;
    if (type != T_A) {
      float acc[96], a1[1];
      tr_mainloop<192, 0>(acc, a1, p, sb, full, empty, 10, wg);
#pragma unroll
      for (int i = 0; i < 12; i++) {
        qf[i][0] = pack_bf16(acc[8 * i], acc[8 * i + 1]); qf[i][1] = pack_bf16(acc[8 * i + 2], acc[8 * i + 3]);
        qf[i][2] = pack_bf16(acc[8 * i + 4], acc[8 * i + 5]); qf[i][3] = pack_bf16(acc[8 * i + 6], acc[8 * i + 7]);
      }
      if (type == T_Q) {
#pragma unroll
        for (int i = 0; i < 12; i++) qp[i * 256] = make_uint4(qf[i][0], qf[i][1], qf[i][2], qf[i][3]);
        __syncwarp();
        mbar_arrive_if(lane == 0, done);
        continue;
      }
    } else {
#pragma unroll
      for (int i = 0; i < 12; i++) { const uint4 v = __ldcg(qp + i * 256); qf[i][0] = v.x; qf[i][1] = v.y; qf[i][2] = v.z; qf[i][3] = v.w; }
    }
    const uint32_t ost = sb + OFF_K + wg * 2 * SEGB;
    const bool second = wi >= 2;
    uint32_t pf[5][4];
    {
      float sa[20], sb2[20];
      uint32_t kbase = ost, kslot = 0;
      if (type == T_A) { kslot = own_slot(); kbase = sb + kslot * STQ; } else mbar_wait(barK + 8 * wg, kph);
      if (STAG && wg) bar_sync(1, 256);
      wgmma_fence();
#pragma unroll
      for (int i = 0; i < 12; i++) {
        wgmma_rs_n40<0>(sa, qf[i][0], qf[i][1], qf[i][2], qf[i][3], make_desc(kbase + i * 1280, 640, 128, 0), i != 0);
        wgmma_rs_n40<0>(sb2, qf[i][0], qf[i][1], qf[i][2], qf[i][3], make_desc(kbase + SEGB + i * 1280, 640, 128, 0), i != 0);
      }
      wgmma_commit();
      wgmma_wait<0>();
      if (STAG && !wg) bar_arrive(1, 256);
      mbar_arrive_if(type == T_A && (threadIdx.x & 127) == 0, empty + 8 * kslot);
      const float cs = 0.07216878364870322f * 1.4426950408889634f;
      const int r0 = 16 * (wi & 1) + g, r1 = r0 + 8;
      float m0 = -INFINITY, m1 = -INFINITY;
#pragma unroll
      for (int n = 0; n < 5; n++) {
#pragma unroll
        for (int e = 0; e < 2; e++) {
          const int key = 8 * n + 2 * q4 + e;
          float x = second ? sb2[4 * n + e] : sa[4 * n + e], y = second ? sb2[4 * n + 2 + e] : sa[4 * n + 2 + e];
          if (n < 4) { if (key > r0) x = -INFINITY; if (key > r1) y = -INFINITY; }
          sa[4 * n + e] = x; sa[4 * n + 2 + e] = y;
          m0 = fmaxf(m0, x); m1 = fmaxf(m1, y);
        }
      }
      m0 = fmaxf(m0, __shfl_xor_sync(0xffffffffu, m0, 1)); m1 = fmaxf(m1, __shfl_xor_sync(0xffffffffu, m1, 1));
      m0 = fmaxf(m0, __shfl_xor_sync(0xffffffffu, m0, 2)); m1 = fmaxf(m1, __shfl_xor_sync(0xffffffffu, m1, 2));
      float s0 = 0.f, s1 = 0.f;
#pragma unroll
      for (int n = 0; n < 5; n++) {
#pragma unroll
        for (int e = 0; e < 2; e++) {
          sa[4 * n + e] = ex2f((sa[4 * n + e] - m0) * cs); sa[4 * n + 2 + e] = ex2f((sa[4 * n + 2 + e] - m1) * cs);
          s0 += sa[4 * n + e]; s1 += sa[4 * n + 2 + e];
        }
      }
      s0 += __shfl_xor_sync(0xffffffffu, s0, 1); s1 += __shfl_xor_sync(0xffffffffu, s1, 1);
      s0 += __shfl_xor_sync(0xffffffffu, s0, 2); s1 += __shfl_xor_sync(0xffffffffu, s1, 2);
      const float i0 = rcpf(s0), i1 = rcpf(s1);
#pragma unroll
      for (int n = 0; n < 5; n++) {
        const uint32_t x = pack_bf16(sa[4 * n] * i0, sa[4 * n + 1] * i0), y = pack_bf16(sa[4 * n + 2] * i1, sa[4 * n + 3] * i1);
        if (n < 4) {
          pf[n >> 1][2 * (n & 1)] = second ? 0u : x; pf[n >> 1][2 * (n & 1) + 1] = second ? 0u : y;
          pf[2 + (n >> 1)][2 * (n & 1)] = second ? x : 0u; pf[2 + (n >> 1)][2 * (n & 1) + 1] = second ? y : 0u;
        } else {
          pf[4][0] = second ? 0u : x; pf[4][1] = second ? 0u : y; pf[4][2] = second ? x : 0u; pf[4][3] = second ? y : 0u;
        }
      }
    }
    {
      float o[96];
#pragma unroll
      for (int i = 0; i < 5; i++) { PIN(pf[i][0]); PIN(pf[i][1]); PIN(pf[i][2]); PIN(pf[i][3]); }
      const uint32_t own = own_slot(), vbase = sb + own * STQ;
      wgmma_fence();
#pragma unroll
      for (int i = 0; i < 5; i++)
        wgmma_rs_n192<1>(o, pf[i][0], pf[i][1], pf[i][2], pf[i][3], i < 4 ? make_desc(vbase + (i >> 1) * SEGB + (i & 1) * 256, 128, 640, 0) : make_desc(vbase + 512, SEGB, 640, 0), i != 0);
      wgmma_commit();
      if (type == T_A) mbar_wait(barK + 8 * wg, kph);
      kph ^= 1;
      wgmma_wait<0>();
      mbar_arrive_if((threadIdx.x & 127) == 0, empty + 8 * own);
      stage_tiles<192>(o, ost, wi, lane);
      fence_proxy_async();
      __syncwarp();
      mbar_arrive_if(lane == 0, done);
    }
  }
}
namespace bf {
constexpr int NS = 4, STAGE = 16384 + 32768;
constexpr int PIECE = 20480;
constexpr int OFF_PHI = 0, OFF_V = 40960, OFF_KV = 65536;
constexpr int OFF_OST = 5 * PIECE;
constexpr int OFF_WOT = 6 * PIECE;
constexpr int OFF_BAR = OFF_WOT + 102400;
constexpr int SMEM = OFF_BAR + 256;
static_assert(NS * STAGE <= OFF_BAR && SMEM <= 232448, "smem");
constexpr int KVACC = 32 * 5 * 1024;
struct Args {
  const unsigned char *wb, *wot;
  unsigned char *kvacc, *o2;
  const bf16* xin;
  bf16* xout;
  unsigned* go;
  const void* prep;
  const bf16 *pf0, *pf1;
  int pfn, pfns, pfwait;
  int tl;
};
}
__device__ __forceinline__ void hedgehog_features(float (&x)[2][5], uint32_t (&w)[2][5]) {
  const float L = 1.4426950408889634f;
  float mx[2], mn[2], sp[2], sn[2], pos[2][5], neg[2][5];
#pragma unroll
  for (int r = 0; r < 2; r++) {
    mx[r] = fmaxf(fmaxf(fmaxf(x[r][0], x[r][1]), fmaxf(x[r][2], x[r][3])), x[r][4]);
    mn[r] = fminf(fminf(fminf(x[r][0], x[r][1]), fminf(x[r][2], x[r][3])), x[r][4]);
  }
#pragma unroll
  for (int o = 1; o < 4; o <<= 1)
#pragma unroll
    for (int r = 0; r < 2; r++) {
      const uint32_t t = __shfl_xor_sync(0xffffffffu, __byte_perm(__float_as_uint(mn[r]), __float_as_uint(mx[r]), 0x7632), o);
      mx[r] = fmaxf(mx[r], bf_hi(t)); mn[r] = fminf(mn[r], bf_lo(t));
    }
#pragma unroll
  for (int r = 0; r < 2; r++) {
#pragma unroll
    for (int i = 0; i < 5; i++) { pos[r][i] = ex2f((x[r][i] - mx[r]) * L); neg[r][i] = ex2f((mn[r] - x[r][i]) * L); }
    sp[r] = ((pos[r][0] + pos[r][1]) + (pos[r][2] + pos[r][3])) + pos[r][4];
    sn[r] = ((neg[r][0] + neg[r][1]) + (neg[r][2] + neg[r][3])) + neg[r][4];
  }
#pragma unroll
  for (int o = 1; o < 4; o <<= 1)
#pragma unroll
    for (int r = 0; r < 2; r++) { sp[r] += __shfl_xor_sync(0xffffffffu, sp[r], o); sn[r] += __shfl_xor_sync(0xffffffffu, sn[r], o); }
#pragma unroll
  for (int r = 0; r < 2; r++) {
    const float ip = rcpf(sp[r]), in_ = rcpf(sn[r]);
    w[r][0] = pack_bf16(pos[r][0] * ip, pos[r][1] * ip); w[r][1] = pack_bf16(pos[r][2] * ip, pos[r][3] * ip);
    w[r][2] = pack_bf16(neg[r][0] * in_, neg[r][1] * in_); w[r][3] = pack_bf16(neg[r][2] * in_, neg[r][3] * in_);
    w[r][4] = pack_bf16(pos[r][4] * ip, neg[r][4] * in_);
  }
}
__device__ __forceinline__ void bulk_g2s_mc(uint32_t dst, const void* src, uint32_t bytes, uint32_t mb) {
  asm volatile("cp.async.bulk.shared::cluster.global.mbarrier::complete_tx::bytes.multicast::cluster [%0], [%1], %2, [%3], %4;"
               :: "r"(dst), "l"(src), "r"(bytes), "r"(mb), "h"((unsigned short)3) : "memory");
}
__device__ __forceinline__ void mbar_arrive_remote_if(bool c, uint32_t b) {
  asm volatile("{\n.reg .pred p;\nsetp.ne.u32 p, %1, 0;\n@p mbarrier.arrive.shared::cluster.b64 _, [%0];\n}" :: "r"(b), "r"((uint32_t)c) : "memory");
}

__global__ void __cluster_dims__(2, 1, 1) __launch_bounds__(384, 1) blayer_kernel(const __grid_constant__ CUtensorMap tmA, const __grid_constant__ bf::Args a) {
  using namespace bf;
  [[maybe_unused]] const int tl = a.tl;
  extern __shared__ __align__(1024) unsigned char smem_raw[];
  const uint32_t sb = smem_u32(smem_raw);
  const int warp = __shfl_sync(0xffffffffu, (int)threadIdx.x >> 5, 0), lane = threadIdx.x & 31;
  const uint32_t full = sb + OFF_BAR, empty = full + 8 * NS, full2 = empty + 8 * NS, empty2 = full2 + 64, barW = empty2 + 16, drained = barW + 8, staged = drained + 8, freeb = staged + 8;
  const int rank = blockIdx.x & 1, u = (blockIdx.x >> 1) & 7, mp = blockIdx.x >> 4;
  const int m = 2 * mp + rank;
  const int m2 = 2 * mp + (u & 1), ns = (u & ~1) + rank;
  const uint32_t dpeer = mapa_u32(sb, rank ^ 1) - sb;
  unsigned* cntO = (unsigned*)(a.kvacc + KVACC);
  if (threadIdx.x == 0) {
    for (int i = 0; i < NS; i++) { mbar_init(full + 8 * i, 1); mbar_init(empty + 8 * i, 4); }
    for (int i = 0; i < 8; i++) mbar_init(full2 + 8 * i, 1);
    mbar_init(empty2, 2); mbar_init(empty2 + 8, 2);
    mbar_init(barW, 1); mbar_init(drained, 1); mbar_init(staged, 8); mbar_init(freeb, 2);
    asm volatile("fence.mbarrier_init.release.cluster;" ::: "memory");
  }
  __syncthreads();
  asm volatile("barrier.cluster.arrive.relaxed.aligned; barrier.cluster.wait.aligned;" ::: "memory");
  if (warp >= 8) {
    asm volatile("setmaxnreg.dec.sync.aligned.u32 40;");
    if (warp == 8) { if (elect_one()) {
      const unsigned char* wsrc = a.wb + (size_t)u * 327680 + rank * 16384;
      if (a.prep) wait_ge(a.prep, 64);
      fence_proxy_async_global();
      for (int kb = 0; kb < NS; kb++) {
        mbar_expect_tx(full + 8 * kb, STAGE);
        bulk_g2s_mc(sb + kb * STAGE + 16384 + rank * 16384, wsrc + kb * 32768, 16384, full + 8 * kb);
      }
      asm volatile("griddepcontrol.wait;" ::: "memory");
      TL_BEGIN0(tl);
      if (blockIdx.x == 0) *a.go = 0;
      for (int kb = 0; kb < NS; kb++) tma_load_2d(sb + kb * STAGE, &tmA, kb * 64, m * 128, full + 8 * kb);
      if (m == 0) prefetch_l2(a.kvacc + u * (KVACC / 8), KVACC / 8);
#pragma unroll 1
      for (int kb = NS; kb < 10; kb++) {
        const uint32_t s = kb & 3, st = sb + s * STAGE, fb = full + 8 * s;
        mbar_wait(empty + 8 * s, ((kb >> 2) - 1) & 1);
        mbar_expect_tx(fb, STAGE);
        tma_load_2d(st, &tmA, kb * 64, m * 128, fb);
        bulk_g2s_mc(st + 16384 + rank * 16384, wsrc + kb * 32768, 16384, fb);
      }
      for (int i = 0; i < 6; i++) mbar_expect_tx(full2 + 8 * i, PIECE);
      mbar_wait(drained, 0);
      mbar_expect_tx(barW, 102400);
      bulk_g2s(sb + OFF_WOT, a.wot + (size_t)ns * 102400, 102400, barW);
      mbar_wait(staged, 0);
      bulk_s2g(a.o2 + (size_t)(m * 8 + u) * PIECE, sb + OFF_OST, PIECE);
      bulk_commit();
      bulk_wait<0>();
      asm volatile("red.relaxed.gpu.global.add.u32 [%0], 1;" :: "l"(cntO + m) : "memory");
      mbar_arrive(freeb); mbar_arrive_remote_if(true, freeb + dpeer);
      wait_ge(cntO + m2, 8, 20);
      mbar_wait(freeb, 0);
      fence_proxy_async_global();
      const unsigned char* osrc = a.o2 + (size_t)m2 * 8 * PIECE;
      for (int i = 0; i < 6; i++) bulk_g2s_mc(sb + i * PIECE + rank * (PIECE / 2), osrc + i * PIECE + rank * (PIECE / 2), PIECE / 2, full2 + 8 * i);
      for (int i = 0; i < 2; i++) {
        mbar_wait(empty2 + 8 * i, 0);
        mbar_expect_tx(full2 + 8 * (6 + i), PIECE);
        bulk_g2s(sb + i * PIECE, osrc + (6 + i) * PIECE, PIECE, full2 + 8 * (6 + i));
      }
    } } else if (warp == 9 && a.pf0) { if (elect_one()) {
      if (a.pfwait) asm volatile("griddepcontrol.wait;" ::: "memory");
      constexpr uint32_t CH = 2048;
      for (int i = 0; i < a.pfn; i++) {
        prefetch_l2((const unsigned char*)a.pf0 + (i * 128 + blockIdx.x) * CH, CH); prefetch_l2((const unsigned char*)a.pf1 + (i * 128 + blockIdx.x) * CH, CH);
        __nanosleep(a.pfns);
      }
    } }
    return;
  }
  asm volatile("setmaxnreg.inc.sync.aligned.u32 232;");
  const int wg = warp >> 2, wi = warp & 3;
  const int q4 = lane & 3;
  const bool lead = (threadIdx.x & 127) == 0;
  float acc[128];
  {
#pragma unroll 1
    for (int kb = 0; kb < 10; kb++) {
      const uint32_t s = kb & 3, st = sb + s * STAGE;
      mbar_wait(full + 8 * s, (kb >> 2) & 1);
      wgmma_fence();
#pragma unroll
      for (int kk = 0; kk < 4; kk++) wgmma_n256<0, 1>(acc, desc_kmajor(st + wg * 8192 + kk * 32), make_desc(st + 16384 + kk * 8192, 4096, 128, 0), (kb | kk) != 0);
      wgmma_commit();
      if (kb > 0 && kb < 7) { wgmma_wait<1>(); const uint32_t e = empty + 8 * ((kb - 1) & 3); mbar_arrive_if(lead, e); mbar_arrive_remote_if(lead, e + dpeer); }
    }
    wgmma_wait<0>();
    bar_sync(1, 256);
    mbar_arrive_if(threadIdx.x == 0, drained);
  }
  TL2((tl >= 12 ? 128 : 0) + 32 + 0);
  const uint32_t srow = (wg * 64 + wi * 16 + (lane & 15)) * 16 + (lane >> 4) * 2048;
  auto features = [&](auto T0, auto HH, uint32_t (&w)[2][5]) {
    constexpr int t = T0.value + 5 * (HH.value >> 1), o = (HH.value & 1) ? 3 : 0, e = HH.value & 1;
    float x[2][5];
#pragma unroll
    for (int r = 0; r < 2; r++) {
      x[r][0] = acc[4 * (t + o) + 2 * r]; x[r][1] = acc[4 * (t + o) + 2 * r + 1]; x[r][2] = acc[4 * (t + o + 1) + 2 * r]; x[r][3] = acc[4 * (t + o + 1) + 2 * r + 1];
      bf16r2(x[r][0], x[r][1]); bf16r2(x[r][2], x[r][3]);
    }
    x[0][4] = acc[4 * (t + 2) + e]; x[1][4] = acc[4 * (t + 2) + 2 + e];
    bf16r2(x[0][4], x[1][4]);
    hedgehog_features(x, w);
  };
  static_for<0, 4>([&](auto HH) {
    constexpr int hh = HH.value, t = 20 + 3 * hh;
    const uint32_t one = q4 == ((hh & 1) ? 0 : 2) ? 0x3f80u : 0u;
    const uint32_t va = sb + OFF_V + hh * 6144 + srow;
    stsm_x4(va, pack_bf16(acc[4 * t], acc[4 * t + 1]), pack_bf16(acc[4 * t + 2], acc[4 * t + 3]), pack_bf16(acc[4 * t + 4], acc[4 * t + 5]), pack_bf16(acc[4 * t + 6], acc[4 * t + 7]));
    const bool pad = (q4 >= 2) != (hh & 1);
    stsm_x2(va + 4096, pad ? one : pack_bf16(acc[4 * t + 8], acc[4 * t + 9]), pad ? one : pack_bf16(acc[4 * t + 10], acc[4 * t + 11]));
    uint32_t w[2][5];
    features(IC<10>{}, HH, w);
    const uint32_t pa = sb + OFF_PHI + hh * 10240 + srow;
    stsm_x4(pa, w[0][0], w[1][0], w[0][1], w[1][1]);
    stsm_x4(pa + 4096, w[0][2], w[1][2], w[0][3], w[1][3]);
    stsm_x2(pa + 8192, w[0][4], w[1][4]);
  });
  fence_proxy_async();
  bar_sync(1, 256);
  TL2((tl >= 12 ? 128 : 0) + 32 + 1);
  {
    float d0[12], d1[12];
    const uint32_t pa = sb + OFF_PHI + wg * 20480, pv = sb + OFF_V + wg * 12288;
    wgmma_fence();
#pragma unroll
    for (int k = 0; k < 8; k++) {
      wgmma_n24<1, 1>(d0, make_desc(pa + k * 256, 128, 2048, 0), make_desc(pv + k * 256, 128, 2048, 0), k != 0);
      wgmma_n24<1, 1>(d1, make_desc(pa + 10240 + k * 256, 128, 2048, 0), make_desc(pv + 6144 + k * 256, 128, 2048, 0), k != 0);
    }
    wgmma_commit();
    wgmma_wait<0>();
    unsigned char* dst = a.kvacc + ((u * 4 + wg * 2) * 5 + 2 * wi) * 1024 + lane * 16;
    auto red4 = [&](bool on, unsigned char* p, float x, float y, float z) {
      asm volatile("{\n.reg .pred p;\nsetp.ne.u32 p, %4, 0;\n@p red.relaxed.gpu.global.add.v4.f32 [%0], {%1,%2,%3,%5};\n}" :: "l"(p), "f"(x), "f"(y), "f"(z), "r"((uint32_t)on), "f"(1.f) : "memory");
    };
    red4(wi < 3, dst, d0[0], d0[1], d0[4]); red4(wi < 3, dst + 512, d0[5], d0[8], d0[9]);
    red4(wi < 3, dst + 5120, d1[0], d1[1], d1[4]); red4(wi < 3, dst + 5632, d1[5], d1[8], d1[9]);
    red4(wi < 2, dst + 1024, d0[2], d0[3], d0[6]); red4(wi < 2, dst + 1536, d0[7], d0[10], d0[11]);
    red4(wi < 2, dst + 6144, d1[2], d1[3], d1[6]); red4(wi < 2, dst + 6656, d1[7], d1[10], d1[11]);
  }
  TL2((tl >= 12 ? 128 : 0) + 32 + 2);
  uint32_t qf[4][2][5];
  static_for<0, 4>([&](auto HH) { features(IC<0>{}, HH, qf[HH.value]); });
  uint4 xr[5];
#pragma unroll
  for (int i = 0; i < 5; i++) {
    const int c = lane + 32 * i;
    xr[i] = __ldcg((const uint4*)(a.xin + (size_t)(m2 * 128 + wg * 64 + wi * 16 + c / 10) * cfg::DM + ns * 80 + (c % 10) * 8));
  }
  {
    const unsigned char* src = a.kvacc + (u * 20 + warp) * 1024 + lane * 16;
    uint4 v[6];
    int spin = 0;
    while (true) {
      v[0] = ld_relaxed_v4_i<0>(src); v[1] = ld_relaxed_v4_i<512>(src); v[2] = ld_relaxed_v4_i<8192>(src); v[3] = ld_relaxed_v4_i<8704>(src);
      v[4] = ld_relaxed_v4_i<0>(src + (wg ? 0 : 16384)); v[5] = ld_relaxed_v4_i<512>(src + (wg ? 0 : 16384));
      const uint32_t c = (v[0].w & v[1].w & v[2].w) & (v[3].w & v[4].w & v[5].w);
      if (!__any_sync(0xffffffffu, (c & 0x41800000u) != 0x41800000u) || ++spin >= SPIN_LIMIT) break;
      __nanosleep(100);
    }
    const uint32_t kd = sb + OFF_KV + warp * 384 + lane * 4;
#pragma unroll
    for (int i = 0; i < 3; i++)
      if (i < 2 || wg == 0) {
        sts32(kd + i * 3072, pack_bf16(__uint_as_float(v[2 * i].x), __uint_as_float(v[2 * i].y)));
        sts32(kd + i * 3072 + 128, pack_bf16(__uint_as_float(v[2 * i].z), __uint_as_float(v[2 * i + 1].x)));
        sts32(kd + i * 3072 + 256, pack_bf16(__uint_as_float(v[2 * i + 1].y), __uint_as_float(v[2 * i + 1].z)));
      }
  }
  fence_proxy_async();
  bar_sync(1, 256);
  TL2((tl >= 12 ? 128 : 0) + 32 + 3);
  {
    float d[4][12];
    uint32_t zero = 0; PIN(zero);
#pragma unroll
    for (int hh = 0; hh < 4; hh++)
#pragma unroll
      for (int i = 0; i < 5; i++) { PIN(qf[hh][0][i]); PIN(qf[hh][1][i]); }
    wgmma_fence();
#pragma unroll
    for (int hh = 0; hh < 4; hh++) {
      const uint32_t kb = sb + OFF_KV + hh * 1920;
      wgmma_rs_n24<1>(d[hh], qf[hh][0][0], qf[hh][1][0], qf[hh][0][1], qf[hh][1][1], make_desc(kb, 384, 128, 0), 0);
      wgmma_rs_n24<1>(d[hh], qf[hh][0][2], qf[hh][1][2], qf[hh][0][3], qf[hh][1][3], make_desc(kb + 768, 384, 128, 0), 1);
      wgmma_rs_n24<1>(d[hh], qf[hh][0][4], qf[hh][1][4], zero, zero, make_desc(kb + 1536, 0, 128, 0), 1);
    }
    wgmma_commit();
    wgmma_wait<0>();
    uint32_t ow[4][6];
#pragma unroll
    for (int hh = 0; hh < 4; hh++) {
      const int zl = (lane & ~3) | ((hh & 1) ? 0 : 2);
      const float da = bf16r(bf16r(__shfl_sync(0xffffffffu, d[hh][8], zl)) + 1e-6f), db = bf16r(bf16r(__shfl_sync(0xffffffffu, d[hh][10], zl)) + 1e-6f);
#pragma unroll
      for (int n = 0; n < 3; n++) {
        bf16r2(d[hh][4 * n], d[hh][4 * n + 1]); bf16r2(d[hh][4 * n + 2], d[hh][4 * n + 3]);
        ow[hh][2 * n] = pack_bf16(__fdividef(d[hh][4 * n], da), __fdividef(d[hh][4 * n + 1], da));
        ow[hh][2 * n + 1] = pack_bf16(__fdividef(d[hh][4 * n + 2], db), __fdividef(d[hh][4 * n + 3], db));
      }
    }
#pragma unroll
    for (int p = 0; p < 2; p++) {
      const uint32_t oa = sb + OFF_OST + p * 10240 + srow;
      stsm_x4(oa, ow[2 * p][0], ow[2 * p][1], ow[2 * p][2], ow[2 * p][3]);
      stsm_x2(oa + 4096, q4 < 2 ? ow[2 * p][4] : ow[2 * p + 1][4], q4 < 2 ? ow[2 * p][5] : ow[2 * p + 1][5]);
      stsm_x4(oa + 6144, ow[2 * p + 1][0], ow[2 * p + 1][1], ow[2 * p + 1][2], ow[2 * p + 1][3]);
    }
    fence_proxy_async();
    __syncwarp();
    mbar_arrive_if(lane == 0, staged);
  }
  TL2((tl >= 12 ? 128 : 0) + 32 + 4);
  float c2[40];
  mbar_wait(barW, 0);
#pragma unroll 1
  for (int i = 0; i < 8; i++) {
    mbar_wait(full2 + 8 * i, 0);
    const uint32_t st = sb + (i < 6 ? i : i - 6) * PIECE + wg * 1024, wo = sb + OFF_WOT + i * 12800;
    wgmma_fence();
#pragma unroll
    for (int kk = 0; kk < 5; kk++) wgmma_n80<0, 1>(c2, make_desc(st + kk * 4096, 2048, 128, 0), make_desc(wo + kk * 2560, 1280, 128, 0), (i | kk) != 0);
    wgmma_commit();
    if (i == 1 || i == 2) { wgmma_wait<1>(); mbar_arrive_if(lead, empty2 + 8 * (i - 1)); }
  }
  wgmma_wait<0>();
  TL2((tl >= 12 ? 128 : 0) + 32 + 5);
  {
    bar_sync(1, 256);
    const uint32_t ost = sb + 2 * PIECE + warp * 3072;
#pragma unroll
    for (int v = 0; v < 10; v += 2)
      stsm_x4(ost + (lane & 15) * 176 + (v + (lane >> 4)) * 16, pack_bf16(c2[4 * v], c2[4 * v + 1]), pack_bf16(c2[4 * v + 2], c2[4 * v + 3]),
              pack_bf16(c2[4 * v + 4], c2[4 * v + 5]), pack_bf16(c2[4 * v + 6], c2[4 * v + 7]));
    __syncwarp();
#pragma unroll
    for (int i = 0; i < 5; i++) {
      const int c = lane + 32 * i, row = c / 10, chunk = c % 10;
      const uint4 y = lds128(ost + row * 176 + chunk * 16);
      const size_t off = (size_t)(m2 * 128 + wg * 64 + wi * 16 + row) * cfg::DM + ns * 80 + chunk * 8;
      const uint4 x = xr[i];
      *(uint4*)(a.xout + off) = make_uint4(pack_bf16(bf_lo(x.x) + bf_lo(y.x), bf_hi(x.x) + bf_hi(y.x)), pack_bf16(bf_lo(x.y) + bf_lo(y.y), bf_hi(x.y) + bf_hi(y.y)),
                                           pack_bf16(bf_lo(x.z) + bf_lo(y.z), bf_hi(x.z) + bf_hi(y.z)), pack_bf16(bf_lo(x.w) + bf_lo(y.w), bf_hi(x.w) + bf_hi(y.w)));
    }
  }
  TL_END(tl);
}
__device__ __align__(32768) unsigned char g_arena[AR_SIZE];
__device__ unsigned g_go[32];
__device__ __align__(1024) uint2 g_xh[2048 * 160];
__device__ __align__(1024) unsigned char g_k[64 * 96 * 5120], g_v[64 * 96 * 5120];
__device__ __align__(1024) bf16 g_o[2048 * 6144];
__device__ __align__(1024) uint4 g_qs[8 * 32 * 12 * 256];
__device__ __align__(1024) bf16 g_xn[2048 * 640], g_xn2[2048 * 640], g_xa[2048 * 640], g_xb[2048 * 640];
__device__ __align__(1024) bf16 g_part[24 * 2048 * 640];
__device__ __align__(1024) bf16 g_wb[2048 * 640], g_wot[640 * 640], g_pq[2048 * 640];
__device__ __align__(1024) float g_kvacc[bf::KVACC / 4 + 64];

typedef CUresult (*EncodeFn)(CUtensorMap*, CUtensorMapDataType, cuuint32_t, void*, const cuuint64_t*, const cuuint64_t*, const cuuint32_t*,
                             const cuuint32_t*, CUtensorMapInterleave, CUtensorMapSwizzle, CUtensorMapL2promotion, CUtensorMapFloatOOBfill);
static EncodeFn g_encode = nullptr;
static CUtensorMap make_map(const void* p, uint64_t cols, uint64_t rows, uint32_t bc, uint32_t br, bool swz = true) {
  CUtensorMap m;
  cuuint64_t dims[2] = {cols, rows}, strides[1] = {cols * 2};
  cuuint32_t box[2] = {bc, br}, es[2] = {1, 1};
  g_encode(&m, CU_TENSOR_MAP_DATA_TYPE_BFLOAT16, 2, const_cast<void*>(p), dims, strides, box, es, CU_TENSOR_MAP_INTERLEAVE_NONE,
           swz ? CU_TENSOR_MAP_SWIZZLE_128B : CU_TENSOR_MAP_SWIZZLE_NONE, CU_TENSOR_MAP_L2_PROMOTION_L2_256B, CU_TENSOR_MAP_FLOAT_OOB_FILL_NONE);
  return m;
}
static CUtensorMap make_map3(const void* p, uint64_t cols, uint64_t rows, uint32_t nb) {
  CUtensorMap m;
  cuuint64_t dims[3] = {64, rows, cols / 64}, strides[2] = {cols * 2, 128};
  cuuint32_t box[3] = {64, 64, nb}, es[3] = {1, 1, 1};
  g_encode(&m, CU_TENSOR_MAP_DATA_TYPE_BFLOAT16, 3, const_cast<void*>(p), dims, strides, box, es, CU_TENSOR_MAP_INTERLEAVE_NONE,
           CU_TENSOR_MAP_SWIZZLE_128B, CU_TENSOR_MAP_L2_PROMOTION_L2_256B, CU_TENSOR_MAP_FLOAT_OOB_FILL_NONE);
  return m;
}
template <class T> static T* sym(const T& s) { void* p = nullptr; cudaGetSymbolAddress(&p, s); return (T*)p; }

struct Ptrs {
  unsigned char *arena, *k, *v; bf16 *o, *xn, *xa, *xb, *wb, *wot, *pq; float *part, *kvacc; uint2* xh; uint4* qs; bf16* xn2; unsigned* go;
};

static tr::Sched make_sched(int layer, const char* str, const int* ks, const int* lr) {
  using namespace tr;
  Sched s = {};
  int n = 0;
  for (int b = 0; b < 16; b++) { s.ks[b] = (uint8_t)abs(ks[b]); s.wide[b] = ks[b] > 0; s.lrows[b] = (uint8_t)lr[b]; }
  for (const char* p = str; *p;) {
    if (*p == ' ') { p++; continue; }
    const char c = *p++;
    char* e;
    const int b = (int)strtol(p, &e, 10); p = e;
    int first = 0, cnt = c == 'o' ? s.ks[b] * (s.wide[b] ? 2 : 5) : (c == 'l' ? 16 / lr[b] : 32);
    if (*p == '.') { first = (int)strtol(p + 1, &e, 10); cnt = (int)strtol(e + 1, &e, 10); p = e; }
    const int type = c == 'a' ? T_QA : (c == 'q' ? T_Q : (c == 't' ? T_A : (c == 'l' ? T_L : (c == 'p' ? T_P : (s.wide[b] ? T_OB : T_OS)))));
    if (type == T_P && layer > 0) continue;
    for (int i = 0; i < cnt && n < MAXITEMS - 1; i++) s.item[n++] = (uint16_t)((type << 11) | (b << 7) | (first + i));
  }
  s.n = n; s.item[n] = T_END << 11;
  return s;
}
static tr::Sched sched_of(int layer) {
  const char* str = "q13 q14 a0 q15 a1 o0 p0.0.16 a2 o1 p0.16.16 a3 o2 a4 o3 a5 o4 l0 a6 o5 l1 a7 o6 l2 a8 o7 l3 a9 o8 l4 a10 o9 l5 a11 o10 l6 a12 o11 l7 t13 o12 t14 t15 o13 o14 l8 l9 l10 l11 o15 l12 l13 l14 l15";
  int ks[16] = {2, 2, 2, 2, 2, 2, 2, 2, 2, 2, 3, 4, 6, -8, -8, -12}, lr[16] = {4, 4, 4, 4, 4, 4, 4, 4, 2, 1, 1, 1, 1, 1, 1, 1};
#ifdef TUNE
  if (getenv("SCHED")) str = getenv("SCHED");
  if (layer == 0 && getenv("SCHED0")) str = getenv("SCHED0");
  if (const char* p = getenv("KS")) for (int b = 0; b < 16; b++) { char* e; ks[b] = (int)strtol(p, &e, 10); p = e; }
  if (const char* p = getenv("LR")) for (int b = 0; b < 16; b++) { char* e; lr[b] = (int)strtol(p, &e, 10); p = e; }
#endif
  return make_sched(layer, str, ks, lr);
}
#ifndef TRAIL_GRID
#define TRAIL_GRID 132
#endif
#ifndef PDL_LN
#define PDL_LN 0
#endif
#ifndef PDL_CH
#define PDL_CH 1
#endif
#ifndef PDL_B
#define PDL_B 1
#endif
#ifndef PFW
#define PFW 100
#endif
#ifndef PF_A
#define PF_A 1
#endif
#ifndef PF_B
#define PF_B 1
#endif
extern "C" void kernel_launch(void* const* d_in, const int* in_sizes, int n_in, void* d_out, int out_size) {
  const bf16* x = (const bf16*)d_in[0];
  const bf16* mem0 = (const bf16*)d_in[1];
  const bf16 *Wq = (const bf16*)d_in[2], *Wk = (const bf16*)d_in[3], *Wv = (const bf16*)d_in[4], *Wo = (const bf16*)d_in[5];
  const bf16 *wqkv = (const bf16*)d_in[8], *wphi = (const bf16*)d_in[9], *wo = (const bf16*)d_in[10];
  bf16* out = (bf16*)d_out;
  static Ptrs P; static bool init = false;
  if (!init) {
    void* fn = nullptr; cudaDriverEntryPointQueryResult qr;
    cudaGetDriverEntryPoint("cuTensorMapEncodeTiled", &fn, cudaEnableDefault, &qr);
    g_encode = (EncodeFn)fn;
    void* p;
    cudaGetSymbolAddress(&p, g_arena); P.arena = (unsigned char*)p;
    cudaGetSymbolAddress(&p, g_k); P.k = (unsigned char*)p;   cudaGetSymbolAddress(&p, g_v); P.v = (unsigned char*)p;
    cudaGetSymbolAddress(&p, g_o); P.o = (bf16*)p;
    cudaGetSymbolAddress(&p, g_xn); P.xn = (bf16*)p;
    cudaGetSymbolAddress(&p, g_xa); P.xa = (bf16*)p;   cudaGetSymbolAddress(&p, g_xb); P.xb = (bf16*)p;
    cudaGetSymbolAddress(&p, g_wb); P.wb = (bf16*)p;   cudaGetSymbolAddress(&p, g_wot); P.wot = (bf16*)p;
    cudaGetSymbolAddress(&p, g_pq); P.pq = (bf16*)p;   cudaGetSymbolAddress(&p, g_part); P.part = (float*)p;
    cudaGetSymbolAddress(&p, g_kvacc); P.kvacc = (float*)p;
    cudaGetSymbolAddress(&p, g_xh); P.xh = (uint2*)p;
    cudaGetSymbolAddress(&p, g_go); P.go = (unsigned*)p;
    cudaGetSymbolAddress(&p, g_qs); P.qs = (uint4*)p;
    cudaGetSymbolAddress(&p, g_xn2); P.xn2 = (bf16*)p;
    cudaFuncSetAttribute(chain_kernel, cudaFuncAttributeMaxDynamicSharedMemorySize, ch::SMEM);
    cudaFuncSetAttribute(trail_kernel, cudaFuncAttributeMaxDynamicSharedMemorySize, tr::SMEM);
    cudaFuncSetAttribute(blayer_kernel, cudaFuncAttributeMaxDynamicSharedMemorySize, bf::SMEM);
    init = true;
  }
  const CUtensorMap tmXn = make_map(P.xn, 640, 2048, 64, 128), tmXn2 = make_map(P.xn2, 640, 2048, 64, 128);
  const CUtensorMap tmWq = make_map3(Wq, 6144, 640, 3);
  const CUtensorMap tmCq = make_map(Wq, 6144, 640, 64, 160), tmCk = make_map(Wk, 6144, 640, 64, 160), tmCv = make_map(Wv, 6144, 640, 64, 160), tmCo = make_map(Wo, 640, 6144, 224, 64, false);
  const CUtensorMap tmWo5 = make_map3(Wo, 640, 6144, 5), tmWo2 = make_map3(Wo, 640, 6144, 2);

  CUtensorMap tmP;
  {
    cuuint64_t dims[3] = {256, 8, 24 * 320}, strides[2] = {1024, 8192};
    cuuint32_t box[3] = {256, 1, 10}, es[3] = {1, 1, 1};
    g_encode(&tmP, CU_TENSOR_MAP_DATA_TYPE_UINT32, 3, P.part, dims, strides, box, es, CU_TENSOR_MAP_INTERLEAVE_NONE, CU_TENSOR_MAP_SWIZZLE_NONE,
             CU_TENSOR_MAP_L2_PROMOTION_NONE, CU_TENSOR_MAP_FLOAT_OOB_FILL_NONE);
  }
  ChainArgs ca;
  ca.xh = P.xh; ca.mem0 = mem0; ca.kg = P.k; ca.vg = P.v;
  ca.arena = P.arena; ca.dbg = nullptr; ca.go = P.go; ca.delay = POLL_DELAY; ca.margin = 150;
#ifdef TUNE
  if (getenv("MG")) ca.margin = atoi(getenv("MG"));
  if (getenv("PD")) ca.delay = atoi(getenv("PD"));
#endif
  ca.tl = 0;
  uint4* zar = (uint4*)P.arena; const int nzar = AR_SIZE / 16;
  uint4* zkv = (uint4*)P.kvacc; const int nzkv = (bf::KVACC / 4 + 64) / 4;

  const PrepArgs pa{wqkv, wphi, wo, (unsigned char*)P.wb, (unsigned char*)P.wot};
  const bf16* xcur = x;
  cudaLaunchAttribute at[1];
  at[0].id = cudaLaunchAttributeProgrammaticStreamSerialization; at[0].val.programmaticStreamSerializationAllowed = 1;
  auto cfgof = [&](int grid, int block, int smem, bool pdl) {
    cudaLaunchConfig_t lc = {};
    lc.gridDim = dim3(grid); lc.blockDim = dim3(block); lc.dynamicSmemBytes = smem; lc.stream = cudaStreamPerThread;
    lc.attrs = at; lc.numAttrs = pdl ? 1 : 0;
    return lc;
  };
  for (int layer = 0; layer < 2; layer++) {
    const int tl = layer * 12;
    cudaLaunchConfig_t lc = cfgof(256, 256, 0, layer > 0 && PDL_LN);
    cudaLaunchKernelEx(&lc, ln_kernel, xcur, P.xn, P.xh, zar, nzar, zkv, nzkv, Wk, Wv, layer == 0 ? PF_A : 0, tl + 0);
    ca.tl = tl + 2; ca.pfw = layer == 0 ? PFW : 100;
#ifdef TUNE
    if (getenv("PFW") && layer == 0) ca.pfw = atoi(getenv("PFW"));
#endif
    lc = cfgof(96, 384, ch::SMEM, PDL_CH);
    cudaLaunchKernelEx(&lc, chain_kernel, ca, tmCq, tmCk, tmCv, tmCo);
    lc = cfgof(TRAIL_GRID, 384, tr::SMEM, true);
    tr::Args ta{P.k, P.v, (unsigned char*)P.o, P.qs, (unsigned char*)P.part, xcur, P.xn, P.xa, P.xn2, P.arena, P.go, tl + 4, 500, 100};
#ifdef TUNE
    if (getenv("NAP")) ta.nap = atoi(getenv("NAP"));
    if (getenv("NAP2")) ta.nap2 = atoi(getenv("NAP2"));
#endif
    cudaLaunchKernelEx(&lc, trail_kernel, tmXn, tmWq, tmWo5, tmWo2, tmP, sched_of(layer), ta, pa);
    lc = cfgof(128, 384, bf::SMEM, PDL_B);
    bf::Args ba{(const unsigned char*)P.wb, (const unsigned char*)P.wot, (unsigned char*)P.kvacc, (unsigned char*)P.pq, P.xa, layer == 0 ? P.xb : out, P.go, layer == 0 ? P.arena + tr::C_P : nullptr,
                      layer == 0 && PF_B ? Wk : nullptr, Wv, 30, 500, 0, tl + 7};
#ifdef TUNE
    if (getenv("PFN")) ba.pfn = atoi(getenv("PFN"));
    if (getenv("PFNS")) ba.pfns = atoi(getenv("PFNS"));
    if (getenv("PFWT")) ba.pfwait = atoi(getenv("PFWT"));
    if (getenv("PFB")) ba.pf0 = layer == 0 && atoi(getenv("PFB")) ? Wk : nullptr;
#endif
    cudaLaunchKernelEx(&lc, blayer_kernel, tmXn2, ba);
    xcur = P.xb;
  }
}
```

```cpp
#include <cuda_runtime.h>
#include <cuda.h>
#include <cuda_bf16.h>
#include <stdint.h>
#include <stdlib.h>
#include <type_traits>

typedef __nv_bfloat16 bf16;

namespace cfg {
constexpr int S = 2048, DM = 640, H = 32, DH = 192, NSEG = 64, SEG = 32, NM = 8;
constexpr int HD = H * DH;
}

__device__ __forceinline__ uint32_t smem_u32(const void* p) { return (uint32_t)__cvta_generic_to_shared(p); }
__device__ __forceinline__ uint32_t mapa_u32(uint32_t a, uint32_t r) {
  uint32_t o; asm("mapa.shared::cluster.u32 %0, %1, %2;" : "=r"(o) : "r"(a), "r"(r)); return o;
}
__device__ __forceinline__ void mbar_init(uint32_t b, uint32_t c) {
  asm volatile("mbarrier.init.shared::cta.b64 [%0], %1;" :: "r"(b), "r"(c) : "memory");
}
__device__ __forceinline__ void mbar_expect_tx(uint32_t b, uint32_t bytes) {
  asm volatile("mbarrier.arrive.expect_tx.shared::cta.b64 _, [%0], %1;" :: "r"(b), "r"(bytes) : "memory");
}
__device__ __forceinline__ void mbar_arrive(uint32_t b) {
  asm volatile("mbarrier.arrive.shared::cta.b64 _, [%0];" :: "r"(b) : "memory");
}
__device__ __forceinline__ void mbar_expect_tx_if(bool c, uint32_t b, uint32_t bytes) {
  asm volatile("{\n.reg .pred p;\nsetp.ne.u32 p, %2, 0;\n@p mbarrier.arrive.expect_tx.shared::cta.b64 _, [%0], %1;\n}" :: "r"(b), "r"(bytes), "r"((uint32_t)c) : "memory");
}
__device__ __forceinline__ void mbar_arrive_if(bool c, uint32_t b) {
  asm volatile("{\n.reg .pred p;\nsetp.ne.u32 p, %1, 0;\n@p mbarrier.arrive.shared::cta.b64 _, [%0];\n}" :: "r"(b), "r"((uint32_t)c) : "memory");
}
__device__ __forceinline__ bool mbar_try(uint32_t b, uint32_t ph) {
  uint32_t p;
  asm volatile("{.reg .pred p; mbarrier.try_wait.parity.shared::cta.b64 p, [%1], %2; selp.u32 %0, 1, 0, p;}"
               : "=r"(p) : "r"(b), "r"(ph) : "memory");
  return p;
}
__device__ __forceinline__ bool mbar_try_cluster(uint32_t b, uint32_t ph) {
  uint32_t p;
  asm volatile("{.reg .pred p; mbarrier.try_wait.parity.acquire.cluster.shared::cta.b64 p, [%1], %2; selp.u32 %0, 1, 0, p;}"
               : "=r"(p) : "r"(b), "r"(ph) : "memory");
  return p;
}
#ifndef SPIN_LIMIT
#define SPIN_LIMIT (1 << 22)
#endif
__device__ __forceinline__ void mbar_wait(uint32_t b, uint32_t ph) {
  asm volatile("{\n.reg .pred p, q;\n.reg .u32 c;\nmov.u32 c, 0;\n"
               "W_%=:\nmbarrier.try_wait.parity.shared::cta.b64 p, [%0], %1;\n@p bra.uni D_%=;\n"
               "add.u32 c, c, 1;\nsetp.lt.u32 q, c, %2;\n@q bra.uni W_%=;\nD_%=:\n}"
               :: "r"(b), "r"(ph), "n"(SPIN_LIMIT) : "memory");
}
__device__ __forceinline__ void mbar_spin(uint32_t b, uint32_t ph) {
  asm volatile("{\n.reg .pred p, q;\n.reg .u32 c;\nmov.u32 c, 0;\n"
               "W_%=:\nmbarrier.test_wait.parity.shared::cta.b64 p, [%0], %1;\n@p bra D_%=;\n"
               "add.u32 c, c, 1;\nsetp.lt.u32 q, c, %2;\n@q bra W_%=;\nD_%=:\n}"
               :: "r"(b), "r"(ph), "n"(SPIN_LIMIT) : "memory");
}
#define PIN(x) asm volatile("" : "+r"(x))
__device__ __forceinline__ void mbar_wait_cluster(uint32_t b, uint32_t ph) {
  int s = 0;
  while (!mbar_try_cluster(b, ph)) { if (++s > SPIN_LIMIT) break; }
}
__device__ __forceinline__ void st_async_v2(uint32_t a, uint32_t x, uint32_t y, uint32_t mb) {
  asm volatile("st.async.weak.shared::cluster.mbarrier::complete_tx::bytes.v2.b32 [%0], {%1,%2}, [%3];"
               :: "r"(a), "r"(x), "r"(y), "r"(mb) : "memory");
}
__device__ __forceinline__ void st_async_v4(uint32_t a, uint32_t x, uint32_t y, uint32_t z, uint32_t w, uint32_t mb) {
  asm volatile("st.async.weak.shared::cluster.mbarrier::complete_tx::bytes.v4.b32 [%0], {%1,%2,%3,%4}, [%5];"
               :: "r"(a), "r"(x), "r"(y), "r"(z), "r"(w), "r"(mb) : "memory");
}
__device__ __forceinline__ void bulk_g2s(uint32_t dst, const void* src, uint32_t bytes, uint32_t mb) {
  asm volatile("cp.async.bulk.shared::cluster.global.mbarrier::complete_tx::bytes [%0], [%1], %2, [%3];"
               :: "r"(dst), "l"(src), "r"(bytes), "r"(mb) : "memory");
}
__device__ __forceinline__ void cp_async16(uint32_t dst, const void* src) {
  asm volatile("cp.async.cg.shared.global [%0], [%1], 16;" :: "r"(dst), "l"(src) : "memory");
}
__device__ __forceinline__ void cp_async_wait_all() { asm volatile("cp.async.wait_all;" ::: "memory"); }
__device__ __forceinline__ void fence_proxy_async() { asm volatile("fence.proxy.async.shared::cta;" ::: "memory"); }
__device__ __forceinline__ void bar_sync(int id, int n) { asm volatile("bar.sync %0, %1;" :: "r"(id), "r"(n) : "memory"); }
__device__ __forceinline__ void bar_arrive(int id, int n) { asm volatile("bar.arrive %0, %1;" :: "r"(id), "r"(n) : "memory"); }
__device__ __forceinline__ void cluster_sync_all() {
  asm volatile("barrier.cluster.arrive.release.aligned; barrier.cluster.wait.acquire.aligned;" ::: "memory");
}
__device__ __forceinline__ void ldsm_x4(uint32_t (&r)[4], uint32_t a) {
  asm volatile("ldmatrix.sync.aligned.m8n8.x4.shared.b16 {%0,%1,%2,%3}, [%4];"
               : "=r"(r[0]), "=r"(r[1]), "=r"(r[2]), "=r"(r[3]) : "r"(a) : "memory");
}
__device__ __forceinline__ void ldsm_x4_t(uint32_t (&r)[4], uint32_t a) {
  asm volatile("ldmatrix.sync.aligned.m8n8.x4.trans.shared.b16 {%0,%1,%2,%3}, [%4];"
               : "=r"(r[0]), "=r"(r[1]), "=r"(r[2]), "=r"(r[3]) : "r"(a) : "memory");
}
template <int IMM> __device__ __forceinline__ void ldsm_x4_i(uint32_t (&r)[4], uint32_t a) {
  asm volatile("ldmatrix.sync.aligned.m8n8.x4.shared.b16 {%0,%1,%2,%3}, [%4+%5];"
               : "=r"(r[0]), "=r"(r[1]), "=r"(r[2]), "=r"(r[3]) : "r"(a), "n"(IMM) : "memory");
}
template <int IMM> __device__ __forceinline__ void ldsm_x4_t_i(uint32_t (&r)[4], uint32_t a) {
  asm volatile("ldmatrix.sync.aligned.m8n8.x4.trans.shared.b16 {%0,%1,%2,%3}, [%4+%5];"
               : "=r"(r[0]), "=r"(r[1]), "=r"(r[2]), "=r"(r[3]) : "r"(a), "n"(IMM) : "memory");
}
template <int IMM> __device__ __forceinline__ uint4 lds128_i(uint32_t a) {
  uint4 v; asm volatile("ld.shared.v4.u32 {%0,%1,%2,%3}, [%4+%5];" : "=r"(v.x), "=r"(v.y), "=r"(v.z), "=r"(v.w) : "r"(a), "n"(IMM) : "memory"); return v;
}
template <int IMM> __device__ __forceinline__ uint2 lds64_i(uint32_t a) {
  uint2 v; asm volatile("ld.shared.v2.u32 {%0,%1}, [%2+%3];" : "=r"(v.x), "=r"(v.y) : "r"(a), "n"(IMM) : "memory"); return v;
}
template <int IMM> __device__ __forceinline__ void sts128_i(uint32_t a, uint32_t x, uint32_t y, uint32_t z, uint32_t w) {
  asm volatile("st.shared.v4.u32 [%0+%5], {%1,%2,%3,%4};" :: "r"(a), "r"(x), "r"(y), "r"(z), "r"(w), "n"(IMM) : "memory");
}
template <int IMM> __device__ __forceinline__ void sts64_i(uint32_t a, uint32_t x, uint32_t y) {
  asm volatile("st.shared.v2.u32 [%0+%3], {%1,%2};" :: "r"(a), "r"(x), "r"(y), "n"(IMM) : "memory");
}
template <int IMM> __device__ __forceinline__ void st_async_v2_i(uint32_t a, uint32_t x, uint32_t y, uint32_t mb) {
  asm volatile("st.async.weak.shared::cluster.mbarrier::complete_tx::bytes.v2.b32 [%0+%4], {%1,%2}, [%3];"
               :: "r"(a), "r"(x), "r"(y), "r"(mb), "n"(IMM) : "memory");
}
template <int IMM> __device__ __forceinline__ uint4 ld_relaxed_v4_i(const void* p) {
  uint4 v; asm volatile("ld.relaxed.gpu.global.v4.u32 {%0,%1,%2,%3}, [%4+%5];" : "=r"(v.x), "=r"(v.y), "=r"(v.z), "=r"(v.w) : "l"(p), "n"(IMM) : "memory"); return v;
}
template <int I, int N, class F> __device__ __forceinline__ void static_for(F&& f) {
  if constexpr (I < N) { f(std::integral_constant<int, I>{}); static_for<I + 1, N>(f); }
}
__device__ __forceinline__ uint32_t movm_t(uint32_t a) {
  uint32_t d; asm volatile("movmatrix.sync.aligned.m8n8.trans.b16 %0, %1;" : "=r"(d) : "r"(a)); return d;
}
__device__ __forceinline__ void mma16816(float (&d)[4], uint32_t a0, uint32_t a1, uint32_t a2, uint32_t a3, uint32_t b0, uint32_t b1) {
  asm volatile("mma.sync.aligned.m16n8k16.row.col.f32.bf16.bf16.f32 {%0,%1,%2,%3}, {%4,%5,%6,%7}, {%8,%9}, {%0,%1,%2,%3};"
               : "+f"(d[0]), "+f"(d[1]), "+f"(d[2]), "+f"(d[3]) : "r"(a0), "r"(a1), "r"(a2), "r"(a3), "r"(b0), "r"(b1));
}
__device__ __forceinline__ uint32_t pack_bf16(float lo, float hi) {
  uint32_t d; asm("cvt.rn.bf16x2.f32 %0, %1, %2;" : "=r"(d) : "f"(hi), "f"(lo)); return d;
}
__device__ __forceinline__ float bf_lo(uint32_t w) { return __uint_as_float(w << 16); }
__device__ __forceinline__ float bf_hi(uint32_t w) { return __uint_as_float(w & 0xffff0000u); }
__device__ __forceinline__ uint4 lds128(uint32_t a) {
  uint4 v; asm volatile("ld.shared.v4.u32 {%0,%1,%2,%3}, [%4];" : "=r"(v.x), "=r"(v.y), "=r"(v.z), "=r"(v.w) : "r"(a) : "memory"); return v;
}
__device__ __forceinline__ uint2 lds64(uint32_t a) {
  uint2 v; asm volatile("ld.shared.v2.u32 {%0,%1}, [%2];" : "=r"(v.x), "=r"(v.y) : "r"(a) : "memory"); return v;
}
__device__ __forceinline__ void sts128(uint32_t a, uint32_t x, uint32_t y, uint32_t z, uint32_t w) {
  asm volatile("st.shared.v4.u32 [%0], {%1,%2,%3,%4};" :: "r"(a), "r"(x), "r"(y), "r"(z), "r"(w) : "memory");
}
__device__ __forceinline__ void sts64(uint32_t a, uint32_t x, uint32_t y) {
  asm volatile("st.shared.v2.u32 [%0], {%1,%2};" :: "r"(a), "r"(x), "r"(y) : "memory");
}
__device__ __forceinline__ uint4 ld_relaxed_v4(const void* p) {
  uint4 v; asm volatile("ld.relaxed.gpu.global.v4.u32 {%0,%1,%2,%3}, [%4];" : "=r"(v.x), "=r"(v.y), "=r"(v.z), "=r"(v.w) : "l"(p) : "memory"); return v;
}
__device__ __forceinline__ uint32_t ld_relaxed_u32(const void* p) {
  uint32_t v; asm volatile("ld.relaxed.gpu.global.u32 %0, [%1];" : "=r"(v) : "l"(p) : "memory"); return v;
}
__device__ __forceinline__ void st_relaxed_v2(void* p, uint32_t a, uint32_t b) {
  asm volatile("st.relaxed.gpu.global.v2.u32 [%0], {%1,%2};" :: "l"(p), "r"(a), "r"(b) : "memory");
}
__device__ __forceinline__ void st_relaxed_u32(void* p, uint32_t v) {
  asm volatile("st.relaxed.gpu.global.u32 [%0], %1;" :: "l"(p), "r"(v) : "memory");
}
__device__ __forceinline__ uint32_t clk32() { uint32_t c; asm volatile("mov.u32 %0, %%clock;" : "=r"(c) :: "memory"); return c; }
__device__ __forceinline__ uint32_t clkdep(uint32_t v) {
  uint32_t c; asm volatile("{.reg .pred p; setp.eq.u32 p, %1, 0xdeadbeef; @p trap; mov.u32 %0, %%clock;}" : "=r"(c) : "r"(v) : "memory"); return c;
}
__device__ __forceinline__ void wgmma_fence() { asm volatile("wgmma.fence.sync.aligned;" ::: "memory"); }
__device__ __forceinline__ void wgmma_commit() { asm volatile("wgmma.commit_group.sync.aligned;" ::: "memory"); }
template <int N> __device__ __forceinline__ void wgmma_wait() { asm volatile("wgmma.wait_group.sync.aligned %0;" :: "n"(N) : "memory"); }
__device__ __forceinline__ void wgmma_n8_ss_ta(float (&d)[4], uint64_t da, uint64_t db, int acc) {
  asm volatile("{\n.reg .pred p;\nsetp.ne.b32 p, %6, 0;\n"
               "wgmma.mma_async.sync.aligned.m64n8k16.f32.bf16.bf16 {%0,%1,%2,%3}, %4, %5, p, 1, 1, 1, 0;\n}\n"
               : "+f"(d[0]), "+f"(d[1]), "+f"(d[2]), "+f"(d[3]) : "l"(da), "l"(db), "r"(acc));
}
__device__ __forceinline__ uint64_t make_desc(uint32_t saddr, uint32_t lbo_bytes, uint32_t sbo_bytes, uint32_t swz) {
  return (uint64_t)((saddr & 0x3FFFF) >> 4) | ((uint64_t)(lbo_bytes >> 4) << 16) | ((uint64_t)(sbo_bytes >> 4) << 32) | ((uint64_t)swz << 62);
}


__device__ __forceinline__ bool elect_one() {
  uint32_t p; asm volatile("{\n.reg .pred p;\nelect.sync _|p, 0xffffffff;\nselp.u32 %0, 1, 0, p;\n}" : "=r"(p)); return p;
}
__device__ __forceinline__ void tma_load_3d(uint32_t dst, const CUtensorMap* tm, int c0, int c1, int c2, uint32_t mb) {
  asm volatile("cp.async.bulk.tensor.3d.shared::cluster.global.mbarrier::complete_tx::bytes [%0], [%1, {%3, %4, %5}], [%2];"
               :: "r"(dst), "l"(tm), "r"(mb), "r"(c0), "r"(c1), "r"(c2) : "memory");
}
__device__ __forceinline__ void tma_load_2d(uint32_t dst, const CUtensorMap* tm, int c0, int c1, uint32_t mb) {
  asm volatile("cp.async.bulk.tensor.2d.shared::cluster.global.mbarrier::complete_tx::bytes [%0], [%1, {%3, %4}], [%2];"
               :: "r"(dst), "l"(tm), "r"(mb), "r"(c0), "r"(c1) : "memory");
}
__device__ __forceinline__ void bulk_s2g(void* dst, uint32_t src, uint32_t bytes) {
  asm volatile("cp.async.bulk.global.shared::cta.bulk_group [%0], [%1], %2;" :: "l"(dst), "r"(src), "r"(bytes) : "memory");
}
__device__ __forceinline__ uint64_t policy_evict_first() {
  uint64_t p; asm volatile("createpolicy.fractional.L2::evict_first.b64 %0, 1.0;" : "=l"(p)); return p;
}
__device__ __forceinline__ void bulk_s2g_hint(void* dst, uint32_t src, uint32_t bytes, uint64_t pol) {
  asm volatile("cp.async.bulk.global.shared::cta.bulk_group.L2::cache_hint [%0], [%1], %2, %3;" :: "l"(dst), "r"(src), "r"(bytes), "l"(pol) : "memory");
}
__device__ __forceinline__ void bulk_commit() { asm volatile("cp.async.bulk.commit_group;" ::: "memory"); }
template <int N> __device__ __forceinline__ void bulk_wait_read() { asm volatile("cp.async.bulk.wait_group.read %0;" :: "n"(N) : "memory"); }
template <int N> __device__ __forceinline__ void bulk_wait() { asm volatile("cp.async.bulk.wait_group %0;" :: "n"(N) : "memory"); }
__device__ __forceinline__ void stsm_x4(uint32_t a, uint32_t r0, uint32_t r1, uint32_t r2, uint32_t r3) {
  asm volatile("stmatrix.sync.aligned.m8n8.x4.shared.b16 [%0], {%1,%2,%3,%4};" :: "r"(a), "r"(r0), "r"(r1), "r"(r2), "r"(r3) : "memory");
}
__device__ __forceinline__ void stsm_x2(uint32_t a, uint32_t r0, uint32_t r1) {
  asm volatile("stmatrix.sync.aligned.m8n8.x2.shared.b16 [%0], {%1,%2};" :: "r"(a), "r"(r0), "r"(r1) : "memory");
}
__device__ __forceinline__ void ldsm_x2(uint32_t (&r)[2], uint32_t a) {
  asm volatile("ldmatrix.sync.aligned.m8n8.x2.shared.b16 {%0,%1}, [%2];" : "=r"(r[0]), "=r"(r[1]) : "r"(a) : "memory");
}
__device__ __forceinline__ void ldsm_x2_t(uint32_t (&r)[2], uint32_t a) {
  asm volatile("ldmatrix.sync.aligned.m8n8.x2.trans.shared.b16 {%0,%1}, [%2];" : "=r"(r[0]), "=r"(r[1]) : "r"(a) : "memory");
}
__device__ __forceinline__ float bf16r(float x) { return __uint_as_float(pack_bf16(0.f, x) & 0xffff0000u); }
__device__ __forceinline__ void bf16r2(float& a, float& b) { const uint32_t w = pack_bf16(a, b); a = bf_lo(w); b = bf_hi(w); }
__device__ __forceinline__ float rcpf(float x) { float r; asm("rcp.approx.ftz.f32 %0, %1;" : "=f"(r) : "f"(x)); return r; }
__device__ __forceinline__ float ex2f(float x) { float e; asm("ex2.approx.ftz.f32 %0, %1;" : "=f"(e) : "f"(x)); return e; }
__device__ __forceinline__ void prefetch_tmap(const CUtensorMap* tm) { asm volatile("prefetch.tensormap [%0];" :: "l"(tm) : "memory"); }

#ifdef TIMELINE
__device__ unsigned long long g_tl[2 * 64];
__device__ unsigned long long g_log[2 * 132 * 64 * 2 + 2];
__device__ unsigned long long g_tl2[4 * 64];
__device__ __forceinline__ unsigned long long gtime() { unsigned long long t; asm volatile("mov.u64 %0, %%globaltimer;" : "=l"(t)); return t; }
#define TL_BEGIN(id) do { if (threadIdx.x == 0) atomicMin(&g_tl[2 * (id)], gtime()); } while (0)
#define TL_END(id) do { if ((threadIdx.x & 31) == 0) atomicMax(&g_tl[2 * (id) + 1], gtime()); } while (0)
#define TL_ACC(idx, t0) do { if (threadIdx.x == 0 && m >= 4 && m < 11) { atomicAdd(&g_tl2[idx], gtime() - (t0)); atomicAdd(&g_tl2[(idx) + 1], 1ull); } } while (0)
#define TL_NOW() gtime()
#define TL2(idx) asm volatile("{\n.reg .pred p;\nsetp.eq.u32 p, %2, 0;\n@p red.relaxed.gpu.global.max.u64 [%0], %1;\n}" :: "l"(&g_tl2[idx]), "l"(gtime()), "r"(threadIdx.x) : "memory")
#define TLW(idx) asm volatile("{\n.reg .pred p;\nsetp.eq.u32 p, %2, 0;\n@p red.relaxed.gpu.global.max.u64 [%0], %1;\n@p red.relaxed.gpu.global.add.u64 [%0+128], %1;\n}" :: "l"(&g_tl2[idx]), "l"(gtime() - g_tl0), "r"(threadIdx.x & 31) : "memory")
#define TL_BEGIN0(id) atomicMin(&g_tl[2 * (id)], gtime())
#else
#define TL_ACC(idx, t0)
#define TL_NOW() 0ull
#define TL2(idx)
#define TL_BEGIN0(id)
#define TLW(idx)
#define TL_BEGIN(id)
#define TL_END(id)
#endif
template <int TA, int TB> __device__ __forceinline__ void wgmma_n24(float (&d)[12], uint64_t da, uint64_t db, int acc) {
  asm volatile("{\n.reg .pred p;\nsetp.ne.b32 p, %14, 0;\n"
    "wgmma.mma_async.sync.aligned.m64n24k16.f32.bf16.bf16 {%0, %1, %2, %3, %4, %5, %6, %7, %8, %9, %10, %11}, %12, %13, p, 1, 1, %15, %16;\n}\n"
    : "+f"(d[0]), "+f"(d[1]), "+f"(d[2]), "+f"(d[3]), "+f"(d[4]), "+f"(d[5]), "+f"(d[6]), "+f"(d[7]), "+f"(d[8]), "+f"(d[9]), "+f"(d[10]), "+f"(d[11])
    : "l"(da), "l"(db), "r"(acc), "n"(TA), "n"(TB));
}

template <int TA, int TB> __device__ __forceinline__ void wgmma_n80(float (&d)[40], uint64_t da, uint64_t db, int acc) {
  asm volatile("{\n.reg .pred p;\nsetp.ne.b32 p, %42, 0;\n"
    "wgmma.mma_async.sync.aligned.m64n80k16.f32.bf16.bf16 {%0, %1, %2, %3, %4, %5, %6, %7, %8, %9, %10, %11, %12, %13, %14, %15, %16, %17, %18, %19, %20, %21, %22, %23, %24, %25, %26, %27, %28, %29, %30, %31, %32, %33, %34, %35, %36, %37, %38, %39}, %40, %41, p, 1, 1, %43, %44;\n}\n"
    : "+f"(d[0]), "+f"(d[1]), "+f"(d[2]), "+f"(d[3]), "+f"(d[4]), "+f"(d[5]), "+f"(d[6]), "+f"(d[7]), "+f"(d[8]), "+f"(d[9]), "+f"(d[10]), "+f"(d[11]), "+f"(d[12]), "+f"(d[13]), "+f"(d[14]), "+f"(d[15]), "+f"(d[16]), "+f"(d[17]), "+f"(d[18]), "+f"(d[19]), "+f"(d[20]), "+f"(d[21]), "+f"(d[22]), "+f"(d[23]), "+f"(d[24]), "+f"(d[25]), "+f"(d[26]), "+f"(d[27]), "+f"(d[28]), "+f"(d[29]), "+f"(d[30]), "+f"(d[31]), "+f"(d[32]), "+f"(d[33]), "+f"(d[34]), "+f"(d[35]), "+f"(d[36]), "+f"(d[37]), "+f"(d[38]), "+f"(d[39])
    : "l"(da), "l"(db), "r"(acc), "n"(TA), "n"(TB));
}

template <int TA, int TB> __device__ __forceinline__ void wgmma_n128(float (&d)[64], uint64_t da, uint64_t db, int acc) {
  asm volatile("{\n.reg .pred p;\nsetp.ne.b32 p, %66, 0;\n"
    "wgmma.mma_async.sync.aligned.m64n128k16.f32.bf16.bf16 {%0, %1, %2, %3, %4, %5, %6, %7, %8, %9, %10, %11, %12, %13, %14, %15, %16, %17, %18, %19, %20, %21, %22, %23, %24, %25, %26, %27, %28, %29, %30, %31, %32, %33, %34, %35, %36, %37, %38, %39, %40, %41, %42, %43, %44, %45, %46, %47, %48, %49, %50, %51, %52, %53, %54, %55, %56, %57, %58, %59, %60, %61, %62, %63}, %64, %65, p, 1, 1, %67, %68;\n}\n"
    : "+f"(d[0]), "+f"(d[1]), "+f"(d[2]), "+f"(d[3]), "+f"(d[4]), "+f"(d[5]), "+f"(d[6]), "+f"(d[7]), "+f"(d[8]), "+f"(d[9]), "+f"(d[10]), "+f"(d[11]), "+f"(d[12]), "+f"(d[13]), "+f"(d[14]), "+f"(d[15]), "+f"(d[16]), "+f"(d[17]), "+f"(d[18]), "+f"(d[19]), "+f"(d[20]), "+f"(d[21]), "+f"(d[22]), "+f"(d[23]), "+f"(d[24]), "+f"(d[25]), "+f"(d[26]), "+f"(d[27]), "+f"(d[28]), "+f"(d[29]), "+f"(d[30]), "+f"(d[31]), "+f"(d[32]), "+f"(d[33]), "+f"(d[34]), "+f"(d[35]), "+f"(d[36]), "+f"(d[37]), "+f"(d[38]), "+f"(d[39]), "+f"(d[40]), "+f"(d[41]), "+f"(d[42]), "+f"(d[43]), "+f"(d[44]), "+f"(d[45]), "+f"(d[46]), "+f"(d[47]), "+f"(d[48]), "+f"(d[49]), "+f"(d[50]), "+f"(d[51]), "+f"(d[52]), "+f"(d[53]), "+f"(d[54]), "+f"(d[55]), "+f"(d[56]), "+f"(d[57]), "+f"(d[58]), "+f"(d[59]), "+f"(d[60]), "+f"(d[61]), "+f"(d[62]), "+f"(d[63])
    : "l"(da), "l"(db), "r"(acc), "n"(TA), "n"(TB));
}

template <int TA, int TB> __device__ __forceinline__ void wgmma_n192(float (&d)[96], uint64_t da, uint64_t db, int acc) {
  asm volatile("{\n.reg .pred p;\nsetp.ne.b32 p, %98, 0;\n"
    "wgmma.mma_async.sync.aligned.m64n192k16.f32.bf16.bf16 {%0, %1, %2, %3, %4, %5, %6, %7, %8, %9, %10, %11, %12, %13, %14, %15, %16, %17, %18, %19, %20, %21, %22, %23, %24, %25, %26, %27, %28, %29, %30, %31, %32, %33, %34, %35, %36, %37, %38, %39, %40, %41, %42, %43, %44, %45, %46, %47, %48, %49, %50, %51, %52, %53, %54, %55, %56, %57, %58, %59, %60, %61, %62, %63, %64, %65, %66, %67, %68, %69, %70, %71, %72, %73, %74, %75, %76, %77, %78, %79, %80, %81, %82, %83, %84, %85, %86, %87, %88, %89, %90, %91, %92, %93, %94, %95}, %96, %97, p, 1, 1, %99, %100;\n}\n"
    : "+f"(d[0]), "+f"(d[1]), "+f"(d[2]), "+f"(d[3]), "+f"(d[4]), "+f"(d[5]), "+f"(d[6]), "+f"(d[7]), "+f"(d[8]), "+f"(d[9]), "+f"(d[10]), "+f"(d[11]), "+f"(d[12]), "+f"(d[13]), "+f"(d[14]), "+f"(d[15]), "+f"(d[16]), "+f"(d[17]), "+f"(d[18]), "+f"(d[19]), "+f"(d[20]), "+f"(d[21]), "+f"(d[22]), "+f"(d[23]), "+f"(d[24]), "+f"(d[25]), "+f"(d[26]), "+f"(d[27]), "+f"(d[28]), "+f"(d[29]), "+f"(d[30]), "+f"(d[31]), "+f"(d[32]), "+f"(d[33]), "+f"(d[34]), "+f"(d[35]), "+f"(d[36]), "+f"(d[37]), "+f"(d[38]), "+f"(d[39]), "+f"(d[40]), "+f"(d[41]), "+f"(d[42]), "+f"(d[43]), "+f"(d[44]), "+f"(d[45]), "+f"(d[46]), "+f"(d[47]), "+f"(d[48]), "+f"(d[49]), "+f"(d[50]), "+f"(d[51]), "+f"(d[52]), "+f"(d[53]), "+f"(d[54]), "+f"(d[55]), "+f"(d[56]), "+f"(d[57]), "+f"(d[58]), "+f"(d[59]), "+f"(d[60]), "+f"(d[61]), "+f"(d[62]), "+f"(d[63]), "+f"(d[64]), "+f"(d[65]), "+f"(d[66]), "+f"(d[67]), "+f"(d[68]), "+f"(d[69]), "+f"(d[70]), "+f"(d[71]), "+f"(d[72]), "+f"(d[73]), "+f"(d[74]), "+f"(d[75]), "+f"(d[76]), "+f"(d[77]), "+f"(d[78]), "+f"(d[79]), "+f"(d[80]), "+f"(d[81]), "+f"(d[82]), "+f"(d[83]), "+f"(d[84]), "+f"(d[85]), "+f"(d[86]), "+f"(d[87]), "+f"(d[88]), "+f"(d[89]), "+f"(d[90]), "+f"(d[91]), "+f"(d[92]), "+f"(d[93]), "+f"(d[94]), "+f"(d[95])
    : "l"(da), "l"(db), "r"(acc), "n"(TA), "n"(TB));
}

template <int TA, int TB> __device__ __forceinline__ void wgmma_n256(float (&d)[128], uint64_t da, uint64_t db, int acc) {
  asm volatile("{\n.reg .pred p;\nsetp.ne.b32 p, %130, 0;\n"
    "wgmma.mma_async.sync.aligned.m64n256k16.f32.bf16.bf16 {%0, %1, %2, %3, %4, %5, %6, %7, %8, %9, %10, %11, %12, %13, %14, %15, %16, %17, %18, %19, %20, %21, %22, %23, %24, %25, %26, %27, %28, %29, %30, %31, %32, %33, %34, %35, %36, %37, %38, %39, %40, %41, %42, %43, %44, %45, %46, %47, %48, %49, %50, %51, %52, %53, %54, %55, %56, %57, %58, %59, %60, %61, %62, %63, %64, %65, %66, %67, %68, %69, %70, %71, %72, %73, %74, %75, %76, %77, %78, %79, %80, %81, %82, %83, %84, %85, %86, %87, %88, %89, %90, %91, %92, %93, %94, %95, %96, %97, %98, %99, %100, %101, %102, %103, %104, %105, %106, %107, %108, %109, %110, %111, %112, %113, %114, %115, %116, %117, %118, %119, %120, %121, %122, %123, %124, %125, %126, %127}, %128, %129, p, 1, 1, %131, %132;\n}\n"
    : "+f"(d[0]), "+f"(d[1]), "+f"(d[2]), "+f"(d[3]), "+f"(d[4]), "+f"(d[5]), "+f"(d[6]), "+f"(d[7]), "+f"(d[8]), "+f"(d[9]), "+f"(d[10]), "+f"(d[11]), "+f"(d[12]), "+f"(d[13]), "+f"(d[14]), "+f"(d[15]), "+f"(d[16]), "+f"(d[17]), "+f"(d[18]), "+f"(d[19]), "+f"(d[20]), "+f"(d[21]), "+f"(d[22]), "+f"(d[23]), "+f"(d[24]), "+f"(d[25]), "+f"(d[26]), "+f"(d[27]), "+f"(d[28]), "+f"(d[29]), "+f"(d[30]), "+f"(d[31]), "+f"(d[32]), "+f"(d[33]), "+f"(d[34]), "+f"(d[35]), "+f"(d[36]), "+f"(d[37]), "+f"(d[38]), "+f"(d[39]), "+f"(d[40]), "+f"(d[41]), "+f"(d[42]), "+f"(d[43]), "+f"(d[44]), "+f"(d[45]), "+f"(d[46]), "+f"(d[47]), "+f"(d[48]), "+f"(d[49]), "+f"(d[50]), "+f"(d[51]), "+f"(d[52]), "+f"(d[53]), "+f"(d[54]), "+f"(d[55]), "+f"(d[56]), "+f"(d[57]), "+f"(d[58]), "+f"(d[59]), "+f"(d[60]), "+f"(d[61]), "+f"(d[62]), "+f"(d[63]), "+f"(d[64]), "+f"(d[65]), "+f"(d[66]), "+f"(d[67]), "+f"(d[68]), "+f"(d[69]), "+f"(d[70]), "+f"(d[71]), "+f"(d[72]), "+f"(d[73]), "+f"(d[74]), "+f"(d[75]), "+f"(d[76]), "+f"(d[77]), "+f"(d[78]), "+f"(d[79]), "+f"(d[80]), "+f"(d[81]), "+f"(d[82]), "+f"(d[83]), "+f"(d[84]), "+f"(d[85]), "+f"(d[86]), "+f"(d[87]), "+f"(d[88]), "+f"(d[89]), "+f"(d[90]), "+f"(d[91]), "+f"(d[92]), "+f"(d[93]), "+f"(d[94]), "+f"(d[95]), "+f"(d[96]), "+f"(d[97]), "+f"(d[98]), "+f"(d[99]), "+f"(d[100]), "+f"(d[101]), "+f"(d[102]), "+f"(d[103]), "+f"(d[104]), "+f"(d[105]), "+f"(d[106]), "+f"(d[107]), "+f"(d[108]), "+f"(d[109]), "+f"(d[110]), "+f"(d[111]), "+f"(d[112]), "+f"(d[113]), "+f"(d[114]), "+f"(d[115]), "+f"(d[116]), "+f"(d[117]), "+f"(d[118]), "+f"(d[119]), "+f"(d[120]), "+f"(d[121]), "+f"(d[122]), "+f"(d[123]), "+f"(d[124]), "+f"(d[125]), "+f"(d[126]), "+f"(d[127])
    : "l"(da), "l"(db), "r"(acc), "n"(TA), "n"(TB));
}

template <int TB> __device__ __forceinline__ void wgmma_rs_n24(float (&d)[12], uint32_t a0, uint32_t a1, uint32_t a2, uint32_t a3, uint64_t db, int acc) {
  asm volatile("{\n.reg .pred p;\nsetp.ne.b32 p, %17, 0;\n"
    "wgmma.mma_async.sync.aligned.m64n24k16.f32.bf16.bf16 {%0, %1, %2, %3, %4, %5, %6, %7, %8, %9, %10, %11}, {%12, %13, %14, %15}, %16, p, 1, 1, %18;\n}\n"
    : "+f"(d[0]), "+f"(d[1]), "+f"(d[2]), "+f"(d[3]), "+f"(d[4]), "+f"(d[5]), "+f"(d[6]), "+f"(d[7]), "+f"(d[8]), "+f"(d[9]), "+f"(d[10]), "+f"(d[11])
    : "r"(a0), "r"(a1), "r"(a2), "r"(a3), "l"(db), "r"(acc), "n"(TB));
}

template <int TB> __device__ __forceinline__ void wgmma_rs_n40(float (&d)[20], uint32_t a0, uint32_t a1, uint32_t a2, uint32_t a3, uint64_t db, int acc) {
  asm volatile("{\n.reg .pred p;\nsetp.ne.b32 p, %25, 0;\n"
    "wgmma.mma_async.sync.aligned.m64n40k16.f32.bf16.bf16 {%0, %1, %2, %3, %4, %5, %6, %7, %8, %9, %10, %11, %12, %13, %14, %15, %16, %17, %18, %19}, {%20, %21, %22, %23}, %24, p, 1, 1, %26;\n}\n"
    : "+f"(d[0]), "+f"(d[1]), "+f"(d[2]), "+f"(d[3]), "+f"(d[4]), "+f"(d[5]), "+f"(d[6]), "+f"(d[7]), "+f"(d[8]), "+f"(d[9]), "+f"(d[10]), "+f"(d[11]), "+f"(d[12]), "+f"(d[13]), "+f"(d[14]), "+f"(d[15]), "+f"(d[16]), "+f"(d[17]), "+f"(d[18]), "+f"(d[19])
    : "r"(a0), "r"(a1), "r"(a2), "r"(a3), "l"(db), "r"(acc), "n"(TB));
}

template <int TB> __device__ __forceinline__ void wgmma_rs_n192(float (&d)[96], uint32_t a0, uint32_t a1, uint32_t a2, uint32_t a3, uint64_t db, int acc) {
  asm volatile("{\n.reg .pred p;\nsetp.ne.b32 p, %101, 0;\n"
    "wgmma.mma_async.sync.aligned.m64n192k16.f32.bf16.bf16 {%0, %1, %2, %3, %4, %5, %6, %7, %8, %9, %10, %11, %12, %13, %14, %15, %16, %17, %18, %19, %20, %21, %22, %23, %24, %25, %26, %27, %28, %29, %30, %31, %32, %33, %34, %35, %36, %37, %38, %39, %40, %41, %42, %43, %44, %45, %46, %47, %48, %49, %50, %51, %52, %53, %54, %55, %56, %57, %58, %59, %60, %61, %62, %63, %64, %65, %66, %67, %68, %69, %70, %71, %72, %73, %74, %75, %76, %77, %78, %79, %80, %81, %82, %83, %84, %85, %86, %87, %88, %89, %90, %91, %92, %93, %94, %95}, {%96, %97, %98, %99}, %100, p, 1, 1, %102;\n}\n"
    : "+f"(d[0]), "+f"(d[1]), "+f"(d[2]), "+f"(d[3]), "+f"(d[4]), "+f"(d[5]), "+f"(d[6]), "+f"(d[7]), "+f"(d[8]), "+f"(d[9]), "+f"(d[10]), "+f"(d[11]), "+f"(d[12]), "+f"(d[13]), "+f"(d[14]), "+f"(d[15]), "+f"(d[16]), "+f"(d[17]), "+f"(d[18]), "+f"(d[19]), "+f"(d[20]), "+f"(d[21]), "+f"(d[22]), "+f"(d[23]), "+f"(d[24]), "+f"(d[25]), "+f"(d[26]), "+f"(d[27]), "+f"(d[28]), "+f"(d[29]), "+f"(d[30]), "+f"(d[31]), "+f"(d[32]), "+f"(d[33]), "+f"(d[34]), "+f"(d[35]), "+f"(d[36]), "+f"(d[37]), "+f"(d[38]), "+f"(d[39]), "+f"(d[40]), "+f"(d[41]), "+f"(d[42]), "+f"(d[43]), "+f"(d[44]), "+f"(d[45]), "+f"(d[46]), "+f"(d[47]), "+f"(d[48]), "+f"(d[49]), "+f"(d[50]), "+f"(d[51]), "+f"(d[52]), "+f"(d[53]), "+f"(d[54]), "+f"(d[55]), "+f"(d[56]), "+f"(d[57]), "+f"(d[58]), "+f"(d[59]), "+f"(d[60]), "+f"(d[61]), "+f"(d[62]), "+f"(d[63]), "+f"(d[64]), "+f"(d[65]), "+f"(d[66]), "+f"(d[67]), "+f"(d[68]), "+f"(d[69]), "+f"(d[70]), "+f"(d[71]), "+f"(d[72]), "+f"(d[73]), "+f"(d[74]), "+f"(d[75]), "+f"(d[76]), "+f"(d[77]), "+f"(d[78]), "+f"(d[79]), "+f"(d[80]), "+f"(d[81]), "+f"(d[82]), "+f"(d[83]), "+f"(d[84]), "+f"(d[85]), "+f"(d[86]), "+f"(d[87]), "+f"(d[88]), "+f"(d[89]), "+f"(d[90]), "+f"(d[91]), "+f"(d[92]), "+f"(d[93]), "+f"(d[94]), "+f"(d[95])
    : "r"(a0), "r"(a1), "r"(a2), "r"(a3), "l"(db), "r"(acc), "n"(TB));
}
constexpr uint32_t AR_ACC = 0;
constexpr uint32_t AR_TAB = 0x100000;
constexpr uint32_t AR_PROG = 0x101000;
__host__ __device__ constexpr uint32_t prog_off(int h, int j) { return AR_PROG + h * 128 + j * 4; }
constexpr uint32_t AR_CNT = 0x108000;
constexpr uint32_t AR_QUEUE = 0x109000;
constexpr uint32_t AR_SIZE = 0x10a000;

struct ChainArgs {
  const bf16* mem0;
  const uint2* xh;
  unsigned char *kg, *vg;
  unsigned char* arena;
  unsigned* go;
  uint32_t* dbg;
  uint32_t delay;
  int margin;
  int tl;
};

namespace ch {
constexpr int OFF_WQ = 0;
constexpr int OFF_X = 81920;
constexpr int OFF_MEM = OFF_X + 40960;
constexpr int OFF_WO = OFF_MEM + 10240;
constexpr int WOK = 8 * 896;
constexpr int OFF_KV = OFF_WO + 10 * WOK;
constexpr int KVB = 5120;
constexpr int OFF_O = OFF_KV + 4 * KVB;
constexpr int OFF_Q = OFF_O + 1024;
constexpr int OFF_S = OFF_O + 3072;
constexpr int OFF_SR = OFF_S + 1536;
constexpr int OFF_LT = OFF_SR + 1280;
constexpr int OFF_BAR = OFF_LT + 512;
constexpr int SMEM = OFF_BAR + 256;
static_assert(SMEM <= 232448, "smem");
constexpr int MB_S = OFF_BAR, MB_O = OFF_BAR + 8, MB_X = OFF_BAR + 16;
constexpr int MB_K = OFF_BAR + 128, MB_V = MB_K + 16, MB_Q = MB_K + 32, MB_R = MB_K + 48;
constexpr int SC_IN = OFF_BAR + 64;
constexpr int SC_MX = OFF_S;
constexpr int SC_W = OFF_BAR + 96;
constexpr int WOS = 448;
enum { B_MEM0 = 1, B_QK, B_SL, B_V, B_O, B_RED, B_X, B_C, B_H, B_MEM1, B_A, B_G, B_E };
#ifndef NQ1
#define NQ1 6
#endif
#ifndef NQ0
#define NQ0 4
#endif
#ifndef NP0
#define NP0 4
#endif
#ifndef NWO
#define NWO 5
#endif
#ifndef NWP
#define NWP 4
#endif
#ifndef NB0
#define NB0 3
#endif
#ifndef BBS
#define BBS 100
#endif
#ifndef VSYNC
#define VSYNC 0
#endif
#ifndef XPOS
#define XPOS 0
#endif
#ifndef XPD
#define XPD 300
#endif
#ifndef WOF
#define WOF 0
#endif
#ifndef XBYTES
#define XBYTES 36864
#endif
#ifndef NRT
#define NRT 7
#endif
#ifndef NRF
#define NRF 2
#endif
#ifndef NPM0
#define NPM0 2
#endif
#ifndef NPM1
#define NPM1 2
#endif
#ifndef RSYNC
#define RSYNC 1
#endif
#ifndef PFK
#define PFK 1
#endif
#ifndef PA0
#define PA0 3
#endif
#ifndef PA1
#define PA1 0
#endif
#ifndef PB0
#define PB0 7
#endif
#ifndef PB1
#define PB1 5
#endif
#ifndef PQE
#define PQE 1
#endif
#ifndef XT
#define XT 30
#endif
static_assert(NPM0 >= 2 && NPM1 >= 2, "the K / V blocks live in the last two k-steps of Wo");
}

#ifndef CHAIN_TIMING
#define CHAIN_TIMING 0
#endif
#if CHAIN_TIMING
#ifndef TR0
#define TR0 41
#endif
#ifndef TSMASK
#define TSMASK 0xffff
#endif
#define TSV(i, v) do { if ((TSMASK >> (i)) & 1) asm volatile("st.shared.u32 [%0+%1], %2;" :: "r"(tsb), "n"((i) * 4), "r"(v) : "memory"); } while (0)
#define TS(i) TSV(i, clk32())
#define TS_SETUP() const uint32_t tsb = sb + ((s == TR0 || s == TR0 + 1) ? OFF_BAR + 128 + ((s - TR0) * 12 + warp) * 48 : OFF_SR + 1152)
#else
#define TS(i)
#define TSV(i, v)
#define TS_SETUP()
#endif
#ifndef POLL_DELAY
#define POLL_DELAY 590
#endif
#ifndef XN
#define XN 40
#endif
#ifndef PF0
#define PF0 8
#endif
#ifndef PFS
#define PFS 3
#endif
#ifndef XDELAY
#define XDELAY 0
#endif
#ifndef NOKM
#define NOKM 0
#endif
#ifndef PFX
#define PFX 3
#endif
#ifndef NVE
#define NVE 10
#endif
#ifndef VET
#define VET 19
#endif
#ifndef MEMFIRST
#define MEMFIRST 1
#endif
#ifndef GD0
#define GD0 -1
#endif
#ifndef PM1
#define PM1 1
#endif
#ifndef GD1
#define GD1 30
#endif
#ifndef GD2
#define GD2 150
#endif
#ifndef CEARLY
#define CEARLY 1
#endif
#ifndef PFACC
#define PFACC 1
#endif
template <int V> using IC = std::integral_constant<int, V>;
__device__ __forceinline__ uint32_t clk_v() { uint64_t c; asm volatile("mov.u64 %0, %%clock64;" : "=l"(c) :: "memory"); return (uint32_t)c; }
__device__ __forceinline__ int fresh(int x) { int y; asm volatile("shfl.sync.bfly.b32 %0, %1, 0, 0x1f, 0xffffffff;" : "=r"(y) : "r"(x)); return y; }
#define SFENCE2(x, d) asm volatile("{\n.reg .pred p;\nsetp.eq.u32 p, %0, 0x7fffffff;\n@p st.shared.u32 [%0], %1;\n}" :: "r"(x), "r"(d) : "memory")
#define SFENCE(x) asm volatile("{\n.reg .pred p;\nsetp.eq.u32 p, %0, 0x7fffffff;\n@p st.shared.u32 [%0], %0;\n}" :: "r"(x) : "memory")
template <int I> __device__ __forceinline__ void bbfence(uint32_t x) {
  asm volatile("{\n.reg .pred p;\nsetp.eq.u32 p, %0, %1;\nL_%=:\n@p st.volatile.shared.u32 [%0], %0;\n@p bra.uni L_%=;\n}" :: "r"(x), "n"(4 * I) : "memory");
}
__device__ __forceinline__ float uniform_f(float x) { return __uint_as_float(__reduce_max_sync(0xffffffffu, __float_as_uint(x))); }

__device__ __forceinline__ void mma16816h(float (&d)[4], const uint32_t (&a)[4], uint32_t b0, uint32_t b1) {
  asm volatile("mma.sync.aligned.m16n8k16.row.col.f32.f16.f16.f32 {%0,%1,%2,%3}, {%4,%5,%6,%7}, {%8,%9}, {%0,%1,%2,%3};"
               : "+f"(d[0]), "+f"(d[1]), "+f"(d[2]), "+f"(d[3]) : "r"(a[0]), "r"(a[1]), "r"(a[2]), "r"(a[3]), "r"(b0), "r"(b1));
}
__device__ __forceinline__ void mma1688(float (&d)[4], uint32_t a0, uint32_t a1, uint32_t b0) {
  asm volatile("mma.sync.aligned.m16n8k8.row.col.f32.bf16.bf16.f32 {%0,%1,%2,%3}, {%4,%5}, {%6}, {%0,%1,%2,%3};"
               : "+f"(d[0]), "+f"(d[1]), "+f"(d[2]), "+f"(d[3]) : "r"(a0), "r"(a1), "r"(b0));
}
template <int OFF16, int ACC> __device__ __forceinline__ void wgmma_rs32h(float (&d)[16], const uint32_t (&a)[4], uint32_t dlo) {
  asm volatile("{\n.reg .pred p;\n.reg .b32 t;\n.reg .b64 db;\nsetp.ne.b32 p, %22, 0;\nadd.u32 t, %20, %21;\nmov.b64 db, {t, 0x40000040};\n"
    "wgmma.mma_async.sync.aligned.m64n32k16.f32.f16.f16 {%0,%1,%2,%3,%4,%5,%6,%7,%8,%9,%10,%11,%12,%13,%14,%15}, {%16,%17,%18,%19}, db, p, 1, 1, 0;\n}\n"
    : "+f"(d[0]), "+f"(d[1]), "+f"(d[2]), "+f"(d[3]), "+f"(d[4]), "+f"(d[5]), "+f"(d[6]), "+f"(d[7]), "+f"(d[8]), "+f"(d[9]), "+f"(d[10]), "+f"(d[11]),
      "+f"(d[12]), "+f"(d[13]), "+f"(d[14]), "+f"(d[15])
    : "r"(a[0]), "r"(a[1]), "r"(a[2]), "r"(a[3]), "r"(dlo), "n"(OFF16), "n"(ACC));
}
template <int IMM> __device__ __forceinline__ void stsm_x4_t_i(uint32_t a, uint32_t r0, uint32_t r1, uint32_t r2, uint32_t r3) {
  asm volatile("stmatrix.sync.aligned.m8n8.x4.trans.shared.b16 [%0+%5], {%1,%2,%3,%4};" :: "r"(a), "r"(r0), "r"(r1), "r"(r2), "r"(r3), "n"(IMM) : "memory");
}
template <int IMM> __device__ __forceinline__ void stsm_x2_t_i(uint32_t a, uint32_t r0, uint32_t r1) {
  asm volatile("stmatrix.sync.aligned.m8n8.x2.trans.shared.b16 [%0+%3], {%1,%2};" :: "r"(a), "r"(r0), "r"(r1), "n"(IMM) : "memory");
}
template <int IMM> __device__ __forceinline__ void st_async_b32_i(uint32_t a, uint32_t x, uint32_t mb) {
  asm volatile("st.async.weak.shared::cluster.mbarrier::complete_tx::bytes.b32 [%0+%3], %1, [%2];" :: "r"(a), "r"(x), "r"(mb), "n"(IMM) : "memory");
}
template <int IMM> __device__ __forceinline__ void ld_relaxed_v4_if(uint4& v, const void* p, uint32_t c) {
  asm volatile("{\n.reg .pred p;\nsetp.ne.u32 p, %6, 0;\n@p ld.relaxed.gpu.global.v4.u32 {%0,%1,%2,%3}, [%4+%5];\n}"
               : "+r"(v.x), "+r"(v.y), "+r"(v.z), "+r"(v.w) : "l"(p), "n"(IMM), "r"(c) : "memory");
}
template <int IMM> __device__ __forceinline__ void ldsm_x2_i(uint32_t (&r)[2], uint32_t a) {
  asm volatile("ldmatrix.sync.aligned.m8n8.x2.shared.b16 {%0,%1}, [%2+%3];" : "=r"(r[0]), "=r"(r[1]) : "r"(a), "n"(IMM) : "memory");
}
template <int IMM> __device__ __forceinline__ uint32_t ldsm_x1_t_i(uint32_t a) {
  uint32_t r; asm volatile("ldmatrix.sync.aligned.m8n8.x1.trans.shared.b16 {%0}, [%1+%2];" : "=r"(r) : "r"(a), "n"(IMM) : "memory"); return r;
}
template <int IMM> __device__ __forceinline__ uint32_t lds32_i(uint32_t a) {
  uint32_t v; asm volatile("ld.shared.u32 %0, [%1+%2];" : "=r"(v) : "r"(a), "n"(IMM) : "memory"); return v;
}
__device__ __forceinline__ void sts32(uint32_t a, uint32_t v) { asm volatile("st.shared.u32 [%0], %1;" :: "r"(a), "r"(v) : "memory"); }
__device__ __forceinline__ uint32_t pack_f16(float lo, float hi) {
  uint32_t d; asm("cvt.rn.f16x2.f32 %0, %1, %2;" : "=r"(d) : "f"(hi), "f"(lo)); return d;
}
__device__ __forceinline__ uint32_t amax_bf2(uint32_t a, uint32_t b) { uint32_t d; asm("max.xorsign.abs.bf16x2 %0, %1, %2;" : "=r"(d) : "r"(a), "r"(b)); return d; }
__device__ __forceinline__ uint32_t amax_h2(uint32_t a, uint32_t b) { uint32_t d; asm("max.xorsign.abs.f16x2 %0, %1, %2;" : "=r"(d) : "r"(a), "r"(b)); return d; }
__device__ __forceinline__ uint32_t amax_fold(uint32_t m) { return __reduce_max_sync(0xffffffffu, max(m & 0x7fffu, (m >> 16) & 0x7fffu)); }
__device__ __forceinline__ int wscale_exp(uint32_t m) { return min(141 - (int)(m >> 7), 100); }
__device__ __forceinline__ float exp2i(int e) { return __uint_as_float((uint32_t)(e + 127) << 23); }
__device__ __forceinline__ uint32_t bf2_to_h2(uint32_t w, float sc) { return pack_f16(bf_lo(w) * sc, bf_hi(w) * sc); }
__device__ __forceinline__ void bf2_to_h2_inplace(uint32_t& w, uint32_t sc2) {
  asm volatile("{\n.reg .b32 t, lo, hi;\nmul.rn.bf16x2 t, %0, %1;\nshl.b32 lo, t, 16;\nand.b32 hi, t, 0xffff0000;\ncvt.rn.f16x2.f32 %0, hi, lo;\n}" : "+r"(w) : "r"(sc2));
}
__device__ __forceinline__ void prefetch_l2(const void* p, uint32_t bytes) { asm volatile("cp.async.bulk.prefetch.L2.global [%0], %1;" :: "l"(p), "r"(bytes) : "memory"); }
__device__ __forceinline__ void prefetch_tma_2d(const CUtensorMap* tm, int c0, int c1) {
  asm volatile("cp.async.bulk.prefetch.tensor.2d.L2.global [%0, {%1, %2}];" :: "l"(tm), "r"(c0), "r"(c1) : "memory");
}
__host__ __device__ constexpr uint32_t acc_voff(int v) { return v < 4 ? v * 1024u : (v == 4 ? 128u : 3072u + 128u); }
__device__ __forceinline__ int unit28(int i) { return i == 3 ? 54 : 14 * i; }
__device__ __forceinline__ int unit24(int i) { return i < 2 ? 48 - 6 * i : 56 + 6 * i; }
__device__ __forceinline__ uint32_t acc_step(int s) { return (s >> 1) * 32768 + (s & 1) * 512; }
__device__ __forceinline__ uint32_t acc_lane(int i, int lane) { return ((lane >> 3) & 1) * 256 + (lane >> 4) * 4096 + i * 8192 + (lane & 7) * 16; }

__device__ __forceinline__ uint32_t ld_acquire_u32(const void* p) {
  uint32_t v; asm volatile("ld.acquire.gpu.global.u32 %0, [%1];" : "=r"(v) : "l"(p) : "memory"); return v;
}
template <int R> __device__ __forceinline__ void ln_rows(const uint2 (&xw)[R][5], int row0, int lane, bf16* __restrict__ xn, uint2* __restrict__ xh) {
  float v[R][20], s[R], q[R];
#pragma unroll
  for (int r = 0; r < R; r++) {
    s[r] = 0.f; q[r] = 0.f;
#pragma unroll
    for (int i = 0; i < 5; i++) { v[r][4 * i] = bf_lo(xw[r][i].x); v[r][4 * i + 1] = bf_hi(xw[r][i].x); v[r][4 * i + 2] = bf_lo(xw[r][i].y); v[r][4 * i + 3] = bf_hi(xw[r][i].y); }
#pragma unroll
    for (int i = 0; i < 5; i++) s[r] += (v[r][4 * i] + v[r][4 * i + 1]) + (v[r][4 * i + 2] + v[r][4 * i + 3]);
  }
#pragma unroll
  for (int o = 16; o; o >>= 1)
#pragma unroll
    for (int r = 0; r < R; r++) s[r] += __shfl_xor_sync(0xffffffffu, s[r], o);
#pragma unroll
  for (int r = 0; r < R; r++) {
    s[r] *= 1.f / cfg::DM;
#pragma unroll
    for (int i = 0; i < 10; i++) { const float d = v[r][2 * i] - s[r], e = v[r][2 * i + 1] - s[r]; q[r] += d * d + e * e; }
  }
#pragma unroll
  for (int o = 16; o; o >>= 1)
#pragma unroll
    for (int r = 0; r < R; r++) q[r] += __shfl_xor_sync(0xffffffffu, q[r], o);
#pragma unroll
  for (int r = 0; r < R; r++) {
    const int row = row0 + r;
    const float mb = bf16r(s[r]), var = bf16r(q[r] * (1.f / cfg::DM));
    float sd; asm("sqrt.approx.f32 %0, %1;" : "=f"(sd) : "f"(bf16r(var + 1e-5f)));
    const float inv = rcpf(bf16r(sd));
#pragma unroll
    for (int i = 0; i < 5; i++) {
      float y[4];
#pragma unroll
      for (int e = 0; e < 4; e++) y[e] = v[r][4 * i + e] - mb;
      bf16r2(y[0], y[1]); bf16r2(y[2], y[3]);
      const uint32_t w0 = pack_bf16(y[0] * inv, y[1] * inv), w1 = pack_bf16(y[2] * inv, y[3] * inv);
      *(uint2*)(xn + (size_t)row * cfg::DM + i * 128 + lane * 4) = make_uint2(w0, w1);
      if (xh) xh[(((size_t)(row >> 5) * 10 + 2 * i + (lane >> 4)) * 32 + (row & 31)) * 16 + ((((lane >> 1) & 7) ^ (row & 7)) << 1) + (lane & 1)] =
          make_uint2(pack_f16(bf_lo(w0), bf_hi(w0)), pack_f16(bf_lo(w1), bf_hi(w1)));
    }
  }
}

__global__ void __cluster_dims__(3, 1, 1) __launch_bounds__(384, 1) chain_kernel(const ChainArgs a, const __grid_constant__ CUtensorMap tmWq,
    const __grid_constant__ CUtensorMap tmWk, const __grid_constant__ CUtensorMap tmWv, const __grid_constant__ CUtensorMap tmWo) {
  using namespace ch;
  extern __shared__ __align__(1024) unsigned char smem_raw[];
  const uint32_t sb = smem_u32(smem_raw);
  const int warp = __shfl_sync(0xffffffffu, (int)threadIdx.x >> 5, 0);
  const int lane = __shfl_sync(0xffffffffu, (int)threadIdx.x & 31, threadIdx.x & 31);
  const int cta = blockIdx.x, h = cta / 3, j = cta % 3;
  const int g = lane >> 2, q4 = lane & 3, r8 = lane & 7, m4 = lane >> 3;
  unsigned char* const arena = a.arena;
  if (sb & 1023u) __trap();
  asm volatile("griddepcontrol.launch_dependents;");
  TL_BEGIN(a.tl);
#ifdef TIMELINE
  const unsigned long long g_tl0 = gtime();
#define PT(i) TLW((a.tl >= 12) * 128 + 64 + (i))
#else
#define PT(i)
#endif
  const int col0 = j == 0 ? 0 : (j == 1 ? 224 : 432);
  auto stage_w = [&](const CUtensorMap* tm, uint32_t dst, uint32_t mb, int half) {
    mbar_expect_tx(mb + 8 * half, 40960);
    tma_load_2d(dst + half * 40960, tm, h * cfg::DH + j * 64, half * 320, mb + 8 * half);
    tma_load_2d(dst + half * 40960 + 20480, tm, h * cfg::DH + j * 64, half * 320 + 160, mb + 8 * half);
  };
  if (threadIdx.x == 256) {
    for (int i = 0; i < 9; i++) mbar_init(sb + MB_K + 8 * i, 1);
    mbar_init(sb + MB_S, 1); mbar_init(sb + MB_O, 1); mbar_init(sb + MB_X, 1);
    asm volatile("fence.mbarrier_init.release.cluster;" ::: "memory");
    for (int i = 0; i < 2; i++) { stage_w(&tmWk, sb + OFF_WQ, sb + MB_K, i); stage_w(&tmWv, sb + OFF_WO, sb + MB_V, i); }
    sts32(sb + SC_W, 0); sts32(sb + SC_W + 4, 0); sts32(sb + SC_W + 8, 0); sts32(sb + SC_IN + 12, 0); sts32(sb + SC_IN + 20, 0);
    mbar_expect_tx(sb + MB_S, 1280); mbar_expect_tx(sb + MB_O, 2048);
  }
  __syncthreads();
  asm volatile("barrier.cluster.arrive.relaxed.aligned;" ::: "memory");
  const uint32_t d1 = mapa_u32(sb, (j + 1) % 3) - sb, d2 = mapa_u32(sb, (j + 2) % 3) - sb;

  if (warp >= 8) {
    asm volatile("setmaxnreg.dec.sync.aligned.u32 40;");
    const int hw = warp - 8, ht = hw * 32 + lane;
    const bool lead = ht == 0;
    auto stage_wo = [&](int i) {
      mbar_expect_tx(sb + MB_R + 8 * i, 64 * WOS);
      tma_load_2d(sb + OFF_WO + i * 64 * WOS, &tmWo, col0, h * cfg::DH + ((i + j) % 3) * 64, sb + MB_R + 8 * i);
    };
    const unsigned char* xg = (const unsigned char*)a.xh;
    auto issue_x = [&](int s) { mbar_expect_tx(sb + MB_X, 40960); bulk_g2s(sb + OFF_X, xg + (size_t)s * 40960, 40960, sb + MB_X); };
    uint4 v[5];
#pragma unroll
    for (int i = 0; i < 5; i++) { const int c = ht + 128 * i; v[i] = ld_relaxed_v4(a.mem0 + (c & 7) * cfg::DM + (c >> 3) * 8); }
    if (hw == 2) {
      asm volatile("griddepcontrol.wait;" ::: "memory");
      if (lane == 0) { if (cta == 0) st_relaxed_u32(a.go, 1); issue_x(0); }
      PT(0);
    }
    if (hw == 0) {
      bar_sync(B_QK, 160); if (lane == 0) stage_w(&tmWq, sb + OFF_WQ, sb + MB_Q, 0);
      bar_sync(B_SL, 160); if (lane == 0) stage_w(&tmWq, sb + OFF_WQ, sb + MB_Q, 1);
    }
    if (hw == 1) {
      bar_sync(B_V, 160); if (lane == 0) stage_wo(0);
      bar_sync(B_O, 160); if (lane == 0) { stage_wo(1); stage_wo(2); }
    }
    __syncwarp();
    {
      uint32_t m = 0;
#pragma unroll
      for (int i = 0; i < 5; i++) {
        m = amax_bf2(amax_bf2(m, amax_bf2(v[i].x, v[i].y)), amax_bf2(v[i].z, v[i].w));
      }
      m = amax_fold(m);
      if (lane == 0) sts32(sb + SC_MX + hw * 4, m);
      bar_sync(B_H, 128);
      const uint4 mm = lds128(sb + SC_MX);
      const int se = max(wscale_exp(max(max(mm.x, mm.y), max(mm.z, mm.w))), -100);
      const float sc = exp2i(se);
#pragma unroll
      for (int i = 0; i < 5; i++) {
        const int c = ht + 128 * i, t = c & 7, chn = c >> 3;
        sts128(sb + OFF_MEM + chn * 128 + ((t ^ (2 * (chn & 3))) << 4), bf2_to_h2(v[i].x, sc), bf2_to_h2(v[i].y, sc), bf2_to_h2(v[i].z, sc), bf2_to_h2(v[i].w, sc));
      }
      if (lead) { sts32(sb + SC_IN, __float_as_uint(exp2i(-se))); sts32(sb + SC_IN + 4, 0x7800u); }
    }
    if (hw == 0) PT(11);
    {
      const uint32_t p0 = sb + OFF_WQ + hw * 2048 + lane * 16;
      uint32_t m = 0;
#pragma unroll 1
      for (int i = 0; i < 10; i++) {
        if (i == 0 || i == 5) mbar_wait(sb + MB_Q + (i ? 8 : 0), 0);
        uint32_t r[4][4];
        static_for<0, 4>([&](auto K) { ldsm_x4_i<K.value * 512>(r[K.value], p0 + i * 8192); });
#pragma unroll
        for (int k = 0; k < 4; k++) m = amax_bf2(amax_bf2(m, amax_bf2(r[k][0], r[k][1])), amax_bf2(r[k][2], r[k][3]));
      }
      if (hw == 0) PT(9);
      m = amax_fold(m);
      if (lane == 0) asm volatile("red.shared.max.u32 [%0], %1;" :: "r"(sb + SC_W + 8), "r"(m) : "memory");
      bar_sync(B_H, 128);
      const uint32_t sc = (uint32_t)(wscale_exp(lds32_i<SC_W + 8>(sb)) + 127) * 0x00800080u;
#pragma unroll 1
      for (int i = 0; i < 10; i++) {
        uint32_t r[4][4];
        static_for<0, 4>([&](auto K) { ldsm_x4_i<K.value * 512>(r[K.value], p0 + i * 8192); });
#pragma unroll
        for (int k = 0; k < 4; k++) {
          bf2_to_h2_inplace(r[k][0], sc); bf2_to_h2_inplace(r[k][1], sc); bf2_to_h2_inplace(r[k][2], sc); bf2_to_h2_inplace(r[k][3], sc);
          stsm_x4(p0 + i * 8192 + k * 512, r[k][0], r[k][1], r[k][2], r[k][3]);
        }
      }
    }
    if (hw == 0) PT(10);
    bar_sync(0, 384);
    if (hw == 3) {
      const uint32_t eye = (m4 == q4) ? ((lane & 4) ? 0x3f800000u : 0x3f80u) : 0u;
      sts128(sb + OFF_LT + lane * 16, eye, eye, (lane & 2) * 64 + g * 16 + (lane & 1) * 8, 0u);
      sts64(sb + OFF_S + 1280 + lane * 8, 0u, 0u);
    }
    if (lead) st_relaxed_u32(arena + AR_TAB + cta * 4, 0x80000000u | (lds32_i<SC_W>(sb) << 15) | lds32_i<SC_W + 4>(sb));
    asm volatile("barrier.cluster.wait.aligned;" ::: "memory");
    bar_sync(B_MEM0, 256); bar_sync(B_MEM1, 256);
    {
      uint32_t v0, v1, v2; int spin = 0;
      do {
        v0 = ld_relaxed_u32(arena + AR_TAB + lane * 4); v1 = ld_relaxed_u32(arena + AR_TAB + 128 + lane * 4); v2 = ld_relaxed_u32(arena + AR_TAB + 256 + lane * 4);
      } while (__any_sync(0xffffffffu, ((v0 & v1 & v2) >> 31) == 0) && ++spin < SPIN_LIMIT);
      const uint32_t mv = (max(max(v0, v1), v2) >> 15) & 0x7fffu, mo = max(max(v0 & 0x7fffu, v1 & 0x7fffu), v2 & 0x7fffu);
      sts32(sb + SC_IN + 8 + (lane & 1) * 16, 15 - ((__reduce_max_sync(0xffffffffu, mv) >> 7) + (__reduce_max_sync(0xffffffffu, mo) >> 7) - 252 + 22));
    }

    auto store_kv = [&](int s) {
      const size_t o = ((size_t)s * 96 + cta) * KVB; const uint32_t src = sb + OFF_KV + (s & 1) * (2 * KVB);
      fence_proxy_async(); bulk_s2g(a.kg + o, src, KVB); bulk_s2g(a.vg + o, src + KVB, KVB); bulk_commit();
    };
    const int cb28 = unit28(hw), du = (unit24(hw) - cb28) * 128;
    uint32_t n16 = lane * 16, hist = 0;
    const uint32_t us1 = sb + d1 + OFF_SR + 256 + (hw >> 1) * 512 + (hw & 1) * 128, us2 = sb + d2 + OFF_SR + (hw >> 1) * 512 + (hw & 1) * 128;
    const uint32_t uo1 = sb + d1 + OFF_O + 2048 + hw * 256, uo2 = sb + d2 + OFF_O + 1024 + hw * 256;
#ifdef STEPCLK
    if (lead) a.dbg[96 * 300 + cta * 2] = clk32();
#endif
#ifdef TIMELINE
    if (cta == 0 && lead) { g_tl2[(a.tl >= 12) * 128 + 0] = clock64(); g_tl2[(a.tl >= 12) * 128 + 1] = gtime(); }
#endif
#pragma unroll 1
    for (int s = 0; s < cfg::NSEG; s++) {
      TS_SETUP();
      const bool last = s == cfg::NSEG - 1;
      if (n16 == 0) {
        if (hw == 2 && !last) issue_x(s + 1);
        if (hw == 0 && (s & 3) == 1 && s > 1) st_relaxed_u32(arena + (prog_off(h, j) + (hist >> 31)), s - 1);
        if (hw == 0 && s > 0) store_kv(s - 1);
        if (PFX && hw == 3 && cta < 80 && s + PFX < cfg::NSEG) prefetch_l2(xg + (size_t)(s + PFX) * 40960 + cta * 512, 512);
        if (PFACC && hw == 1 && s + PFACC < cfg::NSEG - 1)
          asm volatile("prefetch.global.L2 [%0];" :: "l"(arena + (AR_ACC + acc_step(s + PFACC) + acc_lane(cta / 24, (cta & 3) * 8) + acc_voff((cta % 24) >> 2))) : "memory");
      }
      __syncwarp();
      if (last) break;
      const uint32_t kv = (s & 1) * (2 * KVB);
      n16 = fresh(n16);
      uint32_t kb0[4], kb1[4];
      { const uint32_t ka = n16 + (n16 & 384) * 4 + (sb + kv + hw * 128); ldsm_x4_i<OFF_KV>(kb0, ka); ldsm_x4_i<OFF_KV + 2560>(kb1, ka); }
      TS(1);
      bar_sync(B_QK, 384);
      {
        uint32_t q0[4], q1[4], q2[4], q3[4];
        float sa[4] = {0, 0, 0, 0}, sc2[4] = {0, 0, 0, 0};
        ldsm_x4_i<OFF_Q>(q0, n16 + sb); ldsm_x4_i<OFF_Q + 1024>(q2, n16 + sb); ldsm_x4_i<OFF_Q + 512>(q1, n16 + sb);
        bar_arrive(B_A, 288);
        ldsm_x4_i<OFF_Q + 1536>(q3, n16 + sb);
        mma16816(sa, q0[0], q0[1], q0[2], q0[3], kb0[0], kb0[1]);
        mma16816(sc2, q2[0], q2[1], q2[2], q2[3], kb1[0], kb1[1]);
        mma16816(sa, q1[0], q1[1], q1[2], q1[3], kb0[2], kb0[3]);
        mma16816(sc2, q3[0], q3[1], q3[2], q3[3], kb1[2], kb1[3]);
        const float x0 = (sa[0] + sa[2]) + (sc2[0] + sc2[2]), x1 = (sa[1] + sa[3]) + (sc2[1] + sc2[3]);
        const uint32_t xp = pack_bf16(x0, x1);
        st_async_b32_i<0>((n16 >> 2) + us1, xp, sb + MB_S + d1);
        st_async_b32_i<0>((n16 >> 2) + us2, xp, sb + MB_S + d2);
        stsm_x2(n16 + (sb + OFF_S + hw * 256), __float_as_uint(x0), __float_as_uint(x1));
      }
      TS(3);
      uint32_t v0[4], v1[4], vm0, vm1;
      const uint32_t uv = sb + kv + hw * 1280;
      ldsm_x4_t_i<OFF_KV + KVB>(v0, n16 + uv); ldsm_x4_t_i<OFF_KV + KVB + 640>(v1, n16 + uv);
      bar_sync(B_SL, 256);
      float t0[4], t1[4], t2[4];
      { uint32_t x[4]; ldsm_x4_i<OFF_S>(x, n16 + sb); t0[0] = __uint_as_float(x[0]); t0[1] = __uint_as_float(x[1]); t0[2] = __uint_as_float(x[2]); t0[3] = __uint_as_float(x[3]); }
      { uint32_t x[4]; ldsm_x4_i<OFF_S + 512>(x, n16 + sb); t1[0] = __uint_as_float(x[0]); t1[1] = __uint_as_float(x[1]); t1[2] = __uint_as_float(x[2]); t1[3] = __uint_as_float(x[3]); }
      { uint32_t x[4]; ldsm_x4_i<OFF_S + 1024>(x, n16 + sb); t2[0] = __uint_as_float(x[0]); t2[1] = __uint_as_float(x[1]); t2[2] = __uint_as_float(x[2]); t2[3] = __uint_as_float(x[3]); }
      mbar_spin(sb + MB_S, s & 1);
      TS(4);
      uint2 xo;
      {
        uint32_t r0[4], r1[4], r2[2];
        ldsm_x4_i<OFF_SR>(r0, n16 + sb); ldsm_x4_i<OFF_SR + 512>(r1, n16 + sb); ldsm_x2_i<OFF_SR + 1024>(r2, n16 + sb);
        SFENCE(n16);
        const uint2 eye = lds64_i<OFF_LT>(n16 + sb);
        mma16816(t0, r0[0], r0[1], r0[2], r0[3], eye.x, eye.y);
        mma16816(t1, r1[0], r1[1], r1[2], r1[3], eye.x, eye.y);
        mma1688(t2, r2[0], r2[1], eye.x);
        bar_sync(B_V, 256);
        vm0 = ldsm_x1_t_i<OFF_KV + KVB + 512>(n16 + uv); vm1 = ldsm_x1_t_i<OFF_KV + KVB + 1152>(n16 + uv);
        SFENCE(n16);
        xo = lds64_i<OFF_LT + 8>(n16 + sb);
      }
      float sc[10] = {t0[0], t0[1], t0[2], t0[3], t1[0], t1[1], t1[2], t1[3], t2[0] + t2[2], t2[1] + t2[3]};
      const float cs = 0.07216878364870322f * 1.4426950408889634f;
      float mx = fmaxf(fmaxf(fmaxf(sc[0], sc[1]), fmaxf(sc[2], sc[3])), fmaxf(fmaxf(sc[4], sc[5]), fmaxf(sc[6], sc[7])));
      mx = fmaxf(mx, fmaxf(sc[8], sc[9]));
      {
        const float m1 = __shfl_xor_sync(0xffffffffu, mx, 1), m2 = __shfl_xor_sync(0xffffffffu, mx, 2), m3 = __shfl_xor_sync(0xffffffffu, mx, 3);
        mx = fmaxf(fmaxf(mx, m1), fmaxf(m2, m3));
      }
      const float mo = fmaf(mx, -cs, __uint_as_float(xo.x));
      auto ex = [&](int i) -> uint32_t { float x, y;
        asm volatile("ex2.approx.ftz.f32 %0, %1;" : "=f"(x) : "f"(fmaf(sc[i], cs, mo))); asm volatile("ex2.approx.ftz.f32 %0, %1;" : "=f"(y) : "f"(fmaf(sc[i + 1], cs, mo)));
        return pack_bf16(x, y); };
      float oa[4] = {0, 0, 0, 0}, ob[4] = {0, 0, 0, 0}, oc[4] = {0, 0, 0, 0}, od[4] = {0, 0, 0, 0}, rs[4] = {0, 0, 0, 0};
      const uint32_t ones = 0x3f803f80u;
      const uint32_t p4 = ex(8);
      if (MEMFIRST) { mma1688(rs, p4, 0u, ones); mma1688(oa, p4, 0u, vm0); mma1688(ob, p4, 0u, vm1); }
      const uint32_t p0 = ex(0), p1 = ex(2), p2 = ex(4), p3 = ex(6);
      TS(5);
      mma16816(rs, p0, p2, p1, p3, ones, ones);
      mma16816(oa, p0, p2, p1, p3, v0[0], v0[1]);
      mma16816(oc, p0, p2, p1, p3, v0[2], v0[3]);
      mma16816(ob, p0, p2, p1, p3, v1[0], v1[1]);
      mma16816(od, p0, p2, p1, p3, v1[2], v1[3]);
      if (!MEMFIRST) { mma1688(rs, p4, 0u, ones); mma1688(oa, p4, 0u, vm0); mma1688(ob, p4, 0u, vm1); }
      const float inv = rcpf(rs[0] + rs[2]) * __uint_as_float(xo.y);
      {
        const uint32_t y0 = pack_bf16((oa[0] + oc[2]) * inv, (oa[1] + oc[3]) * inv), y1 = pack_bf16((ob[0] + od[2]) * inv, (ob[1] + od[3]) * inv);
        st_async_v2_i<0>(xo.x + uo1, y0, y1, sb + MB_O + d1);
        st_async_v2_i<0>(xo.x + uo2, y0, y1, sb + MB_O + d2);
        sts64_i<OFF_O>(xo.x + (sb + hw * 256), y0, y1);
      }
      bar_arrive(B_O, 384);
      TS(6);
      if (hw == 0) bulk_wait<0>();
      mbar_expect_tx_if(n16 == 0 && hw == 3, sb + MB_S, 1280);
      n16 = fresh(n16);
      const int ln = n16 >> 4;
      auto mslot = [&](int c) -> uint32_t { return sb + OFF_MEM + c * 128 + (((ln >> 2) ^ (2 * (c & 3))) << 4); };
      const int lq = ln & 3;
      const uint32_t ma = mslot(cb28 + lq), mb_ = mslot(cb28 + (lq >> 1)) + (lq & 1) * 8;
      const unsigned char* gp = arena + (AR_ACC + acc_lane(hw, ln) + acc_step(s));
      const bool odd = ln & 1;
      const uint32_t delay = a.delay + ((hist & 2) ? a.margin : 0);
      SFENCE(ma);
      bar_sync(B_RED, 384);
      SFENCE(mb_);
      const uint32_t tw = clk_v();
      TSV(7, tw);
      mbar_expect_tx_if(n16 == 0 && hw == 3, sb + MB_O, 2048);
      while (clk_v() - tw < delay) {}
      TS(8);
      uint4 v[6];
      int spin = 0;
      const uint32_t cm = odd ? 0x5000u : 0u;
      do {
        static_for<0, 6>([&](auto I) { v[I.value] = ld_relaxed_v4_i<acc_voff(I.value)>(gp); });
      } while (__any_sync(0xffffffffu, (~((v[0].w & v[1].w & v[2].w) & (v[3].w & v[4].w & v[5].w)) & cm) != 0) && ++spin < SPIN_LIMIT);
      v[0].w = odd ? v[3].x : v[0].w; v[1].w = odd ? v[3].y : v[1].w; v[2].w = odd ? v[3].z : v[2].w; v[3].w = odd ? 0u : v[3].w;
      sts128_i<0>(ma, v[0].x, v[0].y, v[0].z, v[0].w);
      sts128_i<512>(ma, v[1].x, v[1].y, v[1].z, v[1].w);
      sts128_i<1024>(ma, v[2].x, v[2].y, v[2].z, v[2].w);
      sts128_i<0>(ma + du, v[4].x, v[4].y, v[4].z, v[5].z);
      sts64_i<512>(mb_ + du, v[5].x, v[5].y);
      if (!odd) sts128_i<1536>(mb_, v[3].x, v[3].y, v[3].z, v[3].w);
      hist = (hist * 2 + (spin != 0)) & 0xffffu;
      TSV(11, spin);
#ifdef TIMELINE
      if (spin && ln == 0) atomicAdd(&g_tl2[(a.tl >= 12) * 128 + 4], 1ull);
#endif
      TS(10);
      bar_sync(B_MEM0, 256); bar_sync(B_MEM1, 256);
      uint32_t m = lds32_i<SC_IN + 12>(sb);
      uint32_t m2 = m;
      static_for<0, 3>([&](auto I) { m = amax_h2(amax_h2(amax_h2(amax_h2(m, v[I.value].x), v[I.value].y), v[I.value].z), v[I.value].w); });
      static_for<3, 6>([&](auto I) { m2 = amax_h2(amax_h2(amax_h2(m2, v[I.value].x), v[I.value].y), v[I.value].z); });
      m = amax_fold(amax_h2(amax_h2(m2, v[3].w), m));
      if (n16 == 0) asm volatile("red.shared.max.u32 [%0], %1;" :: "r"(sb + SC_IN + 4 + 16 * ((s + 1) & 1)), "r"(m) : "memory");
    }
    bar_sync(B_RED, 384);
    if (hw == 0 && n16 == 0) {
      store_kv(cfg::NSEG - 1);
      bulk_wait<0>();
      st_relaxed_u32(arena + prog_off(h, j), cfg::NSEG);
    }
    __syncwarp();
#ifdef STEPCLK
    if (hw == 0 && n16 == 0) a.dbg[96 * 300 + cta * 2 + 1 + (hist >> 20)] = clk32();
#endif
#ifdef TIMELINE
    if (cta == 0 && hw == 0 && n16 == 0) { g_tl2[(a.tl >= 12) * 128 + 2] = clock64(); g_tl2[(a.tl >= 12) * 128 + 3] = gtime(); }
#endif
    TL_END(a.tl);
    asm volatile("barrier.cluster.arrive.relaxed.aligned; barrier.cluster.wait.aligned;" ::: "memory");
  } else {
    asm volatile("setmaxnreg.inc.sync.aligned.u32 232;");
    const int wi = warp & 3, hf = warp >> 2, tid = warp * 32 + lane;
    uint32_t w[40][4];
    uint32_t wqa;
    { const int mrow = r8 + ((lane >> 4) << 3), mch = 2 * wi + (m4 & 1); wqa = sb + mrow * 128 + ((mch ^ r8) << 4); }
    {
      const uint32_t wa = wqa + (hf ? OFF_WO : OFF_WQ);
      mbar_wait(sb + (hf ? MB_V : MB_K), 0);
      static_for<0, 20>([&](auto K) { ldsm_x4_t_i<K.value * 2048>(w[K.value], wa); });
      if (warp == 0) PT(1);
      bar_arrive(hf ? B_V : B_QK, 160);
      mbar_wait(sb + (hf ? MB_V : MB_K) + 8, 0);
      static_for<20, 40>([&](auto K) { ldsm_x4_t_i<K.value * 2048>(w[K.value], wa); });
      if (warp == 4) PT(2);
      bar_arrive(hf ? B_O : B_SL, 160);
      SFENCE(wa);
    }
    float iw, iq;
    {
      uint32_t m = 0;
#pragma unroll
      for (int k = 0; k < 40; k++) m = amax_bf2(amax_bf2(m, amax_bf2(w[k][0], w[k][1])), amax_bf2(w[k][2], w[k][3]));
      m = amax_fold(m);
      if (hf && lane == 0) asm volatile("red.shared.max.u32 [%0], %1;" :: "r"(sb + SC_W), "r"(m) : "memory");
      const int e = wscale_exp(m);
      const uint32_t sc = (uint32_t)(e + 127) * 0x00800080u; iw = exp2i(-e);
#pragma unroll
      for (int k = 0; k < 40; k++) { bf2_to_h2_inplace(w[k][0], sc); bf2_to_h2_inplace(w[k][1], sc); bf2_to_h2_inplace(w[k][2], sc); bf2_to_h2_inplace(w[k][3], sc); }
    }
    uint32_t x0[8];
    {
      float xa[16];
      const uint32_t dlo = (((sb + OFF_X) & 0x3FFFF) >> 4) | (1u << 16);
      if (warp == 0) PT(3);
      mbar_wait(sb + MB_X, 0);
      if (warp == 0) PT(4);
      wgmma_fence();
      static_for<0, 40>([&](auto K) { constexpr int k = K.value; wgmma_rs32h<((k >> 2) * 4096 + (k & 3) * 32) / 16, (k != 0)>(xa, w[k], dlo); });
      wgmma_commit();
      wgmma_wait<0>();
#pragma unroll
      for (int i = 0; i < 8; i++) x0[i] = pack_bf16(xa[2 * i] * iw, xa[2 * i + 1] * iw);
    }
    const bool t28 = j == 0 || warp < 4;
    const int bi = j == 0 ? hf : (warp < 4 ? j + 1 : 2 * (j - 1) + ((warp - 4) >> 1)), bv = t28 ? wi : 4 + (warp & 1);
    uint32_t wo1 = sb + OFF_WO + warp * 896 + lane * 16, wo2;
    {
      const int cb = (t28 ? unit28(bi) : unit24(bi)) - col0 / 8;
      uint32_t cp[4];
#pragma unroll
      for (int wd = 0; wd < 4; wd++) {
        int c, p;
        if (bv < 3) { c = 4 * bv + q4; p = wd; }
        else if (bv == 3) { if (q4 & 1) { c = 4 * (wd % 3) + q4; p = 3; } else { c = 12 + (q4 >> 1); p = wd; } }
        else if (bv == 4) { c = q4; p = wd; }
        else { if (wd < 2) { c = 4 + (q4 >> 1); p = 2 * (q4 & 1) + wd; } else { c = q4; p = 3; } }
        cp[wd] = sb + OFF_WO + ((g & 1) + (g & 2) * 4 + (g >> 2) * 2) * WOS + (cb + c) * 16 + p * 4;
      }
      const int cidx = (r8 & 1) + ((r8 >> 2) << 1);
      wo2 = sb + OFF_WO + warp * 896 + ((m4 & 1) ? 768 + (m4 >> 1) * 64 + cidx * 16 : 512 + (m4 >> 1) * 128 + r8 * 16);
      const bool dump = (m4 & 1) && (r8 & 2);
      uint32_t mo = 0;
      const bool regular = bv < 3 || bv == 4;
#pragma unroll 1
      for (int i = 0; i < 3; i++) {
        uint32_t x[4][4], y[4][4];
        const uint32_t o = i * 4 * WOK;
        mbar_wait(sb + MB_R + 8 * i, 0);
        if (warp == 0) PT(5 + i);
        if (regular) {
          static_for<0, 4>([&](auto K) {
            constexpr int kk = K.value;
            const uint4 u = lds128_i<kk * WOK>(cp[0] + o), v = lds128_i<kk * WOK + 4 * WOS>(cp[0] + o);
            x[kk][0] = u.x; x[kk][1] = u.y; x[kk][2] = u.z; x[kk][3] = u.w; y[kk][0] = v.x; y[kk][1] = v.y; y[kk][2] = v.z; y[kk][3] = v.w;
          });
        } else {
          static_for<0, 4>([&](auto K) {
            constexpr int kk = K.value;
#pragma unroll
            for (int wd = 0; wd < 4; wd++) { x[kk][wd] = lds32_i<kk * WOK>(cp[wd] + o); y[kk][wd] = lds32_i<kk * WOK + 4 * WOS>(cp[wd] + o); }
          });
        }
        bar_sync(B_C, 256);
        static_for<0, 4>([&](auto K) {
          constexpr int kk = K.value;
#pragma unroll
          for (int wd = 0; wd < 4; wd++) mo = amax_bf2(mo, amax_bf2(x[kk][wd], y[kk][wd]));
          stsm_x4_t_i<kk * WOK>(wo1 + o, x[kk][0], x[kk][1], y[kk][0], y[kk][1]);
          stsm_x4_t_i<0>(dump ? sb + OFF_S + 512 + lane * 16 : wo2 + o + kk * WOK, x[kk][2], x[kk][3], y[kk][2], y[kk][3]);
        });
      }
      if (warp == 0) PT(8);
      mo = amax_fold(mo);
      if (lane == 0) asm volatile("red.shared.max.u32 [%0], %1;" :: "r"(sb + SC_W + 4), "r"(mo) : "memory");
    }
    __syncwarp();
    auto run = [&](auto HF) {
    constexpr int hf = HF.value;
    uint32_t mema, sta, l16 = sb + lane * 16;
    uint32_t rq[hf ? NQ1 : NQ0][4];
    auto step_addr = [&](uint32_t kv) {
      const int lr = (l16 >> 4) & 7, lm = (l16 >> 7) & 3;
      mema = l16 ^ (lm << 5);
      sta = sb + lr * 16 + (lm < 2 ? OFF_Q + wi * 512 + hf * 128 + lm * 256 : OFF_KV + kv + 512 + (2 * wi + lm - 2) * 640);
    };
    auto x_gemm = [&](uint32_t ph, [[maybe_unused]] uint32_t tsb) {
      float xa[16];
      const uint32_t dlo = (((sb + OFF_X) & 0x3FFFF) >> 4) | (1u << 16);
      constexpr int NP = hf ? NQ1 : NP0;
      if constexpr (hf) {
        static_for<PQE, NP>([&](auto K) { ldsm_x4_t_i<OFF_WQ + K.value * 2048>(rq[K.value], wqa); });
        bar_sync(B_X, 256);
      }
      wgmma_fence();
      static_for<0, 40>([&](auto K) {
        constexpr int k = K.value;
        wgmma_rs32h<((k >> 2) * 4096 + (k & 3) * 32) / 16, (k != 0)>(xa, w[k], dlo);
        if constexpr (!hf && k == PFK && NP > PQE) { SFENCE(wqa); static_for<PQE, NP>([&](auto K) { ldsm_x4_t_i<OFF_WQ + K.value * 2048>(rq[K.value], wqa); }); SFENCE(wqa); }
        if constexpr (!hf && k == XT) bar_arrive(B_X, 256);
      });
      step_addr(ph * (2 * KVB));
      wgmma_commit();
      TS(9);
      wgmma_wait<0>();
      const uint32_t xs = l16 + (wi * 1280 + ph * (2 * KVB));
      stsm_x4_t_i<OFF_KV + hf * KVB>(xs, pack_bf16(xa[0] * iw, xa[1] * iw), pack_bf16(xa[4] * iw, xa[5] * iw), pack_bf16(xa[8] * iw, xa[9] * iw), pack_bf16(xa[12] * iw, xa[13] * iw));
      stsm_x4_t_i<OFF_KV + hf * KVB + 640>(xs, pack_bf16(xa[2] * iw, xa[3] * iw), pack_bf16(xa[6] * iw, xa[7] * iw), pack_bf16(xa[10] * iw, xa[11] * iw), pack_bf16(xa[14] * iw, xa[15] * iw));
    };
    auto wq_addr = [&](uint32_t l) -> uint32_t {
      const int lr = (l >> 4) & 7, lm = (l >> 7) & 3;
      return sb + hf * ((40 - NQ1) * 2048) + (lr + ((lm >> 1) << 3)) * 128 + (((2 * wi + (lm & 1)) ^ lr) << 4);
    };
    constexpr int NPM = hf ? NPM1 : NPM0;
    uint32_t u1[NPM][4], u2[NPM][4];
    static_for<0, NPM>([&](auto K) { ldsm_x4_i<(12 - NPM + K.value) * WOK>(u1[K.value], wo1); ldsm_x4_i<(12 - NPM + K.value) * WOK>(u2[K.value], wo2); });
    bar_sync(0, 384);
    iq = uniform_f(exp2i(-wscale_exp(lds32_i<SC_W + 8>(sb))));
    wqa = wq_addr(l16);
    static_for<0, (hf ? NQ1 : NP0)>([&](auto K) { ldsm_x4_t_i<OFF_WQ + K.value * 2048>(rq[K.value], wqa); });
    step_addr(0);
    stsm_x4_t_i<OFF_KV + hf * KVB>(l16 + wi * 1280, x0[0], x0[2], x0[4], x0[6]);
    stsm_x4_t_i<OFF_KV + hf * KVB + 640>(l16 + wi * 1280, x0[1], x0[3], x0[5], x0[7]);
    asm volatile("barrier.cluster.wait.aligned;" ::: "memory");
    TL_END(a.tl + 1);
#pragma unroll 1
    for (int s = 0; s < cfg::NSEG - 1; s++) {
      TS_SETUP();
#if CHAIN_TIMING
      if (tid == 0 && (s & 7) == 0) a.dbg[96 * 288 + cta * 8 + (s >> 3)] = clk32();
#endif
      bar_sync(hf ? B_MEM1 : B_MEM0, 256);
      const float sin_ = __uint_as_float(lds32_i<SC_IN>(sb + 16 * (s & 1)));
      constexpr int NPQ = (40 - NQ1) / 2;
      if constexpr (hf == 0) {
        float k0[4] = {0, 0, 0, 0}, k1[4] = {0, 0, 0, 0}, q0[4] = {0, 0, 0, 0}, q1[4] = {0, 0, 0, 0};
        constexpr auto pair_of = [](int t) { const int a = t * (20 - NPQ) / 20, b = (t + 1) * (20 - NPQ) / 20; return b > a ? NPQ + a : t - a; };
        uint32_t b[NB0][4];
        static_for<0, NB0>([&](auto T) { ldsm_x4_i<OFF_MEM + pair_of(T.value) * 512>(b[T.value], mema); });
        static_for<NP0, NQ0>([&](auto K) { ldsm_x4_t_i<OFF_WQ + K.value * 2048>(rq[K.value], wqa); });
        if (BBS < 100) bbfence<0>(mema);
        static_for<0, 20>([&](auto T) {
          constexpr int t = T.value, p = pair_of(t);
          uint32_t (&bb)[4] = b[t % NB0];
          if constexpr (p < NPQ) {
            mma16816h(q0, rq[(2 * p) % NQ0], bb[0], bb[1]);
            if constexpr (2 * p + NQ0 < 2 * NPQ) ldsm_x4_t_i<OFF_WQ + (2 * p + NQ0) * 2048>(rq[(2 * p) % NQ0], wqa);
          }
          mma16816h(k0, w[2 * p], bb[0], bb[1]);
          if constexpr (p < NPQ) {
            mma16816h(q1, rq[(2 * p + 1) % NQ0], bb[2], bb[3]);
            if constexpr (2 * p + 1 + NQ0 < 2 * NPQ) ldsm_x4_t_i<OFF_WQ + (2 * p + 1 + NQ0) * 2048>(rq[(2 * p + 1) % NQ0], wqa);
          }
          mma16816h(k1, w[2 * p + 1], bb[2], bb[3]);
          if constexpr (NVE > 0 && t + NB0 == VET) bar_arrive(B_E, 256);
          if constexpr (t + NB0 < 20) ldsm_x4_i<OFF_MEM + pair_of(t + NB0) * 512>(bb, mema);
          if constexpr (t < 20 - NB0 && (t % BBS) == BBS - 1) bbfence<t + 1>(mema);
        });
        const float sq = sin_ * iq, sk = sin_ * iw;
        stsm_x4_t_i<0>(sta, pack_bf16((q0[0] + q1[0]) * sq, (q0[1] + q1[1]) * sq), pack_bf16((q0[2] + q1[2]) * sq, (q0[3] + q1[3]) * sq),
                       pack_bf16((k0[0] + k1[0]) * sk, (k0[1] + k1[1]) * sk), pack_bf16((k0[2] + k1[2]) * sk, (k0[3] + k1[3]) * sk));
        bar_sync(B_QK, 384);
        SFENCE(l16);
        [[maybe_unused]] const uint32_t tq = GD0 < 0 ? 0 : clk_v();
        TS(2);
        {
          if (wi == 3) {
            const uint32_t xr = sb + ((l16 & 511) >> 2), ka = l16 + (l16 & 384) * 4 + (s & 1) * (2 * KVB);
            uint32_t a0[4], a1[4], a2[4], a3[4], kb0[4], kb1[4];
            ldsm_x4_i<OFF_Q>(a0, l16); ldsm_x4_i<OFF_KV + 512>(kb0, ka); ldsm_x4_i<OFF_Q + 1024>(a2, l16); ldsm_x4_i<OFF_KV + 512 + 2560>(kb1, ka);
            ldsm_x4_i<OFF_Q + 512>(a1, l16);
            bar_arrive(B_A, 288);
            ldsm_x4_i<OFF_Q + 1536>(a3, l16);
            float sa[4] = {0, 0, 0, 0}, sc2[4] = {0, 0, 0, 0};
            mma16816(sa, a0[0], a0[1], a0[2], a0[3], kb0[0], kb0[1]);
            mma16816(sc2, a2[0], a2[1], a2[2], a2[3], kb1[0], kb1[1]);
            mma16816(sa, a1[0], a1[1], a1[2], a1[3], kb0[2], kb0[3]);
            mma16816(sc2, a3[0], a3[1], a3[2], a3[3], kb1[2], kb1[3]);
            const float x0 = (sa[0] + sa[2]) + (sc2[0] + sc2[2]), x1 = (sa[1] + sa[3]) + (sc2[1] + sc2[3]);
            const uint32_t xp = pack_bf16(x0, x1);
            st_async_b32_i<OFF_SR + 1024 + 128>(xr + d1, xp, sb + MB_S + d1);
            st_async_b32_i<OFF_SR + 1024>(xr + d2, xp, sb + MB_S + d2);
            stsm_x2(l16 + OFF_S + 1024, __float_as_uint(x0), __float_as_uint(x1));
          } else if (wi == 0) {
            const uint4 si = lds128_i<SC_IN>(sb + 16 * (s & 1));
            const int em = (int)(si.y >> 10) - 14 + (int)(si.x >> 23) - 127;
            const uint32_t osc = __float_as_uint(exp2i(max(min((int)si.z - max(em, 1), 100), -100)));
            sts32(l16 + OFF_LT + 12, osc); sts64_i<SC_IN>(sb + 16 * ((s + 1) & 1), 0x7f000000u - osc, 0u);
          }
          if (GD0 < 0) bar_sync(B_SL, 256);
          else { bar_arrive(B_SL, 256); while (clk_v() - tq < GD0) {} }
        }
      } else {
        float v0[4] = {0, 0, 0, 0}, v1[4] = {0, 0, 0, 0}, q0[4] = {0, 0, 0, 0}, q1[4] = {0, 0, 0, 0};
        uint32_t b[NQ1 / 2][4];
        static_for<0, NQ1 / 2>([&](auto T) { ldsm_x4_i<OFF_MEM + (NPQ + T.value) * 512>(b[T.value], mema); });
        static_for<0, NQ1 / 2>([&](auto T) {
          constexpr int t = T.value, p = NPQ + t;
          uint32_t (&bb)[4] = b[t];
          mma16816h(q0, rq[2 * t], bb[0], bb[1]);
          mma16816h(q1, rq[2 * t + 1], bb[2], bb[3]);
          mma16816h(v0, w[2 * p], bb[0], bb[1]);
          mma16816h(v1, w[2 * p + 1], bb[2], bb[3]);
        });
        const float sq = sin_ * iq, sv = sin_ * iw;
        stsm_x2_t_i<0>(sta, pack_bf16((q0[0] + q1[0]) * sq, (q0[1] + q1[1]) * sq), pack_bf16((q0[2] + q1[2]) * sq, (q0[3] + q1[3]) * sq));
        TS(2);
        bar_arrive(B_QK, 384);
        float v2[4] = {0, 0, 0, 0}, v3[4] = {0, 0, 0, 0};
        auto vpair = [&](auto P, uint32_t (&bb)[4]) {
          constexpr int p = P.value;
          if constexpr (p & 1) { mma16816h(v0, w[2 * p], bb[0], bb[1]); mma16816h(v1, w[2 * p + 1], bb[2], bb[3]); }
          else { mma16816h(v2, w[2 * p], bb[0], bb[1]); mma16816h(v3, w[2 * p + 1], bb[2], bb[3]); }
        };
        if constexpr (NVE > 0) {
          uint32_t e[NVE ? NVE : 1][4];
          bar_sync(B_E, 256);
          static_for<0, NVE>([&](auto T) { ldsm_x4_i<OFF_MEM + T.value * 512>(e[T.value], mema); });
          static_for<0, NVE>([&](auto T) { vpair(T, e[T.value]); });
        }
        bar_sync(B_A, 288);
        uint32_t c[4][4];
        static_for<NVE, NVE + 4>([&](auto T) { ldsm_x4_i<OFF_MEM + T.value * 512>(c[T.value & 3], mema); });
        static_for<NVE, NPQ>([&](auto T) {
          constexpr int p = T.value;
          vpair(T, c[p & 3]);
          if constexpr (p + 4 < NPQ) ldsm_x4_i<OFF_MEM + (p + 4) * 512>(c[p & 3], mema);
        });
        stsm_x2_t_i<OFF_KV + KVB + 512>(l16 + (l16 & 128) * 4 + (wi * 1280 + (s & 1) * (2 * KVB)), pack_bf16(((v0[0] + v1[0]) + (v2[0] + v3[0])) * sv, ((v0[1] + v1[1]) + (v2[1] + v3[1])) * sv),
                            pack_bf16(((v0[2] + v1[2]) + (v2[2] + v3[2])) * sv, ((v0[3] + v1[3]) + (v2[3] + v3[3])) * sv));
        bar_arrive(B_V, 256);
      }
      TS(3);
      {
        uint32_t t1[12][4], t2[12][4];
        const uint32_t o16 = l16;
        wo1 = l16 + (OFF_WO + warp * 896);
        wo2 = sb + OFF_WO + warp * 896 + ((l16 & 128) ? 768 + ((l16 & 256) >> 2) + (l16 & 16) + ((l16 & 64) >> 1) : 512 + ((l16 & 256) >> 1) + (l16 & 112));
        auto ldw = [&](auto K) { if constexpr (K.value < 12 - NPM) { ldsm_x4_i<K.value * WOK>(t1[K.value], wo1); ldsm_x4_i<K.value * WOK>(t2[K.value], wo2); } };
        constexpr int NR_ = NRT - NPM;
        constexpr int PB = (hf ? PB1 : PB0) < NR_ ? (hf ? PB1 : PB0) : NR_, PA = (hf ? PA1 : PA0) < PB ? (hf ? PA1 : PA0) : PB;
        static_for<0, PA>(ldw);
        mbar_spin(sb + MB_X, (s + 1) & 1);
        if constexpr (PB > PA) {
          constexpr int PM = PA + PM1 < PB ? PA + PM1 : PB;
          mbar_spin(sb + MB_S, s & 1);
          const uint32_t t0 = clk_v();
          if constexpr (PM > PA) { while (clk_v() - t0 < GD1) {} static_for<PA, PM>(ldw); }
          if constexpr (PB > PM) { while (clk_v() - t0 < GD2) {} static_for<PM, PB>(ldw); }
        }
        float c0[4] = {0, 0, 0, 0}, c1[4] = {0, 0, 0, 0}, e0[4] = {0, 0, 0, 0}, e1[4] = {0, 0, 0, 0};
        uint32_t ob[6][4];
        auto kstep = [&](auto K) {
          constexpr int k = K.value;
          uint32_t (&bb)[4] = ob[k >> 1];
          uint32_t (&x)[4] = k < 12 - NPM ? t1[k] : u1[k < 12 - NPM ? 0 : k - (12 - NPM)];
          uint32_t (&y)[4] = k < 12 - NPM ? t2[k] : u2[k < 12 - NPM ? 0 : k - (12 - NPM)];
          if constexpr (k & 1) { mma16816(c1, x[0], x[1], x[2], x[3], bb[2], bb[3]); mma16816(e1, y[0], y[1], y[2], y[3], bb[2], bb[3]); }
          else { mma16816(c0, x[0], x[1], x[2], x[3], bb[0], bb[1]); mma16816(e0, y[0], y[1], y[2], y[3], bb[0], bb[1]); }
          if constexpr (k >= NRF) ldw(IC<k + NR_ - NRF>{});
        };
        auto ldo = [&](auto P) { ldsm_x4_i<OFF_O + P.value * 512>(ob[P.value], o16); };
        TS(4);
        bar_sync(B_O, 384);
        ldo(IC<0>{}); ldo(IC<1>{});
        SFENCE(o16);
        static_for<PB, NR_>(ldw);
        static_for<0, 4>(kstep);
        TS(5);
        mbar_spin(sb + MB_O, s & 1);
        TS(6);
        ldo(IC<2>{}); ldo(IC<NPM >= 2 ? 5 : 3>{});
        if (WOF) SFENCE(o16);
        kstep(IC<4>{});
        if constexpr (NPM < 2) { kstep(IC<5>{}); ldo(IC<4>{}); kstep(IC<6>{}); kstep(IC<7>{}); ldo(IC<5>{}); static_for<8, 12>(kstep); }
        else if constexpr (NPM >= 4) { kstep(IC<10>{}); kstep(IC<11>{}); ldo(IC<4>{}); kstep(IC<5>{}); ldo(IC<3>{}); kstep(IC<8>{}); kstep(IC<9>{}); kstep(IC<6>{}); kstep(IC<7>{}); }
        else { kstep(IC<5>{}); ldo(IC<3>{}); kstep(IC<11>{}); kstep(IC<10>{}); ldo(IC<4>{}); kstep(IC<6>{}); kstep(IC<7>{}); if constexpr (NPM == 3) { kstep(IC<9>{}); kstep(IC<8>{}); } else { kstep(IC<8>{}); kstep(IC<9>{}); } }
        l16 = fresh(l16);
        const int ln = (l16 >> 4) & 31;
        if constexpr (CEARLY && hf) { SFENCE2(o16, __float_as_uint(e1[0])); bar_arrive(B_G, 256); }
        unsigned char* gr = arena + (AR_ACC + acc_lane(bi, ln) + acc_voff(bv) + acc_step(s));
        const bool cnt = (ln & 1) || !t28;
        wqa = wq_addr(l16);
        SFENCE(o16);
        static_for<0, PQE>([&](auto K) { ldsm_x4_t_i<OFF_WQ + K.value * 2048>(rq[K.value], wqa); });
        const uint32_t y0 = movm_t(pack_f16(c0[0] + c1[0], c0[1] + c1[1])), y1 = movm_t(pack_f16(c0[2] + c1[2], c0[3] + c1[3]));
        const uint32_t y2 = movm_t(pack_f16(e0[0] + e1[0], e0[1] + e1[1])), y3 = movm_t(pack_f16(e0[2] + e1[2], e0[3] + e1[3]));
        asm volatile("red.relaxed.gpu.global.add.noftz.v4.f16x2 [%0], {%1,%2,%3,%4};" :: "l"(gr), "r"(y0), "r"(y1), "r"(y2), "r"(cnt ? 0x3c00u : y3) : "memory");
        bar_arrive(B_RED, 384);
        if constexpr (CEARLY && !hf) { bar_arrive(B_C, 256); bar_sync(B_G, 256); }
        else bar_sync(B_C, 256);
        TS(7);
      }
#if CHAIN_TIMING
      x_gemm((s + 1) & 1, tsb);
#else
      x_gemm((s + 1) & 1, 0);
#endif
      TS(8);
    }
    };
    if (hf == 0) run(IC<0>{}); else run(IC<1>{});
    {
      const uint32_t l16 = sb + (threadIdx.x & 31) * 16, mema = l16 ^ ((l16 >> 2) & 96);
      float c0[4] = {0, 0, 0, 0}, c1[4] = {0, 0, 0, 0}, c2[4] = {0, 0, 0, 0}, c3[4] = {0, 0, 0, 0};
      bar_sync(hf ? B_MEM1 : B_MEM0, 256);
      const float sc = __uint_as_float(lds32_i<SC_IN + 16>(sb)) * iw;
      static_for<0, 10>([&](auto T) {
        constexpr int p = 2 * T.value;
        uint32_t b0[4], b1[4];
        ldsm_x4_i<OFF_MEM + p * 512>(b0, mema); ldsm_x4_i<OFF_MEM + p * 512 + 512>(b1, mema);
        mma16816h(c0, w[2 * p], b0[0], b0[1]); mma16816h(c1, w[2 * p + 1], b0[2], b0[3]);
        mma16816h(c2, w[2 * p + 2], b1[0], b1[1]); mma16816h(c3, w[2 * p + 3], b1[2], b1[3]);
      });
      stsm_x2_t_i<OFF_KV + 2 * KVB + 512>(l16 + (l16 & 128) * 4 + wi * 1280 + hf * KVB, pack_bf16(((c0[0] + c1[0]) + (c2[0] + c3[0])) * sc, ((c0[1] + c1[1]) + (c2[1] + c3[1])) * sc),
                                          pack_bf16(((c0[2] + c1[2]) + (c2[2] + c3[2])) * sc, ((c0[3] + c1[3]) + (c2[3] + c3[3])) * sc));
    }
    bar_arrive(B_RED, 384);
#if CHAIN_TIMING
    for (int i = tid; i < 288; i += 256) a.dbg[cta * 288 + i] = lds32_i<OFF_BAR + 128>(sb + i * 4);
#endif
    asm volatile("barrier.cluster.arrive.relaxed.aligned; barrier.cluster.wait.aligned;" ::: "memory");
  }
}
struct PrepArgs { const bf16 *wqkv, *wphi, *wo; unsigned char *wb, *wot; };
__device__ __forceinline__ void prep_body(const int cta, const PrepArgs& pa) {
  const int tid = threadIdx.x, lane = tid & 31, warp = tid >> 5, g = lane >> 2, q = lane & 3;
  const int pair = cta >> 1, which = cta & 1;
  uint32_t af[5][2][6];
#pragma unroll
  for (int i = 0; i < 5; i++)
#pragma unroll
    for (int hh = 0; hh < 2; hh++) {
      const uint32_t* r0 = (const uint32_t*)(pa.wqkv + (size_t)((warp * 5 + i) * 16 + g) * 1920 + which * 640 + (2 * pair + hh) * 20) + q;
      const uint32_t* r1 = r0 + 8 * 960;
      af[i][hh][0] = __ldg(r0); af[i][hh][1] = __ldg(r1); af[i][hh][2] = __ldg(r0 + 4); af[i][hh][3] = __ldg(r1 + 4);
      af[i][hh][4] = q < 2 ? __ldg(r0 + 8) : 0u; af[i][hh][5] = q < 2 ? __ldg(r1 + 8) : 0u;
    }
  uint32_t bfr[2][3][3];
#pragma unroll
  for (int hh = 0; hh < 2; hh++)
#pragma unroll
    for (int t = 0; t < 3; t++) {
      const bool on = t < 2 || (g & 1) == hh;
      const unsigned short* ph = (const unsigned short*)pa.wphi + (2 * pair + hh) * 400 + (t < 2 ? 8 * t + g : 16 + (g >> 1)) + 2 * q * 20;
#pragma unroll
      for (int r = 0; r < 3; r++) bfr[hh][t][r] = (on && (r < 2 || q < 2)) ? (uint32_t)__ldg(ph + r * 160) | ((uint32_t)__ldg(ph + r * 160 + 20) << 16) : 0u;
    }
  const int gt = cta * 256 + tid;
#pragma unroll 3
  for (int i = gt; i < 640 * 32; i += 8192) {
    const int k = (i & 7) + (i >> 8) * 8, h = (i >> 3) & 31;
    const uint2* src = (const uint2*)(pa.wqkv + (size_t)k * 1920 + 1280 + h * 20);
    const uint2 a = __ldg(src), b = __ldg(src + 1), c = __ldg(src + 2), d = __ldg(src + 3), e = __ldg(src + 4);
    uint4* dst = (uint4*)(pa.wb + ((size_t)((h >> 2) * 80 + (k >> 3)) * 32 + 20 + 3 * (h & 3)) * 128 + (k & 7) * 16);
    dst[0] = make_uint4(a.x, a.y, b.x, b.y); dst[8] = make_uint4(c.x, c.y, d.x, d.y);
    dst[16] = (h & 1) ? make_uint4(0, 0, e.x, e.y) : make_uint4(e.x, e.y, 0, 0);
  }
#pragma unroll 7
  for (int i = gt; i < 640 * 80; i += 8192) {
    const int r = i & 7, c = (i >> 3) % 80, kg = i / 640, c5 = kg % 5;
    const int row = (kg / 5) * 40 + (c5 < 2 ? 8 * c5 + r : (c5 == 2 ? 16 + (r & 3) + (r >> 2) * 20 : 20 + 8 * (c5 - 3) + r));
    *(uint4*)(pa.wot + ((size_t)((c / 10) * 80 + kg) * 10 + c % 10) * 128 + r * 16) = __ldg((const uint4*)(pa.wo + (size_t)row * cfg::DM + c * 8));
  }
#pragma unroll
  for (int i = 0; i < 5; i++) {
    uint32_t* dst = (uint32_t*)(pa.wb + ((size_t)((pair >> 1) * 80 + (warp * 5 + i) * 2) * 32 + which * 10 + (pair & 1) * 5) * 128) + lane;
#pragma unroll
    for (int t = 0; t < 5; t++) {
      float d[4] = {0, 0, 0, 0};
#pragma unroll
      for (int hh = 0; hh < 2; hh++)
        if (t == 2 || (t > 2) == (hh == 1)) {
          const int tt = t < 3 ? t : t - 3;
          mma16816(d, af[i][hh][0], af[i][hh][1], af[i][hh][2], af[i][hh][3], bfr[hh][tt][0], bfr[hh][tt][1]);
          mma1688(d, af[i][hh][4], af[i][hh][5], bfr[hh][tt][2]);
        }
      dst[t * 32] = pack_bf16(d[0], d[1]); dst[1024 + t * 32] = pack_bf16(d[2], d[3]);
    }
  }
}

__global__ void __launch_bounds__(256, 4) ln_kernel(const bf16* __restrict__ xin, bf16* __restrict__ xn, uint2* __restrict__ xh, uint4* __restrict__ z0, int n0,
                                                    uint4* __restrict__ z1, int n1, const bf16* pfa, const bf16* pfb, int npf, int tl) {
  asm volatile("griddepcontrol.wait;" ::: "memory");
  asm volatile("griddepcontrol.launch_dependents;" ::: "memory");
  TL_BEGIN(tl);
  const int warp = threadIdx.x >> 5, lane = threadIdx.x & 31;
  const int row = blockIdx.x * 8 + warp;
  uint2 xw[1][5];
#pragma unroll
  for (int i = 0; i < 5; i++) xw[0][i] = *(const uint2*)(xin + (size_t)row * cfg::DM + i * 128 + lane * 4);
  for (int i = blockIdx.x * 256 + threadIdx.x; i < n0; i += 256 * 256) z0[i] = make_uint4(0, 0, 0, 0);
  for (int i = blockIdx.x * 256 + threadIdx.x; i < n1; i += 256 * 256) z1[i] = make_uint4(0, 0, 0, 0);
  if (npf && xw[0][4].y != 0x7fc17fc1u) {
    for (int i = 0; i < npf; i++) {
      const uint32_t l = (uint32_t)i * 32768u + (blockIdx.x * 256 + threadIdx.x) / 2;
      if (l < cfg::DM * cfg::HD / 64) asm volatile("prefetch.global.L2 [%0];" :: "l"(((threadIdx.x & 1) ? pfa : pfb) + (size_t)l * 64) : "memory");
    }
  }
  ln_rows<1>(xw, row, lane, xn, xh);
  TL_END(tl);
}
struct Pipe { uint32_t stage, phase; };
template <int NS> __device__ __forceinline__ void pipe_adv(Pipe& p) { if (++p.stage == NS) { p.stage = 0; p.phase ^= 1; } }
constexpr uint32_t SWZ128 = 1;
__device__ __forceinline__ uint64_t desc_kmajor(uint32_t a) { return make_desc(a, 16, 1024, SWZ128); }
__device__ __forceinline__ uint64_t desc_mnmajor(uint32_t a) { return make_desc(a, 8192, 1024, SWZ128); }
__device__ __forceinline__ void wait_ge(const void* p, uint32_t target, uint32_t ns = 32) {
  int spin = 0;
  while (ld_acquire_u32(p) < target) { __nanosleep(ns); if (++spin > (1 << 21)) break; }
}
__device__ __forceinline__ void bulk_g2s_hint(uint32_t dst, const void* src, uint32_t bytes, uint32_t mb, uint64_t pol) {
  asm volatile("cp.async.bulk.shared::cluster.global.mbarrier::complete_tx::bytes.L2::cache_hint [%0], [%1], %2, [%3], %4;"
               :: "r"(dst), "l"(src), "r"(bytes), "r"(mb), "l"(pol) : "memory");
}
#ifndef PF_WB
#define PF_WB 2
#endif
#ifndef PF_XN
#define PF_XN 1
#endif
#ifndef STAG
#define STAG 1
#endif
#ifndef EF_KV
#define EF_KV 1
#endif
#ifndef EF_O
#define EF_O 1
#endif
__device__ __forceinline__ void fence_proxy_async_global() { asm volatile("fence.proxy.async.global;" ::: "memory"); }

namespace tr {
constexpr int NS = 4, STQ = 16384 + 24576, STO = 16384 + 40960;
constexpr int SEGB = 15360;
constexpr int OFF_K = NS * STQ;
constexpr int OFF_BAR = NS * STO;
constexpr int SMEM = OFF_BAR + 256;
static_assert(OFF_K + 4 * SEGB <= OFF_BAR && SMEM <= 232448, "smem");
enum { T_QA = 0, T_Q, T_A, T_OB, T_OS, T_L, T_END, T_P };
constexpr uint32_t C_QA = AR_CNT, C_O = AR_CNT + 64, C_Q = AR_CNT + 128, C_P = AR_CNT + 192;
constexpr int MAXITEMS = 1200;
struct Sched {
  uint8_t ks[16];
  uint8_t wide[16];
  uint8_t lrows[16];
  uint32_t n;
  uint16_t item[MAXITEMS];
};
struct Args {
  const unsigned char *kg, *vg;
  unsigned char* o;
  uint4* qs;
  unsigned char* part;
  const bf16 *xin, *xq;
  bf16 *xout, *xn;
  unsigned char* arena;
  const unsigned* go;
  int tl;
  uint32_t nap, nap2;
};
}

template <int N0, int N1>
__device__ __forceinline__ void tr_mainloop(float (&a0)[N0 / 2], float (&a1)[N1 ? N1 / 2 : 1], Pipe& p, uint32_t sb, uint32_t full, uint32_t empty, int nkb, int wg) {
  using namespace tr;
  constexpr uint32_t ST = N1 ? STO : STQ;
  uint32_t prev = 0;
#pragma unroll
  for (int i = 0; i < N0 / 2; i++) a0[i] = 0.f;
  if constexpr (N1 > 0) {
#pragma unroll
    for (int i = 0; i < N1 / 2; i++) a1[i] = 0.f;
  }
#pragma unroll 1
  for (int kb = 0; kb < nkb; kb++) {
    mbar_wait(full + 8 * p.stage, p.phase);
    const uint32_t st = sb + p.stage * ST;
    wgmma_fence();
#pragma unroll
    for (int kk = 0; kk < 4; kk++) {
      const uint64_t da = desc_kmajor(st + wg * 8192 + kk * 32);
      if constexpr (N0 == 192) wgmma_n192<0, 1>(a0, da, desc_mnmajor(st + 16384 + kk * 2048), (kb | kk) != 0);
      else wgmma_n128<0, 1>(a0, da, desc_mnmajor(st + 16384 + kk * 2048), (kb | kk) != 0);
      if constexpr (N1 > 0) wgmma_n128<0, 1>(a1, da, desc_mnmajor(st + 16384 + 24576 + kk * 2048), (kb | kk) != 0);
    }
    wgmma_commit();
    if (kb > 0) { wgmma_wait<1>(); mbar_arrive_if((threadIdx.x & 127) == 0, empty + 8 * prev); }
    prev = p.stage;
    pipe_adv<NS>(p);
  }
  wgmma_wait<0>();
  mbar_arrive_if((threadIdx.x & 127) == 0, empty + 8 * prev);
}
template <int N> __device__ __forceinline__ void stage_tiles(const float (&o)[N / 2], uint32_t base, int wi, int lane) {
  const uint32_t ra = base + (wi * 16 + (lane & 7) + 8 * ((lane >> 3) & 1)) * 128;
#pragma unroll
  for (int v = 0; v < N / 8; v += 2)
    stsm_x4(ra + (v >> 3) * 8192 + ((((v & 7) + (lane >> 4)) ^ (lane & 7)) << 4), pack_bf16(o[4 * v], o[4 * v + 1]), pack_bf16(o[4 * v + 2], o[4 * v + 3]),
            pack_bf16(o[4 * v + 4], o[4 * v + 5]), pack_bf16(o[4 * v + 6], o[4 * v + 7]));
}
__global__ void __launch_bounds__(384, 1) trail_kernel(const __grid_constant__ CUtensorMap tmX, const __grid_constant__ CUtensorMap tmQ,
                                                       const __grid_constant__ CUtensorMap tmWo5, const __grid_constant__ CUtensorMap tmWo2,
                                                       const __grid_constant__ CUtensorMap tmP, const __grid_constant__ tr::Sched sc,
                                                       const __grid_constant__ tr::Args a, const __grid_constant__ PrepArgs pa) {
  using namespace tr;
  [[maybe_unused]] const int tl = a.tl;
  TL_BEGIN(tl);
  extern __shared__ __align__(1024) unsigned char smem_raw[];
  const uint32_t sb = smem_u32(smem_raw);
  const int warp = __shfl_sync(0xffffffffu, (int)threadIdx.x >> 5, 0), lane = threadIdx.x & 31;
  unsigned char* const arena = a.arena;
  const uint32_t full = sb + OFF_BAR, empty = full + 8 * NS, barK = empty + 8 * NS, barKfree = barK + 16, staged = barKfree + 16;
  const uint32_t kvrdy = staged + 32, mfull = kvrdy + 8, mempty = mfull + 16, mbox = mempty + 16;
  uint32_t go = 0;
  if (threadIdx.x == 256) go = ld_acquire_u32(a.go);
  if (threadIdx.x == 0) {
    for (int i = 0; i < NS; i++) { mbar_init(full + 8 * i, 1); mbar_init(empty + 8 * i, 2); }
    for (int i = 0; i < 2; i++) {
      mbar_init(barK + 8 * i, 1); mbar_init(barKfree + 8 * i, 1); mbar_init(staged + 16 * i, 4); mbar_init(staged + 16 * i + 8, 4);
      mbar_init(mfull + 8 * i, 1); mbar_init(mempty + 8 * i, 11);
    }
    mbar_init(kvrdy, 1);
    asm volatile("fence.mbarrier_init.release.cluster;" ::: "memory");
  }
  __syncthreads();
  Pipe mp{0, 0};
  auto next_item = [&]() -> uint32_t {
    uint32_t it;
    mbar_wait(mfull + 8 * mp.stage, mp.phase);
    asm volatile("ld.shared.u32 %0, [%1];" : "=r"(it) : "r"(mbox + 4 * mp.stage) : "memory");
    return it;
  };
  if (warp >= 8) {
    asm volatile("setmaxnreg.dec.sync.aligned.u32 40;");
    if (warp == 8) { go = __shfl_sync(0xffffffffu, go, 0); if (elect_one()) {
      Pipe p{0, 1};
      mp.phase = 1;
      uint32_t kph = 1, rph = 0, wide = 0, qdone = 0;
      prefetch_tmap(&tmX); prefetch_tmap(&tmQ); prefetch_tmap(&tmWo5); prefetch_tmap(&tmWo2); prefetch_tmap(&tmP);
      const uint64_t ef = policy_evict_first();
      auto ld_kv = [&](uint32_t d, const void* s, uint32_t n, uint32_t mb) { if (EF_KV) bulk_g2s_hint(d, s, n, mb, ef); else bulk_g2s(d, s, n, mb); };
      auto ld_o = [&](uint32_t d, const void* s, uint32_t n, uint32_t mb) { if (EF_O) bulk_g2s_hint(d, s, n, mb, ef); else bulk_g2s(d, s, n, mb); };
      auto stage = [&](uint32_t bytes) -> uint32_t {
        mbar_wait(empty + 8 * p.stage, p.phase);
        mbar_expect_tx(full + 8 * p.stage, bytes);
        return sb + p.stage * (wide ? STO : STQ);
      };
      auto fetch = [&]() -> uint32_t { uint32_t v; asm volatile("atom.relaxed.gpu.global.add.u32 %0, [%1], 1;" : "=r"(v) : "l"(arena + AR_QUEUE) : "memory"); return v; };
      if (!go) wait_ge(a.go, 1, 200);
      fence_proxy_async_global();
      uint32_t next = fetch();
      while (true) {
        const uint32_t item = next;
        const uint32_t code = sc.item[min(item, sc.n)];
        const int type = code >> 11, m = (code >> 7) & 15, k = code & 127;
        if (type == T_A && !((qdone >> m) & 1)) { wait_ge(arena + C_Q + m * 4, 64); qdone |= 1u << m; }
        if (type == T_OB && !wide) for (uint32_t i = 0; i < NS; i++) mbar_wait(empty + 8 * i, i >= p.stage ? p.phase : p.phase ^ 1);
        wide = type == T_OB;
        mbar_wait(mempty + 8 * mp.stage, mp.phase);
        asm volatile("st.shared.u32 [%0], %1;" :: "r"(mbox + 4 * mp.stage), "r"((p.stage << 24) | (type << 16) | (m << 8) | (k & 255)) : "memory");
        mbar_arrive(mfull + 8 * mp.stage);
        pipe_adv<2>(mp);
        if (type == T_END) break;
        if (type == T_P) { next = fetch(); continue; }
        if (type == T_L) {
          const int nr = sc.lrows[m], np = sc.ks[m];
          prefetch_l2(a.xin + (size_t)(m * 128 + k * 8 * nr) * cfg::DM, nr * 10240);
          wait_ge(arena + C_O + m * 4, np * (sc.wide[m] ? 4 : 10), m < 13 ? a.nap : 32);
          fence_proxy_async_global();
#pragma unroll 1
          for (int r = 0; r < nr; r++) {
            const int rg = m * 16 + k * nr + r;
#pragma unroll 1
            for (int q0 = 0; q0 <= np; q0 += 4) {
              const int n = min(4, np + 1 - q0);
              const uint32_t st = stage(n * 10240), fb = full + 8 * p.stage;
#pragma unroll 1
              for (int q = q0; q < q0 + n; q++) {
                if (q == 0) bulk_g2s(st, a.xin + (size_t)rg * 8 * cfg::DM, 10240, fb);
                else tma_load_3d(st + (q - q0) * 10240, &tmP, 0, rg & 7, ((q - 1) * 32 + (rg >> 3)) * 10, fb);
              }
              pipe_adv<NS>(p);
            }
          }
          next = fetch(); continue;
        }
        if (type <= T_A) {
          if (type != T_A)
#pragma unroll 1
            for (int kb = 0; kb < 10; kb++) {
              const uint32_t st = stage(STQ), fb = full + 8 * p.stage;
              tma_load_2d(st, &tmX, kb * 64, m * 128, fb);
              tma_load_3d(st + 16384, &tmQ, 0, kb * 64, k * 3, fb);
              pipe_adv<NS>(p);
              if (type == T_Q && kb == 8) next = fetch();
            }
          if (type != T_Q) {
            const size_t blk = ((size_t)m * 4 * 96 + k * 3) * 5120;
            kph ^= 1;
            mbar_wait(kvrdy, rph); rph ^= 1;
            next = fetch();
            fence_proxy_async_global();
#pragma unroll 1
            for (int w = type == T_A ? 0 : 2; w < 4; w++) {
              const uint32_t st = stage(2 * SEGB), fb = full + 8 * p.stage;
              for (int sg = 0; sg < 2; sg++) ld_kv(st + sg * SEGB, (w < 2 ? a.kg : a.vg) + blk + (size_t)(2 * (w & 1) + sg) * (96 * 5120), SEGB, fb);
              pipe_adv<NS>(p);
            }
          }
        } else {
          const int nn = wide ? 2 : 5, nb = wide ? 5 : 2, nt = k % nn, nkb = 96 / sc.ks[m], k0 = (k / nn) * nkb;
          const Pipe p0 = p;
          for (int kb = 0; kb < nkb; kb++) {
            if (wide && kb < NS && p.stage >= 2) { mbar_wait(barKfree, kph); mbar_wait(barKfree + 8, kph); }
            const uint32_t st = stage(16384 + nb * 8192), fb = full + 8 * p.stage;
            tma_load_3d(st + 16384, wide ? &tmWo5 : &tmWo2, 0, (k0 + kb) * 64, nt * nb, fb);
            if (kb >= NS) ld_o(st, a.o + ((size_t)m * 96 + k0 + kb) * 16384, 16384, fb);
            pipe_adv<NS>(p);
            if (kb == NS - 1 || (kb == nkb - 1 && nkb < NS)) {
              wait_ge(arena + C_QA + m * 4, 64, m < 14 ? a.nap : 32);
              fence_proxy_async_global();
              Pipe q = p0;
#pragma unroll 1
              for (int i = 0; i <= kb; i++) { ld_o(sb + q.stage * (wide ? STO : STQ), a.o + ((size_t)m * 96 + k0 + i) * 16384, 16384, full + 8 * q.stage); pipe_adv<NS>(q); }
            }
          }
          next = fetch();
          for (int w = wide ? -(int)((2 - p.stage) & 3) : 0; w < 2; w++) { mbar_wait(empty + 8 * p.stage, p.phase); mbar_arrive(full + 8 * p.stage); pipe_adv<NS>(p); }
          kph ^= wide;
        }
      }
    } } else if (warp < 11) { if (elect_one()) {
      const int w = warp - 9;
      uint32_t sph = 0;
      [[maybe_unused]] int nlog = 0;
#ifdef TIMELINE
      if (w == 0) { unsigned long long* lg = g_log + (((tl >= 12) * 132 + blockIdx.x) * 64 + nlog++) * 2; lg[0] = T_END << 16; lg[1] = gtime(); lg[2] = ~0ull; }
#endif
      while (true) {
        const uint32_t it = next_item();
        const int type = (it >> 16) & 255, m = (it >> 8) & 255, k = it & 255;
        const uint32_t slot = mp.stage;
        pipe_adv<2>(mp);
        if (type == T_END) break;
        mbar_wait(staged + 16 * w + 8 * slot, (sph >> slot) & 1); sph ^= 1u << slot;
        mbar_arrive(mempty + 8 * slot);
#ifdef TIMELINE
        if (w == 0 && nlog < 63) { unsigned long long* lg = g_log + (((tl >= 12) * 132 + blockIdx.x) * 64 + nlog++) * 2; lg[0] = (type << 16) | (m << 8) | k; lg[1] = gtime(); lg[2] = ~0ull; }
#endif
        if (type == T_L) continue;
        if (type == T_QA || type == T_A) {
          for (int jj = 0; jj < 3; jj++) bulk_s2g(a.o + ((size_t)m * 96 + k * 3 + jj) * 16384 + w * 8192, sb + OFF_K + w * 2 * SEGB + jj * 8192, 8192);
          bulk_commit();
          bulk_wait<0>();
          mbar_arrive(barKfree + 8 * w);
        } else if (type == T_OB || type == T_OS) {
          const bool wide = type == T_OB;
          const int nn = wide ? 2 : 5, nb = wide ? 5 : 2;
          const uint32_t own = wide ? 2 + w : ((it >> 24) + 96 / sc.ks[m] + w) % NS;
          bulk_s2g(a.part + ((size_t)((k / nn) * 32 + m * 2 + w) * 10 + (k % nn) * nb) * 8192, sb + own * (wide ? STO : STQ), nb * 8192);
          bulk_commit();
          bulk_wait<0>();
          mbar_arrive(empty + 8 * own);
          if (wide && w) { mbar_arrive(barKfree); mbar_arrive(barKfree + 8); }
        }
        if (type == T_Q || type == T_P) __threadfence();
        asm volatile("red.relaxed.gpu.global.add.u32 [%0], 1;" :: "l"(arena + (type == T_Q ? C_Q : (type <= T_A ? C_QA : (type == T_P ? C_P : C_O))) + m * 4) : "memory");
      }
    } } else if (elect_one()) {
      const uint64_t ef = policy_evict_first();
      uint32_t kph = 1;
      if (PF_WB && blockIdx.x >= 52) { prefetch_l2(pa.wb + (blockIdx.x - 52) * 32768, 32768); prefetch_l2(pa.wot + (blockIdx.x - 52) * 10240, 10240); }
      if (PF_WB > 1 && blockIdx.x >= 52) { prefetch_l2(a.xn + (blockIdx.x - 52) * 8192, 16384); prefetch_l2(a.xout + (blockIdx.x - 52) * 8192, 16384); }
      while (true) {
        const uint32_t it = next_item();
        const int type = (it >> 16) & 255, m = (it >> 8) & 255, k = it & 255;
        const uint32_t slot = mp.stage;
        pipe_adv<2>(mp);
        if (type == T_END) break;
        if (PF_XN && type == T_QA && m < 15) prefetch_l2(a.xq + ((m + 1) * 128 + k * 4) * cfg::DM, 5120);
        if (type == T_QA || type == T_A) {
          for (int spin = 0; spin < (1 << 21); spin++) {
            const uint4 f = ld_relaxed_v4(arena + prog_off(k, 0));
            if (min(min(f.x, f.y), f.z) >= (uint32_t)(4 * m + 4)) break;
            __nanosleep(m < 15 ? a.nap : a.nap2);
          }
          mbar_arrive(kvrdy);
          fence_proxy_async_global();
          const unsigned char* src = a.kg + ((size_t)m * 4 * 96 + k * 3) * 5120;
#pragma unroll 1
          for (int w = 0; w < 2; w++) {
            mbar_wait(barKfree + 8 * w, kph);
            if (type == T_A) { mbar_arrive(barK + 8 * w); continue; }
            mbar_expect_tx(barK + 8 * w, 2 * SEGB);
            for (int sg = 2 * w; sg < 2 * w + 2; sg++) { if (EF_KV) bulk_g2s_hint(sb + OFF_K + sg * SEGB, src + (size_t)sg * (96 * 5120), SEGB, barK + 8 * w, ef); else bulk_g2s(sb + OFF_K + sg * SEGB, src + (size_t)sg * (96 * 5120), SEGB, barK + 8 * w); }
          }
          kph ^= 1;
        } else if (type == T_OB) {
          mbar_wait(barKfree, kph); mbar_wait(barKfree + 8, kph);
          kph ^= 1;
        }
        mbar_arrive(mempty + 8 * slot);
      }
      if (blockIdx.x == gridDim.x - 1) asm volatile("griddepcontrol.wait;" ::: "memory");
    }
    return;
  }
  asm volatile("setmaxnreg.inc.sync.aligned.u32 232;");
  const int wg = warp >> 2, wi = warp & 3;
  const int g = lane >> 2, q4 = lane & 3;
  asm volatile("griddepcontrol.launch_dependents;" ::: "memory");
  Pipe p{0, 0};
  uint32_t kph = 0;
  auto own_slot = [&]() -> uint32_t {
    const uint32_t sA = p.stage, phA = p.phase; pipe_adv<NS>(p);
    const uint32_t sB = p.stage, phB = p.phase; pipe_adv<NS>(p);
    mbar_wait(full + 8 * sA, phA); mbar_wait(full + 8 * sB, phB);
    mbar_arrive_if((threadIdx.x & 127) == 0, empty + 8 * (wg ? sA : sB));
    return wg ? sB : sA;
  };
  while (true) {
    const uint32_t it = __shfl_sync(0xffffffffu, next_item(), 0);
    const int type = (it >> 16) & 255, m = (it >> 8) & 255, k = it & 255;
    mbar_arrive_if(lane == 0, mempty + 8 * mp.stage);
    const uint32_t done = staged + 16 * wg + 8 * mp.stage;
    pipe_adv<2>(mp);
    if (type == T_END) break;
    if (type == T_P) {
      prep_body(k, pa);
      __syncwarp();
      mbar_arrive_if(lane == 0, done);
      continue;
    }
    if (type == T_L) {
      const int nr = sc.lrows[m], np = sc.ks[m];
      const uint32_t po = (lane >> 4) * 1024 + warp * 128 + ((((lane >> 1) & 7) ^ warp) << 4) + (lane & 1) * 8;
#pragma unroll 1
      for (int r = 0; r < nr; r++) {
        uint2 xw[1][5]; float s[20];
#pragma unroll
        for (int i = 0; i < 20; i++) s[i] = 0.f;
#pragma unroll 1
        for (int q0 = 0; q0 <= np; q0 += 4) {
          const uint32_t st = sb + p.stage * STQ;
          mbar_wait(full + 8 * p.stage, p.phase);
          if (q0 == 0) static_for<0, 5>([&](auto I) { xw[0][I.value] = lds64_i<I.value * 256>(st + warp * 1280 + lane * 8); });
#pragma unroll 1
          for (int q = q0 ? 0 : 1; q < min(4, np + 1 - q0); q++)
            static_for<0, 5>([&](auto I) {
              constexpr int i = I.value;
              const uint2 t = lds64_i<i * 2048>(st + q * 10240 + po);
              s[4 * i] += bf_lo(t.x); s[4 * i + 1] += bf_hi(t.x); s[4 * i + 2] += bf_lo(t.y); s[4 * i + 3] += bf_hi(t.y);
            });
          bar_sync(3 + wg, 128);
          mbar_arrive_if((threadIdx.x & 127) == 0, empty + 8 * p.stage);
          pipe_adv<NS>(p);
        }
        const int row = (m * 16 + k * nr + r) * 8 + warp;
#pragma unroll
        for (int i = 0; i < 5; i++) {
          bf16r2(s[4 * i], s[4 * i + 1]); bf16r2(s[4 * i + 2], s[4 * i + 3]);
          xw[0][i] = make_uint2(pack_bf16(bf_lo(xw[0][i].x) + s[4 * i], bf_hi(xw[0][i].x) + s[4 * i + 1]), pack_bf16(bf_lo(xw[0][i].y) + s[4 * i + 2], bf_hi(xw[0][i].y) + s[4 * i + 3]));
          *(uint2*)(a.xout + (size_t)row * cfg::DM + i * 128 + lane * 4) = xw[0][i];
        }
        ln_rows<1>(xw, row, lane, a.xn, nullptr);
      }
      __syncwarp();
      mbar_arrive_if(lane == 0, done);
      continue;
    }
    if (type >= T_OB) {
      const int nkb = 96 / sc.ks[m];
      if (type == T_OB) {
        float a0[96], a1[64];
        tr_mainloop<192, 128>(a0, a1, p, sb, full, empty, nkb, wg);
        while (p.stage != 2) { mbar_wait(full + 8 * p.stage, p.phase); mbar_arrive_if((threadIdx.x & 127) == 0, empty + 8 * p.stage); pipe_adv<NS>(p); }
        const uint32_t st = sb + own_slot() * STO;
        stage_tiles<192>(a0, st, wi, lane); stage_tiles<128>(a1, st + 24576, wi, lane);
      } else {
        float a0[64], a1[1];
        tr_mainloop<128, 0>(a0, a1, p, sb, full, empty, nkb, wg);
        stage_tiles<128>(a0, sb + own_slot() * STQ, wi, lane);
      }
      fence_proxy_async();
      __syncwarp();
      mbar_arrive_if(lane == 0, done);
      continue;
    }
    uint32_t qf[12][4];
    uint4* qp = a.qs + ((size_t)((m & 7) * 32 + k) * 12) * 256 + threadIdx.x;
    if (type != T_A) {
      float acc[96], a1[1];
      tr_mainloop<192, 0>(acc, a1, p, sb, full, empty, 10, wg);
#pragma unroll
      for (int i = 0; i < 12; i++) {
        qf[i][0] = pack_bf16(acc[8 * i], acc[8 * i + 1]); qf[i][1] = pack_bf16(acc[8 * i + 2], acc[8 * i + 3]);
        qf[i][2] = pack_bf16(acc[8 * i + 4], acc[8 * i + 5]); qf[i][3] = pack_bf16(acc[8 * i + 6], acc[8 * i + 7]);
      }
      if (type == T_Q) {
#pragma unroll
        for (int i = 0; i < 12; i++) qp[i * 256] = make_uint4(qf[i][0], qf[i][1], qf[i][2], qf[i][3]);
        __syncwarp();
        mbar_arrive_if(lane == 0, done);
        continue;
      }
    } else {
#pragma unroll
      for (int i = 0; i < 12; i++) { const uint4 v = __ldcg(qp + i * 256); qf[i][0] = v.x; qf[i][1] = v.y; qf[i][2] = v.z; qf[i][3] = v.w; }
    }
    const uint32_t ost = sb + OFF_K + wg * 2 * SEGB;
    const bool second = wi >= 2;
    uint32_t pf[5][4];
    {
      float sa[20], sb2[20];
      uint32_t kbase = ost, kslot = 0;
      if (type == T_A) { kslot = own_slot(); kbase = sb + kslot * STQ; } else mbar_wait(barK + 8 * wg, kph);
      if (STAG && wg) bar_sync(1, 256);
      wgmma_fence();
#pragma unroll
      for (int i = 0; i < 12; i++) {
        wgmma_rs_n40<0>(sa, qf[i][0], qf[i][1], qf[i][2], qf[i][3], make_desc(kbase + i * 1280, 640, 128, 0), i != 0);
        wgmma_rs_n40<0>(sb2, qf[i][0], qf[i][1], qf[i][2], qf[i][3], make_desc(kbase + SEGB + i * 1280, 640, 128, 0), i != 0);
      }
      wgmma_commit();
      wgmma_wait<0>();
      if (STAG && !wg) bar_arrive(1, 256);
      mbar_arrive_if(type == T_A && (threadIdx.x & 127) == 0, empty + 8 * kslot);
      const float cs = 0.07216878364870322f * 1.4426950408889634f;
      const int r0 = 16 * (wi & 1) + g, r1 = r0 + 8;
      float m0 = -INFINITY, m1 = -INFINITY;
#pragma unroll
      for (int n = 0; n < 5; n++) {
#pragma unroll
        for (int e = 0; e < 2; e++) {
          const int key = 8 * n + 2 * q4 + e;
          float x = second ? sb2[4 * n + e] : sa[4 * n + e], y = second ? sb2[4 * n + 2 + e] : sa[4 * n + 2 + e];
          if (n < 4) { if (key > r0) x = -INFINITY; if (key > r1) y = -INFINITY; }
          sa[4 * n + e] = x; sa[4 * n + 2 + e] = y;
          m0 = fmaxf(m0, x); m1 = fmaxf(m1, y);
        }
      }
      m0 = fmaxf(m0, __shfl_xor_sync(0xffffffffu, m0, 1)); m1 = fmaxf(m1, __shfl_xor_sync(0xffffffffu, m1, 1));
      m0 = fmaxf(m0, __shfl_xor_sync(0xffffffffu, m0, 2)); m1 = fmaxf(m1, __shfl_xor_sync(0xffffffffu, m1, 2));
      float s0 = 0.f, s1 = 0.f;
#pragma unroll
      for (int n = 0; n < 5; n++) {
#pragma unroll
        for (int e = 0; e < 2; e++) {
          sa[4 * n + e] = ex2f((sa[4 * n + e] - m0) * cs); sa[4 * n + 2 + e] = ex2f((sa[4 * n + 2 + e] - m1) * cs);
          s0 += sa[4 * n + e]; s1 += sa[4 * n + 2 + e];
        }
      }
      s0 += __shfl_xor_sync(0xffffffffu, s0, 1); s1 += __shfl_xor_sync(0xffffffffu, s1, 1);
      s0 += __shfl_xor_sync(0xffffffffu, s0, 2); s1 += __shfl_xor_sync(0xffffffffu, s1, 2);
      const float i0 = rcpf(s0), i1 = rcpf(s1);
#pragma unroll
      for (int n = 0; n < 5; n++) {
        const uint32_t x = pack_bf16(sa[4 * n] * i0, sa[4 * n + 1] * i0), y = pack_bf16(sa[4 * n + 2] * i1, sa[4 * n + 3] * i1);
        if (n < 4) {
          pf[n >> 1][2 * (n & 1)] = second ? 0u : x; pf[n >> 1][2 * (n & 1) + 1] = second ? 0u : y;
          pf[2 + (n >> 1)][2 * (n & 1)] = second ? x : 0u; pf[2 + (n >> 1)][2 * (n & 1) + 1] = second ? y : 0u;
        } else {
          pf[4][0] = second ? 0u : x; pf[4][1] = second ? 0u : y; pf[4][2] = second ? x : 0u; pf[4][3] = second ? y : 0u;
        }
      }
    }
    {
      float o[96];
#pragma unroll
      for (int i = 0; i < 5; i++) { PIN(pf[i][0]); PIN(pf[i][1]); PIN(pf[i][2]); PIN(pf[i][3]); }
      const uint32_t own = own_slot(), vbase = sb + own * STQ;
      wgmma_fence();
#pragma unroll
      for (int i = 0; i < 5; i++)
        wgmma_rs_n192<1>(o, pf[i][0], pf[i][1], pf[i][2], pf[i][3], i < 4 ? make_desc(vbase + (i >> 1) * SEGB + (i & 1) * 256, 128, 640, 0) : make_desc(vbase + 512, SEGB, 640, 0), i != 0);
      wgmma_commit();
      if (type == T_A) mbar_wait(barK + 8 * wg, kph);
      kph ^= 1;
      wgmma_wait<0>();
      mbar_arrive_if((threadIdx.x & 127) == 0, empty + 8 * own);
      stage_tiles<192>(o, ost, wi, lane);
      fence_proxy_async();
      __syncwarp();
      mbar_arrive_if(lane == 0, done);
    }
  }
}
namespace bf {
constexpr int NS = 4, STAGE = 16384 + 32768;
constexpr int PIECE = 20480;
constexpr int OFF_PHI = 0, OFF_V = 40960, OFF_KV = 65536;
constexpr int OFF_OST = 5 * PIECE;
constexpr int OFF_WOT = 6 * PIECE;
constexpr int OFF_BAR = OFF_WOT + 102400;
constexpr int SMEM = OFF_BAR + 256;
static_assert(NS * STAGE <= OFF_BAR && SMEM <= 232448, "smem");
constexpr int KVACC = 32 * 5 * 1024;
struct Args {
  const unsigned char *wb, *wot;
  unsigned char *kvacc, *o2;
  const bf16* xin;
  bf16* xout;
  unsigned* go;
  const void* prep;
  const bf16 *pf0, *pf1;
  int pfn, pfns, pfwait;
  int tl;
};
}
__device__ __forceinline__ void hedgehog_features(float (&x)[2][5], uint32_t (&w)[2][5]) {
  const float L = 1.4426950408889634f;
  float mx[2], mn[2], sp[2], sn[2], pos[2][5], neg[2][5];
#pragma unroll
  for (int r = 0; r < 2; r++) {
    mx[r] = fmaxf(fmaxf(fmaxf(x[r][0], x[r][1]), fmaxf(x[r][2], x[r][3])), x[r][4]);
    mn[r] = fminf(fminf(fminf(x[r][0], x[r][1]), fminf(x[r][2], x[r][3])), x[r][4]);
  }
#pragma unroll
  for (int o = 1; o < 4; o <<= 1)
#pragma unroll
    for (int r = 0; r < 2; r++) {
      const uint32_t t = __shfl_xor_sync(0xffffffffu, __byte_perm(__float_as_uint(mn[r]), __float_as_uint(mx[r]), 0x7632), o);
      mx[r] = fmaxf(mx[r], bf_hi(t)); mn[r] = fminf(mn[r], bf_lo(t));
    }
#pragma unroll
  for (int r = 0; r < 2; r++) {
#pragma unroll
    for (int i = 0; i < 5; i++) { pos[r][i] = ex2f((x[r][i] - mx[r]) * L); neg[r][i] = ex2f((mn[r] - x[r][i]) * L); }
    sp[r] = ((pos[r][0] + pos[r][1]) + (pos[r][2] + pos[r][3])) + pos[r][4];
    sn[r] = ((neg[r][0] + neg[r][1]) + (neg[r][2] + neg[r][3])) + neg[r][4];
  }
#pragma unroll
  for (int o = 1; o < 4; o <<= 1)
#pragma unroll
    for (int r = 0; r < 2; r++) { sp[r] += __shfl_xor_sync(0xffffffffu, sp[r], o); sn[r] += __shfl_xor_sync(0xffffffffu, sn[r], o); }
#pragma unroll
  for (int r = 0; r < 2; r++) {
    const float ip = rcpf(sp[r]), in_ = rcpf(sn[r]);
    w[r][0] = pack_bf16(pos[r][0] * ip, pos[r][1] * ip); w[r][1] = pack_bf16(pos[r][2] * ip, pos[r][3] * ip);
    w[r][2] = pack_bf16(neg[r][0] * in_, neg[r][1] * in_); w[r][3] = pack_bf16(neg[r][2] * in_, neg[r][3] * in_);
    w[r][4] = pack_bf16(pos[r][4] * ip, neg[r][4] * in_);
  }
}
__device__ __forceinline__ void bulk_g2s_mc(uint32_t dst, const void* src, uint32_t bytes, uint32_t mb) {
  asm volatile("cp.async.bulk.shared::cluster.global.mbarrier::complete_tx::bytes.multicast::cluster [%0], [%1], %2, [%3], %4;"
               :: "r"(dst), "l"(src), "r"(bytes), "r"(mb), "h"((unsigned short)3) : "memory");
}
__device__ __forceinline__ void mbar_arrive_remote_if(bool c, uint32_t b) {
  asm volatile("{\n.reg .pred p;\nsetp.ne.u32 p, %1, 0;\n@p mbarrier.arrive.shared::cluster.b64 _, [%0];\n}" :: "r"(b), "r"((uint32_t)c) : "memory");
}

__global__ void __cluster_dims__(2, 1, 1) __launch_bounds__(384, 1) blayer_kernel(const __grid_constant__ CUtensorMap tmA, const __grid_constant__ bf::Args a) {
  using namespace bf;
  [[maybe_unused]] const int tl = a.tl;
  extern __shared__ __align__(1024) unsigned char smem_raw[];
  const uint32_t sb = smem_u32(smem_raw);
  const int warp = __shfl_sync(0xffffffffu, (int)threadIdx.x >> 5, 0), lane = threadIdx.x & 31;
  const uint32_t full = sb + OFF_BAR, empty = full + 8 * NS, full2 = empty + 8 * NS, empty2 = full2 + 64, barW = empty2 + 16, drained = barW + 8, staged = drained + 8, freeb = staged + 8;
  const int rank = blockIdx.x & 1, u = (blockIdx.x >> 1) & 7, mp = blockIdx.x >> 4;
  const int m = 2 * mp + rank;
  const int m2 = 2 * mp + (u & 1), ns = (u & ~1) + rank;
  const uint32_t dpeer = mapa_u32(sb, rank ^ 1) - sb;
  unsigned* cntO = (unsigned*)(a.kvacc + KVACC);
  if (threadIdx.x == 0) {
    for (int i = 0; i < NS; i++) { mbar_init(full + 8 * i, 1); mbar_init(empty + 8 * i, 4); }
    for (int i = 0; i < 8; i++) mbar_init(full2 + 8 * i, 1);
    mbar_init(empty2, 2); mbar_init(empty2 + 8, 2);
    mbar_init(barW, 1); mbar_init(drained, 1); mbar_init(staged, 8); mbar_init(freeb, 2);
    asm volatile("fence.mbarrier_init.release.cluster;" ::: "memory");
  }
  __syncthreads();
  asm volatile("barrier.cluster.arrive.relaxed.aligned; barrier.cluster.wait.aligned;" ::: "memory");
  if (warp >= 8) {
    asm volatile("setmaxnreg.dec.sync.aligned.u32 40;");
    if (warp == 8) { if (elect_one()) {
      const unsigned char* wsrc = a.wb + (size_t)u * 327680 + rank * 16384;
      if (a.prep) wait_ge(a.prep, 64);
      fence_proxy_async_global();
      for (int kb = 0; kb < NS; kb++) {
        mbar_expect_tx(full + 8 * kb, STAGE);
        bulk_g2s_mc(sb + kb * STAGE + 16384 + rank * 16384, wsrc + kb * 32768, 16384, full + 8 * kb);
      }
      asm volatile("griddepcontrol.wait;" ::: "memory");
      TL_BEGIN0(tl);
      if (blockIdx.x == 0) *a.go = 0;
      for (int kb = 0; kb < NS; kb++) tma_load_2d(sb + kb * STAGE, &tmA, kb * 64, m * 128, full + 8 * kb);
      if (m == 0) prefetch_l2(a.kvacc + u * (KVACC / 8), KVACC / 8);
#pragma unroll 1
      for (int kb = NS; kb < 10; kb++) {
        const uint32_t s = kb & 3, st = sb + s * STAGE, fb = full + 8 * s;
        mbar_wait(empty + 8 * s, ((kb >> 2) - 1) & 1);
        mbar_expect_tx(fb, STAGE);
        tma_load_2d(st, &tmA, kb * 64, m * 128, fb);
        bulk_g2s_mc(st + 16384 + rank * 16384, wsrc + kb * 32768, 16384, fb);
      }
      for (int i = 0; i < 6; i++) mbar_expect_tx(full2 + 8 * i, PIECE);
      mbar_wait(drained, 0);
      mbar_expect_tx(barW, 102400);
      bulk_g2s(sb + OFF_WOT, a.wot + (size_t)ns * 102400, 102400, barW);
      mbar_wait(staged, 0);
      bulk_s2g(a.o2 + (size_t)(m * 8 + u) * PIECE, sb + OFF_OST, PIECE);
      bulk_commit();
      bulk_wait<0>();
      asm volatile("red.relaxed.gpu.global.add.u32 [%0], 1;" :: "l"(cntO + m) : "memory");
      mbar_arrive(freeb); mbar_arrive_remote_if(true, freeb + dpeer);
      wait_ge(cntO + m2, 8, 20);
      mbar_wait(freeb, 0);
      fence_proxy_async_global();
      const unsigned char* osrc = a.o2 + (size_t)m2 * 8 * PIECE;
      for (int i = 0; i < 6; i++) bulk_g2s_mc(sb + i * PIECE + rank * (PIECE / 2), osrc + i * PIECE + rank * (PIECE / 2), PIECE / 2, full2 + 8 * i);
      for (int i = 0; i < 2; i++) {
        mbar_wait(empty2 + 8 * i, 0);
        mbar_expect_tx(full2 + 8 * (6 + i), PIECE);
        bulk_g2s(sb + i * PIECE, osrc + (6 + i) * PIECE, PIECE, full2 + 8 * (6 + i));
      }
    } } else if (warp == 9 && a.pf0) { if (elect_one()) {
      if (a.pfwait) asm volatile("griddepcontrol.wait;" ::: "memory");
      constexpr uint32_t CH = 2048;
      for (int i = 0; i < a.pfn; i++) {
        prefetch_l2((const unsigned char*)a.pf0 + (i * 128 + blockIdx.x) * CH, CH); prefetch_l2((const unsigned char*)a.pf1 + (i * 128 + blockIdx.x) * CH, CH);
        __nanosleep(a.pfns);
      }
    } }
    return;
  }
  asm volatile("setmaxnreg.inc.sync.aligned.u32 232;");
  const int wg = warp >> 2, wi = warp & 3;
  const int q4 = lane & 3;
  const bool lead = (threadIdx.x & 127) == 0;
  float acc[128];
  {
#pragma unroll 1
    for (int kb = 0; kb < 10; kb++) {
      const uint32_t s = kb & 3, st = sb + s * STAGE;
      mbar_wait(full + 8 * s, (kb >> 2) & 1);
      wgmma_fence();
#pragma unroll
      for (int kk = 0; kk < 4; kk++) wgmma_n256<0, 1>(acc, desc_kmajor(st + wg * 8192 + kk * 32), make_desc(st + 16384 + kk * 8192, 4096, 128, 0), (kb | kk) != 0);
      wgmma_commit();
      if (kb > 0 && kb < 7) { wgmma_wait<1>(); const uint32_t e = empty + 8 * ((kb - 1) & 3); mbar_arrive_if(lead, e); mbar_arrive_remote_if(lead, e + dpeer); }
    }
    wgmma_wait<0>();
    bar_sync(1, 256);
    mbar_arrive_if(threadIdx.x == 0, drained);
  }
  TL2((tl >= 12 ? 128 : 0) + 32 + 0);
  const uint32_t srow = (wg * 64 + wi * 16 + (lane & 15)) * 16 + (lane >> 4) * 2048;
  auto features = [&](auto T0, auto HH, uint32_t (&w)[2][5]) {
    constexpr int t = T0.value + 5 * (HH.value >> 1), o = (HH.value & 1) ? 3 : 0, e = HH.value & 1;
    float x[2][5];
#pragma unroll
    for (int r = 0; r < 2; r++) {
      x[r][0] = acc[4 * (t + o) + 2 * r]; x[r][1] = acc[4 * (t + o) + 2 * r + 1]; x[r][2] = acc[4 * (t + o + 1) + 2 * r]; x[r][3] = acc[4 * (t + o + 1) + 2 * r + 1];
      bf16r2(x[r][0], x[r][1]); bf16r2(x[r][2], x[r][3]);
    }
    x[0][4] = acc[4 * (t + 2) + e]; x[1][4] = acc[4 * (t + 2) + 2 + e];
    bf16r2(x[0][4], x[1][4]);
    hedgehog_features(x, w);
  };
  static_for<0, 4>([&](auto HH) {
    constexpr int hh = HH.value, t = 20 + 3 * hh;
    const uint32_t one = q4 == ((hh & 1) ? 0 : 2) ? 0x3f80u : 0u;
    const uint32_t va = sb + OFF_V + hh * 6144 + srow;
    stsm_x4(va, pack_bf16(acc[4 * t], acc[4 * t + 1]), pack_bf16(acc[4 * t + 2], acc[4 * t + 3]), pack_bf16(acc[4 * t + 4], acc[4 * t + 5]), pack_bf16(acc[4 * t + 6], acc[4 * t + 7]));
    const bool pad = (q4 >= 2) != (hh & 1);
    stsm_x2(va + 4096, pad ? one : pack_bf16(acc[4 * t + 8], acc[4 * t + 9]), pad ? one : pack_bf16(acc[4 * t + 10], acc[4 * t + 11]));
    uint32_t w[2][5];
    features(IC<10>{}, HH, w);
    const uint32_t pa = sb + OFF_PHI + hh * 10240 + srow;
    stsm_x4(pa, w[0][0], w[1][0], w[0][1], w[1][1]);
    stsm_x4(pa + 4096, w[0][2], w[1][2], w[0][3], w[1][3]);
    stsm_x2(pa + 8192, w[0][4], w[1][4]);
  });
  fence_proxy_async();
  bar_sync(1, 256);
  TL2((tl >= 12 ? 128 : 0) + 32 + 1);
  {
    float d0[12], d1[12];
    const uint32_t pa = sb + OFF_PHI + wg * 20480, pv = sb + OFF_V + wg * 12288;
    wgmma_fence();
#pragma unroll
    for (int k = 0; k < 8; k++) {
      wgmma_n24<1, 1>(d0, make_desc(pa + k * 256, 128, 2048, 0), make_desc(pv + k * 256, 128, 2048, 0), k != 0);
      wgmma_n24<1, 1>(d1, make_desc(pa + 10240 + k * 256, 128, 2048, 0), make_desc(pv + 6144 + k * 256, 128, 2048, 0), k != 0);
    }
    wgmma_commit();
    wgmma_wait<0>();
    unsigned char* dst = a.kvacc + ((u * 4 + wg * 2) * 5 + 2 * wi) * 1024 + lane * 16;
    auto red4 = [&](bool on, unsigned char* p, float x, float y, float z) {
      asm volatile("{\n.reg .pred p;\nsetp.ne.u32 p, %4, 0;\n@p red.relaxed.gpu.global.add.v4.f32 [%0], {%1,%2,%3,%5};\n}" :: "l"(p), "f"(x), "f"(y), "f"(z), "r"((uint32_t)on), "f"(1.f) : "memory");
    };
    red4(wi < 3, dst, d0[0], d0[1], d0[4]); red4(wi < 3, dst + 512, d0[5], d0[8], d0[9]);
    red4(wi < 3, dst + 5120, d1[0], d1[1], d1[4]); red4(wi < 3, dst + 5632, d1[5], d1[8], d1[9]);
    red4(wi < 2, dst + 1024, d0[2], d0[3], d0[6]); red4(wi < 2, dst + 1536, d0[7], d0[10], d0[11]);
    red4(wi < 2, dst + 6144, d1[2], d1[3], d1[6]); red4(wi < 2, dst + 6656, d1[7], d1[10], d1[11]);
  }
  TL2((tl >= 12 ? 128 : 0) + 32 + 2);
  uint32_t qf[4][2][5];
  static_for<0, 4>([&](auto HH) { features(IC<0>{}, HH, qf[HH.value]); });
  uint4 xr[5];
#pragma unroll
  for (int i = 0; i < 5; i++) {
    const int c = lane + 32 * i;
    xr[i] = __ldcg((const uint4*)(a.xin + (size_t)(m2 * 128 + wg * 64 + wi * 16 + c / 10) * cfg::DM + ns * 80 + (c % 10) * 8));
  }
  {
    const unsigned char* src = a.kvacc + (u * 20 + warp) * 1024 + lane * 16;
    uint4 v[6];
    int spin = 0;
    while (true) {
      v[0] = ld_relaxed_v4_i<0>(src); v[1] = ld_relaxed_v4_i<512>(src); v[2] = ld_relaxed_v4_i<8192>(src); v[3] = ld_relaxed_v4_i<8704>(src);
      v[4] = ld_relaxed_v4_i<0>(src + (wg ? 0 : 16384)); v[5] = ld_relaxed_v4_i<512>(src + (wg ? 0 : 16384));
      const uint32_t c = (v[0].w & v[1].w & v[2].w) & (v[3].w & v[4].w & v[5].w);
      if (!__any_sync(0xffffffffu, (c & 0x41800000u) != 0x41800000u) || ++spin >= SPIN_LIMIT) break;
      __nanosleep(100);
    }
    const uint32_t kd = sb + OFF_KV + warp * 384 + lane * 4;
#pragma unroll
    for (int i = 0; i < 3; i++)
      if (i < 2 || wg == 0) {
        sts32(kd + i * 3072, pack_bf16(__uint_as_float(v[2 * i].x), __uint_as_float(v[2 * i].y)));
        sts32(kd + i * 3072 + 128, pack_bf16(__uint_as_float(v[2 * i].z), __uint_as_float(v[2 * i + 1].x)));
        sts32(kd + i * 3072 + 256, pack_bf16(__uint_as_float(v[2 * i + 1].y), __uint_as_float(v[2 * i + 1].z)));
      }
  }
  fence_proxy_async();
  bar_sync(1, 256);
  TL2((tl >= 12 ? 128 : 0) + 32 + 3);
  {
    float d[4][12];
    uint32_t zero = 0; PIN(zero);
#pragma unroll
    for (int hh = 0; hh < 4; hh++)
#pragma unroll
      for (int i = 0; i < 5; i++) { PIN(qf[hh][0][i]); PIN(qf[hh][1][i]); }
    wgmma_fence();
#pragma unroll
    for (int hh = 0; hh < 4; hh++) {
      const uint32_t kb = sb + OFF_KV + hh * 1920;
      wgmma_rs_n24<1>(d[hh], qf[hh][0][0], qf[hh][1][0], qf[hh][0][1], qf[hh][1][1], make_desc(kb, 384, 128, 0), 0);
      wgmma_rs_n24<1>(d[hh], qf[hh][0][2], qf[hh][1][2], qf[hh][0][3], qf[hh][1][3], make_desc(kb + 768, 384, 128, 0), 1);
      wgmma_rs_n24<1>(d[hh], qf[hh][0][4], qf[hh][1][4], zero, zero, make_desc(kb + 1536, 0, 128, 0), 1);
    }
    wgmma_commit();
    wgmma_wait<0>();
    uint32_t ow[4][6];
#pragma unroll
    for (int hh = 0; hh < 4; hh++) {
      const int zl = (lane & ~3) | ((hh & 1) ? 0 : 2);
      const float da = bf16r(bf16r(__shfl_sync(0xffffffffu, d[hh][8], zl)) + 1e-6f), db = bf16r(bf16r(__shfl_sync(0xffffffffu, d[hh][10], zl)) + 1e-6f);
#pragma unroll
      for (int n = 0; n < 3; n++) {
        bf16r2(d[hh][4 * n], d[hh][4 * n + 1]); bf16r2(d[hh][4 * n + 2], d[hh][4 * n + 3]);
        ow[hh][2 * n] = pack_bf16(__fdividef(d[hh][4 * n], da), __fdividef(d[hh][4 * n + 1], da));
        ow[hh][2 * n + 1] = pack_bf16(__fdividef(d[hh][4 * n + 2], db), __fdividef(d[hh][4 * n + 3], db));
      }
    }
#pragma unroll
    for (int p = 0; p < 2; p++) {
      const uint32_t oa = sb + OFF_OST + p * 10240 + srow;
      stsm_x4(oa, ow[2 * p][0], ow[2 * p][1], ow[2 * p][2], ow[2 * p][3]);
      stsm_x2(oa + 4096, q4 < 2 ? ow[2 * p][4] : ow[2 * p + 1][4], q4 < 2 ? ow[2 * p][5] : ow[2 * p + 1][5]);
      stsm_x4(oa + 6144, ow[2 * p + 1][0], ow[2 * p + 1][1], ow[2 * p + 1][2], ow[2 * p + 1][3]);
    }
    fence_proxy_async();
    __syncwarp();
    mbar_arrive_if(lane == 0, staged);
  }
  TL2((tl >= 12 ? 128 : 0) + 32 + 4);
  float c2[40];
  mbar_wait(barW, 0);
#pragma unroll 1
  for (int i = 0; i < 8; i++) {
    mbar_wait(full2 + 8 * i, 0);
    const uint32_t st = sb + (i < 6 ? i : i - 6) * PIECE + wg * 1024, wo = sb + OFF_WOT + i * 12800;
    wgmma_fence();
#pragma unroll
    for (int kk = 0; kk < 5; kk++) wgmma_n80<0, 1>(c2, make_desc(st + kk * 4096, 2048, 128, 0), make_desc(wo + kk * 2560, 1280, 128, 0), (i | kk) != 0);
    wgmma_commit();
    if (i == 1 || i == 2) { wgmma_wait<1>(); mbar_arrive_if(lead, empty2 + 8 * (i - 1)); }
  }
  wgmma_wait<0>();
  TL2((tl >= 12 ? 128 : 0) + 32 + 5);
  {
    bar_sync(1, 256);
    const uint32_t ost = sb + 2 * PIECE + warp * 3072;
#pragma unroll
    for (int v = 0; v < 10; v += 2)
      stsm_x4(ost + (lane & 15) * 176 + (v + (lane >> 4)) * 16, pack_bf16(c2[4 * v], c2[4 * v + 1]), pack_bf16(c2[4 * v + 2], c2[4 * v + 3]),
              pack_bf16(c2[4 * v + 4], c2[4 * v + 5]), pack_bf16(c2[4 * v + 6], c2[4 * v + 7]));
    __syncwarp();
#pragma unroll
    for (int i = 0; i < 5; i++) {
      const int c = lane + 32 * i, row = c / 10, chunk = c % 10;
      const uint4 y = lds128(ost + row * 176 + chunk * 16);
      const size_t off = (size_t)(m2 * 128 + wg * 64 + wi * 16 + row) * cfg::DM + ns * 80 + chunk * 8;
      const uint4 x = xr[i];
      *(uint4*)(a.xout + off) = make_uint4(pack_bf16(bf_lo(x.x) + bf_lo(y.x), bf_hi(x.x) + bf_hi(y.x)), pack_bf16(bf_lo(x.y) + bf_lo(y.y), bf_hi(x.y) + bf_hi(y.y)),
                                           pack_bf16(bf_lo(x.z) + bf_lo(y.z), bf_hi(x.z) + bf_hi(y.z)), pack_bf16(bf_lo(x.w) + bf_lo(y.w), bf_hi(x.w) + bf_hi(y.w)));
    }
  }
  TL_END(tl);
}
__device__ __align__(32768) unsigned char g_arena[AR_SIZE];
__device__ unsigned g_go[32];
__device__ __align__(1024) uint2 g_xh[2048 * 160];
__device__ __align__(1024) unsigned char g_k[64 * 96 * 5120], g_v[64 * 96 * 5120];
__device__ __align__(1024) bf16 g_o[2048 * 6144];
__device__ __align__(1024) uint4 g_qs[8 * 32 * 12 * 256];
__device__ __align__(1024) bf16 g_xn[2048 * 640], g_xn2[2048 * 640], g_xa[2048 * 640], g_xb[2048 * 640];
__device__ __align__(1024) bf16 g_part[24 * 2048 * 640];
__device__ __align__(1024) bf16 g_wb[2048 * 640], g_wot[640 * 640], g_pq[2048 * 640];
__device__ __align__(1024) float g_kvacc[bf::KVACC / 4 + 64];

typedef CUresult (*EncodeFn)(CUtensorMap*, CUtensorMapDataType, cuuint32_t, void*, const cuuint64_t*, const cuuint64_t*, const cuuint32_t*,
                             const cuuint32_t*, CUtensorMapInterleave, CUtensorMapSwizzle, CUtensorMapL2promotion, CUtensorMapFloatOOBfill);
static EncodeFn g_encode = nullptr;
static CUtensorMap make_map(const void* p, uint64_t cols, uint64_t rows, uint32_t bc, uint32_t br, bool swz = true) {
  CUtensorMap m;
  cuuint64_t dims[2] = {cols, rows}, strides[1] = {cols * 2};
  cuuint32_t box[2] = {bc, br}, es[2] = {1, 1};
  g_encode(&m, CU_TENSOR_MAP_DATA_TYPE_BFLOAT16, 2, const_cast<void*>(p), dims, strides, box, es, CU_TENSOR_MAP_INTERLEAVE_NONE,
           swz ? CU_TENSOR_MAP_SWIZZLE_128B : CU_TENSOR_MAP_SWIZZLE_NONE, CU_TENSOR_MAP_L2_PROMOTION_L2_256B, CU_TENSOR_MAP_FLOAT_OOB_FILL_NONE);
  return m;
}
static CUtensorMap make_map3(const void* p, uint64_t cols, uint64_t rows, uint32_t nb) {
  CUtensorMap m;
  cuuint64_t dims[3] = {64, rows, cols / 64}, strides[2] = {cols * 2, 128};
  cuuint32_t box[3] = {64, 64, nb}, es[3] = {1, 1, 1};
  g_encode(&m, CU_TENSOR_MAP_DATA_TYPE_BFLOAT16, 3, const_cast<void*>(p), dims, strides, box, es, CU_TENSOR_MAP_INTERLEAVE_NONE,
           CU_TENSOR_MAP_SWIZZLE_128B, CU_TENSOR_MAP_L2_PROMOTION_L2_256B, CU_TENSOR_MAP_FLOAT_OOB_FILL_NONE);
  return m;
}
template <class T> static T* sym(const T& s) { void* p = nullptr; cudaGetSymbolAddress(&p, s); return (T*)p; }

struct Ptrs {
  unsigned char *arena, *k, *v; bf16 *o, *xn, *xa, *xb, *wb, *wot, *pq; float *part, *kvacc; uint2* xh; uint4* qs; bf16* xn2; unsigned* go;
};

static tr::Sched make_sched(int layer, const char* str, const int* ks, const int* lr) {
  using namespace tr;
  Sched s = {};
  int n = 0;
  for (int b = 0; b < 16; b++) { s.ks[b] = (uint8_t)abs(ks[b]); s.wide[b] = ks[b] > 0; s.lrows[b] = (uint8_t)lr[b]; }
  for (const char* p = str; *p;) {
    if (*p == ' ') { p++; continue; }
    const char c = *p++;
    char* e;
    const int b = (int)strtol(p, &e, 10); p = e;
    int first = 0, cnt = c == 'o' ? s.ks[b] * (s.wide[b] ? 2 : 5) : (c == 'l' ? 16 / lr[b] : 32);
    if (*p == '.') { first = (int)strtol(p + 1, &e, 10); cnt = (int)strtol(e + 1, &e, 10); p = e; }
    const int type = c == 'a' ? T_QA : (c == 'q' ? T_Q : (c == 't' ? T_A : (c == 'l' ? T_L : (c == 'p' ? T_P : (s.wide[b] ? T_OB : T_OS)))));
    if (type == T_P && layer > 0) continue;
    for (int i = 0; i < cnt && n < MAXITEMS - 1; i++) s.item[n++] = (uint16_t)((type << 11) | (b << 7) | (first + i));
  }
  s.n = n; s.item[n] = T_END << 11;
  return s;
}
static tr::Sched sched_of(int layer) {
  const char* str = "q13 q14 a0 q15 a1 o0 p0.0.16 a2 o1 p0.16.16 a3 o2 a4 o3 a5 o4 l0 a6 o5 l1 a7 o6 l2 a8 o7 l3 a9 o8 l4 a10 o9 l5 a11 o10 l6 a12 o11 l7 t13 o12 t14 t15 o13 o14 l8 l9 l10 l11 o15 l12 l13 l14 l15";
  int ks[16] = {2, 2, 2, 2, 2, 2, 2, 2, 2, 2, 3, 4, 6, -8, -8, -12}, lr[16] = {4, 4, 4, 4, 4, 4, 4, 4, 2, 1, 1, 1, 1, 1, 1, 1};
#ifdef TUNE
  if (getenv("SCHED")) str = getenv("SCHED");
  if (layer == 0 && getenv("SCHED0")) str = getenv("SCHED0");
  if (const char* p = getenv("KS")) for (int b = 0; b < 16; b++) { char* e; ks[b] = (int)strtol(p, &e, 10); p = e; }
  if (const char* p = getenv("LR")) for (int b = 0; b < 16; b++) { char* e; lr[b] = (int)strtol(p, &e, 10); p = e; }
#endif
  return make_sched(layer, str, ks, lr);
}
#ifndef TRAIL_GRID
#define TRAIL_GRID 132
#endif
#ifndef PDL_LN
#define PDL_LN 0
#endif
#ifndef PDL_CH
#define PDL_CH 1
#endif
#ifndef PDL_B
#define PDL_B 1
#endif
#ifndef PF_A
#define PF_A 1
#endif
#ifndef PF_B
#define PF_B 1
#endif
extern "C" void kernel_launch(void* const* d_in, const int* in_sizes, int n_in, void* d_out, int out_size) {
  const bf16* x = (const bf16*)d_in[0];
  const bf16* mem0 = (const bf16*)d_in[1];
  const bf16 *Wq = (const bf16*)d_in[2], *Wk = (const bf16*)d_in[3], *Wv = (const bf16*)d_in[4], *Wo = (const bf16*)d_in[5];
  const bf16 *wqkv = (const bf16*)d_in[8], *wphi = (const bf16*)d_in[9], *wo = (const bf16*)d_in[10];
  bf16* out = (bf16*)d_out;
  static Ptrs P; static bool init = false;
  if (!init) {
    void* fn = nullptr; cudaDriverEntryPointQueryResult qr;
    cudaGetDriverEntryPoint("cuTensorMapEncodeTiled", &fn, cudaEnableDefault, &qr);
    g_encode = (EncodeFn)fn;
    void* p;
    cudaGetSymbolAddress(&p, g_arena); P.arena = (unsigned char*)p;
    cudaGetSymbolAddress(&p, g_k); P.k = (unsigned char*)p;   cudaGetSymbolAddress(&p, g_v); P.v = (unsigned char*)p;
    cudaGetSymbolAddress(&p, g_o); P.o = (bf16*)p;
    cudaGetSymbolAddress(&p, g_xn); P.xn = (bf16*)p;
    cudaGetSymbolAddress(&p, g_xa); P.xa = (bf16*)p;   cudaGetSymbolAddress(&p, g_xb); P.xb = (bf16*)p;
    cudaGetSymbolAddress(&p, g_wb); P.wb = (bf16*)p;   cudaGetSymbolAddress(&p, g_wot); P.wot = (bf16*)p;
    cudaGetSymbolAddress(&p, g_pq); P.pq = (bf16*)p;   cudaGetSymbolAddress(&p, g_part); P.part = (float*)p;
    cudaGetSymbolAddress(&p, g_kvacc); P.kvacc = (float*)p;
    cudaGetSymbolAddress(&p, g_xh); P.xh = (uint2*)p;
    cudaGetSymbolAddress(&p, g_go); P.go = (unsigned*)p;
    cudaGetSymbolAddress(&p, g_qs); P.qs = (uint4*)p;
    cudaGetSymbolAddress(&p, g_xn2); P.xn2 = (bf16*)p;
    cudaFuncSetAttribute(chain_kernel, cudaFuncAttributeMaxDynamicSharedMemorySize, ch::SMEM);
    cudaFuncSetAttribute(trail_kernel, cudaFuncAttributeMaxDynamicSharedMemorySize, tr::SMEM);
    cudaFuncSetAttribute(blayer_kernel, cudaFuncAttributeMaxDynamicSharedMemorySize, bf::SMEM);
    init = true;
  }
  const CUtensorMap tmXn = make_map(P.xn, 640, 2048, 64, 128), tmXn2 = make_map(P.xn2, 640, 2048, 64, 128);
  const CUtensorMap tmWq = make_map3(Wq, 6144, 640, 3);
  const CUtensorMap tmCq = make_map(Wq, 6144, 640, 64, 160), tmCk = make_map(Wk, 6144, 640, 64, 160), tmCv = make_map(Wv, 6144, 640, 64, 160), tmCo = make_map(Wo, 640, 6144, 224, 64, false);
  const CUtensorMap tmWo5 = make_map3(Wo, 640, 6144, 5), tmWo2 = make_map3(Wo, 640, 6144, 2);

  CUtensorMap tmP;
  {
    cuuint64_t dims[3] = {256, 8, 24 * 320}, strides[2] = {1024, 8192};
    cuuint32_t box[3] = {256, 1, 10}, es[3] = {1, 1, 1};
    g_encode(&tmP, CU_TENSOR_MAP_DATA_TYPE_UINT32, 3, P.part, dims, strides, box, es, CU_TENSOR_MAP_INTERLEAVE_NONE, CU_TENSOR_MAP_SWIZZLE_NONE,
             CU_TENSOR_MAP_L2_PROMOTION_NONE, CU_TENSOR_MAP_FLOAT_OOB_FILL_NONE);
  }
  ChainArgs ca;
  ca.xh = P.xh; ca.mem0 = mem0; ca.kg = P.k; ca.vg = P.v;
  ca.arena = P.arena; ca.dbg = nullptr; ca.go = P.go; ca.delay = POLL_DELAY; ca.margin = 150;
#ifdef TUNE
  if (getenv("MG")) ca.margin = atoi(getenv("MG"));
  if (getenv("PD")) ca.delay = atoi(getenv("PD"));
#endif
  ca.tl = 0;
  uint4* zar = (uint4*)P.arena; const int nzar = AR_SIZE / 16;
  uint4* zkv = (uint4*)P.kvacc; const int nzkv = (bf::KVACC / 4 + 64) / 4;

  const PrepArgs pa{wqkv, wphi, wo, (unsigned char*)P.wb, (unsigned char*)P.wot};
  const bf16* xcur = x;
  cudaLaunchAttribute at[1];
  at[0].id = cudaLaunchAttributeProgrammaticStreamSerialization; at[0].val.programmaticStreamSerializationAllowed = 1;
  auto cfgof = [&](int grid, int block, int smem, bool pdl) {
    cudaLaunchConfig_t lc = {};
    lc.gridDim = dim3(grid); lc.blockDim = dim3(block); lc.dynamicSmemBytes = smem; lc.stream = cudaStreamPerThread;
    lc.attrs = at; lc.numAttrs = pdl ? 1 : 0;
    return lc;
  };
  for (int layer = 0; layer < 2; layer++) {
    const int tl = layer * 12;
    cudaLaunchConfig_t lc = cfgof(256, 256, 0, layer > 0 && PDL_LN);
    cudaLaunchKernelEx(&lc, ln_kernel, xcur, P.xn, P.xh, zar, nzar, zkv, nzkv, Wk, Wv, layer == 0 ? PF_A : 0, tl + 0);
    ca.tl = tl + 2;
    lc = cfgof(96, 384, ch::SMEM, PDL_CH);
    cudaLaunchKernelEx(&lc, chain_kernel, ca, tmCq, tmCk, tmCv, tmCo);
    lc = cfgof(TRAIL_GRID, 384, tr::SMEM, true);
    tr::Args ta{P.k, P.v, (unsigned char*)P.o, P.qs, (unsigned char*)P.part, xcur, P.xn, P.xa, P.xn2, P.arena, P.go, tl + 4, 500, 100};
#ifdef TUNE
    if (getenv("NAP")) ta.nap = atoi(getenv("NAP"));
    if (getenv("NAP2")) ta.nap2 = atoi(getenv("NAP2"));
#endif
    cudaLaunchKernelEx(&lc, trail_kernel, tmXn, tmWq, tmWo5, tmWo2, tmP, sched_of(layer), ta, pa);
    lc = cfgof(128, 384, bf::SMEM, PDL_B);
    bf::Args ba{(const unsigned char*)P.wb, (const unsigned char*)P.wot, (unsigned char*)P.kvacc, (unsigned char*)P.pq, P.xa, layer == 0 ? P.xb : out, P.go, layer == 0 ? P.arena + tr::C_P : nullptr,
                      layer == 0 && PF_B ? Wk : nullptr, Wv, 30, 500, 0, tl + 7};
#ifdef TUNE
    if (getenv("PFN")) ba.pfn = atoi(getenv("PFN"));
    if (getenv("PFNS")) ba.pfns = atoi(getenv("PFNS"));
    if (getenv("PFWT")) ba.pfwait = atoi(getenv("PFWT"));
    if (getenv("PFB")) ba.pf0 = layer == 0 && atoi(getenv("PFB")) ? Wk : nullptr;
#endif
    cudaLaunchKernelEx(&lc, blayer_kernel, tmXn2, ba);
    xcur = P.xb;
  }
}
```

```cpp
#include <cuda_runtime.h>
#include <cuda.h>
#include <cuda_bf16.h>
#include <stdint.h>
#include <stdlib.h>
#include <type_traits>

typedef __nv_bfloat16 bf16;

namespace cfg {
constexpr int S = 2048, DM = 640, H = 32, DH = 192, NSEG = 64, SEG = 32, NM = 8;
constexpr int HD = H * DH;
}

__device__ __forceinline__ uint32_t smem_u32(const void* p) { return (uint32_t)__cvta_generic_to_shared(p); }
__device__ __forceinline__ uint32_t mapa_u32(uint32_t a, uint32_t r) {
  uint32_t o; asm("mapa.shared::cluster.u32 %0, %1, %2;" : "=r"(o) : "r"(a), "r"(r)); return o;
}
__device__ __forceinline__ void mbar_init(uint32_t b, uint32_t c) {
  asm volatile("mbarrier.init.shared::cta.b64 [%0], %1;" :: "r"(b), "r"(c) : "memory");
}
__device__ __forceinline__ void mbar_expect_tx(uint32_t b, uint32_t bytes) {
  asm volatile("mbarrier.arrive.expect_tx.shared::cta.b64 _, [%0], %1;" :: "r"(b), "r"(bytes) : "memory");
}
__device__ __forceinline__ void mbar_arrive(uint32_t b) {
  asm volatile("mbarrier.arrive.shared::cta.b64 _, [%0];" :: "r"(b) : "memory");
}
__device__ __forceinline__ void mbar_expect_tx_if(bool c, uint32_t b, uint32_t bytes) {
  asm volatile("{\n.reg .pred p;\nsetp.ne.u32 p, %2, 0;\n@p mbarrier.arrive.expect_tx.shared::cta.b64 _, [%0], %1;\n}" :: "r"(b), "r"(bytes), "r"((uint32_t)c) : "memory");
}
__device__ __forceinline__ void mbar_arrive_if(bool c, uint32_t b) {
  asm volatile("{\n.reg .pred p;\nsetp.ne.u32 p, %1, 0;\n@p mbarrier.arrive.shared::cta.b64 _, [%0];\n}" :: "r"(b), "r"((uint32_t)c) : "memory");
}
__device__ __forceinline__ bool mbar_try(uint32_t b, uint32_t ph) {
  uint32_t p;
  asm volatile("{.reg .pred p; mbarrier.try_wait.parity.shared::cta.b64 p, [%1], %2; selp.u32 %0, 1, 0, p;}"
               : "=r"(p) : "r"(b), "r"(ph) : "memory");
  return p;
}
__device__ __forceinline__ bool mbar_try_cluster(uint32_t b, uint32_t ph) {
  uint32_t p;
  asm volatile("{.reg .pred p; mbarrier.try_wait.parity.acquire.cluster.shared::cta.b64 p, [%1], %2; selp.u32 %0, 1, 0, p;}"
               : "=r"(p) : "r"(b), "r"(ph) : "memory");
  return p;
}
#ifndef SPIN_LIMIT
#define SPIN_LIMIT (1 << 20)
#endif
__device__ __forceinline__ void mbar_wait(uint32_t b, uint32_t ph) {
  asm volatile("{\n.reg .pred p, q;\n.reg .u32 c;\nmov.u32 c, 0;\n"
               "W_%=:\nmbarrier.try_wait.parity.shared::cta.b64 p, [%0], %1;\n@p bra.uni D_%=;\n"
               "add.u32 c, c, 1;\nsetp.lt.u32 q, c, %2;\n@q bra.uni W_%=;\nD_%=:\n}"
               :: "r"(b), "r"(ph), "n"(SPIN_LIMIT) : "memory");
}
__device__ __forceinline__ void mbar_spin(uint32_t b, uint32_t ph) {
  asm volatile("{\n.reg .pred p, q;\n.reg .u32 c;\nmov.u32 c, 0;\n"
               "W_%=:\nmbarrier.test_wait.parity.shared::cta.b64 p, [%0], %1;\n@p bra D_%=;\n"
               "add.u32 c, c, 1;\nsetp.lt.u32 q, c, %2;\n@q bra W_%=;\nD_%=:\n}"
               :: "r"(b), "r"(ph), "n"(SPIN_LIMIT) : "memory");
}
#define PIN(x) asm volatile("" : "+r"(x))
__device__ __forceinline__ void mbar_wait_cluster(uint32_t b, uint32_t ph) {
  int s = 0;
  while (!mbar_try_cluster(b, ph)) { if (++s > SPIN_LIMIT) break; }
}
__device__ __forceinline__ void st_async_v2(uint32_t a, uint32_t x, uint32_t y, uint32_t mb) {
  asm volatile("st.async.weak.shared::cluster.mbarrier::complete_tx::bytes.v2.b32 [%0], {%1,%2}, [%3];"
               :: "r"(a), "r"(x), "r"(y), "r"(mb) : "memory");
}
__device__ __forceinline__ void st_async_v4(uint32_t a, uint32_t x, uint32_t y, uint32_t z, uint32_t w, uint32_t mb) {
  asm volatile("st.async.weak.shared::cluster.mbarrier::complete_tx::bytes.v4.b32 [%0], {%1,%2,%3,%4}, [%5];"
               :: "r"(a), "r"(x), "r"(y), "r"(z), "r"(w), "r"(mb) : "memory");
}
__device__ __forceinline__ void bulk_g2s(uint32_t dst, const void* src, uint32_t bytes, uint32_t mb) {
  asm volatile("cp.async.bulk.shared::cluster.global.mbarrier::complete_tx::bytes [%0], [%1], %2, [%3];"
               :: "r"(dst), "l"(src), "r"(bytes), "r"(mb) : "memory");
}
__device__ __forceinline__ void cp_async16(uint32_t dst, const void* src) {
  asm volatile("cp.async.cg.shared.global [%0], [%1], 16;" :: "r"(dst), "l"(src) : "memory");
}
__device__ __forceinline__ void cp_async_wait_all() { asm volatile("cp.async.wait_all;" ::: "memory"); }
__device__ __forceinline__ void fence_proxy_async() { asm volatile("fence.proxy.async.shared::cta;" ::: "memory"); }
__device__ __forceinline__ void bar_sync(int id, int n) { asm volatile("bar.sync %0, %1;" :: "r"(id), "r"(n) : "memory"); }
__device__ __forceinline__ void bar_arrive(int id, int n) { asm volatile("bar.arrive %0, %1;" :: "r"(id), "r"(n) : "memory"); }
__device__ __forceinline__ void cluster_sync_all() {
  asm volatile("barrier.cluster.arrive.release.aligned; barrier.cluster.wait.acquire.aligned;" ::: "memory");
}
__device__ __forceinline__ void ldsm_x4(uint32_t (&r)[4], uint32_t a) {
  asm volatile("ldmatrix.sync.aligned.m8n8.x4.shared.b16 {%0,%1,%2,%3}, [%4];"
               : "=r"(r[0]), "=r"(r[1]), "=r"(r[2]), "=r"(r[3]) : "r"(a) : "memory");
}
__device__ __forceinline__ void ldsm_x4_t(uint32_t (&r)[4], uint32_t a) {
  asm volatile("ldmatrix.sync.aligned.m8n8.x4.trans.shared.b16 {%0,%1,%2,%3}, [%4];"
               : "=r"(r[0]), "=r"(r[1]), "=r"(r[2]), "=r"(r[3]) : "r"(a) : "memory");
}
template <int IMM> __device__ __forceinline__ void ldsm_x4_i(uint32_t (&r)[4], uint32_t a) {
  asm volatile("ldmatrix.sync.aligned.m8n8.x4.shared.b16 {%0,%1,%2,%3}, [%4+%5];"
               : "=r"(r[0]), "=r"(r[1]), "=r"(r[2]), "=r"(r[3]) : "r"(a), "n"(IMM) : "memory");
}
template <int IMM> __device__ __forceinline__ void ldsm_x4_t_i(uint32_t (&r)[4], uint32_t a) {
  asm volatile("ldmatrix.sync.aligned.m8n8.x4.trans.shared.b16 {%0,%1,%2,%3}, [%4+%5];"
               : "=r"(r[0]), "=r"(r[1]), "=r"(r[2]), "=r"(r[3]) : "r"(a), "n"(IMM) : "memory");
}
template <int IMM> __device__ __forceinline__ uint4 lds128_i(uint32_t a) {
  uint4 v; asm volatile("ld.shared.v4.u32 {%0,%1,%2,%3}, [%4+%5];" : "=r"(v.x), "=r"(v.y), "=r"(v.z), "=r"(v.w) : "r"(a), "n"(IMM) : "memory"); return v;
}
template <int IMM> __device__ __forceinline__ uint2 lds64_i(uint32_t a) {
  uint2 v; asm volatile("ld.shared.v2.u32 {%0,%1}, [%2+%3];" : "=r"(v.x), "=r"(v.y) : "r"(a), "n"(IMM) : "memory"); return v;
}
template <int IMM> __device__ __forceinline__ void sts128_i(uint32_t a, uint32_t x, uint32_t y, uint32_t z, uint32_t w) {
  asm volatile("st.shared.v4.u32 [%0+%5], {%1,%2,%3,%4};" :: "r"(a), "r"(x), "r"(y), "r"(z), "r"(w), "n"(IMM) : "memory");
}
template <int IMM> __device__ __forceinline__ void sts64_i(uint32_t a, uint32_t x, uint32_t y) {
  asm volatile("st.shared.v2.u32 [%0+%3], {%1,%2};" :: "r"(a), "r"(x), "r"(y), "n"(IMM) : "memory");
}
template <int IMM> __device__ __forceinline__ void st_async_v2_i(uint32_t a, uint32_t x, uint32_t y, uint32_t mb) {
  asm volatile("st.async.weak.shared::cluster.mbarrier::complete_tx::bytes.v2.b32 [%0+%4], {%1,%2}, [%3];"
               :: "r"(a), "r"(x), "r"(y), "r"(mb), "n"(IMM) : "memory");
}
template <int IMM> __device__ __forceinline__ uint4 ld_relaxed_v4_i(const void* p) {
  uint4 v; asm volatile("ld.relaxed.gpu.global.v4.u32 {%0,%1,%2,%3}, [%4+%5];" : "=r"(v.x), "=r"(v.y), "=r"(v.z), "=r"(v.w) : "l"(p), "n"(IMM) : "memory"); return v;
}
template <int I, int N, class F> __device__ __forceinline__ void static_for(F&& f) {
  if constexpr (I < N) { f(std::integral_constant<int, I>{}); static_for<I + 1, N>(f); }
}
__device__ __forceinline__ uint32_t movm_t(uint32_t a) {
  uint32_t d; asm volatile("movmatrix.sync.aligned.m8n8.trans.b16 %0, %1;" : "=r"(d) : "r"(a)); return d;
}
__device__ __forceinline__ void mma16816(float (&d)[4], uint32_t a0, uint32_t a1, uint32_t a2, uint32_t a3, uint32_t b0, uint32_t b1) {
  asm volatile("mma.sync.aligned.m16n8k16.row.col.f32.bf16.bf16.f32 {%0,%1,%2,%3}, {%4,%5,%6,%7}, {%8,%9}, {%0,%1,%2,%3};"
               : "+f"(d[0]), "+f"(d[1]), "+f"(d[2]), "+f"(d[3]) : "r"(a0), "r"(a1), "r"(a2), "r"(a3), "r"(b0), "r"(b1));
}
__device__ __forceinline__ uint32_t pack_bf16(float lo, float hi) {
  uint32_t d; asm("cvt.rn.bf16x2.f32 %0, %1, %2;" : "=r"(d) : "f"(hi), "f"(lo)); return d;
}
__device__ __forceinline__ float bf_lo(uint32_t w) { return __uint_as_float(w << 16); }
__device__ __forceinline__ float bf_hi(uint32_t w) { return __uint_as_float(w & 0xffff0000u); }
__device__ __forceinline__ uint4 lds128(uint32_t a) {
  uint4 v; asm volatile("ld.shared.v4.u32 {%0,%1,%2,%3}, [%4];" : "=r"(v.x), "=r"(v.y), "=r"(v.z), "=r"(v.w) : "r"(a) : "memory"); return v;
}
__device__ __forceinline__ uint2 lds64(uint32_t a) {
  uint2 v; asm volatile("ld.shared.v2.u32 {%0,%1}, [%2];" : "=r"(v.x), "=r"(v.y) : "r"(a) : "memory"); return v;
}
__device__ __forceinline__ void sts128(uint32_t a, uint32_t x, uint32_t y, uint32_t z, uint32_t w) {
  asm volatile("st.shared.v4.u32 [%0], {%1,%2,%3,%4};" :: "r"(a), "r"(x), "r"(y), "r"(z), "r"(w) : "memory");
}
__device__ __forceinline__ void sts64(uint32_t a, uint32_t x, uint32_t y) {
  asm volatile("st.shared.v2.u32 [%0], {%1,%2};" :: "r"(a), "r"(x), "r"(y) : "memory");
}
__device__ __forceinline__ uint4 ld_relaxed_v4(const void* p) {
  uint4 v; asm volatile("ld.relaxed.gpu.global.v4.u32 {%0,%1,%2,%3}, [%4];" : "=r"(v.x), "=r"(v.y), "=r"(v.z), "=r"(v.w) : "l"(p) : "memory"); return v;
}
__device__ __forceinline__ uint32_t ld_relaxed_u32(const void* p) {
  uint32_t v; asm volatile("ld.relaxed.gpu.global.u32 %0, [%1];" : "=r"(v) : "l"(p) : "memory"); return v;
}
__device__ __forceinline__ void st_relaxed_v2(void* p, uint32_t a, uint32_t b) {
  asm volatile("st.relaxed.gpu.global.v2.u32 [%0], {%1,%2};" :: "l"(p), "r"(a), "r"(b) : "memory");
}
__device__ __forceinline__ void st_relaxed_u32(void* p, uint32_t v) {
  asm volatile("st.relaxed.gpu.global.u32 [%0], %1;" :: "l"(p), "r"(v) : "memory");
}
__device__ __forceinline__ uint32_t clk32() { uint32_t c; asm volatile("mov.u32 %0, %%clock;" : "=r"(c) :: "memory"); return c; }
__device__ __forceinline__ uint32_t clkdep(uint32_t v) {
  uint32_t c; asm volatile("{.reg .pred p; setp.eq.u32 p, %1, 0xdeadbeef; @p trap; mov.u32 %0, %%clock;}" : "=r"(c) : "r"(v) : "memory"); return c;
}
__device__ __forceinline__ void wgmma_fence() { asm volatile("wgmma.fence.sync.aligned;" ::: "memory"); }
__device__ __forceinline__ void wgmma_commit() { asm volatile("wgmma.commit_group.sync.aligned;" ::: "memory"); }
template <int N> __device__ __forceinline__ void wgmma_wait() { asm volatile("wgmma.wait_group.sync.aligned %0;" :: "n"(N) : "memory"); }
__device__ __forceinline__ void wgmma_n8_ss_ta(float (&d)[4], uint64_t da, uint64_t db, int acc) {
  asm volatile("{\n.reg .pred p;\nsetp.ne.b32 p, %6, 0;\n"
               "wgmma.mma_async.sync.aligned.m64n8k16.f32.bf16.bf16 {%0,%1,%2,%3}, %4, %5, p, 1, 1, 1, 0;\n}\n"
               : "+f"(d[0]), "+f"(d[1]), "+f"(d[2]), "+f"(d[3]) : "l"(da), "l"(db), "r"(acc));
}
__device__ __forceinline__ uint64_t make_desc(uint32_t saddr, uint32_t lbo_bytes, uint32_t sbo_bytes, uint32_t swz) {
  return (uint64_t)((saddr & 0x3FFFF) >> 4) | ((uint64_t)(lbo_bytes >> 4) << 16) | ((uint64_t)(sbo_bytes >> 4) << 32) | ((uint64_t)swz << 62);
}


__device__ __forceinline__ bool elect_one() {
  uint32_t p; asm volatile("{\n.reg .pred p;\nelect.sync _|p, 0xffffffff;\nselp.u32 %0, 1, 0, p;\n}" : "=r"(p)); return p;
}
__device__ __forceinline__ void tma_load_3d(uint32_t dst, const CUtensorMap* tm, int c0, int c1, int c2, uint32_t mb) {
  asm volatile("cp.async.bulk.tensor.3d.shared::cluster.global.mbarrier::complete_tx::bytes [%0], [%1, {%3, %4, %5}], [%2];"
               :: "r"(dst), "l"(tm), "r"(mb), "r"(c0), "r"(c1), "r"(c2) : "memory");
}
__device__ __forceinline__ void tma_load_2d(uint32_t dst, const CUtensorMap* tm, int c0, int c1, uint32_t mb) {
  asm volatile("cp.async.bulk.tensor.2d.shared::cluster.global.mbarrier::complete_tx::bytes [%0], [%1, {%3, %4}], [%2];"
               :: "r"(dst), "l"(tm), "r"(mb), "r"(c0), "r"(c1) : "memory");
}
__device__ __forceinline__ void bulk_s2g(void* dst, uint32_t src, uint32_t bytes) {
  asm volatile("cp.async.bulk.global.shared::cta.bulk_group [%0], [%1], %2;" :: "l"(dst), "r"(src), "r"(bytes) : "memory");
}
__device__ __forceinline__ uint64_t policy_evict_first() {
  uint64_t p; asm volatile("createpolicy.fractional.L2::evict_first.b64 %0, 1.0;" : "=l"(p)); return p;
}
__device__ __forceinline__ void bulk_s2g_hint(void* dst, uint32_t src, uint32_t bytes, uint64_t pol) {
  asm volatile("cp.async.bulk.global.shared::cta.bulk_group.L2::cache_hint [%0], [%1], %2, %3;" :: "l"(dst), "r"(src), "r"(bytes), "l"(pol) : "memory");
}
__device__ __forceinline__ void bulk_commit() { asm volatile("cp.async.bulk.commit_group;" ::: "memory"); }
template <int N> __device__ __forceinline__ void bulk_wait_read() { asm volatile("cp.async.bulk.wait_group.read %0;" :: "n"(N) : "memory"); }
template <int N> __device__ __forceinline__ void bulk_wait() { asm volatile("cp.async.bulk.wait_group %0;" :: "n"(N) : "memory"); }
__device__ __forceinline__ void stsm_x4(uint32_t a, uint32_t r0, uint32_t r1, uint32_t r2, uint32_t r3) {
  asm volatile("stmatrix.sync.aligned.m8n8.x4.shared.b16 [%0], {%1,%2,%3,%4};" :: "r"(a), "r"(r0), "r"(r1), "r"(r2), "r"(r3) : "memory");
}
__device__ __forceinline__ void stsm_x2(uint32_t a, uint32_t r0, uint32_t r1) {
  asm volatile("stmatrix.sync.aligned.m8n8.x2.shared.b16 [%0], {%1,%2};" :: "r"(a), "r"(r0), "r"(r1) : "memory");
}
__device__ __forceinline__ void ldsm_x2(uint32_t (&r)[2], uint32_t a) {
  asm volatile("ldmatrix.sync.aligned.m8n8.x2.shared.b16 {%0,%1}, [%2];" : "=r"(r[0]), "=r"(r[1]) : "r"(a) : "memory");
}
__device__ __forceinline__ void ldsm_x2_t(uint32_t (&r)[2], uint32_t a) {
  asm volatile("ldmatrix.sync.aligned.m8n8.x2.trans.shared.b16 {%0,%1}, [%2];" : "=r"(r[0]), "=r"(r[1]) : "r"(a) : "memory");
}
__device__ __forceinline__ float bf16r(float x) { return __uint_as_float(pack_bf16(0.f, x) & 0xffff0000u); }
__device__ __forceinline__ void bf16r2(float& a, float& b) { const uint32_t w = pack_bf16(a, b); a = bf_lo(w); b = bf_hi(w); }
__device__ __forceinline__ float rcpf(float x) { float r; asm("rcp.approx.ftz.f32 %0, %1;" : "=f"(r) : "f"(x)); return r; }
__device__ __forceinline__ float ex2f(float x) { float e; asm("ex2.approx.ftz.f32 %0, %1;" : "=f"(e) : "f"(x)); return e; }
__device__ __forceinline__ void prefetch_tmap(const CUtensorMap* tm) { asm volatile("prefetch.tensormap [%0];" :: "l"(tm) : "memory"); }

#ifdef TIMELINE
__device__ unsigned long long g_tl[2 * 64];
__device__ unsigned long long g_log[2 * 132 * 64 * 2 + 2];
__device__ unsigned long long g_tl2[4 * 64];
__device__ __forceinline__ unsigned long long gtime() { unsigned long long t; asm volatile("mov.u64 %0, %%globaltimer;" : "=l"(t)); return t; }
#define TL_BEGIN(id) do { if (threadIdx.x == 0) atomicMin(&g_tl[2 * (id)], gtime()); } while (0)
#define TL_END(id) do { if ((threadIdx.x & 31) == 0) atomicMax(&g_tl[2 * (id) + 1], gtime()); } while (0)
#define TL_ACC(idx, t0) do { if (threadIdx.x == 0 && m >= 4 && m < 11) { atomicAdd(&g_tl2[idx], gtime() - (t0)); atomicAdd(&g_tl2[(idx) + 1], 1ull); } } while (0)
#define TL_NOW() gtime()
#define TL2(idx) asm volatile("{\n.reg .pred p;\nsetp.eq.u32 p, %2, 0;\n@p red.relaxed.gpu.global.max.u64 [%0], %1;\n}" :: "l"(&g_tl2[idx]), "l"(gtime()), "r"(threadIdx.x) : "memory")
#define TLW(idx) asm volatile("{\n.reg .pred p;\nsetp.eq.u32 p, %2, 0;\n@p red.relaxed.gpu.global.max.u64 [%0], %1;\n@p red.relaxed.gpu.global.add.u64 [%0+128], %1;\n}" :: "l"(&g_tl2[idx]), "l"(gtime() - g_tl0), "r"(threadIdx.x & 31) : "memory")
#define TL_BEGIN0(id) atomicMin(&g_tl[2 * (id)], gtime())
#else
#define TL_ACC(idx, t0)
#define TL_NOW() 0ull
#define TL2(idx)
#define TL_BEGIN0(id)
#define TLW(idx)
#define TL_BEGIN(id)
#define TL_END(id)
#endif
template <int TA, int TB> __device__ __forceinline__ void wgmma_n24(float (&d)[12], uint64_t da, uint64_t db, int acc) {
  asm volatile("{\n.reg .pred p;\nsetp.ne.b32 p, %14, 0;\n"
    "wgmma.mma_async.sync.aligned.m64n24k16.f32.bf16.bf16 {%0, %1, %2, %3, %4, %5, %6, %7, %8, %9, %10, %11}, %12, %13, p, 1, 1, %15, %16;\n}\n"
    : "+f"(d[0]), "+f"(d[1]), "+f"(d[2]), "+f"(d[3]), "+f"(d[4]), "+f"(d[5]), "+f"(d[6]), "+f"(d[7]), "+f"(d[8]), "+f"(d[9]), "+f"(d[10]), "+f"(d[11])
    : "l"(da), "l"(db), "r"(acc), "n"(TA), "n"(TB));
}

template <int TA, int TB> __device__ __forceinline__ void wgmma_n80(float (&d)[40], uint64_t da, uint64_t db, int acc) {
  asm volatile("{\n.reg .pred p;\nsetp.ne.b32 p, %42, 0;\n"
    "wgmma.mma_async.sync.aligned.m64n80k16.f32.bf16.bf16 {%0, %1, %2, %3, %4, %5, %6, %7, %8, %9, %10, %11, %12, %13, %14, %15, %16, %17, %18, %19, %20, %21, %22, %23, %24, %25, %26, %27, %28, %29, %30, %31, %32, %33, %34, %35, %36, %37, %38, %39}, %40, %41, p, 1, 1, %43, %44;\n}\n"
    : "+f"(d[0]), "+f"(d[1]), "+f"(d[2]), "+f"(d[3]), "+f"(d[4]), "+f"(d[5]), "+f"(d[6]), "+f"(d[7]), "+f"(d[8]), "+f"(d[9]), "+f"(d[10]), "+f"(d[11]), "+f"(d[12]), "+f"(d[13]), "+f"(d[14]), "+f"(d[15]), "+f"(d[16]), "+f"(d[17]), "+f"(d[18]), "+f"(d[19]), "+f"(d[20]), "+f"(d[21]), "+f"(d[22]), "+f"(d[23]), "+f"(d[24]), "+f"(d[25]), "+f"(d[26]), "+f"(d[27]), "+f"(d[28]), "+f"(d[29]), "+f"(d[30]), "+f"(d[31]), "+f"(d[32]), "+f"(d[33]), "+f"(d[34]), "+f"(d[35]), "+f"(d[36]), "+f"(d[37]), "+f"(d[38]), "+f"(d[39])
    : "l"(da), "l"(db), "r"(acc), "n"(TA), "n"(TB));
}

template <int TA, int TB> __device__ __forceinline__ void wgmma_n128(float (&d)[64], uint64_t da, uint64_t db, int acc) {
  asm volatile("{\n.reg .pred p;\nsetp.ne.b32 p, %66, 0;\n"
    "wgmma.mma_async.sync.aligned.m64n128k16.f32.bf16.bf16 {%0, %1, %2, %3, %4, %5, %6, %7, %8, %9, %10, %11, %12, %13, %14, %15, %16, %17, %18, %19, %20, %21, %22, %23, %24, %25, %26, %27, %28, %29, %30, %31, %32, %33, %34, %35, %36, %37, %38, %39, %40, %41, %42, %43, %44, %45, %46, %47, %48, %49, %50, %51, %52, %53, %54, %55, %56, %57, %58, %59, %60, %61, %62, %63}, %64, %65, p, 1, 1, %67, %68;\n}\n"
    : "+f"(d[0]), "+f"(d[1]), "+f"(d[2]), "+f"(d[3]), "+f"(d[4]), "+f"(d[5]), "+f"(d[6]), "+f"(d[7]), "+f"(d[8]), "+f"(d[9]), "+f"(d[10]), "+f"(d[11]), "+f"(d[12]), "+f"(d[13]), "+f"(d[14]), "+f"(d[15]), "+f"(d[16]), "+f"(d[17]), "+f"(d[18]), "+f"(d[19]), "+f"(d[20]), "+f"(d[21]), "+f"(d[22]), "+f"(d[23]), "+f"(d[24]), "+f"(d[25]), "+f"(d[26]), "+f"(d[27]), "+f"(d[28]), "+f"(d[29]), "+f"(d[30]), "+f"(d[31]), "+f"(d[32]), "+f"(d[33]), "+f"(d[34]), "+f"(d[35]), "+f"(d[36]), "+f"(d[37]), "+f"(d[38]), "+f"(d[39]), "+f"(d[40]), "+f"(d[41]), "+f"(d[42]), "+f"(d[43]), "+f"(d[44]), "+f"(d[45]), "+f"(d[46]), "+f"(d[47]), "+f"(d[48]), "+f"(d[49]), "+f"(d[50]), "+f"(d[51]), "+f"(d[52]), "+f"(d[53]), "+f"(d[54]), "+f"(d[55]), "+f"(d[56]), "+f"(d[57]), "+f"(d[58]), "+f"(d[59]), "+f"(d[60]), "+f"(d[61]), "+f"(d[62]), "+f"(d[63])
    : "l"(da), "l"(db), "r"(acc), "n"(TA), "n"(TB));
}

template <int TA, int TB> __device__ __forceinline__ void wgmma_n192(float (&d)[96], uint64_t da, uint64_t db, int acc) {
  asm volatile("{\n.reg .pred p;\nsetp.ne.b32 p, %98, 0;\n"
    "wgmma.mma_async.sync.aligned.m64n192k16.f32.bf16.bf16 {%0, %1, %2, %3, %4, %5, %6, %7, %8, %9, %10, %11, %12, %13, %14, %15, %16, %17, %18, %19, %20, %21, %22, %23, %24, %25, %26, %27, %28, %29, %30, %31, %32, %33, %34, %35, %36, %37, %38, %39, %40, %41, %42, %43, %44, %45, %46, %47, %48, %49, %50, %51, %52, %53, %54, %55, %56, %57, %58, %59, %60, %61, %62, %63, %64, %65, %66, %67, %68, %69, %70, %71, %72, %73, %74, %75, %76, %77, %78, %79, %80, %81, %82, %83, %84, %85, %86, %87, %88, %89, %90, %91, %92, %93, %94, %95}, %96, %97, p, 1, 1, %99, %100;\n}\n"
    : "+f"(d[0]), "+f"(d[1]), "+f"(d[2]), "+f"(d[3]), "+f"(d[4]), "+f"(d[5]), "+f"(d[6]), "+f"(d[7]), "+f"(d[8]), "+f"(d[9]), "+f"(d[10]), "+f"(d[11]), "+f"(d[12]), "+f"(d[13]), "+f"(d[14]), "+f"(d[15]), "+f"(d[16]), "+f"(d[17]), "+f"(d[18]), "+f"(d[19]), "+f"(d[20]), "+f"(d[21]), "+f"(d[22]), "+f"(d[23]), "+f"(d[24]), "+f"(d[25]), "+f"(d[26]), "+f"(d[27]), "+f"(d[28]), "+f"(d[29]), "+f"(d[30]), "+f"(d[31]), "+f"(d[32]), "+f"(d[33]), "+f"(d[34]), "+f"(d[35]), "+f"(d[36]), "+f"(d[37]), "+f"(d[38]), "+f"(d[39]), "+f"(d[40]), "+f"(d[41]), "+f"(d[42]), "+f"(d[43]), "+f"(d[44]), "+f"(d[45]), "+f"(d[46]), "+f"(d[47]), "+f"(d[48]), "+f"(d[49]), "+f"(d[50]), "+f"(d[51]), "+f"(d[52]), "+f"(d[53]), "+f"(d[54]), "+f"(d[55]), "+f"(d[56]), "+f"(d[57]), "+f"(d[58]), "+f"(d[59]), "+f"(d[60]), "+f"(d[61]), "+f"(d[62]), "+f"(d[63]), "+f"(d[64]), "+f"(d[65]), "+f"(d[66]), "+f"(d[67]), "+f"(d[68]), "+f"(d[69]), "+f"(d[70]), "+f"(d[71]), "+f"(d[72]), "+f"(d[73]), "+f"(d[74]), "+f"(d[75]), "+f"(d[76]), "+f"(d[77]), "+f"(d[78]), "+f"(d[79]), "+f"(d[80]), "+f"(d[81]), "+f"(d[82]), "+f"(d[83]), "+f"(d[84]), "+f"(d[85]), "+f"(d[86]), "+f"(d[87]), "+f"(d[88]), "+f"(d[89]), "+f"(d[90]), "+f"(d[91]), "+f"(d[92]), "+f"(d[93]), "+f"(d[94]), "+f"(d[95])
    : "l"(da), "l"(db), "r"(acc), "n"(TA), "n"(TB));
}

template <int TA, int TB> __device__ __forceinline__ void wgmma_n256(float (&d)[128], uint64_t da, uint64_t db, int acc) {
  asm volatile("{\n.reg .pred p;\nsetp.ne.b32 p, %130, 0;\n"
    "wgmma.mma_async.sync.aligned.m64n256k16.f32.bf16.bf16 {%0, %1, %2, %3, %4, %5, %6, %7, %8, %9, %10, %11, %12, %13, %14, %15, %16, %17, %18, %19, %20, %21, %22, %23, %24, %25, %26, %27, %28, %29, %30, %31, %32, %33, %34, %35, %36, %37, %38, %39, %40, %41, %42, %43, %44, %45, %46, %47, %48, %49, %50, %51, %52, %53, %54, %55, %56, %57, %58, %59, %60, %61, %62, %63, %64, %65, %66, %67, %68, %69, %70, %71, %72, %73, %74, %75, %76, %77, %78, %79, %80, %81, %82, %83, %84, %85, %86, %87, %88, %89, %90, %91, %92, %93, %94, %95, %96, %97, %98, %99, %100, %101, %102, %103, %104, %105, %106, %107, %108, %109, %110, %111, %112, %113, %114, %115, %116, %117, %118, %119, %120, %121, %122, %123, %124, %125, %126, %127}, %128, %129, p, 1, 1, %131, %132;\n}\n"
    : "+f"(d[0]), "+f"(d[1]), "+f"(d[2]), "+f"(d[3]), "+f"(d[4]), "+f"(d[5]), "+f"(d[6]), "+f"(d[7]), "+f"(d[8]), "+f"(d[9]), "+f"(d[10]), "+f"(d[11]), "+f"(d[12]), "+f"(d[13]), "+f"(d[14]), "+f"(d[15]), "+f"(d[16]), "+f"(d[17]), "+f"(d[18]), "+f"(d[19]), "+f"(d[20]), "+f"(d[21]), "+f"(d[22]), "+f"(d[23]), "+f"(d[24]), "+f"(d[25]), "+f"(d[26]), "+f"(d[27]), "+f"(d[28]), "+f"(d[29]), "+f"(d[30]), "+f"(d[31]), "+f"(d[32]), "+f"(d[33]), "+f"(d[34]), "+f"(d[35]), "+f"(d[36]), "+f"(d[37]), "+f"(d[38]), "+f"(d[39]), "+f"(d[40]), "+f"(d[41]), "+f"(d[42]), "+f"(d[43]), "+f"(d[44]), "+f"(d[45]), "+f"(d[46]), "+f"(d[47]), "+f"(d[48]), "+f"(d[49]), "+f"(d[50]), "+f"(d[51]), "+f"(d[52]), "+f"(d[53]), "+f"(d[54]), "+f"(d[55]), "+f"(d[56]), "+f"(d[57]), "+f"(d[58]), "+f"(d[59]), "+f"(d[60]), "+f"(d[61]), "+f"(d[62]), "+f"(d[63]), "+f"(d[64]), "+f"(d[65]), "+f"(d[66]), "+f"(d[67]), "+f"(d[68]), "+f"(d[69]), "+f"(d[70]), "+f"(d[71]), "+f"(d[72]), "+f"(d[73]), "+f"(d[74]), "+f"(d[75]), "+f"(d[76]), "+f"(d[77]), "+f"(d[78]), "+f"(d[79]), "+f"(d[80]), "+f"(d[81]), "+f"(d[82]), "+f"(d[83]), "+f"(d[84]), "+f"(d[85]), "+f"(d[86]), "+f"(d[87]), "+f"(d[88]), "+f"(d[89]), "+f"(d[90]), "+f"(d[91]), "+f"(d[92]), "+f"(d[93]), "+f"(d[94]), "+f"(d[95]), "+f"(d[96]), "+f"(d[97]), "+f"(d[98]), "+f"(d[99]), "+f"(d[100]), "+f"(d[101]), "+f"(d[102]), "+f"(d[103]), "+f"(d[104]), "+f"(d[105]), "+f"(d[106]), "+f"(d[107]), "+f"(d[108]), "+f"(d[109]), "+f"(d[110]), "+f"(d[111]), "+f"(d[112]), "+f"(d[113]), "+f"(d[114]), "+f"(d[115]), "+f"(d[116]), "+f"(d[117]), "+f"(d[118]), "+f"(d[119]), "+f"(d[120]), "+f"(d[121]), "+f"(d[122]), "+f"(d[123]), "+f"(d[124]), "+f"(d[125]), "+f"(d[126]), "+f"(d[127])
    : "l"(da), "l"(db), "r"(acc), "n"(TA), "n"(TB));
}

template <int TB> __device__ __forceinline__ void wgmma_rs_n24(float (&d)[12], uint32_t a0, uint32_t a1, uint32_t a2, uint32_t a3, uint64_t db, int acc) {
  asm volatile("{\n.reg .pred p;\nsetp.ne.b32 p, %17, 0;\n"
    "wgmma.mma_async.sync.aligned.m64n24k16.f32.bf16.bf16 {%0, %1, %2, %3, %4, %5, %6, %7, %8, %9, %10, %11}, {%12, %13, %14, %15}, %16, p, 1, 1, %18;\n}\n"
    : "+f"(d[0]), "+f"(d[1]), "+f"(d[2]), "+f"(d[3]), "+f"(d[4]), "+f"(d[5]), "+f"(d[6]), "+f"(d[7]), "+f"(d[8]), "+f"(d[9]), "+f"(d[10]), "+f"(d[11])
    : "r"(a0), "r"(a1), "r"(a2), "r"(a3), "l"(db), "r"(acc), "n"(TB));
}

template <int TB> __device__ __forceinline__ void wgmma_rs_n40(float (&d)[20], uint32_t a0, uint32_t a1, uint32_t a2, uint32_t a3, uint64_t db, int acc) {
  asm volatile("{\n.reg .pred p;\nsetp.ne.b32 p, %25, 0;\n"
    "wgmma.mma_async.sync.aligned.m64n40k16.f32.bf16.bf16 {%0, %1, %2, %3, %4, %5, %6, %7, %8, %9, %10, %11, %12, %13, %14, %15, %16, %17, %18, %19}, {%20, %21, %22, %23}, %24, p, 1, 1, %26;\n}\n"
    : "+f"(d[0]), "+f"(d[1]), "+f"(d[2]), "+f"(d[3]), "+f"(d[4]), "+f"(d[5]), "+f"(d[6]), "+f"(d[7]), "+f"(d[8]), "+f"(d[9]), "+f"(d[10]), "+f"(d[11]), "+f"(d[12]), "+f"(d[13]), "+f"(d[14]), "+f"(d[15]), "+f"(d[16]), "+f"(d[17]), "+f"(d[18]), "+f"(d[19])
    : "r"(a0), "r"(a1), "r"(a2), "r"(a3), "l"(db), "r"(acc), "n"(TB));
}

template <int TB> __device__ __forceinline__ void wgmma_rs_n192(float (&d)[96], uint32_t a0, uint32_t a1, uint32_t a2, uint32_t a3, uint64_t db, int acc) {
  asm volatile("{\n.reg .pred p;\nsetp.ne.b32 p, %101, 0;\n"
    "wgmma.mma_async.sync.aligned.m64n192k16.f32.bf16.bf16 {%0, %1, %2, %3, %4, %5, %6, %7, %8, %9, %10, %11, %12, %13, %14, %15, %16, %17, %18, %19, %20, %21, %22, %23, %24, %25, %26, %27, %28, %29, %30, %31, %32, %33, %34, %35, %36, %37, %38, %39, %40, %41, %42, %43, %44, %45, %46, %47, %48, %49, %50, %51, %52, %53, %54, %55, %56, %57, %58, %59, %60, %61, %62, %63, %64, %65, %66, %67, %68, %69, %70, %71, %72, %73, %74, %75, %76, %77, %78, %79, %80, %81, %82, %83, %84, %85, %86, %87, %88, %89, %90, %91, %92, %93, %94, %95}, {%96, %97, %98, %99}, %100, p, 1, 1, %102;\n}\n"
    : "+f"(d[0]), "+f"(d[1]), "+f"(d[2]), "+f"(d[3]), "+f"(d[4]), "+f"(d[5]), "+f"(d[6]), "+f"(d[7]), "+f"(d[8]), "+f"(d[9]), "+f"(d[10]), "+f"(d[11]), "+f"(d[12]), "+f"(d[13]), "+f"(d[14]), "+f"(d[15]), "+f"(d[16]), "+f"(d[17]), "+f"(d[18]), "+f"(d[19]), "+f"(d[20]), "+f"(d[21]), "+f"(d[22]), "+f"(d[23]), "+f"(d[24]), "+f"(d[25]), "+f"(d[26]), "+f"(d[27]), "+f"(d[28]), "+f"(d[29]), "+f"(d[30]), "+f"(d[31]), "+f"(d[32]), "+f"(d[33]), "+f"(d[34]), "+f"(d[35]), "+f"(d[36]), "+f"(d[37]), "+f"(d[38]), "+f"(d[39]), "+f"(d[40]), "+f"(d[41]), "+f"(d[42]), "+f"(d[43]), "+f"(d[44]), "+f"(d[45]), "+f"(d[46]), "+f"(d[47]), "+f"(d[48]), "+f"(d[49]), "+f"(d[50]), "+f"(d[51]), "+f"(d[52]), "+f"(d[53]), "+f"(d[54]), "+f"(d[55]), "+f"(d[56]), "+f"(d[57]), "+f"(d[58]), "+f"(d[59]), "+f"(d[60]), "+f"(d[61]), "+f"(d[62]), "+f"(d[63]), "+f"(d[64]), "+f"(d[65]), "+f"(d[66]), "+f"(d[67]), "+f"(d[68]), "+f"(d[69]), "+f"(d[70]), "+f"(d[71]), "+f"(d[72]), "+f"(d[73]), "+f"(d[74]), "+f"(d[75]), "+f"(d[76]), "+f"(d[77]), "+f"(d[78]), "+f"(d[79]), "+f"(d[80]), "+f"(d[81]), "+f"(d[82]), "+f"(d[83]), "+f"(d[84]), "+f"(d[85]), "+f"(d[86]), "+f"(d[87]), "+f"(d[88]), "+f"(d[89]), "+f"(d[90]), "+f"(d[91]), "+f"(d[92]), "+f"(d[93]), "+f"(d[94]), "+f"(d[95])
    : "r"(a0), "r"(a1), "r"(a2), "r"(a3), "l"(db), "r"(acc), "n"(TB));
}
constexpr uint32_t AR_ACC = 0;
constexpr uint32_t AR_TAB = 0x100000;
constexpr uint32_t AR_PROG = 0x101000;
__host__ __device__ constexpr uint32_t prog_off(int h, int j) { return AR_PROG + h * 128 + j * 4; }
constexpr uint32_t AR_CNT = 0x108000;
constexpr uint32_t AR_QUEUE = 0x109000;
constexpr uint32_t AR_SIZE = 0x10a000;

struct ChainArgs {
  const bf16* mem0;
  const uint2* xh;
  unsigned char *kg, *vg;
  unsigned char* arena;
  unsigned* go;
  uint32_t* dbg;
  uint32_t delay;
  int margin;
  int tl;
};

namespace ch {
constexpr int OFF_WQ = 0;
constexpr int OFF_X = 81920;
constexpr int OFF_MEM = OFF_X + 40960;
constexpr int OFF_WO = OFF_MEM + 10240;
constexpr int WOK = 8 * 896;
constexpr int OFF_KV = OFF_WO + 10 * WOK;
constexpr int KVB = 5120;
constexpr int OFF_O = OFF_KV + 4 * KVB;
constexpr int OFF_Q = OFF_O + 1024;
constexpr int OFF_S = OFF_O + 3072;
constexpr int OFF_SR = OFF_S + 1536;
constexpr int OFF_LT = OFF_SR + 1280;
constexpr int OFF_BAR = OFF_LT + 512;
constexpr int SMEM = OFF_BAR + 256;
static_assert(SMEM <= 232448, "smem");
constexpr int MB_S = OFF_BAR, MB_O = OFF_BAR + 8, MB_X = OFF_BAR + 16;
constexpr int MB_K = OFF_BAR + 128, MB_V = MB_K + 16, MB_Q = MB_K + 32, MB_R = MB_K + 48;
constexpr int SC_IN = OFF_BAR + 64;
constexpr int SC_MX = OFF_S;
constexpr int SC_W = OFF_BAR + 96;
constexpr int WOS = 448;
enum { B_MEM0 = 1, B_QK, B_SL, B_V, B_O, B_RED, B_X, B_C, B_H, B_MEM1, B_A, B_G, B_E };
#ifndef NQ1
#define NQ1 6
#endif
#ifndef NQ0
#define NQ0 4
#endif
#ifndef NP0
#define NP0 4
#endif
#ifndef NWO
#define NWO 5
#endif
#ifndef NWP
#define NWP 4
#endif
#ifndef NB0
#define NB0 3
#endif
#ifndef BBS
#define BBS 100
#endif
#ifndef VSYNC
#define VSYNC 0
#endif
#ifndef XPOS
#define XPOS 0
#endif
#ifndef XPD
#define XPD 300
#endif
#ifndef WOF
#define WOF 0
#endif
#ifndef XBYTES
#define XBYTES 36864
#endif
#ifndef NRT
#define NRT 7
#endif
#ifndef NRF
#define NRF 2
#endif
#ifndef NPM0
#define NPM0 2
#endif
#ifndef NPM1
#define NPM1 2
#endif
#ifndef RSYNC
#define RSYNC 1
#endif
#ifndef PFK
#define PFK 1
#endif
#ifndef PA0
#define PA0 3
#endif
#ifndef PA1
#define PA1 0
#endif
#ifndef PB0
#define PB0 7
#endif
#ifndef PB1
#define PB1 5
#endif
#ifndef PQE
#define PQE 1
#endif
#ifndef XT
#define XT 30
#endif
static_assert(NPM0 >= 2 && NPM1 >= 2, "the K / V blocks live in the last two k-steps of Wo");
}

#ifndef CHAIN_TIMING
#define CHAIN_TIMING 0
#endif
#if CHAIN_TIMING
#ifndef TR0
#define TR0 41
#endif
#ifndef TSMASK
#define TSMASK 0xffff
#endif
#define TSV(i, v) do { if ((TSMASK >> (i)) & 1) asm volatile("st.shared.u32 [%0+%1], %2;" :: "r"(tsb), "n"((i) * 4), "r"(v) : "memory"); } while (0)
#define TS(i) TSV(i, clk32())
#define TS_SETUP() const uint32_t tsb = sb + ((s == TR0 || s == TR0 + 1) ? OFF_BAR + 128 + ((s - TR0) * 12 + warp) * 48 : OFF_SR + 1152)
#else
#define TS(i)
#define TSV(i, v)
#define TS_SETUP()
#endif
#ifndef POLL_DELAY
#define POLL_DELAY 590
#endif
#ifndef XN
#define XN 40
#endif
#ifndef PF0
#define PF0 8
#endif
#ifndef PFS
#define PFS 3
#endif
#ifndef XDELAY
#define XDELAY 0
#endif
#ifndef NOKM
#define NOKM 0
#endif
#ifndef PFX
#define PFX 3
#endif
#ifndef NVE
#define NVE 10
#endif
#ifndef VET
#define VET 19
#endif
#ifndef MEMFIRST
#define MEMFIRST 1
#endif
#ifndef GD0
#define GD0 -1
#endif
#ifndef PM1
#define PM1 1
#endif
#ifndef GD1
#define GD1 30
#endif
#ifndef GD2
#define GD2 150
#endif
#ifndef CEARLY
#define CEARLY 1
#endif
#ifndef PFACC
#define PFACC 1
#endif
template <int V> using IC = std::integral_constant<int, V>;
__device__ __forceinline__ uint32_t clk_v() { uint64_t c; asm volatile("mov.u64 %0, %%clock64;" : "=l"(c) :: "memory"); return (uint32_t)c; }
__device__ __forceinline__ int fresh(int x) { int y; asm volatile("shfl.sync.bfly.b32 %0, %1, 0, 0x1f, 0xffffffff;" : "=r"(y) : "r"(x)); return y; }
#define SFENCE2(x, d) asm volatile("{\n.reg .pred p;\nsetp.eq.u32 p, %0, 0x7fffffff;\n@p st.shared.u32 [%0], %1;\n}" :: "r"(x), "r"(d) : "memory")
#define SFENCE(x) asm volatile("{\n.reg .pred p;\nsetp.eq.u32 p, %0, 0x7fffffff;\n@p st.shared.u32 [%0], %0;\n}" :: "r"(x) : "memory")
template <int I> __device__ __forceinline__ void bbfence(uint32_t x) {
  asm volatile("{\n.reg .pred p;\nsetp.eq.u32 p, %0, %1;\nL_%=:\n@p st.volatile.shared.u32 [%0], %0;\n@p bra.uni L_%=;\n}" :: "r"(x), "n"(4 * I) : "memory");
}
__device__ __forceinline__ float uniform_f(float x) { return __uint_as_float(__reduce_max_sync(0xffffffffu, __float_as_uint(x))); }

__device__ __forceinline__ void mma16816h(float (&d)[4], const uint32_t (&a)[4], uint32_t b0, uint32_t b1) {
  asm volatile("mma.sync.aligned.m16n8k16.row.col.f32.f16.f16.f32 {%0,%1,%2,%3}, {%4,%5,%6,%7}, {%8,%9}, {%0,%1,%2,%3};"
               : "+f"(d[0]), "+f"(d[1]), "+f"(d[2]), "+f"(d[3]) : "r"(a[0]), "r"(a[1]), "r"(a[2]), "r"(a[3]), "r"(b0), "r"(b1));
}
__device__ __forceinline__ void mma1688(float (&d)[4], uint32_t a0, uint32_t a1, uint32_t b0) {
  asm volatile("mma.sync.aligned.m16n8k8.row.col.f32.bf16.bf16.f32 {%0,%1,%2,%3}, {%4,%5}, {%6}, {%0,%1,%2,%3};"
               : "+f"(d[0]), "+f"(d[1]), "+f"(d[2]), "+f"(d[3]) : "r"(a0), "r"(a1), "r"(b0));
}
template <int OFF16, int ACC> __device__ __forceinline__ void wgmma_rs32h(float (&d)[16], const uint32_t (&a)[4], uint32_t dlo) {
  asm volatile("{\n.reg .pred p;\n.reg .b32 t;\n.reg .b64 db;\nsetp.ne.b32 p, %22, 0;\nadd.u32 t, %20, %21;\nmov.b64 db, {t, 0x40000040};\n"
    "wgmma.mma_async.sync.aligned.m64n32k16.f32.f16.f16 {%0,%1,%2,%3,%4,%5,%6,%7,%8,%9,%10,%11,%12,%13,%14,%15}, {%16,%17,%18,%19}, db, p, 1, 1, 0;\n}\n"
    : "+f"(d[0]), "+f"(d[1]), "+f"(d[2]), "+f"(d[3]), "+f"(d[4]), "+f"(d[5]), "+f"(d[6]), "+f"(d[7]), "+f"(d[8]), "+f"(d[9]), "+f"(d[10]), "+f"(d[11]),
      "+f"(d[12]), "+f"(d[13]), "+f"(d[14]), "+f"(d[15])
    : "r"(a[0]), "r"(a[1]), "r"(a[2]), "r"(a[3]), "r"(dlo), "n"(OFF16), "n"(ACC));
}
template <int IMM> __device__ __forceinline__ void stsm_x4_t_i(uint32_t a, uint32_t r0, uint32_t r1, uint32_t r2, uint32_t r3) {
  asm volatile("stmatrix.sync.aligned.m8n8.x4.trans.shared.b16 [%0+%5], {%1,%2,%3,%4};" :: "r"(a), "r"(r0), "r"(r1), "r"(r2), "r"(r3), "n"(IMM) : "memory");
}
template <int IMM> __device__ __forceinline__ void stsm_x2_t_i(uint32_t a, uint32_t r0, uint32_t r1) {
  asm volatile("stmatrix.sync.aligned.m8n8.x2.trans.shared.b16 [%0+%3], {%1,%2};" :: "r"(a), "r"(r0), "r"(r1), "n"(IMM) : "memory");
}
template <int IMM> __device__ __forceinline__ void st_async_b32_i(uint32_t a, uint32_t x, uint32_t mb) {
  asm volatile("st.async.weak.shared::cluster.mbarrier::complete_tx::bytes.b32 [%0+%3], %1, [%2];" :: "r"(a), "r"(x), "r"(mb), "n"(IMM) : "memory");
}
template <int IMM> __device__ __forceinline__ void ld_relaxed_v4_if(uint4& v, const void* p, uint32_t c) {
  asm volatile("{\n.reg .pred p;\nsetp.ne.u32 p, %6, 0;\n@p ld.relaxed.gpu.global.v4.u32 {%0,%1,%2,%3}, [%4+%5];\n}"
               : "+r"(v.x), "+r"(v.y), "+r"(v.z), "+r"(v.w) : "l"(p), "n"(IMM), "r"(c) : "memory");
}
template <int IMM> __device__ __forceinline__ void ldsm_x2_i(uint32_t (&r)[2], uint32_t a) {
  asm volatile("ldmatrix.sync.aligned.m8n8.x2.shared.b16 {%0,%1}, [%2+%3];" : "=r"(r[0]), "=r"(r[1]) : "r"(a), "n"(IMM) : "memory");
}
template <int IMM> __device__ __forceinline__ uint32_t ldsm_x1_t_i(uint32_t a) {
  uint32_t r; asm volatile("ldmatrix.sync.aligned.m8n8.x1.trans.shared.b16 {%0}, [%1+%2];" : "=r"(r) : "r"(a), "n"(IMM) : "memory"); return r;
}
template <int IMM> __device__ __forceinline__ uint32_t lds32_i(uint32_t a) {
  uint32_t v; asm volatile("ld.shared.u32 %0, [%1+%2];" : "=r"(v) : "r"(a), "n"(IMM) : "memory"); return v;
}
__device__ __forceinline__ void sts32(uint32_t a, uint32_t v) { asm volatile("st.shared.u32 [%0], %1;" :: "r"(a), "r"(v) : "memory"); }
__device__ __forceinline__ uint32_t pack_f16(float lo, float hi) {
  uint32_t d; asm("cvt.rn.f16x2.f32 %0, %1, %2;" : "=r"(d) : "f"(hi), "f"(lo)); return d;
}
__device__ __forceinline__ uint32_t amax_bf2(uint32_t a, uint32_t b) { uint32_t d; asm("max.xorsign.abs.bf16x2 %0, %1, %2;" : "=r"(d) : "r"(a), "r"(b)); return d; }
__device__ __forceinline__ uint32_t amax_h2(uint32_t a, uint32_t b) { uint32_t d; asm("max.xorsign.abs.f16x2 %0, %1, %2;" : "=r"(d) : "r"(a), "r"(b)); return d; }
__device__ __forceinline__ uint32_t amax_fold(uint32_t m) { return __reduce_max_sync(0xffffffffu, max(m & 0x7fffu, (m >> 16) & 0x7fffu)); }
__device__ __forceinline__ int wscale_exp(uint32_t m) { return min(141 - (int)(m >> 7), 100); }
__device__ __forceinline__ float exp2i(int e) { return __uint_as_float((uint32_t)(e + 127) << 23); }
__device__ __forceinline__ uint32_t bf2_to_h2(uint32_t w, float sc) { return pack_f16(bf_lo(w) * sc, bf_hi(w) * sc); }
__device__ __forceinline__ void bf2_to_h2_inplace(uint32_t& w, uint32_t sc2) {
  asm volatile("{\n.reg .b32 t, lo, hi;\nmul.rn.bf16x2 t, %0, %1;\nshl.b32 lo, t, 16;\nand.b32 hi, t, 0xffff0000;\ncvt.rn.f16x2.f32 %0, hi, lo;\n}" : "+r"(w) : "r"(sc2));
}
__device__ __forceinline__ void prefetch_l2(const void* p, uint32_t bytes) { asm volatile("cp.async.bulk.prefetch.L2.global [%0], %1;" :: "l"(p), "r"(bytes) : "memory"); }
__device__ __forceinline__ void prefetch_tma_2d(const CUtensorMap* tm, int c0, int c1) {
  asm volatile("cp.async.bulk.prefetch.tensor.2d.L2.global [%0, {%1, %2}];" :: "l"(tm), "r"(c0), "r"(c1) : "memory");
}
__host__ __device__ constexpr uint32_t acc_voff(int v) { return v < 4 ? v * 1024u : (v == 4 ? 128u : 3072u + 128u); }
__device__ __forceinline__ int unit28(int i) { return i == 3 ? 54 : 14 * i; }
__device__ __forceinline__ int unit24(int i) { return i < 2 ? 48 - 6 * i : 56 + 6 * i; }
__device__ __forceinline__ uint32_t acc_step(int s) { return (s >> 1) * 32768 + (s & 1) * 512; }
__device__ __forceinline__ uint32_t acc_lane(int i, int lane) { return ((lane >> 3) & 1) * 256 + (lane >> 4) * 4096 + i * 8192 + (lane & 7) * 16; }

__device__ __forceinline__ uint32_t ld_acquire_u32(const void* p) {
  uint32_t v; asm volatile("ld.acquire.gpu.global.u32 %0, [%1];" : "=r"(v) : "l"(p) : "memory"); return v;
}
template <int R> __device__ __forceinline__ void ln_rows(const uint2 (&xw)[R][5], int row0, int lane, bf16* __restrict__ xn, uint2* __restrict__ xh) {
  float v[R][20], s[R], q[R];
#pragma unroll
  for (int r = 0; r < R; r++) {
    s[r] = 0.f; q[r] = 0.f;
#pragma unroll
    for (int i = 0; i < 5; i++) { v[r][4 * i] = bf_lo(xw[r][i].x); v[r][4 * i + 1] = bf_hi(xw[r][i].x); v[r][4 * i + 2] = bf_lo(xw[r][i].y); v[r][4 * i + 3] = bf_hi(xw[r][i].y); }
#pragma unroll
    for (int i = 0; i < 5; i++) s[r] += (v[r][4 * i] + v[r][4 * i + 1]) + (v[r][4 * i + 2] + v[r][4 * i + 3]);
  }
#pragma unroll
  for (int o = 16; o; o >>= 1)
#pragma unroll
    for (int r = 0; r < R; r++) s[r] += __shfl_xor_sync(0xffffffffu, s[r], o);
#pragma unroll
  for (int r = 0; r < R; r++) {
    s[r] *= 1.f / cfg::DM;
#pragma unroll
    for (int i = 0; i < 10; i++) { const float d = v[r][2 * i] - s[r], e = v[r][2 * i + 1] - s[r]; q[r] += d * d + e * e; }
  }
#pragma unroll
  for (int o = 16; o; o >>= 1)
#pragma unroll
    for (int r = 0; r < R; r++) q[r] += __shfl_xor_sync(0xffffffffu, q[r], o);
#pragma unroll
  for (int r = 0; r < R; r++) {
    const int row = row0 + r;
    const float mb = bf16r(s[r]), var = bf16r(q[r] * (1.f / cfg::DM));
    float sd; asm("sqrt.approx.f32 %0, %1;" : "=f"(sd) : "f"(bf16r(var + 1e-5f)));
    const float inv = rcpf(bf16r(sd));
#pragma unroll
    for (int i = 0; i < 5; i++) {
      float y[4];
#pragma unroll
      for (int e = 0; e < 4; e++) y[e] = v[r][4 * i + e] - mb;
      bf16r2(y[0], y[1]); bf16r2(y[2], y[3]);
      const uint32_t w0 = pack_bf16(y[0] * inv, y[1] * inv), w1 = pack_bf16(y[2] * inv, y[3] * inv);
      *(uint2*)(xn + (size_t)row * cfg::DM + i * 128 + lane * 4) = make_uint2(w0, w1);
      if (xh) xh[(((size_t)(row >> 5) * 10 + 2 * i + (lane >> 4)) * 32 + (row & 31)) * 16 + ((((lane >> 1) & 7) ^ (row & 7)) << 1) + (lane & 1)] =
          make_uint2(pack_f16(bf_lo(w0), bf_hi(w0)), pack_f16(bf_lo(w1), bf_hi(w1)));
    }
  }
}

__global__ void __cluster_dims__(3, 1, 1) __launch_bounds__(384, 1) chain_kernel(const ChainArgs a, const __grid_constant__ CUtensorMap tmWq,
    const __grid_constant__ CUtensorMap tmWk, const __grid_constant__ CUtensorMap tmWv, const __grid_constant__ CUtensorMap tmWo) {
  using namespace ch;
  extern __shared__ __align__(1024) unsigned char smem_raw[];
  const uint32_t sb = smem_u32(smem_raw);
  const int warp = __shfl_sync(0xffffffffu, (int)threadIdx.x >> 5, 0);
  const int lane = __shfl_sync(0xffffffffu, (int)threadIdx.x & 31, threadIdx.x & 31);
  const int cta = blockIdx.x, h = cta / 3, j = cta % 3;
  const int g = lane >> 2, q4 = lane & 3, r8 = lane & 7, m4 = lane >> 3;
  unsigned char* const arena = a.arena;
  if (sb & 1023u) __trap();
  asm volatile("griddepcontrol.launch_dependents;");
  TL_BEGIN(a.tl);
#ifdef TIMELINE
  const unsigned long long g_tl0 = gtime();
#define PT(i) TLW((a.tl >= 12) * 128 + 64 + (i))
#else
#define PT(i)
#endif
  const int col0 = j == 0 ? 0 : (j == 1 ? 224 : 432);
  auto stage_w = [&](const CUtensorMap* tm, uint32_t dst, uint32_t mb, int half) {
    mbar_expect_tx(mb + 8 * half, 40960);
    tma_load_2d(dst + half * 40960, tm, h * cfg::DH + j * 64, half * 320, mb + 8 * half);
    tma_load_2d(dst + half * 40960 + 20480, tm, h * cfg::DH + j * 64, half * 320 + 160, mb + 8 * half);
  };
  if (threadIdx.x == 256) {
    for (int i = 0; i < 9; i++) mbar_init(sb + MB_K + 8 * i, 1);
    mbar_init(sb + MB_S, 1); mbar_init(sb + MB_O, 1); mbar_init(sb + MB_X, 1);
    asm volatile("fence.mbarrier_init.release.cluster;" ::: "memory");
    for (int i = 0; i < 2; i++) { stage_w(&tmWk, sb + OFF_WQ, sb + MB_K, i); stage_w(&tmWv, sb + OFF_WO, sb + MB_V, i); }
    sts32(sb + SC_W, 0); sts32(sb + SC_W + 4, 0); sts32(sb + SC_W + 8, 0); sts32(sb + SC_IN + 12, 0); sts32(sb + SC_IN + 20, 0);
    mbar_expect_tx(sb + MB_S, 1280); mbar_expect_tx(sb + MB_O, 2048);
  }
  __syncthreads();
  asm volatile("barrier.cluster.arrive.relaxed.aligned;" ::: "memory");
  const uint32_t d1 = mapa_u32(sb, (j + 1) % 3) - sb, d2 = mapa_u32(sb, (j + 2) % 3) - sb;

  if (warp >= 8) {
    asm volatile("setmaxnreg.dec.sync.aligned.u32 40;");
    const int hw = warp - 8, ht = hw * 32 + lane;
    const bool lead = ht == 0;
    auto stage_wo = [&](int i) {
      mbar_expect_tx(sb + MB_R + 8 * i, 64 * WOS);
      tma_load_2d(sb + OFF_WO + i * 64 * WOS, &tmWo, col0, h * cfg::DH + ((i + j) % 3) * 64, sb + MB_R + 8 * i);
    };
    const unsigned char* xg = (const unsigned char*)a.xh;
    auto issue_x = [&](int s) { mbar_expect_tx(sb + MB_X, 40960); bulk_g2s(sb + OFF_X, xg + (size_t)s * 40960, 40960, sb + MB_X); };
    uint4 v[5];
#pragma unroll
    for (int i = 0; i < 5; i++) { const int c = ht + 128 * i; v[i] = ld_relaxed_v4(a.mem0 + (c & 7) * cfg::DM + (c >> 3) * 8); }
    if (hw == 2) {
      asm volatile("griddepcontrol.wait;" ::: "memory");
      if (lane == 0) { if (cta == 0) st_relaxed_u32(a.go, 1); issue_x(0); }
      PT(0);
    }
    if (hw == 0) {
      bar_sync(B_QK, 160); if (lane == 0) stage_w(&tmWq, sb + OFF_WQ, sb + MB_Q, 0);
      bar_sync(B_SL, 160); if (lane == 0) stage_w(&tmWq, sb + OFF_WQ, sb + MB_Q, 1);
    }
    if (hw == 1) {
      bar_sync(B_V, 160); if (lane == 0) stage_wo(0);
      bar_sync(B_O, 160); if (lane == 0) { stage_wo(1); stage_wo(2); }
    }
    __syncwarp();
    {
      uint32_t m = 0;
#pragma unroll
      for (int i = 0; i < 5; i++) {
        m = amax_bf2(amax_bf2(m, amax_bf2(v[i].x, v[i].y)), amax_bf2(v[i].z, v[i].w));
      }
      m = amax_fold(m);
      if (lane == 0) sts32(sb + SC_MX + hw * 4, m);
      bar_sync(B_H, 128);
      const uint4 mm = lds128(sb + SC_MX);
      const int se = max(wscale_exp(max(max(mm.x, mm.y), max(mm.z, mm.w))), -100);
      const float sc = exp2i(se);
#pragma unroll
      for (int i = 0; i < 5; i++) {
        const int c = ht + 128 * i, t = c & 7, chn = c >> 3;
        sts128(sb + OFF_MEM + chn * 128 + ((t ^ (2 * (chn & 3))) << 4), bf2_to_h2(v[i].x, sc), bf2_to_h2(v[i].y, sc), bf2_to_h2(v[i].z, sc), bf2_to_h2(v[i].w, sc));
      }
      if (lead) { sts32(sb + SC_IN, __float_as_uint(exp2i(-se))); sts32(sb + SC_IN + 4, 0x7800u); }
    }
    if (hw == 0) PT(11);
    {
      const uint32_t p0 = sb + OFF_WQ + hw * 2048 + lane * 16;
      uint32_t m = 0;
#pragma unroll 1
      for (int i = 0; i < 10; i++) {
        if (i == 0 || i == 5) mbar_wait(sb + MB_Q + (i ? 8 : 0), 0);
        uint32_t r[4][4];
        static_for<0, 4>([&](auto K) { ldsm_x4_i<K.value * 512>(r[K.value], p0 + i * 8192); });
#pragma unroll
        for (int k = 0; k < 4; k++) m = amax_bf2(amax_bf2(m, amax_bf2(r[k][0], r[k][1])), amax_bf2(r[k][2], r[k][3]));
      }
      if (hw == 0) PT(9);
      m = amax_fold(m);
      if (lane == 0) asm volatile("red.shared.max.u32 [%0], %1;" :: "r"(sb + SC_W + 8), "r"(m) : "memory");
      bar_sync(B_H, 128);
      const uint32_t sc = (uint32_t)(wscale_exp(lds32_i<SC_W + 8>(sb)) + 127) * 0x00800080u;
#pragma unroll 1
      for (int i = 0; i < 10; i++) {
        uint32_t r[4][4];
        static_for<0, 4>([&](auto K) { ldsm_x4_i<K.value * 512>(r[K.value], p0 + i * 8192); });
#pragma unroll
        for (int k = 0; k < 4; k++) {
          bf2_to_h2_inplace(r[k][0], sc); bf2_to_h2_inplace(r[k][1], sc); bf2_to_h2_inplace(r[k][2], sc); bf2_to_h2_inplace(r[k][3], sc);
          stsm_x4(p0 + i * 8192 + k * 512, r[k][0], r[k][1], r[k][2], r[k][3]);
        }
      }
    }
    if (hw == 0) PT(10);
    bar_sync(0, 384);
    if (hw == 3) {
      const uint32_t eye = (m4 == q4) ? ((lane & 4) ? 0x3f800000u : 0x3f80u) : 0u;
      sts128(sb + OFF_LT + lane * 16, eye, eye, (lane & 2) * 64 + g * 16 + (lane & 1) * 8, 0u);
      sts64(sb + OFF_S + 1280 + lane * 8, 0u, 0u);
    }
    if (lead) st_relaxed_u32(arena + AR_TAB + cta * 4, 0x80000000u | (lds32_i<SC_W>(sb) << 15) | lds32_i<SC_W + 4>(sb));
    asm volatile("barrier.cluster.wait.aligned;" ::: "memory");
    bar_sync(B_MEM0, 256); bar_sync(B_MEM1, 256);
    {
      uint32_t v0, v1, v2; int spin = 0;
      do {
        v0 = ld_relaxed_u32(arena + AR_TAB + lane * 4); v1 = ld_relaxed_u32(arena + AR_TAB + 128 + lane * 4); v2 = ld_relaxed_u32(arena + AR_TAB + 256 + lane * 4);
      } while (__any_sync(0xffffffffu, ((v0 & v1 & v2) >> 31) == 0) && ++spin < SPIN_LIMIT);
      const uint32_t mv = (max(max(v0, v1), v2) >> 15) & 0x7fffu, mo = max(max(v0 & 0x7fffu, v1 & 0x7fffu), v2 & 0x7fffu);
      sts32(sb + SC_IN + 8 + (lane & 1) * 16, 15 - ((__reduce_max_sync(0xffffffffu, mv) >> 7) + (__reduce_max_sync(0xffffffffu, mo) >> 7) - 252 + 22));
    }

    auto store_kv = [&](int s) {
      const size_t o = ((size_t)s * 96 + cta) * KVB; const uint32_t src = sb + OFF_KV + (s & 1) * (2 * KVB);
      fence_proxy_async(); bulk_s2g(a.kg + o, src, KVB); bulk_s2g(a.vg + o, src + KVB, KVB); bulk_commit();
    };
    const int cb28 = unit28(hw), du = (unit24(hw) - cb28) * 128;
    uint32_t n16 = lane * 16, hist = 0;
    const uint32_t us1 = sb + d1 + OFF_SR + 256 + (hw >> 1) * 512 + (hw & 1) * 128, us2 = sb + d2 + OFF_SR + (hw >> 1) * 512 + (hw & 1) * 128;
    const uint32_t uo1 = sb + d1 + OFF_O + 2048 + hw * 256, uo2 = sb + d2 + OFF_O + 1024 + hw * 256;
#ifdef STEPCLK
    if (lead) a.dbg[96 * 300 + cta * 2] = clk32();
#endif
#ifdef TIMELINE
    if (cta == 0 && lead) { g_tl2[(a.tl >= 12) * 128 + 0] = clock64(); g_tl2[(a.tl >= 12) * 128 + 1] = gtime(); }
#endif
#pragma unroll 1
    for (int s = 0; s < cfg::NSEG; s++) {
      TS_SETUP();
      const bool last = s == cfg::NSEG - 1;
      if (n16 == 0) {
        if (hw == 2 && !last) issue_x(s + 1);
        if (hw == 0 && (s & 3) == 1 && s > 1) st_relaxed_u32(arena + (prog_off(h, j) + (hist >> 31)), s - 1);
        if (hw == 0 && s > 0) store_kv(s - 1);
        if (PFX && hw == 3 && cta < 80 && s + PFX < cfg::NSEG) prefetch_l2(xg + (size_t)(s + PFX) * 40960 + cta * 512, 512);
        if (PFACC && hw == 1 && s + PFACC < cfg::NSEG - 1)
          asm volatile("prefetch.global.L2 [%0];" :: "l"(arena + (AR_ACC + acc_step(s + PFACC) + acc_lane(cta / 24, (cta & 3) * 8) + acc_voff((cta % 24) >> 2))) : "memory");
      }
      __syncwarp();
      if (last) break;
      const uint32_t kv = (s & 1) * (2 * KVB);
      n16 = fresh(n16);
      uint32_t kb0[4], kb1[4];
      { const uint32_t ka = n16 + (n16 & 384) * 4 + (sb + kv + hw * 128); ldsm_x4_i<OFF_KV>(kb0, ka); ldsm_x4_i<OFF_KV + 2560>(kb1, ka); }
      TS(1);
      bar_sync(B_QK, 384);
      {
        uint32_t q0[4], q1[4], q2[4], q3[4];
        float sa[4] = {0, 0, 0, 0}, sc2[4] = {0, 0, 0, 0};
        ldsm_x4_i<OFF_Q>(q0, n16 + sb); ldsm_x4_i<OFF_Q + 1024>(q2, n16 + sb); ldsm_x4_i<OFF_Q + 512>(q1, n16 + sb);
        bar_arrive(B_A, 288);
        ldsm_x4_i<OFF_Q + 1536>(q3, n16 + sb);
        mma16816(sa, q0[0], q0[1], q0[2], q0[3], kb0[0], kb0[1]);
        mma16816(sc2, q2[0], q2[1], q2[2], q2[3], kb1[0], kb1[1]);
        mma16816(sa, q1[0], q1[1], q1[2], q1[3], kb0[2], kb0[3]);
        mma16816(sc2, q3[0], q3[1], q3[2], q3[3], kb1[2], kb1[3]);
        const float x0 = (sa[0] + sa[2]) + (sc2[0] + sc2[2]), x1 = (sa[1] + sa[3]) + (sc2[1] + sc2[3]);
        const uint32_t xp = pack_bf16(x0, x1);
        st_async_b32_i<0>((n16 >> 2) + us1, xp, sb + MB_S + d1);
        st_async_b32_i<0>((n16 >> 2) + us2, xp, sb + MB_S + d2);
        stsm_x2(n16 + (sb + OFF_S + hw * 256), __float_as_uint(x0), __float_as_uint(x1));
      }
      TS(3);
      uint32_t v0[4], v1[4], vm0, vm1;
      const uint32_t uv = sb + kv + hw * 1280;
      ldsm_x4_t_i<OFF_KV + KVB>(v0, n16 + uv); ldsm_x4_t_i<OFF_KV + KVB + 640>(v1, n16 + uv);
      bar_sync(B_SL, 256);
      float t0[4], t1[4], t2[4];
      { uint32_t x[4]; ldsm_x4_i<OFF_S>(x, n16 + sb); t0[0] = __uint_as_float(x[0]); t0[1] = __uint_as_float(x[1]); t0[2] = __uint_as_float(x[2]); t0[3] = __uint_as_float(x[3]); }
      { uint32_t x[4]; ldsm_x4_i<OFF_S + 512>(x, n16 + sb); t1[0] = __uint_as_float(x[0]); t1[1] = __uint_as_float(x[1]); t1[2] = __uint_as_float(x[2]); t1[3] = __uint_as_float(x[3]); }
      { uint32_t x[4]; ldsm_x4_i<OFF_S + 1024>(x, n16 + sb); t2[0] = __uint_as_float(x[0]); t2[1] = __uint_as_float(x[1]); t2[2] = __uint_as_float(x[2]); t2[3] = __uint_as_float(x[3]); }
      mbar_spin(sb + MB_S, s & 1);
      TS(4);
      uint2 xo;
      {
        uint32_t r0[4], r1[4], r2[2];
        ldsm_x4_i<OFF_SR>(r0, n16 + sb); ldsm_x4_i<OFF_SR + 512>(r1, n16 + sb); ldsm_x2_i<OFF_SR + 1024>(r2, n16 + sb);
        SFENCE(n16);
        const uint2 eye = lds64_i<OFF_LT>(n16 + sb);
        mma16816(t0, r0[0], r0[1], r0[2], r0[3], eye.x, eye.y);
        mma16816(t1, r1[0], r1[1], r1[2], r1[3], eye.x, eye.y);
        mma1688(t2, r2[0], r2[1], eye.x);
        bar_sync(B_V, 256);
        vm0 = ldsm_x1_t_i<OFF_KV + KVB + 512>(n16 + uv); vm1 = ldsm_x1_t_i<OFF_KV + KVB + 1152>(n16 + uv);
        SFENCE(n16);
        xo = lds64_i<OFF_LT + 8>(n16 + sb);
      }
      float sc[10] = {t0[0], t0[1], t0[2], t0[3], t1[0], t1[1], t1[2], t1[3], t2[0] + t2[2], t2[1] + t2[3]};
      const float cs = 0.07216878364870322f * 1.4426950408889634f;
      float mx = fmaxf(fmaxf(fmaxf(sc[0], sc[1]), fmaxf(sc[2], sc[3])), fmaxf(fmaxf(sc[4], sc[5]), fmaxf(sc[6], sc[7])));
      mx = fmaxf(mx, fmaxf(sc[8], sc[9]));
      {
        const float m1 = __shfl_xor_sync(0xffffffffu, mx, 1), m2 = __shfl_xor_sync(0xffffffffu, mx, 2), m3 = __shfl_xor_sync(0xffffffffu, mx, 3);
        mx = fmaxf(fmaxf(mx, m1), fmaxf(m2, m3));
      }
      const float mo = fmaf(mx, -cs, __uint_as_float(xo.x));
      auto ex = [&](int i) -> uint32_t { float x, y;
        asm volatile("ex2.approx.ftz.f32 %0, %1;" : "=f"(x) : "f"(fmaf(sc[i], cs, mo))); asm volatile("ex2.approx.ftz.f32 %0, %1;" : "=f"(y) : "f"(fmaf(sc[i + 1], cs, mo)));
        return pack_bf16(x, y); };
      float oa[4] = {0, 0, 0, 0}, ob[4] = {0, 0, 0, 0}, oc[4] = {0, 0, 0, 0}, od[4] = {0, 0, 0, 0}, rs[4] = {0, 0, 0, 0};
      const uint32_t ones = 0x3f803f80u;
      const uint32_t p4 = ex(8);
      if (MEMFIRST) { mma1688(rs, p4, 0u, ones); mma1688(oa, p4, 0u, vm0); mma1688(ob, p4, 0u, vm1); }
      const uint32_t p0 = ex(0), p1 = ex(2), p2 = ex(4), p3 = ex(6);
      TS(5);
      mma16816(rs, p0, p2, p1, p3, ones, ones);
      mma16816(oa, p0, p2, p1, p3, v0[0], v0[1]);
      mma16816(oc, p0, p2, p1, p3, v0[2], v0[3]);
      mma16816(ob, p0, p2, p1, p3, v1[0], v1[1]);
      mma16816(od, p0, p2, p1, p3, v1[2], v1[3]);
      if (!MEMFIRST) { mma1688(rs, p4, 0u, ones); mma1688(oa, p4, 0u, vm0); mma1688(ob, p4, 0u, vm1); }
      const float inv = rcpf(rs[0] + rs[2]) * __uint_as_float(xo.y);
      {
        const uint32_t y0 = pack_bf16((oa[0] + oc[2]) * inv, (oa[1] + oc[3]) * inv), y1 = pack_bf16((ob[0] + od[2]) * inv, (ob[1] + od[3]) * inv);
        st_async_v2_i<0>(xo.x + uo1, y0, y1, sb + MB_O + d1);
        st_async_v2_i<0>(xo.x + uo2, y0, y1, sb + MB_O + d2);
        sts64_i<OFF_O>(xo.x + (sb + hw * 256), y0, y1);
      }
      bar_arrive(B_O, 384);
      TS(6);
      if (hw == 0) bulk_wait<0>();
      mbar_expect_tx_if(n16 == 0 && hw == 3, sb + MB_S, 1280);
      n16 = fresh(n16);
      const int ln = n16 >> 4;
      auto mslot = [&](int c) -> uint32_t { return sb + OFF_MEM + c * 128 + (((ln >> 2) ^ (2 * (c & 3))) << 4); };
      const int lq = ln & 3;
      const uint32_t ma = mslot(cb28 + lq), mb_ = mslot(cb28 + (lq >> 1)) + (lq & 1) * 8;
      const unsigned char* gp = arena + (AR_ACC + acc_lane(hw, ln) + acc_step(s));
      const bool odd = ln & 1;
      const uint32_t delay = a.delay + ((hist & 2) ? a.margin : 0);
      SFENCE(ma);
      bar_sync(B_RED, 384);
      SFENCE(mb_);
      const uint32_t tw = clk_v();
      TSV(7, tw);
      mbar_expect_tx_if(n16 == 0 && hw == 3, sb + MB_O, 2048);
      while (clk_v() - tw < delay) {}
      TS(8);
      uint4 v[6];
      int spin = 0;
      const uint32_t cm = odd ? 0x5000u : 0u;
      do {
        static_for<0, 6>([&](auto I) { v[I.value] = ld_relaxed_v4_i<acc_voff(I.value)>(gp); });
      } while (__any_sync(0xffffffffu, (~((v[0].w & v[1].w & v[2].w) & (v[3].w & v[4].w & v[5].w)) & cm) != 0) && ++spin < SPIN_LIMIT);
      v[0].w = odd ? v[3].x : v[0].w; v[1].w = odd ? v[3].y : v[1].w; v[2].w = odd ? v[3].z : v[2].w; v[3].w = odd ? 0u : v[3].w;
      sts128_i<0>(ma, v[0].x, v[0].y, v[0].z, v[0].w);
      sts128_i<512>(ma, v[1].x, v[1].y, v[1].z, v[1].w);
      sts128_i<1024>(ma, v[2].x, v[2].y, v[2].z, v[2].w);
      sts128_i<0>(ma + du, v[4].x, v[4].y, v[4].z, v[5].z);
      sts64_i<512>(mb_ + du, v[5].x, v[5].y);
      if (!odd) sts128_i<1536>(mb_, v[3].x, v[3].y, v[3].z, v[3].w);
      hist = (hist * 2 + (spin != 0)) & 0xffffu;
      TSV(11, spin);
#ifdef TIMELINE
      if (spin && ln == 0) atomicAdd(&g_tl2[(a.tl >= 12) * 128 + 4], 1ull);
#endif
      TS(10);
      bar_sync(B_MEM0, 256); bar_sync(B_MEM1, 256);
      uint32_t m = lds32_i<SC_IN + 12>(sb);
      uint32_t m2 = m;
      static_for<0, 3>([&](auto I) { m = amax_h2(amax_h2(amax_h2(amax_h2(m, v[I.value].x), v[I.value].y), v[I.value].z), v[I.value].w); });
      static_for<3, 6>([&](auto I) { m2 = amax_h2(amax_h2(amax_h2(m2, v[I.value].x), v[I.value].y), v[I.value].z); });
      m = amax_fold(amax_h2(amax_h2(m2, v[3].w), m));
      if (n16 == 0) asm volatile("red.shared.max.u32 [%0], %1;" :: "r"(sb + SC_IN + 4 + 16 * ((s + 1) & 1)), "r"(m) : "memory");
    }
    bar_sync(B_RED, 384);
    if (hw == 0 && n16 == 0) {
      store_kv(cfg::NSEG - 1);
      bulk_wait<0>();
      st_relaxed_u32(arena + prog_off(h, j), cfg::NSEG);
    }
    __syncwarp();
#ifdef STEPCLK
    if (hw == 0 && n16 == 0) a.dbg[96 * 300 + cta * 2 + 1 + (hist >> 20)] = clk32();
#endif
#ifdef TIMELINE
    if (cta == 0 && hw == 0 && n16 == 0) { g_tl2[(a.tl >= 12) * 128 + 2] = clock64(); g_tl2[(a.tl >= 12) * 128 + 3] = gtime(); }
#endif
    TL_END(a.tl);
    asm volatile("barrier.cluster.arrive.relaxed.aligned; barrier.cluster.wait.aligned;" ::: "memory");
  } else {
    asm volatile("setmaxnreg.inc.sync.aligned.u32 232;");
    const int wi = warp & 3, hf = warp >> 2, tid = warp * 32 + lane;
    uint32_t w[40][4];
    uint32_t wqa;
    { const int mrow = r8 + ((lane >> 4) << 3), mch = 2 * wi + (m4 & 1); wqa = sb + mrow * 128 + ((mch ^ r8) << 4); }
    {
      const uint32_t wa = wqa + (hf ? OFF_WO : OFF_WQ);
      mbar_wait(sb + (hf ? MB_V : MB_K), 0);
      static_for<0, 20>([&](auto K) { ldsm_x4_t_i<K.value * 2048>(w[K.value], wa); });
      if (warp == 0) PT(1);
      bar_arrive(hf ? B_V : B_QK, 160);
      mbar_wait(sb + (hf ? MB_V : MB_K) + 8, 0);
      static_for<20, 40>([&](auto K) { ldsm_x4_t_i<K.value * 2048>(w[K.value], wa); });
      if (warp == 4) PT(2);
      bar_arrive(hf ? B_O : B_SL, 160);
      SFENCE(wa);
    }
    float iw, iq;
    {
      uint32_t m = 0;
#pragma unroll
      for (int k = 0; k < 40; k++) m = amax_bf2(amax_bf2(m, amax_bf2(w[k][0], w[k][1])), amax_bf2(w[k][2], w[k][3]));
      m = amax_fold(m);
      if (hf && lane == 0) asm volatile("red.shared.max.u32 [%0], %1;" :: "r"(sb + SC_W), "r"(m) : "memory");
      const int e = wscale_exp(m);
      const uint32_t sc = (uint32_t)(e + 127) * 0x00800080u; iw = exp2i(-e);
#pragma unroll
      for (int k = 0; k < 40; k++) { bf2_to_h2_inplace(w[k][0], sc); bf2_to_h2_inplace(w[k][1], sc); bf2_to_h2_inplace(w[k][2], sc); bf2_to_h2_inplace(w[k][3], sc); }
    }
    uint32_t x0[8];
    {
      float xa[16];
      const uint32_t dlo = (((sb + OFF_X) & 0x3FFFF) >> 4) | (1u << 16);
      if (warp == 0) PT(3);
      mbar_wait(sb + MB_X, 0);
      if (warp == 0) PT(4);
      wgmma_fence();
      static_for<0, 40>([&](auto K) { constexpr int k = K.value; wgmma_rs32h<((k >> 2) * 4096 + (k & 3) * 32) / 16, (k != 0)>(xa, w[k], dlo); });
      wgmma_commit();
      wgmma_wait<0>();
#pragma unroll
      for (int i = 0; i < 8; i++) x0[i] = pack_bf16(xa[2 * i] * iw, xa[2 * i + 1] * iw);
    }
    const bool t28 = j == 0 || warp < 4;
    const int bi = j == 0 ? hf : (warp < 4 ? j + 1 : 2 * (j - 1) + ((warp - 4) >> 1)), bv = t28 ? wi : 4 + (warp & 1);
    uint32_t wo1 = sb + OFF_WO + warp * 896 + lane * 16, wo2;
    {
      const int cb = (t28 ? unit28(bi) : unit24(bi)) - col0 / 8;
      uint32_t cp[4];
#pragma unroll
      for (int wd = 0; wd < 4; wd++) {
        int c, p;
        if (bv < 3) { c = 4 * bv + q4; p = wd; }
        else if (bv == 3) { if (q4 & 1) { c = 4 * (wd % 3) + q4; p = 3; } else { c = 12 + (q4 >> 1); p = wd; } }
        else if (bv == 4) { c = q4; p = wd; }
        else { if (wd < 2) { c = 4 + (q4 >> 1); p = 2 * (q4 & 1) + wd; } else { c = q4; p = 3; } }
        cp[wd] = sb + OFF_WO + ((g & 1) + (g & 2) * 4 + (g >> 2) * 2) * WOS + (cb + c) * 16 + p * 4;
      }
      const int cidx = (r8 & 1) + ((r8 >> 2) << 1);
      wo2 = sb + OFF_WO + warp * 896 + ((m4 & 1) ? 768 + (m4 >> 1) * 64 + cidx * 16 : 512 + (m4 >> 1) * 128 + r8 * 16);
      const bool dump = (m4 & 1) && (r8 & 2);
      uint32_t mo = 0;
      const bool regular = bv < 3 || bv == 4;
#pragma unroll 1
      for (int i = 0; i < 3; i++) {
        uint32_t x[4][4], y[4][4];
        const uint32_t o = i * 4 * WOK;
        mbar_wait(sb + MB_R + 8 * i, 0);
        if (warp == 0) PT(5 + i);
        if (regular) {
          static_for<0, 4>([&](auto K) {
            constexpr int kk = K.value;
            const uint4 u = lds128_i<kk * WOK>(cp[0] + o), v = lds128_i<kk * WOK + 4 * WOS>(cp[0] + o);
            x[kk][0] = u.x; x[kk][1] = u.y; x[kk][2] = u.z; x[kk][3] = u.w; y[kk][0] = v.x; y[kk][1] = v.y; y[kk][2] = v.z; y[kk][3] = v.w;
          });
        } else {
          static_for<0, 4>([&](auto K) {
            constexpr int kk = K.value;
#pragma unroll
            for (int wd = 0; wd < 4; wd++) { x[kk][wd] = lds32_i<kk * WOK>(cp[wd] + o); y[kk][wd] = lds32_i<kk * WOK + 4 * WOS>(cp[wd] + o); }
          });
        }
        bar_sync(B_C, 256);
        static_for<0, 4>([&](auto K) {
          constexpr int kk = K.value;
#pragma unroll
          for (int wd = 0; wd < 4; wd++) mo = amax_bf2(mo, amax_bf2(x[kk][wd], y[kk][wd]));
          stsm_x4_t_i<kk * WOK>(wo1 + o, x[kk][0], x[kk][1], y[kk][0], y[kk][1]);
          stsm_x4_t_i<0>(dump ? sb + OFF_S + 512 + lane * 16 : wo2 + o + kk * WOK, x[kk][2], x[kk][3], y[kk][2], y[kk][3]);
        });
      }
      if (warp == 0) PT(8);
      mo = amax_fold(mo);
      if (lane == 0) asm volatile("red.shared.max.u32 [%0], %1;" :: "r"(sb + SC_W + 4), "r"(mo) : "memory");
    }
    __syncwarp();
    auto run = [&](auto HF) {
    constexpr int hf = HF.value;
    uint32_t mema, sta, l16 = sb + lane * 16;
    uint32_t rq[hf ? NQ1 : NQ0][4];
    auto step_addr = [&](uint32_t kv) {
      const int lr = (l16 >> 4) & 7, lm = (l16 >> 7) & 3;
      mema = l16 ^ (lm << 5);
      sta = sb + lr * 16 + (lm < 2 ? OFF_Q + wi * 512 + hf * 128 + lm * 256 : OFF_KV + kv + 512 + (2 * wi + lm - 2) * 640);
    };
    auto x_gemm = [&](uint32_t ph, [[maybe_unused]] uint32_t tsb) {
      float xa[16];
      const uint32_t dlo = (((sb + OFF_X) & 0x3FFFF) >> 4) | (1u << 16);
      constexpr int NP = hf ? NQ1 : NP0;
      if constexpr (hf) {
        static_for<PQE, NP>([&](auto K) { ldsm_x4_t_i<OFF_WQ + K.value * 2048>(rq[K.value], wqa); });
        bar_sync(B_X, 256);
      }
      wgmma_fence();
      static_for<0, 40>([&](auto K) {
        constexpr int k = K.value;
        wgmma_rs32h<((k >> 2) * 4096 + (k & 3) * 32) / 16, (k != 0)>(xa, w[k], dlo);
        if constexpr (!hf && k == PFK && NP > PQE) { SFENCE(wqa); static_for<PQE, NP>([&](auto K) { ldsm_x4_t_i<OFF_WQ + K.value * 2048>(rq[K.value], wqa); }); SFENCE(wqa); }
        if constexpr (!hf && k == XT) bar_arrive(B_X, 256);
      });
      step_addr(ph * (2 * KVB));
      wgmma_commit();
      TS(9);
      wgmma_wait<0>();
      const uint32_t xs = l16 + (wi * 1280 + ph * (2 * KVB));
      stsm_x4_t_i<OFF_KV + hf * KVB>(xs, pack_bf16(xa[0] * iw, xa[1] * iw), pack_bf16(xa[4] * iw, xa[5] * iw), pack_bf16(xa[8] * iw, xa[9] * iw), pack_bf16(xa[12] * iw, xa[13] * iw));
      stsm_x4_t_i<OFF_KV + hf * KVB + 640>(xs, pack_bf16(xa[2] * iw, xa[3] * iw), pack_bf16(xa[6] * iw, xa[7] * iw), pack_bf16(xa[10] * iw, xa[11] * iw), pack_bf16(xa[14] * iw, xa[15] * iw));
    };
    auto wq_addr = [&](uint32_t l) -> uint32_t {
      const int lr = (l >> 4) & 7, lm = (l >> 7) & 3;
      return sb + hf * ((40 - NQ1) * 2048) + (lr + ((lm >> 1) << 3)) * 128 + (((2 * wi + (lm & 1)) ^ lr) << 4);
    };
    constexpr int NPM = hf ? NPM1 : NPM0;
    uint32_t u1[NPM][4], u2[NPM][4];
    static_for<0, NPM>([&](auto K) { ldsm_x4_i<(12 - NPM + K.value) * WOK>(u1[K.value], wo1); ldsm_x4_i<(12 - NPM + K.value) * WOK>(u2[K.value], wo2); });
    bar_sync(0, 384);
    iq = uniform_f(exp2i(-wscale_exp(lds32_i<SC_W + 8>(sb))));
    wqa = wq_addr(l16);
    static_for<0, (hf ? NQ1 : NP0)>([&](auto K) { ldsm_x4_t_i<OFF_WQ + K.value * 2048>(rq[K.value], wqa); });
    step_addr(0);
    stsm_x4_t_i<OFF_KV + hf * KVB>(l16 + wi * 1280, x0[0], x0[2], x0[4], x0[6]);
    stsm_x4_t_i<OFF_KV + hf * KVB + 640>(l16 + wi * 1280, x0[1], x0[3], x0[5], x0[7]);
    asm volatile("barrier.cluster.wait.aligned;" ::: "memory");
    TL_END(a.tl + 1);
#pragma unroll 1
    for (int s = 0; s < cfg::NSEG - 1; s++) {
      TS_SETUP();
#if CHAIN_TIMING
      if (tid == 0 && (s & 7) == 0) a.dbg[96 * 288 + cta * 8 + (s >> 3)] = clk32();
#endif
      bar_sync(hf ? B_MEM1 : B_MEM0, 256);
      const float sin_ = __uint_as_float(lds32_i<SC_IN>(sb + 16 * (s & 1)));
      constexpr int NPQ = (40 - NQ1) / 2;
      if constexpr (hf == 0) {
        float k0[4] = {0, 0, 0, 0}, k1[4] = {0, 0, 0, 0}, q0[4] = {0, 0, 0, 0}, q1[4] = {0, 0, 0, 0};
        constexpr auto pair_of = [](int t) { const int a = t * (20 - NPQ) / 20, b = (t + 1) * (20 - NPQ) / 20; return b > a ? NPQ + a : t - a; };
        uint32_t b[NB0][4];
        static_for<0, NB0>([&](auto T) { ldsm_x4_i<OFF_MEM + pair_of(T.value) * 512>(b[T.value], mema); });
        static_for<NP0, NQ0>([&](auto K) { ldsm_x4_t_i<OFF_WQ + K.value * 2048>(rq[K.value], wqa); });
        if (BBS < 100) bbfence<0>(mema);
        static_for<0, 20>([&](auto T) {
          constexpr int t = T.value, p = pair_of(t);
          uint32_t (&bb)[4] = b[t % NB0];
          if constexpr (p < NPQ) {
            mma16816h(q0, rq[(2 * p) % NQ0], bb[0], bb[1]);
            if constexpr (2 * p + NQ0 < 2 * NPQ) ldsm_x4_t_i<OFF_WQ + (2 * p + NQ0) * 2048>(rq[(2 * p) % NQ0], wqa);
          }
          mma16816h(k0, w[2 * p], bb[0], bb[1]);
          if constexpr (p < NPQ) {
            mma16816h(q1, rq[(2 * p + 1) % NQ0], bb[2], bb[3]);
            if constexpr (2 * p + 1 + NQ0 < 2 * NPQ) ldsm_x4_t_i<OFF_WQ + (2 * p + 1 + NQ0) * 2048>(rq[(2 * p + 1) % NQ0], wqa);
          }
          mma16816h(k1, w[2 * p + 1], bb[2], bb[3]);
          if constexpr (NVE > 0 && t + NB0 == VET) bar_arrive(B_E, 256);
          if constexpr (t + NB0 < 20) ldsm_x4_i<OFF_MEM + pair_of(t + NB0) * 512>(bb, mema);
          if constexpr (t < 20 - NB0 && (t % BBS) == BBS - 1) bbfence<t + 1>(mema);
        });
        const float sq = sin_ * iq, sk = sin_ * iw;
        stsm_x4_t_i<0>(sta, pack_bf16((q0[0] + q1[0]) * sq, (q0[1] + q1[1]) * sq), pack_bf16((q0[2] + q1[2]) * sq, (q0[3] + q1[3]) * sq),
                       pack_bf16((k0[0] + k1[0]) * sk, (k0[1] + k1[1]) * sk), pack_bf16((k0[2] + k1[2]) * sk, (k0[3] + k1[3]) * sk));
        bar_sync(B_QK, 384);
        SFENCE(l16);
        [[maybe_unused]] const uint32_t tq = GD0 < 0 ? 0 : clk_v();
        TS(2);
        {
          if (wi == 3) {
            const uint32_t xr = sb + ((l16 & 511) >> 2), ka = l16 + (l16 & 384) * 4 + (s & 1) * (2 * KVB);
            uint32_t a0[4], a1[4], a2[4], a3[4], kb0[4], kb1[4];
            ldsm_x4_i<OFF_Q>(a0, l16); ldsm_x4_i<OFF_KV + 512>(kb0, ka); ldsm_x4_i<OFF_Q + 1024>(a2, l16); ldsm_x4_i<OFF_KV + 512 + 2560>(kb1, ka);
            ldsm_x4_i<OFF_Q + 512>(a1, l16);
            bar_arrive(B_A, 288);
            ldsm_x4_i<OFF_Q + 1536>(a3, l16);
            float sa[4] = {0, 0, 0, 0}, sc2[4] = {0, 0, 0, 0};
            mma16816(sa, a0[0], a0[1], a0[2], a0[3], kb0[0], kb0[1]);
            mma16816(sc2, a2[0], a2[1], a2[2], a2[3], kb1[0], kb1[1]);
            mma16816(sa, a1[0], a1[1], a1[2], a1[3], kb0[2], kb0[3]);
            mma16816(sc2, a3[0], a3[1], a3[2], a3[3], kb1[2], kb1[3]);
            const float x0 = (sa[0] + sa[2]) + (sc2[0] + sc2[2]), x1 = (sa[1] + sa[3]) + (sc2[1] + sc2[3]);
            const uint32_t xp = pack_bf16(x0, x1);
            st_async_b32_i<OFF_SR + 1024 + 128>(xr + d1, xp, sb + MB_S + d1);
            st_async_b32_i<OFF_SR + 1024>(xr + d2, xp, sb + MB_S + d2);
            stsm_x2(l16 + OFF_S + 1024, __float_as_uint(x0), __float_as_uint(x1));
          } else if (wi == 0) {
            const uint4 si = lds128_i<SC_IN>(sb + 16 * (s & 1));
            const int em = (int)(si.y >> 10) - 14 + (int)(si.x >> 23) - 127;
            const uint32_t osc = __float_as_uint(exp2i(max(min((int)si.z - max(em, 1), 100), -100)));
            sts32(l16 + OFF_LT + 12, osc); sts64_i<SC_IN>(sb + 16 * ((s + 1) & 1), 0x7f000000u - osc, 0u);
          }
          if (GD0 < 0) bar_sync(B_SL, 256);
          else { bar_arrive(B_SL, 256); while (clk_v() - tq < GD0) {} }
        }
      } else {
        float v0[4] = {0, 0, 0, 0}, v1[4] = {0, 0, 0, 0}, q0[4] = {0, 0, 0, 0}, q1[4] = {0, 0, 0, 0};
        uint32_t b[NQ1 / 2][4];
        static_for<0, NQ1 / 2>([&](auto T) { ldsm_x4_i<OFF_MEM + (NPQ + T.value) * 512>(b[T.value], mema); });
        static_for<0, NQ1 / 2>([&](auto T) {
          constexpr int t = T.value, p = NPQ + t;
          uint32_t (&bb)[4] = b[t];
          mma16816h(q0, rq[2 * t], bb[0], bb[1]);
          mma16816h(q1, rq[2 * t + 1], bb[2], bb[3]);
          mma16816h(v0, w[2 * p], bb[0], bb[1]);
          mma16816h(v1, w[2 * p + 1], bb[2], bb[3]);
        });
        const float sq = sin_ * iq, sv = sin_ * iw;
        stsm_x2_t_i<0>(sta, pack_bf16((q0[0] + q1[0]) * sq, (q0[1] + q1[1]) * sq), pack_bf16((q0[2] + q1[2]) * sq, (q0[3] + q1[3]) * sq));
        TS(2);
        bar_arrive(B_QK, 384);
        float v2[4] = {0, 0, 0, 0}, v3[4] = {0, 0, 0, 0};
        auto vpair = [&](auto P, uint32_t (&bb)[4]) {
          constexpr int p = P.value;
          if constexpr (p & 1) { mma16816h(v0, w[2 * p], bb[0], bb[1]); mma16816h(v1, w[2 * p + 1], bb[2], bb[3]); }
          else { mma16816h(v2, w[2 * p], bb[0], bb[1]); mma16816h(v3, w[2 * p + 1], bb[2], bb[3]); }
        };
        if constexpr (NVE > 0) {
          uint32_t e[NVE ? NVE : 1][4];
          bar_sync(B_E, 256);
          static_for<0, NVE>([&](auto T) { ldsm_x4_i<OFF_MEM + T.value * 512>(e[T.value], mema); });
          static_for<0, NVE>([&](auto T) { vpair(T, e[T.value]); });
        }
        bar_sync(B_A, 288);
        uint32_t c[4][4];
        static_for<NVE, NVE + 4>([&](auto T) { ldsm_x4_i<OFF_MEM + T.value * 512>(c[T.value & 3], mema); });
        static_for<NVE, NPQ>([&](auto T) {
          constexpr int p = T.value;
          vpair(T, c[p & 3]);
          if constexpr (p + 4 < NPQ) ldsm_x4_i<OFF_MEM + (p + 4) * 512>(c[p & 3], mema);
        });
        stsm_x2_t_i<OFF_KV + KVB + 512>(l16 + (l16 & 128) * 4 + (wi * 1280 + (s & 1) * (2 * KVB)), pack_bf16(((v0[0] + v1[0]) + (v2[0] + v3[0])) * sv, ((v0[1] + v1[1]) + (v2[1] + v3[1])) * sv),
                            pack_bf16(((v0[2] + v1[2]) + (v2[2] + v3[2])) * sv, ((v0[3] + v1[3]) + (v2[3] + v3[3])) * sv));
        bar_arrive(B_V, 256);
      }
      TS(3);
      {
        uint32_t t1[12][4], t2[12][4];
        const uint32_t o16 = l16;
        wo1 = l16 + (OFF_WO + warp * 896);
        wo2 = sb + OFF_WO + warp * 896 + ((l16 & 128) ? 768 + ((l16 & 256) >> 2) + (l16 & 16) + ((l16 & 64) >> 1) : 512 + ((l16 & 256) >> 1) + (l16 & 112));
        auto ldw = [&](auto K) { if constexpr (K.value < 12 - NPM) { ldsm_x4_i<K.value * WOK>(t1[K.value], wo1); ldsm_x4_i<K.value * WOK>(t2[K.value], wo2); } };
        constexpr int NR_ = NRT - NPM;
        constexpr int PB = (hf ? PB1 : PB0) < NR_ ? (hf ? PB1 : PB0) : NR_, PA = (hf ? PA1 : PA0) < PB ? (hf ? PA1 : PA0) : PB;
        static_for<0, PA>(ldw);
        mbar_spin(sb + MB_X, (s + 1) & 1);
        if constexpr (PB > PA) {
          constexpr int PM = PA + PM1 < PB ? PA + PM1 : PB;
          mbar_spin(sb + MB_S, s & 1);
          const uint32_t t0 = clk_v();
          if constexpr (PM > PA) { while (clk_v() - t0 < GD1) {} static_for<PA, PM>(ldw); }
          if constexpr (PB > PM) { while (clk_v() - t0 < GD2) {} static_for<PM, PB>(ldw); }
        }
        float c0[4] = {0, 0, 0, 0}, c1[4] = {0, 0, 0, 0}, e0[4] = {0, 0, 0, 0}, e1[4] = {0, 0, 0, 0};
        uint32_t ob[6][4];
        auto kstep = [&](auto K) {
          constexpr int k = K.value;
          uint32_t (&bb)[4] = ob[k >> 1];
          uint32_t (&x)[4] = k < 12 - NPM ? t1[k] : u1[k < 12 - NPM ? 0 : k - (12 - NPM)];
          uint32_t (&y)[4] = k < 12 - NPM ? t2[k] : u2[k < 12 - NPM ? 0 : k - (12 - NPM)];
          if constexpr (k & 1) { mma16816(c1, x[0], x[1], x[2], x[3], bb[2], bb[3]); mma16816(e1, y[0], y[1], y[2], y[3], bb[2], bb[3]); }
          else { mma16816(c0, x[0], x[1], x[2], x[3], bb[0], bb[1]); mma16816(e0, y[0], y[1], y[2], y[3], bb[0], bb[1]); }
          if constexpr (k >= NRF) ldw(IC<k + NR_ - NRF>{});
        };
        auto ldo = [&](auto P) { ldsm_x4_i<OFF_O + P.value * 512>(ob[P.value], o16); };
        TS(4);
        bar_sync(B_O, 384);
        ldo(IC<0>{}); ldo(IC<1>{});
        SFENCE(o16);
        static_for<PB, NR_>(ldw);
        static_for<0, 4>(kstep);
        TS(5);
        mbar_spin(sb + MB_O, s & 1);
        TS(6);
        ldo(IC<2>{}); ldo(IC<NPM >= 2 ? 5 : 3>{});
        if (WOF) SFENCE(o16);
        kstep(IC<4>{});
        if constexpr (NPM < 2) { kstep(IC<5>{}); ldo(IC<4>{}); kstep(IC<6>{}); kstep(IC<7>{}); ldo(IC<5>{}); static_for<8, 12>(kstep); }
        else if constexpr (NPM >= 4) { kstep(IC<10>{}); kstep(IC<11>{}); ldo(IC<4>{}); kstep(IC<5>{}); ldo(IC<3>{}); kstep(IC<8>{}); kstep(IC<9>{}); kstep(IC<6>{}); kstep(IC<7>{}); }
        else { kstep(IC<5>{}); ldo(IC<3>{}); kstep(IC<11>{}); kstep(IC<10>{}); ldo(IC<4>{}); kstep(IC<6>{}); kstep(IC<7>{}); if constexpr (NPM == 3) { kstep(IC<9>{}); kstep(IC<8>{}); } else { kstep(IC<8>{}); kstep(IC<9>{}); } }
        l16 = fresh(l16);
        const int ln = (l16 >> 4) & 31;
        if constexpr (CEARLY && hf) { SFENCE2(o16, __float_as_uint(e1[0])); bar_arrive(B_G, 256); }
        unsigned char* gr = arena + (AR_ACC + acc_lane(bi, ln) + acc_voff(bv) + acc_step(s));
        const bool cnt = (ln & 1) || !t28;
        wqa = wq_addr(l16);
        SFENCE(o16);
        static_for<0, PQE>([&](auto K) { ldsm_x4_t_i<OFF_WQ + K.value * 2048>(rq[K.value], wqa); });
        const uint32_t y0 = movm_t(pack_f16(c0[0] + c1[0], c0[1] + c1[1])), y1 = movm_t(pack_f16(c0[2] + c1[2], c0[3] + c1[3]));
        const uint32_t y2 = movm_t(pack_f16(e0[0] + e1[0], e0[1] + e1[1])), y3 = movm_t(pack_f16(e0[2] + e1[2], e0[3] + e1[3]));
        asm volatile("red.relaxed.gpu.global.add.noftz.v4.f16x2 [%0], {%1,%2,%3,%4};" :: "l"(gr), "r"(y0), "r"(y1), "r"(y2), "r"(cnt ? 0x3c00u : y3) : "memory");
        bar_arrive(B_RED, 384);
        if constexpr (CEARLY && !hf) { bar_arrive(B_C, 256); bar_sync(B_G, 256); }
        else bar_sync(B_C, 256);
        TS(7);
      }
#if CHAIN_TIMING
      x_gemm((s + 1) & 1, tsb);
#else
      x_gemm((s + 1) & 1, 0);
#endif
      TS(8);
    }
    };
    if (hf == 0) run(IC<0>{}); else run(IC<1>{});
    {
      const uint32_t l16 = sb + (threadIdx.x & 31) * 16, mema = l16 ^ ((l16 >> 2) & 96);
      float c0[4] = {0, 0, 0, 0}, c1[4] = {0, 0, 0, 0}, c2[4] = {0, 0, 0, 0}, c3[4] = {0, 0, 0, 0};
      bar_sync(hf ? B_MEM1 : B_MEM0, 256);
      const float sc = __uint_as_float(lds32_i<SC_IN + 16>(sb)) * iw;
      static_for<0, 10>([&](auto T) {
        constexpr int p = 2 * T.value;
        uint32_t b0[4], b1[4];
        ldsm_x4_i<OFF_MEM + p * 512>(b0, mema); ldsm_x4_i<OFF_MEM + p * 512 + 512>(b1, mema);
        mma16816h(c0, w[2 * p], b0[0], b0[1]); mma16816h(c1, w[2 * p + 1], b0[2], b0[3]);
        mma16816h(c2, w[2 * p + 2], b1[0], b1[1]); mma16816h(c3, w[2 * p + 3], b1[2], b1[3]);
      });
      stsm_x2_t_i<OFF_KV + 2 * KVB + 512>(l16 + (l16 & 128) * 4 + wi * 1280 + hf * KVB, pack_bf16(((c0[0] + c1[0]) + (c2[0] + c3[0])) * sc, ((c0[1] + c1[1]) + (c2[1] + c3[1])) * sc),
                                          pack_bf16(((c0[2] + c1[2]) + (c2[2] + c3[2])) * sc, ((c0[3] + c1[3]) + (c2[3] + c3[3])) * sc));
    }
    bar_arrive(B_RED, 384);
#if CHAIN_TIMING
    for (int i = tid; i < 288; i += 256) a.dbg[cta * 288 + i] = lds32_i<OFF_BAR + 128>(sb + i * 4);
#endif
    asm volatile("barrier.cluster.arrive.relaxed.aligned; barrier.cluster.wait.aligned;" ::: "memory");
  }
}
struct PrepArgs { const bf16 *wqkv, *wphi, *wo; unsigned char *wb, *wot; };
__device__ __forceinline__ void prep_body(const int cta, const PrepArgs& pa) {
  const int tid = threadIdx.x, lane = tid & 31, warp = tid >> 5, g = lane >> 2, q = lane & 3;
  const int pair = cta >> 1, which = cta & 1;
  uint32_t af[5][2][6];
#pragma unroll
  for (int i = 0; i < 5; i++)
#pragma unroll
    for (int hh = 0; hh < 2; hh++) {
      const uint32_t* r0 = (const uint32_t*)(pa.wqkv + (size_t)((warp * 5 + i) * 16 + g) * 1920 + which * 640 + (2 * pair + hh) * 20) + q;
      const uint32_t* r1 = r0 + 8 * 960;
      af[i][hh][0] = __ldg(r0); af[i][hh][1] = __ldg(r1); af[i][hh][2] = __ldg(r0 + 4); af[i][hh][3] = __ldg(r1 + 4);
      af[i][hh][4] = q < 2 ? __ldg(r0 + 8) : 0u; af[i][hh][5] = q < 2 ? __ldg(r1 + 8) : 0u;
    }
  uint32_t bfr[2][3][3];
#pragma unroll
  for (int hh = 0; hh < 2; hh++)
#pragma unroll
    for (int t = 0; t < 3; t++) {
      const bool on = t < 2 || (g & 1) == hh;
      const unsigned short* ph = (const unsigned short*)pa.wphi + (2 * pair + hh) * 400 + (t < 2 ? 8 * t + g : 16 + (g >> 1)) + 2 * q * 20;
#pragma unroll
      for (int r = 0; r < 3; r++) bfr[hh][t][r] = (on && (r < 2 || q < 2)) ? (uint32_t)__ldg(ph + r * 160) | ((uint32_t)__ldg(ph + r * 160 + 20) << 16) : 0u;
    }
  const int gt = cta * 256 + tid;
#pragma unroll 3
  for (int i = gt; i < 640 * 32; i += 8192) {
    const int k = (i & 7) + (i >> 8) * 8, h = (i >> 3) & 31;
    const uint2* src = (const uint2*)(pa.wqkv + (size_t)k * 1920 + 1280 + h * 20);
    const uint2 a = __ldg(src), b = __ldg(src + 1), c = __ldg(src + 2), d = __ldg(src + 3), e = __ldg(src + 4);
    uint4* dst = (uint4*)(pa.wb + ((size_t)((h >> 2) * 80 + (k >> 3)) * 32 + 20 + 3 * (h & 3)) * 128 + (k & 7) * 16);
    dst[0] = make_uint4(a.x, a.y, b.x, b.y); dst[8] = make_uint4(c.x, c.y, d.x, d.y);
    dst[16] = (h & 1) ? make_uint4(0, 0, e.x, e.y) : make_uint4(e.x, e.y, 0, 0);
  }
#pragma unroll 7
  for (int i = gt; i < 640 * 80; i += 8192) {
    const int r = i & 7, c = (i >> 3) % 80, kg = i / 640, c5 = kg % 5;
    const int row = (kg / 5) * 40 + (c5 < 2 ? 8 * c5 + r : (c5 == 2 ? 16 + (r & 3) + (r >> 2) * 20 : 20 + 8 * (c5 - 3) + r));
    *(uint4*)(pa.wot + ((size_t)((c / 10) * 80 + kg) * 10 + c % 10) * 128 + r * 16) = __ldg((const uint4*)(pa.wo + (size_t)row * cfg::DM + c * 8));
  }
#pragma unroll
  for (int i = 0; i < 5; i++) {
    uint32_t* dst = (uint32_t*)(pa.wb + ((size_t)((pair >> 1) * 80 + (warp * 5 + i) * 2) * 32 + which * 10 + (pair & 1) * 5) * 128) + lane;
#pragma unroll
    for (int t = 0; t < 5; t++) {
      float d[4] = {0, 0, 0, 0};
#pragma unroll
      for (int hh = 0; hh < 2; hh++)
        if (t == 2 || (t > 2) == (hh == 1)) {
          const int tt = t < 3 ? t : t - 3;
          mma16816(d, af[i][hh][0], af[i][hh][1], af[i][hh][2], af[i][hh][3], bfr[hh][tt][0], bfr[hh][tt][1]);
          mma1688(d, af[i][hh][4], af[i][hh][5], bfr[hh][tt][2]);
        }
      dst[t * 32] = pack_bf16(d[0], d[1]); dst[1024 + t * 32] = pack_bf16(d[2], d[3]);
    }
  }
}

__global__ void __launch_bounds__(256, 4) ln_kernel(const bf16* __restrict__ xin, bf16* __restrict__ xn, uint2* __restrict__ xh, uint4* __restrict__ z0, int n0,
                                                    uint4* __restrict__ z1, int n1, const bf16* pfa, const bf16* pfb, int npf, int tl) {
  asm volatile("griddepcontrol.wait;" ::: "memory");
  asm volatile("griddepcontrol.launch_dependents;" ::: "memory");
  TL_BEGIN(tl);
  const int warp = threadIdx.x >> 5, lane = threadIdx.x & 31;
  const int row = blockIdx.x * 8 + warp;
  uint2 xw[1][5];
#pragma unroll
  for (int i = 0; i < 5; i++) xw[0][i] = *(const uint2*)(xin + (size_t)row * cfg::DM + i * 128 + lane * 4);
  for (int i = blockIdx.x * 256 + threadIdx.x; i < n0; i += 256 * 256) z0[i] = make_uint4(0, 0, 0, 0);
  for (int i = blockIdx.x * 256 + threadIdx.x; i < n1; i += 256 * 256) z1[i] = make_uint4(0, 0, 0, 0);
  if (npf && xw[0][4].y != 0x7fc17fc1u) {
    for (int i = 0; i < npf; i++) {
      const uint32_t l = (uint32_t)i * 32768u + (blockIdx.x * 256 + threadIdx.x) / 2;
      if (l < cfg::DM * cfg::HD / 64) asm volatile("prefetch.global.L2 [%0];" :: "l"(((threadIdx.x & 1) ? pfa : pfb) + (size_t)l * 64) : "memory");
    }
  }
  ln_rows<1>(xw, row, lane, xn, xh);
  TL_END(tl);
}
struct Pipe { uint32_t stage, phase; };
template <int NS> __device__ __forceinline__ void pipe_adv(Pipe& p) { if (++p.stage == NS) { p.stage = 0; p.phase ^= 1; } }
constexpr uint32_t SWZ128 = 1;
__device__ __forceinline__ uint64_t desc_kmajor(uint32_t a) { return make_desc(a, 16, 1024, SWZ128); }
__device__ __forceinline__ uint64_t desc_mnmajor(uint32_t a) { return make_desc(a, 8192, 1024, SWZ128); }
__device__ __forceinline__ void wait_ge(const void* p, uint32_t target, uint32_t ns = 32) {
  int spin = 0;
  while (ld_acquire_u32(p) < target) { __nanosleep(ns); if (++spin > (1 << 21)) break; }
}
__device__ __forceinline__ void bulk_g2s_hint(uint32_t dst, const void* src, uint32_t bytes, uint32_t mb, uint64_t pol) {
  asm volatile("cp.async.bulk.shared::cluster.global.mbarrier::complete_tx::bytes.L2::cache_hint [%0], [%1], %2, [%3], %4;"
               :: "r"(dst), "l"(src), "r"(bytes), "r"(mb), "l"(pol) : "memory");
}
#ifndef PF_WB
#define PF_WB 2
#endif
#ifndef PF_XN
#define PF_XN 1
#endif
#ifndef STAG
#define STAG 1
#endif
#ifndef EF_KV
#define EF_KV 1
#endif
#ifndef EF_O
#define EF_O 1
#endif
__device__ __forceinline__ void fence_proxy_async_global() { asm volatile("fence.proxy.async.global;" ::: "memory"); }

namespace tr {
constexpr int NS = 4, STQ = 16384 + 24576, STO = 16384 + 40960;
constexpr int SEGB = 15360;
constexpr int OFF_K = NS * STQ;
constexpr int OFF_BAR = NS * STO;
constexpr int SMEM = OFF_BAR + 256;
static_assert(OFF_K + 4 * SEGB <= OFF_BAR && SMEM <= 232448, "smem");
enum { T_QA = 0, T_Q, T_A, T_OB, T_OS, T_L, T_END, T_P };
constexpr uint32_t C_QA = AR_CNT, C_O = AR_CNT + 64, C_Q = AR_CNT + 128, C_P = AR_CNT + 192;
constexpr int MAXITEMS = 1200;
struct Sched {
  uint8_t ks[16];
  uint8_t wide[16];
  uint8_t lrows[16];
  uint32_t n;
  uint16_t item[MAXITEMS];
};
struct Args {
  const unsigned char *kg, *vg;
  unsigned char* o;
  uint4* qs;
  unsigned char* part;
  const bf16 *xin, *xq;
  bf16 *xout, *xn;
  unsigned char* arena;
  const unsigned* go;
  int tl;
  uint32_t nap, nap2;
};
}

template <int N0, int N1>
__device__ __forceinline__ void tr_mainloop(float (&a0)[N0 / 2], float (&a1)[N1 ? N1 / 2 : 1], Pipe& p, uint32_t sb, uint32_t full, uint32_t empty, int nkb, int wg) {
  using namespace tr;
  constexpr uint32_t ST = N1 ? STO : STQ;
  uint32_t prev = 0;
#pragma unroll
  for (int i = 0; i < N0 / 2; i++) a0[i] = 0.f;
  if constexpr (N1 > 0) {
#pragma unroll
    for (int i = 0; i < N1 / 2; i++) a1[i] = 0.f;
  }
#pragma unroll 1
  for (int kb = 0; kb < nkb; kb++) {
    mbar_wait(full + 8 * p.stage, p.phase);
    const uint32_t st = sb + p.stage * ST;
    wgmma_fence();
#pragma unroll
    for (int kk = 0; kk < 4; kk++) {
      const uint64_t da = desc_kmajor(st + wg * 8192 + kk * 32);
      if constexpr (N0 == 192) wgmma_n192<0, 1>(a0, da, desc_mnmajor(st + 16384 + kk * 2048), (kb | kk) != 0);
      else wgmma_n128<0, 1>(a0, da, desc_mnmajor(st + 16384 + kk * 2048), (kb | kk) != 0);
      if constexpr (N1 > 0) wgmma_n128<0, 1>(a1, da, desc_mnmajor(st + 16384 + 24576 + kk * 2048), (kb | kk) != 0);
    }
    wgmma_commit();
    if (kb > 0) { wgmma_wait<1>(); mbar_arrive_if((threadIdx.x & 127) == 0, empty + 8 * prev); }
    prev = p.stage;
    pipe_adv<NS>(p);
  }
  wgmma_wait<0>();
  mbar_arrive_if((threadIdx.x & 127) == 0, empty + 8 * prev);
}
template <int N> __device__ __forceinline__ void stage_tiles(const float (&o)[N / 2], uint32_t base, int wi, int lane) {
  const uint32_t ra = base + (wi * 16 + (lane & 7) + 8 * ((lane >> 3) & 1)) * 128;
#pragma unroll
  for (int v = 0; v < N / 8; v += 2)
    stsm_x4(ra + (v >> 3) * 8192 + ((((v & 7) + (lane >> 4)) ^ (lane & 7)) << 4), pack_bf16(o[4 * v], o[4 * v + 1]), pack_bf16(o[4 * v + 2], o[4 * v + 3]),
            pack_bf16(o[4 * v + 4], o[4 * v + 5]), pack_bf16(o[4 * v + 6], o[4 * v + 7]));
}
__global__ void __launch_bounds__(384, 1) trail_kernel(const __grid_constant__ CUtensorMap tmX, const __grid_constant__ CUtensorMap tmQ,
                                                       const __grid_constant__ CUtensorMap tmWo5, const __grid_constant__ CUtensorMap tmWo2,
                                                       const __grid_constant__ CUtensorMap tmP, const __grid_constant__ tr::Sched sc,
                                                       const __grid_constant__ tr::Args a, const __grid_constant__ PrepArgs pa) {
  using namespace tr;
  [[maybe_unused]] const int tl = a.tl;
  TL_BEGIN(tl);
  extern __shared__ __align__(1024) unsigned char smem_raw[];
  const uint32_t sb = smem_u32(smem_raw);
  const int warp = __shfl_sync(0xffffffffu, (int)threadIdx.x >> 5, 0), lane = threadIdx.x & 31;
  unsigned char* const arena = a.arena;
  const uint32_t full = sb + OFF_BAR, empty = full + 8 * NS, barK = empty + 8 * NS, barKfree = barK + 16, staged = barKfree + 16;
  const uint32_t kvrdy = staged + 32, mfull = kvrdy + 8, mempty = mfull + 16, mbox = mempty + 16;
  uint32_t go = 0;
  if (threadIdx.x == 256) go = ld_acquire_u32(a.go);
  if (threadIdx.x == 0) {
    for (int i = 0; i < NS; i++) { mbar_init(full + 8 * i, 1); mbar_init(empty + 8 * i, 2); }
    for (int i = 0; i < 2; i++) {
      mbar_init(barK + 8 * i, 1); mbar_init(barKfree + 8 * i, 1); mbar_init(staged + 16 * i, 4); mbar_init(staged + 16 * i + 8, 4);
      mbar_init(mfull + 8 * i, 1); mbar_init(mempty + 8 * i, 11);
    }
    mbar_init(kvrdy, 1);
    asm volatile("fence.mbarrier_init.release.cluster;" ::: "memory");
  }
  __syncthreads();
  Pipe mp{0, 0};
  auto next_item = [&]() -> uint32_t {
    uint32_t it;
    mbar_wait(mfull + 8 * mp.stage, mp.phase);
    asm volatile("ld.shared.u32 %0, [%1];" : "=r"(it) : "r"(mbox + 4 * mp.stage) : "memory");
    return it;
  };
  if (warp >= 8) {
    asm volatile("setmaxnreg.dec.sync.aligned.u32 40;");
    if (warp == 8) { go = __shfl_sync(0xffffffffu, go, 0); if (elect_one()) {
      Pipe p{0, 1};
      mp.phase = 1;
      uint32_t kph = 1, rph = 0, wide = 0, qdone = 0;
      prefetch_tmap(&tmX); prefetch_tmap(&tmQ); prefetch_tmap(&tmWo5); prefetch_tmap(&tmWo2); prefetch_tmap(&tmP);
      const uint64_t ef = policy_evict_first();
      auto ld_kv = [&](uint32_t d, const void* s, uint32_t n, uint32_t mb) { if (EF_KV) bulk_g2s_hint(d, s, n, mb, ef); else bulk_g2s(d, s, n, mb); };
      auto ld_o = [&](uint32_t d, const void* s, uint32_t n, uint32_t mb) { if (EF_O) bulk_g2s_hint(d, s, n, mb, ef); else bulk_g2s(d, s, n, mb); };
      auto stage = [&](uint32_t bytes) -> uint32_t {
        mbar_wait(empty + 8 * p.stage, p.phase);
        mbar_expect_tx(full + 8 * p.stage, bytes);
        return sb + p.stage * (wide ? STO : STQ);
      };
      auto fetch = [&]() -> uint32_t { uint32_t v; asm volatile("atom.relaxed.gpu.global.add.u32 %0, [%1], 1;" : "=r"(v) : "l"(arena + AR_QUEUE) : "memory"); return v; };
      if (!go) wait_ge(a.go, 1, 200);
      fence_proxy_async_global();
      uint32_t next = fetch();
      while (true) {
        const uint32_t item = next;
        const uint32_t code = sc.item[min(item, sc.n)];
        const int type = code >> 11, m = (code >> 7) & 15, k = code & 127;
        if (type == T_A && !((qdone >> m) & 1)) { wait_ge(arena + C_Q + m * 4, 64); qdone |= 1u << m; }
        if (type == T_OB && !wide) for (uint32_t i = 0; i < NS; i++) mbar_wait(empty + 8 * i, i >= p.stage ? p.phase : p.phase ^ 1);
        wide = type == T_OB;
        mbar_wait(mempty + 8 * mp.stage, mp.phase);
        asm volatile("st.shared.u32 [%0], %1;" :: "r"(mbox + 4 * mp.stage), "r"((p.stage << 24) | (type << 16) | (m << 8) | (k & 255)) : "memory");
        mbar_arrive(mfull + 8 * mp.stage);
        pipe_adv<2>(mp);
        if (type == T_END) break;
        if (type == T_P) { next = fetch(); continue; }
        if (type == T_L) {
          const int nr = sc.lrows[m], np = sc.ks[m];
          prefetch_l2(a.xin + (size_t)(m * 128 + k * 8 * nr) * cfg::DM, nr * 10240);
          wait_ge(arena + C_O + m * 4, np * (sc.wide[m] ? 4 : 10), m < 13 ? a.nap : 32);
          fence_proxy_async_global();
#pragma unroll 1
          for (int r = 0; r < nr; r++) {
            const int rg = m * 16 + k * nr + r;
#pragma unroll 1
            for (int q0 = 0; q0 <= np; q0 += 4) {
              const int n = min(4, np + 1 - q0);
              const uint32_t st = stage(n * 10240), fb = full + 8 * p.stage;
#pragma unroll 1
              for (int q = q0; q < q0 + n; q++) {
                if (q == 0) bulk_g2s(st, a.xin + (size_t)rg * 8 * cfg::DM, 10240, fb);
                else tma_load_3d(st + (q - q0) * 10240, &tmP, 0, rg & 7, ((q - 1) * 32 + (rg >> 3)) * 10, fb);
              }
              pipe_adv<NS>(p);
            }
          }
          next = fetch(); continue;
        }
        if (type <= T_A) {
          if (type != T_A)
#pragma unroll 1
            for (int kb = 0; kb < 10; kb++) {
              const uint32_t st = stage(STQ), fb = full + 8 * p.stage;
              tma_load_2d(st, &tmX, kb * 64, m * 128, fb);
              tma_load_3d(st + 16384, &tmQ, 0, kb * 64, k * 3, fb);
              pipe_adv<NS>(p);
              if (type == T_Q && kb == 8) next = fetch();
            }
          if (type != T_Q) {
            const size_t blk = ((size_t)m * 4 * 96 + k * 3) * 5120;
            kph ^= 1;
            mbar_wait(kvrdy, rph); rph ^= 1;
            next = fetch();
            fence_proxy_async_global();
#pragma unroll 1
            for (int w = type == T_A ? 0 : 2; w < 4; w++) {
              const uint32_t st = stage(2 * SEGB), fb = full + 8 * p.stage;
              for (int sg = 0; sg < 2; sg++) ld_kv(st + sg * SEGB, (w < 2 ? a.kg : a.vg) + blk + (size_t)(2 * (w & 1) + sg) * (96 * 5120), SEGB, fb);
              pipe_adv<NS>(p);
            }
          }
        } else {
          const int nn = wide ? 2 : 5, nb = wide ? 5 : 2, nt = k % nn, nkb = 96 / sc.ks[m], k0 = (k / nn) * nkb;
          const Pipe p0 = p;
          for (int kb = 0; kb < nkb; kb++) {
            if (wide && kb < NS && p.stage >= 2) { mbar_wait(barKfree, kph); mbar_wait(barKfree + 8, kph); }
            const uint32_t st = stage(16384 + nb * 8192), fb = full + 8 * p.stage;
            tma_load_3d(st + 16384, wide ? &tmWo5 : &tmWo2, 0, (k0 + kb) * 64, nt * nb, fb);
            if (kb >= NS) ld_o(st, a.o + ((size_t)m * 96 + k0 + kb) * 16384, 16384, fb);
            pipe_adv<NS>(p);
            if (kb == NS - 1 || (kb == nkb - 1 && nkb < NS)) {
              wait_ge(arena + C_QA + m * 4, 64, m < 14 ? a.nap : 32);
              fence_proxy_async_global();
              Pipe q = p0;
#pragma unroll 1
              for (int i = 0; i <= kb; i++) { ld_o(sb + q.stage * (wide ? STO : STQ), a.o + ((size_t)m * 96 + k0 + i) * 16384, 16384, full + 8 * q.stage); pipe_adv<NS>(q); }
            }
          }
          next = fetch();
          for (int w = wide ? -(int)((2 - p.stage) & 3) : 0; w < 2; w++) { mbar_wait(empty + 8 * p.stage, p.phase); mbar_arrive(full + 8 * p.stage); pipe_adv<NS>(p); }
          kph ^= wide;
        }
      }
    } } else if (warp < 11) { if (elect_one()) {
      const int w = warp - 9;
      uint32_t sph = 0;
      [[maybe_unused]] int nlog = 0;
#ifdef TIMELINE
      if (w == 0) { unsigned long long* lg = g_log + (((tl >= 12) * 132 + blockIdx.x) * 64 + nlog++) * 2; lg[0] = T_END << 16; lg[1] = gtime(); lg[2] = ~0ull; }
#endif
      while (true) {
        const uint32_t it = next_item();
        const int type = (it >> 16) & 255, m = (it >> 8) & 255, k = it & 255;
        const uint32_t slot = mp.stage;
        pipe_adv<2>(mp);
        if (type == T_END) break;
        mbar_wait(staged + 16 * w + 8 * slot, (sph >> slot) & 1); sph ^= 1u << slot;
        mbar_arrive(mempty + 8 * slot);
#ifdef TIMELINE
        if (w == 0 && nlog < 63) { unsigned long long* lg = g_log + (((tl >= 12) * 132 + blockIdx.x) * 64 + nlog++) * 2; lg[0] = (type << 16) | (m << 8) | k; lg[1] = gtime(); lg[2] = ~0ull; }
#endif
        if (type == T_L) continue;
        if (type == T_QA || type == T_A) {
          for (int jj = 0; jj < 3; jj++) bulk_s2g(a.o + ((size_t)m * 96 + k * 3 + jj) * 16384 + w * 8192, sb + OFF_K + w * 2 * SEGB + jj * 8192, 8192);
          bulk_commit();
          bulk_wait<0>();
          mbar_arrive(barKfree + 8 * w);
        } else if (type == T_OB || type == T_OS) {
          const bool wide = type == T_OB;
          const int nn = wide ? 2 : 5, nb = wide ? 5 : 2;
          const uint32_t own = wide ? 2 + w : ((it >> 24) + 96 / sc.ks[m] + w) % NS;
          bulk_s2g(a.part + ((size_t)((k / nn) * 32 + m * 2 + w) * 10 + (k % nn) * nb) * 8192, sb + own * (wide ? STO : STQ), nb * 8192);
          bulk_commit();
          bulk_wait<0>();
          mbar_arrive(empty + 8 * own);
          if (wide && w) { mbar_arrive(barKfree); mbar_arrive(barKfree + 8); }
        }
        if (type == T_Q || type == T_P) __threadfence();
        asm volatile("red.relaxed.gpu.global.add.u32 [%0], 1;" :: "l"(arena + (type == T_Q ? C_Q : (type <= T_A ? C_QA : (type == T_P ? C_P : C_O))) + m * 4) : "memory");
      }
    } } else if (elect_one()) {
      const uint64_t ef = policy_evict_first();
      uint32_t kph = 1;
      if (PF_WB && blockIdx.x >= 52) { prefetch_l2(pa.wb + (blockIdx.x - 52) * 32768, 32768); prefetch_l2(pa.wot + (blockIdx.x - 52) * 10240, 10240); }
      if (PF_WB > 1 && blockIdx.x >= 52) { prefetch_l2(a.xn + (blockIdx.x - 52) * 8192, 16384); prefetch_l2(a.xout + (blockIdx.x - 52) * 8192, 16384); }
      while (true) {
        const uint32_t it = next_item();
        const int type = (it >> 16) & 255, m = (it >> 8) & 255, k = it & 255;
        const uint32_t slot = mp.stage;
        pipe_adv<2>(mp);
        if (type == T_END) break;
        if (PF_XN && type == T_QA && m < 15) prefetch_l2(a.xq + ((m + 1) * 128 + k * 4) * cfg::DM, 5120);
        if (type == T_QA || type == T_A) {
          for (int spin = 0; spin < (1 << 21); spin++) {
            const uint4 f = ld_relaxed_v4(arena + prog_off(k, 0));
            if (min(min(f.x, f.y), f.z) >= (uint32_t)(4 * m + 4)) break;
            __nanosleep(m < 15 ? a.nap : a.nap2);
          }
          mbar_arrive(kvrdy);
          fence_proxy_async_global();
          const unsigned char* src = a.kg + ((size_t)m * 4 * 96 + k * 3) * 5120;
#pragma unroll 1
          for (int w = 0; w < 2; w++) {
            mbar_wait(barKfree + 8 * w, kph);
            if (type == T_A) { mbar_arrive(barK + 8 * w); continue; }
            mbar_expect_tx(barK + 8 * w, 2 * SEGB);
            for (int sg = 2 * w; sg < 2 * w + 2; sg++) { if (EF_KV) bulk_g2s_hint(sb + OFF_K + sg * SEGB, src + (size_t)sg * (96 * 5120), SEGB, barK + 8 * w, ef); else bulk_g2s(sb + OFF_K + sg * SEGB, src + (size_t)sg * (96 * 5120), SEGB, barK + 8 * w); }
          }
          kph ^= 1;
        } else if (type == T_OB) {
          mbar_wait(barKfree, kph); mbar_wait(barKfree + 8, kph);
          kph ^= 1;
        }
        mbar_arrive(mempty + 8 * slot);
      }
      if (blockIdx.x == gridDim.x - 1) asm volatile("griddepcontrol.wait;" ::: "memory");
    }
    return;
  }
  asm volatile("setmaxnreg.inc.sync.aligned.u32 232;");
  const int wg = warp >> 2, wi = warp & 3;
  const int g = lane >> 2, q4 = lane & 3;
  asm volatile("griddepcontrol.launch_dependents;" ::: "memory");
  Pipe p{0, 0};
  uint32_t kph = 0;
  auto own_slot = [&]() -> uint32_t {
    const uint32_t sA = p.stage, phA = p.phase; pipe_adv<NS>(p);
    const uint32_t sB = p.stage, phB = p.phase; pipe_adv<NS>(p);
    if (wi == 0) mbar_wait(full + 8 * (wg ? sA : sB), wg ? phA : phB);
    mbar_wait(full + 8 * (wg ? sB : sA), wg ? phB : phA);
    mbar_arrive_if((threadIdx.x & 127) == 0, empty + 8 * (wg ? sA : sB));
    return wg ? sB : sA;
  };
  while (true) {
    const uint32_t it = __shfl_sync(0xffffffffu, next_item(), 0);
    const int type = (it >> 16) & 255, m = (it >> 8) & 255, k = it & 255;
    mbar_arrive_if(lane == 0, mempty + 8 * mp.stage);
    const uint32_t done = staged + 16 * wg + 8 * mp.stage;
    pipe_adv<2>(mp);
    if (type == T_END) break;
    if (type == T_P) {
      prep_body(k, pa);
      __syncwarp();
      mbar_arrive_if(lane == 0, done);
      continue;
    }
    if (type == T_L) {
      const int nr = sc.lrows[m], np = sc.ks[m];
      const uint32_t po = (lane >> 4) * 1024 + warp * 128 + ((((lane >> 1) & 7) ^ warp) << 4) + (lane & 1) * 8;
#pragma unroll 1
      for (int r = 0; r < nr; r++) {
        uint2 xw[1][5]; float s[20];
#pragma unroll
        for (int i = 0; i < 20; i++) s[i] = 0.f;
#pragma unroll 1
        for (int q0 = 0; q0 <= np; q0 += 4) {
          const uint32_t st = sb + p.stage * STQ;
          mbar_wait(full + 8 * p.stage, p.phase);
          if (q0 == 0) static_for<0, 5>([&](auto I) { xw[0][I.value] = lds64_i<I.value * 256>(st + warp * 1280 + lane * 8); });
#pragma unroll 1
          for (int q = q0 ? 0 : 1; q < min(4, np + 1 - q0); q++)
            static_for<0, 5>([&](auto I) {
              constexpr int i = I.value;
              const uint2 t = lds64_i<i * 2048>(st + q * 10240 + po);
              s[4 * i] += bf_lo(t.x); s[4 * i + 1] += bf_hi(t.x); s[4 * i + 2] += bf_lo(t.y); s[4 * i + 3] += bf_hi(t.y);
            });
          bar_sync(3 + wg, 128);
          mbar_arrive_if((threadIdx.x & 127) == 0, empty + 8 * p.stage);
          pipe_adv<NS>(p);
        }
        const int row = (m * 16 + k * nr + r) * 8 + warp;
#pragma unroll
        for (int i = 0; i < 5; i++) {
          bf16r2(s[4 * i], s[4 * i + 1]); bf16r2(s[4 * i + 2], s[4 * i + 3]);
          xw[0][i] = make_uint2(pack_bf16(bf_lo(xw[0][i].x) + s[4 * i], bf_hi(xw[0][i].x) + s[4 * i + 1]), pack_bf16(bf_lo(xw[0][i].y) + s[4 * i + 2], bf_hi(xw[0][i].y) + s[4 * i + 3]));
          *(uint2*)(a.xout + (size_t)row * cfg::DM + i * 128 + lane * 4) = xw[0][i];
        }
        ln_rows<1>(xw, row, lane, a.xn, nullptr);
      }
      __syncwarp();
      mbar_arrive_if(lane == 0, done);
      continue;
    }
    if (type >= T_OB) {
      const int nkb = 96 / sc.ks[m];
      if (type == T_OB) {
        float a0[96], a1[64];
        tr_mainloop<192, 128>(a0, a1, p, sb, full, empty, nkb, wg);
        while (p.stage != 2) { if (wi == 0) mbar_wait(full + 8 * p.stage, p.phase); mbar_arrive_if((threadIdx.x & 127) == 0, empty + 8 * p.stage); pipe_adv<NS>(p); }
        const uint32_t st = sb + own_slot() * STO;
        stage_tiles<192>(a0, st, wi, lane); stage_tiles<128>(a1, st + 24576, wi, lane);
      } else {
        float a0[64], a1[1];
        tr_mainloop<128, 0>(a0, a1, p, sb, full, empty, nkb, wg);
        stage_tiles<128>(a0, sb + own_slot() * STQ, wi, lane);
      }
      fence_proxy_async();
      __syncwarp();
      mbar_arrive_if(lane == 0, done);
      continue;
    }
    uint32_t qf[12][4];
    uint4* qp = a.qs + ((size_t)((m & 7) * 32 + k) * 12) * 256 + threadIdx.x;
    if (type != T_A) {
      float acc[96], a1[1];
      tr_mainloop<192, 0>(acc, a1, p, sb, full, empty, 10, wg);
#pragma unroll
      for (int i = 0; i < 12; i++) {
        qf[i][0] = pack_bf16(acc[8 * i], acc[8 * i + 1]); qf[i][1] = pack_bf16(acc[8 * i + 2], acc[8 * i + 3]);
        qf[i][2] = pack_bf16(acc[8 * i + 4], acc[8 * i + 5]); qf[i][3] = pack_bf16(acc[8 * i + 6], acc[8 * i + 7]);
      }
      if (type == T_Q) {
#pragma unroll
        for (int i = 0; i < 12; i++) qp[i * 256] = make_uint4(qf[i][0], qf[i][1], qf[i][2], qf[i][3]);
        __syncwarp();
        mbar_arrive_if(lane == 0, done);
        continue;
      }
    } else {
#pragma unroll
      for (int i = 0; i < 12; i++) { const uint4 v = __ldcg(qp + i * 256); qf[i][0] = v.x; qf[i][1] = v.y; qf[i][2] = v.z; qf[i][3] = v.w; }
    }
    const uint32_t ost = sb + OFF_K + wg * 2 * SEGB;
    const bool second = wi >= 2;
    uint32_t pf[5][4];
    {
      float sa[20], sb2[20];
      uint32_t kbase = ost, kslot = 0;
      if (type == T_A) { kslot = own_slot(); kbase = sb + kslot * STQ; } else mbar_wait(barK + 8 * wg, kph);
      if (STAG && wg) bar_sync(1, 256);
      wgmma_fence();
#pragma unroll
      for (int i = 0; i < 12; i++) {
        wgmma_rs_n40<0>(sa, qf[i][0], qf[i][1], qf[i][2], qf[i][3], make_desc(kbase + i * 1280, 640, 128, 0), i != 0);
        wgmma_rs_n40<0>(sb2, qf[i][0], qf[i][1], qf[i][2], qf[i][3], make_desc(kbase + SEGB + i * 1280, 640, 128, 0), i != 0);
      }
      wgmma_commit();
      wgmma_wait<0>();
      if (STAG && !wg) bar_arrive(1, 256);
      mbar_arrive_if(type == T_A && (threadIdx.x & 127) == 0, empty + 8 * kslot);
      const float cs = 0.07216878364870322f * 1.4426950408889634f;
      const int r0 = 16 * (wi & 1) + g, r1 = r0 + 8;
      float m0 = -INFINITY, m1 = -INFINITY;
#pragma unroll
      for (int n = 0; n < 5; n++) {
#pragma unroll
        for (int e = 0; e < 2; e++) {
          const int key = 8 * n + 2 * q4 + e;
          float x = second ? sb2[4 * n + e] : sa[4 * n + e], y = second ? sb2[4 * n + 2 + e] : sa[4 * n + 2 + e];
          if (n < 4) { if (key > r0) x = -INFINITY; if (key > r1) y = -INFINITY; }
          sa[4 * n + e] = x; sa[4 * n + 2 + e] = y;
          m0 = fmaxf(m0, x); m1 = fmaxf(m1, y);
        }
      }
      m0 = fmaxf(m0, __shfl_xor_sync(0xffffffffu, m0, 1)); m1 = fmaxf(m1, __shfl_xor_sync(0xffffffffu, m1, 1));
      m0 = fmaxf(m0, __shfl_xor_sync(0xffffffffu, m0, 2)); m1 = fmaxf(m1, __shfl_xor_sync(0xffffffffu, m1, 2));
      float s0 = 0.f, s1 = 0.f;
#pragma unroll
      for (int n = 0; n < 5; n++) {
#pragma unroll
        for (int e = 0; e < 2; e++) {
          sa[4 * n + e] = ex2f((sa[4 * n + e] - m0) * cs); sa[4 * n + 2 + e] = ex2f((sa[4 * n + 2 + e] - m1) * cs);
          s0 += sa[4 * n + e]; s1 += sa[4 * n + 2 + e];
        }
      }
      s0 += __shfl_xor_sync(0xffffffffu, s0, 1); s1 += __shfl_xor_sync(0xffffffffu, s1, 1);
      s0 += __shfl_xor_sync(0xffffffffu, s0, 2); s1 += __shfl_xor_sync(0xffffffffu, s1, 2);
      const float i0 = rcpf(s0), i1 = rcpf(s1);
#pragma unroll
      for (int n = 0; n < 5; n++) {
        const uint32_t x = pack_bf16(sa[4 * n] * i0, sa[4 * n + 1] * i0), y = pack_bf16(sa[4 * n + 2] * i1, sa[4 * n + 3] * i1);
        if (n < 4) {
          pf[n >> 1][2 * (n & 1)] = second ? 0u : x; pf[n >> 1][2 * (n & 1) + 1] = second ? 0u : y;
          pf[2 + (n >> 1)][2 * (n & 1)] = second ? x : 0u; pf[2 + (n >> 1)][2 * (n & 1) + 1] = second ? y : 0u;
        } else {
          pf[4][0] = second ? 0u : x; pf[4][1] = second ? 0u : y; pf[4][2] = second ? x : 0u; pf[4][3] = second ? y : 0u;
        }
      }
    }
    {
      float o[96];
#pragma unroll
      for (int i = 0; i < 5; i++) { PIN(pf[i][0]); PIN(pf[i][1]); PIN(pf[i][2]); PIN(pf[i][3]); }
      const uint32_t own = own_slot(), vbase = sb + own * STQ;
      wgmma_fence();
#pragma unroll
      for (int i = 0; i < 5; i++)
        wgmma_rs_n192<1>(o, pf[i][0], pf[i][1], pf[i][2], pf[i][3], i < 4 ? make_desc(vbase + (i >> 1) * SEGB + (i & 1) * 256, 128, 640, 0) : make_desc(vbase + 512, SEGB, 640, 0), i != 0);
      wgmma_commit();
      if (type == T_A) mbar_wait(barK + 8 * wg, kph);
      kph ^= 1;
      wgmma_wait<0>();
      mbar_arrive_if((threadIdx.x & 127) == 0, empty + 8 * own);
      stage_tiles<192>(o, ost, wi, lane);
      fence_proxy_async();
      __syncwarp();
      mbar_arrive_if(lane == 0, done);
    }
  }
}
namespace bf {
constexpr int NS = 4, STAGE = 16384 + 32768;
constexpr int PIECE = 20480;
constexpr int OFF_PHI = 0, OFF_V = 40960, OFF_KV = 65536;
constexpr int OFF_OST = 5 * PIECE;
constexpr int OFF_WOT = 6 * PIECE;
constexpr int OFF_BAR = OFF_WOT + 102400;
constexpr int SMEM = OFF_BAR + 256;
static_assert(NS * STAGE <= OFF_BAR && SMEM <= 232448, "smem");
constexpr int KVACC = 32 * 5 * 1024;
struct Args {
  const unsigned char *wb, *wot;
  unsigned char *kvacc, *o2;
  const bf16* xin;
  bf16* xout;
  unsigned* go;
  const void* prep;
  const bf16 *pf0, *pf1;
  int pfn, pfns, pfwait;
  int tl;
};
}
__device__ __forceinline__ void hedgehog_features(float (&x)[2][5], uint32_t (&w)[2][5]) {
  const float L = 1.4426950408889634f;
  float mx[2], mn[2], sp[2], sn[2], pos[2][5], neg[2][5];
#pragma unroll
  for (int r = 0; r < 2; r++) {
    mx[r] = fmaxf(fmaxf(fmaxf(x[r][0], x[r][1]), fmaxf(x[r][2], x[r][3])), x[r][4]);
    mn[r] = fminf(fminf(fminf(x[r][0], x[r][1]), fminf(x[r][2], x[r][3])), x[r][4]);
  }
#pragma unroll
  for (int o = 1; o < 4; o <<= 1)
#pragma unroll
    for (int r = 0; r < 2; r++) {
      const uint32_t t = __shfl_xor_sync(0xffffffffu, __byte_perm(__float_as_uint(mn[r]), __float_as_uint(mx[r]), 0x7632), o);
      mx[r] = fmaxf(mx[r], bf_hi(t)); mn[r] = fminf(mn[r], bf_lo(t));
    }
#pragma unroll
  for (int r = 0; r < 2; r++) {
#pragma unroll
    for (int i = 0; i < 5; i++) { pos[r][i] = ex2f((x[r][i] - mx[r]) * L); neg[r][i] = ex2f((mn[r] - x[r][i]) * L); }
    sp[r] = ((pos[r][0] + pos[r][1]) + (pos[r][2] + pos[r][3])) + pos[r][4];
    sn[r] = ((neg[r][0] + neg[r][1]) + (neg[r][2] + neg[r][3])) + neg[r][4];
  }
#pragma unroll
  for (int o = 1; o < 4; o <<= 1)
#pragma unroll
    for (int r = 0; r < 2; r++) { sp[r] += __shfl_xor_sync(0xffffffffu, sp[r], o); sn[r] += __shfl_xor_sync(0xffffffffu, sn[r], o); }
#pragma unroll
  for (int r = 0; r < 2; r++) {
    const float ip = rcpf(sp[r]), in_ = rcpf(sn[r]);
    w[r][0] = pack_bf16(pos[r][0] * ip, pos[r][1] * ip); w[r][1] = pack_bf16(pos[r][2] * ip, pos[r][3] * ip);
    w[r][2] = pack_bf16(neg[r][0] * in_, neg[r][1] * in_); w[r][3] = pack_bf16(neg[r][2] * in_, neg[r][3] * in_);
    w[r][4] = pack_bf16(pos[r][4] * ip, neg[r][4] * in_);
  }
}
__device__ __forceinline__ void bulk_g2s_mc(uint32_t dst, const void* src, uint32_t bytes, uint32_t mb) {
  asm volatile("cp.async.bulk.shared::cluster.global.mbarrier::complete_tx::bytes.multicast::cluster [%0], [%1], %2, [%3], %4;"
               :: "r"(dst), "l"(src), "r"(bytes), "r"(mb), "h"((unsigned short)3) : "memory");
}
__device__ __forceinline__ void mbar_arrive_remote_if(bool c, uint32_t b) {
  asm volatile("{\n.reg .pred p;\nsetp.ne.u32 p, %1, 0;\n@p mbarrier.arrive.shared::cluster.b64 _, [%0];\n}" :: "r"(b), "r"((uint32_t)c) : "memory");
}

__global__ void __cluster_dims__(2, 1, 1) __launch_bounds__(384, 1) blayer_kernel(const __grid_constant__ CUtensorMap tmA, const __grid_constant__ bf::Args a) {
  using namespace bf;
  [[maybe_unused]] const int tl = a.tl;
  extern __shared__ __align__(1024) unsigned char smem_raw[];
  const uint32_t sb = smem_u32(smem_raw);
  const int warp = __shfl_sync(0xffffffffu, (int)threadIdx.x >> 5, 0), lane = threadIdx.x & 31;
  const uint32_t full = sb + OFF_BAR, empty = full + 8 * NS, full2 = empty + 8 * NS, empty2 = full2 + 64, barW = empty2 + 16, drained = barW + 8, staged = drained + 8, freeb = staged + 8;
  const int rank = blockIdx.x & 1, u = (blockIdx.x >> 1) & 7, mp = blockIdx.x >> 4;
  const int m = 2 * mp + rank;
  const int m2 = 2 * mp + (u & 1), ns = (u & ~1) + rank;
  const uint32_t dpeer = mapa_u32(sb, rank ^ 1) - sb;
  unsigned* cntO = (unsigned*)(a.kvacc + KVACC);
  if (threadIdx.x == 0) {
    for (int i = 0; i < NS; i++) { mbar_init(full + 8 * i, 1); mbar_init(empty + 8 * i, 4); }
    for (int i = 0; i < 8; i++) mbar_init(full2 + 8 * i, 1);
    mbar_init(empty2, 2); mbar_init(empty2 + 8, 2);
    mbar_init(barW, 1); mbar_init(drained, 1); mbar_init(staged, 8); mbar_init(freeb, 2);
    asm volatile("fence.mbarrier_init.release.cluster;" ::: "memory");
  }
  __syncthreads();
  asm volatile("barrier.cluster.arrive.relaxed.aligned; barrier.cluster.wait.aligned;" ::: "memory");
  if (warp >= 8) {
    asm volatile("setmaxnreg.dec.sync.aligned.u32 40;");
    if (warp == 8) { if (elect_one()) {
      const unsigned char* wsrc = a.wb + (size_t)u * 327680 + rank * 16384;
      if (a.prep) wait_ge(a.prep, 64);
      fence_proxy_async_global();
      for (int kb = 0; kb < NS; kb++) {
        mbar_expect_tx(full + 8 * kb, STAGE);
        bulk_g2s_mc(sb + kb * STAGE + 16384 + rank * 16384, wsrc + kb * 32768, 16384, full + 8 * kb);
      }
      asm volatile("griddepcontrol.wait;" ::: "memory");
      TL_BEGIN0(tl);
      if (blockIdx.x == 0) *a.go = 0;
      for (int kb = 0; kb < NS; kb++) tma_load_2d(sb + kb * STAGE, &tmA, kb * 64, m * 128, full + 8 * kb);
      if (m == 0) prefetch_l2(a.kvacc + u * (KVACC / 8), KVACC / 8);
#pragma unroll 1
      for (int kb = NS; kb < 10; kb++) {
        const uint32_t s = kb & 3, st = sb + s * STAGE, fb = full + 8 * s;
        mbar_wait(empty + 8 * s, ((kb >> 2) - 1) & 1);
        mbar_expect_tx(fb, STAGE);
        tma_load_2d(st, &tmA, kb * 64, m * 128, fb);
        bulk_g2s_mc(st + 16384 + rank * 16384, wsrc + kb * 32768, 16384, fb);
      }
      for (int i = 0; i < 6; i++) mbar_expect_tx(full2 + 8 * i, PIECE);
      mbar_wait(drained, 0);
      mbar_expect_tx(barW, 102400);
      bulk_g2s(sb + OFF_WOT, a.wot + (size_t)ns * 102400, 102400, barW);
      mbar_wait(staged, 0);
      bulk_s2g(a.o2 + (size_t)(m * 8 + u) * PIECE, sb + OFF_OST, PIECE);
      bulk_commit();
      bulk_wait<0>();
      asm volatile("red.relaxed.gpu.global.add.u32 [%0], 1;" :: "l"(cntO + m) : "memory");
      mbar_arrive(freeb); mbar_arrive_remote_if(true, freeb + dpeer);
      wait_ge(cntO + m2, 8, 20);
      mbar_wait(freeb, 0);
      fence_proxy_async_global();
      const unsigned char* osrc = a.o2 + (size_t)m2 * 8 * PIECE;
      for (int i = 0; i < 6; i++) bulk_g2s_mc(sb + i * PIECE + rank * (PIECE / 2), osrc + i * PIECE + rank * (PIECE / 2), PIECE / 2, full2 + 8 * i);
      for (int i = 0; i < 2; i++) {
        mbar_wait(empty2 + 8 * i, 0);
        mbar_expect_tx(full2 + 8 * (6 + i), PIECE);
        bulk_g2s(sb + i * PIECE, osrc + (6 + i) * PIECE, PIECE, full2 + 8 * (6 + i));
      }
    } } else if (warp == 9 && a.pf0) { if (elect_one()) {
      if (a.pfwait) asm volatile("griddepcontrol.wait;" ::: "memory");
      constexpr uint32_t CH = 2048;
      for (int i = 0; i < a.pfn; i++) {
        prefetch_l2((const unsigned char*)a.pf0 + (i * 128 + blockIdx.x) * CH, CH); prefetch_l2((const unsigned char*)a.pf1 + (i * 128 + blockIdx.x) * CH, CH);
        __nanosleep(a.pfns);
      }
    } }
    return;
  }
  asm volatile("setmaxnreg.inc.sync.aligned.u32 232;");
  const int wg = warp >> 2, wi = warp & 3;
  const int q4 = lane & 3;
  const bool lead = (threadIdx.x & 127) == 0;
  float acc[128];
  {
#pragma unroll 1
    for (int kb = 0; kb < 10; kb++) {
      const uint32_t s = kb & 3, st = sb + s * STAGE;
      mbar_wait(full + 8 * s, (kb >> 2) & 1);
      wgmma_fence();
#pragma unroll
      for (int kk = 0; kk < 4; kk++) wgmma_n256<0, 1>(acc, desc_kmajor(st + wg * 8192 + kk * 32), make_desc(st + 16384 + kk * 8192, 4096, 128, 0), (kb | kk) != 0);
      wgmma_commit();
      if (kb > 0 && kb < 7) { wgmma_wait<1>(); const uint32_t e = empty + 8 * ((kb - 1) & 3); mbar_arrive_if(lead, e); mbar_arrive_remote_if(lead, e + dpeer); }
    }
    wgmma_wait<0>();
    bar_sync(1, 256);
    mbar_arrive_if(threadIdx.x == 0, drained);
  }
  TL2((tl >= 12 ? 128 : 0) + 32 + 0);
  const uint32_t srow = (wg * 64 + wi * 16 + (lane & 15)) * 16 + (lane >> 4) * 2048;
  auto features = [&](auto T0, auto HH, uint32_t (&w)[2][5]) {
    constexpr int t = T0.value + 5 * (HH.value >> 1), o = (HH.value & 1) ? 3 : 0, e = HH.value & 1;
    float x[2][5];
#pragma unroll
    for (int r = 0; r < 2; r++) {
      x[r][0] = acc[4 * (t + o) + 2 * r]; x[r][1] = acc[4 * (t + o) + 2 * r + 1]; x[r][2] = acc[4 * (t + o + 1) + 2 * r]; x[r][3] = acc[4 * (t + o + 1) + 2 * r + 1];
      bf16r2(x[r][0], x[r][1]); bf16r2(x[r][2], x[r][3]);
    }
    x[0][4] = acc[4 * (t + 2) + e]; x[1][4] = acc[4 * (t + 2) + 2 + e];
    bf16r2(x[0][4], x[1][4]);
    hedgehog_features(x, w);
  };
  static_for<0, 4>([&](auto HH) {
    constexpr int hh = HH.value, t = 20 + 3 * hh;
    const uint32_t one = q4 == ((hh & 1) ? 0 : 2) ? 0x3f80u : 0u;
    const uint32_t va = sb + OFF_V + hh * 6144 + srow;
    stsm_x4(va, pack_bf16(acc[4 * t], acc[4 * t + 1]), pack_bf16(acc[4 * t + 2], acc[4 * t + 3]), pack_bf16(acc[4 * t + 4], acc[4 * t + 5]), pack_bf16(acc[4 * t + 6], acc[4 * t + 7]));
    const bool pad = (q4 >= 2) != (hh & 1);
    stsm_x2(va + 4096, pad ? one : pack_bf16(acc[4 * t + 8], acc[4 * t + 9]), pad ? one : pack_bf16(acc[4 * t + 10], acc[4 * t + 11]));
    uint32_t w[2][5];
    features(IC<10>{}, HH, w);
    const uint32_t pa = sb + OFF_PHI + hh * 10240 + srow;
    stsm_x4(pa, w[0][0], w[1][0], w[0][1], w[1][1]);
    stsm_x4(pa + 4096, w[0][2], w[1][2], w[0][3], w[1][3]);
    stsm_x2(pa + 8192, w[0][4], w[1][4]);
  });
  fence_proxy_async();
  bar_sync(1, 256);
  TL2((tl >= 12 ? 128 : 0) + 32 + 1);
  {
    float d0[12], d1[12];
    const uint32_t pa = sb + OFF_PHI + wg * 20480, pv = sb + OFF_V + wg * 12288;
    wgmma_fence();
#pragma unroll
    for (int k = 0; k < 8; k++) {
      wgmma_n24<1, 1>(d0, make_desc(pa + k * 256, 128, 2048, 0), make_desc(pv + k * 256, 128, 2048, 0), k != 0);
      wgmma_n24<1, 1>(d1, make_desc(pa + 10240 + k * 256, 128, 2048, 0), make_desc(pv + 6144 + k * 256, 128, 2048, 0), k != 0);
    }
    wgmma_commit();
    wgmma_wait<0>();
    unsigned char* dst = a.kvacc + ((u * 4 + wg * 2) * 5 + 2 * wi) * 1024 + lane * 16;
    auto red4 = [&](bool on, unsigned char* p, float x, float y, float z) {
      asm volatile("{\n.reg .pred p;\nsetp.ne.u32 p, %4, 0;\n@p red.relaxed.gpu.global.add.v4.f32 [%0], {%1,%2,%3,%5};\n}" :: "l"(p), "f"(x), "f"(y), "f"(z), "r"((uint32_t)on), "f"(1.f) : "memory");
    };
    red4(wi < 3, dst, d0[0], d0[1], d0[4]); red4(wi < 3, dst + 512, d0[5], d0[8], d0[9]);
    red4(wi < 3, dst + 5120, d1[0], d1[1], d1[4]); red4(wi < 3, dst + 5632, d1[5], d1[8], d1[9]);
    red4(wi < 2, dst + 1024, d0[2], d0[3], d0[6]); red4(wi < 2, dst + 1536, d0[7], d0[10], d0[11]);
    red4(wi < 2, dst + 6144, d1[2], d1[3], d1[6]); red4(wi < 2, dst + 6656, d1[7], d1[10], d1[11]);
  }
  TL2((tl >= 12 ? 128 : 0) + 32 + 2);
  uint32_t qf[4][2][5];
  static_for<0, 4>([&](auto HH) { features(IC<0>{}, HH, qf[HH.value]); });
  uint4 xr[5];
#pragma unroll
  for (int i = 0; i < 5; i++) {
    const int c = lane + 32 * i;
    xr[i] = __ldcg((const uint4*)(a.xin + (size_t)(m2 * 128 + wg * 64 + wi * 16 + c / 10) * cfg::DM + ns * 80 + (c % 10) * 8));
  }
  {
    const unsigned char* src = a.kvacc + (u * 20 + warp) * 1024 + lane * 16;
    uint4 v[6];
    int spin = 0;
    while (true) {
      v[0] = ld_relaxed_v4_i<0>(src); v[1] = ld_relaxed_v4_i<512>(src); v[2] = ld_relaxed_v4_i<8192>(src); v[3] = ld_relaxed_v4_i<8704>(src);
      v[4] = ld_relaxed_v4_i<0>(src + (wg ? 0 : 16384)); v[5] = ld_relaxed_v4_i<512>(src + (wg ? 0 : 16384));
      const uint32_t c = (v[0].w & v[1].w & v[2].w) & (v[3].w & v[4].w & v[5].w);
      if (!__any_sync(0xffffffffu, (c & 0x41800000u) != 0x41800000u) || ++spin >= SPIN_LIMIT) break;
      __nanosleep(100);
    }
    const uint32_t kd = sb + OFF_KV + warp * 384 + lane * 4;
#pragma unroll
    for (int i = 0; i < 3; i++)
      if (i < 2 || wg == 0) {
        sts32(kd + i * 3072, pack_bf16(__uint_as_float(v[2 * i].x), __uint_as_float(v[2 * i].y)));
        sts32(kd + i * 3072 + 128, pack_bf16(__uint_as_float(v[2 * i].z), __uint_as_float(v[2 * i + 1].x)));
        sts32(kd + i * 3072 + 256, pack_bf16(__uint_as_float(v[2 * i + 1].y), __uint_as_float(v[2 * i + 1].z)));
      }
  }
  fence_proxy_async();
  bar_sync(1, 256);
  TL2((tl >= 12 ? 128 : 0) + 32 + 3);
  {
    float d[4][12];
    uint32_t zero = 0; PIN(zero);
#pragma unroll
    for (int hh = 0; hh < 4; hh++)
#pragma unroll
      for (int i = 0; i < 5; i++) { PIN(qf[hh][0][i]); PIN(qf[hh][1][i]); }
    wgmma_fence();
#pragma unroll
    for (int hh = 0; hh < 4; hh++) {
      const uint32_t kb = sb + OFF_KV + hh * 1920;
      wgmma_rs_n24<1>(d[hh], qf[hh][0][0], qf[hh][1][0], qf[hh][0][1], qf[hh][1][1], make_desc(kb, 384, 128, 0), 0);
      wgmma_rs_n24<1>(d[hh], qf[hh][0][2], qf[hh][1][2], qf[hh][0][3], qf[hh][1][3], make_desc(kb + 768, 384, 128, 0), 1);
      wgmma_rs_n24<1>(d[hh], qf[hh][0][4], qf[hh][1][4], zero, zero, make_desc(kb + 1536, 0, 128, 0), 1);
    }
    wgmma_commit();
    wgmma_wait<0>();
    uint32_t ow[4][6];
#pragma unroll
    for (int hh = 0; hh < 4; hh++) {
      const int zl = (lane & ~3) | ((hh & 1) ? 0 : 2);
      const float da = bf16r(bf16r(__shfl_sync(0xffffffffu, d[hh][8], zl)) + 1e-6f), db = bf16r(bf16r(__shfl_sync(0xffffffffu, d[hh][10], zl)) + 1e-6f);
#pragma unroll
      for (int n = 0; n < 3; n++) {
        bf16r2(d[hh][4 * n], d[hh][4 * n + 1]); bf16r2(d[hh][4 * n + 2], d[hh][4 * n + 3]);
        ow[hh][2 * n] = pack_bf16(__fdividef(d[hh][4 * n], da), __fdividef(d[hh][4 * n + 1], da));
        ow[hh][2 * n + 1] = pack_bf16(__fdividef(d[hh][4 * n + 2], db), __fdividef(d[hh][4 * n + 3], db));
      }
    }
#pragma unroll
    for (int p = 0; p < 2; p++) {
      const uint32_t oa = sb + OFF_OST + p * 10240 + srow;
      stsm_x4(oa, ow[2 * p][0], ow[2 * p][1], ow[2 * p][2], ow[2 * p][3]);
      stsm_x2(oa + 4096, q4 < 2 ? ow[2 * p][4] : ow[2 * p + 1][4], q4 < 2 ? ow[2 * p][5] : ow[2 * p + 1][5]);
      stsm_x4(oa + 6144, ow[2 * p + 1][0], ow[2 * p + 1][1], ow[2 * p + 1][2], ow[2 * p + 1][3]);
    }
    fence_proxy_async();
    __syncwarp();
    mbar_arrive_if(lane == 0, staged);
  }
  TL2((tl >= 12 ? 128 : 0) + 32 + 4);
  float c2[40];
  mbar_wait(barW, 0);
#pragma unroll 1
  for (int i = 0; i < 8; i++) {
    mbar_wait(full2 + 8 * i, 0);
    const uint32_t st = sb + (i < 6 ? i : i - 6) * PIECE + wg * 1024, wo = sb + OFF_WOT + i * 12800;
    wgmma_fence();
#pragma unroll
    for (int kk = 0; kk < 5; kk++) wgmma_n80<0, 1>(c2, make_desc(st + kk * 4096, 2048, 128, 0), make_desc(wo + kk * 2560, 1280, 128, 0), (i | kk) != 0);
    wgmma_commit();
    if (i == 1 || i == 2) { wgmma_wait<1>(); mbar_arrive_if(lead, empty2 + 8 * (i - 1)); }
  }
  wgmma_wait<0>();
  TL2((tl >= 12 ? 128 : 0) + 32 + 5);
  {
    bar_sync(1, 256);
    const uint32_t ost = sb + 2 * PIECE + warp * 3072;
#pragma unroll
    for (int v = 0; v < 10; v += 2)
      stsm_x4(ost + (lane & 15) * 176 + (v + (lane >> 4)) * 16, pack_bf16(c2[4 * v], c2[4 * v + 1]), pack_bf16(c2[4 * v + 2], c2[4 * v + 3]),
              pack_bf16(c2[4 * v + 4], c2[4 * v + 5]), pack_bf16(c2[4 * v + 6], c2[4 * v + 7]));
    __syncwarp();
#pragma unroll
    for (int i = 0; i < 5; i++) {
      const int c = lane + 32 * i, row = c / 10, chunk = c % 10;
      const uint4 y = lds128(ost + row * 176 + chunk * 16);
      const size_t off = (size_t)(m2 * 128 + wg * 64 + wi * 16 + row) * cfg::DM + ns * 80 + chunk * 8;
      const uint4 x = xr[i];
      *(uint4*)(a.xout + off) = make_uint4(pack_bf16(bf_lo(x.x) + bf_lo(y.x), bf_hi(x.x) + bf_hi(y.x)), pack_bf16(bf_lo(x.y) + bf_lo(y.y), bf_hi(x.y) + bf_hi(y.y)),
                                           pack_bf16(bf_lo(x.z) + bf_lo(y.z), bf_hi(x.z) + bf_hi(y.z)), pack_bf16(bf_lo(x.w) + bf_lo(y.w), bf_hi(x.w) + bf_hi(y.w)));
    }
  }
  TL_END(tl);
}
__device__ __align__(32768) unsigned char g_arena[AR_SIZE];
__device__ unsigned g_go[32];
__device__ __align__(1024) uint2 g_xh[2048 * 160];
__device__ __align__(1024) unsigned char g_k[64 * 96 * 5120], g_v[64 * 96 * 5120];
__device__ __align__(1024) bf16 g_o[2048 * 6144];
__device__ __align__(1024) uint4 g_qs[8 * 32 * 12 * 256];
__device__ __align__(1024) bf16 g_xn[2048 * 640], g_xn2[2048 * 640], g_xa[2048 * 640], g_xb[2048 * 640];
__device__ __align__(1024) bf16 g_part[24 * 2048 * 640];
__device__ __align__(1024) bf16 g_wb[2048 * 640], g_wot[640 * 640], g_pq[2048 * 640];
__device__ __align__(1024) float g_kvacc[bf::KVACC / 4 + 64];

typedef CUresult (*EncodeFn)(CUtensorMap*, CUtensorMapDataType, cuuint32_t, void*, const cuuint64_t*, const cuuint64_t*, const cuuint32_t*,
                             const cuuint32_t*, CUtensorMapInterleave, CUtensorMapSwizzle, CUtensorMapL2promotion, CUtensorMapFloatOOBfill);
static EncodeFn g_encode = nullptr;
static CUtensorMap make_map(const void* p, uint64_t cols, uint64_t rows, uint32_t bc, uint32_t br, bool swz = true) {
  CUtensorMap m;
  cuuint64_t dims[2] = {cols, rows}, strides[1] = {cols * 2};
  cuuint32_t box[2] = {bc, br}, es[2] = {1, 1};
  g_encode(&m, CU_TENSOR_MAP_DATA_TYPE_BFLOAT16, 2, const_cast<void*>(p), dims, strides, box, es, CU_TENSOR_MAP_INTERLEAVE_NONE,
           swz ? CU_TENSOR_MAP_SWIZZLE_128B : CU_TENSOR_MAP_SWIZZLE_NONE, CU_TENSOR_MAP_L2_PROMOTION_L2_256B, CU_TENSOR_MAP_FLOAT_OOB_FILL_NONE);
  return m;
}
static CUtensorMap make_map3(const void* p, uint64_t cols, uint64_t rows, uint32_t nb) {
  CUtensorMap m;
  cuuint64_t dims[3] = {64, rows, cols / 64}, strides[2] = {cols * 2, 128};
  cuuint32_t box[3] = {64, 64, nb}, es[3] = {1, 1, 1};
  g_encode(&m, CU_TENSOR_MAP_DATA_TYPE_BFLOAT16, 3, const_cast<void*>(p), dims, strides, box, es, CU_TENSOR_MAP_INTERLEAVE_NONE,
           CU_TENSOR_MAP_SWIZZLE_128B, CU_TENSOR_MAP_L2_PROMOTION_L2_256B, CU_TENSOR_MAP_FLOAT_OOB_FILL_NONE);
  return m;
}
template <class T> static T* sym(const T& s) { void* p = nullptr; cudaGetSymbolAddress(&p, s); return (T*)p; }

struct Ptrs {
  unsigned char *arena, *k, *v; bf16 *o, *xn, *xa, *xb, *wb, *wot, *pq; float *part, *kvacc; uint2* xh; uint4* qs; bf16* xn2; unsigned* go;
};

static tr::Sched make_sched(int layer, const char* str, const int* ks, const int* lr) {
  using namespace tr;
  Sched s = {};
  int n = 0;
  for (int b = 0; b < 16; b++) { s.ks[b] = (uint8_t)abs(ks[b]); s.wide[b] = ks[b] > 0; s.lrows[b] = (uint8_t)lr[b]; }
  for (const char* p = str; *p;) {
    if (*p == ' ') { p++; continue; }
    const char c = *p++;
    char* e;
    const int b = (int)strtol(p, &e, 10); p = e;
    int first = 0, cnt = c == 'o' ? s.ks[b] * (s.wide[b] ? 2 : 5) : (c == 'l' ? 16 / lr[b] : 32);
    if (*p == '.') { first = (int)strtol(p + 1, &e, 10); cnt = (int)strtol(e + 1, &e, 10); p = e; }
    const int type = c == 'a' ? T_QA : (c == 'q' ? T_Q : (c == 't' ? T_A : (c == 'l' ? T_L : (c == 'p' ? T_P : (s.wide[b] ? T_OB : T_OS)))));
    if (type == T_P && layer > 0) continue;
    for (int i = 0; i < cnt && n < MAXITEMS - 1; i++) s.item[n++] = (uint16_t)((type << 11) | (b << 7) | (first + i));
  }
  s.n = n; s.item[n] = T_END << 11;
  return s;
}
static tr::Sched sched_of(int layer) {
  const char* str = "q13 q14 a0 q15 a1 o0 p0.0.16 o1 a2 p0.16.16 a3 o2 a4 o3 a5 o4 l0 a6 o5 l1 a7 o6 l2 a8 o7 l3 a9 o8 l4 a10 o9 l5 a11.0.24 o10 a11.24.8 a12 l6 o11 l7 t13 o12 t14 t15 o14 o13 l10 o15 l9 l14 l11 l8 l12 l13 l15";
  int ks[16] = {2, 2, 2, 2, 2, 3, 2, 3, 2, 2, 2, 3, 4, -6, -6, -12}, lr[16] = {4, 4, 4, 4, 4, 4, 4, 4, 4, 1, 4, 1, 1, 1, 1, 1};
#ifdef TUNE
  if (getenv("SCHED")) str = getenv("SCHED");
  if (layer == 0 && getenv("SCHED0")) str = getenv("SCHED0");
  if (const char* p = getenv("KS")) for (int b = 0; b < 16; b++) { char* e; ks[b] = (int)strtol(p, &e, 10); p = e; }
  if (const char* p = getenv("LR")) for (int b = 0; b < 16; b++) { char* e; lr[b] = (int)strtol(p, &e, 10); p = e; }
#endif
  return make_sched(layer, str, ks, lr);
}
#ifndef TRAIL_GRID
#define TRAIL_GRID 132
#endif
#ifndef PDL_LN
#define PDL_LN 0
#endif
#ifndef PDL_CH
#define PDL_CH 1
#endif
#ifndef PDL_B
#define PDL_B 1
#endif
#ifndef PF_A
#define PF_A 1
#endif
#ifndef PF_B
#define PF_B 1
#endif
extern "C" void kernel_launch(void* const* d_in, const int* in_sizes, int n_in, void* d_out, int out_size) {
  const bf16* x = (const bf16*)d_in[0];
  const bf16* mem0 = (const bf16*)d_in[1];
  const bf16 *Wq = (const bf16*)d_in[2], *Wk = (const bf16*)d_in[3], *Wv = (const bf16*)d_in[4], *Wo = (const bf16*)d_in[5];
  const bf16 *wqkv = (const bf16*)d_in[8], *wphi = (const bf16*)d_in[9], *wo = (const bf16*)d_in[10];
  bf16* out = (bf16*)d_out;
  static Ptrs P; static bool init = false;
  if (!init) {
    void* fn = nullptr; cudaDriverEntryPointQueryResult qr;
    cudaGetDriverEntryPoint("cuTensorMapEncodeTiled", &fn, cudaEnableDefault, &qr);
    g_encode = (EncodeFn)fn;
    void* p;
    cudaGetSymbolAddress(&p, g_arena); P.arena = (unsigned char*)p;
    cudaGetSymbolAddress(&p, g_k); P.k = (unsigned char*)p;   cudaGetSymbolAddress(&p, g_v); P.v = (unsigned char*)p;
    cudaGetSymbolAddress(&p, g_o); P.o = (bf16*)p;
    cudaGetSymbolAddress(&p, g_xn); P.xn = (bf16*)p;
    cudaGetSymbolAddress(&p, g_xa); P.xa = (bf16*)p;   cudaGetSymbolAddress(&p, g_xb); P.xb = (bf16*)p;
    cudaGetSymbolAddress(&p, g_wb); P.wb = (bf16*)p;   cudaGetSymbolAddress(&p, g_wot); P.wot = (bf16*)p;
    cudaGetSymbolAddress(&p, g_pq); P.pq = (bf16*)p;   cudaGetSymbolAddress(&p, g_part); P.part = (float*)p;
    cudaGetSymbolAddress(&p, g_kvacc); P.kvacc = (float*)p;
    cudaGetSymbolAddress(&p, g_xh); P.xh = (uint2*)p;
    cudaGetSymbolAddress(&p, g_go); P.go = (unsigned*)p;
    cudaGetSymbolAddress(&p, g_qs); P.qs = (uint4*)p;
    cudaGetSymbolAddress(&p, g_xn2); P.xn2 = (bf16*)p;
    cudaFuncSetAttribute(chain_kernel, cudaFuncAttributeMaxDynamicSharedMemorySize, ch::SMEM);
    cudaFuncSetAttribute(trail_kernel, cudaFuncAttributeMaxDynamicSharedMemorySize, tr::SMEM);
    cudaFuncSetAttribute(blayer_kernel, cudaFuncAttributeMaxDynamicSharedMemorySize, bf::SMEM);
    init = true;
  }
  const CUtensorMap tmXn = make_map(P.xn, 640, 2048, 64, 128), tmXn2 = make_map(P.xn2, 640, 2048, 64, 128);
  const CUtensorMap tmWq = make_map3(Wq, 6144, 640, 3);
  const CUtensorMap tmCq = make_map(Wq, 6144, 640, 64, 160), tmCk = make_map(Wk, 6144, 640, 64, 160), tmCv = make_map(Wv, 6144, 640, 64, 160), tmCo = make_map(Wo, 640, 6144, 224, 64, false);
  const CUtensorMap tmWo5 = make_map3(Wo, 640, 6144, 5), tmWo2 = make_map3(Wo, 640, 6144, 2);

  CUtensorMap tmP;
  {
    cuuint64_t dims[3] = {256, 8, 24 * 320}, strides[2] = {1024, 8192};
    cuuint32_t box[3] = {256, 1, 10}, es[3] = {1, 1, 1};
    g_encode(&tmP, CU_TENSOR_MAP_DATA_TYPE_UINT32, 3, P.part, dims, strides, box, es, CU_TENSOR_MAP_INTERLEAVE_NONE, CU_TENSOR_MAP_SWIZZLE_NONE,
             CU_TENSOR_MAP_L2_PROMOTION_NONE, CU_TENSOR_MAP_FLOAT_OOB_FILL_NONE);
  }
  ChainArgs ca;
  ca.xh = P.xh; ca.mem0 = mem0; ca.kg = P.k; ca.vg = P.v;
  ca.arena = P.arena; ca.dbg = nullptr; ca.go = P.go; ca.delay = POLL_DELAY; ca.margin = 150;
#ifdef TUNE
  if (getenv("MG")) ca.margin = atoi(getenv("MG"));
  if (getenv("PD")) ca.delay = atoi(getenv("PD"));
#endif
  ca.tl = 0;
  uint4* zar = (uint4*)P.arena; const int nzar = AR_SIZE / 16;
  uint4* zkv = (uint4*)P.kvacc; const int nzkv = (bf::KVACC / 4 + 64) / 4;

  const PrepArgs pa{wqkv, wphi, wo, (unsigned char*)P.wb, (unsigned char*)P.wot};
  const bf16* xcur = x;
  cudaLaunchAttribute at[1];
  at[0].id = cudaLaunchAttributeProgrammaticStreamSerialization; at[0].val.programmaticStreamSerializationAllowed = 1;
  auto cfgof = [&](int grid, int block, int smem, bool pdl) {
    cudaLaunchConfig_t lc = {};
    lc.gridDim = dim3(grid); lc.blockDim = dim3(block); lc.dynamicSmemBytes = smem; lc.stream = cudaStreamPerThread;
    lc.attrs = at; lc.numAttrs = pdl ? 1 : 0;
    return lc;
  };
  for (int layer = 0; layer < 2; layer++) {
    const int tl = layer * 12;
    cudaLaunchConfig_t lc = cfgof(256, 256, 0, layer > 0 && PDL_LN);
    cudaLaunchKernelEx(&lc, ln_kernel, xcur, P.xn, P.xh, zar, nzar, zkv, nzkv, Wk, Wv, layer == 0 ? PF_A : 0, tl + 0);
    ca.tl = tl + 2;
    lc = cfgof(96, 384, ch::SMEM, PDL_CH);
    cudaLaunchKernelEx(&lc, chain_kernel, ca, tmCq, tmCk, tmCv, tmCo);
    lc = cfgof(TRAIL_GRID, 384, tr::SMEM, true);
    tr::Args ta{P.k, P.v, (unsigned char*)P.o, P.qs, (unsigned char*)P.part, xcur, P.xn, P.xa, P.xn2, P.arena, P.go, tl + 4, 100, 60};
#ifdef TUNE
    if (getenv("NAP")) ta.nap = atoi(getenv("NAP"));
    if (getenv("NAP2")) ta.nap2 = atoi(getenv("NAP2"));
#endif
    cudaLaunchKernelEx(&lc, trail_kernel, tmXn, tmWq, tmWo5, tmWo2, tmP, sched_of(layer), ta, pa);
    lc = cfgof(128, 384, bf::SMEM, PDL_B);
    bf::Args ba{(const unsigned char*)P.wb, (const unsigned char*)P.wot, (unsigned char*)P.kvacc, (unsigned char*)P.pq, P.xa, layer == 0 ? P.xb : out, P.go, layer == 0 ? P.arena + tr::C_P : nullptr,
                      layer == 0 && PF_B ? Wk : nullptr, Wv, 30, 500, 0, tl + 7};
#ifdef TUNE
    if (getenv("PFN")) ba.pfn = atoi(getenv("PFN"));
    if (getenv("PFNS")) ba.pfns = atoi(getenv("PFNS"));
    if (getenv("PFWT")) ba.pfwait = atoi(getenv("PFWT"));
    if (getenv("PFB")) ba.pf0 = layer == 0 && atoi(getenv("PFB")) ? Wk : nullptr;
#endif
    cudaLaunchKernelEx(&lc, blayer_kernel, tmXn2, ba);
    xcur = P.xb;
  }
}
```

```cpp
#include <cuda_runtime.h>
#include <cuda.h>
#include <cuda_bf16.h>
#include <stdint.h>
#include <stdlib.h>
#include <type_traits>

typedef __nv_bfloat16 bf16;

namespace cfg {
constexpr int S = 2048, DM = 640, H = 32, DH = 192, NSEG = 64, SEG = 32, NM = 8;
constexpr int HD = H * DH;
}

__device__ __forceinline__ uint32_t smem_u32(const void* p) { return (uint32_t)__cvta_generic_to_shared(p); }
__device__ __forceinline__ uint32_t mapa_u32(uint32_t a, uint32_t r) {
  uint32_t o; asm("mapa.shared::cluster.u32 %0, %1, %2;" : "=r"(o) : "r"(a), "r"(r)); return o;
}
__device__ __forceinline__ void mbar_init(uint32_t b, uint32_t c) {
  asm volatile("mbarrier.init.shared::cta.b64 [%0], %1;" :: "r"(b), "r"(c) : "memory");
}
__device__ __forceinline__ void mbar_expect_tx(uint32_t b, uint32_t bytes) {
  asm volatile("mbarrier.arrive.expect_tx.shared::cta.b64 _, [%0], %1;" :: "r"(b), "r"(bytes) : "memory");
}
__device__ __forceinline__ void mbar_arrive(uint32_t b) {
  asm volatile("mbarrier.arrive.shared::cta.b64 _, [%0];" :: "r"(b) : "memory");
}
__device__ __forceinline__ void mbar_expect_tx_if(bool c, uint32_t b, uint32_t bytes) {
  asm volatile("{\n.reg .pred p;\nsetp.ne.u32 p, %2, 0;\n@p mbarrier.arrive.expect_tx.shared::cta.b64 _, [%0], %1;\n}" :: "r"(b), "r"(bytes), "r"((uint32_t)c) : "memory");
}
__device__ __forceinline__ void mbar_arrive_if(bool c, uint32_t b) {
  asm volatile("{\n.reg .pred p;\nsetp.ne.u32 p, %1, 0;\n@p mbarrier.arrive.shared::cta.b64 _, [%0];\n}" :: "r"(b), "r"((uint32_t)c) : "memory");
}
__device__ __forceinline__ bool mbar_try(uint32_t b, uint32_t ph) {
  uint32_t p;
  asm volatile("{.reg .pred p; mbarrier.try_wait.parity.shared::cta.b64 p, [%1], %2; selp.u32 %0, 1, 0, p;}"
               : "=r"(p) : "r"(b), "r"(ph) : "memory");
  return p;
}
__device__ __forceinline__ bool mbar_try_cluster(uint32_t b, uint32_t ph) {
  uint32_t p;
  asm volatile("{.reg .pred p; mbarrier.try_wait.parity.acquire.cluster.shared::cta.b64 p, [%1], %2; selp.u32 %0, 1, 0, p;}"
               : "=r"(p) : "r"(b), "r"(ph) : "memory");
  return p;
}
#ifndef SPIN_LIMIT
#define SPIN_LIMIT (1 << 20)
#endif
__device__ __forceinline__ void mbar_wait(uint32_t b, uint32_t ph) {
  asm volatile("{\n.reg .pred p, q;\n.reg .u32 c;\nmov.u32 c, 0;\n"
               "W_%=:\nmbarrier.try_wait.parity.shared::cta.b64 p, [%0], %1;\n@p bra.uni D_%=;\n"
               "add.u32 c, c, 1;\nsetp.lt.u32 q, c, %2;\n@q bra.uni W_%=;\nD_%=:\n}"
               :: "r"(b), "r"(ph), "n"(SPIN_LIMIT) : "memory");
}
__device__ __forceinline__ void mbar_spin(uint32_t b, uint32_t ph) {
  asm volatile("{\n.reg .pred p, q;\n.reg .u32 c;\nmov.u32 c, 0;\n"
               "W_%=:\nmbarrier.test_wait.parity.shared::cta.b64 p, [%0], %1;\n@p bra D_%=;\n"
               "add.u32 c, c, 1;\nsetp.lt.u32 q, c, %2;\n@q bra W_%=;\nD_%=:\n}"
               :: "r"(b), "r"(ph), "n"(SPIN_LIMIT) : "memory");
}
#define PIN(x) asm volatile("" : "+r"(x))
__device__ __forceinline__ void mbar_wait_cluster(uint32_t b, uint32_t ph) {
  int s = 0;
  while (!mbar_try_cluster(b, ph)) { if (++s > SPIN_LIMIT) break; }
}
__device__ __forceinline__ void st_async_v2(uint32_t a, uint32_t x, uint32_t y, uint32_t mb) {
  asm volatile("st.async.weak.shared::cluster.mbarrier::complete_tx::bytes.v2.b32 [%0], {%1,%2}, [%3];"
               :: "r"(a), "r"(x), "r"(y), "r"(mb) : "memory");
}
__device__ __forceinline__ void st_async_v4(uint32_t a, uint32_t x, uint32_t y, uint32_t z, uint32_t w, uint32_t mb) {
  asm volatile("st.async.weak.shared::cluster.mbarrier::complete_tx::bytes.v4.b32 [%0], {%1,%2,%3,%4}, [%5];"
               :: "r"(a), "r"(x), "r"(y), "r"(z), "r"(w), "r"(mb) : "memory");
}
__device__ __forceinline__ void bulk_g2s(uint32_t dst, const void* src, uint32_t bytes, uint32_t mb) {
  asm volatile("cp.async.bulk.shared::cluster.global.mbarrier::complete_tx::bytes [%0], [%1], %2, [%3];"
               :: "r"(dst), "l"(src), "r"(bytes), "r"(mb) : "memory");
}
__device__ __forceinline__ void cp_async16(uint32_t dst, const void* src) {
  asm volatile("cp.async.cg.shared.global [%0], [%1], 16;" :: "r"(dst), "l"(src) : "memory");
}
__device__ __forceinline__ void cp_async_wait_all() { asm volatile("cp.async.wait_all;" ::: "memory"); }
__device__ __forceinline__ void fence_proxy_async() { asm volatile("fence.proxy.async.shared::cta;" ::: "memory"); }
__device__ __forceinline__ void bar_sync(int id, int n) { asm volatile("bar.sync %0, %1;" :: "r"(id), "r"(n) : "memory"); }
__device__ __forceinline__ void bar_arrive(int id, int n) { asm volatile("bar.arrive %0, %1;" :: "r"(id), "r"(n) : "memory"); }
__device__ __forceinline__ void cluster_sync_all() {
  asm volatile("barrier.cluster.arrive.release.aligned; barrier.cluster.wait.acquire.aligned;" ::: "memory");
}
__device__ __forceinline__ void ldsm_x4(uint32_t (&r)[4], uint32_t a) {
  asm volatile("ldmatrix.sync.aligned.m8n8.x4.shared.b16 {%0,%1,%2,%3}, [%4];"
               : "=r"(r[0]), "=r"(r[1]), "=r"(r[2]), "=r"(r[3]) : "r"(a) : "memory");
}
__device__ __forceinline__ void ldsm_x4_t(uint32_t (&r)[4], uint32_t a) {
  asm volatile("ldmatrix.sync.aligned.m8n8.x4.trans.shared.b16 {%0,%1,%2,%3}, [%4];"
               : "=r"(r[0]), "=r"(r[1]), "=r"(r[2]), "=r"(r[3]) : "r"(a) : "memory");
}
template <int IMM> __device__ __forceinline__ void ldsm_x4_i(uint32_t (&r)[4], uint32_t a) {
  asm volatile("ldmatrix.sync.aligned.m8n8.x4.shared.b16 {%0,%1,%2,%3}, [%4+%5];"
               : "=r"(r[0]), "=r"(r[1]), "=r"(r[2]), "=r"(r[3]) : "r"(a), "n"(IMM) : "memory");
}
template <int IMM> __device__ __forceinline__ void ldsm_x4_t_i(uint32_t (&r)[4], uint32_t a) {
  asm volatile("ldmatrix.sync.aligned.m8n8.x4.trans.shared.b16 {%0,%1,%2,%3}, [%4+%5];"
               : "=r"(r[0]), "=r"(r[1]), "=r"(r[2]), "=r"(r[3]) : "r"(a), "n"(IMM) : "memory");
}
template <int IMM> __device__ __forceinline__ uint4 lds128_i(uint32_t a) {
  uint4 v; asm volatile("ld.shared.v4.u32 {%0,%1,%2,%3}, [%4+%5];" : "=r"(v.x), "=r"(v.y), "=r"(v.z), "=r"(v.w) : "r"(a), "n"(IMM) : "memory"); return v;
}
template <int IMM> __device__ __forceinline__ uint2 lds64_i(uint32_t a) {
  uint2 v; asm volatile("ld.shared.v2.u32 {%0,%1}, [%2+%3];" : "=r"(v.x), "=r"(v.y) : "r"(a), "n"(IMM) : "memory"); return v;
}
template <int IMM> __device__ __forceinline__ void sts128_i(uint32_t a, uint32_t x, uint32_t y, uint32_t z, uint32_t w) {
  asm volatile("st.shared.v4.u32 [%0+%5], {%1,%2,%3,%4};" :: "r"(a), "r"(x), "r"(y), "r"(z), "r"(w), "n"(IMM) : "memory");
}
template <int IMM> __device__ __forceinline__ void sts64_i(uint32_t a, uint32_t x, uint32_t y) {
  asm volatile("st.shared.v2.u32 [%0+%3], {%1,%2};" :: "r"(a), "r"(x), "r"(y), "n"(IMM) : "memory");
}
template <int IMM> __device__ __forceinline__ void st_async_v2_i(uint32_t a, uint32_t x, uint32_t y, uint32_t mb) {
  asm volatile("st.async.weak.shared::cluster.mbarrier::complete_tx::bytes.v2.b32 [%0+%4], {%1,%2}, [%3];"
               :: "r"(a), "r"(x), "r"(y), "r"(mb), "n"(IMM) : "memory");
}
template <int IMM> __device__ __forceinline__ uint4 ld_relaxed_v4_i(const void* p) {
  uint4 v; asm volatile("ld.relaxed.gpu.global.v4.u32 {%0,%1,%2,%3}, [%4+%5];" : "=r"(v.x), "=r"(v.y), "=r"(v.z), "=r"(v.w) : "l"(p), "n"(IMM) : "memory"); return v;
}
template <int I, int N, class F> __device__ __forceinline__ void static_for(F&& f) {
  if constexpr (I < N) { f(std::integral_constant<int, I>{}); static_for<I + 1, N>(f); }
}
__device__ __forceinline__ uint32_t movm_t(uint32_t a) {
  uint32_t d; asm volatile("movmatrix.sync.aligned.m8n8.trans.b16 %0, %1;" : "=r"(d) : "r"(a)); return d;
}
__device__ __forceinline__ void mma16816(float (&d)[4], uint32_t a0, uint32_t a1, uint32_t a2, uint32_t a3, uint32_t b0, uint32_t b1) {
  asm volatile("mma.sync.aligned.m16n8k16.row.col.f32.bf16.bf16.f32 {%0,%1,%2,%3}, {%4,%5,%6,%7}, {%8,%9}, {%0,%1,%2,%3};"
               : "+f"(d[0]), "+f"(d[1]), "+f"(d[2]), "+f"(d[3]) : "r"(a0), "r"(a1), "r"(a2), "r"(a3), "r"(b0), "r"(b1));
}
__device__ __forceinline__ uint32_t pack_bf16(float lo, float hi) {
  uint32_t d; asm("cvt.rn.bf16x2.f32 %0, %1, %2;" : "=r"(d) : "f"(hi), "f"(lo)); return d;
}
__device__ __forceinline__ float bf_lo(uint32_t w) { return __uint_as_float(w << 16); }
__device__ __forceinline__ float bf_hi(uint32_t w) { return __uint_as_float(w & 0xffff0000u); }
__device__ __forceinline__ uint4 lds128(uint32_t a) {
  uint4 v; asm volatile("ld.shared.v4.u32 {%0,%1,%2,%3}, [%4];" : "=r"(v.x), "=r"(v.y), "=r"(v.z), "=r"(v.w) : "r"(a) : "memory"); return v;
}
__device__ __forceinline__ uint2 lds64(uint32_t a) {
  uint2 v; asm volatile("ld.shared.v2.u32 {%0,%1}, [%2];" : "=r"(v.x), "=r"(v.y) : "r"(a) : "memory"); return v;
}
__device__ __forceinline__ void sts128(uint32_t a, uint32_t x, uint32_t y, uint32_t z, uint32_t w) {
  asm volatile("st.shared.v4.u32 [%0], {%1,%2,%3,%4};" :: "r"(a), "r"(x), "r"(y), "r"(z), "r"(w) : "memory");
}
__device__ __forceinline__ void sts64(uint32_t a, uint32_t x, uint32_t y) {
  asm volatile("st.shared.v2.u32 [%0], {%1,%2};" :: "r"(a), "r"(x), "r"(y) : "memory");
}
__device__ __forceinline__ uint4 ld_relaxed_v4(const void* p) {
  uint4 v; asm volatile("ld.relaxed.gpu.global.v4.u32 {%0,%1,%2,%3}, [%4];" : "=r"(v.x), "=r"(v.y), "=r"(v.z), "=r"(v.w) : "l"(p) : "memory"); return v;
}
__device__ __forceinline__ uint32_t ld_relaxed_u32(const void* p) {
  uint32_t v; asm volatile("ld.relaxed.gpu.global.u32 %0, [%1];" : "=r"(v) : "l"(p) : "memory"); return v;
}
__device__ __forceinline__ void st_relaxed_v2(void* p, uint32_t a, uint32_t b) {
  asm volatile("st.relaxed.gpu.global.v2.u32 [%0], {%1,%2};" :: "l"(p), "r"(a), "r"(b) : "memory");
}
__device__ __forceinline__ void st_relaxed_u32(void* p, uint32_t v) {
  asm volatile("st.relaxed.gpu.global.u32 [%0], %1;" :: "l"(p), "r"(v) : "memory");
}
__device__ __forceinline__ void st_release_u32(void* p, uint32_t v) {
  asm volatile("st.release.gpu.global.u32 [%0], %1;" :: "l"(p), "r"(v) : "memory");
}
__device__ __forceinline__ void red_release_inc(void* p) { asm volatile("red.release.gpu.global.add.u32 [%0], 1;" :: "l"(p) : "memory"); }
__device__ __forceinline__ uint32_t clk32() { uint32_t c; asm volatile("mov.u32 %0, %%clock;" : "=r"(c) :: "memory"); return c; }
__device__ __forceinline__ uint32_t clkdep(uint32_t v) {
  uint32_t c; asm volatile("{.reg .pred p; setp.eq.u32 p, %1, 0xdeadbeef; @p trap; mov.u32 %0, %%clock;}" : "=r"(c) : "r"(v) : "memory"); return c;
}
__device__ __forceinline__ void wgmma_fence() { asm volatile("wgmma.fence.sync.aligned;" ::: "memory"); }
__device__ __forceinline__ void wgmma_commit() { asm volatile("wgmma.commit_group.sync.aligned;" ::: "memory"); }
template <int N> __device__ __forceinline__ void wgmma_wait() { asm volatile("wgmma.wait_group.sync.aligned %0;" :: "n"(N) : "memory"); }
__device__ __forceinline__ void wgmma_n8_ss_ta(float (&d)[4], uint64_t da, uint64_t db, int acc) {
  asm volatile("{\n.reg .pred p;\nsetp.ne.b32 p, %6, 0;\n"
               "wgmma.mma_async.sync.aligned.m64n8k16.f32.bf16.bf16 {%0,%1,%2,%3}, %4, %5, p, 1, 1, 1, 0;\n}\n"
               : "+f"(d[0]), "+f"(d[1]), "+f"(d[2]), "+f"(d[3]) : "l"(da), "l"(db), "r"(acc));
}
__device__ __forceinline__ uint64_t make_desc(uint32_t saddr, uint32_t lbo_bytes, uint32_t sbo_bytes, uint32_t swz) {
  return (uint64_t)((saddr & 0x3FFFF) >> 4) | ((uint64_t)(lbo_bytes >> 4) << 16) | ((uint64_t)(sbo_bytes >> 4) << 32) | ((uint64_t)swz << 62);
}


__device__ __forceinline__ bool elect_one() {
  uint32_t p; asm volatile("{\n.reg .pred p;\nelect.sync _|p, 0xffffffff;\nselp.u32 %0, 1, 0, p;\n}" : "=r"(p)); return p;
}
__device__ __forceinline__ void tma_load_3d(uint32_t dst, const CUtensorMap* tm, int c0, int c1, int c2, uint32_t mb) {
  asm volatile("cp.async.bulk.tensor.3d.shared::cluster.global.mbarrier::complete_tx::bytes [%0], [%1, {%3, %4, %5}], [%2];"
               :: "r"(dst), "l"(tm), "r"(mb), "r"(c0), "r"(c1), "r"(c2) : "memory");
}
__device__ __forceinline__ void tma_load_2d(uint32_t dst, const CUtensorMap* tm, int c0, int c1, uint32_t mb) {
  asm volatile("cp.async.bulk.tensor.2d.shared::cluster.global.mbarrier::complete_tx::bytes [%0], [%1, {%3, %4}], [%2];"
               :: "r"(dst), "l"(tm), "r"(mb), "r"(c0), "r"(c1) : "memory");
}
__device__ __forceinline__ void bulk_s2g(void* dst, uint32_t src, uint32_t bytes) {
  asm volatile("cp.async.bulk.global.shared::cta.bulk_group [%0], [%1], %2;" :: "l"(dst), "r"(src), "r"(bytes) : "memory");
}
__device__ __forceinline__ uint64_t policy_evict_first() {
  uint64_t p; asm volatile("createpolicy.fractional.L2::evict_first.b64 %0, 1.0;" : "=l"(p)); return p;
}
__device__ __forceinline__ void bulk_s2g_hint(void* dst, uint32_t src, uint32_t bytes, uint64_t pol) {
  asm volatile("cp.async.bulk.global.shared::cta.bulk_group.L2::cache_hint [%0], [%1], %2, %3;" :: "l"(dst), "r"(src), "r"(bytes), "l"(pol) : "memory");
}
__device__ __forceinline__ void bulk_commit() { asm volatile("cp.async.bulk.commit_group;" ::: "memory"); }
template <int N> __device__ __forceinline__ void bulk_wait_read() { asm volatile("cp.async.bulk.wait_group.read %0;" :: "n"(N) : "memory"); }
template <int N> __device__ __forceinline__ void bulk_wait() { asm volatile("cp.async.bulk.wait_group %0;" :: "n"(N) : "memory"); }
__device__ __forceinline__ void stsm_x4(uint32_t a, uint32_t r0, uint32_t r1, uint32_t r2, uint32_t r3) {
  asm volatile("stmatrix.sync.aligned.m8n8.x4.shared.b16 [%0], {%1,%2,%3,%4};" :: "r"(a), "r"(r0), "r"(r1), "r"(r2), "r"(r3) : "memory");
}
__device__ __forceinline__ void stsm_x2(uint32_t a, uint32_t r0, uint32_t r1) {
  asm volatile("stmatrix.sync.aligned.m8n8.x2.shared.b16 [%0], {%1,%2};" :: "r"(a), "r"(r0), "r"(r1) : "memory");
}
__device__ __forceinline__ void ldsm_x2(uint32_t (&r)[2], uint32_t a) {
  asm volatile("ldmatrix.sync.aligned.m8n8.x2.shared.b16 {%0,%1}, [%2];" : "=r"(r[0]), "=r"(r[1]) : "r"(a) : "memory");
}
__device__ __forceinline__ void ldsm_x2_t(uint32_t (&r)[2], uint32_t a) {
  asm volatile("ldmatrix.sync.aligned.m8n8.x2.trans.shared.b16 {%0,%1}, [%2];" : "=r"(r[0]), "=r"(r[1]) : "r"(a) : "memory");
}
__device__ __forceinline__ float bf16r(float x) { return __uint_as_float(pack_bf16(0.f, x) & 0xffff0000u); }
__device__ __forceinline__ void bf16r2(float& a, float& b) { const uint32_t w = pack_bf16(a, b); a = bf_lo(w); b = bf_hi(w); }
__device__ __forceinline__ float rcpf(float x) { float r; asm("rcp.approx.ftz.f32 %0, %1;" : "=f"(r) : "f"(x)); return r; }
__device__ __forceinline__ float ex2f(float x) { float e; asm("ex2.approx.ftz.f32 %0, %1;" : "=f"(e) : "f"(x)); return e; }
__device__ __forceinline__ void prefetch_tmap(const CUtensorMap* tm) { asm volatile("prefetch.tensormap [%0];" :: "l"(tm) : "memory"); }

#ifdef TIMELINE
__device__ unsigned long long g_tl[2 * 64];
__device__ unsigned long long g_log[2 * 132 * 64 * 2 + 2];
__device__ unsigned long long g_tl2[4 * 64];
__device__ __forceinline__ unsigned long long gtime() { unsigned long long t; asm volatile("mov.u64 %0, %%globaltimer;" : "=l"(t)); return t; }
#define TL_BEGIN(id) do { if (threadIdx.x == 0) atomicMin(&g_tl[2 * (id)], gtime()); } while (0)
#define TL_END(id) do { if ((threadIdx.x & 31) == 0) atomicMax(&g_tl[2 * (id) + 1], gtime()); } while (0)
#define TL_ACC(idx, t0) do { if (threadIdx.x == 0 && m >= 4 && m < 11) { atomicAdd(&g_tl2[idx], gtime() - (t0)); atomicAdd(&g_tl2[(idx) + 1], 1ull); } } while (0)
#define TL_NOW() gtime()
#define TL2(idx) asm volatile("{\n.reg .pred p;\nsetp.eq.u32 p, %2, 0;\n@p red.relaxed.gpu.global.max.u64 [%0], %1;\n}" :: "l"(&g_tl2[idx]), "l"(gtime()), "r"(threadIdx.x) : "memory")
#define TLW(idx) asm volatile("{\n.reg .pred p;\nsetp.eq.u32 p, %2, 0;\n@p red.relaxed.gpu.global.max.u64 [%0], %1;\n@p red.relaxed.gpu.global.add.u64 [%0+128], %1;\n}" :: "l"(&g_tl2[idx]), "l"(gtime() - g_tl0), "r"(threadIdx.x & 31) : "memory")
#define TL_BEGIN0(id) atomicMin(&g_tl[2 * (id)], gtime())
#else
#define TL_ACC(idx, t0)
#define TL_NOW() 0ull
#define TL2(idx)
#define TL_BEGIN0(id)
#define TLW(idx)
#define TL_BEGIN(id)
#define TL_END(id)
#endif
template <int TA, int TB> __device__ __forceinline__ void wgmma_n24(float (&d)[12], uint64_t da, uint64_t db, int acc) {
  asm volatile("{\n.reg .pred p;\nsetp.ne.b32 p, %14, 0;\n"
    "wgmma.mma_async.sync.aligned.m64n24k16.f32.bf16.bf16 {%0, %1, %2, %3, %4, %5, %6, %7, %8, %9, %10, %11}, %12, %13, p, 1, 1, %15, %16;\n}\n"
    : "+f"(d[0]), "+f"(d[1]), "+f"(d[2]), "+f"(d[3]), "+f"(d[4]), "+f"(d[5]), "+f"(d[6]), "+f"(d[7]), "+f"(d[8]), "+f"(d[9]), "+f"(d[10]), "+f"(d[11])
    : "l"(da), "l"(db), "r"(acc), "n"(TA), "n"(TB));
}

template <int TA, int TB> __device__ __forceinline__ void wgmma_n80(float (&d)[40], uint64_t da, uint64_t db, int acc) {
  asm volatile("{\n.reg .pred p;\nsetp.ne.b32 p, %42, 0;\n"
    "wgmma.mma_async.sync.aligned.m64n80k16.f32.bf16.bf16 {%0, %1, %2, %3, %4, %5, %6, %7, %8, %9, %10, %11, %12, %13, %14, %15, %16, %17, %18, %19, %20, %21, %22, %23, %24, %25, %26, %27, %28, %29, %30, %31, %32, %33, %34, %35, %36, %37, %38, %39}, %40, %41, p, 1, 1, %43, %44;\n}\n"
    : "+f"(d[0]), "+f"(d[1]), "+f"(d[2]), "+f"(d[3]), "+f"(d[4]), "+f"(d[5]), "+f"(d[6]), "+f"(d[7]), "+f"(d[8]), "+f"(d[9]), "+f"(d[10]), "+f"(d[11]), "+f"(d[12]), "+f"(d[13]), "+f"(d[14]), "+f"(d[15]), "+f"(d[16]), "+f"(d[17]), "+f"(d[18]), "+f"(d[19]), "+f"(d[20]), "+f"(d[21]), "+f"(d[22]), "+f"(d[23]), "+f"(d[24]), "+f"(d[25]), "+f"(d[26]), "+f"(d[27]), "+f"(d[28]), "+f"(d[29]), "+f"(d[30]), "+f"(d[31]), "+f"(d[32]), "+f"(d[33]), "+f"(d[34]), "+f"(d[35]), "+f"(d[36]), "+f"(d[37]), "+f"(d[38]), "+f"(d[39])
    : "l"(da), "l"(db), "r"(acc), "n"(TA), "n"(TB));
}

template <int TA, int TB> __device__ __forceinline__ void wgmma_n128(float (&d)[64], uint64_t da, uint64_t db, int acc) {
  asm volatile("{\n.reg .pred p;\nsetp.ne.b32 p, %66, 0;\n"
    "wgmma.mma_async.sync.aligned.m64n128k16.f32.bf16.bf16 {%0, %1, %2, %3, %4, %5, %6, %7, %8, %9, %10, %11, %12, %13, %14, %15, %16, %17, %18, %19, %20, %21, %22, %23, %24, %25, %26, %27, %28, %29, %30, %31, %32, %33, %34, %35, %36, %37, %38, %39, %40, %41, %42, %43, %44, %45, %46, %47, %48, %49, %50, %51, %52, %53, %54, %55, %56, %57, %58, %59, %60, %61, %62, %63}, %64, %65, p, 1, 1, %67, %68;\n}\n"
    : "+f"(d[0]), "+f"(d[1]), "+f"(d[2]), "+f"(d[3]), "+f"(d[4]), "+f"(d[5]), "+f"(d[6]), "+f"(d[7]), "+f"(d[8]), "+f"(d[9]), "+f"(d[10]), "+f"(d[11]), "+f"(d[12]), "+f"(d[13]), "+f"(d[14]), "+f"(d[15]), "+f"(d[16]), "+f"(d[17]), "+f"(d[18]), "+f"(d[19]), "+f"(d[20]), "+f"(d[21]), "+f"(d[22]), "+f"(d[23]), "+f"(d[24]), "+f"(d[25]), "+f"(d[26]), "+f"(d[27]), "+f"(d[28]), "+f"(d[29]), "+f"(d[30]), "+f"(d[31]), "+f"(d[32]), "+f"(d[33]), "+f"(d[34]), "+f"(d[35]), "+f"(d[36]), "+f"(d[37]), "+f"(d[38]), "+f"(d[39]), "+f"(d[40]), "+f"(d[41]), "+f"(d[42]), "+f"(d[43]), "+f"(d[44]), "+f"(d[45]), "+f"(d[46]), "+f"(d[47]), "+f"(d[48]), "+f"(d[49]), "+f"(d[50]), "+f"(d[51]), "+f"(d[52]), "+f"(d[53]), "+f"(d[54]), "+f"(d[55]), "+f"(d[56]), "+f"(d[57]), "+f"(d[58]), "+f"(d[59]), "+f"(d[60]), "+f"(d[61]), "+f"(d[62]), "+f"(d[63])
    : "l"(da), "l"(db), "r"(acc), "n"(TA), "n"(TB));
}

template <int TA, int TB> __device__ __forceinline__ void wgmma_n192(float (&d)[96], uint64_t da, uint64_t db, int acc) {
  asm volatile("{\n.reg .pred p;\nsetp.ne.b32 p, %98, 0;\n"
    "wgmma.mma_async.sync.aligned.m64n192k16.f32.bf16.bf16 {%0, %1, %2, %3, %4, %5, %6, %7, %8, %9, %10, %11, %12, %13, %14, %15, %16, %17, %18, %19, %20, %21, %22, %23, %24, %25, %26, %27, %28, %29, %30, %31, %32, %33, %34, %35, %36, %37, %38, %39, %40, %41, %42, %43, %44, %45, %46, %47, %48, %49, %50, %51, %52, %53, %54, %55, %56, %57, %58, %59, %60, %61, %62, %63, %64, %65, %66, %67, %68, %69, %70, %71, %72, %73, %74, %75, %76, %77, %78, %79, %80, %81, %82, %83, %84, %85, %86, %87, %88, %89, %90, %91, %92, %93, %94, %95}, %96, %97, p, 1, 1, %99, %100;\n}\n"
    : "+f"(d[0]), "+f"(d[1]), "+f"(d[2]), "+f"(d[3]), "+f"(d[4]), "+f"(d[5]), "+f"(d[6]), "+f"(d[7]), "+f"(d[8]), "+f"(d[9]), "+f"(d[10]), "+f"(d[11]), "+f"(d[12]), "+f"(d[13]), "+f"(d[14]), "+f"(d[15]), "+f"(d[16]), "+f"(d[17]), "+f"(d[18]), "+f"(d[19]), "+f"(d[20]), "+f"(d[21]), "+f"(d[22]), "+f"(d[23]), "+f"(d[24]), "+f"(d[25]), "+f"(d[26]), "+f"(d[27]), "+f"(d[28]), "+f"(d[29]), "+f"(d[30]), "+f"(d[31]), "+f"(d[32]), "+f"(d[33]), "+f"(d[34]), "+f"(d[35]), "+f"(d[36]), "+f"(d[37]), "+f"(d[38]), "+f"(d[39]), "+f"(d[40]), "+f"(d[41]), "+f"(d[42]), "+f"(d[43]), "+f"(d[44]), "+f"(d[45]), "+f"(d[46]), "+f"(d[47]), "+f"(d[48]), "+f"(d[49]), "+f"(d[50]), "+f"(d[51]), "+f"(d[52]), "+f"(d[53]), "+f"(d[54]), "+f"(d[55]), "+f"(d[56]), "+f"(d[57]), "+f"(d[58]), "+f"(d[59]), "+f"(d[60]), "+f"(d[61]), "+f"(d[62]), "+f"(d[63]), "+f"(d[64]), "+f"(d[65]), "+f"(d[66]), "+f"(d[67]), "+f"(d[68]), "+f"(d[69]), "+f"(d[70]), "+f"(d[71]), "+f"(d[72]), "+f"(d[73]), "+f"(d[74]), "+f"(d[75]), "+f"(d[76]), "+f"(d[77]), "+f"(d[78]), "+f"(d[79]), "+f"(d[80]), "+f"(d[81]), "+f"(d[82]), "+f"(d[83]), "+f"(d[84]), "+f"(d[85]), "+f"(d[86]), "+f"(d[87]), "+f"(d[88]), "+f"(d[89]), "+f"(d[90]), "+f"(d[91]), "+f"(d[92]), "+f"(d[93]), "+f"(d[94]), "+f"(d[95])
    : "l"(da), "l"(db), "r"(acc), "n"(TA), "n"(TB));
}

template <int TA, int TB> __device__ __forceinline__ void wgmma_n256(float (&d)[128], uint64_t da, uint64_t db, int acc) {
  asm volatile("{\n.reg .pred p;\nsetp.ne.b32 p, %130, 0;\n"
    "wgmma.mma_async.sync.aligned.m64n256k16.f32.bf16.bf16 {%0, %1, %2, %3, %4, %5, %6, %7, %8, %9, %10, %11, %12, %13, %14, %15, %16, %17, %18, %19, %20, %21, %22, %23, %24, %25, %26, %27, %28, %29, %30, %31, %32, %33, %34, %35, %36, %37, %38, %39, %40, %41, %42, %43, %44, %45, %46, %47, %48, %49, %50, %51, %52, %53, %54, %55, %56, %57, %58, %59, %60, %61, %62, %63, %64, %65, %66, %67, %68, %69, %70, %71, %72, %73, %74, %75, %76, %77, %78, %79, %80, %81, %82, %83, %84, %85, %86, %87, %88, %89, %90, %91, %92, %93, %94, %95, %96, %97, %98, %99, %100, %101, %102, %103, %104, %105, %106, %107, %108, %109, %110, %111, %112, %113, %114, %115, %116, %117, %118, %119, %120, %121, %122, %123, %124, %125, %126, %127}, %128, %129, p, 1, 1, %131, %132;\n}\n"
    : "+f"(d[0]), "+f"(d[1]), "+f"(d[2]), "+f"(d[3]), "+f"(d[4]), "+f"(d[5]), "+f"(d[6]), "+f"(d[7]), "+f"(d[8]), "+f"(d[9]), "+f"(d[10]), "+f"(d[11]), "+f"(d[12]), "+f"(d[13]), "+f"(d[14]), "+f"(d[15]), "+f"(d[16]), "+f"(d[17]), "+f"(d[18]), "+f"(d[19]), "+f"(d[20]), "+f"(d[21]), "+f"(d[22]), "+f"(d[23]), "+f"(d[24]), "+f"(d[25]), "+f"(d[26]), "+f"(d[27]), "+f"(d[28]), "+f"(d[29]), "+f"(d[30]), "+f"(d[31]), "+f"(d[32]), "+f"(d[33]), "+f"(d[34]), "+f"(d[35]), "+f"(d[36]), "+f"(d[37]), "+f"(d[38]), "+f"(d[39]), "+f"(d[40]), "+f"(d[41]), "+f"(d[42]), "+f"(d[43]), "+f"(d[44]), "+f"(d[45]), "+f"(d[46]), "+f"(d[47]), "+f"(d[48]), "+f"(d[49]), "+f"(d[50]), "+f"(d[51]), "+f"(d[52]), "+f"(d[53]), "+f"(d[54]), "+f"(d[55]), "+f"(d[56]), "+f"(d[57]), "+f"(d[58]), "+f"(d[59]), "+f"(d[60]), "+f"(d[61]), "+f"(d[62]), "+f"(d[63]), "+f"(d[64]), "+f"(d[65]), "+f"(d[66]), "+f"(d[67]), "+f"(d[68]), "+f"(d[69]), "+f"(d[70]), "+f"(d[71]), "+f"(d[72]), "+f"(d[73]), "+f"(d[74]), "+f"(d[75]), "+f"(d[76]), "+f"(d[77]), "+f"(d[78]), "+f"(d[79]), "+f"(d[80]), "+f"(d[81]), "+f"(d[82]), "+f"(d[83]), "+f"(d[84]), "+f"(d[85]), "+f"(d[86]), "+f"(d[87]), "+f"(d[88]), "+f"(d[89]), "+f"(d[90]), "+f"(d[91]), "+f"(d[92]), "+f"(d[93]), "+f"(d[94]), "+f"(d[95]), "+f"(d[96]), "+f"(d[97]), "+f"(d[98]), "+f"(d[99]), "+f"(d[100]), "+f"(d[101]), "+f"(d[102]), "+f"(d[103]), "+f"(d[104]), "+f"(d[105]), "+f"(d[106]), "+f"(d[107]), "+f"(d[108]), "+f"(d[109]), "+f"(d[110]), "+f"(d[111]), "+f"(d[112]), "+f"(d[113]), "+f"(d[114]), "+f"(d[115]), "+f"(d[116]), "+f"(d[117]), "+f"(d[118]), "+f"(d[119]), "+f"(d[120]), "+f"(d[121]), "+f"(d[122]), "+f"(d[123]), "+f"(d[124]), "+f"(d[125]), "+f"(d[126]), "+f"(d[127])
    : "l"(da), "l"(db), "r"(acc), "n"(TA), "n"(TB));
}

template <int TB> __device__ __forceinline__ void wgmma_rs_n24(float (&d)[12], uint32_t a0, uint32_t a1, uint32_t a2, uint32_t a3, uint64_t db, int acc) {
  asm volatile("{\n.reg .pred p;\nsetp.ne.b32 p, %17, 0;\n"
    "wgmma.mma_async.sync.aligned.m64n24k16.f32.bf16.bf16 {%0, %1, %2, %3, %4, %5, %6, %7, %8, %9, %10, %11}, {%12, %13, %14, %15}, %16, p, 1, 1, %18;\n}\n"
    : "+f"(d[0]), "+f"(d[1]), "+f"(d[2]), "+f"(d[3]), "+f"(d[4]), "+f"(d[5]), "+f"(d[6]), "+f"(d[7]), "+f"(d[8]), "+f"(d[9]), "+f"(d[10]), "+f"(d[11])
    : "r"(a0), "r"(a1), "r"(a2), "r"(a3), "l"(db), "r"(acc), "n"(TB));
}

template <int TB> __device__ __forceinline__ void wgmma_rs_n40(float (&d)[20], uint32_t a0, uint32_t a1, uint32_t a2, uint32_t a3, uint64_t db, int acc) {
  asm volatile("{\n.reg .pred p;\nsetp.ne.b32 p, %25, 0;\n"
    "wgmma.mma_async.sync.aligned.m64n40k16.f32.bf16.bf16 {%0, %1, %2, %3, %4, %5, %6, %7, %8, %9, %10, %11, %12, %13, %14, %15, %16, %17, %18, %19}, {%20, %21, %22, %23}, %24, p, 1, 1, %26;\n}\n"
    : "+f"(d[0]), "+f"(d[1]), "+f"(d[2]), "+f"(d[3]), "+f"(d[4]), "+f"(d[5]), "+f"(d[6]), "+f"(d[7]), "+f"(d[8]), "+f"(d[9]), "+f"(d[10]), "+f"(d[11]), "+f"(d[12]), "+f"(d[13]), "+f"(d[14]), "+f"(d[15]), "+f"(d[16]), "+f"(d[17]), "+f"(d[18]), "+f"(d[19])
    : "r"(a0), "r"(a1), "r"(a2), "r"(a3), "l"(db), "r"(acc), "n"(TB));
}

template <int TB> __device__ __forceinline__ void wgmma_rs_n192(float (&d)[96], uint32_t a0, uint32_t a1, uint32_t a2, uint32_t a3, uint64_t db, int acc) {
  asm volatile("{\n.reg .pred p;\nsetp.ne.b32 p, %101, 0;\n"
    "wgmma.mma_async.sync.aligned.m64n192k16.f32.bf16.bf16 {%0, %1, %2, %3, %4, %5, %6, %7, %8, %9, %10, %11, %12, %13, %14, %15, %16, %17, %18, %19, %20, %21, %22, %23, %24, %25, %26, %27, %28, %29, %30, %31, %32, %33, %34, %35, %36, %37, %38, %39, %40, %41, %42, %43, %44, %45, %46, %47, %48, %49, %50, %51, %52, %53, %54, %55, %56, %57, %58, %59, %60, %61, %62, %63, %64, %65, %66, %67, %68, %69, %70, %71, %72, %73, %74, %75, %76, %77, %78, %79, %80, %81, %82, %83, %84, %85, %86, %87, %88, %89, %90, %91, %92, %93, %94, %95}, {%96, %97, %98, %99}, %100, p, 1, 1, %102;\n}\n"
    : "+f"(d[0]), "+f"(d[1]), "+f"(d[2]), "+f"(d[3]), "+f"(d[4]), "+f"(d[5]), "+f"(d[6]), "+f"(d[7]), "+f"(d[8]), "+f"(d[9]), "+f"(d[10]), "+f"(d[11]), "+f"(d[12]), "+f"(d[13]), "+f"(d[14]), "+f"(d[15]), "+f"(d[16]), "+f"(d[17]), "+f"(d[18]), "+f"(d[19]), "+f"(d[20]), "+f"(d[21]), "+f"(d[22]), "+f"(d[23]), "+f"(d[24]), "+f"(d[25]), "+f"(d[26]), "+f"(d[27]), "+f"(d[28]), "+f"(d[29]), "+f"(d[30]), "+f"(d[31]), "+f"(d[32]), "+f"(d[33]), "+f"(d[34]), "+f"(d[35]), "+f"(d[36]), "+f"(d[37]), "+f"(d[38]), "+f"(d[39]), "+f"(d[40]), "+f"(d[41]), "+f"(d[42]), "+f"(d[43]), "+f"(d[44]), "+f"(d[45]), "+f"(d[46]), "+f"(d[47]), "+f"(d[48]), "+f"(d[49]), "+f"(d[50]), "+f"(d[51]), "+f"(d[52]), "+f"(d[53]), "+f"(d[54]), "+f"(d[55]), "+f"(d[56]), "+f"(d[57]), "+f"(d[58]), "+f"(d[59]), "+f"(d[60]), "+f"(d[61]), "+f"(d[62]), "+f"(d[63]), "+f"(d[64]), "+f"(d[65]), "+f"(d[66]), "+f"(d[67]), "+f"(d[68]), "+f"(d[69]), "+f"(d[70]), "+f"(d[71]), "+f"(d[72]), "+f"(d[73]), "+f"(d[74]), "+f"(d[75]), "+f"(d[76]), "+f"(d[77]), "+f"(d[78]), "+f"(d[79]), "+f"(d[80]), "+f"(d[81]), "+f"(d[82]), "+f"(d[83]), "+f"(d[84]), "+f"(d[85]), "+f"(d[86]), "+f"(d[87]), "+f"(d[88]), "+f"(d[89]), "+f"(d[90]), "+f"(d[91]), "+f"(d[92]), "+f"(d[93]), "+f"(d[94]), "+f"(d[95])
    : "r"(a0), "r"(a1), "r"(a2), "r"(a3), "l"(db), "r"(acc), "n"(TB));
}
constexpr uint32_t AR_ACC = 0;
constexpr uint32_t AR_TAB = 0x100000;
constexpr uint32_t AR_PROG = 0x101000;
__host__ __device__ constexpr uint32_t prog_off(int h, int j) { return AR_PROG + h * 128 + j * 4; }
constexpr uint32_t AR_CNT = 0x108000;
constexpr uint32_t AR_QUEUE = 0x109000;
constexpr uint32_t AR_SIZE = 0x10a000;

struct ChainArgs {
  const bf16* mem0;
  const uint2* xh;
  unsigned char *kg, *vg;
  unsigned char* arena;
  unsigned* go;
  uint32_t* dbg;
  uint32_t delay;
  int margin, pubrel;
  int tl;
};

namespace ch {
constexpr int OFF_WQ = 0;
constexpr int OFF_X = 81920;
constexpr int OFF_MEM = OFF_X + 40960;
constexpr int OFF_WO = OFF_MEM + 10240;
constexpr int WOK = 8 * 896;
constexpr int OFF_KV = OFF_WO + 10 * WOK;
constexpr int KVB = 5120;
constexpr int OFF_O = OFF_KV + 4 * KVB;
constexpr int OFF_Q = OFF_O + 1024;
constexpr int OFF_S = OFF_O + 3072;
constexpr int OFF_SR = OFF_S + 1536;
constexpr int OFF_LT = OFF_SR + 1280;
constexpr int OFF_BAR = OFF_LT + 512;
constexpr int SMEM = OFF_BAR + 256;
static_assert(SMEM <= 232448, "smem");
constexpr int MB_S = OFF_BAR, MB_O = OFF_BAR + 8, MB_X = OFF_BAR + 16;
constexpr int MB_K = OFF_BAR + 128, MB_V = MB_K + 16, MB_Q = MB_K + 32, MB_R = MB_K + 48;
constexpr int SC_IN = OFF_BAR + 64;
constexpr int SC_MX = OFF_S;
constexpr int SC_W = OFF_BAR + 96;
constexpr int WOS = 448;
enum { B_MEM0 = 1, B_QK, B_SL, B_V, B_O, B_RED, B_X, B_C, B_H, B_MEM1, B_A, B_G, B_E };
#ifndef NQ1
#define NQ1 6
#endif
#ifndef NQ0
#define NQ0 4
#endif
#ifndef NP0
#define NP0 4
#endif
#ifndef NWO
#define NWO 5
#endif
#ifndef NWP
#define NWP 4
#endif
#ifndef NB0
#define NB0 3
#endif
#ifndef BBS
#define BBS 100
#endif
#ifndef VSYNC
#define VSYNC 0
#endif
#ifndef XPOS
#define XPOS 0
#endif
#ifndef XPD
#define XPD 300
#endif
#ifndef WOF
#define WOF 0
#endif
#ifndef XBYTES
#define XBYTES 36864
#endif
#ifndef NRT
#define NRT 7
#endif
#ifndef NRF
#define NRF 2
#endif
#ifndef NPM0
#define NPM0 2
#endif
#ifndef NPM1
#define NPM1 2
#endif
#ifndef RSYNC
#define RSYNC 1
#endif
#ifndef PFK
#define PFK 1
#endif
#ifndef PA0
#define PA0 3
#endif
#ifndef PA1
#define PA1 0
#endif
#ifndef PB0
#define PB0 7
#endif
#ifndef PB1
#define PB1 5
#endif
#ifndef PQE
#define PQE 1
#endif
#ifndef XT
#define XT 30
#endif
static_assert(NPM0 >= 2 && NPM1 >= 2, "the K / V blocks live in the last two k-steps of Wo");
}

#ifndef CHAIN_TIMING
#define CHAIN_TIMING 0
#endif
#if CHAIN_TIMING
#ifndef TR0
#define TR0 41
#endif
#ifndef TSMASK
#define TSMASK 0xffff
#endif
#define TSV(i, v) do { if ((TSMASK >> (i)) & 1) asm volatile("st.shared.u32 [%0+%1], %2;" :: "r"(tsb), "n"((i) * 4), "r"(v) : "memory"); } while (0)
#define TS(i) TSV(i, clk32())
#define TS_SETUP() const uint32_t tsb = sb + ((s == TR0 || s == TR0 + 1) ? OFF_BAR + 128 + ((s - TR0) * 12 + warp) * 48 : OFF_SR + 1152)
#else
#define TS(i)
#define TSV(i, v)
#define TS_SETUP()
#endif
#ifndef POLL_DELAY
#define POLL_DELAY 590
#endif
#ifndef XN
#define XN 40
#endif
#ifndef PF0
#define PF0 8
#endif
#ifndef PFS
#define PFS 3
#endif
#ifndef XDELAY
#define XDELAY 0
#endif
#ifndef NOKM
#define NOKM 0
#endif
#ifndef PFX
#define PFX 3
#endif
#ifndef NVE
#define NVE 10
#endif
#ifndef VET
#define VET 19
#endif
#ifndef MEMFIRST
#define MEMFIRST 1
#endif
#ifndef GD0
#define GD0 -1
#endif
#ifndef PM1
#define PM1 1
#endif
#ifndef GD1
#define GD1 30
#endif
#ifndef GD2
#define GD2 150
#endif
#ifndef CEARLY
#define CEARLY 1
#endif
#ifndef PFACC
#define PFACC 1
#endif
template <int V> using IC = std::integral_constant<int, V>;
__device__ __forceinline__ uint32_t clk_v() { uint64_t c; asm volatile("mov.u64 %0, %%clock64;" : "=l"(c) :: "memory"); return (uint32_t)c; }
__device__ __forceinline__ int fresh(int x) { int y; asm volatile("shfl.sync.bfly.b32 %0, %1, 0, 0x1f, 0xffffffff;" : "=r"(y) : "r"(x)); return y; }
#define SFENCE2(x, d) asm volatile("{\n.reg .pred p;\nsetp.eq.u32 p, %0, 0x7fffffff;\n@p st.shared.u32 [%0], %1;\n}" :: "r"(x), "r"(d) : "memory")
#define SFENCE(x) asm volatile("{\n.reg .pred p;\nsetp.eq.u32 p, %0, 0x7fffffff;\n@p st.shared.u32 [%0], %0;\n}" :: "r"(x) : "memory")
template <int I> __device__ __forceinline__ void bbfence(uint32_t x) {
  asm volatile("{\n.reg .pred p;\nsetp.eq.u32 p, %0, %1;\nL_%=:\n@p st.volatile.shared.u32 [%0], %0;\n@p bra.uni L_%=;\n}" :: "r"(x), "n"(4 * I) : "memory");
}
__device__ __forceinline__ float uniform_f(float x) { return __uint_as_float(__reduce_max_sync(0xffffffffu, __float_as_uint(x))); }

__device__ __forceinline__ void mma16816h(float (&d)[4], const uint32_t (&a)[4], uint32_t b0, uint32_t b1) {
  asm volatile("mma.sync.aligned.m16n8k16.row.col.f32.f16.f16.f32 {%0,%1,%2,%3}, {%4,%5,%6,%7}, {%8,%9}, {%0,%1,%2,%3};"
               : "+f"(d[0]), "+f"(d[1]), "+f"(d[2]), "+f"(d[3]) : "r"(a[0]), "r"(a[1]), "r"(a[2]), "r"(a[3]), "r"(b0), "r"(b1));
}
__device__ __forceinline__ void mma1688(float (&d)[4], uint32_t a0, uint32_t a1, uint32_t b0) {
  asm volatile("mma.sync.aligned.m16n8k8.row.col.f32.bf16.bf16.f32 {%0,%1,%2,%3}, {%4,%5}, {%6}, {%0,%1,%2,%3};"
               : "+f"(d[0]), "+f"(d[1]), "+f"(d[2]), "+f"(d[3]) : "r"(a0), "r"(a1), "r"(b0));
}
template <int OFF16, int ACC> __device__ __forceinline__ void wgmma_rs32h(float (&d)[16], const uint32_t (&a)[4], uint32_t dlo) {
  asm volatile("{\n.reg .pred p;\n.reg .b32 t;\n.reg .b64 db;\nsetp.ne.b32 p, %22, 0;\nadd.u32 t, %20, %21;\nmov.b64 db, {t, 0x40000040};\n"
    "wgmma.mma_async.sync.aligned.m64n32k16.f32.f16.f16 {%0,%1,%2,%3,%4,%5,%6,%7,%8,%9,%10,%11,%12,%13,%14,%15}, {%16,%17,%18,%19}, db, p, 1, 1, 0;\n}\n"
    : "+f"(d[0]), "+f"(d[1]), "+f"(d[2]), "+f"(d[3]), "+f"(d[4]), "+f"(d[5]), "+f"(d[6]), "+f"(d[7]), "+f"(d[8]), "+f"(d[9]), "+f"(d[10]), "+f"(d[11]),
      "+f"(d[12]), "+f"(d[13]), "+f"(d[14]), "+f"(d[15])
    : "r"(a[0]), "r"(a[1]), "r"(a[2]), "r"(a[3]), "r"(dlo), "n"(OFF16), "n"(ACC));
}
template <int IMM> __device__ __forceinline__ void stsm_x4_t_i(uint32_t a, uint32_t r0, uint32_t r1, uint32_t r2, uint32_t r3) {
  asm volatile("stmatrix.sync.aligned.m8n8.x4.trans.shared.b16 [%0+%5], {%1,%2,%3,%4};" :: "r"(a), "r"(r0), "r"(r1), "r"(r2), "r"(r3), "n"(IMM) : "memory");
}
template <int IMM> __device__ __forceinline__ void stsm_x2_t_i(uint32_t a, uint32_t r0, uint32_t r1) {
  asm volatile("stmatrix.sync.aligned.m8n8.x2.trans.shared.b16 [%0+%3], {%1,%2};" :: "r"(a), "r"(r0), "r"(r1), "n"(IMM) : "memory");
}
template <int IMM> __device__ __forceinline__ void st_async_b32_i(uint32_t a, uint32_t x, uint32_t mb) {
  asm volatile("st.async.weak.shared::cluster.mbarrier::complete_tx::bytes.b32 [%0+%3], %1, [%2];" :: "r"(a), "r"(x), "r"(mb), "n"(IMM) : "memory");
}
template <int IMM> __device__ __forceinline__ void ld_relaxed_v4_if(uint4& v, const void* p, uint32_t c) {
  asm volatile("{\n.reg .pred p;\nsetp.ne.u32 p, %6, 0;\n@p ld.relaxed.gpu.global.v4.u32 {%0,%1,%2,%3}, [%4+%5];\n}"
               : "+r"(v.x), "+r"(v.y), "+r"(v.z), "+r"(v.w) : "l"(p), "n"(IMM), "r"(c) : "memory");
}
template <int IMM> __device__ __forceinline__ void ldsm_x2_i(uint32_t (&r)[2], uint32_t a) {
  asm volatile("ldmatrix.sync.aligned.m8n8.x2.shared.b16 {%0,%1}, [%2+%3];" : "=r"(r[0]), "=r"(r[1]) : "r"(a), "n"(IMM) : "memory");
}
template <int IMM> __device__ __forceinline__ uint32_t ldsm_x1_t_i(uint32_t a) {
  uint32_t r; asm volatile("ldmatrix.sync.aligned.m8n8.x1.trans.shared.b16 {%0}, [%1+%2];" : "=r"(r) : "r"(a), "n"(IMM) : "memory"); return r;
}
template <int IMM> __device__ __forceinline__ uint32_t lds32_i(uint32_t a) {
  uint32_t v; asm volatile("ld.shared.u32 %0, [%1+%2];" : "=r"(v) : "r"(a), "n"(IMM) : "memory"); return v;
}
__device__ __forceinline__ void sts32(uint32_t a, uint32_t v) { asm volatile("st.shared.u32 [%0], %1;" :: "r"(a), "r"(v) : "memory"); }
__device__ __forceinline__ uint32_t pack_f16(float lo, float hi) {
  uint32_t d; asm("cvt.rn.f16x2.f32 %0, %1, %2;" : "=r"(d) : "f"(hi), "f"(lo)); return d;
}
__device__ __forceinline__ uint32_t amax_bf2(uint32_t a, uint32_t b) { uint32_t d; asm("max.xorsign.abs.bf16x2 %0, %1, %2;" : "=r"(d) : "r"(a), "r"(b)); return d; }
__device__ __forceinline__ uint32_t amax_h2(uint32_t a, uint32_t b) { uint32_t d; asm("max.xorsign.abs.f16x2 %0, %1, %2;" : "=r"(d) : "r"(a), "r"(b)); return d; }
__device__ __forceinline__ uint32_t amax_fold(uint32_t m) { return __reduce_max_sync(0xffffffffu, max(m & 0x7fffu, (m >> 16) & 0x7fffu)); }
__device__ __forceinline__ int wscale_exp(uint32_t m) { return min(141 - (int)(m >> 7), 100); }
__device__ __forceinline__ float exp2i(int e) { return __uint_as_float((uint32_t)(e + 127) << 23); }
__device__ __forceinline__ uint32_t bf2_to_h2(uint32_t w, float sc) { return pack_f16(bf_lo(w) * sc, bf_hi(w) * sc); }
__device__ __forceinline__ void bf2_to_h2_inplace(uint32_t& w, uint32_t sc2) {
  asm volatile("{\n.reg .b32 t, lo, hi;\nmul.rn.bf16x2 t, %0, %1;\nshl.b32 lo, t, 16;\nand.b32 hi, t, 0xffff0000;\ncvt.rn.f16x2.f32 %0, hi, lo;\n}" : "+r"(w) : "r"(sc2));
}
__device__ __forceinline__ void prefetch_l2(const void* p, uint32_t bytes) { asm volatile("cp.async.bulk.prefetch.L2.global [%0], %1;" :: "l"(p), "r"(bytes) : "memory"); }
__device__ __forceinline__ void prefetch_tma_2d(const CUtensorMap* tm, int c0, int c1) {
  asm volatile("cp.async.bulk.prefetch.tensor.2d.L2.global [%0, {%1, %2}];" :: "l"(tm), "r"(c0), "r"(c1) : "memory");
}
__host__ __device__ constexpr uint32_t acc_voff(int v) { return v < 4 ? v * 1024u : (v == 4 ? 128u : 3072u + 128u); }
__device__ __forceinline__ int unit28(int i) { return i == 3 ? 54 : 14 * i; }
__device__ __forceinline__ int unit24(int i) { return i < 2 ? 48 - 6 * i : 56 + 6 * i; }
__device__ __forceinline__ uint32_t acc_step(int s) { return (s >> 1) * 32768 + (s & 1) * 512; }
__device__ __forceinline__ uint32_t acc_lane(int i, int lane) { return ((lane >> 3) & 1) * 256 + (lane >> 4) * 4096 + i * 8192 + (lane & 7) * 16; }

__device__ __forceinline__ uint32_t ld_acquire_u32(const void* p) {
  uint32_t v; asm volatile("ld.acquire.gpu.global.u32 %0, [%1];" : "=r"(v) : "l"(p) : "memory"); return v;
}
template <int R> __device__ __forceinline__ void ln_rows(const uint2 (&xw)[R][5], int row0, int lane, bf16* __restrict__ xn, uint2* __restrict__ xh) {
  float v[R][20], s[R], q[R];
#pragma unroll
  for (int r = 0; r < R; r++) {
    s[r] = 0.f; q[r] = 0.f;
#pragma unroll
    for (int i = 0; i < 5; i++) { v[r][4 * i] = bf_lo(xw[r][i].x); v[r][4 * i + 1] = bf_hi(xw[r][i].x); v[r][4 * i + 2] = bf_lo(xw[r][i].y); v[r][4 * i + 3] = bf_hi(xw[r][i].y); }
#pragma unroll
    for (int i = 0; i < 5; i++) s[r] += (v[r][4 * i] + v[r][4 * i + 1]) + (v[r][4 * i + 2] + v[r][4 * i + 3]);
  }
#pragma unroll
  for (int o = 16; o; o >>= 1)
#pragma unroll
    for (int r = 0; r < R; r++) s[r] += __shfl_xor_sync(0xffffffffu, s[r], o);
#pragma unroll
  for (int r = 0; r < R; r++) {
    s[r] *= 1.f / cfg::DM;
#pragma unroll
    for (int i = 0; i < 10; i++) { const float d = v[r][2 * i] - s[r], e = v[r][2 * i + 1] - s[r]; q[r] += d * d + e * e; }
  }
#pragma unroll
  for (int o = 16; o; o >>= 1)
#pragma unroll
    for (int r = 0; r < R; r++) q[r] += __shfl_xor_sync(0xffffffffu, q[r], o);
#pragma unroll
  for (int r = 0; r < R; r++) {
    const int row = row0 + r;
    const float mb = bf16r(s[r]), var = bf16r(q[r] * (1.f / cfg::DM));
    float sd; asm("sqrt.approx.f32 %0, %1;" : "=f"(sd) : "f"(bf16r(var + 1e-5f)));
    const float inv = rcpf(bf16r(sd));
#pragma unroll
    for (int i = 0; i < 5; i++) {
      float y[4];
#pragma unroll
      for (int e = 0; e < 4; e++) y[e] = v[r][4 * i + e] - mb;
      bf16r2(y[0], y[1]); bf16r2(y[2], y[3]);
      const uint32_t w0 = pack_bf16(y[0] * inv, y[1] * inv), w1 = pack_bf16(y[2] * inv, y[3] * inv);
      *(uint2*)(xn + (size_t)row * cfg::DM + i * 128 + lane * 4) = make_uint2(w0, w1);
      if (xh) xh[(((size_t)(row >> 5) * 10 + 2 * i + (lane >> 4)) * 32 + (row & 31)) * 16 + ((((lane >> 1) & 7) ^ (row & 7)) << 1) + (lane & 1)] =
          make_uint2(pack_f16(bf_lo(w0), bf_hi(w0)), pack_f16(bf_lo(w1), bf_hi(w1)));
    }
  }
}

__global__ void __cluster_dims__(3, 1, 1) __launch_bounds__(384, 1) chain_kernel(const ChainArgs a, const __grid_constant__ CUtensorMap tmWq,
    const __grid_constant__ CUtensorMap tmWk, const __grid_constant__ CUtensorMap tmWv, const __grid_constant__ CUtensorMap tmWo) {
  using namespace ch;
  extern __shared__ __align__(1024) unsigned char smem_raw[];
  const uint32_t sb = smem_u32(smem_raw);
  const int warp = __shfl_sync(0xffffffffu, (int)threadIdx.x >> 5, 0);
  const int lane = __shfl_sync(0xffffffffu, (int)threadIdx.x & 31, threadIdx.x & 31);
  const int cta = blockIdx.x, h = cta / 3, j = cta % 3;
  const int g = lane >> 2, q4 = lane & 3, r8 = lane & 7, m4 = lane >> 3;
  unsigned char* const arena = a.arena;
  if (sb & 1023u) __trap();
  asm volatile("griddepcontrol.launch_dependents;");
  TL_BEGIN(a.tl);
#ifdef TIMELINE
  const unsigned long long g_tl0 = gtime();
#define PT(i) TLW((a.tl >= 12) * 128 + 64 + (i))
#else
#define PT(i)
#endif
  const int col0 = j == 0 ? 0 : (j == 1 ? 224 : 432);
  auto stage_w = [&](const CUtensorMap* tm, uint32_t dst, uint32_t mb, int half) {
    mbar_expect_tx(mb + 8 * half, 40960);
    tma_load_2d(dst + half * 40960, tm, h * cfg::DH + j * 64, half * 320, mb + 8 * half);
    tma_load_2d(dst + half * 40960 + 20480, tm, h * cfg::DH + j * 64, half * 320 + 160, mb + 8 * half);
  };
  if (threadIdx.x == 256) {
    for (int i = 0; i < 9; i++) mbar_init(sb + MB_K + 8 * i, 1);
    mbar_init(sb + MB_S, 1); mbar_init(sb + MB_O, 1); mbar_init(sb + MB_X, 1);
    asm volatile("fence.mbarrier_init.release.cluster;" ::: "memory");
    for (int i = 0; i < 2; i++) { stage_w(&tmWk, sb + OFF_WQ, sb + MB_K, i); stage_w(&tmWv, sb + OFF_WO, sb + MB_V, i); }
    sts32(sb + SC_W, 0); sts32(sb + SC_W + 4, 0); sts32(sb + SC_W + 8, 0); sts32(sb + SC_IN + 12, 0); sts32(sb + SC_IN + 20, 0);
    mbar_expect_tx(sb + MB_S, 1280); mbar_expect_tx(sb + MB_O, 2048);
  }
  __syncthreads();
  asm volatile("barrier.cluster.arrive.relaxed.aligned;" ::: "memory");
  const uint32_t d1 = mapa_u32(sb, (j + 1) % 3) - sb, d2 = mapa_u32(sb, (j + 2) % 3) - sb;

  if (warp >= 8) {
    asm volatile("setmaxnreg.dec.sync.aligned.u32 40;");
    const int hw = warp - 8, ht = hw * 32 + lane;
    const bool lead = ht == 0;
    auto stage_wo = [&](int i) {
      mbar_expect_tx(sb + MB_R + 8 * i, 64 * WOS);
      tma_load_2d(sb + OFF_WO + i * 64 * WOS, &tmWo, col0, h * cfg::DH + ((i + j) % 3) * 64, sb + MB_R + 8 * i);
    };
    const unsigned char* xg = (const unsigned char*)a.xh;
    auto issue_x = [&](int s) { mbar_expect_tx(sb + MB_X, 40960); bulk_g2s(sb + OFF_X, xg + (size_t)s * 40960, 40960, sb + MB_X); };
    uint4 v[5];
#pragma unroll
    for (int i = 0; i < 5; i++) { const int c = ht + 128 * i; v[i] = ld_relaxed_v4(a.mem0 + (c & 7) * cfg::DM + (c >> 3) * 8); }
    if (hw == 2) {
      asm volatile("griddepcontrol.wait;" ::: "memory");
      if (lane == 0) { if (cta == 0) st_relaxed_u32(a.go, 1); issue_x(0); }
      PT(0);
    }
    if (hw == 0) {
      bar_sync(B_QK, 160); if (lane == 0) stage_w(&tmWq, sb + OFF_WQ, sb + MB_Q, 0);
      bar_sync(B_SL, 160); if (lane == 0) stage_w(&tmWq, sb + OFF_WQ, sb + MB_Q, 1);
    }
    if (hw == 1) {
      bar_sync(B_V, 160); if (lane == 0) stage_wo(0);
      bar_sync(B_O, 160); if (lane == 0) { stage_wo(1); stage_wo(2); }
    }
    __syncwarp();
    {
      uint32_t m = 0;
#pragma unroll
      for (int i = 0; i < 5; i++) {
        m = amax_bf2(amax_bf2(m, amax_bf2(v[i].x, v[i].y)), amax_bf2(v[i].z, v[i].w));
      }
      m = amax_fold(m);
      if (lane == 0) sts32(sb + SC_MX + hw * 4, m);
      bar_sync(B_H, 128);
      const uint4 mm = lds128(sb + SC_MX);
      const int se = max(wscale_exp(max(max(mm.x, mm.y), max(mm.z, mm.w))), -100);
      const float sc = exp2i(se);
#pragma unroll
      for (int i = 0; i < 5; i++) {
        const int c = ht + 128 * i, t = c & 7, chn = c >> 3;
        sts128(sb + OFF_MEM + chn * 128 + ((t ^ (2 * (chn & 3))) << 4), bf2_to_h2(v[i].x, sc), bf2_to_h2(v[i].y, sc), bf2_to_h2(v[i].z, sc), bf2_to_h2(v[i].w, sc));
      }
      if (lead) { sts32(sb + SC_IN, __float_as_uint(exp2i(-se))); sts32(sb + SC_IN + 4, 0x7800u); }
    }
    if (hw == 0) PT(11);
    {
      const uint32_t p0 = sb + OFF_WQ + hw * 2048 + lane * 16;
      uint32_t m = 0;
#pragma unroll 1
      for (int i = 0; i < 10; i++) {
        if (i == 0 || i == 5) mbar_wait(sb + MB_Q + (i ? 8 : 0), 0);
        uint32_t r[4][4];
        static_for<0, 4>([&](auto K) { ldsm_x4_i<K.value * 512>(r[K.value], p0 + i * 8192); });
#pragma unroll
        for (int k = 0; k < 4; k++) m = amax_bf2(amax_bf2(m, amax_bf2(r[k][0], r[k][1])), amax_bf2(r[k][2], r[k][3]));
      }
      if (hw == 0) PT(9);
      m = amax_fold(m);
      if (lane == 0) asm volatile("red.shared.max.u32 [%0], %1;" :: "r"(sb + SC_W + 8), "r"(m) : "memory");
      bar_sync(B_H, 128);
      const uint32_t sc = (uint32_t)(wscale_exp(lds32_i<SC_W + 8>(sb)) + 127) * 0x00800080u;
#pragma unroll 1
      for (int i = 0; i < 10; i++) {
        uint32_t r[4][4];
        static_for<0, 4>([&](auto K) { ldsm_x4_i<K.value * 512>(r[K.value], p0 + i * 8192); });
#pragma unroll
        for (int k = 0; k < 4; k++) {
          bf2_to_h2_inplace(r[k][0], sc); bf2_to_h2_inplace(r[k][1], sc); bf2_to_h2_inplace(r[k][2], sc); bf2_to_h2_inplace(r[k][3], sc);
          stsm_x4(p0 + i * 8192 + k * 512, r[k][0], r[k][1], r[k][2], r[k][3]);
        }
      }
    }
    if (hw == 0) PT(10);
    bar_sync(0, 384);
    if (hw == 3) {
      const uint32_t eye = (m4 == q4) ? ((lane & 4) ? 0x3f800000u : 0x3f80u) : 0u;
      sts128(sb + OFF_LT + lane * 16, eye, eye, (lane & 2) * 64 + g * 16 + (lane & 1) * 8, 0u);
      sts64(sb + OFF_S + 1280 + lane * 8, 0u, 0u);
    }
    if (lead) st_relaxed_u32(arena + AR_TAB + cta * 4, 0x80000000u | (lds32_i<SC_W>(sb) << 15) | lds32_i<SC_W + 4>(sb));
    asm volatile("barrier.cluster.wait.aligned;" ::: "memory");
    bar_sync(B_MEM0, 256); bar_sync(B_MEM1, 256);
    {
      uint32_t v0, v1, v2; int spin = 0;
      do {
        v0 = ld_relaxed_u32(arena + AR_TAB + lane * 4); v1 = ld_relaxed_u32(arena + AR_TAB + 128 + lane * 4); v2 = ld_relaxed_u32(arena + AR_TAB + 256 + lane * 4);
      } while (__any_sync(0xffffffffu, ((v0 & v1 & v2) >> 31) == 0) && ++spin < SPIN_LIMIT);
      const uint32_t mv = (max(max(v0, v1), v2) >> 15) & 0x7fffu, mo = max(max(v0 & 0x7fffu, v1 & 0x7fffu), v2 & 0x7fffu);
      sts32(sb + SC_IN + 8 + (lane & 1) * 16, 15 - ((__reduce_max_sync(0xffffffffu, mv) >> 7) + (__reduce_max_sync(0xffffffffu, mo) >> 7) - 252 + 22));
    }

    auto store_kv = [&](int s) {
      const size_t o = ((size_t)s * 96 + cta) * KVB; const uint32_t src = sb + OFF_KV + (s & 1) * (2 * KVB);
      fence_proxy_async(); bulk_s2g(a.kg + o, src, KVB); bulk_s2g(a.vg + o, src + KVB, KVB); bulk_commit();
    };
    const int cb28 = unit28(hw), du = (unit24(hw) - cb28) * 128;
    uint32_t n16 = lane * 16, hist = 0;
    const uint32_t us1 = sb + d1 + OFF_SR + 256 + (hw >> 1) * 512 + (hw & 1) * 128, us2 = sb + d2 + OFF_SR + (hw >> 1) * 512 + (hw & 1) * 128;
    const uint32_t uo1 = sb + d1 + OFF_O + 2048 + hw * 256, uo2 = sb + d2 + OFF_O + 1024 + hw * 256;
#ifdef STEPCLK
    if (lead) a.dbg[96 * 300 + cta * 2] = clk32();
#endif
#ifdef TIMELINE
    if (cta == 0 && lead) { g_tl2[(a.tl >= 12) * 128 + 0] = clock64(); g_tl2[(a.tl >= 12) * 128 + 1] = gtime(); }
#endif
#pragma unroll 1
    for (int s = 0; s < cfg::NSEG; s++) {
      TS_SETUP();
      const bool last = s == cfg::NSEG - 1;
      if (n16 == 0) {
        if (hw == 2 && !last) issue_x(s + 1);
        if (hw == 0 && (s & 3) == 1 && s > 1) st_relaxed_u32(arena + (prog_off(h, j) + (hist >> 31)), s - 1);
        if (hw == 0 && s > 0) store_kv(s - 1);
        if (PFX && hw == 3 && cta < 80 && s + PFX < cfg::NSEG) prefetch_l2(xg + (size_t)(s + PFX) * 40960 + cta * 512, 512);
        if (PFACC && hw == 1 && s + PFACC < cfg::NSEG - 1)
          asm volatile("prefetch.global.L2 [%0];" :: "l"(arena + (AR_ACC + acc_step(s + PFACC) + acc_lane(cta / 24, (cta & 3) * 8) + acc_voff((cta % 24) >> 2))) : "memory");
      }
      __syncwarp();
      if (last) break;
      const uint32_t kv = (s & 1) * (2 * KVB);
      n16 = fresh(n16);
      uint32_t kb0[4], kb1[4];
      { const uint32_t ka = n16 + (n16 & 384) * 4 + (sb + kv + hw * 128); ldsm_x4_i<OFF_KV>(kb0, ka); ldsm_x4_i<OFF_KV + 2560>(kb1, ka); }
      TS(1);
      bar_sync(B_QK, 384);
      {
        uint32_t q0[4], q1[4], q2[4], q3[4];
        float sa[4] = {0, 0, 0, 0}, sc2[4] = {0, 0, 0, 0};
        ldsm_x4_i<OFF_Q>(q0, n16 + sb); ldsm_x4_i<OFF_Q + 1024>(q2, n16 + sb); ldsm_x4_i<OFF_Q + 512>(q1, n16 + sb);
        bar_arrive(B_A, 288);
        ldsm_x4_i<OFF_Q + 1536>(q3, n16 + sb);
        mma16816(sa, q0[0], q0[1], q0[2], q0[3], kb0[0], kb0[1]);
        mma16816(sc2, q2[0], q2[1], q2[2], q2[3], kb1[0], kb1[1]);
        mma16816(sa, q1[0], q1[1], q1[2], q1[3], kb0[2], kb0[3]);
        mma16816(sc2, q3[0], q3[1], q3[2], q3[3], kb1[2], kb1[3]);
        const float x0 = (sa[0] + sa[2]) + (sc2[0] + sc2[2]), x1 = (sa[1] + sa[3]) + (sc2[1] + sc2[3]);
        const uint32_t xp = pack_bf16(x0, x1);
        st_async_b32_i<0>((n16 >> 2) + us1, xp, sb + MB_S + d1);
        st_async_b32_i<0>((n16 >> 2) + us2, xp, sb + MB_S + d2);
        stsm_x2(n16 + (sb + OFF_S + hw * 256), __float_as_uint(x0), __float_as_uint(x1));
      }
      TS(3);
      uint32_t v0[4], v1[4], vm0, vm1;
      const uint32_t uv = sb + kv + hw * 1280;
      ldsm_x4_t_i<OFF_KV + KVB>(v0, n16 + uv); ldsm_x4_t_i<OFF_KV + KVB + 640>(v1, n16 + uv);
      bar_sync(B_SL, 256);
      float t0[4], t1[4], t2[4];
      { uint32_t x[4]; ldsm_x4_i<OFF_S>(x, n16 + sb); t0[0] = __uint_as_float(x[0]); t0[1] = __uint_as_float(x[1]); t0[2] = __uint_as_float(x[2]); t0[3] = __uint_as_float(x[3]); }
      { uint32_t x[4]; ldsm_x4_i<OFF_S + 512>(x, n16 + sb); t1[0] = __uint_as_float(x[0]); t1[1] = __uint_as_float(x[1]); t1[2] = __uint_as_float(x[2]); t1[3] = __uint_as_float(x[3]); }
      { uint32_t x[4]; ldsm_x4_i<OFF_S + 1024>(x, n16 + sb); t2[0] = __uint_as_float(x[0]); t2[1] = __uint_as_float(x[1]); t2[2] = __uint_as_float(x[2]); t2[3] = __uint_as_float(x[3]); }
      mbar_spin(sb + MB_S, s & 1);
      TS(4);
      uint2 xo;
      {
        uint32_t r0[4], r1[4], r2[2];
        ldsm_x4_i<OFF_SR>(r0, n16 + sb); ldsm_x4_i<OFF_SR + 512>(r1, n16 + sb); ldsm_x2_i<OFF_SR + 1024>(r2, n16 + sb);
        SFENCE(n16);
        const uint2 eye = lds64_i<OFF_LT>(n16 + sb);
        mma16816(t0, r0[0], r0[1], r0[2], r0[3], eye.x, eye.y);
        mma16816(t1, r1[0], r1[1], r1[2], r1[3], eye.x, eye.y);
        mma1688(t2, r2[0], r2[1], eye.x);
        bar_sync(B_V, 256);
        vm0 = ldsm_x1_t_i<OFF_KV + KVB + 512>(n16 + uv); vm1 = ldsm_x1_t_i<OFF_KV + KVB + 1152>(n16 + uv);
        SFENCE(n16);
        xo = lds64_i<OFF_LT + 8>(n16 + sb);
      }
      float sc[10] = {t0[0], t0[1], t0[2], t0[3], t1[0], t1[1], t1[2], t1[3], t2[0] + t2[2], t2[1] + t2[3]};
      const float cs = 0.07216878364870322f * 1.4426950408889634f;
      float mx = fmaxf(fmaxf(fmaxf(sc[0], sc[1]), fmaxf(sc[2], sc[3])), fmaxf(fmaxf(sc[4], sc[5]), fmaxf(sc[6], sc[7])));
      mx = fmaxf(mx, fmaxf(sc[8], sc[9]));
      {
        const float m1 = __shfl_xor_sync(0xffffffffu, mx, 1), m2 = __shfl_xor_sync(0xffffffffu, mx, 2), m3 = __shfl_xor_sync(0xffffffffu, mx, 3);
        mx = fmaxf(fmaxf(mx, m1), fmaxf(m2, m3));
      }
      const float mo = fmaf(mx, -cs, __uint_as_float(xo.x));
      auto ex = [&](int i) -> uint32_t { float x, y;
        asm volatile("ex2.approx.ftz.f32 %0, %1;" : "=f"(x) : "f"(fmaf(sc[i], cs, mo))); asm volatile("ex2.approx.ftz.f32 %0, %1;" : "=f"(y) : "f"(fmaf(sc[i + 1], cs, mo)));
        return pack_bf16(x, y); };
      float oa[4] = {0, 0, 0, 0}, ob[4] = {0, 0, 0, 0}, oc[4] = {0, 0, 0, 0}, od[4] = {0, 0, 0, 0}, rs[4] = {0, 0, 0, 0};
      const uint32_t ones = 0x3f803f80u;
      const uint32_t p4 = ex(8);
      if (MEMFIRST) { mma1688(rs, p4, 0u, ones); mma1688(oa, p4, 0u, vm0); mma1688(ob, p4, 0u, vm1); }
      const uint32_t p0 = ex(0), p1 = ex(2), p2 = ex(4), p3 = ex(6);
      TS(5);
      mma16816(rs, p0, p2, p1, p3, ones, ones);
      mma16816(oa, p0, p2, p1, p3, v0[0], v0[1]);
      mma16816(oc, p0, p2, p1, p3, v0[2], v0[3]);
      mma16816(ob, p0, p2, p1, p3, v1[0], v1[1]);
      mma16816(od, p0, p2, p1, p3, v1[2], v1[3]);
      if (!MEMFIRST) { mma1688(rs, p4, 0u, ones); mma1688(oa, p4, 0u, vm0); mma1688(ob, p4, 0u, vm1); }
      const float inv = rcpf(rs[0] + rs[2]) * __uint_as_float(xo.y);
      {
        const uint32_t y0 = pack_bf16((oa[0] + oc[2]) * inv, (oa[1] + oc[3]) * inv), y1 = pack_bf16((ob[0] + od[2]) * inv, (ob[1] + od[3]) * inv);
        st_async_v2_i<0>(xo.x + uo1, y0, y1, sb + MB_O + d1);
        st_async_v2_i<0>(xo.x + uo2, y0, y1, sb + MB_O + d2);
        sts64_i<OFF_O>(xo.x + (sb + hw * 256), y0, y1);
      }
      bar_arrive(B_O, 384);
      TS(6);
      if (hw == 0) {
        bulk_wait<0>();
        if ((s & 3) == 0 && a.pubrel) asm volatile("fence.acq_rel.gpu;" ::: "memory");
      }
      mbar_expect_tx_if(n16 == 0 && hw == 3, sb + MB_S, 1280);
      n16 = fresh(n16);
      const int ln = n16 >> 4;
      auto mslot = [&](int c) -> uint32_t { return sb + OFF_MEM + c * 128 + (((ln >> 2) ^ (2 * (c & 3))) << 4); };
      const int lq = ln & 3;
      const uint32_t ma = mslot(cb28 + lq), mb_ = mslot(cb28 + (lq >> 1)) + (lq & 1) * 8;
      const unsigned char* gp = arena + (AR_ACC + acc_lane(hw, ln) + acc_step(s));
      const bool odd = ln & 1;
      const uint32_t delay = a.delay + ((hist & 2) ? a.margin : 0);
      SFENCE(ma);
      bar_sync(B_RED, 384);
      SFENCE(mb_);
      const uint32_t tw = clk_v();
      TSV(7, tw);
      mbar_expect_tx_if(n16 == 0 && hw == 3, sb + MB_O, 2048);
      while (clk_v() - tw < delay) {}
      TS(8);
      uint4 v[6];
      int spin = 0;
      const uint32_t cm = odd ? 0x5000u : 0u;
      do {
        static_for<0, 6>([&](auto I) { v[I.value] = ld_relaxed_v4_i<acc_voff(I.value)>(gp); });
      } while (__any_sync(0xffffffffu, (~((v[0].w & v[1].w & v[2].w) & (v[3].w & v[4].w & v[5].w)) & cm) != 0) && ++spin < SPIN_LIMIT);
      v[0].w = odd ? v[3].x : v[0].w; v[1].w = odd ? v[3].y : v[1].w; v[2].w = odd ? v[3].z : v[2].w; v[3].w = odd ? 0u : v[3].w;
      sts128_i<0>(ma, v[0].x, v[0].y, v[0].z, v[0].w);
      sts128_i<512>(ma, v[1].x, v[1].y, v[1].z, v[1].w);
      sts128_i<1024>(ma, v[2].x, v[2].y, v[2].z, v[2].w);
      sts128_i<0>(ma + du, v[4].x, v[4].y, v[4].z, v[5].z);
      sts64_i<512>(mb_ + du, v[5].x, v[5].y);
      if (!odd) sts128_i<1536>(mb_, v[3].x, v[3].y, v[3].z, v[3].w);
      hist = (hist * 2 + (spin != 0)) & 0xffffu;
      TSV(11, spin);
#ifdef TIMELINE
      if (spin && ln == 0) atomicAdd(&g_tl2[(a.tl >= 12) * 128 + 4], 1ull);
#endif
      TS(10);
      bar_sync(B_MEM0, 256); bar_sync(B_MEM1, 256);
      uint32_t m = lds32_i<SC_IN + 12>(sb);
      uint32_t m2 = m;
      static_for<0, 3>([&](auto I) { m = amax_h2(amax_h2(amax_h2(amax_h2(m, v[I.value].x), v[I.value].y), v[I.value].z), v[I.value].w); });
      static_for<3, 6>([&](auto I) { m2 = amax_h2(amax_h2(amax_h2(m2, v[I.value].x), v[I.value].y), v[I.value].z); });
      m = amax_fold(amax_h2(amax_h2(m2, v[3].w), m));
      if (n16 == 0) asm volatile("red.shared.max.u32 [%0], %1;" :: "r"(sb + SC_IN + 4 + 16 * ((s + 1) & 1)), "r"(m) : "memory");
    }
    bar_sync(B_RED, 384);
    if (hw == 0 && n16 == 0) {
      store_kv(cfg::NSEG - 1);
      bulk_wait<0>();
      st_release_u32(arena + prog_off(h, j), cfg::NSEG);
    }
    __syncwarp();
#ifdef STEPCLK
    if (hw == 0 && n16 == 0) a.dbg[96 * 300 + cta * 2 + 1 + (hist >> 20)] = clk32();
#endif
#ifdef TIMELINE
    if (cta == 0 && hw == 0 && n16 == 0) { g_tl2[(a.tl >= 12) * 128 + 2] = clock64(); g_tl2[(a.tl >= 12) * 128 + 3] = gtime(); }
#endif
    TL_END(a.tl);
    asm volatile("barrier.cluster.arrive.relaxed.aligned; barrier.cluster.wait.aligned;" ::: "memory");
  } else {
    asm volatile("setmaxnreg.inc.sync.aligned.u32 232;");
    const int wi = warp & 3, hf = warp >> 2, tid = warp * 32 + lane;
    uint32_t w[40][4], wm = 0;
    uint32_t wqa;
    { const int mrow = r8 + ((lane >> 4) << 3), mch = 2 * wi + (m4 & 1); wqa = sb + mrow * 128 + ((mch ^ r8) << 4); }
    {
      const uint32_t wa = wqa + (hf ? OFF_WO : OFF_WQ);
      mbar_wait(sb + (hf ? MB_V : MB_K), 0);
      static_for<0, 20>([&](auto K) { ldsm_x4_t_i<K.value * 2048>(w[K.value], wa); });
#pragma unroll
      for (int k = 0; k < 20; k++) wm = amax_bf2(amax_bf2(wm, amax_bf2(w[k][0], w[k][1])), amax_bf2(w[k][2], w[k][3]));
      SFENCE2(wa, wm);
      if (warp == 0) PT(1);
      bar_arrive(hf ? B_V : B_QK, 160);
      mbar_wait(sb + (hf ? MB_V : MB_K) + 8, 0);
      static_for<20, 40>([&](auto K) { ldsm_x4_t_i<K.value * 2048>(w[K.value], wa); });
#pragma unroll
      for (int k = 20; k < 40; k++) wm = amax_bf2(amax_bf2(wm, amax_bf2(w[k][0], w[k][1])), amax_bf2(w[k][2], w[k][3]));
      SFENCE2(wa, wm);
      if (warp == 4) PT(2);
      bar_arrive(hf ? B_O : B_SL, 160);
      SFENCE(wa);
    }
    float iw, iq;
    {
      const uint32_t m = amax_fold(wm);
      if (hf && lane == 0) asm volatile("red.shared.max.u32 [%0], %1;" :: "r"(sb + SC_W), "r"(m) : "memory");
      const int e = wscale_exp(m);
      const uint32_t sc = (uint32_t)(e + 127) * 0x00800080u; iw = exp2i(-e);
#pragma unroll
      for (int k = 0; k < 40; k++) { bf2_to_h2_inplace(w[k][0], sc); bf2_to_h2_inplace(w[k][1], sc); bf2_to_h2_inplace(w[k][2], sc); bf2_to_h2_inplace(w[k][3], sc); }
    }
    uint32_t x0[8];
    {
      float xa[16];
      const uint32_t dlo = (((sb + OFF_X) & 0x3FFFF) >> 4) | (1u << 16);
      if (warp == 0) PT(3);
      mbar_wait(sb + MB_X, 0);
      if (warp == 0) PT(4);
      wgmma_fence();
      static_for<0, 40>([&](auto K) { constexpr int k = K.value; wgmma_rs32h<((k >> 2) * 4096 + (k & 3) * 32) / 16, (k != 0)>(xa, w[k], dlo); });
      wgmma_commit();
      wgmma_wait<0>();
#pragma unroll
      for (int i = 0; i < 8; i++) x0[i] = pack_bf16(xa[2 * i] * iw, xa[2 * i + 1] * iw);
    }
    const bool t28 = j == 0 || warp < 4;
    const int bi = j == 0 ? hf : (warp < 4 ? j + 1 : 2 * (j - 1) + ((warp - 4) >> 1)), bv = t28 ? wi : 4 + (warp & 1);
    uint32_t wo1 = sb + OFF_WO + warp * 896 + lane * 16, wo2;
    {
      const int cb = (t28 ? unit28(bi) : unit24(bi)) - col0 / 8;
      uint32_t cp[4];
#pragma unroll
      for (int wd = 0; wd < 4; wd++) {
        int c, p;
        if (bv < 3) { c = 4 * bv + q4; p = wd; }
        else if (bv == 3) { if (q4 & 1) { c = 4 * (wd % 3) + q4; p = 3; } else { c = 12 + (q4 >> 1); p = wd; } }
        else if (bv == 4) { c = q4; p = wd; }
        else { if (wd < 2) { c = 4 + (q4 >> 1); p = 2 * (q4 & 1) + wd; } else { c = q4; p = 3; } }
        cp[wd] = sb + OFF_WO + ((g & 1) + (g & 2) * 4 + (g >> 2) * 2) * WOS + (cb + c) * 16 + p * 4;
      }
      const int cidx = (r8 & 1) + ((r8 >> 2) << 1);
      wo2 = sb + OFF_WO + warp * 896 + ((m4 & 1) ? 768 + (m4 >> 1) * 64 + cidx * 16 : 512 + (m4 >> 1) * 128 + r8 * 16);
      const bool dump = (m4 & 1) && (r8 & 2);
      uint32_t mo = 0;
      const bool regular = bv < 3 || bv == 4;
#pragma unroll 1
      for (int i = 0; i < 3; i++) {
        uint32_t x[4][4], y[4][4];
        const uint32_t o = i * 4 * WOK;
        mbar_wait(sb + MB_R + 8 * i, 0);
        if (warp == 0) PT(5 + i);
        if (regular) {
          static_for<0, 4>([&](auto K) {
            constexpr int kk = K.value;
            const uint4 u = lds128_i<kk * WOK>(cp[0] + o), v = lds128_i<kk * WOK + 4 * WOS>(cp[0] + o);
            x[kk][0] = u.x; x[kk][1] = u.y; x[kk][2] = u.z; x[kk][3] = u.w; y[kk][0] = v.x; y[kk][1] = v.y; y[kk][2] = v.z; y[kk][3] = v.w;
          });
        } else {
          static_for<0, 4>([&](auto K) {
            constexpr int kk = K.value;
#pragma unroll
            for (int wd = 0; wd < 4; wd++) { x[kk][wd] = lds32_i<kk * WOK>(cp[wd] + o); y[kk][wd] = lds32_i<kk * WOK + 4 * WOS>(cp[wd] + o); }
          });
        }
        bar_sync(B_C, 256);
        static_for<0, 4>([&](auto K) {
          constexpr int kk = K.value;
#pragma unroll
          for (int wd = 0; wd < 4; wd++) mo = amax_bf2(mo, amax_bf2(x[kk][wd], y[kk][wd]));
          stsm_x4_t_i<kk * WOK>(wo1 + o, x[kk][0], x[kk][1], y[kk][0], y[kk][1]);
          stsm_x4_t_i<0>(dump ? sb + OFF_S + 512 + lane * 16 : wo2 + o + kk * WOK, x[kk][2], x[kk][3], y[kk][2], y[kk][3]);
        });
      }
      if (warp == 0) PT(8);
      mo = amax_fold(mo);
      if (lane == 0) asm volatile("red.shared.max.u32 [%0], %1;" :: "r"(sb + SC_W + 4), "r"(mo) : "memory");
    }
    __syncwarp();
    auto run = [&](auto HF) {
    constexpr int hf = HF.value;
    uint32_t mema, sta, l16 = sb + lane * 16;
    uint32_t rq[hf ? NQ1 : NQ0][4];
    auto step_addr = [&](uint32_t kv) {
      const int lr = (l16 >> 4) & 7, lm = (l16 >> 7) & 3;
      mema = l16 ^ (lm << 5);
      sta = sb + lr * 16 + (lm < 2 ? OFF_Q + wi * 512 + hf * 128 + lm * 256 : OFF_KV + kv + 512 + (2 * wi + lm - 2) * 640);
    };
    auto x_gemm = [&](uint32_t ph, [[maybe_unused]] uint32_t tsb) {
      float xa[16];
      const uint32_t dlo = (((sb + OFF_X) & 0x3FFFF) >> 4) | (1u << 16);
      constexpr int NP = hf ? NQ1 : NP0;
      if constexpr (hf) {
        static_for<PQE, NP>([&](auto K) { ldsm_x4_t_i<OFF_WQ + K.value * 2048>(rq[K.value], wqa); });
        bar_sync(B_X, 256);
      }
      wgmma_fence();
      static_for<0, 40>([&](auto K) {
        constexpr int k = K.value;
        wgmma_rs32h<((k >> 2) * 4096 + (k & 3) * 32) / 16, (k != 0)>(xa, w[k], dlo);
        if constexpr (!hf && k == PFK && NP > PQE) { SFENCE(wqa); static_for<PQE, NP>([&](auto K) { ldsm_x4_t_i<OFF_WQ + K.value * 2048>(rq[K.value], wqa); }); SFENCE(wqa); }
        if constexpr (!hf && k == XT) bar_arrive(B_X, 256);
      });
      step_addr(ph * (2 * KVB));
      wgmma_commit();
      TS(9);
      wgmma_wait<0>();
      const uint32_t xs = l16 + (wi * 1280 + ph * (2 * KVB));
      stsm_x4_t_i<OFF_KV + hf * KVB>(xs, pack_bf16(xa[0] * iw, xa[1] * iw), pack_bf16(xa[4] * iw, xa[5] * iw), pack_bf16(xa[8] * iw, xa[9] * iw), pack_bf16(xa[12] * iw, xa[13] * iw));
      stsm_x4_t_i<OFF_KV + hf * KVB + 640>(xs, pack_bf16(xa[2] * iw, xa[3] * iw), pack_bf16(xa[6] * iw, xa[7] * iw), pack_bf16(xa[10] * iw, xa[11] * iw), pack_bf16(xa[14] * iw, xa[15] * iw));
    };
    auto wq_addr = [&](uint32_t l) -> uint32_t {
      const int lr = (l >> 4) & 7, lm = (l >> 7) & 3;
      return sb + hf * ((40 - NQ1) * 2048) + (lr + ((lm >> 1) << 3)) * 128 + (((2 * wi + (lm & 1)) ^ lr) << 4);
    };
    constexpr int NPM = hf ? NPM1 : NPM0;
    uint32_t u1[NPM][4], u2[NPM][4];
    static_for<0, NPM>([&](auto K) { ldsm_x4_i<(12 - NPM + K.value) * WOK>(u1[K.value], wo1); ldsm_x4_i<(12 - NPM + K.value) * WOK>(u2[K.value], wo2); });
    bar_sync(0, 384);
    iq = uniform_f(exp2i(-wscale_exp(lds32_i<SC_W + 8>(sb))));
    wqa = wq_addr(l16);
    static_for<0, (hf ? NQ1 : NP0)>([&](auto K) { ldsm_x4_t_i<OFF_WQ + K.value * 2048>(rq[K.value], wqa); });
    step_addr(0);
    stsm_x4_t_i<OFF_KV + hf * KVB>(l16 + wi * 1280, x0[0], x0[2], x0[4], x0[6]);
    stsm_x4_t_i<OFF_KV + hf * KVB + 640>(l16 + wi * 1280, x0[1], x0[3], x0[5], x0[7]);
    asm volatile("barrier.cluster.wait.aligned;" ::: "memory");
    TL_END(a.tl + 1);
#pragma unroll 1
    for (int s = 0; s < cfg::NSEG - 1; s++) {
      TS_SETUP();
#if CHAIN_TIMING
      if (tid == 0 && (s & 7) == 0) a.dbg[96 * 288 + cta * 8 + (s >> 3)] = clk32();
#endif
      bar_sync(hf ? B_MEM1 : B_MEM0, 256);
      const float sin_ = __uint_as_float(lds32_i<SC_IN>(sb + 16 * (s & 1)));
      constexpr int NPQ = (40 - NQ1) / 2;
      if constexpr (hf == 0) {
        float k0[4] = {0, 0, 0, 0}, k1[4] = {0, 0, 0, 0}, q0[4] = {0, 0, 0, 0}, q1[4] = {0, 0, 0, 0};
        constexpr auto pair_of = [](int t) { const int a = t * (20 - NPQ) / 20, b = (t + 1) * (20 - NPQ) / 20; return b > a ? NPQ + a : t - a; };
        uint32_t b[NB0][4];
        static_for<0, NB0>([&](auto T) { ldsm_x4_i<OFF_MEM + pair_of(T.value) * 512>(b[T.value], mema); });
        static_for<NP0, NQ0>([&](auto K) { ldsm_x4_t_i<OFF_WQ + K.value * 2048>(rq[K.value], wqa); });
        if (BBS < 100) bbfence<0>(mema);
        static_for<0, 20>([&](auto T) {
          constexpr int t = T.value, p = pair_of(t);
          uint32_t (&bb)[4] = b[t % NB0];
          if constexpr (p < NPQ) {
            mma16816h(q0, rq[(2 * p) % NQ0], bb[0], bb[1]);
            if constexpr (2 * p + NQ0 < 2 * NPQ) ldsm_x4_t_i<OFF_WQ + (2 * p + NQ0) * 2048>(rq[(2 * p) % NQ0], wqa);
          }
          mma16816h(k0, w[2 * p], bb[0], bb[1]);
          if constexpr (p < NPQ) {
            mma16816h(q1, rq[(2 * p + 1) % NQ0], bb[2], bb[3]);
            if constexpr (2 * p + 1 + NQ0 < 2 * NPQ) ldsm_x4_t_i<OFF_WQ + (2 * p + 1 + NQ0) * 2048>(rq[(2 * p + 1) % NQ0], wqa);
          }
          mma16816h(k1, w[2 * p + 1], bb[2], bb[3]);
          if constexpr (NVE > 0 && t + NB0 == VET) bar_arrive(B_E, 256);
          if constexpr (t + NB0 < 20) ldsm_x4_i<OFF_MEM + pair_of(t + NB0) * 512>(bb, mema);
          if constexpr (t < 20 - NB0 && (t % BBS) == BBS - 1) bbfence<t + 1>(mema);
        });
        const float sq = sin_ * iq, sk = sin_ * iw;
        stsm_x4_t_i<0>(sta, pack_bf16((q0[0] + q1[0]) * sq, (q0[1] + q1[1]) * sq), pack_bf16((q0[2] + q1[2]) * sq, (q0[3] + q1[3]) * sq),
                       pack_bf16((k0[0] + k1[0]) * sk, (k0[1] + k1[1]) * sk), pack_bf16((k0[2] + k1[2]) * sk, (k0[3] + k1[3]) * sk));
        bar_sync(B_QK, 384);
        SFENCE(l16);
        [[maybe_unused]] const uint32_t tq = GD0 < 0 ? 0 : clk_v();
        TS(2);
        {
          if (wi == 3) {
            const uint32_t xr = sb + ((l16 & 511) >> 2), ka = l16 + (l16 & 384) * 4 + (s & 1) * (2 * KVB);
            uint32_t a0[4], a1[4], a2[4], a3[4], kb0[4], kb1[4];
            ldsm_x4_i<OFF_Q>(a0, l16); ldsm_x4_i<OFF_KV + 512>(kb0, ka); ldsm_x4_i<OFF_Q + 1024>(a2, l16); ldsm_x4_i<OFF_KV + 512 + 2560>(kb1, ka);
            ldsm_x4_i<OFF_Q + 512>(a1, l16);
            bar_arrive(B_A, 288);
            ldsm_x4_i<OFF_Q + 1536>(a3, l16);
            float sa[4] = {0, 0, 0, 0}, sc2[4] = {0, 0, 0, 0};
            mma16816(sa, a0[0], a0[1], a0[2], a0[3], kb0[0], kb0[1]);
            mma16816(sc2, a2[0], a2[1], a2[2], a2[3], kb1[0], kb1[1]);
            mma16816(sa, a1[0], a1[1], a1[2], a1[3], kb0[2], kb0[3]);
            mma16816(sc2, a3[0], a3[1], a3[2], a3[3], kb1[2], kb1[3]);
            const float x0 = (sa[0] + sa[2]) + (sc2[0] + sc2[2]), x1 = (sa[1] + sa[3]) + (sc2[1] + sc2[3]);
            const uint32_t xp = pack_bf16(x0, x1);
            st_async_b32_i<OFF_SR + 1024 + 128>(xr + d1, xp, sb + MB_S + d1);
            st_async_b32_i<OFF_SR + 1024>(xr + d2, xp, sb + MB_S + d2);
            stsm_x2(l16 + OFF_S + 1024, __float_as_uint(x0), __float_as_uint(x1));
          } else if (wi == 0) {
            const uint4 si = lds128_i<SC_IN>(sb + 16 * (s & 1));
            const int em = (int)(si.y >> 10) - 14 + (int)(si.x >> 23) - 127;
            const uint32_t osc = __float_as_uint(exp2i(max(min((int)si.z - max(em, 1), 100), -100)));
            sts32(l16 + OFF_LT + 12, osc); sts64_i<SC_IN>(sb + 16 * ((s + 1) & 1), 0x7f000000u - osc, 0u);
          }
          if (GD0 < 0) bar_sync(B_SL, 256);
          else { bar_arrive(B_SL, 256); while (clk_v() - tq < GD0) {} }
        }
      } else {
        float v0[4] = {0, 0, 0, 0}, v1[4] = {0, 0, 0, 0}, q0[4] = {0, 0, 0, 0}, q1[4] = {0, 0, 0, 0};
        uint32_t b[NQ1 / 2][4];
        static_for<0, NQ1 / 2>([&](auto T) { ldsm_x4_i<OFF_MEM + (NPQ + T.value) * 512>(b[T.value], mema); });
        static_for<0, NQ1 / 2>([&](auto T) {
          constexpr int t = T.value, p = NPQ + t;
          uint32_t (&bb)[4] = b[t];
          mma16816h(q0, rq[2 * t], bb[0], bb[1]);
          mma16816h(q1, rq[2 * t + 1], bb[2], bb[3]);
          mma16816h(v0, w[2 * p], bb[0], bb[1]);
          mma16816h(v1, w[2 * p + 1], bb[2], bb[3]);
        });
        const float sq = sin_ * iq, sv = sin_ * iw;
        stsm_x2_t_i<0>(sta, pack_bf16((q0[0] + q1[0]) * sq, (q0[1] + q1[1]) * sq), pack_bf16((q0[2] + q1[2]) * sq, (q0[3] + q1[3]) * sq));
        TS(2);
        bar_arrive(B_QK, 384);
        float v2[4] = {0, 0, 0, 0}, v3[4] = {0, 0, 0, 0};
        auto vpair = [&](auto P, uint32_t (&bb)[4]) {
          constexpr int p = P.value;
          if constexpr (p & 1) { mma16816h(v0, w[2 * p], bb[0], bb[1]); mma16816h(v1, w[2 * p + 1], bb[2], bb[3]); }
          else { mma16816h(v2, w[2 * p], bb[0], bb[1]); mma16816h(v3, w[2 * p + 1], bb[2], bb[3]); }
        };
        if constexpr (NVE > 0) {
          uint32_t e[NVE ? NVE : 1][4];
          bar_sync(B_E, 256);
          static_for<0, NVE>([&](auto T) { ldsm_x4_i<OFF_MEM + T.value * 512>(e[T.value], mema); });
          static_for<0, NVE>([&](auto T) { vpair(T, e[T.value]); });
        }
        bar_sync(B_A, 288);
        uint32_t c[4][4];
        static_for<NVE, NVE + 4>([&](auto T) { ldsm_x4_i<OFF_MEM + T.value * 512>(c[T.value & 3], mema); });
        static_for<NVE, NPQ>([&](auto T) {
          constexpr int p = T.value;
          vpair(T, c[p & 3]);
          if constexpr (p + 4 < NPQ) ldsm_x4_i<OFF_MEM + (p + 4) * 512>(c[p & 3], mema);
        });
        stsm_x2_t_i<OFF_KV + KVB + 512>(l16 + (l16 & 128) * 4 + (wi * 1280 + (s & 1) * (2 * KVB)), pack_bf16(((v0[0] + v1[0]) + (v2[0] + v3[0])) * sv, ((v0[1] + v1[1]) + (v2[1] + v3[1])) * sv),
                            pack_bf16(((v0[2] + v1[2]) + (v2[2] + v3[2])) * sv, ((v0[3] + v1[3]) + (v2[3] + v3[3])) * sv));
        bar_arrive(B_V, 256);
      }
      TS(3);
      {
        uint32_t t1[12][4], t2[12][4];
        const uint32_t o16 = l16;
        wo1 = l16 + (OFF_WO + warp * 896);
        wo2 = sb + OFF_WO + warp * 896 + ((l16 & 128) ? 768 + ((l16 & 256) >> 2) + (l16 & 16) + ((l16 & 64) >> 1) : 512 + ((l16 & 256) >> 1) + (l16 & 112));
        auto ldw = [&](auto K) { if constexpr (K.value < 12 - NPM) { ldsm_x4_i<K.value * WOK>(t1[K.value], wo1); ldsm_x4_i<K.value * WOK>(t2[K.value], wo2); } };
        constexpr int NR_ = NRT - NPM;
        constexpr int PB = (hf ? PB1 : PB0) < NR_ ? (hf ? PB1 : PB0) : NR_, PA = (hf ? PA1 : PA0) < PB ? (hf ? PA1 : PA0) : PB;
        static_for<0, PA>(ldw);
        mbar_spin(sb + MB_X, (s + 1) & 1);
        if constexpr (PB > PA) {
          constexpr int PM = PA + PM1 < PB ? PA + PM1 : PB;
          mbar_spin(sb + MB_S, s & 1);
          const uint32_t t0 = clk_v();
          if constexpr (PM > PA) { while (clk_v() - t0 < GD1) {} static_for<PA, PM>(ldw); }
          if constexpr (PB > PM) { while (clk_v() - t0 < GD2) {} static_for<PM, PB>(ldw); }
        }
        float c0[4] = {0, 0, 0, 0}, c1[4] = {0, 0, 0, 0}, e0[4] = {0, 0, 0, 0}, e1[4] = {0, 0, 0, 0};
        uint32_t ob[6][4];
        auto kstep = [&](auto K) {
          constexpr int k = K.value;
          uint32_t (&bb)[4] = ob[k >> 1];
          uint32_t (&x)[4] = k < 12 - NPM ? t1[k] : u1[k < 12 - NPM ? 0 : k - (12 - NPM)];
          uint32_t (&y)[4] = k < 12 - NPM ? t2[k] : u2[k < 12 - NPM ? 0 : k - (12 - NPM)];
          if constexpr (k & 1) { mma16816(c1, x[0], x[1], x[2], x[3], bb[2], bb[3]); mma16816(e1, y[0], y[1], y[2], y[3], bb[2], bb[3]); }
          else { mma16816(c0, x[0], x[1], x[2], x[3], bb[0], bb[1]); mma16816(e0, y[0], y[1], y[2], y[3], bb[0], bb[1]); }
          if constexpr (k >= NRF) ldw(IC<k + NR_ - NRF>{});
        };
        auto ldo = [&](auto P) { ldsm_x4_i<OFF_O + P.value * 512>(ob[P.value], o16); };
        TS(4);
        bar_sync(B_O, 384);
        ldo(IC<0>{}); ldo(IC<1>{});
        SFENCE(o16);
        static_for<PB, NR_>(ldw);
        static_for<0, 4>(kstep);
        TS(5);
        mbar_spin(sb + MB_O, s & 1);
        TS(6);
        ldo(IC<2>{}); ldo(IC<NPM >= 2 ? 5 : 3>{});
        if (WOF) SFENCE(o16);
        kstep(IC<4>{});
        if constexpr (NPM < 2) { kstep(IC<5>{}); ldo(IC<4>{}); kstep(IC<6>{}); kstep(IC<7>{}); ldo(IC<5>{}); static_for<8, 12>(kstep); }
        else if constexpr (NPM >= 4) { kstep(IC<10>{}); kstep(IC<11>{}); ldo(IC<4>{}); kstep(IC<5>{}); ldo(IC<3>{}); kstep(IC<8>{}); kstep(IC<9>{}); kstep(IC<6>{}); kstep(IC<7>{}); }
        else { kstep(IC<5>{}); ldo(IC<3>{}); kstep(IC<11>{}); kstep(IC<10>{}); ldo(IC<4>{}); kstep(IC<6>{}); kstep(IC<7>{}); if constexpr (NPM == 3) { kstep(IC<9>{}); kstep(IC<8>{}); } else { kstep(IC<8>{}); kstep(IC<9>{}); } }
        l16 = fresh(l16);
        const int ln = (l16 >> 4) & 31;
        if constexpr (CEARLY && hf) { SFENCE2(o16, __float_as_uint(e1[0])); bar_arrive(B_G, 256); }
        unsigned char* gr = arena + (AR_ACC + acc_lane(bi, ln) + acc_voff(bv) + acc_step(s));
        const bool cnt = (ln & 1) || !t28;
        wqa = wq_addr(l16);
        SFENCE(o16);
        static_for<0, PQE>([&](auto K) { ldsm_x4_t_i<OFF_WQ + K.value * 2048>(rq[K.value], wqa); });
        const uint32_t y0 = movm_t(pack_f16(c0[0] + c1[0], c0[1] + c1[1])), y1 = movm_t(pack_f16(c0[2] + c1[2], c0[3] + c1[3]));
        const uint32_t y2 = movm_t(pack_f16(e0[0] + e1[0], e0[1] + e1[1])), y3 = movm_t(pack_f16(e0[2] + e1[2], e0[3] + e1[3]));
        asm volatile("red.relaxed.gpu.global.add.noftz.v4.f16x2 [%0], {%1,%2,%3,%4};" :: "l"(gr), "r"(y0), "r"(y1), "r"(y2), "r"(cnt ? 0x3c00u : y3) : "memory");
        bar_arrive(B_RED, 384);
        if constexpr (CEARLY && !hf) { bar_arrive(B_C, 256); bar_sync(B_G, 256); }
        else bar_sync(B_C, 256);
        TS(7);
      }
#if CHAIN_TIMING
      x_gemm((s + 1) & 1, tsb);
#else
      x_gemm((s + 1) & 1, 0);
#endif
      TS(8);
    }
    };
    if (hf == 0) run(IC<0>{}); else run(IC<1>{});
    {
      const uint32_t l16 = sb + (threadIdx.x & 31) * 16, mema = l16 ^ ((l16 >> 2) & 96);
      float c0[4] = {0, 0, 0, 0}, c1[4] = {0, 0, 0, 0}, c2[4] = {0, 0, 0, 0}, c3[4] = {0, 0, 0, 0};
      bar_sync(hf ? B_MEM1 : B_MEM0, 256);
      const float sc = __uint_as_float(lds32_i<SC_IN + 16>(sb)) * iw;
      static_for<0, 10>([&](auto T) {
        constexpr int p = 2 * T.value;
        uint32_t b0[4], b1[4];
        ldsm_x4_i<OFF_MEM + p * 512>(b0, mema); ldsm_x4_i<OFF_MEM + p * 512 + 512>(b1, mema);
        mma16816h(c0, w[2 * p], b0[0], b0[1]); mma16816h(c1, w[2 * p + 1], b0[2], b0[3]);
        mma16816h(c2, w[2 * p + 2], b1[0], b1[1]); mma16816h(c3, w[2 * p + 3], b1[2], b1[3]);
      });
      stsm_x2_t_i<OFF_KV + 2 * KVB + 512>(l16 + (l16 & 128) * 4 + wi * 1280 + hf * KVB, pack_bf16(((c0[0] + c1[0]) + (c2[0] + c3[0])) * sc, ((c0[1] + c1[1]) + (c2[1] + c3[1])) * sc),
                                          pack_bf16(((c0[2] + c1[2]) + (c2[2] + c3[2])) * sc, ((c0[3] + c1[3]) + (c2[3] + c3[3])) * sc));
      fence_proxy_async();
    }
    bar_arrive(B_RED, 384);
#if CHAIN_TIMING
    for (int i = tid; i < 288; i += 256) a.dbg[cta * 288 + i] = lds32_i<OFF_BAR + 128>(sb + i * 4);
#endif
    asm volatile("barrier.cluster.arrive.relaxed.aligned; barrier.cluster.wait.aligned;" ::: "memory");
  }
}
struct PrepArgs { const bf16 *wqkv, *wphi, *wo; unsigned char *wb, *wot; };
__device__ __forceinline__ void prep_body(const int cta, const PrepArgs& pa) {
  const int tid = threadIdx.x, lane = tid & 31, warp = tid >> 5, g = lane >> 2, q = lane & 3;
  const int pair = cta >> 1, which = cta & 1;
  uint32_t af[5][2][6];
#pragma unroll
  for (int i = 0; i < 5; i++)
#pragma unroll
    for (int hh = 0; hh < 2; hh++) {
      const uint32_t* r0 = (const uint32_t*)(pa.wqkv + (size_t)((warp * 5 + i) * 16 + g) * 1920 + which * 640 + (2 * pair + hh) * 20) + q;
      const uint32_t* r1 = r0 + 8 * 960;
      af[i][hh][0] = __ldg(r0); af[i][hh][1] = __ldg(r1); af[i][hh][2] = __ldg(r0 + 4); af[i][hh][3] = __ldg(r1 + 4);
      af[i][hh][4] = q < 2 ? __ldg(r0 + 8) : 0u; af[i][hh][5] = q < 2 ? __ldg(r1 + 8) : 0u;
    }
  uint32_t bfr[2][3][3];
#pragma unroll
  for (int hh = 0; hh < 2; hh++)
#pragma unroll
    for (int t = 0; t < 3; t++) {
      const bool on = t < 2 || (g & 1) == hh;
      const unsigned short* ph = (const unsigned short*)pa.wphi + (2 * pair + hh) * 400 + (t < 2 ? 8 * t + g : 16 + (g >> 1)) + 2 * q * 20;
#pragma unroll
      for (int r = 0; r < 3; r++) bfr[hh][t][r] = (on && (r < 2 || q < 2)) ? (uint32_t)__ldg(ph + r * 160) | ((uint32_t)__ldg(ph + r * 160 + 20) << 16) : 0u;
    }
  const int gt = cta * 256 + tid;
#pragma unroll 3
  for (int i = gt; i < 640 * 32; i += 8192) {
    const int k = (i & 7) + (i >> 8) * 8, h = (i >> 3) & 31;
    const uint2* src = (const uint2*)(pa.wqkv + (size_t)k * 1920 + 1280 + h * 20);
    const uint2 a = __ldg(src), b = __ldg(src + 1), c = __ldg(src + 2), d = __ldg(src + 3), e = __ldg(src + 4);
    uint4* dst = (uint4*)(pa.wb + ((size_t)((h >> 2) * 80 + (k >> 3)) * 32 + 20 + 3 * (h & 3)) * 128 + (k & 7) * 16);
    dst[0] = make_uint4(a.x, a.y, b.x, b.y); dst[8] = make_uint4(c.x, c.y, d.x, d.y);
    dst[16] = (h & 1) ? make_uint4(0, 0, e.x, e.y) : make_uint4(e.x, e.y, 0, 0);
  }
#pragma unroll 7
  for (int i = gt; i < 640 * 80; i += 8192) {
    const int r = i & 7, c = (i >> 3) % 80, kg = i / 640, c5 = kg % 5;
    const int row = (kg / 5) * 40 + (c5 < 2 ? 8 * c5 + r : (c5 == 2 ? 16 + (r & 3) + (r >> 2) * 20 : 20 + 8 * (c5 - 3) + r));
    *(uint4*)(pa.wot + ((size_t)((c / 10) * 80 + kg) * 10 + c % 10) * 128 + r * 16) = __ldg((const uint4*)(pa.wo + (size_t)row * cfg::DM + c * 8));
  }
#pragma unroll
  for (int i = 0; i < 5; i++) {
    uint32_t* dst = (uint32_t*)(pa.wb + ((size_t)((pair >> 1) * 80 + (warp * 5 + i) * 2) * 32 + which * 10 + (pair & 1) * 5) * 128) + lane;
#pragma unroll
    for (int t = 0; t < 5; t++) {
      float d[4] = {0, 0, 0, 0};
#pragma unroll
      for (int hh = 0; hh < 2; hh++)
        if (t == 2 || (t > 2) == (hh == 1)) {
          const int tt = t < 3 ? t : t - 3;
          mma16816(d, af[i][hh][0], af[i][hh][1], af[i][hh][2], af[i][hh][3], bfr[hh][tt][0], bfr[hh][tt][1]);
          mma1688(d, af[i][hh][4], af[i][hh][5], bfr[hh][tt][2]);
        }
      dst[t * 32] = pack_bf16(d[0], d[1]); dst[1024 + t * 32] = pack_bf16(d[2], d[3]);
    }
  }
}

__global__ void __launch_bounds__(256, 4) ln_kernel(const bf16* __restrict__ xin, bf16* __restrict__ xn, uint2* __restrict__ xh, uint4* __restrict__ z0, int n0,
                                                    uint4* __restrict__ z1, int n1, const bf16* pfa, const bf16* pfb, int npf, int tl) {
  asm volatile("griddepcontrol.wait;" ::: "memory");
  asm volatile("griddepcontrol.launch_dependents;" ::: "memory");
  TL_BEGIN(tl);
  const int warp = threadIdx.x >> 5, lane = threadIdx.x & 31;
  const int row = blockIdx.x * 8 + warp;
  uint2 xw[1][5];
#pragma unroll
  for (int i = 0; i < 5; i++) xw[0][i] = *(const uint2*)(xin + (size_t)row * cfg::DM + i * 128 + lane * 4);
  for (int i = blockIdx.x * 256 + threadIdx.x; i < n0; i += 256 * 256) z0[i] = make_uint4(0, 0, 0, 0);
  for (int i = blockIdx.x * 256 + threadIdx.x; i < n1; i += 256 * 256) z1[i] = make_uint4(0, 0, 0, 0);
  if (npf && xw[0][4].y != 0x7fc17fc1u) {
    for (int i = 0; i < npf; i++) {
      const uint32_t l = (uint32_t)i * 32768u + (blockIdx.x * 256 + threadIdx.x) / 2;
      if (l < cfg::DM * cfg::HD / 64) asm volatile("prefetch.global.L2 [%0];" :: "l"(((threadIdx.x & 1) ? pfa : pfb) + (size_t)l * 64) : "memory");
    }
  }
  ln_rows<1>(xw, row, lane, xn, xh);
  TL_END(tl);
}
struct Pipe { uint32_t stage, phase; };
template <int NS> __device__ __forceinline__ void pipe_adv(Pipe& p) { if (++p.stage == NS) { p.stage = 0; p.phase ^= 1; } }
constexpr uint32_t SWZ128 = 1;
__device__ __forceinline__ uint64_t desc_kmajor(uint32_t a) { return make_desc(a, 16, 1024, SWZ128); }
__device__ __forceinline__ uint64_t desc_mnmajor(uint32_t a) { return make_desc(a, 8192, 1024, SWZ128); }
__device__ __forceinline__ void wait_ge(const void* p, uint32_t target, uint32_t ns = 32) {
  int spin = 0;
  while (ld_acquire_u32(p) < target) { __nanosleep(ns); if (++spin > (1 << 21)) break; }
}
__device__ __forceinline__ void bulk_g2s_hint(uint32_t dst, const void* src, uint32_t bytes, uint32_t mb, uint64_t pol) {
  asm volatile("cp.async.bulk.shared::cluster.global.mbarrier::complete_tx::bytes.L2::cache_hint [%0], [%1], %2, [%3], %4;"
               :: "r"(dst), "l"(src), "r"(bytes), "r"(mb), "l"(pol) : "memory");
}
#ifndef PF_WB
#define PF_WB 2
#endif
#ifndef PF_XN
#define PF_XN 1
#endif
#ifndef STAG
#define STAG 1
#endif
#ifndef EF_KV
#define EF_KV 1
#endif
#ifndef EF_O
#define EF_O 1
#endif
__device__ __forceinline__ void fence_proxy_async_global() { asm volatile("fence.proxy.async.global;" ::: "memory"); }

namespace tr {
constexpr int NS = 4, STQ = 16384 + 24576, STO = 16384 + 40960;
constexpr int SEGB = 15360;
constexpr int OFF_K = NS * STQ;
constexpr int OFF_BAR = NS * STO;
constexpr int SMEM = OFF_BAR + 256;
static_assert(OFF_K + 4 * SEGB <= OFF_BAR && SMEM <= 232448, "smem");
enum { T_QA = 0, T_Q, T_A, T_OB, T_OS, T_L, T_END, T_P };
constexpr uint32_t C_QA = AR_CNT, C_O = AR_CNT + 64, C_Q = AR_CNT + 128, C_P = AR_CNT + 192;
constexpr int MAXITEMS = 1200;
struct Sched {
  uint8_t ks[16];
  uint8_t wide[16];
  uint8_t lrows[16];
  uint32_t n;
  uint16_t item[MAXITEMS];
};
struct Args {
  const unsigned char *kg, *vg;
  unsigned char* o;
  uint4* qs;
  unsigned char* part;
  const bf16 *xin, *xq;
  bf16 *xout, *xn;
  unsigned char* arena;
  const unsigned* go;
  int tl;
  uint32_t nap, nap2;
};
}

template <int N0, int N1>
__device__ __forceinline__ void tr_mainloop(float (&a0)[N0 / 2], float (&a1)[N1 ? N1 / 2 : 1], Pipe& p, uint32_t sb, uint32_t full, uint32_t empty, int nkb, int wg) {
  using namespace tr;
  constexpr uint32_t ST = N1 ? STO : STQ;
  uint32_t prev = 0;
#pragma unroll
  for (int i = 0; i < N0 / 2; i++) a0[i] = 0.f;
  if constexpr (N1 > 0) {
#pragma unroll
    for (int i = 0; i < N1 / 2; i++) a1[i] = 0.f;
  }
#pragma unroll 1
  for (int kb = 0; kb < nkb; kb++) {
    mbar_wait(full + 8 * p.stage, p.phase);
    const uint32_t st = sb + p.stage * ST;
    wgmma_fence();
#pragma unroll
    for (int kk = 0; kk < 4; kk++) {
      const uint64_t da = desc_kmajor(st + wg * 8192 + kk * 32);
      if constexpr (N0 == 192) wgmma_n192<0, 1>(a0, da, desc_mnmajor(st + 16384 + kk * 2048), (kb | kk) != 0);
      else wgmma_n128<0, 1>(a0, da, desc_mnmajor(st + 16384 + kk * 2048), (kb | kk) != 0);
      if constexpr (N1 > 0) wgmma_n128<0, 1>(a1, da, desc_mnmajor(st + 16384 + 24576 + kk * 2048), (kb | kk) != 0);
    }
    wgmma_commit();
    if (kb > 0) { wgmma_wait<1>(); mbar_arrive_if((threadIdx.x & 127) == 0, empty + 8 * prev); }
    prev = p.stage;
    pipe_adv<NS>(p);
  }
  wgmma_wait<0>();
  mbar_arrive_if((threadIdx.x & 127) == 0, empty + 8 * prev);
}
template <int N> __device__ __forceinline__ void stage_tiles(const float (&o)[N / 2], uint32_t base, int wi, int lane) {
  const uint32_t ra = base + (wi * 16 + (lane & 7) + 8 * ((lane >> 3) & 1)) * 128;
#pragma unroll
  for (int v = 0; v < N / 8; v += 2)
    stsm_x4(ra + (v >> 3) * 8192 + ((((v & 7) + (lane >> 4)) ^ (lane & 7)) << 4), pack_bf16(o[4 * v], o[4 * v + 1]), pack_bf16(o[4 * v + 2], o[4 * v + 3]),
            pack_bf16(o[4 * v + 4], o[4 * v + 5]), pack_bf16(o[4 * v + 6], o[4 * v + 7]));
}
__global__ void __launch_bounds__(384, 1) trail_kernel(const __grid_constant__ CUtensorMap tmX, const __grid_constant__ CUtensorMap tmQ,
                                                       const __grid_constant__ CUtensorMap tmWo5, const __grid_constant__ CUtensorMap tmWo2,
                                                       const __grid_constant__ CUtensorMap tmP, const __grid_constant__ tr::Sched sc,
                                                       const __grid_constant__ tr::Args a, const __grid_constant__ PrepArgs pa) {
  using namespace tr;
  [[maybe_unused]] const int tl = a.tl;
  TL_BEGIN(tl);
  extern __shared__ __align__(1024) unsigned char smem_raw[];
  const uint32_t sb = smem_u32(smem_raw);
  const int warp = __shfl_sync(0xffffffffu, (int)threadIdx.x >> 5, 0), lane = threadIdx.x & 31;
  unsigned char* const arena = a.arena;
  const uint32_t full = sb + OFF_BAR, empty = full + 8 * NS, barK = empty + 8 * NS, barKfree = barK + 16, staged = barKfree + 16;
  const uint32_t kvrdy = staged + 32, mfull = kvrdy + 8, mempty = mfull + 16, mbox = mempty + 16;
  uint32_t go = 0;
  if (threadIdx.x == 256) go = ld_acquire_u32(a.go);
  if (threadIdx.x == 0) {
    for (int i = 0; i < NS; i++) { mbar_init(full + 8 * i, 1); mbar_init(empty + 8 * i, 2); }
    for (int i = 0; i < 2; i++) {
      mbar_init(barK + 8 * i, 1); mbar_init(barKfree + 8 * i, 1); mbar_init(staged + 16 * i, 4); mbar_init(staged + 16 * i + 8, 4);
      mbar_init(mfull + 8 * i, 1); mbar_init(mempty + 8 * i, 11);
    }
    mbar_init(kvrdy, 1);
    asm volatile("fence.mbarrier_init.release.cluster;" ::: "memory");
  }
  __syncthreads();
  Pipe mp{0, 0};
  auto next_item = [&]() -> uint32_t {
    uint32_t it;
    mbar_wait(mfull + 8 * mp.stage, mp.phase);
    asm volatile("ld.shared.u32 %0, [%1];" : "=r"(it) : "r"(mbox + 4 * mp.stage) : "memory");
    return it;
  };
  if (warp >= 8) {
    asm volatile("setmaxnreg.dec.sync.aligned.u32 40;");
    if (warp == 8) { go = __shfl_sync(0xffffffffu, go, 0); if (elect_one()) {
      Pipe p{0, 1};
      mp.phase = 1;
      uint32_t kph = 1, rph = 0, wide = 0, qdone = 0;
      prefetch_tmap(&tmX); prefetch_tmap(&tmQ); prefetch_tmap(&tmWo5); prefetch_tmap(&tmWo2); prefetch_tmap(&tmP);
      const uint64_t ef = policy_evict_first();
      auto ld_kv = [&](uint32_t d, const void* s, uint32_t n, uint32_t mb) { if (EF_KV) bulk_g2s_hint(d, s, n, mb, ef); else bulk_g2s(d, s, n, mb); };
      auto ld_o = [&](uint32_t d, const void* s, uint32_t n, uint32_t mb) { if (EF_O) bulk_g2s_hint(d, s, n, mb, ef); else bulk_g2s(d, s, n, mb); };
      auto stage = [&](uint32_t bytes) -> uint32_t {
        mbar_wait(empty + 8 * p.stage, p.phase);
        mbar_expect_tx(full + 8 * p.stage, bytes);
        return sb + p.stage * (wide ? STO : STQ);
      };
      auto fetch = [&]() -> uint32_t { uint32_t v; asm volatile("atom.relaxed.gpu.global.add.u32 %0, [%1], 1;" : "=r"(v) : "l"(arena + AR_QUEUE) : "memory"); return v; };
      if (!go) wait_ge(a.go, 1, 200);
      fence_proxy_async_global();
      uint32_t next = fetch();
      while (true) {
        const uint32_t item = next;
        const uint32_t code = sc.item[min(item, sc.n)];
        const int type = code >> 11, m = (code >> 7) & 15, k = code & 127;
        if (type == T_A && !((qdone >> m) & 1)) { wait_ge(arena + C_Q + m * 4, 64); qdone |= 1u << m; }
        if (type == T_OB && !wide) for (uint32_t i = 0; i < NS; i++) mbar_wait(empty + 8 * i, i >= p.stage ? p.phase : p.phase ^ 1);
        wide = type == T_OB;
        mbar_wait(mempty + 8 * mp.stage, mp.phase);
        asm volatile("st.shared.u32 [%0], %1;" :: "r"(mbox + 4 * mp.stage), "r"((p.stage << 24) | (type << 16) | (m << 8) | (k & 255)) : "memory");
        mbar_arrive(mfull + 8 * mp.stage);
        pipe_adv<2>(mp);
        if (type == T_END) break;
        if (type == T_P) { next = fetch(); continue; }
        if (type == T_L) {
          const int nr = sc.lrows[m], np = sc.ks[m];
          prefetch_l2(a.xin + (size_t)(m * 128 + k * 8 * nr) * cfg::DM, nr * 10240);
          wait_ge(arena + C_O + m * 4, np * (sc.wide[m] ? 4 : 10), m < 13 ? a.nap : 32);
          fence_proxy_async_global();
#pragma unroll 1
          for (int r = 0; r < nr; r++) {
            const int rg = m * 16 + k * nr + r;
#pragma unroll 1
            for (int q0 = 0; q0 <= np; q0 += 4) {
              const int n = min(4, np + 1 - q0);
              const uint32_t st = stage(n * 10240), fb = full + 8 * p.stage;
#pragma unroll 1
              for (int q = q0; q < q0 + n; q++) {
                if (q == 0) bulk_g2s(st, a.xin + (size_t)rg * 8 * cfg::DM, 10240, fb);
                else tma_load_3d(st + (q - q0) * 10240, &tmP, 0, rg & 7, ((q - 1) * 32 + (rg >> 3)) * 10, fb);
              }
              pipe_adv<NS>(p);
            }
          }
          next = fetch(); continue;
        }
        if (type <= T_A) {
          if (type != T_A)
#pragma unroll 1
            for (int kb = 0; kb < 10; kb++) {
              const uint32_t st = stage(STQ), fb = full + 8 * p.stage;
              tma_load_2d(st, &tmX, kb * 64, m * 128, fb);
              tma_load_3d(st + 16384, &tmQ, 0, kb * 64, k * 3, fb);
              pipe_adv<NS>(p);
              if (type == T_Q && kb == 8) next = fetch();
            }
          if (type != T_Q) {
            const size_t blk = ((size_t)m * 4 * 96 + k * 3) * 5120;
            kph ^= 1;
            mbar_wait(kvrdy, rph); rph ^= 1;
            next = fetch();
            fence_proxy_async_global();
#pragma unroll 1
            for (int w = type == T_A ? 0 : 2; w < 4; w++) {
              const uint32_t st = stage(2 * SEGB), fb = full + 8 * p.stage;
              for (int sg = 0; sg < 2; sg++) ld_kv(st + sg * SEGB, (w < 2 ? a.kg : a.vg) + blk + (size_t)(2 * (w & 1) + sg) * (96 * 5120), SEGB, fb);
              pipe_adv<NS>(p);
            }
          }
        } else {
          const int nn = wide ? 2 : 5, nb = wide ? 5 : 2, nt = k % nn, nkb = 96 / sc.ks[m], k0 = (k / nn) * nkb;
          const Pipe p0 = p;
          for (int kb = 0; kb < nkb; kb++) {
            if (wide && kb < NS && p.stage >= 2) { mbar_wait(barKfree, kph); mbar_wait(barKfree + 8, kph); }
            const uint32_t st = stage(16384 + nb * 8192), fb = full + 8 * p.stage;
            tma_load_3d(st + 16384, wide ? &tmWo5 : &tmWo2, 0, (k0 + kb) * 64, nt * nb, fb);
            if (kb >= NS) ld_o(st, a.o + ((size_t)m * 96 + k0 + kb) * 16384, 16384, fb);
            pipe_adv<NS>(p);
            if (kb == NS - 1 || (kb == nkb - 1 && nkb < NS)) {
              wait_ge(arena + C_QA + m * 4, 64, m < 14 ? a.nap : 32);
              fence_proxy_async_global();
              Pipe q = p0;
#pragma unroll 1
              for (int i = 0; i <= kb; i++) { ld_o(sb + q.stage * (wide ? STO : STQ), a.o + ((size_t)m * 96 + k0 + i) * 16384, 16384, full + 8 * q.stage); pipe_adv<NS>(q); }
            }
          }
          next = fetch();
          for (int w = wide ? -(int)((2 - p.stage) & 3) : 0; w < 2; w++) { mbar_wait(empty + 8 * p.stage, p.phase); mbar_arrive(full + 8 * p.stage); pipe_adv<NS>(p); }
          kph ^= wide;
        }
      }
    } } else if (warp < 11) { if (elect_one()) {
      const int w = warp - 9;
      uint32_t sph = 0;
      [[maybe_unused]] int nlog = 0;
#ifdef TIMELINE
      if (w == 0) { unsigned long long* lg = g_log + (((tl >= 12) * 132 + blockIdx.x) * 64 + nlog++) * 2; lg[0] = T_END << 16; lg[1] = gtime(); lg[2] = ~0ull; }
#endif
      while (true) {
        const uint32_t it = next_item();
        const int type = (it >> 16) & 255, m = (it >> 8) & 255, k = it & 255;
        const uint32_t slot = mp.stage;
        pipe_adv<2>(mp);
        if (type == T_END) break;
        mbar_wait(staged + 16 * w + 8 * slot, (sph >> slot) & 1); sph ^= 1u << slot;
        mbar_arrive(mempty + 8 * slot);
#ifdef TIMELINE
        if (w == 0 && nlog < 63) { unsigned long long* lg = g_log + (((tl >= 12) * 132 + blockIdx.x) * 64 + nlog++) * 2; lg[0] = (type << 16) | (m << 8) | k; lg[1] = gtime(); lg[2] = ~0ull; }
#endif
        if (type == T_L) continue;
        if (type == T_QA || type == T_A) {
          for (int jj = 0; jj < 3; jj++) bulk_s2g(a.o + ((size_t)m * 96 + k * 3 + jj) * 16384 + w * 8192, sb + OFF_K + w * 2 * SEGB + jj * 8192, 8192);
          bulk_commit();
          bulk_wait<0>();
          mbar_arrive(barKfree + 8 * w);
        } else if (type == T_OB || type == T_OS) {
          const bool wide = type == T_OB;
          const int nn = wide ? 2 : 5, nb = wide ? 5 : 2;
          const uint32_t own = wide ? 2 + w : ((it >> 24) + 96 / sc.ks[m] + w) % NS;
          bulk_s2g(a.part + ((size_t)((k / nn) * 32 + m * 2 + w) * 10 + (k % nn) * nb) * 8192, sb + own * (wide ? STO : STQ), nb * 8192);
          bulk_commit();
          bulk_wait<0>();
          mbar_arrive(empty + 8 * own);
          if (wide && w) { mbar_arrive(barKfree); mbar_arrive(barKfree + 8); }
        }
        red_release_inc(arena + (type == T_Q ? C_Q : (type <= T_A ? C_QA : (type == T_P ? C_P : C_O))) + m * 4);
      }
    } } else if (elect_one()) {
      const uint64_t ef = policy_evict_first();
      uint32_t kph = 1;
      if (PF_WB && blockIdx.x >= 52) { prefetch_l2(pa.wb + (blockIdx.x - 52) * 32768, 32768); prefetch_l2(pa.wot + (blockIdx.x - 52) * 10240, 10240); }
      if (PF_WB > 1 && blockIdx.x >= 52) { prefetch_l2(a.xn + (blockIdx.x - 52) * 8192, 16384); prefetch_l2(a.xout + (blockIdx.x - 52) * 8192, 16384); }
      while (true) {
        const uint32_t it = next_item();
        const int type = (it >> 16) & 255, m = (it >> 8) & 255, k = it & 255;
        const uint32_t slot = mp.stage;
        pipe_adv<2>(mp);
        if (type == T_END) break;
        if (PF_XN && type == T_QA && m < 15) prefetch_l2(a.xq + ((m + 1) * 128 + k * 4) * cfg::DM, 5120);
        if (type == T_QA || type == T_A) {
          for (int spin = 0; spin < (1 << 21); spin++) {
            const uint4 f = ld_relaxed_v4(arena + prog_off(k, 0));
            if (min(min(f.x, f.y), f.z) >= (uint32_t)(4 * m + 4)) break;
            __nanosleep(m < 15 ? a.nap : a.nap2);
          }
          mbar_arrive(kvrdy);
          fence_proxy_async_global();
          const unsigned char* src = a.kg + ((size_t)m * 4 * 96 + k * 3) * 5120;
#pragma unroll 1
          for (int w = 0; w < 2; w++) {
            mbar_wait(barKfree + 8 * w, kph);
            if (type == T_A) { mbar_arrive(barK + 8 * w); continue; }
            mbar_expect_tx(barK + 8 * w, 2 * SEGB);
            for (int sg = 2 * w; sg < 2 * w + 2; sg++) { if (EF_KV) bulk_g2s_hint(sb + OFF_K + sg * SEGB, src + (size_t)sg * (96 * 5120), SEGB, barK + 8 * w, ef); else bulk_g2s(sb + OFF_K + sg * SEGB, src + (size_t)sg * (96 * 5120), SEGB, barK + 8 * w); }
          }
          kph ^= 1;
        } else if (type == T_OB) {
          mbar_wait(barKfree, kph); mbar_wait(barKfree + 8, kph);
          kph ^= 1;
        }
        mbar_arrive(mempty + 8 * slot);
      }
      if (blockIdx.x == gridDim.x - 1) asm volatile("griddepcontrol.wait;" ::: "memory");
    }
    return;
  }
  asm volatile("setmaxnreg.inc.sync.aligned.u32 232;");
  const int wg = warp >> 2, wi = warp & 3;
  const int g = lane >> 2, q4 = lane & 3;
  asm volatile("griddepcontrol.launch_dependents;" ::: "memory");
  Pipe p{0, 0};
  uint32_t kph = 0;
  auto own_slot = [&]() -> uint32_t {
    const uint32_t sA = p.stage, phA = p.phase; pipe_adv<NS>(p);
    const uint32_t sB = p.stage, phB = p.phase; pipe_adv<NS>(p);
    if (wi == 0) mbar_wait(full + 8 * (wg ? sA : sB), wg ? phA : phB);
    mbar_wait(full + 8 * (wg ? sB : sA), wg ? phB : phA);
    mbar_arrive_if((threadIdx.x & 127) == 0, empty + 8 * (wg ? sA : sB));
    return wg ? sB : sA;
  };
  while (true) {
    const uint32_t it = __shfl_sync(0xffffffffu, next_item(), 0);
    const int type = (it >> 16) & 255, m = (it >> 8) & 255, k = it & 255;
    mbar_arrive_if(lane == 0, mempty + 8 * mp.stage);
    const uint32_t done = staged + 16 * wg + 8 * mp.stage;
    pipe_adv<2>(mp);
    if (type == T_END) break;
    if (type == T_P) {
      prep_body(k, pa);
      __syncwarp();
      mbar_arrive_if(lane == 0, done);
      continue;
    }
    if (type == T_L) {
      const int nr = sc.lrows[m], np = sc.ks[m];
      const uint32_t po = (lane >> 4) * 1024 + warp * 128 + ((((lane >> 1) & 7) ^ warp) << 4) + (lane & 1) * 8;
#pragma unroll 1
      for (int r = 0; r < nr; r++) {
        uint2 xw[1][5]; float s[20];
#pragma unroll
        for (int i = 0; i < 20; i++) s[i] = 0.f;
#pragma unroll 1
        for (int q0 = 0; q0 <= np; q0 += 4) {
          const uint32_t st = sb + p.stage * STQ;
          mbar_wait(full + 8 * p.stage, p.phase);
          if (q0 == 0) static_for<0, 5>([&](auto I) { xw[0][I.value] = lds64_i<I.value * 256>(st + warp * 1280 + lane * 8); });
#pragma unroll 1
          for (int q = q0 ? 0 : 1; q < min(4, np + 1 - q0); q++)
            static_for<0, 5>([&](auto I) {
              constexpr int i = I.value;
              const uint2 t = lds64_i<i * 2048>(st + q * 10240 + po);
              s[4 * i] += bf_lo(t.x); s[4 * i + 1] += bf_hi(t.x); s[4 * i + 2] += bf_lo(t.y); s[4 * i + 3] += bf_hi(t.y);
            });
          bar_sync(3 + wg, 128);
          mbar_arrive_if((threadIdx.x & 127) == 0, empty + 8 * p.stage);
          pipe_adv<NS>(p);
        }
        const int row = (m * 16 + k * nr + r) * 8 + warp;
#pragma unroll
        for (int i = 0; i < 5; i++) {
          bf16r2(s[4 * i], s[4 * i + 1]); bf16r2(s[4 * i + 2], s[4 * i + 3]);
          xw[0][i] = make_uint2(pack_bf16(bf_lo(xw[0][i].x) + s[4 * i], bf_hi(xw[0][i].x) + s[4 * i + 1]), pack_bf16(bf_lo(xw[0][i].y) + s[4 * i + 2], bf_hi(xw[0][i].y) + s[4 * i + 3]));
          *(uint2*)(a.xout + (size_t)row * cfg::DM + i * 128 + lane * 4) = xw[0][i];
        }
        ln_rows<1>(xw, row, lane, a.xn, nullptr);
      }
      __syncwarp();
      mbar_arrive_if(lane == 0, done);
      continue;
    }
    if (type >= T_OB) {
      const int nkb = 96 / sc.ks[m];
      if (type == T_OB) {
        float a0[96], a1[64];
        tr_mainloop<192, 128>(a0, a1, p, sb, full, empty, nkb, wg);
        while (p.stage != 2) { if (wi == 0) mbar_wait(full + 8 * p.stage, p.phase); mbar_arrive_if((threadIdx.x & 127) == 0, empty + 8 * p.stage); pipe_adv<NS>(p); }
        const uint32_t st = sb + own_slot() * STO;
        stage_tiles<192>(a0, st, wi, lane); stage_tiles<128>(a1, st + 24576, wi, lane);
      } else {
        float a0[64], a1[1];
        tr_mainloop<128, 0>(a0, a1, p, sb, full, empty, nkb, wg);
        stage_tiles<128>(a0, sb + own_slot() * STQ, wi, lane);
      }
      fence_proxy_async();
      __syncwarp();
      mbar_arrive_if(lane == 0, done);
      continue;
    }
    uint32_t qf[12][4];
    uint4* qp = a.qs + ((size_t)((m & 7) * 32 + k) * 12) * 256 + threadIdx.x;
    if (type != T_A) {
      float acc[96], a1[1];
      tr_mainloop<192, 0>(acc, a1, p, sb, full, empty, 10, wg);
#pragma unroll
      for (int i = 0; i < 12; i++) {
        qf[i][0] = pack_bf16(acc[8 * i], acc[8 * i + 1]); qf[i][1] = pack_bf16(acc[8 * i + 2], acc[8 * i + 3]);
        qf[i][2] = pack_bf16(acc[8 * i + 4], acc[8 * i + 5]); qf[i][3] = pack_bf16(acc[8 * i + 6], acc[8 * i + 7]);
      }
      if (type == T_Q) {
#pragma unroll
        for (int i = 0; i < 12; i++) qp[i * 256] = make_uint4(qf[i][0], qf[i][1], qf[i][2], qf[i][3]);
        __syncwarp();
        mbar_arrive_if(lane == 0, done);
        continue;
      }
    } else {
#pragma unroll
      for (int i = 0; i < 12; i++) { const uint4 v = __ldcg(qp + i * 256); qf[i][0] = v.x; qf[i][1] = v.y; qf[i][2] = v.z; qf[i][3] = v.w; }
    }
    const uint32_t ost = sb + OFF_K + wg * 2 * SEGB;
    const bool second = wi >= 2;
    uint32_t pf[5][4];
    {
      float sa[20], sb2[20];
      uint32_t kbase = ost, kslot = 0;
      if (type == T_A) { kslot = own_slot(); kbase = sb + kslot * STQ; } else mbar_wait(barK + 8 * wg, kph);
      if (STAG && wg) bar_sync(1, 256);
      wgmma_fence();
#pragma unroll
      for (int i = 0; i < 12; i++) {
        wgmma_rs_n40<0>(sa, qf[i][0], qf[i][1], qf[i][2], qf[i][3], make_desc(kbase + i * 1280, 640, 128, 0), i != 0);
        wgmma_rs_n40<0>(sb2, qf[i][0], qf[i][1], qf[i][2], qf[i][3], make_desc(kbase + SEGB + i * 1280, 640, 128, 0), i != 0);
      }
      wgmma_commit();
      wgmma_wait<0>();
      if (STAG && !wg) bar_arrive(1, 256);
      mbar_arrive_if(type == T_A && (threadIdx.x & 127) == 0, empty + 8 * kslot);
      const float cs = 0.07216878364870322f * 1.4426950408889634f;
      const int r0 = 16 * (wi & 1) + g, r1 = r0 + 8;
      float m0 = -INFINITY, m1 = -INFINITY;
#pragma unroll
      for (int n = 0; n < 5; n++) {
#pragma unroll
        for (int e = 0; e < 2; e++) {
          const int key = 8 * n + 2 * q4 + e;
          float x = second ? sb2[4 * n + e] : sa[4 * n + e], y = second ? sb2[4 * n + 2 + e] : sa[4 * n + 2 + e];
          if (n < 4) { if (key > r0) x = -INFINITY; if (key > r1) y = -INFINITY; }
          sa[4 * n + e] = x; sa[4 * n + 2 + e] = y;
          m0 = fmaxf(m0, x); m1 = fmaxf(m1, y);
        }
      }
      m0 = fmaxf(m0, __shfl_xor_sync(0xffffffffu, m0, 1)); m1 = fmaxf(m1, __shfl_xor_sync(0xffffffffu, m1, 1));
      m0 = fmaxf(m0, __shfl_xor_sync(0xffffffffu, m0, 2)); m1 = fmaxf(m1, __shfl_xor_sync(0xffffffffu, m1, 2));
      float s0 = 0.f, s1 = 0.f;
#pragma unroll
      for (int n = 0; n < 5; n++) {
#pragma unroll
        for (int e = 0; e < 2; e++) {
          sa[4 * n + e] = ex2f((sa[4 * n + e] - m0) * cs); sa[4 * n + 2 + e] = ex2f((sa[4 * n + 2 + e] - m1) * cs);
          s0 += sa[4 * n + e]; s1 += sa[4 * n + 2 + e];
        }
      }
      s0 += __shfl_xor_sync(0xffffffffu, s0, 1); s1 += __shfl_xor_sync(0xffffffffu, s1, 1);
      s0 += __shfl_xor_sync(0xffffffffu, s0, 2); s1 += __shfl_xor_sync(0xffffffffu, s1, 2);
      const float i0 = rcpf(s0), i1 = rcpf(s1);
#pragma unroll
      for (int n = 0; n < 5; n++) {
        const uint32_t x = pack_bf16(sa[4 * n] * i0, sa[4 * n + 1] * i0), y = pack_bf16(sa[4 * n + 2] * i1, sa[4 * n + 3] * i1);
        if (n < 4) {
          pf[n >> 1][2 * (n & 1)] = second ? 0u : x; pf[n >> 1][2 * (n & 1) + 1] = second ? 0u : y;
          pf[2 + (n >> 1)][2 * (n & 1)] = second ? x : 0u; pf[2 + (n >> 1)][2 * (n & 1) + 1] = second ? y : 0u;
        } else {
          pf[4][0] = second ? 0u : x; pf[4][1] = second ? 0u : y; pf[4][2] = second ? x : 0u; pf[4][3] = second ? y : 0u;
        }
      }
    }
    {
      float o[96];
#pragma unroll
      for (int i = 0; i < 5; i++) { PIN(pf[i][0]); PIN(pf[i][1]); PIN(pf[i][2]); PIN(pf[i][3]); }
      const uint32_t own = own_slot(), vbase = sb + own * STQ;
      wgmma_fence();
#pragma unroll
      for (int i = 0; i < 5; i++)
        wgmma_rs_n192<1>(o, pf[i][0], pf[i][1], pf[i][2], pf[i][3], i < 4 ? make_desc(vbase + (i >> 1) * SEGB + (i & 1) * 256, 128, 640, 0) : make_desc(vbase + 512, SEGB, 640, 0), i != 0);
      wgmma_commit();
      if (type == T_A) mbar_wait(barK + 8 * wg, kph);
      kph ^= 1;
      wgmma_wait<0>();
      mbar_arrive_if((threadIdx.x & 127) == 0, empty + 8 * own);
      stage_tiles<192>(o, ost, wi, lane);
      fence_proxy_async();
      __syncwarp();
      mbar_arrive_if(lane == 0, done);
    }
  }
}
namespace bf {
constexpr int NS = 4, STAGE = 16384 + 32768;
constexpr int PIECE = 20480;
constexpr int OFF_PHI = 0, OFF_V = 40960, OFF_KV = 65536;
constexpr int OFF_OST = 5 * PIECE;
constexpr int OFF_WOT = 6 * PIECE;
constexpr int OFF_BAR = OFF_WOT + 102400;
constexpr int SMEM = OFF_BAR + 256;
static_assert(NS * STAGE <= OFF_BAR && SMEM <= 232448, "smem");
constexpr int KVACC = 32 * 5 * 1024;
struct Args {
  const unsigned char *wb, *wot;
  unsigned char *kvacc, *o2;
  const bf16* xin;
  bf16* xout;
  unsigned* go;
  const void* prep;
  const bf16 *pf0, *pf1;
  int pfn, pfns, pfwait;
  int tl;
};
}
__device__ __forceinline__ void hedgehog_features(float (&x)[2][5], uint32_t (&w)[2][5]) {
  const float L = 1.4426950408889634f;
  float mx[2], mn[2], sp[2], sn[2], pos[2][5], neg[2][5];
#pragma unroll
  for (int r = 0; r < 2; r++) {
    mx[r] = fmaxf(fmaxf(fmaxf(x[r][0], x[r][1]), fmaxf(x[r][2], x[r][3])), x[r][4]);
    mn[r] = fminf(fminf(fminf(x[r][0], x[r][1]), fminf(x[r][2], x[r][3])), x[r][4]);
  }
#pragma unroll
  for (int o = 1; o < 4; o <<= 1)
#pragma unroll
    for (int r = 0; r < 2; r++) {
      const uint32_t t = __shfl_xor_sync(0xffffffffu, __byte_perm(__float_as_uint(mn[r]), __float_as_uint(mx[r]), 0x7632), o);
      mx[r] = fmaxf(mx[r], bf_hi(t)); mn[r] = fminf(mn[r], bf_lo(t));
    }
#pragma unroll
  for (int r = 0; r < 2; r++) {
#pragma unroll
    for (int i = 0; i < 5; i++) { pos[r][i] = ex2f((x[r][i] - mx[r]) * L); neg[r][i] = ex2f((mn[r] - x[r][i]) * L); }
    sp[r] = ((pos[r][0] + pos[r][1]) + (pos[r][2] + pos[r][3])) + pos[r][4];
    sn[r] = ((neg[r][0] + neg[r][1]) + (neg[r][2] + neg[r][3])) + neg[r][4];
  }
#pragma unroll
  for (int o = 1; o < 4; o <<= 1)
#pragma unroll
    for (int r = 0; r < 2; r++) { sp[r] += __shfl_xor_sync(0xffffffffu, sp[r], o); sn[r] += __shfl_xor_sync(0xffffffffu, sn[r], o); }
#pragma unroll
  for (int r = 0; r < 2; r++) {
    const float ip = rcpf(sp[r]), in_ = rcpf(sn[r]);
    w[r][0] = pack_bf16(pos[r][0] * ip, pos[r][1] * ip); w[r][1] = pack_bf16(pos[r][2] * ip, pos[r][3] * ip);
    w[r][2] = pack_bf16(neg[r][0] * in_, neg[r][1] * in_); w[r][3] = pack_bf16(neg[r][2] * in_, neg[r][3] * in_);
    w[r][4] = pack_bf16(pos[r][4] * ip, neg[r][4] * in_);
  }
}
__device__ __forceinline__ void bulk_g2s_mc(uint32_t dst, const void* src, uint32_t bytes, uint32_t mb) {
  asm volatile("cp.async.bulk.shared::cluster.global.mbarrier::complete_tx::bytes.multicast::cluster [%0], [%1], %2, [%3], %4;"
               :: "r"(dst), "l"(src), "r"(bytes), "r"(mb), "h"((unsigned short)3) : "memory");
}
__device__ __forceinline__ void mbar_arrive_remote_if(bool c, uint32_t b) {
  asm volatile("{\n.reg .pred p;\nsetp.ne.u32 p, %1, 0;\n@p mbarrier.arrive.shared::cluster.b64 _, [%0];\n}" :: "r"(b), "r"((uint32_t)c) : "memory");
}

__global__ void __cluster_dims__(2, 1, 1) __launch_bounds__(384, 1) blayer_kernel(const __grid_constant__ CUtensorMap tmA, const __grid_constant__ bf::Args a) {
  using namespace bf;
  [[maybe_unused]] const int tl = a.tl;
  extern __shared__ __align__(1024) unsigned char smem_raw[];
  const uint32_t sb = smem_u32(smem_raw);
  const int warp = __shfl_sync(0xffffffffu, (int)threadIdx.x >> 5, 0), lane = threadIdx.x & 31;
  const uint32_t full = sb + OFF_BAR, empty = full + 8 * NS, full2 = empty + 8 * NS, empty2 = full2 + 64, barW = empty2 + 16, drained = barW + 8, staged = drained + 8, freeb = staged + 8;
  const int rank = blockIdx.x & 1, u = (blockIdx.x >> 1) & 7, mp = blockIdx.x >> 4;
  const int m = 2 * mp + rank;
  const int m2 = 2 * mp + (u & 1), ns = (u & ~1) + rank;
  const uint32_t dpeer = mapa_u32(sb, rank ^ 1) - sb;
  unsigned* cntO = (unsigned*)(a.kvacc + KVACC);
  if (threadIdx.x == 0) {
    for (int i = 0; i < NS; i++) { mbar_init(full + 8 * i, 1); mbar_init(empty + 8 * i, 4); }
    for (int i = 0; i < 8; i++) mbar_init(full2 + 8 * i, 1);
    mbar_init(empty2, 2); mbar_init(empty2 + 8, 2);
    mbar_init(barW, 1); mbar_init(drained, 1); mbar_init(staged, 8); mbar_init(freeb, 2);
    asm volatile("fence.mbarrier_init.release.cluster;" ::: "memory");
  }
  __syncthreads();
  asm volatile("barrier.cluster.arrive.relaxed.aligned; barrier.cluster.wait.aligned;" ::: "memory");
  if (warp >= 8) {
    asm volatile("setmaxnreg.dec.sync.aligned.u32 40;");
    if (warp == 8) { if (elect_one()) {
      const unsigned char* wsrc = a.wb + (size_t)u * 327680 + rank * 16384;
      if (a.prep) wait_ge(a.prep, 64);
      fence_proxy_async_global();
      for (int kb = 0; kb < NS; kb++) {
        mbar_expect_tx(full + 8 * kb, STAGE);
        bulk_g2s_mc(sb + kb * STAGE + 16384 + rank * 16384, wsrc + kb * 32768, 16384, full + 8 * kb);
      }
      asm volatile("griddepcontrol.wait;" ::: "memory");
      TL_BEGIN0(tl);
      if (blockIdx.x == 0) *a.go = 0;
      for (int kb = 0; kb < NS; kb++) tma_load_2d(sb + kb * STAGE, &tmA, kb * 64, m * 128, full + 8 * kb);
      if (m == 0) prefetch_l2(a.kvacc + u * (KVACC / 8), KVACC / 8);
#pragma unroll 1
      for (int kb = NS; kb < 10; kb++) {
        const uint32_t s = kb & 3, st = sb + s * STAGE, fb = full + 8 * s;
        mbar_wait(empty + 8 * s, ((kb >> 2) - 1) & 1);
        mbar_expect_tx(fb, STAGE);
        tma_load_2d(st, &tmA, kb * 64, m * 128, fb);
        bulk_g2s_mc(st + 16384 + rank * 16384, wsrc + kb * 32768, 16384, fb);
      }
      for (int i = 0; i < 6; i++) mbar_expect_tx(full2 + 8 * i, PIECE);
      mbar_wait(drained, 0);
      mbar_expect_tx(barW, 102400);
      bulk_g2s(sb + OFF_WOT, a.wot + (size_t)ns * 102400, 102400, barW);
      mbar_wait(staged, 0);
      bulk_s2g(a.o2 + (size_t)(m * 8 + u) * PIECE, sb + OFF_OST, PIECE);
      bulk_commit();
      bulk_wait<0>();
      mbar_arrive(freeb); mbar_arrive_remote_if(true, freeb + dpeer);
      red_release_inc(cntO + m);
      wait_ge(cntO + m2, 8, 20);
      mbar_wait(freeb, 0);
      fence_proxy_async_global();
      const unsigned char* osrc = a.o2 + (size_t)m2 * 8 * PIECE;
      for (int i = 0; i < 6; i++) bulk_g2s_mc(sb + i * PIECE + rank * (PIECE / 2), osrc + i * PIECE + rank * (PIECE / 2), PIECE / 2, full2 + 8 * i);
      for (int i = 0; i < 2; i++) {
        mbar_wait(empty2 + 8 * i, 0);
        mbar_expect_tx(full2 + 8 * (6 + i), PIECE);
        bulk_g2s(sb + i * PIECE, osrc + (6 + i) * PIECE, PIECE, full2 + 8 * (6 + i));
      }
    } } else if (warp == 9 && a.pf0) { if (elect_one()) {
      if (a.pfwait) asm volatile("griddepcontrol.wait;" ::: "memory");
      constexpr uint32_t CH = 2048;
      for (int i = 0; i < a.pfn; i++) {
        prefetch_l2((const unsigned char*)a.pf0 + (i * 128 + blockIdx.x) * CH, CH); prefetch_l2((const unsigned char*)a.pf1 + (i * 128 + blockIdx.x) * CH, CH);
        __nanosleep(a.pfns);
      }
    } }
    return;
  }
  asm volatile("setmaxnreg.inc.sync.aligned.u32 232;");
  const int wg = warp >> 2, wi = warp & 3;
  const int q4 = lane & 3;
  const bool lead = (threadIdx.x & 127) == 0;
  float acc[128];
  {
#pragma unroll 1
    for (int kb = 0; kb < 10; kb++) {
      const uint32_t s = kb & 3, st = sb + s * STAGE;
      mbar_wait(full + 8 * s, (kb >> 2) & 1);
      wgmma_fence();
#pragma unroll
      for (int kk = 0; kk < 4; kk++) wgmma_n256<0, 1>(acc, desc_kmajor(st + wg * 8192 + kk * 32), make_desc(st + 16384 + kk * 8192, 4096, 128, 0), (kb | kk) != 0);
      wgmma_commit();
      if (kb > 0 && kb < 7) { wgmma_wait<1>(); const uint32_t e = empty + 8 * ((kb - 1) & 3); mbar_arrive_if(lead, e); mbar_arrive_remote_if(lead, e + dpeer); }
    }
    wgmma_wait<0>();
    bar_sync(1, 256);
    mbar_arrive_if(threadIdx.x == 0, drained);
  }
  TL2((tl >= 12 ? 128 : 0) + 32 + 0);
  const uint32_t srow = (wg * 64 + wi * 16 + (lane & 15)) * 16 + (lane >> 4) * 2048;
  auto features = [&](auto T0, auto HH, uint32_t (&w)[2][5]) {
    constexpr int t = T0.value + 5 * (HH.value >> 1), o = (HH.value & 1) ? 3 : 0, e = HH.value & 1;
    float x[2][5];
#pragma unroll
    for (int r = 0; r < 2; r++) {
      x[r][0] = acc[4 * (t + o) + 2 * r]; x[r][1] = acc[4 * (t + o) + 2 * r + 1]; x[r][2] = acc[4 * (t + o + 1) + 2 * r]; x[r][3] = acc[4 * (t + o + 1) + 2 * r + 1];
      bf16r2(x[r][0], x[r][1]); bf16r2(x[r][2], x[r][3]);
    }
    x[0][4] = acc[4 * (t + 2) + e]; x[1][4] = acc[4 * (t + 2) + 2 + e];
    bf16r2(x[0][4], x[1][4]);
    hedgehog_features(x, w);
  };
  static_for<0, 4>([&](auto HH) {
    constexpr int hh = HH.value, t = 20 + 3 * hh;
    const uint32_t one = q4 == ((hh & 1) ? 0 : 2) ? 0x3f80u : 0u;
    const uint32_t va = sb + OFF_V + hh * 6144 + srow;
    stsm_x4(va, pack_bf16(acc[4 * t], acc[4 * t + 1]), pack_bf16(acc[4 * t + 2], acc[4 * t + 3]), pack_bf16(acc[4 * t + 4], acc[4 * t + 5]), pack_bf16(acc[4 * t + 6], acc[4 * t + 7]));
    const bool pad = (q4 >= 2) != (hh & 1);
    stsm_x2(va + 4096, pad ? one : pack_bf16(acc[4 * t + 8], acc[4 * t + 9]), pad ? one : pack_bf16(acc[4 * t + 10], acc[4 * t + 11]));
    uint32_t w[2][5];
    features(IC<10>{}, HH, w);
    const uint32_t pa = sb + OFF_PHI + hh * 10240 + srow;
    stsm_x4(pa, w[0][0], w[1][0], w[0][1], w[1][1]);
    stsm_x4(pa + 4096, w[0][2], w[1][2], w[0][3], w[1][3]);
    stsm_x2(pa + 8192, w[0][4], w[1][4]);
  });
  fence_proxy_async();
  bar_sync(1, 256);
  TL2((tl >= 12 ? 128 : 0) + 32 + 1);
  {
    float d0[12], d1[12];
    const uint32_t pa = sb + OFF_PHI + wg * 20480, pv = sb + OFF_V + wg * 12288;
    wgmma_fence();
#pragma unroll
    for (int k = 0; k < 8; k++) {
      wgmma_n24<1, 1>(d0, make_desc(pa + k * 256, 128, 2048, 0), make_desc(pv + k * 256, 128, 2048, 0), k != 0);
      wgmma_n24<1, 1>(d1, make_desc(pa + 10240 + k * 256, 128, 2048, 0), make_desc(pv + 6144 + k * 256, 128, 2048, 0), k != 0);
    }
    wgmma_commit();
    wgmma_wait<0>();
    unsigned char* dst = a.kvacc + ((u * 4 + wg * 2) * 5 + 2 * wi) * 1024 + lane * 16;
    auto red4 = [&](bool on, unsigned char* p, float x, float y, float z) {
      asm volatile("{\n.reg .pred p;\nsetp.ne.u32 p, %4, 0;\n@p red.relaxed.gpu.global.add.v4.f32 [%0], {%1,%2,%3,%5};\n}" :: "l"(p), "f"(x), "f"(y), "f"(z), "r"((uint32_t)on), "f"(1.f) : "memory");
    };
    red4(wi < 3, dst, d0[0], d0[1], d0[4]); red4(wi < 3, dst + 512, d0[5], d0[8], d0[9]);
    red4(wi < 3, dst + 5120, d1[0], d1[1], d1[4]); red4(wi < 3, dst + 5632, d1[5], d1[8], d1[9]);
    red4(wi < 2, dst + 1024, d0[2], d0[3], d0[6]); red4(wi < 2, dst + 1536, d0[7], d0[10], d0[11]);
    red4(wi < 2, dst + 6144, d1[2], d1[3], d1[6]); red4(wi < 2, dst + 6656, d1[7], d1[10], d1[11]);
  }
  TL2((tl >= 12 ? 128 : 0) + 32 + 2);
  uint32_t qf[4][2][5];
  static_for<0, 4>([&](auto HH) { features(IC<0>{}, HH, qf[HH.value]); });
  uint4 xr[5];
#pragma unroll
  for (int i = 0; i < 5; i++) {
    const int c = lane + 32 * i;
    xr[i] = __ldcg((const uint4*)(a.xin + (size_t)(m2 * 128 + wg * 64 + wi * 16 + c / 10) * cfg::DM + ns * 80 + (c % 10) * 8));
  }
  {
    const unsigned char* src = a.kvacc + (u * 20 + warp) * 1024 + lane * 16;
    uint4 v[6];
    int spin = 0;
    while (true) {
      v[0] = ld_relaxed_v4_i<0>(src); v[1] = ld_relaxed_v4_i<512>(src); v[2] = ld_relaxed_v4_i<8192>(src); v[3] = ld_relaxed_v4_i<8704>(src);
      v[4] = ld_relaxed_v4_i<0>(src + (wg ? 0 : 16384)); v[5] = ld_relaxed_v4_i<512>(src + (wg ? 0 : 16384));
      const uint32_t c = (v[0].w & v[1].w & v[2].w) & (v[3].w & v[4].w & v[5].w);
      if (!__any_sync(0xffffffffu, (c & 0x41800000u) != 0x41800000u) || ++spin >= SPIN_LIMIT) break;
      __nanosleep(100);
    }
    const uint32_t kd = sb + OFF_KV + warp * 384 + lane * 4;
#pragma unroll
    for (int i = 0; i < 3; i++)
      if (i < 2 || wg == 0) {
        sts32(kd + i * 3072, pack_bf16(__uint_as_float(v[2 * i].x), __uint_as_float(v[2 * i].y)));
        sts32(kd + i * 3072 + 128, pack_bf16(__uint_as_float(v[2 * i].z), __uint_as_float(v[2 * i + 1].x)));
        sts32(kd + i * 3072 + 256, pack_bf16(__uint_as_float(v[2 * i + 1].y), __uint_as_float(v[2 * i + 1].z)));
      }
  }
  fence_proxy_async();
  bar_sync(1, 256);
  TL2((tl >= 12 ? 128 : 0) + 32 + 3);
  {
    float d[4][12];
    uint32_t zero = 0; PIN(zero);
#pragma unroll
    for (int hh = 0; hh < 4; hh++)
#pragma unroll
      for (int i = 0; i < 5; i++) { PIN(qf[hh][0][i]); PIN(qf[hh][1][i]); }
    wgmma_fence();
#pragma unroll
    for (int hh = 0; hh < 4; hh++) {
      const uint32_t kb = sb + OFF_KV + hh * 1920;
      wgmma_rs_n24<1>(d[hh], qf[hh][0][0], qf[hh][1][0], qf[hh][0][1], qf[hh][1][1], make_desc(kb, 384, 128, 0), 0);
      wgmma_rs_n24<1>(d[hh], qf[hh][0][2], qf[hh][1][2], qf[hh][0][3], qf[hh][1][3], make_desc(kb + 768, 384, 128, 0), 1);
      wgmma_rs_n24<1>(d[hh], qf[hh][0][4], qf[hh][1][4], zero, zero, make_desc(kb + 1536, 0, 128, 0), 1);
    }
    wgmma_commit();
    wgmma_wait<0>();
    uint32_t ow[4][6];
#pragma unroll
    for (int hh = 0; hh < 4; hh++) {
      const int zl = (lane & ~3) | ((hh & 1) ? 0 : 2);
      const float da = bf16r(bf16r(__shfl_sync(0xffffffffu, d[hh][8], zl)) + 1e-6f), db = bf16r(bf16r(__shfl_sync(0xffffffffu, d[hh][10], zl)) + 1e-6f);
#pragma unroll
      for (int n = 0; n < 3; n++) {
        bf16r2(d[hh][4 * n], d[hh][4 * n + 1]); bf16r2(d[hh][4 * n + 2], d[hh][4 * n + 3]);
        ow[hh][2 * n] = pack_bf16(__fdividef(d[hh][4 * n], da), __fdividef(d[hh][4 * n + 1], da));
        ow[hh][2 * n + 1] = pack_bf16(__fdividef(d[hh][4 * n + 2], db), __fdividef(d[hh][4 * n + 3], db));
      }
    }
#pragma unroll
    for (int p = 0; p < 2; p++) {
      const uint32_t oa = sb + OFF_OST + p * 10240 + srow;
      stsm_x4(oa, ow[2 * p][0], ow[2 * p][1], ow[2 * p][2], ow[2 * p][3]);
      stsm_x2(oa + 4096, q4 < 2 ? ow[2 * p][4] : ow[2 * p + 1][4], q4 < 2 ? ow[2 * p][5] : ow[2 * p + 1][5]);
      stsm_x4(oa + 6144, ow[2 * p + 1][0], ow[2 * p + 1][1], ow[2 * p + 1][2], ow[2 * p + 1][3]);
    }
    fence_proxy_async();
    __syncwarp();
    mbar_arrive_if(lane == 0, staged);
  }
  TL2((tl >= 12 ? 128 : 0) + 32 + 4);
  float c2[40];
  mbar_wait(barW, 0);
#pragma unroll 1
  for (int i = 0; i < 8; i++) {
    mbar_wait(full2 + 8 * i, 0);
    const uint32_t st = sb + (i < 6 ? i : i - 6) * PIECE + wg * 1024, wo = sb + OFF_WOT + i * 12800;
    wgmma_fence();
#pragma unroll
    for (int kk = 0; kk < 5; kk++) wgmma_n80<0, 1>(c2, make_desc(st + kk * 4096, 2048, 128, 0), make_desc(wo + kk * 2560, 1280, 128, 0), (i | kk) != 0);
    wgmma_commit();
    if (i == 1 || i == 2) { wgmma_wait<1>(); mbar_arrive_if(lead, empty2 + 8 * (i - 1)); }
  }
  wgmma_wait<0>();
  TL2((tl >= 12 ? 128 : 0) + 32 + 5);
  {
    bar_sync(1, 256);
    const uint32_t ost = sb + 2 * PIECE + warp * 3072;
#pragma unroll
    for (int v = 0; v < 10; v += 2)
      stsm_x4(ost + (lane & 15) * 176 + (v + (lane >> 4)) * 16, pack_bf16(c2[4 * v], c2[4 * v + 1]), pack_bf16(c2[4 * v + 2], c2[4 * v + 3]),
              pack_bf16(c2[4 * v + 4], c2[4 * v + 5]), pack_bf16(c2[4 * v + 6], c2[4 * v + 7]));
    __syncwarp();
#pragma unroll
    for (int i = 0; i < 5; i++) {
      const int c = lane + 32 * i, row = c / 10, chunk = c % 10;
      const uint4 y = lds128(ost + row * 176 + chunk * 16);
      const size_t off = (size_t)(m2 * 128 + wg * 64 + wi * 16 + row) * cfg::DM + ns * 80 + chunk * 8;
      const uint4 x = xr[i];
      *(uint4*)(a.xout + off) = make_uint4(pack_bf16(bf_lo(x.x) + bf_lo(y.x), bf_hi(x.x) + bf_hi(y.x)), pack_bf16(bf_lo(x.y) + bf_lo(y.y), bf_hi(x.y) + bf_hi(y.y)),
                                           pack_bf16(bf_lo(x.z) + bf_lo(y.z), bf_hi(x.z) + bf_hi(y.z)), pack_bf16(bf_lo(x.w) + bf_lo(y.w), bf_hi(x.w) + bf_hi(y.w)));
    }
  }
  TL_END(tl);
}
__device__ __align__(32768) unsigned char g_arena[AR_SIZE];
__device__ unsigned g_go[32];
__device__ __align__(1024) uint2 g_xh[2048 * 160];
__device__ __align__(1024) unsigned char g_k[64 * 96 * 5120], g_v[64 * 96 * 5120];
__device__ __align__(1024) bf16 g_o[2048 * 6144];
__device__ __align__(1024) uint4 g_qs[8 * 32 * 12 * 256];
__device__ __align__(1024) bf16 g_xn[2048 * 640], g_xn2[2048 * 640], g_xa[2048 * 640], g_xb[2048 * 640];
__device__ __align__(1024) bf16 g_part[24 * 2048 * 640];
__device__ __align__(1024) bf16 g_wb[2048 * 640], g_wot[640 * 640], g_pq[2048 * 640];
__device__ __align__(1024) float g_kvacc[bf::KVACC / 4 + 64];

typedef CUresult (*EncodeFn)(CUtensorMap*, CUtensorMapDataType, cuuint32_t, void*, const cuuint64_t*, const cuuint64_t*, const cuuint32_t*,
                             const cuuint32_t*, CUtensorMapInterleave, CUtensorMapSwizzle, CUtensorMapL2promotion, CUtensorMapFloatOOBfill);
static EncodeFn g_encode = nullptr;
static CUtensorMap make_map(const void* p, uint64_t cols, uint64_t rows, uint32_t bc, uint32_t br, bool swz = true) {
  CUtensorMap m;
  cuuint64_t dims[2] = {cols, rows}, strides[1] = {cols * 2};
  cuuint32_t box[2] = {bc, br}, es[2] = {1, 1};
  g_encode(&m, CU_TENSOR_MAP_DATA_TYPE_BFLOAT16, 2, const_cast<void*>(p), dims, strides, box, es, CU_TENSOR_MAP_INTERLEAVE_NONE,
           swz ? CU_TENSOR_MAP_SWIZZLE_128B : CU_TENSOR_MAP_SWIZZLE_NONE, CU_TENSOR_MAP_L2_PROMOTION_L2_256B, CU_TENSOR_MAP_FLOAT_OOB_FILL_NONE);
  return m;
}
static CUtensorMap make_map3(const void* p, uint64_t cols, uint64_t rows, uint32_t nb) {
  CUtensorMap m;
  cuuint64_t dims[3] = {64, rows, cols / 64}, strides[2] = {cols * 2, 128};
  cuuint32_t box[3] = {64, 64, nb}, es[3] = {1, 1, 1};
  g_encode(&m, CU_TENSOR_MAP_DATA_TYPE_BFLOAT16, 3, const_cast<void*>(p), dims, strides, box, es, CU_TENSOR_MAP_INTERLEAVE_NONE,
           CU_TENSOR_MAP_SWIZZLE_128B, CU_TENSOR_MAP_L2_PROMOTION_L2_256B, CU_TENSOR_MAP_FLOAT_OOB_FILL_NONE);
  return m;
}
template <class T> static T* sym(const T& s) { void* p = nullptr; cudaGetSymbolAddress(&p, s); return (T*)p; }

struct Ptrs {
  unsigned char *arena, *k, *v; bf16 *o, *xn, *xa, *xb, *wb, *wot, *pq; float *part, *kvacc; uint2* xh; uint4* qs; bf16* xn2; unsigned* go;
};

static tr::Sched make_sched(int layer, const char* str, const int* ks, const int* lr) {
  using namespace tr;
  Sched s = {};
  int n = 0;
  for (int b = 0; b < 16; b++) { s.ks[b] = (uint8_t)abs(ks[b]); s.wide[b] = ks[b] > 0; s.lrows[b] = (uint8_t)lr[b]; }
  for (const char* p = str; *p;) {
    if (*p == ' ') { p++; continue; }
    const char c = *p++;
    char* e;
    const int b = (int)strtol(p, &e, 10); p = e;
    int first = 0, cnt = c == 'o' ? s.ks[b] * (s.wide[b] ? 2 : 5) : (c == 'l' ? 16 / lr[b] : 32);
    if (*p == '.') { first = (int)strtol(p + 1, &e, 10); cnt = (int)strtol(e + 1, &e, 10); p = e; }
    const int type = c == 'a' ? T_QA : (c == 'q' ? T_Q : (c == 't' ? T_A : (c == 'l' ? T_L : (c == 'p' ? T_P : (s.wide[b] ? T_OB : T_OS)))));
    if (type == T_P && layer > 0) continue;
    for (int i = 0; i < cnt && n < MAXITEMS - 1; i++) s.item[n++] = (uint16_t)((type << 11) | (b << 7) | (first + i));
  }
  s.n = n; s.item[n] = T_END << 11;
  return s;
}
static tr::Sched sched_of(int layer) {
  const char* str = "q13 q14 a0 q15 a1 o0 p0.0.16 o1 a2 p0.16.16 a3 o2 a4 o3 a5 o4 l0 a6 o5 l1 a7 o6 l2 a8 o7 l3 a9 o8 l4 a10 o9 l5 a11.0.24 o10 a11.24.8 a12 l6 o11 l7 t13 o12 t14 t15 o14 o13 l10 o15 l9 l14 l11 l8 l12 l13 l15";
  int ks[16] = {2, 2, 2, 2, 2, 3, 2, 3, 2, 2, 2, 3, 4, -6, -6, -12}, lr[16] = {4, 4, 4, 4, 4, 4, 4, 4, 4, 1, 4, 1, 1, 1, 1, 1};
#ifdef TUNE
  if (getenv("SCHED")) str = getenv("SCHED");
  if (layer == 0 && getenv("SCHED0")) str = getenv("SCHED0");
  if (const char* p = getenv("KS")) for (int b = 0; b < 16; b++) { char* e; ks[b] = (int)strtol(p, &e, 10); p = e; }
  if (const char* p = getenv("LR")) for (int b = 0; b < 16; b++) { char* e; lr[b] = (int)strtol(p, &e, 10); p = e; }
#endif
  return make_sched(layer, str, ks, lr);
}
#ifndef TRAIL_GRID
#define TRAIL_GRID 132
#endif
#ifndef PDL_LN
#define PDL_LN 0
#endif
#ifndef PDL_CH
#define PDL_CH 1
#endif
#ifndef PDL_B
#define PDL_B 1
#endif
#ifndef PF_A
#define PF_A 1
#endif
#ifndef PF_B
#define PF_B 1
#endif
extern "C" void kernel_launch(void* const* d_in, const int* in_sizes, int n_in, void* d_out, int out_size) {
  const bf16* x = (const bf16*)d_in[0];
  const bf16* mem0 = (const bf16*)d_in[1];
  const bf16 *Wq = (const bf16*)d_in[2], *Wk = (const bf16*)d_in[3], *Wv = (const bf16*)d_in[4], *Wo = (const bf16*)d_in[5];
  const bf16 *wqkv = (const bf16*)d_in[8], *wphi = (const bf16*)d_in[9], *wo = (const bf16*)d_in[10];
  bf16* out = (bf16*)d_out;
  static Ptrs P; static bool init = false;
  if (!init) {
    void* fn = nullptr; cudaDriverEntryPointQueryResult qr;
    cudaGetDriverEntryPoint("cuTensorMapEncodeTiled", &fn, cudaEnableDefault, &qr);
    g_encode = (EncodeFn)fn;
    void* p;
    cudaGetSymbolAddress(&p, g_arena); P.arena = (unsigned char*)p;
    cudaGetSymbolAddress(&p, g_k); P.k = (unsigned char*)p;   cudaGetSymbolAddress(&p, g_v); P.v = (unsigned char*)p;
    cudaGetSymbolAddress(&p, g_o); P.o = (bf16*)p;
    cudaGetSymbolAddress(&p, g_xn); P.xn = (bf16*)p;
    cudaGetSymbolAddress(&p, g_xa); P.xa = (bf16*)p;   cudaGetSymbolAddress(&p, g_xb); P.xb = (bf16*)p;
    cudaGetSymbolAddress(&p, g_wb); P.wb = (bf16*)p;   cudaGetSymbolAddress(&p, g_wot); P.wot = (bf16*)p;
    cudaGetSymbolAddress(&p, g_pq); P.pq = (bf16*)p;   cudaGetSymbolAddress(&p, g_part); P.part = (float*)p;
    cudaGetSymbolAddress(&p, g_kvacc); P.kvacc = (float*)p;
    cudaGetSymbolAddress(&p, g_xh); P.xh = (uint2*)p;
    cudaGetSymbolAddress(&p, g_go); P.go = (unsigned*)p;
    cudaGetSymbolAddress(&p, g_qs); P.qs = (uint4*)p;
    cudaGetSymbolAddress(&p, g_xn2); P.xn2 = (bf16*)p;
    cudaFuncSetAttribute(chain_kernel, cudaFuncAttributeMaxDynamicSharedMemorySize, ch::SMEM);
    cudaFuncSetAttribute(trail_kernel, cudaFuncAttributeMaxDynamicSharedMemorySize, tr::SMEM);
    cudaFuncSetAttribute(blayer_kernel, cudaFuncAttributeMaxDynamicSharedMemorySize, bf::SMEM);
    init = true;
  }
  const CUtensorMap tmXn = make_map(P.xn, 640, 2048, 64, 128), tmXn2 = make_map(P.xn2, 640, 2048, 64, 128);
  const CUtensorMap tmWq = make_map3(Wq, 6144, 640, 3);
  const CUtensorMap tmCq = make_map(Wq, 6144, 640, 64, 160), tmCk = make_map(Wk, 6144, 640, 64, 160), tmCv = make_map(Wv, 6144, 640, 64, 160), tmCo = make_map(Wo, 640, 6144, 224, 64, false);
  const CUtensorMap tmWo5 = make_map3(Wo, 640, 6144, 5), tmWo2 = make_map3(Wo, 640, 6144, 2);

  CUtensorMap tmP;
  {
    cuuint64_t dims[3] = {256, 8, 24 * 320}, strides[2] = {1024, 8192};
    cuuint32_t box[3] = {256, 1, 10}, es[3] = {1, 1, 1};
    g_encode(&tmP, CU_TENSOR_MAP_DATA_TYPE_UINT32, 3, P.part, dims, strides, box, es, CU_TENSOR_MAP_INTERLEAVE_NONE, CU_TENSOR_MAP_SWIZZLE_NONE,
             CU_TENSOR_MAP_L2_PROMOTION_NONE, CU_TENSOR_MAP_FLOAT_OOB_FILL_NONE);
  }
  ChainArgs ca;
  ca.xh = P.xh; ca.mem0 = mem0; ca.kg = P.k; ca.vg = P.v;
  ca.arena = P.arena; ca.dbg = nullptr; ca.go = P.go; ca.delay = POLL_DELAY; ca.margin = 150; ca.pubrel = 1;
#ifdef TUNE
  if (getenv("PR")) ca.pubrel = atoi(getenv("PR"));
  if (getenv("MG")) ca.margin = atoi(getenv("MG"));
  if (getenv("PD")) ca.delay = atoi(getenv("PD"));
#endif
  ca.tl = 0;
  uint4* zar = (uint4*)P.arena; const int nzar = AR_SIZE / 16;
  uint4* zkv = (uint4*)P.kvacc; const int nzkv = (bf::KVACC / 4 + 64) / 4;

  const PrepArgs pa{wqkv, wphi, wo, (unsigned char*)P.wb, (unsigned char*)P.wot};
  const bf16* xcur = x;
  cudaLaunchAttribute at[1];
  at[0].id = cudaLaunchAttributeProgrammaticStreamSerialization; at[0].val.programmaticStreamSerializationAllowed = 1;
  auto cfgof = [&](int grid, int block, int smem, bool pdl) {
    cudaLaunchConfig_t lc = {};
    lc.gridDim = dim3(grid); lc.blockDim = dim3(block); lc.dynamicSmemBytes = smem; lc.stream = cudaStreamPerThread;
    lc.attrs = at; lc.numAttrs = pdl ? 1 : 0;
    return lc;
  };
  int nlayers = 2;
#ifdef TUNE
  if (getenv("LAYERS")) nlayers = atoi(getenv("LAYERS"));
#endif
  for (int layer = 0; layer < nlayers; layer++) {
    const int tl = layer * 12;
    cudaLaunchConfig_t lc = cfgof(256, 256, 0, layer > 0 && PDL_LN);
    cudaLaunchKernelEx(&lc, ln_kernel, xcur, P.xn, P.xh, zar, nzar, zkv, nzkv, Wk, Wv, layer == 0 ? PF_A : 0, tl + 0);
    ca.tl = tl + 2;
    lc = cfgof(96, 384, ch::SMEM, PDL_CH);
    cudaLaunchKernelEx(&lc, chain_kernel, ca, tmCq, tmCk, tmCv, tmCo);
    lc = cfgof(TRAIL_GRID, 384, tr::SMEM, true);
    tr::Args ta{P.k, P.v, (unsigned char*)P.o, P.qs, (unsigned char*)P.part, xcur, P.xn, P.xa, P.xn2, P.arena, P.go, tl + 4, 100, 60};
#ifdef TUNE
    if (getenv("NAP")) ta.nap = atoi(getenv("NAP"));
    if (getenv("NAP2")) ta.nap2 = atoi(getenv("NAP2"));
#endif
    cudaLaunchKernelEx(&lc, trail_kernel, tmXn, tmWq, tmWo5, tmWo2, tmP, sched_of(layer), ta, pa);
    lc = cfgof(128, 384, bf::SMEM, PDL_B);
    bf::Args ba{(const unsigned char*)P.wb, (const unsigned char*)P.wot, (unsigned char*)P.kvacc, (unsigned char*)P.pq, P.xa, layer == 0 ? P.xb : out, P.go, layer == 0 ? P.arena + tr::C_P : nullptr,
                      layer == 0 && PF_B ? Wk : nullptr, Wv, 30, 500, 0, tl + 7};
#ifdef TUNE
    if (getenv("PFN")) ba.pfn = atoi(getenv("PFN"));
    if (getenv("PFNS")) ba.pfns = atoi(getenv("PFNS"));
    if (getenv("PFWT")) ba.pfwait = atoi(getenv("PFWT"));
    if (getenv("PFB")) ba.pf0 = layer == 0 && atoi(getenv("PFB")) ? Wk : nullptr;
#endif
    cudaLaunchKernelEx(&lc, blayer_kernel, tmXn2, ba);
    xcur = P.xb;
  }
}
```

```cpp
#include <cuda_runtime.h>
#include <cuda.h>
#include <cuda_bf16.h>
#include <stdint.h>
#include <stdlib.h>
#include <type_traits>

typedef __nv_bfloat16 bf16;

namespace cfg {
constexpr int S = 2048, DM = 640, H = 32, DH = 192, NSEG = 64, SEG = 32, NM = 8;
constexpr int HD = H * DH;
}

__device__ __forceinline__ uint32_t smem_u32(const void* p) { return (uint32_t)__cvta_generic_to_shared(p); }
__device__ __forceinline__ uint32_t mapa_u32(uint32_t a, uint32_t r) {
  uint32_t o; asm("mapa.shared::cluster.u32 %0, %1, %2;" : "=r"(o) : "r"(a), "r"(r)); return o;
}
__device__ __forceinline__ void mbar_init(uint32_t b, uint32_t c) {
  asm volatile("mbarrier.init.shared::cta.b64 [%0], %1;" :: "r"(b), "r"(c) : "memory");
}
__device__ __forceinline__ void mbar_expect_tx(uint32_t b, uint32_t bytes) {
  asm volatile("mbarrier.arrive.expect_tx.shared::cta.b64 _, [%0], %1;" :: "r"(b), "r"(bytes) : "memory");
}
__device__ __forceinline__ void mbar_arrive(uint32_t b) {
  asm volatile("mbarrier.arrive.shared::cta.b64 _, [%0];" :: "r"(b) : "memory");
}
__device__ __forceinline__ void mbar_expect_tx_if(bool c, uint32_t b, uint32_t bytes) {
  asm volatile("{\n.reg .pred p;\nsetp.ne.u32 p, %2, 0;\n@p mbarrier.arrive.expect_tx.shared::cta.b64 _, [%0], %1;\n}" :: "r"(b), "r"(bytes), "r"((uint32_t)c) : "memory");
}
__device__ __forceinline__ void mbar_arrive_if(bool c, uint32_t b) {
  asm volatile("{\n.reg .pred p;\nsetp.ne.u32 p, %1, 0;\n@p mbarrier.arrive.shared::cta.b64 _, [%0];\n}" :: "r"(b), "r"((uint32_t)c) : "memory");
}
__device__ __forceinline__ bool mbar_try(uint32_t b, uint32_t ph) {
  uint32_t p;
  asm volatile("{.reg .pred p; mbarrier.try_wait.parity.shared::cta.b64 p, [%1], %2; selp.u32 %0, 1, 0, p;}"
               : "=r"(p) : "r"(b), "r"(ph) : "memory");
  return p;
}
__device__ __forceinline__ bool mbar_try_cluster(uint32_t b, uint32_t ph) {
  uint32_t p;
  asm volatile("{.reg .pred p; mbarrier.try_wait.parity.acquire.cluster.shared::cta.b64 p, [%1], %2; selp.u32 %0, 1, 0, p;}"
               : "=r"(p) : "r"(b), "r"(ph) : "memory");
  return p;
}
#ifndef SPIN_LIMIT
#define SPIN_LIMIT (1 << 20)
#endif
__device__ __forceinline__ void mbar_wait(uint32_t b, uint32_t ph) {
  asm volatile("{\n.reg .pred p, q;\n.reg .u32 c;\nmov.u32 c, 0;\n"
               "W_%=:\nmbarrier.try_wait.parity.shared::cta.b64 p, [%0], %1;\n@p bra.uni D_%=;\n"
               "add.u32 c, c, 1;\nsetp.lt.u32 q, c, %2;\n@q bra.uni W_%=;\nD_%=:\n}"
               :: "r"(b), "r"(ph), "n"(SPIN_LIMIT) : "memory");
}
__device__ __forceinline__ void mbar_spin(uint32_t b, uint32_t ph) {
  asm volatile("{\n.reg .pred p, q;\n.reg .u32 c;\nmov.u32 c, 0;\n"
               "W_%=:\nmbarrier.test_wait.parity.shared::cta.b64 p, [%0], %1;\n@p bra D_%=;\n"
               "add.u32 c, c, 1;\nsetp.lt.u32 q, c, %2;\n@q bra W_%=;\nD_%=:\n}"
               :: "r"(b), "r"(ph), "n"(SPIN_LIMIT) : "memory");
}
#define PIN(x) asm volatile("" : "+r"(x))
__device__ __forceinline__ void mbar_wait_cluster(uint32_t b, uint32_t ph) {
  int s = 0;
  while (!mbar_try_cluster(b, ph)) { if (++s > SPIN_LIMIT) break; }
}
__device__ __forceinline__ void st_async_v2(uint32_t a, uint32_t x, uint32_t y, uint32_t mb) {
  asm volatile("st.async.weak.shared::cluster.mbarrier::complete_tx::bytes.v2.b32 [%0], {%1,%2}, [%3];"
               :: "r"(a), "r"(x), "r"(y), "r"(mb) : "memory");
}
__device__ __forceinline__ void st_async_v4(uint32_t a, uint32_t x, uint32_t y, uint32_t z, uint32_t w, uint32_t mb) {
  asm volatile("st.async.weak.shared::cluster.mbarrier::complete_tx::bytes.v4.b32 [%0], {%1,%2,%3,%4}, [%5];"
               :: "r"(a), "r"(x), "r"(y), "r"(z), "r"(w), "r"(mb) : "memory");
}
__device__ __forceinline__ void bulk_g2s(uint32_t dst, const void* src, uint32_t bytes, uint32_t mb) {
  asm volatile("cp.async.bulk.shared::cluster.global.mbarrier::complete_tx::bytes [%0], [%1], %2, [%3];"
               :: "r"(dst), "l"(src), "r"(bytes), "r"(mb) : "memory");
}
__device__ __forceinline__ void cp_async16(uint32_t dst, const void* src) {
  asm volatile("cp.async.cg.shared.global [%0], [%1], 16;" :: "r"(dst), "l"(src) : "memory");
}
__device__ __forceinline__ void cp_async_wait_all() { asm volatile("cp.async.wait_all;" ::: "memory"); }
__device__ __forceinline__ void fence_proxy_async() { asm volatile("fence.proxy.async.shared::cta;" ::: "memory"); }
__device__ __forceinline__ void bar_sync(int id, int n) { asm volatile("bar.sync %0, %1;" :: "r"(id), "r"(n) : "memory"); }
__device__ __forceinline__ void bar_arrive(int id, int n) { asm volatile("bar.arrive %0, %1;" :: "r"(id), "r"(n) : "memory"); }
__device__ __forceinline__ void cluster_sync_all() {
  asm volatile("barrier.cluster.arrive.release.aligned; barrier.cluster.wait.acquire.aligned;" ::: "memory");
}
__device__ __forceinline__ void ldsm_x4(uint32_t (&r)[4], uint32_t a) {
  asm volatile("ldmatrix.sync.aligned.m8n8.x4.shared.b16 {%0,%1,%2,%3}, [%4];"
               : "=r"(r[0]), "=r"(r[1]), "=r"(r[2]), "=r"(r[3]) : "r"(a) : "memory");
}
__device__ __forceinline__ void ldsm_x4_t(uint32_t (&r)[4], uint32_t a) {
  asm volatile("ldmatrix.sync.aligned.m8n8.x4.trans.shared.b16 {%0,%1,%2,%3}, [%4];"
               : "=r"(r[0]), "=r"(r[1]), "=r"(r[2]), "=r"(r[3]) : "r"(a) : "memory");
}
template <int IMM> __device__ __forceinline__ void ldsm_x4_i(uint32_t (&r)[4], uint32_t a) {
  asm volatile("ldmatrix.sync.aligned.m8n8.x4.shared.b16 {%0,%1,%2,%3}, [%4+%5];"
               : "=r"(r[0]), "=r"(r[1]), "=r"(r[2]), "=r"(r[3]) : "r"(a), "n"(IMM) : "memory");
}
template <int IMM> __device__ __forceinline__ void ldsm_x4_t_i(uint32_t (&r)[4], uint32_t a) {
  asm volatile("ldmatrix.sync.aligned.m8n8.x4.trans.shared.b16 {%0,%1,%2,%3}, [%4+%5];"
               : "=r"(r[0]), "=r"(r[1]), "=r"(r[2]), "=r"(r[3]) : "r"(a), "n"(IMM) : "memory");
}
template <int IMM> __device__ __forceinline__ uint4 lds128_i(uint32_t a) {
  uint4 v; asm volatile("ld.shared.v4.u32 {%0,%1,%2,%3}, [%4+%5];" : "=r"(v.x), "=r"(v.y), "=r"(v.z), "=r"(v.w) : "r"(a), "n"(IMM) : "memory"); return v;
}
template <int IMM> __device__ __forceinline__ uint2 lds64_i(uint32_t a) {
  uint2 v; asm volatile("ld.shared.v2.u32 {%0,%1}, [%2+%3];" : "=r"(v.x), "=r"(v.y) : "r"(a), "n"(IMM) : "memory"); return v;
}
template <int IMM> __device__ __forceinline__ void sts128_i(uint32_t a, uint32_t x, uint32_t y, uint32_t z, uint32_t w) {
  asm volatile("st.shared.v4.u32 [%0+%5], {%1,%2,%3,%4};" :: "r"(a), "r"(x), "r"(y), "r"(z), "r"(w), "n"(IMM) : "memory");
}
template <int IMM> __device__ __forceinline__ void sts64_i(uint32_t a, uint32_t x, uint32_t y) {
  asm volatile("st.shared.v2.u32 [%0+%3], {%1,%2};" :: "r"(a), "r"(x), "r"(y), "n"(IMM) : "memory");
}
template <int IMM> __device__ __forceinline__ void st_async_v2_i(uint32_t a, uint32_t x, uint32_t y, uint32_t mb) {
  asm volatile("st.async.weak.shared::cluster.mbarrier::complete_tx::bytes.v2.b32 [%0+%4], {%1,%2}, [%3];"
               :: "r"(a), "r"(x), "r"(y), "r"(mb), "n"(IMM) : "memory");
}
template <int IMM> __device__ __forceinline__ uint4 ld_relaxed_v4_i(const void* p) {
  uint4 v; asm volatile("ld.relaxed.gpu.global.v4.u32 {%0,%1,%2,%3}, [%4+%5];" : "=r"(v.x), "=r"(v.y), "=r"(v.z), "=r"(v.w) : "l"(p), "n"(IMM) : "memory"); return v;
}
template <int I, int N, class F> __device__ __forceinline__ void static_for(F&& f) {
  if constexpr (I < N) { f(std::integral_constant<int, I>{}); static_for<I + 1, N>(f); }
}
__device__ __forceinline__ uint32_t movm_t(uint32_t a) {
  uint32_t d; asm volatile("movmatrix.sync.aligned.m8n8.trans.b16 %0, %1;" : "=r"(d) : "r"(a)); return d;
}
__device__ __forceinline__ void mma16816(float (&d)[4], uint32_t a0, uint32_t a1, uint32_t a2, uint32_t a3, uint32_t b0, uint32_t b1) {
  asm volatile("mma.sync.aligned.m16n8k16.row.col.f32.bf16.bf16.f32 {%0,%1,%2,%3}, {%4,%5,%6,%7}, {%8,%9}, {%0,%1,%2,%3};"
               : "+f"(d[0]), "+f"(d[1]), "+f"(d[2]), "+f"(d[3]) : "r"(a0), "r"(a1), "r"(a2), "r"(a3), "r"(b0), "r"(b1));
}
__device__ __forceinline__ uint32_t pack_bf16(float lo, float hi) {
  uint32_t d; asm("cvt.rn.bf16x2.f32 %0, %1, %2;" : "=r"(d) : "f"(hi), "f"(lo)); return d;
}
__device__ __forceinline__ float bf_lo(uint32_t w) { return __uint_as_float(w << 16); }
__device__ __forceinline__ float bf_hi(uint32_t w) { return __uint_as_float(w & 0xffff0000u); }
__device__ __forceinline__ uint4 lds128(uint32_t a) {
  uint4 v; asm volatile("ld.shared.v4.u32 {%0,%1,%2,%3}, [%4];" : "=r"(v.x), "=r"(v.y), "=r"(v.z), "=r"(v.w) : "r"(a) : "memory"); return v;
}
__device__ __forceinline__ uint2 lds64(uint32_t a) {
  uint2 v; asm volatile("ld.shared.v2.u32 {%0,%1}, [%2];" : "=r"(v.x), "=r"(v.y) : "r"(a) : "memory"); return v;
}
__device__ __forceinline__ void sts128(uint32_t a, uint32_t x, uint32_t y, uint32_t z, uint32_t w) {
  asm volatile("st.shared.v4.u32 [%0], {%1,%2,%3,%4};" :: "r"(a), "r"(x), "r"(y), "r"(z), "r"(w) : "memory");
}
__device__ __forceinline__ void sts64(uint32_t a, uint32_t x, uint32_t y) {
  asm volatile("st.shared.v2.u32 [%0], {%1,%2};" :: "r"(a), "r"(x), "r"(y) : "memory");
}
__device__ __forceinline__ uint4 ld_relaxed_v4(const void* p) {
  uint4 v; asm volatile("ld.relaxed.gpu.global.v4.u32 {%0,%1,%2,%3}, [%4];" : "=r"(v.x), "=r"(v.y), "=r"(v.z), "=r"(v.w) : "l"(p) : "memory"); return v;
}
__device__ __forceinline__ uint32_t ld_relaxed_u32(const void* p) {
  uint32_t v; asm volatile("ld.relaxed.gpu.global.u32 %0, [%1];" : "=r"(v) : "l"(p) : "memory"); return v;
}
__device__ __forceinline__ void st_relaxed_v2(void* p, uint32_t a, uint32_t b) {
  asm volatile("st.relaxed.gpu.global.v2.u32 [%0], {%1,%2};" :: "l"(p), "r"(a), "r"(b) : "memory");
}
__device__ __forceinline__ void st_relaxed_u32(void* p, uint32_t v) {
  asm volatile("st.relaxed.gpu.global.u32 [%0], %1;" :: "l"(p), "r"(v) : "memory");
}
__device__ __forceinline__ void st_release_u32(void* p, uint32_t v) {
  asm volatile("st.release.gpu.global.u32 [%0], %1;" :: "l"(p), "r"(v) : "memory");
}
__device__ __forceinline__ void red_release_inc(void* p) { asm volatile("red.release.gpu.global.add.u32 [%0], 1;" :: "l"(p) : "memory"); }
__device__ __forceinline__ uint32_t clk32() { uint32_t c; asm volatile("mov.u32 %0, %%clock;" : "=r"(c) :: "memory"); return c; }
__device__ __forceinline__ uint32_t clkdep(uint32_t v) {
  uint32_t c; asm volatile("{.reg .pred p; setp.eq.u32 p, %1, 0xdeadbeef; @p trap; mov.u32 %0, %%clock;}" : "=r"(c) : "r"(v) : "memory"); return c;
}
__device__ __forceinline__ void wgmma_fence() { asm volatile("wgmma.fence.sync.aligned;" ::: "memory"); }
__device__ __forceinline__ void wgmma_commit() { asm volatile("wgmma.commit_group.sync.aligned;" ::: "memory"); }
template <int N> __device__ __forceinline__ void wgmma_wait() { asm volatile("wgmma.wait_group.sync.aligned %0;" :: "n"(N) : "memory"); }
__device__ __forceinline__ void wgmma_n8_ss_ta(float (&d)[4], uint64_t da, uint64_t db, int acc) {
  asm volatile("{\n.reg .pred p;\nsetp.ne.b32 p, %6, 0;\n"
               "wgmma.mma_async.sync.aligned.m64n8k16.f32.bf16.bf16 {%0,%1,%2,%3}, %4, %5, p, 1, 1, 1, 0;\n}\n"
               : "+f"(d[0]), "+f"(d[1]), "+f"(d[2]), "+f"(d[3]) : "l"(da), "l"(db), "r"(acc));
}
__device__ __forceinline__ uint64_t make_desc(uint32_t saddr, uint32_t lbo_bytes, uint32_t sbo_bytes, uint32_t swz) {
  return (uint64_t)((saddr & 0x3FFFF) >> 4) | ((uint64_t)(lbo_bytes >> 4) << 16) | ((uint64_t)(sbo_bytes >> 4) << 32) | ((uint64_t)swz << 62);
}


__device__ __forceinline__ bool elect_one() {
  uint32_t p; asm volatile("{\n.reg .pred p;\nelect.sync _|p, 0xffffffff;\nselp.u32 %0, 1, 0, p;\n}" : "=r"(p)); return p;
}
__device__ __forceinline__ void tma_load_3d(uint32_t dst, const CUtensorMap* tm, int c0, int c1, int c2, uint32_t mb) {
  asm volatile("cp.async.bulk.tensor.3d.shared::cluster.global.mbarrier::complete_tx::bytes [%0], [%1, {%3, %4, %5}], [%2];"
               :: "r"(dst), "l"(tm), "r"(mb), "r"(c0), "r"(c1), "r"(c2) : "memory");
}
__device__ __forceinline__ void tma_load_2d(uint32_t dst, const CUtensorMap* tm, int c0, int c1, uint32_t mb) {
  asm volatile("cp.async.bulk.tensor.2d.shared::cluster.global.mbarrier::complete_tx::bytes [%0], [%1, {%3, %4}], [%2];"
               :: "r"(dst), "l"(tm), "r"(mb), "r"(c0), "r"(c1) : "memory");
}
__device__ __forceinline__ void bulk_s2g(void* dst, uint32_t src, uint32_t bytes) {
  asm volatile("cp.async.bulk.global.shared::cta.bulk_group [%0], [%1], %2;" :: "l"(dst), "r"(src), "r"(bytes) : "memory");
}
__device__ __forceinline__ uint64_t policy_evict_first() {
  uint64_t p; asm volatile("createpolicy.fractional.L2::evict_first.b64 %0, 1.0;" : "=l"(p)); return p;
}
__device__ __forceinline__ void bulk_s2g_hint(void* dst, uint32_t src, uint32_t bytes, uint64_t pol) {
  asm volatile("cp.async.bulk.global.shared::cta.bulk_group.L2::cache_hint [%0], [%1], %2, %3;" :: "l"(dst), "r"(src), "r"(bytes), "l"(pol) : "memory");
}
__device__ __forceinline__ void bulk_commit() { asm volatile("cp.async.bulk.commit_group;" ::: "memory"); }
template <int N> __device__ __forceinline__ void bulk_wait_read() { asm volatile("cp.async.bulk.wait_group.read %0;" :: "n"(N) : "memory"); }
template <int N> __device__ __forceinline__ void bulk_wait() { asm volatile("cp.async.bulk.wait_group %0;" :: "n"(N) : "memory"); }
__device__ __forceinline__ void stsm_x4(uint32_t a, uint32_t r0, uint32_t r1, uint32_t r2, uint32_t r3) {
  asm volatile("stmatrix.sync.aligned.m8n8.x4.shared.b16 [%0], {%1,%2,%3,%4};" :: "r"(a), "r"(r0), "r"(r1), "r"(r2), "r"(r3) : "memory");
}
__device__ __forceinline__ void stsm_x2(uint32_t a, uint32_t r0, uint32_t r1) {
  asm volatile("stmatrix.sync.aligned.m8n8.x2.shared.b16 [%0], {%1,%2};" :: "r"(a), "r"(r0), "r"(r1) : "memory");
}
__device__ __forceinline__ void ldsm_x2(uint32_t (&r)[2], uint32_t a) {
  asm volatile("ldmatrix.sync.aligned.m8n8.x2.shared.b16 {%0,%1}, [%2];" : "=r"(r[0]), "=r"(r[1]) : "r"(a) : "memory");
}
__device__ __forceinline__ void ldsm_x2_t(uint32_t (&r)[2], uint32_t a) {
  asm volatile("ldmatrix.sync.aligned.m8n8.x2.trans.shared.b16 {%0,%1}, [%2];" : "=r"(r[0]), "=r"(r[1]) : "r"(a) : "memory");
}
__device__ __forceinline__ float bf16r(float x) { return __uint_as_float(pack_bf16(0.f, x) & 0xffff0000u); }
__device__ __forceinline__ void bf16r2(float& a, float& b) { const uint32_t w = pack_bf16(a, b); a = bf_lo(w); b = bf_hi(w); }
__device__ __forceinline__ float rcpf(float x) { float r; asm("rcp.approx.ftz.f32 %0, %1;" : "=f"(r) : "f"(x)); return r; }
__device__ __forceinline__ float ex2f(float x) { float e; asm("ex2.approx.ftz.f32 %0, %1;" : "=f"(e) : "f"(x)); return e; }
__device__ __forceinline__ void prefetch_tmap(const CUtensorMap* tm) { asm volatile("prefetch.tensormap [%0];" :: "l"(tm) : "memory"); }

#ifdef TIMELINE
__device__ unsigned long long g_tl[2 * 64];
__device__ unsigned long long g_log[2 * 132 * 64 * 2 + 2];
__device__ unsigned long long g_tl2[4 * 64];
__device__ __forceinline__ unsigned long long gtime() { unsigned long long t; asm volatile("mov.u64 %0, %%globaltimer;" : "=l"(t)); return t; }
#define TL_BEGIN(id) do { if (threadIdx.x == 0) atomicMin(&g_tl[2 * (id)], gtime()); } while (0)
#define TL_END(id) do { if ((threadIdx.x & 31) == 0) atomicMax(&g_tl[2 * (id) + 1], gtime()); } while (0)
#define TL_ACC(idx, t0) do { if (threadIdx.x == 0 && m >= 4 && m < 11) { atomicAdd(&g_tl2[idx], gtime() - (t0)); atomicAdd(&g_tl2[(idx) + 1], 1ull); } } while (0)
#define TL_NOW() gtime()
#define TL2(idx) asm volatile("{\n.reg .pred p;\nsetp.eq.u32 p, %2, 0;\n@p red.relaxed.gpu.global.max.u64 [%0], %1;\n}" :: "l"(&g_tl2[idx]), "l"(gtime()), "r"(threadIdx.x) : "memory")
#define TLW(idx) asm volatile("{\n.reg .pred p;\nsetp.eq.u32 p, %2, 0;\n@p red.relaxed.gpu.global.max.u64 [%0], %1;\n@p red.relaxed.gpu.global.add.u64 [%0+128], %1;\n}" :: "l"(&g_tl2[idx]), "l"(gtime() - g_tl0), "r"(threadIdx.x & 31) : "memory")
#define TL_BEGIN0(id) atomicMin(&g_tl[2 * (id)], gtime())
#else
#define TL_ACC(idx, t0)
#define TL_NOW() 0ull
#define TL2(idx)
#define TL_BEGIN0(id)
#define TLW(idx)
#define TL_BEGIN(id)
#define TL_END(id)
#endif
template <int TA, int TB> __device__ __forceinline__ void wgmma_n24(float (&d)[12], uint64_t da, uint64_t db, int acc) {
  asm volatile("{\n.reg .pred p;\nsetp.ne.b32 p, %14, 0;\n"
    "wgmma.mma_async.sync.aligned.m64n24k16.f32.bf16.bf16 {%0, %1, %2, %3, %4, %5, %6, %7, %8, %9, %10, %11}, %12, %13, p, 1, 1, %15, %16;\n}\n"
    : "+f"(d[0]), "+f"(d[1]), "+f"(d[2]), "+f"(d[3]), "+f"(d[4]), "+f"(d[5]), "+f"(d[6]), "+f"(d[7]), "+f"(d[8]), "+f"(d[9]), "+f"(d[10]), "+f"(d[11])
    : "l"(da), "l"(db), "r"(acc), "n"(TA), "n"(TB));
}

template <int TA, int TB> __device__ __forceinline__ void wgmma_n80(float (&d)[40], uint64_t da, uint64_t db, int acc) {
  asm volatile("{\n.reg .pred p;\nsetp.ne.b32 p, %42, 0;\n"
    "wgmma.mma_async.sync.aligned.m64n80k16.f32.bf16.bf16 {%0, %1, %2, %3, %4, %5, %6, %7, %8, %9, %10, %11, %12, %13, %14, %15, %16, %17, %18, %19, %20, %21, %22, %23, %24, %25, %26, %27, %28, %29, %30, %31, %32, %33, %34, %35, %36, %37, %38, %39}, %40, %41, p, 1, 1, %43, %44;\n}\n"
    : "+f"(d[0]), "+f"(d[1]), "+f"(d[2]), "+f"(d[3]), "+f"(d[4]), "+f"(d[5]), "+f"(d[6]), "+f"(d[7]), "+f"(d[8]), "+f"(d[9]), "+f"(d[10]), "+f"(d[11]), "+f"(d[12]), "+f"(d[13]), "+f"(d[14]), "+f"(d[15]), "+f"(d[16]), "+f"(d[17]), "+f"(d[18]), "+f"(d[19]), "+f"(d[20]), "+f"(d[21]), "+f"(d[22]), "+f"(d[23]), "+f"(d[24]), "+f"(d[25]), "+f"(d[26]), "+f"(d[27]), "+f"(d[28]), "+f"(d[29]), "+f"(d[30]), "+f"(d[31]), "+f"(d[32]), "+f"(d[33]), "+f"(d[34]), "+f"(d[35]), "+f"(d[36]), "+f"(d[37]), "+f"(d[38]), "+f"(d[39])
    : "l"(da), "l"(db), "r"(acc), "n"(TA), "n"(TB));
}

template <int TA, int TB> __device__ __forceinline__ void wgmma_n128(float (&d)[64], uint64_t da, uint64_t db, int acc) {
  asm volatile("{\n.reg .pred p;\nsetp.ne.b32 p, %66, 0;\n"
    "wgmma.mma_async.sync.aligned.m64n128k16.f32.bf16.bf16 {%0, %1, %2, %3, %4, %5, %6, %7, %8, %9, %10, %11, %12, %13, %14, %15, %16, %17, %18, %19, %20, %21, %22, %23, %24, %25, %26, %27, %28, %29, %30, %31, %32, %33, %34, %35, %36, %37, %38, %39, %40, %41, %42, %43, %44, %45, %46, %47, %48, %49, %50, %51, %52, %53, %54, %55, %56, %57, %58, %59, %60, %61, %62, %63}, %64, %65, p, 1, 1, %67, %68;\n}\n"
    : "+f"(d[0]), "+f"(d[1]), "+f"(d[2]), "+f"(d[3]), "+f"(d[4]), "+f"(d[5]), "+f"(d[6]), "+f"(d[7]), "+f"(d[8]), "+f"(d[9]), "+f"(d[10]), "+f"(d[11]), "+f"(d[12]), "+f"(d[13]), "+f"(d[14]), "+f"(d[15]), "+f"(d[16]), "+f"(d[17]), "+f"(d[18]), "+f"(d[19]), "+f"(d[20]), "+f"(d[21]), "+f"(d[22]), "+f"(d[23]), "+f"(d[24]), "+f"(d[25]), "+f"(d[26]), "+f"(d[27]), "+f"(d[28]), "+f"(d[29]), "+f"(d[30]), "+f"(d[31]), "+f"(d[32]), "+f"(d[33]), "+f"(d[34]), "+f"(d[35]), "+f"(d[36]), "+f"(d[37]), "+f"(d[38]), "+f"(d[39]), "+f"(d[40]), "+f"(d[41]), "+f"(d[42]), "+f"(d[43]), "+f"(d[44]), "+f"(d[45]), "+f"(d[46]), "+f"(d[47]), "+f"(d[48]), "+f"(d[49]), "+f"(d[50]), "+f"(d[51]), "+f"(d[52]), "+f"(d[53]), "+f"(d[54]), "+f"(d[55]), "+f"(d[56]), "+f"(d[57]), "+f"(d[58]), "+f"(d[59]), "+f"(d[60]), "+f"(d[61]), "+f"(d[62]), "+f"(d[63])
    : "l"(da), "l"(db), "r"(acc), "n"(TA), "n"(TB));
}

template <int TA, int TB> __device__ __forceinline__ void wgmma_n192(float (&d)[96], uint64_t da, uint64_t db, int acc) {
  asm volatile("{\n.reg .pred p;\nsetp.ne.b32 p, %98, 0;\n"
    "wgmma.mma_async.sync.aligned.m64n192k16.f32.bf16.bf16 {%0, %1, %2, %3, %4, %5, %6, %7, %8, %9, %10, %11, %12, %13, %14, %15, %16, %17, %18, %19, %20, %21, %22, %23, %24, %25, %26, %27, %28, %29, %30, %31, %32, %33, %34, %35, %36, %37, %38, %39, %40, %41, %42, %43, %44, %45, %46, %47, %48, %49, %50, %51, %52, %53, %54, %55, %56, %57, %58, %59, %60, %61, %62, %63, %64, %65, %66, %67, %68, %69, %70, %71, %72, %73, %74, %75, %76, %77, %78, %79, %80, %81, %82, %83, %84, %85, %86, %87, %88, %89, %90, %91, %92, %93, %94, %95}, %96, %97, p, 1, 1, %99, %100;\n}\n"
    : "+f"(d[0]), "+f"(d[1]), "+f"(d[2]), "+f"(d[3]), "+f"(d[4]), "+f"(d[5]), "+f"(d[6]), "+f"(d[7]), "+f"(d[8]), "+f"(d[9]), "+f"(d[10]), "+f"(d[11]), "+f"(d[12]), "+f"(d[13]), "+f"(d[14]), "+f"(d[15]), "+f"(d[16]), "+f"(d[17]), "+f"(d[18]), "+f"(d[19]), "+f"(d[20]), "+f"(d[21]), "+f"(d[22]), "+f"(d[23]), "+f"(d[24]), "+f"(d[25]), "+f"(d[26]), "+f"(d[27]), "+f"(d[28]), "+f"(d[29]), "+f"(d[30]), "+f"(d[31]), "+f"(d[32]), "+f"(d[33]), "+f"(d[34]), "+f"(d[35]), "+f"(d[36]), "+f"(d[37]), "+f"(d[38]), "+f"(d[39]), "+f"(d[40]), "+f"(d[41]), "+f"(d[42]), "+f"(d[43]), "+f"(d[44]), "+f"(d[45]), "+f"(d[46]), "+f"(d[47]), "+f"(d[48]), "+f"(d[49]), "+f"(d[50]), "+f"(d[51]), "+f"(d[52]), "+f"(d[53]), "+f"(d[54]), "+f"(d[55]), "+f"(d[56]), "+f"(d[57]), "+f"(d[58]), "+f"(d[59]), "+f"(d[60]), "+f"(d[61]), "+f"(d[62]), "+f"(d[63]), "+f"(d[64]), "+f"(d[65]), "+f"(d[66]), "+f"(d[67]), "+f"(d[68]), "+f"(d[69]), "+f"(d[70]), "+f"(d[71]), "+f"(d[72]), "+f"(d[73]), "+f"(d[74]), "+f"(d[75]), "+f"(d[76]), "+f"(d[77]), "+f"(d[78]), "+f"(d[79]), "+f"(d[80]), "+f"(d[81]), "+f"(d[82]), "+f"(d[83]), "+f"(d[84]), "+f"(d[85]), "+f"(d[86]), "+f"(d[87]), "+f"(d[88]), "+f"(d[89]), "+f"(d[90]), "+f"(d[91]), "+f"(d[92]), "+f"(d[93]), "+f"(d[94]), "+f"(d[95])
    : "l"(da), "l"(db), "r"(acc), "n"(TA), "n"(TB));
}

template <int TA, int TB> __device__ __forceinline__ void wgmma_n256(float (&d)[128], uint64_t da, uint64_t db, int acc) {
  asm volatile("{\n.reg .pred p;\nsetp.ne.b32 p, %130, 0;\n"
    "wgmma.mma_async.sync.aligned.m64n256k16.f32.bf16.bf16 {%0, %1, %2, %3, %4, %5, %6, %7, %8, %9, %10, %11, %12, %13, %14, %15, %16, %17, %18, %19, %20, %21, %22, %23, %24, %25, %26, %27, %28, %29, %30, %31, %32, %33, %34, %35, %36, %37, %38, %39, %40, %41, %42, %43, %44, %45, %46, %47, %48, %49, %50, %51, %52, %53, %54, %55, %56, %57, %58, %59, %60, %61, %62, %63, %64, %65, %66, %67, %68, %69, %70, %71, %72, %73, %74, %75, %76, %77, %78, %79, %80, %81, %82, %83, %84, %85, %86, %87, %88, %89, %90, %91, %92, %93, %94, %95, %96, %97, %98, %99, %100, %101, %102, %103, %104, %105, %106, %107, %108, %109, %110, %111, %112, %113, %114, %115, %116, %117, %118, %119, %120, %121, %122, %123, %124, %125, %126, %127}, %128, %129, p, 1, 1, %131, %132;\n}\n"
    : "+f"(d[0]), "+f"(d[1]), "+f"(d[2]), "+f"(d[3]), "+f"(d[4]), "+f"(d[5]), "+f"(d[6]), "+f"(d[7]), "+f"(d[8]), "+f"(d[9]), "+f"(d[10]), "+f"(d[11]), "+f"(d[12]), "+f"(d[13]), "+f"(d[14]), "+f"(d[15]), "+f"(d[16]), "+f"(d[17]), "+f"(d[18]), "+f"(d[19]), "+f"(d[20]), "+f"(d[21]), "+f"(d[22]), "+f"(d[23]), "+f"(d[24]), "+f"(d[25]), "+f"(d[26]), "+f"(d[27]), "+f"(d[28]), "+f"(d[29]), "+f"(d[30]), "+f"(d[31]), "+f"(d[32]), "+f"(d[33]), "+f"(d[34]), "+f"(d[35]), "+f"(d[36]), "+f"(d[37]), "+f"(d[38]), "+f"(d[39]), "+f"(d[40]), "+f"(d[41]), "+f"(d[42]), "+f"(d[43]), "+f"(d[44]), "+f"(d[45]), "+f"(d[46]), "+f"(d[47]), "+f"(d[48]), "+f"(d[49]), "+f"(d[50]), "+f"(d[51]), "+f"(d[52]), "+f"(d[53]), "+f"(d[54]), "+f"(d[55]), "+f"(d[56]), "+f"(d[57]), "+f"(d[58]), "+f"(d[59]), "+f"(d[60]), "+f"(d[61]), "+f"(d[62]), "+f"(d[63]), "+f"(d[64]), "+f"(d[65]), "+f"(d[66]), "+f"(d[67]), "+f"(d[68]), "+f"(d[69]), "+f"(d[70]), "+f"(d[71]), "+f"(d[72]), "+f"(d[73]), "+f"(d[74]), "+f"(d[75]), "+f"(d[76]), "+f"(d[77]), "+f"(d[78]), "+f"(d[79]), "+f"(d[80]), "+f"(d[81]), "+f"(d[82]), "+f"(d[83]), "+f"(d[84]), "+f"(d[85]), "+f"(d[86]), "+f"(d[87]), "+f"(d[88]), "+f"(d[89]), "+f"(d[90]), "+f"(d[91]), "+f"(d[92]), "+f"(d[93]), "+f"(d[94]), "+f"(d[95]), "+f"(d[96]), "+f"(d[97]), "+f"(d[98]), "+f"(d[99]), "+f"(d[100]), "+f"(d[101]), "+f"(d[102]), "+f"(d[103]), "+f"(d[104]), "+f"(d[105]), "+f"(d[106]), "+f"(d[107]), "+f"(d[108]), "+f"(d[109]), "+f"(d[110]), "+f"(d[111]), "+f"(d[112]), "+f"(d[113]), "+f"(d[114]), "+f"(d[115]), "+f"(d[116]), "+f"(d[117]), "+f"(d[118]), "+f"(d[119]), "+f"(d[120]), "+f"(d[121]), "+f"(d[122]), "+f"(d[123]), "+f"(d[124]), "+f"(d[125]), "+f"(d[126]), "+f"(d[127])
    : "l"(da), "l"(db), "r"(acc), "n"(TA), "n"(TB));
}

template <int TB> __device__ __forceinline__ void wgmma_rs_n24(float (&d)[12], uint32_t a0, uint32_t a1, uint32_t a2, uint32_t a3, uint64_t db, int acc) {
  asm volatile("{\n.reg .pred p;\nsetp.ne.b32 p, %17, 0;\n"
    "wgmma.mma_async.sync.aligned.m64n24k16.f32.bf16.bf16 {%0, %1, %2, %3, %4, %5, %6, %7, %8, %9, %10, %11}, {%12, %13, %14, %15}, %16, p, 1, 1, %18;\n}\n"
    : "+f"(d[0]), "+f"(d[1]), "+f"(d[2]), "+f"(d[3]), "+f"(d[4]), "+f"(d[5]), "+f"(d[6]), "+f"(d[7]), "+f"(d[8]), "+f"(d[9]), "+f"(d[10]), "+f"(d[11])
    : "r"(a0), "r"(a1), "r"(a2), "r"(a3), "l"(db), "r"(acc), "n"(TB));
}

template <int TB> __device__ __forceinline__ void wgmma_rs_n40(float (&d)[20], uint32_t a0, uint32_t a1, uint32_t a2, uint32_t a3, uint64_t db, int acc) {
  asm volatile("{\n.reg .pred p;\nsetp.ne.b32 p, %25, 0;\n"
    "wgmma.mma_async.sync.aligned.m64n40k16.f32.bf16.bf16 {%0, %1, %2, %3, %4, %5, %6, %7, %8, %9, %10, %11, %12, %13, %14, %15, %16, %17, %18, %19}, {%20, %21, %22, %23}, %24, p, 1, 1, %26;\n}\n"
    : "+f"(d[0]), "+f"(d[1]), "+f"(d[2]), "+f"(d[3]), "+f"(d[4]), "+f"(d[5]), "+f"(d[6]), "+f"(d[7]), "+f"(d[8]), "+f"(d[9]), "+f"(d[10]), "+f"(d[11]), "+f"(d[12]), "+f"(d[13]), "+f"(d[14]), "+f"(d[15]), "+f"(d[16]), "+f"(d[17]), "+f"(d[18]), "+f"(d[19])
    : "r"(a0), "r"(a1), "r"(a2), "r"(a3), "l"(db), "r"(acc), "n"(TB));
}

template <int TB> __device__ __forceinline__ void wgmma_rs_n192(float (&d)[96], uint32_t a0, uint32_t a1, uint32_t a2, uint32_t a3, uint64_t db, int acc) {
  asm volatile("{\n.reg .pred p;\nsetp.ne.b32 p, %101, 0;\n"
    "wgmma.mma_async.sync.aligned.m64n192k16.f32.bf16.bf16 {%0, %1, %2, %3, %4, %5, %6, %7, %8, %9, %10, %11, %12, %13, %14, %15, %16, %17, %18, %19, %20, %21, %22, %23, %24, %25, %26, %27, %28, %29, %30, %31, %32, %33, %34, %35, %36, %37, %38, %39, %40, %41, %42, %43, %44, %45, %46, %47, %48, %49, %50, %51, %52, %53, %54, %55, %56, %57, %58, %59, %60, %61, %62, %63, %64, %65, %66, %67, %68, %69, %70, %71, %72, %73, %74, %75, %76, %77, %78, %79, %80, %81, %82, %83, %84, %85, %86, %87, %88, %89, %90, %91, %92, %93, %94, %95}, {%96, %97, %98, %99}, %100, p, 1, 1, %102;\n}\n"
    : "+f"(d[0]), "+f"(d[1]), "+f"(d[2]), "+f"(d[3]), "+f"(d[4]), "+f"(d[5]), "+f"(d[6]), "+f"(d[7]), "+f"(d[8]), "+f"(d[9]), "+f"(d[10]), "+f"(d[11]), "+f"(d[12]), "+f"(d[13]), "+f"(d[14]), "+f"(d[15]), "+f"(d[16]), "+f"(d[17]), "+f"(d[18]), "+f"(d[19]), "+f"(d[20]), "+f"(d[21]), "+f"(d[22]), "+f"(d[23]), "+f"(d[24]), "+f"(d[25]), "+f"(d[26]), "+f"(d[27]), "+f"(d[28]), "+f"(d[29]), "+f"(d[30]), "+f"(d[31]), "+f"(d[32]), "+f"(d[33]), "+f"(d[34]), "+f"(d[35]), "+f"(d[36]), "+f"(d[37]), "+f"(d[38]), "+f"(d[39]), "+f"(d[40]), "+f"(d[41]), "+f"(d[42]), "+f"(d[43]), "+f"(d[44]), "+f"(d[45]), "+f"(d[46]), "+f"(d[47]), "+f"(d[48]), "+f"(d[49]), "+f"(d[50]), "+f"(d[51]), "+f"(d[52]), "+f"(d[53]), "+f"(d[54]), "+f"(d[55]), "+f"(d[56]), "+f"(d[57]), "+f"(d[58]), "+f"(d[59]), "+f"(d[60]), "+f"(d[61]), "+f"(d[62]), "+f"(d[63]), "+f"(d[64]), "+f"(d[65]), "+f"(d[66]), "+f"(d[67]), "+f"(d[68]), "+f"(d[69]), "+f"(d[70]), "+f"(d[71]), "+f"(d[72]), "+f"(d[73]), "+f"(d[74]), "+f"(d[75]), "+f"(d[76]), "+f"(d[77]), "+f"(d[78]), "+f"(d[79]), "+f"(d[80]), "+f"(d[81]), "+f"(d[82]), "+f"(d[83]), "+f"(d[84]), "+f"(d[85]), "+f"(d[86]), "+f"(d[87]), "+f"(d[88]), "+f"(d[89]), "+f"(d[90]), "+f"(d[91]), "+f"(d[92]), "+f"(d[93]), "+f"(d[94]), "+f"(d[95])
    : "r"(a0), "r"(a1), "r"(a2), "r"(a3), "l"(db), "r"(acc), "n"(TB));
}
constexpr uint32_t AR_ACC = 0;
constexpr uint32_t AR_TAB = 0x100000;
constexpr uint32_t AR_PROG = 0x101000;
__host__ __device__ constexpr uint32_t prog_off(int h, int j) { return AR_PROG + h * 128 + j * 4; }
constexpr uint32_t AR_CNT = 0x108000;
constexpr uint32_t AR_QUEUE = 0x109000;
constexpr uint32_t AR_SIZE = 0x10a000;

struct ChainArgs {
  const bf16* mem0;
  const uint2* xh;
  unsigned char *kg, *vg;
  unsigned char* arena;
  unsigned* go;
  uint32_t* dbg;
  uint32_t delay;
  int margin, pubrel;
  int tl;
};

namespace ch {
constexpr int OFF_WQ = 0;
constexpr int OFF_X = 81920;
constexpr int OFF_MEM = OFF_X + 40960;
constexpr int OFF_WO = OFF_MEM + 10240;
constexpr int WOK = 8 * 896;
constexpr int OFF_KV = OFF_WO + 10 * WOK;
constexpr int KVB = 5120;
constexpr int OFF_O = OFF_KV + 4 * KVB;
constexpr int OFF_Q = OFF_O + 1024;
constexpr int OFF_S = OFF_O + 3072;
constexpr int OFF_SR = OFF_S + 1536;
constexpr int OFF_LT = OFF_SR + 1280;
constexpr int OFF_BAR = OFF_LT + 512;
constexpr int SMEM = OFF_BAR + 256;
static_assert(SMEM <= 232448, "smem");
constexpr int MB_S = OFF_BAR, MB_O = OFF_BAR + 8, MB_X = OFF_BAR + 16;
constexpr int MB_K = OFF_BAR + 128, MB_V = MB_K + 16, MB_Q = MB_K + 32, MB_R = MB_K + 48;
constexpr int SC_IN = OFF_BAR + 64;
constexpr int SC_MX = OFF_S;
constexpr int SC_TW = OFF_BAR + 48;
constexpr int SC_W = OFF_BAR + 96;
constexpr int WOS = 448;
enum { B_MEM0 = 1, B_QK, B_SL, B_V, B_O, B_RED, B_X, B_C, B_H, B_MEM1, B_A, B_G, B_E };
#ifndef NQ1
#define NQ1 6
#endif
#ifndef NQ0
#define NQ0 4
#endif
#ifndef NP0
#define NP0 4
#endif
#ifndef NWO
#define NWO 5
#endif
#ifndef NWP
#define NWP 4
#endif
#ifndef NB0
#define NB0 3
#endif
#ifndef BBS
#define BBS 100
#endif
#ifndef VSYNC
#define VSYNC 0
#endif
#ifndef XPOS
#define XPOS 0
#endif
#ifndef XPD
#define XPD 300
#endif
#ifndef WOF
#define WOF 0
#endif
#ifndef XBYTES
#define XBYTES 36864
#endif
#ifndef NRT
#define NRT 7
#endif
#ifndef NRF
#define NRF 2
#endif
#ifndef NPM0
#define NPM0 2
#endif
#ifndef NPM1
#define NPM1 2
#endif
#ifndef RSYNC
#define RSYNC 1
#endif
#ifndef PFK
#define PFK 1
#endif
#ifndef PA0
#define PA0 3
#endif
#ifndef PA1
#define PA1 0
#endif
#ifndef PB0
#define PB0 7
#endif
#ifndef PB1
#define PB1 5
#endif
#ifndef PQE
#define PQE 1
#endif
#ifndef XT
#define XT 30
#endif
static_assert(NPM0 >= 2 && NPM1 >= 2, "the K / V blocks live in the last two k-steps of Wo");
}

#ifndef CHAIN_TIMING
#define CHAIN_TIMING 0
#endif
#if CHAIN_TIMING
#ifndef TR0
#define TR0 41
#endif
#ifndef TSMASK
#define TSMASK 0xffff
#endif
#define TSV(i, v) do { if ((TSMASK >> (i)) & 1) asm volatile("st.shared.u32 [%0+%1], %2;" :: "r"(tsb), "n"((i) * 4), "r"(v) : "memory"); } while (0)
#define TS(i) TSV(i, clk32())
#define TS_SETUP() const uint32_t tsb = sb + ((s == TR0 || s == TR0 + 1) ? OFF_BAR + 128 + ((s - TR0) * 12 + warp) * 48 : OFF_SR + 1152)
#else
#define TS(i)
#define TSV(i, v)
#define TS_SETUP()
#endif
#ifndef POLL_DELAY
#define POLL_DELAY 590
#endif
#ifndef XN
#define XN 40
#endif
#ifndef PF0
#define PF0 8
#endif
#ifndef PFS
#define PFS 3
#endif
#ifndef XDELAY
#define XDELAY 0
#endif
#ifndef NOKM
#define NOKM 0
#endif
#ifndef PFX
#define PFX 3
#endif
#ifndef NVE
#define NVE 10
#endif
#ifndef VET
#define VET 19
#endif
#ifndef MEMFIRST
#define MEMFIRST 1
#endif
#ifndef PM1
#define PM1 1
#endif
#ifndef GD1
#define GD1 30
#endif
#ifndef GD2
#define GD2 150
#endif
#ifndef CEARLY
#define CEARLY 1
#endif
#ifndef PFACC
#define PFACC 1
#endif
template <int V> using IC = std::integral_constant<int, V>;
__device__ __forceinline__ uint32_t clk_v() { uint64_t c; asm volatile("mov.u64 %0, %%clock64;" : "=l"(c) :: "memory"); return (uint32_t)c; }
__device__ __forceinline__ int fresh(int x) { int y; asm volatile("shfl.sync.bfly.b32 %0, %1, 0, 0x1f, 0xffffffff;" : "=r"(y) : "r"(x)); return y; }
#define SFENCE2(x, d) asm volatile("{\n.reg .pred p;\nsetp.eq.u32 p, %0, 0x7fffffff;\n@p st.shared.u32 [%0], %1;\n}" :: "r"(x), "r"(d) : "memory")
#define SFENCE(x) asm volatile("{\n.reg .pred p;\nsetp.eq.u32 p, %0, 0x7fffffff;\n@p st.shared.u32 [%0], %0;\n}" :: "r"(x) : "memory")
template <int I> __device__ __forceinline__ void bbfence(uint32_t x) {
  asm volatile("{\n.reg .pred p;\nsetp.eq.u32 p, %0, %1;\nL_%=:\n@p st.volatile.shared.u32 [%0], %0;\n@p bra.uni L_%=;\n}" :: "r"(x), "n"(4 * I) : "memory");
}
__device__ __forceinline__ float uniform_f(float x) { return __uint_as_float(__reduce_max_sync(0xffffffffu, __float_as_uint(x))); }

__device__ __forceinline__ void mma16816h(float (&d)[4], const uint32_t (&a)[4], uint32_t b0, uint32_t b1) {
  asm volatile("mma.sync.aligned.m16n8k16.row.col.f32.f16.f16.f32 {%0,%1,%2,%3}, {%4,%5,%6,%7}, {%8,%9}, {%0,%1,%2,%3};"
               : "+f"(d[0]), "+f"(d[1]), "+f"(d[2]), "+f"(d[3]) : "r"(a[0]), "r"(a[1]), "r"(a[2]), "r"(a[3]), "r"(b0), "r"(b1));
}
__device__ __forceinline__ void mma1688(float (&d)[4], uint32_t a0, uint32_t a1, uint32_t b0) {
  asm volatile("mma.sync.aligned.m16n8k8.row.col.f32.bf16.bf16.f32 {%0,%1,%2,%3}, {%4,%5}, {%6}, {%0,%1,%2,%3};"
               : "+f"(d[0]), "+f"(d[1]), "+f"(d[2]), "+f"(d[3]) : "r"(a0), "r"(a1), "r"(b0));
}
template <int OFF16, int ACC> __device__ __forceinline__ void wgmma_rs32h(float (&d)[16], const uint32_t (&a)[4], uint32_t dlo) {
  asm volatile("{\n.reg .pred p;\n.reg .b32 t;\n.reg .b64 db;\nsetp.ne.b32 p, %22, 0;\nadd.u32 t, %20, %21;\nmov.b64 db, {t, 0x40000040};\n"
    "wgmma.mma_async.sync.aligned.m64n32k16.f32.f16.f16 {%0,%1,%2,%3,%4,%5,%6,%7,%8,%9,%10,%11,%12,%13,%14,%15}, {%16,%17,%18,%19}, db, p, 1, 1, 0;\n}\n"
    : "+f"(d[0]), "+f"(d[1]), "+f"(d[2]), "+f"(d[3]), "+f"(d[4]), "+f"(d[5]), "+f"(d[6]), "+f"(d[7]), "+f"(d[8]), "+f"(d[9]), "+f"(d[10]), "+f"(d[11]),
      "+f"(d[12]), "+f"(d[13]), "+f"(d[14]), "+f"(d[15])
    : "r"(a[0]), "r"(a[1]), "r"(a[2]), "r"(a[3]), "r"(dlo), "n"(OFF16), "n"(ACC));
}
template <int IMM> __device__ __forceinline__ void stsm_x4_t_i(uint32_t a, uint32_t r0, uint32_t r1, uint32_t r2, uint32_t r3) {
  asm volatile("stmatrix.sync.aligned.m8n8.x4.trans.shared.b16 [%0+%5], {%1,%2,%3,%4};" :: "r"(a), "r"(r0), "r"(r1), "r"(r2), "r"(r3), "n"(IMM) : "memory");
}
template <int IMM> __device__ __forceinline__ void stsm_x2_t_i(uint32_t a, uint32_t r0, uint32_t r1) {
  asm volatile("stmatrix.sync.aligned.m8n8.x2.trans.shared.b16 [%0+%3], {%1,%2};" :: "r"(a), "r"(r0), "r"(r1), "n"(IMM) : "memory");
}
template <int IMM> __device__ __forceinline__ void st_async_b32_i(uint32_t a, uint32_t x, uint32_t mb) {
  asm volatile("st.async.weak.shared::cluster.mbarrier::complete_tx::bytes.b32 [%0+%3], %1, [%2];" :: "r"(a), "r"(x), "r"(mb), "n"(IMM) : "memory");
}
template <int IMM> __device__ __forceinline__ void ld_relaxed_v4_if(uint4& v, const void* p, uint32_t c) {
  asm volatile("{\n.reg .pred p;\nsetp.ne.u32 p, %6, 0;\n@p ld.relaxed.gpu.global.v4.u32 {%0,%1,%2,%3}, [%4+%5];\n}"
               : "+r"(v.x), "+r"(v.y), "+r"(v.z), "+r"(v.w) : "l"(p), "n"(IMM), "r"(c) : "memory");
}
template <int IMM> __device__ __forceinline__ void ldsm_x2_i(uint32_t (&r)[2], uint32_t a) {
  asm volatile("ldmatrix.sync.aligned.m8n8.x2.shared.b16 {%0,%1}, [%2+%3];" : "=r"(r[0]), "=r"(r[1]) : "r"(a), "n"(IMM) : "memory");
}
template <int IMM> __device__ __forceinline__ uint32_t ldsm_x1_t_i(uint32_t a) {
  uint32_t r; asm volatile("ldmatrix.sync.aligned.m8n8.x1.trans.shared.b16 {%0}, [%1+%2];" : "=r"(r) : "r"(a), "n"(IMM) : "memory"); return r;
}
template <int IMM> __device__ __forceinline__ uint32_t lds32_i(uint32_t a) {
  uint32_t v; asm volatile("ld.shared.u32 %0, [%1+%2];" : "=r"(v) : "r"(a), "n"(IMM) : "memory"); return v;
}
__device__ __forceinline__ void sts32(uint32_t a, uint32_t v) { asm volatile("st.shared.u32 [%0], %1;" :: "r"(a), "r"(v) : "memory"); }
__device__ __forceinline__ uint32_t pack_f16(float lo, float hi) {
  uint32_t d; asm("cvt.rn.f16x2.f32 %0, %1, %2;" : "=r"(d) : "f"(hi), "f"(lo)); return d;
}
__device__ __forceinline__ uint32_t amax_bf2(uint32_t a, uint32_t b) { uint32_t d; asm("max.xorsign.abs.bf16x2 %0, %1, %2;" : "=r"(d) : "r"(a), "r"(b)); return d; }
__device__ __forceinline__ uint32_t amax_h2(uint32_t a, uint32_t b) { uint32_t d; asm("max.xorsign.abs.f16x2 %0, %1, %2;" : "=r"(d) : "r"(a), "r"(b)); return d; }
__device__ __forceinline__ uint32_t amax_fold(uint32_t m) { return __reduce_max_sync(0xffffffffu, max(m & 0x7fffu, (m >> 16) & 0x7fffu)); }
__device__ __forceinline__ int wscale_exp(uint32_t m) { return min(141 - (int)(m >> 7), 100); }
__device__ __forceinline__ float exp2i(int e) { return __uint_as_float((uint32_t)(e + 127) << 23); }
__device__ __forceinline__ uint32_t bf2_to_h2(uint32_t w, float sc) { return pack_f16(bf_lo(w) * sc, bf_hi(w) * sc); }
__device__ __forceinline__ void bf2_to_h2_inplace(uint32_t& w, uint32_t sc2) {
  asm volatile("{\n.reg .b32 t, lo, hi;\nmul.rn.bf16x2 t, %0, %1;\nshl.b32 lo, t, 16;\nand.b32 hi, t, 0xffff0000;\ncvt.rn.f16x2.f32 %0, hi, lo;\n}" : "+r"(w) : "r"(sc2));
}
__device__ __forceinline__ void prefetch_l2(const void* p, uint32_t bytes) { asm volatile("cp.async.bulk.prefetch.L2.global [%0], %1;" :: "l"(p), "r"(bytes) : "memory"); }
__device__ __forceinline__ void prefetch_tma_2d(const CUtensorMap* tm, int c0, int c1) {
  asm volatile("cp.async.bulk.prefetch.tensor.2d.L2.global [%0, {%1, %2}];" :: "l"(tm), "r"(c0), "r"(c1) : "memory");
}
__host__ __device__ constexpr uint32_t acc_voff(int v) { return v < 4 ? v * 1024u : (v == 4 ? 128u : 3072u + 128u); }
__device__ __forceinline__ int unit28(int i) { return i == 3 ? 54 : 14 * i; }
__device__ __forceinline__ int unit24(int i) { return i < 2 ? 48 - 6 * i : 56 + 6 * i; }
__device__ __forceinline__ uint32_t acc_step(int s) { return (s >> 1) * 32768 + (s & 1) * 512; }
__device__ __forceinline__ uint32_t acc_lane(int i, int lane) { return ((lane >> 3) & 1) * 256 + (lane >> 4) * 4096 + i * 8192 + (lane & 7) * 16; }

__device__ __forceinline__ uint32_t ld_acquire_u32(const void* p) {
  uint32_t v; asm volatile("ld.acquire.gpu.global.u32 %0, [%1];" : "=r"(v) : "l"(p) : "memory"); return v;
}
template <int R> __device__ __forceinline__ void ln_rows(const uint2 (&xw)[R][5], int row0, int lane, bf16* __restrict__ xn, uint2* __restrict__ xh) {
  float v[R][20], s[R], q[R];
#pragma unroll
  for (int r = 0; r < R; r++) {
    s[r] = 0.f; q[r] = 0.f;
#pragma unroll
    for (int i = 0; i < 5; i++) { v[r][4 * i] = bf_lo(xw[r][i].x); v[r][4 * i + 1] = bf_hi(xw[r][i].x); v[r][4 * i + 2] = bf_lo(xw[r][i].y); v[r][4 * i + 3] = bf_hi(xw[r][i].y); }
#pragma unroll
    for (int i = 0; i < 5; i++) s[r] += (v[r][4 * i] + v[r][4 * i + 1]) + (v[r][4 * i + 2] + v[r][4 * i + 3]);
  }
#pragma unroll
  for (int o = 16; o; o >>= 1)
#pragma unroll
    for (int r = 0; r < R; r++) s[r] += __shfl_xor_sync(0xffffffffu, s[r], o);
#pragma unroll
  for (int r = 0; r < R; r++) {
    s[r] *= 1.f / cfg::DM;
#pragma unroll
    for (int i = 0; i < 10; i++) { const float d = v[r][2 * i] - s[r], e = v[r][2 * i + 1] - s[r]; q[r] += d * d + e * e; }
  }
#pragma unroll
  for (int o = 16; o; o >>= 1)
#pragma unroll
    for (int r = 0; r < R; r++) q[r] += __shfl_xor_sync(0xffffffffu, q[r], o);
#pragma unroll
  for (int r = 0; r < R; r++) {
    const int row = row0 + r;
    const float mb = bf16r(s[r]), var = bf16r(q[r] * (1.f / cfg::DM));
    float sd; asm("sqrt.approx.f32 %0, %1;" : "=f"(sd) : "f"(bf16r(var + 1e-5f)));
    const float inv = rcpf(bf16r(sd));
#pragma unroll
    for (int i = 0; i < 5; i++) {
      float y[4];
#pragma unroll
      for (int e = 0; e < 4; e++) y[e] = v[r][4 * i + e] - mb;
      bf16r2(y[0], y[1]); bf16r2(y[2], y[3]);
      const uint32_t w0 = pack_bf16(y[0] * inv, y[1] * inv), w1 = pack_bf16(y[2] * inv, y[3] * inv);
      *(uint2*)(xn + (size_t)row * cfg::DM + i * 128 + lane * 4) = make_uint2(w0, w1);
      if (xh) xh[(((size_t)(row >> 5) * 10 + 2 * i + (lane >> 4)) * 32 + (row & 31)) * 16 + ((((lane >> 1) & 7) ^ (row & 7)) << 1) + (lane & 1)] =
          make_uint2(pack_f16(bf_lo(w0), bf_hi(w0)), pack_f16(bf_lo(w1), bf_hi(w1)));
    }
  }
}

__global__ void __cluster_dims__(3, 1, 1) __launch_bounds__(384, 1) chain_kernel(const ChainArgs a, const __grid_constant__ CUtensorMap tmWq,
    const __grid_constant__ CUtensorMap tmWk, const __grid_constant__ CUtensorMap tmWv, const __grid_constant__ CUtensorMap tmWo) {
  using namespace ch;
  extern __shared__ __align__(1024) unsigned char smem_raw[];
  const uint32_t sb = smem_u32(smem_raw);
  const int warp = __shfl_sync(0xffffffffu, (int)threadIdx.x >> 5, 0);
  const int lane = __shfl_sync(0xffffffffu, (int)threadIdx.x & 31, threadIdx.x & 31);
  const int cta = blockIdx.x, h = cta / 3, j = cta % 3;
  const int g = lane >> 2, q4 = lane & 3, r8 = lane & 7, m4 = lane >> 3;
  unsigned char* const arena = a.arena;
  if (sb & 1023u) __trap();
  asm volatile("griddepcontrol.launch_dependents;");
  TL_BEGIN(a.tl);
#ifdef TIMELINE
  const unsigned long long g_tl0 = gtime();
#define PT(i) TLW((a.tl >= 12) * 128 + 64 + (i))
#else
#define PT(i)
#endif
  const int col0 = j == 0 ? 0 : (j == 1 ? 224 : 432);
  auto stage_w = [&](const CUtensorMap* tm, uint32_t dst, uint32_t mb, int half) {
    mbar_expect_tx(mb + 8 * half, 40960);
    tma_load_2d(dst + half * 40960, tm, h * cfg::DH + j * 64, half * 320, mb + 8 * half);
    tma_load_2d(dst + half * 40960 + 20480, tm, h * cfg::DH + j * 64, half * 320 + 160, mb + 8 * half);
  };
  if (threadIdx.x == 256) {
    for (int i = 0; i < 9; i++) mbar_init(sb + MB_K + 8 * i, 1);
    mbar_init(sb + MB_S, 1); mbar_init(sb + MB_O, 1); mbar_init(sb + MB_X, 1);
    asm volatile("fence.mbarrier_init.release.cluster;" ::: "memory");
    for (int i = 0; i < 2; i++) { stage_w(&tmWk, sb + OFF_WQ, sb + MB_K, i); stage_w(&tmWv, sb + OFF_WO, sb + MB_V, i); }
    sts32(sb + SC_W, 0); sts32(sb + SC_W + 4, 0); sts32(sb + SC_W + 8, 0); sts32(sb + SC_IN + 12, 0); sts32(sb + SC_IN + 20, 0); sts32(sb + SC_TW + 4, 99);
    mbar_expect_tx(sb + MB_S, 1280); mbar_expect_tx(sb + MB_O, 2048);
  }
  __syncthreads();
  asm volatile("barrier.cluster.arrive.relaxed.aligned;" ::: "memory");
  const uint32_t d1 = mapa_u32(sb, (j + 1) % 3) - sb, d2 = mapa_u32(sb, (j + 2) % 3) - sb;

  if (warp >= 8) {
    asm volatile("setmaxnreg.dec.sync.aligned.u32 40;");
    const int hw = warp - 8, ht = hw * 32 + lane;
    const bool lead = ht == 0;
    auto stage_wo = [&](int i) {
      mbar_expect_tx(sb + MB_R + 8 * i, 64 * WOS);
      tma_load_2d(sb + OFF_WO + i * 64 * WOS, &tmWo, col0, h * cfg::DH + ((i + j) % 3) * 64, sb + MB_R + 8 * i);
    };
    const unsigned char* xg = (const unsigned char*)a.xh;
    auto issue_x = [&](int s) { mbar_expect_tx(sb + MB_X, 40960); bulk_g2s(sb + OFF_X, xg + (size_t)s * 40960, 40960, sb + MB_X); };
    uint4 v[5];
#pragma unroll
    for (int i = 0; i < 5; i++) { const int c = ht + 128 * i; v[i] = ld_relaxed_v4(a.mem0 + (c & 7) * cfg::DM + (c >> 3) * 8); }
    if (hw == 2) {
      asm volatile("griddepcontrol.wait;" ::: "memory");
      if (lane == 0) { if (cta == 0) st_relaxed_u32(a.go, 1); issue_x(0); }
      PT(0);
    }
    if (hw == 0) {
      bar_sync(B_QK, 160); if (lane == 0) stage_w(&tmWq, sb + OFF_WQ, sb + MB_Q, 0);
      bar_sync(B_SL, 160); if (lane == 0) stage_w(&tmWq, sb + OFF_WQ, sb + MB_Q, 1);
    }
    if (hw == 1) {
      bar_sync(B_V, 160); if (lane == 0) stage_wo(0);
      bar_sync(B_O, 160); if (lane == 0) { stage_wo(1); stage_wo(2); }
    }
    __syncwarp();
    {
      uint32_t m = 0;
#pragma unroll
      for (int i = 0; i < 5; i++) {
        m = amax_bf2(amax_bf2(m, amax_bf2(v[i].x, v[i].y)), amax_bf2(v[i].z, v[i].w));
      }
      m = amax_fold(m);
      if (lane == 0) sts32(sb + SC_MX + hw * 4, m);
      bar_sync(B_H, 128);
      const uint4 mm = lds128(sb + SC_MX);
      const int se = max(wscale_exp(max(max(mm.x, mm.y), max(mm.z, mm.w))), -100);
      const float sc = exp2i(se);
#pragma unroll
      for (int i = 0; i < 5; i++) {
        const int c = ht + 128 * i, t = c & 7, chn = c >> 3;
        sts128(sb + OFF_MEM + chn * 128 + ((t ^ (2 * (chn & 3))) << 4), bf2_to_h2(v[i].x, sc), bf2_to_h2(v[i].y, sc), bf2_to_h2(v[i].z, sc), bf2_to_h2(v[i].w, sc));
      }
      if (lead) { sts32(sb + SC_IN, __float_as_uint(exp2i(-se))); sts32(sb + SC_IN + 4, 0x7800u); }
    }
    if (hw == 0) PT(11);
    {
      const uint32_t p0 = sb + OFF_WQ + hw * 2048 + lane * 16;
      uint32_t m = 0;
#pragma unroll 1
      for (int i = 0; i < 10; i++) {
        if (i == 0 || i == 5) mbar_wait(sb + MB_Q + (i ? 8 : 0), 0);
        uint32_t r[4][4];
        static_for<0, 4>([&](auto K) { ldsm_x4_i<K.value * 512>(r[K.value], p0 + i * 8192); });
#pragma unroll
        for (int k = 0; k < 4; k++) m = amax_bf2(amax_bf2(m, amax_bf2(r[k][0], r[k][1])), amax_bf2(r[k][2], r[k][3]));
      }
      if (hw == 0) PT(9);
      m = amax_fold(m);
      if (lane == 0) asm volatile("red.shared.max.u32 [%0], %1;" :: "r"(sb + SC_W + 8), "r"(m) : "memory");
      bar_sync(B_H, 128);
      const uint32_t sc = (uint32_t)(wscale_exp(lds32_i<SC_W + 8>(sb)) + 127) * 0x00800080u;
#pragma unroll 1
      for (int i = 0; i < 10; i++) {
        uint32_t r[4][4];
        static_for<0, 4>([&](auto K) { ldsm_x4_i<K.value * 512>(r[K.value], p0 + i * 8192); });
#pragma unroll
        for (int k = 0; k < 4; k++) {
          bf2_to_h2_inplace(r[k][0], sc); bf2_to_h2_inplace(r[k][1], sc); bf2_to_h2_inplace(r[k][2], sc); bf2_to_h2_inplace(r[k][3], sc);
          stsm_x4(p0 + i * 8192 + k * 512, r[k][0], r[k][1], r[k][2], r[k][3]);
        }
      }
    }
    if (hw == 0) PT(10);
    bar_sync(0, 384);
    if (hw == 3) {
      const uint32_t eye = (m4 == q4) ? ((lane & 4) ? 0x3f800000u : 0x3f80u) : 0u;
      sts128(sb + OFF_LT + lane * 16, eye, eye, (lane & 2) * 64 + g * 16 + (lane & 1) * 8, 0u);
      sts64(sb + OFF_S + 1280 + lane * 8, 0u, 0u);
    }
    if (lead) st_relaxed_u32(arena + AR_TAB + cta * 4, 0x80000000u | (lds32_i<SC_W>(sb) << 15) | lds32_i<SC_W + 4>(sb));
    asm volatile("barrier.cluster.wait.aligned;" ::: "memory");
    bar_sync(B_MEM0, 256); bar_sync(B_MEM1, 256);
    {
      uint32_t v0, v1, v2; int spin = 0;
      do {
        v0 = ld_relaxed_u32(arena + AR_TAB + lane * 4); v1 = ld_relaxed_u32(arena + AR_TAB + 128 + lane * 4); v2 = ld_relaxed_u32(arena + AR_TAB + 256 + lane * 4);
      } while (__any_sync(0xffffffffu, ((v0 & v1 & v2) >> 31) == 0) && ++spin < SPIN_LIMIT);
      const uint32_t mv = (max(max(v0, v1), v2) >> 15) & 0x7fffu, mo = max(max(v0 & 0x7fffu, v1 & 0x7fffu), v2 & 0x7fffu);
      sts32(sb + SC_IN + 8 + (lane & 1) * 16, 15 - ((__reduce_max_sync(0xffffffffu, mv) >> 7) + (__reduce_max_sync(0xffffffffu, mo) >> 7) - 252 + 22));
    }

    auto store_kv = [&](int s) {
      const size_t o = ((size_t)s * 96 + cta) * KVB; const uint32_t src = sb + OFF_KV + (s & 1) * (2 * KVB);
      fence_proxy_async(); bulk_s2g(a.kg + o, src, KVB); bulk_s2g(a.vg + o, src + KVB, KVB); bulk_commit();
    };
    const int cb28 = unit28(hw), du = (unit24(hw) - cb28) * 128;
    uint32_t n16 = lane * 16, hist = 0;
    const uint32_t us1 = sb + d1 + OFF_SR + 256 + (hw >> 1) * 512 + (hw & 1) * 128, us2 = sb + d2 + OFF_SR + (hw >> 1) * 512 + (hw & 1) * 128;
    const uint32_t uo1 = sb + d1 + OFF_O + 2048 + hw * 256, uo2 = sb + d2 + OFF_O + 1024 + hw * 256;
#ifdef STEPCLK
    if (lead) a.dbg[96 * 300 + cta * 2] = clk32();
#endif
#ifdef TIMELINE
    if (cta == 0 && lead) { g_tl2[(a.tl >= 12) * 128 + 0] = clock64(); g_tl2[(a.tl >= 12) * 128 + 1] = gtime(); }
#endif
#pragma unroll 1
    for (int s = 0; s < cfg::NSEG; s++) {
      TS_SETUP();
      const bool last = s == cfg::NSEG - 1;
      if (n16 == 0) {
        if (hw == 2 && !last) issue_x(s + 1);
        if (hw == 0 && (s & 3) == 1 && s > 1) st_relaxed_u32(arena + (prog_off(h, j) + lds32_i<SC_IN + 12>(sb)), s - 1);
        if (hw == 0 && s > 0) store_kv(s - 1);
        if (PFX && hw == 3 && cta < 80 && s + PFX < cfg::NSEG) prefetch_l2(xg + (size_t)(s + PFX) * 40960 + cta * 512, 512);
        if (PFACC && hw == 1 && s + PFACC < cfg::NSEG - 1)
          asm volatile("prefetch.global.L2 [%0];" :: "l"(arena + (AR_ACC + acc_step(s + PFACC) + acc_lane(cta / 24, (cta & 3) * 8) + acc_voff((cta % 24) >> 2))) : "memory");
      }
      __syncwarp();
      if (last) break;
      const uint32_t kv = (s & 1) * (2 * KVB);
      n16 = fresh(n16);
      uint32_t kb0[4], kb1[4];
      { const uint32_t ka = n16 + (n16 & 384) * 4 + (sb + kv + hw * 128); ldsm_x4_i<OFF_KV>(kb0, ka); ldsm_x4_i<OFF_KV + 2560>(kb1, ka); }
      TS(1);
      bar_sync(B_QK, 384);
      {
        uint32_t q0[4], q1[4], q2[4], q3[4];
        float sa[4] = {0, 0, 0, 0}, sc2[4] = {0, 0, 0, 0};
        ldsm_x4_i<OFF_Q>(q0, n16 + sb); ldsm_x4_i<OFF_Q + 1024>(q2, n16 + sb); ldsm_x4_i<OFF_Q + 512>(q1, n16 + sb);
        bar_arrive(B_A, 288);
        ldsm_x4_i<OFF_Q + 1536>(q3, n16 + sb);
        mma16816(sa, q0[0], q0[1], q0[2], q0[3], kb0[0], kb0[1]);
        mma16816(sc2, q2[0], q2[1], q2[2], q2[3], kb1[0], kb1[1]);
        mma16816(sa, q1[0], q1[1], q1[2], q1[3], kb0[2], kb0[3]);
        mma16816(sc2, q3[0], q3[1], q3[2], q3[3], kb1[2], kb1[3]);
        const float x0 = (sa[0] + sa[2]) + (sc2[0] + sc2[2]), x1 = (sa[1] + sa[3]) + (sc2[1] + sc2[3]);
        const uint32_t xp = pack_bf16(x0, x1);
        st_async_b32_i<0>((n16 >> 2) + us1, xp, sb + MB_S + d1);
        st_async_b32_i<0>((n16 >> 2) + us2, xp, sb + MB_S + d2);
        stsm_x2(n16 + (sb + OFF_S + hw * 256), __float_as_uint(x0), __float_as_uint(x1));
      }
      TS(3);
      uint32_t v0[4], v1[4], vm0, vm1;
      const uint32_t uv = sb + kv + hw * 1280;
      ldsm_x4_t_i<OFF_KV + KVB>(v0, n16 + uv); ldsm_x4_t_i<OFF_KV + KVB + 640>(v1, n16 + uv);
      bar_sync(B_SL, 256);
      float t0[4], t1[4], t2[4];
      { uint32_t x[4]; ldsm_x4_i<OFF_S>(x, n16 + sb); t0[0] = __uint_as_float(x[0]); t0[1] = __uint_as_float(x[1]); t0[2] = __uint_as_float(x[2]); t0[3] = __uint_as_float(x[3]); }
      { uint32_t x[4]; ldsm_x4_i<OFF_S + 512>(x, n16 + sb); t1[0] = __uint_as_float(x[0]); t1[1] = __uint_as_float(x[1]); t1[2] = __uint_as_float(x[2]); t1[3] = __uint_as_float(x[3]); }
      { uint32_t x[4]; ldsm_x4_i<OFF_S + 1024>(x, n16 + sb); t2[0] = __uint_as_float(x[0]); t2[1] = __uint_as_float(x[1]); t2[2] = __uint_as_float(x[2]); t2[3] = __uint_as_float(x[3]); }
      mbar_spin(sb + MB_S, s & 1);
      TS(4);
      uint2 xo;
      {
        uint32_t r0[4], r1[4], r2[2];
        ldsm_x4_i<OFF_SR>(r0, n16 + sb); ldsm_x4_i<OFF_SR + 512>(r1, n16 + sb); ldsm_x2_i<OFF_SR + 1024>(r2, n16 + sb);
        SFENCE(n16);
        const uint2 eye = lds64_i<OFF_LT>(n16 + sb);
        mma16816(t0, r0[0], r0[1], r0[2], r0[3], eye.x, eye.y);
        mma16816(t1, r1[0], r1[1], r1[2], r1[3], eye.x, eye.y);
        mma1688(t2, r2[0], r2[1], eye.x);
        bar_sync(B_V, 256);
        vm0 = ldsm_x1_t_i<OFF_KV + KVB + 512>(n16 + uv); vm1 = ldsm_x1_t_i<OFF_KV + KVB + 1152>(n16 + uv);
        SFENCE(n16);
        xo = lds64_i<OFF_LT + 8>(n16 + sb);
      }
      float sc[10] = {t0[0], t0[1], t0[2], t0[3], t1[0], t1[1], t1[2], t1[3], t2[0] + t2[2], t2[1] + t2[3]};
      const float cs = 0.07216878364870322f * 1.4426950408889634f;
      float mx = fmaxf(fmaxf(fmaxf(sc[0], sc[1]), fmaxf(sc[2], sc[3])), fmaxf(fmaxf(sc[4], sc[5]), fmaxf(sc[6], sc[7])));
      mx = fmaxf(mx, fmaxf(sc[8], sc[9]));
      {
        const float m1 = __shfl_xor_sync(0xffffffffu, mx, 1), m2 = __shfl_xor_sync(0xffffffffu, mx, 2), m3 = __shfl_xor_sync(0xffffffffu, mx, 3);
        mx = fmaxf(fmaxf(mx, m1), fmaxf(m2, m3));
      }
      const float mo = fmaf(mx, -cs, __uint_as_float(xo.x));
      auto ex = [&](int i) -> uint32_t { float x, y;
        asm volatile("ex2.approx.ftz.f32 %0, %1;" : "=f"(x) : "f"(fmaf(sc[i], cs, mo))); asm volatile("ex2.approx.ftz.f32 %0, %1;" : "=f"(y) : "f"(fmaf(sc[i + 1], cs, mo)));
        return pack_bf16(x, y); };
      float oa[4] = {0, 0, 0, 0}, ob[4] = {0, 0, 0, 0}, oc[4] = {0, 0, 0, 0}, od[4] = {0, 0, 0, 0}, rs[4] = {0, 0, 0, 0};
      const uint32_t ones = 0x3f803f80u;
      const uint32_t p4 = ex(8);
      if (MEMFIRST) { mma1688(rs, p4, 0u, ones); mma1688(oa, p4, 0u, vm0); mma1688(ob, p4, 0u, vm1); }
      const uint32_t p0 = ex(0), p1 = ex(2), p2 = ex(4), p3 = ex(6);
      TS(5);
      mma16816(rs, p0, p2, p1, p3, ones, ones);
      mma16816(oa, p0, p2, p1, p3, v0[0], v0[1]);
      mma16816(oc, p0, p2, p1, p3, v0[2], v0[3]);
      mma16816(ob, p0, p2, p1, p3, v1[0], v1[1]);
      mma16816(od, p0, p2, p1, p3, v1[2], v1[3]);
      if (!MEMFIRST) { mma1688(rs, p4, 0u, ones); mma1688(oa, p4, 0u, vm0); mma1688(ob, p4, 0u, vm1); }
      const float inv = rcpf(rs[0] + rs[2]) * __uint_as_float(xo.y);
      {
        const uint32_t y0 = pack_bf16((oa[0] + oc[2]) * inv, (oa[1] + oc[3]) * inv), y1 = pack_bf16((ob[0] + od[2]) * inv, (ob[1] + od[3]) * inv);
        st_async_v2_i<0>(xo.x + uo1, y0, y1, sb + MB_O + d1);
        st_async_v2_i<0>(xo.x + uo2, y0, y1, sb + MB_O + d2);
        sts64_i<OFF_O>(xo.x + (sb + hw * 256), y0, y1);
      }
      bar_arrive(B_O, 384);
      TS(6);
      if (hw == 0) bulk_wait<0>();
      mbar_expect_tx_if(n16 == 0 && hw == 3, sb + MB_S, 1280);
      n16 = fresh(n16);
      const int ln = n16 >> 4;
      auto mslot = [&](int c) -> uint32_t { return sb + OFF_MEM + c * 128 + (((ln >> 2) ^ (2 * (c & 3))) << 4); };
      const int lq = ln & 3;
      const uint32_t ma = mslot(cb28 + lq), mb_ = mslot(cb28 + (lq >> 1)) + (lq & 1) * 8;
      const unsigned char* gp = arena + (AR_ACC + acc_lane(hw, ln) + acc_step(s));
      const bool odd = ln & 1;
      const uint32_t delay = a.delay + ((hist & 2) ? a.margin : 0);
      SFENCE(ma);
      uint32_t tw;
      if (hw == 0 && (s & 3) == 0 && a.pubrel) {
        bar_arrive(B_RED, 384);
        asm volatile("fence.acq_rel.gpu;" ::: "memory");
        uint2 t; int sp = 0;
        do { asm volatile("ld.volatile.shared.v2.u32 {%0,%1}, [%2];" : "=r"(t.x), "=r"(t.y) : "r"(sb + SC_TW) : "memory"); } while (__any_sync(0xffffffffu, t.y != (uint32_t)s) && ++sp < SPIN_LIMIT);
        tw = t.x;
      } else {
        bar_sync(B_RED, 384);
        SFENCE(mb_);
        tw = clk_v();
        if (hw == 1) asm volatile("st.volatile.shared.v2.u32 [%0], {%1,%2};" :: "r"(sb + SC_TW), "r"(tw), "r"(s) : "memory");
      }
      TSV(7, tw);
      mbar_expect_tx_if(n16 == 0 && hw == 3, sb + MB_O, 2048);
      while (clk_v() - tw < delay) {}
      TS(8);
      uint4 v[6];
      int spin = 0;
      const uint32_t cm = odd ? 0x5000u : 0u;
      do {
        static_for<0, 6>([&](auto I) { v[I.value] = ld_relaxed_v4_i<acc_voff(I.value)>(gp); });
      } while (__any_sync(0xffffffffu, (~((v[0].w & v[1].w & v[2].w) & (v[3].w & v[4].w & v[5].w)) & cm) != 0) && ++spin < SPIN_LIMIT);
      v[0].w = odd ? v[3].x : v[0].w; v[1].w = odd ? v[3].y : v[1].w; v[2].w = odd ? v[3].z : v[2].w; v[3].w = odd ? 0u : v[3].w;
      sts128_i<0>(ma, v[0].x, v[0].y, v[0].z, v[0].w);
      sts128_i<512>(ma, v[1].x, v[1].y, v[1].z, v[1].w);
      sts128_i<1024>(ma, v[2].x, v[2].y, v[2].z, v[2].w);
      sts128_i<0>(ma + du, v[4].x, v[4].y, v[4].z, v[5].z);
      sts64_i<512>(mb_ + du, v[5].x, v[5].y);
      if (!odd) sts128_i<1536>(mb_, v[3].x, v[3].y, v[3].z, v[3].w);
      hist = (hist * 2 + (spin != 0)) & 0xffffu;
      TSV(11, spin);
#ifdef TIMELINE
      if (spin && ln == 0) atomicAdd(&g_tl2[(a.tl >= 12) * 128 + 4], 1ull);
#endif
      TS(10);
      bar_sync(B_MEM0, 256); bar_sync(B_MEM1, 256);
      uint32_t m = lds32_i<SC_IN + 12>(sb);
      uint32_t m2 = m;
      static_for<0, 3>([&](auto I) { m = amax_h2(amax_h2(amax_h2(amax_h2(m, v[I.value].x), v[I.value].y), v[I.value].z), v[I.value].w); });
      static_for<3, 6>([&](auto I) { m2 = amax_h2(amax_h2(amax_h2(m2, v[I.value].x), v[I.value].y), v[I.value].z); });
      m = amax_fold(amax_h2(amax_h2(m2, v[3].w), m));
      if (n16 == 0) asm volatile("red.shared.max.u32 [%0], %1;" :: "r"(sb + SC_IN + 4 + 16 * ((s + 1) & 1)), "r"(m) : "memory");
    }
    bar_sync(B_RED, 384);
    if (hw == 0 && n16 == 0) {
      store_kv(cfg::NSEG - 1);
      bulk_wait<0>();
      st_release_u32(arena + (prog_off(h, j) + lds32_i<SC_IN + 12>(sb)), cfg::NSEG);
    }
    __syncwarp();
#ifdef STEPCLK
    if (hw == 0 && n16 == 0) a.dbg[96 * 300 + cta * 2 + 1 + (hist >> 20)] = clk32();
#endif
#ifdef TIMELINE
    if (cta == 0 && hw == 0 && n16 == 0) { g_tl2[(a.tl >= 12) * 128 + 2] = clock64(); g_tl2[(a.tl >= 12) * 128 + 3] = gtime(); }
#endif
    TL_END(a.tl);
    asm volatile("barrier.cluster.arrive.relaxed.aligned; barrier.cluster.wait.aligned;" ::: "memory");
  } else {
    asm volatile("setmaxnreg.inc.sync.aligned.u32 232;");
    const int wi = warp & 3, hf = warp >> 2, tid = warp * 32 + lane;
    uint32_t w[40][4], wm = 0;
    uint32_t wqa;
    { const int mrow = r8 + ((lane >> 4) << 3), mch = 2 * wi + (m4 & 1); wqa = sb + mrow * 128 + ((mch ^ r8) << 4); }
    {
      const uint32_t wa = wqa + (hf ? OFF_WO : OFF_WQ);
      mbar_wait(sb + (hf ? MB_V : MB_K), 0);
      static_for<0, 20>([&](auto K) { ldsm_x4_t_i<K.value * 2048>(w[K.value], wa); });
#pragma unroll
      for (int k = 0; k < 20; k++) wm = amax_bf2(amax_bf2(wm, amax_bf2(w[k][0], w[k][1])), amax_bf2(w[k][2], w[k][3]));
      SFENCE2(wa, wm);
      if (warp == 0) PT(1);
      bar_arrive(hf ? B_V : B_QK, 160);
      mbar_wait(sb + (hf ? MB_V : MB_K) + 8, 0);
      static_for<20, 40>([&](auto K) { ldsm_x4_t_i<K.value * 2048>(w[K.value], wa); });
#pragma unroll
      for (int k = 20; k < 40; k++) wm = amax_bf2(amax_bf2(wm, amax_bf2(w[k][0], w[k][1])), amax_bf2(w[k][2], w[k][3]));
      SFENCE2(wa, wm);
      if (warp == 4) PT(2);
      bar_arrive(hf ? B_O : B_SL, 160);
      SFENCE(wa);
    }
    float iw, iq;
    {
      const uint32_t m = amax_fold(wm);
      if (hf && lane == 0) asm volatile("red.shared.max.u32 [%0], %1;" :: "r"(sb + SC_W), "r"(m) : "memory");
      const int e = wscale_exp(m);
      const uint32_t sc = (uint32_t)(e + 127) * 0x00800080u; iw = exp2i(-e);
#pragma unroll
      for (int k = 0; k < 40; k++) { bf2_to_h2_inplace(w[k][0], sc); bf2_to_h2_inplace(w[k][1], sc); bf2_to_h2_inplace(w[k][2], sc); bf2_to_h2_inplace(w[k][3], sc); }
    }
    uint32_t x0[8];
    {
      float xa[16];
      const uint32_t dlo = (((sb + OFF_X) & 0x3FFFF) >> 4) | (1u << 16);
      if (warp == 0) PT(3);
      mbar_wait(sb + MB_X, 0);
      if (warp == 0) PT(4);
      wgmma_fence();
      static_for<0, 40>([&](auto K) { constexpr int k = K.value; wgmma_rs32h<((k >> 2) * 4096 + (k & 3) * 32) / 16, (k != 0)>(xa, w[k], dlo); });
      wgmma_commit();
      wgmma_wait<0>();
#pragma unroll
      for (int i = 0; i < 8; i++) x0[i] = pack_bf16(xa[2 * i] * iw, xa[2 * i + 1] * iw);
    }
    const bool t28 = j == 0 || warp < 4;
    const int bi = j == 0 ? hf : (warp < 4 ? j + 1 : 2 * (j - 1) + ((warp - 4) >> 1)), bv = t28 ? wi : 4 + (warp & 1);
    uint32_t wo1 = sb + OFF_WO + warp * 896 + lane * 16, wo2;
    {
      const int cb = (t28 ? unit28(bi) : unit24(bi)) - col0 / 8;
      uint32_t cp[4];
#pragma unroll
      for (int wd = 0; wd < 4; wd++) {
        int c, p;
        if (bv < 3) { c = 4 * bv + q4; p = wd; }
        else if (bv == 3) { if (q4 & 1) { c = 4 * (wd % 3) + q4; p = 3; } else { c = 12 + (q4 >> 1); p = wd; } }
        else if (bv == 4) { c = q4; p = wd; }
        else { if (wd < 2) { c = 4 + (q4 >> 1); p = 2 * (q4 & 1) + wd; } else { c = q4; p = 3; } }
        cp[wd] = sb + OFF_WO + ((g & 1) + (g & 2) * 4 + (g >> 2) * 2) * WOS + (cb + c) * 16 + p * 4;
      }
      const int cidx = (r8 & 1) + ((r8 >> 2) << 1);
      wo2 = sb + OFF_WO + warp * 896 + ((m4 & 1) ? 768 + (m4 >> 1) * 64 + cidx * 16 : 512 + (m4 >> 1) * 128 + r8 * 16);
      const bool dump = (m4 & 1) && (r8 & 2);
      uint32_t mo = 0;
      const bool regular = bv < 3 || bv == 4;
#pragma unroll 1
      for (int i = 0; i < 3; i++) {
        uint32_t x[4][4], y[4][4];
        const uint32_t o = i * 4 * WOK;
        mbar_wait(sb + MB_R + 8 * i, 0);
        if (warp == 0) PT(5 + i);
        if (regular) {
          static_for<0, 4>([&](auto K) {
            constexpr int kk = K.value;
            const uint4 u = lds128_i<kk * WOK>(cp[0] + o), v = lds128_i<kk * WOK + 4 * WOS>(cp[0] + o);
            x[kk][0] = u.x; x[kk][1] = u.y; x[kk][2] = u.z; x[kk][3] = u.w; y[kk][0] = v.x; y[kk][1] = v.y; y[kk][2] = v.z; y[kk][3] = v.w;
          });
        } else {
          static_for<0, 4>([&](auto K) {
            constexpr int kk = K.value;
#pragma unroll
            for (int wd = 0; wd < 4; wd++) { x[kk][wd] = lds32_i<kk * WOK>(cp[wd] + o); y[kk][wd] = lds32_i<kk * WOK + 4 * WOS>(cp[wd] + o); }
          });
        }
        bar_sync(B_C, 256);
        static_for<0, 4>([&](auto K) {
          constexpr int kk = K.value;
#pragma unroll
          for (int wd = 0; wd < 4; wd++) mo = amax_bf2(mo, amax_bf2(x[kk][wd], y[kk][wd]));
          stsm_x4_t_i<kk * WOK>(wo1 + o, x[kk][0], x[kk][1], y[kk][0], y[kk][1]);
          stsm_x4_t_i<0>(dump ? sb + OFF_S + 512 + lane * 16 : wo2 + o + kk * WOK, x[kk][2], x[kk][3], y[kk][2], y[kk][3]);
        });
      }
      if (warp == 0) PT(8);
      mo = amax_fold(mo);
      if (lane == 0) asm volatile("red.shared.max.u32 [%0], %1;" :: "r"(sb + SC_W + 4), "r"(mo) : "memory");
    }
    __syncwarp();
    auto run = [&](auto HF) {
    constexpr int hf = HF.value;
    uint32_t mema, sta, l16 = sb + lane * 16;
    uint32_t rq[hf ? NQ1 : NQ0][4];
    auto step_addr = [&](uint32_t kv) {
      const int lr = (l16 >> 4) & 7, lm = (l16 >> 7) & 3;
      mema = l16 ^ (lm << 5);
      sta = sb + lr * 16 + (lm < 2 ? OFF_Q + wi * 512 + hf * 128 + lm * 256 : OFF_KV + kv + 512 + (2 * wi + lm - 2) * 640);
    };
    auto x_gemm = [&](uint32_t ph, [[maybe_unused]] uint32_t tsb) {
      float xa[16];
      const uint32_t dlo = (((sb + OFF_X) & 0x3FFFF) >> 4) | (1u << 16);
      constexpr int NP = hf ? NQ1 : NP0;
      if constexpr (hf) {
        static_for<PQE, NP>([&](auto K) { ldsm_x4_t_i<OFF_WQ + K.value * 2048>(rq[K.value], wqa); });
        bar_sync(B_X, 256);
      }
      wgmma_fence();
      static_for<0, 40>([&](auto K) {
        constexpr int k = K.value;
        wgmma_rs32h<((k >> 2) * 4096 + (k & 3) * 32) / 16, (k != 0)>(xa, w[k], dlo);
        if constexpr (!hf && k == PFK && NP > PQE) { SFENCE(wqa); static_for<PQE, NP>([&](auto K) { ldsm_x4_t_i<OFF_WQ + K.value * 2048>(rq[K.value], wqa); }); SFENCE(wqa); }
        if constexpr (!hf && k == XT) bar_arrive(B_X, 256);
      });
      step_addr(ph * (2 * KVB));
      wgmma_commit();
      TS(9);
      wgmma_wait<0>();
      const uint32_t xs = l16 + (wi * 1280 + ph * (2 * KVB));
      stsm_x4_t_i<OFF_KV + hf * KVB>(xs, pack_bf16(xa[0] * iw, xa[1] * iw), pack_bf16(xa[4] * iw, xa[5] * iw), pack_bf16(xa[8] * iw, xa[9] * iw), pack_bf16(xa[12] * iw, xa[13] * iw));
      stsm_x4_t_i<OFF_KV + hf * KVB + 640>(xs, pack_bf16(xa[2] * iw, xa[3] * iw), pack_bf16(xa[6] * iw, xa[7] * iw), pack_bf16(xa[10] * iw, xa[11] * iw), pack_bf16(xa[14] * iw, xa[15] * iw));
    };
    auto wq_addr = [&](uint32_t l) -> uint32_t {
      const int lr = (l >> 4) & 7, lm = (l >> 7) & 3;
      return sb + hf * ((40 - NQ1) * 2048) + (lr + ((lm >> 1) << 3)) * 128 + (((2 * wi + (lm & 1)) ^ lr) << 4);
    };
    constexpr int NPM = hf ? NPM1 : NPM0;
    uint32_t u1[NPM][4], u2[NPM][4];
    static_for<0, NPM>([&](auto K) { ldsm_x4_i<(12 - NPM + K.value) * WOK>(u1[K.value], wo1); ldsm_x4_i<(12 - NPM + K.value) * WOK>(u2[K.value], wo2); });
    bar_sync(0, 384);
    iq = uniform_f(exp2i(-wscale_exp(lds32_i<SC_W + 8>(sb))));
    wqa = wq_addr(l16);
    static_for<0, (hf ? NQ1 : NP0)>([&](auto K) { ldsm_x4_t_i<OFF_WQ + K.value * 2048>(rq[K.value], wqa); });
    step_addr(0);
    stsm_x4_t_i<OFF_KV + hf * KVB>(l16 + wi * 1280, x0[0], x0[2], x0[4], x0[6]);
    stsm_x4_t_i<OFF_KV + hf * KVB + 640>(l16 + wi * 1280, x0[1], x0[3], x0[5], x0[7]);
    asm volatile("barrier.cluster.wait.aligned;" ::: "memory");
    TL_END(a.tl + 1);
#pragma unroll 1
    for (int s = 0; s < cfg::NSEG - 1; s++) {
      TS_SETUP();
#if CHAIN_TIMING
      if (tid == 0 && (s & 7) == 0) a.dbg[96 * 288 + cta * 8 + (s >> 3)] = clk32();
#endif
      bar_sync(hf ? B_MEM1 : B_MEM0, 256);
      const float sin_ = __uint_as_float(lds32_i<SC_IN>(sb + 16 * (s & 1)));
      constexpr int NPQ = (40 - NQ1) / 2;
      if constexpr (hf == 0) {
        float k0[4] = {0, 0, 0, 0}, k1[4] = {0, 0, 0, 0}, q0[4] = {0, 0, 0, 0}, q1[4] = {0, 0, 0, 0};
        constexpr auto pair_of = [](int t) { const int a = t * (20 - NPQ) / 20, b = (t + 1) * (20 - NPQ) / 20; return b > a ? NPQ + a : t - a; };
        uint32_t b[NB0][4];
        static_for<0, NB0>([&](auto T) { ldsm_x4_i<OFF_MEM + pair_of(T.value) * 512>(b[T.value], mema); });
        static_for<NP0, NQ0>([&](auto K) { ldsm_x4_t_i<OFF_WQ + K.value * 2048>(rq[K.value], wqa); });
        if (BBS < 100) bbfence<0>(mema);
        static_for<0, 20>([&](auto T) {
          constexpr int t = T.value, p = pair_of(t);
          uint32_t (&bb)[4] = b[t % NB0];
          if constexpr (p < NPQ) {
            mma16816h(q0, rq[(2 * p) % NQ0], bb[0], bb[1]);
            if constexpr (2 * p + NQ0 < 2 * NPQ) ldsm_x4_t_i<OFF_WQ + (2 * p + NQ0) * 2048>(rq[(2 * p) % NQ0], wqa);
          }
          mma16816h(k0, w[2 * p], bb[0], bb[1]);
          if constexpr (p < NPQ) {
            mma16816h(q1, rq[(2 * p + 1) % NQ0], bb[2], bb[3]);
            if constexpr (2 * p + 1 + NQ0 < 2 * NPQ) ldsm_x4_t_i<OFF_WQ + (2 * p + 1 + NQ0) * 2048>(rq[(2 * p + 1) % NQ0], wqa);
          }
          mma16816h(k1, w[2 * p + 1], bb[2], bb[3]);
          if constexpr (NVE > 0 && t + NB0 == VET) bar_arrive(B_E, 256);
          if constexpr (t + NB0 < 20) ldsm_x4_i<OFF_MEM + pair_of(t + NB0) * 512>(bb, mema);
          if constexpr (t < 20 - NB0 && (t % BBS) == BBS - 1) bbfence<t + 1>(mema);
        });
        const float sq = sin_ * iq, sk = sin_ * iw;
        stsm_x4_t_i<0>(sta, pack_bf16((q0[0] + q1[0]) * sq, (q0[1] + q1[1]) * sq), pack_bf16((q0[2] + q1[2]) * sq, (q0[3] + q1[3]) * sq),
                       pack_bf16((k0[0] + k1[0]) * sk, (k0[1] + k1[1]) * sk), pack_bf16((k0[2] + k1[2]) * sk, (k0[3] + k1[3]) * sk));
        bar_sync(B_QK, 384);
        TS(2);
        {
          if (wi == 3) {
            const uint32_t xr = sb + ((l16 & 511) >> 2), ka = l16 + (l16 & 384) * 4 + (s & 1) * (2 * KVB);
            uint32_t a0[4], a1[4], a2[4], a3[4], kb0[4], kb1[4];
            ldsm_x4_i<OFF_Q>(a0, l16); ldsm_x4_i<OFF_KV + 512>(kb0, ka); ldsm_x4_i<OFF_Q + 1024>(a2, l16); ldsm_x4_i<OFF_KV + 512 + 2560>(kb1, ka);
            ldsm_x4_i<OFF_Q + 512>(a1, l16);
            bar_arrive(B_A, 288);
            ldsm_x4_i<OFF_Q + 1536>(a3, l16);
            float sa[4] = {0, 0, 0, 0}, sc2[4] = {0, 0, 0, 0};
            mma16816(sa, a0[0], a0[1], a0[2], a0[3], kb0[0], kb0[1]);
            mma16816(sc2, a2[0], a2[1], a2[2], a2[3], kb1[0], kb1[1]);
            mma16816(sa, a1[0], a1[1], a1[2], a1[3], kb0[2], kb0[3]);
            mma16816(sc2, a3[0], a3[1], a3[2], a3[3], kb1[2], kb1[3]);
            const float x0 = (sa[0] + sa[2]) + (sc2[0] + sc2[2]), x1 = (sa[1] + sa[3]) + (sc2[1] + sc2[3]);
            const uint32_t xp = pack_bf16(x0, x1);
            st_async_b32_i<OFF_SR + 1024 + 128>(xr + d1, xp, sb + MB_S + d1);
            st_async_b32_i<OFF_SR + 1024>(xr + d2, xp, sb + MB_S + d2);
            stsm_x2(l16 + OFF_S + 1024, __float_as_uint(x0), __float_as_uint(x1));
          } else if (wi == 0) {
            const uint4 si = lds128_i<SC_IN>(sb + 16 * (s & 1));
            const int em = (int)(si.y >> 10) - 14 + (int)(si.x >> 23) - 127;
            const uint32_t osc = __float_as_uint(exp2i(max(min((int)si.z - max(em, 1), 100), -100)));
            sts32(l16 + OFF_LT + 12, osc); sts64_i<SC_IN>(sb + 16 * ((s + 1) & 1), 0x7f000000u - osc, 0u);
          }
          bar_sync(B_SL, 256);
        }
      } else {
        float v0[4] = {0, 0, 0, 0}, v1[4] = {0, 0, 0, 0}, q0[4] = {0, 0, 0, 0}, q1[4] = {0, 0, 0, 0};
        uint32_t b[NQ1 / 2][4];
        static_for<0, NQ1 / 2>([&](auto T) { ldsm_x4_i<OFF_MEM + (NPQ + T.value) * 512>(b[T.value], mema); });
        static_for<0, NQ1 / 2>([&](auto T) {
          constexpr int t = T.value, p = NPQ + t;
          uint32_t (&bb)[4] = b[t];
          mma16816h(q0, rq[2 * t], bb[0], bb[1]);
          mma16816h(q1, rq[2 * t + 1], bb[2], bb[3]);
          mma16816h(v0, w[2 * p], bb[0], bb[1]);
          mma16816h(v1, w[2 * p + 1], bb[2], bb[3]);
        });
        const float sq = sin_ * iq, sv = sin_ * iw;
        stsm_x2_t_i<0>(sta, pack_bf16((q0[0] + q1[0]) * sq, (q0[1] + q1[1]) * sq), pack_bf16((q0[2] + q1[2]) * sq, (q0[3] + q1[3]) * sq));
        TS(2);
        bar_arrive(B_QK, 384);
        float v2[4] = {0, 0, 0, 0}, v3[4] = {0, 0, 0, 0};
        auto vpair = [&](auto P, uint32_t (&bb)[4]) {
          constexpr int p = P.value;
          if constexpr (p & 1) { mma16816h(v0, w[2 * p], bb[0], bb[1]); mma16816h(v1, w[2 * p + 1], bb[2], bb[3]); }
          else { mma16816h(v2, w[2 * p], bb[0], bb[1]); mma16816h(v3, w[2 * p + 1], bb[2], bb[3]); }
        };
        if constexpr (NVE > 0) {
          uint32_t e[NVE ? NVE : 1][4];
          bar_sync(B_E, 256);
          static_for<0, NVE>([&](auto T) { ldsm_x4_i<OFF_MEM + T.value * 512>(e[T.value], mema); });
          static_for<0, NVE>([&](auto T) { vpair(T, e[T.value]); });
        }
        bar_sync(B_A, 288);
        uint32_t c[4][4];
        static_for<NVE, NVE + 4>([&](auto T) { ldsm_x4_i<OFF_MEM + T.value * 512>(c[T.value & 3], mema); });
        static_for<NVE, NPQ>([&](auto T) {
          constexpr int p = T.value;
          vpair(T, c[p & 3]);
          if constexpr (p + 4 < NPQ) ldsm_x4_i<OFF_MEM + (p + 4) * 512>(c[p & 3], mema);
        });
        stsm_x2_t_i<OFF_KV + KVB + 512>(l16 + (l16 & 128) * 4 + (wi * 1280 + (s & 1) * (2 * KVB)), pack_bf16(((v0[0] + v1[0]) + (v2[0] + v3[0])) * sv, ((v0[1] + v1[1]) + (v2[1] + v3[1])) * sv),
                            pack_bf16(((v0[2] + v1[2]) + (v2[2] + v3[2])) * sv, ((v0[3] + v1[3]) + (v2[3] + v3[3])) * sv));
        bar_arrive(B_V, 256);
      }
      TS(3);
      {
        uint32_t t1[12][4], t2[12][4];
        const uint32_t o16 = l16;
        wo1 = l16 + (OFF_WO + warp * 896);
        wo2 = sb + OFF_WO + warp * 896 + ((l16 & 128) ? 768 + ((l16 & 256) >> 2) + (l16 & 16) + ((l16 & 64) >> 1) : 512 + ((l16 & 256) >> 1) + (l16 & 112));
        auto ldw = [&](auto K) { if constexpr (K.value < 12 - NPM) { ldsm_x4_i<K.value * WOK>(t1[K.value], wo1); ldsm_x4_i<K.value * WOK>(t2[K.value], wo2); } };
        constexpr int NR_ = NRT - NPM;
        constexpr int PB = (hf ? PB1 : PB0) < NR_ ? (hf ? PB1 : PB0) : NR_, PA = (hf ? PA1 : PA0) < PB ? (hf ? PA1 : PA0) : PB;
        static_for<0, PA>(ldw);
        mbar_spin(sb + MB_X, (s + 1) & 1);
        if constexpr (PB > PA) {
          constexpr int PM = PA + PM1 < PB ? PA + PM1 : PB;
          mbar_spin(sb + MB_S, s & 1);
          const uint32_t t0 = clk_v();
          if constexpr (PM > PA) { while (clk_v() - t0 < GD1) {} static_for<PA, PM>(ldw); }
          if constexpr (PB > PM) { while (clk_v() - t0 < GD2) {} static_for<PM, PB>(ldw); }
        }
        float c0[4] = {0, 0, 0, 0}, c1[4] = {0, 0, 0, 0}, e0[4] = {0, 0, 0, 0}, e1[4] = {0, 0, 0, 0};
        uint32_t ob[6][4];
        auto kstep = [&](auto K) {
          constexpr int k = K.value;
          uint32_t (&bb)[4] = ob[k >> 1];
          uint32_t (&x)[4] = k < 12 - NPM ? t1[k] : u1[k < 12 - NPM ? 0 : k - (12 - NPM)];
          uint32_t (&y)[4] = k < 12 - NPM ? t2[k] : u2[k < 12 - NPM ? 0 : k - (12 - NPM)];
          if constexpr (k & 1) { mma16816(c1, x[0], x[1], x[2], x[3], bb[2], bb[3]); mma16816(e1, y[0], y[1], y[2], y[3], bb[2], bb[3]); }
          else { mma16816(c0, x[0], x[1], x[2], x[3], bb[0], bb[1]); mma16816(e0, y[0], y[1], y[2], y[3], bb[0], bb[1]); }
          if constexpr (k >= NRF) ldw(IC<k + NR_ - NRF>{});
        };
        auto ldo = [&](auto P) { ldsm_x4_i<OFF_O + P.value * 512>(ob[P.value], o16); };
        TS(4);
        bar_sync(B_O, 384);
        ldo(IC<0>{}); ldo(IC<1>{});
        SFENCE(o16);
        static_for<PB, NR_>(ldw);
        static_for<0, 4>(kstep);
        TS(5);
        mbar_spin(sb + MB_O, s & 1);
        TS(6);
        ldo(IC<2>{}); ldo(IC<NPM >= 2 ? 5 : 3>{});
        if (WOF) SFENCE(o16);
        kstep(IC<4>{});
        if constexpr (NPM < 2) { kstep(IC<5>{}); ldo(IC<4>{}); kstep(IC<6>{}); kstep(IC<7>{}); ldo(IC<5>{}); static_for<8, 12>(kstep); }
        else if constexpr (NPM >= 4) { kstep(IC<10>{}); kstep(IC<11>{}); ldo(IC<4>{}); kstep(IC<5>{}); ldo(IC<3>{}); kstep(IC<8>{}); kstep(IC<9>{}); kstep(IC<6>{}); kstep(IC<7>{}); }
        else { kstep(IC<5>{}); ldo(IC<3>{}); kstep(IC<11>{}); kstep(IC<10>{}); ldo(IC<4>{}); kstep(IC<6>{}); kstep(IC<7>{}); if constexpr (NPM == 3) { kstep(IC<9>{}); kstep(IC<8>{}); } else { kstep(IC<8>{}); kstep(IC<9>{}); } }
        l16 = fresh(l16);
        const int ln = (l16 >> 4) & 31;
        if constexpr (CEARLY && hf) { SFENCE2(o16, __float_as_uint(e1[0])); bar_arrive(B_G, 256); }
        unsigned char* gr = arena + (AR_ACC + acc_lane(bi, ln) + acc_voff(bv) + acc_step(s));
        const bool cnt = (ln & 1) || !t28;
        wqa = wq_addr(l16);
        SFENCE(o16);
        static_for<0, PQE>([&](auto K) { ldsm_x4_t_i<OFF_WQ + K.value * 2048>(rq[K.value], wqa); });
        const uint32_t y0 = movm_t(pack_f16(c0[0] + c1[0], c0[1] + c1[1])), y1 = movm_t(pack_f16(c0[2] + c1[2], c0[3] + c1[3]));
        const uint32_t y2 = movm_t(pack_f16(e0[0] + e1[0], e0[1] + e1[1])), y3 = movm_t(pack_f16(e0[2] + e1[2], e0[3] + e1[3]));
        asm volatile("red.relaxed.gpu.global.add.noftz.v4.f16x2 [%0], {%1,%2,%3,%4};" :: "l"(gr), "r"(y0), "r"(y1), "r"(y2), "r"(cnt ? 0x3c00u : y3) : "memory");
        bar_arrive(B_RED, 384);
        if constexpr (CEARLY && !hf) { bar_arrive(B_C, 256); bar_sync(B_G, 256); }
        else bar_sync(B_C, 256);
        TS(7);
      }
#if CHAIN_TIMING
      x_gemm((s + 1) & 1, tsb);
#else
      x_gemm((s + 1) & 1, 0);
#endif
      TS(8);
    }
    };
    if (hf == 0) run(IC<0>{}); else run(IC<1>{});
    {
      const uint32_t l16 = sb + (threadIdx.x & 31) * 16, mema = l16 ^ ((l16 >> 2) & 96);
      float c0[4] = {0, 0, 0, 0}, c1[4] = {0, 0, 0, 0}, c2[4] = {0, 0, 0, 0}, c3[4] = {0, 0, 0, 0};
      bar_sync(hf ? B_MEM1 : B_MEM0, 256);
      const float sc = __uint_as_float(lds32_i<SC_IN + 16>(sb)) * iw;
      static_for<0, 10>([&](auto T) {
        constexpr int p = 2 * T.value;
        uint32_t b0[4], b1[4];
        ldsm_x4_i<OFF_MEM + p * 512>(b0, mema); ldsm_x4_i<OFF_MEM + p * 512 + 512>(b1, mema);
        mma16816h(c0, w[2 * p], b0[0], b0[1]); mma16816h(c1, w[2 * p + 1], b0[2], b0[3]);
        mma16816h(c2, w[2 * p + 2], b1[0], b1[1]); mma16816h(c3, w[2 * p + 3], b1[2], b1[3]);
      });
      stsm_x2_t_i<OFF_KV + 2 * KVB + 512>(l16 + (l16 & 128) * 4 + wi * 1280 + hf * KVB, pack_bf16(((c0[0] + c1[0]) + (c2[0] + c3[0])) * sc, ((c0[1] + c1[1]) + (c2[1] + c3[1])) * sc),
                                          pack_bf16(((c0[2] + c1[2]) + (c2[2] + c3[2])) * sc, ((c0[3] + c1[3]) + (c2[3] + c3[3])) * sc));
      fence_proxy_async();
    }
    bar_arrive(B_RED, 384);
#if CHAIN_TIMING
    for (int i = tid; i < 288; i += 256) a.dbg[cta * 288 + i] = lds32_i<OFF_BAR + 128>(sb + i * 4);
#endif
    asm volatile("barrier.cluster.arrive.relaxed.aligned; barrier.cluster.wait.aligned;" ::: "memory");
  }
}
struct PrepArgs { const bf16 *wqkv, *wphi, *wo; unsigned char *wb, *wot; };
__device__ __forceinline__ void prep_body(const int cta, const PrepArgs& pa) {
  const int tid = threadIdx.x, lane = tid & 31, warp = tid >> 5, g = lane >> 2, q = lane & 3;
  const int pair = cta >> 1, which = cta & 1;
  uint32_t af[5][2][6];
#pragma unroll
  for (int i = 0; i < 5; i++)
#pragma unroll
    for (int hh = 0; hh < 2; hh++) {
      const uint32_t* r0 = (const uint32_t*)(pa.wqkv + (size_t)((warp * 5 + i) * 16 + g) * 1920 + which * 640 + (2 * pair + hh) * 20) + q;
      const uint32_t* r1 = r0 + 8 * 960;
      af[i][hh][0] = __ldg(r0); af[i][hh][1] = __ldg(r1); af[i][hh][2] = __ldg(r0 + 4); af[i][hh][3] = __ldg(r1 + 4);
      af[i][hh][4] = q < 2 ? __ldg(r0 + 8) : 0u; af[i][hh][5] = q < 2 ? __ldg(r1 + 8) : 0u;
    }
  uint32_t bfr[2][3][3];
#pragma unroll
  for (int hh = 0; hh < 2; hh++)
#pragma unroll
    for (int t = 0; t < 3; t++) {
      const bool on = t < 2 || (g & 1) == hh;
      const unsigned short* ph = (const unsigned short*)pa.wphi + (2 * pair + hh) * 400 + (t < 2 ? 8 * t + g : 16 + (g >> 1)) + 2 * q * 20;
#pragma unroll
      for (int r = 0; r < 3; r++) bfr[hh][t][r] = (on && (r < 2 || q < 2)) ? (uint32_t)__ldg(ph + r * 160) | ((uint32_t)__ldg(ph + r * 160 + 20) << 16) : 0u;
    }
  const int gt = cta * 256 + tid;
#pragma unroll 3
  for (int i = gt; i < 640 * 32; i += 8192) {
    const int k = (i & 7) + (i >> 8) * 8, h = (i >> 3) & 31;
    const uint2* src = (const uint2*)(pa.wqkv + (size_t)k * 1920 + 1280 + h * 20);
    const uint2 a = __ldg(src), b = __ldg(src + 1), c = __ldg(src + 2), d = __ldg(src + 3), e = __ldg(src + 4);
    uint4* dst = (uint4*)(pa.wb + ((size_t)((h >> 2) * 80 + (k >> 3)) * 32 + 20 + 3 * (h & 3)) * 128 + (k & 7) * 16);
    dst[0] = make_uint4(a.x, a.y, b.x, b.y); dst[8] = make_uint4(c.x, c.y, d.x, d.y);
    dst[16] = (h & 1) ? make_uint4(0, 0, e.x, e.y) : make_uint4(e.x, e.y, 0, 0);
  }
#pragma unroll 7
  for (int i = gt; i < 640 * 80; i += 8192) {
    const int r = i & 7, c = (i >> 3) % 80, kg = i / 640, c5 = kg % 5;
    const int row = (kg / 5) * 40 + (c5 < 2 ? 8 * c5 + r : (c5 == 2 ? 16 + (r & 3) + (r >> 2) * 20 : 20 + 8 * (c5 - 3) + r));
    *(uint4*)(pa.wot + ((size_t)((c / 10) * 80 + kg) * 10 + c % 10) * 128 + r * 16) = __ldg((const uint4*)(pa.wo + (size_t)row * cfg::DM + c * 8));
  }
#pragma unroll
  for (int i = 0; i < 5; i++) {
    uint32_t* dst = (uint32_t*)(pa.wb + ((size_t)((pair >> 1) * 80 + (warp * 5 + i) * 2) * 32 + which * 10 + (pair & 1) * 5) * 128) + lane;
#pragma unroll
    for (int t = 0; t < 5; t++) {
      float d[4] = {0, 0, 0, 0};
#pragma unroll
      for (int hh = 0; hh < 2; hh++)
        if (t == 2 || (t > 2) == (hh == 1)) {
          const int tt = t < 3 ? t : t - 3;
          mma16816(d, af[i][hh][0], af[i][hh][1], af[i][hh][2], af[i][hh][3], bfr[hh][tt][0], bfr[hh][tt][1]);
          mma1688(d, af[i][hh][4], af[i][hh][5], bfr[hh][tt][2]);
        }
      dst[t * 32] = pack_bf16(d[0], d[1]); dst[1024 + t * 32] = pack_bf16(d[2], d[3]);
    }
  }
}

__global__ void __launch_bounds__(256, 4) ln_kernel(const bf16* __restrict__ xin, bf16* __restrict__ xn, uint2* __restrict__ xh, uint4* __restrict__ z0, int n0,
                                                    uint4* __restrict__ z1, int n1, const bf16* pfa, const bf16* pfb, int npf, int tl) {
  asm volatile("griddepcontrol.wait;" ::: "memory");
  asm volatile("griddepcontrol.launch_dependents;" ::: "memory");
  TL_BEGIN(tl);
  const int warp = threadIdx.x >> 5, lane = threadIdx.x & 31;
  const int row = blockIdx.x * 8 + warp;
  uint2 xw[1][5];
#pragma unroll
  for (int i = 0; i < 5; i++) xw[0][i] = *(const uint2*)(xin + (size_t)row * cfg::DM + i * 128 + lane * 4);
  for (int i = blockIdx.x * 256 + threadIdx.x; i < n0; i += 256 * 256) z0[i] = make_uint4(0, 0, 0, 0);
  for (int i = blockIdx.x * 256 + threadIdx.x; i < n1; i += 256 * 256) z1[i] = make_uint4(0, 0, 0, 0);
  if (npf && xw[0][4].y != 0x7fc17fc1u) {
    for (int i = 0; i < npf; i++) {
      const uint32_t l = (uint32_t)i * 32768u + (blockIdx.x * 256 + threadIdx.x) / 2;
      if (l < cfg::DM * cfg::HD / 64) asm volatile("prefetch.global.L2 [%0];" :: "l"(((threadIdx.x & 1) ? pfa : pfb) + (size_t)l * 64) : "memory");
    }
  }
  ln_rows<1>(xw, row, lane, xn, xh);
  TL_END(tl);
}
struct Pipe { uint32_t stage, phase; };
template <int NS> __device__ __forceinline__ void pipe_adv(Pipe& p) { if (++p.stage == NS) { p.stage = 0; p.phase ^= 1; } }
constexpr uint32_t SWZ128 = 1;
__device__ __forceinline__ uint64_t desc_kmajor(uint32_t a) { return make_desc(a, 16, 1024, SWZ128); }
__device__ __forceinline__ uint64_t desc_mnmajor(uint32_t a) { return make_desc(a, 8192, 1024, SWZ128); }
__device__ __forceinline__ void wait_ge(const void* p, uint32_t target, uint32_t ns = 32) {
  int spin = 0;
  while (ld_acquire_u32(p) < target) { __nanosleep(ns); if (++spin > (1 << 21)) break; }
}
__device__ __forceinline__ void bulk_g2s_hint(uint32_t dst, const void* src, uint32_t bytes, uint32_t mb, uint64_t pol) {
  asm volatile("cp.async.bulk.shared::cluster.global.mbarrier::complete_tx::bytes.L2::cache_hint [%0], [%1], %2, [%3], %4;"
               :: "r"(dst), "l"(src), "r"(bytes), "r"(mb), "l"(pol) : "memory");
}
#ifndef PF_WB
#define PF_WB 2
#endif
#ifndef PF_XN
#define PF_XN 1
#endif
#ifndef STAG
#define STAG 1
#endif
#ifndef EF_KV
#define EF_KV 1
#endif
#ifndef EF_O
#define EF_O 1
#endif
__device__ __forceinline__ void fence_proxy_async_global() { asm volatile("fence.proxy.async.global;" ::: "memory"); }

namespace tr {
constexpr int NS = 4, STQ = 16384 + 24576, STO = 16384 + 40960;
constexpr int SEGB = 15360;
constexpr int OFF_K = NS * STQ;
constexpr int OFF_BAR = NS * STO;
constexpr int SMEM = OFF_BAR + 256;
static_assert(OFF_K + 4 * SEGB <= OFF_BAR && SMEM <= 232448, "smem");
enum { T_QA = 0, T_Q, T_A, T_OB, T_OS, T_L, T_END, T_P };
constexpr uint32_t C_QA = AR_CNT, C_O = AR_CNT + 64, C_Q = AR_CNT + 128, C_P = AR_CNT + 192;
constexpr int MAXITEMS = 1200;
struct Sched {
  uint8_t ks[16];
  uint8_t wide[16];
  uint8_t lrows[16];
  uint32_t n;
  uint16_t item[MAXITEMS];
};
struct Args {
  const unsigned char *kg, *vg;
  unsigned char* o;
  uint4* qs;
  unsigned char* part;
  const bf16 *xin, *xq;
  bf16 *xout, *xn;
  unsigned char* arena;
  const unsigned* go;
  int tl;
  uint32_t nap, nap2;
};
}

template <int N0, int N1>
__device__ __forceinline__ void tr_mainloop(float (&a0)[N0 / 2], float (&a1)[N1 ? N1 / 2 : 1], Pipe& p, uint32_t sb, uint32_t full, uint32_t empty, int nkb, int wg) {
  using namespace tr;
  constexpr uint32_t ST = N1 ? STO : STQ;
  uint32_t prev = 0;
#pragma unroll
  for (int i = 0; i < N0 / 2; i++) a0[i] = 0.f;
  if constexpr (N1 > 0) {
#pragma unroll
    for (int i = 0; i < N1 / 2; i++) a1[i] = 0.f;
  }
#pragma unroll 1
  for (int kb = 0; kb < nkb; kb++) {
    mbar_wait(full + 8 * p.stage, p.phase);
    const uint32_t st = sb + p.stage * ST;
    wgmma_fence();
#pragma unroll
    for (int kk = 0; kk < 4; kk++) {
      const uint64_t da = desc_kmajor(st + wg * 8192 + kk * 32);
      if constexpr (N0 == 192) wgmma_n192<0, 1>(a0, da, desc_mnmajor(st + 16384 + kk * 2048), (kb | kk) != 0);
      else wgmma_n128<0, 1>(a0, da, desc_mnmajor(st + 16384 + kk * 2048), (kb | kk) != 0);
      if constexpr (N1 > 0) wgmma_n128<0, 1>(a1, da, desc_mnmajor(st + 16384 + 24576 + kk * 2048), (kb | kk) != 0);
    }
    wgmma_commit();
    if (kb > 0) { wgmma_wait<1>(); mbar_arrive_if((threadIdx.x & 127) == 0, empty + 8 * prev); }
    prev = p.stage;
    pipe_adv<NS>(p);
  }
  wgmma_wait<0>();
  mbar_arrive_if((threadIdx.x & 127) == 0, empty + 8 * prev);
}
template <int N> __device__ __forceinline__ void stage_tiles(const float (&o)[N / 2], uint32_t base, int wi, int lane) {
  const uint32_t ra = base + (wi * 16 + (lane & 7) + 8 * ((lane >> 3) & 1)) * 128;
#pragma unroll
  for (int v = 0; v < N / 8; v += 2)
    stsm_x4(ra + (v >> 3) * 8192 + ((((v & 7) + (lane >> 4)) ^ (lane & 7)) << 4), pack_bf16(o[4 * v], o[4 * v + 1]), pack_bf16(o[4 * v + 2], o[4 * v + 3]),
            pack_bf16(o[4 * v + 4], o[4 * v + 5]), pack_bf16(o[4 * v + 6], o[4 * v + 7]));
}
__global__ void __launch_bounds__(384, 1) trail_kernel(const __grid_constant__ CUtensorMap tmX, const __grid_constant__ CUtensorMap tmQ,
                                                       const __grid_constant__ CUtensorMap tmWo5, const __grid_constant__ CUtensorMap tmWo2,
                                                       const __grid_constant__ CUtensorMap tmP, const __grid_constant__ tr::Sched sc,
                                                       const __grid_constant__ tr::Args a, const __grid_constant__ PrepArgs pa) {
  using namespace tr;
  [[maybe_unused]] const int tl = a.tl;
  TL_BEGIN(tl);
  extern __shared__ __align__(1024) unsigned char smem_raw[];
  const uint32_t sb = smem_u32(smem_raw);
  const int warp = __shfl_sync(0xffffffffu, (int)threadIdx.x >> 5, 0), lane = threadIdx.x & 31;
  unsigned char* const arena = a.arena;
  const uint32_t full = sb + OFF_BAR, empty = full + 8 * NS, barK = empty + 8 * NS, barKfree = barK + 16, staged = barKfree + 16;
  const uint32_t kvrdy = staged + 32, mfull = kvrdy + 8, mempty = mfull + 16, mbox = mempty + 16;
  uint32_t go = 0;
  if (threadIdx.x == 256) go = ld_acquire_u32(a.go);
  if (threadIdx.x == 0) {
    for (int i = 0; i < NS; i++) { mbar_init(full + 8 * i, 1); mbar_init(empty + 8 * i, 2); }
    for (int i = 0; i < 2; i++) {
      mbar_init(barK + 8 * i, 1); mbar_init(barKfree + 8 * i, 1); mbar_init(staged + 16 * i, 4); mbar_init(staged + 16 * i + 8, 4);
      mbar_init(mfull + 8 * i, 1); mbar_init(mempty + 8 * i, 11);
    }
    mbar_init(kvrdy, 1);
    asm volatile("fence.mbarrier_init.release.cluster;" ::: "memory");
  }
  __syncthreads();
  Pipe mp{0, 0};
  auto next_item = [&]() -> uint32_t {
    uint32_t it;
    mbar_wait(mfull + 8 * mp.stage, mp.phase);
    asm volatile("ld.shared.u32 %0, [%1];" : "=r"(it) : "r"(mbox + 4 * mp.stage) : "memory");
    return it;
  };
  if (warp >= 8) {
    asm volatile("setmaxnreg.dec.sync.aligned.u32 40;");
    if (warp == 8) { go = __shfl_sync(0xffffffffu, go, 0); if (elect_one()) {
      Pipe p{0, 1};
      mp.phase = 1;
      uint32_t kph = 1, rph = 0, wide = 0, qdone = 0;
      prefetch_tmap(&tmX); prefetch_tmap(&tmQ); prefetch_tmap(&tmWo5); prefetch_tmap(&tmWo2); prefetch_tmap(&tmP);
      const uint64_t ef = policy_evict_first();
      auto ld_kv = [&](uint32_t d, const void* s, uint32_t n, uint32_t mb) { if (EF_KV) bulk_g2s_hint(d, s, n, mb, ef); else bulk_g2s(d, s, n, mb); };
      auto ld_o = [&](uint32_t d, const void* s, uint32_t n, uint32_t mb) { if (EF_O) bulk_g2s_hint(d, s, n, mb, ef); else bulk_g2s(d, s, n, mb); };
      auto stage = [&](uint32_t bytes) -> uint32_t {
        mbar_wait(empty + 8 * p.stage, p.phase);
        mbar_expect_tx(full + 8 * p.stage, bytes);
        return sb + p.stage * (wide ? STO : STQ);
      };
      auto fetch = [&]() -> uint32_t { uint32_t v; asm volatile("atom.relaxed.gpu.global.add.u32 %0, [%1], 1;" : "=r"(v) : "l"(arena + AR_QUEUE) : "memory"); return v; };
      if (!go) wait_ge(a.go, 1, 200);
      fence_proxy_async_global();
      uint32_t next = fetch();
      while (true) {
        const uint32_t item = next;
        const uint32_t code = sc.item[min(item, sc.n)];
        const int type = code >> 11, m = (code >> 7) & 15, k = code & 127;
        if (type == T_A && !((qdone >> m) & 1)) { wait_ge(arena + C_Q + m * 4, 64); qdone |= 1u << m; }
        if (type == T_OB && !wide) for (uint32_t i = 0; i < NS; i++) mbar_wait(empty + 8 * i, i >= p.stage ? p.phase : p.phase ^ 1);
        wide = type == T_OB;
        mbar_wait(mempty + 8 * mp.stage, mp.phase);
        asm volatile("st.shared.u32 [%0], %1;" :: "r"(mbox + 4 * mp.stage), "r"((p.stage << 24) | (type << 16) | (m << 8) | (k & 255)) : "memory");
        mbar_arrive(mfull + 8 * mp.stage);
        pipe_adv<2>(mp);
        if (type == T_END) break;
        if (type == T_P) { next = fetch(); continue; }
        if (type == T_L) {
          const int nr = sc.lrows[m], np = sc.ks[m];
          prefetch_l2(a.xin + (size_t)(m * 128 + k * 8 * nr) * cfg::DM, nr * 10240);
          wait_ge(arena + C_O + m * 4, np * (sc.wide[m] ? 4 : 10), m < 13 ? a.nap : 32);
          fence_proxy_async_global();
#pragma unroll 1
          for (int r = 0; r < nr; r++) {
            const int rg = m * 16 + k * nr + r;
#pragma unroll 1
            for (int q0 = 0; q0 <= np; q0 += 4) {
              const int n = min(4, np + 1 - q0);
              const uint32_t st = stage(n * 10240), fb = full + 8 * p.stage;
#pragma unroll 1
              for (int q = q0; q < q0 + n; q++) {
                if (q == 0) bulk_g2s(st, a.xin + (size_t)rg * 8 * cfg::DM, 10240, fb);
                else tma_load_3d(st + (q - q0) * 10240, &tmP, 0, rg & 7, ((q - 1) * 32 + (rg >> 3)) * 10, fb);
              }
              pipe_adv<NS>(p);
            }
          }
          next = fetch(); continue;
        }
        if (type <= T_A) {
          if (type != T_A)
#pragma unroll 1
            for (int kb = 0; kb < 10; kb++) {
              const uint32_t st = stage(STQ), fb = full + 8 * p.stage;
              tma_load_2d(st, &tmX, kb * 64, m * 128, fb);
              tma_load_3d(st + 16384, &tmQ, 0, kb * 64, k * 3, fb);
              pipe_adv<NS>(p);
              if (type == T_Q && kb == 8) next = fetch();
            }
          if (type != T_Q) {
            const size_t blk = ((size_t)m * 4 * 96 + k * 3) * 5120;
            kph ^= 1;
            mbar_wait(kvrdy, rph); rph ^= 1;
            next = fetch();
            fence_proxy_async_global();
#pragma unroll 1
            for (int w = type == T_A ? 0 : 2; w < 4; w++) {
              const uint32_t st = stage(2 * SEGB), fb = full + 8 * p.stage;
              for (int sg = 0; sg < 2; sg++) ld_kv(st + sg * SEGB, (w < 2 ? a.kg : a.vg) + blk + (size_t)(2 * (w & 1) + sg) * (96 * 5120), SEGB, fb);
              pipe_adv<NS>(p);
            }
          }
        } else {
          const int nn = wide ? 2 : 5, nb = wide ? 5 : 2, nt = k % nn, nkb = 96 / sc.ks[m], k0 = (k / nn) * nkb;
          const Pipe p0 = p;
          for (int kb = 0; kb < nkb; kb++) {
            if (wide && kb < NS && p.stage >= 2) { mbar_wait(barKfree, kph); mbar_wait(barKfree + 8, kph); }
            const uint32_t st = stage(16384 + nb * 8192), fb = full + 8 * p.stage;
            tma_load_3d(st + 16384, wide ? &tmWo5 : &tmWo2, 0, (k0 + kb) * 64, nt * nb, fb);
            if (kb >= NS) ld_o(st, a.o + ((size_t)m * 96 + k0 + kb) * 16384, 16384, fb);
            pipe_adv<NS>(p);
            if (kb == NS - 1 || (kb == nkb - 1 && nkb < NS)) {
              wait_ge(arena + C_QA + m * 4, 64, m < 14 ? a.nap : 32);
              fence_proxy_async_global();
              Pipe q = p0;
#pragma unroll 1
              for (int i = 0; i <= kb; i++) { ld_o(sb + q.stage * (wide ? STO : STQ), a.o + ((size_t)m * 96 + k0 + i) * 16384, 16384, full + 8 * q.stage); pipe_adv<NS>(q); }
            }
          }
          next = fetch();
          for (int w = wide ? -(int)((2 - p.stage) & 3) : 0; w < 2; w++) { mbar_wait(empty + 8 * p.stage, p.phase); mbar_arrive(full + 8 * p.stage); pipe_adv<NS>(p); }
          kph ^= wide;
        }
      }
    } } else if (warp < 11) { if (elect_one()) {
      const int w = warp - 9;
      uint32_t sph = 0;
      [[maybe_unused]] int nlog = 0;
#ifdef TIMELINE
      if (w == 0) { unsigned long long* lg = g_log + (((tl >= 12) * 132 + blockIdx.x) * 64 + nlog++) * 2; lg[0] = T_END << 16; lg[1] = gtime(); lg[2] = ~0ull; }
#endif
      while (true) {
        const uint32_t it = next_item();
        const int type = (it >> 16) & 255, m = (it >> 8) & 255, k = it & 255;
        const uint32_t slot = mp.stage;
        pipe_adv<2>(mp);
        if (type == T_END) break;
        mbar_wait(staged + 16 * w + 8 * slot, (sph >> slot) & 1); sph ^= 1u << slot;
        mbar_arrive(mempty + 8 * slot);
#ifdef TIMELINE
        if (w == 0 && nlog < 63) { unsigned long long* lg = g_log + (((tl >= 12) * 132 + blockIdx.x) * 64 + nlog++) * 2; lg[0] = (type << 16) | (m << 8) | k; lg[1] = gtime(); lg[2] = ~0ull; }
#endif
        if (type == T_L) continue;
        if (type == T_QA || type == T_A) {
          for (int jj = 0; jj < 3; jj++) bulk_s2g(a.o + ((size_t)m * 96 + k * 3 + jj) * 16384 + w * 8192, sb + OFF_K + w * 2 * SEGB + jj * 8192, 8192);
          bulk_commit();
          bulk_wait<0>();
          mbar_arrive(barKfree + 8 * w);
        } else if (type == T_OB || type == T_OS) {
          const bool wide = type == T_OB;
          const int nn = wide ? 2 : 5, nb = wide ? 5 : 2;
          const uint32_t own = wide ? 2 + w : ((it >> 24) + 96 / sc.ks[m] + w) % NS;
          bulk_s2g(a.part + ((size_t)((k / nn) * 32 + m * 2 + w) * 10 + (k % nn) * nb) * 8192, sb + own * (wide ? STO : STQ), nb * 8192);
          bulk_commit();
          bulk_wait<0>();
          mbar_arrive(empty + 8 * own);
          if (wide && w) { mbar_arrive(barKfree); mbar_arrive(barKfree + 8); }
        }
        red_release_inc(arena + (type == T_Q ? C_Q : (type <= T_A ? C_QA : (type == T_P ? C_P : C_O))) + m * 4);
      }
    } } else if (elect_one()) {
      const uint64_t ef = policy_evict_first();
      uint32_t kph = 1;
      if (PF_WB && blockIdx.x >= 52) { prefetch_l2(pa.wb + (blockIdx.x - 52) * 32768, 32768); prefetch_l2(pa.wot + (blockIdx.x - 52) * 10240, 10240); }
      if (PF_WB > 1 && blockIdx.x >= 52) { prefetch_l2(a.xn + (blockIdx.x - 52) * 8192, 16384); prefetch_l2(a.xout + (blockIdx.x - 52) * 8192, 16384); }
      while (true) {
        const uint32_t it = next_item();
        const int type = (it >> 16) & 255, m = (it >> 8) & 255, k = it & 255;
        const uint32_t slot = mp.stage;
        pipe_adv<2>(mp);
        if (type == T_END) break;
        if (PF_XN && type == T_QA && m < 15) prefetch_l2(a.xq + ((m + 1) * 128 + k * 4) * cfg::DM, 5120);
        if (type == T_QA || type == T_A) {
          for (int spin = 0; spin < (1 << 21); spin++) {
            uint4 f;
            asm volatile("ld.acquire.gpu.global.v4.u32 {%0,%1,%2,%3}, [%4];" : "=r"(f.x), "=r"(f.y), "=r"(f.z), "=r"(f.w) : "l"(arena + prog_off(k, 0)) : "memory");
            if (min(min(f.x, f.y), f.z) >= (uint32_t)(4 * m + 4)) break;
            __nanosleep(m < 15 ? a.nap : a.nap2);
          }
          mbar_arrive(kvrdy);
          fence_proxy_async_global();
          const unsigned char* src = a.kg + ((size_t)m * 4 * 96 + k * 3) * 5120;
#pragma unroll 1
          for (int w = 0; w < 2; w++) {
            mbar_wait(barKfree + 8 * w, kph);
            if (type == T_A) { mbar_arrive(barK + 8 * w); continue; }
            mbar_expect_tx(barK + 8 * w, 2 * SEGB);
            for (int sg = 2 * w; sg < 2 * w + 2; sg++) { if (EF_KV) bulk_g2s_hint(sb + OFF_K + sg * SEGB, src + (size_t)sg * (96 * 5120), SEGB, barK + 8 * w, ef); else bulk_g2s(sb + OFF_K + sg * SEGB, src + (size_t)sg * (96 * 5120), SEGB, barK + 8 * w); }
          }
          kph ^= 1;
        } else if (type == T_OB) {
          mbar_wait(barKfree, kph); mbar_wait(barKfree + 8, kph);
          kph ^= 1;
        }
        mbar_arrive(mempty + 8 * slot);
      }
      if (blockIdx.x == gridDim.x - 1) asm volatile("griddepcontrol.wait;" ::: "memory");
    }
    return;
  }
  asm volatile("setmaxnreg.inc.sync.aligned.u32 232;");
  const int wg = warp >> 2, wi = warp & 3;
  const int g = lane >> 2, q4 = lane & 3;
  asm volatile("griddepcontrol.launch_dependents;" ::: "memory");
  Pipe p{0, 0};
  uint32_t kph = 0;
  auto own_slot = [&]() -> uint32_t {
    const uint32_t sA = p.stage, phA = p.phase; pipe_adv<NS>(p);
    const uint32_t sB = p.stage, phB = p.phase; pipe_adv<NS>(p);
    if (wi == 0) mbar_wait(full + 8 * (wg ? sA : sB), wg ? phA : phB);
    mbar_wait(full + 8 * (wg ? sB : sA), wg ? phB : phA);
    mbar_arrive_if((threadIdx.x & 127) == 0, empty + 8 * (wg ? sA : sB));
    return wg ? sB : sA;
  };
  while (true) {
    const uint32_t it = __shfl_sync(0xffffffffu, next_item(), 0);
    const int type = (it >> 16) & 255, m = (it >> 8) & 255, k = it & 255;
    mbar_arrive_if(lane == 0, mempty + 8 * mp.stage);
    const uint32_t done = staged + 16 * wg + 8 * mp.stage;
    pipe_adv<2>(mp);
    if (type == T_END) break;
    if (type == T_P) {
      prep_body(k, pa);
      __syncwarp();
      mbar_arrive_if(lane == 0, done);
      continue;
    }
    if (type == T_L) {
      const int nr = sc.lrows[m], np = sc.ks[m];
      const uint32_t po = (lane >> 4) * 1024 + warp * 128 + ((((lane >> 1) & 7) ^ warp) << 4) + (lane & 1) * 8;
#pragma unroll 1
      for (int r = 0; r < nr; r++) {
        uint2 xw[1][5]; float s[20];
#pragma unroll
        for (int i = 0; i < 20; i++) s[i] = 0.f;
#pragma unroll 1
        for (int q0 = 0; q0 <= np; q0 += 4) {
          const uint32_t st = sb + p.stage * STQ;
          mbar_wait(full + 8 * p.stage, p.phase);
          if (q0 == 0) static_for<0, 5>([&](auto I) { xw[0][I.value] = lds64_i<I.value * 256>(st + warp * 1280 + lane * 8); });
#pragma unroll 1
          for (int q = q0 ? 0 : 1; q < min(4, np + 1 - q0); q++)
            static_for<0, 5>([&](auto I) {
              constexpr int i = I.value;
              const uint2 t = lds64_i<i * 2048>(st + q * 10240 + po);
              s[4 * i] += bf_lo(t.x); s[4 * i + 1] += bf_hi(t.x); s[4 * i + 2] += bf_lo(t.y); s[4 * i + 3] += bf_hi(t.y);
            });
          bar_sync(3 + wg, 128);
          mbar_arrive_if((threadIdx.x & 127) == 0, empty + 8 * p.stage);
          pipe_adv<NS>(p);
        }
        const int row = (m * 16 + k * nr + r) * 8 + warp;
#pragma unroll
        for (int i = 0; i < 5; i++) {
          bf16r2(s[4 * i], s[4 * i + 1]); bf16r2(s[4 * i + 2], s[4 * i + 3]);
          xw[0][i] = make_uint2(pack_bf16(bf_lo(xw[0][i].x) + s[4 * i], bf_hi(xw[0][i].x) + s[4 * i + 1]), pack_bf16(bf_lo(xw[0][i].y) + s[4 * i + 2], bf_hi(xw[0][i].y) + s[4 * i + 3]));
          *(uint2*)(a.xout + (size_t)row * cfg::DM + i * 128 + lane * 4) = xw[0][i];
        }
        ln_rows<1>(xw, row, lane, a.xn, nullptr);
      }
      __syncwarp();
      mbar_arrive_if(lane == 0, done);
      continue;
    }
    if (type >= T_OB) {
      const int nkb = 96 / sc.ks[m];
      if (type == T_OB) {
        float a0[96], a1[64];
        tr_mainloop<192, 128>(a0, a1, p, sb, full, empty, nkb, wg);
        while (p.stage != 2) { if (wi == 0) mbar_wait(full + 8 * p.stage, p.phase); mbar_arrive_if((threadIdx.x & 127) == 0, empty + 8 * p.stage); pipe_adv<NS>(p); }
        const uint32_t st = sb + own_slot() * STO;
        stage_tiles<192>(a0, st, wi, lane); stage_tiles<128>(a1, st + 24576, wi, lane);
      } else {
        float a0[64], a1[1];
        tr_mainloop<128, 0>(a0, a1, p, sb, full, empty, nkb, wg);
        stage_tiles<128>(a0, sb + own_slot() * STQ, wi, lane);
      }
      fence_proxy_async();
      __syncwarp();
      mbar_arrive_if(lane == 0, done);
      continue;
    }
    uint32_t qf[12][4];
    uint4* qp = a.qs + ((size_t)((m & 7) * 32 + k) * 12) * 256 + threadIdx.x;
    if (type != T_A) {
      float acc[96], a1[1];
      tr_mainloop<192, 0>(acc, a1, p, sb, full, empty, 10, wg);
#pragma unroll
      for (int i = 0; i < 12; i++) {
        qf[i][0] = pack_bf16(acc[8 * i], acc[8 * i + 1]); qf[i][1] = pack_bf16(acc[8 * i + 2], acc[8 * i + 3]);
        qf[i][2] = pack_bf16(acc[8 * i + 4], acc[8 * i + 5]); qf[i][3] = pack_bf16(acc[8 * i + 6], acc[8 * i + 7]);
      }
      if (type == T_Q) {
#pragma unroll
        for (int i = 0; i < 12; i++) qp[i * 256] = make_uint4(qf[i][0], qf[i][1], qf[i][2], qf[i][3]);
        __syncwarp();
        mbar_arrive_if(lane == 0, done);
        continue;
      }
    } else {
#pragma unroll
      for (int i = 0; i < 12; i++) { const uint4 v = __ldcg(qp + i * 256); qf[i][0] = v.x; qf[i][1] = v.y; qf[i][2] = v.z; qf[i][3] = v.w; }
    }
    const uint32_t ost = sb + OFF_K + wg * 2 * SEGB;
    const bool second = wi >= 2;
    uint32_t pf[5][4];
    {
      float sa[20], sb2[20];
      uint32_t kbase = ost, kslot = 0;
      if (type == T_A) { kslot = own_slot(); kbase = sb + kslot * STQ; } else mbar_wait(barK + 8 * wg, kph);
      if (STAG && wg) bar_sync(1, 256);
      wgmma_fence();
#pragma unroll
      for (int i = 0; i < 12; i++) {
        wgmma_rs_n40<0>(sa, qf[i][0], qf[i][1], qf[i][2], qf[i][3], make_desc(kbase + i * 1280, 640, 128, 0), i != 0);
        wgmma_rs_n40<0>(sb2, qf[i][0], qf[i][1], qf[i][2], qf[i][3], make_desc(kbase + SEGB + i * 1280, 640, 128, 0), i != 0);
      }
      wgmma_commit();
      wgmma_wait<0>();
      if (STAG && !wg) bar_arrive(1, 256);
      mbar_arrive_if(type == T_A && (threadIdx.x & 127) == 0, empty + 8 * kslot);
      const float cs = 0.07216878364870322f * 1.4426950408889634f;
      const int r0 = 16 * (wi & 1) + g, r1 = r0 + 8;
      float m0 = -INFINITY, m1 = -INFINITY;
#pragma unroll
      for (int n = 0; n < 5; n++) {
#pragma unroll
        for (int e = 0; e < 2; e++) {
          const int key = 8 * n + 2 * q4 + e;
          float x = second ? sb2[4 * n + e] : sa[4 * n + e], y = second ? sb2[4 * n + 2 + e] : sa[4 * n + 2 + e];
          if (n < 4) { if (key > r0) x = -INFINITY; if (key > r1) y = -INFINITY; }
          sa[4 * n + e] = x; sa[4 * n + 2 + e] = y;
          m0 = fmaxf(m0, x); m1 = fmaxf(m1, y);
        }
      }
      m0 = fmaxf(m0, __shfl_xor_sync(0xffffffffu, m0, 1)); m1 = fmaxf(m1, __shfl_xor_sync(0xffffffffu, m1, 1));
      m0 = fmaxf(m0, __shfl_xor_sync(0xffffffffu, m0, 2)); m1 = fmaxf(m1, __shfl_xor_sync(0xffffffffu, m1, 2));
      float s0 = 0.f, s1 = 0.f;
#pragma unroll
      for (int n = 0; n < 5; n++) {
#pragma unroll
        for (int e = 0; e < 2; e++) {
          sa[4 * n + e] = ex2f((sa[4 * n + e] - m0) * cs); sa[4 * n + 2 + e] = ex2f((sa[4 * n + 2 + e] - m1) * cs);
          s0 += sa[4 * n + e]; s1 += sa[4 * n + 2 + e];
        }
      }
      s0 += __shfl_xor_sync(0xffffffffu, s0, 1); s1 += __shfl_xor_sync(0xffffffffu, s1, 1);
      s0 += __shfl_xor_sync(0xffffffffu, s0, 2); s1 += __shfl_xor_sync(0xffffffffu, s1, 2);
      const float i0 = rcpf(s0), i1 = rcpf(s1);
#pragma unroll
      for (int n = 0; n < 5; n++) {
        const uint32_t x = pack_bf16(sa[4 * n] * i0, sa[4 * n + 1] * i0), y = pack_bf16(sa[4 * n + 2] * i1, sa[4 * n + 3] * i1);
        if (n < 4) {
          pf[n >> 1][2 * (n & 1)] = second ? 0u : x; pf[n >> 1][2 * (n & 1) + 1] = second ? 0u : y;
          pf[2 + (n >> 1)][2 * (n & 1)] = second ? x : 0u; pf[2 + (n >> 1)][2 * (n & 1) + 1] = second ? y : 0u;
        } else {
          pf[4][0] = second ? 0u : x; pf[4][1] = second ? 0u : y; pf[4][2] = second ? x : 0u; pf[4][3] = second ? y : 0u;
        }
      }
    }
    {
      float o[96];
#pragma unroll
      for (int i = 0; i < 5; i++) { PIN(pf[i][0]); PIN(pf[i][1]); PIN(pf[i][2]); PIN(pf[i][3]); }
      const uint32_t own = own_slot(), vbase = sb + own * STQ;
      wgmma_fence();
#pragma unroll
      for (int i = 0; i < 5; i++)
        wgmma_rs_n192<1>(o, pf[i][0], pf[i][1], pf[i][2], pf[i][3], i < 4 ? make_desc(vbase + (i >> 1) * SEGB + (i & 1) * 256, 128, 640, 0) : make_desc(vbase + 512, SEGB, 640, 0), i != 0);
      wgmma_commit();
      if (type == T_A) mbar_wait(barK + 8 * wg, kph);
      kph ^= 1;
      wgmma_wait<0>();
      mbar_arrive_if((threadIdx.x & 127) == 0, empty + 8 * own);
      stage_tiles<192>(o, ost, wi, lane);
      fence_proxy_async();
      __syncwarp();
      mbar_arrive_if(lane == 0, done);
    }
  }
}
namespace bf {
constexpr int NS = 4, STAGE = 16384 + 32768;
constexpr int PIECE = 20480;
constexpr int OFF_PHI = 0, OFF_V = 40960, OFF_KV = 65536;
constexpr int OFF_OST = 5 * PIECE;
constexpr int OFF_WOT = 6 * PIECE;
constexpr int OFF_BAR = OFF_WOT + 102400;
constexpr int SMEM = OFF_BAR + 256;
static_assert(NS * STAGE <= OFF_BAR && SMEM <= 232448, "smem");
constexpr int KVACC = 32 * 5 * 1024;
struct Args {
  const unsigned char *wb, *wot;
  unsigned char *kvacc, *o2;
  const bf16* xin;
  bf16* xout;
  unsigned* go;
  const void* prep;
  const bf16 *pf0, *pf1;
  int pfn, pfns, pfwait;
  int tl;
};
}
__device__ __forceinline__ void hedgehog_features(float (&x)[2][5], uint32_t (&w)[2][5]) {
  const float L = 1.4426950408889634f;
  float mx[2], mn[2], sp[2], sn[2], pos[2][5], neg[2][5];
#pragma unroll
  for (int r = 0; r < 2; r++) {
    mx[r] = fmaxf(fmaxf(fmaxf(x[r][0], x[r][1]), fmaxf(x[r][2], x[r][3])), x[r][4]);
    mn[r] = fminf(fminf(fminf(x[r][0], x[r][1]), fminf(x[r][2], x[r][3])), x[r][4]);
  }
#pragma unroll
  for (int o = 1; o < 4; o <<= 1)
#pragma unroll
    for (int r = 0; r < 2; r++) {
      const uint32_t t = __shfl_xor_sync(0xffffffffu, __byte_perm(__float_as_uint(mn[r]), __float_as_uint(mx[r]), 0x7632), o);
      mx[r] = fmaxf(mx[r], bf_hi(t)); mn[r] = fminf(mn[r], bf_lo(t));
    }
#pragma unroll
  for (int r = 0; r < 2; r++) {
#pragma unroll
    for (int i = 0; i < 5; i++) { pos[r][i] = ex2f((x[r][i] - mx[r]) * L); neg[r][i] = ex2f((mn[r] - x[r][i]) * L); }
    sp[r] = ((pos[r][0] + pos[r][1]) + (pos[r][2] + pos[r][3])) + pos[r][4];
    sn[r] = ((neg[r][0] + neg[r][1]) + (neg[r][2] + neg[r][3])) + neg[r][4];
  }
#pragma unroll
  for (int o = 1; o < 4; o <<= 1)
#pragma unroll
    for (int r = 0; r < 2; r++) { sp[r] += __shfl_xor_sync(0xffffffffu, sp[r], o); sn[r] += __shfl_xor_sync(0xffffffffu, sn[r], o); }
#pragma unroll
  for (int r = 0; r < 2; r++) {
    const float ip = rcpf(sp[r]), in_ = rcpf(sn[r]);
    w[r][0] = pack_bf16(pos[r][0] * ip, pos[r][1] * ip); w[r][1] = pack_bf16(pos[r][2] * ip, pos[r][3] * ip);
    w[r][2] = pack_bf16(neg[r][0] * in_, neg[r][1] * in_); w[r][3] = pack_bf16(neg[r][2] * in_, neg[r][3] * in_);
    w[r][4] = pack_bf16(pos[r][4] * ip, neg[r][4] * in_);
  }
}
__device__ __forceinline__ void bulk_g2s_mc(uint32_t dst, const void* src, uint32_t bytes, uint32_t mb) {
  asm volatile("cp.async.bulk.shared::cluster.global.mbarrier::complete_tx::bytes.multicast::cluster [%0], [%1], %2, [%3], %4;"
               :: "r"(dst), "l"(src), "r"(bytes), "r"(mb), "h"((unsigned short)3) : "memory");
}
__device__ __forceinline__ void mbar_arrive_remote_if(bool c, uint32_t b) {
  asm volatile("{\n.reg .pred p;\nsetp.ne.u32 p, %1, 0;\n@p mbarrier.arrive.shared::cluster.b64 _, [%0];\n}" :: "r"(b), "r"((uint32_t)c) : "memory");
}

__global__ void __cluster_dims__(2, 1, 1) __launch_bounds__(384, 1) blayer_kernel(const __grid_constant__ CUtensorMap tmA, const __grid_constant__ bf::Args a) {
  using namespace bf;
  [[maybe_unused]] const int tl = a.tl;
  extern __shared__ __align__(1024) unsigned char smem_raw[];
  const uint32_t sb = smem_u32(smem_raw);
  const int warp = __shfl_sync(0xffffffffu, (int)threadIdx.x >> 5, 0), lane = threadIdx.x & 31;
  const uint32_t full = sb + OFF_BAR, empty = full + 8 * NS, full2 = empty + 8 * NS, empty2 = full2 + 64, barW = empty2 + 16, drained = barW + 8, staged = drained + 8, freeb = staged + 8;
  const int rank = blockIdx.x & 1, u = (blockIdx.x >> 1) & 7, mp = blockIdx.x >> 4;
  const int m = 2 * mp + rank;
  const int m2 = 2 * mp + (u & 1), ns = (u & ~1) + rank;
  const uint32_t dpeer = mapa_u32(sb, rank ^ 1) - sb;
  unsigned* cntO = (unsigned*)(a.kvacc + KVACC);
  if (threadIdx.x == 0) {
    for (int i = 0; i < NS; i++) { mbar_init(full + 8 * i, 1); mbar_init(empty + 8 * i, 4); }
    for (int i = 0; i < 8; i++) mbar_init(full2 + 8 * i, 1);
    mbar_init(empty2, 2); mbar_init(empty2 + 8, 2);
    mbar_init(barW, 1); mbar_init(drained, 1); mbar_init(staged, 8); mbar_init(freeb, 2);
    asm volatile("fence.mbarrier_init.release.cluster;" ::: "memory");
  }
  __syncthreads();
  asm volatile("barrier.cluster.arrive.relaxed.aligned; barrier.cluster.wait.aligned;" ::: "memory");
  if (warp >= 8) {
    asm volatile("setmaxnreg.dec.sync.aligned.u32 40;");
    if (warp == 8) { if (elect_one()) {
      const unsigned char* wsrc = a.wb + (size_t)u * 327680 + rank * 16384;
      if (a.prep) wait_ge(a.prep, 64);
      fence_proxy_async_global();
      for (int kb = 0; kb < NS; kb++) {
        mbar_expect_tx(full + 8 * kb, STAGE);
        bulk_g2s_mc(sb + kb * STAGE + 16384 + rank * 16384, wsrc + kb * 32768, 16384, full + 8 * kb);
      }
      asm volatile("griddepcontrol.wait;" ::: "memory");
      TL_BEGIN0(tl);
      if (blockIdx.x == 0) *a.go = 0;
      for (int kb = 0; kb < NS; kb++) tma_load_2d(sb + kb * STAGE, &tmA, kb * 64, m * 128, full + 8 * kb);
      if (m == 0) prefetch_l2(a.kvacc + u * (KVACC / 8), KVACC / 8);
#pragma unroll 1
      for (int kb = NS; kb < 10; kb++) {
        const uint32_t s = kb & 3, st = sb + s * STAGE, fb = full + 8 * s;
        mbar_wait(empty + 8 * s, ((kb >> 2) - 1) & 1);
        mbar_expect_tx(fb, STAGE);
        tma_load_2d(st, &tmA, kb * 64, m * 128, fb);
        bulk_g2s_mc(st + 16384 + rank * 16384, wsrc + kb * 32768, 16384, fb);
      }
      for (int i = 0; i < 6; i++) mbar_expect_tx(full2 + 8 * i, PIECE);
      mbar_wait(drained, 0);
      mbar_expect_tx(barW, 102400);
      bulk_g2s(sb + OFF_WOT, a.wot + (size_t)ns * 102400, 102400, barW);
      mbar_wait(staged, 0);
      bulk_s2g(a.o2 + (size_t)(m * 8 + u) * PIECE, sb + OFF_OST, PIECE);
      bulk_commit();
      bulk_wait<0>();
      mbar_arrive(freeb); mbar_arrive_remote_if(true, freeb + dpeer);
      red_release_inc(cntO + m);
      wait_ge(cntO + m2, 8, 20);
      mbar_wait(freeb, 0);
      fence_proxy_async_global();
      const unsigned char* osrc = a.o2 + (size_t)m2 * 8 * PIECE;
      for (int i = 0; i < 6; i++) bulk_g2s_mc(sb + i * PIECE + rank * (PIECE / 2), osrc + i * PIECE + rank * (PIECE / 2), PIECE / 2, full2 + 8 * i);
      for (int i = 0; i < 2; i++) {
        mbar_wait(empty2 + 8 * i, 0);
        mbar_expect_tx(full2 + 8 * (6 + i), PIECE);
        bulk_g2s(sb + i * PIECE, osrc + (6 + i) * PIECE, PIECE, full2 + 8 * (6 + i));
      }
    } } else if (warp == 9 && a.pf0) { if (elect_one()) {
      if (a.pfwait) asm volatile("griddepcontrol.wait;" ::: "memory");
      constexpr uint32_t CH = 2048;
      for (int i = 0; i < a.pfn; i++) {
        prefetch_l2((const unsigned char*)a.pf0 + (i * 128 + blockIdx.x) * CH, CH); prefetch_l2((const unsigned char*)a.pf1 + (i * 128 + blockIdx.x) * CH, CH);
        __nanosleep(a.pfns);
      }
    } }
    return;
  }
  asm volatile("setmaxnreg.inc.sync.aligned.u32 232;");
  const int wg = warp >> 2, wi = warp & 3;
  const int q4 = lane & 3;
  const bool lead = (threadIdx.x & 127) == 0;
  float acc[128];
  {
#pragma unroll 1
    for (int kb = 0; kb < 10; kb++) {
      const uint32_t s = kb & 3, st = sb + s * STAGE;
      mbar_wait(full + 8 * s, (kb >> 2) & 1);
      wgmma_fence();
#pragma unroll
      for (int kk = 0; kk < 4; kk++) wgmma_n256<0, 1>(acc, desc_kmajor(st + wg * 8192 + kk * 32), make_desc(st + 16384 + kk * 8192, 4096, 128, 0), (kb | kk) != 0);
      wgmma_commit();
      if (kb > 0 && kb < 7) { wgmma_wait<1>(); const uint32_t e = empty + 8 * ((kb - 1) & 3); mbar_arrive_if(lead, e); mbar_arrive_remote_if(lead, e + dpeer); }
    }
    wgmma_wait<0>();
    bar_sync(1, 256);
    mbar_arrive_if(threadIdx.x == 0, drained);
  }
  TL2((tl >= 12 ? 128 : 0) + 32 + 0);
  const uint32_t srow = (wg * 64 + wi * 16 + (lane & 15)) * 16 + (lane >> 4) * 2048;
  auto features = [&](auto T0, auto HH, uint32_t (&w)[2][5]) {
    constexpr int t = T0.value + 5 * (HH.value >> 1), o = (HH.value & 1) ? 3 : 0, e = HH.value & 1;
    float x[2][5];
#pragma unroll
    for (int r = 0; r < 2; r++) {
      x[r][0] = acc[4 * (t + o) + 2 * r]; x[r][1] = acc[4 * (t + o) + 2 * r + 1]; x[r][2] = acc[4 * (t + o + 1) + 2 * r]; x[r][3] = acc[4 * (t + o + 1) + 2 * r + 1];
      bf16r2(x[r][0], x[r][1]); bf16r2(x[r][2], x[r][3]);
    }
    x[0][4] = acc[4 * (t + 2) + e]; x[1][4] = acc[4 * (t + 2) + 2 + e];
    bf16r2(x[0][4], x[1][4]);
    hedgehog_features(x, w);
  };
  static_for<0, 4>([&](auto HH) {
    constexpr int hh = HH.value, t = 20 + 3 * hh;
    const uint32_t one = q4 == ((hh & 1) ? 0 : 2) ? 0x3f80u : 0u;
    const uint32_t va = sb + OFF_V + hh * 6144 + srow;
    stsm_x4(va, pack_bf16(acc[4 * t], acc[4 * t + 1]), pack_bf16(acc[4 * t + 2], acc[4 * t + 3]), pack_bf16(acc[4 * t + 4], acc[4 * t + 5]), pack_bf16(acc[4 * t + 6], acc[4 * t + 7]));
    const bool pad = (q4 >= 2) != (hh & 1);
    stsm_x2(va + 4096, pad ? one : pack_bf16(acc[4 * t + 8], acc[4 * t + 9]), pad ? one : pack_bf16(acc[4 * t + 10], acc[4 * t + 11]));
    uint32_t w[2][5];
    features(IC<10>{}, HH, w);
    const uint32_t pa = sb + OFF_PHI + hh * 10240 + srow;
    stsm_x4(pa, w[0][0], w[1][0], w[0][1], w[1][1]);
    stsm_x4(pa + 4096, w[0][2], w[1][2], w[0][3], w[1][3]);
    stsm_x2(pa + 8192, w[0][4], w[1][4]);
  });
  fence_proxy_async();
  bar_sync(1, 256);
  TL2((tl >= 12 ? 128 : 0) + 32 + 1);
  {
    float d0[12], d1[12];
    const uint32_t pa = sb + OFF_PHI + wg * 20480, pv = sb + OFF_V + wg * 12288;
    wgmma_fence();
#pragma unroll
    for (int k = 0; k < 8; k++) {
      wgmma_n24<1, 1>(d0, make_desc(pa + k * 256, 128, 2048, 0), make_desc(pv + k * 256, 128, 2048, 0), k != 0);
      wgmma_n24<1, 1>(d1, make_desc(pa + 10240 + k * 256, 128, 2048, 0), make_desc(pv + 6144 + k * 256, 128, 2048, 0), k != 0);
    }
    wgmma_commit();
    wgmma_wait<0>();
    unsigned char* dst = a.kvacc + ((u * 4 + wg * 2) * 5 + 2 * wi) * 1024 + lane * 16;
    auto red4 = [&](bool on, unsigned char* p, float x, float y, float z) {
      asm volatile("{\n.reg .pred p;\nsetp.ne.u32 p, %4, 0;\n@p red.relaxed.gpu.global.add.v4.f32 [%0], {%1,%2,%3,%5};\n}" :: "l"(p), "f"(x), "f"(y), "f"(z), "r"((uint32_t)on), "f"(1.f) : "memory");
    };
    red4(wi < 3, dst, d0[0], d0[1], d0[4]); red4(wi < 3, dst + 512, d0[5], d0[8], d0[9]);
    red4(wi < 3, dst + 5120, d1[0], d1[1], d1[4]); red4(wi < 3, dst + 5632, d1[5], d1[8], d1[9]);
    red4(wi < 2, dst + 1024, d0[2], d0[3], d0[6]); red4(wi < 2, dst + 1536, d0[7], d0[10], d0[11]);
    red4(wi < 2, dst + 6144, d1[2], d1[3], d1[6]); red4(wi < 2, dst + 6656, d1[7], d1[10], d1[11]);
  }
  TL2((tl >= 12 ? 128 : 0) + 32 + 2);
  uint32_t qf[4][2][5];
  static_for<0, 4>([&](auto HH) { features(IC<0>{}, HH, qf[HH.value]); });
  uint4 xr[5];
#pragma unroll
  for (int i = 0; i < 5; i++) {
    const int c = lane + 32 * i;
    xr[i] = __ldcg((const uint4*)(a.xin + (size_t)(m2 * 128 + wg * 64 + wi * 16 + c / 10) * cfg::DM + ns * 80 + (c % 10) * 8));
  }
  {
    const unsigned char* src = a.kvacc + (u * 20 + warp) * 1024 + lane * 16;
    uint4 v[6];
    int spin = 0;
    while (true) {
      v[0] = ld_relaxed_v4_i<0>(src); v[1] = ld_relaxed_v4_i<512>(src); v[2] = ld_relaxed_v4_i<8192>(src); v[3] = ld_relaxed_v4_i<8704>(src);
      v[4] = ld_relaxed_v4_i<0>(src + (wg ? 0 : 16384)); v[5] = ld_relaxed_v4_i<512>(src + (wg ? 0 : 16384));
      const uint32_t c = (v[0].w & v[1].w & v[2].w) & (v[3].w & v[4].w & v[5].w);
      if (!__any_sync(0xffffffffu, (c & 0x41800000u) != 0x41800000u) || ++spin >= SPIN_LIMIT) break;
      __nanosleep(100);
    }
    const uint32_t kd = sb + OFF_KV + warp * 384 + lane * 4;
#pragma unroll
    for (int i = 0; i < 3; i++)
      if (i < 2 || wg == 0) {
        sts32(kd + i * 3072, pack_bf16(__uint_as_float(v[2 * i].x), __uint_as_float(v[2 * i].y)));
        sts32(kd + i * 3072 + 128, pack_bf16(__uint_as_float(v[2 * i].z), __uint_as_float(v[2 * i + 1].x)));
        sts32(kd + i * 3072 + 256, pack_bf16(__uint_as_float(v[2 * i + 1].y), __uint_as_float(v[2 * i + 1].z)));
      }
  }
  fence_proxy_async();
  bar_sync(1, 256);
  TL2((tl >= 12 ? 128 : 0) + 32 + 3);
  {
    float d[4][12];
    uint32_t zero = 0; PIN(zero);
#pragma unroll
    for (int hh = 0; hh < 4; hh++)
#pragma unroll
      for (int i = 0; i < 5; i++) { PIN(qf[hh][0][i]); PIN(qf[hh][1][i]); }
    wgmma_fence();
#pragma unroll
    for (int hh = 0; hh < 4; hh++) {
      const uint32_t kb = sb + OFF_KV + hh * 1920;
      wgmma_rs_n24<1>(d[hh], qf[hh][0][0], qf[hh][1][0], qf[hh][0][1], qf[hh][1][1], make_desc(kb, 384, 128, 0), 0);
      wgmma_rs_n24<1>(d[hh], qf[hh][0][2], qf[hh][1][2], qf[hh][0][3], qf[hh][1][3], make_desc(kb + 768, 384, 128, 0), 1);
      wgmma_rs_n24<1>(d[hh], qf[hh][0][4], qf[hh][1][4], zero, zero, make_desc(kb + 1536, 0, 128, 0), 1);
    }
    wgmma_commit();
    wgmma_wait<0>();
    uint32_t ow[4][6];
#pragma unroll
    for (int hh = 0; hh < 4; hh++) {
      const int zl = (lane & ~3) | ((hh & 1) ? 0 : 2);
      const float da = bf16r(bf16r(__shfl_sync(0xffffffffu, d[hh][8], zl)) + 1e-6f), db = bf16r(bf16r(__shfl_sync(0xffffffffu, d[hh][10], zl)) + 1e-6f);
#pragma unroll
      for (int n = 0; n < 3; n++) {
        bf16r2(d[hh][4 * n], d[hh][4 * n + 1]); bf16r2(d[hh][4 * n + 2], d[hh][4 * n + 3]);
        ow[hh][2 * n] = pack_bf16(__fdividef(d[hh][4 * n], da), __fdividef(d[hh][4 * n + 1], da));
        ow[hh][2 * n + 1] = pack_bf16(__fdividef(d[hh][4 * n + 2], db), __fdividef(d[hh][4 * n + 3], db));
      }
    }
#pragma unroll
    for (int p = 0; p < 2; p++) {
      const uint32_t oa = sb + OFF_OST + p * 10240 + srow;
      stsm_x4(oa, ow[2 * p][0], ow[2 * p][1], ow[2 * p][2], ow[2 * p][3]);
      stsm_x2(oa + 4096, q4 < 2 ? ow[2 * p][4] : ow[2 * p + 1][4], q4 < 2 ? ow[2 * p][5] : ow[2 * p + 1][5]);
      stsm_x4(oa + 6144, ow[2 * p + 1][0], ow[2 * p + 1][1], ow[2 * p + 1][2], ow[2 * p + 1][3]);
    }
    fence_proxy_async();
    __syncwarp();
    mbar_arrive_if(lane == 0, staged);
  }
  TL2((tl >= 12 ? 128 : 0) + 32 + 4);
  float c2[40];
  mbar_wait(barW, 0);
#pragma unroll 1
  for (int i = 0; i < 8; i++) {
    mbar_wait(full2 + 8 * i, 0);
    const uint32_t st = sb + (i < 6 ? i : i - 6) * PIECE + wg * 1024, wo = sb + OFF_WOT + i * 12800;
    wgmma_fence();
#pragma unroll
    for (int kk = 0; kk < 5; kk++) wgmma_n80<0, 1>(c2, make_desc(st + kk * 4096, 2048, 128, 0), make_desc(wo + kk * 2560, 1280, 128, 0), (i | kk) != 0);
    wgmma_commit();
    if (i == 1 || i == 2) { wgmma_wait<1>(); mbar_arrive_if(lead, empty2 + 8 * (i - 1)); }
  }
  wgmma_wait<0>();
  TL2((tl >= 12 ? 128 : 0) + 32 + 5);
  {
    bar_sync(1, 256);
    const uint32_t ost = sb + 2 * PIECE + warp * 3072;
#pragma unroll
    for (int v = 0; v < 10; v += 2)
      stsm_x4(ost + (lane & 15) * 176 + (v + (lane >> 4)) * 16, pack_bf16(c2[4 * v], c2[4 * v + 1]), pack_bf16(c2[4 * v + 2], c2[4 * v + 3]),
              pack_bf16(c2[4 * v + 4], c2[4 * v + 5]), pack_bf16(c2[4 * v + 6], c2[4 * v + 7]));
    __syncwarp();
#pragma unroll
    for (int i = 0; i < 5; i++) {
      const int c = lane + 32 * i, row = c / 10, chunk = c % 10;
      const uint4 y = lds128(ost + row * 176 + chunk * 16);
      const size_t off = (size_t)(m2 * 128 + wg * 64 + wi * 16 + row) * cfg::DM + ns * 80 + chunk * 8;
      const uint4 x = xr[i];
      *(uint4*)(a.xout + off) = make_uint4(pack_bf16(bf_lo(x.x) + bf_lo(y.x), bf_hi(x.x) + bf_hi(y.x)), pack_bf16(bf_lo(x.y) + bf_lo(y.y), bf_hi(x.y) + bf_hi(y.y)),
                                           pack_bf16(bf_lo(x.z) + bf_lo(y.z), bf_hi(x.z) + bf_hi(y.z)), pack_bf16(bf_lo(x.w) + bf_lo(y.w), bf_hi(x.w) + bf_hi(y.w)));
    }
  }
  TL_END(tl);
}
__device__ __align__(32768) unsigned char g_arena[AR_SIZE];
__device__ unsigned g_go[32];
__device__ __align__(1024) uint2 g_xh[2048 * 160];
__device__ __align__(1024) unsigned char g_k[64 * 96 * 5120], g_v[64 * 96 * 5120];
__device__ __align__(1024) bf16 g_o[2048 * 6144];
__device__ __align__(1024) uint4 g_qs[8 * 32 * 12 * 256];
__device__ __align__(1024) bf16 g_xn[2048 * 640], g_xn2[2048 * 640], g_xa[2048 * 640], g_xb[2048 * 640];
__device__ __align__(1024) bf16 g_part[24 * 2048 * 640];
__device__ __align__(1024) bf16 g_wb[2048 * 640], g_wot[640 * 640], g_pq[2048 * 640];
__device__ __align__(1024) float g_kvacc[bf::KVACC / 4 + 64];

typedef CUresult (*EncodeFn)(CUtensorMap*, CUtensorMapDataType, cuuint32_t, void*, const cuuint64_t*, const cuuint64_t*, const cuuint32_t*,
                             const cuuint32_t*, CUtensorMapInterleave, CUtensorMapSwizzle, CUtensorMapL2promotion, CUtensorMapFloatOOBfill);
static EncodeFn g_encode = nullptr;
static CUtensorMap make_map(const void* p, uint64_t cols, uint64_t rows, uint32_t bc, uint32_t br, bool swz = true) {
  CUtensorMap m;
  cuuint64_t dims[2] = {cols, rows}, strides[1] = {cols * 2};
  cuuint32_t box[2] = {bc, br}, es[2] = {1, 1};
  g_encode(&m, CU_TENSOR_MAP_DATA_TYPE_BFLOAT16, 2, const_cast<void*>(p), dims, strides, box, es, CU_TENSOR_MAP_INTERLEAVE_NONE,
           swz ? CU_TENSOR_MAP_SWIZZLE_128B : CU_TENSOR_MAP_SWIZZLE_NONE, CU_TENSOR_MAP_L2_PROMOTION_L2_256B, CU_TENSOR_MAP_FLOAT_OOB_FILL_NONE);
  return m;
}
static CUtensorMap make_map3(const void* p, uint64_t cols, uint64_t rows, uint32_t nb) {
  CUtensorMap m;
  cuuint64_t dims[3] = {64, rows, cols / 64}, strides[2] = {cols * 2, 128};
  cuuint32_t box[3] = {64, 64, nb}, es[3] = {1, 1, 1};
  g_encode(&m, CU_TENSOR_MAP_DATA_TYPE_BFLOAT16, 3, const_cast<void*>(p), dims, strides, box, es, CU_TENSOR_MAP_INTERLEAVE_NONE,
           CU_TENSOR_MAP_SWIZZLE_128B, CU_TENSOR_MAP_L2_PROMOTION_L2_256B, CU_TENSOR_MAP_FLOAT_OOB_FILL_NONE);
  return m;
}
template <class T> static T* sym(const T& s) { void* p = nullptr; cudaGetSymbolAddress(&p, s); return (T*)p; }

struct Ptrs {
  unsigned char *arena, *k, *v; bf16 *o, *xn, *xa, *xb, *wb, *wot, *pq; float *part, *kvacc; uint2* xh; uint4* qs; bf16* xn2; unsigned* go;
};

static tr::Sched make_sched(int layer, const char* str, const int* ks, const int* lr) {
  using namespace tr;
  Sched s = {};
  int n = 0;
  for (int b = 0; b < 16; b++) { s.ks[b] = (uint8_t)abs(ks[b]); s.wide[b] = ks[b] > 0; s.lrows[b] = (uint8_t)lr[b]; }
  for (const char* p = str; *p;) {
    if (*p == ' ') { p++; continue; }
    const char c = *p++;
    char* e;
    const int b = (int)strtol(p, &e, 10); p = e;
    int first = 0, cnt = c == 'o' ? s.ks[b] * (s.wide[b] ? 2 : 5) : (c == 'l' ? 16 / lr[b] : 32);
    if (*p == '.') { first = (int)strtol(p + 1, &e, 10); cnt = (int)strtol(e + 1, &e, 10); p = e; }
    const int type = c == 'a' ? T_QA : (c == 'q' ? T_Q : (c == 't' ? T_A : (c == 'l' ? T_L : (c == 'p' ? T_P : (s.wide[b] ? T_OB : T_OS)))));
    if (type == T_P && layer > 0) continue;
    for (int i = 0; i < cnt && n < MAXITEMS - 1; i++) s.item[n++] = (uint16_t)((type << 11) | (b << 7) | (first + i));
  }
  s.n = n; s.item[n] = T_END << 11;
  return s;
}
static tr::Sched sched_of(int layer) {
  const char* str = "q13 q14 a0 q15 a1 o0 p0.0.16 o1 a2 p0.16.16 a3 o2 a4 o3 a5 o4 l0 a6 o5 l1 a7 o6 l2 a8 o7 l3 a9 o8 l4 a10 o9 l5 a11.0.24 o10 a11.24.8 a12 l6 o11 l7 t13 o12 t14 t15 o14 o13 l10 o15 l9 l14 l11 l8 l12 l13 l15";
  int ks[16] = {2, 2, 2, 2, 2, 3, 2, 3, 2, 2, 2, 3, 4, -6, -6, -12}, lr[16] = {4, 4, 4, 4, 4, 4, 4, 4, 4, 1, 4, 1, 1, 1, 1, 1};
#ifdef TUNE
  if (getenv("SCHED")) str = getenv("SCHED");
  if (layer == 0 && getenv("SCHED0")) str = getenv("SCHED0");
  if (const char* p = getenv("KS")) for (int b = 0; b < 16; b++) { char* e; ks[b] = (int)strtol(p, &e, 10); p = e; }
  if (const char* p = getenv("LR")) for (int b = 0; b < 16; b++) { char* e; lr[b] = (int)strtol(p, &e, 10); p = e; }
#endif
  return make_sched(layer, str, ks, lr);
}
#ifndef TRAIL_GRID
#define TRAIL_GRID 132
#endif
#ifndef PDL_LN
#define PDL_LN 0
#endif
#ifndef PDL_CH
#define PDL_CH 1
#endif
#ifndef PDL_B
#define PDL_B 1
#endif
#ifndef PF_A
#define PF_A 1
#endif
#ifndef PF_B
#define PF_B 1
#endif
extern "C" void kernel_launch(void* const* d_in, const int* in_sizes, int n_in, void* d_out, int out_size) {
  const bf16* x = (const bf16*)d_in[0];
  const bf16* mem0 = (const bf16*)d_in[1];
  const bf16 *Wq = (const bf16*)d_in[2], *Wk = (const bf16*)d_in[3], *Wv = (const bf16*)d_in[4], *Wo = (const bf16*)d_in[5];
  const bf16 *wqkv = (const bf16*)d_in[8], *wphi = (const bf16*)d_in[9], *wo = (const bf16*)d_in[10];
  bf16* out = (bf16*)d_out;
  static Ptrs P; static bool init = false;
  if (!init) {
    void* fn = nullptr; cudaDriverEntryPointQueryResult qr;
    cudaGetDriverEntryPoint("cuTensorMapEncodeTiled", &fn, cudaEnableDefault, &qr);
    g_encode = (EncodeFn)fn;
    void* p;
    cudaGetSymbolAddress(&p, g_arena); P.arena = (unsigned char*)p;
    cudaGetSymbolAddress(&p, g_k); P.k = (unsigned char*)p;   cudaGetSymbolAddress(&p, g_v); P.v = (unsigned char*)p;
    cudaGetSymbolAddress(&p, g_o); P.o = (bf16*)p;
    cudaGetSymbolAddress(&p, g_xn); P.xn = (bf16*)p;
    cudaGetSymbolAddress(&p, g_xa); P.xa = (bf16*)p;   cudaGetSymbolAddress(&p, g_xb); P.xb = (bf16*)p;
    cudaGetSymbolAddress(&p, g_wb); P.wb = (bf16*)p;   cudaGetSymbolAddress(&p, g_wot); P.wot = (bf16*)p;
    cudaGetSymbolAddress(&p, g_pq); P.pq = (bf16*)p;   cudaGetSymbolAddress(&p, g_part); P.part = (float*)p;
    cudaGetSymbolAddress(&p, g_kvacc); P.kvacc = (float*)p;
    cudaGetSymbolAddress(&p, g_xh); P.xh = (uint2*)p;
    cudaGetSymbolAddress(&p, g_go); P.go = (unsigned*)p;
    cudaGetSymbolAddress(&p, g_qs); P.qs = (uint4*)p;
    cudaGetSymbolAddress(&p, g_xn2); P.xn2 = (bf16*)p;
    cudaFuncSetAttribute(chain_kernel, cudaFuncAttributeMaxDynamicSharedMemorySize, ch::SMEM);
    cudaFuncSetAttribute(trail_kernel, cudaFuncAttributeMaxDynamicSharedMemorySize, tr::SMEM);
    cudaFuncSetAttribute(blayer_kernel, cudaFuncAttributeMaxDynamicSharedMemorySize, bf::SMEM);
    init = true;
  }
  const CUtensorMap tmXn = make_map(P.xn, 640, 2048, 64, 128), tmXn2 = make_map(P.xn2, 640, 2048, 64, 128);
  const CUtensorMap tmWq = make_map3(Wq, 6144, 640, 3);
  const CUtensorMap tmCq = make_map(Wq, 6144, 640, 64, 160), tmCk = make_map(Wk, 6144, 640, 64, 160), tmCv = make_map(Wv, 6144, 640, 64, 160), tmCo = make_map(Wo, 640, 6144, 224, 64, false);
  const CUtensorMap tmWo5 = make_map3(Wo, 640, 6144, 5), tmWo2 = make_map3(Wo, 640, 6144, 2);

  CUtensorMap tmP;
  {
    cuuint64_t dims[3] = {256, 8, 24 * 320}, strides[2] = {1024, 8192};
    cuuint32_t box[3] = {256, 1, 10}, es[3] = {1, 1, 1};
    g_encode(&tmP, CU_TENSOR_MAP_DATA_TYPE_UINT32, 3, P.part, dims, strides, box, es, CU_TENSOR_MAP_INTERLEAVE_NONE, CU_TENSOR_MAP_SWIZZLE_NONE,
             CU_TENSOR_MAP_L2_PROMOTION_NONE, CU_TENSOR_MAP_FLOAT_OOB_FILL_NONE);
  }
  ChainArgs ca;
  ca.xh = P.xh; ca.mem0 = mem0; ca.kg = P.k; ca.vg = P.v;
  ca.arena = P.arena; ca.dbg = nullptr; ca.go = P.go; ca.delay = POLL_DELAY; ca.margin = 150; ca.pubrel = 1;
#ifdef TUNE
  if (getenv("PR")) ca.pubrel = atoi(getenv("PR"));
  if (getenv("MG")) ca.margin = atoi(getenv("MG"));
  if (getenv("PD")) ca.delay = atoi(getenv("PD"));
#endif
  ca.tl = 0;
  uint4* zar = (uint4*)P.arena; const int nzar = AR_SIZE / 16;
  uint4* zkv = (uint4*)P.kvacc; const int nzkv = (bf::KVACC / 4 + 64) / 4;

  const PrepArgs pa{wqkv, wphi, wo, (unsigned char*)P.wb, (unsigned char*)P.wot};
  const bf16* xcur = x;
  cudaLaunchAttribute at[1];
  at[0].id = cudaLaunchAttributeProgrammaticStreamSerialization; at[0].val.programmaticStreamSerializationAllowed = 1;
  auto cfgof = [&](int grid, int block, int smem, bool pdl) {
    cudaLaunchConfig_t lc = {};
    lc.gridDim = dim3(grid); lc.blockDim = dim3(block); lc.dynamicSmemBytes = smem; lc.stream = cudaStreamPerThread;
    lc.attrs = at; lc.numAttrs = pdl ? 1 : 0;
    return lc;
  };
  int nlayers = 2;
#ifdef TUNE
  if (getenv("LAYERS")) nlayers = atoi(getenv("LAYERS"));
#endif
  for (int layer = 0; layer < nlayers; layer++) {
    const int tl = layer * 12;
    cudaLaunchConfig_t lc = cfgof(256, 256, 0, layer > 0 && PDL_LN);
    cudaLaunchKernelEx(&lc, ln_kernel, xcur, P.xn, P.xh, zar, nzar, zkv, nzkv, Wk, Wv, layer == 0 ? PF_A : 0, tl + 0);
    ca.tl = tl + 2;
    lc = cfgof(96, 384, ch::SMEM, PDL_CH);
    cudaLaunchKernelEx(&lc, chain_kernel, ca, tmCq, tmCk, tmCv, tmCo);
    lc = cfgof(TRAIL_GRID, 384, tr::SMEM, true);
    tr::Args ta{P.k, P.v, (unsigned char*)P.o, P.qs, (unsigned char*)P.part, xcur, P.xn, P.xa, P.xn2, P.arena, P.go, tl + 4, 100, 60};
#ifdef TUNE
    if (getenv("NAP")) ta.nap = atoi(getenv("NAP"));
    if (getenv("NAP2")) ta.nap2 = atoi(getenv("NAP2"));
#endif
    cudaLaunchKernelEx(&lc, trail_kernel, tmXn, tmWq, tmWo5, tmWo2, tmP, sched_of(layer), ta, pa);
    lc = cfgof(128, 384, bf::SMEM, PDL_B);
    bf::Args ba{(const unsigned char*)P.wb, (const unsigned char*)P.wot, (unsigned char*)P.kvacc, (unsigned char*)P.pq, P.xa, layer == 0 ? P.xb : out, P.go, layer == 0 ? P.arena + tr::C_P : nullptr,
                      layer == 0 && PF_B ? Wk : nullptr, Wv, 30, 500, 0, tl + 7};
#ifdef TUNE
    if (getenv("PFN")) ba.pfn = atoi(getenv("PFN"));
    if (getenv("PFNS")) ba.pfns = atoi(getenv("PFNS"));
    if (getenv("PFWT")) ba.pfwait = atoi(getenv("PFWT"));
    if (getenv("PFB")) ba.pf0 = layer == 0 && atoi(getenv("PFB")) ? Wk : nullptr;
#endif
    cudaLaunchKernelEx(&lc, blayer_kernel, tmXn2, ba);
    xcur = P.xb;
  }
}
```

```cpp
#include <cuda_runtime.h>
#include <cuda.h>
#include <cuda_bf16.h>
#include <stdint.h>
#include <stdlib.h>
#include <type_traits>

typedef __nv_bfloat16 bf16;

namespace cfg {
constexpr int S = 2048, DM = 640, H = 32, DH = 192, NSEG = 64, SEG = 32, NM = 8;
constexpr int HD = H * DH;
}

__device__ __forceinline__ uint32_t smem_u32(const void* p) { return (uint32_t)__cvta_generic_to_shared(p); }
__device__ __forceinline__ uint32_t mapa_u32(uint32_t a, uint32_t r) {
  uint32_t o; asm("mapa.shared::cluster.u32 %0, %1, %2;" : "=r"(o) : "r"(a), "r"(r)); return o;
}
__device__ __forceinline__ void mbar_init(uint32_t b, uint32_t c) {
  asm volatile("mbarrier.init.shared::cta.b64 [%0], %1;" :: "r"(b), "r"(c) : "memory");
}
__device__ __forceinline__ void mbar_expect_tx(uint32_t b, uint32_t bytes) {
  asm volatile("mbarrier.arrive.expect_tx.shared::cta.b64 _, [%0], %1;" :: "r"(b), "r"(bytes) : "memory");
}
__device__ __forceinline__ void mbar_arrive(uint32_t b) {
  asm volatile("mbarrier.arrive.shared::cta.b64 _, [%0];" :: "r"(b) : "memory");
}
__device__ __forceinline__ void mbar_expect_tx_if(bool c, uint32_t b, uint32_t bytes) {
  asm volatile("{\n.reg .pred p;\nsetp.ne.u32 p, %2, 0;\n@p mbarrier.arrive.expect_tx.shared::cta.b64 _, [%0], %1;\n}" :: "r"(b), "r"(bytes), "r"((uint32_t)c) : "memory");
}
__device__ __forceinline__ void mbar_arrive_if(bool c, uint32_t b) {
  asm volatile("{\n.reg .pred p;\nsetp.ne.u32 p, %1, 0;\n@p mbarrier.arrive.shared::cta.b64 _, [%0];\n}" :: "r"(b), "r"((uint32_t)c) : "memory");
}
__device__ __forceinline__ bool mbar_try(uint32_t b, uint32_t ph) {
  uint32_t p;
  asm volatile("{.reg .pred p; mbarrier.try_wait.parity.shared::cta.b64 p, [%1], %2; selp.u32 %0, 1, 0, p;}"
               : "=r"(p) : "r"(b), "r"(ph) : "memory");
  return p;
}
__device__ __forceinline__ bool mbar_try_cluster(uint32_t b, uint32_t ph) {
  uint32_t p;
  asm volatile("{.reg .pred p; mbarrier.try_wait.parity.acquire.cluster.shared::cta.b64 p, [%1], %2; selp.u32 %0, 1, 0, p;}"
               : "=r"(p) : "r"(b), "r"(ph) : "memory");
  return p;
}
#ifndef SPIN_LIMIT
#define SPIN_LIMIT (1 << 20)
#endif
__device__ __forceinline__ void mbar_wait(uint32_t b, uint32_t ph) {
  asm volatile("{\n.reg .pred p, q;\n.reg .u32 c;\nmov.u32 c, 0;\n"
               "W_%=:\nmbarrier.try_wait.parity.shared::cta.b64 p, [%0], %1;\n@p bra.uni D_%=;\n"
               "add.u32 c, c, 1;\nsetp.lt.u32 q, c, %2;\n@q bra.uni W_%=;\nD_%=:\n}"
               :: "r"(b), "r"(ph), "n"(SPIN_LIMIT) : "memory");
}
__device__ __forceinline__ void mbar_spin(uint32_t b, uint32_t ph) {
  asm volatile("{\n.reg .pred p, q;\n.reg .u32 c;\nmov.u32 c, 0;\n"
               "W_%=:\nmbarrier.test_wait.parity.shared::cta.b64 p, [%0], %1;\n@p bra D_%=;\n"
               "add.u32 c, c, 1;\nsetp.lt.u32 q, c, %2;\n@q bra W_%=;\nD_%=:\n}"
               :: "r"(b), "r"(ph), "n"(SPIN_LIMIT) : "memory");
}
#define PIN(x) asm volatile("" : "+r"(x))
__device__ __forceinline__ void mbar_wait_cluster(uint32_t b, uint32_t ph) {
  int s = 0;
  while (!mbar_try_cluster(b, ph)) { if (++s > SPIN_LIMIT) break; }
}
__device__ __forceinline__ void st_async_v2(uint32_t a, uint32_t x, uint32_t y, uint32_t mb) {
  asm volatile("st.async.weak.shared::cluster.mbarrier::complete_tx::bytes.v2.b32 [%0], {%1,%2}, [%3];"
               :: "r"(a), "r"(x), "r"(y), "r"(mb) : "memory");
}
__device__ __forceinline__ void st_async_v4(uint32_t a, uint32_t x, uint32_t y, uint32_t z, uint32_t w, uint32_t mb) {
  asm volatile("st.async.weak.shared::cluster.mbarrier::complete_tx::bytes.v4.b32 [%0], {%1,%2,%3,%4}, [%5];"
               :: "r"(a), "r"(x), "r"(y), "r"(z), "r"(w), "r"(mb) : "memory");
}
__device__ __forceinline__ void bulk_g2s(uint32_t dst, const void* src, uint32_t bytes, uint32_t mb) {
  asm volatile("cp.async.bulk.shared::cluster.global.mbarrier::complete_tx::bytes [%0], [%1], %2, [%3];"
               :: "r"(dst), "l"(src), "r"(bytes), "r"(mb) : "memory");
}
__device__ __forceinline__ void cp_async16(uint32_t dst, const void* src) {
  asm volatile("cp.async.cg.shared.global [%0], [%1], 16;" :: "r"(dst), "l"(src) : "memory");
}
__device__ __forceinline__ void cp_async_wait_all() { asm volatile("cp.async.wait_all;" ::: "memory"); }
__device__ __forceinline__ void fence_proxy_async() { asm volatile("fence.proxy.async.shared::cta;" ::: "memory"); }
__device__ __forceinline__ void bar_sync(int id, int n) { asm volatile("bar.sync %0, %1;" :: "r"(id), "r"(n) : "memory"); }
__device__ __forceinline__ void bar_arrive(int id, int n) { asm volatile("bar.arrive %0, %1;" :: "r"(id), "r"(n) : "memory"); }
__device__ __forceinline__ void cluster_sync_all() {
  asm volatile("barrier.cluster.arrive.release.aligned; barrier.cluster.wait.acquire.aligned;" ::: "memory");
}
__device__ __forceinline__ void ldsm_x4(uint32_t (&r)[4], uint32_t a) {
  asm volatile("ldmatrix.sync.aligned.m8n8.x4.shared.b16 {%0,%1,%2,%3}, [%4];"
               : "=r"(r[0]), "=r"(r[1]), "=r"(r[2]), "=r"(r[3]) : "r"(a) : "memory");
}
__device__ __forceinline__ void ldsm_x4_t(uint32_t (&r)[4], uint32_t a) {
  asm volatile("ldmatrix.sync.aligned.m8n8.x4.trans.shared.b16 {%0,%1,%2,%3}, [%4];"
               : "=r"(r[0]), "=r"(r[1]), "=r"(r[2]), "=r"(r[3]) : "r"(a) : "memory");
}
template <int IMM> __device__ __forceinline__ void ldsm_x4_i(uint32_t (&r)[4], uint32_t a) {
  asm volatile("ldmatrix.sync.aligned.m8n8.x4.shared.b16 {%0,%1,%2,%3}, [%4+%5];"
               : "=r"(r[0]), "=r"(r[1]), "=r"(r[2]), "=r"(r[3]) : "r"(a), "n"(IMM) : "memory");
}
template <int IMM> __device__ __forceinline__ void ldsm_x4_t_i(uint32_t (&r)[4], uint32_t a) {
  asm volatile("ldmatrix.sync.aligned.m8n8.x4.trans.shared.b16 {%0,%1,%2,%3}, [%4+%5];"
               : "=r"(r[0]), "=r"(r[1]), "=r"(r[2]), "=r"(r[3]) : "r"(a), "n"(IMM) : "memory");
}
template <int IMM> __device__ __forceinline__ uint4 lds128_i(uint32_t a) {
  uint4 v; asm volatile("ld.shared.v4.u32 {%0,%1,%2,%3}, [%4+%5];" : "=r"(v.x), "=r"(v.y), "=r"(v.z), "=r"(v.w) : "r"(a), "n"(IMM) : "memory"); return v;
}
template <int IMM> __device__ __forceinline__ uint2 lds64_i(uint32_t a) {
  uint2 v; asm volatile("ld.shared.v2.u32 {%0,%1}, [%2+%3];" : "=r"(v.x), "=r"(v.y) : "r"(a), "n"(IMM) : "memory"); return v;
}
template <int IMM> __device__ __forceinline__ void sts128_i(uint32_t a, uint32_t x, uint32_t y, uint32_t z, uint32_t w) {
  asm volatile("st.shared.v4.u32 [%0+%5], {%1,%2,%3,%4};" :: "r"(a), "r"(x), "r"(y), "r"(z), "r"(w), "n"(IMM) : "memory");
}
template <int IMM> __device__ __forceinline__ void sts64_i(uint32_t a, uint32_t x, uint32_t y) {
  asm volatile("st.shared.v2.u32 [%0+%3], {%1,%2};" :: "r"(a), "r"(x), "r"(y), "n"(IMM) : "memory");
}
template <int IMM> __device__ __forceinline__ void st_async_v2_i(uint32_t a, uint32_t x, uint32_t y, uint32_t mb) {
  asm volatile("st.async.weak.shared::cluster.mbarrier::complete_tx::bytes.v2.b32 [%0+%4], {%1,%2}, [%3];"
               :: "r"(a), "r"(x), "r"(y), "r"(mb), "n"(IMM) : "memory");
}
template <int IMM> __device__ __forceinline__ uint4 ld_relaxed_v4_i(const void* p) {
  uint4 v; asm volatile("ld.relaxed.gpu.global.v4.u32 {%0,%1,%2,%3}, [%4+%5];" : "=r"(v.x), "=r"(v.y), "=r"(v.z), "=r"(v.w) : "l"(p), "n"(IMM) : "memory"); return v;
}
template <int I, int N, class F> __device__ __forceinline__ void static_for(F&& f) {
  if constexpr (I < N) { f(std::integral_constant<int, I>{}); static_for<I + 1, N>(f); }
}
__device__ __forceinline__ uint32_t movm_t(uint32_t a) {
  uint32_t d; asm volatile("movmatrix.sync.aligned.m8n8.trans.b16 %0, %1;" : "=r"(d) : "r"(a)); return d;
}
__device__ __forceinline__ void mma16816(float (&d)[4], uint32_t a0, uint32_t a1, uint32_t a2, uint32_t a3, uint32_t b0, uint32_t b1) {
  asm volatile("mma.sync.aligned.m16n8k16.row.col.f32.bf16.bf16.f32 {%0,%1,%2,%3}, {%4,%5,%6,%7}, {%8,%9}, {%0,%1,%2,%3};"
               : "+f"(d[0]), "+f"(d[1]), "+f"(d[2]), "+f"(d[3]) : "r"(a0), "r"(a1), "r"(a2), "r"(a3), "r"(b0), "r"(b1));
}
__device__ __forceinline__ uint32_t pack_bf16(float lo, float hi) {
  uint32_t d; asm("cvt.rn.bf16x2.f32 %0, %1, %2;" : "=r"(d) : "f"(hi), "f"(lo)); return d;
}
__device__ __forceinline__ float bf_lo(uint32_t w) { return __uint_as_float(w << 16); }
__device__ __forceinline__ float bf_hi(uint32_t w) { return __uint_as_float(w & 0xffff0000u); }
__device__ __forceinline__ uint4 lds128(uint32_t a) {
  uint4 v; asm volatile("ld.shared.v4.u32 {%0,%1,%2,%3}, [%4];" : "=r"(v.x), "=r"(v.y), "=r"(v.z), "=r"(v.w) : "r"(a) : "memory"); return v;
}
__device__ __forceinline__ uint2 lds64(uint32_t a) {
  uint2 v; asm volatile("ld.shared.v2.u32 {%0,%1}, [%2];" : "=r"(v.x), "=r"(v.y) : "r"(a) : "memory"); return v;
}
__device__ __forceinline__ void sts128(uint32_t a, uint32_t x, uint32_t y, uint32_t z, uint32_t w) {
  asm volatile("st.shared.v4.u32 [%0], {%1,%2,%3,%4};" :: "r"(a), "r"(x), "r"(y), "r"(z), "r"(w) : "memory");
}
__device__ __forceinline__ void sts64(uint32_t a, uint32_t x, uint32_t y) {
  asm volatile("st.shared.v2.u32 [%0], {%1,%2};" :: "r"(a), "r"(x), "r"(y) : "memory");
}
__device__ __forceinline__ uint4 ld_relaxed_v4(const void* p) {
  uint4 v; asm volatile("ld.relaxed.gpu.global.v4.u32 {%0,%1,%2,%3}, [%4];" : "=r"(v.x), "=r"(v.y), "=r"(v.z), "=r"(v.w) : "l"(p) : "memory"); return v;
}
__device__ __forceinline__ uint32_t ld_relaxed_u32(const void* p) {
  uint32_t v; asm volatile("ld.relaxed.gpu.global.u32 %0, [%1];" : "=r"(v) : "l"(p) : "memory"); return v;
}
__device__ __forceinline__ void st_relaxed_v2(void* p, uint32_t a, uint32_t b) {
  asm volatile("st.relaxed.gpu.global.v2.u32 [%0], {%1,%2};" :: "l"(p), "r"(a), "r"(b) : "memory");
}
__device__ __forceinline__ void st_relaxed_u32(void* p, uint32_t v) {
  asm volatile("st.relaxed.gpu.global.u32 [%0], %1;" :: "l"(p), "r"(v) : "memory");
}
__device__ __forceinline__ void st_release_u32(void* p, uint32_t v) {
  asm volatile("st.release.gpu.global.u32 [%0], %1;" :: "l"(p), "r"(v) : "memory");
}
__device__ __forceinline__ void red_release_inc(void* p) { asm volatile("red.release.gpu.global.add.u32 [%0], 1;" :: "l"(p) : "memory"); }
__device__ __forceinline__ uint32_t clk32() { uint32_t c; asm volatile("mov.u32 %0, %%clock;" : "=r"(c) :: "memory"); return c; }
__device__ __forceinline__ uint32_t clkdep(uint32_t v) {
  uint32_t c; asm volatile("{.reg .pred p; setp.eq.u32 p, %1, 0xdeadbeef; @p trap; mov.u32 %0, %%clock;}" : "=r"(c) : "r"(v) : "memory"); return c;
}
__device__ __forceinline__ void wgmma_fence() { asm volatile("wgmma.fence.sync.aligned;" ::: "memory"); }
__device__ __forceinline__ void wgmma_commit() { asm volatile("wgmma.commit_group.sync.aligned;" ::: "memory"); }
template <int N> __device__ __forceinline__ void wgmma_wait() { asm volatile("wgmma.wait_group.sync.aligned %0;" :: "n"(N) : "memory"); }
__device__ __forceinline__ void wgmma_n8_ss_ta(float (&d)[4], uint64_t da, uint64_t db, int acc) {
  asm volatile("{\n.reg .pred p;\nsetp.ne.b32 p, %6, 0;\n"
               "wgmma.mma_async.sync.aligned.m64n8k16.f32.bf16.bf16 {%0,%1,%2,%3}, %4, %5, p, 1, 1, 1, 0;\n}\n"
               : "+f"(d[0]), "+f"(d[1]), "+f"(d[2]), "+f"(d[3]) : "l"(da), "l"(db), "r"(acc));
}
__device__ __forceinline__ uint64_t make_desc(uint32_t saddr, uint32_t lbo_bytes, uint32_t sbo_bytes, uint32_t swz) {
  return (uint64_t)((saddr & 0x3FFFF) >> 4) | ((uint64_t)(lbo_bytes >> 4) << 16) | ((uint64_t)(sbo_bytes >> 4) << 32) | ((uint64_t)swz << 62);
}


__device__ __forceinline__ bool elect_one() {
  uint32_t p; asm volatile("{\n.reg .pred p;\nelect.sync _|p, 0xffffffff;\nselp.u32 %0, 1, 0, p;\n}" : "=r"(p)); return p;
}
__device__ __forceinline__ void tma_load_3d(uint32_t dst, const CUtensorMap* tm, int c0, int c1, int c2, uint32_t mb) {
  asm volatile("cp.async.bulk.tensor.3d.shared::cluster.global.mbarrier::complete_tx::bytes [%0], [%1, {%3, %4, %5}], [%2];"
               :: "r"(dst), "l"(tm), "r"(mb), "r"(c0), "r"(c1), "r"(c2) : "memory");
}
__device__ __forceinline__ void tma_load_2d(uint32_t dst, const CUtensorMap* tm, int c0, int c1, uint32_t mb) {
  asm volatile("cp.async.bulk.tensor.2d.shared::cluster.global.mbarrier::complete_tx::bytes [%0], [%1, {%3, %4}], [%2];"
               :: "r"(dst), "l"(tm), "r"(mb), "r"(c0), "r"(c1) : "memory");
}
__device__ __forceinline__ void bulk_s2g(void* dst, uint32_t src, uint32_t bytes) {
  asm volatile("cp.async.bulk.global.shared::cta.bulk_group [%0], [%1], %2;" :: "l"(dst), "r"(src), "r"(bytes) : "memory");
}
__device__ __forceinline__ uint64_t policy_evict_first() {
  uint64_t p; asm volatile("createpolicy.fractional.L2::evict_first.b64 %0, 1.0;" : "=l"(p)); return p;
}
__device__ __forceinline__ void bulk_s2g_hint(void* dst, uint32_t src, uint32_t bytes, uint64_t pol) {
  asm volatile("cp.async.bulk.global.shared::cta.bulk_group.L2::cache_hint [%0], [%1], %2, %3;" :: "l"(dst), "r"(src), "r"(bytes), "l"(pol) : "memory");
}
__device__ __forceinline__ void bulk_commit() { asm volatile("cp.async.bulk.commit_group;" ::: "memory"); }
template <int N> __device__ __forceinline__ void bulk_wait_read() { asm volatile("cp.async.bulk.wait_group.read %0;" :: "n"(N) : "memory"); }
template <int N> __device__ __forceinline__ void bulk_wait() { asm volatile("cp.async.bulk.wait_group %0;" :: "n"(N) : "memory"); }
__device__ __forceinline__ void stsm_x4(uint32_t a, uint32_t r0, uint32_t r1, uint32_t r2, uint32_t r3) {
  asm volatile("stmatrix.sync.aligned.m8n8.x4.shared.b16 [%0], {%1,%2,%3,%4};" :: "r"(a), "r"(r0), "r"(r1), "r"(r2), "r"(r3) : "memory");
}
__device__ __forceinline__ void stsm_x2(uint32_t a, uint32_t r0, uint32_t r1) {
  asm volatile("stmatrix.sync.aligned.m8n8.x2.shared.b16 [%0], {%1,%2};" :: "r"(a), "r"(r0), "r"(r1) : "memory");
}
__device__ __forceinline__ void ldsm_x2(uint32_t (&r)[2], uint32_t a) {
  asm volatile("ldmatrix.sync.aligned.m8n8.x2.shared.b16 {%0,%1}, [%2];" : "=r"(r[0]), "=r"(r[1]) : "r"(a) : "memory");
}
__device__ __forceinline__ void ldsm_x2_t(uint32_t (&r)[2], uint32_t a) {
  asm volatile("ldmatrix.sync.aligned.m8n8.x2.trans.shared.b16 {%0,%1}, [%2];" : "=r"(r[0]), "=r"(r[1]) : "r"(a) : "memory");
}
__device__ __forceinline__ float bf16r(float x) { return __uint_as_float(pack_bf16(0.f, x) & 0xffff0000u); }
__device__ __forceinline__ void bf16r2(float& a, float& b) { const uint32_t w = pack_bf16(a, b); a = bf_lo(w); b = bf_hi(w); }
__device__ __forceinline__ float rcpf(float x) { float r; asm("rcp.approx.ftz.f32 %0, %1;" : "=f"(r) : "f"(x)); return r; }
__device__ __forceinline__ float ex2f(float x) { float e; asm("ex2.approx.ftz.f32 %0, %1;" : "=f"(e) : "f"(x)); return e; }
__device__ __forceinline__ void prefetch_tmap(const CUtensorMap* tm) { asm volatile("prefetch.tensormap [%0];" :: "l"(tm) : "memory"); }

#ifdef TIMELINE
__device__ unsigned long long g_tl[2 * 64];
__device__ unsigned g_step[2 * 64 * 96 * 4];
__device__ unsigned long long g_log[2 * 132 * 64 * 2 + 2];
__device__ unsigned long long g_tl2[4 * 64];
__device__ __forceinline__ unsigned long long gtime() { unsigned long long t; asm volatile("mov.u64 %0, %%globaltimer;" : "=l"(t)); return t; }
#define TL_BEGIN(id) do { if (threadIdx.x == 0) atomicMin(&g_tl[2 * (id)], gtime()); } while (0)
#define TL_END(id) do { if ((threadIdx.x & 31) == 0) atomicMax(&g_tl[2 * (id) + 1], gtime()); } while (0)
#define TL_ACC(idx, t0) do { if (threadIdx.x == 0 && m >= 4 && m < 11) { atomicAdd(&g_tl2[idx], gtime() - (t0)); atomicAdd(&g_tl2[(idx) + 1], 1ull); } } while (0)
#define TL_NOW() gtime()
#define TL2(idx) asm volatile("{\n.reg .pred p;\nsetp.eq.u32 p, %2, 0;\n@p red.relaxed.gpu.global.max.u64 [%0], %1;\n}" :: "l"(&g_tl2[idx]), "l"(gtime()), "r"(threadIdx.x) : "memory")
#define TLW(idx) asm volatile("{\n.reg .pred p;\nsetp.eq.u32 p, %2, 0;\n@p red.relaxed.gpu.global.max.u64 [%0], %1;\n@p red.relaxed.gpu.global.add.u64 [%0+128], %1;\n}" :: "l"(&g_tl2[idx]), "l"(gtime() - g_tl0), "r"(threadIdx.x & 31) : "memory")
#define TL_BEGIN0(id) atomicMin(&g_tl[2 * (id)], gtime())
#else
#define TL_ACC(idx, t0)
#define TL_NOW() 0ull
#define TL2(idx)
#define TL_BEGIN0(id)
#define TLW(idx)
#define TL_BEGIN(id)
#define TL_END(id)
#endif
template <int TA, int TB> __device__ __forceinline__ void wgmma_n24(float (&d)[12], uint64_t da, uint64_t db, int acc) {
  asm volatile("{\n.reg .pred p;\nsetp.ne.b32 p, %14, 0;\n"
    "wgmma.mma_async.sync.aligned.m64n24k16.f32.bf16.bf16 {%0, %1, %2, %3, %4, %5, %6, %7, %8, %9, %10, %11}, %12, %13, p, 1, 1, %15, %16;\n}\n"
    : "+f"(d[0]), "+f"(d[1]), "+f"(d[2]), "+f"(d[3]), "+f"(d[4]), "+f"(d[5]), "+f"(d[6]), "+f"(d[7]), "+f"(d[8]), "+f"(d[9]), "+f"(d[10]), "+f"(d[11])
    : "l"(da), "l"(db), "r"(acc), "n"(TA), "n"(TB));
}

template <int TA, int TB> __device__ __forceinline__ void wgmma_n80(float (&d)[40], uint64_t da, uint64_t db, int acc) {
  asm volatile("{\n.reg .pred p;\nsetp.ne.b32 p, %42, 0;\n"
    "wgmma.mma_async.sync.aligned.m64n80k16.f32.bf16.bf16 {%0, %1, %2, %3, %4, %5, %6, %7, %8, %9, %10, %11, %12, %13, %14, %15, %16, %17, %18, %19, %20, %21, %22, %23, %24, %25, %26, %27, %28, %29, %30, %31, %32, %33, %34, %35, %36, %37, %38, %39}, %40, %41, p, 1, 1, %43, %44;\n}\n"
    : "+f"(d[0]), "+f"(d[1]), "+f"(d[2]), "+f"(d[3]), "+f"(d[4]), "+f"(d[5]), "+f"(d[6]), "+f"(d[7]), "+f"(d[8]), "+f"(d[9]), "+f"(d[10]), "+f"(d[11]), "+f"(d[12]), "+f"(d[13]), "+f"(d[14]), "+f"(d[15]), "+f"(d[16]), "+f"(d[17]), "+f"(d[18]), "+f"(d[19]), "+f"(d[20]), "+f"(d[21]), "+f"(d[22]), "+f"(d[23]), "+f"(d[24]), "+f"(d[25]), "+f"(d[26]), "+f"(d[27]), "+f"(d[28]), "+f"(d[29]), "+f"(d[30]), "+f"(d[31]), "+f"(d[32]), "+f"(d[33]), "+f"(d[34]), "+f"(d[35]), "+f"(d[36]), "+f"(d[37]), "+f"(d[38]), "+f"(d[39])
    : "l"(da), "l"(db), "r"(acc), "n"(TA), "n"(TB));
}

template <int TA, int TB> __device__ __forceinline__ void wgmma_n128(float (&d)[64], uint64_t da, uint64_t db, int acc) {
  asm volatile("{\n.reg .pred p;\nsetp.ne.b32 p, %66, 0;\n"
    "wgmma.mma_async.sync.aligned.m64n128k16.f32.bf16.bf16 {%0, %1, %2, %3, %4, %5, %6, %7, %8, %9, %10, %11, %12, %13, %14, %15, %16, %17, %18, %19, %20, %21, %22, %23, %24, %25, %26, %27, %28, %29, %30, %31, %32, %33, %34, %35, %36, %37, %38, %39, %40, %41, %42, %43, %44, %45, %46, %47, %48, %49, %50, %51, %52, %53, %54, %55, %56, %57, %58, %59, %60, %61, %62, %63}, %64, %65, p, 1, 1, %67, %68;\n}\n"
    : "+f"(d[0]), "+f"(d[1]), "+f"(d[2]), "+f"(d[3]), "+f"(d[4]), "+f"(d[5]), "+f"(d[6]), "+f"(d[7]), "+f"(d[8]), "+f"(d[9]), "+f"(d[10]), "+f"(d[11]), "+f"(d[12]), "+f"(d[13]), "+f"(d[14]), "+f"(d[15]), "+f"(d[16]), "+f"(d[17]), "+f"(d[18]), "+f"(d[19]), "+f"(d[20]), "+f"(d[21]), "+f"(d[22]), "+f"(d[23]), "+f"(d[24]), "+f"(d[25]), "+f"(d[26]), "+f"(d[27]), "+f"(d[28]), "+f"(d[29]), "+f"(d[30]), "+f"(d[31]), "+f"(d[32]), "+f"(d[33]), "+f"(d[34]), "+f"(d[35]), "+f"(d[36]), "+f"(d[37]), "+f"(d[38]), "+f"(d[39]), "+f"(d[40]), "+f"(d[41]), "+f"(d[42]), "+f"(d[43]), "+f"(d[44]), "+f"(d[45]), "+f"(d[46]), "+f"(d[47]), "+f"(d[48]), "+f"(d[49]), "+f"(d[50]), "+f"(d[51]), "+f"(d[52]), "+f"(d[53]), "+f"(d[54]), "+f"(d[55]), "+f"(d[56]), "+f"(d[57]), "+f"(d[58]), "+f"(d[59]), "+f"(d[60]), "+f"(d[61]), "+f"(d[62]), "+f"(d[63])
    : "l"(da), "l"(db), "r"(acc), "n"(TA), "n"(TB));
}

template <int TA, int TB> __device__ __forceinline__ void wgmma_n192(float (&d)[96], uint64_t da, uint64_t db, int acc) {
  asm volatile("{\n.reg .pred p;\nsetp.ne.b32 p, %98, 0;\n"
    "wgmma.mma_async.sync.aligned.m64n192k16.f32.bf16.bf16 {%0, %1, %2, %3, %4, %5, %6, %7, %8, %9, %10, %11, %12, %13, %14, %15, %16, %17, %18, %19, %20, %21, %22, %23, %24, %25, %26, %27, %28, %29, %30, %31, %32, %33, %34, %35, %36, %37, %38, %39, %40, %41, %42, %43, %44, %45, %46, %47, %48, %49, %50, %51, %52, %53, %54, %55, %56, %57, %58, %59, %60, %61, %62, %63, %64, %65, %66, %67, %68, %69, %70, %71, %72, %73, %74, %75, %76, %77, %78, %79, %80, %81, %82, %83, %84, %85, %86, %87, %88, %89, %90, %91, %92, %93, %94, %95}, %96, %97, p, 1, 1, %99, %100;\n}\n"
    : "+f"(d[0]), "+f"(d[1]), "+f"(d[2]), "+f"(d[3]), "+f"(d[4]), "+f"(d[5]), "+f"(d[6]), "+f"(d[7]), "+f"(d[8]), "+f"(d[9]), "+f"(d[10]), "+f"(d[11]), "+f"(d[12]), "+f"(d[13]), "+f"(d[14]), "+f"(d[15]), "+f"(d[16]), "+f"(d[17]), "+f"(d[18]), "+f"(d[19]), "+f"(d[20]), "+f"(d[21]), "+f"(d[22]), "+f"(d[23]), "+f"(d[24]), "+f"(d[25]), "+f"(d[26]), "+f"(d[27]), "+f"(d[28]), "+f"(d[29]), "+f"(d[30]), "+f"(d[31]), "+f"(d[32]), "+f"(d[33]), "+f"(d[34]), "+f"(d[35]), "+f"(d[36]), "+f"(d[37]), "+f"(d[38]), "+f"(d[39]), "+f"(d[40]), "+f"(d[41]), "+f"(d[42]), "+f"(d[43]), "+f"(d[44]), "+f"(d[45]), "+f"(d[46]), "+f"(d[47]), "+f"(d[48]), "+f"(d[49]), "+f"(d[50]), "+f"(d[51]), "+f"(d[52]), "+f"(d[53]), "+f"(d[54]), "+f"(d[55]), "+f"(d[56]), "+f"(d[57]), "+f"(d[58]), "+f"(d[59]), "+f"(d[60]), "+f"(d[61]), "+f"(d[62]), "+f"(d[63]), "+f"(d[64]), "+f"(d[65]), "+f"(d[66]), "+f"(d[67]), "+f"(d[68]), "+f"(d[69]), "+f"(d[70]), "+f"(d[71]), "+f"(d[72]), "+f"(d[73]), "+f"(d[74]), "+f"(d[75]), "+f"(d[76]), "+f"(d[77]), "+f"(d[78]), "+f"(d[79]), "+f"(d[80]), "+f"(d[81]), "+f"(d[82]), "+f"(d[83]), "+f"(d[84]), "+f"(d[85]), "+f"(d[86]), "+f"(d[87]), "+f"(d[88]), "+f"(d[89]), "+f"(d[90]), "+f"(d[91]), "+f"(d[92]), "+f"(d[93]), "+f"(d[94]), "+f"(d[95])
    : "l"(da), "l"(db), "r"(acc), "n"(TA), "n"(TB));
}

template <int TA, int TB> __device__ __forceinline__ void wgmma_n256(float (&d)[128], uint64_t da, uint64_t db, int acc) {
  asm volatile("{\n.reg .pred p;\nsetp.ne.b32 p, %130, 0;\n"
    "wgmma.mma_async.sync.aligned.m64n256k16.f32.bf16.bf16 {%0, %1, %2, %3, %4, %5, %6, %7, %8, %9, %10, %11, %12, %13, %14, %15, %16, %17, %18, %19, %20, %21, %22, %23, %24, %25, %26, %27, %28, %29, %30, %31, %32, %33, %34, %35, %36, %37, %38, %39, %40, %41, %42, %43, %44, %45, %46, %47, %48, %49, %50, %51, %52, %53, %54, %55, %56, %57, %58, %59, %60, %61, %62, %63, %64, %65, %66, %67, %68, %69, %70, %71, %72, %73, %74, %75, %76, %77, %78, %79, %80, %81, %82, %83, %84, %85, %86, %87, %88, %89, %90, %91, %92, %93, %94, %95, %96, %97, %98, %99, %100, %101, %102, %103, %104, %105, %106, %107, %108, %109, %110, %111, %112, %113, %114, %115, %116, %117, %118, %119, %120, %121, %122, %123, %124, %125, %126, %127}, %128, %129, p, 1, 1, %131, %132;\n}\n"
    : "+f"(d[0]), "+f"(d[1]), "+f"(d[2]), "+f"(d[3]), "+f"(d[4]), "+f"(d[5]), "+f"(d[6]), "+f"(d[7]), "+f"(d[8]), "+f"(d[9]), "+f"(d[10]), "+f"(d[11]), "+f"(d[12]), "+f"(d[13]), "+f"(d[14]), "+f"(d[15]), "+f"(d[16]), "+f"(d[17]), "+f"(d[18]), "+f"(d[19]), "+f"(d[20]), "+f"(d[21]), "+f"(d[22]), "+f"(d[23]), "+f"(d[24]), "+f"(d[25]), "+f"(d[26]), "+f"(d[27]), "+f"(d[28]), "+f"(d[29]), "+f"(d[30]), "+f"(d[31]), "+f"(d[32]), "+f"(d[33]), "+f"(d[34]), "+f"(d[35]), "+f"(d[36]), "+f"(d[37]), "+f"(d[38]), "+f"(d[39]), "+f"(d[40]), "+f"(d[41]), "+f"(d[42]), "+f"(d[43]), "+f"(d[44]), "+f"(d[45]), "+f"(d[46]), "+f"(d[47]), "+f"(d[48]), "+f"(d[49]), "+f"(d[50]), "+f"(d[51]), "+f"(d[52]), "+f"(d[53]), "+f"(d[54]), "+f"(d[55]), "+f"(d[56]), "+f"(d[57]), "+f"(d[58]), "+f"(d[59]), "+f"(d[60]), "+f"(d[61]), "+f"(d[62]), "+f"(d[63]), "+f"(d[64]), "+f"(d[65]), "+f"(d[66]), "+f"(d[67]), "+f"(d[68]), "+f"(d[69]), "+f"(d[70]), "+f"(d[71]), "+f"(d[72]), "+f"(d[73]), "+f"(d[74]), "+f"(d[75]), "+f"(d[76]), "+f"(d[77]), "+f"(d[78]), "+f"(d[79]), "+f"(d[80]), "+f"(d[81]), "+f"(d[82]), "+f"(d[83]), "+f"(d[84]), "+f"(d[85]), "+f"(d[86]), "+f"(d[87]), "+f"(d[88]), "+f"(d[89]), "+f"(d[90]), "+f"(d[91]), "+f"(d[92]), "+f"(d[93]), "+f"(d[94]), "+f"(d[95]), "+f"(d[96]), "+f"(d[97]), "+f"(d[98]), "+f"(d[99]), "+f"(d[100]), "+f"(d[101]), "+f"(d[102]), "+f"(d[103]), "+f"(d[104]), "+f"(d[105]), "+f"(d[106]), "+f"(d[107]), "+f"(d[108]), "+f"(d[109]), "+f"(d[110]), "+f"(d[111]), "+f"(d[112]), "+f"(d[113]), "+f"(d[114]), "+f"(d[115]), "+f"(d[116]), "+f"(d[117]), "+f"(d[118]), "+f"(d[119]), "+f"(d[120]), "+f"(d[121]), "+f"(d[122]), "+f"(d[123]), "+f"(d[124]), "+f"(d[125]), "+f"(d[126]), "+f"(d[127])
    : "l"(da), "l"(db), "r"(acc), "n"(TA), "n"(TB));
}

template <int TB> __device__ __forceinline__ void wgmma_rs_n24(float (&d)[12], uint32_t a0, uint32_t a1, uint32_t a2, uint32_t a3, uint64_t db, int acc) {
  asm volatile("{\n.reg .pred p;\nsetp.ne.b32 p, %17, 0;\n"
    "wgmma.mma_async.sync.aligned.m64n24k16.f32.bf16.bf16 {%0, %1, %2, %3, %4, %5, %6, %7, %8, %9, %10, %11}, {%12, %13, %14, %15}, %16, p, 1, 1, %18;\n}\n"
    : "+f"(d[0]), "+f"(d[1]), "+f"(d[2]), "+f"(d[3]), "+f"(d[4]), "+f"(d[5]), "+f"(d[6]), "+f"(d[7]), "+f"(d[8]), "+f"(d[9]), "+f"(d[10]), "+f"(d[11])
    : "r"(a0), "r"(a1), "r"(a2), "r"(a3), "l"(db), "r"(acc), "n"(TB));
}

template <int TB> __device__ __forceinline__ void wgmma_rs_n40(float (&d)[20], uint32_t a0, uint32_t a1, uint32_t a2, uint32_t a3, uint64_t db, int acc) {
  asm volatile("{\n.reg .pred p;\nsetp.ne.b32 p, %25, 0;\n"
    "wgmma.mma_async.sync.aligned.m64n40k16.f32.bf16.bf16 {%0, %1, %2, %3, %4, %5, %6, %7, %8, %9, %10, %11, %12, %13, %14, %15, %16, %17, %18, %19}, {%20, %21, %22, %23}, %24, p, 1, 1, %26;\n}\n"
    : "+f"(d[0]), "+f"(d[1]), "+f"(d[2]), "+f"(d[3]), "+f"(d[4]), "+f"(d[5]), "+f"(d[6]), "+f"(d[7]), "+f"(d[8]), "+f"(d[9]), "+f"(d[10]), "+f"(d[11]), "+f"(d[12]), "+f"(d[13]), "+f"(d[14]), "+f"(d[15]), "+f"(d[16]), "+f"(d[17]), "+f"(d[18]), "+f"(d[19])
    : "r"(a0), "r"(a1), "r"(a2), "r"(a3), "l"(db), "r"(acc), "n"(TB));
}

template <int TB> __device__ __forceinline__ void wgmma_rs_n192(float (&d)[96], uint32_t a0, uint32_t a1, uint32_t a2, uint32_t a3, uint64_t db, int acc) {
  asm volatile("{\n.reg .pred p;\nsetp.ne.b32 p, %101, 0;\n"
    "wgmma.mma_async.sync.aligned.m64n192k16.f32.bf16.bf16 {%0, %1, %2, %3, %4, %5, %6, %7, %8, %9, %10, %11, %12, %13, %14, %15, %16, %17, %18, %19, %20, %21, %22, %23, %24, %25, %26, %27, %28, %29, %30, %31, %32, %33, %34, %35, %36, %37, %38, %39, %40, %41, %42, %43, %44, %45, %46, %47, %48, %49, %50, %51, %52, %53, %54, %55, %56, %57, %58, %59, %60, %61, %62, %63, %64, %65, %66, %67, %68, %69, %70, %71, %72, %73, %74, %75, %76, %77, %78, %79, %80, %81, %82, %83, %84, %85, %86, %87, %88, %89, %90, %91, %92, %93, %94, %95}, {%96, %97, %98, %99}, %100, p, 1, 1, %102;\n}\n"
    : "+f"(d[0]), "+f"(d[1]), "+f"(d[2]), "+f"(d[3]), "+f"(d[4]), "+f"(d[5]), "+f"(d[6]), "+f"(d[7]), "+f"(d[8]), "+f"(d[9]), "+f"(d[10]), "+f"(d[11]), "+f"(d[12]), "+f"(d[13]), "+f"(d[14]), "+f"(d[15]), "+f"(d[16]), "+f"(d[17]), "+f"(d[18]), "+f"(d[19]), "+f"(d[20]), "+f"(d[21]), "+f"(d[22]), "+f"(d[23]), "+f"(d[24]), "+f"(d[25]), "+f"(d[26]), "+f"(d[27]), "+f"(d[28]), "+f"(d[29]), "+f"(d[30]), "+f"(d[31]), "+f"(d[32]), "+f"(d[33]), "+f"(d[34]), "+f"(d[35]), "+f"(d[36]), "+f"(d[37]), "+f"(d[38]), "+f"(d[39]), "+f"(d[40]), "+f"(d[41]), "+f"(d[42]), "+f"(d[43]), "+f"(d[44]), "+f"(d[45]), "+f"(d[46]), "+f"(d[47]), "+f"(d[48]), "+f"(d[49]), "+f"(d[50]), "+f"(d[51]), "+f"(d[52]), "+f"(d[53]), "+f"(d[54]), "+f"(d[55]), "+f"(d[56]), "+f"(d[57]), "+f"(d[58]), "+f"(d[59]), "+f"(d[60]), "+f"(d[61]), "+f"(d[62]), "+f"(d[63]), "+f"(d[64]), "+f"(d[65]), "+f"(d[66]), "+f"(d[67]), "+f"(d[68]), "+f"(d[69]), "+f"(d[70]), "+f"(d[71]), "+f"(d[72]), "+f"(d[73]), "+f"(d[74]), "+f"(d[75]), "+f"(d[76]), "+f"(d[77]), "+f"(d[78]), "+f"(d[79]), "+f"(d[80]), "+f"(d[81]), "+f"(d[82]), "+f"(d[83]), "+f"(d[84]), "+f"(d[85]), "+f"(d[86]), "+f"(d[87]), "+f"(d[88]), "+f"(d[89]), "+f"(d[90]), "+f"(d[91]), "+f"(d[92]), "+f"(d[93]), "+f"(d[94]), "+f"(d[95])
    : "r"(a0), "r"(a1), "r"(a2), "r"(a3), "l"(db), "r"(acc), "n"(TB));
}
constexpr uint32_t AR_ACC = 0;
constexpr uint32_t AR_TAB = 0x100000;
constexpr uint32_t AR_PROG = 0x101000;
__host__ __device__ constexpr uint32_t prog_off(int h, int j) { return AR_PROG + h * 128 + j * 4; }
constexpr uint32_t AR_CNT = 0x108000;
constexpr uint32_t AR_QUEUE = 0x109000;
constexpr uint32_t AR_SIZE = 0x10a000;

struct ChainArgs {
  const bf16* mem0;
  const uint2* xh;
  unsigned char *kg, *vg;
  unsigned char* arena;
  unsigned* go;
  uint32_t* dbg;
  uint32_t delay;
  int margin, pubrel;
  int tl;
};

namespace ch {
constexpr int OFF_WQ = 0;
constexpr int OFF_X = 81920;
constexpr int OFF_MEM = OFF_X + 40960;
constexpr int OFF_WO = OFF_MEM + 10240;
constexpr int WOK = 8 * 896;
constexpr int OFF_KV = OFF_WO + 10 * WOK;
constexpr int KVB = 5120;
constexpr int OFF_O = OFF_KV + 4 * KVB;
constexpr int OFF_Q = OFF_O + 1024;
constexpr int OFF_S = OFF_O + 3072;
constexpr int OFF_SR = OFF_S + 1536;
constexpr int OFF_LT = OFF_SR + 1280;
constexpr int OFF_BAR = OFF_LT + 512;
constexpr int SMEM = OFF_BAR + 256;
static_assert(SMEM <= 232448, "smem");
constexpr int MB_S = OFF_BAR, MB_O = OFF_BAR + 8, MB_X = OFF_BAR + 16;
constexpr int MB_K = OFF_BAR + 128, MB_V = MB_K + 16, MB_Q = MB_K + 32, MB_R = MB_K + 48;
constexpr int SC_IN = OFF_BAR + 64;
constexpr int SC_MX = OFF_S;
constexpr int SC_TW = OFF_BAR + 48;
constexpr int SC_W = OFF_BAR + 96;
constexpr int WOS = 448;
enum { B_MEM0 = 1, B_QK, B_SL, B_V, B_O, B_RED, B_X, B_C, B_H, B_MEM1, B_A, B_G, B_E };
#ifndef NQ1
#define NQ1 6
#endif
#ifndef NQ0
#define NQ0 4
#endif
#ifndef NP0
#define NP0 4
#endif
#ifndef NWO
#define NWO 5
#endif
#ifndef NWP
#define NWP 4
#endif
#ifndef NB0
#define NB0 3
#endif
#ifndef BBS
#define BBS 100
#endif
#ifndef VSYNC
#define VSYNC 0
#endif
#ifndef XPOS
#define XPOS 0
#endif
#ifndef XPD
#define XPD 300
#endif
#ifndef WOF
#define WOF 0
#endif
#ifndef XBYTES
#define XBYTES 36864
#endif
#ifndef NRT
#define NRT 7
#endif
#ifndef NRF
#define NRF 2
#endif
#ifndef NPM0
#define NPM0 2
#endif
#ifndef NPM1
#define NPM1 2
#endif
#ifndef RSYNC
#define RSYNC 1
#endif
#ifndef PFK
#define PFK 1
#endif
#ifndef PA0
#define PA0 3
#endif
#ifndef PA1
#define PA1 0
#endif
#ifndef PB0
#define PB0 7
#endif
#ifndef PB1
#define PB1 5
#endif
#ifndef PQE
#define PQE 1
#endif
#ifndef XT
#define XT 30
#endif
static_assert(NPM0 >= 2 && NPM1 >= 2, "the K / V blocks live in the last two k-steps of Wo");
}

#ifndef CHAIN_TIMING
#define CHAIN_TIMING 0
#endif
#if CHAIN_TIMING
#ifndef TR0
#define TR0 41
#endif
#ifndef TSMASK
#define TSMASK 0xffff
#endif
#define TSV(i, v) do { if ((TSMASK >> (i)) & 1) asm volatile("st.shared.u32 [%0+%1], %2;" :: "r"(tsb), "n"((i) * 4), "r"(v) : "memory"); } while (0)
#define TS(i) TSV(i, clk32())
#define TS_SETUP() const uint32_t tsb = sb + ((s == TR0 || s == TR0 + 1) ? OFF_BAR + 128 + ((s - TR0) * 12 + warp) * 48 : OFF_SR + 1152)
#else
#define TS(i)
#define TSV(i, v)
#define TS_SETUP()
#endif
#ifndef POLL_DELAY
#define POLL_DELAY 620
#endif
#ifndef XN
#define XN 40
#endif
#ifndef PF0
#define PF0 8
#endif
#ifndef PFS
#define PFS 3
#endif
#ifndef XDELAY
#define XDELAY 0
#endif
#ifndef NOKM
#define NOKM 0
#endif
#ifndef PFX
#define PFX 3
#endif
#ifndef NVE
#define NVE 10
#endif
#ifndef VET
#define VET 19
#endif
#ifndef MEMFIRST
#define MEMFIRST 1
#endif
#ifndef PM1
#define PM1 1
#endif
#ifndef GD1
#define GD1 30
#endif
#ifndef GD2
#define GD2 150
#endif
#ifndef CEARLY
#define CEARLY 1
#endif
#ifndef NPL
#define NPL 0
#endif
#ifndef PFACC
#define PFACC 1
#endif
template <int V> using IC = std::integral_constant<int, V>;
__device__ __forceinline__ uint32_t clk_v() { uint64_t c; asm volatile("mov.u64 %0, %%clock64;" : "=l"(c) :: "memory"); return (uint32_t)c; }
__device__ __forceinline__ int fresh(int x) { int y; asm volatile("shfl.sync.bfly.b32 %0, %1, 0, 0x1f, 0xffffffff;" : "=r"(y) : "r"(x)); return y; }
#define SFENCE2(x, d) asm volatile("{\n.reg .pred p;\nsetp.eq.u32 p, %0, 0x7fffffff;\n@p st.shared.u32 [%0], %1;\n}" :: "r"(x), "r"(d) : "memory")
#define SFENCE(x) asm volatile("{\n.reg .pred p;\nsetp.eq.u32 p, %0, 0x7fffffff;\n@p st.shared.u32 [%0], %0;\n}" :: "r"(x) : "memory")
template <int I> __device__ __forceinline__ void bbfence(uint32_t x) {
  asm volatile("{\n.reg .pred p;\nsetp.eq.u32 p, %0, %1;\nL_%=:\n@p st.volatile.shared.u32 [%0], %0;\n@p bra.uni L_%=;\n}" :: "r"(x), "n"(4 * I) : "memory");
}
__device__ __forceinline__ float uniform_f(float x) { return __uint_as_float(__reduce_max_sync(0xffffffffu, __float_as_uint(x))); }

__device__ __forceinline__ void mma16816h(float (&d)[4], const uint32_t (&a)[4], uint32_t b0, uint32_t b1) {
  asm volatile("mma.sync.aligned.m16n8k16.row.col.f32.f16.f16.f32 {%0,%1,%2,%3}, {%4,%5,%6,%7}, {%8,%9}, {%0,%1,%2,%3};"
               : "+f"(d[0]), "+f"(d[1]), "+f"(d[2]), "+f"(d[3]) : "r"(a[0]), "r"(a[1]), "r"(a[2]), "r"(a[3]), "r"(b0), "r"(b1));
}
__device__ __forceinline__ void mma1688(float (&d)[4], uint32_t a0, uint32_t a1, uint32_t b0) {
  asm volatile("mma.sync.aligned.m16n8k8.row.col.f32.bf16.bf16.f32 {%0,%1,%2,%3}, {%4,%5}, {%6}, {%0,%1,%2,%3};"
               : "+f"(d[0]), "+f"(d[1]), "+f"(d[2]), "+f"(d[3]) : "r"(a0), "r"(a1), "r"(b0));
}
template <int OFF16, int ACC> __device__ __forceinline__ void wgmma_rs32h(float (&d)[16], const uint32_t (&a)[4], uint32_t dlo) {
  asm volatile("{\n.reg .pred p;\n.reg .b32 t;\n.reg .b64 db;\nsetp.ne.b32 p, %22, 0;\nadd.u32 t, %20, %21;\nmov.b64 db, {t, 0x40000040};\n"
    "wgmma.mma_async.sync.aligned.m64n32k16.f32.f16.f16 {%0,%1,%2,%3,%4,%5,%6,%7,%8,%9,%10,%11,%12,%13,%14,%15}, {%16,%17,%18,%19}, db, p, 1, 1, 0;\n}\n"
    : "+f"(d[0]), "+f"(d[1]), "+f"(d[2]), "+f"(d[3]), "+f"(d[4]), "+f"(d[5]), "+f"(d[6]), "+f"(d[7]), "+f"(d[8]), "+f"(d[9]), "+f"(d[10]), "+f"(d[11]),
      "+f"(d[12]), "+f"(d[13]), "+f"(d[14]), "+f"(d[15])
    : "r"(a[0]), "r"(a[1]), "r"(a[2]), "r"(a[3]), "r"(dlo), "n"(OFF16), "n"(ACC));
}
template <int IMM> __device__ __forceinline__ void stsm_x4_t_i(uint32_t a, uint32_t r0, uint32_t r1, uint32_t r2, uint32_t r3) {
  asm volatile("stmatrix.sync.aligned.m8n8.x4.trans.shared.b16 [%0+%5], {%1,%2,%3,%4};" :: "r"(a), "r"(r0), "r"(r1), "r"(r2), "r"(r3), "n"(IMM) : "memory");
}
template <int IMM> __device__ __forceinline__ void stsm_x2_t_i(uint32_t a, uint32_t r0, uint32_t r1) {
  asm volatile("stmatrix.sync.aligned.m8n8.x2.trans.shared.b16 [%0+%3], {%1,%2};" :: "r"(a), "r"(r0), "r"(r1), "n"(IMM) : "memory");
}
template <int IMM> __device__ __forceinline__ void st_async_b32_i(uint32_t a, uint32_t x, uint32_t mb) {
  asm volatile("st.async.weak.shared::cluster.mbarrier::complete_tx::bytes.b32 [%0+%3], %1, [%2];" :: "r"(a), "r"(x), "r"(mb), "n"(IMM) : "memory");
}
template <int IMM> __device__ __forceinline__ void ld_relaxed_v4_if(uint4& v, const void* p, uint32_t c) {
  asm volatile("{\n.reg .pred p;\nsetp.ne.u32 p, %6, 0;\n@p ld.relaxed.gpu.global.v4.u32 {%0,%1,%2,%3}, [%4+%5];\n}"
               : "+r"(v.x), "+r"(v.y), "+r"(v.z), "+r"(v.w) : "l"(p), "n"(IMM), "r"(c) : "memory");
}
template <int IMM> __device__ __forceinline__ void ldsm_x2_i(uint32_t (&r)[2], uint32_t a) {
  asm volatile("ldmatrix.sync.aligned.m8n8.x2.shared.b16 {%0,%1}, [%2+%3];" : "=r"(r[0]), "=r"(r[1]) : "r"(a), "n"(IMM) : "memory");
}
template <int IMM> __device__ __forceinline__ uint32_t ldsm_x1_t_i(uint32_t a) {
  uint32_t r; asm volatile("ldmatrix.sync.aligned.m8n8.x1.trans.shared.b16 {%0}, [%1+%2];" : "=r"(r) : "r"(a), "n"(IMM) : "memory"); return r;
}
template <int IMM> __device__ __forceinline__ uint32_t lds32_i(uint32_t a) {
  uint32_t v; asm volatile("ld.shared.u32 %0, [%1+%2];" : "=r"(v) : "r"(a), "n"(IMM) : "memory"); return v;
}
__device__ __forceinline__ void sts32(uint32_t a, uint32_t v) { asm volatile("st.shared.u32 [%0], %1;" :: "r"(a), "r"(v) : "memory"); }
__device__ __forceinline__ uint32_t pack_f16(float lo, float hi) {
  uint32_t d; asm("cvt.rn.f16x2.f32 %0, %1, %2;" : "=r"(d) : "f"(hi), "f"(lo)); return d;
}
__device__ __forceinline__ uint32_t amax_bf2(uint32_t a, uint32_t b) { uint32_t d; asm("max.xorsign.abs.bf16x2 %0, %1, %2;" : "=r"(d) : "r"(a), "r"(b)); return d; }
__device__ __forceinline__ uint32_t amax_h2(uint32_t a, uint32_t b) { uint32_t d; asm("max.xorsign.abs.f16x2 %0, %1, %2;" : "=r"(d) : "r"(a), "r"(b)); return d; }
__device__ __forceinline__ uint32_t amax_fold(uint32_t m) { return __reduce_max_sync(0xffffffffu, max(m & 0x7fffu, (m >> 16) & 0x7fffu)); }
__device__ __forceinline__ int wscale_exp(uint32_t m) { return min(141 - (int)(m >> 7), 100); }
__device__ __forceinline__ float exp2i(int e) { return __uint_as_float((uint32_t)(e + 127) << 23); }
__device__ __forceinline__ uint32_t bf2_to_h2(uint32_t w, float sc) { return pack_f16(bf_lo(w) * sc, bf_hi(w) * sc); }
__device__ __forceinline__ void bf2_to_h2_inplace(uint32_t& w, uint32_t sc2) {
  asm volatile("{\n.reg .b32 t, lo, hi;\nmul.rn.bf16x2 t, %0, %1;\nshl.b32 lo, t, 16;\nand.b32 hi, t, 0xffff0000;\ncvt.rn.f16x2.f32 %0, hi, lo;\n}" : "+r"(w) : "r"(sc2));
}
__device__ __forceinline__ void prefetch_l2(const void* p, uint32_t bytes) { asm volatile("cp.async.bulk.prefetch.L2.global [%0], %1;" :: "l"(p), "r"(bytes) : "memory"); }
__device__ __forceinline__ void prefetch_tma_2d(const CUtensorMap* tm, int c0, int c1) {
  asm volatile("cp.async.bulk.prefetch.tensor.2d.L2.global [%0, {%1, %2}];" :: "l"(tm), "r"(c0), "r"(c1) : "memory");
}
__host__ __device__ constexpr uint32_t acc_voff(int v) { return v < 4 ? v * 1024u : (v == 4 ? 128u : 3072u + 128u); }
__device__ __forceinline__ int unit28(int i) { return i == 3 ? 54 : 14 * i; }
__device__ __forceinline__ int unit24(int i) { return i < 2 ? 48 - 6 * i : 56 + 6 * i; }
__device__ __forceinline__ uint32_t acc_step(int s) { return (s >> 1) * 32768 + (s & 1) * 512; }
__device__ __forceinline__ uint32_t acc_lane(int i, int lane) { return ((lane >> 3) & 1) * 256 + (lane >> 4) * 4096 + i * 8192 + (lane & 7) * 16; }

__device__ __forceinline__ uint32_t ld_acquire_u32(const void* p) {
  uint32_t v; asm volatile("ld.acquire.gpu.global.u32 %0, [%1];" : "=r"(v) : "l"(p) : "memory"); return v;
}
template <int R> __device__ __forceinline__ void ln_rows(const uint2 (&xw)[R][5], int row0, int lane, bf16* __restrict__ xn, uint2* __restrict__ xh) {
  float v[R][20], s[R], q[R];
#pragma unroll
  for (int r = 0; r < R; r++) {
    s[r] = 0.f; q[r] = 0.f;
#pragma unroll
    for (int i = 0; i < 5; i++) { v[r][4 * i] = bf_lo(xw[r][i].x); v[r][4 * i + 1] = bf_hi(xw[r][i].x); v[r][4 * i + 2] = bf_lo(xw[r][i].y); v[r][4 * i + 3] = bf_hi(xw[r][i].y); }
#pragma unroll
    for (int i = 0; i < 5; i++) s[r] += (v[r][4 * i] + v[r][4 * i + 1]) + (v[r][4 * i + 2] + v[r][4 * i + 3]);
  }
#pragma unroll
  for (int o = 16; o; o >>= 1)
#pragma unroll
    for (int r = 0; r < R; r++) s[r] += __shfl_xor_sync(0xffffffffu, s[r], o);
#pragma unroll
  for (int r = 0; r < R; r++) {
    s[r] *= 1.f / cfg::DM;
#pragma unroll
    for (int i = 0; i < 10; i++) { const float d = v[r][2 * i] - s[r], e = v[r][2 * i + 1] - s[r]; q[r] += d * d + e * e; }
  }
#pragma unroll
  for (int o = 16; o; o >>= 1)
#pragma unroll
    for (int r = 0; r < R; r++) q[r] += __shfl_xor_sync(0xffffffffu, q[r], o);
#pragma unroll
  for (int r = 0; r < R; r++) {
    const int row = row0 + r;
    const float mb = bf16r(s[r]), var = bf16r(q[r] * (1.f / cfg::DM));
    float sd; asm("sqrt.approx.f32 %0, %1;" : "=f"(sd) : "f"(bf16r(var + 1e-5f)));
    const float inv = rcpf(bf16r(sd));
#pragma unroll
    for (int i = 0; i < 5; i++) {
      float y[4];
#pragma unroll
      for (int e = 0; e < 4; e++) y[e] = v[r][4 * i + e] - mb;
      bf16r2(y[0], y[1]); bf16r2(y[2], y[3]);
      const uint32_t w0 = pack_bf16(y[0] * inv, y[1] * inv), w1 = pack_bf16(y[2] * inv, y[3] * inv);
      *(uint2*)(xn + (size_t)row * cfg::DM + i * 128 + lane * 4) = make_uint2(w0, w1);
      if (xh) xh[(((size_t)(row >> 5) * 10 + 2 * i + (lane >> 4)) * 32 + (row & 31)) * 16 + ((((lane >> 1) & 7) ^ (row & 7)) << 1) + (lane & 1)] =
          make_uint2(pack_f16(bf_lo(w0), bf_hi(w0)), pack_f16(bf_lo(w1), bf_hi(w1)));
    }
  }
}

__global__ void __cluster_dims__(3, 1, 1) __launch_bounds__(384, 1) chain_kernel(const ChainArgs a, const __grid_constant__ CUtensorMap tmWq,
    const __grid_constant__ CUtensorMap tmWk, const __grid_constant__ CUtensorMap tmWv, const __grid_constant__ CUtensorMap tmWo) {
  using namespace ch;
  extern __shared__ __align__(1024) unsigned char smem_raw[];
  const uint32_t sb = smem_u32(smem_raw);
  const int warp = __shfl_sync(0xffffffffu, (int)threadIdx.x >> 5, 0);
  const int lane = __shfl_sync(0xffffffffu, (int)threadIdx.x & 31, threadIdx.x & 31);
  const int cta = blockIdx.x, h = cta / 3, j = cta % 3;
  const int g = lane >> 2, q4 = lane & 3, r8 = lane & 7, m4 = lane >> 3;
  unsigned char* const arena = a.arena;
  if (sb & 1023u) __trap();
  asm volatile("griddepcontrol.launch_dependents;");
  TL_BEGIN(a.tl);
#ifdef TIMELINE
  const unsigned long long g_tl0 = gtime();
#define PT(i) TLW((a.tl >= 12) * 128 + 64 + (i))
#else
#define PT(i)
#endif
  const int col0 = j == 0 ? 0 : (j == 1 ? 224 : 432);
  auto stage_w = [&](const CUtensorMap* tm, uint32_t dst, uint32_t mb, int half) {
    mbar_expect_tx(mb + 8 * half, 40960);
    tma_load_2d(dst + half * 40960, tm, h * cfg::DH + j * 64, half * 320, mb + 8 * half);
    tma_load_2d(dst + half * 40960 + 20480, tm, h * cfg::DH + j * 64, half * 320 + 160, mb + 8 * half);
  };
  if (threadIdx.x == 256) {
    for (int i = 0; i < 9; i++) mbar_init(sb + MB_K + 8 * i, 1);
    mbar_init(sb + MB_S, 1); mbar_init(sb + MB_O, 1); mbar_init(sb + MB_X, 1);
    asm volatile("fence.mbarrier_init.release.cluster;" ::: "memory");
    for (int i = 0; i < 2; i++) { stage_w(&tmWk, sb + OFF_WQ, sb + MB_K, i); stage_w(&tmWv, sb + OFF_WO, sb + MB_V, i); }
    sts32(sb + SC_W, 0); sts32(sb + SC_W + 4, 0); sts32(sb + SC_W + 8, 0); sts32(sb + SC_IN + 12, 0); sts32(sb + SC_IN + 20, 0); sts32(sb + SC_TW + 4, 99);
    mbar_expect_tx(sb + MB_S, 1280); mbar_expect_tx(sb + MB_O, 2048);
  }
  __syncthreads();
  asm volatile("barrier.cluster.arrive.relaxed.aligned;" ::: "memory");
  const uint32_t d1 = mapa_u32(sb, (j + 1) % 3) - sb, d2 = mapa_u32(sb, (j + 2) % 3) - sb;

  if (warp >= 8) {
    asm volatile("setmaxnreg.dec.sync.aligned.u32 40;");
    const int hw = warp - 8, ht = hw * 32 + lane;
    const bool lead = ht == 0;
    auto stage_wo = [&](int i) {
      mbar_expect_tx(sb + MB_R + 8 * i, 64 * WOS);
      tma_load_2d(sb + OFF_WO + i * 64 * WOS, &tmWo, col0, h * cfg::DH + ((i + j) % 3) * 64, sb + MB_R + 8 * i);
    };
    const unsigned char* xg = (const unsigned char*)a.xh;
    auto issue_x = [&](int s) { mbar_expect_tx(sb + MB_X, 40960); bulk_g2s(sb + OFF_X, xg + (size_t)s * 40960, 40960, sb + MB_X); };
    uint4 v[5];
#pragma unroll
    for (int i = 0; i < 5; i++) { const int c = ht + 128 * i; v[i] = ld_relaxed_v4(a.mem0 + (c & 7) * cfg::DM + (c >> 3) * 8); }
    if (hw == 2) {
      asm volatile("griddepcontrol.wait;" ::: "memory");
      if (lane == 0) { if (cta == 0) st_relaxed_u32(a.go, 1); issue_x(0); }
      PT(0);
    }
    if (hw == 0) {
      bar_sync(B_QK, 160); if (lane == 0) stage_w(&tmWq, sb + OFF_WQ, sb + MB_Q, 0);
      bar_sync(B_SL, 160); if (lane == 0) stage_w(&tmWq, sb + OFF_WQ, sb + MB_Q, 1);
    }
    if (hw == 1) {
      bar_sync(B_V, 160); if (lane == 0) stage_wo(0);
      bar_sync(B_O, 160); if (lane == 0) { stage_wo(1); stage_wo(2); }
    }
    __syncwarp();
    {
      uint32_t m = 0;
#pragma unroll
      for (int i = 0; i < 5; i++) {
        m = amax_bf2(amax_bf2(m, amax_bf2(v[i].x, v[i].y)), amax_bf2(v[i].z, v[i].w));
      }
      m = amax_fold(m);
      if (lane == 0) sts32(sb + SC_MX + hw * 4, m);
      bar_sync(B_H, 128);
      const uint4 mm = lds128(sb + SC_MX);
      const int se = max(wscale_exp(max(max(mm.x, mm.y), max(mm.z, mm.w))), -100);
      const float sc = exp2i(se);
#pragma unroll
      for (int i = 0; i < 5; i++) {
        const int c = ht + 128 * i, t = c & 7, chn = c >> 3;
        sts128(sb + OFF_MEM + chn * 128 + ((t ^ (2 * (chn & 3))) << 4), bf2_to_h2(v[i].x, sc), bf2_to_h2(v[i].y, sc), bf2_to_h2(v[i].z, sc), bf2_to_h2(v[i].w, sc));
      }
      if (lead) { sts32(sb + SC_IN, __float_as_uint(exp2i(-se))); sts32(sb + SC_IN + 4, 0x7800u); }
    }
    if (hw == 0) PT(11);
    {
      const uint32_t p0 = sb + OFF_WQ + hw * 2048 + lane * 16;
      uint32_t m = 0;
#pragma unroll 1
      for (int i = 0; i < 10; i++) {
        if (i == 0 || i == 5) mbar_wait(sb + MB_Q + (i ? 8 : 0), 0);
        uint32_t r[4][4];
        static_for<0, 4>([&](auto K) { ldsm_x4_i<K.value * 512>(r[K.value], p0 + i * 8192); });
#pragma unroll
        for (int k = 0; k < 4; k++) m = amax_bf2(amax_bf2(m, amax_bf2(r[k][0], r[k][1])), amax_bf2(r[k][2], r[k][3]));
      }
      if (hw == 0) PT(9);
      m = amax_fold(m);
      if (lane == 0) asm volatile("red.shared.max.u32 [%0], %1;" :: "r"(sb + SC_W + 8), "r"(m) : "memory");
      bar_sync(B_H, 128);
      const uint32_t sc = (uint32_t)(wscale_exp(lds32_i<SC_W + 8>(sb)) + 127) * 0x00800080u;
#pragma unroll 1
      for (int i = 0; i < 10; i++) {
        uint32_t r[4][4];
        static_for<0, 4>([&](auto K) { ldsm_x4_i<K.value * 512>(r[K.value], p0 + i * 8192); });
#pragma unroll
        for (int k = 0; k < 4; k++) {
          bf2_to_h2_inplace(r[k][0], sc); bf2_to_h2_inplace(r[k][1], sc); bf2_to_h2_inplace(r[k][2], sc); bf2_to_h2_inplace(r[k][3], sc);
          stsm_x4(p0 + i * 8192 + k * 512, r[k][0], r[k][1], r[k][2], r[k][3]);
        }
      }
    }
    if (hw == 0) PT(10);
    bar_sync(0, 384);
    if (hw == 3) {
      const uint32_t eye = (m4 == q4) ? ((lane & 4) ? 0x3f800000u : 0x3f80u) : 0u;
      sts128(sb + OFF_LT + lane * 16, eye, eye, (lane & 2) * 64 + g * 16 + (lane & 1) * 8, 0u);
      sts64(sb + OFF_S + 1280 + lane * 8, 0u, 0u);
    }
    if (lead) st_relaxed_u32(arena + AR_TAB + cta * 4, 0x80000000u | (lds32_i<SC_W>(sb) << 15) | lds32_i<SC_W + 4>(sb));
    asm volatile("barrier.cluster.wait.aligned;" ::: "memory");
    bar_sync(B_MEM0, 256); bar_sync(B_MEM1, 256);
    {
      uint32_t v0, v1, v2; int spin = 0;
      do {
        v0 = ld_relaxed_u32(arena + AR_TAB + lane * 4); v1 = ld_relaxed_u32(arena + AR_TAB + 128 + lane * 4); v2 = ld_relaxed_u32(arena + AR_TAB + 256 + lane * 4);
      } while (__any_sync(0xffffffffu, ((v0 & v1 & v2) >> 31) == 0) && ++spin < SPIN_LIMIT);
      const uint32_t mv = (max(max(v0, v1), v2) >> 15) & 0x7fffu, mo = max(max(v0 & 0x7fffu, v1 & 0x7fffu), v2 & 0x7fffu);
      sts32(sb + SC_IN + 8 + (lane & 1) * 16, 15 - ((__reduce_max_sync(0xffffffffu, mv) >> 7) + (__reduce_max_sync(0xffffffffu, mo) >> 7) - 252 + 22));
    }

    auto store_kv = [&](int s) {
      const size_t o = ((size_t)s * 96 + cta) * KVB; const uint32_t src = sb + OFF_KV + (s & 1) * (2 * KVB);
      fence_proxy_async(); bulk_s2g(a.kg + o, src, KVB); bulk_s2g(a.vg + o, src + KVB, KVB); bulk_commit();
    };
    const int cb28 = unit28(hw), du = (unit24(hw) - cb28) * 128;
    uint32_t n16 = lane * 16, hist = 0;
    const uint32_t us1 = sb + d1 + OFF_SR + 256 + (hw >> 1) * 512 + (hw & 1) * 128, us2 = sb + d2 + OFF_SR + (hw >> 1) * 512 + (hw & 1) * 128;
    const uint32_t uo1 = sb + d1 + OFF_O + 2048 + hw * 256, uo2 = sb + d2 + OFF_O + 1024 + hw * 256;
#ifdef STEPCLK
    if (lead) a.dbg[96 * 300 + cta * 2] = clk32();
#endif
#ifdef TIMELINE
    if (cta == 0 && lead) { g_tl2[(a.tl >= 12) * 128 + 0] = clock64(); g_tl2[(a.tl >= 12) * 128 + 1] = gtime(); }
#endif
#pragma unroll 1
    for (int s = 0; s < cfg::NSEG; s++) {
      TS_SETUP();
      const bool last = s == cfg::NSEG - 1;
      if (n16 == 0) {
        if (hw == 2 && !last) issue_x(s + 1);
        if (hw == 0 && (s & 3) == 1 && s > 1) st_relaxed_u32(arena + (prog_off(h, j) + lds32_i<SC_IN + 12>(sb)), s - 1);
        if (hw == 0 && s > 0) store_kv(s - 1);
        if (PFX && hw == 3 && cta < 80 && s + PFX < cfg::NSEG) prefetch_l2(xg + (size_t)(s + PFX) * 40960 + cta * 512, 512);
        if (PFACC && hw == 1 && s + PFACC < cfg::NSEG - 1)
          asm volatile("prefetch.global.L2 [%0];" :: "l"(arena + (AR_ACC + acc_step(s + PFACC) + acc_lane(cta / 24, (cta & 3) * 8) + acc_voff((cta % 24) >> 2))) : "memory");
      }
      __syncwarp();
      if (last) break;
      const uint32_t kv = (s & 1) * (2 * KVB);
      n16 = fresh(n16);
      uint32_t kb0[4], kb1[4];
      { const uint32_t ka = n16 + (n16 & 384) * 4 + (sb + kv + hw * 128); ldsm_x4_i<OFF_KV>(kb0, ka); ldsm_x4_i<OFF_KV + 2560>(kb1, ka); }
      TS(1);
      bar_sync(B_QK, 384);
      {
        uint32_t q0[4], q1[4], q2[4], q3[4];
        float sa[4] = {0, 0, 0, 0}, sc2[4] = {0, 0, 0, 0};
        ldsm_x4_i<OFF_Q>(q0, n16 + sb); ldsm_x4_i<OFF_Q + 1024>(q2, n16 + sb); ldsm_x4_i<OFF_Q + 512>(q1, n16 + sb);
        bar_arrive(B_A, 288);
        ldsm_x4_i<OFF_Q + 1536>(q3, n16 + sb);
        mma16816(sa, q0[0], q0[1], q0[2], q0[3], kb0[0], kb0[1]);
        mma16816(sc2, q2[0], q2[1], q2[2], q2[3], kb1[0], kb1[1]);
        mma16816(sa, q1[0], q1[1], q1[2], q1[3], kb0[2], kb0[3]);
        mma16816(sc2, q3[0], q3[1], q3[2], q3[3], kb1[2], kb1[3]);
        const float x0 = (sa[0] + sa[2]) + (sc2[0] + sc2[2]), x1 = (sa[1] + sa[3]) + (sc2[1] + sc2[3]);
        const uint32_t xp = pack_bf16(x0, x1);
        st_async_b32_i<0>((n16 >> 2) + us1, xp, sb + MB_S + d1);
        st_async_b32_i<0>((n16 >> 2) + us2, xp, sb + MB_S + d2);
        stsm_x2(n16 + (sb + OFF_S + hw * 256), __float_as_uint(x0), __float_as_uint(x1));
      }
      TS(3);
      uint32_t v0[4], v1[4], vm0, vm1;
      const uint32_t uv = sb + kv + hw * 1280;
      ldsm_x4_t_i<OFF_KV + KVB>(v0, n16 + uv); ldsm_x4_t_i<OFF_KV + KVB + 640>(v1, n16 + uv);
      bar_sync(B_SL, 256);
      float t0[4], t1[4], t2[4];
      { uint32_t x[4]; ldsm_x4_i<OFF_S>(x, n16 + sb); t0[0] = __uint_as_float(x[0]); t0[1] = __uint_as_float(x[1]); t0[2] = __uint_as_float(x[2]); t0[3] = __uint_as_float(x[3]); }
      { uint32_t x[4]; ldsm_x4_i<OFF_S + 512>(x, n16 + sb); t1[0] = __uint_as_float(x[0]); t1[1] = __uint_as_float(x[1]); t1[2] = __uint_as_float(x[2]); t1[3] = __uint_as_float(x[3]); }
      { uint32_t x[4]; ldsm_x4_i<OFF_S + 1024>(x, n16 + sb); t2[0] = __uint_as_float(x[0]); t2[1] = __uint_as_float(x[1]); t2[2] = __uint_as_float(x[2]); t2[3] = __uint_as_float(x[3]); }
      mbar_spin(sb + MB_S, s & 1);
      TS(4);
      uint2 xo;
      {
        uint32_t r0[4], r1[4], r2[2];
        ldsm_x4_i<OFF_SR>(r0, n16 + sb); ldsm_x4_i<OFF_SR + 512>(r1, n16 + sb); ldsm_x2_i<OFF_SR + 1024>(r2, n16 + sb);
        SFENCE(n16);
        const uint2 eye = lds64_i<OFF_LT>(n16 + sb);
        mma16816(t0, r0[0], r0[1], r0[2], r0[3], eye.x, eye.y);
        mma16816(t1, r1[0], r1[1], r1[2], r1[3], eye.x, eye.y);
        mma1688(t2, r2[0], r2[1], eye.x);
        bar_sync(B_V, 256);
        vm0 = ldsm_x1_t_i<OFF_KV + KVB + 512>(n16 + uv); vm1 = ldsm_x1_t_i<OFF_KV + KVB + 1152>(n16 + uv);
        SFENCE(n16);
        xo = lds64_i<OFF_LT + 8>(n16 + sb);
      }
      float sc[10] = {t0[0], t0[1], t0[2], t0[3], t1[0], t1[1], t1[2], t1[3], t2[0] + t2[2], t2[1] + t2[3]};
      const float cs = 0.07216878364870322f * 1.4426950408889634f;
      float mx = fmaxf(fmaxf(fmaxf(sc[0], sc[1]), fmaxf(sc[2], sc[3])), fmaxf(fmaxf(sc[4], sc[5]), fmaxf(sc[6], sc[7])));
      mx = fmaxf(mx, fmaxf(sc[8], sc[9]));
      {
        const float m1 = __shfl_xor_sync(0xffffffffu, mx, 1), m2 = __shfl_xor_sync(0xffffffffu, mx, 2), m3 = __shfl_xor_sync(0xffffffffu, mx, 3);
        mx = fmaxf(fmaxf(mx, m1), fmaxf(m2, m3));
      }
      const float mo = fmaf(mx, -cs, __uint_as_float(xo.x));
      auto ex = [&](int i) -> uint32_t { float x, y;
        asm volatile("ex2.approx.ftz.f32 %0, %1;" : "=f"(x) : "f"(fmaf(sc[i], cs, mo))); asm volatile("ex2.approx.ftz.f32 %0, %1;" : "=f"(y) : "f"(fmaf(sc[i + 1], cs, mo)));
        return pack_bf16(x, y); };
      float oa[4] = {0, 0, 0, 0}, ob[4] = {0, 0, 0, 0}, oc[4] = {0, 0, 0, 0}, od[4] = {0, 0, 0, 0}, rs[4] = {0, 0, 0, 0};
      const uint32_t ones = 0x3f803f80u;
      const uint32_t p4 = ex(8);
      if (MEMFIRST) { mma1688(rs, p4, 0u, ones); mma1688(oa, p4, 0u, vm0); mma1688(ob, p4, 0u, vm1); }
      const uint32_t p0 = ex(0), p1 = ex(2), p2 = ex(4), p3 = ex(6);
      TS(5);
      mma16816(rs, p0, p2, p1, p3, ones, ones);
      mma16816(oa, p0, p2, p1, p3, v0[0], v0[1]);
      mma16816(oc, p0, p2, p1, p3, v0[2], v0[3]);
      mma16816(ob, p0, p2, p1, p3, v1[0], v1[1]);
      mma16816(od, p0, p2, p1, p3, v1[2], v1[3]);
      if (!MEMFIRST) { mma1688(rs, p4, 0u, ones); mma1688(oa, p4, 0u, vm0); mma1688(ob, p4, 0u, vm1); }
      const float inv = rcpf(rs[0] + rs[2]) * __uint_as_float(xo.y);
      {
        const uint32_t y0 = pack_bf16((oa[0] + oc[2]) * inv, (oa[1] + oc[3]) * inv), y1 = pack_bf16((ob[0] + od[2]) * inv, (ob[1] + od[3]) * inv);
        st_async_v2_i<0>(xo.x + uo1, y0, y1, sb + MB_O + d1);
        st_async_v2_i<0>(xo.x + uo2, y0, y1, sb + MB_O + d2);
        sts64_i<OFF_O>(xo.x + (sb + hw * 256), y0, y1);
      }
      bar_arrive(B_O, 384);
      TS(6);
      if (hw == 0) bulk_wait<0>();
      mbar_expect_tx_if(n16 == 0 && hw == 3, sb + MB_S, 1280);
      n16 = fresh(n16);
      const int ln = n16 >> 4;
      auto mslot = [&](int c) -> uint32_t { return sb + OFF_MEM + c * 128 + (((ln >> 2) ^ (2 * (c & 3))) << 4); };
      const int lq = ln & 3;
      const uint32_t ma = mslot(cb28 + lq), mb_ = mslot(cb28 + (lq >> 1)) + (lq & 1) * 8;
      const unsigned char* gp = arena + (AR_ACC + acc_lane(hw, ln) + acc_step(s));
      const bool odd = ln & 1;
      const uint32_t delay = a.delay + ((hist & 2) ? a.margin : 0);
      SFENCE(ma);
      uint32_t tw;
      if (hw == 0 && (s & 3) == 0 && a.pubrel) {
        bar_arrive(B_RED, 384);
        asm volatile("fence.acq_rel.gpu;" ::: "memory");
        uint2 t; int sp = 0;
        do { asm volatile("ld.volatile.shared.v2.u32 {%0,%1}, [%2];" : "=r"(t.x), "=r"(t.y) : "r"(sb + SC_TW) : "memory"); } while (__any_sync(0xffffffffu, t.y != (uint32_t)s) && ++sp < SPIN_LIMIT);
        tw = t.x;
      } else {
        bar_sync(B_RED, 384);
        SFENCE(mb_);
        tw = clk_v();
        if (hw == 1) asm volatile("st.volatile.shared.v2.u32 [%0], {%1,%2};" :: "r"(sb + SC_TW), "r"(tw), "r"(s) : "memory");
      }
      TSV(7, tw);
      mbar_expect_tx_if(n16 == 0 && hw == 3, sb + MB_O, 2048);
      while (clk_v() - tw < delay) {}
      TS(8);
      uint4 v[6];
      int spin = 0;
      const uint32_t cm = odd ? 0x5000u : 0u;
      do {
        static_for<0, 6>([&](auto I) { v[I.value] = ld_relaxed_v4_i<acc_voff(I.value)>(gp); });
      } while (__any_sync(0xffffffffu, (~((v[0].w & v[1].w & v[2].w) & (v[3].w & v[4].w & v[5].w)) & cm) != 0) && ++spin < SPIN_LIMIT);
      v[0].w = odd ? v[3].x : v[0].w; v[1].w = odd ? v[3].y : v[1].w; v[2].w = odd ? v[3].z : v[2].w; v[3].w = odd ? 0u : v[3].w;
      sts128_i<0>(ma, v[0].x, v[0].y, v[0].z, v[0].w);
      sts128_i<512>(ma, v[1].x, v[1].y, v[1].z, v[1].w);
      sts128_i<1024>(ma, v[2].x, v[2].y, v[2].z, v[2].w);
      sts128_i<0>(ma + du, v[4].x, v[4].y, v[4].z, v[5].z);
      sts64_i<512>(mb_ + du, v[5].x, v[5].y);
      if (!odd) sts128_i<1536>(mb_, v[3].x, v[3].y, v[3].z, v[3].w);
      hist = (hist * 2 + (spin != 0)) & 0xffffu;
      TSV(11, spin);
#ifdef TIMELINE
      if (hw == 2 && ln == 0) { uint32_t gt; asm volatile("mov.u32 %0, %%globaltimer_lo;" : "=r"(gt)); *(uint4*)(g_step + (((a.tl >= 12) * 64 + s) * 96 + cta) * 4) = make_uint4(gt, spin, clk_v() - tw, tw); }
#endif
      TS(10);
      bar_sync(B_MEM0, 256); bar_sync(B_MEM1, 256);
      uint32_t m = lds32_i<SC_IN + 12>(sb);
      uint32_t m2 = m;
      static_for<0, 3>([&](auto I) { m = amax_h2(amax_h2(amax_h2(amax_h2(m, v[I.value].x), v[I.value].y), v[I.value].z), v[I.value].w); });
      static_for<3, 6>([&](auto I) { m2 = amax_h2(amax_h2(amax_h2(m2, v[I.value].x), v[I.value].y), v[I.value].z); });
      m = amax_fold(amax_h2(amax_h2(m2, v[3].w), m));
      if (n16 == 0) asm volatile("red.shared.max.u32 [%0], %1;" :: "r"(sb + SC_IN + 4 + 16 * ((s + 1) & 1)), "r"(m) : "memory");
    }
    bar_sync(B_RED, 384);
    if (hw == 0 && n16 == 0) {
      store_kv(cfg::NSEG - 1);
      bulk_wait<0>();
      st_release_u32(arena + (prog_off(h, j) + lds32_i<SC_IN + 12>(sb)), cfg::NSEG);
    }
    __syncwarp();
#ifdef STEPCLK
    if (hw == 0 && n16 == 0) a.dbg[96 * 300 + cta * 2 + 1 + (hist >> 20)] = clk32();
#endif
#ifdef TIMELINE
    if (cta == 0 && hw == 0 && n16 == 0) { g_tl2[(a.tl >= 12) * 128 + 2] = clock64(); g_tl2[(a.tl >= 12) * 128 + 3] = gtime(); }
#endif
    TL_END(a.tl);
    asm volatile("barrier.cluster.arrive.relaxed.aligned; barrier.cluster.wait.aligned;" ::: "memory");
  } else {
    asm volatile("setmaxnreg.inc.sync.aligned.u32 232;");
    const int wi = warp & 3, hf = warp >> 2, tid = warp * 32 + lane;
    uint32_t w[40][4], wm = 0;
    uint32_t wqa;
    { const int mrow = r8 + ((lane >> 4) << 3), mch = 2 * wi + (m4 & 1); wqa = sb + mrow * 128 + ((mch ^ r8) << 4); }
    {
      const uint32_t wa = wqa + (hf ? OFF_WO : OFF_WQ);
      mbar_wait(sb + (hf ? MB_V : MB_K), 0);
      static_for<0, 20>([&](auto K) { ldsm_x4_t_i<K.value * 2048>(w[K.value], wa); });
#pragma unroll
      for (int k = 0; k < 20; k++) wm = amax_bf2(amax_bf2(wm, amax_bf2(w[k][0], w[k][1])), amax_bf2(w[k][2], w[k][3]));
      SFENCE2(wa, wm);
      if (warp == 0) PT(1);
      bar_arrive(hf ? B_V : B_QK, 160);
      mbar_wait(sb + (hf ? MB_V : MB_K) + 8, 0);
      static_for<20, 40>([&](auto K) { ldsm_x4_t_i<K.value * 2048>(w[K.value], wa); });
#pragma unroll
      for (int k = 20; k < 40; k++) wm = amax_bf2(amax_bf2(wm, amax_bf2(w[k][0], w[k][1])), amax_bf2(w[k][2], w[k][3]));
      SFENCE2(wa, wm);
      if (warp == 4) PT(2);
      bar_arrive(hf ? B_O : B_SL, 160);
      SFENCE(wa);
    }
    float iw, iq;
    {
      const uint32_t m = amax_fold(wm);
      if (hf && lane == 0) asm volatile("red.shared.max.u32 [%0], %1;" :: "r"(sb + SC_W), "r"(m) : "memory");
      const int e = wscale_exp(m);
      const uint32_t sc = (uint32_t)(e + 127) * 0x00800080u; iw = exp2i(-e);
#pragma unroll
      for (int k = 0; k < 40; k++) { bf2_to_h2_inplace(w[k][0], sc); bf2_to_h2_inplace(w[k][1], sc); bf2_to_h2_inplace(w[k][2], sc); bf2_to_h2_inplace(w[k][3], sc); }
    }
    uint32_t x0[8];
    {
      float xa[16];
      const uint32_t dlo = (((sb + OFF_X) & 0x3FFFF) >> 4) | (1u << 16);
      if (warp == 0) PT(3);
      mbar_wait(sb + MB_X, 0);
      if (warp == 0) PT(4);
      wgmma_fence();
      static_for<0, 40>([&](auto K) { constexpr int k = K.value; wgmma_rs32h<((k >> 2) * 4096 + (k & 3) * 32) / 16, (k != 0)>(xa, w[k], dlo); });
      wgmma_commit();
      wgmma_wait<0>();
#pragma unroll
      for (int i = 0; i < 8; i++) x0[i] = pack_bf16(xa[2 * i] * iw, xa[2 * i + 1] * iw);
    }
    const bool t28 = j == 0 || warp < 4;
    const int bi = j == 0 ? hf : (warp < 4 ? j + 1 : 2 * (j - 1) + ((warp - 4) >> 1)), bv = t28 ? wi : 4 + (warp & 1);
    uint32_t wo1 = sb + OFF_WO + warp * 896 + lane * 16, wo2;
    {
      const int cb = (t28 ? unit28(bi) : unit24(bi)) - col0 / 8;
      uint32_t cp[4];
#pragma unroll
      for (int wd = 0; wd < 4; wd++) {
        int c, p;
        if (bv < 3) { c = 4 * bv + q4; p = wd; }
        else if (bv == 3) { if (q4 & 1) { c = 4 * (wd % 3) + q4; p = 3; } else { c = 12 + (q4 >> 1); p = wd; } }
        else if (bv == 4) { c = q4; p = wd; }
        else { if (wd < 2) { c = 4 + (q4 >> 1); p = 2 * (q4 & 1) + wd; } else { c = q4; p = 3; } }
        cp[wd] = sb + OFF_WO + ((g & 1) + (g & 2) * 4 + (g >> 2) * 2) * WOS + (cb + c) * 16 + p * 4;
      }
      const int cidx = (r8 & 1) + ((r8 >> 2) << 1);
      wo2 = sb + OFF_WO + warp * 896 + ((m4 & 1) ? 768 + (m4 >> 1) * 64 + cidx * 16 : 512 + (m4 >> 1) * 128 + r8 * 16);
      const bool dump = (m4 & 1) && (r8 & 2);
      uint32_t mo = 0;
      const bool regular = bv < 3 || bv == 4;
#pragma unroll 1
      for (int i = 0; i < 3; i++) {
        uint32_t x[4][4], y[4][4];
        const uint32_t o = i * 4 * WOK;
        mbar_wait(sb + MB_R + 8 * i, 0);
        if (warp == 0) PT(5 + i);
        if (regular) {
          static_for<0, 4>([&](auto K) {
            constexpr int kk = K.value;
            const uint4 u = lds128_i<kk * WOK>(cp[0] + o), v = lds128_i<kk * WOK + 4 * WOS>(cp[0] + o);
            x[kk][0] = u.x; x[kk][1] = u.y; x[kk][2] = u.z; x[kk][3] = u.w; y[kk][0] = v.x; y[kk][1] = v.y; y[kk][2] = v.z; y[kk][3] = v.w;
          });
        } else {
          static_for<0, 4>([&](auto K) {
            constexpr int kk = K.value;
#pragma unroll
            for (int wd = 0; wd < 4; wd++) { x[kk][wd] = lds32_i<kk * WOK>(cp[wd] + o); y[kk][wd] = lds32_i<kk * WOK + 4 * WOS>(cp[wd] + o); }
          });
        }
        bar_sync(B_C, 256);
        static_for<0, 4>([&](auto K) {
          constexpr int kk = K.value;
#pragma unroll
          for (int wd = 0; wd < 4; wd++) mo = amax_bf2(mo, amax_bf2(x[kk][wd], y[kk][wd]));
          stsm_x4_t_i<kk * WOK>(wo1 + o, x[kk][0], x[kk][1], y[kk][0], y[kk][1]);
          stsm_x4_t_i<0>(dump ? sb + OFF_S + 512 + lane * 16 : wo2 + o + kk * WOK, x[kk][2], x[kk][3], y[kk][2], y[kk][3]);
        });
      }
      if (warp == 0) PT(8);
      mo = amax_fold(mo);
      if (lane == 0) asm volatile("red.shared.max.u32 [%0], %1;" :: "r"(sb + SC_W + 4), "r"(mo) : "memory");
    }
    __syncwarp();
    auto run = [&](auto HF) {
    constexpr int hf = HF.value;
    uint32_t mema, sta, l16 = sb + lane * 16;
    uint32_t rq[hf ? NQ1 : NQ0][4];
    auto step_addr = [&](uint32_t kv) {
      const int lr = (l16 >> 4) & 7, lm = (l16 >> 7) & 3;
      mema = l16 ^ (lm << 5);
      sta = sb + lr * 16 + (lm < 2 ? OFF_Q + wi * 512 + hf * 128 + lm * 256 : OFF_KV + kv + 512 + (2 * wi + lm - 2) * 640);
    };
    auto x_gemm = [&](uint32_t ph, [[maybe_unused]] uint32_t tsb) {
      float xa[16];
      const uint32_t dlo = (((sb + OFF_X) & 0x3FFFF) >> 4) | (1u << 16);
      constexpr int NP = hf ? NQ1 : NP0;
      if constexpr (hf) {
        static_for<PQE, NP>([&](auto K) { ldsm_x4_t_i<OFF_WQ + K.value * 2048>(rq[K.value], wqa); });
        bar_sync(B_X, 256);
      }
      wgmma_fence();
      static_for<0, 40>([&](auto K) {
        constexpr int k = K.value;
        wgmma_rs32h<((k >> 2) * 4096 + (k & 3) * 32) / 16, (k != 0)>(xa, w[k], dlo);
        if constexpr (!hf && k == PFK && NP > PQE) { SFENCE(wqa); static_for<PQE, NP>([&](auto K) { ldsm_x4_t_i<OFF_WQ + K.value * 2048>(rq[K.value], wqa); }); SFENCE(wqa); }
        if constexpr (!hf && k == XT) bar_arrive(B_X, 256);
      });
      step_addr(ph * (2 * KVB));
      wgmma_commit();
      TS(9);
      wgmma_wait<0>();
      const uint32_t xs = l16 + (wi * 1280 + ph * (2 * KVB));
      stsm_x4_t_i<OFF_KV + hf * KVB>(xs, pack_bf16(xa[0] * iw, xa[1] * iw), pack_bf16(xa[4] * iw, xa[5] * iw), pack_bf16(xa[8] * iw, xa[9] * iw), pack_bf16(xa[12] * iw, xa[13] * iw));
      stsm_x4_t_i<OFF_KV + hf * KVB + 640>(xs, pack_bf16(xa[2] * iw, xa[3] * iw), pack_bf16(xa[6] * iw, xa[7] * iw), pack_bf16(xa[10] * iw, xa[11] * iw), pack_bf16(xa[14] * iw, xa[15] * iw));
      if constexpr (!hf) static_for<NP0, NP0 + NPL>([&](auto K) { ldsm_x4_t_i<OFF_WQ + K.value * 2048>(rq[K.value], wqa); });
    };
    auto wq_addr = [&](uint32_t l) -> uint32_t {
      const int lr = (l >> 4) & 7, lm = (l >> 7) & 3;
      return sb + hf * ((40 - NQ1) * 2048) + (lr + ((lm >> 1) << 3)) * 128 + (((2 * wi + (lm & 1)) ^ lr) << 4);
    };
    constexpr int NPM = hf ? NPM1 : NPM0;
    uint32_t u1[NPM][4], u2[NPM][4];
    static_for<0, NPM>([&](auto K) { ldsm_x4_i<(12 - NPM + K.value) * WOK>(u1[K.value], wo1); ldsm_x4_i<(12 - NPM + K.value) * WOK>(u2[K.value], wo2); });
    bar_sync(0, 384);
    iq = uniform_f(exp2i(-wscale_exp(lds32_i<SC_W + 8>(sb))));
    wqa = wq_addr(l16);
    static_for<0, (hf ? NQ1 : NP0 + NPL)>([&](auto K) { ldsm_x4_t_i<OFF_WQ + K.value * 2048>(rq[K.value], wqa); });
    step_addr(0);
    stsm_x4_t_i<OFF_KV + hf * KVB>(l16 + wi * 1280, x0[0], x0[2], x0[4], x0[6]);
    stsm_x4_t_i<OFF_KV + hf * KVB + 640>(l16 + wi * 1280, x0[1], x0[3], x0[5], x0[7]);
    asm volatile("barrier.cluster.wait.aligned;" ::: "memory");
    TL_END(a.tl + 1);
#pragma unroll 1
    for (int s = 0; s < cfg::NSEG - 1; s++) {
      TS_SETUP();
#if CHAIN_TIMING
      if (tid == 0 && (s & 7) == 0) a.dbg[96 * 288 + cta * 8 + (s >> 3)] = clk32();
#endif
      bar_sync(hf ? B_MEM1 : B_MEM0, 256);
      const float sin_ = __uint_as_float(lds32_i<SC_IN>(sb + 16 * (s & 1)));
      constexpr int NPQ = (40 - NQ1) / 2;
      if constexpr (hf == 0) {
        float k0[4] = {0, 0, 0, 0}, k1[4] = {0, 0, 0, 0}, q0[4] = {0, 0, 0, 0}, q1[4] = {0, 0, 0, 0};
        constexpr auto pair_of = [](int t) { const int a = t * (20 - NPQ) / 20, b = (t + 1) * (20 - NPQ) / 20; return b > a ? NPQ + a : t - a; };
        uint32_t b[NB0][4];
        static_for<0, NB0>([&](auto T) { ldsm_x4_i<OFF_MEM + pair_of(T.value) * 512>(b[T.value], mema); });
        static_for<NP0 + NPL, NQ0>([&](auto K) { ldsm_x4_t_i<OFF_WQ + K.value * 2048>(rq[K.value], wqa); });
        if (BBS < 100) bbfence<0>(mema);
        static_for<0, 20>([&](auto T) {
          constexpr int t = T.value, p = pair_of(t);
          uint32_t (&bb)[4] = b[t % NB0];
          if constexpr (p < NPQ) {
            mma16816h(q0, rq[(2 * p) % NQ0], bb[0], bb[1]);
            if constexpr (2 * p + NQ0 < 2 * NPQ) ldsm_x4_t_i<OFF_WQ + (2 * p + NQ0) * 2048>(rq[(2 * p) % NQ0], wqa);
          }
          mma16816h(k0, w[2 * p], bb[0], bb[1]);
          if constexpr (p < NPQ) {
            mma16816h(q1, rq[(2 * p + 1) % NQ0], bb[2], bb[3]);
            if constexpr (2 * p + 1 + NQ0 < 2 * NPQ) ldsm_x4_t_i<OFF_WQ + (2 * p + 1 + NQ0) * 2048>(rq[(2 * p + 1) % NQ0], wqa);
          }
          mma16816h(k1, w[2 * p + 1], bb[2], bb[3]);
          if constexpr (NVE > 0 && t + NB0 == VET) bar_arrive(B_E, 256);
          if constexpr (t + NB0 < 20) ldsm_x4_i<OFF_MEM + pair_of(t + NB0) * 512>(bb, mema);
          if constexpr (t < 20 - NB0 && (t % BBS) == BBS - 1) bbfence<t + 1>(mema);
        });
        const float sq = sin_ * iq, sk = sin_ * iw;
        stsm_x4_t_i<0>(sta, pack_bf16((q0[0] + q1[0]) * sq, (q0[1] + q1[1]) * sq), pack_bf16((q0[2] + q1[2]) * sq, (q0[3] + q1[3]) * sq),
                       pack_bf16((k0[0] + k1[0]) * sk, (k0[1] + k1[1]) * sk), pack_bf16((k0[2] + k1[2]) * sk, (k0[3] + k1[3]) * sk));
        bar_sync(B_QK, 384);
        TS(2);
        {
          if (wi == 3) {
            const uint32_t xr = sb + ((l16 & 511) >> 2), ka = l16 + (l16 & 384) * 4 + (s & 1) * (2 * KVB);
            uint32_t a0[4], a1[4], a2[4], a3[4], kb0[4], kb1[4];
            ldsm_x4_i<OFF_Q>(a0, l16); ldsm_x4_i<OFF_KV + 512>(kb0, ka); ldsm_x4_i<OFF_Q + 1024>(a2, l16); ldsm_x4_i<OFF_KV + 512 + 2560>(kb1, ka);
            ldsm_x4_i<OFF_Q + 512>(a1, l16);
            bar_arrive(B_A, 288);
            ldsm_x4_i<OFF_Q + 1536>(a3, l16);
            float sa[4] = {0, 0, 0, 0}, sc2[4] = {0, 0, 0, 0};
            mma16816(sa, a0[0], a0[1], a0[2], a0[3], kb0[0], kb0[1]);
            mma16816(sc2, a2[0], a2[1], a2[2], a2[3], kb1[0], kb1[1]);
            mma16816(sa, a1[0], a1[1], a1[2], a1[3], kb0[2], kb0[3]);
            mma16816(sc2, a3[0], a3[1], a3[2], a3[3], kb1[2], kb1[3]);
            const float x0 = (sa[0] + sa[2]) + (sc2[0] + sc2[2]), x1 = (sa[1] + sa[3]) + (sc2[1] + sc2[3]);
            const uint32_t xp = pack_bf16(x0, x1);
            st_async_b32_i<OFF_SR + 1024 + 128>(xr + d1, xp, sb + MB_S + d1);
            st_async_b32_i<OFF_SR + 1024>(xr + d2, xp, sb + MB_S + d2);
            stsm_x2(l16 + OFF_S + 1024, __float_as_uint(x0), __float_as_uint(x1));
          } else if (wi == 0) {
            const uint4 si = lds128_i<SC_IN>(sb + 16 * (s & 1));
            const int em = (int)(si.y >> 10) - 14 + (int)(si.x >> 23) - 127;
            const uint32_t osc = __float_as_uint(exp2i(max(min((int)si.z - max(em, 1), 100), -100)));
            sts32(l16 + OFF_LT + 12, osc); sts64_i<SC_IN>(sb + 16 * ((s + 1) & 1), 0x7f000000u - osc, 0u);
          }
          bar_sync(B_SL, 256);
        }
      } else {
        float v0[4] = {0, 0, 0, 0}, v1[4] = {0, 0, 0, 0}, q0[4] = {0, 0, 0, 0}, q1[4] = {0, 0, 0, 0};
        uint32_t b[NQ1 / 2][4];
        static_for<0, NQ1 / 2>([&](auto T) { ldsm_x4_i<OFF_MEM + (NPQ + T.value) * 512>(b[T.value], mema); });
        static_for<0, NQ1 / 2>([&](auto T) {
          constexpr int t = T.value, p = NPQ + t;
          uint32_t (&bb)[4] = b[t];
          mma16816h(q0, rq[2 * t], bb[0], bb[1]);
          mma16816h(q1, rq[2 * t + 1], bb[2], bb[3]);
          mma16816h(v0, w[2 * p], bb[0], bb[1]);
          mma16816h(v1, w[2 * p + 1], bb[2], bb[3]);
        });
        const float sq = sin_ * iq, sv = sin_ * iw;
        stsm_x2_t_i<0>(sta, pack_bf16((q0[0] + q1[0]) * sq, (q0[1] + q1[1]) * sq), pack_bf16((q0[2] + q1[2]) * sq, (q0[3] + q1[3]) * sq));
        TS(2);
        bar_arrive(B_QK, 384);
        float v2[4] = {0, 0, 0, 0}, v3[4] = {0, 0, 0, 0};
        auto vpair = [&](auto P, uint32_t (&bb)[4]) {
          constexpr int p = P.value;
          if constexpr (p & 1) { mma16816h(v0, w[2 * p], bb[0], bb[1]); mma16816h(v1, w[2 * p + 1], bb[2], bb[3]); }
          else { mma16816h(v2, w[2 * p], bb[0], bb[1]); mma16816h(v3, w[2 * p + 1], bb[2], bb[3]); }
        };
        if constexpr (NVE > 0) {
          uint32_t e[NVE ? NVE : 1][4];
          bar_sync(B_E, 256);
          static_for<0, NVE>([&](auto T) { ldsm_x4_i<OFF_MEM + T.value * 512>(e[T.value], mema); });
          static_for<0, NVE>([&](auto T) { vpair(T, e[T.value]); });
        }
        bar_sync(B_A, 288);
        uint32_t c[4][4];
        static_for<NVE, NVE + 4>([&](auto T) { ldsm_x4_i<OFF_MEM + T.value * 512>(c[T.value & 3], mema); });
        static_for<NVE, NPQ>([&](auto T) {
          constexpr int p = T.value;
          vpair(T, c[p & 3]);
          if constexpr (p + 4 < NPQ) ldsm_x4_i<OFF_MEM + (p + 4) * 512>(c[p & 3], mema);
        });
        stsm_x2_t_i<OFF_KV + KVB + 512>(l16 + (l16 & 128) * 4 + (wi * 1280 + (s & 1) * (2 * KVB)), pack_bf16(((v0[0] + v1[0]) + (v2[0] + v3[0])) * sv, ((v0[1] + v1[1]) + (v2[1] + v3[1])) * sv),
                            pack_bf16(((v0[2] + v1[2]) + (v2[2] + v3[2])) * sv, ((v0[3] + v1[3]) + (v2[3] + v3[3])) * sv));
        bar_arrive(B_V, 256);
      }
      TS(3);
      {
        uint32_t t1[12][4], t2[12][4];
        const uint32_t o16 = l16;
        wo1 = l16 + (OFF_WO + warp * 896);
        wo2 = sb + OFF_WO + warp * 896 + ((l16 & 128) ? 768 + ((l16 & 256) >> 2) + (l16 & 16) + ((l16 & 64) >> 1) : 512 + ((l16 & 256) >> 1) + (l16 & 112));
        auto ldw = [&](auto K) { if constexpr (K.value < 12 - NPM) { ldsm_x4_i<K.value * WOK>(t1[K.value], wo1); ldsm_x4_i<K.value * WOK>(t2[K.value], wo2); } };
        constexpr int NR_ = NRT - NPM;
        constexpr int PB = (hf ? PB1 : PB0) < NR_ ? (hf ? PB1 : PB0) : NR_, PA = (hf ? PA1 : PA0) < PB ? (hf ? PA1 : PA0) : PB;
        static_for<0, PA>(ldw);
        mbar_spin(sb + MB_X, (s + 1) & 1);
        if constexpr (PB > PA) {
          constexpr int PM = PA + PM1 < PB ? PA + PM1 : PB;
          mbar_spin(sb + MB_S, s & 1);
          const uint32_t t0 = clk_v();
          if constexpr (PM > PA) { while (clk_v() - t0 < GD1) {} static_for<PA, PM>(ldw); }
          if constexpr (PB > PM) { while (clk_v() - t0 < GD2) {} static_for<PM, PB>(ldw); }
        }
        float c0[4] = {0, 0, 0, 0}, c1[4] = {0, 0, 0, 0}, e0[4] = {0, 0, 0, 0}, e1[4] = {0, 0, 0, 0};
        uint32_t ob[6][4];
        auto kstep = [&](auto K) {
          constexpr int k = K.value;
          uint32_t (&bb)[4] = ob[k >> 1];
          uint32_t (&x)[4] = k < 12 - NPM ? t1[k] : u1[k < 12 - NPM ? 0 : k - (12 - NPM)];
          uint32_t (&y)[4] = k < 12 - NPM ? t2[k] : u2[k < 12 - NPM ? 0 : k - (12 - NPM)];
          if constexpr (k & 1) { mma16816(c1, x[0], x[1], x[2], x[3], bb[2], bb[3]); mma16816(e1, y[0], y[1], y[2], y[3], bb[2], bb[3]); }
          else { mma16816(c0, x[0], x[1], x[2], x[3], bb[0], bb[1]); mma16816(e0, y[0], y[1], y[2], y[3], bb[0], bb[1]); }
          if constexpr (k >= NRF) ldw(IC<k + NR_ - NRF>{});
        };
        auto ldo = [&](auto P) { ldsm_x4_i<OFF_O + P.value * 512>(ob[P.value], o16); };
        TS(4);
        bar_sync(B_O, 384);
        ldo(IC<0>{}); ldo(IC<1>{});
        SFENCE(o16);
        static_for<PB, NR_>(ldw);
        static_for<0, 4>(kstep);
        TS(5);
        mbar_spin(sb + MB_O, s & 1);
        TS(6);
        ldo(IC<2>{}); ldo(IC<NPM >= 2 ? 5 : 3>{});
        if (WOF) SFENCE(o16);
        kstep(IC<4>{});
        if constexpr (NPM < 2) { kstep(IC<5>{}); ldo(IC<4>{}); kstep(IC<6>{}); kstep(IC<7>{}); ldo(IC<5>{}); static_for<8, 12>(kstep); }
        else if constexpr (NPM >= 4) { kstep(IC<10>{}); kstep(IC<11>{}); ldo(IC<4>{}); kstep(IC<5>{}); ldo(IC<3>{}); kstep(IC<8>{}); kstep(IC<9>{}); kstep(IC<6>{}); kstep(IC<7>{}); }
        else { kstep(IC<5>{}); ldo(IC<3>{}); kstep(IC<11>{}); kstep(IC<10>{}); ldo(IC<4>{}); kstep(IC<6>{}); kstep(IC<7>{}); if constexpr (NPM == 3) { kstep(IC<9>{}); kstep(IC<8>{}); } else { kstep(IC<8>{}); kstep(IC<9>{}); } }
        l16 = fresh(l16);
        const int ln = (l16 >> 4) & 31;
        if constexpr (CEARLY && hf) { SFENCE2(o16, __float_as_uint(e1[0])); bar_arrive(B_G, 256); }
        unsigned char* gr = arena + (AR_ACC + acc_lane(bi, ln) + acc_voff(bv) + acc_step(s));
        const bool cnt = (ln & 1) || !t28;
        wqa = wq_addr(l16);
        SFENCE(o16);
        static_for<0, PQE>([&](auto K) { ldsm_x4_t_i<OFF_WQ + K.value * 2048>(rq[K.value], wqa); });
        const uint32_t y0 = movm_t(pack_f16(c0[0] + c1[0], c0[1] + c1[1])), y1 = movm_t(pack_f16(c0[2] + c1[2], c0[3] + c1[3]));
        const uint32_t y2 = movm_t(pack_f16(e0[0] + e1[0], e0[1] + e1[1])), y3 = movm_t(pack_f16(e0[2] + e1[2], e0[3] + e1[3]));
        asm volatile("red.relaxed.gpu.global.add.noftz.v4.f16x2 [%0], {%1,%2,%3,%4};" :: "l"(gr), "r"(y0), "r"(y1), "r"(y2), "r"(cnt ? 0x3c00u : y3) : "memory");
        bar_arrive(B_RED, 384);
        if constexpr (CEARLY && !hf) { bar_arrive(B_C, 256); bar_sync(B_G, 256); }
        else bar_sync(B_C, 256);
        TS(7);
      }
#if CHAIN_TIMING
      x_gemm((s + 1) & 1, tsb);
#else
      x_gemm((s + 1) & 1, 0);
#endif
      TS(8);
    }
    };
    if (hf == 0) run(IC<0>{}); else run(IC<1>{});
    {
      const uint32_t l16 = sb + (threadIdx.x & 31) * 16, mema = l16 ^ ((l16 >> 2) & 96);
      float c0[4] = {0, 0, 0, 0}, c1[4] = {0, 0, 0, 0}, c2[4] = {0, 0, 0, 0}, c3[4] = {0, 0, 0, 0};
      bar_sync(hf ? B_MEM1 : B_MEM0, 256);
      const float sc = __uint_as_float(lds32_i<SC_IN + 16>(sb)) * iw;
      static_for<0, 10>([&](auto T) {
        constexpr int p = 2 * T.value;
        uint32_t b0[4], b1[4];
        ldsm_x4_i<OFF_MEM + p * 512>(b0, mema); ldsm_x4_i<OFF_MEM + p * 512 + 512>(b1, mema);
        mma16816h(c0, w[2 * p], b0[0], b0[1]); mma16816h(c1, w[2 * p + 1], b0[2], b0[3]);
        mma16816h(c2, w[2 * p + 2], b1[0], b1[1]); mma16816h(c3, w[2 * p + 3], b1[2], b1[3]);
      });
      stsm_x2_t_i<OFF_KV + 2 * KVB + 512>(l16 + (l16 & 128) * 4 + wi * 1280 + hf * KVB, pack_bf16(((c0[0] + c1[0]) + (c2[0] + c3[0])) * sc, ((c0[1] + c1[1]) + (c2[1] + c3[1])) * sc),
                                          pack_bf16(((c0[2] + c1[2]) + (c2[2] + c3[2])) * sc, ((c0[3] + c1[3]) + (c2[3] + c3[3])) * sc));
      fence_proxy_async();
    }
    bar_arrive(B_RED, 384);
#if CHAIN_TIMING
    for (int i = tid; i < 288; i += 256) a.dbg[cta * 288 + i] = lds32_i<OFF_BAR + 128>(sb + i * 4);
#endif
    asm volatile("barrier.cluster.arrive.relaxed.aligned; barrier.cluster.wait.aligned;" ::: "memory");
  }
}
struct PrepArgs { const bf16 *wqkv, *wphi, *wo; unsigned char *wb, *wot; };
__device__ __forceinline__ void prep_body(const int cta, const PrepArgs& pa) {
  const int tid = threadIdx.x, lane = tid & 31, warp = tid >> 5, g = lane >> 2, q = lane & 3;
  const int pair = cta >> 1, which = cta & 1;
  uint32_t bfr[2][3][3];
#pragma unroll
  for (int hh = 0; hh < 2; hh++)
#pragma unroll
    for (int t = 0; t < 3; t++) {
      const unsigned short* ph = (const unsigned short*)pa.wphi + (2 * pair + hh) * 400 + (t < 2 ? 8 * t + g : 16 + (g >> 1)) + 2 * q * 20;
#pragma unroll
      for (int r = 0; r < 3; r++) {
        const int o = (r < 2 || q < 2) ? r * 160 : 0;
        const uint32_t v = (uint32_t)__ldg(ph + o) | ((uint32_t)__ldg(ph + o + 20) << 16);
        bfr[hh][t][r] = ((t < 2 || (g & 1) == hh) && (r < 2 || q < 2)) ? v : 0u;
      }
    }
  const int gt = cta * 256 + tid;
#pragma unroll 1
  for (int i = 0; i < 5; i++) {
    uint32_t af[2][6];
#pragma unroll
    for (int hh = 0; hh < 2; hh++) {
      const uint32_t* r0 = (const uint32_t*)(pa.wqkv + (size_t)((warp * 5 + i) * 16 + g) * 1920 + which * 640 + (2 * pair + hh) * 20) + q;
      af[hh][0] = __ldg(r0); af[hh][1] = __ldg(r0 + 7680); af[hh][2] = __ldg(r0 + 4); af[hh][3] = __ldg(r0 + 7684);
      af[hh][4] = __ldg(r0 + 8); af[hh][5] = __ldg(r0 + 7688);
    }
    const int iv = i * 4096 + (gt >> 1), k = (iv & 7) + (iv >> 8) * 8, h = (iv >> 3) & 31;
    const uint2* src = (const uint2*)(pa.wqkv + (size_t)k * 1920 + 1280 + h * 20) + (gt & 1) * 2;
    const uint2 a = __ldg(src), b = __ldg(src + 1), e = __ldg(src + 2);
    uint4 wv[2]; uint32_t wd[2];
#pragma unroll
    for (int n = 0; n < 2; n++) {
      const int iw = min((2 * i + n) * 5120 + gt, 640 * 80 - 1), r = iw & 7, c = (iw >> 3) % 80, kg = iw / 640, c5 = kg % 5;
      const int row = (kg / 5) * 40 + (c5 < 2 ? 8 * c5 + r : (c5 == 2 ? 16 + (r & 3) + (r >> 2) * 20 : 20 + 8 * (c5 - 3) + r));
      wv[n] = __ldg((const uint4*)(pa.wo + (size_t)row * cfg::DM + c * 8));
      wd[n] = (((c / 10) * 80 + kg) * 10 + c % 10) * 128 + r * 16;
    }
    uint4* dv = (uint4*)(pa.wb + ((size_t)((h >> 2) * 80 + (k >> 3)) * 32 + 20 + 3 * (h & 3)) * 128 + (k & 7) * 16);
    dv[(gt & 1) * 8] = make_uint4(a.x, a.y, b.x, b.y);
    if (gt & 1) dv[16] = (h & 1) ? make_uint4(0, 0, e.x, e.y) : make_uint4(e.x, e.y, 0, 0);
    if (gt < 5120) { *(uint4*)(pa.wot + wd[0]) = wv[0]; *(uint4*)(pa.wot + wd[1]) = wv[1]; }
    uint32_t* dst = (uint32_t*)(pa.wb + ((size_t)((pair >> 1) * 80 + (warp * 5 + i) * 2) * 32 + which * 10 + (pair & 1) * 5) * 128) + lane;
#pragma unroll
    for (int t = 0; t < 5; t++) {
      float d[4] = {0, 0, 0, 0};
#pragma unroll
      for (int hh = 0; hh < 2; hh++)
        if (t == 2 || (t > 2) == (hh == 1)) {
          const int tt = t < 3 ? t : t - 3;
          mma16816(d, af[hh][0], af[hh][1], af[hh][2], af[hh][3], bfr[hh][tt][0], bfr[hh][tt][1]);
          mma1688(d, q < 2 ? af[hh][4] : 0u, q < 2 ? af[hh][5] : 0u, bfr[hh][tt][2]);
        }
      dst[t * 32] = pack_bf16(d[0], d[1]); dst[1024 + t * 32] = pack_bf16(d[2], d[3]);
    }
  }
}

__global__ void __launch_bounds__(256, 4) ln_kernel(const bf16* __restrict__ xin, bf16* __restrict__ xn, uint2* __restrict__ xh, uint4* __restrict__ z0, int n0,
                                                    uint4* __restrict__ z1, int n1, const bf16* pfa, const bf16* pfb, int npf, int tl) {
  asm volatile("griddepcontrol.wait;" ::: "memory");
  asm volatile("griddepcontrol.launch_dependents;" ::: "memory");
  TL_BEGIN(tl);
  const int warp = threadIdx.x >> 5, lane = threadIdx.x & 31;
  const int row = blockIdx.x * 8 + warp;
  uint2 xw[1][5];
#pragma unroll
  for (int i = 0; i < 5; i++) xw[0][i] = *(const uint2*)(xin + (size_t)row * cfg::DM + i * 128 + lane * 4);
  for (int i = blockIdx.x * 256 + threadIdx.x; i < n0; i += 256 * 256) z0[i] = make_uint4(0, 0, 0, 0);
  for (int i = blockIdx.x * 256 + threadIdx.x; i < n1; i += 256 * 256) z1[i] = make_uint4(0, 0, 0, 0);
  if (npf && xw[0][4].y != 0x7fc17fc1u) {
    for (int i = 0; i < npf; i++) {
      const uint32_t l = (uint32_t)i * 32768u + (blockIdx.x * 256 + threadIdx.x) / 2;
      if (l < cfg::DM * cfg::HD / 64) asm volatile("prefetch.global.L2 [%0];" :: "l"(((threadIdx.x & 1) ? pfa : pfb) + (size_t)l * 64) : "memory");
    }
  }
  ln_rows<1>(xw, row, lane, xn, xh);
  TL_END(tl);
}
struct Pipe { uint32_t stage, phase; };
template <int NS> __device__ __forceinline__ void pipe_adv(Pipe& p) { if (++p.stage == NS) { p.stage = 0; p.phase ^= 1; } }
constexpr uint32_t SWZ128 = 1;
__device__ __forceinline__ uint64_t desc_kmajor(uint32_t a) { return make_desc(a, 16, 1024, SWZ128); }
__device__ __forceinline__ uint64_t desc_mnmajor(uint32_t a) { return make_desc(a, 8192, 1024, SWZ128); }
__device__ __forceinline__ void wait_ge(const void* p, uint32_t target, uint32_t ns = 32) {
  int spin = 0;
  while (ld_acquire_u32(p) < target) { __nanosleep(ns); if (++spin > (1 << 21)) break; }
}
__device__ __forceinline__ void bulk_g2s_hint(uint32_t dst, const void* src, uint32_t bytes, uint32_t mb, uint64_t pol) {
  asm volatile("cp.async.bulk.shared::cluster.global.mbarrier::complete_tx::bytes.L2::cache_hint [%0], [%1], %2, [%3], %4;"
               :: "r"(dst), "l"(src), "r"(bytes), "r"(mb), "l"(pol) : "memory");
}
#ifndef PF_WB
#define PF_WB 2
#endif
#ifndef PF_XN
#define PF_XN 1
#endif
#ifndef STAG
#define STAG 1
#endif
#ifndef EF_KV
#define EF_KV 1
#endif
#ifndef EF_O
#define EF_O 1
#endif
__device__ __forceinline__ void fence_proxy_async_global() { asm volatile("fence.proxy.async.global;" ::: "memory"); }

namespace tr {
constexpr int NS = 4, STQ = 16384 + 24576, STO = 16384 + 40960;
constexpr int SEGB = 15360;
constexpr int OFF_K = NS * STQ;
constexpr int OFF_BAR = NS * STO;
constexpr int SMEM = OFF_BAR + 256;
static_assert(OFF_K + 4 * SEGB <= OFF_BAR && SMEM <= 232448, "smem");
enum { T_QA = 0, T_Q, T_A, T_OB, T_OS, T_L, T_END, T_P };
constexpr uint32_t C_QA = AR_CNT, C_O = AR_CNT + 64, C_Q = AR_CNT + 128, C_P = AR_CNT + 192;
constexpr int MAXITEMS = 1200;
struct Sched {
  uint8_t ks[16];
  uint8_t wide[16];
  uint8_t lrows[16];
  uint32_t n;
  uint16_t item[MAXITEMS];
};
struct Args {
  const unsigned char *kg, *vg;
  unsigned char* o;
  uint4* qs;
  unsigned char* part;
  const bf16 *xin, *xq;
  bf16 *xout, *xn;
  unsigned char* arena;
  const unsigned* go;
  int tl;
  uint32_t nap, nap2;
  int pfprep;
};
}

template <int N0, int N1>
__device__ __forceinline__ void tr_mainloop(float (&a0)[N0 / 2], float (&a1)[N1 ? N1 / 2 : 1], Pipe& p, uint32_t sb, uint32_t full, uint32_t empty, int nkb, int wg) {
  using namespace tr;
  constexpr uint32_t ST = N1 ? STO : STQ;
  uint32_t prev = 0;
#pragma unroll
  for (int i = 0; i < N0 / 2; i++) a0[i] = 0.f;
  if constexpr (N1 > 0) {
#pragma unroll
    for (int i = 0; i < N1 / 2; i++) a1[i] = 0.f;
  }
#pragma unroll 1
  for (int kb = 0; kb < nkb; kb++) {
    mbar_wait(full + 8 * p.stage, p.phase);
    const uint32_t st = sb + p.stage * ST;
    wgmma_fence();
#pragma unroll
    for (int kk = 0; kk < 4; kk++) {
      const uint64_t da = desc_kmajor(st + wg * 8192 + kk * 32);
      if constexpr (N0 == 192) wgmma_n192<0, 1>(a0, da, desc_mnmajor(st + 16384 + kk * 2048), (kb | kk) != 0);
      else wgmma_n128<0, 1>(a0, da, desc_mnmajor(st + 16384 + kk * 2048), (kb | kk) != 0);
      if constexpr (N1 > 0) wgmma_n128<0, 1>(a1, da, desc_mnmajor(st + 16384 + 24576 + kk * 2048), (kb | kk) != 0);
    }
    wgmma_commit();
    if (kb > 0) { wgmma_wait<1>(); mbar_arrive_if((threadIdx.x & 127) == 0, empty + 8 * prev); }
    prev = p.stage;
    pipe_adv<NS>(p);
  }
  wgmma_wait<0>();
  mbar_arrive_if((threadIdx.x & 127) == 0, empty + 8 * prev);
}
template <int N> __device__ __forceinline__ void stage_tiles(const float (&o)[N / 2], uint32_t base, int wi, int lane) {
  const uint32_t ra = base + (wi * 16 + (lane & 7) + 8 * ((lane >> 3) & 1)) * 128;
#pragma unroll
  for (int v = 0; v < N / 8; v += 2)
    stsm_x4(ra + (v >> 3) * 8192 + ((((v & 7) + (lane >> 4)) ^ (lane & 7)) << 4), pack_bf16(o[4 * v], o[4 * v + 1]), pack_bf16(o[4 * v + 2], o[4 * v + 3]),
            pack_bf16(o[4 * v + 4], o[4 * v + 5]), pack_bf16(o[4 * v + 6], o[4 * v + 7]));
}
__global__ void __launch_bounds__(384, 1) trail_kernel(const __grid_constant__ CUtensorMap tmX, const __grid_constant__ CUtensorMap tmQ,
                                                       const __grid_constant__ CUtensorMap tmWo5, const __grid_constant__ CUtensorMap tmWo2,
                                                       const __grid_constant__ CUtensorMap tmP, const __grid_constant__ tr::Sched sc,
                                                       const __grid_constant__ tr::Args a, const __grid_constant__ PrepArgs pa) {
  using namespace tr;
  [[maybe_unused]] const int tl = a.tl;
  TL_BEGIN(tl);
  extern __shared__ __align__(1024) unsigned char smem_raw[];
  const uint32_t sb = smem_u32(smem_raw);
  const int warp = __shfl_sync(0xffffffffu, (int)threadIdx.x >> 5, 0), lane = threadIdx.x & 31;
  unsigned char* const arena = a.arena;
  const uint32_t full = sb + OFF_BAR, empty = full + 8 * NS, barK = empty + 8 * NS, barKfree = barK + 16, staged = barKfree + 16;
  const uint32_t kvrdy = staged + 32, mfull = kvrdy + 8, mempty = mfull + 16, mbox = mempty + 16;
  uint32_t go = 0;
  if (threadIdx.x == 256) go = ld_acquire_u32(a.go);
  if (threadIdx.x == 0) {
    for (int i = 0; i < NS; i++) { mbar_init(full + 8 * i, 1); mbar_init(empty + 8 * i, 2); }
    for (int i = 0; i < 2; i++) {
      mbar_init(barK + 8 * i, 1); mbar_init(barKfree + 8 * i, 1); mbar_init(staged + 16 * i, 4); mbar_init(staged + 16 * i + 8, 4);
      mbar_init(mfull + 8 * i, 1); mbar_init(mempty + 8 * i, 11);
    }
    mbar_init(kvrdy, 1);
    asm volatile("fence.mbarrier_init.release.cluster;" ::: "memory");
  }
  __syncthreads();
  Pipe mp{0, 0};
  auto next_item = [&]() -> uint32_t {
    uint32_t it;
    mbar_wait(mfull + 8 * mp.stage, mp.phase);
    asm volatile("ld.shared.u32 %0, [%1];" : "=r"(it) : "r"(mbox + 4 * mp.stage) : "memory");
    return it;
  };
  if (warp >= 8) {
    asm volatile("setmaxnreg.dec.sync.aligned.u32 40;");
    if (warp == 8) { go = __shfl_sync(0xffffffffu, go, 0); if (elect_one()) {
      Pipe p{0, 1};
      mp.phase = 1;
      uint32_t kph = 1, rph = 0, wide = 0, qdone = 0;
      prefetch_tmap(&tmX); prefetch_tmap(&tmQ); prefetch_tmap(&tmWo5); prefetch_tmap(&tmWo2); prefetch_tmap(&tmP);
      const uint64_t ef = policy_evict_first();
      auto ld_kv = [&](uint32_t d, const void* s, uint32_t n, uint32_t mb) { if (EF_KV) bulk_g2s_hint(d, s, n, mb, ef); else bulk_g2s(d, s, n, mb); };
      auto ld_o = [&](uint32_t d, const void* s, uint32_t n, uint32_t mb) { if (EF_O) bulk_g2s_hint(d, s, n, mb, ef); else bulk_g2s(d, s, n, mb); };
      auto stage = [&](uint32_t bytes) -> uint32_t {
        mbar_wait(empty + 8 * p.stage, p.phase);
        mbar_expect_tx(full + 8 * p.stage, bytes);
        return sb + p.stage * (wide ? STO : STQ);
      };
      auto fetch = [&]() -> uint32_t { uint32_t v; asm volatile("atom.relaxed.gpu.global.add.u32 %0, [%1], 1;" : "=r"(v) : "l"(arena + AR_QUEUE) : "memory"); return v; };
      if (!go) wait_ge(a.go, 1, 200);
      fence_proxy_async_global();
      uint32_t next = fetch();
      while (true) {
        const uint32_t item = next;
        const uint32_t code = sc.item[min(item, sc.n)];
        const int type = (code >> 11) & 7, m = (code >> 7) & 15, k = code & 127;
        const bool late = code >> 14;
        auto done_wait = [&]() { mbar_wait(mempty + 8 * (mp.stage ^ 1), mp.stage ? mp.phase ^ 1 : mp.phase); };
        if (type == T_A && !((qdone >> m) & 1)) { wait_ge(arena + C_Q + m * 4, 64); qdone |= 1u << m; }
        if (type == T_OB && !wide) for (uint32_t i = 0; i < NS; i++) mbar_wait(empty + 8 * i, i >= p.stage ? p.phase : p.phase ^ 1);
        wide = type == T_OB;
        mbar_wait(mempty + 8 * mp.stage, mp.phase);
        asm volatile("st.shared.u32 [%0], %1;" :: "r"(mbox + 4 * mp.stage), "r"((p.stage << 24) | (type << 16) | (m << 8) | (k & 255)) : "memory");
        mbar_arrive(mfull + 8 * mp.stage);
        pipe_adv<2>(mp);
        if (type == T_END) break;
        if (type == T_P) { done_wait(); next = fetch(); continue; }
        if (type == T_L) {
          const int nr = sc.lrows[m], np = sc.ks[m];
          prefetch_l2(a.xin + (size_t)(m * 128 + k * 8 * nr) * cfg::DM, nr * 10240);
          wait_ge(arena + C_O + m * 4, np * (sc.wide[m] ? 4 : 10), m < 13 ? a.nap : 32);
          fence_proxy_async_global();
#pragma unroll 1
          for (int r = 0; r < nr; r++) {
            const int rg = m * 16 + k * nr + r;
#pragma unroll 1
            for (int q0 = 0; q0 <= np; q0 += 4) {
              const int n = min(4, np + 1 - q0);
              const uint32_t st = stage(n * 10240), fb = full + 8 * p.stage;
#pragma unroll 1
              for (int q = q0; q < q0 + n; q++) {
                if (q == 0) bulk_g2s(st, a.xin + (size_t)rg * 8 * cfg::DM, 10240, fb);
                else tma_load_3d(st + (q - q0) * 10240, &tmP, 0, rg & 7, ((q - 1) * 32 + (rg >> 3)) * 10, fb);
              }
              pipe_adv<NS>(p);
            }
          }
          if (late) done_wait();
          next = fetch(); continue;
        }
        if (type <= T_A) {
          if (type != T_A)
#pragma unroll 1
            for (int kb = 0; kb < 10; kb++) {
              const uint32_t st = stage(STQ), fb = full + 8 * p.stage;
              tma_load_2d(st, &tmX, kb * 64, m * 128, fb);
              tma_load_3d(st + 16384, &tmQ, 0, kb * 64, k * 3, fb);
              pipe_adv<NS>(p);
              if (type == T_Q && kb == 8) next = fetch();
            }
          if (type != T_Q) {
            const size_t blk = ((size_t)m * 4 * 96 + k * 3) * 5120;
            kph ^= 1;
            mbar_wait(kvrdy, rph); rph ^= 1;
            if (!late) next = fetch();
            fence_proxy_async_global();
#pragma unroll 1
            for (int w = type == T_A ? 0 : 2; w < 4; w++) {
              const uint32_t st = stage(2 * SEGB), fb = full + 8 * p.stage;
              for (int sg = 0; sg < 2; sg++) ld_kv(st + sg * SEGB, (w < 2 ? a.kg : a.vg) + blk + (size_t)(2 * (w & 1) + sg) * (96 * 5120), SEGB, fb);
              pipe_adv<NS>(p);
            }
            if (late) { done_wait(); next = fetch(); }
          }
        } else {
          const int nn = wide ? 2 : 5, nb = wide ? 5 : 2, nt = k % nn, nkb = 96 / sc.ks[m], k0 = (k / nn) * nkb;
          const Pipe p0 = p;
          for (int kb = 0; kb < nkb; kb++) {
            if (wide && kb < NS && p.stage >= 2) { mbar_wait(barKfree, kph); mbar_wait(barKfree + 8, kph); }
            const uint32_t st = stage(16384 + nb * 8192), fb = full + 8 * p.stage;
            tma_load_3d(st + 16384, wide ? &tmWo5 : &tmWo2, 0, (k0 + kb) * 64, nt * nb, fb);
            if (kb >= NS) ld_o(st, a.o + ((size_t)m * 96 + k0 + kb) * 16384, 16384, fb);
            pipe_adv<NS>(p);
            if (kb == NS - 1 || (kb == nkb - 1 && nkb < NS)) {
              wait_ge(arena + C_QA + m * 4, 64, m < 14 ? a.nap : 32);
              fence_proxy_async_global();
              Pipe q = p0;
#pragma unroll 1
              for (int i = 0; i <= kb; i++) { ld_o(sb + q.stage * (wide ? STO : STQ), a.o + ((size_t)m * 96 + k0 + i) * 16384, 16384, full + 8 * q.stage); pipe_adv<NS>(q); }
            }
          }
          if (!late) next = fetch();
          for (int w = wide ? -(int)((2 - p.stage) & 3) : 0; w < 2; w++) { mbar_wait(empty + 8 * p.stage, p.phase); mbar_arrive(full + 8 * p.stage); pipe_adv<NS>(p); }
          kph ^= wide;
          if (late) { done_wait(); next = fetch(); }
        }
      }
    } } else if (warp < 11) { if (elect_one()) {
      const int w = warp - 9;
      uint32_t sph = 0;
      [[maybe_unused]] int nlog = 0;
#ifdef TIMELINE
      if (w == 0) { unsigned long long* lg = g_log + (((tl >= 12) * 132 + blockIdx.x) * 64 + nlog++) * 2; lg[0] = T_END << 16; lg[1] = gtime(); lg[2] = ~0ull; }
#endif
      while (true) {
        const uint32_t it = next_item();
        const int type = (it >> 16) & 255, m = (it >> 8) & 255, k = it & 255;
        const uint32_t slot = mp.stage;
        pipe_adv<2>(mp);
        if (type == T_END) break;
        mbar_wait(staged + 16 * w + 8 * slot, (sph >> slot) & 1); sph ^= 1u << slot;
        mbar_arrive(mempty + 8 * slot);
#ifdef TIMELINE
        if (w == 0 && nlog < 63) { unsigned long long* lg = g_log + (((tl >= 12) * 132 + blockIdx.x) * 64 + nlog++) * 2; lg[0] = (type << 16) | (m << 8) | k; lg[1] = gtime(); lg[2] = ~0ull; }
#endif
        if (type == T_L) continue;
        if (type == T_QA || type == T_A) {
          for (int jj = 0; jj < 3; jj++) bulk_s2g(a.o + ((size_t)m * 96 + k * 3 + jj) * 16384 + w * 8192, sb + OFF_K + w * 2 * SEGB + jj * 8192, 8192);
          bulk_commit();
          bulk_wait<0>();
          mbar_arrive(barKfree + 8 * w);
        } else if (type == T_OB || type == T_OS) {
          const bool wide = type == T_OB;
          const int nn = wide ? 2 : 5, nb = wide ? 5 : 2;
          const uint32_t own = wide ? 2 + w : ((it >> 24) + 96 / sc.ks[m] + w) % NS;
          bulk_s2g(a.part + ((size_t)((k / nn) * 32 + m * 2 + w) * 10 + (k % nn) * nb) * 8192, sb + own * (wide ? STO : STQ), nb * 8192);
          bulk_commit();
          bulk_wait<0>();
          mbar_arrive(empty + 8 * own);
          if (wide && w) { mbar_arrive(barKfree); mbar_arrive(barKfree + 8); }
        }
        red_release_inc(arena + (type == T_Q ? C_Q : (type <= T_A ? C_QA : (type == T_P ? C_P : C_O))) + m * 4);
      }
    } } else if (elect_one()) {
      const uint64_t ef = policy_evict_first();
      uint32_t kph = 1;
      if (PF_WB && blockIdx.x >= 52) { prefetch_l2(pa.wb + (blockIdx.x - 52) * 32768, 32768); prefetch_l2(pa.wot + (blockIdx.x - 52) * 10240, 10240); }
      if (PF_WB > 1 && blockIdx.x >= 52) { prefetch_l2(a.xn + (blockIdx.x - 52) * 8192, 16384); prefetch_l2(a.xout + (blockIdx.x - 52) * 8192, 16384); }
      while (true) {
        const uint32_t it = next_item();
        const int type = (it >> 16) & 255, m = (it >> 8) & 255, k = it & 255;
        const uint32_t slot = mp.stage;
        pipe_adv<2>(mp);
        if (type == T_END) break;
        if (a.pfprep && type == T_QA && m == 0) { prefetch_l2(pa.wqkv + k * 38400, 76800); prefetch_l2(pa.wo + k * 12800, 25600); }
        if (PF_XN && type == T_QA && m < 15) prefetch_l2(a.xq + ((m + 1) * 128 + k * 4) * cfg::DM, 5120);
        if (type == T_QA || type == T_A) {
          for (int spin = 0; spin < (1 << 21); spin++) {
            uint4 f;
            asm volatile("ld.acquire.gpu.global.v4.u32 {%0,%1,%2,%3}, [%4];" : "=r"(f.x), "=r"(f.y), "=r"(f.z), "=r"(f.w) : "l"(arena + prog_off(k, 0)) : "memory");
            if (min(min(f.x, f.y), f.z) >= (uint32_t)(4 * m + 4)) break;
            __nanosleep(m < 15 ? a.nap : a.nap2);
          }
          mbar_arrive(kvrdy);
          fence_proxy_async_global();
          const unsigned char* src = a.kg + ((size_t)m * 4 * 96 + k * 3) * 5120;
#pragma unroll 1
          for (int w = 0; w < 2; w++) {
            mbar_wait(barKfree + 8 * w, kph);
            if (type == T_A) { mbar_arrive(barK + 8 * w); continue; }
            mbar_expect_tx(barK + 8 * w, 2 * SEGB);
            for (int sg = 2 * w; sg < 2 * w + 2; sg++) { if (EF_KV) bulk_g2s_hint(sb + OFF_K + sg * SEGB, src + (size_t)sg * (96 * 5120), SEGB, barK + 8 * w, ef); else bulk_g2s(sb + OFF_K + sg * SEGB, src + (size_t)sg * (96 * 5120), SEGB, barK + 8 * w); }
          }
          kph ^= 1;
        } else if (type == T_OB) {
          mbar_wait(barKfree, kph); mbar_wait(barKfree + 8, kph);
          kph ^= 1;
        }
        mbar_arrive(mempty + 8 * slot);
      }
      if (blockIdx.x == gridDim.x - 1) asm volatile("griddepcontrol.wait;" ::: "memory");
    }
    return;
  }
  asm volatile("setmaxnreg.inc.sync.aligned.u32 232;");
  const int wg = warp >> 2, wi = warp & 3;
  const int g = lane >> 2, q4 = lane & 3;
  asm volatile("griddepcontrol.launch_dependents;" ::: "memory");
  Pipe p{0, 0};
  uint32_t kph = 0;
  auto own_slot = [&]() -> uint32_t {
    const uint32_t sA = p.stage, phA = p.phase; pipe_adv<NS>(p);
    const uint32_t sB = p.stage, phB = p.phase; pipe_adv<NS>(p);
    if (wi == 0) mbar_wait(full + 8 * (wg ? sA : sB), wg ? phA : phB);
    mbar_wait(full + 8 * (wg ? sB : sA), wg ? phB : phA);
    mbar_arrive_if((threadIdx.x & 127) == 0, empty + 8 * (wg ? sA : sB));
    return wg ? sB : sA;
  };
  while (true) {
    const uint32_t it = __shfl_sync(0xffffffffu, next_item(), 0);
    const int type = (it >> 16) & 255, m = (it >> 8) & 255, k = it & 255;
    mbar_arrive_if(lane == 0, mempty + 8 * mp.stage);
    const uint32_t done = staged + 16 * wg + 8 * mp.stage;
    pipe_adv<2>(mp);
    if (type == T_END) break;
    if (type == T_P) {
      prep_body(k, pa);
      __syncwarp();
      mbar_arrive_if(lane == 0, done);
      continue;
    }
    if (type == T_L) {
      const int nr = sc.lrows[m], np = sc.ks[m];
      const uint32_t po = (lane >> 4) * 1024 + warp * 128 + ((((lane >> 1) & 7) ^ warp) << 4) + (lane & 1) * 8;
#pragma unroll 1
      for (int r = 0; r < nr; r++) {
        uint2 xw[1][5]; float s[20];
#pragma unroll
        for (int i = 0; i < 20; i++) s[i] = 0.f;
#pragma unroll 1
        for (int q0 = 0; q0 <= np; q0 += 4) {
          const uint32_t st = sb + p.stage * STQ;
          mbar_wait(full + 8 * p.stage, p.phase);
          if (q0 == 0) static_for<0, 5>([&](auto I) { xw[0][I.value] = lds64_i<I.value * 256>(st + warp * 1280 + lane * 8); });
#pragma unroll 1
          for (int q = q0 ? 0 : 1; q < min(4, np + 1 - q0); q++)
            static_for<0, 5>([&](auto I) {
              constexpr int i = I.value;
              const uint2 t = lds64_i<i * 2048>(st + q * 10240 + po);
              s[4 * i] += bf_lo(t.x); s[4 * i + 1] += bf_hi(t.x); s[4 * i + 2] += bf_lo(t.y); s[4 * i + 3] += bf_hi(t.y);
            });
          bar_sync(3 + wg, 128);
          mbar_arrive_if((threadIdx.x & 127) == 0, empty + 8 * p.stage);
          pipe_adv<NS>(p);
        }
        const int row = (m * 16 + k * nr + r) * 8 + warp;
#pragma unroll
        for (int i = 0; i < 5; i++) {
          bf16r2(s[4 * i], s[4 * i + 1]); bf16r2(s[4 * i + 2], s[4 * i + 3]);
          xw[0][i] = make_uint2(pack_bf16(bf_lo(xw[0][i].x) + s[4 * i], bf_hi(xw[0][i].x) + s[4 * i + 1]), pack_bf16(bf_lo(xw[0][i].y) + s[4 * i + 2], bf_hi(xw[0][i].y) + s[4 * i + 3]));
          *(uint2*)(a.xout + (size_t)row * cfg::DM + i * 128 + lane * 4) = xw[0][i];
        }
        ln_rows<1>(xw, row, lane, a.xn, nullptr);
      }
      __syncwarp();
      mbar_arrive_if(lane == 0, done);
      continue;
    }
    if (type >= T_OB) {
      const int nkb = 96 / sc.ks[m];
      if (type == T_OB) {
        float a0[96], a1[64];
        tr_mainloop<192, 128>(a0, a1, p, sb, full, empty, nkb, wg);
        while (p.stage != 2) { if (wi == 0) mbar_wait(full + 8 * p.stage, p.phase); mbar_arrive_if((threadIdx.x & 127) == 0, empty + 8 * p.stage); pipe_adv<NS>(p); }
        const uint32_t st = sb + own_slot() * STO;
        stage_tiles<192>(a0, st, wi, lane); stage_tiles<128>(a1, st + 24576, wi, lane);
      } else {
        float a0[64], a1[1];
        tr_mainloop<128, 0>(a0, a1, p, sb, full, empty, nkb, wg);
        stage_tiles<128>(a0, sb + own_slot() * STQ, wi, lane);
      }
      fence_proxy_async();
      __syncwarp();
      mbar_arrive_if(lane == 0, done);
      continue;
    }
    uint32_t qf[12][4];
    uint4* qp = a.qs + ((size_t)((m & 7) * 32 + k) * 12) * 256 + threadIdx.x;
    if (type != T_A) {
      float acc[96], a1[1];
      tr_mainloop<192, 0>(acc, a1, p, sb, full, empty, 10, wg);
#pragma unroll
      for (int i = 0; i < 12; i++) {
        qf[i][0] = pack_bf16(acc[8 * i], acc[8 * i + 1]); qf[i][1] = pack_bf16(acc[8 * i + 2], acc[8 * i + 3]);
        qf[i][2] = pack_bf16(acc[8 * i + 4], acc[8 * i + 5]); qf[i][3] = pack_bf16(acc[8 * i + 6], acc[8 * i + 7]);
      }
      if (type == T_Q) {
#pragma unroll
        for (int i = 0; i < 12; i++) qp[i * 256] = make_uint4(qf[i][0], qf[i][1], qf[i][2], qf[i][3]);
        __syncwarp();
        mbar_arrive_if(lane == 0, done);
        continue;
      }
    } else {
#pragma unroll
      for (int i = 0; i < 12; i++) { const uint4 v = __ldcg(qp + i * 256); qf[i][0] = v.x; qf[i][1] = v.y; qf[i][2] = v.z; qf[i][3] = v.w; }
    }
    const uint32_t ost = sb + OFF_K + wg * 2 * SEGB;
    const bool second = wi >= 2;
    uint32_t pf[5][4];
    {
      float sa[20], sb2[20];
      uint32_t kbase = ost, kslot = 0;
      if (type == T_A) { kslot = own_slot(); kbase = sb + kslot * STQ; } else mbar_wait(barK + 8 * wg, kph);
      if (STAG && wg) bar_sync(1, 256);
      wgmma_fence();
#pragma unroll
      for (int i = 0; i < 12; i++) {
        wgmma_rs_n40<0>(sa, qf[i][0], qf[i][1], qf[i][2], qf[i][3], make_desc(kbase + i * 1280, 640, 128, 0), i != 0);
        wgmma_rs_n40<0>(sb2, qf[i][0], qf[i][1], qf[i][2], qf[i][3], make_desc(kbase + SEGB + i * 1280, 640, 128, 0), i != 0);
      }
      wgmma_commit();
      wgmma_wait<0>();
      if (STAG && !wg) bar_arrive(1, 256);
      mbar_arrive_if(type == T_A && (threadIdx.x & 127) == 0, empty + 8 * kslot);
      const float cs = 0.07216878364870322f * 1.4426950408889634f;
      const int r0 = 16 * (wi & 1) + g, r1 = r0 + 8;
      float m0 = -INFINITY, m1 = -INFINITY;
#pragma unroll
      for (int n = 0; n < 5; n++) {
#pragma unroll
        for (int e = 0; e < 2; e++) {
          const int key = 8 * n + 2 * q4 + e;
          float x = second ? sb2[4 * n + e] : sa[4 * n + e], y = second ? sb2[4 * n + 2 + e] : sa[4 * n + 2 + e];
          if (n < 4) { if (key > r0) x = -INFINITY; if (key > r1) y = -INFINITY; }
          sa[4 * n + e] = x; sa[4 * n + 2 + e] = y;
          m0 = fmaxf(m0, x); m1 = fmaxf(m1, y);
        }
      }
      m0 = fmaxf(m0, __shfl_xor_sync(0xffffffffu, m0, 1)); m1 = fmaxf(m1, __shfl_xor_sync(0xffffffffu, m1, 1));
      m0 = fmaxf(m0, __shfl_xor_sync(0xffffffffu, m0, 2)); m1 = fmaxf(m1, __shfl_xor_sync(0xffffffffu, m1, 2));
      float s0 = 0.f, s1 = 0.f;
#pragma unroll
      for (int n = 0; n < 5; n++) {
#pragma unroll
        for (int e = 0; e < 2; e++) {
          sa[4 * n + e] = ex2f((sa[4 * n + e] - m0) * cs); sa[4 * n + 2 + e] = ex2f((sa[4 * n + 2 + e] - m1) * cs);
          s0 += sa[4 * n + e]; s1 += sa[4 * n + 2 + e];
        }
      }
      s0 += __shfl_xor_sync(0xffffffffu, s0, 1); s1 += __shfl_xor_sync(0xffffffffu, s1, 1);
      s0 += __shfl_xor_sync(0xffffffffu, s0, 2); s1 += __shfl_xor_sync(0xffffffffu, s1, 2);
      const float i0 = rcpf(s0), i1 = rcpf(s1);
#pragma unroll
      for (int n = 0; n < 5; n++) {
        const uint32_t x = pack_bf16(sa[4 * n] * i0, sa[4 * n + 1] * i0), y = pack_bf16(sa[4 * n + 2] * i1, sa[4 * n + 3] * i1);
        if (n < 4) {
          pf[n >> 1][2 * (n & 1)] = second ? 0u : x; pf[n >> 1][2 * (n & 1) + 1] = second ? 0u : y;
          pf[2 + (n >> 1)][2 * (n & 1)] = second ? x : 0u; pf[2 + (n >> 1)][2 * (n & 1) + 1] = second ? y : 0u;
        } else {
          pf[4][0] = second ? 0u : x; pf[4][1] = second ? 0u : y; pf[4][2] = second ? x : 0u; pf[4][3] = second ? y : 0u;
        }
      }
    }
    {
      float o[96];
#pragma unroll
      for (int i = 0; i < 5; i++) { PIN(pf[i][0]); PIN(pf[i][1]); PIN(pf[i][2]); PIN(pf[i][3]); }
      const uint32_t own = own_slot(), vbase = sb + own * STQ;
      wgmma_fence();
#pragma unroll
      for (int i = 0; i < 5; i++)
        wgmma_rs_n192<1>(o, pf[i][0], pf[i][1], pf[i][2], pf[i][3], i < 4 ? make_desc(vbase + (i >> 1) * SEGB + (i & 1) * 256, 128, 640, 0) : make_desc(vbase + 512, SEGB, 640, 0), i != 0);
      wgmma_commit();
      if (type == T_A) mbar_wait(barK + 8 * wg, kph);
      kph ^= 1;
      wgmma_wait<0>();
      mbar_arrive_if((threadIdx.x & 127) == 0, empty + 8 * own);
      stage_tiles<192>(o, ost, wi, lane);
      fence_proxy_async();
      __syncwarp();
      mbar_arrive_if(lane == 0, done);
    }
  }
}
namespace bf {
constexpr int NS = 4, STAGE = 16384 + 32768;
constexpr int PIECE = 20480;
constexpr int OFF_PHI = 0, OFF_V = 40960, OFF_KV = 65536;
constexpr int OFF_OST = 5 * PIECE;
constexpr int OFF_WOT = 6 * PIECE;
constexpr int OFF_BAR = OFF_WOT + 102400;
constexpr int SMEM = OFF_BAR + 256;
static_assert(NS * STAGE <= OFF_BAR && SMEM <= 232448, "smem");
constexpr int KVACC = 32 * 5 * 1024;
struct Args {
  const unsigned char *wb, *wot;
  unsigned char *kvacc, *o2;
  const bf16* xin;
  bf16* xout;
  unsigned* go;
  const void* prep;
  const bf16 *pf0, *pf1;
  int pfn, pfns, pfwait;
  int tl;
};
}
__device__ __forceinline__ void hedgehog_features(float (&x)[2][5], uint32_t (&w)[2][5]) {
  const float L = 1.4426950408889634f;
  float mx[2], mn[2], sp[2], sn[2], pos[2][5], neg[2][5];
#pragma unroll
  for (int r = 0; r < 2; r++) {
    mx[r] = fmaxf(fmaxf(fmaxf(x[r][0], x[r][1]), fmaxf(x[r][2], x[r][3])), x[r][4]);
    mn[r] = fminf(fminf(fminf(x[r][0], x[r][1]), fminf(x[r][2], x[r][3])), x[r][4]);
  }
#pragma unroll
  for (int o = 1; o < 4; o <<= 1)
#pragma unroll
    for (int r = 0; r < 2; r++) {
      const uint32_t t = __shfl_xor_sync(0xffffffffu, __byte_perm(__float_as_uint(mn[r]), __float_as_uint(mx[r]), 0x7632), o);
      mx[r] = fmaxf(mx[r], bf_hi(t)); mn[r] = fminf(mn[r], bf_lo(t));
    }
#pragma unroll
  for (int r = 0; r < 2; r++) {
#pragma unroll
    for (int i = 0; i < 5; i++) { pos[r][i] = ex2f((x[r][i] - mx[r]) * L); neg[r][i] = ex2f((mn[r] - x[r][i]) * L); }
    sp[r] = ((pos[r][0] + pos[r][1]) + (pos[r][2] + pos[r][3])) + pos[r][4];
    sn[r] = ((neg[r][0] + neg[r][1]) + (neg[r][2] + neg[r][3])) + neg[r][4];
  }
#pragma unroll
  for (int o = 1; o < 4; o <<= 1)
#pragma unroll
    for (int r = 0; r < 2; r++) { sp[r] += __shfl_xor_sync(0xffffffffu, sp[r], o); sn[r] += __shfl_xor_sync(0xffffffffu, sn[r], o); }
#pragma unroll
  for (int r = 0; r < 2; r++) {
    const float ip = rcpf(sp[r]), in_ = rcpf(sn[r]);
    w[r][0] = pack_bf16(pos[r][0] * ip, pos[r][1] * ip); w[r][1] = pack_bf16(pos[r][2] * ip, pos[r][3] * ip);
    w[r][2] = pack_bf16(neg[r][0] * in_, neg[r][1] * in_); w[r][3] = pack_bf16(neg[r][2] * in_, neg[r][3] * in_);
    w[r][4] = pack_bf16(pos[r][4] * ip, neg[r][4] * in_);
  }
}
__device__ __forceinline__ void bulk_g2s_mc(uint32_t dst, const void* src, uint32_t bytes, uint32_t mb) {
  asm volatile("cp.async.bulk.shared::cluster.global.mbarrier::complete_tx::bytes.multicast::cluster [%0], [%1], %2, [%3], %4;"
               :: "r"(dst), "l"(src), "r"(bytes), "r"(mb), "h"((unsigned short)3) : "memory");
}
__device__ __forceinline__ void mbar_arrive_remote_if(bool c, uint32_t b) {
  asm volatile("{\n.reg .pred p;\nsetp.ne.u32 p, %1, 0;\n@p mbarrier.arrive.shared::cluster.b64 _, [%0];\n}" :: "r"(b), "r"((uint32_t)c) : "memory");
}

__global__ void __cluster_dims__(2, 1, 1) __launch_bounds__(384, 1) blayer_kernel(const __grid_constant__ CUtensorMap tmA, const __grid_constant__ bf::Args a) {
  using namespace bf;
  [[maybe_unused]] const int tl = a.tl;
  extern __shared__ __align__(1024) unsigned char smem_raw[];
  const uint32_t sb = smem_u32(smem_raw);
  const int warp = __shfl_sync(0xffffffffu, (int)threadIdx.x >> 5, 0), lane = threadIdx.x & 31;
  const uint32_t full = sb + OFF_BAR, empty = full + 8 * NS, full2 = empty + 8 * NS, empty2 = full2 + 64, barW = empty2 + 16, drained = barW + 8, staged = drained + 8, freeb = staged + 8;
  const int rank = blockIdx.x & 1, u = (blockIdx.x >> 1) & 7, mp = blockIdx.x >> 4;
  const int m = 2 * mp + rank;
  const int m2 = 2 * mp + (u & 1), ns = (u & ~1) + rank;
  const uint32_t dpeer = mapa_u32(sb, rank ^ 1) - sb;
  unsigned* cntO = (unsigned*)(a.kvacc + KVACC);
  if (threadIdx.x == 0) {
    for (int i = 0; i < NS; i++) { mbar_init(full + 8 * i, 1); mbar_init(empty + 8 * i, 4); }
    for (int i = 0; i < 8; i++) mbar_init(full2 + 8 * i, 1);
    mbar_init(empty2, 2); mbar_init(empty2 + 8, 2);
    mbar_init(barW, 1); mbar_init(drained, 1); mbar_init(staged, 8); mbar_init(freeb, 2);
    asm volatile("fence.mbarrier_init.release.cluster;" ::: "memory");
  }
  __syncthreads();
  asm volatile("barrier.cluster.arrive.relaxed.aligned; barrier.cluster.wait.aligned;" ::: "memory");
  if (warp >= 8) {
    asm volatile("setmaxnreg.dec.sync.aligned.u32 40;");
    if (warp == 8) { if (elect_one()) {
      const unsigned char* wsrc = a.wb + (size_t)u * 327680 + rank * 16384;
      if (a.prep) wait_ge(a.prep, 64);
      fence_proxy_async_global();
      for (int kb = 0; kb < NS; kb++) {
        mbar_expect_tx(full + 8 * kb, STAGE);
        bulk_g2s_mc(sb + kb * STAGE + 16384 + rank * 16384, wsrc + kb * 32768, 16384, full + 8 * kb);
      }
      asm volatile("griddepcontrol.wait;" ::: "memory");
      TL_BEGIN0(tl);
      if (blockIdx.x == 0) *a.go = 0;
      for (int kb = 0; kb < NS; kb++) tma_load_2d(sb + kb * STAGE, &tmA, kb * 64, m * 128, full + 8 * kb);
      if (m == 0) prefetch_l2(a.kvacc + u * (KVACC / 8), KVACC / 8);
#pragma unroll 1
      for (int kb = NS; kb < 10; kb++) {
        const uint32_t s = kb & 3, st = sb + s * STAGE, fb = full + 8 * s;
        mbar_wait(empty + 8 * s, ((kb >> 2) - 1) & 1);
        mbar_expect_tx(fb, STAGE);
        tma_load_2d(st, &tmA, kb * 64, m * 128, fb);
        bulk_g2s_mc(st + 16384 + rank * 16384, wsrc + kb * 32768, 16384, fb);
      }
      for (int i = 0; i < 6; i++) mbar_expect_tx(full2 + 8 * i, PIECE);
      mbar_wait(drained, 0);
      mbar_expect_tx(barW, 102400);
      bulk_g2s(sb + OFF_WOT, a.wot + (size_t)ns * 102400, 102400, barW);
      mbar_wait(staged, 0);
      bulk_s2g(a.o2 + (size_t)(m * 8 + u) * PIECE, sb + OFF_OST, PIECE);
      bulk_commit();
      bulk_wait<0>();
      mbar_arrive(freeb); mbar_arrive_remote_if(true, freeb + dpeer);
      red_release_inc(cntO + m);
      wait_ge(cntO + m2, 8, 20);
      mbar_wait(freeb, 0);
      fence_proxy_async_global();
      const unsigned char* osrc = a.o2 + (size_t)m2 * 8 * PIECE;
      for (int i = 0; i < 6; i++) bulk_g2s_mc(sb + i * PIECE + rank * (PIECE / 2), osrc + i * PIECE + rank * (PIECE / 2), PIECE / 2, full2 + 8 * i);
      for (int i = 0; i < 2; i++) {
        mbar_wait(empty2 + 8 * i, 0);
        mbar_expect_tx(full2 + 8 * (6 + i), PIECE);
        bulk_g2s(sb + i * PIECE, osrc + (6 + i) * PIECE, PIECE, full2 + 8 * (6 + i));
      }
    } } else if (warp == 9 && a.pf0) { if (elect_one()) {
      if (a.pfwait) asm volatile("griddepcontrol.wait;" ::: "memory");
      constexpr uint32_t CH = 2048;
      for (int i = 0; i < a.pfn; i++) {
        prefetch_l2((const unsigned char*)a.pf0 + (i * 128 + blockIdx.x) * CH, CH); prefetch_l2((const unsigned char*)a.pf1 + (i * 128 + blockIdx.x) * CH, CH);
        __nanosleep(a.pfns);
      }
    } }
    return;
  }
  asm volatile("setmaxnreg.inc.sync.aligned.u32 232;");
  const int wg = warp >> 2, wi = warp & 3;
  const int q4 = lane & 3;
  const bool lead = (threadIdx.x & 127) == 0;
  float acc[128];
  {
#pragma unroll 1
    for (int kb = 0; kb < 10; kb++) {
      const uint32_t s = kb & 3, st = sb + s * STAGE;
      mbar_wait(full + 8 * s, (kb >> 2) & 1);
      wgmma_fence();
#pragma unroll
      for (int kk = 0; kk < 4; kk++) wgmma_n256<0, 1>(acc, desc_kmajor(st + wg * 8192 + kk * 32), make_desc(st + 16384 + kk * 8192, 4096, 128, 0), (kb | kk) != 0);
      wgmma_commit();
      if (kb > 0 && kb < 7) { wgmma_wait<1>(); const uint32_t e = empty + 8 * ((kb - 1) & 3); mbar_arrive_if(lead, e); mbar_arrive_remote_if(lead, e + dpeer); }
    }
    wgmma_wait<0>();
    bar_sync(1, 256);
    mbar_arrive_if(threadIdx.x == 0, drained);
  }
  TL2((tl >= 12 ? 128 : 0) + 32 + 0);
  const uint32_t srow = (wg * 64 + wi * 16 + (lane & 15)) * 16 + (lane >> 4) * 2048;
  auto features = [&](auto T0, auto HH, uint32_t (&w)[2][5]) {
    constexpr int t = T0.value + 5 * (HH.value >> 1), o = (HH.value & 1) ? 3 : 0, e = HH.value & 1;
    float x[2][5];
#pragma unroll
    for (int r = 0; r < 2; r++) {
      x[r][0] = acc[4 * (t + o) + 2 * r]; x[r][1] = acc[4 * (t + o) + 2 * r + 1]; x[r][2] = acc[4 * (t + o + 1) + 2 * r]; x[r][3] = acc[4 * (t + o + 1) + 2 * r + 1];
      bf16r2(x[r][0], x[r][1]); bf16r2(x[r][2], x[r][3]);
    }
    x[0][4] = acc[4 * (t + 2) + e]; x[1][4] = acc[4 * (t + 2) + 2 + e];
    bf16r2(x[0][4], x[1][4]);
    hedgehog_features(x, w);
  };
  static_for<0, 4>([&](auto HH) {
    constexpr int hh = HH.value, t = 20 + 3 * hh;
    const uint32_t one = q4 == ((hh & 1) ? 0 : 2) ? 0x3f80u : 0u;
    const uint32_t va = sb + OFF_V + hh * 6144 + srow;
    stsm_x4(va, pack_bf16(acc[4 * t], acc[4 * t + 1]), pack_bf16(acc[4 * t + 2], acc[4 * t + 3]), pack_bf16(acc[4 * t + 4], acc[4 * t + 5]), pack_bf16(acc[4 * t + 6], acc[4 * t + 7]));
    const bool pad = (q4 >= 2) != (hh & 1);
    stsm_x2(va + 4096, pad ? one : pack_bf16(acc[4 * t + 8], acc[4 * t + 9]), pad ? one : pack_bf16(acc[4 * t + 10], acc[4 * t + 11]));
    uint32_t w[2][5];
    features(IC<10>{}, HH, w);
    const uint32_t pa = sb + OFF_PHI + hh * 10240 + srow;
    stsm_x4(pa, w[0][0], w[1][0], w[0][1], w[1][1]);
    stsm_x4(pa + 4096, w[0][2], w[1][2], w[0][3], w[1][3]);
    stsm_x2(pa + 8192, w[0][4], w[1][4]);
  });
  fence_proxy_async();
  bar_sync(1, 256);
  TL2((tl >= 12 ? 128 : 0) + 32 + 1);
  {
    float d0[12], d1[12];
    const uint32_t pa = sb + OFF_PHI + wg * 20480, pv = sb + OFF_V + wg * 12288;
    wgmma_fence();
#pragma unroll
    for (int k = 0; k < 8; k++) {
      wgmma_n24<1, 1>(d0, make_desc(pa + k * 256, 128, 2048, 0), make_desc(pv + k * 256, 128, 2048, 0), k != 0);
      wgmma_n24<1, 1>(d1, make_desc(pa + 10240 + k * 256, 128, 2048, 0), make_desc(pv + 6144 + k * 256, 128, 2048, 0), k != 0);
    }
    wgmma_commit();
    wgmma_wait<0>();
    unsigned char* dst = a.kvacc + ((u * 4 + wg * 2) * 5 + 2 * wi) * 1024 + lane * 16;
    auto red4 = [&](bool on, unsigned char* p, float x, float y, float z) {
      asm volatile("{\n.reg .pred p;\nsetp.ne.u32 p, %4, 0;\n@p red.relaxed.gpu.global.add.v4.f32 [%0], {%1,%2,%3,%5};\n}" :: "l"(p), "f"(x), "f"(y), "f"(z), "r"((uint32_t)on), "f"(1.f) : "memory");
    };
    red4(wi < 3, dst, d0[0], d0[1], d0[4]); red4(wi < 3, dst + 512, d0[5], d0[8], d0[9]);
    red4(wi < 3, dst + 5120, d1[0], d1[1], d1[4]); red4(wi < 3, dst + 5632, d1[5], d1[8], d1[9]);
    red4(wi < 2, dst + 1024, d0[2], d0[3], d0[6]); red4(wi < 2, dst + 1536, d0[7], d0[10], d0[11]);
    red4(wi < 2, dst + 6144, d1[2], d1[3], d1[6]); red4(wi < 2, dst + 6656, d1[7], d1[10], d1[11]);
  }
  TL2((tl >= 12 ? 128 : 0) + 32 + 2);
  uint32_t qf[4][2][5];
  static_for<0, 4>([&](auto HH) { features(IC<0>{}, HH, qf[HH.value]); });
  uint4 xr[5];
#pragma unroll
  for (int i = 0; i < 5; i++) {
    const int c = lane + 32 * i;
    xr[i] = __ldcg((const uint4*)(a.xin + (size_t)(m2 * 128 + wg * 64 + wi * 16 + c / 10) * cfg::DM + ns * 80 + (c % 10) * 8));
  }
  {
    const unsigned char* src = a.kvacc + (u * 20 + warp) * 1024 + lane * 16;
    uint4 v[6];
    int spin = 0;
    while (true) {
      v[0] = ld_relaxed_v4_i<0>(src); v[1] = ld_relaxed_v4_i<512>(src); v[2] = ld_relaxed_v4_i<8192>(src); v[3] = ld_relaxed_v4_i<8704>(src);
      v[4] = ld_relaxed_v4_i<0>(src + (wg ? 0 : 16384)); v[5] = ld_relaxed_v4_i<512>(src + (wg ? 0 : 16384));
      const uint32_t c = (v[0].w & v[1].w & v[2].w) & (v[3].w & v[4].w & v[5].w);
      if (!__any_sync(0xffffffffu, (c & 0x41800000u) != 0x41800000u) || ++spin >= SPIN_LIMIT) break;
      __nanosleep(100);
    }
    const uint32_t kd = sb + OFF_KV + warp * 384 + lane * 4;
#pragma unroll
    for (int i = 0; i < 3; i++)
      if (i < 2 || wg == 0) {
        sts32(kd + i * 3072, pack_bf16(__uint_as_float(v[2 * i].x), __uint_as_float(v[2 * i].y)));
        sts32(kd + i * 3072 + 128, pack_bf16(__uint_as_float(v[2 * i].z), __uint_as_float(v[2 * i + 1].x)));
        sts32(kd + i * 3072 + 256, pack_bf16(__uint_as_float(v[2 * i + 1].y), __uint_as_float(v[2 * i + 1].z)));
      }
  }
  fence_proxy_async();
  bar_sync(1, 256);
  TL2((tl >= 12 ? 128 : 0) + 32 + 3);
  {
    float d[4][12];
    uint32_t zero = 0; PIN(zero);
#pragma unroll
    for (int hh = 0; hh < 4; hh++)
#pragma unroll
      for (int i = 0; i < 5; i++) { PIN(qf[hh][0][i]); PIN(qf[hh][1][i]); }
    wgmma_fence();
#pragma unroll
    for (int hh = 0; hh < 4; hh++) {
      const uint32_t kb = sb + OFF_KV + hh * 1920;
      wgmma_rs_n24<1>(d[hh], qf[hh][0][0], qf[hh][1][0], qf[hh][0][1], qf[hh][1][1], make_desc(kb, 384, 128, 0), 0);
      wgmma_rs_n24<1>(d[hh], qf[hh][0][2], qf[hh][1][2], qf[hh][0][3], qf[hh][1][3], make_desc(kb + 768, 384, 128, 0), 1);
      wgmma_rs_n24<1>(d[hh], qf[hh][0][4], qf[hh][1][4], zero, zero, make_desc(kb + 1536, 0, 128, 0), 1);
    }
    wgmma_commit();
    wgmma_wait<0>();
    uint32_t ow[4][6];
#pragma unroll
    for (int hh = 0; hh < 4; hh++) {
      const int zl = (lane & ~3) | ((hh & 1) ? 0 : 2);
      const float da = bf16r(bf16r(__shfl_sync(0xffffffffu, d[hh][8], zl)) + 1e-6f), db = bf16r(bf16r(__shfl_sync(0xffffffffu, d[hh][10], zl)) + 1e-6f);
#pragma unroll
      for (int n = 0; n < 3; n++) {
        bf16r2(d[hh][4 * n], d[hh][4 * n + 1]); bf16r2(d[hh][4 * n + 2], d[hh][4 * n + 3]);
        ow[hh][2 * n] = pack_bf16(__fdividef(d[hh][4 * n], da), __fdividef(d[hh][4 * n + 1], da));
        ow[hh][2 * n + 1] = pack_bf16(__fdividef(d[hh][4 * n + 2], db), __fdividef(d[hh][4 * n + 3], db));
      }
    }
#pragma unroll
    for (int p = 0; p < 2; p++) {
      const uint32_t oa = sb + OFF_OST + p * 10240 + srow;
      stsm_x4(oa, ow[2 * p][0], ow[2 * p][1], ow[2 * p][2], ow[2 * p][3]);
      stsm_x2(oa + 4096, q4 < 2 ? ow[2 * p][4] : ow[2 * p + 1][4], q4 < 2 ? ow[2 * p][5] : ow[2 * p + 1][5]);
      stsm_x4(oa + 6144, ow[2 * p + 1][0], ow[2 * p + 1][1], ow[2 * p + 1][2], ow[2 * p + 1][3]);
    }
    fence_proxy_async();
    __syncwarp();
    mbar_arrive_if(lane == 0, staged);
  }
  TL2((tl >= 12 ? 128 : 0) + 32 + 4);
  float c2[40];
  mbar_wait(barW, 0);
#pragma unroll 1
  for (int i = 0; i < 8; i++) {
    mbar_wait(full2 + 8 * i, 0);
    const uint32_t st = sb + (i < 6 ? i : i - 6) * PIECE + wg * 1024, wo = sb + OFF_WOT + i * 12800;
    wgmma_fence();
#pragma unroll
    for (int kk = 0; kk < 5; kk++) wgmma_n80<0, 1>(c2, make_desc(st + kk * 4096, 2048, 128, 0), make_desc(wo + kk * 2560, 1280, 128, 0), (i | kk) != 0);
    wgmma_commit();
    if (i == 1 || i == 2) { wgmma_wait<1>(); mbar_arrive_if(lead, empty2 + 8 * (i - 1)); }
  }
  wgmma_wait<0>();
  TL2((tl >= 12 ? 128 : 0) + 32 + 5);
  {
    bar_sync(1, 256);
    const uint32_t ost = sb + 2 * PIECE + warp * 3072;
#pragma unroll
    for (int v = 0; v < 10; v += 2)
      stsm_x4(ost + (lane & 15) * 176 + (v + (lane >> 4)) * 16, pack_bf16(c2[4 * v], c2[4 * v + 1]), pack_bf16(c2[4 * v + 2], c2[4 * v + 3]),
              pack_bf16(c2[4 * v + 4], c2[4 * v + 5]), pack_bf16(c2[4 * v + 6], c2[4 * v + 7]));
    __syncwarp();
#pragma unroll
    for (int i = 0; i < 5; i++) {
      const int c = lane + 32 * i, row = c / 10, chunk = c % 10;
      const uint4 y = lds128(ost + row * 176 + chunk * 16);
      const size_t off = (size_t)(m2 * 128 + wg * 64 + wi * 16 + row) * cfg::DM + ns * 80 + chunk * 8;
      const uint4 x = xr[i];
      *(uint4*)(a.xout + off) = make_uint4(pack_bf16(bf_lo(x.x) + bf_lo(y.x), bf_hi(x.x) + bf_hi(y.x)), pack_bf16(bf_lo(x.y) + bf_lo(y.y), bf_hi(x.y) + bf_hi(y.y)),
                                           pack_bf16(bf_lo(x.z) + bf_lo(y.z), bf_hi(x.z) + bf_hi(y.z)), pack_bf16(bf_lo(x.w) + bf_lo(y.w), bf_hi(x.w) + bf_hi(y.w)));
    }
  }
  TL_END(tl);
}
__device__ __align__(32768) unsigned char g_arena[AR_SIZE];
__device__ unsigned g_go[32];
__device__ __align__(1024) uint2 g_xh[2048 * 160];
__device__ __align__(1024) unsigned char g_k[64 * 96 * 5120], g_v[64 * 96 * 5120];
__device__ __align__(1024) bf16 g_o[2048 * 6144];
__device__ __align__(1024) uint4 g_qs[8 * 32 * 12 * 256];
__device__ __align__(1024) bf16 g_xn[2048 * 640], g_xn2[2048 * 640], g_xa[2048 * 640], g_xb[2048 * 640];
__device__ __align__(1024) bf16 g_part[24 * 2048 * 640];
__device__ __align__(1024) bf16 g_wb[2048 * 640], g_wot[640 * 640], g_pq[2048 * 640];
__device__ __align__(1024) float g_kvacc[bf::KVACC / 4 + 64];

typedef CUresult (*EncodeFn)(CUtensorMap*, CUtensorMapDataType, cuuint32_t, void*, const cuuint64_t*, const cuuint64_t*, const cuuint32_t*,
                             const cuuint32_t*, CUtensorMapInterleave, CUtensorMapSwizzle, CUtensorMapL2promotion, CUtensorMapFloatOOBfill);
static EncodeFn g_encode = nullptr;
static CUtensorMap make_map(const void* p, uint64_t cols, uint64_t rows, uint32_t bc, uint32_t br, bool swz = true) {
  CUtensorMap m;
  cuuint64_t dims[2] = {cols, rows}, strides[1] = {cols * 2};
  cuuint32_t box[2] = {bc, br}, es[2] = {1, 1};
  g_encode(&m, CU_TENSOR_MAP_DATA_TYPE_BFLOAT16, 2, const_cast<void*>(p), dims, strides, box, es, CU_TENSOR_MAP_INTERLEAVE_NONE,
           swz ? CU_TENSOR_MAP_SWIZZLE_128B : CU_TENSOR_MAP_SWIZZLE_NONE, CU_TENSOR_MAP_L2_PROMOTION_L2_256B, CU_TENSOR_MAP_FLOAT_OOB_FILL_NONE);
  return m;
}
static CUtensorMap make_map3(const void* p, uint64_t cols, uint64_t rows, uint32_t nb) {
  CUtensorMap m;
  cuuint64_t dims[3] = {64, rows, cols / 64}, strides[2] = {cols * 2, 128};
  cuuint32_t box[3] = {64, 64, nb}, es[3] = {1, 1, 1};
  g_encode(&m, CU_TENSOR_MAP_DATA_TYPE_BFLOAT16, 3, const_cast<void*>(p), dims, strides, box, es, CU_TENSOR_MAP_INTERLEAVE_NONE,
           CU_TENSOR_MAP_SWIZZLE_128B, CU_TENSOR_MAP_L2_PROMOTION_L2_256B, CU_TENSOR_MAP_FLOAT_OOB_FILL_NONE);
  return m;
}
template <class T> static T* sym(const T& s) { void* p = nullptr; cudaGetSymbolAddress(&p, s); return (T*)p; }

struct Ptrs {
  unsigned char *arena, *k, *v; bf16 *o, *xn, *xa, *xb, *wb, *wot, *pq; float *part, *kvacc; uint2* xh; uint4* qs; bf16* xn2; unsigned* go;
};

static tr::Sched make_sched(int layer, const char* str, const int* ks, const int* lr) {
  using namespace tr;
  Sched s = {};
  int n = 0;
  for (int b = 0; b < 16; b++) { s.ks[b] = (uint8_t)abs(ks[b]); s.wide[b] = ks[b] > 0; s.lrows[b] = (uint8_t)lr[b]; }
  for (const char* p = str; *p;) {
    if (*p == ' ') { p++; continue; }
    const bool late = *p < 'a';
    const char c = *p++ | 32;
    char* e;
    const int b = (int)strtol(p, &e, 10); p = e;
    int first = 0, cnt = c == 'o' ? s.ks[b] * (s.wide[b] ? 2 : 5) : (c == 'l' ? 16 / lr[b] : 32);
    if (*p == '.') { first = (int)strtol(p + 1, &e, 10); cnt = (int)strtol(e + 1, &e, 10); p = e; }
    const int type = c == 'a' ? T_QA : (c == 'q' ? T_Q : (c == 't' ? T_A : (c == 'l' ? T_L : (c == 'p' ? T_P : (s.wide[b] ? T_OB : T_OS)))));
    if (type == T_P && layer > 0) continue;
    for (int i = 0; i < cnt && n < MAXITEMS - 1; i++) s.item[n++] = (uint16_t)((late << 14) | (type << 11) | (b << 7) | (first + i));
  }
  s.n = n; s.item[n] = T_END << 11;
  return s;
}
static tr::Sched sched_of(int layer) {
  const char* str = "q12 q13 q14 a0 q15 a1 p0.0.16 o0 o1 a2 p0.16.16 o2 a3 a4 o3 a5 o4 a6 l0 o5 l1 a7 o6 l2 a8 o7 a9 o8 l3 l4 a10 O9 l5 a11 O10 t12 l6 l7 o11 O12 t13 t14 T15 O13 o15 O14 L10 L9 l15 l13 L8 l14 l12 l11";
  int ks[16] = {2, 2, 2, 2, 2, 2, 2, 2, 2, 3, 3, 3, 3, -4, -6, -8}, lr[16] = {4, 4, 4, 4, 4, 4, 4, 4, 1, 4, 1, 1, 1, 1, 1, 1};
#ifdef TUNE
  if (getenv("SCHED")) str = getenv("SCHED");
  if (layer == 0 && getenv("SCHED0")) str = getenv("SCHED0");
  if (const char* p = getenv(layer == 0 && getenv("KS0") ? "KS0" : "KS")) for (int b = 0; b < 16; b++) { char* e; ks[b] = (int)strtol(p, &e, 10); p = e; }
  if (const char* p = getenv("LR")) for (int b = 0; b < 16; b++) { char* e; lr[b] = (int)strtol(p, &e, 10); p = e; }
#endif
  return make_sched(layer, str, ks, lr);
}
#ifndef TRAIL_GRID
#define TRAIL_GRID 132
#endif
#ifndef PDL_LN
#define PDL_LN 0
#endif
#ifndef PDL_CH
#define PDL_CH 1
#endif
#ifndef PDL_B
#define PDL_B 1
#endif
#ifndef PF_A
#define PF_A 1
#endif
#ifndef PF_B
#define PF_B 1
#endif
extern "C" void kernel_launch(void* const* d_in, const int* in_sizes, int n_in, void* d_out, int out_size) {
  const bf16* x = (const bf16*)d_in[0];
  const bf16* mem0 = (const bf16*)d_in[1];
  const bf16 *Wq = (const bf16*)d_in[2], *Wk = (const bf16*)d_in[3], *Wv = (const bf16*)d_in[4], *Wo = (const bf16*)d_in[5];
  const bf16 *wqkv = (const bf16*)d_in[8], *wphi = (const bf16*)d_in[9], *wo = (const bf16*)d_in[10];
  bf16* out = (bf16*)d_out;
  static Ptrs P; static bool init = false;
  if (!init) {
    void* fn = nullptr; cudaDriverEntryPointQueryResult qr;
    cudaGetDriverEntryPoint("cuTensorMapEncodeTiled", &fn, cudaEnableDefault, &qr);
    g_encode = (EncodeFn)fn;
    void* p;
    cudaGetSymbolAddress(&p, g_arena); P.arena = (unsigned char*)p;
    cudaGetSymbolAddress(&p, g_k); P.k = (unsigned char*)p;   cudaGetSymbolAddress(&p, g_v); P.v = (unsigned char*)p;
    cudaGetSymbolAddress(&p, g_o); P.o = (bf16*)p;
    cudaGetSymbolAddress(&p, g_xn); P.xn = (bf16*)p;
    cudaGetSymbolAddress(&p, g_xa); P.xa = (bf16*)p;   cudaGetSymbolAddress(&p, g_xb); P.xb = (bf16*)p;
    cudaGetSymbolAddress(&p, g_wb); P.wb = (bf16*)p;   cudaGetSymbolAddress(&p, g_wot); P.wot = (bf16*)p;
    cudaGetSymbolAddress(&p, g_pq); P.pq = (bf16*)p;   cudaGetSymbolAddress(&p, g_part); P.part = (float*)p;
    cudaGetSymbolAddress(&p, g_kvacc); P.kvacc = (float*)p;
    cudaGetSymbolAddress(&p, g_xh); P.xh = (uint2*)p;
    cudaGetSymbolAddress(&p, g_go); P.go = (unsigned*)p;
    cudaGetSymbolAddress(&p, g_qs); P.qs = (uint4*)p;
    cudaGetSymbolAddress(&p, g_xn2); P.xn2 = (bf16*)p;
    cudaFuncSetAttribute(chain_kernel, cudaFuncAttributeMaxDynamicSharedMemorySize, ch::SMEM);
    cudaFuncSetAttribute(trail_kernel, cudaFuncAttributeMaxDynamicSharedMemorySize, tr::SMEM);
    cudaFuncSetAttribute(blayer_kernel, cudaFuncAttributeMaxDynamicSharedMemorySize, bf::SMEM);
    init = true;
  }
  const CUtensorMap tmXn = make_map(P.xn, 640, 2048, 64, 128), tmXn2 = make_map(P.xn2, 640, 2048, 64, 128);
  const CUtensorMap tmWq = make_map3(Wq, 6144, 640, 3);
  const CUtensorMap tmCq = make_map(Wq, 6144, 640, 64, 160), tmCk = make_map(Wk, 6144, 640, 64, 160), tmCv = make_map(Wv, 6144, 640, 64, 160), tmCo = make_map(Wo, 640, 6144, 224, 64, false);
  const CUtensorMap tmWo5 = make_map3(Wo, 640, 6144, 5), tmWo2 = make_map3(Wo, 640, 6144, 2);

  CUtensorMap tmP;
  {
    cuuint64_t dims[3] = {256, 8, 24 * 320}, strides[2] = {1024, 8192};
    cuuint32_t box[3] = {256, 1, 10}, es[3] = {1, 1, 1};
    g_encode(&tmP, CU_TENSOR_MAP_DATA_TYPE_UINT32, 3, P.part, dims, strides, box, es, CU_TENSOR_MAP_INTERLEAVE_NONE, CU_TENSOR_MAP_SWIZZLE_NONE,
             CU_TENSOR_MAP_L2_PROMOTION_NONE, CU_TENSOR_MAP_FLOAT_OOB_FILL_NONE);
  }
  ChainArgs ca;
  ca.xh = P.xh; ca.mem0 = mem0; ca.kg = P.k; ca.vg = P.v;
  ca.arena = P.arena; ca.dbg = nullptr; ca.go = P.go; ca.delay = POLL_DELAY; ca.margin = 150; ca.pubrel = 1;
#ifdef TUNE
  if (getenv("PR")) ca.pubrel = atoi(getenv("PR"));
  if (getenv("MG")) ca.margin = atoi(getenv("MG"));
  if (getenv("PD")) ca.delay = atoi(getenv("PD"));
#endif
  ca.tl = 0;
  uint4* zar = (uint4*)P.arena; const int nzar = AR_SIZE / 16;
  uint4* zkv = (uint4*)P.kvacc; const int nzkv = (bf::KVACC / 4 + 64) / 4;

  const PrepArgs pa{wqkv, wphi, wo, (unsigned char*)P.wb, (unsigned char*)P.wot};
  const bf16* xcur = x;
  cudaLaunchAttribute at[1];
  at[0].id = cudaLaunchAttributeProgrammaticStreamSerialization; at[0].val.programmaticStreamSerializationAllowed = 1;
  auto cfgof = [&](int grid, int block, int smem, bool pdl) {
    cudaLaunchConfig_t lc = {};
    lc.gridDim = dim3(grid); lc.blockDim = dim3(block); lc.dynamicSmemBytes = smem; lc.stream = cudaStreamPerThread;
    lc.attrs = at; lc.numAttrs = pdl ? 1 : 0;
    return lc;
  };
  int nlayers = 2;
#ifdef TUNE
  if (getenv("LAYERS")) nlayers = atoi(getenv("LAYERS"));
#endif
  for (int layer = 0; layer < nlayers; layer++) {
    const int tl = layer * 12;
    cudaLaunchConfig_t lc = cfgof(256, 256, 0, layer > 0 && PDL_LN);
    cudaLaunchKernelEx(&lc, ln_kernel, xcur, P.xn, P.xh, zar, nzar, zkv, nzkv, Wk, Wv, layer == 0 ? PF_A : 0, tl + 0);
    ca.tl = tl + 2;
    lc = cfgof(96, 384, ch::SMEM, PDL_CH);
    cudaLaunchKernelEx(&lc, chain_kernel, ca, tmCq, tmCk, tmCv, tmCo);
    lc = cfgof(TRAIL_GRID, 384, tr::SMEM, true);
    tr::Args ta{P.k, P.v, (unsigned char*)P.o, P.qs, (unsigned char*)P.part, xcur, P.xn, P.xa, P.xn2, P.arena, P.go, tl + 4, 30, 20, layer == 0};
#ifdef TUNE
    if (getenv("NAP")) ta.nap = atoi(getenv("NAP"));
    if (getenv("NAP2")) ta.nap2 = atoi(getenv("NAP2"));
#endif
    cudaLaunchKernelEx(&lc, trail_kernel, tmXn, tmWq, tmWo5, tmWo2, tmP, sched_of(layer), ta, pa);
    lc = cfgof(128, 384, bf::SMEM, PDL_B);
    bf::Args ba{(const unsigned char*)P.wb, (const unsigned char*)P.wot, (unsigned char*)P.kvacc, (unsigned char*)P.pq, P.xa, layer == 0 ? P.xb : out, P.go, layer == 0 ? P.arena + tr::C_P : nullptr,
                      layer == 0 && PF_B ? Wk : nullptr, Wv, 30, 500, 0, tl + 7};
#ifdef TUNE
    if (getenv("PFN")) ba.pfn = atoi(getenv("PFN"));
    if (getenv("PFNS")) ba.pfns = atoi(getenv("PFNS"));
    if (getenv("PFWT")) ba.pfwait = atoi(getenv("PFWT"));
    if (getenv("PFB")) ba.pf0 = layer == 0 && atoi(getenv("PFB")) ? Wk : nullptr;
#endif
    cudaLaunchKernelEx(&lc, blayer_kernel, tmXn2, ba);
    xcur = P.xb;
  }
}
```

```cpp
#include <cuda_runtime.h>
#include <cuda.h>
#include <cuda_bf16.h>
#include <stdint.h>
#include <stdlib.h>
#include <type_traits>

typedef __nv_bfloat16 bf16;

namespace cfg {
constexpr int S = 2048, DM = 640, H = 32, DH = 192, NSEG = 64, SEG = 32, NM = 8;
constexpr int HD = H * DH;
}

__device__ __forceinline__ uint32_t smem_u32(const void* p) { return (uint32_t)__cvta_generic_to_shared(p); }
__device__ __forceinline__ uint32_t mapa_u32(uint32_t a, uint32_t r) {
  uint32_t o; asm("mapa.shared::cluster.u32 %0, %1, %2;" : "=r"(o) : "r"(a), "r"(r)); return o;
}
__device__ __forceinline__ void mbar_init(uint32_t b, uint32_t c) {
  asm volatile("mbarrier.init.shared::cta.b64 [%0], %1;" :: "r"(b), "r"(c) : "memory");
}
__device__ __forceinline__ void mbar_expect_tx(uint32_t b, uint32_t bytes) {
  asm volatile("mbarrier.arrive.expect_tx.shared::cta.b64 _, [%0], %1;" :: "r"(b), "r"(bytes) : "memory");
}
__device__ __forceinline__ void mbar_arrive(uint32_t b) {
  asm volatile("mbarrier.arrive.shared::cta.b64 _, [%0];" :: "r"(b) : "memory");
}
__device__ __forceinline__ void mbar_expect_tx_if(bool c, uint32_t b, uint32_t bytes) {
  asm volatile("{\n.reg .pred p;\nsetp.ne.u32 p, %2, 0;\n@p mbarrier.arrive.expect_tx.shared::cta.b64 _, [%0], %1;\n}" :: "r"(b), "r"(bytes), "r"((uint32_t)c) : "memory");
}
__device__ __forceinline__ void mbar_arrive_if(bool c, uint32_t b) {
  asm volatile("{\n.reg .pred p;\nsetp.ne.u32 p, %1, 0;\n@p mbarrier.arrive.shared::cta.b64 _, [%0];\n}" :: "r"(b), "r"((uint32_t)c) : "memory");
}
__device__ __forceinline__ bool mbar_try(uint32_t b, uint32_t ph) {
  uint32_t p;
  asm volatile("{.reg .pred p; mbarrier.try_wait.parity.shared::cta.b64 p, [%1], %2; selp.u32 %0, 1, 0, p;}"
               : "=r"(p) : "r"(b), "r"(ph) : "memory");
  return p;
}
__device__ __forceinline__ bool mbar_try_cluster(uint32_t b, uint32_t ph) {
  uint32_t p;
  asm volatile("{.reg .pred p; mbarrier.try_wait.parity.acquire.cluster.shared::cta.b64 p, [%1], %2; selp.u32 %0, 1, 0, p;}"
               : "=r"(p) : "r"(b), "r"(ph) : "memory");
  return p;
}
#ifndef SPIN_LIMIT
#define SPIN_LIMIT (1 << 20)
#endif
__device__ __forceinline__ void mbar_wait(uint32_t b, uint32_t ph) {
  asm volatile("{\n.reg .pred p, q;\n.reg .u32 c;\nmov.u32 c, 0;\n"
               "W_%=:\nmbarrier.try_wait.parity.shared::cta.b64 p, [%0], %1;\n@p bra.uni D_%=;\n"
               "add.u32 c, c, 1;\nsetp.lt.u32 q, c, %2;\n@q bra.uni W_%=;\nD_%=:\n}"
               :: "r"(b), "r"(ph), "n"(SPIN_LIMIT) : "memory");
}
__device__ __forceinline__ void mbar_spin(uint32_t b, uint32_t ph) {
  asm volatile("{\n.reg .pred p, q;\n.reg .u32 c;\nmov.u32 c, 0;\n"
               "W_%=:\nmbarrier.test_wait.parity.shared::cta.b64 p, [%0], %1;\n@p bra D_%=;\n"
               "add.u32 c, c, 1;\nsetp.lt.u32 q, c, %2;\n@q bra W_%=;\nD_%=:\n}"
               :: "r"(b), "r"(ph), "n"(SPIN_LIMIT) : "memory");
}
#define PIN(x) asm volatile("" : "+r"(x))
__device__ __forceinline__ void mbar_wait_cluster(uint32_t b, uint32_t ph) {
  int s = 0;
  while (!mbar_try_cluster(b, ph)) { if (++s > SPIN_LIMIT) break; }
}
__device__ __forceinline__ void st_async_v2(uint32_t a, uint32_t x, uint32_t y, uint32_t mb) {
  asm volatile("st.async.weak.shared::cluster.mbarrier::complete_tx::bytes.v2.b32 [%0], {%1,%2}, [%3];"
               :: "r"(a), "r"(x), "r"(y), "r"(mb) : "memory");
}
__device__ __forceinline__ void st_async_v4(uint32_t a, uint32_t x, uint32_t y, uint32_t z, uint32_t w, uint32_t mb) {
  asm volatile("st.async.weak.shared::cluster.mbarrier::complete_tx::bytes.v4.b32 [%0], {%1,%2,%3,%4}, [%5];"
               :: "r"(a), "r"(x), "r"(y), "r"(z), "r"(w), "r"(mb) : "memory");
}
__device__ __forceinline__ void bulk_g2s(uint32_t dst, const void* src, uint32_t bytes, uint32_t mb) {
  asm volatile("cp.async.bulk.shared::cluster.global.mbarrier::complete_tx::bytes [%0], [%1], %2, [%3];"
               :: "r"(dst), "l"(src), "r"(bytes), "r"(mb) : "memory");
}
__device__ __forceinline__ void cp_async16(uint32_t dst, const void* src) {
  asm volatile("cp.async.cg.shared.global [%0], [%1], 16;" :: "r"(dst), "l"(src) : "memory");
}
__device__ __forceinline__ void cp_async_wait_all() { asm volatile("cp.async.wait_all;" ::: "memory"); }
__device__ __forceinline__ void fence_proxy_async() { asm volatile("fence.proxy.async.shared::cta;" ::: "memory"); }
__device__ __forceinline__ void bar_sync(int id, int n) { asm volatile("bar.sync %0, %1;" :: "r"(id), "r"(n) : "memory"); }
__device__ __forceinline__ void bar_arrive(int id, int n) { asm volatile("bar.arrive %0, %1;" :: "r"(id), "r"(n) : "memory"); }
__device__ __forceinline__ void cluster_sync_all() {
  asm volatile("barrier.cluster.arrive.release.aligned; barrier.cluster.wait.acquire.aligned;" ::: "memory");
}
__device__ __forceinline__ void ldsm_x4(uint32_t (&r)[4], uint32_t a) {
  asm volatile("ldmatrix.sync.aligned.m8n8.x4.shared.b16 {%0,%1,%2,%3}, [%4];"
               : "=r"(r[0]), "=r"(r[1]), "=r"(r[2]), "=r"(r[3]) : "r"(a) : "memory");
}
__device__ __forceinline__ void ldsm_x4_t(uint32_t (&r)[4], uint32_t a) {
  asm volatile("ldmatrix.sync.aligned.m8n8.x4.trans.shared.b16 {%0,%1,%2,%3}, [%4];"
               : "=r"(r[0]), "=r"(r[1]), "=r"(r[2]), "=r"(r[3]) : "r"(a) : "memory");
}
template <int IMM> __device__ __forceinline__ void ldsm_x4_i(uint32_t (&r)[4], uint32_t a) {
  asm volatile("ldmatrix.sync.aligned.m8n8.x4.shared.b16 {%0,%1,%2,%3}, [%4+%5];"
               : "=r"(r[0]), "=r"(r[1]), "=r"(r[2]), "=r"(r[3]) : "r"(a), "n"(IMM) : "memory");
}
template <int IMM> __device__ __forceinline__ void ldsm_x4_t_i(uint32_t (&r)[4], uint32_t a) {
  asm volatile("ldmatrix.sync.aligned.m8n8.x4.trans.shared.b16 {%0,%1,%2,%3}, [%4+%5];"
               : "=r"(r[0]), "=r"(r[1]), "=r"(r[2]), "=r"(r[3]) : "r"(a), "n"(IMM) : "memory");
}
template <int IMM> __device__ __forceinline__ uint4 lds128_i(uint32_t a) {
  uint4 v; asm volatile("ld.shared.v4.u32 {%0,%1,%2,%3}, [%4+%5];" : "=r"(v.x), "=r"(v.y), "=r"(v.z), "=r"(v.w) : "r"(a), "n"(IMM) : "memory"); return v;
}
template <int IMM> __device__ __forceinline__ uint2 lds64_i(uint32_t a) {
  uint2 v; asm volatile("ld.shared.v2.u32 {%0,%1}, [%2+%3];" : "=r"(v.x), "=r"(v.y) : "r"(a), "n"(IMM) : "memory"); return v;
}
template <int IMM> __device__ __forceinline__ void sts128_i(uint32_t a, uint32_t x, uint32_t y, uint32_t z, uint32_t w) {
  asm volatile("st.shared.v4.u32 [%0+%5], {%1,%2,%3,%4};" :: "r"(a), "r"(x), "r"(y), "r"(z), "r"(w), "n"(IMM) : "memory");
}
template <int IMM> __device__ __forceinline__ void sts64_i(uint32_t a, uint32_t x, uint32_t y) {
  asm volatile("st.shared.v2.u32 [%0+%3], {%1,%2};" :: "r"(a), "r"(x), "r"(y), "n"(IMM) : "memory");
}
template <int IMM> __device__ __forceinline__ void st_async_v2_i(uint32_t a, uint32_t x, uint32_t y, uint32_t mb) {
  asm volatile("st.async.weak.shared::cluster.mbarrier::complete_tx::bytes.v2.b32 [%0+%4], {%1,%2}, [%3];"
               :: "r"(a), "r"(x), "r"(y), "r"(mb), "n"(IMM) : "memory");
}
template <int IMM> __device__ __forceinline__ uint4 ld_relaxed_v4_i(const void* p) {
  uint4 v; asm volatile("ld.relaxed.gpu.global.v4.u32 {%0,%1,%2,%3}, [%4+%5];" : "=r"(v.x), "=r"(v.y), "=r"(v.z), "=r"(v.w) : "l"(p), "n"(IMM) : "memory"); return v;
}
template <int I, int N, class F> __device__ __forceinline__ void static_for(F&& f) {
  if constexpr (I < N) { f(std::integral_constant<int, I>{}); static_for<I + 1, N>(f); }
}
__device__ __forceinline__ uint32_t movm_t(uint32_t a) {
  uint32_t d; asm volatile("movmatrix.sync.aligned.m8n8.trans.b16 %0, %1;" : "=r"(d) : "r"(a)); return d;
}
__device__ __forceinline__ void mma16816(float (&d)[4], uint32_t a0, uint32_t a1, uint32_t a2, uint32_t a3, uint32_t b0, uint32_t b1) {
  asm volatile("mma.sync.aligned.m16n8k16.row.col.f32.bf16.bf16.f32 {%0,%1,%2,%3}, {%4,%5,%6,%7}, {%8,%9}, {%0,%1,%2,%3};"
               : "+f"(d[0]), "+f"(d[1]), "+f"(d[2]), "+f"(d[3]) : "r"(a0), "r"(a1), "r"(a2), "r"(a3), "r"(b0), "r"(b1));
}
__device__ __forceinline__ uint32_t pack_bf16(float lo, float hi) {
  uint32_t d; asm("cvt.rn.bf16x2.f32 %0, %1, %2;" : "=r"(d) : "f"(hi), "f"(lo)); return d;
}
__device__ __forceinline__ float bf_lo(uint32_t w) { return __uint_as_float(w << 16); }
__device__ __forceinline__ float bf_hi(uint32_t w) { return __uint_as_float(w & 0xffff0000u); }
__device__ __forceinline__ uint4 lds128(uint32_t a) {
  uint4 v; asm volatile("ld.shared.v4.u32 {%0,%1,%2,%3}, [%4];" : "=r"(v.x), "=r"(v.y), "=r"(v.z), "=r"(v.w) : "r"(a) : "memory"); return v;
}
__device__ __forceinline__ uint2 lds64(uint32_t a) {
  uint2 v; asm volatile("ld.shared.v2.u32 {%0,%1}, [%2];" : "=r"(v.x), "=r"(v.y) : "r"(a) : "memory"); return v;
}
__device__ __forceinline__ void sts128(uint32_t a, uint32_t x, uint32_t y, uint32_t z, uint32_t w) {
  asm volatile("st.shared.v4.u32 [%0], {%1,%2,%3,%4};" :: "r"(a), "r"(x), "r"(y), "r"(z), "r"(w) : "memory");
}
__device__ __forceinline__ void sts64(uint32_t a, uint32_t x, uint32_t y) {
  asm volatile("st.shared.v2.u32 [%0], {%1,%2};" :: "r"(a), "r"(x), "r"(y) : "memory");
}
__device__ __forceinline__ uint4 ld_relaxed_v4(const void* p) {
  uint4 v; asm volatile("ld.relaxed.gpu.global.v4.u32 {%0,%1,%2,%3}, [%4];" : "=r"(v.x), "=r"(v.y), "=r"(v.z), "=r"(v.w) : "l"(p) : "memory"); return v;
}
__device__ __forceinline__ uint32_t ld_relaxed_u32(const void* p) {
  uint32_t v; asm volatile("ld.relaxed.gpu.global.u32 %0, [%1];" : "=r"(v) : "l"(p) : "memory"); return v;
}
__device__ __forceinline__ void st_relaxed_v2(void* p, uint32_t a, uint32_t b) {
  asm volatile("st.relaxed.gpu.global.v2.u32 [%0], {%1,%2};" :: "l"(p), "r"(a), "r"(b) : "memory");
}
__device__ __forceinline__ void st_relaxed_u32(void* p, uint32_t v) {
  asm volatile("st.relaxed.gpu.global.u32 [%0], %1;" :: "l"(p), "r"(v) : "memory");
}
__device__ __forceinline__ void st_release_u32(void* p, uint32_t v) {
  asm volatile("st.release.gpu.global.u32 [%0], %1;" :: "l"(p), "r"(v) : "memory");
}
__device__ __forceinline__ void red_release_inc(void* p) { asm volatile("red.release.gpu.global.add.u32 [%0], 1;" :: "l"(p) : "memory"); }
__device__ __forceinline__ uint32_t clk32() { uint32_t c; asm volatile("mov.u32 %0, %%clock;" : "=r"(c) :: "memory"); return c; }
__device__ __forceinline__ uint32_t clkdep(uint32_t v) {
  uint32_t c; asm volatile("{.reg .pred p; setp.eq.u32 p, %1, 0xdeadbeef; @p trap; mov.u32 %0, %%clock;}" : "=r"(c) : "r"(v) : "memory"); return c;
}
__device__ __forceinline__ void wgmma_fence() { asm volatile("wgmma.fence.sync.aligned;" ::: "memory"); }
__device__ __forceinline__ void wgmma_commit() { asm volatile("wgmma.commit_group.sync.aligned;" ::: "memory"); }
template <int N> __device__ __forceinline__ void wgmma_wait() { asm volatile("wgmma.wait_group.sync.aligned %0;" :: "n"(N) : "memory"); }
__device__ __forceinline__ void wgmma_n8_ss_ta(float (&d)[4], uint64_t da, uint64_t db, int acc) {
  asm volatile("{\n.reg .pred p;\nsetp.ne.b32 p, %6, 0;\n"
               "wgmma.mma_async.sync.aligned.m64n8k16.f32.bf16.bf16 {%0,%1,%2,%3}, %4, %5, p, 1, 1, 1, 0;\n}\n"
               : "+f"(d[0]), "+f"(d[1]), "+f"(d[2]), "+f"(d[3]) : "l"(da), "l"(db), "r"(acc));
}
__device__ __forceinline__ uint64_t make_desc(uint32_t saddr, uint32_t lbo_bytes, uint32_t sbo_bytes, uint32_t swz) {
  return (uint64_t)((saddr & 0x3FFFF) >> 4) | ((uint64_t)(lbo_bytes >> 4) << 16) | ((uint64_t)(sbo_bytes >> 4) << 32) | ((uint64_t)swz << 62);
}


__device__ __forceinline__ bool elect_one() {
  uint32_t p; asm volatile("{\n.reg .pred p;\nelect.sync _|p, 0xffffffff;\nselp.u32 %0, 1, 0, p;\n}" : "=r"(p)); return p;
}
__device__ __forceinline__ void tma_load_3d(uint32_t dst, const CUtensorMap* tm, int c0, int c1, int c2, uint32_t mb) {
  asm volatile("cp.async.bulk.tensor.3d.shared::cluster.global.mbarrier::complete_tx::bytes [%0], [%1, {%3, %4, %5}], [%2];"
               :: "r"(dst), "l"(tm), "r"(mb), "r"(c0), "r"(c1), "r"(c2) : "memory");
}
__device__ __forceinline__ void tma_load_2d(uint32_t dst, const CUtensorMap* tm, int c0, int c1, uint32_t mb) {
  asm volatile("cp.async.bulk.tensor.2d.shared::cluster.global.mbarrier::complete_tx::bytes [%0], [%1, {%3, %4}], [%2];"
               :: "r"(dst), "l"(tm), "r"(mb), "r"(c0), "r"(c1) : "memory");
}
__device__ __forceinline__ void bulk_s2g(void* dst, uint32_t src, uint32_t bytes) {
  asm volatile("cp.async.bulk.global.shared::cta.bulk_group [%0], [%1], %2;" :: "l"(dst), "r"(src), "r"(bytes) : "memory");
}
__device__ __forceinline__ uint64_t policy_evict_first() {
  uint64_t p; asm volatile("createpolicy.fractional.L2::evict_first.b64 %0, 1.0;" : "=l"(p)); return p;
}
__device__ __forceinline__ void bulk_s2g_hint(void* dst, uint32_t src, uint32_t bytes, uint64_t pol) {
  asm volatile("cp.async.bulk.global.shared::cta.bulk_group.L2::cache_hint [%0], [%1], %2, %3;" :: "l"(dst), "r"(src), "r"(bytes), "l"(pol) : "memory");
}
__device__ __forceinline__ void bulk_commit() { asm volatile("cp.async.bulk.commit_group;" ::: "memory"); }
template <int N> __device__ __forceinline__ void bulk_wait_read() { asm volatile("cp.async.bulk.wait_group.read %0;" :: "n"(N) : "memory"); }
template <int N> __device__ __forceinline__ void bulk_wait() { asm volatile("cp.async.bulk.wait_group %0;" :: "n"(N) : "memory"); }
__device__ __forceinline__ void stsm_x4(uint32_t a, uint32_t r0, uint32_t r1, uint32_t r2, uint32_t r3) {
  asm volatile("stmatrix.sync.aligned.m8n8.x4.shared.b16 [%0], {%1,%2,%3,%4};" :: "r"(a), "r"(r0), "r"(r1), "r"(r2), "r"(r3) : "memory");
}
__device__ __forceinline__ void stsm_x2(uint32_t a, uint32_t r0, uint32_t r1) {
  asm volatile("stmatrix.sync.aligned.m8n8.x2.shared.b16 [%0], {%1,%2};" :: "r"(a), "r"(r0), "r"(r1) : "memory");
}
__device__ __forceinline__ void ldsm_x2(uint32_t (&r)[2], uint32_t a) {
  asm volatile("ldmatrix.sync.aligned.m8n8.x2.shared.b16 {%0,%1}, [%2];" : "=r"(r[0]), "=r"(r[1]) : "r"(a) : "memory");
}
__device__ __forceinline__ void ldsm_x2_t(uint32_t (&r)[2], uint32_t a) {
  asm volatile("ldmatrix.sync.aligned.m8n8.x2.trans.shared.b16 {%0,%1}, [%2];" : "=r"(r[0]), "=r"(r[1]) : "r"(a) : "memory");
}
__device__ __forceinline__ float bf16r(float x) { return __uint_as_float(pack_bf16(0.f, x) & 0xffff0000u); }
__device__ __forceinline__ void bf16r2(float& a, float& b) { const uint32_t w = pack_bf16(a, b); a = bf_lo(w); b = bf_hi(w); }
__device__ __forceinline__ float rcpf(float x) { float r; asm("rcp.approx.ftz.f32 %0, %1;" : "=f"(r) : "f"(x)); return r; }
__device__ __forceinline__ float ex2f(float x) { float e; asm("ex2.approx.ftz.f32 %0, %1;" : "=f"(e) : "f"(x)); return e; }
__device__ __forceinline__ void prefetch_tmap(const CUtensorMap* tm) { asm volatile("prefetch.tensormap [%0];" :: "l"(tm) : "memory"); }

#ifdef TIMELINE
__device__ unsigned long long g_tl[2 * 64];
__device__ unsigned g_step[2 * 64 * 96 * 4];
__device__ unsigned long long g_log[2 * 132 * 64 * 2 + 2];
__device__ unsigned long long g_tl2[4 * 64];
__device__ __forceinline__ unsigned long long gtime() { unsigned long long t; asm volatile("mov.u64 %0, %%globaltimer;" : "=l"(t)); return t; }
#define TL_BEGIN(id) do { if (threadIdx.x == 0) atomicMin(&g_tl[2 * (id)], gtime()); } while (0)
#define TL_END(id) do { if ((threadIdx.x & 31) == 0) atomicMax(&g_tl[2 * (id) + 1], gtime()); } while (0)
#define TL_ACC(idx, t0) do { if (threadIdx.x == 0 && m >= 4 && m < 11) { atomicAdd(&g_tl2[idx], gtime() - (t0)); atomicAdd(&g_tl2[(idx) + 1], 1ull); } } while (0)
#define TL_NOW() gtime()
#define TL2(idx) asm volatile("{\n.reg .pred p;\nsetp.eq.u32 p, %2, 0;\n@p red.relaxed.gpu.global.max.u64 [%0], %1;\n}" :: "l"(&g_tl2[idx]), "l"(gtime()), "r"(threadIdx.x) : "memory")
#define TLW(idx) asm volatile("{\n.reg .pred p;\nsetp.eq.u32 p, %2, 0;\n@p red.relaxed.gpu.global.max.u64 [%0], %1;\n@p red.relaxed.gpu.global.add.u64 [%0+128], %1;\n}" :: "l"(&g_tl2[idx]), "l"(gtime() - g_tl0), "r"(threadIdx.x & 31) : "memory")
#define TL_BEGIN0(id) atomicMin(&g_tl[2 * (id)], gtime())
#else
#define TL_ACC(idx, t0)
#define TL_NOW() 0ull
#define TL2(idx)
#define TL_BEGIN0(id)
#define TLW(idx)
#define TL_BEGIN(id)
#define TL_END(id)
#endif
template <int TA, int TB> __device__ __forceinline__ void wgmma_n24(float (&d)[12], uint64_t da, uint64_t db, int acc) {
  asm volatile("{\n.reg .pred p;\nsetp.ne.b32 p, %14, 0;\n"
    "wgmma.mma_async.sync.aligned.m64n24k16.f32.bf16.bf16 {%0, %1, %2, %3, %4, %5, %6, %7, %8, %9, %10, %11}, %12, %13, p, 1, 1, %15, %16;\n}\n"
    : "+f"(d[0]), "+f"(d[1]), "+f"(d[2]), "+f"(d[3]), "+f"(d[4]), "+f"(d[5]), "+f"(d[6]), "+f"(d[7]), "+f"(d[8]), "+f"(d[9]), "+f"(d[10]), "+f"(d[11])
    : "l"(da), "l"(db), "r"(acc), "n"(TA), "n"(TB));
}

template <int TA, int TB> __device__ __forceinline__ void wgmma_n80(float (&d)[40], uint64_t da, uint64_t db, int acc) {
  asm volatile("{\n.reg .pred p;\nsetp.ne.b32 p, %42, 0;\n"
    "wgmma.mma_async.sync.aligned.m64n80k16.f32.bf16.bf16 {%0, %1, %2, %3, %4, %5, %6, %7, %8, %9, %10, %11, %12, %13, %14, %15, %16, %17, %18, %19, %20, %21, %22, %23, %24, %25, %26, %27, %28, %29, %30, %31, %32, %33, %34, %35, %36, %37, %38, %39}, %40, %41, p, 1, 1, %43, %44;\n}\n"
    : "+f"(d[0]), "+f"(d[1]), "+f"(d[2]), "+f"(d[3]), "+f"(d[4]), "+f"(d[5]), "+f"(d[6]), "+f"(d[7]), "+f"(d[8]), "+f"(d[9]), "+f"(d[10]), "+f"(d[11]), "+f"(d[12]), "+f"(d[13]), "+f"(d[14]), "+f"(d[15]), "+f"(d[16]), "+f"(d[17]), "+f"(d[18]), "+f"(d[19]), "+f"(d[20]), "+f"(d[21]), "+f"(d[22]), "+f"(d[23]), "+f"(d[24]), "+f"(d[25]), "+f"(d[26]), "+f"(d[27]), "+f"(d[28]), "+f"(d[29]), "+f"(d[30]), "+f"(d[31]), "+f"(d[32]), "+f"(d[33]), "+f"(d[34]), "+f"(d[35]), "+f"(d[36]), "+f"(d[37]), "+f"(d[38]), "+f"(d[39])
    : "l"(da), "l"(db), "r"(acc), "n"(TA), "n"(TB));
}

template <int TA, int TB> __device__ __forceinline__ void wgmma_n128(float (&d)[64], uint64_t da, uint64_t db, int acc) {
  asm volatile("{\n.reg .pred p;\nsetp.ne.b32 p, %66, 0;\n"
    "wgmma.mma_async.sync.aligned.m64n128k16.f32.bf16.bf16 {%0, %1, %2, %3, %4, %5, %6, %7, %8, %9, %10, %11, %12, %13, %14, %15, %16, %17, %18, %19, %20, %21, %22, %23, %24, %25, %26, %27, %28, %29, %30, %31, %32, %33, %34, %35, %36, %37, %38, %39, %40, %41, %42, %43, %44, %45, %46, %47, %48, %49, %50, %51, %52, %53, %54, %55, %56, %57, %58, %59, %60, %61, %62, %63}, %64, %65, p, 1, 1, %67, %68;\n}\n"
    : "+f"(d[0]), "+f"(d[1]), "+f"(d[2]), "+f"(d[3]), "+f"(d[4]), "+f"(d[5]), "+f"(d[6]), "+f"(d[7]), "+f"(d[8]), "+f"(d[9]), "+f"(d[10]), "+f"(d[11]), "+f"(d[12]), "+f"(d[13]), "+f"(d[14]), "+f"(d[15]), "+f"(d[16]), "+f"(d[17]), "+f"(d[18]), "+f"(d[19]), "+f"(d[20]), "+f"(d[21]), "+f"(d[22]), "+f"(d[23]), "+f"(d[24]), "+f"(d[25]), "+f"(d[26]), "+f"(d[27]), "+f"(d[28]), "+f"(d[29]), "+f"(d[30]), "+f"(d[31]), "+f"(d[32]), "+f"(d[33]), "+f"(d[34]), "+f"(d[35]), "+f"(d[36]), "+f"(d[37]), "+f"(d[38]), "+f"(d[39]), "+f"(d[40]), "+f"(d[41]), "+f"(d[42]), "+f"(d[43]), "+f"(d[44]), "+f"(d[45]), "+f"(d[46]), "+f"(d[47]), "+f"(d[48]), "+f"(d[49]), "+f"(d[50]), "+f"(d[51]), "+f"(d[52]), "+f"(d[53]), "+f"(d[54]), "+f"(d[55]), "+f"(d[56]), "+f"(d[57]), "+f"(d[58]), "+f"(d[59]), "+f"(d[60]), "+f"(d[61]), "+f"(d[62]), "+f"(d[63])
    : "l"(da), "l"(db), "r"(acc), "n"(TA), "n"(TB));
}

template <int TA, int TB> __device__ __forceinline__ void wgmma_n192(float (&d)[96], uint64_t da, uint64_t db, int acc) {
  asm volatile("{\n.reg .pred p;\nsetp.ne.b32 p, %98, 0;\n"
    "wgmma.mma_async.sync.aligned.m64n192k16.f32.bf16.bf16 {%0, %1, %2, %3, %4, %5, %6, %7, %8, %9, %10, %11, %12, %13, %14, %15, %16, %17, %18, %19, %20, %21, %22, %23, %24, %25, %26, %27, %28, %29, %30, %31, %32, %33, %34, %35, %36, %37, %38, %39, %40, %41, %42, %43, %44, %45, %46, %47, %48, %49, %50, %51, %52, %53, %54, %55, %56, %57, %58, %59, %60, %61, %62, %63, %64, %65, %66, %67, %68, %69, %70, %71, %72, %73, %74, %75, %76, %77, %78, %79, %80, %81, %82, %83, %84, %85, %86, %87, %88, %89, %90, %91, %92, %93, %94, %95}, %96, %97, p, 1, 1, %99, %100;\n}\n"
    : "+f"(d[0]), "+f"(d[1]), "+f"(d[2]), "+f"(d[3]), "+f"(d[4]), "+f"(d[5]), "+f"(d[6]), "+f"(d[7]), "+f"(d[8]), "+f"(d[9]), "+f"(d[10]), "+f"(d[11]), "+f"(d[12]), "+f"(d[13]), "+f"(d[14]), "+f"(d[15]), "+f"(d[16]), "+f"(d[17]), "+f"(d[18]), "+f"(d[19]), "+f"(d[20]), "+f"(d[21]), "+f"(d[22]), "+f"(d[23]), "+f"(d[24]), "+f"(d[25]), "+f"(d[26]), "+f"(d[27]), "+f"(d[28]), "+f"(d[29]), "+f"(d[30]), "+f"(d[31]), "+f"(d[32]), "+f"(d[33]), "+f"(d[34]), "+f"(d[35]), "+f"(d[36]), "+f"(d[37]), "+f"(d[38]), "+f"(d[39]), "+f"(d[40]), "+f"(d[41]), "+f"(d[42]), "+f"(d[43]), "+f"(d[44]), "+f"(d[45]), "+f"(d[46]), "+f"(d[47]), "+f"(d[48]), "+f"(d[49]), "+f"(d[50]), "+f"(d[51]), "+f"(d[52]), "+f"(d[53]), "+f"(d[54]), "+f"(d[55]), "+f"(d[56]), "+f"(d[57]), "+f"(d[58]), "+f"(d[59]), "+f"(d[60]), "+f"(d[61]), "+f"(d[62]), "+f"(d[63]), "+f"(d[64]), "+f"(d[65]), "+f"(d[66]), "+f"(d[67]), "+f"(d[68]), "+f"(d[69]), "+f"(d[70]), "+f"(d[71]), "+f"(d[72]), "+f"(d[73]), "+f"(d[74]), "+f"(d[75]), "+f"(d[76]), "+f"(d[77]), "+f"(d[78]), "+f"(d[79]), "+f"(d[80]), "+f"(d[81]), "+f"(d[82]), "+f"(d[83]), "+f"(d[84]), "+f"(d[85]), "+f"(d[86]), "+f"(d[87]), "+f"(d[88]), "+f"(d[89]), "+f"(d[90]), "+f"(d[91]), "+f"(d[92]), "+f"(d[93]), "+f"(d[94]), "+f"(d[95])
    : "l"(da), "l"(db), "r"(acc), "n"(TA), "n"(TB));
}

template <int TA, int TB> __device__ __forceinline__ void wgmma_n256(float (&d)[128], uint64_t da, uint64_t db, int acc) {
  asm volatile("{\n.reg .pred p;\nsetp.ne.b32 p, %130, 0;\n"
    "wgmma.mma_async.sync.aligned.m64n256k16.f32.bf16.bf16 {%0, %1, %2, %3, %4, %5, %6, %7, %8, %9, %10, %11, %12, %13, %14, %15, %16, %17, %18, %19, %20, %21, %22, %23, %24, %25, %26, %27, %28, %29, %30, %31, %32, %33, %34, %35, %36, %37, %38, %39, %40, %41, %42, %43, %44, %45, %46, %47, %48, %49, %50, %51, %52, %53, %54, %55, %56, %57, %58, %59, %60, %61, %62, %63, %64, %65, %66, %67, %68, %69, %70, %71, %72, %73, %74, %75, %76, %77, %78, %79, %80, %81, %82, %83, %84, %85, %86, %87, %88, %89, %90, %91, %92, %93, %94, %95, %96, %97, %98, %99, %100, %101, %102, %103, %104, %105, %106, %107, %108, %109, %110, %111, %112, %113, %114, %115, %116, %117, %118, %119, %120, %121, %122, %123, %124, %125, %126, %127}, %128, %129, p, 1, 1, %131, %132;\n}\n"
    : "+f"(d[0]), "+f"(d[1]), "+f"(d[2]), "+f"(d[3]), "+f"(d[4]), "+f"(d[5]), "+f"(d[6]), "+f"(d[7]), "+f"(d[8]), "+f"(d[9]), "+f"(d[10]), "+f"(d[11]), "+f"(d[12]), "+f"(d[13]), "+f"(d[14]), "+f"(d[15]), "+f"(d[16]), "+f"(d[17]), "+f"(d[18]), "+f"(d[19]), "+f"(d[20]), "+f"(d[21]), "+f"(d[22]), "+f"(d[23]), "+f"(d[24]), "+f"(d[25]), "+f"(d[26]), "+f"(d[27]), "+f"(d[28]), "+f"(d[29]), "+f"(d[30]), "+f"(d[31]), "+f"(d[32]), "+f"(d[33]), "+f"(d[34]), "+f"(d[35]), "+f"(d[36]), "+f"(d[37]), "+f"(d[38]), "+f"(d[39]), "+f"(d[40]), "+f"(d[41]), "+f"(d[42]), "+f"(d[43]), "+f"(d[44]), "+f"(d[45]), "+f"(d[46]), "+f"(d[47]), "+f"(d[48]), "+f"(d[49]), "+f"(d[50]), "+f"(d[51]), "+f"(d[52]), "+f"(d[53]), "+f"(d[54]), "+f"(d[55]), "+f"(d[56]), "+f"(d[57]), "+f"(d[58]), "+f"(d[59]), "+f"(d[60]), "+f"(d[61]), "+f"(d[62]), "+f"(d[63]), "+f"(d[64]), "+f"(d[65]), "+f"(d[66]), "+f"(d[67]), "+f"(d[68]), "+f"(d[69]), "+f"(d[70]), "+f"(d[71]), "+f"(d[72]), "+f"(d[73]), "+f"(d[74]), "+f"(d[75]), "+f"(d[76]), "+f"(d[77]), "+f"(d[78]), "+f"(d[79]), "+f"(d[80]), "+f"(d[81]), "+f"(d[82]), "+f"(d[83]), "+f"(d[84]), "+f"(d[85]), "+f"(d[86]), "+f"(d[87]), "+f"(d[88]), "+f"(d[89]), "+f"(d[90]), "+f"(d[91]), "+f"(d[92]), "+f"(d[93]), "+f"(d[94]), "+f"(d[95]), "+f"(d[96]), "+f"(d[97]), "+f"(d[98]), "+f"(d[99]), "+f"(d[100]), "+f"(d[101]), "+f"(d[102]), "+f"(d[103]), "+f"(d[104]), "+f"(d[105]), "+f"(d[106]), "+f"(d[107]), "+f"(d[108]), "+f"(d[109]), "+f"(d[110]), "+f"(d[111]), "+f"(d[112]), "+f"(d[113]), "+f"(d[114]), "+f"(d[115]), "+f"(d[116]), "+f"(d[117]), "+f"(d[118]), "+f"(d[119]), "+f"(d[120]), "+f"(d[121]), "+f"(d[122]), "+f"(d[123]), "+f"(d[124]), "+f"(d[125]), "+f"(d[126]), "+f"(d[127])
    : "l"(da), "l"(db), "r"(acc), "n"(TA), "n"(TB));
}

template <int TB> __device__ __forceinline__ void wgmma_rs_n24(float (&d)[12], uint32_t a0, uint32_t a1, uint32_t a2, uint32_t a3, uint64_t db, int acc) {
  asm volatile("{\n.reg .pred p;\nsetp.ne.b32 p, %17, 0;\n"
    "wgmma.mma_async.sync.aligned.m64n24k16.f32.bf16.bf16 {%0, %1, %2, %3, %4, %5, %6, %7, %8, %9, %10, %11}, {%12, %13, %14, %15}, %16, p, 1, 1, %18;\n}\n"
    : "+f"(d[0]), "+f"(d[1]), "+f"(d[2]), "+f"(d[3]), "+f"(d[4]), "+f"(d[5]), "+f"(d[6]), "+f"(d[7]), "+f"(d[8]), "+f"(d[9]), "+f"(d[10]), "+f"(d[11])
    : "r"(a0), "r"(a1), "r"(a2), "r"(a3), "l"(db), "r"(acc), "n"(TB));
}

template <int TB> __device__ __forceinline__ void wgmma_rs_n40(float (&d)[20], uint32_t a0, uint32_t a1, uint32_t a2, uint32_t a3, uint64_t db, int acc) {
  asm volatile("{\n.reg .pred p;\nsetp.ne.b32 p, %25, 0;\n"
    "wgmma.mma_async.sync.aligned.m64n40k16.f32.bf16.bf16 {%0, %1, %2, %3, %4, %5, %6, %7, %8, %9, %10, %11, %12, %13, %14, %15, %16, %17, %18, %19}, {%20, %21, %22, %23}, %24, p, 1, 1, %26;\n}\n"
    : "+f"(d[0]), "+f"(d[1]), "+f"(d[2]), "+f"(d[3]), "+f"(d[4]), "+f"(d[5]), "+f"(d[6]), "+f"(d[7]), "+f"(d[8]), "+f"(d[9]), "+f"(d[10]), "+f"(d[11]), "+f"(d[12]), "+f"(d[13]), "+f"(d[14]), "+f"(d[15]), "+f"(d[16]), "+f"(d[17]), "+f"(d[18]), "+f"(d[19])
    : "r"(a0), "r"(a1), "r"(a2), "r"(a3), "l"(db), "r"(acc), "n"(TB));
}

template <int TB> __device__ __forceinline__ void wgmma_rs_n192(float (&d)[96], uint32_t a0, uint32_t a1, uint32_t a2, uint32_t a3, uint64_t db, int acc) {
  asm volatile("{\n.reg .pred p;\nsetp.ne.b32 p, %101, 0;\n"
    "wgmma.mma_async.sync.aligned.m64n192k16.f32.bf16.bf16 {%0, %1, %2, %3, %4, %5, %6, %7, %8, %9, %10, %11, %12, %13, %14, %15, %16, %17, %18, %19, %20, %21, %22, %23, %24, %25, %26, %27, %28, %29, %30, %31, %32, %33, %34, %35, %36, %37, %38, %39, %40, %41, %42, %43, %44, %45, %46, %47, %48, %49, %50, %51, %52, %53, %54, %55, %56, %57, %58, %59, %60, %61, %62, %63, %64, %65, %66, %67, %68, %69, %70, %71, %72, %73, %74, %75, %76, %77, %78, %79, %80, %81, %82, %83, %84, %85, %86, %87, %88, %89, %90, %91, %92, %93, %94, %95}, {%96, %97, %98, %99}, %100, p, 1, 1, %102;\n}\n"
    : "+f"(d[0]), "+f"(d[1]), "+f"(d[2]), "+f"(d[3]), "+f"(d[4]), "+f"(d[5]), "+f"(d[6]), "+f"(d[7]), "+f"(d[8]), "+f"(d[9]), "+f"(d[10]), "+f"(d[11]), "+f"(d[12]), "+f"(d[13]), "+f"(d[14]), "+f"(d[15]), "+f"(d[16]), "+f"(d[17]), "+f"(d[18]), "+f"(d[19]), "+f"(d[20]), "+f"(d[21]), "+f"(d[22]), "+f"(d[23]), "+f"(d[24]), "+f"(d[25]), "+f"(d[26]), "+f"(d[27]), "+f"(d[28]), "+f"(d[29]), "+f"(d[30]), "+f"(d[31]), "+f"(d[32]), "+f"(d[33]), "+f"(d[34]), "+f"(d[35]), "+f"(d[36]), "+f"(d[37]), "+f"(d[38]), "+f"(d[39]), "+f"(d[40]), "+f"(d[41]), "+f"(d[42]), "+f"(d[43]), "+f"(d[44]), "+f"(d[45]), "+f"(d[46]), "+f"(d[47]), "+f"(d[48]), "+f"(d[49]), "+f"(d[50]), "+f"(d[51]), "+f"(d[52]), "+f"(d[53]), "+f"(d[54]), "+f"(d[55]), "+f"(d[56]), "+f"(d[57]), "+f"(d[58]), "+f"(d[59]), "+f"(d[60]), "+f"(d[61]), "+f"(d[62]), "+f"(d[63]), "+f"(d[64]), "+f"(d[65]), "+f"(d[66]), "+f"(d[67]), "+f"(d[68]), "+f"(d[69]), "+f"(d[70]), "+f"(d[71]), "+f"(d[72]), "+f"(d[73]), "+f"(d[74]), "+f"(d[75]), "+f"(d[76]), "+f"(d[77]), "+f"(d[78]), "+f"(d[79]), "+f"(d[80]), "+f"(d[81]), "+f"(d[82]), "+f"(d[83]), "+f"(d[84]), "+f"(d[85]), "+f"(d[86]), "+f"(d[87]), "+f"(d[88]), "+f"(d[89]), "+f"(d[90]), "+f"(d[91]), "+f"(d[92]), "+f"(d[93]), "+f"(d[94]), "+f"(d[95])
    : "r"(a0), "r"(a1), "r"(a2), "r"(a3), "l"(db), "r"(acc), "n"(TB));
}
constexpr uint32_t AR_ACC = 0;
constexpr uint32_t AR_TAB = 0x100000;
constexpr uint32_t AR_PROG = 0x101000;
__host__ __device__ constexpr uint32_t prog_off(int h, int j) { return AR_PROG + h * 128 + j * 4; }
constexpr uint32_t AR_CNT = 0x108000;
constexpr uint32_t AR_QUEUE = 0x109000;
constexpr uint32_t AR_SIZE = 0x10a000;

struct ChainArgs {
  const bf16* mem0;
  const uint2* xh;
  unsigned char *kg, *vg;
  unsigned char* arena;
  unsigned* go;
  uint32_t* dbg;
  uint32_t delay;
  int margin, pubrel;
  int tl;
};

namespace ch {
constexpr int OFF_WQ = 0;
constexpr int OFF_X = 81920;
constexpr int OFF_MEM = OFF_X + 40960;
constexpr int OFF_WO = OFF_MEM + 10240;
constexpr int WOK = 8 * 896;
constexpr int OFF_KV = OFF_WO + 10 * WOK;
constexpr int KVB = 5120;
constexpr int OFF_O = OFF_KV + 4 * KVB;
constexpr int OFF_Q = OFF_O + 1024;
constexpr int OFF_S = OFF_O + 3072;
constexpr int OFF_SR = OFF_S + 1536;
constexpr int OFF_LT = OFF_SR + 1280;
constexpr int OFF_BAR = OFF_LT + 512;
constexpr int SMEM = OFF_BAR + 256;
static_assert(SMEM <= 232448, "smem");
constexpr int MB_S = OFF_BAR, MB_O = OFF_BAR + 8, MB_X = OFF_BAR + 16;
constexpr int MB_K = OFF_BAR + 128, MB_V = MB_K + 16, MB_Q = MB_K + 32, MB_R = MB_K + 48;
constexpr int SC_IN = OFF_BAR + 64;
constexpr int SC_MX = OFF_S;
constexpr int SC_TW = OFF_BAR + 48;
constexpr int SC_W = OFF_BAR + 96;
constexpr int WOS = 448;
enum { B_MEM0 = 1, B_QK, B_SL, B_V, B_O, B_RED, B_X, B_C, B_H, B_MEM1, B_A, B_G, B_E };
#ifndef NQ1
#define NQ1 14
#endif
#ifndef NQ0
#define NQ0 8
#endif
#ifndef NP0
#define NP0 6
#endif
#ifndef NWO
#define NWO 5
#endif
#ifndef NWP
#define NWP 4
#endif
#ifndef NB0
#define NB0 3
#endif
#ifndef BBS
#define BBS 100
#endif
#ifndef VSYNC
#define VSYNC 0
#endif
#ifndef XPOS
#define XPOS 0
#endif
#ifndef XPD
#define XPD 300
#endif
#ifndef WOF
#define WOF 0
#endif
#ifndef XBYTES
#define XBYTES 36864
#endif
#ifndef NRT
#define NRT 7
#endif
#ifndef NRF
#define NRF 2
#endif
#ifndef NPM0
#define NPM0 2
#endif
#ifndef NPM1
#define NPM1 2
#endif
#ifndef RSYNC
#define RSYNC 1
#endif
#ifndef PFK
#define PFK 3
#endif
#ifndef PA0
#define PA0 3
#endif
#ifndef PA1
#define PA1 0
#endif
#ifndef PB0
#define PB0 7
#endif
#ifndef PB1
#define PB1 5
#endif
#ifndef PQE
#define PQE 1
#endif
#ifndef XT
#define XT 38
#endif
static_assert(NPM0 >= 2 && NPM1 >= 2, "the K / V blocks live in the last two k-steps of Wo");
}

#ifndef CHAIN_TIMING
#define CHAIN_TIMING 0
#endif
#if CHAIN_TIMING
#ifndef TR0
#define TR0 41
#endif
#ifndef TSMASK
#define TSMASK 0xffff
#endif
#define TSV(i, v) do { if ((TSMASK >> (i)) & 1) asm volatile("st.shared.u32 [%0+%1], %2;" :: "r"(tsb), "n"((i) * 4), "r"(v) : "memory"); } while (0)
#define TS(i) TSV(i, clk32())
#define TS_SETUP() const uint32_t tsb = sb + ((s == TR0 || s == TR0 + 1) ? OFF_BAR + 128 + ((s - TR0) * 12 + warp) * 48 : OFF_SR + 1152)
#else
#define TS(i)
#define TSV(i, v)
#define TS_SETUP()
#endif
#ifndef POLL_DELAY
#define POLL_DELAY 620
#endif
#ifndef XN
#define XN 40
#endif
#ifndef PF0
#define PF0 8
#endif
#ifndef PFS
#define PFS 3
#endif
#ifndef XDELAY
#define XDELAY 0
#endif
#ifndef NOKM
#define NOKM 0
#endif
#ifndef PFX
#define PFX 3
#endif
#ifndef NVE
#define NVE 8
#endif
#ifndef VET
#define VET 19
#endif
#ifndef MEMFIRST
#define MEMFIRST 0
#endif
#ifndef PM1
#define PM1 1
#endif
#ifndef GD1
#define GD1 30
#endif
#ifndef GD2
#define GD2 150
#endif
#ifndef CEARLY
#define CEARLY 0
#endif
#ifndef NPL
#define NPL 2
#endif
#ifndef NP1
#define NP1 (NQ1 < 6 ? NQ1 : 6)
#endif
#ifndef PFACC
#define PFACC 1
#endif
template <int V> using IC = std::integral_constant<int, V>;
__device__ __forceinline__ uint32_t clk_v() { uint64_t c; asm volatile("mov.u64 %0, %%clock64;" : "=l"(c) :: "memory"); return (uint32_t)c; }
__device__ __forceinline__ int fresh(int x) { int y; asm volatile("shfl.sync.bfly.b32 %0, %1, 0, 0x1f, 0xffffffff;" : "=r"(y) : "r"(x)); return y; }
#define SFENCE2(x, d) asm volatile("{\n.reg .pred p;\nsetp.eq.u32 p, %0, 0x7fffffff;\n@p st.shared.u32 [%0], %1;\n}" :: "r"(x), "r"(d) : "memory")
#define SFENCE(x) asm volatile("{\n.reg .pred p;\nsetp.eq.u32 p, %0, 0x7fffffff;\n@p st.shared.u32 [%0], %0;\n}" :: "r"(x) : "memory")
template <int I> __device__ __forceinline__ void bbfence(uint32_t x) {
  asm volatile("{\n.reg .pred p;\nsetp.eq.u32 p, %0, %1;\nL_%=:\n@p st.volatile.shared.u32 [%0], %0;\n@p bra.uni L_%=;\n}" :: "r"(x), "n"(4 * I) : "memory");
}
__device__ __forceinline__ float uniform_f(float x) { return __uint_as_float(__reduce_max_sync(0xffffffffu, __float_as_uint(x))); }

__device__ __forceinline__ void mma16816h(float (&d)[4], const uint32_t (&a)[4], uint32_t b0, uint32_t b1) {
  asm volatile("mma.sync.aligned.m16n8k16.row.col.f32.f16.f16.f32 {%0,%1,%2,%3}, {%4,%5,%6,%7}, {%8,%9}, {%0,%1,%2,%3};"
               : "+f"(d[0]), "+f"(d[1]), "+f"(d[2]), "+f"(d[3]) : "r"(a[0]), "r"(a[1]), "r"(a[2]), "r"(a[3]), "r"(b0), "r"(b1));
}
__device__ __forceinline__ void mma1688(float (&d)[4], uint32_t a0, uint32_t a1, uint32_t b0) {
  asm volatile("mma.sync.aligned.m16n8k8.row.col.f32.bf16.bf16.f32 {%0,%1,%2,%3}, {%4,%5}, {%6}, {%0,%1,%2,%3};"
               : "+f"(d[0]), "+f"(d[1]), "+f"(d[2]), "+f"(d[3]) : "r"(a0), "r"(a1), "r"(b0));
}
template <int OFF16, int ACC> __device__ __forceinline__ void wgmma_rs32h(float (&d)[16], const uint32_t (&a)[4], uint32_t dlo) {
  asm volatile("{\n.reg .pred p;\n.reg .b32 t;\n.reg .b64 db;\nsetp.ne.b32 p, %22, 0;\nadd.u32 t, %20, %21;\nmov.b64 db, {t, 0x40000040};\n"
    "wgmma.mma_async.sync.aligned.m64n32k16.f32.f16.f16 {%0,%1,%2,%3,%4,%5,%6,%7,%8,%9,%10,%11,%12,%13,%14,%15}, {%16,%17,%18,%19}, db, p, 1, 1, 0;\n}\n"
    : "+f"(d[0]), "+f"(d[1]), "+f"(d[2]), "+f"(d[3]), "+f"(d[4]), "+f"(d[5]), "+f"(d[6]), "+f"(d[7]), "+f"(d[8]), "+f"(d[9]), "+f"(d[10]), "+f"(d[11]),
      "+f"(d[12]), "+f"(d[13]), "+f"(d[14]), "+f"(d[15])
    : "r"(a[0]), "r"(a[1]), "r"(a[2]), "r"(a[3]), "r"(dlo), "n"(OFF16), "n"(ACC));
}
template <int IMM> __device__ __forceinline__ void stsm_x4_t_i(uint32_t a, uint32_t r0, uint32_t r1, uint32_t r2, uint32_t r3) {
  asm volatile("stmatrix.sync.aligned.m8n8.x4.trans.shared.b16 [%0+%5], {%1,%2,%3,%4};" :: "r"(a), "r"(r0), "r"(r1), "r"(r2), "r"(r3), "n"(IMM) : "memory");
}
template <int IMM> __device__ __forceinline__ void stsm_x2_t_i(uint32_t a, uint32_t r0, uint32_t r1) {
  asm volatile("stmatrix.sync.aligned.m8n8.x2.trans.shared.b16 [%0+%3], {%1,%2};" :: "r"(a), "r"(r0), "r"(r1), "n"(IMM) : "memory");
}
template <int IMM> __device__ __forceinline__ void st_async_b32_i(uint32_t a, uint32_t x, uint32_t mb) {
  asm volatile("st.async.weak.shared::cluster.mbarrier::complete_tx::bytes.b32 [%0+%3], %1, [%2];" :: "r"(a), "r"(x), "r"(mb), "n"(IMM) : "memory");
}
template <int IMM> __device__ __forceinline__ void ld_relaxed_v4_if(uint4& v, const void* p, uint32_t c) {
  asm volatile("{\n.reg .pred p;\nsetp.ne.u32 p, %6, 0;\n@p ld.relaxed.gpu.global.v4.u32 {%0,%1,%2,%3}, [%4+%5];\n}"
               : "+r"(v.x), "+r"(v.y), "+r"(v.z), "+r"(v.w) : "l"(p), "n"(IMM), "r"(c) : "memory");
}
template <int IMM> __device__ __forceinline__ void ldsm_x2_i(uint32_t (&r)[2], uint32_t a) {
  asm volatile("ldmatrix.sync.aligned.m8n8.x2.shared.b16 {%0,%1}, [%2+%3];" : "=r"(r[0]), "=r"(r[1]) : "r"(a), "n"(IMM) : "memory");
}
template <int IMM> __device__ __forceinline__ uint32_t ldsm_x1_t_i(uint32_t a) {
  uint32_t r; asm volatile("ldmatrix.sync.aligned.m8n8.x1.trans.shared.b16 {%0}, [%1+%2];" : "=r"(r) : "r"(a), "n"(IMM) : "memory"); return r;
}
template <int IMM> __device__ __forceinline__ uint32_t lds32_i(uint32_t a) {
  uint32_t v; asm volatile("ld.shared.u32 %0, [%1+%2];" : "=r"(v) : "r"(a), "n"(IMM) : "memory"); return v;
}
__device__ __forceinline__ void sts32(uint32_t a, uint32_t v) { asm volatile("st.shared.u32 [%0], %1;" :: "r"(a), "r"(v) : "memory"); }
__device__ __forceinline__ uint32_t pack_f16(float lo, float hi) {
  uint32_t d; asm("cvt.rn.f16x2.f32 %0, %1, %2;" : "=r"(d) : "f"(hi), "f"(lo)); return d;
}
__device__ __forceinline__ uint32_t amax_bf2(uint32_t a, uint32_t b) { uint32_t d; asm("max.xorsign.abs.bf16x2 %0, %1, %2;" : "=r"(d) : "r"(a), "r"(b)); return d; }
__device__ __forceinline__ uint32_t amax_h2(uint32_t a, uint32_t b) { uint32_t d; asm("max.xorsign.abs.f16x2 %0, %1, %2;" : "=r"(d) : "r"(a), "r"(b)); return d; }
__device__ __forceinline__ uint32_t amax_fold(uint32_t m) { return __reduce_max_sync(0xffffffffu, max(m & 0x7fffu, (m >> 16) & 0x7fffu)); }
__device__ __forceinline__ int wscale_exp(uint32_t m) { return min(141 - (int)(m >> 7), 100); }
__device__ __forceinline__ float exp2i(int e) { return __uint_as_float((uint32_t)(e + 127) << 23); }
__device__ __forceinline__ uint32_t bf2_to_h2(uint32_t w, float sc) { return pack_f16(bf_lo(w) * sc, bf_hi(w) * sc); }
__device__ __forceinline__ void bf2_to_h2_inplace(uint32_t& w, uint32_t sc2) {
  asm volatile("{\n.reg .b32 t, lo, hi;\nmul.rn.bf16x2 t, %0, %1;\nshl.b32 lo, t, 16;\nand.b32 hi, t, 0xffff0000;\ncvt.rn.f16x2.f32 %0, hi, lo;\n}" : "+r"(w) : "r"(sc2));
}
__device__ __forceinline__ void prefetch_l2(const void* p, uint32_t bytes) { asm volatile("cp.async.bulk.prefetch.L2.global [%0], %1;" :: "l"(p), "r"(bytes) : "memory"); }
__device__ __forceinline__ void prefetch_tma_2d(const CUtensorMap* tm, int c0, int c1) {
  asm volatile("cp.async.bulk.prefetch.tensor.2d.L2.global [%0, {%1, %2}];" :: "l"(tm), "r"(c0), "r"(c1) : "memory");
}
__host__ __device__ constexpr uint32_t acc_voff(int v) { return v < 4 ? v * 1024u : (v == 4 ? 128u : 3072u + 128u); }
__device__ __forceinline__ int unit28(int i) { return i == 3 ? 54 : 14 * i; }
__device__ __forceinline__ int unit24(int i) { return i < 2 ? 48 - 6 * i : 56 + 6 * i; }
__device__ __forceinline__ uint32_t acc_step(int s) { return (s >> 1) * 32768 + (s & 1) * 512; }
__device__ __forceinline__ uint32_t acc_lane(int i, int lane) { return ((lane >> 3) & 1) * 256 + (lane >> 4) * 4096 + i * 8192 + (lane & 7) * 16; }

__device__ __forceinline__ uint32_t ld_acquire_u32(const void* p) {
  uint32_t v; asm volatile("ld.acquire.gpu.global.u32 %0, [%1];" : "=r"(v) : "l"(p) : "memory"); return v;
}
template <int R> __device__ __forceinline__ void ln_rows(const uint2 (&xw)[R][5], int row0, int lane, bf16* __restrict__ xn, uint2* __restrict__ xh) {
  float v[R][20], s[R], q[R];
#pragma unroll
  for (int r = 0; r < R; r++) {
    s[r] = 0.f; q[r] = 0.f;
#pragma unroll
    for (int i = 0; i < 5; i++) { v[r][4 * i] = bf_lo(xw[r][i].x); v[r][4 * i + 1] = bf_hi(xw[r][i].x); v[r][4 * i + 2] = bf_lo(xw[r][i].y); v[r][4 * i + 3] = bf_hi(xw[r][i].y); }
#pragma unroll
    for (int i = 0; i < 5; i++) s[r] += (v[r][4 * i] + v[r][4 * i + 1]) + (v[r][4 * i + 2] + v[r][4 * i + 3]);
  }
#pragma unroll
  for (int o = 16; o; o >>= 1)
#pragma unroll
    for (int r = 0; r < R; r++) s[r] += __shfl_xor_sync(0xffffffffu, s[r], o);
#pragma unroll
  for (int r = 0; r < R; r++) {
    s[r] *= 1.f / cfg::DM;
#pragma unroll
    for (int i = 0; i < 10; i++) { const float d = v[r][2 * i] - s[r], e = v[r][2 * i + 1] - s[r]; q[r] += d * d + e * e; }
  }
#pragma unroll
  for (int o = 16; o; o >>= 1)
#pragma unroll
    for (int r = 0; r < R; r++) q[r] += __shfl_xor_sync(0xffffffffu, q[r], o);
#pragma unroll
  for (int r = 0; r < R; r++) {
    const int row = row0 + r;
    const float mb = bf16r(s[r]), var = bf16r(q[r] * (1.f / cfg::DM));
    float sd; asm("sqrt.approx.f32 %0, %1;" : "=f"(sd) : "f"(bf16r(var + 1e-5f)));
    const float inv = rcpf(bf16r(sd));
#pragma unroll
    for (int i = 0; i < 5; i++) {
      float y[4];
#pragma unroll
      for (int e = 0; e < 4; e++) y[e] = v[r][4 * i + e] - mb;
      bf16r2(y[0], y[1]); bf16r2(y[2], y[3]);
      const uint32_t w0 = pack_bf16(y[0] * inv, y[1] * inv), w1 = pack_bf16(y[2] * inv, y[3] * inv);
      *(uint2*)(xn + (size_t)row * cfg::DM + i * 128 + lane * 4) = make_uint2(w0, w1);
      if (xh) xh[(((size_t)(row >> 5) * 10 + 2 * i + (lane >> 4)) * 32 + (row & 31)) * 16 + ((((lane >> 1) & 7) ^ (row & 7)) << 1) + (lane & 1)] =
          make_uint2(pack_f16(bf_lo(w0), bf_hi(w0)), pack_f16(bf_lo(w1), bf_hi(w1)));
    }
  }
}

__global__ void __cluster_dims__(3, 1, 1) __launch_bounds__(384, 1) chain_kernel(const ChainArgs a, const __grid_constant__ CUtensorMap tmWq,
    const __grid_constant__ CUtensorMap tmWk, const __grid_constant__ CUtensorMap tmWv, const __grid_constant__ CUtensorMap tmWo) {
  using namespace ch;
  extern __shared__ __align__(1024) unsigned char smem_raw[];
  const uint32_t sb = smem_u32(smem_raw);
  const int warp = __shfl_sync(0xffffffffu, (int)threadIdx.x >> 5, 0);
  const int lane = __shfl_sync(0xffffffffu, (int)threadIdx.x & 31, threadIdx.x & 31);
  const int cta = blockIdx.x, h = cta / 3, j = cta % 3;
  const int g = lane >> 2, q4 = lane & 3, r8 = lane & 7, m4 = lane >> 3;
  unsigned char* const arena = a.arena;
  if (sb & 1023u) __trap();
  asm volatile("griddepcontrol.launch_dependents;");
  TL_BEGIN(a.tl);
#ifdef TIMELINE
  const unsigned long long g_tl0 = gtime();
#define PT(i) TLW((a.tl >= 12) * 128 + 64 + (i))
#else
#define PT(i)
#endif
  const int col0 = j == 0 ? 0 : (j == 1 ? 224 : 432);
  auto stage_w = [&](const CUtensorMap* tm, uint32_t dst, uint32_t mb, int half) {
    mbar_expect_tx(mb + 8 * half, 40960);
    tma_load_2d(dst + half * 40960, tm, h * cfg::DH + j * 64, half * 320, mb + 8 * half);
    tma_load_2d(dst + half * 40960 + 20480, tm, h * cfg::DH + j * 64, half * 320 + 160, mb + 8 * half);
  };
  if (threadIdx.x == 256) {
    for (int i = 0; i < 9; i++) mbar_init(sb + MB_K + 8 * i, 1);
    mbar_init(sb + MB_S, 1); mbar_init(sb + MB_O, 1); mbar_init(sb + MB_X, 1);
    asm volatile("fence.mbarrier_init.release.cluster;" ::: "memory");
    for (int i = 0; i < 2; i++) { stage_w(&tmWk, sb + OFF_WQ, sb + MB_K, i); stage_w(&tmWv, sb + OFF_WO, sb + MB_V, i); }
    sts32(sb + SC_W, 0); sts32(sb + SC_W + 4, 0); sts32(sb + SC_W + 8, 0); sts32(sb + SC_IN + 12, 0); sts32(sb + SC_IN + 20, 0); sts32(sb + SC_TW + 4, 99);
    mbar_expect_tx(sb + MB_S, 1280); mbar_expect_tx(sb + MB_O, 2048);
  }
  __syncthreads();
  asm volatile("barrier.cluster.arrive.relaxed.aligned;" ::: "memory");
  const uint32_t d1 = mapa_u32(sb, (j + 1) % 3) - sb, d2 = mapa_u32(sb, (j + 2) % 3) - sb;

  if (warp >= 8) {
    asm volatile("setmaxnreg.dec.sync.aligned.u32 40;");
    const int hw = warp - 8, ht = hw * 32 + lane;
    const bool lead = ht == 0;
    auto stage_wo = [&](int i) {
      mbar_expect_tx(sb + MB_R + 8 * i, 64 * WOS);
      tma_load_2d(sb + OFF_WO + i * 64 * WOS, &tmWo, col0, h * cfg::DH + ((i + j) % 3) * 64, sb + MB_R + 8 * i);
    };
    const unsigned char* xg = (const unsigned char*)a.xh;
    auto issue_x = [&](int s) { mbar_expect_tx(sb + MB_X, 40960); bulk_g2s(sb + OFF_X, xg + (size_t)s * 40960, 40960, sb + MB_X); };
    uint4 v[5];
#pragma unroll
    for (int i = 0; i < 5; i++) { const int c = ht + 128 * i; v[i] = ld_relaxed_v4(a.mem0 + (c & 7) * cfg::DM + (c >> 3) * 8); }
    if (hw == 2) {
      asm volatile("griddepcontrol.wait;" ::: "memory");
      if (lane == 0) { if (cta == 0) st_relaxed_u32(a.go, 1); issue_x(0); }
      PT(0);
    }
    if (hw == 0) {
      bar_sync(B_QK, 160); if (lane == 0) stage_w(&tmWq, sb + OFF_WQ, sb + MB_Q, 0);
      bar_sync(B_SL, 160); if (lane == 0) stage_w(&tmWq, sb + OFF_WQ, sb + MB_Q, 1);
    }
    if (hw == 1) {
      bar_sync(B_V, 160); if (lane == 0) stage_wo(0);
      bar_sync(B_O, 160); if (lane == 0) { stage_wo(1); stage_wo(2); }
    }
    __syncwarp();
    {
      uint32_t m = 0;
#pragma unroll
      for (int i = 0; i < 5; i++) {
        m = amax_bf2(amax_bf2(m, amax_bf2(v[i].x, v[i].y)), amax_bf2(v[i].z, v[i].w));
      }
      m = amax_fold(m);
      if (lane == 0) sts32(sb + SC_MX + hw * 4, m);
      bar_sync(B_H, 128);
      const uint4 mm = lds128(sb + SC_MX);
      const int se = max(wscale_exp(max(max(mm.x, mm.y), max(mm.z, mm.w))), -100);
      const float sc = exp2i(se);
#pragma unroll
      for (int i = 0; i < 5; i++) {
        const int c = ht + 128 * i, t = c & 7, chn = c >> 3;
        sts128(sb + OFF_MEM + chn * 128 + ((t ^ (2 * (chn & 3))) << 4), bf2_to_h2(v[i].x, sc), bf2_to_h2(v[i].y, sc), bf2_to_h2(v[i].z, sc), bf2_to_h2(v[i].w, sc));
      }
      if (lead) { sts32(sb + SC_IN, __float_as_uint(exp2i(-se))); sts32(sb + SC_IN + 4, 0x7800u); }
    }
    if (hw == 0) PT(11);
    {
      const uint32_t p0 = sb + OFF_WQ + hw * 2048 + lane * 16;
      uint32_t m = 0;
#pragma unroll 1
      for (int i = 0; i < 10; i++) {
        if (i == 0 || i == 5) mbar_wait(sb + MB_Q + (i ? 8 : 0), 0);
        uint32_t r[4][4];
        static_for<0, 4>([&](auto K) { ldsm_x4_i<K.value * 512>(r[K.value], p0 + i * 8192); });
#pragma unroll
        for (int k = 0; k < 4; k++) m = amax_bf2(amax_bf2(m, amax_bf2(r[k][0], r[k][1])), amax_bf2(r[k][2], r[k][3]));
      }
      if (hw == 0) PT(9);
      m = amax_fold(m);
      if (lane == 0) asm volatile("red.shared.max.u32 [%0], %1;" :: "r"(sb + SC_W + 8), "r"(m) : "memory");
      bar_sync(B_H, 128);
      const uint32_t sc = (uint32_t)(wscale_exp(lds32_i<SC_W + 8>(sb)) + 127) * 0x00800080u;
#pragma unroll 1
      for (int i = 0; i < 10; i++) {
        uint32_t r[4][4];
        static_for<0, 4>([&](auto K) { ldsm_x4_i<K.value * 512>(r[K.value], p0 + i * 8192); });
#pragma unroll
        for (int k = 0; k < 4; k++) {
          bf2_to_h2_inplace(r[k][0], sc); bf2_to_h2_inplace(r[k][1], sc); bf2_to_h2_inplace(r[k][2], sc); bf2_to_h2_inplace(r[k][3], sc);
          stsm_x4(p0 + i * 8192 + k * 512, r[k][0], r[k][1], r[k][2], r[k][3]);
        }
      }
    }
    if (hw == 0) PT(10);
    bar_sync(0, 384);
    if (hw == 3) {
      const uint32_t eye = (m4 == q4) ? ((lane & 4) ? 0x3f800000u : 0x3f80u) : 0u;
      sts128(sb + OFF_LT + lane * 16, eye, eye, (lane & 2) * 64 + g * 16 + (lane & 1) * 8, 0u);
      sts64(sb + OFF_S + 1280 + lane * 8, 0u, 0u);
    }
    if (lead) st_relaxed_u32(arena + AR_TAB + cta * 4, 0x80000000u | (lds32_i<SC_W>(sb) << 15) | lds32_i<SC_W + 4>(sb));
    asm volatile("barrier.cluster.wait.aligned;" ::: "memory");
    bar_sync(B_MEM0, 256); bar_sync(B_MEM1, 256);
    {
      uint32_t v0, v1, v2; int spin = 0;
      do {
        v0 = ld_relaxed_u32(arena + AR_TAB + lane * 4); v1 = ld_relaxed_u32(arena + AR_TAB + 128 + lane * 4); v2 = ld_relaxed_u32(arena + AR_TAB + 256 + lane * 4);
      } while (__any_sync(0xffffffffu, ((v0 & v1 & v2) >> 31) == 0) && ++spin < SPIN_LIMIT);
      const uint32_t mv = (max(max(v0, v1), v2) >> 15) & 0x7fffu, mo = max(max(v0 & 0x7fffu, v1 & 0x7fffu), v2 & 0x7fffu);
      sts32(sb + SC_IN + 8 + (lane & 1) * 16, 15 - ((__reduce_max_sync(0xffffffffu, mv) >> 7) + (__reduce_max_sync(0xffffffffu, mo) >> 7) - 252 + 22));
    }

    auto store_kv = [&](int s) {
      const size_t o = ((size_t)s * 96 + cta) * KVB; const uint32_t src = sb + OFF_KV + (s & 1) * (2 * KVB);
      fence_proxy_async(); bulk_s2g(a.kg + o, src, KVB); bulk_s2g(a.vg + o, src + KVB, KVB); bulk_commit();
    };
    const int cb28 = unit28(hw), du = (unit24(hw) - cb28) * 128;
    uint32_t n16 = lane * 16, hist = 0;
    const uint32_t us1 = sb + d1 + OFF_SR + 256 + (hw >> 1) * 512 + (hw & 1) * 128, us2 = sb + d2 + OFF_SR + (hw >> 1) * 512 + (hw & 1) * 128;
    const uint32_t uo1 = sb + d1 + OFF_O + 2048 + hw * 256, uo2 = sb + d2 + OFF_O + 1024 + hw * 256;
#ifdef STEPCLK
    if (lead) a.dbg[96 * 300 + cta * 2] = clk32();
#endif
#ifdef TIMELINE
    if (cta == 0 && lead) { g_tl2[(a.tl >= 12) * 128 + 0] = clock64(); g_tl2[(a.tl >= 12) * 128 + 1] = gtime(); }
#endif
#pragma unroll 1
    for (int s = 0; s < cfg::NSEG; s++) {
      TS_SETUP();
      const bool last = s == cfg::NSEG - 1;
      if (n16 == 0) {
        if (hw == 2 && !last) issue_x(s + 1);
        if (hw == 0 && (s & 3) == 1 && s > 1) st_relaxed_u32(arena + (prog_off(h, j) + lds32_i<SC_IN + 12>(sb)), s - 1);
        if (hw == 0 && s > 0) store_kv(s - 1);
        if (PFX && hw == 3 && cta < 80 && s + PFX < cfg::NSEG) prefetch_l2(xg + (size_t)(s + PFX) * 40960 + cta * 512, 512);
        if (PFACC && hw == 1 && s + PFACC < cfg::NSEG - 1)
          asm volatile("prefetch.global.L2 [%0];" :: "l"(arena + (AR_ACC + acc_step(s + PFACC) + acc_lane(cta / 24, (cta & 3) * 8) + acc_voff((cta % 24) >> 2))) : "memory");
      }
      __syncwarp();
      if (last) break;
      const uint32_t kv = (s & 1) * (2 * KVB);
      n16 = fresh(n16);
      uint32_t kb0[4], kb1[4];
      { const uint32_t ka = n16 + (n16 & 384) * 4 + (sb + kv + hw * 128); ldsm_x4_i<OFF_KV>(kb0, ka); ldsm_x4_i<OFF_KV + 2560>(kb1, ka); }
      TS(1);
      bar_sync(B_QK, 384);
      {
        uint32_t q0[4], q1[4], q2[4], q3[4];
        float sa[4] = {0, 0, 0, 0}, sc2[4] = {0, 0, 0, 0};
        ldsm_x4_i<OFF_Q>(q0, n16 + sb); ldsm_x4_i<OFF_Q + 1024>(q2, n16 + sb); ldsm_x4_i<OFF_Q + 512>(q1, n16 + sb);
        bar_arrive(B_A, 288);
        ldsm_x4_i<OFF_Q + 1536>(q3, n16 + sb);
        mma16816(sa, q0[0], q0[1], q0[2], q0[3], kb0[0], kb0[1]);
        mma16816(sc2, q2[0], q2[1], q2[2], q2[3], kb1[0], kb1[1]);
        mma16816(sa, q1[0], q1[1], q1[2], q1[3], kb0[2], kb0[3]);
        mma16816(sc2, q3[0], q3[1], q3[2], q3[3], kb1[2], kb1[3]);
        const float x0 = (sa[0] + sa[2]) + (sc2[0] + sc2[2]), x1 = (sa[1] + sa[3]) + (sc2[1] + sc2[3]);
        const uint32_t xp = pack_bf16(x0, x1);
        st_async_b32_i<0>((n16 >> 2) + us1, xp, sb + MB_S + d1);
        st_async_b32_i<0>((n16 >> 2) + us2, xp, sb + MB_S + d2);
        stsm_x2(n16 + (sb + OFF_S + hw * 256), __float_as_uint(x0), __float_as_uint(x1));
      }
      TS(3);
      uint32_t v0[4], v1[4], vm0, vm1;
      const uint32_t uv = sb + kv + hw * 1280;
      ldsm_x4_t_i<OFF_KV + KVB>(v0, n16 + uv); ldsm_x4_t_i<OFF_KV + KVB + 640>(v1, n16 + uv);
      bar_sync(B_SL, 256);
      float t0[4], t1[4], t2[4];
      { uint32_t x[4]; ldsm_x4_i<OFF_S>(x, n16 + sb); t0[0] = __uint_as_float(x[0]); t0[1] = __uint_as_float(x[1]); t0[2] = __uint_as_float(x[2]); t0[3] = __uint_as_float(x[3]); }
      { uint32_t x[4]; ldsm_x4_i<OFF_S + 512>(x, n16 + sb); t1[0] = __uint_as_float(x[0]); t1[1] = __uint_as_float(x[1]); t1[2] = __uint_as_float(x[2]); t1[3] = __uint_as_float(x[3]); }
      { uint32_t x[4]; ldsm_x4_i<OFF_S + 1024>(x, n16 + sb); t2[0] = __uint_as_float(x[0]); t2[1] = __uint_as_float(x[1]); t2[2] = __uint_as_float(x[2]); t2[3] = __uint_as_float(x[3]); }
      mbar_spin(sb + MB_S, s & 1);
      TS(4);
      uint2 xo;
      {
        uint32_t r0[4], r1[4], r2[2];
        ldsm_x4_i<OFF_SR>(r0, n16 + sb); ldsm_x4_i<OFF_SR + 512>(r1, n16 + sb); ldsm_x2_i<OFF_SR + 1024>(r2, n16 + sb);
        SFENCE(n16);
        const uint2 eye = lds64_i<OFF_LT>(n16 + sb);
        mma16816(t0, r0[0], r0[1], r0[2], r0[3], eye.x, eye.y);
        mma16816(t1, r1[0], r1[1], r1[2], r1[3], eye.x, eye.y);
        mma1688(t2, r2[0], r2[1], eye.x);
        bar_sync(B_V, 256);
        vm0 = ldsm_x1_t_i<OFF_KV + KVB + 512>(n16 + uv); vm1 = ldsm_x1_t_i<OFF_KV + KVB + 1152>(n16 + uv);
        SFENCE(n16);
        xo = lds64_i<OFF_LT + 8>(n16 + sb);
      }
      float sc[10] = {t0[0], t0[1], t0[2], t0[3], t1[0], t1[1], t1[2], t1[3], t2[0] + t2[2], t2[1] + t2[3]};
      const float cs = 0.07216878364870322f * 1.4426950408889634f;
      float mx = fmaxf(fmaxf(fmaxf(sc[0], sc[1]), fmaxf(sc[2], sc[3])), fmaxf(fmaxf(sc[4], sc[5]), fmaxf(sc[6], sc[7])));
      mx = fmaxf(mx, fmaxf(sc[8], sc[9]));
      {
        const float m1 = __shfl_xor_sync(0xffffffffu, mx, 1), m2 = __shfl_xor_sync(0xffffffffu, mx, 2), m3 = __shfl_xor_sync(0xffffffffu, mx, 3);
        mx = fmaxf(fmaxf(mx, m1), fmaxf(m2, m3));
      }
      const float mo = fmaf(mx, -cs, __uint_as_float(xo.x));
      auto ex = [&](int i) -> uint32_t { float x, y;
        asm volatile("ex2.approx.ftz.f32 %0, %1;" : "=f"(x) : "f"(fmaf(sc[i], cs, mo))); asm volatile("ex2.approx.ftz.f32 %0, %1;" : "=f"(y) : "f"(fmaf(sc[i + 1], cs, mo)));
        return pack_bf16(x, y); };
      float oa[4] = {0, 0, 0, 0}, ob[4] = {0, 0, 0, 0}, oc[4] = {0, 0, 0, 0}, od[4] = {0, 0, 0, 0}, rs[4] = {0, 0, 0, 0};
      const uint32_t ones = 0x3f803f80u;
      const uint32_t p4 = ex(8);
      if (MEMFIRST) { mma1688(rs, p4, 0u, ones); mma1688(oa, p4, 0u, vm0); mma1688(ob, p4, 0u, vm1); }
      const uint32_t p0 = ex(0), p1 = ex(2), p2 = ex(4), p3 = ex(6);
      TS(5);
      mma16816(rs, p0, p2, p1, p3, ones, ones);
      mma16816(oa, p0, p2, p1, p3, v0[0], v0[1]);
      mma16816(oc, p0, p2, p1, p3, v0[2], v0[3]);
      mma16816(ob, p0, p2, p1, p3, v1[0], v1[1]);
      mma16816(od, p0, p2, p1, p3, v1[2], v1[3]);
      if (!MEMFIRST) { mma1688(rs, p4, 0u, ones); mma1688(oa, p4, 0u, vm0); mma1688(ob, p4, 0u, vm1); }
      const float inv = rcpf(rs[0] + rs[2]) * __uint_as_float(xo.y);
      {
        const uint32_t y0 = pack_bf16((oa[0] + oc[2]) * inv, (oa[1] + oc[3]) * inv), y1 = pack_bf16((ob[0] + od[2]) * inv, (ob[1] + od[3]) * inv);
        st_async_v2_i<0>(xo.x + uo1, y0, y1, sb + MB_O + d1);
        st_async_v2_i<0>(xo.x + uo2, y0, y1, sb + MB_O + d2);
        sts64_i<OFF_O>(xo.x + (sb + hw * 256), y0, y1);
      }
      bar_arrive(B_O, 384);
      TS(6);
      if (hw == 0) bulk_wait<0>();
      mbar_expect_tx_if(n16 == 0 && hw == 3, sb + MB_S, 1280);
      n16 = fresh(n16);
      const int ln = n16 >> 4;
      auto mslot = [&](int c) -> uint32_t { return sb + OFF_MEM + c * 128 + (((ln >> 2) ^ (2 * (c & 3))) << 4); };
      const int lq = ln & 3;
      const uint32_t ma = mslot(cb28 + lq), mb_ = mslot(cb28 + (lq >> 1)) + (lq & 1) * 8;
      const unsigned char* gp = arena + (AR_ACC + acc_lane(hw, ln) + acc_step(s));
      const bool odd = ln & 1;
      const uint32_t delay = a.delay + ((hist & 2) ? a.margin : 0);
      SFENCE(ma);
      uint32_t tw;
      if (hw == 0 && (s & 3) == 0 && a.pubrel) {
        bar_arrive(B_RED, 384);
        asm volatile("fence.acq_rel.gpu;" ::: "memory");
        uint2 t; int sp = 0;
        do { asm volatile("ld.volatile.shared.v2.u32 {%0,%1}, [%2];" : "=r"(t.x), "=r"(t.y) : "r"(sb + SC_TW) : "memory"); } while (__any_sync(0xffffffffu, t.y != (uint32_t)s) && ++sp < SPIN_LIMIT);
        tw = t.x;
      } else {
        bar_sync(B_RED, 384);
        SFENCE(mb_);
        tw = clk_v();
        if (hw == 1) asm volatile("st.volatile.shared.v2.u32 [%0], {%1,%2};" :: "r"(sb + SC_TW), "r"(tw), "r"(s) : "memory");
      }
      TSV(7, tw);
      mbar_expect_tx_if(n16 == 0 && hw == 3, sb + MB_O, 2048);
      while (clk_v() - tw < delay) {}
      TS(8);
      uint4 v[6];
      int spin = 0;
      const uint32_t cm = odd ? 0x5000u : 0u;
      do {
        static_for<0, 6>([&](auto I) { v[I.value] = ld_relaxed_v4_i<acc_voff(I.value)>(gp); });
      } while (__any_sync(0xffffffffu, (~((v[0].w & v[1].w & v[2].w) & (v[3].w & v[4].w & v[5].w)) & cm) != 0) && ++spin < SPIN_LIMIT);
      v[0].w = odd ? v[3].x : v[0].w; v[1].w = odd ? v[3].y : v[1].w; v[2].w = odd ? v[3].z : v[2].w; v[3].w = odd ? 0u : v[3].w;
      sts128_i<0>(ma, v[0].x, v[0].y, v[0].z, v[0].w);
      sts128_i<512>(ma, v[1].x, v[1].y, v[1].z, v[1].w);
      sts128_i<1024>(ma, v[2].x, v[2].y, v[2].z, v[2].w);
      sts128_i<0>(ma + du, v[4].x, v[4].y, v[4].z, v[5].z);
      sts64_i<512>(mb_ + du, v[5].x, v[5].y);
      if (!odd) sts128_i<1536>(mb_, v[3].x, v[3].y, v[3].z, v[3].w);
      hist = (hist * 2 + (spin != 0)) & 0xffffu;
      TSV(11, spin);
#ifdef TIMELINE
      if (hw == 2 && ln == 0) { uint32_t gt; asm volatile("mov.u32 %0, %%globaltimer_lo;" : "=r"(gt)); *(uint4*)(g_step + (((a.tl >= 12) * 64 + s) * 96 + cta) * 4) = make_uint4(gt, spin, clk_v() - tw, tw); }
#endif
      TS(10);
      bar_sync(B_MEM0, 256); bar_sync(B_MEM1, 256);
      uint32_t m = lds32_i<SC_IN + 12>(sb);
      uint32_t m2 = m;
      static_for<0, 3>([&](auto I) { m = amax_h2(amax_h2(amax_h2(amax_h2(m, v[I.value].x), v[I.value].y), v[I.value].z), v[I.value].w); });
      static_for<3, 6>([&](auto I) { m2 = amax_h2(amax_h2(amax_h2(m2, v[I.value].x), v[I.value].y), v[I.value].z); });
      m = amax_fold(amax_h2(amax_h2(m2, v[3].w), m));
      if (n16 == 0) asm volatile("red.shared.max.u32 [%0], %1;" :: "r"(sb + SC_IN + 4 + 16 * ((s + 1) & 1)), "r"(m) : "memory");
    }
    bar_sync(B_RED, 384);
    if (hw == 0 && n16 == 0) {
      store_kv(cfg::NSEG - 1);
      bulk_wait<0>();
      st_release_u32(arena + (prog_off(h, j) + lds32_i<SC_IN + 12>(sb)), cfg::NSEG);
    }
    __syncwarp();
#ifdef STEPCLK
    if (hw == 0 && n16 == 0) a.dbg[96 * 300 + cta * 2 + 1 + (hist >> 20)] = clk32();
#endif
#ifdef TIMELINE
    if (cta == 0 && hw == 0 && n16 == 0) { g_tl2[(a.tl >= 12) * 128 + 2] = clock64(); g_tl2[(a.tl >= 12) * 128 + 3] = gtime(); }
#endif
    TL_END(a.tl);
    asm volatile("barrier.cluster.arrive.relaxed.aligned; barrier.cluster.wait.aligned;" ::: "memory");
  } else {
    asm volatile("setmaxnreg.inc.sync.aligned.u32 232;");
    const int wi = warp & 3, hf = warp >> 2, tid = warp * 32 + lane;
    uint32_t w[40][4], wm = 0;
    uint32_t wqa;
    { const int mrow = r8 + ((lane >> 4) << 3), mch = 2 * wi + (m4 & 1); wqa = sb + mrow * 128 + ((mch ^ r8) << 4); }
    {
      const uint32_t wa = wqa + (hf ? OFF_WO : OFF_WQ);
      mbar_wait(sb + (hf ? MB_V : MB_K), 0);
      static_for<0, 20>([&](auto K) { ldsm_x4_t_i<K.value * 2048>(w[K.value], wa); });
#pragma unroll
      for (int k = 0; k < 20; k++) wm = amax_bf2(amax_bf2(wm, amax_bf2(w[k][0], w[k][1])), amax_bf2(w[k][2], w[k][3]));
      SFENCE2(wa, wm);
      if (warp == 0) PT(1);
      bar_arrive(hf ? B_V : B_QK, 160);
      mbar_wait(sb + (hf ? MB_V : MB_K) + 8, 0);
      static_for<20, 40>([&](auto K) { ldsm_x4_t_i<K.value * 2048>(w[K.value], wa); });
#pragma unroll
      for (int k = 20; k < 40; k++) wm = amax_bf2(amax_bf2(wm, amax_bf2(w[k][0], w[k][1])), amax_bf2(w[k][2], w[k][3]));
      SFENCE2(wa, wm);
      if (warp == 4) PT(2);
      bar_arrive(hf ? B_O : B_SL, 160);
      SFENCE(wa);
    }
    float iw, iq;
    {
      const uint32_t m = amax_fold(wm);
      if (hf && lane == 0) asm volatile("red.shared.max.u32 [%0], %1;" :: "r"(sb + SC_W), "r"(m) : "memory");
      const int e = wscale_exp(m);
      const uint32_t sc = (uint32_t)(e + 127) * 0x00800080u; iw = exp2i(-e);
#pragma unroll
      for (int k = 0; k < 40; k++) { bf2_to_h2_inplace(w[k][0], sc); bf2_to_h2_inplace(w[k][1], sc); bf2_to_h2_inplace(w[k][2], sc); bf2_to_h2_inplace(w[k][3], sc); }
    }
    uint32_t x0[8];
    {
      float xa[16];
      const uint32_t dlo = (((sb + OFF_X) & 0x3FFFF) >> 4) | (1u << 16);
      if (warp == 0) PT(3);
      mbar_wait(sb + MB_X, 0);
      if (warp == 0) PT(4);
      wgmma_fence();
      static_for<0, 40>([&](auto K) { constexpr int k = K.value; wgmma_rs32h<((k >> 2) * 4096 + (k & 3) * 32) / 16, (k != 0)>(xa, w[k], dlo); });
      wgmma_commit();
      wgmma_wait<0>();
#pragma unroll
      for (int i = 0; i < 8; i++) x0[i] = pack_bf16(xa[2 * i] * iw, xa[2 * i + 1] * iw);
    }
    const bool t28 = j == 0 || warp < 4;
    const int bi = j == 0 ? hf : (warp < 4 ? j + 1 : 2 * (j - 1) + ((warp - 4) >> 1)), bv = t28 ? wi : 4 + (warp & 1);
    uint32_t wo1 = sb + OFF_WO + warp * 896 + lane * 16, wo2;
    {
      const int cb = (t28 ? unit28(bi) : unit24(bi)) - col0 / 8;
      uint32_t cp[4];
#pragma unroll
      for (int wd = 0; wd < 4; wd++) {
        int c, p;
        if (bv < 3) { c = 4 * bv + q4; p = wd; }
        else if (bv == 3) { if (q4 & 1) { c = 4 * (wd % 3) + q4; p = 3; } else { c = 12 + (q4 >> 1); p = wd; } }
        else if (bv == 4) { c = q4; p = wd; }
        else { if (wd < 2) { c = 4 + (q4 >> 1); p = 2 * (q4 & 1) + wd; } else { c = q4; p = 3; } }
        cp[wd] = sb + OFF_WO + ((g & 1) + (g & 2) * 4 + (g >> 2) * 2) * WOS + (cb + c) * 16 + p * 4;
      }
      const int cidx = (r8 & 1) + ((r8 >> 2) << 1);
      wo2 = sb + OFF_WO + warp * 896 + ((m4 & 1) ? 768 + (m4 >> 1) * 64 + cidx * 16 : 512 + (m4 >> 1) * 128 + r8 * 16);
      const bool dump = (m4 & 1) && (r8 & 2);
      uint32_t mo = 0;
      const bool regular = bv < 3 || bv == 4;
#pragma unroll 1
      for (int i = 0; i < 3; i++) {
        uint32_t x[4][4], y[4][4];
        const uint32_t o = i * 4 * WOK;
        mbar_wait(sb + MB_R + 8 * i, 0);
        if (warp == 0) PT(5 + i);
        if (regular) {
          static_for<0, 4>([&](auto K) {
            constexpr int kk = K.value;
            const uint4 u = lds128_i<kk * WOK>(cp[0] + o), v = lds128_i<kk * WOK + 4 * WOS>(cp[0] + o);
            x[kk][0] = u.x; x[kk][1] = u.y; x[kk][2] = u.z; x[kk][3] = u.w; y[kk][0] = v.x; y[kk][1] = v.y; y[kk][2] = v.z; y[kk][3] = v.w;
          });
        } else {
          static_for<0, 4>([&](auto K) {
            constexpr int kk = K.value;
#pragma unroll
            for (int wd = 0; wd < 4; wd++) { x[kk][wd] = lds32_i<kk * WOK>(cp[wd] + o); y[kk][wd] = lds32_i<kk * WOK + 4 * WOS>(cp[wd] + o); }
          });
        }
        bar_sync(B_C, 256);
        static_for<0, 4>([&](auto K) {
          constexpr int kk = K.value;
#pragma unroll
          for (int wd = 0; wd < 4; wd++) mo = amax_bf2(mo, amax_bf2(x[kk][wd], y[kk][wd]));
          stsm_x4_t_i<kk * WOK>(wo1 + o, x[kk][0], x[kk][1], y[kk][0], y[kk][1]);
          stsm_x4_t_i<0>(dump ? sb + OFF_S + 512 + lane * 16 : wo2 + o + kk * WOK, x[kk][2], x[kk][3], y[kk][2], y[kk][3]);
        });
      }
      if (warp == 0) PT(8);
      mo = amax_fold(mo);
      if (lane == 0) asm volatile("red.shared.max.u32 [%0], %1;" :: "r"(sb + SC_W + 4), "r"(mo) : "memory");
    }
    __syncwarp();
    auto run = [&](auto HF) {
    constexpr int hf = HF.value;
    uint32_t mema, sta, l16 = sb + lane * 16;
    uint32_t rq[hf ? NP1 : NQ0][4];
    auto step_addr = [&](uint32_t kv) {
      const int lr = (l16 >> 4) & 7, lm = (l16 >> 7) & 3;
      mema = l16 ^ (lm << 5);
      sta = sb + lr * 16 + (lm < 2 ? OFF_Q + wi * 512 + hf * 128 + lm * 256 : OFF_KV + kv + 512 + (2 * wi + lm - 2) * 640);
    };
    auto x_gemm = [&](uint32_t ph, [[maybe_unused]] uint32_t tsb) {
      float xa[16];
      const uint32_t dlo = (((sb + OFF_X) & 0x3FFFF) >> 4) | (1u << 16);
      constexpr int NP = hf ? NP1 : NP0;
      if constexpr (hf) {
        static_for<PQE, NP>([&](auto K) { ldsm_x4_t_i<OFF_WQ + K.value * 2048>(rq[K.value], wqa); });
        bar_sync(B_X, 256);
      }
      wgmma_fence();
      static_for<0, 40>([&](auto K) {
        constexpr int k = K.value;
        wgmma_rs32h<((k >> 2) * 4096 + (k & 3) * 32) / 16, (k != 0)>(xa, w[k], dlo);
        if constexpr (!hf && k == PFK && NP > PQE) { SFENCE(wqa); static_for<PQE, NP>([&](auto K) { ldsm_x4_t_i<OFF_WQ + K.value * 2048>(rq[K.value], wqa); }); SFENCE(wqa); }
        if constexpr (!hf && k == XT) bar_arrive(B_X, 256);
      });
      step_addr(ph * (2 * KVB));
      wgmma_commit();
      TS(9);
      wgmma_wait<0>();
      const uint32_t xs = l16 + (wi * 1280 + ph * (2 * KVB));
      stsm_x4_t_i<OFF_KV + hf * KVB>(xs, pack_bf16(xa[0] * iw, xa[1] * iw), pack_bf16(xa[4] * iw, xa[5] * iw), pack_bf16(xa[8] * iw, xa[9] * iw), pack_bf16(xa[12] * iw, xa[13] * iw));
      stsm_x4_t_i<OFF_KV + hf * KVB + 640>(xs, pack_bf16(xa[2] * iw, xa[3] * iw), pack_bf16(xa[6] * iw, xa[7] * iw), pack_bf16(xa[10] * iw, xa[11] * iw), pack_bf16(xa[14] * iw, xa[15] * iw));
      if constexpr (!hf) static_for<NP0, NP0 + NPL>([&](auto K) { ldsm_x4_t_i<OFF_WQ + K.value * 2048>(rq[K.value], wqa); });
    };
    auto wq_addr = [&](uint32_t l) -> uint32_t {
      const int lr = (l >> 4) & 7, lm = (l >> 7) & 3;
      return sb + hf * ((40 - NQ1) * 2048) + (lr + ((lm >> 1) << 3)) * 128 + (((2 * wi + (lm & 1)) ^ lr) << 4);
    };
    constexpr int NPM = hf ? NPM1 : NPM0;
    uint32_t u1[NPM][4], u2[NPM][4];
    static_for<0, NPM>([&](auto K) { ldsm_x4_i<(12 - NPM + K.value) * WOK>(u1[K.value], wo1); ldsm_x4_i<(12 - NPM + K.value) * WOK>(u2[K.value], wo2); });
    bar_sync(0, 384);
    iq = uniform_f(exp2i(-wscale_exp(lds32_i<SC_W + 8>(sb))));
    wqa = wq_addr(l16);
    static_for<0, (hf ? NP1 : NP0 + NPL)>([&](auto K) { ldsm_x4_t_i<OFF_WQ + K.value * 2048>(rq[K.value], wqa); });
    step_addr(0);
    stsm_x4_t_i<OFF_KV + hf * KVB>(l16 + wi * 1280, x0[0], x0[2], x0[4], x0[6]);
    stsm_x4_t_i<OFF_KV + hf * KVB + 640>(l16 + wi * 1280, x0[1], x0[3], x0[5], x0[7]);
    asm volatile("barrier.cluster.wait.aligned;" ::: "memory");
    TL_END(a.tl + 1);
#pragma unroll 1
    for (int s = 0; s < cfg::NSEG - 1; s++) {
      TS_SETUP();
#if CHAIN_TIMING
      if (tid == 0 && (s & 7) == 0) a.dbg[96 * 288 + cta * 8 + (s >> 3)] = clk32();
#endif
      bar_sync(hf ? B_MEM1 : B_MEM0, 256);
      const float sin_ = __uint_as_float(lds32_i<SC_IN>(sb + 16 * (s & 1)));
      constexpr int NPQ = (40 - NQ1) / 2;
      if constexpr (hf == 0) {
        float k0[4] = {0, 0, 0, 0}, k1[4] = {0, 0, 0, 0}, q0[4] = {0, 0, 0, 0}, q1[4] = {0, 0, 0, 0};
        constexpr auto pair_of = [](int t) { const int a = t * (20 - NPQ) / 20, b = (t + 1) * (20 - NPQ) / 20; return b > a ? NPQ + a : t - a; };
        uint32_t b[NB0][4];
        static_for<0, NB0>([&](auto T) { ldsm_x4_i<OFF_MEM + pair_of(T.value) * 512>(b[T.value], mema); });
        static_for<NP0 + NPL, NQ0>([&](auto K) { ldsm_x4_t_i<OFF_WQ + K.value * 2048>(rq[K.value], wqa); });
        if (BBS < 100) bbfence<0>(mema);
        static_for<0, 20>([&](auto T) {
          constexpr int t = T.value, p = pair_of(t);
          uint32_t (&bb)[4] = b[t % NB0];
          if constexpr (p < NPQ) {
            mma16816h(q0, rq[(2 * p) % NQ0], bb[0], bb[1]);
            if constexpr (2 * p + NQ0 < 2 * NPQ) ldsm_x4_t_i<OFF_WQ + (2 * p + NQ0) * 2048>(rq[(2 * p) % NQ0], wqa);
          }
          mma16816h(k0, w[2 * p], bb[0], bb[1]);
          if constexpr (p < NPQ) {
            mma16816h(q1, rq[(2 * p + 1) % NQ0], bb[2], bb[3]);
            if constexpr (2 * p + 1 + NQ0 < 2 * NPQ) ldsm_x4_t_i<OFF_WQ + (2 * p + 1 + NQ0) * 2048>(rq[(2 * p + 1) % NQ0], wqa);
          }
          mma16816h(k1, w[2 * p + 1], bb[2], bb[3]);
          if constexpr (NVE > 0 && t + NB0 == VET) bar_arrive(B_E, 256);
          if constexpr (t + NB0 < 20) ldsm_x4_i<OFF_MEM + pair_of(t + NB0) * 512>(bb, mema);
          if constexpr (t < 20 - NB0 && (t % BBS) == BBS - 1) bbfence<t + 1>(mema);
        });
        const float sq = sin_ * iq, sk = sin_ * iw;
        stsm_x4_t_i<0>(sta, pack_bf16((q0[0] + q1[0]) * sq, (q0[1] + q1[1]) * sq), pack_bf16((q0[2] + q1[2]) * sq, (q0[3] + q1[3]) * sq),
                       pack_bf16((k0[0] + k1[0]) * sk, (k0[1] + k1[1]) * sk), pack_bf16((k0[2] + k1[2]) * sk, (k0[3] + k1[3]) * sk));
        bar_sync(B_QK, 384);
        TS(2);
        {
          if (wi == 3) {
            const uint32_t xr = sb + ((l16 & 511) >> 2), ka = l16 + (l16 & 384) * 4 + (s & 1) * (2 * KVB);
            uint32_t a0[4], a1[4], a2[4], a3[4], kb0[4], kb1[4];
            ldsm_x4_i<OFF_Q>(a0, l16); ldsm_x4_i<OFF_KV + 512>(kb0, ka); ldsm_x4_i<OFF_Q + 1024>(a2, l16); ldsm_x4_i<OFF_KV + 512 + 2560>(kb1, ka);
            ldsm_x4_i<OFF_Q + 512>(a1, l16);
            bar_arrive(B_A, 288);
            ldsm_x4_i<OFF_Q + 1536>(a3, l16);
            float sa[4] = {0, 0, 0, 0}, sc2[4] = {0, 0, 0, 0};
            mma16816(sa, a0[0], a0[1], a0[2], a0[3], kb0[0], kb0[1]);
            mma16816(sc2, a2[0], a2[1], a2[2], a2[3], kb1[0], kb1[1]);
            mma16816(sa, a1[0], a1[1], a1[2], a1[3], kb0[2], kb0[3]);
            mma16816(sc2, a3[0], a3[1], a3[2], a3[3], kb1[2], kb1[3]);
            const float x0 = (sa[0] + sa[2]) + (sc2[0] + sc2[2]), x1 = (sa[1] + sa[3]) + (sc2[1] + sc2[3]);
            const uint32_t xp = pack_bf16(x0, x1);
            st_async_b32_i<OFF_SR + 1024 + 128>(xr + d1, xp, sb + MB_S + d1);
            st_async_b32_i<OFF_SR + 1024>(xr + d2, xp, sb + MB_S + d2);
            stsm_x2(l16 + OFF_S + 1024, __float_as_uint(x0), __float_as_uint(x1));
          } else if (wi == 0) {
            const uint4 si = lds128_i<SC_IN>(sb + 16 * (s & 1));
            const int em = (int)(si.y >> 10) - 14 + (int)(si.x >> 23) - 127;
            const uint32_t osc = __float_as_uint(exp2i(max(min((int)si.z - max(em, 1), 100), -100)));
            sts32(l16 + OFF_LT + 12, osc); sts64_i<SC_IN>(sb + 16 * ((s + 1) & 1), 0x7f000000u - osc, 0u);
          }
          bar_sync(B_SL, 256);
        }
      } else {
        float v0[4] = {0, 0, 0, 0}, v1[4] = {0, 0, 0, 0}, q0[4] = {0, 0, 0, 0}, q1[4] = {0, 0, 0, 0};
        constexpr int NB1 = NQ1 / 2 < 3 ? NQ1 / 2 : 3;
        uint32_t b[NB1][4];
        static_for<0, NB1>([&](auto T) { ldsm_x4_i<OFF_MEM + (NPQ + T.value) * 512>(b[T.value], mema); });
        static_for<0, NQ1 / 2>([&](auto T) {
          constexpr int t = T.value, p = NPQ + t;
          uint32_t (&bb)[4] = b[t % NB1];
          mma16816h(q0, rq[(2 * t) % NP1], bb[0], bb[1]);
          if constexpr (2 * t + NP1 < NQ1) ldsm_x4_t_i<OFF_WQ + (2 * t + NP1) * 2048>(rq[(2 * t) % NP1], wqa);
          mma16816h(q1, rq[(2 * t + 1) % NP1], bb[2], bb[3]);
          if constexpr (2 * t + 1 + NP1 < NQ1) ldsm_x4_t_i<OFF_WQ + (2 * t + 1 + NP1) * 2048>(rq[(2 * t + 1) % NP1], wqa);
          mma16816h(v0, w[2 * p], bb[0], bb[1]);
          mma16816h(v1, w[2 * p + 1], bb[2], bb[3]);
          if constexpr (t + NB1 < NQ1 / 2) ldsm_x4_i<OFF_MEM + (p + NB1) * 512>(bb, mema);
        });
        const float sq = sin_ * iq, sv = sin_ * iw;
        stsm_x2_t_i<0>(sta, pack_bf16((q0[0] + q1[0]) * sq, (q0[1] + q1[1]) * sq), pack_bf16((q0[2] + q1[2]) * sq, (q0[3] + q1[3]) * sq));
        TS(2);
        bar_arrive(B_QK, 384);
        float v2[4] = {0, 0, 0, 0}, v3[4] = {0, 0, 0, 0};
        auto vpair = [&](auto P, uint32_t (&bb)[4]) {
          constexpr int p = P.value;
          if constexpr (p & 1) { mma16816h(v0, w[2 * p], bb[0], bb[1]); mma16816h(v1, w[2 * p + 1], bb[2], bb[3]); }
          else { mma16816h(v2, w[2 * p], bb[0], bb[1]); mma16816h(v3, w[2 * p + 1], bb[2], bb[3]); }
        };
        if constexpr (NVE > 0) {
          uint32_t e[NVE ? NVE : 1][4];
          bar_sync(B_E, 256);
          static_for<0, NVE>([&](auto T) { ldsm_x4_i<OFF_MEM + T.value * 512>(e[T.value], mema); });
          static_for<0, NVE>([&](auto T) { vpair(T, e[T.value]); });
        }
        bar_sync(B_A, 288);
        uint32_t c[4][4];
        static_for<NVE, (NVE + 4 < NPQ ? NVE + 4 : NPQ)>([&](auto T) { ldsm_x4_i<OFF_MEM + T.value * 512>(c[T.value & 3], mema); });
        static_for<NVE, NPQ>([&](auto T) {
          constexpr int p = T.value;
          vpair(T, c[p & 3]);
          if constexpr (p + 4 < NPQ) ldsm_x4_i<OFF_MEM + (p + 4) * 512>(c[p & 3], mema);
        });
        stsm_x2_t_i<OFF_KV + KVB + 512>(l16 + (l16 & 128) * 4 + (wi * 1280 + (s & 1) * (2 * KVB)), pack_bf16(((v0[0] + v1[0]) + (v2[0] + v3[0])) * sv, ((v0[1] + v1[1]) + (v2[1] + v3[1])) * sv),
                            pack_bf16(((v0[2] + v1[2]) + (v2[2] + v3[2])) * sv, ((v0[3] + v1[3]) + (v2[3] + v3[3])) * sv));
        bar_arrive(B_V, 256);
      }
      TS(3);
      {
        uint32_t t1[12][4], t2[12][4];
        const uint32_t o16 = l16;
        wo1 = l16 + (OFF_WO + warp * 896);
        wo2 = sb + OFF_WO + warp * 896 + ((l16 & 128) ? 768 + ((l16 & 256) >> 2) + (l16 & 16) + ((l16 & 64) >> 1) : 512 + ((l16 & 256) >> 1) + (l16 & 112));
        auto ldw = [&](auto K) { if constexpr (K.value < 12 - NPM) { ldsm_x4_i<K.value * WOK>(t1[K.value], wo1); ldsm_x4_i<K.value * WOK>(t2[K.value], wo2); } };
        constexpr int NR_ = NRT - NPM;
        constexpr int PB = (hf ? PB1 : PB0) < NR_ ? (hf ? PB1 : PB0) : NR_, PA = (hf ? PA1 : PA0) < PB ? (hf ? PA1 : PA0) : PB;
        static_for<0, PA>(ldw);
        mbar_spin(sb + MB_X, (s + 1) & 1);
        if constexpr (PB > PA) {
          constexpr int PM = PA + PM1 < PB ? PA + PM1 : PB;
          mbar_spin(sb + MB_S, s & 1);
          const uint32_t t0 = clk_v();
          if constexpr (PM > PA) { while (clk_v() - t0 < GD1) {} static_for<PA, PM>(ldw); }
          if constexpr (PB > PM) { while (clk_v() - t0 < GD2) {} static_for<PM, PB>(ldw); }
        }
        float c0[4] = {0, 0, 0, 0}, c1[4] = {0, 0, 0, 0}, e0[4] = {0, 0, 0, 0}, e1[4] = {0, 0, 0, 0};
        uint32_t ob[6][4];
        auto kstep = [&](auto K) {
          constexpr int k = K.value;
          uint32_t (&bb)[4] = ob[k >> 1];
          uint32_t (&x)[4] = k < 12 - NPM ? t1[k] : u1[k < 12 - NPM ? 0 : k - (12 - NPM)];
          uint32_t (&y)[4] = k < 12 - NPM ? t2[k] : u2[k < 12 - NPM ? 0 : k - (12 - NPM)];
          if constexpr (k & 1) { mma16816(c1, x[0], x[1], x[2], x[3], bb[2], bb[3]); mma16816(e1, y[0], y[1], y[2], y[3], bb[2], bb[3]); }
          else { mma16816(c0, x[0], x[1], x[2], x[3], bb[0], bb[1]); mma16816(e0, y[0], y[1], y[2], y[3], bb[0], bb[1]); }
          if constexpr (k >= NRF) ldw(IC<k + NR_ - NRF>{});
        };
        auto ldo = [&](auto P) { ldsm_x4_i<OFF_O + P.value * 512>(ob[P.value], o16); };
        TS(4);
        bar_sync(B_O, 384);
        ldo(IC<0>{}); ldo(IC<1>{});
        SFENCE(o16);
        static_for<PB, NR_>(ldw);
        static_for<0, 4>(kstep);
        TS(5);
        mbar_spin(sb + MB_O, s & 1);
        TS(6);
        ldo(IC<2>{}); ldo(IC<NPM >= 2 ? 5 : 3>{});
        if (WOF) SFENCE(o16);
        kstep(IC<4>{});
        if constexpr (NPM < 2) { kstep(IC<5>{}); ldo(IC<4>{}); kstep(IC<6>{}); kstep(IC<7>{}); ldo(IC<5>{}); static_for<8, 12>(kstep); }
        else if constexpr (NPM >= 4) { kstep(IC<10>{}); kstep(IC<11>{}); ldo(IC<4>{}); kstep(IC<5>{}); ldo(IC<3>{}); kstep(IC<8>{}); kstep(IC<9>{}); kstep(IC<6>{}); kstep(IC<7>{}); }
        else { kstep(IC<5>{}); ldo(IC<3>{}); kstep(IC<11>{}); kstep(IC<10>{}); ldo(IC<4>{}); kstep(IC<6>{}); kstep(IC<7>{}); if constexpr (NPM == 3) { kstep(IC<9>{}); kstep(IC<8>{}); } else { kstep(IC<8>{}); kstep(IC<9>{}); } }
        l16 = fresh(l16);
        const int ln = (l16 >> 4) & 31;
        if constexpr (CEARLY && hf) { SFENCE2(o16, __float_as_uint(e1[0])); bar_arrive(B_G, 256); }
        unsigned char* gr = arena + (AR_ACC + acc_lane(bi, ln) + acc_voff(bv) + acc_step(s));
        const bool cnt = (ln & 1) || !t28;
        wqa = wq_addr(l16);
        SFENCE(o16);
        static_for<0, PQE>([&](auto K) { ldsm_x4_t_i<OFF_WQ + K.value * 2048>(rq[K.value], wqa); });
        const uint32_t y0 = movm_t(pack_f16(c0[0] + c1[0], c0[1] + c1[1])), y1 = movm_t(pack_f16(c0[2] + c1[2], c0[3] + c1[3]));
        const uint32_t y2 = movm_t(pack_f16(e0[0] + e1[0], e0[1] + e1[1])), y3 = movm_t(pack_f16(e0[2] + e1[2], e0[3] + e1[3]));
        asm volatile("red.relaxed.gpu.global.add.noftz.v4.f16x2 [%0], {%1,%2,%3,%4};" :: "l"(gr), "r"(y0), "r"(y1), "r"(y2), "r"(cnt ? 0x3c00u : y3) : "memory");
        bar_arrive(B_RED, 384);
        if constexpr (CEARLY && !hf) { bar_arrive(B_C, 256); bar_sync(B_G, 256); }
        else bar_sync(B_C, 256);
        TS(7);
      }
#if CHAIN_TIMING
      x_gemm((s + 1) & 1, tsb);
#else
      x_gemm((s + 1) & 1, 0);
#endif
      TS(8);
    }
    };
    if (hf == 0) run(IC<0>{}); else run(IC<1>{});
    {
      const uint32_t l16 = sb + (threadIdx.x & 31) * 16, mema = l16 ^ ((l16 >> 2) & 96);
      float c0[4] = {0, 0, 0, 0}, c1[4] = {0, 0, 0, 0}, c2[4] = {0, 0, 0, 0}, c3[4] = {0, 0, 0, 0};
      bar_sync(hf ? B_MEM1 : B_MEM0, 256);
      const float sc = __uint_as_float(lds32_i<SC_IN + 16>(sb)) * iw;
      static_for<0, 10>([&](auto T) {
        constexpr int p = 2 * T.value;
        uint32_t b0[4], b1[4];
        ldsm_x4_i<OFF_MEM + p * 512>(b0, mema); ldsm_x4_i<OFF_MEM + p * 512 + 512>(b1, mema);
        mma16816h(c0, w[2 * p], b0[0], b0[1]); mma16816h(c1, w[2 * p + 1], b0[2], b0[3]);
        mma16816h(c2, w[2 * p + 2], b1[0], b1[1]); mma16816h(c3, w[2 * p + 3], b1[2], b1[3]);
      });
      stsm_x2_t_i<OFF_KV + 2 * KVB + 512>(l16 + (l16 & 128) * 4 + wi * 1280 + hf * KVB, pack_bf16(((c0[0] + c1[0]) + (c2[0] + c3[0])) * sc, ((c0[1] + c1[1]) + (c2[1] + c3[1])) * sc),
                                          pack_bf16(((c0[2] + c1[2]) + (c2[2] + c3[2])) * sc, ((c0[3] + c1[3]) + (c2[3] + c3[3])) * sc));
      fence_proxy_async();
    }
    bar_arrive(B_RED, 384);
#if CHAIN_TIMING
    for (int i = tid; i < 288; i += 256) a.dbg[cta * 288 + i] = lds32_i<OFF_BAR + 128>(sb + i * 4);
#endif
    asm volatile("barrier.cluster.arrive.relaxed.aligned; barrier.cluster.wait.aligned;" ::: "memory");
  }
}
struct PrepArgs { const bf16 *wqkv, *wphi, *wo; unsigned char *wb, *wot; };
__device__ __forceinline__ void prep_body(const int cta, const PrepArgs& pa) {
  const int tid = threadIdx.x, lane = tid & 31, warp = tid >> 5, g = lane >> 2, q = lane & 3;
  const int pair = cta >> 1, which = cta & 1;
  uint32_t bfr[2][3][3];
#pragma unroll
  for (int hh = 0; hh < 2; hh++)
#pragma unroll
    for (int t = 0; t < 3; t++) {
      const unsigned short* ph = (const unsigned short*)pa.wphi + (2 * pair + hh) * 400 + (t < 2 ? 8 * t + g : 16 + (g >> 1)) + 2 * q * 20;
#pragma unroll
      for (int r = 0; r < 3; r++) {
        const int o = (r < 2 || q < 2) ? r * 160 : 0;
        const uint32_t v = (uint32_t)__ldg(ph + o) | ((uint32_t)__ldg(ph + o + 20) << 16);
        bfr[hh][t][r] = ((t < 2 || (g & 1) == hh) && (r < 2 || q < 2)) ? v : 0u;
      }
    }
  const int gt = cta * 256 + tid;
#pragma unroll 1
  for (int i = 0; i < 5; i++) {
    uint32_t af[2][6];
#pragma unroll
    for (int hh = 0; hh < 2; hh++) {
      const uint32_t* r0 = (const uint32_t*)(pa.wqkv + (size_t)((warp * 5 + i) * 16 + g) * 1920 + which * 640 + (2 * pair + hh) * 20) + q;
      af[hh][0] = __ldg(r0); af[hh][1] = __ldg(r0 + 7680); af[hh][2] = __ldg(r0 + 4); af[hh][3] = __ldg(r0 + 7684);
      af[hh][4] = __ldg(r0 + 8); af[hh][5] = __ldg(r0 + 7688);
    }
    const int iv = i * 4096 + (gt >> 1), k = (iv & 7) + (iv >> 8) * 8, h = (iv >> 3) & 31;
    const uint2* src = (const uint2*)(pa.wqkv + (size_t)k * 1920 + 1280 + h * 20) + (gt & 1) * 2;
    const uint2 a = __ldg(src), b = __ldg(src + 1), e = __ldg(src + 2);
    uint4 wv[2]; uint32_t wd[2];
#pragma unroll
    for (int n = 0; n < 2; n++) {
      const int iw = min((2 * i + n) * 5120 + gt, 640 * 80 - 1), r = iw & 7, c = (iw >> 3) % 80, kg = iw / 640, c5 = kg % 5;
      const int row = (kg / 5) * 40 + (c5 < 2 ? 8 * c5 + r : (c5 == 2 ? 16 + (r & 3) + (r >> 2) * 20 : 20 + 8 * (c5 - 3) + r));
      wv[n] = __ldg((const uint4*)(pa.wo + (size_t)row * cfg::DM + c * 8));
      wd[n] = (((c / 10) * 80 + kg) * 10 + c % 10) * 128 + r * 16;
    }
    uint4* dv = (uint4*)(pa.wb + ((size_t)((h >> 2) * 80 + (k >> 3)) * 32 + 20 + 3 * (h & 3)) * 128 + (k & 7) * 16);
    dv[(gt & 1) * 8] = make_uint4(a.x, a.y, b.x, b.y);
    if (gt & 1) dv[16] = (h & 1) ? make_uint4(0, 0, e.x, e.y) : make_uint4(e.x, e.y, 0, 0);
    if (gt < 5120) { *(uint4*)(pa.wot + wd[0]) = wv[0]; *(uint4*)(pa.wot + wd[1]) = wv[1]; }
    uint32_t* dst = (uint32_t*)(pa.wb + ((size_t)((pair >> 1) * 80 + (warp * 5 + i) * 2) * 32 + which * 10 + (pair & 1) * 5) * 128) + lane;
#pragma unroll
    for (int t = 0; t < 5; t++) {
      float d[4] = {0, 0, 0, 0};
#pragma unroll
      for (int hh = 0; hh < 2; hh++)
        if (t == 2 || (t > 2) == (hh == 1)) {
          const int tt = t < 3 ? t : t - 3;
          mma16816(d, af[hh][0], af[hh][1], af[hh][2], af[hh][3], bfr[hh][tt][0], bfr[hh][tt][1]);
          mma1688(d, q < 2 ? af[hh][4] : 0u, q < 2 ? af[hh][5] : 0u, bfr[hh][tt][2]);
        }
      dst[t * 32] = pack_bf16(d[0], d[1]); dst[1024 + t * 32] = pack_bf16(d[2], d[3]);
    }
  }
}

__global__ void __launch_bounds__(256, 4) ln_kernel(const bf16* __restrict__ xin, bf16* __restrict__ xn, uint2* __restrict__ xh, uint4* __restrict__ z0, int n0,
                                                    uint4* __restrict__ z1, int n1, const bf16* pfa, const bf16* pfb, int npf, int tl) {
  asm volatile("griddepcontrol.wait;" ::: "memory");
  asm volatile("griddepcontrol.launch_dependents;" ::: "memory");
  TL_BEGIN(tl);
  const int warp = threadIdx.x >> 5, lane = threadIdx.x & 31;
  const int row = blockIdx.x * 8 + warp;
  uint2 xw[1][5];
#pragma unroll
  for (int i = 0; i < 5; i++) xw[0][i] = *(const uint2*)(xin + (size_t)row * cfg::DM + i * 128 + lane * 4);
  for (int i = blockIdx.x * 256 + threadIdx.x; i < n0; i += 256 * 256) z0[i] = make_uint4(0, 0, 0, 0);
  for (int i = blockIdx.x * 256 + threadIdx.x; i < n1; i += 256 * 256) z1[i] = make_uint4(0, 0, 0, 0);
  if (npf && xw[0][4].y != 0x7fc17fc1u) {
    for (int i = 0; i < npf; i++) {
      const uint32_t l = (uint32_t)i * 32768u + (blockIdx.x * 256 + threadIdx.x) / 2;
      if (l < cfg::DM * cfg::HD / 64) asm volatile("prefetch.global.L2 [%0];" :: "l"(((threadIdx.x & 1) ? pfa : pfb) + (size_t)l * 64) : "memory");
    }
  }
  ln_rows<1>(xw, row, lane, xn, xh);
  TL_END(tl);
}
struct Pipe { uint32_t stage, phase; };
template <int NS> __device__ __forceinline__ void pipe_adv(Pipe& p) { if (++p.stage == NS) { p.stage = 0; p.phase ^= 1; } }
constexpr uint32_t SWZ128 = 1;
__device__ __forceinline__ uint64_t desc_kmajor(uint32_t a) { return make_desc(a, 16, 1024, SWZ128); }
__device__ __forceinline__ uint64_t desc_mnmajor(uint32_t a) { return make_desc(a, 8192, 1024, SWZ128); }
__device__ __forceinline__ void wait_ge(const void* p, uint32_t target, uint32_t ns = 32) {
  int spin = 0;
  while (ld_acquire_u32(p) < target) { __nanosleep(ns); if (++spin > (1 << 21)) break; }
}
__device__ __forceinline__ void bulk_g2s_hint(uint32_t dst, const void* src, uint32_t bytes, uint32_t mb, uint64_t pol) {
  asm volatile("cp.async.bulk.shared::cluster.global.mbarrier::complete_tx::bytes.L2::cache_hint [%0], [%1], %2, [%3], %4;"
               :: "r"(dst), "l"(src), "r"(bytes), "r"(mb), "l"(pol) : "memory");
}
#ifndef PF_WB
#define PF_WB 2
#endif
#ifndef PF_XN
#define PF_XN 1
#endif
#ifndef STAG
#define STAG 1
#endif
#ifndef EF_KV
#define EF_KV 1
#endif
#ifndef EF_O
#define EF_O 1
#endif
__device__ __forceinline__ void fence_proxy_async_global() { asm volatile("fence.proxy.async.global;" ::: "memory"); }

namespace tr {
constexpr int NS = 4, STQ = 16384 + 24576, STO = 16384 + 40960;
constexpr int SEGB = 15360;
constexpr int OFF_K = NS * STQ;
constexpr int OFF_BAR = NS * STO;
constexpr int SMEM = OFF_BAR + 256;
static_assert(OFF_K + 4 * SEGB <= OFF_BAR && SMEM <= 232448, "smem");
enum { T_QA = 0, T_Q, T_A, T_OB, T_OS, T_L, T_END, T_P };
constexpr uint32_t C_QA = AR_CNT, C_O = AR_CNT + 64, C_Q = AR_CNT + 128, C_P = AR_CNT + 192;
constexpr int MAXITEMS = 1200;
struct Sched {
  uint8_t ks[16];
  uint8_t wide[16];
  uint8_t lrows[16];
  uint32_t n;
  uint16_t item[MAXITEMS];
};
struct Args {
  const unsigned char *kg, *vg;
  unsigned char* o;
  uint4* qs;
  unsigned char* part;
  const bf16 *xin, *xq;
  bf16 *xout, *xn;
  unsigned char* arena;
  const unsigned* go;
  int tl;
  uint32_t nap, nap2;
  int pfprep;
};
}

template <int N0, int N1>
__device__ __forceinline__ void tr_mainloop(float (&a0)[N0 / 2], float (&a1)[N1 ? N1 / 2 : 1], Pipe& p, uint32_t sb, uint32_t full, uint32_t empty, int nkb, int wg) {
  using namespace tr;
  constexpr uint32_t ST = N1 ? STO : STQ;
  uint32_t prev = 0;
#pragma unroll
  for (int i = 0; i < N0 / 2; i++) a0[i] = 0.f;
  if constexpr (N1 > 0) {
#pragma unroll
    for (int i = 0; i < N1 / 2; i++) a1[i] = 0.f;
  }
#pragma unroll 1
  for (int kb = 0; kb < nkb; kb++) {
    mbar_wait(full + 8 * p.stage, p.phase);
    const uint32_t st = sb + p.stage * ST;
    wgmma_fence();
#pragma unroll
    for (int kk = 0; kk < 4; kk++) {
      const uint64_t da = desc_kmajor(st + wg * 8192 + kk * 32);
      if constexpr (N0 == 192) wgmma_n192<0, 1>(a0, da, desc_mnmajor(st + 16384 + kk * 2048), (kb | kk) != 0);
      else wgmma_n128<0, 1>(a0, da, desc_mnmajor(st + 16384 + kk * 2048), (kb | kk) != 0);
      if constexpr (N1 > 0) wgmma_n128<0, 1>(a1, da, desc_mnmajor(st + 16384 + 24576 + kk * 2048), (kb | kk) != 0);
    }
    wgmma_commit();
    if (kb > 0) { wgmma_wait<1>(); mbar_arrive_if((threadIdx.x & 127) == 0, empty + 8 * prev); }
    prev = p.stage;
    pipe_adv<NS>(p);
  }
  wgmma_wait<0>();
  mbar_arrive_if((threadIdx.x & 127) == 0, empty + 8 * prev);
}
template <int N> __device__ __forceinline__ void stage_tiles(const float (&o)[N / 2], uint32_t base, int wi, int lane) {
  const uint32_t ra = base + (wi * 16 + (lane & 7) + 8 * ((lane >> 3) & 1)) * 128;
#pragma unroll
  for (int v = 0; v < N / 8; v += 2)
    stsm_x4(ra + (v >> 3) * 8192 + ((((v & 7) + (lane >> 4)) ^ (lane & 7)) << 4), pack_bf16(o[4 * v], o[4 * v + 1]), pack_bf16(o[4 * v + 2], o[4 * v + 3]),
            pack_bf16(o[4 * v + 4], o[4 * v + 5]), pack_bf16(o[4 * v + 6], o[4 * v + 7]));
}
__global__ void __launch_bounds__(384, 1) trail_kernel(const __grid_constant__ CUtensorMap tmX, const __grid_constant__ CUtensorMap tmQ,
                                                       const __grid_constant__ CUtensorMap tmWo5, const __grid_constant__ CUtensorMap tmWo2,
                                                       const __grid_constant__ CUtensorMap tmP, const __grid_constant__ tr::Sched sc,
                                                       const __grid_constant__ tr::Args a, const __grid_constant__ PrepArgs pa) {
  using namespace tr;
  [[maybe_unused]] const int tl = a.tl;
  TL_BEGIN(tl);
  extern __shared__ __align__(1024) unsigned char smem_raw[];
  const uint32_t sb = smem_u32(smem_raw);
  const int warp = __shfl_sync(0xffffffffu, (int)threadIdx.x >> 5, 0), lane = threadIdx.x & 31;
  unsigned char* const arena = a.arena;
  const uint32_t full = sb + OFF_BAR, empty = full + 8 * NS, barK = empty + 8 * NS, barKfree = barK + 16, staged = barKfree + 16;
  const uint32_t kvrdy = staged + 32, mfull = kvrdy + 8, mempty = mfull + 16, mbox = mempty + 16;
  uint32_t go = 0;
  if (threadIdx.x == 256) go = ld_acquire_u32(a.go);
  if (threadIdx.x == 0) {
    for (int i = 0; i < NS; i++) { mbar_init(full + 8 * i, 1); mbar_init(empty + 8 * i, 2); }
    for (int i = 0; i < 2; i++) {
      mbar_init(barK + 8 * i, 1); mbar_init(barKfree + 8 * i, 1); mbar_init(staged + 16 * i, 4); mbar_init(staged + 16 * i + 8, 4);
      mbar_init(mfull + 8 * i, 1); mbar_init(mempty + 8 * i, 11);
    }
    mbar_init(kvrdy, 1);
    asm volatile("fence.mbarrier_init.release.cluster;" ::: "memory");
  }
  __syncthreads();
  Pipe mp{0, 0};
  auto next_item = [&]() -> uint32_t {
    uint32_t it;
    mbar_wait(mfull + 8 * mp.stage, mp.phase);
    asm volatile("ld.shared.u32 %0, [%1];" : "=r"(it) : "r"(mbox + 4 * mp.stage) : "memory");
    return it;
  };
  if (warp >= 8) {
    asm volatile("setmaxnreg.dec.sync.aligned.u32 40;");
    if (warp == 8) { go = __shfl_sync(0xffffffffu, go, 0); if (elect_one()) {
      Pipe p{0, 1};
      mp.phase = 1;
      uint32_t kph = 1, rph = 0, wide = 0, qdone = 0;
      prefetch_tmap(&tmX); prefetch_tmap(&tmQ); prefetch_tmap(&tmWo5); prefetch_tmap(&tmWo2); prefetch_tmap(&tmP);
      const uint64_t ef = policy_evict_first();
      auto ld_kv = [&](uint32_t d, const void* s, uint32_t n, uint32_t mb) { if (EF_KV) bulk_g2s_hint(d, s, n, mb, ef); else bulk_g2s(d, s, n, mb); };
      auto ld_o = [&](uint32_t d, const void* s, uint32_t n, uint32_t mb) { if (EF_O) bulk_g2s_hint(d, s, n, mb, ef); else bulk_g2s(d, s, n, mb); };
      auto stage = [&](uint32_t bytes) -> uint32_t {
        mbar_wait(empty + 8 * p.stage, p.phase);
        mbar_expect_tx(full + 8 * p.stage, bytes);
        return sb + p.stage * (wide ? STO : STQ);
      };
      auto fetch = [&]() -> uint32_t { uint32_t v; asm volatile("atom.relaxed.gpu.global.add.u32 %0, [%1], 1;" : "=r"(v) : "l"(arena + AR_QUEUE) : "memory"); return v; };
      if (!go) wait_ge(a.go, 1, 200);
      fence_proxy_async_global();
      uint32_t next = fetch();
      while (true) {
        const uint32_t item = next;
        const uint32_t code = sc.item[min(item, sc.n)];
        const int type = (code >> 11) & 7, m = (code >> 7) & 15, k = code & 127;
        const bool late = code >> 14;
        auto done_wait = [&]() { mbar_wait(mempty + 8 * (mp.stage ^ 1), mp.stage ? mp.phase ^ 1 : mp.phase); };
        if (type == T_A && !((qdone >> m) & 1)) { wait_ge(arena + C_Q + m * 4, 64); qdone |= 1u << m; }
        if (type == T_OB && !wide) for (uint32_t i = 0; i < NS; i++) mbar_wait(empty + 8 * i, i >= p.stage ? p.phase : p.phase ^ 1);
        wide = type == T_OB;
        mbar_wait(mempty + 8 * mp.stage, mp.phase);
        asm volatile("st.shared.u32 [%0], %1;" :: "r"(mbox + 4 * mp.stage), "r"((p.stage << 24) | (type << 16) | (m << 8) | (k & 255)) : "memory");
        mbar_arrive(mfull + 8 * mp.stage);
        pipe_adv<2>(mp);
        if (type == T_END) break;
        if (type == T_P) { done_wait(); next = fetch(); continue; }
        if (type == T_L) {
          const int nr = sc.lrows[m], np = sc.ks[m];
          prefetch_l2(a.xin + (size_t)(m * 128 + k * 8 * nr) * cfg::DM, nr * 10240);
          wait_ge(arena + C_O + m * 4, np * (sc.wide[m] ? 4 : 10), m < 13 ? a.nap : 32);
          fence_proxy_async_global();
#pragma unroll 1
          for (int r = 0; r < nr; r++) {
            const int rg = m * 16 + k * nr + r;
#pragma unroll 1
            for (int q0 = 0; q0 <= np; q0 += 4) {
              const int n = min(4, np + 1 - q0);
              const uint32_t st = stage(n * 10240), fb = full + 8 * p.stage;
#pragma unroll 1
              for (int q = q0; q < q0 + n; q++) {
                if (q == 0) bulk_g2s(st, a.xin + (size_t)rg * 8 * cfg::DM, 10240, fb);
                else tma_load_3d(st + (q - q0) * 10240, &tmP, 0, rg & 7, ((q - 1) * 32 + (rg >> 3)) * 10, fb);
              }
              pipe_adv<NS>(p);
            }
          }
          if (late) done_wait();
          next = fetch(); continue;
        }
        if (type <= T_A) {
          if (type != T_A)
#pragma unroll 1
            for (int kb = 0; kb < 10; kb++) {
              const uint32_t st = stage(STQ), fb = full + 8 * p.stage;
              tma_load_2d(st, &tmX, kb * 64, m * 128, fb);
              tma_load_3d(st + 16384, &tmQ, 0, kb * 64, k * 3, fb);
              pipe_adv<NS>(p);
              if (type == T_Q && kb == 8) next = fetch();
            }
          if (type != T_Q) {
            const size_t blk = ((size_t)m * 4 * 96 + k * 3) * 5120;
            kph ^= 1;
            mbar_wait(kvrdy, rph); rph ^= 1;
            if (!late) next = fetch();
            fence_proxy_async_global();
#pragma unroll 1
            for (int w = type == T_A ? 0 : 2; w < 4; w++) {
              const uint32_t st = stage(2 * SEGB), fb = full + 8 * p.stage;
              for (int sg = 0; sg < 2; sg++) ld_kv(st + sg * SEGB, (w < 2 ? a.kg : a.vg) + blk + (size_t)(2 * (w & 1) + sg) * (96 * 5120), SEGB, fb);
              pipe_adv<NS>(p);
            }
            if (late) { done_wait(); next = fetch(); }
          }
        } else {
          const int nn = wide ? 2 : 5, nb = wide ? 5 : 2, nt = k % nn, nkb = 96 / sc.ks[m], k0 = (k / nn) * nkb;
          const Pipe p0 = p;
          for (int kb = 0; kb < nkb; kb++) {
            if (wide && kb < NS && p.stage >= 2) { mbar_wait(barKfree, kph); mbar_wait(barKfree + 8, kph); }
            const uint32_t st = stage(16384 + nb * 8192), fb = full + 8 * p.stage;
            tma_load_3d(st + 16384, wide ? &tmWo5 : &tmWo2, 0, (k0 + kb) * 64, nt * nb, fb);
            if (kb >= NS) ld_o(st, a.o + ((size_t)m * 96 + k0 + kb) * 16384, 16384, fb);
            pipe_adv<NS>(p);
            if (kb == NS - 1 || (kb == nkb - 1 && nkb < NS)) {
              wait_ge(arena + C_QA + m * 4, 64, m < 14 ? a.nap : 32);
              fence_proxy_async_global();
              Pipe q = p0;
#pragma unroll 1
              for (int i = 0; i <= kb; i++) { ld_o(sb + q.stage * (wide ? STO : STQ), a.o + ((size_t)m * 96 + k0 + i) * 16384, 16384, full + 8 * q.stage); pipe_adv<NS>(q); }
            }
          }
          if (!late) next = fetch();
          for (int w = wide ? -(int)((2 - p.stage) & 3) : 0; w < 2; w++) { mbar_wait(empty + 8 * p.stage, p.phase); mbar_arrive(full + 8 * p.stage); pipe_adv<NS>(p); }
          kph ^= wide;
          if (late) { done_wait(); next = fetch(); }
        }
      }
    } } else if (warp < 11) { if (elect_one()) {
      const int w = warp - 9;
      uint32_t sph = 0;
      [[maybe_unused]] int nlog = 0;
#ifdef TIMELINE
      if (w == 0) { unsigned long long* lg = g_log + (((tl >= 12) * 132 + blockIdx.x) * 64 + nlog++) * 2; lg[0] = T_END << 16; lg[1] = gtime(); lg[2] = ~0ull; }
#endif
      while (true) {
        const uint32_t it = next_item();
        const int type = (it >> 16) & 255, m = (it >> 8) & 255, k = it & 255;
        const uint32_t slot = mp.stage;
        pipe_adv<2>(mp);
        if (type == T_END) break;
        mbar_wait(staged + 16 * w + 8 * slot, (sph >> slot) & 1); sph ^= 1u << slot;
        mbar_arrive(mempty + 8 * slot);
#ifdef TIMELINE
        if (w == 0 && nlog < 63) { unsigned long long* lg = g_log + (((tl >= 12) * 132 + blockIdx.x) * 64 + nlog++) * 2; lg[0] = (type << 16) | (m << 8) | k; lg[1] = gtime(); lg[2] = ~0ull; }
#endif
        if (type == T_L) continue;
        if (type == T_QA || type == T_A) {
          for (int jj = 0; jj < 3; jj++) bulk_s2g(a.o + ((size_t)m * 96 + k * 3 + jj) * 16384 + w * 8192, sb + OFF_K + w * 2 * SEGB + jj * 8192, 8192);
          bulk_commit();
          bulk_wait<0>();
          mbar_arrive(barKfree + 8 * w);
        } else if (type == T_OB || type == T_OS) {
          const bool wide = type == T_OB;
          const int nn = wide ? 2 : 5, nb = wide ? 5 : 2;
          const uint32_t own = wide ? 2 + w : ((it >> 24) + 96 / sc.ks[m] + w) % NS;
          bulk_s2g(a.part + ((size_t)((k / nn) * 32 + m * 2 + w) * 10 + (k % nn) * nb) * 8192, sb + own * (wide ? STO : STQ), nb * 8192);
          bulk_commit();
          bulk_wait<0>();
          mbar_arrive(empty + 8 * own);
          if (wide && w) { mbar_arrive(barKfree); mbar_arrive(barKfree + 8); }
        }
        red_release_inc(arena + (type == T_Q ? C_Q : (type <= T_A ? C_QA : (type == T_P ? C_P : C_O))) + m * 4);
      }
    } } else if (elect_one()) {
      const uint64_t ef = policy_evict_first();
      uint32_t kph = 1;
      if (PF_WB && blockIdx.x >= 52) { prefetch_l2(pa.wb + (blockIdx.x - 52) * 32768, 32768); prefetch_l2(pa.wot + (blockIdx.x - 52) * 10240, 10240); }
      if (PF_WB > 1 && blockIdx.x >= 52) { prefetch_l2(a.xn + (blockIdx.x - 52) * 8192, 16384); prefetch_l2(a.xout + (blockIdx.x - 52) * 8192, 16384); }
      while (true) {
        const uint32_t it = next_item();
        const int type = (it >> 16) & 255, m = (it >> 8) & 255, k = it & 255;
        const uint32_t slot = mp.stage;
        pipe_adv<2>(mp);
        if (type == T_END) break;
        if (a.pfprep && type == T_QA && m == 0) { prefetch_l2(pa.wqkv + k * 38400, 76800); prefetch_l2(pa.wo + k * 12800, 25600); }
        if (PF_XN && type == T_QA && m < 15) prefetch_l2(a.xq + ((m + 1) * 128 + k * 4) * cfg::DM, 5120);
        if (type == T_QA || type == T_A) {
          for (int spin = 0; spin < (1 << 21); spin++) {
            uint4 f;
            asm volatile("ld.acquire.gpu.global.v4.u32 {%0,%1,%2,%3}, [%4];" : "=r"(f.x), "=r"(f.y), "=r"(f.z), "=r"(f.w) : "l"(arena + prog_off(k, 0)) : "memory");
            if (min(min(f.x, f.y), f.z) >= (uint32_t)(4 * m + 4)) break;
            __nanosleep(m < 15 ? a.nap : a.nap2);
          }
          mbar_arrive(kvrdy);
          fence_proxy_async_global();
          const unsigned char* src = a.kg + ((size_t)m * 4 * 96 + k * 3) * 5120;
#pragma unroll 1
          for (int w = 0; w < 2; w++) {
            mbar_wait(barKfree + 8 * w, kph);
            if (type == T_A) { mbar_arrive(barK + 8 * w); continue; }
            mbar_expect_tx(barK + 8 * w, 2 * SEGB);
            for (int sg = 2 * w; sg < 2 * w + 2; sg++) { if (EF_KV) bulk_g2s_hint(sb + OFF_K + sg * SEGB, src + (size_t)sg * (96 * 5120), SEGB, barK + 8 * w, ef); else bulk_g2s(sb + OFF_K + sg * SEGB, src + (size_t)sg * (96 * 5120), SEGB, barK + 8 * w); }
          }
          kph ^= 1;
        } else if (type == T_OB) {
          mbar_wait(barKfree, kph); mbar_wait(barKfree + 8, kph);
          kph ^= 1;
        }
        mbar_arrive(mempty + 8 * slot);
      }
      if (blockIdx.x == gridDim.x - 1) asm volatile("griddepcontrol.wait;" ::: "memory");
    }
    return;
  }
  asm volatile("setmaxnreg.inc.sync.aligned.u32 232;");
  const int wg = warp >> 2, wi = warp & 3;
  const int g = lane >> 2, q4 = lane & 3;
  asm volatile("griddepcontrol.launch_dependents;" ::: "memory");
  Pipe p{0, 0};
  uint32_t kph = 0;
  auto own_slot = [&]() -> uint32_t {
    const uint32_t sA = p.stage, phA = p.phase; pipe_adv<NS>(p);
    const uint32_t sB = p.stage, phB = p.phase; pipe_adv<NS>(p);
    if (wi == 0) mbar_wait(full + 8 * (wg ? sA : sB), wg ? phA : phB);
    mbar_wait(full + 8 * (wg ? sB : sA), wg ? phB : phA);
    mbar_arrive_if((threadIdx.x & 127) == 0, empty + 8 * (wg ? sA : sB));
    return wg ? sB : sA;
  };
  while (true) {
    const uint32_t it = __shfl_sync(0xffffffffu, next_item(), 0);
    const int type = (it >> 16) & 255, m = (it >> 8) & 255, k = it & 255;
    mbar_arrive_if(lane == 0, mempty + 8 * mp.stage);
    const uint32_t done = staged + 16 * wg + 8 * mp.stage;
    pipe_adv<2>(mp);
    if (type == T_END) break;
    if (type == T_P) {
      prep_body(k, pa);
      __syncwarp();
      mbar_arrive_if(lane == 0, done);
      continue;
    }
    if (type == T_L) {
      const int nr = sc.lrows[m], np = sc.ks[m];
      const uint32_t po = (lane >> 4) * 1024 + warp * 128 + ((((lane >> 1) & 7) ^ warp) << 4) + (lane & 1) * 8;
#pragma unroll 1
      for (int r = 0; r < nr; r++) {
        uint2 xw[1][5]; float s[20];
#pragma unroll
        for (int i = 0; i < 20; i++) s[i] = 0.f;
#pragma unroll 1
        for (int q0 = 0; q0 <= np; q0 += 4) {
          const uint32_t st = sb + p.stage * STQ;
          mbar_wait(full + 8 * p.stage, p.phase);
          if (q0 == 0) static_for<0, 5>([&](auto I) { xw[0][I.value] = lds64_i<I.value * 256>(st + warp * 1280 + lane * 8); });
#pragma unroll 1
          for (int q = q0 ? 0 : 1; q < min(4, np + 1 - q0); q++)
            static_for<0, 5>([&](auto I) {
              constexpr int i = I.value;
              const uint2 t = lds64_i<i * 2048>(st + q * 10240 + po);
              s[4 * i] += bf_lo(t.x); s[4 * i + 1] += bf_hi(t.x); s[4 * i + 2] += bf_lo(t.y); s[4 * i + 3] += bf_hi(t.y);
            });
          bar_sync(3 + wg, 128);
          mbar_arrive_if((threadIdx.x & 127) == 0, empty + 8 * p.stage);
          pipe_adv<NS>(p);
        }
        const int row = (m * 16 + k * nr + r) * 8 + warp;
#pragma unroll
        for (int i = 0; i < 5; i++) {
          bf16r2(s[4 * i], s[4 * i + 1]); bf16r2(s[4 * i + 2], s[4 * i + 3]);
          xw[0][i] = make_uint2(pack_bf16(bf_lo(xw[0][i].x) + s[4 * i], bf_hi(xw[0][i].x) + s[4 * i + 1]), pack_bf16(bf_lo(xw[0][i].y) + s[4 * i + 2], bf_hi(xw[0][i].y) + s[4 * i + 3]));
          *(uint2*)(a.xout + (size_t)row * cfg::DM + i * 128 + lane * 4) = xw[0][i];
        }
        ln_rows<1>(xw, row, lane, a.xn, nullptr);
      }
      __syncwarp();
      mbar_arrive_if(lane == 0, done);
      continue;
    }
    if (type >= T_OB) {
      const int nkb = 96 / sc.ks[m];
      if (type == T_OB) {
        float a0[96], a1[64];
        tr_mainloop<192, 128>(a0, a1, p, sb, full, empty, nkb, wg);
        while (p.stage != 2) { if (wi == 0) mbar_wait(full + 8 * p.stage, p.phase); mbar_arrive_if((threadIdx.x & 127) == 0, empty + 8 * p.stage); pipe_adv<NS>(p); }
        const uint32_t st = sb + own_slot() * STO;
        stage_tiles<192>(a0, st, wi, lane); stage_tiles<128>(a1, st + 24576, wi, lane);
      } else {
        float a0[64], a1[1];
        tr_mainloop<128, 0>(a0, a1, p, sb, full, empty, nkb, wg);
        stage_tiles<128>(a0, sb + own_slot() * STQ, wi, lane);
      }
      fence_proxy_async();
      __syncwarp();
      mbar_arrive_if(lane == 0, done);
      continue;
    }
    uint32_t qf[12][4];
    uint4* qp = a.qs + ((size_t)((m & 7) * 32 + k) * 12) * 256 + threadIdx.x;
    if (type != T_A) {
      float acc[96], a1[1];
      tr_mainloop<192, 0>(acc, a1, p, sb, full, empty, 10, wg);
#pragma unroll
      for (int i = 0; i < 12; i++) {
        qf[i][0] = pack_bf16(acc[8 * i], acc[8 * i + 1]); qf[i][1] = pack_bf16(acc[8 * i + 2], acc[8 * i + 3]);
        qf[i][2] = pack_bf16(acc[8 * i + 4], acc[8 * i + 5]); qf[i][3] = pack_bf16(acc[8 * i + 6], acc[8 * i + 7]);
      }
      if (type == T_Q) {
#pragma unroll
        for (int i = 0; i < 12; i++) qp[i * 256] = make_uint4(qf[i][0], qf[i][1], qf[i][2], qf[i][3]);
        __syncwarp();
        mbar_arrive_if(lane == 0, done);
        continue;
      }
    } else {
#pragma unroll
      for (int i = 0; i < 12; i++) { const uint4 v = __ldcg(qp + i * 256); qf[i][0] = v.x; qf[i][1] = v.y; qf[i][2] = v.z; qf[i][3] = v.w; }
    }
    const uint32_t ost = sb + OFF_K + wg * 2 * SEGB;
    const bool second = wi >= 2;
    uint32_t pf[5][4];
    {
      float sa[20], sb2[20];
      uint32_t kbase = ost, kslot = 0;
      if (type == T_A) { kslot = own_slot(); kbase = sb + kslot * STQ; } else mbar_wait(barK + 8 * wg, kph);
      if (STAG && wg) bar_sync(1, 256);
      wgmma_fence();
#pragma unroll
      for (int i = 0; i < 12; i++) {
        wgmma_rs_n40<0>(sa, qf[i][0], qf[i][1], qf[i][2], qf[i][3], make_desc(kbase + i * 1280, 640, 128, 0), i != 0);
        wgmma_rs_n40<0>(sb2, qf[i][0], qf[i][1], qf[i][2], qf[i][3], make_desc(kbase + SEGB + i * 1280, 640, 128, 0), i != 0);
      }
      wgmma_commit();
      wgmma_wait<0>();
      if (STAG && !wg) bar_arrive(1, 256);
      mbar_arrive_if(type == T_A && (threadIdx.x & 127) == 0, empty + 8 * kslot);
      const float cs = 0.07216878364870322f * 1.4426950408889634f;
      const int r0 = 16 * (wi & 1) + g, r1 = r0 + 8;
      float m0 = -INFINITY, m1 = -INFINITY;
#pragma unroll
      for (int n = 0; n < 5; n++) {
#pragma unroll
        for (int e = 0; e < 2; e++) {
          const int key = 8 * n + 2 * q4 + e;
          float x = second ? sb2[4 * n + e] : sa[4 * n + e], y = second ? sb2[4 * n + 2 + e] : sa[4 * n + 2 + e];
          if (n < 4) { if (key > r0) x = -INFINITY; if (key > r1) y = -INFINITY; }
          sa[4 * n + e] = x; sa[4 * n + 2 + e] = y;
          m0 = fmaxf(m0, x); m1 = fmaxf(m1, y);
        }
      }
      m0 = fmaxf(m0, __shfl_xor_sync(0xffffffffu, m0, 1)); m1 = fmaxf(m1, __shfl_xor_sync(0xffffffffu, m1, 1));
      m0 = fmaxf(m0, __shfl_xor_sync(0xffffffffu, m0, 2)); m1 = fmaxf(m1, __shfl_xor_sync(0xffffffffu, m1, 2));
      float s0 = 0.f, s1 = 0.f;
#pragma unroll
      for (int n = 0; n < 5; n++) {
#pragma unroll
        for (int e = 0; e < 2; e++) {
          sa[4 * n + e] = ex2f((sa[4 * n + e] - m0) * cs); sa[4 * n + 2 + e] = ex2f((sa[4 * n + 2 + e] - m1) * cs);
          s0 += sa[4 * n + e]; s1 += sa[4 * n + 2 + e];
        }
      }
      s0 += __shfl_xor_sync(0xffffffffu, s0, 1); s1 += __shfl_xor_sync(0xffffffffu, s1, 1);
      s0 += __shfl_xor_sync(0xffffffffu, s0, 2); s1 += __shfl_xor_sync(0xffffffffu, s1, 2);
      const float i0 = rcpf(s0), i1 = rcpf(s1);
#pragma unroll
      for (int n = 0; n < 5; n++) {
        const uint32_t x = pack_bf16(sa[4 * n] * i0, sa[4 * n + 1] * i0), y = pack_bf16(sa[4 * n + 2] * i1, sa[4 * n + 3] * i1);
        if (n < 4) {
          pf[n >> 1][2 * (n & 1)] = second ? 0u : x; pf[n >> 1][2 * (n & 1) + 1] = second ? 0u : y;
          pf[2 + (n >> 1)][2 * (n & 1)] = second ? x : 0u; pf[2 + (n >> 1)][2 * (n & 1) + 1] = second ? y : 0u;
        } else {
          pf[4][0] = second ? 0u : x; pf[4][1] = second ? 0u : y; pf[4][2] = second ? x : 0u; pf[4][3] = second ? y : 0u;
        }
      }
    }
    {
      float o[96];
#pragma unroll
      for (int i = 0; i < 5; i++) { PIN(pf[i][0]); PIN(pf[i][1]); PIN(pf[i][2]); PIN(pf[i][3]); }
      const uint32_t own = own_slot(), vbase = sb + own * STQ;
      wgmma_fence();
#pragma unroll
      for (int i = 0; i < 5; i++)
        wgmma_rs_n192<1>(o, pf[i][0], pf[i][1], pf[i][2], pf[i][3], i < 4 ? make_desc(vbase + (i >> 1) * SEGB + (i & 1) * 256, 128, 640, 0) : make_desc(vbase + 512, SEGB, 640, 0), i != 0);
      wgmma_commit();
      if (type == T_A) mbar_wait(barK + 8 * wg, kph);
      kph ^= 1;
      wgmma_wait<0>();
      mbar_arrive_if((threadIdx.x & 127) == 0, empty + 8 * own);
      stage_tiles<192>(o, ost, wi, lane);
      fence_proxy_async();
      __syncwarp();
      mbar_arrive_if(lane == 0, done);
    }
  }
}
namespace bf {
constexpr int NS = 4, STAGE = 16384 + 32768;
constexpr int PIECE = 20480;
constexpr int OFF_PHI = 0, OFF_V = 40960, OFF_KV = 65536;
constexpr int OFF_OST = 5 * PIECE;
constexpr int OFF_WOT = 6 * PIECE;
constexpr int OFF_BAR = OFF_WOT + 102400;
constexpr int SMEM = OFF_BAR + 256;
static_assert(NS * STAGE <= OFF_BAR && SMEM <= 232448, "smem");
constexpr int KVACC = 32 * 5 * 1024;
struct Args {
  const unsigned char *wb, *wot;
  unsigned char *kvacc, *o2;
  const bf16* xin;
  bf16* xout;
  unsigned* go;
  const void* prep;
  const bf16 *pf0, *pf1;
  int pfn, pfns, pfwait;
  int tl;
};
}
__device__ __forceinline__ void hedgehog_features(float (&x)[2][5], uint32_t (&w)[2][5]) {
  const float L = 1.4426950408889634f;
  float mx[2], mn[2], sp[2], sn[2], pos[2][5], neg[2][5];
#pragma unroll
  for (int r = 0; r < 2; r++) {
    mx[r] = fmaxf(fmaxf(fmaxf(x[r][0], x[r][1]), fmaxf(x[r][2], x[r][3])), x[r][4]);
    mn[r] = fminf(fminf(fminf(x[r][0], x[r][1]), fminf(x[r][2], x[r][3])), x[r][4]);
  }
#pragma unroll
  for (int o = 1; o < 4; o <<= 1)
#pragma unroll
    for (int r = 0; r < 2; r++) {
      const uint32_t t = __shfl_xor_sync(0xffffffffu, __byte_perm(__float_as_uint(mn[r]), __float_as_uint(mx[r]), 0x7632), o);
      mx[r] = fmaxf(mx[r], bf_hi(t)); mn[r] = fminf(mn[r], bf_lo(t));
    }
#pragma unroll
  for (int r = 0; r < 2; r++) {
#pragma unroll
    for (int i = 0; i < 5; i++) { pos[r][i] = ex2f((x[r][i] - mx[r]) * L); neg[r][i] = ex2f((mn[r] - x[r][i]) * L); }
    sp[r] = ((pos[r][0] + pos[r][1]) + (pos[r][2] + pos[r][3])) + pos[r][4];
    sn[r] = ((neg[r][0] + neg[r][1]) + (neg[r][2] + neg[r][3])) + neg[r][4];
  }
#pragma unroll
  for (int o = 1; o < 4; o <<= 1)
#pragma unroll
    for (int r = 0; r < 2; r++) { sp[r] += __shfl_xor_sync(0xffffffffu, sp[r], o); sn[r] += __shfl_xor_sync(0xffffffffu, sn[r], o); }
#pragma unroll
  for (int r = 0; r < 2; r++) {
    const float ip = rcpf(sp[r]), in_ = rcpf(sn[r]);
    w[r][0] = pack_bf16(pos[r][0] * ip, pos[r][1] * ip); w[r][1] = pack_bf16(pos[r][2] * ip, pos[r][3] * ip);
    w[r][2] = pack_bf16(neg[r][0] * in_, neg[r][1] * in_); w[r][3] = pack_bf16(neg[r][2] * in_, neg[r][3] * in_);
    w[r][4] = pack_bf16(pos[r][4] * ip, neg[r][4] * in_);
  }
}
__device__ __forceinline__ void bulk_g2s_mc(uint32_t dst, const void* src, uint32_t bytes, uint32_t mb) {
  asm volatile("cp.async.bulk.shared::cluster.global.mbarrier::complete_tx::bytes.multicast::cluster [%0], [%1], %2, [%3], %4;"
               :: "r"(dst), "l"(src), "r"(bytes), "r"(mb), "h"((unsigned short)3) : "memory");
}
__device__ __forceinline__ void mbar_arrive_remote_if(bool c, uint32_t b) {
  asm volatile("{\n.reg .pred p;\nsetp.ne.u32 p, %1, 0;\n@p mbarrier.arrive.shared::cluster.b64 _, [%0];\n}" :: "r"(b), "r"((uint32_t)c) : "memory");
}

__global__ void __cluster_dims__(2, 1, 1) __launch_bounds__(384, 1) blayer_kernel(const __grid_constant__ CUtensorMap tmA, const __grid_constant__ bf::Args a) {
  using namespace bf;
  [[maybe_unused]] const int tl = a.tl;
  extern __shared__ __align__(1024) unsigned char smem_raw[];
  const uint32_t sb = smem_u32(smem_raw);
  const int warp = __shfl_sync(0xffffffffu, (int)threadIdx.x >> 5, 0), lane = threadIdx.x & 31;
  const uint32_t full = sb + OFF_BAR, empty = full + 8 * NS, full2 = empty + 8 * NS, empty2 = full2 + 64, barW = empty2 + 16, drained = barW + 8, staged = drained + 8, freeb = staged + 8;
  const int rank = blockIdx.x & 1, u = (blockIdx.x >> 1) & 7, mp = blockIdx.x >> 4;
  const int m = 2 * mp + rank;
  const int m2 = 2 * mp + (u & 1), ns = (u & ~1) + rank;
  const uint32_t dpeer = mapa_u32(sb, rank ^ 1) - sb;
  unsigned* cntO = (unsigned*)(a.kvacc + KVACC);
  if (threadIdx.x == 0) {
    for (int i = 0; i < NS; i++) { mbar_init(full + 8 * i, 1); mbar_init(empty + 8 * i, 4); }
    for (int i = 0; i < 8; i++) mbar_init(full2 + 8 * i, 1);
    mbar_init(empty2, 2); mbar_init(empty2 + 8, 2);
    mbar_init(barW, 1); mbar_init(drained, 1); mbar_init(staged, 8); mbar_init(freeb, 2);
    asm volatile("fence.mbarrier_init.release.cluster;" ::: "memory");
  }
  __syncthreads();
  asm volatile("barrier.cluster.arrive.relaxed.aligned; barrier.cluster.wait.aligned;" ::: "memory");
  if (warp >= 8) {
    asm volatile("setmaxnreg.dec.sync.aligned.u32 40;");
    if (warp == 8) { if (elect_one()) {
      const unsigned char* wsrc = a.wb + (size_t)u * 327680 + rank * 16384;
      if (a.prep) wait_ge(a.prep, 64);
      fence_proxy_async_global();
      for (int kb = 0; kb < NS; kb++) {
        mbar_expect_tx(full + 8 * kb, STAGE);
        bulk_g2s_mc(sb + kb * STAGE + 16384 + rank * 16384, wsrc + kb * 32768, 16384, full + 8 * kb);
      }
      asm volatile("griddepcontrol.wait;" ::: "memory");
      TL_BEGIN0(tl);
      if (blockIdx.x == 0) *a.go = 0;
      for (int kb = 0; kb < NS; kb++) tma_load_2d(sb + kb * STAGE, &tmA, kb * 64, m * 128, full + 8 * kb);
      if (m == 0) prefetch_l2(a.kvacc + u * (KVACC / 8), KVACC / 8);
#pragma unroll 1
      for (int kb = NS; kb < 10; kb++) {
        const uint32_t s = kb & 3, st = sb + s * STAGE, fb = full + 8 * s;
        mbar_wait(empty + 8 * s, ((kb >> 2) - 1) & 1);
        mbar_expect_tx(fb, STAGE);
        tma_load_2d(st, &tmA, kb * 64, m * 128, fb);
        bulk_g2s_mc(st + 16384 + rank * 16384, wsrc + kb * 32768, 16384, fb);
      }
      for (int i = 0; i < 6; i++) mbar_expect_tx(full2 + 8 * i, PIECE);
      mbar_wait(drained, 0);
      mbar_expect_tx(barW, 102400);
      bulk_g2s(sb + OFF_WOT, a.wot + (size_t)ns * 102400, 102400, barW);
      mbar_wait(staged, 0);
      bulk_s2g(a.o2 + (size_t)(m * 8 + u) * PIECE, sb + OFF_OST, PIECE);
      bulk_commit();
      bulk_wait<0>();
      mbar_arrive(freeb); mbar_arrive_remote_if(true, freeb + dpeer);
      red_release_inc(cntO + m);
      wait_ge(cntO + m2, 8, 20);
      mbar_wait(freeb, 0);
      fence_proxy_async_global();
      const unsigned char* osrc = a.o2 + (size_t)m2 * 8 * PIECE;
      for (int i = 0; i < 6; i++) bulk_g2s_mc(sb + i * PIECE + rank * (PIECE / 2), osrc + i * PIECE + rank * (PIECE / 2), PIECE / 2, full2 + 8 * i);
      for (int i = 0; i < 2; i++) {
        mbar_wait(empty2 + 8 * i, 0);
        mbar_expect_tx(full2 + 8 * (6 + i), PIECE);
        bulk_g2s(sb + i * PIECE, osrc + (6 + i) * PIECE, PIECE, full2 + 8 * (6 + i));
      }
    } } else if (warp == 9 && a.pf0) { if (elect_one()) {
      if (a.pfwait) asm volatile("griddepcontrol.wait;" ::: "memory");
      constexpr uint32_t CH = 2048;
      for (int i = 0; i < a.pfn; i++) {
        prefetch_l2((const unsigned char*)a.pf0 + (i * 128 + blockIdx.x) * CH, CH); prefetch_l2((const unsigned char*)a.pf1 + (i * 128 + blockIdx.x) * CH, CH);
        __nanosleep(a.pfns);
      }
    } }
    return;
  }
  asm volatile("setmaxnreg.inc.sync.aligned.u32 232;");
  const int wg = warp >> 2, wi = warp & 3;
  const int q4 = lane & 3;
  const bool lead = (threadIdx.x & 127) == 0;
  float acc[128];
  {
#pragma unroll 1
    for (int kb = 0; kb < 10; kb++) {
      const uint32_t s = kb & 3, st = sb + s * STAGE;
      mbar_wait(full + 8 * s, (kb >> 2) & 1);
      wgmma_fence();
#pragma unroll
      for (int kk = 0; kk < 4; kk++) wgmma_n256<0, 1>(acc, desc_kmajor(st + wg * 8192 + kk * 32), make_desc(st + 16384 + kk * 8192, 4096, 128, 0), (kb | kk) != 0);
      wgmma_commit();
      if (kb > 0 && kb < 7) { wgmma_wait<1>(); const uint32_t e = empty + 8 * ((kb - 1) & 3); mbar_arrive_if(lead, e); mbar_arrive_remote_if(lead, e + dpeer); }
    }
    wgmma_wait<0>();
    bar_sync(1, 256);
    mbar_arrive_if(threadIdx.x == 0, drained);
  }
  TL2((tl >= 12 ? 128 : 0) + 32 + 0);
  const uint32_t srow = (wg * 64 + wi * 16 + (lane & 15)) * 16 + (lane >> 4) * 2048;
  auto features = [&](auto T0, auto HH, uint32_t (&w)[2][5]) {
    constexpr int t = T0.value + 5 * (HH.value >> 1), o = (HH.value & 1) ? 3 : 0, e = HH.value & 1;
    float x[2][5];
#pragma unroll
    for (int r = 0; r < 2; r++) {
      x[r][0] = acc[4 * (t + o) + 2 * r]; x[r][1] = acc[4 * (t + o) + 2 * r + 1]; x[r][2] = acc[4 * (t + o + 1) + 2 * r]; x[r][3] = acc[4 * (t + o + 1) + 2 * r + 1];
      bf16r2(x[r][0], x[r][1]); bf16r2(x[r][2], x[r][3]);
    }
    x[0][4] = acc[4 * (t + 2) + e]; x[1][4] = acc[4 * (t + 2) + 2 + e];
    bf16r2(x[0][4], x[1][4]);
    hedgehog_features(x, w);
  };
  static_for<0, 4>([&](auto HH) {
    constexpr int hh = HH.value, t = 20 + 3 * hh;
    const uint32_t one = q4 == ((hh & 1) ? 0 : 2) ? 0x3f80u : 0u;
    const uint32_t va = sb + OFF_V + hh * 6144 + srow;
    stsm_x4(va, pack_bf16(acc[4 * t], acc[4 * t + 1]), pack_bf16(acc[4 * t + 2], acc[4 * t + 3]), pack_bf16(acc[4 * t + 4], acc[4 * t + 5]), pack_bf16(acc[4 * t + 6], acc[4 * t + 7]));
    const bool pad = (q4 >= 2) != (hh & 1);
    stsm_x2(va + 4096, pad ? one : pack_bf16(acc[4 * t + 8], acc[4 * t + 9]), pad ? one : pack_bf16(acc[4 * t + 10], acc[4 * t + 11]));
    uint32_t w[2][5];
    features(IC<10>{}, HH, w);
    const uint32_t pa = sb + OFF_PHI + hh * 10240 + srow;
    stsm_x4(pa, w[0][0], w[1][0], w[0][1], w[1][1]);
    stsm_x4(pa + 4096, w[0][2], w[1][2], w[0][3], w[1][3]);
    stsm_x2(pa + 8192, w[0][4], w[1][4]);
  });
  fence_proxy_async();
  bar_sync(1, 256);
  TL2((tl >= 12 ? 128 : 0) + 32 + 1);
  {
    float d0[12], d1[12];
    const uint32_t pa = sb + OFF_PHI + wg * 20480, pv = sb + OFF_V + wg * 12288;
    wgmma_fence();
#pragma unroll
    for (int k = 0; k < 8; k++) {
      wgmma_n24<1, 1>(d0, make_desc(pa + k * 256, 128, 2048, 0), make_desc(pv + k * 256, 128, 2048, 0), k != 0);
      wgmma_n24<1, 1>(d1, make_desc(pa + 10240 + k * 256, 128, 2048, 0), make_desc(pv + 6144 + k * 256, 128, 2048, 0), k != 0);
    }
    wgmma_commit();
    wgmma_wait<0>();
    unsigned char* dst = a.kvacc + ((u * 4 + wg * 2) * 5 + 2 * wi) * 1024 + lane * 16;
    auto red4 = [&](bool on, unsigned char* p, float x, float y, float z) {
      asm volatile("{\n.reg .pred p;\nsetp.ne.u32 p, %4, 0;\n@p red.relaxed.gpu.global.add.v4.f32 [%0], {%1,%2,%3,%5};\n}" :: "l"(p), "f"(x), "f"(y), "f"(z), "r"((uint32_t)on), "f"(1.f) : "memory");
    };
    red4(wi < 3, dst, d0[0], d0[1], d0[4]); red4(wi < 3, dst + 512, d0[5], d0[8], d0[9]);
    red4(wi < 3, dst + 5120, d1[0], d1[1], d1[4]); red4(wi < 3, dst + 5632, d1[5], d1[8], d1[9]);
    red4(wi < 2, dst + 1024, d0[2], d0[3], d0[6]); red4(wi < 2, dst + 1536, d0[7], d0[10], d0[11]);
    red4(wi < 2, dst + 6144, d1[2], d1[3], d1[6]); red4(wi < 2, dst + 6656, d1[7], d1[10], d1[11]);
  }
  TL2((tl >= 12 ? 128 : 0) + 32 + 2);
  uint32_t qf[4][2][5];
  static_for<0, 4>([&](auto HH) { features(IC<0>{}, HH, qf[HH.value]); });
  uint4 xr[5];
#pragma unroll
  for (int i = 0; i < 5; i++) {
    const int c = lane + 32 * i;
    xr[i] = __ldcg((const uint4*)(a.xin + (size_t)(m2 * 128 + wg * 64 + wi * 16 + c / 10) * cfg::DM + ns * 80 + (c % 10) * 8));
  }
  {
    const unsigned char* src = a.kvacc + (u * 20 + warp) * 1024 + lane * 16;
    uint4 v[6];
    int spin = 0;
    while (true) {
      v[0] = ld_relaxed_v4_i<0>(src); v[1] = ld_relaxed_v4_i<512>(src); v[2] = ld_relaxed_v4_i<8192>(src); v[3] = ld_relaxed_v4_i<8704>(src);
      v[4] = ld_relaxed_v4_i<0>(src + (wg ? 0 : 16384)); v[5] = ld_relaxed_v4_i<512>(src + (wg ? 0 : 16384));
      const uint32_t c = (v[0].w & v[1].w & v[2].w) & (v[3].w & v[4].w & v[5].w);
      if (!__any_sync(0xffffffffu, (c & 0x41800000u) != 0x41800000u) || ++spin >= SPIN_LIMIT) break;
      __nanosleep(100);
    }
    const uint32_t kd = sb + OFF_KV + warp * 384 + lane * 4;
#pragma unroll
    for (int i = 0; i < 3; i++)
      if (i < 2 || wg == 0) {
        sts32(kd + i * 3072, pack_bf16(__uint_as_float(v[2 * i].x), __uint_as_float(v[2 * i].y)));
        sts32(kd + i * 3072 + 128, pack_bf16(__uint_as_float(v[2 * i].z), __uint_as_float(v[2 * i + 1].x)));
        sts32(kd + i * 3072 + 256, pack_bf16(__uint_as_float(v[2 * i + 1].y), __uint_as_float(v[2 * i + 1].z)));
      }
  }
  fence_proxy_async();
  bar_sync(1, 256);
  TL2((tl >= 12 ? 128 : 0) + 32 + 3);
  {
    float d[4][12];
    uint32_t zero = 0; PIN(zero);
#pragma unroll
    for (int hh = 0; hh < 4; hh++)
#pragma unroll
      for (int i = 0; i < 5; i++) { PIN(qf[hh][0][i]); PIN(qf[hh][1][i]); }
    wgmma_fence();
#pragma unroll
    for (int hh = 0; hh < 4; hh++) {
      const uint32_t kb = sb + OFF_KV + hh * 1920;
      wgmma_rs_n24<1>(d[hh], qf[hh][0][0], qf[hh][1][0], qf[hh][0][1], qf[hh][1][1], make_desc(kb, 384, 128, 0), 0);
      wgmma_rs_n24<1>(d[hh], qf[hh][0][2], qf[hh][1][2], qf[hh][0][3], qf[hh][1][3], make_desc(kb + 768, 384, 128, 0), 1);
      wgmma_rs_n24<1>(d[hh], qf[hh][0][4], qf[hh][1][4], zero, zero, make_desc(kb + 1536, 0, 128, 0), 1);
    }
    wgmma_commit();
    wgmma_wait<0>();
    uint32_t ow[4][6];
#pragma unroll
    for (int hh = 0; hh < 4; hh++) {
      const int zl = (lane & ~3) | ((hh & 1) ? 0 : 2);
      const float da = bf16r(bf16r(__shfl_sync(0xffffffffu, d[hh][8], zl)) + 1e-6f), db = bf16r(bf16r(__shfl_sync(0xffffffffu, d[hh][10], zl)) + 1e-6f);
#pragma unroll
      for (int n = 0; n < 3; n++) {
        bf16r2(d[hh][4 * n], d[hh][4 * n + 1]); bf16r2(d[hh][4 * n + 2], d[hh][4 * n + 3]);
        ow[hh][2 * n] = pack_bf16(__fdividef(d[hh][4 * n], da), __fdividef(d[hh][4 * n + 1], da));
        ow[hh][2 * n + 1] = pack_bf16(__fdividef(d[hh][4 * n + 2], db), __fdividef(d[hh][4 * n + 3], db));
      }
    }
#pragma unroll
    for (int p = 0; p < 2; p++) {
      const uint32_t oa = sb + OFF_OST + p * 10240 + srow;
      stsm_x4(oa, ow[2 * p][0], ow[2 * p][1], ow[2 * p][2], ow[2 * p][3]);
      stsm_x2(oa + 4096, q4 < 2 ? ow[2 * p][4] : ow[2 * p + 1][4], q4 < 2 ? ow[2 * p][5] : ow[2 * p + 1][5]);
      stsm_x4(oa + 6144, ow[2 * p + 1][0], ow[2 * p + 1][1], ow[2 * p + 1][2], ow[2 * p + 1][3]);
    }
    fence_proxy_async();
    __syncwarp();
    mbar_arrive_if(lane == 0, staged);
  }
  TL2((tl >= 12 ? 128 : 0) + 32 + 4);
  float c2[40];
  mbar_wait(barW, 0);
#pragma unroll 1
  for (int i = 0; i < 8; i++) {
    mbar_wait(full2 + 8 * i, 0);
    const uint32_t st = sb + (i < 6 ? i : i - 6) * PIECE + wg * 1024, wo = sb + OFF_WOT + i * 12800;
    wgmma_fence();
#pragma unroll
    for (int kk = 0; kk < 5; kk++) wgmma_n80<0, 1>(c2, make_desc(st + kk * 4096, 2048, 128, 0), make_desc(wo + kk * 2560, 1280, 128, 0), (i | kk) != 0);
    wgmma_commit();
    if (i == 1 || i == 2) { wgmma_wait<1>(); mbar_arrive_if(lead, empty2 + 8 * (i - 1)); }
  }
  wgmma_wait<0>();
  TL2((tl >= 12 ? 128 : 0) + 32 + 5);
  {
    bar_sync(1, 256);
    const uint32_t ost = sb + 2 * PIECE + warp * 3072;
#pragma unroll
    for (int v = 0; v < 10; v += 2)
      stsm_x4(ost + (lane & 15) * 176 + (v + (lane >> 4)) * 16, pack_bf16(c2[4 * v], c2[4 * v + 1]), pack_bf16(c2[4 * v + 2], c2[4 * v + 3]),
              pack_bf16(c2[4 * v + 4], c2[4 * v + 5]), pack_bf16(c2[4 * v + 6], c2[4 * v + 7]));
    __syncwarp();
#pragma unroll
    for (int i = 0; i < 5; i++) {
      const int c = lane + 32 * i, row = c / 10, chunk = c % 10;
      const uint4 y = lds128(ost + row * 176 + chunk * 16);
      const size_t off = (size_t)(m2 * 128 + wg * 64 + wi * 16 + row) * cfg::DM + ns * 80 + chunk * 8;
      const uint4 x = xr[i];
      *(uint4*)(a.xout + off) = make_uint4(pack_bf16(bf_lo(x.x) + bf_lo(y.x), bf_hi(x.x) + bf_hi(y.x)), pack_bf16(bf_lo(x.y) + bf_lo(y.y), bf_hi(x.y) + bf_hi(y.y)),
                                           pack_bf16(bf_lo(x.z) + bf_lo(y.z), bf_hi(x.z) + bf_hi(y.z)), pack_bf16(bf_lo(x.w) + bf_lo(y.w), bf_hi(x.w) + bf_hi(y.w)));
    }
  }
  TL_END(tl);
}
__device__ __align__(32768) unsigned char g_arena[AR_SIZE];
__device__ unsigned g_go[32];
__device__ __align__(1024) uint2 g_xh[2048 * 160];
__device__ __align__(1024) unsigned char g_k[64 * 96 * 5120], g_v[64 * 96 * 5120];
__device__ __align__(1024) bf16 g_o[2048 * 6144];
__device__ __align__(1024) uint4 g_qs[8 * 32 * 12 * 256];
__device__ __align__(1024) bf16 g_xn[2048 * 640], g_xn2[2048 * 640], g_xa[2048 * 640], g_xb[2048 * 640];
__device__ __align__(1024) bf16 g_part[24 * 2048 * 640];
__device__ __align__(1024) bf16 g_wb[2048 * 640], g_wot[640 * 640], g_pq[2048 * 640];
__device__ __align__(1024) float g_kvacc[bf::KVACC / 4 + 64];

typedef CUresult (*EncodeFn)(CUtensorMap*, CUtensorMapDataType, cuuint32_t, void*, const cuuint64_t*, const cuuint64_t*, const cuuint32_t*,
                             const cuuint32_t*, CUtensorMapInterleave, CUtensorMapSwizzle, CUtensorMapL2promotion, CUtensorMapFloatOOBfill);
static EncodeFn g_encode = nullptr;
static CUtensorMap make_map(const void* p, uint64_t cols, uint64_t rows, uint32_t bc, uint32_t br, bool swz = true) {
  CUtensorMap m;
  cuuint64_t dims[2] = {cols, rows}, strides[1] = {cols * 2};
  cuuint32_t box[2] = {bc, br}, es[2] = {1, 1};
  g_encode(&m, CU_TENSOR_MAP_DATA_TYPE_BFLOAT16, 2, const_cast<void*>(p), dims, strides, box, es, CU_TENSOR_MAP_INTERLEAVE_NONE,
           swz ? CU_TENSOR_MAP_SWIZZLE_128B : CU_TENSOR_MAP_SWIZZLE_NONE, CU_TENSOR_MAP_L2_PROMOTION_L2_256B, CU_TENSOR_MAP_FLOAT_OOB_FILL_NONE);
  return m;
}
static CUtensorMap make_map3(const void* p, uint64_t cols, uint64_t rows, uint32_t nb) {
  CUtensorMap m;
  cuuint64_t dims[3] = {64, rows, cols / 64}, strides[2] = {cols * 2, 128};
  cuuint32_t box[3] = {64, 64, nb}, es[3] = {1, 1, 1};
  g_encode(&m, CU_TENSOR_MAP_DATA_TYPE_BFLOAT16, 3, const_cast<void*>(p), dims, strides, box, es, CU_TENSOR_MAP_INTERLEAVE_NONE,
           CU_TENSOR_MAP_SWIZZLE_128B, CU_TENSOR_MAP_L2_PROMOTION_L2_256B, CU_TENSOR_MAP_FLOAT_OOB_FILL_NONE);
  return m;
}
template <class T> static T* sym(const T& s) { void* p = nullptr; cudaGetSymbolAddress(&p, s); return (T*)p; }

struct Ptrs {
  unsigned char *arena, *k, *v; bf16 *o, *xn, *xa, *xb, *wb, *wot, *pq; float *part, *kvacc; uint2* xh; uint4* qs; bf16* xn2; unsigned* go;
};

static tr::Sched make_sched(int layer, const char* str, const int* ks, const int* lr) {
  using namespace tr;
  Sched s = {};
  int n = 0;
  for (int b = 0; b < 16; b++) { s.ks[b] = (uint8_t)abs(ks[b]); s.wide[b] = ks[b] > 0; s.lrows[b] = (uint8_t)lr[b]; }
  for (const char* p = str; *p;) {
    if (*p == ' ') { p++; continue; }
    const bool late = *p < 'a';
    const char c = *p++ | 32;
    char* e;
    const int b = (int)strtol(p, &e, 10); p = e;
    int first = 0, cnt = c == 'o' ? s.ks[b] * (s.wide[b] ? 2 : 5) : (c == 'l' ? 16 / lr[b] : 32);
    if (*p == '.') { first = (int)strtol(p + 1, &e, 10); cnt = (int)strtol(e + 1, &e, 10); p = e; }
    const int type = c == 'a' ? T_QA : (c == 'q' ? T_Q : (c == 't' ? T_A : (c == 'l' ? T_L : (c == 'p' ? T_P : (s.wide[b] ? T_OB : T_OS)))));
    if (type == T_P && layer > 0) continue;
    for (int i = 0; i < cnt && n < MAXITEMS - 1; i++) s.item[n++] = (uint16_t)((late << 14) | (type << 11) | (b << 7) | (first + i));
  }
  s.n = n; s.item[n] = T_END << 11;
  return s;
}
static tr::Sched sched_of(int layer) {
  const char* str = "q12 q13 q14 a0 q15 a1 p0.0.16 o0 o1 a2 p0.16.16 o2 a3 a4 o3 a5 o4 a6 l0 o5 l1 a7 o6 l2 a8 o7 a9 o8 l3 l4 a10 O9 l5 a11 O10 t12 l6 l7 o11 O12 t13 t14 T15 O13 o15 O14 L10 L9 l15 l13 L8 l14 l12 l11";
  int ks[16] = {2, 2, 2, 2, 2, 2, 2, 2, 2, 3, 3, 3, 3, -4, -6, -8}, lr[16] = {4, 4, 4, 4, 4, 4, 4, 4, 1, 4, 1, 1, 1, 1, 1, 1};
#ifdef TUNE
  const bool mine = !getenv("ONLY") || atoi(getenv("ONLY")) == layer;
  if (mine && getenv("SCHED")) str = getenv("SCHED");
  if (const char* p = mine ? getenv("KS") : nullptr) for (int b = 0; b < 16; b++) { char* e; ks[b] = (int)strtol(p, &e, 10); p = e; }
  if (const char* p = mine ? getenv("LR") : nullptr) for (int b = 0; b < 16; b++) { char* e; lr[b] = (int)strtol(p, &e, 10); p = e; }
#endif
  return make_sched(layer, str, ks, lr);
}
#ifndef TRAIL_GRID
#define TRAIL_GRID 132
#endif
#ifndef PDL_LN
#define PDL_LN 0
#endif
#ifndef PDL_CH
#define PDL_CH 1
#endif
#ifndef PDL_B
#define PDL_B 1
#endif
#ifndef PF_A
#define PF_A 1
#endif
#ifndef PF_B
#define PF_B 1
#endif
extern "C" void kernel_launch(void* const* d_in, const int* in_sizes, int n_in, void* d_out, int out_size) {
  const bf16* x = (const bf16*)d_in[0];
  const bf16* mem0 = (const bf16*)d_in[1];
  const bf16 *Wq = (const bf16*)d_in[2], *Wk = (const bf16*)d_in[3], *Wv = (const bf16*)d_in[4], *Wo = (const bf16*)d_in[5];
  const bf16 *wqkv = (const bf16*)d_in[8], *wphi = (const bf16*)d_in[9], *wo = (const bf16*)d_in[10];
  bf16* out = (bf16*)d_out;
  static Ptrs P; static bool init = false;
  if (!init) {
    void* fn = nullptr; cudaDriverEntryPointQueryResult qr;
    cudaGetDriverEntryPoint("cuTensorMapEncodeTiled", &fn, cudaEnableDefault, &qr);
    g_encode = (EncodeFn)fn;
    void* p;
    cudaGetSymbolAddress(&p, g_arena); P.arena = (unsigned char*)p;
    cudaGetSymbolAddress(&p, g_k); P.k = (unsigned char*)p;   cudaGetSymbolAddress(&p, g_v); P.v = (unsigned char*)p;
    cudaGetSymbolAddress(&p, g_o); P.o = (bf16*)p;
    cudaGetSymbolAddress(&p, g_xn); P.xn = (bf16*)p;
    cudaGetSymbolAddress(&p, g_xa); P.xa = (bf16*)p;   cudaGetSymbolAddress(&p, g_xb); P.xb = (bf16*)p;
    cudaGetSymbolAddress(&p, g_wb); P.wb = (bf16*)p;   cudaGetSymbolAddress(&p, g_wot); P.wot = (bf16*)p;
    cudaGetSymbolAddress(&p, g_pq); P.pq = (bf16*)p;   cudaGetSymbolAddress(&p, g_part); P.part = (float*)p;
    cudaGetSymbolAddress(&p, g_kvacc); P.kvacc = (float*)p;
    cudaGetSymbolAddress(&p, g_xh); P.xh = (uint2*)p;
    cudaGetSymbolAddress(&p, g_go); P.go = (unsigned*)p;
    cudaGetSymbolAddress(&p, g_qs); P.qs = (uint4*)p;
    cudaGetSymbolAddress(&p, g_xn2); P.xn2 = (bf16*)p;
    cudaFuncSetAttribute(chain_kernel, cudaFuncAttributeMaxDynamicSharedMemorySize, ch::SMEM);
    cudaFuncSetAttribute(trail_kernel, cudaFuncAttributeMaxDynamicSharedMemorySize, tr::SMEM);
    cudaFuncSetAttribute(blayer_kernel, cudaFuncAttributeMaxDynamicSharedMemorySize, bf::SMEM);
    init = true;
  }
  const CUtensorMap tmXn = make_map(P.xn, 640, 2048, 64, 128), tmXn2 = make_map(P.xn2, 640, 2048, 64, 128);
  const CUtensorMap tmWq = make_map3(Wq, 6144, 640, 3);
  const CUtensorMap tmCq = make_map(Wq, 6144, 640, 64, 160), tmCk = make_map(Wk, 6144, 640, 64, 160), tmCv = make_map(Wv, 6144, 640, 64, 160), tmCo = make_map(Wo, 640, 6144, 224, 64, false);
  const CUtensorMap tmWo5 = make_map3(Wo, 640, 6144, 5), tmWo2 = make_map3(Wo, 640, 6144, 2);

  CUtensorMap tmP;
  {
    cuuint64_t dims[3] = {256, 8, 24 * 320}, strides[2] = {1024, 8192};
    cuuint32_t box[3] = {256, 1, 10}, es[3] = {1, 1, 1};
    g_encode(&tmP, CU_TENSOR_MAP_DATA_TYPE_UINT32, 3, P.part, dims, strides, box, es, CU_TENSOR_MAP_INTERLEAVE_NONE, CU_TENSOR_MAP_SWIZZLE_NONE,
             CU_TENSOR_MAP_L2_PROMOTION_NONE, CU_TENSOR_MAP_FLOAT_OOB_FILL_NONE);
  }
  ChainArgs ca;
  ca.xh = P.xh; ca.mem0 = mem0; ca.kg = P.k; ca.vg = P.v;
  ca.arena = P.arena; ca.dbg = nullptr; ca.go = P.go; ca.delay = POLL_DELAY; ca.margin = 150; ca.pubrel = 1;
#ifdef TUNE
  if (getenv("PR")) ca.pubrel = atoi(getenv("PR"));
  if (getenv("MG")) ca.margin = atoi(getenv("MG"));
  if (getenv("PD")) ca.delay = atoi(getenv("PD"));
#endif
  ca.tl = 0;
  uint4* zar = (uint4*)P.arena; const int nzar = AR_SIZE / 16;
  uint4* zkv = (uint4*)P.kvacc; const int nzkv = (bf::KVACC / 4 + 64) / 4;

  const PrepArgs pa{wqkv, wphi, wo, (unsigned char*)P.wb, (unsigned char*)P.wot};
  const bf16* xcur = x;
  cudaLaunchAttribute at[1];
  at[0].id = cudaLaunchAttributeProgrammaticStreamSerialization; at[0].val.programmaticStreamSerializationAllowed = 1;
  auto cfgof = [&](int grid, int block, int smem, bool pdl) {
    cudaLaunchConfig_t lc = {};
    lc.gridDim = dim3(grid); lc.blockDim = dim3(block); lc.dynamicSmemBytes = smem; lc.stream = cudaStreamPerThread;
    lc.attrs = at; lc.numAttrs = pdl ? 1 : 0;
    return lc;
  };
  int nlayers = 2;
#ifdef TUNE
  if (getenv("LAYERS")) nlayers = atoi(getenv("LAYERS"));
#endif
  for (int layer = 0; layer < nlayers; layer++) {
    const int tl = layer * 12;
    cudaLaunchConfig_t lc = cfgof(256, 256, 0, layer > 0 && PDL_LN);
    cudaLaunchKernelEx(&lc, ln_kernel, xcur, P.xn, P.xh, zar, nzar, zkv, nzkv, Wk, Wv, layer == 0 ? PF_A : 0, tl + 0);
    ca.tl = tl + 2;
    lc = cfgof(96, 384, ch::SMEM, PDL_CH);
    cudaLaunchKernelEx(&lc, chain_kernel, ca, tmCq, tmCk, tmCv, tmCo);
    lc = cfgof(TRAIL_GRID, 384, tr::SMEM, true);
    tr::Args ta{P.k, P.v, (unsigned char*)P.o, P.qs, (unsigned char*)P.part, xcur, P.xn, P.xa, P.xn2, P.arena, P.go, tl + 4, 30, 20, layer == 0};
#ifdef TUNE
    if (getenv("NAP")) ta.nap = atoi(getenv("NAP"));
    if (getenv("NAP2")) ta.nap2 = atoi(getenv("NAP2"));
#endif
    cudaLaunchKernelEx(&lc, trail_kernel, tmXn, tmWq, tmWo5, tmWo2, tmP, sched_of(layer), ta, pa);
    lc = cfgof(128, 384, bf::SMEM, PDL_B);
    bf::Args ba{(const unsigned char*)P.wb, (const unsigned char*)P.wot, (unsigned char*)P.kvacc, (unsigned char*)P.pq, P.xa, layer == 0 ? P.xb : out, P.go, layer == 0 ? P.arena + tr::C_P : nullptr,
                      layer == 0 && PF_B ? Wk : nullptr, Wv, 30, 500, 0, tl + 7};
#ifdef TUNE
    if (getenv("PFN")) ba.pfn = atoi(getenv("PFN"));
    if (getenv("PFNS")) ba.pfns = atoi(getenv("PFNS"));
    if (getenv("PFWT")) ba.pfwait = atoi(getenv("PFWT"));
    if (getenv("PFB")) ba.pf0 = layer == 0 && atoi(getenv("PFB")) ? Wk : nullptr;
#endif
    cudaLaunchKernelEx(&lc, blayer_kernel, tmXn2, ba);
    xcur = P.xb;
  }
}
```

```cpp
#include <cuda_runtime.h>
#include <cuda.h>
#include <cuda_bf16.h>
#include <stdint.h>
#include <stdlib.h>
#include <type_traits>

typedef __nv_bfloat16 bf16;

namespace cfg {
constexpr int S = 2048, DM = 640, H = 32, DH = 192, NSEG = 64, SEG = 32, NM = 8;
constexpr int HD = H * DH;
}

__device__ __forceinline__ uint32_t smem_u32(const void* p) { return (uint32_t)__cvta_generic_to_shared(p); }
__device__ __forceinline__ uint32_t mapa_u32(uint32_t a, uint32_t r) {
  uint32_t o; asm("mapa.shared::cluster.u32 %0, %1, %2;" : "=r"(o) : "r"(a), "r"(r)); return o;
}
__device__ __forceinline__ void mbar_init(uint32_t b, uint32_t c) {
  asm volatile("mbarrier.init.shared::cta.b64 [%0], %1;" :: "r"(b), "r"(c) : "memory");
}
__device__ __forceinline__ void mbar_expect_tx(uint32_t b, uint32_t bytes) {
  asm volatile("mbarrier.arrive.expect_tx.shared::cta.b64 _, [%0], %1;" :: "r"(b), "r"(bytes) : "memory");
}
__device__ __forceinline__ void mbar_arrive(uint32_t b) {
  asm volatile("mbarrier.arrive.shared::cta.b64 _, [%0];" :: "r"(b) : "memory");
}
__device__ __forceinline__ void mbar_expect_tx_if(bool c, uint32_t b, uint32_t bytes) {
  asm volatile("{\n.reg .pred p;\nsetp.ne.u32 p, %2, 0;\n@p mbarrier.arrive.expect_tx.shared::cta.b64 _, [%0], %1;\n}" :: "r"(b), "r"(bytes), "r"((uint32_t)c) : "memory");
}
__device__ __forceinline__ void mbar_arrive_if(bool c, uint32_t b) {
  asm volatile("{\n.reg .pred p;\nsetp.ne.u32 p, %1, 0;\n@p mbarrier.arrive.shared::cta.b64 _, [%0];\n}" :: "r"(b), "r"((uint32_t)c) : "memory");
}
__device__ __forceinline__ bool mbar_try(uint32_t b, uint32_t ph) {
  uint32_t p;
  asm volatile("{.reg .pred p; mbarrier.try_wait.parity.shared::cta.b64 p, [%1], %2; selp.u32 %0, 1, 0, p;}"
               : "=r"(p) : "r"(b), "r"(ph) : "memory");
  return p;
}
__device__ __forceinline__ bool mbar_try_cluster(uint32_t b, uint32_t ph) {
  uint32_t p;
  asm volatile("{.reg .pred p; mbarrier.try_wait.parity.acquire.cluster.shared::cta.b64 p, [%1], %2; selp.u32 %0, 1, 0, p;}"
               : "=r"(p) : "r"(b), "r"(ph) : "memory");
  return p;
}
#ifndef SPIN_LIMIT
#define SPIN_LIMIT (1 << 20)
#endif
__device__ __forceinline__ void mbar_wait(uint32_t b, uint32_t ph) {
  asm volatile("{\n.reg .pred p, q;\n.reg .u32 c;\nmov.u32 c, 0;\n"
               "W_%=:\nmbarrier.try_wait.parity.shared::cta.b64 p, [%0], %1;\n@p bra.uni D_%=;\n"
               "add.u32 c, c, 1;\nsetp.lt.u32 q, c, %2;\n@q bra.uni W_%=;\nD_%=:\n}"
               :: "r"(b), "r"(ph), "n"(SPIN_LIMIT) : "memory");
}
__device__ __forceinline__ void mbar_wait_if(bool cnd, uint32_t b, uint32_t ph) {
  asm volatile("{\n.reg .pred p, q;\n.reg .u32 c;\nsetp.eq.u32 q, %3, 0;\n@q bra.uni D_%=;\nmov.u32 c, 0;\n"
               "W_%=:\nmbarrier.try_wait.parity.shared::cta.b64 p, [%0], %1;\n@p bra.uni D_%=;\n"
               "add.u32 c, c, 1;\nsetp.lt.u32 q, c, %2;\n@q bra.uni W_%=;\nD_%=:\n}"
               :: "r"(b), "r"(ph), "n"(SPIN_LIMIT), "r"((uint32_t)cnd) : "memory");
}
__device__ __forceinline__ void mbar_spin(uint32_t b, uint32_t ph) {
  asm volatile("{\n.reg .pred p, q;\n.reg .u32 c;\nmov.u32 c, 0;\n"
               "W_%=:\nmbarrier.test_wait.parity.shared::cta.b64 p, [%0], %1;\n@p bra D_%=;\n"
               "add.u32 c, c, 1;\nsetp.lt.u32 q, c, %2;\n@q bra W_%=;\nD_%=:\n}"
               :: "r"(b), "r"(ph), "n"(SPIN_LIMIT) : "memory");
}
#define PIN(x) asm volatile("" : "+r"(x))
__device__ __forceinline__ void mbar_wait_cluster(uint32_t b, uint32_t ph) {
  int s = 0;
  while (!mbar_try_cluster(b, ph)) { if (++s > SPIN_LIMIT) break; }
}
__device__ __forceinline__ void st_async_v2(uint32_t a, uint32_t x, uint32_t y, uint32_t mb) {
  asm volatile("st.async.weak.shared::cluster.mbarrier::complete_tx::bytes.v2.b32 [%0], {%1,%2}, [%3];"
               :: "r"(a), "r"(x), "r"(y), "r"(mb) : "memory");
}
__device__ __forceinline__ void st_async_v4(uint32_t a, uint32_t x, uint32_t y, uint32_t z, uint32_t w, uint32_t mb) {
  asm volatile("st.async.weak.shared::cluster.mbarrier::complete_tx::bytes.v4.b32 [%0], {%1,%2,%3,%4}, [%5];"
               :: "r"(a), "r"(x), "r"(y), "r"(z), "r"(w), "r"(mb) : "memory");
}
__device__ __forceinline__ void bulk_g2s(uint32_t dst, const void* src, uint32_t bytes, uint32_t mb) {
  asm volatile("cp.async.bulk.shared::cluster.global.mbarrier::complete_tx::bytes [%0], [%1], %2, [%3];"
               :: "r"(dst), "l"(src), "r"(bytes), "r"(mb) : "memory");
}
__device__ __forceinline__ void cp_async16(uint32_t dst, const void* src) {
  asm volatile("cp.async.cg.shared.global [%0], [%1], 16;" :: "r"(dst), "l"(src) : "memory");
}
__device__ __forceinline__ void cp_async_wait_all() { asm volatile("cp.async.wait_all;" ::: "memory"); }
__device__ __forceinline__ void fence_proxy_async() { asm volatile("fence.proxy.async.shared::cta;" ::: "memory"); }
__device__ __forceinline__ void bar_sync(int id, int n) { asm volatile("bar.sync %0, %1;" :: "r"(id), "r"(n) : "memory"); }
__device__ __forceinline__ void bar_arrive(int id, int n) { asm volatile("bar.arrive %0, %1;" :: "r"(id), "r"(n) : "memory"); }
__device__ __forceinline__ void cluster_sync_all() {
  asm volatile("barrier.cluster.arrive.release.aligned; barrier.cluster.wait.acquire.aligned;" ::: "memory");
}
__device__ __forceinline__ void ldsm_x4(uint32_t (&r)[4], uint32_t a) {
  asm volatile("ldmatrix.sync.aligned.m8n8.x4.shared.b16 {%0,%1,%2,%3}, [%4];"
               : "=r"(r[0]), "=r"(r[1]), "=r"(r[2]), "=r"(r[3]) : "r"(a) : "memory");
}
__device__ __forceinline__ void ldsm_x4_t(uint32_t (&r)[4], uint32_t a) {
  asm volatile("ldmatrix.sync.aligned.m8n8.x4.trans.shared.b16 {%0,%1,%2,%3}, [%4];"
               : "=r"(r[0]), "=r"(r[1]), "=r"(r[2]), "=r"(r[3]) : "r"(a) : "memory");
}
template <int IMM> __device__ __forceinline__ void ldsm_x4_i(uint32_t (&r)[4], uint32_t a) {
  asm volatile("ldmatrix.sync.aligned.m8n8.x4.shared.b16 {%0,%1,%2,%3}, [%4+%5];"
               : "=r"(r[0]), "=r"(r[1]), "=r"(r[2]), "=r"(r[3]) : "r"(a), "n"(IMM) : "memory");
}
template <int IMM> __device__ __forceinline__ void ldsm_x4_t_i(uint32_t (&r)[4], uint32_t a) {
  asm volatile("ldmatrix.sync.aligned.m8n8.x4.trans.shared.b16 {%0,%1,%2,%3}, [%4+%5];"
               : "=r"(r[0]), "=r"(r[1]), "=r"(r[2]), "=r"(r[3]) : "r"(a), "n"(IMM) : "memory");
}
template <int IMM> __device__ __forceinline__ uint4 lds128_i(uint32_t a) {
  uint4 v; asm volatile("ld.shared.v4.u32 {%0,%1,%2,%3}, [%4+%5];" : "=r"(v.x), "=r"(v.y), "=r"(v.z), "=r"(v.w) : "r"(a), "n"(IMM) : "memory"); return v;
}
template <int IMM> __device__ __forceinline__ uint2 lds64_i(uint32_t a) {
  uint2 v; asm volatile("ld.shared.v2.u32 {%0,%1}, [%2+%3];" : "=r"(v.x), "=r"(v.y) : "r"(a), "n"(IMM) : "memory"); return v;
}
template <int IMM> __device__ __forceinline__ void sts128_i(uint32_t a, uint32_t x, uint32_t y, uint32_t z, uint32_t w) {
  asm volatile("st.shared.v4.u32 [%0+%5], {%1,%2,%3,%4};" :: "r"(a), "r"(x), "r"(y), "r"(z), "r"(w), "n"(IMM) : "memory");
}
template <int IMM> __device__ __forceinline__ void sts64_i(uint32_t a, uint32_t x, uint32_t y) {
  asm volatile("st.shared.v2.u32 [%0+%3], {%1,%2};" :: "r"(a), "r"(x), "r"(y), "n"(IMM) : "memory");
}
template <int IMM> __device__ __forceinline__ void st_async_v2_i(uint32_t a, uint32_t x, uint32_t y, uint32_t mb) {
  asm volatile("st.async.weak.shared::cluster.mbarrier::complete_tx::bytes.v2.b32 [%0+%4], {%1,%2}, [%3];"
               :: "r"(a), "r"(x), "r"(y), "r"(mb), "n"(IMM) : "memory");
}
template <int IMM> __device__ __forceinline__ uint4 ld_relaxed_v4_i(const void* p) {
  uint4 v; asm volatile("ld.relaxed.gpu.global.v4.u32 {%0,%1,%2,%3}, [%4+%5];" : "=r"(v.x), "=r"(v.y), "=r"(v.z), "=r"(v.w) : "l"(p), "n"(IMM) : "memory"); return v;
}
template <int I, int N, class F> __device__ __forceinline__ void static_for(F&& f) {
  if constexpr (I < N) { f(std::integral_constant<int, I>{}); static_for<I + 1, N>(f); }
}
__device__ __forceinline__ uint32_t movm_t(uint32_t a) {
  uint32_t d; asm volatile("movmatrix.sync.aligned.m8n8.trans.b16 %0, %1;" : "=r"(d) : "r"(a)); return d;
}
__device__ __forceinline__ void mma16816(float (&d)[4], uint32_t a0, uint32_t a1, uint32_t a2, uint32_t a3, uint32_t b0, uint32_t b1) {
  asm volatile("mma.sync.aligned.m16n8k16.row.col.f32.bf16.bf16.f32 {%0,%1,%2,%3}, {%4,%5,%6,%7}, {%8,%9}, {%0,%1,%2,%3};"
               : "+f"(d[0]), "+f"(d[1]), "+f"(d[2]), "+f"(d[3]) : "r"(a0), "r"(a1), "r"(a2), "r"(a3), "r"(b0), "r"(b1));
}
__device__ __forceinline__ uint32_t pack_bf16(float lo, float hi) {
  uint32_t d; asm("cvt.rn.bf16x2.f32 %0, %1, %2;" : "=r"(d) : "f"(hi), "f"(lo)); return d;
}
__device__ __forceinline__ float bf_lo(uint32_t w) { return __uint_as_float(w << 16); }
__device__ __forceinline__ float bf_hi(uint32_t w) { return __uint_as_float(w & 0xffff0000u); }
__device__ __forceinline__ uint4 lds128(uint32_t a) {
  uint4 v; asm volatile("ld.shared.v4.u32 {%0,%1,%2,%3}, [%4];" : "=r"(v.x), "=r"(v.y), "=r"(v.z), "=r"(v.w) : "r"(a) : "memory"); return v;
}
__device__ __forceinline__ uint2 lds64(uint32_t a) {
  uint2 v; asm volatile("ld.shared.v2.u32 {%0,%1}, [%2];" : "=r"(v.x), "=r"(v.y) : "r"(a) : "memory"); return v;
}
__device__ __forceinline__ void sts128(uint32_t a, uint32_t x, uint32_t y, uint32_t z, uint32_t w) {
  asm volatile("st.shared.v4.u32 [%0], {%1,%2,%3,%4};" :: "r"(a), "r"(x), "r"(y), "r"(z), "r"(w) : "memory");
}
__device__ __forceinline__ void sts64(uint32_t a, uint32_t x, uint32_t y) {
  asm volatile("st.shared.v2.u32 [%0], {%1,%2};" :: "r"(a), "r"(x), "r"(y) : "memory");
}
__device__ __forceinline__ uint4 ld_relaxed_v4(const void* p) {
  uint4 v; asm volatile("ld.relaxed.gpu.global.v4.u32 {%0,%1,%2,%3}, [%4];" : "=r"(v.x), "=r"(v.y), "=r"(v.z), "=r"(v.w) : "l"(p) : "memory"); return v;
}
__device__ __forceinline__ uint32_t ld_relaxed_u32(const void* p) {
  uint32_t v; asm volatile("ld.relaxed.gpu.global.u32 %0, [%1];" : "=r"(v) : "l"(p) : "memory"); return v;
}
__device__ __forceinline__ void st_relaxed_v2(void* p, uint32_t a, uint32_t b) {
  asm volatile("st.relaxed.gpu.global.v2.u32 [%0], {%1,%2};" :: "l"(p), "r"(a), "r"(b) : "memory");
}
__device__ __forceinline__ void st_relaxed_u32(void* p, uint32_t v) {
  asm volatile("st.relaxed.gpu.global.u32 [%0], %1;" :: "l"(p), "r"(v) : "memory");
}
__device__ __forceinline__ void st_release_u32(void* p, uint32_t v) {
  asm volatile("st.release.gpu.global.u32 [%0], %1;" :: "l"(p), "r"(v) : "memory");
}
__device__ __forceinline__ void red_release_inc(void* p) { asm volatile("red.release.gpu.global.add.u32 [%0], 1;" :: "l"(p) : "memory"); }
__device__ __forceinline__ uint32_t clk32() { uint32_t c; asm volatile("mov.u32 %0, %%clock;" : "=r"(c) :: "memory"); return c; }
__device__ __forceinline__ uint32_t clkdep(uint32_t v) {
  uint32_t c; asm volatile("{.reg .pred p; setp.eq.u32 p, %1, 0xdeadbeef; @p trap; mov.u32 %0, %%clock;}" : "=r"(c) : "r"(v) : "memory"); return c;
}
__device__ __forceinline__ void wgmma_fence() { asm volatile("wgmma.fence.sync.aligned;" ::: "memory"); }
__device__ __forceinline__ void wgmma_commit() { asm volatile("wgmma.commit_group.sync.aligned;" ::: "memory"); }
template <int N> __device__ __forceinline__ void wgmma_wait() { asm volatile("wgmma.wait_group.sync.aligned %0;" :: "n"(N) : "memory"); }
__device__ __forceinline__ void wgmma_n8_ss_ta(float (&d)[4], uint64_t da, uint64_t db, int acc) {
  asm volatile("{\n.reg .pred p;\nsetp.ne.b32 p, %6, 0;\n"
               "wgmma.mma_async.sync.aligned.m64n8k16.f32.bf16.bf16 {%0,%1,%2,%3}, %4, %5, p, 1, 1, 1, 0;\n}\n"
               : "+f"(d[0]), "+f"(d[1]), "+f"(d[2]), "+f"(d[3]) : "l"(da), "l"(db), "r"(acc));
}
__device__ __forceinline__ uint64_t make_desc(uint32_t saddr, uint32_t lbo_bytes, uint32_t sbo_bytes, uint32_t swz) {
  return (uint64_t)((saddr & 0x3FFFF) >> 4) | ((uint64_t)(lbo_bytes >> 4) << 16) | ((uint64_t)(sbo_bytes >> 4) << 32) | ((uint64_t)swz << 62);
}


template <uint32_t LBO, uint32_t SBO, uint32_t SWZ> __device__ __forceinline__ uint64_t desc16(uint32_t a16, uint32_t off = 0) {
  return (uint64_t)(a16 + ((off >> 4) + ((LBO >> 4) << 16))) | ((uint64_t)((SBO >> 4) | (SWZ << 30)) << 32);
}

__device__ __forceinline__ bool elect_one() {
  uint32_t p; asm volatile("{\n.reg .pred p;\nelect.sync _|p, 0xffffffff;\nselp.u32 %0, 1, 0, p;\n}" : "=r"(p)); return p;
}
__device__ __forceinline__ void tma_load_3d(uint32_t dst, const CUtensorMap* tm, int c0, int c1, int c2, uint32_t mb) {
  asm volatile("cp.async.bulk.tensor.3d.shared::cluster.global.mbarrier::complete_tx::bytes [%0], [%1, {%3, %4, %5}], [%2];"
               :: "r"(dst), "l"(tm), "r"(mb), "r"(c0), "r"(c1), "r"(c2) : "memory");
}
__device__ __forceinline__ void tma_load_2d(uint32_t dst, const CUtensorMap* tm, int c0, int c1, uint32_t mb) {
  asm volatile("cp.async.bulk.tensor.2d.shared::cluster.global.mbarrier::complete_tx::bytes [%0], [%1, {%3, %4}], [%2];"
               :: "r"(dst), "l"(tm), "r"(mb), "r"(c0), "r"(c1) : "memory");
}
__device__ __forceinline__ void bulk_s2g(void* dst, uint32_t src, uint32_t bytes) {
  asm volatile("cp.async.bulk.global.shared::cta.bulk_group [%0], [%1], %2;" :: "l"(dst), "r"(src), "r"(bytes) : "memory");
}
__device__ __forceinline__ uint64_t policy_evict_first() {
  uint64_t p; asm volatile("createpolicy.fractional.L2::evict_first.b64 %0, 1.0;" : "=l"(p)); return p;
}
__device__ __forceinline__ void bulk_s2g_hint(void* dst, uint32_t src, uint32_t bytes, uint64_t pol) {
  asm volatile("cp.async.bulk.global.shared::cta.bulk_group.L2::cache_hint [%0], [%1], %2, %3;" :: "l"(dst), "r"(src), "r"(bytes), "l"(pol) : "memory");
}
__device__ __forceinline__ void bulk_commit() { asm volatile("cp.async.bulk.commit_group;" ::: "memory"); }
template <int N> __device__ __forceinline__ void bulk_wait_read() { asm volatile("cp.async.bulk.wait_group.read %0;" :: "n"(N) : "memory"); }
template <int N> __device__ __forceinline__ void bulk_wait() { asm volatile("cp.async.bulk.wait_group %0;" :: "n"(N) : "memory"); }
__device__ __forceinline__ void stsm_x4(uint32_t a, uint32_t r0, uint32_t r1, uint32_t r2, uint32_t r3) {
  asm volatile("stmatrix.sync.aligned.m8n8.x4.shared.b16 [%0], {%1,%2,%3,%4};" :: "r"(a), "r"(r0), "r"(r1), "r"(r2), "r"(r3) : "memory");
}
__device__ __forceinline__ void stsm_x2(uint32_t a, uint32_t r0, uint32_t r1) {
  asm volatile("stmatrix.sync.aligned.m8n8.x2.shared.b16 [%0], {%1,%2};" :: "r"(a), "r"(r0), "r"(r1) : "memory");
}
__device__ __forceinline__ void ldsm_x2(uint32_t (&r)[2], uint32_t a) {
  asm volatile("ldmatrix.sync.aligned.m8n8.x2.shared.b16 {%0,%1}, [%2];" : "=r"(r[0]), "=r"(r[1]) : "r"(a) : "memory");
}
__device__ __forceinline__ void ldsm_x2_t(uint32_t (&r)[2], uint32_t a) {
  asm volatile("ldmatrix.sync.aligned.m8n8.x2.trans.shared.b16 {%0,%1}, [%2];" : "=r"(r[0]), "=r"(r[1]) : "r"(a) : "memory");
}
__device__ __forceinline__ float bf16r(float x) { return __uint_as_float(pack_bf16(0.f, x) & 0xffff0000u); }
__device__ __forceinline__ void bf16r2(float& a, float& b) { const uint32_t w = pack_bf16(a, b); a = bf_lo(w); b = bf_hi(w); }
__device__ __forceinline__ float rcpf(float x) { float r; asm("rcp.approx.ftz.f32 %0, %1;" : "=f"(r) : "f"(x)); return r; }
__device__ __forceinline__ float ex2f(float x) { float e; asm("ex2.approx.ftz.f32 %0, %1;" : "=f"(e) : "f"(x)); return e; }
__device__ __forceinline__ void prefetch_tmap(const CUtensorMap* tm) { asm volatile("prefetch.tensormap [%0];" :: "l"(tm) : "memory"); }

#ifdef TIMELINE
__device__ unsigned long long g_tl[2 * 64];
__device__ unsigned g_step[2 * 64 * 96 * 4];
__device__ unsigned long long g_log[2 * 132 * 64 * 2 + 2];
__device__ unsigned long long g_tl2[4 * 64];
__device__ __forceinline__ unsigned long long gtime() { unsigned long long t; asm volatile("mov.u64 %0, %%globaltimer;" : "=l"(t)); return t; }
#define TL_BEGIN(id) do { if (threadIdx.x == 0) atomicMin(&g_tl[2 * (id)], gtime()); } while (0)
#define TL_END(id) do { if ((threadIdx.x & 31) == 0) atomicMax(&g_tl[2 * (id) + 1], gtime()); } while (0)
#define TL_ACC(idx, t0) do { if (threadIdx.x == 0 && m >= 4 && m < 11) { atomicAdd(&g_tl2[idx], gtime() - (t0)); atomicAdd(&g_tl2[(idx) + 1], 1ull); } } while (0)
#define TL_NOW() gtime()
#define TL2(idx) asm volatile("{\n.reg .pred p;\nsetp.eq.u32 p, %2, 0;\n@p red.relaxed.gpu.global.max.u64 [%0], %1;\n}" :: "l"(&g_tl2[idx]), "l"(gtime()), "r"(threadIdx.x) : "memory")
#define TLW(idx) asm volatile("{\n.reg .pred p;\nsetp.eq.u32 p, %2, 0;\n@p red.relaxed.gpu.global.max.u64 [%0], %1;\n@p red.relaxed.gpu.global.add.u64 [%0+128], %1;\n}" :: "l"(&g_tl2[idx]), "l"(gtime() - g_tl0), "r"(threadIdx.x & 31) : "memory")
#define TL_BEGIN0(id) atomicMin(&g_tl[2 * (id)], gtime())
#else
#define TL_ACC(idx, t0)
#define TL_NOW() 0ull
#define TL2(idx)
#define TL_BEGIN0(id)
#define TLW(idx)
#define TL_BEGIN(id)
#define TL_END(id)
#endif
template <int TA, int TB> __device__ __forceinline__ void wgmma_n24(float (&d)[12], uint64_t da, uint64_t db, int acc) {
  asm volatile("{\n.reg .pred p;\nsetp.ne.b32 p, %14, 0;\n"
    "wgmma.mma_async.sync.aligned.m64n24k16.f32.bf16.bf16 {%0, %1, %2, %3, %4, %5, %6, %7, %8, %9, %10, %11}, %12, %13, p, 1, 1, %15, %16;\n}\n"
    : "+f"(d[0]), "+f"(d[1]), "+f"(d[2]), "+f"(d[3]), "+f"(d[4]), "+f"(d[5]), "+f"(d[6]), "+f"(d[7]), "+f"(d[8]), "+f"(d[9]), "+f"(d[10]), "+f"(d[11])
    : "l"(da), "l"(db), "r"(acc), "n"(TA), "n"(TB));
}

template <int TA, int TB> __device__ __forceinline__ void wgmma_n80(float (&d)[40], uint64_t da, uint64_t db, int acc) {
  asm volatile("{\n.reg .pred p;\nsetp.ne.b32 p, %42, 0;\n"
    "wgmma.mma_async.sync.aligned.m64n80k16.f32.bf16.bf16 {%0, %1, %2, %3, %4, %5, %6, %7, %8, %9, %10, %11, %12, %13, %14, %15, %16, %17, %18, %19, %20, %21, %22, %23, %24, %25, %26, %27, %28, %29, %30, %31, %32, %33, %34, %35, %36, %37, %38, %39}, %40, %41, p, 1, 1, %43, %44;\n}\n"
    : "+f"(d[0]), "+f"(d[1]), "+f"(d[2]), "+f"(d[3]), "+f"(d[4]), "+f"(d[5]), "+f"(d[6]), "+f"(d[7]), "+f"(d[8]), "+f"(d[9]), "+f"(d[10]), "+f"(d[11]), "+f"(d[12]), "+f"(d[13]), "+f"(d[14]), "+f"(d[15]), "+f"(d[16]), "+f"(d[17]), "+f"(d[18]), "+f"(d[19]), "+f"(d[20]), "+f"(d[21]), "+f"(d[22]), "+f"(d[23]), "+f"(d[24]), "+f"(d[25]), "+f"(d[26]), "+f"(d[27]), "+f"(d[28]), "+f"(d[29]), "+f"(d[30]), "+f"(d[31]), "+f"(d[32]), "+f"(d[33]), "+f"(d[34]), "+f"(d[35]), "+f"(d[36]), "+f"(d[37]), "+f"(d[38]), "+f"(d[39])
    : "l"(da), "l"(db), "r"(acc), "n"(TA), "n"(TB));
}

template <int TA, int TB> __device__ __forceinline__ void wgmma_n128(float (&d)[64], uint64_t da, uint64_t db, int acc) {
  asm volatile("{\n.reg .pred p;\nsetp.ne.b32 p, %66, 0;\n"
    "wgmma.mma_async.sync.aligned.m64n128k16.f32.bf16.bf16 {%0, %1, %2, %3, %4, %5, %6, %7, %8, %9, %10, %11, %12, %13, %14, %15, %16, %17, %18, %19, %20, %21, %22, %23, %24, %25, %26, %27, %28, %29, %30, %31, %32, %33, %34, %35, %36, %37, %38, %39, %40, %41, %42, %43, %44, %45, %46, %47, %48, %49, %50, %51, %52, %53, %54, %55, %56, %57, %58, %59, %60, %61, %62, %63}, %64, %65, p, 1, 1, %67, %68;\n}\n"
    : "+f"(d[0]), "+f"(d[1]), "+f"(d[2]), "+f"(d[3]), "+f"(d[4]), "+f"(d[5]), "+f"(d[6]), "+f"(d[7]), "+f"(d[8]), "+f"(d[9]), "+f"(d[10]), "+f"(d[11]), "+f"(d[12]), "+f"(d[13]), "+f"(d[14]), "+f"(d[15]), "+f"(d[16]), "+f"(d[17]), "+f"(d[18]), "+f"(d[19]), "+f"(d[20]), "+f"(d[21]), "+f"(d[22]), "+f"(d[23]), "+f"(d[24]), "+f"(d[25]), "+f"(d[26]), "+f"(d[27]), "+f"(d[28]), "+f"(d[29]), "+f"(d[30]), "+f"(d[31]), "+f"(d[32]), "+f"(d[33]), "+f"(d[34]), "+f"(d[35]), "+f"(d[36]), "+f"(d[37]), "+f"(d[38]), "+f"(d[39]), "+f"(d[40]), "+f"(d[41]), "+f"(d[42]), "+f"(d[43]), "+f"(d[44]), "+f"(d[45]), "+f"(d[46]), "+f"(d[47]), "+f"(d[48]), "+f"(d[49]), "+f"(d[50]), "+f"(d[51]), "+f"(d[52]), "+f"(d[53]), "+f"(d[54]), "+f"(d[55]), "+f"(d[56]), "+f"(d[57]), "+f"(d[58]), "+f"(d[59]), "+f"(d[60]), "+f"(d[61]), "+f"(d[62]), "+f"(d[63])
    : "l"(da), "l"(db), "r"(acc), "n"(TA), "n"(TB));
}

template <int TA, int TB> __device__ __forceinline__ void wgmma_n192(float (&d)[96], uint64_t da, uint64_t db, int acc) {
  asm volatile("{\n.reg .pred p;\nsetp.ne.b32 p, %98, 0;\n"
    "wgmma.mma_async.sync.aligned.m64n192k16.f32.bf16.bf16 {%0, %1, %2, %3, %4, %5, %6, %7, %8, %9, %10, %11, %12, %13, %14, %15, %16, %17, %18, %19, %20, %21, %22, %23, %24, %25, %26, %27, %28, %29, %30, %31, %32, %33, %34, %35, %36, %37, %38, %39, %40, %41, %42, %43, %44, %45, %46, %47, %48, %49, %50, %51, %52, %53, %54, %55, %56, %57, %58, %59, %60, %61, %62, %63, %64, %65, %66, %67, %68, %69, %70, %71, %72, %73, %74, %75, %76, %77, %78, %79, %80, %81, %82, %83, %84, %85, %86, %87, %88, %89, %90, %91, %92, %93, %94, %95}, %96, %97, p, 1, 1, %99, %100;\n}\n"
    : "+f"(d[0]), "+f"(d[1]), "+f"(d[2]), "+f"(d[3]), "+f"(d[4]), "+f"(d[5]), "+f"(d[6]), "+f"(d[7]), "+f"(d[8]), "+f"(d[9]), "+f"(d[10]), "+f"(d[11]), "+f"(d[12]), "+f"(d[13]), "+f"(d[14]), "+f"(d[15]), "+f"(d[16]), "+f"(d[17]), "+f"(d[18]), "+f"(d[19]), "+f"(d[20]), "+f"(d[21]), "+f"(d[22]), "+f"(d[23]), "+f"(d[24]), "+f"(d[25]), "+f"(d[26]), "+f"(d[27]), "+f"(d[28]), "+f"(d[29]), "+f"(d[30]), "+f"(d[31]), "+f"(d[32]), "+f"(d[33]), "+f"(d[34]), "+f"(d[35]), "+f"(d[36]), "+f"(d[37]), "+f"(d[38]), "+f"(d[39]), "+f"(d[40]), "+f"(d[41]), "+f"(d[42]), "+f"(d[43]), "+f"(d[44]), "+f"(d[45]), "+f"(d[46]), "+f"(d[47]), "+f"(d[48]), "+f"(d[49]), "+f"(d[50]), "+f"(d[51]), "+f"(d[52]), "+f"(d[53]), "+f"(d[54]), "+f"(d[55]), "+f"(d[56]), "+f"(d[57]), "+f"(d[58]), "+f"(d[59]), "+f"(d[60]), "+f"(d[61]), "+f"(d[62]), "+f"(d[63]), "+f"(d[64]), "+f"(d[65]), "+f"(d[66]), "+f"(d[67]), "+f"(d[68]), "+f"(d[69]), "+f"(d[70]), "+f"(d[71]), "+f"(d[72]), "+f"(d[73]), "+f"(d[74]), "+f"(d[75]), "+f"(d[76]), "+f"(d[77]), "+f"(d[78]), "+f"(d[79]), "+f"(d[80]), "+f"(d[81]), "+f"(d[82]), "+f"(d[83]), "+f"(d[84]), "+f"(d[85]), "+f"(d[86]), "+f"(d[87]), "+f"(d[88]), "+f"(d[89]), "+f"(d[90]), "+f"(d[91]), "+f"(d[92]), "+f"(d[93]), "+f"(d[94]), "+f"(d[95])
    : "l"(da), "l"(db), "r"(acc), "n"(TA), "n"(TB));
}

template <int TA, int TB> __device__ __forceinline__ void wgmma_n256(float (&d)[128], uint64_t da, uint64_t db, int acc) {
  asm volatile("{\n.reg .pred p;\nsetp.ne.b32 p, %130, 0;\n"
    "wgmma.mma_async.sync.aligned.m64n256k16.f32.bf16.bf16 {%0, %1, %2, %3, %4, %5, %6, %7, %8, %9, %10, %11, %12, %13, %14, %15, %16, %17, %18, %19, %20, %21, %22, %23, %24, %25, %26, %27, %28, %29, %30, %31, %32, %33, %34, %35, %36, %37, %38, %39, %40, %41, %42, %43, %44, %45, %46, %47, %48, %49, %50, %51, %52, %53, %54, %55, %56, %57, %58, %59, %60, %61, %62, %63, %64, %65, %66, %67, %68, %69, %70, %71, %72, %73, %74, %75, %76, %77, %78, %79, %80, %81, %82, %83, %84, %85, %86, %87, %88, %89, %90, %91, %92, %93, %94, %95, %96, %97, %98, %99, %100, %101, %102, %103, %104, %105, %106, %107, %108, %109, %110, %111, %112, %113, %114, %115, %116, %117, %118, %119, %120, %121, %122, %123, %124, %125, %126, %127}, %128, %129, p, 1, 1, %131, %132;\n}\n"
    : "+f"(d[0]), "+f"(d[1]), "+f"(d[2]), "+f"(d[3]), "+f"(d[4]), "+f"(d[5]), "+f"(d[6]), "+f"(d[7]), "+f"(d[8]), "+f"(d[9]), "+f"(d[10]), "+f"(d[11]), "+f"(d[12]), "+f"(d[13]), "+f"(d[14]), "+f"(d[15]), "+f"(d[16]), "+f"(d[17]), "+f"(d[18]), "+f"(d[19]), "+f"(d[20]), "+f"(d[21]), "+f"(d[22]), "+f"(d[23]), "+f"(d[24]), "+f"(d[25]), "+f"(d[26]), "+f"(d[27]), "+f"(d[28]), "+f"(d[29]), "+f"(d[30]), "+f"(d[31]), "+f"(d[32]), "+f"(d[33]), "+f"(d[34]), "+f"(d[35]), "+f"(d[36]), "+f"(d[37]), "+f"(d[38]), "+f"(d[39]), "+f"(d[40]), "+f"(d[41]), "+f"(d[42]), "+f"(d[43]), "+f"(d[44]), "+f"(d[45]), "+f"(d[46]), "+f"(d[47]), "+f"(d[48]), "+f"(d[49]), "+f"(d[50]), "+f"(d[51]), "+f"(d[52]), "+f"(d[53]), "+f"(d[54]), "+f"(d[55]), "+f"(d[56]), "+f"(d[57]), "+f"(d[58]), "+f"(d[59]), "+f"(d[60]), "+f"(d[61]), "+f"(d[62]), "+f"(d[63]), "+f"(d[64]), "+f"(d[65]), "+f"(d[66]), "+f"(d[67]), "+f"(d[68]), "+f"(d[69]), "+f"(d[70]), "+f"(d[71]), "+f"(d[72]), "+f"(d[73]), "+f"(d[74]), "+f"(d[75]), "+f"(d[76]), "+f"(d[77]), "+f"(d[78]), "+f"(d[79]), "+f"(d[80]), "+f"(d[81]), "+f"(d[82]), "+f"(d[83]), "+f"(d[84]), "+f"(d[85]), "+f"(d[86]), "+f"(d[87]), "+f"(d[88]), "+f"(d[89]), "+f"(d[90]), "+f"(d[91]), "+f"(d[92]), "+f"(d[93]), "+f"(d[94]), "+f"(d[95]), "+f"(d[96]), "+f"(d[97]), "+f"(d[98]), "+f"(d[99]), "+f"(d[100]), "+f"(d[101]), "+f"(d[102]), "+f"(d[103]), "+f"(d[104]), "+f"(d[105]), "+f"(d[106]), "+f"(d[107]), "+f"(d[108]), "+f"(d[109]), "+f"(d[110]), "+f"(d[111]), "+f"(d[112]), "+f"(d[113]), "+f"(d[114]), "+f"(d[115]), "+f"(d[116]), "+f"(d[117]), "+f"(d[118]), "+f"(d[119]), "+f"(d[120]), "+f"(d[121]), "+f"(d[122]), "+f"(d[123]), "+f"(d[124]), "+f"(d[125]), "+f"(d[126]), "+f"(d[127])
    : "l"(da), "l"(db), "r"(acc), "n"(TA), "n"(TB));
}

template <int TB> __device__ __forceinline__ void wgmma_rs_n24(float (&d)[12], uint32_t a0, uint32_t a1, uint32_t a2, uint32_t a3, uint64_t db, int acc) {
  asm volatile("{\n.reg .pred p;\nsetp.ne.b32 p, %17, 0;\n"
    "wgmma.mma_async.sync.aligned.m64n24k16.f32.bf16.bf16 {%0, %1, %2, %3, %4, %5, %6, %7, %8, %9, %10, %11}, {%12, %13, %14, %15}, %16, p, 1, 1, %18;\n}\n"
    : "+f"(d[0]), "+f"(d[1]), "+f"(d[2]), "+f"(d[3]), "+f"(d[4]), "+f"(d[5]), "+f"(d[6]), "+f"(d[7]), "+f"(d[8]), "+f"(d[9]), "+f"(d[10]), "+f"(d[11])
    : "r"(a0), "r"(a1), "r"(a2), "r"(a3), "l"(db), "r"(acc), "n"(TB));
}

template <int TB> __device__ __forceinline__ void wgmma_rs_n40(float (&d)[20], uint32_t a0, uint32_t a1, uint32_t a2, uint32_t a3, uint64_t db, int acc) {
  asm volatile("{\n.reg .pred p;\nsetp.ne.b32 p, %25, 0;\n"
    "wgmma.mma_async.sync.aligned.m64n40k16.f32.bf16.bf16 {%0, %1, %2, %3, %4, %5, %6, %7, %8, %9, %10, %11, %12, %13, %14, %15, %16, %17, %18, %19}, {%20, %21, %22, %23}, %24, p, 1, 1, %26;\n}\n"
    : "+f"(d[0]), "+f"(d[1]), "+f"(d[2]), "+f"(d[3]), "+f"(d[4]), "+f"(d[5]), "+f"(d[6]), "+f"(d[7]), "+f"(d[8]), "+f"(d[9]), "+f"(d[10]), "+f"(d[11]), "+f"(d[12]), "+f"(d[13]), "+f"(d[14]), "+f"(d[15]), "+f"(d[16]), "+f"(d[17]), "+f"(d[18]), "+f"(d[19])
    : "r"(a0), "r"(a1), "r"(a2), "r"(a3), "l"(db), "r"(acc), "n"(TB));
}

template <int TB> __device__ __forceinline__ void wgmma_rs_n192(float (&d)[96], uint32_t a0, uint32_t a1, uint32_t a2, uint32_t a3, uint64_t db, int acc) {
  asm volatile("{\n.reg .pred p;\nsetp.ne.b32 p, %101, 0;\n"
    "wgmma.mma_async.sync.aligned.m64n192k16.f32.bf16.bf16 {%0, %1, %2, %3, %4, %5, %6, %7, %8, %9, %10, %11, %12, %13, %14, %15, %16, %17, %18, %19, %20, %21, %22, %23, %24, %25, %26, %27, %28, %29, %30, %31, %32, %33, %34, %35, %36, %37, %38, %39, %40, %41, %42, %43, %44, %45, %46, %47, %48, %49, %50, %51, %52, %53, %54, %55, %56, %57, %58, %59, %60, %61, %62, %63, %64, %65, %66, %67, %68, %69, %70, %71, %72, %73, %74, %75, %76, %77, %78, %79, %80, %81, %82, %83, %84, %85, %86, %87, %88, %89, %90, %91, %92, %93, %94, %95}, {%96, %97, %98, %99}, %100, p, 1, 1, %102;\n}\n"
    : "+f"(d[0]), "+f"(d[1]), "+f"(d[2]), "+f"(d[3]), "+f"(d[4]), "+f"(d[5]), "+f"(d[6]), "+f"(d[7]), "+f"(d[8]), "+f"(d[9]), "+f"(d[10]), "+f"(d[11]), "+f"(d[12]), "+f"(d[13]), "+f"(d[14]), "+f"(d[15]), "+f"(d[16]), "+f"(d[17]), "+f"(d[18]), "+f"(d[19]), "+f"(d[20]), "+f"(d[21]), "+f"(d[22]), "+f"(d[23]), "+f"(d[24]), "+f"(d[25]), "+f"(d[26]), "+f"(d[27]), "+f"(d[28]), "+f"(d[29]), "+f"(d[30]), "+f"(d[31]), "+f"(d[32]), "+f"(d[33]), "+f"(d[34]), "+f"(d[35]), "+f"(d[36]), "+f"(d[37]), "+f"(d[38]), "+f"(d[39]), "+f"(d[40]), "+f"(d[41]), "+f"(d[42]), "+f"(d[43]), "+f"(d[44]), "+f"(d[45]), "+f"(d[46]), "+f"(d[47]), "+f"(d[48]), "+f"(d[49]), "+f"(d[50]), "+f"(d[51]), "+f"(d[52]), "+f"(d[53]), "+f"(d[54]), "+f"(d[55]), "+f"(d[56]), "+f"(d[57]), "+f"(d[58]), "+f"(d[59]), "+f"(d[60]), "+f"(d[61]), "+f"(d[62]), "+f"(d[63]), "+f"(d[64]), "+f"(d[65]), "+f"(d[66]), "+f"(d[67]), "+f"(d[68]), "+f"(d[69]), "+f"(d[70]), "+f"(d[71]), "+f"(d[72]), "+f"(d[73]), "+f"(d[74]), "+f"(d[75]), "+f"(d[76]), "+f"(d[77]), "+f"(d[78]), "+f"(d[79]), "+f"(d[80]), "+f"(d[81]), "+f"(d[82]), "+f"(d[83]), "+f"(d[84]), "+f"(d[85]), "+f"(d[86]), "+f"(d[87]), "+f"(d[88]), "+f"(d[89]), "+f"(d[90]), "+f"(d[91]), "+f"(d[92]), "+f"(d[93]), "+f"(d[94]), "+f"(d[95])
    : "r"(a0), "r"(a1), "r"(a2), "r"(a3), "l"(db), "r"(acc), "n"(TB));
}
constexpr uint32_t AR_ACC = 0;
constexpr uint32_t AR_TAB = 0x100000;
constexpr uint32_t AR_PROG = 0x101000;
__host__ __device__ constexpr uint32_t prog_off(int h, int j) { return AR_PROG + h * 128 + j * 4; }
constexpr uint32_t AR_CNT = 0x108000;
constexpr uint32_t AR_QUEUE = 0x109000;
constexpr uint32_t AR_SIZE = 0x10a000;

struct ChainArgs {
  const bf16* mem0;
  const uint2* xh;
  unsigned char *kg, *vg;
  unsigned char* arena;
  unsigned* go;
  uint32_t* dbg;
  uint32_t delay;
  int margin, pubrel;
  int tl;
};

namespace ch {
constexpr int OFF_WQ = 0;
constexpr int OFF_X = 81920;
constexpr int OFF_MEM = OFF_X + 40960;
constexpr int OFF_WO = OFF_MEM + 10240;
constexpr int WOK = 8 * 896;
constexpr int OFF_KV = OFF_WO + 10 * WOK;
constexpr int KVB = 5120;
constexpr int OFF_O = OFF_KV + 4 * KVB;
constexpr int OFF_Q = OFF_O + 1024;
constexpr int OFF_S = OFF_O + 3072;
constexpr int OFF_SR = OFF_S + 1536;
constexpr int OFF_LT = OFF_SR + 1280;
constexpr int OFF_BAR = OFF_LT + 512;
constexpr int SMEM = OFF_BAR + 256;
static_assert(SMEM <= 232448, "smem");
constexpr int MB_S = OFF_BAR, MB_O = OFF_BAR + 8, MB_X = OFF_BAR + 16;
constexpr int MB_K = OFF_BAR + 128, MB_V = MB_K + 16, MB_Q = MB_K + 32, MB_R = MB_K + 48;
constexpr int SC_IN = OFF_BAR + 64;
constexpr int SC_MX = OFF_S;
constexpr int SC_TW = OFF_BAR + 48;
constexpr int SC_W = OFF_BAR + 96;
constexpr int WOS = 448;
enum { B_MEM0 = 1, B_QK, B_SL, B_V, B_O, B_RED, B_X, B_C, B_H, B_MEM1, B_A, B_G, B_E };
#ifndef NQ1
#define NQ1 14
#endif
#ifndef NQ0
#define NQ0 8
#endif
#ifndef NP0
#define NP0 6
#endif
#ifndef NWO
#define NWO 5
#endif
#ifndef NWP
#define NWP 4
#endif
#ifndef NB0
#define NB0 3
#endif
#ifndef BBS
#define BBS 100
#endif
#ifndef VSYNC
#define VSYNC 0
#endif
#ifndef XPOS
#define XPOS 0
#endif
#ifndef XPD
#define XPD 300
#endif
#ifndef WOF
#define WOF 0
#endif
#ifndef XBYTES
#define XBYTES 36864
#endif
#ifndef NRT
#define NRT 7
#endif
#ifndef NRF
#define NRF 2
#endif
#ifndef NPM0
#define NPM0 2
#endif
#ifndef NPM1
#define NPM1 2
#endif
#ifndef RSYNC
#define RSYNC 1
#endif
#ifndef PFK
#define PFK 3
#endif
#ifndef PA0
#define PA0 3
#endif
#ifndef PA1
#define PA1 0
#endif
#ifndef PB0
#define PB0 7
#endif
#ifndef PB1
#define PB1 5
#endif
#ifndef PQE
#define PQE 1
#endif
#ifndef XT
#define XT 38
#endif
static_assert(NPM0 >= 2 && NPM1 >= 2, "the K / V blocks live in the last two k-steps of Wo");
}

#ifndef CHAIN_TIMING
#define CHAIN_TIMING 0
#endif
#if CHAIN_TIMING
#ifndef TR0
#define TR0 41
#endif
#ifndef TSMASK
#define TSMASK 0xffff
#endif
#define TSV(i, v) do { if ((TSMASK >> (i)) & 1) asm volatile("st.shared.u32 [%0+%1], %2;" :: "r"(tsb), "n"((i) * 4), "r"(v) : "memory"); } while (0)
#define TS(i) TSV(i, clk32())
#define TS_SETUP() const uint32_t tsb = sb + ((s == TR0 || s == TR0 + 1) ? OFF_BAR + 128 + ((s - TR0) * 12 + warp) * 48 : OFF_SR + 1152)
#else
#define TS(i)
#define TSV(i, v)
#define TS_SETUP()
#endif
#ifndef POLL_DELAY
#define POLL_DELAY 620
#endif
#ifndef XN
#define XN 40
#endif
#ifndef PF0
#define PF0 8
#endif
#ifndef PFS
#define PFS 3
#endif
#ifndef XDELAY
#define XDELAY 0
#endif
#ifndef NOKM
#define NOKM 0
#endif
#ifndef PFX
#define PFX 3
#endif
#ifndef NVE
#define NVE 8
#endif
#ifndef VET
#define VET 19
#endif
#ifndef MEMFIRST
#define MEMFIRST 0
#endif
#ifndef PM1
#define PM1 1
#endif
#ifndef GD1
#define GD1 30
#endif
#ifndef GD2
#define GD2 150
#endif
#ifndef CEARLY
#define CEARLY 0
#endif
#ifndef NPL
#define NPL 2
#endif
#ifndef NP1
#define NP1 (NQ1 < 6 ? NQ1 : 6)
#endif
#ifndef PFACC
#define PFACC 1
#endif
template <int V> using IC = std::integral_constant<int, V>;
__device__ __forceinline__ uint32_t clk_v() { uint64_t c; asm volatile("mov.u64 %0, %%clock64;" : "=l"(c) :: "memory"); return (uint32_t)c; }
__device__ __forceinline__ int fresh(int x) { int y; asm volatile("shfl.sync.bfly.b32 %0, %1, 0, 0x1f, 0xffffffff;" : "=r"(y) : "r"(x)); return y; }
#define SFENCE2(x, d) asm volatile("{\n.reg .pred p;\nsetp.eq.u32 p, %0, 0x7fffffff;\n@p st.shared.u32 [%0], %1;\n}" :: "r"(x), "r"(d) : "memory")
#define SFENCE(x) asm volatile("{\n.reg .pred p;\nsetp.eq.u32 p, %0, 0x7fffffff;\n@p st.shared.u32 [%0], %0;\n}" :: "r"(x) : "memory")
template <int I> __device__ __forceinline__ void bbfence(uint32_t x) {
  asm volatile("{\n.reg .pred p;\nsetp.eq.u32 p, %0, %1;\nL_%=:\n@p st.volatile.shared.u32 [%0], %0;\n@p bra.uni L_%=;\n}" :: "r"(x), "n"(4 * I) : "memory");
}
__device__ __forceinline__ float uniform_f(float x) { return __uint_as_float(__reduce_max_sync(0xffffffffu, __float_as_uint(x))); }

__device__ __forceinline__ void mma16816h(float (&d)[4], const uint32_t (&a)[4], uint32_t b0, uint32_t b1) {
  asm volatile("mma.sync.aligned.m16n8k16.row.col.f32.f16.f16.f32 {%0,%1,%2,%3}, {%4,%5,%6,%7}, {%8,%9}, {%0,%1,%2,%3};"
               : "+f"(d[0]), "+f"(d[1]), "+f"(d[2]), "+f"(d[3]) : "r"(a[0]), "r"(a[1]), "r"(a[2]), "r"(a[3]), "r"(b0), "r"(b1));
}
__device__ __forceinline__ void mma1688(float (&d)[4], uint32_t a0, uint32_t a1, uint32_t b0) {
  asm volatile("mma.sync.aligned.m16n8k8.row.col.f32.bf16.bf16.f32 {%0,%1,%2,%3}, {%4,%5}, {%6}, {%0,%1,%2,%3};"
               : "+f"(d[0]), "+f"(d[1]), "+f"(d[2]), "+f"(d[3]) : "r"(a0), "r"(a1), "r"(b0));
}
template <int OFF16, int ACC> __device__ __forceinline__ void wgmma_rs32h(float (&d)[16], const uint32_t (&a)[4], uint32_t dlo) {
  asm volatile("{\n.reg .pred p;\n.reg .b32 t;\n.reg .b64 db;\nsetp.ne.b32 p, %22, 0;\nadd.u32 t, %20, %21;\nmov.b64 db, {t, 0x40000040};\n"
    "wgmma.mma_async.sync.aligned.m64n32k16.f32.f16.f16 {%0,%1,%2,%3,%4,%5,%6,%7,%8,%9,%10,%11,%12,%13,%14,%15}, {%16,%17,%18,%19}, db, p, 1, 1, 0;\n}\n"
    : "+f"(d[0]), "+f"(d[1]), "+f"(d[2]), "+f"(d[3]), "+f"(d[4]), "+f"(d[5]), "+f"(d[6]), "+f"(d[7]), "+f"(d[8]), "+f"(d[9]), "+f"(d[10]), "+f"(d[11]),
      "+f"(d[12]), "+f"(d[13]), "+f"(d[14]), "+f"(d[15])
    : "r"(a[0]), "r"(a[1]), "r"(a[2]), "r"(a[3]), "r"(dlo), "n"(OFF16), "n"(ACC));
}
template <int IMM> __device__ __forceinline__ void stsm_x4_t_i(uint32_t a, uint32_t r0, uint32_t r1, uint32_t r2, uint32_t r3) {
  asm volatile("stmatrix.sync.aligned.m8n8.x4.trans.shared.b16 [%0+%5], {%1,%2,%3,%4};" :: "r"(a), "r"(r0), "r"(r1), "r"(r2), "r"(r3), "n"(IMM) : "memory");
}
template <int IMM> __device__ __forceinline__ void stsm_x2_t_i(uint32_t a, uint32_t r0, uint32_t r1) {
  asm volatile("stmatrix.sync.aligned.m8n8.x2.trans.shared.b16 [%0+%3], {%1,%2};" :: "r"(a), "r"(r0), "r"(r1), "n"(IMM) : "memory");
}
template <int IMM> __device__ __forceinline__ void st_async_b32_i(uint32_t a, uint32_t x, uint32_t mb) {
  asm volatile("st.async.weak.shared::cluster.mbarrier::complete_tx::bytes.b32 [%0+%3], %1, [%2];" :: "r"(a), "r"(x), "r"(mb), "n"(IMM) : "memory");
}
template <int IMM> __device__ __forceinline__ void ld_relaxed_v4_if(uint4& v, const void* p, uint32_t c) {
  asm volatile("{\n.reg .pred p;\nsetp.ne.u32 p, %6, 0;\n@p ld.relaxed.gpu.global.v4.u32 {%0,%1,%2,%3}, [%4+%5];\n}"
               : "+r"(v.x), "+r"(v.y), "+r"(v.z), "+r"(v.w) : "l"(p), "n"(IMM), "r"(c) : "memory");
}
template <int IMM> __device__ __forceinline__ void ldsm_x2_i(uint32_t (&r)[2], uint32_t a) {
  asm volatile("ldmatrix.sync.aligned.m8n8.x2.shared.b16 {%0,%1}, [%2+%3];" : "=r"(r[0]), "=r"(r[1]) : "r"(a), "n"(IMM) : "memory");
}
template <int IMM> __device__ __forceinline__ uint32_t ldsm_x1_t_i(uint32_t a) {
  uint32_t r; asm volatile("ldmatrix.sync.aligned.m8n8.x1.trans.shared.b16 {%0}, [%1+%2];" : "=r"(r) : "r"(a), "n"(IMM) : "memory"); return r;
}
template <int IMM> __device__ __forceinline__ uint32_t lds32_i(uint32_t a) {
  uint32_t v; asm volatile("ld.shared.u32 %0, [%1+%2];" : "=r"(v) : "r"(a), "n"(IMM) : "memory"); return v;
}
__device__ __forceinline__ void sts32(uint32_t a, uint32_t v) { asm volatile("st.shared.u32 [%0], %1;" :: "r"(a), "r"(v) : "memory"); }
__device__ __forceinline__ uint32_t pack_f16(float lo, float hi) {
  uint32_t d; asm("cvt.rn.f16x2.f32 %0, %1, %2;" : "=r"(d) : "f"(hi), "f"(lo)); return d;
}
__device__ __forceinline__ uint32_t amax_bf2(uint32_t a, uint32_t b) { uint32_t d; asm("max.xorsign.abs.bf16x2 %0, %1, %2;" : "=r"(d) : "r"(a), "r"(b)); return d; }
__device__ __forceinline__ uint32_t amax_h2(uint32_t a, uint32_t b) { uint32_t d; asm("max.xorsign.abs.f16x2 %0, %1, %2;" : "=r"(d) : "r"(a), "r"(b)); return d; }
__device__ __forceinline__ uint32_t amax_fold(uint32_t m) { return __reduce_max_sync(0xffffffffu, max(m & 0x7fffu, (m >> 16) & 0x7fffu)); }
__device__ __forceinline__ int wscale_exp(uint32_t m) { return min(141 - (int)(m >> 7), 100); }
__device__ __forceinline__ float exp2i(int e) { return __uint_as_float((uint32_t)(e + 127) << 23); }
__device__ __forceinline__ uint32_t bf2_to_h2(uint32_t w, float sc) { return pack_f16(bf_lo(w) * sc, bf_hi(w) * sc); }
__device__ __forceinline__ void bf2_to_h2_inplace(uint32_t& w, uint32_t sc2) {
  asm volatile("{\n.reg .b32 t, lo, hi;\nmul.rn.bf16x2 t, %0, %1;\nshl.b32 lo, t, 16;\nand.b32 hi, t, 0xffff0000;\ncvt.rn.f16x2.f32 %0, hi, lo;\n}" : "+r"(w) : "r"(sc2));
}
__device__ __forceinline__ void prefetch_l2(const void* p, uint32_t bytes) { asm volatile("cp.async.bulk.prefetch.L2.global [%0], %1;" :: "l"(p), "r"(bytes) : "memory"); }
__device__ __forceinline__ void prefetch_tma_2d(const CUtensorMap* tm, int c0, int c1) {
  asm volatile("cp.async.bulk.prefetch.tensor.2d.L2.global [%0, {%1, %2}];" :: "l"(tm), "r"(c0), "r"(c1) : "memory");
}
__host__ __device__ constexpr uint32_t acc_voff(int v) { return v < 4 ? v * 1024u : (v == 4 ? 128u : 3072u + 128u); }
__device__ __forceinline__ int unit28(int i) { return i == 3 ? 54 : 14 * i; }
__device__ __forceinline__ int unit24(int i) { return i < 2 ? 48 - 6 * i : 56 + 6 * i; }
__device__ __forceinline__ uint32_t acc_step(int s) { return (s >> 1) * 32768 + (s & 1) * 512; }
__device__ __forceinline__ uint32_t acc_lane(int i, int lane) { return ((lane >> 3) & 1) * 256 + (lane >> 4) * 4096 + i * 8192 + (lane & 7) * 16; }

__device__ __forceinline__ uint32_t ld_acquire_u32(const void* p) {
  uint32_t v; asm volatile("ld.acquire.gpu.global.u32 %0, [%1];" : "=r"(v) : "l"(p) : "memory"); return v;
}
template <int R> __device__ __forceinline__ void ln_rows(const uint2 (&xw)[R][5], int row0, int lane, bf16* __restrict__ xn, uint2* __restrict__ xh) {
  float v[R][20], s[R], q[R];
#pragma unroll
  for (int r = 0; r < R; r++) {
    s[r] = 0.f; q[r] = 0.f;
#pragma unroll
    for (int i = 0; i < 5; i++) { v[r][4 * i] = bf_lo(xw[r][i].x); v[r][4 * i + 1] = bf_hi(xw[r][i].x); v[r][4 * i + 2] = bf_lo(xw[r][i].y); v[r][4 * i + 3] = bf_hi(xw[r][i].y); }
#pragma unroll
    for (int i = 0; i < 5; i++) s[r] += (v[r][4 * i] + v[r][4 * i + 1]) + (v[r][4 * i + 2] + v[r][4 * i + 3]);
  }
#pragma unroll
  for (int o = 16; o; o >>= 1)
#pragma unroll
    for (int r = 0; r < R; r++) s[r] += __shfl_xor_sync(0xffffffffu, s[r], o);
#pragma unroll
  for (int r = 0; r < R; r++) {
    s[r] *= 1.f / cfg::DM;
#pragma unroll
    for (int i = 0; i < 10; i++) { const float d = v[r][2 * i] - s[r], e = v[r][2 * i + 1] - s[r]; q[r] += d * d + e * e; }
  }
#pragma unroll
  for (int o = 16; o; o >>= 1)
#pragma unroll
    for (int r = 0; r < R; r++) q[r] += __shfl_xor_sync(0xffffffffu, q[r], o);
#pragma unroll
  for (int r = 0; r < R; r++) {
    const int row = row0 + r;
    const float mb = bf16r(s[r]), var = bf16r(q[r] * (1.f / cfg::DM));
    float sd; asm("sqrt.approx.f32 %0, %1;" : "=f"(sd) : "f"(bf16r(var + 1e-5f)));
    const float inv = rcpf(bf16r(sd));
#pragma unroll
    for (int i = 0; i < 5; i++) {
      float y[4];
#pragma unroll
      for (int e = 0; e < 4; e++) y[e] = v[r][4 * i + e] - mb;
      bf16r2(y[0], y[1]); bf16r2(y[2], y[3]);
      const uint32_t w0 = pack_bf16(y[0] * inv, y[1] * inv), w1 = pack_bf16(y[2] * inv, y[3] * inv);
      *(uint2*)(xn + (size_t)row * cfg::DM + i * 128 + lane * 4) = make_uint2(w0, w1);
      if (xh) xh[(((size_t)(row >> 5) * 10 + 2 * i + (lane >> 4)) * 32 + (row & 31)) * 16 + ((((lane >> 1) & 7) ^ (row & 7)) << 1) + (lane & 1)] =
          make_uint2(pack_f16(bf_lo(w0), bf_hi(w0)), pack_f16(bf_lo(w1), bf_hi(w1)));
    }
  }
}

__global__ void __cluster_dims__(3, 1, 1) __launch_bounds__(384, 1) chain_kernel(const ChainArgs a, const __grid_constant__ CUtensorMap tmWq,
    const __grid_constant__ CUtensorMap tmWk, const __grid_constant__ CUtensorMap tmWv, const __grid_constant__ CUtensorMap tmWo) {
  using namespace ch;
  extern __shared__ __align__(1024) unsigned char smem_raw[];
  const uint32_t sb = smem_u32(smem_raw);
  const int warp = __shfl_sync(0xffffffffu, (int)threadIdx.x >> 5, 0);
  const int lane = __shfl_sync(0xffffffffu, (int)threadIdx.x & 31, threadIdx.x & 31);
  const int cta = blockIdx.x, h = cta / 3, j = cta % 3;
  const int g = lane >> 2, q4 = lane & 3, r8 = lane & 7, m4 = lane >> 3;
  unsigned char* const arena = a.arena;
  if (sb & 1023u) __trap();
  asm volatile("griddepcontrol.launch_dependents;");
  TL_BEGIN(a.tl);
#ifdef TIMELINE
  const unsigned long long g_tl0 = gtime();
#define PT(i) TLW((a.tl >= 12) * 128 + 64 + (i))
#else
#define PT(i)
#endif
  const int col0 = j == 0 ? 0 : (j == 1 ? 224 : 432);
  auto stage_w = [&](const CUtensorMap* tm, uint32_t dst, uint32_t mb, int half) {
    mbar_expect_tx(mb + 8 * half, 40960);
    tma_load_2d(dst + half * 40960, tm, h * cfg::DH + j * 64, half * 320, mb + 8 * half);
    tma_load_2d(dst + half * 40960 + 20480, tm, h * cfg::DH + j * 64, half * 320 + 160, mb + 8 * half);
  };
  if (threadIdx.x == 256) {
    for (int i = 0; i < 9; i++) mbar_init(sb + MB_K + 8 * i, 1);
    mbar_init(sb + MB_S, 1); mbar_init(sb + MB_O, 1); mbar_init(sb + MB_X, 1);
    asm volatile("fence.mbarrier_init.release.cluster;" ::: "memory");
    for (int i = 0; i < 2; i++) { stage_w(&tmWk, sb + OFF_WQ, sb + MB_K, i); stage_w(&tmWv, sb + OFF_WO, sb + MB_V, i); }
    sts32(sb + SC_W, 0); sts32(sb + SC_W + 4, 0); sts32(sb + SC_W + 8, 0); sts32(sb + SC_IN + 12, 0); sts32(sb + SC_IN + 20, 0); sts32(sb + SC_TW + 4, 99);
    mbar_expect_tx(sb + MB_S, 1280); mbar_expect_tx(sb + MB_O, 2048);
  }
  __syncthreads();
  asm volatile("barrier.cluster.arrive.relaxed.aligned;" ::: "memory");
  const uint32_t d1 = mapa_u32(sb, (j + 1) % 3) - sb, d2 = mapa_u32(sb, (j + 2) % 3) - sb;

  if (warp >= 8) {
    asm volatile("setmaxnreg.dec.sync.aligned.u32 40;");
    const int hw = warp - 8, ht = hw * 32 + lane;
    const bool lead = ht == 0;
    auto stage_wo = [&](int i) {
      mbar_expect_tx(sb + MB_R + 8 * i, 64 * WOS);
      tma_load_2d(sb + OFF_WO + i * 64 * WOS, &tmWo, col0, h * cfg::DH + ((i + j) % 3) * 64, sb + MB_R + 8 * i);
    };
    const unsigned char* xg = (const unsigned char*)a.xh;
    auto issue_x = [&](int s) { mbar_expect_tx(sb + MB_X, 40960); bulk_g2s(sb + OFF_X, xg + (size_t)s * 40960, 40960, sb + MB_X); };
    uint4 v[5];
#pragma unroll
    for (int i = 0; i < 5; i++) { const int c = ht + 128 * i; v[i] = ld_relaxed_v4(a.mem0 + (c & 7) * cfg::DM + (c >> 3) * 8); }
    if (hw == 2) {
      asm volatile("griddepcontrol.wait;" ::: "memory");
      if (lane == 0) { if (cta == 0) st_relaxed_u32(a.go, 1); issue_x(0); }
      PT(0);
    }
    if (hw == 0) {
      bar_sync(B_QK, 160); if (lane == 0) stage_w(&tmWq, sb + OFF_WQ, sb + MB_Q, 0);
      bar_sync(B_SL, 160); if (lane == 0) stage_w(&tmWq, sb + OFF_WQ, sb + MB_Q, 1);
    }
    if (hw == 1) {
      bar_sync(B_V, 160); if (lane == 0) stage_wo(0);
      bar_sync(B_O, 160); if (lane == 0) { stage_wo(1); stage_wo(2); }
    }
    __syncwarp();
    {
      uint32_t m = 0;
#pragma unroll
      for (int i = 0; i < 5; i++) {
        m = amax_bf2(amax_bf2(m, amax_bf2(v[i].x, v[i].y)), amax_bf2(v[i].z, v[i].w));
      }
      m = amax_fold(m);
      if (lane == 0) sts32(sb + SC_MX + hw * 4, m);
      bar_sync(B_H, 128);
      const uint4 mm = lds128(sb + SC_MX);
      const int se = max(wscale_exp(max(max(mm.x, mm.y), max(mm.z, mm.w))), -100);
      const float sc = exp2i(se);
#pragma unroll
      for (int i = 0; i < 5; i++) {
        const int c = ht + 128 * i, t = c & 7, chn = c >> 3;
        sts128(sb + OFF_MEM + chn * 128 + ((t ^ (2 * (chn & 3))) << 4), bf2_to_h2(v[i].x, sc), bf2_to_h2(v[i].y, sc), bf2_to_h2(v[i].z, sc), bf2_to_h2(v[i].w, sc));
      }
      if (lead) { sts32(sb + SC_IN, __float_as_uint(exp2i(-se))); sts32(sb + SC_IN + 4, 0x7800u); }
    }
    if (hw == 0) PT(11);
    {
      const uint32_t p0 = sb + OFF_WQ + hw * 2048 + lane * 16;
      uint32_t m = 0;
#pragma unroll 1
      for (int i = 0; i < 10; i++) {
        if (i == 0 || i == 5) mbar_wait(sb + MB_Q + (i ? 8 : 0), 0);
        uint32_t r[4][4];
        static_for<0, 4>([&](auto K) { ldsm_x4_i<K.value * 512>(r[K.value], p0 + i * 8192); });
#pragma unroll
        for (int k = 0; k < 4; k++) m = amax_bf2(amax_bf2(m, amax_bf2(r[k][0], r[k][1])), amax_bf2(r[k][2], r[k][3]));
      }
      if (hw == 0) PT(9);
      m = amax_fold(m);
      if (lane == 0) asm volatile("red.shared.max.u32 [%0], %1;" :: "r"(sb + SC_W + 8), "r"(m) : "memory");
      bar_sync(B_H, 128);
      const uint32_t sc = (uint32_t)(wscale_exp(lds32_i<SC_W + 8>(sb)) + 127) * 0x00800080u;
#pragma unroll 1
      for (int i = 0; i < 10; i++) {
        uint32_t r[4][4];
        static_for<0, 4>([&](auto K) { ldsm_x4_i<K.value * 512>(r[K.value], p0 + i * 8192); });
#pragma unroll
        for (int k = 0; k < 4; k++) {
          bf2_to_h2_inplace(r[k][0], sc); bf2_to_h2_inplace(r[k][1], sc); bf2_to_h2_inplace(r[k][2], sc); bf2_to_h2_inplace(r[k][3], sc);
          stsm_x4(p0 + i * 8192 + k * 512, r[k][0], r[k][1], r[k][2], r[k][3]);
        }
      }
    }
    if (hw == 0) PT(10);
    bar_sync(0, 384);
    if (hw == 3) {
      const uint32_t eye = (m4 == q4) ? ((lane & 4) ? 0x3f800000u : 0x3f80u) : 0u;
      sts128(sb + OFF_LT + lane * 16, eye, eye, (lane & 2) * 64 + g * 16 + (lane & 1) * 8, 0u);
      sts64(sb + OFF_S + 1280 + lane * 8, 0u, 0u);
    }
    if (lead) st_relaxed_u32(arena + AR_TAB + cta * 4, 0x80000000u | (lds32_i<SC_W>(sb) << 15) | lds32_i<SC_W + 4>(sb));
    asm volatile("barrier.cluster.wait.aligned;" ::: "memory");
    bar_sync(B_MEM0, 256); bar_sync(B_MEM1, 256);
    {
      uint32_t v0, v1, v2; int spin = 0;
      do {
        v0 = ld_relaxed_u32(arena + AR_TAB + lane * 4); v1 = ld_relaxed_u32(arena + AR_TAB + 128 + lane * 4); v2 = ld_relaxed_u32(arena + AR_TAB + 256 + lane * 4);
      } while (__any_sync(0xffffffffu, ((v0 & v1 & v2) >> 31) == 0) && ++spin < SPIN_LIMIT);
      const uint32_t mv = (max(max(v0, v1), v2) >> 15) & 0x7fffu, mo = max(max(v0 & 0x7fffu, v1 & 0x7fffu), v2 & 0x7fffu);
      sts32(sb + SC_IN + 8 + (lane & 1) * 16, 15 - ((__reduce_max_sync(0xffffffffu, mv) >> 7) + (__reduce_max_sync(0xffffffffu, mo) >> 7) - 252 + 22));
    }

    auto store_kv = [&](int s) {
      const size_t o = ((size_t)s * 96 + cta) * KVB; const uint32_t src = sb + OFF_KV + (s & 1) * (2 * KVB);
      fence_proxy_async(); bulk_s2g(a.kg + o, src, KVB); bulk_s2g(a.vg + o, src + KVB, KVB); bulk_commit();
    };
    const int cb28 = unit28(hw), du = (unit24(hw) - cb28) * 128;
    uint32_t n16 = lane * 16, hist = 0;
    const uint32_t us1 = sb + d1 + OFF_SR + 256 + (hw >> 1) * 512 + (hw & 1) * 128, us2 = sb + d2 + OFF_SR + (hw >> 1) * 512 + (hw & 1) * 128;
    const uint32_t uo1 = sb + d1 + OFF_O + 2048 + hw * 256, uo2 = sb + d2 + OFF_O + 1024 + hw * 256;
#ifdef STEPCLK
    if (lead) a.dbg[96 * 300 + cta * 2] = clk32();
#endif
#ifdef TIMELINE
    if (cta == 0 && lead) { g_tl2[(a.tl >= 12) * 128 + 0] = clock64(); g_tl2[(a.tl >= 12) * 128 + 1] = gtime(); }
#endif
#pragma unroll 1
    for (int s = 0; s < cfg::NSEG; s++) {
      TS_SETUP();
      const bool last = s == cfg::NSEG - 1;
      if (n16 == 0) {
        if (hw == 2 && !last) issue_x(s + 1);
        if (hw == 0 && (s & 3) == 1 && s > 1) st_relaxed_u32(arena + (prog_off(h, j) + lds32_i<SC_IN + 12>(sb)), s - 1);
        if (hw == 0 && s > 0) store_kv(s - 1);
        if (PFX && hw == 3 && cta < 80 && s + PFX < cfg::NSEG) prefetch_l2(xg + (size_t)(s + PFX) * 40960 + cta * 512, 512);
        if (PFACC && hw == 1 && s + PFACC < cfg::NSEG - 1)
          asm volatile("prefetch.global.L2 [%0];" :: "l"(arena + (AR_ACC + acc_step(s + PFACC) + acc_lane(cta / 24, (cta & 3) * 8) + acc_voff((cta % 24) >> 2))) : "memory");
      }
      __syncwarp();
      if (last) break;
      const uint32_t kv = (s & 1) * (2 * KVB);
      n16 = fresh(n16);
      uint32_t kb0[4], kb1[4];
      { const uint32_t ka = n16 + (n16 & 384) * 4 + (sb + kv + hw * 128); ldsm_x4_i<OFF_KV>(kb0, ka); ldsm_x4_i<OFF_KV + 2560>(kb1, ka); }
      TS(1);
      bar_sync(B_QK, 384);
      {
        uint32_t q0[4], q1[4], q2[4], q3[4];
        float sa[4] = {0, 0, 0, 0}, sc2[4] = {0, 0, 0, 0};
        ldsm_x4_i<OFF_Q>(q0, n16 + sb); ldsm_x4_i<OFF_Q + 1024>(q2, n16 + sb); ldsm_x4_i<OFF_Q + 512>(q1, n16 + sb);
        bar_arrive(B_A, 288);
        ldsm_x4_i<OFF_Q + 1536>(q3, n16 + sb);
        mma16816(sa, q0[0], q0[1], q0[2], q0[3], kb0[0], kb0[1]);
        mma16816(sc2, q2[0], q2[1], q2[2], q2[3], kb1[0], kb1[1]);
        mma16816(sa, q1[0], q1[1], q1[2], q1[3], kb0[2], kb0[3]);
        mma16816(sc2, q3[0], q3[1], q3[2], q3[3], kb1[2], kb1[3]);
        const float x0 = (sa[0] + sa[2]) + (sc2[0] + sc2[2]), x1 = (sa[1] + sa[3]) + (sc2[1] + sc2[3]);
        const uint32_t xp = pack_bf16(x0, x1);
        st_async_b32_i<0>((n16 >> 2) + us1, xp, sb + MB_S + d1);
        st_async_b32_i<0>((n16 >> 2) + us2, xp, sb + MB_S + d2);
        stsm_x2(n16 + (sb + OFF_S + hw * 256), __float_as_uint(x0), __float_as_uint(x1));
      }
      TS(3);
      uint32_t v0[4], v1[4], vm0, vm1;
      const uint32_t uv = sb + kv + hw * 1280;
      ldsm_x4_t_i<OFF_KV + KVB>(v0, n16 + uv); ldsm_x4_t_i<OFF_KV + KVB + 640>(v1, n16 + uv);
      bar_sync(B_SL, 256);
      float t0[4], t1[4], t2[4];
      { uint32_t x[4]; ldsm_x4_i<OFF_S>(x, n16 + sb); t0[0] = __uint_as_float(x[0]); t0[1] = __uint_as_float(x[1]); t0[2] = __uint_as_float(x[2]); t0[3] = __uint_as_float(x[3]); }
      { uint32_t x[4]; ldsm_x4_i<OFF_S + 512>(x, n16 + sb); t1[0] = __uint_as_float(x[0]); t1[1] = __uint_as_float(x[1]); t1[2] = __uint_as_float(x[2]); t1[3] = __uint_as_float(x[3]); }
      { uint32_t x[4]; ldsm_x4_i<OFF_S + 1024>(x, n16 + sb); t2[0] = __uint_as_float(x[0]); t2[1] = __uint_as_float(x[1]); t2[2] = __uint_as_float(x[2]); t2[3] = __uint_as_float(x[3]); }
      mbar_spin(sb + MB_S, s & 1);
      TS(4);
      uint2 xo;
      {
        uint32_t r0[4], r1[4], r2[2];
        ldsm_x4_i<OFF_SR>(r0, n16 + sb); ldsm_x4_i<OFF_SR + 512>(r1, n16 + sb); ldsm_x2_i<OFF_SR + 1024>(r2, n16 + sb);
        SFENCE(n16);
        const uint2 eye = lds64_i<OFF_LT>(n16 + sb);
        mma16816(t0, r0[0], r0[1], r0[2], r0[3], eye.x, eye.y);
        mma16816(t1, r1[0], r1[1], r1[2], r1[3], eye.x, eye.y);
        mma1688(t2, r2[0], r2[1], eye.x);
        bar_sync(B_V, 256);
        vm0 = ldsm_x1_t_i<OFF_KV + KVB + 512>(n16 + uv); vm1 = ldsm_x1_t_i<OFF_KV + KVB + 1152>(n16 + uv);
        SFENCE(n16);
        xo = lds64_i<OFF_LT + 8>(n16 + sb);
      }
      float sc[10] = {t0[0], t0[1], t0[2], t0[3], t1[0], t1[1], t1[2], t1[3], t2[0] + t2[2], t2[1] + t2[3]};
      const float cs = 0.07216878364870322f * 1.4426950408889634f;
      float mx = fmaxf(fmaxf(fmaxf(sc[0], sc[1]), fmaxf(sc[2], sc[3])), fmaxf(fmaxf(sc[4], sc[5]), fmaxf(sc[6], sc[7])));
      mx = fmaxf(mx, fmaxf(sc[8], sc[9]));
      {
        const float m1 = __shfl_xor_sync(0xffffffffu, mx, 1), m2 = __shfl_xor_sync(0xffffffffu, mx, 2), m3 = __shfl_xor_sync(0xffffffffu, mx, 3);
        mx = fmaxf(fmaxf(mx, m1), fmaxf(m2, m3));
      }
      const float mo = fmaf(mx, -cs, __uint_as_float(xo.x));
      auto ex = [&](int i) -> uint32_t { float x, y;
        asm volatile("ex2.approx.ftz.f32 %0, %1;" : "=f"(x) : "f"(fmaf(sc[i], cs, mo))); asm volatile("ex2.approx.ftz.f32 %0, %1;" : "=f"(y) : "f"(fmaf(sc[i + 1], cs, mo)));
        return pack_bf16(x, y); };
      float oa[4] = {0, 0, 0, 0}, ob[4] = {0, 0, 0, 0}, oc[4] = {0, 0, 0, 0}, od[4] = {0, 0, 0, 0}, rs[4] = {0, 0, 0, 0};
      const uint32_t ones = 0x3f803f80u;
      const uint32_t p4 = ex(8);
      if (MEMFIRST) { mma1688(rs, p4, 0u, ones); mma1688(oa, p4, 0u, vm0); mma1688(ob, p4, 0u, vm1); }
      const uint32_t p0 = ex(0), p1 = ex(2), p2 = ex(4), p3 = ex(6);
      TS(5);
      mma16816(rs, p0, p2, p1, p3, ones, ones);
      mma16816(oa, p0, p2, p1, p3, v0[0], v0[1]);
      mma16816(oc, p0, p2, p1, p3, v0[2], v0[3]);
      mma16816(ob, p0, p2, p1, p3, v1[0], v1[1]);
      mma16816(od, p0, p2, p1, p3, v1[2], v1[3]);
      if (!MEMFIRST) { mma1688(rs, p4, 0u, ones); mma1688(oa, p4, 0u, vm0); mma1688(ob, p4, 0u, vm1); }
      const float inv = rcpf(rs[0] + rs[2]) * __uint_as_float(xo.y);
      {
        const uint32_t y0 = pack_bf16((oa[0] + oc[2]) * inv, (oa[1] + oc[3]) * inv), y1 = pack_bf16((ob[0] + od[2]) * inv, (ob[1] + od[3]) * inv);
        st_async_v2_i<0>(xo.x + uo1, y0, y1, sb + MB_O + d1);
        st_async_v2_i<0>(xo.x + uo2, y0, y1, sb + MB_O + d2);
        sts64_i<OFF_O>(xo.x + (sb + hw * 256), y0, y1);
      }
      bar_arrive(B_O, 384);
      TS(6);
      if (hw == 0) bulk_wait<0>();
      mbar_expect_tx_if(n16 == 0 && hw == 3, sb + MB_S, 1280);
      n16 = fresh(n16);
      const int ln = n16 >> 4;
      auto mslot = [&](int c) -> uint32_t { return sb + OFF_MEM + c * 128 + (((ln >> 2) ^ (2 * (c & 3))) << 4); };
      const int lq = ln & 3;
      const uint32_t ma = mslot(cb28 + lq), mb_ = mslot(cb28 + (lq >> 1)) + (lq & 1) * 8;
      const unsigned char* gp = arena + (AR_ACC + acc_lane(hw, ln) + acc_step(s));
      const bool odd = ln & 1;
      const uint32_t delay = a.delay + ((hist & 2) ? a.margin : 0);
      SFENCE(ma);
      uint32_t tw;
      if (hw == 0 && (s & 3) == 0 && a.pubrel) {
        bar_arrive(B_RED, 384);
        asm volatile("fence.acq_rel.gpu;" ::: "memory");
        uint2 t; int sp = 0;
        do { asm volatile("ld.volatile.shared.v2.u32 {%0,%1}, [%2];" : "=r"(t.x), "=r"(t.y) : "r"(sb + SC_TW) : "memory"); } while (__any_sync(0xffffffffu, t.y != (uint32_t)s) && ++sp < SPIN_LIMIT);
        tw = t.x;
      } else {
        bar_sync(B_RED, 384);
        SFENCE(mb_);
        tw = clk_v();
        if (hw == 1) asm volatile("st.volatile.shared.v2.u32 [%0], {%1,%2};" :: "r"(sb + SC_TW), "r"(tw), "r"(s) : "memory");
      }
      TSV(7, tw);
      mbar_expect_tx_if(n16 == 0 && hw == 3, sb + MB_O, 2048);
      while (clk_v() - tw < delay) {}
      TS(8);
      uint4 v[6];
      int spin = 0;
      const uint32_t cm = odd ? 0x5000u : 0u;
      do {
        static_for<0, 6>([&](auto I) { v[I.value] = ld_relaxed_v4_i<acc_voff(I.value)>(gp); });
      } while (__any_sync(0xffffffffu, (~((v[0].w & v[1].w & v[2].w) & (v[3].w & v[4].w & v[5].w)) & cm) != 0) && ++spin < SPIN_LIMIT);
      v[0].w = odd ? v[3].x : v[0].w; v[1].w = odd ? v[3].y : v[1].w; v[2].w = odd ? v[3].z : v[2].w; v[3].w = odd ? 0u : v[3].w;
      sts128_i<0>(ma, v[0].x, v[0].y, v[0].z, v[0].w);
      sts128_i<512>(ma, v[1].x, v[1].y, v[1].z, v[1].w);
      sts128_i<1024>(ma, v[2].x, v[2].y, v[2].z, v[2].w);
      sts128_i<0>(ma + du, v[4].x, v[4].y, v[4].z, v[5].z);
      sts64_i<512>(mb_ + du, v[5].x, v[5].y);
      if (!odd) sts128_i<1536>(mb_, v[3].x, v[3].y, v[3].z, v[3].w);
      hist = (hist * 2 + (spin != 0)) & 0xffffu;
      TSV(11, spin);
#ifdef TIMELINE
      if (hw == 2 && ln == 0) { uint32_t gt; asm volatile("mov.u32 %0, %%globaltimer_lo;" : "=r"(gt)); *(uint4*)(g_step + (((a.tl >= 12) * 64 + s) * 96 + cta) * 4) = make_uint4(gt, spin, clk_v() - tw, tw); }
#endif
      TS(10);
      bar_sync(B_MEM0, 256); bar_sync(B_MEM1, 256);
      uint32_t m = lds32_i<SC_IN + 12>(sb);
      uint32_t m2 = m;
      static_for<0, 3>([&](auto I) { m = amax_h2(amax_h2(amax_h2(amax_h2(m, v[I.value].x), v[I.value].y), v[I.value].z), v[I.value].w); });
      static_for<3, 6>([&](auto I) { m2 = amax_h2(amax_h2(amax_h2(m2, v[I.value].x), v[I.value].y), v[I.value].z); });
      m = amax_fold(amax_h2(amax_h2(m2, v[3].w), m));
      if (n16 == 0) asm volatile("red.shared.max.u32 [%0], %1;" :: "r"(sb + SC_IN + 4 + 16 * ((s + 1) & 1)), "r"(m) : "memory");
    }
    bar_sync(B_RED, 384);
    if (hw == 0 && n16 == 0) {
      store_kv(cfg::NSEG - 1);
      bulk_wait<0>();
      st_release_u32(arena + (prog_off(h, j) + lds32_i<SC_IN + 12>(sb)), cfg::NSEG);
    }
    __syncwarp();
#ifdef STEPCLK
    if (hw == 0 && n16 == 0) a.dbg[96 * 300 + cta * 2 + 1 + (hist >> 20)] = clk32();
#endif
#ifdef TIMELINE
    if (cta == 0 && hw == 0 && n16 == 0) { g_tl2[(a.tl >= 12) * 128 + 2] = clock64(); g_tl2[(a.tl >= 12) * 128 + 3] = gtime(); }
#endif
    TL_END(a.tl);
    asm volatile("barrier.cluster.arrive.relaxed.aligned; barrier.cluster.wait.aligned;" ::: "memory");
  } else {
    asm volatile("setmaxnreg.inc.sync.aligned.u32 232;");
    const int wi = warp & 3, hf = warp >> 2, tid = warp * 32 + lane;
    uint32_t w[40][4], wm = 0;
    uint32_t wqa;
    { const int mrow = r8 + ((lane >> 4) << 3), mch = 2 * wi + (m4 & 1); wqa = sb + mrow * 128 + ((mch ^ r8) << 4); }
    {
      const uint32_t wa = wqa + (hf ? OFF_WO : OFF_WQ);
      mbar_wait(sb + (hf ? MB_V : MB_K), 0);
      static_for<0, 20>([&](auto K) { ldsm_x4_t_i<K.value * 2048>(w[K.value], wa); });
#pragma unroll
      for (int k = 0; k < 20; k++) wm = amax_bf2(amax_bf2(wm, amax_bf2(w[k][0], w[k][1])), amax_bf2(w[k][2], w[k][3]));
      SFENCE2(wa, wm);
      if (warp == 0) PT(1);
      bar_arrive(hf ? B_V : B_QK, 160);
      mbar_wait(sb + (hf ? MB_V : MB_K) + 8, 0);
      static_for<20, 40>([&](auto K) { ldsm_x4_t_i<K.value * 2048>(w[K.value], wa); });
#pragma unroll
      for (int k = 20; k < 40; k++) wm = amax_bf2(amax_bf2(wm, amax_bf2(w[k][0], w[k][1])), amax_bf2(w[k][2], w[k][3]));
      SFENCE2(wa, wm);
      if (warp == 4) PT(2);
      bar_arrive(hf ? B_O : B_SL, 160);
      SFENCE(wa);
    }
    float iw, iq;
    {
      const uint32_t m = amax_fold(wm);
      if (hf && lane == 0) asm volatile("red.shared.max.u32 [%0], %1;" :: "r"(sb + SC_W), "r"(m) : "memory");
      const int e = wscale_exp(m);
      const uint32_t sc = (uint32_t)(e + 127) * 0x00800080u; iw = exp2i(-e);
#pragma unroll
      for (int k = 0; k < 40; k++) { bf2_to_h2_inplace(w[k][0], sc); bf2_to_h2_inplace(w[k][1], sc); bf2_to_h2_inplace(w[k][2], sc); bf2_to_h2_inplace(w[k][3], sc); }
    }
    uint32_t x0[8];
    {
      float xa[16];
      const uint32_t dlo = (((sb + OFF_X) & 0x3FFFF) >> 4) | (1u << 16);
      if (warp == 0) PT(3);
      mbar_wait(sb + MB_X, 0);
      if (warp == 0) PT(4);
      wgmma_fence();
      static_for<0, 40>([&](auto K) { constexpr int k = K.value; wgmma_rs32h<((k >> 2) * 4096 + (k & 3) * 32) / 16, (k != 0)>(xa, w[k], dlo); });
      wgmma_commit();
      wgmma_wait<0>();
#pragma unroll
      for (int i = 0; i < 8; i++) x0[i] = pack_bf16(xa[2 * i] * iw, xa[2 * i + 1] * iw);
    }
    const bool t28 = j == 0 || warp < 4;
    const int bi = j == 0 ? hf : (warp < 4 ? j + 1 : 2 * (j - 1) + ((warp - 4) >> 1)), bv = t28 ? wi : 4 + (warp & 1);
    uint32_t wo1 = sb + OFF_WO + warp * 896 + lane * 16, wo2;
    {
      const int cb = (t28 ? unit28(bi) : unit24(bi)) - col0 / 8;
      uint32_t cp[4];
#pragma unroll
      for (int wd = 0; wd < 4; wd++) {
        int c, p;
        if (bv < 3) { c = 4 * bv + q4; p = wd; }
        else if (bv == 3) { if (q4 & 1) { c = 4 * (wd % 3) + q4; p = 3; } else { c = 12 + (q4 >> 1); p = wd; } }
        else if (bv == 4) { c = q4; p = wd; }
        else { if (wd < 2) { c = 4 + (q4 >> 1); p = 2 * (q4 & 1) + wd; } else { c = q4; p = 3; } }
        cp[wd] = sb + OFF_WO + ((g & 1) + (g & 2) * 4 + (g >> 2) * 2) * WOS + (cb + c) * 16 + p * 4;
      }
      const int cidx = (r8 & 1) + ((r8 >> 2) << 1);
      wo2 = sb + OFF_WO + warp * 896 + ((m4 & 1) ? 768 + (m4 >> 1) * 64 + cidx * 16 : 512 + (m4 >> 1) * 128 + r8 * 16);
      const bool dump = (m4 & 1) && (r8 & 2);
      uint32_t mo = 0;
      const bool regular = bv < 3 || bv == 4;
#pragma unroll 1
      for (int i = 0; i < 3; i++) {
        uint32_t x[4][4], y[4][4];
        const uint32_t o = i * 4 * WOK;
        mbar_wait(sb + MB_R + 8 * i, 0);
        if (warp == 0) PT(5 + i);
        if (regular) {
          static_for<0, 4>([&](auto K) {
            constexpr int kk = K.value;
            const uint4 u = lds128_i<kk * WOK>(cp[0] + o), v = lds128_i<kk * WOK + 4 * WOS>(cp[0] + o);
            x[kk][0] = u.x; x[kk][1] = u.y; x[kk][2] = u.z; x[kk][3] = u.w; y[kk][0] = v.x; y[kk][1] = v.y; y[kk][2] = v.z; y[kk][3] = v.w;
          });
        } else {
          static_for<0, 4>([&](auto K) {
            constexpr int kk = K.value;
#pragma unroll
            for (int wd = 0; wd < 4; wd++) { x[kk][wd] = lds32_i<kk * WOK>(cp[wd] + o); y[kk][wd] = lds32_i<kk * WOK + 4 * WOS>(cp[wd] + o); }
          });
        }
        bar_sync(B_C, 256);
        static_for<0, 4>([&](auto K) {
          constexpr int kk = K.value;
#pragma unroll
          for (int wd = 0; wd < 4; wd++) mo = amax_bf2(mo, amax_bf2(x[kk][wd], y[kk][wd]));
          stsm_x4_t_i<kk * WOK>(wo1 + o, x[kk][0], x[kk][1], y[kk][0], y[kk][1]);
          stsm_x4_t_i<0>(dump ? sb + OFF_S + 512 + lane * 16 : wo2 + o + kk * WOK, x[kk][2], x[kk][3], y[kk][2], y[kk][3]);
        });
      }
      if (warp == 0) PT(8);
      mo = amax_fold(mo);
      if (lane == 0) asm volatile("red.shared.max.u32 [%0], %1;" :: "r"(sb + SC_W + 4), "r"(mo) : "memory");
    }
    __syncwarp();
    auto run = [&](auto HF) {
    constexpr int hf = HF.value;
    uint32_t mema, sta, l16 = sb + lane * 16;
    uint32_t rq[hf ? NP1 : NQ0][4];
    auto step_addr = [&](uint32_t kv) {
      const int lr = (l16 >> 4) & 7, lm = (l16 >> 7) & 3;
      mema = l16 ^ (lm << 5);
      sta = sb + lr * 16 + (lm < 2 ? OFF_Q + wi * 512 + hf * 128 + lm * 256 : OFF_KV + kv + 512 + (2 * wi + lm - 2) * 640);
    };
    auto x_gemm = [&](uint32_t ph, [[maybe_unused]] uint32_t tsb) {
      float xa[16];
      const uint32_t dlo = (((sb + OFF_X) & 0x3FFFF) >> 4) | (1u << 16);
      constexpr int NP = hf ? NP1 : NP0;
      if constexpr (hf) {
        static_for<PQE, NP>([&](auto K) { ldsm_x4_t_i<OFF_WQ + K.value * 2048>(rq[K.value], wqa); });
        bar_sync(B_X, 256);
      }
      wgmma_fence();
      static_for<0, 40>([&](auto K) {
        constexpr int k = K.value;
        wgmma_rs32h<((k >> 2) * 4096 + (k & 3) * 32) / 16, (k != 0)>(xa, w[k], dlo);
        if constexpr (!hf && k == PFK && NP > PQE) { SFENCE(wqa); static_for<PQE, NP>([&](auto K) { ldsm_x4_t_i<OFF_WQ + K.value * 2048>(rq[K.value], wqa); }); SFENCE(wqa); }
        if constexpr (!hf && k == XT) bar_arrive(B_X, 256);
      });
      step_addr(ph * (2 * KVB));
      wgmma_commit();
      TS(9);
      wgmma_wait<0>();
      const uint32_t xs = l16 + (wi * 1280 + ph * (2 * KVB));
      stsm_x4_t_i<OFF_KV + hf * KVB>(xs, pack_bf16(xa[0] * iw, xa[1] * iw), pack_bf16(xa[4] * iw, xa[5] * iw), pack_bf16(xa[8] * iw, xa[9] * iw), pack_bf16(xa[12] * iw, xa[13] * iw));
      stsm_x4_t_i<OFF_KV + hf * KVB + 640>(xs, pack_bf16(xa[2] * iw, xa[3] * iw), pack_bf16(xa[6] * iw, xa[7] * iw), pack_bf16(xa[10] * iw, xa[11] * iw), pack_bf16(xa[14] * iw, xa[15] * iw));
      if constexpr (!hf) static_for<NP0, NP0 + NPL>([&](auto K) { ldsm_x4_t_i<OFF_WQ + K.value * 2048>(rq[K.value], wqa); });
    };
    auto wq_addr = [&](uint32_t l) -> uint32_t {
      const int lr = (l >> 4) & 7, lm = (l >> 7) & 3;
      return sb + hf * ((40 - NQ1) * 2048) + (lr + ((lm >> 1) << 3)) * 128 + (((2 * wi + (lm & 1)) ^ lr) << 4);
    };
    constexpr int NPM = hf ? NPM1 : NPM0;
    uint32_t u1[NPM][4], u2[NPM][4];
    static_for<0, NPM>([&](auto K) { ldsm_x4_i<(12 - NPM + K.value) * WOK>(u1[K.value], wo1); ldsm_x4_i<(12 - NPM + K.value) * WOK>(u2[K.value], wo2); });
    bar_sync(0, 384);
    iq = uniform_f(exp2i(-wscale_exp(lds32_i<SC_W + 8>(sb))));
    wqa = wq_addr(l16);
    static_for<0, (hf ? NP1 : NP0 + NPL)>([&](auto K) { ldsm_x4_t_i<OFF_WQ + K.value * 2048>(rq[K.value], wqa); });
    step_addr(0);
    stsm_x4_t_i<OFF_KV + hf * KVB>(l16 + wi * 1280, x0[0], x0[2], x0[4], x0[6]);
    stsm_x4_t_i<OFF_KV + hf * KVB + 640>(l16 + wi * 1280, x0[1], x0[3], x0[5], x0[7]);
    asm volatile("barrier.cluster.wait.aligned;" ::: "memory");
    TL_END(a.tl + 1);
#pragma unroll 1
    for (int s = 0; s < cfg::NSEG - 1; s++) {
      TS_SETUP();
#if CHAIN_TIMING
      if (tid == 0 && (s & 7) == 0) a.dbg[96 * 288 + cta * 8 + (s >> 3)] = clk32();
#endif
      bar_sync(hf ? B_MEM1 : B_MEM0, 256);
      const float sin_ = __uint_as_float(lds32_i<SC_IN>(sb + 16 * (s & 1)));
      constexpr int NPQ = (40 - NQ1) / 2;
      if constexpr (hf == 0) {
        float k0[4] = {0, 0, 0, 0}, k1[4] = {0, 0, 0, 0}, q0[4] = {0, 0, 0, 0}, q1[4] = {0, 0, 0, 0};
        constexpr auto pair_of = [](int t) { const int a = t * (20 - NPQ) / 20, b = (t + 1) * (20 - NPQ) / 20; return b > a ? NPQ + a : t - a; };
        uint32_t b[NB0][4];
        static_for<0, NB0>([&](auto T) { ldsm_x4_i<OFF_MEM + pair_of(T.value) * 512>(b[T.value], mema); });
        static_for<NP0 + NPL, NQ0>([&](auto K) { ldsm_x4_t_i<OFF_WQ + K.value * 2048>(rq[K.value], wqa); });
        if (BBS < 100) bbfence<0>(mema);
        static_for<0, 20>([&](auto T) {
          constexpr int t = T.value, p = pair_of(t);
          uint32_t (&bb)[4] = b[t % NB0];
          if constexpr (p < NPQ) {
            mma16816h(q0, rq[(2 * p) % NQ0], bb[0], bb[1]);
            if constexpr (2 * p + NQ0 < 2 * NPQ) ldsm_x4_t_i<OFF_WQ + (2 * p + NQ0) * 2048>(rq[(2 * p) % NQ0], wqa);
          }
          mma16816h(k0, w[2 * p], bb[0], bb[1]);
          if constexpr (p < NPQ) {
            mma16816h(q1, rq[(2 * p + 1) % NQ0], bb[2], bb[3]);
            if constexpr (2 * p + 1 + NQ0 < 2 * NPQ) ldsm_x4_t_i<OFF_WQ + (2 * p + 1 + NQ0) * 2048>(rq[(2 * p + 1) % NQ0], wqa);
          }
          mma16816h(k1, w[2 * p + 1], bb[2], bb[3]);
          if constexpr (NVE > 0 && t + NB0 == VET) bar_arrive(B_E, 256);
          if constexpr (t + NB0 < 20) ldsm_x4_i<OFF_MEM + pair_of(t + NB0) * 512>(bb, mema);
          if constexpr (t < 20 - NB0 && (t % BBS) == BBS - 1) bbfence<t + 1>(mema);
        });
        const float sq = sin_ * iq, sk = sin_ * iw;
        stsm_x4_t_i<0>(sta, pack_bf16((q0[0] + q1[0]) * sq, (q0[1] + q1[1]) * sq), pack_bf16((q0[2] + q1[2]) * sq, (q0[3] + q1[3]) * sq),
                       pack_bf16((k0[0] + k1[0]) * sk, (k0[1] + k1[1]) * sk), pack_bf16((k0[2] + k1[2]) * sk, (k0[3] + k1[3]) * sk));
        bar_sync(B_QK, 384);
        TS(2);
        {
          if (wi == 3) {
            const uint32_t xr = sb + ((l16 & 511) >> 2), ka = l16 + (l16 & 384) * 4 + (s & 1) * (2 * KVB);
            uint32_t a0[4], a1[4], a2[4], a3[4], kb0[4], kb1[4];
            ldsm_x4_i<OFF_Q>(a0, l16); ldsm_x4_i<OFF_KV + 512>(kb0, ka); ldsm_x4_i<OFF_Q + 1024>(a2, l16); ldsm_x4_i<OFF_KV + 512 + 2560>(kb1, ka);
            ldsm_x4_i<OFF_Q + 512>(a1, l16);
            bar_arrive(B_A, 288);
            ldsm_x4_i<OFF_Q + 1536>(a3, l16);
            float sa[4] = {0, 0, 0, 0}, sc2[4] = {0, 0, 0, 0};
            mma16816(sa, a0[0], a0[1], a0[2], a0[3], kb0[0], kb0[1]);
            mma16816(sc2, a2[0], a2[1], a2[2], a2[3], kb1[0], kb1[1]);
            mma16816(sa, a1[0], a1[1], a1[2], a1[3], kb0[2], kb0[3]);
            mma16816(sc2, a3[0], a3[1], a3[2], a3[3], kb1[2], kb1[3]);
            const float x0 = (sa[0] + sa[2]) + (sc2[0] + sc2[2]), x1 = (sa[1] + sa[3]) + (sc2[1] + sc2[3]);
            const uint32_t xp = pack_bf16(x0, x1);
            st_async_b32_i<OFF_SR + 1024 + 128>(xr + d1, xp, sb + MB_S + d1);
            st_async_b32_i<OFF_SR + 1024>(xr + d2, xp, sb + MB_S + d2);
            stsm_x2(l16 + OFF_S + 1024, __float_as_uint(x0), __float_as_uint(x1));
          } else if (wi == 0) {
            const uint4 si = lds128_i<SC_IN>(sb + 16 * (s & 1));
            const int em = (int)(si.y >> 10) - 14 + (int)(si.x >> 23) - 127;
            const uint32_t osc = __float_as_uint(exp2i(max(min((int)si.z - max(em, 1), 100), -100)));
            sts32(l16 + OFF_LT + 12, osc); sts64_i<SC_IN>(sb + 16 * ((s + 1) & 1), 0x7f000000u - osc, 0u);
          }
          bar_sync(B_SL, 256);
        }
      } else {
        float v0[4] = {0, 0, 0, 0}, v1[4] = {0, 0, 0, 0}, q0[4] = {0, 0, 0, 0}, q1[4] = {0, 0, 0, 0};
        constexpr int NB1 = NQ1 / 2 < 3 ? NQ1 / 2 : 3;
        uint32_t b[NB1][4];
        static_for<0, NB1>([&](auto T) { ldsm_x4_i<OFF_MEM + (NPQ + T.value) * 512>(b[T.value], mema); });
        static_for<0, NQ1 / 2>([&](auto T) {
          constexpr int t = T.value, p = NPQ + t;
          uint32_t (&bb)[4] = b[t % NB1];
          mma16816h(q0, rq[(2 * t) % NP1], bb[0], bb[1]);
          if constexpr (2 * t + NP1 < NQ1) ldsm_x4_t_i<OFF_WQ + (2 * t + NP1) * 2048>(rq[(2 * t) % NP1], wqa);
          mma16816h(q1, rq[(2 * t + 1) % NP1], bb[2], bb[3]);
          if constexpr (2 * t + 1 + NP1 < NQ1) ldsm_x4_t_i<OFF_WQ + (2 * t + 1 + NP1) * 2048>(rq[(2 * t + 1) % NP1], wqa);
          mma16816h(v0, w[2 * p], bb[0], bb[1]);
          mma16816h(v1, w[2 * p + 1], bb[2], bb[3]);
          if constexpr (t + NB1 < NQ1 / 2) ldsm_x4_i<OFF_MEM + (p + NB1) * 512>(bb, mema);
        });
        const float sq = sin_ * iq, sv = sin_ * iw;
        stsm_x2_t_i<0>(sta, pack_bf16((q0[0] + q1[0]) * sq, (q0[1] + q1[1]) * sq), pack_bf16((q0[2] + q1[2]) * sq, (q0[3] + q1[3]) * sq));
        TS(2);
        bar_arrive(B_QK, 384);
        float v2[4] = {0, 0, 0, 0}, v3[4] = {0, 0, 0, 0};
        auto vpair = [&](auto P, uint32_t (&bb)[4]) {
          constexpr int p = P.value;
          if constexpr (p & 1) { mma16816h(v0, w[2 * p], bb[0], bb[1]); mma16816h(v1, w[2 * p + 1], bb[2], bb[3]); }
          else { mma16816h(v2, w[2 * p], bb[0], bb[1]); mma16816h(v3, w[2 * p + 1], bb[2], bb[3]); }
        };
        if constexpr (NVE > 0) {
          uint32_t e[NVE ? NVE : 1][4];
          bar_sync(B_E, 256);
          static_for<0, NVE>([&](auto T) { ldsm_x4_i<OFF_MEM + T.value * 512>(e[T.value], mema); });
          static_for<0, NVE>([&](auto T) { vpair(T, e[T.value]); });
        }
        bar_sync(B_A, 288);
        uint32_t c[4][4];
        static_for<NVE, (NVE + 4 < NPQ ? NVE + 4 : NPQ)>([&](auto T) { ldsm_x4_i<OFF_MEM + T.value * 512>(c[T.value & 3], mema); });
        static_for<NVE, NPQ>([&](auto T) {
          constexpr int p = T.value;
          vpair(T, c[p & 3]);
          if constexpr (p + 4 < NPQ) ldsm_x4_i<OFF_MEM + (p + 4) * 512>(c[p & 3], mema);
        });
        stsm_x2_t_i<OFF_KV + KVB + 512>(l16 + (l16 & 128) * 4 + (wi * 1280 + (s & 1) * (2 * KVB)), pack_bf16(((v0[0] + v1[0]) + (v2[0] + v3[0])) * sv, ((v0[1] + v1[1]) + (v2[1] + v3[1])) * sv),
                            pack_bf16(((v0[2] + v1[2]) + (v2[2] + v3[2])) * sv, ((v0[3] + v1[3]) + (v2[3] + v3[3])) * sv));
        bar_arrive(B_V, 256);
      }
      TS(3);
      {
        uint32_t t1[12][4], t2[12][4];
        const uint32_t o16 = l16;
        wo1 = l16 + (OFF_WO + warp * 896);
        wo2 = sb + OFF_WO + warp * 896 + ((l16 & 128) ? 768 + ((l16 & 256) >> 2) + (l16 & 16) + ((l16 & 64) >> 1) : 512 + ((l16 & 256) >> 1) + (l16 & 112));
        auto ldw = [&](auto K) { if constexpr (K.value < 12 - NPM) { ldsm_x4_i<K.value * WOK>(t1[K.value], wo1); ldsm_x4_i<K.value * WOK>(t2[K.value], wo2); } };
        constexpr int NR_ = NRT - NPM;
        constexpr int PB = (hf ? PB1 : PB0) < NR_ ? (hf ? PB1 : PB0) : NR_, PA = (hf ? PA1 : PA0) < PB ? (hf ? PA1 : PA0) : PB;
        static_for<0, PA>(ldw);
        mbar_spin(sb + MB_X, (s + 1) & 1);
        if constexpr (PB > PA) {
          constexpr int PM = PA + PM1 < PB ? PA + PM1 : PB;
          mbar_spin(sb + MB_S, s & 1);
          const uint32_t t0 = clk_v();
          if constexpr (PM > PA) { while (clk_v() - t0 < GD1) {} static_for<PA, PM>(ldw); }
          if constexpr (PB > PM) { while (clk_v() - t0 < GD2) {} static_for<PM, PB>(ldw); }
        }
        float c0[4] = {0, 0, 0, 0}, c1[4] = {0, 0, 0, 0}, e0[4] = {0, 0, 0, 0}, e1[4] = {0, 0, 0, 0};
        uint32_t ob[6][4];
        auto kstep = [&](auto K) {
          constexpr int k = K.value;
          uint32_t (&bb)[4] = ob[k >> 1];
          uint32_t (&x)[4] = k < 12 - NPM ? t1[k] : u1[k < 12 - NPM ? 0 : k - (12 - NPM)];
          uint32_t (&y)[4] = k < 12 - NPM ? t2[k] : u2[k < 12 - NPM ? 0 : k - (12 - NPM)];
          if constexpr (k & 1) { mma16816(c1, x[0], x[1], x[2], x[3], bb[2], bb[3]); mma16816(e1, y[0], y[1], y[2], y[3], bb[2], bb[3]); }
          else { mma16816(c0, x[0], x[1], x[2], x[3], bb[0], bb[1]); mma16816(e0, y[0], y[1], y[2], y[3], bb[0], bb[1]); }
          if constexpr (k >= NRF) ldw(IC<k + NR_ - NRF>{});
        };
        auto ldo = [&](auto P) { ldsm_x4_i<OFF_O + P.value * 512>(ob[P.value], o16); };
        TS(4);
        bar_sync(B_O, 384);
        ldo(IC<0>{}); ldo(IC<1>{});
        SFENCE(o16);
        static_for<PB, NR_>(ldw);
        static_for<0, 4>(kstep);
        TS(5);
        mbar_spin(sb + MB_O, s & 1);
        TS(6);
        ldo(IC<2>{}); ldo(IC<NPM >= 2 ? 5 : 3>{});
        if (WOF) SFENCE(o16);
        kstep(IC<4>{});
        if constexpr (NPM < 2) { kstep(IC<5>{}); ldo(IC<4>{}); kstep(IC<6>{}); kstep(IC<7>{}); ldo(IC<5>{}); static_for<8, 12>(kstep); }
        else if constexpr (NPM >= 4) { kstep(IC<10>{}); kstep(IC<11>{}); ldo(IC<4>{}); kstep(IC<5>{}); ldo(IC<3>{}); kstep(IC<8>{}); kstep(IC<9>{}); kstep(IC<6>{}); kstep(IC<7>{}); }
        else { kstep(IC<5>{}); ldo(IC<3>{}); kstep(IC<11>{}); kstep(IC<10>{}); ldo(IC<4>{}); kstep(IC<6>{}); kstep(IC<7>{}); if constexpr (NPM == 3) { kstep(IC<9>{}); kstep(IC<8>{}); } else { kstep(IC<8>{}); kstep(IC<9>{}); } }
        l16 = fresh(l16);
        const int ln = (l16 >> 4) & 31;
        if constexpr (CEARLY && hf) { SFENCE2(o16, __float_as_uint(e1[0])); bar_arrive(B_G, 256); }
        unsigned char* gr = arena + (AR_ACC + acc_lane(bi, ln) + acc_voff(bv) + acc_step(s));
        const bool cnt = (ln & 1) || !t28;
        wqa = wq_addr(l16);
        SFENCE(o16);
        static_for<0, PQE>([&](auto K) { ldsm_x4_t_i<OFF_WQ + K.value * 2048>(rq[K.value], wqa); });
        const uint32_t y0 = movm_t(pack_f16(c0[0] + c1[0], c0[1] + c1[1])), y1 = movm_t(pack_f16(c0[2] + c1[2], c0[3] + c1[3]));
        const uint32_t y2 = movm_t(pack_f16(e0[0] + e1[0], e0[1] + e1[1])), y3 = movm_t(pack_f16(e0[2] + e1[2], e0[3] + e1[3]));
        asm volatile("red.relaxed.gpu.global.add.noftz.v4.f16x2 [%0], {%1,%2,%3,%4};" :: "l"(gr), "r"(y0), "r"(y1), "r"(y2), "r"(cnt ? 0x3c00u : y3) : "memory");
        bar_arrive(B_RED, 384);
        if constexpr (CEARLY && !hf) { bar_arrive(B_C, 256); bar_sync(B_G, 256); }
        else bar_sync(B_C, 256);
        TS(7);
      }
#if CHAIN_TIMING
      x_gemm((s + 1) & 1, tsb);
#else
      x_gemm((s + 1) & 1, 0);
#endif
      TS(8);
    }
    };
    if (hf == 0) run(IC<0>{}); else run(IC<1>{});
    {
      const uint32_t l16 = sb + (threadIdx.x & 31) * 16, mema = l16 ^ ((l16 >> 2) & 96);
      float c0[4] = {0, 0, 0, 0}, c1[4] = {0, 0, 0, 0}, c2[4] = {0, 0, 0, 0}, c3[4] = {0, 0, 0, 0};
      bar_sync(hf ? B_MEM1 : B_MEM0, 256);
      const float sc = __uint_as_float(lds32_i<SC_IN + 16>(sb)) * iw;
      static_for<0, 10>([&](auto T) {
        constexpr int p = 2 * T.value;
        uint32_t b0[4], b1[4];
        ldsm_x4_i<OFF_MEM + p * 512>(b0, mema); ldsm_x4_i<OFF_MEM + p * 512 + 512>(b1, mema);
        mma16816h(c0, w[2 * p], b0[0], b0[1]); mma16816h(c1, w[2 * p + 1], b0[2], b0[3]);
        mma16816h(c2, w[2 * p + 2], b1[0], b1[1]); mma16816h(c3, w[2 * p + 3], b1[2], b1[3]);
      });
      stsm_x2_t_i<OFF_KV + 2 * KVB + 512>(l16 + (l16 & 128) * 4 + wi * 1280 + hf * KVB, pack_bf16(((c0[0] + c1[0]) + (c2[0] + c3[0])) * sc, ((c0[1] + c1[1]) + (c2[1] + c3[1])) * sc),
                                          pack_bf16(((c0[2] + c1[2]) + (c2[2] + c3[2])) * sc, ((c0[3] + c1[3]) + (c2[3] + c3[3])) * sc));
      fence_proxy_async();
    }
    bar_arrive(B_RED, 384);
#if CHAIN_TIMING
    for (int i = tid; i < 288; i += 256) a.dbg[cta * 288 + i] = lds32_i<OFF_BAR + 128>(sb + i * 4);
#endif
    asm volatile("barrier.cluster.arrive.relaxed.aligned; barrier.cluster.wait.aligned;" ::: "memory");
  }
}
struct PrepArgs { const bf16 *wqkv, *wphi, *wo; unsigned char *wb, *wot; };
__device__ __forceinline__ void prep_body(const int cta, const PrepArgs& pa) {
  const int tid = threadIdx.x, lane = tid & 31, warp = tid >> 5, g = lane >> 2, q = lane & 3;
  const int pair = cta >> 1, which = cta & 1;
  uint32_t bfr[2][3][3];
#pragma unroll
  for (int hh = 0; hh < 2; hh++)
#pragma unroll
    for (int t = 0; t < 3; t++) {
      const unsigned short* ph = (const unsigned short*)pa.wphi + (2 * pair + hh) * 400 + (t < 2 ? 8 * t + g : 16 + (g >> 1)) + 2 * q * 20;
#pragma unroll
      for (int r = 0; r < 3; r++) {
        const int o = (r < 2 || q < 2) ? r * 160 : 0;
        const uint32_t v = (uint32_t)__ldg(ph + o) | ((uint32_t)__ldg(ph + o + 20) << 16);
        bfr[hh][t][r] = ((t < 2 || (g & 1) == hh) && (r < 2 || q < 2)) ? v : 0u;
      }
    }
  const int gt = cta * 256 + tid;
#pragma unroll 1
  for (int i = 0; i < 5; i++) {
    uint32_t af[2][6];
#pragma unroll
    for (int hh = 0; hh < 2; hh++) {
      const uint32_t* r0 = (const uint32_t*)(pa.wqkv + (size_t)((warp * 5 + i) * 16 + g) * 1920 + which * 640 + (2 * pair + hh) * 20) + q;
      af[hh][0] = __ldg(r0); af[hh][1] = __ldg(r0 + 7680); af[hh][2] = __ldg(r0 + 4); af[hh][3] = __ldg(r0 + 7684);
      af[hh][4] = __ldg(r0 + 8); af[hh][5] = __ldg(r0 + 7688);
    }
    const int iv = i * 4096 + (gt >> 1), k = (iv & 7) + (iv >> 8) * 8, h = (iv >> 3) & 31;
    const uint2* src = (const uint2*)(pa.wqkv + (size_t)k * 1920 + 1280 + h * 20) + (gt & 1) * 2;
    const uint2 a = __ldg(src), b = __ldg(src + 1), e = __ldg(src + 2);
    uint4 wv[2]; uint32_t wd[2];
#pragma unroll
    for (int n = 0; n < 2; n++) {
      const int iw = min((2 * i + n) * 5120 + gt, 640 * 80 - 1), r = iw & 7, c = (iw >> 3) % 80, kg = iw / 640, c5 = kg % 5;
      const int row = (kg / 5) * 40 + (c5 < 2 ? 8 * c5 + r : (c5 == 2 ? 16 + (r & 3) + (r >> 2) * 20 : 20 + 8 * (c5 - 3) + r));
      wv[n] = __ldg((const uint4*)(pa.wo + (size_t)row * cfg::DM + c * 8));
      wd[n] = (((c / 10) * 80 + kg) * 10 + c % 10) * 128 + r * 16;
    }
    uint4* dv = (uint4*)(pa.wb + ((size_t)((h >> 2) * 80 + (k >> 3)) * 32 + 20 + 3 * (h & 3)) * 128 + (k & 7) * 16);
    dv[(gt & 1) * 8] = make_uint4(a.x, a.y, b.x, b.y);
    if (gt & 1) dv[16] = (h & 1) ? make_uint4(0, 0, e.x, e.y) : make_uint4(e.x, e.y, 0, 0);
    if (gt < 5120) { *(uint4*)(pa.wot + wd[0]) = wv[0]; *(uint4*)(pa.wot + wd[1]) = wv[1]; }
    uint32_t* dst = (uint32_t*)(pa.wb + ((size_t)((pair >> 1) * 80 + (warp * 5 + i) * 2) * 32 + which * 10 + (pair & 1) * 5) * 128) + lane;
#pragma unroll
    for (int t = 0; t < 5; t++) {
      float d[4] = {0, 0, 0, 0};
#pragma unroll
      for (int hh = 0; hh < 2; hh++)
        if (t == 2 || (t > 2) == (hh == 1)) {
          const int tt = t < 3 ? t : t - 3;
          mma16816(d, af[hh][0], af[hh][1], af[hh][2], af[hh][3], bfr[hh][tt][0], bfr[hh][tt][1]);
          mma1688(d, q < 2 ? af[hh][4] : 0u, q < 2 ? af[hh][5] : 0u, bfr[hh][tt][2]);
        }
      dst[t * 32] = pack_bf16(d[0], d[1]); dst[1024 + t * 32] = pack_bf16(d[2], d[3]);
    }
  }
}

__global__ void __launch_bounds__(256, 4) ln_kernel(const bf16* __restrict__ xin, bf16* __restrict__ xn, uint2* __restrict__ xh, uint4* __restrict__ z0, int n0,
                                                    uint4* __restrict__ z1, int n1, const bf16* pfa, const bf16* pfb, int npf, int tl) {
  asm volatile("griddepcontrol.wait;" ::: "memory");
  asm volatile("griddepcontrol.launch_dependents;" ::: "memory");
  TL_BEGIN(tl);
  const int warp = threadIdx.x >> 5, lane = threadIdx.x & 31;
  const int row = blockIdx.x * 8 + warp;
  uint2 xw[1][5];
#pragma unroll
  for (int i = 0; i < 5; i++) xw[0][i] = *(const uint2*)(xin + (size_t)row * cfg::DM + i * 128 + lane * 4);
  for (int i = blockIdx.x * 256 + threadIdx.x; i < n0; i += 256 * 256) z0[i] = make_uint4(0, 0, 0, 0);
  for (int i = blockIdx.x * 256 + threadIdx.x; i < n1; i += 256 * 256) z1[i] = make_uint4(0, 0, 0, 0);
  if (npf && xw[0][4].y != 0x7fc17fc1u) {
    for (int i = 0; i < npf; i++) {
      const uint32_t l = (uint32_t)i * 32768u + (blockIdx.x * 256 + threadIdx.x) / 2;
      if (l < cfg::DM * cfg::HD / 64) asm volatile("prefetch.global.L2 [%0];" :: "l"(((threadIdx.x & 1) ? pfa : pfb) + (size_t)l * 64) : "memory");
    }
  }
  ln_rows<1>(xw, row, lane, xn, xh);
  TL_END(tl);
}
struct Pipe { uint32_t stage, phase; };
template <int NS> __device__ __forceinline__ void pipe_adv(Pipe& p) { if (++p.stage == NS) { p.stage = 0; p.phase ^= 1; } }
constexpr uint32_t SWZ128 = 1;
__device__ __forceinline__ uint64_t desc_kmajor(uint32_t a) { return make_desc(a, 16, 1024, SWZ128); }
__device__ __forceinline__ uint64_t desc_mnmajor(uint32_t a) { return make_desc(a, 8192, 1024, SWZ128); }
__device__ __forceinline__ void wait_ge(const void* p, uint32_t target, uint32_t ns = 32) {
  int spin = 0;
  while (ld_acquire_u32(p) < target) { __nanosleep(ns); if (++spin > (1 << 21)) break; }
}
__device__ __forceinline__ void bulk_g2s_hint(uint32_t dst, const void* src, uint32_t bytes, uint32_t mb, uint64_t pol) {
  asm volatile("cp.async.bulk.shared::cluster.global.mbarrier::complete_tx::bytes.L2::cache_hint [%0], [%1], %2, [%3], %4;"
               :: "r"(dst), "l"(src), "r"(bytes), "r"(mb), "l"(pol) : "memory");
}
#ifndef PF_WB
#define PF_WB 2
#endif
#ifndef PF_XN
#define PF_XN 1
#endif
#ifndef ZINIT
#define ZINIT 1
#endif
#ifndef STAG
#define STAG 1
#endif
#ifndef EF_KV
#define EF_KV 1
#endif
#ifndef EF_O
#define EF_O 1
#endif
__device__ __forceinline__ void fence_proxy_async_global() { asm volatile("fence.proxy.async.global;" ::: "memory"); }

namespace tr {
constexpr int NS = 4, STQ = 16384 + 24576, STO = 16384 + 40960;
constexpr int SEGB = 15360;
constexpr int OFF_K = NS * STQ;
constexpr int OFF_BAR = NS * STO;
constexpr int SMEM = OFF_BAR + 256;
static_assert(OFF_K + 4 * SEGB <= OFF_BAR && SMEM <= 232448, "smem");
enum { T_QA = 0, T_Q, T_A, T_OB, T_OS, T_L, T_END, T_P };
constexpr uint32_t C_QA = AR_CNT, C_O = AR_CNT + 64, C_Q = AR_CNT + 128, C_P = AR_CNT + 192;
constexpr int MAXITEMS = 1200;
struct Sched {
  uint8_t ks[16];
  uint8_t wide[16];
  uint8_t lrows[16];
  uint32_t n;
  uint16_t item[MAXITEMS];
};
struct Args {
  const unsigned char *kg, *vg;
  unsigned char* o;
  uint4* qs;
  unsigned char* part;
  const bf16 *xin, *xq;
  bf16 *xout, *xn;
  unsigned char* arena;
  const unsigned* go;
  int tl;
  uint32_t nap, nap2;
  int pfprep;
};
}

template <int N0, int N1>
__device__ __forceinline__ void tr_mainloop(float (&a0)[N0 / 2], float (&a1)[N1 ? N1 / 2 : 1], Pipe& p, uint32_t sb, uint32_t full, uint32_t empty, int nkb, int wg) {
  using namespace tr;
  constexpr uint32_t ST = N1 ? STO : STQ;
  uint32_t prev = 0;
#pragma unroll
  for (int i = 0; i < N0 / 2; i++) { if (ZINIT) a0[i] = 0.f; else asm volatile("" : "=f"(a0[i])); }
  if constexpr (N1 > 0) {
#pragma unroll
    for (int i = 0; i < N1 / 2; i++) a1[i] = 0.f;
  }
#pragma unroll 1
  for (int kb = 0; kb < nkb; kb++) {
    mbar_wait(full + 8 * p.stage, p.phase);
    const uint32_t st = ((sb & 0x3FFFF) >> 4) + p.stage * (ST / 16), sa = st + wg * 512;
    wgmma_fence();
#pragma unroll
    for (int kk = 0; kk < 4; kk++) {
      const uint64_t da = desc16<16, 1024, 1>(sa, kk * 32);
      if constexpr (N0 == 192) wgmma_n192<0, 1>(a0, da, desc16<8192, 1024, 1>(st, 16384 + kk * 2048), (kb | kk) != 0);
      else wgmma_n128<0, 1>(a0, da, desc16<8192, 1024, 1>(st, 16384 + kk * 2048), (kb | kk) != 0);
      if constexpr (N1 > 0) wgmma_n128<0, 1>(a1, da, desc16<8192, 1024, 1>(st, 16384 + 24576 + kk * 2048), (kb | kk) != 0);
    }
    wgmma_commit();
    if (kb > 0) { wgmma_wait<1>(); mbar_arrive_if((threadIdx.x & 127) == 0, empty + 8 * prev); }
    prev = p.stage;
    pipe_adv<NS>(p);
  }
  wgmma_wait<0>();
  mbar_arrive_if((threadIdx.x & 127) == 0, empty + 8 * prev);
}
template <int N> __device__ __forceinline__ void stage_tiles(const float (&o)[N / 2], uint32_t base, int wi, int lane) {
  const uint32_t ra = base + (wi * 16 + (lane & 7) + 8 * ((lane >> 3) & 1)) * 128;
#pragma unroll
  for (int v = 0; v < N / 8; v += 2)
    stsm_x4(ra + (v >> 3) * 8192 + ((((v & 7) + (lane >> 4)) ^ (lane & 7)) << 4), pack_bf16(o[4 * v], o[4 * v + 1]), pack_bf16(o[4 * v + 2], o[4 * v + 3]),
            pack_bf16(o[4 * v + 4], o[4 * v + 5]), pack_bf16(o[4 * v + 6], o[4 * v + 7]));
}
__global__ void __launch_bounds__(384, 1) trail_kernel(const __grid_constant__ CUtensorMap tmX, const __grid_constant__ CUtensorMap tmQ,
                                                       const __grid_constant__ CUtensorMap tmWo5, const __grid_constant__ CUtensorMap tmWo2,
                                                       const __grid_constant__ CUtensorMap tmP, const __grid_constant__ tr::Sched sc,
                                                       const __grid_constant__ tr::Args a, const __grid_constant__ PrepArgs pa) {
  using namespace tr;
  [[maybe_unused]] const int tl = a.tl;
  TL_BEGIN(tl);
  extern __shared__ __align__(1024) unsigned char smem_raw[];
  const uint32_t sb = smem_u32(smem_raw);
  const int warp = __shfl_sync(0xffffffffu, (int)threadIdx.x >> 5, 0), lane = threadIdx.x & 31;
  unsigned char* const arena = a.arena;
  const uint32_t full = sb + OFF_BAR, empty = full + 8 * NS, barK = empty + 8 * NS, barKfree = barK + 16, staged = barKfree + 16;
  const uint32_t kvrdy = staged + 32, mfull = kvrdy + 8, mempty = mfull + 16, mbox = mempty + 16;
  uint32_t go = 0;
  if (threadIdx.x == 256) go = ld_acquire_u32(a.go);
  if (threadIdx.x == 0) {
    for (int i = 0; i < NS; i++) { mbar_init(full + 8 * i, 1); mbar_init(empty + 8 * i, 2); }
    for (int i = 0; i < 2; i++) {
      mbar_init(barK + 8 * i, 1); mbar_init(barKfree + 8 * i, 1); mbar_init(staged + 16 * i, 4); mbar_init(staged + 16 * i + 8, 4);
      mbar_init(mfull + 8 * i, 1); mbar_init(mempty + 8 * i, 11);
    }
    mbar_init(kvrdy, 1);
    asm volatile("fence.mbarrier_init.release.cluster;" ::: "memory");
  }
  __syncthreads();
  Pipe mp{0, 0};
  auto next_item = [&]() -> uint32_t {
    uint32_t it;
    mbar_wait(mfull + 8 * mp.stage, mp.phase);
    asm volatile("ld.shared.u32 %0, [%1];" : "=r"(it) : "r"(mbox + 4 * mp.stage) : "memory");
    return it;
  };
  if (warp >= 8) {
    asm volatile("setmaxnreg.dec.sync.aligned.u32 40;");
    if (warp == 8) { go = __shfl_sync(0xffffffffu, go, 0); if (elect_one()) {
      Pipe p{0, 1};
      mp.phase = 1;
      uint32_t kph = 1, rph = 0, wide = 0, qdone = 0;
      prefetch_tmap(&tmX); prefetch_tmap(&tmQ); prefetch_tmap(&tmWo5); prefetch_tmap(&tmWo2); prefetch_tmap(&tmP);
      const uint64_t ef = policy_evict_first();
      auto ld_kv = [&](uint32_t d, const void* s, uint32_t n, uint32_t mb) { if (EF_KV) bulk_g2s_hint(d, s, n, mb, ef); else bulk_g2s(d, s, n, mb); };
      auto ld_o = [&](uint32_t d, const void* s, uint32_t n, uint32_t mb) { if (EF_O) bulk_g2s_hint(d, s, n, mb, ef); else bulk_g2s(d, s, n, mb); };
      auto stage = [&](uint32_t bytes) -> uint32_t {
        mbar_wait(empty + 8 * p.stage, p.phase);
        mbar_expect_tx(full + 8 * p.stage, bytes);
        return sb + p.stage * (wide ? STO : STQ);
      };
      auto fetch = [&]() -> uint32_t { uint32_t v; asm volatile("atom.relaxed.gpu.global.add.u32 %0, [%1], 1;" : "=r"(v) : "l"(arena + AR_QUEUE) : "memory"); return v; };
      if (!go) wait_ge(a.go, 1, 200);
      fence_proxy_async_global();
      uint32_t next = fetch();
      while (true) {
        const uint32_t item = next;
        const uint32_t code = sc.item[min(item, sc.n)];
        const int type = (code >> 11) & 7, m = (code >> 7) & 15, k = code & 127;
        const bool late = code >> 14;
        auto done_wait = [&]() { mbar_wait(mempty + 8 * (mp.stage ^ 1), mp.stage ? mp.phase ^ 1 : mp.phase); };
        if (type == T_A && !((qdone >> m) & 1)) { wait_ge(arena + C_Q + m * 4, 64); qdone |= 1u << m; }
        if (type == T_OB && !wide) for (uint32_t i = 0; i < NS; i++) mbar_wait(empty + 8 * i, i >= p.stage ? p.phase : p.phase ^ 1);
        wide = type == T_OB;
        mbar_wait(mempty + 8 * mp.stage, mp.phase);
        asm volatile("st.shared.u32 [%0], %1;" :: "r"(mbox + 4 * mp.stage), "r"((p.stage << 24) | (type << 16) | (m << 8) | (k & 255)) : "memory");
        mbar_arrive(mfull + 8 * mp.stage);
        pipe_adv<2>(mp);
        if (type == T_END) break;
        if (type == T_P) { done_wait(); next = fetch(); continue; }
        if (type == T_L) {
          const int nr = sc.lrows[m], np = sc.ks[m];
          prefetch_l2(a.xin + (size_t)(m * 128 + k * 8 * nr) * cfg::DM, nr * 10240);
          wait_ge(arena + C_O + m * 4, np * (sc.wide[m] ? 4 : 10), m < 13 ? a.nap : 32);
          fence_proxy_async_global();
#pragma unroll 1
          for (int r = 0; r < nr; r++) {
            const int rg = m * 16 + k * nr + r;
#pragma unroll 1
            for (int q0 = 0; q0 <= np; q0 += 4) {
              const int n = min(4, np + 1 - q0);
              const uint32_t st = stage(n * 10240), fb = full + 8 * p.stage;
#pragma unroll 1
              for (int q = q0; q < q0 + n; q++) {
                if (q == 0) bulk_g2s(st, a.xin + (size_t)rg * 8 * cfg::DM, 10240, fb);
                else tma_load_3d(st + (q - q0) * 10240, &tmP, 0, rg & 7, ((q - 1) * 32 + (rg >> 3)) * 10, fb);
              }
              pipe_adv<NS>(p);
            }
          }
          if (late) done_wait();
          next = fetch(); continue;
        }
        if (type <= T_A) {
          if (type != T_A)
#pragma unroll 1
            for (int kb = 0; kb < 10; kb++) {
              const uint32_t st = stage(STQ), fb = full + 8 * p.stage;
              tma_load_2d(st, &tmX, kb * 64, m * 128, fb);
              tma_load_3d(st + 16384, &tmQ, 0, kb * 64, k * 3, fb);
              pipe_adv<NS>(p);
              if (type == T_Q && kb == 8) next = fetch();
            }
          if (type != T_Q) {
            const size_t blk = ((size_t)m * 4 * 96 + k * 3) * 5120;
            kph ^= 1;
            mbar_wait(kvrdy, rph); rph ^= 1;
            if (!late) next = fetch();
            fence_proxy_async_global();
#pragma unroll 1
            for (int w = type == T_A ? 0 : 2; w < 4; w++) {
              const uint32_t st = stage(2 * SEGB), fb = full + 8 * p.stage;
              for (int sg = 0; sg < 2; sg++) ld_kv(st + sg * SEGB, (w < 2 ? a.kg : a.vg) + blk + (size_t)(2 * (w & 1) + sg) * (96 * 5120), SEGB, fb);
              pipe_adv<NS>(p);
            }
            if (late) { done_wait(); next = fetch(); }
          }
        } else {
          const int nn = wide ? 2 : 5, nb = wide ? 5 : 2, nt = k % nn, nkb = 96 / sc.ks[m], k0 = (k / nn) * nkb;
          const Pipe p0 = p;
          for (int kb = 0; kb < nkb; kb++) {
            if (wide && kb < NS && p.stage >= 2) { mbar_wait(barKfree, kph); mbar_wait(barKfree + 8, kph); }
            const uint32_t st = stage(16384 + nb * 8192), fb = full + 8 * p.stage;
            tma_load_3d(st + 16384, wide ? &tmWo5 : &tmWo2, 0, (k0 + kb) * 64, nt * nb, fb);
            if (kb >= NS) ld_o(st, a.o + ((size_t)m * 96 + k0 + kb) * 16384, 16384, fb);
            pipe_adv<NS>(p);
            if (kb == NS - 1 || (kb == nkb - 1 && nkb < NS)) {
              wait_ge(arena + C_QA + m * 4, 64, m < 14 ? a.nap : 32);
              fence_proxy_async_global();
              Pipe q = p0;
#pragma unroll 1
              for (int i = 0; i <= kb; i++) { ld_o(sb + q.stage * (wide ? STO : STQ), a.o + ((size_t)m * 96 + k0 + i) * 16384, 16384, full + 8 * q.stage); pipe_adv<NS>(q); }
            }
          }
          if (!late) next = fetch();
          for (int w = wide ? -(int)((2 - p.stage) & 3) : 0; w < 2; w++) { mbar_wait(empty + 8 * p.stage, p.phase); mbar_arrive(full + 8 * p.stage); pipe_adv<NS>(p); }
          kph ^= wide;
          if (late) { done_wait(); next = fetch(); }
        }
      }
    } } else if (warp < 11) { if (elect_one()) {
      const int w = warp - 9;
      uint32_t sph = 0;
      [[maybe_unused]] int nlog = 0;
#ifdef TIMELINE
      if (w == 0) { unsigned long long* lg = g_log + (((tl >= 12) * 132 + blockIdx.x) * 64 + nlog++) * 2; lg[0] = T_END << 16; lg[1] = gtime(); lg[2] = ~0ull; }
#endif
      while (true) {
        const uint32_t it = next_item();
        const int type = (it >> 16) & 255, m = (it >> 8) & 255, k = it & 255;
        const uint32_t slot = mp.stage;
        pipe_adv<2>(mp);
        if (type == T_END) break;
        mbar_wait(staged + 16 * w + 8 * slot, (sph >> slot) & 1); sph ^= 1u << slot;
        mbar_arrive(mempty + 8 * slot);
#ifdef TIMELINE
        if (w == 0 && nlog < 63) { unsigned long long* lg = g_log + (((tl >= 12) * 132 + blockIdx.x) * 64 + nlog++) * 2; lg[0] = (type << 16) | (m << 8) | k; lg[1] = gtime(); lg[2] = ~0ull; }
#endif
        if (type == T_L) continue;
        if (type == T_QA || type == T_A) {
          for (int jj = 0; jj < 3; jj++) bulk_s2g(a.o + ((size_t)m * 96 + k * 3 + jj) * 16384 + w * 8192, sb + OFF_K + w * 2 * SEGB + jj * 8192, 8192);
          bulk_commit();
          bulk_wait<0>();
          mbar_arrive(barKfree + 8 * w);
        } else if (type == T_OB || type == T_OS) {
          const bool wide = type == T_OB;
          const int nn = wide ? 2 : 5, nb = wide ? 5 : 2;
          const uint32_t own = wide ? 2 + w : ((it >> 24) + 96 / sc.ks[m] + w) % NS;
          bulk_s2g(a.part + ((size_t)((k / nn) * 32 + m * 2 + w) * 10 + (k % nn) * nb) * 8192, sb + own * (wide ? STO : STQ), nb * 8192);
          bulk_commit();
          bulk_wait<0>();
          mbar_arrive(empty + 8 * own);
          if (wide && w) { mbar_arrive(barKfree); mbar_arrive(barKfree + 8); }
        }
        red_release_inc(arena + (type == T_Q ? C_Q : (type <= T_A ? C_QA : (type == T_P ? C_P : C_O))) + m * 4);
      }
    } } else if (elect_one()) {
      const uint64_t ef = policy_evict_first();
      uint32_t kph = 1;
      if (PF_WB && blockIdx.x >= 52) { prefetch_l2(pa.wb + (blockIdx.x - 52) * 32768, 32768); prefetch_l2(pa.wot + (blockIdx.x - 52) * 10240, 10240); }
      if (PF_WB > 1 && blockIdx.x >= 52) { prefetch_l2(a.xn + (blockIdx.x - 52) * 8192, 16384); prefetch_l2(a.xout + (blockIdx.x - 52) * 8192, 16384); }
      while (true) {
        const uint32_t it = next_item();
        const int type = (it >> 16) & 255, m = (it >> 8) & 255, k = it & 255;
        const uint32_t slot = mp.stage;
        pipe_adv<2>(mp);
        if (type == T_END) break;
        if (a.pfprep && type == T_QA && m == 0) { prefetch_l2(pa.wqkv + k * 38400, 76800); prefetch_l2(pa.wo + k * 12800, 25600); }
        if (PF_XN && type == T_QA && m < 15) prefetch_l2(a.xq + ((m + 1) * 128 + k * 4) * cfg::DM, 5120);
        if (type == T_QA || type == T_A) {
          for (int spin = 0; spin < (1 << 21); spin++) {
            uint4 f;
            asm volatile("ld.acquire.gpu.global.v4.u32 {%0,%1,%2,%3}, [%4];" : "=r"(f.x), "=r"(f.y), "=r"(f.z), "=r"(f.w) : "l"(arena + prog_off(k, 0)) : "memory");
            if (min(min(f.x, f.y), f.z) >= (uint32_t)(4 * m + 4)) break;
            __nanosleep(m < 15 ? a.nap : a.nap2);
          }
          mbar_arrive(kvrdy);
          fence_proxy_async_global();
          const unsigned char* src = a.kg + ((size_t)m * 4 * 96 + k * 3) * 5120;
#pragma unroll 1
          for (int w = 0; w < 2; w++) {
            mbar_wait(barKfree + 8 * w, kph);
            if (type == T_A) { mbar_arrive(barK + 8 * w); continue; }
            mbar_expect_tx(barK + 8 * w, 2 * SEGB);
            for (int sg = 2 * w; sg < 2 * w + 2; sg++) { if (EF_KV) bulk_g2s_hint(sb + OFF_K + sg * SEGB, src + (size_t)sg * (96 * 5120), SEGB, barK + 8 * w, ef); else bulk_g2s(sb + OFF_K + sg * SEGB, src + (size_t)sg * (96 * 5120), SEGB, barK + 8 * w); }
          }
          kph ^= 1;
        } else if (type == T_OB) {
          mbar_wait(barKfree, kph); mbar_wait(barKfree + 8, kph);
          kph ^= 1;
        }
        mbar_arrive(mempty + 8 * slot);
      }
      if (blockIdx.x == gridDim.x - 1) asm volatile("griddepcontrol.wait;" ::: "memory");
    }
    return;
  }
  asm volatile("setmaxnreg.inc.sync.aligned.u32 232;");
  const int wg = warp >> 2, wi = warp & 3;
  const int g = lane >> 2, q4 = lane & 3;
  asm volatile("griddepcontrol.launch_dependents;" ::: "memory");
  Pipe p{0, 0};
  uint32_t kph = 0;
  auto own_slot = [&]() -> uint32_t {
    const uint32_t sA = p.stage, phA = p.phase; pipe_adv<NS>(p);
    const uint32_t sB = p.stage, phB = p.phase; pipe_adv<NS>(p);
    mbar_wait_if(wi == 0, full + 8 * (wg ? sA : sB), wg ? phA : phB);
    mbar_wait(full + 8 * (wg ? sB : sA), wg ? phB : phA);
    mbar_arrive_if((threadIdx.x & 127) == 0, empty + 8 * (wg ? sA : sB));
    return wg ? sB : sA;
  };
  while (true) {
    const uint32_t it = __shfl_sync(0xffffffffu, next_item(), 0);
    const int type = (it >> 16) & 255, m = (it >> 8) & 255, k = it & 255;
    mbar_arrive_if(lane == 0, mempty + 8 * mp.stage);
    const uint32_t done = staged + 16 * wg + 8 * mp.stage;
    pipe_adv<2>(mp);
    if (type == T_END) break;
    if (type == T_P) {
      prep_body(k, pa);
      bar_sync(3 + wg, 128);
      mbar_arrive_if(lane == 0, done);
      continue;
    }
    if (type == T_L) {
      const int nr = sc.lrows[m], np = sc.ks[m];
      const uint32_t po = (lane >> 4) * 1024 + warp * 128 + ((((lane >> 1) & 7) ^ warp) << 4) + (lane & 1) * 8;
#pragma unroll 1
      for (int r = 0; r < nr; r++) {
        uint2 xw[1][5]; float s[20];
#pragma unroll
        for (int i = 0; i < 20; i++) s[i] = 0.f;
#pragma unroll 1
        for (int q0 = 0; q0 <= np; q0 += 4) {
          const uint32_t st = sb + p.stage * STQ;
          mbar_wait(full + 8 * p.stage, p.phase);
          if (q0 == 0) static_for<0, 5>([&](auto I) { xw[0][I.value] = lds64_i<I.value * 256>(st + warp * 1280 + lane * 8); });
#pragma unroll 1
          for (int q = q0 ? 0 : 1; q < min(4, np + 1 - q0); q++)
            static_for<0, 5>([&](auto I) {
              constexpr int i = I.value;
              const uint2 t = lds64_i<i * 2048>(st + q * 10240 + po);
              s[4 * i] += bf_lo(t.x); s[4 * i + 1] += bf_hi(t.x); s[4 * i + 2] += bf_lo(t.y); s[4 * i + 3] += bf_hi(t.y);
            });
          bar_sync(3 + wg, 128);
          mbar_arrive_if((threadIdx.x & 127) == 0, empty + 8 * p.stage);
          pipe_adv<NS>(p);
        }
        const int row = (m * 16 + k * nr + r) * 8 + warp;
#pragma unroll
        for (int i = 0; i < 5; i++) {
          bf16r2(s[4 * i], s[4 * i + 1]); bf16r2(s[4 * i + 2], s[4 * i + 3]);
          xw[0][i] = make_uint2(pack_bf16(bf_lo(xw[0][i].x) + s[4 * i], bf_hi(xw[0][i].x) + s[4 * i + 1]), pack_bf16(bf_lo(xw[0][i].y) + s[4 * i + 2], bf_hi(xw[0][i].y) + s[4 * i + 3]));
          *(uint2*)(a.xout + (size_t)row * cfg::DM + i * 128 + lane * 4) = xw[0][i];
        }
        ln_rows<1>(xw, row, lane, a.xn, nullptr);
      }
      __syncwarp();
      mbar_arrive_if(lane == 0, done);
      continue;
    }
    if (type >= T_OB) {
      const int nkb = 96 / sc.ks[m];
      if (type == T_OB) {
        float a0[96], a1[64];
        tr_mainloop<192, 128>(a0, a1, p, sb, full, empty, nkb, wg);
        while (p.stage != 2) { mbar_wait_if(wi == 0, full + 8 * p.stage, p.phase); mbar_arrive_if((threadIdx.x & 127) == 0, empty + 8 * p.stage); pipe_adv<NS>(p); }
        const uint32_t st = sb + own_slot() * STO;
        stage_tiles<192>(a0, st, wi, lane); stage_tiles<128>(a1, st + 24576, wi, lane);
      } else {
        float a0[64], a1[1];
        tr_mainloop<128, 0>(a0, a1, p, sb, full, empty, nkb, wg);
        stage_tiles<128>(a0, sb + own_slot() * STQ, wi, lane);
      }
      fence_proxy_async();
      __syncwarp();
      mbar_arrive_if(lane == 0, done);
      continue;
    }
    uint32_t qf[12][4];
    uint4* qp = a.qs + ((size_t)((m & 7) * 32 + k) * 12) * 256 + threadIdx.x;
    if (type != T_A) {
      float acc[96], a1[1];
      tr_mainloop<192, 0>(acc, a1, p, sb, full, empty, 10, wg);
#pragma unroll
      for (int i = 0; i < 12; i++) {
        qf[i][0] = pack_bf16(acc[8 * i], acc[8 * i + 1]); qf[i][1] = pack_bf16(acc[8 * i + 2], acc[8 * i + 3]);
        qf[i][2] = pack_bf16(acc[8 * i + 4], acc[8 * i + 5]); qf[i][3] = pack_bf16(acc[8 * i + 6], acc[8 * i + 7]);
      }
      if (type == T_Q) {
#pragma unroll
        for (int i = 0; i < 12; i++) qp[i * 256] = make_uint4(qf[i][0], qf[i][1], qf[i][2], qf[i][3]);
        __syncwarp();
        mbar_arrive_if(lane == 0, done);
        continue;
      }
    } else {
#pragma unroll
      for (int i = 0; i < 12; i++) { const uint4 v = __ldcg(qp + i * 256); qf[i][0] = v.x; qf[i][1] = v.y; qf[i][2] = v.z; qf[i][3] = v.w; }
    }
    const uint32_t ost = sb + OFF_K + wg * 2 * SEGB;
    const bool second = wi >= 2;
    uint32_t pf[5][4];
    {
      float sa[20], sb2[20];
      uint32_t kbase = ost, kslot = 0;
      if (type == T_A) { kslot = own_slot(); kbase = sb + kslot * STQ; } else mbar_wait(barK + 8 * wg, kph);
      kbase = (kbase & 0x3FFFF) >> 4;
      if (STAG && wg) bar_sync(1, 256);
      wgmma_fence();
#pragma unroll
      for (int i = 0; i < 12; i++) {
        wgmma_rs_n40<0>(sa, qf[i][0], qf[i][1], qf[i][2], qf[i][3], desc16<640, 128, 0>(kbase, i * 1280), i != 0);
        wgmma_rs_n40<0>(sb2, qf[i][0], qf[i][1], qf[i][2], qf[i][3], desc16<640, 128, 0>(kbase, SEGB + i * 1280), i != 0);
      }
      wgmma_commit();
      if (STAG && !wg) bar_arrive(1, 256);
      wgmma_wait<0>();
      mbar_arrive_if(type == T_A && (threadIdx.x & 127) == 0, empty + 8 * kslot);
      const float cs = 0.07216878364870322f * 1.4426950408889634f;
      const int r0 = 16 * (wi & 1) + g, r1 = r0 + 8;
      float m0 = -INFINITY, m1 = -INFINITY;
#pragma unroll
      for (int n = 0; n < 5; n++) {
#pragma unroll
        for (int e = 0; e < 2; e++) {
          const int key = 8 * n + 2 * q4 + e;
          float x = second ? sb2[4 * n + e] : sa[4 * n + e], y = second ? sb2[4 * n + 2 + e] : sa[4 * n + 2 + e];
          if (n < 4) { if (key > r0) x = -INFINITY; if (key > r1) y = -INFINITY; }
          sa[4 * n + e] = x; sa[4 * n + 2 + e] = y;
          m0 = fmaxf(m0, x); m1 = fmaxf(m1, y);
        }
      }
      m0 = fmaxf(fmaxf(m0, __shfl_xor_sync(0xffffffffu, m0, 1)), fmaxf(__shfl_xor_sync(0xffffffffu, m0, 2), __shfl_xor_sync(0xffffffffu, m0, 3)));
      m1 = fmaxf(fmaxf(m1, __shfl_xor_sync(0xffffffffu, m1, 1)), fmaxf(__shfl_xor_sync(0xffffffffu, m1, 2), __shfl_xor_sync(0xffffffffu, m1, 3)));
      m0 *= -cs; m1 *= -cs;
      float s0 = 0.f, s1 = 0.f;
#pragma unroll
      for (int n = 0; n < 5; n++) {
#pragma unroll
        for (int e = 0; e < 2; e++) {
          sa[4 * n + e] = ex2f(fmaf(sa[4 * n + e], cs, m0)); sa[4 * n + 2 + e] = ex2f(fmaf(sa[4 * n + 2 + e], cs, m1));
          s0 += sa[4 * n + e]; s1 += sa[4 * n + 2 + e];
        }
      }
      s0 = (s0 + __shfl_xor_sync(0xffffffffu, s0, 1)) + (__shfl_xor_sync(0xffffffffu, s0, 2) + __shfl_xor_sync(0xffffffffu, s0, 3));
      s1 = (s1 + __shfl_xor_sync(0xffffffffu, s1, 1)) + (__shfl_xor_sync(0xffffffffu, s1, 2) + __shfl_xor_sync(0xffffffffu, s1, 3));
      const float i0 = rcpf(s0), i1 = rcpf(s1);
#pragma unroll
      for (int n = 0; n < 5; n++) {
        const uint32_t x = pack_bf16(sa[4 * n] * i0, sa[4 * n + 1] * i0), y = pack_bf16(sa[4 * n + 2] * i1, sa[4 * n + 3] * i1);
        if (n < 4) {
          pf[n >> 1][2 * (n & 1)] = second ? 0u : x; pf[n >> 1][2 * (n & 1) + 1] = second ? 0u : y;
          pf[2 + (n >> 1)][2 * (n & 1)] = second ? x : 0u; pf[2 + (n >> 1)][2 * (n & 1) + 1] = second ? y : 0u;
        } else {
          pf[4][0] = second ? 0u : x; pf[4][1] = second ? 0u : y; pf[4][2] = second ? x : 0u; pf[4][3] = second ? y : 0u;
        }
      }
    }
    {
      float o[96];
#pragma unroll
      for (int i = 0; i < 5; i++) { PIN(pf[i][0]); PIN(pf[i][1]); PIN(pf[i][2]); PIN(pf[i][3]); }
      const uint32_t own = own_slot(), vbase = ((sb & 0x3FFFF) >> 4) + own * (STQ / 16);
      wgmma_fence();
#pragma unroll
      for (int i = 0; i < 5; i++)
        wgmma_rs_n192<1>(o, pf[i][0], pf[i][1], pf[i][2], pf[i][3], i < 4 ? desc16<128, 640, 0>(vbase, (i >> 1) * SEGB + (i & 1) * 256) : desc16<SEGB, 640, 0>(vbase, 512), i != 0);
      wgmma_commit();
      if (type == T_A) mbar_wait(barK + 8 * wg, kph);
      kph ^= 1;
      wgmma_wait<0>();
      mbar_arrive_if((threadIdx.x & 127) == 0, empty + 8 * own);
      stage_tiles<192>(o, ost, wi, lane);
      fence_proxy_async();
      __syncwarp();
      mbar_arrive_if(lane == 0, done);
    }
  }
}
namespace bf {
constexpr int NS = 4, STAGE = 16384 + 32768;
constexpr int PIECE = 20480;
constexpr int OFF_PHI = 0, OFF_V = 40960, OFF_KV = 65536;
constexpr int OFF_OST = 5 * PIECE;
constexpr int OFF_WOT = 6 * PIECE;
constexpr int OFF_BAR = OFF_WOT + 102400;
constexpr int SMEM = OFF_BAR + 256;
static_assert(NS * STAGE <= OFF_BAR && SMEM <= 232448, "smem");
constexpr int KVACC = 32 * 5 * 1024;
struct Args {
  const unsigned char *wb, *wot;
  unsigned char *kvacc, *o2;
  const bf16* xin;
  bf16* xout;
  unsigned* go;
  const void* prep;
  const bf16 *pf0, *pf1;
  int pfn, pfns, pfwait;
  int tl;
};
}
__device__ __forceinline__ void hedgehog_features(float (&x)[2][5], uint32_t (&w)[2][5]) {
  const float L = 1.4426950408889634f;
  float mx[2], mn[2], sp[2], sn[2], pos[2][5], neg[2][5];
#pragma unroll
  for (int r = 0; r < 2; r++) {
    mx[r] = fmaxf(fmaxf(fmaxf(x[r][0], x[r][1]), fmaxf(x[r][2], x[r][3])), x[r][4]);
    mn[r] = fminf(fminf(fminf(x[r][0], x[r][1]), fminf(x[r][2], x[r][3])), x[r][4]);
  }
#pragma unroll
  for (int o = 1; o < 4; o <<= 1)
#pragma unroll
    for (int r = 0; r < 2; r++) {
      const uint32_t t = __shfl_xor_sync(0xffffffffu, __byte_perm(__float_as_uint(mn[r]), __float_as_uint(mx[r]), 0x7632), o);
      mx[r] = fmaxf(mx[r], bf_hi(t)); mn[r] = fminf(mn[r], bf_lo(t));
    }
#pragma unroll
  for (int r = 0; r < 2; r++) {
#pragma unroll
    for (int i = 0; i < 5; i++) { pos[r][i] = ex2f((x[r][i] - mx[r]) * L); neg[r][i] = ex2f((mn[r] - x[r][i]) * L); }
    sp[r] = ((pos[r][0] + pos[r][1]) + (pos[r][2] + pos[r][3])) + pos[r][4];
    sn[r] = ((neg[r][0] + neg[r][1]) + (neg[r][2] + neg[r][3])) + neg[r][4];
  }
#pragma unroll
  for (int o = 1; o < 4; o <<= 1)
#pragma unroll
    for (int r = 0; r < 2; r++) { sp[r] += __shfl_xor_sync(0xffffffffu, sp[r], o); sn[r] += __shfl_xor_sync(0xffffffffu, sn[r], o); }
#pragma unroll
  for (int r = 0; r < 2; r++) {
    const float ip = rcpf(sp[r]), in_ = rcpf(sn[r]);
    w[r][0] = pack_bf16(pos[r][0] * ip, pos[r][1] * ip); w[r][1] = pack_bf16(pos[r][2] * ip, pos[r][3] * ip);
    w[r][2] = pack_bf16(neg[r][0] * in_, neg[r][1] * in_); w[r][3] = pack_bf16(neg[r][2] * in_, neg[r][3] * in_);
    w[r][4] = pack_bf16(pos[r][4] * ip, neg[r][4] * in_);
  }
}
__device__ __forceinline__ void bulk_g2s_mc(uint32_t dst, const void* src, uint32_t bytes, uint32_t mb) {
  asm volatile("cp.async.bulk.shared::cluster.global.mbarrier::complete_tx::bytes.multicast::cluster [%0], [%1], %2, [%3], %4;"
               :: "r"(dst), "l"(src), "r"(bytes), "r"(mb), "h"((unsigned short)3) : "memory");
}
__device__ __forceinline__ void mbar_arrive_remote_if(bool c, uint32_t b) {
  asm volatile("{\n.reg .pred p;\nsetp.ne.u32 p, %1, 0;\n@p mbarrier.arrive.shared::cluster.b64 _, [%0];\n}" :: "r"(b), "r"((uint32_t)c) : "memory");
}

__global__ void __cluster_dims__(2, 1, 1) __launch_bounds__(384, 1) blayer_kernel(const __grid_constant__ CUtensorMap tmA, const __grid_constant__ bf::Args a) {
  using namespace bf;
  [[maybe_unused]] const int tl = a.tl;
  extern __shared__ __align__(1024) unsigned char smem_raw[];
  const uint32_t sb = smem_u32(smem_raw);
  const int warp = __shfl_sync(0xffffffffu, (int)threadIdx.x >> 5, 0), lane = threadIdx.x & 31;
  const uint32_t full = sb + OFF_BAR, empty = full + 8 * NS, full2 = empty + 8 * NS, empty2 = full2 + 64, barW = empty2 + 16, drained = barW + 8, staged = drained + 8, freeb = staged + 8;
  const int rank = blockIdx.x & 1, u = (blockIdx.x >> 1) & 7, mp = blockIdx.x >> 4;
  const int m = 2 * mp + rank;
  const int m2 = 2 * mp + (u & 1), ns = (u & ~1) + rank;
  const uint32_t dpeer = mapa_u32(sb, rank ^ 1) - sb;
  unsigned* cntO = (unsigned*)(a.kvacc + KVACC);
  if (threadIdx.x == 0) {
    for (int i = 0; i < NS; i++) { mbar_init(full + 8 * i, 1); mbar_init(empty + 8 * i, 4); }
    for (int i = 0; i < 8; i++) mbar_init(full2 + 8 * i, 1);
    mbar_init(empty2, 2); mbar_init(empty2 + 8, 2);
    mbar_init(barW, 1); mbar_init(drained, 1); mbar_init(staged, 8); mbar_init(freeb, 2);
    asm volatile("fence.mbarrier_init.release.cluster;" ::: "memory");
  }
  __syncthreads();
  asm volatile("barrier.cluster.arrive.relaxed.aligned; barrier.cluster.wait.aligned;" ::: "memory");
  if (warp >= 8) {
    asm volatile("setmaxnreg.dec.sync.aligned.u32 40;");
    if (warp == 8) { if (elect_one()) {
      const unsigned char* wsrc = a.wb + (size_t)u * 327680 + rank * 16384;
      if (a.prep) wait_ge(a.prep, 64);
      fence_proxy_async_global();
      for (int kb = 0; kb < NS; kb++) {
        mbar_expect_tx(full + 8 * kb, STAGE);
        bulk_g2s_mc(sb + kb * STAGE + 16384 + rank * 16384, wsrc + kb * 32768, 16384, full + 8 * kb);
      }
      asm volatile("griddepcontrol.wait;" ::: "memory");
      TL_BEGIN0(tl);
      if (blockIdx.x == 0) *a.go = 0;
      for (int kb = 0; kb < NS; kb++) tma_load_2d(sb + kb * STAGE, &tmA, kb * 64, m * 128, full + 8 * kb);
      if (m == 0) prefetch_l2(a.kvacc + u * (KVACC / 8), KVACC / 8);
#pragma unroll 1
      for (int kb = NS; kb < 10; kb++) {
        const uint32_t s = kb & 3, st = sb + s * STAGE, fb = full + 8 * s;
        mbar_wait(empty + 8 * s, ((kb >> 2) - 1) & 1);
        mbar_expect_tx(fb, STAGE);
        tma_load_2d(st, &tmA, kb * 64, m * 128, fb);
        bulk_g2s_mc(st + 16384 + rank * 16384, wsrc + kb * 32768, 16384, fb);
      }
      for (int i = 0; i < 6; i++) mbar_expect_tx(full2 + 8 * i, PIECE);
      mbar_wait(drained, 0);
      mbar_expect_tx(barW, 102400);
      bulk_g2s(sb + OFF_WOT, a.wot + (size_t)ns * 102400, 102400, barW);
      mbar_wait(staged, 0);
      bulk_s2g(a.o2 + (size_t)(m * 8 + u) * PIECE, sb + OFF_OST, PIECE);
      bulk_commit();
      bulk_wait<0>();
      mbar_arrive(freeb); mbar_arrive_remote_if(true, freeb + dpeer);
      red_release_inc(cntO + m);
      wait_ge(cntO + m2, 8, 20);
      mbar_wait(freeb, 0);
      fence_proxy_async_global();
      const unsigned char* osrc = a.o2 + (size_t)m2 * 8 * PIECE;
      for (int i = 0; i < 6; i++) bulk_g2s_mc(sb + i * PIECE + rank * (PIECE / 2), osrc + i * PIECE + rank * (PIECE / 2), PIECE / 2, full2 + 8 * i);
      for (int i = 0; i < 2; i++) {
        mbar_wait(empty2 + 8 * i, 0);
        mbar_expect_tx(full2 + 8 * (6 + i), PIECE);
        bulk_g2s(sb + i * PIECE, osrc + (6 + i) * PIECE, PIECE, full2 + 8 * (6 + i));
      }
    } } else if (warp == 9 && a.pf0) { if (elect_one()) {
      if (a.pfwait) asm volatile("griddepcontrol.wait;" ::: "memory");
      constexpr uint32_t CH = 2048;
      for (int i = 0; i < a.pfn; i++) {
        prefetch_l2((const unsigned char*)a.pf0 + (i * 128 + blockIdx.x) * CH, CH); prefetch_l2((const unsigned char*)a.pf1 + (i * 128 + blockIdx.x) * CH, CH);
        __nanosleep(a.pfns);
      }
    } }
    return;
  }
  asm volatile("setmaxnreg.inc.sync.aligned.u32 232;");
  const int wg = warp >> 2, wi = warp & 3;
  const int q4 = lane & 3;
  const bool lead = (threadIdx.x & 127) == 0;
  const uint32_t s16 = (sb & 0x3FFFF) >> 4;
  float acc[128];
  {
#pragma unroll 1
    for (int kb = 0; kb < 10; kb++) {
      const uint32_t s = kb & 3, st = s16 + s * (STAGE / 16);
      mbar_wait(full + 8 * s, (kb >> 2) & 1);
      wgmma_fence();
#pragma unroll
      for (int kk = 0; kk < 4; kk++) wgmma_n256<0, 1>(acc, desc16<16, 1024, 1>(st + wg * 512, kk * 32), desc16<4096, 128, 0>(st, 16384 + kk * 8192), (kb | kk) != 0);
      wgmma_commit();
      if (kb > 0 && kb < 7) { wgmma_wait<1>(); const uint32_t e = empty + 8 * ((kb - 1) & 3); mbar_arrive_if(lead, e); mbar_arrive_remote_if(lead, e + dpeer); }
    }
    wgmma_wait<0>();
    bar_sync(1, 256);
    mbar_arrive_if(threadIdx.x == 0, drained);
  }
  TL2((tl >= 12 ? 128 : 0) + 32 + 0);
  const uint32_t srow = (wg * 64 + wi * 16 + (lane & 15)) * 16 + (lane >> 4) * 2048;
  auto features = [&](auto T0, auto HH, uint32_t (&w)[2][5]) {
    constexpr int t = T0.value + 5 * (HH.value >> 1), o = (HH.value & 1) ? 3 : 0, e = HH.value & 1;
    float x[2][5];
#pragma unroll
    for (int r = 0; r < 2; r++) {
      x[r][0] = acc[4 * (t + o) + 2 * r]; x[r][1] = acc[4 * (t + o) + 2 * r + 1]; x[r][2] = acc[4 * (t + o + 1) + 2 * r]; x[r][3] = acc[4 * (t + o + 1) + 2 * r + 1];
      bf16r2(x[r][0], x[r][1]); bf16r2(x[r][2], x[r][3]);
    }
    x[0][4] = acc[4 * (t + 2) + e]; x[1][4] = acc[4 * (t + 2) + 2 + e];
    bf16r2(x[0][4], x[1][4]);
    hedgehog_features(x, w);
  };
  static_for<0, 4>([&](auto HH) {
    constexpr int hh = HH.value, t = 20 + 3 * hh;
    const uint32_t one = q4 == ((hh & 1) ? 0 : 2) ? 0x3f80u : 0u;
    const uint32_t va = sb + OFF_V + hh * 6144 + srow;
    stsm_x4(va, pack_bf16(acc[4 * t], acc[4 * t + 1]), pack_bf16(acc[4 * t + 2], acc[4 * t + 3]), pack_bf16(acc[4 * t + 4], acc[4 * t + 5]), pack_bf16(acc[4 * t + 6], acc[4 * t + 7]));
    const bool pad = (q4 >= 2) != (hh & 1);
    stsm_x2(va + 4096, pad ? one : pack_bf16(acc[4 * t + 8], acc[4 * t + 9]), pad ? one : pack_bf16(acc[4 * t + 10], acc[4 * t + 11]));
    uint32_t w[2][5];
    features(IC<10>{}, HH, w);
    const uint32_t pa = sb + OFF_PHI + hh * 10240 + srow;
    stsm_x4(pa, w[0][0], w[1][0], w[0][1], w[1][1]);
    stsm_x4(pa + 4096, w[0][2], w[1][2], w[0][3], w[1][3]);
    stsm_x2(pa + 8192, w[0][4], w[1][4]);
  });
  fence_proxy_async();
  bar_sync(1, 256);
  TL2((tl >= 12 ? 128 : 0) + 32 + 1);
  {
    float d0[12], d1[12];
    const uint32_t pa = s16 + wg * 1280, pv = s16 + wg * 768;
    wgmma_fence();
#pragma unroll
    for (int k = 0; k < 8; k++) {
      wgmma_n24<1, 1>(d0, desc16<128, 2048, 0>(pa, OFF_PHI + k * 256), desc16<128, 2048, 0>(pv, OFF_V + k * 256), k != 0);
      wgmma_n24<1, 1>(d1, desc16<128, 2048, 0>(pa, OFF_PHI + 10240 + k * 256), desc16<128, 2048, 0>(pv, OFF_V + 6144 + k * 256), k != 0);
    }
    wgmma_commit();
    wgmma_wait<0>();
    unsigned char* dst = a.kvacc + ((u * 4 + wg * 2) * 5 + 2 * wi) * 1024 + lane * 16;
    auto red4 = [&](bool on, unsigned char* p, float x, float y, float z) {
      asm volatile("{\n.reg .pred p;\nsetp.ne.u32 p, %4, 0;\n@p red.relaxed.gpu.global.add.v4.f32 [%0], {%1,%2,%3,%5};\n}" :: "l"(p), "f"(x), "f"(y), "f"(z), "r"((uint32_t)on), "f"(1.f) : "memory");
    };
    red4(wi < 3, dst, d0[0], d0[1], d0[4]); red4(wi < 3, dst + 512, d0[5], d0[8], d0[9]);
    red4(wi < 3, dst + 5120, d1[0], d1[1], d1[4]); red4(wi < 3, dst + 5632, d1[5], d1[8], d1[9]);
    red4(wi < 2, dst + 1024, d0[2], d0[3], d0[6]); red4(wi < 2, dst + 1536, d0[7], d0[10], d0[11]);
    red4(wi < 2, dst + 6144, d1[2], d1[3], d1[6]); red4(wi < 2, dst + 6656, d1[7], d1[10], d1[11]);
  }
  TL2((tl >= 12 ? 128 : 0) + 32 + 2);
  uint32_t qf[4][2][5];
  static_for<0, 4>([&](auto HH) { features(IC<0>{}, HH, qf[HH.value]); });
  uint4 xr[5];
#pragma unroll
  for (int i = 0; i < 5; i++) {
    const int c = lane + 32 * i;
    xr[i] = __ldcg((const uint4*)(a.xin + (size_t)(m2 * 128 + wg * 64 + wi * 16 + c / 10) * cfg::DM + ns * 80 + (c % 10) * 8));
  }
  {
    const unsigned char* src = a.kvacc + (u * 20 + warp) * 1024 + lane * 16;
    uint4 v[6];
    int spin = 0;
    while (true) {
      v[0] = ld_relaxed_v4_i<0>(src); v[1] = ld_relaxed_v4_i<512>(src); v[2] = ld_relaxed_v4_i<8192>(src); v[3] = ld_relaxed_v4_i<8704>(src);
      v[4] = ld_relaxed_v4_i<0>(src + (wg ? 0 : 16384)); v[5] = ld_relaxed_v4_i<512>(src + (wg ? 0 : 16384));
      const uint32_t c = (v[0].w & v[1].w & v[2].w) & (v[3].w & v[4].w & v[5].w);
      if (!__any_sync(0xffffffffu, (c & 0x41800000u) != 0x41800000u) || ++spin >= SPIN_LIMIT) break;
      __nanosleep(100);
    }
    const uint32_t kd = sb + OFF_KV + warp * 384 + lane * 4;
#pragma unroll
    for (int i = 0; i < 3; i++)
      if (i < 2 || wg == 0) {
        sts32(kd + i * 3072, pack_bf16(__uint_as_float(v[2 * i].x), __uint_as_float(v[2 * i].y)));
        sts32(kd + i * 3072 + 128, pack_bf16(__uint_as_float(v[2 * i].z), __uint_as_float(v[2 * i + 1].x)));
        sts32(kd + i * 3072 + 256, pack_bf16(__uint_as_float(v[2 * i + 1].y), __uint_as_float(v[2 * i + 1].z)));
      }
  }
  fence_proxy_async();
  bar_sync(1, 256);
  TL2((tl >= 12 ? 128 : 0) + 32 + 3);
  {
    float d[4][12];
    uint32_t zero = 0; PIN(zero);
#pragma unroll
    for (int hh = 0; hh < 4; hh++)
#pragma unroll
      for (int i = 0; i < 5; i++) { PIN(qf[hh][0][i]); PIN(qf[hh][1][i]); }
    wgmma_fence();
#pragma unroll
    for (int hh = 0; hh < 4; hh++) {
      const uint32_t kb = OFF_KV + hh * 1920;
      wgmma_rs_n24<1>(d[hh], qf[hh][0][0], qf[hh][1][0], qf[hh][0][1], qf[hh][1][1], desc16<384, 128, 0>(s16, kb), 0);
      wgmma_rs_n24<1>(d[hh], qf[hh][0][2], qf[hh][1][2], qf[hh][0][3], qf[hh][1][3], desc16<384, 128, 0>(s16, kb + 768), 1);
      wgmma_rs_n24<1>(d[hh], qf[hh][0][4], qf[hh][1][4], zero, zero, desc16<0, 128, 0>(s16, kb + 1536), 1);
    }
    wgmma_commit();
    wgmma_wait<0>();
    uint32_t ow[4][6];
#pragma unroll
    for (int hh = 0; hh < 4; hh++) {
      const int zl = (lane & ~3) | ((hh & 1) ? 0 : 2);
      const float da = bf16r(bf16r(__shfl_sync(0xffffffffu, d[hh][8], zl)) + 1e-6f), db = bf16r(bf16r(__shfl_sync(0xffffffffu, d[hh][10], zl)) + 1e-6f);
#pragma unroll
      for (int n = 0; n < 3; n++) {
        bf16r2(d[hh][4 * n], d[hh][4 * n + 1]); bf16r2(d[hh][4 * n + 2], d[hh][4 * n + 3]);
        ow[hh][2 * n] = pack_bf16(__fdividef(d[hh][4 * n], da), __fdividef(d[hh][4 * n + 1], da));
        ow[hh][2 * n + 1] = pack_bf16(__fdividef(d[hh][4 * n + 2], db), __fdividef(d[hh][4 * n + 3], db));
      }
    }
#pragma unroll
    for (int p = 0; p < 2; p++) {
      const uint32_t oa = sb + OFF_OST + p * 10240 + srow;
      stsm_x4(oa, ow[2 * p][0], ow[2 * p][1], ow[2 * p][2], ow[2 * p][3]);
      stsm_x2(oa + 4096, q4 < 2 ? ow[2 * p][4] : ow[2 * p + 1][4], q4 < 2 ? ow[2 * p][5] : ow[2 * p + 1][5]);
      stsm_x4(oa + 6144, ow[2 * p + 1][0], ow[2 * p + 1][1], ow[2 * p + 1][2], ow[2 * p + 1][3]);
    }
    fence_proxy_async();
    __syncwarp();
    mbar_arrive_if(lane == 0, staged);
  }
  TL2((tl >= 12 ? 128 : 0) + 32 + 4);
  float c2[40];
  mbar_wait(barW, 0);
#pragma unroll 1
  for (int i = 0; i < 8; i++) {
    mbar_wait(full2 + 8 * i, 0);
    const uint32_t st = s16 + (i < 6 ? i : i - 6) * (PIECE / 16) + wg * 64, wo = s16 + i * 800;
    wgmma_fence();
#pragma unroll
    for (int kk = 0; kk < 5; kk++) wgmma_n80<0, 1>(c2, desc16<2048, 128, 0>(st, kk * 4096), desc16<1280, 128, 0>(wo, OFF_WOT + kk * 2560), (i | kk) != 0);
    wgmma_commit();
    if (i == 1 || i == 2) { wgmma_wait<1>(); mbar_arrive_if(lead, empty2 + 8 * (i - 1)); }
  }
  wgmma_wait<0>();
  TL2((tl >= 12 ? 128 : 0) + 32 + 5);
  {
    bar_sync(1, 256);
    const uint32_t ost = sb + 2 * PIECE + warp * 3072;
#pragma unroll
    for (int v = 0; v < 10; v += 2)
      stsm_x4(ost + (lane & 15) * 176 + (v + (lane >> 4)) * 16, pack_bf16(c2[4 * v], c2[4 * v + 1]), pack_bf16(c2[4 * v + 2], c2[4 * v + 3]),
              pack_bf16(c2[4 * v + 4], c2[4 * v + 5]), pack_bf16(c2[4 * v + 6], c2[4 * v + 7]));
    __syncwarp();
#pragma unroll
    for (int i = 0; i < 5; i++) {
      const int c = lane + 32 * i, row = c / 10, chunk = c % 10;
      const uint4 y = lds128(ost + row * 176 + chunk * 16);
      const size_t off = (size_t)(m2 * 128 + wg * 64 + wi * 16 + row) * cfg::DM + ns * 80 + chunk * 8;
      const uint4 x = xr[i];
      *(uint4*)(a.xout + off) = make_uint4(pack_bf16(bf_lo(x.x) + bf_lo(y.x), bf_hi(x.x) + bf_hi(y.x)), pack_bf16(bf_lo(x.y) + bf_lo(y.y), bf_hi(x.y) + bf_hi(y.y)),
                                           pack_bf16(bf_lo(x.z) + bf_lo(y.z), bf_hi(x.z) + bf_hi(y.z)), pack_bf16(bf_lo(x.w) + bf_lo(y.w), bf_hi(x.w) + bf_hi(y.w)));
    }
  }
  TL_END(tl);
}
__device__ __align__(32768) unsigned char g_arena[AR_SIZE];
__device__ unsigned g_go[32];
__device__ __align__(1024) uint2 g_xh[2048 * 160];
__device__ __align__(1024) unsigned char g_k[64 * 96 * 5120], g_v[64 * 96 * 5120];
__device__ __align__(1024) bf16 g_o[2048 * 6144];
__device__ __align__(1024) uint4 g_qs[8 * 32 * 12 * 256];
__device__ __align__(1024) bf16 g_xn[2048 * 640], g_xn2[2048 * 640], g_xa[2048 * 640], g_xb[2048 * 640];
__device__ __align__(1024) bf16 g_part[24 * 2048 * 640];
__device__ __align__(1024) bf16 g_wb[2048 * 640], g_wot[640 * 640], g_pq[2048 * 640];
__device__ __align__(1024) float g_kvacc[bf::KVACC / 4 + 64];

typedef CUresult (*EncodeFn)(CUtensorMap*, CUtensorMapDataType, cuuint32_t, void*, const cuuint64_t*, const cuuint64_t*, const cuuint32_t*,
                             const cuuint32_t*, CUtensorMapInterleave, CUtensorMapSwizzle, CUtensorMapL2promotion, CUtensorMapFloatOOBfill);
static EncodeFn g_encode = nullptr;
static CUtensorMap make_map(const void* p, uint64_t cols, uint64_t rows, uint32_t bc, uint32_t br, bool swz = true) {
  CUtensorMap m;
  cuuint64_t dims[2] = {cols, rows}, strides[1] = {cols * 2};
  cuuint32_t box[2] = {bc, br}, es[2] = {1, 1};
  g_encode(&m, CU_TENSOR_MAP_DATA_TYPE_BFLOAT16, 2, const_cast<void*>(p), dims, strides, box, es, CU_TENSOR_MAP_INTERLEAVE_NONE,
           swz ? CU_TENSOR_MAP_SWIZZLE_128B : CU_TENSOR_MAP_SWIZZLE_NONE, CU_TENSOR_MAP_L2_PROMOTION_L2_256B, CU_TENSOR_MAP_FLOAT_OOB_FILL_NONE);
  return m;
}
static CUtensorMap make_map3(const void* p, uint64_t cols, uint64_t rows, uint32_t nb) {
  CUtensorMap m;
  cuuint64_t dims[3] = {64, rows, cols / 64}, strides[2] = {cols * 2, 128};
  cuuint32_t box[3] = {64, 64, nb}, es[3] = {1, 1, 1};
  g_encode(&m, CU_TENSOR_MAP_DATA_TYPE_BFLOAT16, 3, const_cast<void*>(p), dims, strides, box, es, CU_TENSOR_MAP_INTERLEAVE_NONE,
           CU_TENSOR_MAP_SWIZZLE_128B, CU_TENSOR_MAP_L2_PROMOTION_L2_256B, CU_TENSOR_MAP_FLOAT_OOB_FILL_NONE);
  return m;
}
template <class T> static T* sym(const T& s) { void* p = nullptr; cudaGetSymbolAddress(&p, s); return (T*)p; }

struct Ptrs {
  unsigned char *arena, *k, *v; bf16 *o, *xn, *xa, *xb, *wb, *wot, *pq; float *part, *kvacc; uint2* xh; uint4* qs; bf16* xn2; unsigned* go;
};

static tr::Sched make_sched(int layer, const char* str, const int* ks, const int* lr) {
  using namespace tr;
  Sched s = {};
  int n = 0;
  for (int b = 0; b < 16; b++) { s.ks[b] = (uint8_t)abs(ks[b]); s.wide[b] = ks[b] > 0; s.lrows[b] = (uint8_t)lr[b]; }
  for (const char* p = str; *p;) {
    if (*p == ' ') { p++; continue; }
    const bool late = *p < 'a';
    const char c = *p++ | 32;
    char* e;
    const int b = (int)strtol(p, &e, 10); p = e;
    int first = 0, cnt = c == 'o' ? s.ks[b] * (s.wide[b] ? 2 : 5) : (c == 'l' ? 16 / lr[b] : 32);
    if (*p == '.') { first = (int)strtol(p + 1, &e, 10); cnt = (int)strtol(e + 1, &e, 10); p = e; }
    const int type = c == 'a' ? T_QA : (c == 'q' ? T_Q : (c == 't' ? T_A : (c == 'l' ? T_L : (c == 'p' ? T_P : (s.wide[b] ? T_OB : T_OS)))));
    if (type == T_P && layer > 0) continue;
    for (int i = 0; i < cnt && n < MAXITEMS - 1; i++) s.item[n++] = (uint16_t)((late << 14) | (type << 11) | (b << 7) | (first + i));
  }
  s.n = n; s.item[n] = T_END << 11;
  return s;
}
static tr::Sched sched_of(int layer) {
  const char* str = "q12 q13 q14 a0 q15 a1 p0.0.16 o0 o1 a2 p0.16.16 o2 a3 a4 o3 a5 o4 a6 l0 o5 l1 a7 o6 l2 a8 o7 a9 o8 l3 l4 a10 O9 l5 a11 O10 t12 l6 l7 o11 O12 t13 t14 T15 O13 o15 O14 L10 L9 l15 l13 L8 l14 l12 l11";
  int ks[16] = {2, 2, 2, 2, 2, 2, 2, 2, 2, 3, 3, 3, 3, -4, -6, -8}, lr[16] = {4, 4, 4, 4, 4, 4, 4, 4, 1, 4, 1, 1, 1, 1, 1, 1};
#ifdef TUNE
  const bool mine = !getenv("ONLY") || atoi(getenv("ONLY")) == layer;
  if (mine && getenv("SCHED")) str = getenv("SCHED");
  if (const char* p = mine ? getenv("KS") : nullptr) for (int b = 0; b < 16; b++) { char* e; ks[b] = (int)strtol(p, &e, 10); p = e; }
  if (const char* p = mine ? getenv("LR") : nullptr) for (int b = 0; b < 16; b++) { char* e; lr[b] = (int)strtol(p, &e, 10); p = e; }
#endif
  return make_sched(layer, str, ks, lr);
}
#ifndef TRAIL_GRID
#define TRAIL_GRID 132
#endif
#ifndef PDL_LN
#define PDL_LN 0
#endif
#ifndef PDL_CH
#define PDL_CH 1
#endif
#ifndef PDL_B
#define PDL_B 1
#endif
#ifndef PF_A
#define PF_A 1
#endif
#ifndef PF_B
#define PF_B 1
#endif
extern "C" void kernel_launch(void* const* d_in, const int* in_sizes, int n_in, void* d_out, int out_size) {
  const bf16* x = (const bf16*)d_in[0];
  const bf16* mem0 = (const bf16*)d_in[1];
  const bf16 *Wq = (const bf16*)d_in[2], *Wk = (const bf16*)d_in[3], *Wv = (const bf16*)d_in[4], *Wo = (const bf16*)d_in[5];
  const bf16 *wqkv = (const bf16*)d_in[8], *wphi = (const bf16*)d_in[9], *wo = (const bf16*)d_in[10];
  bf16* out = (bf16*)d_out;
  static Ptrs P; static bool init = false;
  if (!init) {
    void* fn = nullptr; cudaDriverEntryPointQueryResult qr;
    cudaGetDriverEntryPoint("cuTensorMapEncodeTiled", &fn, cudaEnableDefault, &qr);
    g_encode = (EncodeFn)fn;
    void* p;
    cudaGetSymbolAddress(&p, g_arena); P.arena = (unsigned char*)p;
    cudaGetSymbolAddress(&p, g_k); P.k = (unsigned char*)p;   cudaGetSymbolAddress(&p, g_v); P.v = (unsigned char*)p;
    cudaGetSymbolAddress(&p, g_o); P.o = (bf16*)p;
    cudaGetSymbolAddress(&p, g_xn); P.xn = (bf16*)p;
    cudaGetSymbolAddress(&p, g_xa); P.xa = (bf16*)p;   cudaGetSymbolAddress(&p, g_xb); P.xb = (bf16*)p;
    cudaGetSymbolAddress(&p, g_wb); P.wb = (bf16*)p;   cudaGetSymbolAddress(&p, g_wot); P.wot = (bf16*)p;
    cudaGetSymbolAddress(&p, g_pq); P.pq = (bf16*)p;   cudaGetSymbolAddress(&p, g_part); P.part = (float*)p;
    cudaGetSymbolAddress(&p, g_kvacc); P.kvacc = (float*)p;
    cudaGetSymbolAddress(&p, g_xh); P.xh = (uint2*)p;
    cudaGetSymbolAddress(&p, g_go); P.go = (unsigned*)p;
    cudaGetSymbolAddress(&p, g_qs); P.qs = (uint4*)p;
    cudaGetSymbolAddress(&p, g_xn2); P.xn2 = (bf16*)p;
    cudaFuncSetAttribute(chain_kernel, cudaFuncAttributeMaxDynamicSharedMemorySize, ch::SMEM);
    cudaFuncSetAttribute(trail_kernel, cudaFuncAttributeMaxDynamicSharedMemorySize, tr::SMEM);
    cudaFuncSetAttribute(blayer_kernel, cudaFuncAttributeMaxDynamicSharedMemorySize, bf::SMEM);
    init = true;
  }
  const CUtensorMap tmXn = make_map(P.xn, 640, 2048, 64, 128), tmXn2 = make_map(P.xn2, 640, 2048, 64, 128);
  const CUtensorMap tmWq = make_map3(Wq, 6144, 640, 3);
  const CUtensorMap tmCq = make_map(Wq, 6144, 640, 64, 160), tmCk = make_map(Wk, 6144, 640, 64, 160), tmCv = make_map(Wv, 6144, 640, 64, 160), tmCo = make_map(Wo, 640, 6144, 224, 64, false);
  const CUtensorMap tmWo5 = make_map3(Wo, 640, 6144, 5), tmWo2 = make_map3(Wo, 640, 6144, 2);

  CUtensorMap tmP;
  {
    cuuint64_t dims[3] = {256, 8, 24 * 320}, strides[2] = {1024, 8192};
    cuuint32_t box[3] = {256, 1, 10}, es[3] = {1, 1, 1};
    g_encode(&tmP, CU_TENSOR_MAP_DATA_TYPE_UINT32, 3, P.part, dims, strides, box, es, CU_TENSOR_MAP_INTERLEAVE_NONE, CU_TENSOR_MAP_SWIZZLE_NONE,
             CU_TENSOR_MAP_L2_PROMOTION_NONE, CU_TENSOR_MAP_FLOAT_OOB_FILL_NONE);
  }
  ChainArgs ca;
  ca.xh = P.xh; ca.mem0 = mem0; ca.kg = P.k; ca.vg = P.v;
  ca.arena = P.arena; ca.dbg = nullptr; ca.go = P.go; ca.delay = POLL_DELAY; ca.margin = 150; ca.pubrel = 1;
#ifdef TUNE
  if (getenv("PR")) ca.pubrel = atoi(getenv("PR"));
  if (getenv("MG")) ca.margin = atoi(getenv("MG"));
  if (getenv("PD")) ca.delay = atoi(getenv("PD"));
#endif
  ca.tl = 0;
  uint4* zar = (uint4*)P.arena; const int nzar = AR_SIZE / 16;
  uint4* zkv = (uint4*)P.kvacc; const int nzkv = (bf::KVACC / 4 + 64) / 4;

  const PrepArgs pa{wqkv, wphi, wo, (unsigned char*)P.wb, (unsigned char*)P.wot};
  const bf16* xcur = x;
  cudaLaunchAttribute at[1];
  at[0].id = cudaLaunchAttributeProgrammaticStreamSerialization; at[0].val.programmaticStreamSerializationAllowed = 1;
  auto cfgof = [&](int grid, int block, int smem, bool pdl) {
    cudaLaunchConfig_t lc = {};
    lc.gridDim = dim3(grid); lc.blockDim = dim3(block); lc.dynamicSmemBytes = smem; lc.stream = cudaStreamPerThread;
    lc.attrs = at; lc.numAttrs = pdl ? 1 : 0;
    return lc;
  };
  int nlayers = 2;
#ifdef TUNE
  if (getenv("LAYERS")) nlayers = atoi(getenv("LAYERS"));
#endif
  for (int layer = 0; layer < nlayers; layer++) {
    const int tl = layer * 12;
    cudaLaunchConfig_t lc = cfgof(256, 256, 0, layer > 0 && PDL_LN);
    cudaLaunchKernelEx(&lc, ln_kernel, xcur, P.xn, P.xh, zar, nzar, zkv, nzkv, Wk, Wv, layer == 0 ? PF_A : 0, tl + 0);
    ca.tl = tl + 2;
    lc = cfgof(96, 384, ch::SMEM, PDL_CH);
    cudaLaunchKernelEx(&lc, chain_kernel, ca, tmCq, tmCk, tmCv, tmCo);
    lc = cfgof(TRAIL_GRID, 384, tr::SMEM, true);
    tr::Args ta{P.k, P.v, (unsigned char*)P.o, P.qs, (unsigned char*)P.part, xcur, P.xn, P.xa, P.xn2, P.arena, P.go, tl + 4, 30, 20, layer == 0};
#ifdef TUNE
    if (getenv("NAP")) ta.nap = atoi(getenv("NAP"));
    if (getenv("NAP2")) ta.nap2 = atoi(getenv("NAP2"));
#endif
    cudaLaunchKernelEx(&lc, trail_kernel, tmXn, tmWq, tmWo5, tmWo2, tmP, sched_of(layer), ta, pa);
    lc = cfgof(128, 384, bf::SMEM, PDL_B);
    bf::Args ba{(const unsigned char*)P.wb, (const unsigned char*)P.wot, (unsigned char*)P.kvacc, (unsigned char*)P.pq, P.xa, layer == 0 ? P.xb : out, P.go, layer == 0 ? P.arena + tr::C_P : nullptr,
                      layer == 0 && PF_B ? Wk : nullptr, Wv, 30, 500, 0, tl + 7};
#ifdef TUNE
    if (getenv("PFN")) ba.pfn = atoi(getenv("PFN"));
    if (getenv("PFNS")) ba.pfns = atoi(getenv("PFNS"));
    if (getenv("PFWT")) ba.pfwait = atoi(getenv("PFWT"));
    if (getenv("PFB")) ba.pf0 = layer == 0 && atoi(getenv("PFB")) ? Wk : nullptr;
#endif
    cudaLaunchKernelEx(&lc, blayer_kernel, tmXn2, ba);
    xcur = P.xb;
  }
}
```

```cpp
#include <cuda_runtime.h>
#include <cuda.h>
#include <cuda_bf16.h>
#include <stdint.h>
#include <stdlib.h>
#include <type_traits>

typedef __nv_bfloat16 bf16;

namespace cfg {
constexpr int S = 2048, DM = 640, H = 32, DH = 192, NSEG = 64, SEG = 32, NM = 8;
constexpr int HD = H * DH;
}

__device__ __forceinline__ uint32_t smem_u32(const void* p) { return (uint32_t)__cvta_generic_to_shared(p); }
__device__ __forceinline__ uint32_t mapa_u32(uint32_t a, uint32_t r) {
  uint32_t o; asm("mapa.shared::cluster.u32 %0, %1, %2;" : "=r"(o) : "r"(a), "r"(r)); return o;
}
__device__ __forceinline__ void mbar_init(uint32_t b, uint32_t c) {
  asm volatile("mbarrier.init.shared::cta.b64 [%0], %1;" :: "r"(b), "r"(c) : "memory");
}
__device__ __forceinline__ void mbar_expect_tx(uint32_t b, uint32_t bytes) {
  asm volatile("mbarrier.arrive.expect_tx.shared::cta.b64 _, [%0], %1;" :: "r"(b), "r"(bytes) : "memory");
}
__device__ __forceinline__ void mbar_arrive(uint32_t b) {
  asm volatile("mbarrier.arrive.shared::cta.b64 _, [%0];" :: "r"(b) : "memory");
}
__device__ __forceinline__ void mbar_expect_tx_if(bool c, uint32_t b, uint32_t bytes) {
  asm volatile("{\n.reg .pred p;\nsetp.ne.u32 p, %2, 0;\n@p mbarrier.arrive.expect_tx.shared::cta.b64 _, [%0], %1;\n}" :: "r"(b), "r"(bytes), "r"((uint32_t)c) : "memory");
}
__device__ __forceinline__ void mbar_arrive_if(bool c, uint32_t b) {
  asm volatile("{\n.reg .pred p;\nsetp.ne.u32 p, %1, 0;\n@p mbarrier.arrive.shared::cta.b64 _, [%0];\n}" :: "r"(b), "r"((uint32_t)c) : "memory");
}
__device__ __forceinline__ bool mbar_try(uint32_t b, uint32_t ph) {
  uint32_t p;
  asm volatile("{.reg .pred p; mbarrier.try_wait.parity.shared::cta.b64 p, [%1], %2; selp.u32 %0, 1, 0, p;}"
               : "=r"(p) : "r"(b), "r"(ph) : "memory");
  return p;
}
__device__ __forceinline__ bool mbar_try_cluster(uint32_t b, uint32_t ph) {
  uint32_t p;
  asm volatile("{.reg .pred p; mbarrier.try_wait.parity.acquire.cluster.shared::cta.b64 p, [%1], %2; selp.u32 %0, 1, 0, p;}"
               : "=r"(p) : "r"(b), "r"(ph) : "memory");
  return p;
}
#ifndef SPIN_LIMIT
#define SPIN_LIMIT (1 << 20)
#endif
__device__ __forceinline__ void mbar_wait(uint32_t b, uint32_t ph) {
  asm volatile("{\n.reg .pred p, q;\n.reg .u32 c;\nmov.u32 c, 0;\n"
               "W_%=:\nmbarrier.try_wait.parity.shared::cta.b64 p, [%0], %1;\n@p bra.uni D_%=;\n"
               "add.u32 c, c, 1;\nsetp.lt.u32 q, c, %2;\n@q bra.uni W_%=;\nD_%=:\n}"
               :: "r"(b), "r"(ph), "n"(SPIN_LIMIT) : "memory");
}
__device__ __forceinline__ void mbar_wait_if(bool cnd, uint32_t b, uint32_t ph) {
  asm volatile("{\n.reg .pred p, q;\n.reg .u32 c;\nsetp.eq.u32 q, %3, 0;\n@q bra.uni D_%=;\nmov.u32 c, 0;\n"
               "W_%=:\nmbarrier.try_wait.parity.shared::cta.b64 p, [%0], %1;\n@p bra.uni D_%=;\n"
               "add.u32 c, c, 1;\nsetp.lt.u32 q, c, %2;\n@q bra.uni W_%=;\nD_%=:\n}"
               :: "r"(b), "r"(ph), "n"(SPIN_LIMIT), "r"((uint32_t)cnd) : "memory");
}
__device__ __forceinline__ void mbar_spin(uint32_t b, uint32_t ph) {
  asm volatile("{\n.reg .pred p, q;\n.reg .u32 c;\nmov.u32 c, 0;\n"
               "W_%=:\nmbarrier.test_wait.parity.shared::cta.b64 p, [%0], %1;\n@p bra D_%=;\n"
               "add.u32 c, c, 1;\nsetp.lt.u32 q, c, %2;\n@q bra W_%=;\nD_%=:\n}"
               :: "r"(b), "r"(ph), "n"(SPIN_LIMIT) : "memory");
}
#define PIN(x) asm volatile("" : "+r"(x))
__device__ __forceinline__ void mbar_wait_cluster(uint32_t b, uint32_t ph) {
  int s = 0;
  while (!mbar_try_cluster(b, ph)) { if (++s > SPIN_LIMIT) break; }
}
__device__ __forceinline__ void st_async_v2(uint32_t a, uint32_t x, uint32_t y, uint32_t mb) {
  asm volatile("st.async.weak.shared::cluster.mbarrier::complete_tx::bytes.v2.b32 [%0], {%1,%2}, [%3];"
               :: "r"(a), "r"(x), "r"(y), "r"(mb) : "memory");
}
__device__ __forceinline__ void st_async_v4(uint32_t a, uint32_t x, uint32_t y, uint32_t z, uint32_t w, uint32_t mb) {
  asm volatile("st.async.weak.shared::cluster.mbarrier::complete_tx::bytes.v4.b32 [%0], {%1,%2,%3,%4}, [%5];"
               :: "r"(a), "r"(x), "r"(y), "r"(z), "r"(w), "r"(mb) : "memory");
}
__device__ __forceinline__ void bulk_g2s(uint32_t dst, const void* src, uint32_t bytes, uint32_t mb) {
  asm volatile("cp.async.bulk.shared::cluster.global.mbarrier::complete_tx::bytes [%0], [%1], %2, [%3];"
               :: "r"(dst), "l"(src), "r"(bytes), "r"(mb) : "memory");
}
__device__ __forceinline__ void cp_async16(uint32_t dst, const void* src) {
  asm volatile("cp.async.cg.shared.global [%0], [%1], 16;" :: "r"(dst), "l"(src) : "memory");
}
__device__ __forceinline__ void cp_async_wait_all() { asm volatile("cp.async.wait_all;" ::: "memory"); }
__device__ __forceinline__ void fence_proxy_async() { asm volatile("fence.proxy.async.shared::cta;" ::: "memory"); }
__device__ __forceinline__ void bar_sync(int id, int n) { asm volatile("bar.sync %0, %1;" :: "r"(id), "r"(n) : "memory"); }
__device__ __forceinline__ void bar_arrive(int id, int n) { asm volatile("bar.arrive %0, %1;" :: "r"(id), "r"(n) : "memory"); }
__device__ __forceinline__ void cluster_sync_all() {
  asm volatile("barrier.cluster.arrive.release.aligned; barrier.cluster.wait.acquire.aligned;" ::: "memory");
}
__device__ __forceinline__ void ldsm_x4(uint32_t (&r)[4], uint32_t a) {
  asm volatile("ldmatrix.sync.aligned.m8n8.x4.shared.b16 {%0,%1,%2,%3}, [%4];"
               : "=r"(r[0]), "=r"(r[1]), "=r"(r[2]), "=r"(r[3]) : "r"(a) : "memory");
}
__device__ __forceinline__ void ldsm_x4_t(uint32_t (&r)[4], uint32_t a) {
  asm volatile("ldmatrix.sync.aligned.m8n8.x4.trans.shared.b16 {%0,%1,%2,%3}, [%4];"
               : "=r"(r[0]), "=r"(r[1]), "=r"(r[2]), "=r"(r[3]) : "r"(a) : "memory");
}
template <int IMM> __device__ __forceinline__ void ldsm_x4_i(uint32_t (&r)[4], uint32_t a) {
  asm volatile("ldmatrix.sync.aligned.m8n8.x4.shared.b16 {%0,%1,%2,%3}, [%4+%5];"
               : "=r"(r[0]), "=r"(r[1]), "=r"(r[2]), "=r"(r[3]) : "r"(a), "n"(IMM) : "memory");
}
template <int IMM> __device__ __forceinline__ void ldsm_x4_t_i(uint32_t (&r)[4], uint32_t a) {
  asm volatile("ldmatrix.sync.aligned.m8n8.x4.trans.shared.b16 {%0,%1,%2,%3}, [%4+%5];"
               : "=r"(r[0]), "=r"(r[1]), "=r"(r[2]), "=r"(r[3]) : "r"(a), "n"(IMM) : "memory");
}
template <int IMM> __device__ __forceinline__ uint4 lds128_i(uint32_t a) {
  uint4 v; asm volatile("ld.shared.v4.u32 {%0,%1,%2,%3}, [%4+%5];" : "=r"(v.x), "=r"(v.y), "=r"(v.z), "=r"(v.w) : "r"(a), "n"(IMM) : "memory"); return v;
}
template <int IMM> __device__ __forceinline__ uint2 lds64_i(uint32_t a) {
  uint2 v; asm volatile("ld.shared.v2.u32 {%0,%1}, [%2+%3];" : "=r"(v.x), "=r"(v.y) : "r"(a), "n"(IMM) : "memory"); return v;
}
template <int IMM> __device__ __forceinline__ void sts128_i(uint32_t a, uint32_t x, uint32_t y, uint32_t z, uint32_t w) {
  asm volatile("st.shared.v4.u32 [%0+%5], {%1,%2,%3,%4};" :: "r"(a), "r"(x), "r"(y), "r"(z), "r"(w), "n"(IMM) : "memory");
}
template <int IMM> __device__ __forceinline__ void sts64_i(uint32_t a, uint32_t x, uint32_t y) {
  asm volatile("st.shared.v2.u32 [%0+%3], {%1,%2};" :: "r"(a), "r"(x), "r"(y), "n"(IMM) : "memory");
}
template <int IMM> __device__ __forceinline__ void st_async_v2_i(uint32_t a, uint32_t x, uint32_t y, uint32_t mb) {
  asm volatile("st.async.weak.shared::cluster.mbarrier::complete_tx::bytes.v2.b32 [%0+%4], {%1,%2}, [%3];"
               :: "r"(a), "r"(x), "r"(y), "r"(mb), "n"(IMM) : "memory");
}
template <int IMM> __device__ __forceinline__ uint4 ld_relaxed_v4_i(const void* p) {
  uint4 v; asm volatile("ld.relaxed.gpu.global.v4.u32 {%0,%1,%2,%3}, [%4+%5];" : "=r"(v.x), "=r"(v.y), "=r"(v.z), "=r"(v.w) : "l"(p), "n"(IMM) : "memory"); return v;
}
template <int I, int N, class F> __device__ __forceinline__ void static_for(F&& f) {
  if constexpr (I < N) { f(std::integral_constant<int, I>{}); static_for<I + 1, N>(f); }
}
__device__ __forceinline__ uint32_t movm_t(uint32_t a) {
  uint32_t d; asm volatile("movmatrix.sync.aligned.m8n8.trans.b16 %0, %1;" : "=r"(d) : "r"(a)); return d;
}
__device__ __forceinline__ void mma16816(float (&d)[4], uint32_t a0, uint32_t a1, uint32_t a2, uint32_t a3, uint32_t b0, uint32_t b1) {
  asm volatile("mma.sync.aligned.m16n8k16.row.col.f32.bf16.bf16.f32 {%0,%1,%2,%3}, {%4,%5,%6,%7}, {%8,%9}, {%0,%1,%2,%3};"
               : "+f"(d[0]), "+f"(d[1]), "+f"(d[2]), "+f"(d[3]) : "r"(a0), "r"(a1), "r"(a2), "r"(a3), "r"(b0), "r"(b1));
}
__device__ __forceinline__ uint32_t pack_bf16(float lo, float hi) {
  uint32_t d; asm("cvt.rn.bf16x2.f32 %0, %1, %2;" : "=r"(d) : "f"(hi), "f"(lo)); return d;
}
__device__ __forceinline__ float bf_lo(uint32_t w) { return __uint_as_float(w << 16); }
__device__ __forceinline__ float bf_hi(uint32_t w) { return __uint_as_float(w & 0xffff0000u); }
__device__ __forceinline__ uint4 lds128(uint32_t a) {
  uint4 v; asm volatile("ld.shared.v4.u32 {%0,%1,%2,%3}, [%4];" : "=r"(v.x), "=r"(v.y), "=r"(v.z), "=r"(v.w) : "r"(a) : "memory"); return v;
}
__device__ __forceinline__ uint2 lds64(uint32_t a) {
  uint2 v; asm volatile("ld.shared.v2.u32 {%0,%1}, [%2];" : "=r"(v.x), "=r"(v.y) : "r"(a) : "memory"); return v;
}
__device__ __forceinline__ void sts128(uint32_t a, uint32_t x, uint32_t y, uint32_t z, uint32_t w) {
  asm volatile("st.shared.v4.u32 [%0], {%1,%2,%3,%4};" :: "r"(a), "r"(x), "r"(y), "r"(z), "r"(w) : "memory");
}
__device__ __forceinline__ void sts64(uint32_t a, uint32_t x, uint32_t y) {
  asm volatile("st.shared.v2.u32 [%0], {%1,%2};" :: "r"(a), "r"(x), "r"(y) : "memory");
}
__device__ __forceinline__ uint4 ld_relaxed_v4(const void* p) {
  uint4 v; asm volatile("ld.relaxed.gpu.global.v4.u32 {%0,%1,%2,%3}, [%4];" : "=r"(v.x), "=r"(v.y), "=r"(v.z), "=r"(v.w) : "l"(p) : "memory"); return v;
}
__device__ __forceinline__ uint32_t ld_relaxed_u32(const void* p) {
  uint32_t v; asm volatile("ld.relaxed.gpu.global.u32 %0, [%1];" : "=r"(v) : "l"(p) : "memory"); return v;
}
__device__ __forceinline__ void st_relaxed_v2(void* p, uint32_t a, uint32_t b) {
  asm volatile("st.relaxed.gpu.global.v2.u32 [%0], {%1,%2};" :: "l"(p), "r"(a), "r"(b) : "memory");
}
__device__ __forceinline__ void st_relaxed_u32(void* p, uint32_t v) {
  asm volatile("st.relaxed.gpu.global.u32 [%0], %1;" :: "l"(p), "r"(v) : "memory");
}
__device__ __forceinline__ void st_release_u32(void* p, uint32_t v) {
  asm volatile("st.release.gpu.global.u32 [%0], %1;" :: "l"(p), "r"(v) : "memory");
}
__device__ __forceinline__ void red_release_inc(void* p) { asm volatile("red.release.gpu.global.add.u32 [%0], 1;" :: "l"(p) : "memory"); }
__device__ __forceinline__ uint32_t clk32() { uint32_t c; asm volatile("mov.u32 %0, %%clock;" : "=r"(c) :: "memory"); return c; }
__device__ __forceinline__ uint32_t clkdep(uint32_t v) {
  uint32_t c; asm volatile("{.reg .pred p; setp.eq.u32 p, %1, 0xdeadbeef; @p trap; mov.u32 %0, %%clock;}" : "=r"(c) : "r"(v) : "memory"); return c;
}
__device__ __forceinline__ void wgmma_fence() { asm volatile("wgmma.fence.sync.aligned;" ::: "memory"); }
__device__ __forceinline__ void wgmma_commit() { asm volatile("wgmma.commit_group.sync.aligned;" ::: "memory"); }
template <int N> __device__ __forceinline__ void wgmma_wait() { asm volatile("wgmma.wait_group.sync.aligned %0;" :: "n"(N) : "memory"); }
__device__ __forceinline__ void wgmma_n8_ss_ta(float (&d)[4], uint64_t da, uint64_t db, int acc) {
  asm volatile("{\n.reg .pred p;\nsetp.ne.b32 p, %6, 0;\n"
               "wgmma.mma_async.sync.aligned.m64n8k16.f32.bf16.bf16 {%0,%1,%2,%3}, %4, %5, p, 1, 1, 1, 0;\n}\n"
               : "+f"(d[0]), "+f"(d[1]), "+f"(d[2]), "+f"(d[3]) : "l"(da), "l"(db), "r"(acc));
}
__device__ __forceinline__ uint64_t make_desc(uint32_t saddr, uint32_t lbo_bytes, uint32_t sbo_bytes, uint32_t swz) {
  return (uint64_t)((saddr & 0x3FFFF) >> 4) | ((uint64_t)(lbo_bytes >> 4) << 16) | ((uint64_t)(sbo_bytes >> 4) << 32) | ((uint64_t)swz << 62);
}


template <uint32_t LBO, uint32_t SBO, uint32_t SWZ> __device__ __forceinline__ uint64_t desc16(uint32_t a16, uint32_t off = 0) {
  return (uint64_t)(a16 + ((off >> 4) + ((LBO >> 4) << 16))) | ((uint64_t)((SBO >> 4) | (SWZ << 30)) << 32);
}

__device__ __forceinline__ bool elect_one() {
  uint32_t p; asm volatile("{\n.reg .pred p;\nelect.sync _|p, 0xffffffff;\nselp.u32 %0, 1, 0, p;\n}" : "=r"(p)); return p;
}
__device__ __forceinline__ void tma_load_3d(uint32_t dst, const CUtensorMap* tm, int c0, int c1, int c2, uint32_t mb) {
  asm volatile("cp.async.bulk.tensor.3d.shared::cluster.global.mbarrier::complete_tx::bytes [%0], [%1, {%3, %4, %5}], [%2];"
               :: "r"(dst), "l"(tm), "r"(mb), "r"(c0), "r"(c1), "r"(c2) : "memory");
}
__device__ __forceinline__ void tma_load_2d(uint32_t dst, const CUtensorMap* tm, int c0, int c1, uint32_t mb) {
  asm volatile("cp.async.bulk.tensor.2d.shared::cluster.global.mbarrier::complete_tx::bytes [%0], [%1, {%3, %4}], [%2];"
               :: "r"(dst), "l"(tm), "r"(mb), "r"(c0), "r"(c1) : "memory");
}
__device__ __forceinline__ void bulk_s2g(void* dst, uint32_t src, uint32_t bytes) {
  asm volatile("cp.async.bulk.global.shared::cta.bulk_group [%0], [%1], %2;" :: "l"(dst), "r"(src), "r"(bytes) : "memory");
}
__device__ __forceinline__ uint64_t policy_evict_first() {
  uint64_t p; asm volatile("createpolicy.fractional.L2::evict_first.b64 %0, 1.0;" : "=l"(p)); return p;
}
__device__ __forceinline__ void bulk_s2g_hint(void* dst, uint32_t src, uint32_t bytes, uint64_t pol) {
  asm volatile("cp.async.bulk.global.shared::cta.bulk_group.L2::cache_hint [%0], [%1], %2, %3;" :: "l"(dst), "r"(src), "r"(bytes), "l"(pol) : "memory");
}
__device__ __forceinline__ void bulk_commit() { asm volatile("cp.async.bulk.commit_group;" ::: "memory"); }
template <int N> __device__ __forceinline__ void bulk_wait_read() { asm volatile("cp.async.bulk.wait_group.read %0;" :: "n"(N) : "memory"); }
template <int N> __device__ __forceinline__ void bulk_wait() { asm volatile("cp.async.bulk.wait_group %0;" :: "n"(N) : "memory"); }
__device__ __forceinline__ void stsm_x4(uint32_t a, uint32_t r0, uint32_t r1, uint32_t r2, uint32_t r3) {
  asm volatile("stmatrix.sync.aligned.m8n8.x4.shared.b16 [%0], {%1,%2,%3,%4};" :: "r"(a), "r"(r0), "r"(r1), "r"(r2), "r"(r3) : "memory");
}
__device__ __forceinline__ void stsm_x2(uint32_t a, uint32_t r0, uint32_t r1) {
  asm volatile("stmatrix.sync.aligned.m8n8.x2.shared.b16 [%0], {%1,%2};" :: "r"(a), "r"(r0), "r"(r1) : "memory");
}
__device__ __forceinline__ void ldsm_x2(uint32_t (&r)[2], uint32_t a) {
  asm volatile("ldmatrix.sync.aligned.m8n8.x2.shared.b16 {%0,%1}, [%2];" : "=r"(r[0]), "=r"(r[1]) : "r"(a) : "memory");
}
__device__ __forceinline__ void ldsm_x2_t(uint32_t (&r)[2], uint32_t a) {
  asm volatile("ldmatrix.sync.aligned.m8n8.x2.trans.shared.b16 {%0,%1}, [%2];" : "=r"(r[0]), "=r"(r[1]) : "r"(a) : "memory");
}
__device__ __forceinline__ float bf16r(float x) { return __uint_as_float(pack_bf16(0.f, x) & 0xffff0000u); }
__device__ __forceinline__ void bf16r2(float& a, float& b) { const uint32_t w = pack_bf16(a, b); a = bf_lo(w); b = bf_hi(w); }
__device__ __forceinline__ float rcpf(float x) { float r; asm("rcp.approx.ftz.f32 %0, %1;" : "=f"(r) : "f"(x)); return r; }
__device__ __forceinline__ float ex2f(float x) { float e; asm("ex2.approx.ftz.f32 %0, %1;" : "=f"(e) : "f"(x)); return e; }
__device__ __forceinline__ void prefetch_tmap(const CUtensorMap* tm) { asm volatile("prefetch.tensormap [%0];" :: "l"(tm) : "memory"); }

#ifdef TIMELINE
__device__ unsigned long long g_tl[2 * 64];
__device__ unsigned g_step[2 * 64 * 96 * 4];
__device__ unsigned long long g_log[2 * 132 * 64 * 2 + 2];
__device__ unsigned long long g_tl2[4 * 64];
__device__ __forceinline__ unsigned long long gtime() { unsigned long long t; asm volatile("mov.u64 %0, %%globaltimer;" : "=l"(t)); return t; }
#define TL_BEGIN(id) do { if (threadIdx.x == 0) atomicMin(&g_tl[2 * (id)], gtime()); } while (0)
#define TL_END(id) do { if ((threadIdx.x & 31) == 0) atomicMax(&g_tl[2 * (id) + 1], gtime()); } while (0)
#define TL_ACC(idx, t0) do { if (threadIdx.x == 0 && m >= 4 && m < 11) { atomicAdd(&g_tl2[idx], gtime() - (t0)); atomicAdd(&g_tl2[(idx) + 1], 1ull); } } while (0)
#define TL_NOW() gtime()
#define TL2(idx) asm volatile("{\n.reg .pred p;\nsetp.eq.u32 p, %2, 0;\n@p red.relaxed.gpu.global.max.u64 [%0], %1;\n}" :: "l"(&g_tl2[idx]), "l"(gtime()), "r"(threadIdx.x) : "memory")
#define TLW(idx) asm volatile("{\n.reg .pred p;\nsetp.eq.u32 p, %2, 0;\n@p red.relaxed.gpu.global.max.u64 [%0], %1;\n@p red.relaxed.gpu.global.add.u64 [%0+128], %1;\n}" :: "l"(&g_tl2[idx]), "l"(gtime() - g_tl0), "r"(threadIdx.x & 31) : "memory")
#define TL_BEGIN0(id) atomicMin(&g_tl[2 * (id)], gtime())
#else
#define TL_ACC(idx, t0)
#define TL_NOW() 0ull
#define TL2(idx)
#define TL_BEGIN0(id)
#define TLW(idx)
#define TL_BEGIN(id)
#define TL_END(id)
#endif
template <int TA, int TB> __device__ __forceinline__ void wgmma_n24(float (&d)[12], uint64_t da, uint64_t db, int acc) {
  asm volatile("{\n.reg .pred p;\nsetp.ne.b32 p, %14, 0;\n"
    "wgmma.mma_async.sync.aligned.m64n24k16.f32.bf16.bf16 {%0, %1, %2, %3, %4, %5, %6, %7, %8, %9, %10, %11}, %12, %13, p, 1, 1, %15, %16;\n}\n"
    : "+f"(d[0]), "+f"(d[1]), "+f"(d[2]), "+f"(d[3]), "+f"(d[4]), "+f"(d[5]), "+f"(d[6]), "+f"(d[7]), "+f"(d[8]), "+f"(d[9]), "+f"(d[10]), "+f"(d[11])
    : "l"(da), "l"(db), "r"(acc), "n"(TA), "n"(TB));
}

template <int TA, int TB> __device__ __forceinline__ void wgmma_n80(float (&d)[40], uint64_t da, uint64_t db, int acc) {
  asm volatile("{\n.reg .pred p;\nsetp.ne.b32 p, %42, 0;\n"
    "wgmma.mma_async.sync.aligned.m64n80k16.f32.bf16.bf16 {%0, %1, %2, %3, %4, %5, %6, %7, %8, %9, %10, %11, %12, %13, %14, %15, %16, %17, %18, %19, %20, %21, %22, %23, %24, %25, %26, %27, %28, %29, %30, %31, %32, %33, %34, %35, %36, %37, %38, %39}, %40, %41, p, 1, 1, %43, %44;\n}\n"
    : "+f"(d[0]), "+f"(d[1]), "+f"(d[2]), "+f"(d[3]), "+f"(d[4]), "+f"(d[5]), "+f"(d[6]), "+f"(d[7]), "+f"(d[8]), "+f"(d[9]), "+f"(d[10]), "+f"(d[11]), "+f"(d[12]), "+f"(d[13]), "+f"(d[14]), "+f"(d[15]), "+f"(d[16]), "+f"(d[17]), "+f"(d[18]), "+f"(d[19]), "+f"(d[20]), "+f"(d[21]), "+f"(d[22]), "+f"(d[23]), "+f"(d[24]), "+f"(d[25]), "+f"(d[26]), "+f"(d[27]), "+f"(d[28]), "+f"(d[29]), "+f"(d[30]), "+f"(d[31]), "+f"(d[32]), "+f"(d[33]), "+f"(d[34]), "+f"(d[35]), "+f"(d[36]), "+f"(d[37]), "+f"(d[38]), "+f"(d[39])
    : "l"(da), "l"(db), "r"(acc), "n"(TA), "n"(TB));
}

template <int TA, int TB> __device__ __forceinline__ void wgmma_n128(float (&d)[64], uint64_t da, uint64_t db, int acc) {
  asm volatile("{\n.reg .pred p;\nsetp.ne.b32 p, %66, 0;\n"
    "wgmma.mma_async.sync.aligned.m64n128k16.f32.bf16.bf16 {%0, %1, %2, %3, %4, %5, %6, %7, %8, %9, %10, %11, %12, %13, %14, %15, %16, %17, %18, %19, %20, %21, %22, %23, %24, %25, %26, %27, %28, %29, %30, %31, %32, %33, %34, %35, %36, %37, %38, %39, %40, %41, %42, %43, %44, %45, %46, %47, %48, %49, %50, %51, %52, %53, %54, %55, %56, %57, %58, %59, %60, %61, %62, %63}, %64, %65, p, 1, 1, %67, %68;\n}\n"
    : "+f"(d[0]), "+f"(d[1]), "+f"(d[2]), "+f"(d[3]), "+f"(d[4]), "+f"(d[5]), "+f"(d[6]), "+f"(d[7]), "+f"(d[8]), "+f"(d[9]), "+f"(d[10]), "+f"(d[11]), "+f"(d[12]), "+f"(d[13]), "+f"(d[14]), "+f"(d[15]), "+f"(d[16]), "+f"(d[17]), "+f"(d[18]), "+f"(d[19]), "+f"(d[20]), "+f"(d[21]), "+f"(d[22]), "+f"(d[23]), "+f"(d[24]), "+f"(d[25]), "+f"(d[26]), "+f"(d[27]), "+f"(d[28]), "+f"(d[29]), "+f"(d[30]), "+f"(d[31]), "+f"(d[32]), "+f"(d[33]), "+f"(d[34]), "+f"(d[35]), "+f"(d[36]), "+f"(d[37]), "+f"(d[38]), "+f"(d[39]), "+f"(d[40]), "+f"(d[41]), "+f"(d[42]), "+f"(d[43]), "+f"(d[44]), "+f"(d[45]), "+f"(d[46]), "+f"(d[47]), "+f"(d[48]), "+f"(d[49]), "+f"(d[50]), "+f"(d[51]), "+f"(d[52]), "+f"(d[53]), "+f"(d[54]), "+f"(d[55]), "+f"(d[56]), "+f"(d[57]), "+f"(d[58]), "+f"(d[59]), "+f"(d[60]), "+f"(d[61]), "+f"(d[62]), "+f"(d[63])
    : "l"(da), "l"(db), "r"(acc), "n"(TA), "n"(TB));
}

template <int TA, int TB> __device__ __forceinline__ void wgmma_n192(float (&d)[96], uint64_t da, uint64_t db, int acc) {
  asm volatile("{\n.reg .pred p;\nsetp.ne.b32 p, %98, 0;\n"
    "wgmma.mma_async.sync.aligned.m64n192k16.f32.bf16.bf16 {%0, %1, %2, %3, %4, %5, %6, %7, %8, %9, %10, %11, %12, %13, %14, %15, %16, %17, %18, %19, %20, %21, %22, %23, %24, %25, %26, %27, %28, %29, %30, %31, %32, %33, %34, %35, %36, %37, %38, %39, %40, %41, %42, %43, %44, %45, %46, %47, %48, %49, %50, %51, %52, %53, %54, %55, %56, %57, %58, %59, %60, %61, %62, %63, %64, %65, %66, %67, %68, %69, %70, %71, %72, %73, %74, %75, %76, %77, %78, %79, %80, %81, %82, %83, %84, %85, %86, %87, %88, %89, %90, %91, %92, %93, %94, %95}, %96, %97, p, 1, 1, %99, %100;\n}\n"
    : "+f"(d[0]), "+f"(d[1]), "+f"(d[2]), "+f"(d[3]), "+f"(d[4]), "+f"(d[5]), "+f"(d[6]), "+f"(d[7]), "+f"(d[8]), "+f"(d[9]), "+f"(d[10]), "+f"(d[11]), "+f"(d[12]), "+f"(d[13]), "+f"(d[14]), "+f"(d[15]), "+f"(d[16]), "+f"(d[17]), "+f"(d[18]), "+f"(d[19]), "+f"(d[20]), "+f"(d[21]), "+f"(d[22]), "+f"(d[23]), "+f"(d[24]), "+f"(d[25]), "+f"(d[26]), "+f"(d[27]), "+f"(d[28]), "+f"(d[29]), "+f"(d[30]), "+f"(d[31]), "+f"(d[32]), "+f"(d[33]), "+f"(d[34]), "+f"(d[35]), "+f"(d[36]), "+f"(d[37]), "+f"(d[38]), "+f"(d[39]), "+f"(d[40]), "+f"(d[41]), "+f"(d[42]), "+f"(d[43]), "+f"(d[44]), "+f"(d[45]), "+f"(d[46]), "+f"(d[47]), "+f"(d[48]), "+f"(d[49]), "+f"(d[50]), "+f"(d[51]), "+f"(d[52]), "+f"(d[53]), "+f"(d[54]), "+f"(d[55]), "+f"(d[56]), "+f"(d[57]), "+f"(d[58]), "+f"(d[59]), "+f"(d[60]), "+f"(d[61]), "+f"(d[62]), "+f"(d[63]), "+f"(d[64]), "+f"(d[65]), "+f"(d[66]), "+f"(d[67]), "+f"(d[68]), "+f"(d[69]), "+f"(d[70]), "+f"(d[71]), "+f"(d[72]), "+f"(d[73]), "+f"(d[74]), "+f"(d[75]), "+f"(d[76]), "+f"(d[77]), "+f"(d[78]), "+f"(d[79]), "+f"(d[80]), "+f"(d[81]), "+f"(d[82]), "+f"(d[83]), "+f"(d[84]), "+f"(d[85]), "+f"(d[86]), "+f"(d[87]), "+f"(d[88]), "+f"(d[89]), "+f"(d[90]), "+f"(d[91]), "+f"(d[92]), "+f"(d[93]), "+f"(d[94]), "+f"(d[95])
    : "l"(da), "l"(db), "r"(acc), "n"(TA), "n"(TB));
}

template <int TA, int TB> __device__ __forceinline__ void wgmma_n256(float (&d)[128], uint64_t da, uint64_t db, int acc) {
  asm volatile("{\n.reg .pred p;\nsetp.ne.b32 p, %130, 0;\n"
    "wgmma.mma_async.sync.aligned.m64n256k16.f32.bf16.bf16 {%0, %1, %2, %3, %4, %5, %6, %7, %8, %9, %10, %11, %12, %13, %14, %15, %16, %17, %18, %19, %20, %21, %22, %23, %24, %25, %26, %27, %28, %29, %30, %31, %32, %33, %34, %35, %36, %37, %38, %39, %40, %41, %42, %43, %44, %45, %46, %47, %48, %49, %50, %51, %52, %53, %54, %55, %56, %57, %58, %59, %60, %61, %62, %63, %64, %65, %66, %67, %68, %69, %70, %71, %72, %73, %74, %75, %76, %77, %78, %79, %80, %81, %82, %83, %84, %85, %86, %87, %88, %89, %90, %91, %92, %93, %94, %95, %96, %97, %98, %99, %100, %101, %102, %103, %104, %105, %106, %107, %108, %109, %110, %111, %112, %113, %114, %115, %116, %117, %118, %119, %120, %121, %122, %123, %124, %125, %126, %127}, %128, %129, p, 1, 1, %131, %132;\n}\n"
    : "+f"(d[0]), "+f"(d[1]), "+f"(d[2]), "+f"(d[3]), "+f"(d[4]), "+f"(d[5]), "+f"(d[6]), "+f"(d[7]), "+f"(d[8]), "+f"(d[9]), "+f"(d[10]), "+f"(d[11]), "+f"(d[12]), "+f"(d[13]), "+f"(d[14]), "+f"(d[15]), "+f"(d[16]), "+f"(d[17]), "+f"(d[18]), "+f"(d[19]), "+f"(d[20]), "+f"(d[21]), "+f"(d[22]), "+f"(d[23]), "+f"(d[24]), "+f"(d[25]), "+f"(d[26]), "+f"(d[27]), "+f"(d[28]), "+f"(d[29]), "+f"(d[30]), "+f"(d[31]), "+f"(d[32]), "+f"(d[33]), "+f"(d[34]), "+f"(d[35]), "+f"(d[36]), "+f"(d[37]), "+f"(d[38]), "+f"(d[39]), "+f"(d[40]), "+f"(d[41]), "+f"(d[42]), "+f"(d[43]), "+f"(d[44]), "+f"(d[45]), "+f"(d[46]), "+f"(d[47]), "+f"(d[48]), "+f"(d[49]), "+f"(d[50]), "+f"(d[51]), "+f"(d[52]), "+f"(d[53]), "+f"(d[54]), "+f"(d[55]), "+f"(d[56]), "+f"(d[57]), "+f"(d[58]), "+f"(d[59]), "+f"(d[60]), "+f"(d[61]), "+f"(d[62]), "+f"(d[63]), "+f"(d[64]), "+f"(d[65]), "+f"(d[66]), "+f"(d[67]), "+f"(d[68]), "+f"(d[69]), "+f"(d[70]), "+f"(d[71]), "+f"(d[72]), "+f"(d[73]), "+f"(d[74]), "+f"(d[75]), "+f"(d[76]), "+f"(d[77]), "+f"(d[78]), "+f"(d[79]), "+f"(d[80]), "+f"(d[81]), "+f"(d[82]), "+f"(d[83]), "+f"(d[84]), "+f"(d[85]), "+f"(d[86]), "+f"(d[87]), "+f"(d[88]), "+f"(d[89]), "+f"(d[90]), "+f"(d[91]), "+f"(d[92]), "+f"(d[93]), "+f"(d[94]), "+f"(d[95]), "+f"(d[96]), "+f"(d[97]), "+f"(d[98]), "+f"(d[99]), "+f"(d[100]), "+f"(d[101]), "+f"(d[102]), "+f"(d[103]), "+f"(d[104]), "+f"(d[105]), "+f"(d[106]), "+f"(d[107]), "+f"(d[108]), "+f"(d[109]), "+f"(d[110]), "+f"(d[111]), "+f"(d[112]), "+f"(d[113]), "+f"(d[114]), "+f"(d[115]), "+f"(d[116]), "+f"(d[117]), "+f"(d[118]), "+f"(d[119]), "+f"(d[120]), "+f"(d[121]), "+f"(d[122]), "+f"(d[123]), "+f"(d[124]), "+f"(d[125]), "+f"(d[126]), "+f"(d[127])
    : "l"(da), "l"(db), "r"(acc), "n"(TA), "n"(TB));
}

template <int TB> __device__ __forceinline__ void wgmma_rs_n24(float (&d)[12], uint32_t a0, uint32_t a1, uint32_t a2, uint32_t a3, uint64_t db, int acc) {
  asm volatile("{\n.reg .pred p;\nsetp.ne.b32 p, %17, 0;\n"
    "wgmma.mma_async.sync.aligned.m64n24k16.f32.bf16.bf16 {%0, %1, %2, %3, %4, %5, %6, %7, %8, %9, %10, %11}, {%12, %13, %14, %15}, %16, p, 1, 1, %18;\n}\n"
    : "+f"(d[0]), "+f"(d[1]), "+f"(d[2]), "+f"(d[3]), "+f"(d[4]), "+f"(d[5]), "+f"(d[6]), "+f"(d[7]), "+f"(d[8]), "+f"(d[9]), "+f"(d[10]), "+f"(d[11])
    : "r"(a0), "r"(a1), "r"(a2), "r"(a3), "l"(db), "r"(acc), "n"(TB));
}

template <int TB> __device__ __forceinline__ void wgmma_rs_n40(float (&d)[20], uint32_t a0, uint32_t a1, uint32_t a2, uint32_t a3, uint64_t db, int acc) {
  asm volatile("{\n.reg .pred p;\nsetp.ne.b32 p, %25, 0;\n"
    "wgmma.mma_async.sync.aligned.m64n40k16.f32.bf16.bf16 {%0, %1, %2, %3, %4, %5, %6, %7, %8, %9, %10, %11, %12, %13, %14, %15, %16, %17, %18, %19}, {%20, %21, %22, %23}, %24, p, 1, 1, %26;\n}\n"
    : "+f"(d[0]), "+f"(d[1]), "+f"(d[2]), "+f"(d[3]), "+f"(d[4]), "+f"(d[5]), "+f"(d[6]), "+f"(d[7]), "+f"(d[8]), "+f"(d[9]), "+f"(d[10]), "+f"(d[11]), "+f"(d[12]), "+f"(d[13]), "+f"(d[14]), "+f"(d[15]), "+f"(d[16]), "+f"(d[17]), "+f"(d[18]), "+f"(d[19])
    : "r"(a0), "r"(a1), "r"(a2), "r"(a3), "l"(db), "r"(acc), "n"(TB));
}

template <int TB> __device__ __forceinline__ void wgmma_rs_n192(float (&d)[96], uint32_t a0, uint32_t a1, uint32_t a2, uint32_t a3, uint64_t db, int acc) {
  asm volatile("{\n.reg .pred p;\nsetp.ne.b32 p, %101, 0;\n"
    "wgmma.mma_async.sync.aligned.m64n192k16.f32.bf16.bf16 {%0, %1, %2, %3, %4, %5, %6, %7, %8, %9, %10, %11, %12, %13, %14, %15, %16, %17, %18, %19, %20, %21, %22, %23, %24, %25, %26, %27, %28, %29, %30, %31, %32, %33, %34, %35, %36, %37, %38, %39, %40, %41, %42, %43, %44, %45, %46, %47, %48, %49, %50, %51, %52, %53, %54, %55, %56, %57, %58, %59, %60, %61, %62, %63, %64, %65, %66, %67, %68, %69, %70, %71, %72, %73, %74, %75, %76, %77, %78, %79, %80, %81, %82, %83, %84, %85, %86, %87, %88, %89, %90, %91, %92, %93, %94, %95}, {%96, %97, %98, %99}, %100, p, 1, 1, %102;\n}\n"
    : "+f"(d[0]), "+f"(d[1]), "+f"(d[2]), "+f"(d[3]), "+f"(d[4]), "+f"(d[5]), "+f"(d[6]), "+f"(d[7]), "+f"(d[8]), "+f"(d[9]), "+f"(d[10]), "+f"(d[11]), "+f"(d[12]), "+f"(d[13]), "+f"(d[14]), "+f"(d[15]), "+f"(d[16]), "+f"(d[17]), "+f"(d[18]), "+f"(d[19]), "+f"(d[20]), "+f"(d[21]), "+f"(d[22]), "+f"(d[23]), "+f"(d[24]), "+f"(d[25]), "+f"(d[26]), "+f"(d[27]), "+f"(d[28]), "+f"(d[29]), "+f"(d[30]), "+f"(d[31]), "+f"(d[32]), "+f"(d[33]), "+f"(d[34]), "+f"(d[35]), "+f"(d[36]), "+f"(d[37]), "+f"(d[38]), "+f"(d[39]), "+f"(d[40]), "+f"(d[41]), "+f"(d[42]), "+f"(d[43]), "+f"(d[44]), "+f"(d[45]), "+f"(d[46]), "+f"(d[47]), "+f"(d[48]), "+f"(d[49]), "+f"(d[50]), "+f"(d[51]), "+f"(d[52]), "+f"(d[53]), "+f"(d[54]), "+f"(d[55]), "+f"(d[56]), "+f"(d[57]), "+f"(d[58]), "+f"(d[59]), "+f"(d[60]), "+f"(d[61]), "+f"(d[62]), "+f"(d[63]), "+f"(d[64]), "+f"(d[65]), "+f"(d[66]), "+f"(d[67]), "+f"(d[68]), "+f"(d[69]), "+f"(d[70]), "+f"(d[71]), "+f"(d[72]), "+f"(d[73]), "+f"(d[74]), "+f"(d[75]), "+f"(d[76]), "+f"(d[77]), "+f"(d[78]), "+f"(d[79]), "+f"(d[80]), "+f"(d[81]), "+f"(d[82]), "+f"(d[83]), "+f"(d[84]), "+f"(d[85]), "+f"(d[86]), "+f"(d[87]), "+f"(d[88]), "+f"(d[89]), "+f"(d[90]), "+f"(d[91]), "+f"(d[92]), "+f"(d[93]), "+f"(d[94]), "+f"(d[95])
    : "r"(a0), "r"(a1), "r"(a2), "r"(a3), "l"(db), "r"(acc), "n"(TB));
}
constexpr uint32_t AR_ACC = 0;
constexpr uint32_t AR_TAB = 0x100000;
constexpr uint32_t AR_PROG = 0x101000;
__host__ __device__ constexpr uint32_t prog_off(int h, int j) { return AR_PROG + h * 128 + j * 4; }
constexpr uint32_t AR_CNT = 0x108000;
constexpr uint32_t AR_QUEUE = 0x109000;
constexpr uint32_t AR_SIZE = 0x10a000;

struct ChainArgs {
  const bf16* mem0;
  const uint2* xh;
  unsigned char *kg, *vg;
  unsigned char* arena;
  unsigned* go;
  uint32_t* dbg;
  uint32_t delay;
  int margin, pubrel, dry;
  int tl;
};

namespace ch {
constexpr int OFF_WQ = 0;
constexpr int OFF_X = 81920;
constexpr int OFF_MEM = OFF_X + 40960;
constexpr int OFF_WO = OFF_MEM + 10240;
constexpr int WOK = 8 * 896;
constexpr int OFF_KV = OFF_WO + 10 * WOK;
constexpr int KVB = 5120;
constexpr int OFF_O = OFF_KV + 4 * KVB;
constexpr int OFF_Q = OFF_O + 1024;
constexpr int OFF_S = OFF_O + 3072;
constexpr int OFF_SR = OFF_S + 1536;
constexpr int OFF_LT = OFF_SR + 1280;
constexpr int OFF_BAR = OFF_LT + 512;
constexpr int SMEM = OFF_BAR + 256;
static_assert(SMEM <= 232448, "smem");
constexpr int MB_S = OFF_BAR, MB_O = OFF_BAR + 8, MB_X = OFF_BAR + 16;
constexpr int MB_K = OFF_BAR + 128, MB_V = MB_K + 16, MB_Q = MB_K + 32, MB_R = MB_K + 48;
constexpr int SC_IN = OFF_BAR + 64;
constexpr int SC_MX = OFF_S;
constexpr int SC_TW = OFF_BAR + 48;
constexpr int SC_W = OFF_BAR + 96;
constexpr int WOS = 448;
enum { B_MEM0 = 1, B_QK, B_SL, B_V, B_O, B_RED, B_X, B_C, B_H, B_MEM1, B_A, B_G, B_E };
#ifndef NQ1
#define NQ1 14
#endif
#ifndef NQ0
#define NQ0 8
#endif
#ifndef NP0
#define NP0 5
#endif
#ifndef NWO
#define NWO 5
#endif
#ifndef NWP
#define NWP 4
#endif
#ifndef NB0
#define NB0 2
#endif
#ifndef BBS
#define BBS 100
#endif
#ifndef VSYNC
#define VSYNC 0
#endif
#ifndef XPOS
#define XPOS 0
#endif
#ifndef XPD
#define XPD 300
#endif
#ifndef WOF
#define WOF 0
#endif
#ifndef XBYTES
#define XBYTES 36864
#endif
#ifndef NRT
#define NRT 7
#endif
#ifndef NRF
#define NRF 2
#endif
#ifndef NPM0
#define NPM0 2
#endif
#ifndef NPM1
#define NPM1 2
#endif
#ifndef RSYNC
#define RSYNC 1
#endif
#ifndef PFK
#define PFK 1
#endif
#ifndef PA0
#define PA0 3
#endif
#ifndef PA1
#define PA1 0
#endif
#ifndef PB0
#define PB0 7
#endif
#ifndef PB1
#define PB1 5
#endif
#ifndef PQE
#define PQE 1
#endif
#ifndef XT
#define XT 38
#endif
static_assert(NPM0 >= 2 && NPM1 >= 2, "the K / V blocks live in the last two k-steps of Wo");
}

#ifndef CHAIN_TIMING
#define CHAIN_TIMING 0
#endif
#if CHAIN_TIMING
#ifndef TR0
#define TR0 41
#endif
#ifndef TSMASK
#define TSMASK 0xffff
#endif
#define TSV(i, v) do { if ((TSMASK >> (i)) & 1) asm volatile("st.shared.u32 [%0+%1], %2;" :: "r"(tsb), "n"((i) * 4), "r"(v) : "memory"); } while (0)
#define TS(i) TSV(i, clk32())
#define TS_SETUP() const uint32_t tsb = sb + ((s == TR0 || s == TR0 + 1) ? OFF_BAR + 128 + ((s - TR0) * 12 + warp) * 48 : OFF_SR + 1152)
#else
#define TS(i)
#define TSV(i, v)
#define TS_SETUP()
#endif
#ifndef POLL_DELAY
#define POLL_DELAY 620
#endif
#ifndef XN
#define XN 40
#endif
#ifndef PF0
#define PF0 8
#endif
#ifndef PFS
#define PFS 3
#endif
#ifndef XDELAY
#define XDELAY 0
#endif
#ifndef NOKM
#define NOKM 0
#endif
#ifndef PFX
#define PFX 3
#endif
#ifndef NVE
#define NVE 8
#endif
#ifndef VET
#define VET 19
#endif
#ifndef MEMFIRST
#define MEMFIRST 0
#endif
#ifndef PM1
#define PM1 1
#endif
#ifndef GD1
#define GD1 30
#endif
#ifndef GD2
#define GD2 150
#endif
#ifndef CEARLY
#define CEARLY 0
#endif
#ifndef NPL
#define NPL 2
#endif
#ifndef NP1
#define NP1 (NQ1 < 6 ? NQ1 : 6)
#endif
#ifndef PF2
#define PF2 0
#endif
#ifndef PFACC
#define PFACC 1
#endif
template <int V> using IC = std::integral_constant<int, V>;
__device__ __forceinline__ uint32_t clk_v() { uint64_t c; asm volatile("mov.u64 %0, %%clock64;" : "=l"(c) :: "memory"); return (uint32_t)c; }
__device__ __forceinline__ int fresh(int x) { int y; asm volatile("shfl.sync.bfly.b32 %0, %1, 0, 0x1f, 0xffffffff;" : "=r"(y) : "r"(x)); return y; }
#define SFENCE2(x, d) asm volatile("{\n.reg .pred p;\nsetp.eq.u32 p, %0, 0x7fffffff;\n@p st.shared.u32 [%0], %1;\n}" :: "r"(x), "r"(d) : "memory")
#define SFENCE(x) asm volatile("{\n.reg .pred p;\nsetp.eq.u32 p, %0, 0x7fffffff;\n@p st.shared.u32 [%0], %0;\n}" :: "r"(x) : "memory")
template <int I> __device__ __forceinline__ void bbfence(uint32_t x) {
  asm volatile("{\n.reg .pred p;\nsetp.eq.u32 p, %0, %1;\nL_%=:\n@p st.volatile.shared.u32 [%0], %0;\n@p bra.uni L_%=;\n}" :: "r"(x), "n"(4 * I) : "memory");
}
__device__ __forceinline__ float uniform_f(float x) { return __uint_as_float(__reduce_max_sync(0xffffffffu, __float_as_uint(x))); }

__device__ __forceinline__ void mma16816h(float (&d)[4], const uint32_t (&a)[4], uint32_t b0, uint32_t b1) {
  asm volatile("mma.sync.aligned.m16n8k16.row.col.f32.f16.f16.f32 {%0,%1,%2,%3}, {%4,%5,%6,%7}, {%8,%9}, {%0,%1,%2,%3};"
               : "+f"(d[0]), "+f"(d[1]), "+f"(d[2]), "+f"(d[3]) : "r"(a[0]), "r"(a[1]), "r"(a[2]), "r"(a[3]), "r"(b0), "r"(b1));
}
__device__ __forceinline__ void mma1688(float (&d)[4], uint32_t a0, uint32_t a1, uint32_t b0) {
  asm volatile("mma.sync.aligned.m16n8k8.row.col.f32.bf16.bf16.f32 {%0,%1,%2,%3}, {%4,%5}, {%6}, {%0,%1,%2,%3};"
               : "+f"(d[0]), "+f"(d[1]), "+f"(d[2]), "+f"(d[3]) : "r"(a0), "r"(a1), "r"(b0));
}
template <int OFF16, int ACC> __device__ __forceinline__ void wgmma_rs32h(float (&d)[16], const uint32_t (&a)[4], uint32_t dlo) {
  asm volatile("{\n.reg .pred p;\n.reg .b32 t;\n.reg .b64 db;\nsetp.ne.b32 p, %22, 0;\nadd.u32 t, %20, %21;\nmov.b64 db, {t, 0x40000040};\n"
    "wgmma.mma_async.sync.aligned.m64n32k16.f32.f16.f16 {%0,%1,%2,%3,%4,%5,%6,%7,%8,%9,%10,%11,%12,%13,%14,%15}, {%16,%17,%18,%19}, db, p, 1, 1, 0;\n}\n"
    : "+f"(d[0]), "+f"(d[1]), "+f"(d[2]), "+f"(d[3]), "+f"(d[4]), "+f"(d[5]), "+f"(d[6]), "+f"(d[7]), "+f"(d[8]), "+f"(d[9]), "+f"(d[10]), "+f"(d[11]),
      "+f"(d[12]), "+f"(d[13]), "+f"(d[14]), "+f"(d[15])
    : "r"(a[0]), "r"(a[1]), "r"(a[2]), "r"(a[3]), "r"(dlo), "n"(OFF16), "n"(ACC));
}
template <int IMM> __device__ __forceinline__ void stsm_x4_t_i(uint32_t a, uint32_t r0, uint32_t r1, uint32_t r2, uint32_t r3) {
  asm volatile("stmatrix.sync.aligned.m8n8.x4.trans.shared.b16 [%0+%5], {%1,%2,%3,%4};" :: "r"(a), "r"(r0), "r"(r1), "r"(r2), "r"(r3), "n"(IMM) : "memory");
}
template <int IMM> __device__ __forceinline__ void stsm_x2_t_i(uint32_t a, uint32_t r0, uint32_t r1) {
  asm volatile("stmatrix.sync.aligned.m8n8.x2.trans.shared.b16 [%0+%3], {%1,%2};" :: "r"(a), "r"(r0), "r"(r1), "n"(IMM) : "memory");
}
template <int IMM> __device__ __forceinline__ void st_async_b32_i(uint32_t a, uint32_t x, uint32_t mb) {
  asm volatile("st.async.weak.shared::cluster.mbarrier::complete_tx::bytes.b32 [%0+%3], %1, [%2];" :: "r"(a), "r"(x), "r"(mb), "n"(IMM) : "memory");
}
template <int IMM> __device__ __forceinline__ void ld_relaxed_v4_if(uint4& v, const void* p, uint32_t c) {
  asm volatile("{\n.reg .pred p;\nsetp.ne.u32 p, %6, 0;\n@p ld.relaxed.gpu.global.v4.u32 {%0,%1,%2,%3}, [%4+%5];\n}"
               : "+r"(v.x), "+r"(v.y), "+r"(v.z), "+r"(v.w) : "l"(p), "n"(IMM), "r"(c) : "memory");
}
template <int IMM> __device__ __forceinline__ void ldsm_x2_i(uint32_t (&r)[2], uint32_t a) {
  asm volatile("ldmatrix.sync.aligned.m8n8.x2.shared.b16 {%0,%1}, [%2+%3];" : "=r"(r[0]), "=r"(r[1]) : "r"(a), "n"(IMM) : "memory");
}
template <int IMM> __device__ __forceinline__ uint32_t ldsm_x1_t_i(uint32_t a) {
  uint32_t r; asm volatile("ldmatrix.sync.aligned.m8n8.x1.trans.shared.b16 {%0}, [%1+%2];" : "=r"(r) : "r"(a), "n"(IMM) : "memory"); return r;
}
template <int IMM> __device__ __forceinline__ uint32_t lds32_i(uint32_t a) {
  uint32_t v; asm volatile("ld.shared.u32 %0, [%1+%2];" : "=r"(v) : "r"(a), "n"(IMM) : "memory"); return v;
}
__device__ __forceinline__ void sts32(uint32_t a, uint32_t v) { asm volatile("st.shared.u32 [%0], %1;" :: "r"(a), "r"(v) : "memory"); }
__device__ __forceinline__ uint32_t pack_f16(float lo, float hi) {
  uint32_t d; asm("cvt.rn.f16x2.f32 %0, %1, %2;" : "=r"(d) : "f"(hi), "f"(lo)); return d;
}
__device__ __forceinline__ uint32_t amax_bf2(uint32_t a, uint32_t b) { uint32_t d; asm("max.xorsign.abs.bf16x2 %0, %1, %2;" : "=r"(d) : "r"(a), "r"(b)); return d; }
__device__ __forceinline__ uint32_t amax_h2(uint32_t a, uint32_t b) { uint32_t d; asm("max.xorsign.abs.f16x2 %0, %1, %2;" : "=r"(d) : "r"(a), "r"(b)); return d; }
__device__ __forceinline__ uint32_t amax_fold(uint32_t m) { return __reduce_max_sync(0xffffffffu, max(m & 0x7fffu, (m >> 16) & 0x7fffu)); }
__device__ __forceinline__ int wscale_exp(uint32_t m) { return min(141 - (int)(m >> 7), 100); }
__device__ __forceinline__ float exp2i(int e) { return __uint_as_float((uint32_t)(e + 127) << 23); }
__device__ __forceinline__ uint32_t bf2_to_h2(uint32_t w, float sc) { return pack_f16(bf_lo(w) * sc, bf_hi(w) * sc); }
__device__ __forceinline__ void bf2_to_h2_inplace(uint32_t& w, uint32_t sc2) {
  asm volatile("{\n.reg .b32 t, lo, hi;\nmul.rn.bf16x2 t, %0, %1;\nshl.b32 lo, t, 16;\nand.b32 hi, t, 0xffff0000;\ncvt.rn.f16x2.f32 %0, hi, lo;\n}" : "+r"(w) : "r"(sc2));
}
__device__ __forceinline__ void prefetch_l2(const void* p, uint32_t bytes) { asm volatile("cp.async.bulk.prefetch.L2.global [%0], %1;" :: "l"(p), "r"(bytes) : "memory"); }
__device__ __forceinline__ void prefetch_tma_2d(const CUtensorMap* tm, int c0, int c1) {
  asm volatile("cp.async.bulk.prefetch.tensor.2d.L2.global [%0, {%1, %2}];" :: "l"(tm), "r"(c0), "r"(c1) : "memory");
}
__host__ __device__ constexpr uint32_t acc_voff(int v) { return v < 4 ? v * 1024u : (v == 4 ? 128u : 3072u + 128u); }
__device__ __forceinline__ int unit28(int i) { return i == 3 ? 54 : 14 * i; }
__device__ __forceinline__ int unit24(int i) { return i < 2 ? 48 - 6 * i : 56 + 6 * i; }
__device__ __forceinline__ uint32_t acc_step(int s) { return (s >> 1) * 32768 + (s & 1) * 512; }
__device__ __forceinline__ uint32_t acc_lane(int i, int lane) { return ((lane >> 3) & 1) * 256 + (lane >> 4) * 4096 + i * 8192 + (lane & 7) * 16; }

__device__ __forceinline__ uint32_t ld_acquire_u32(const void* p) {
  uint32_t v; asm volatile("ld.acquire.gpu.global.u32 %0, [%1];" : "=r"(v) : "l"(p) : "memory"); return v;
}
template <int R> __device__ __forceinline__ void ln_rows(const uint2 (&xw)[R][5], int row0, int lane, bf16* __restrict__ xn, uint2* __restrict__ xh) {
  float v[R][20], s[R], q[R];
#pragma unroll
  for (int r = 0; r < R; r++) {
    s[r] = 0.f; q[r] = 0.f;
#pragma unroll
    for (int i = 0; i < 5; i++) { v[r][4 * i] = bf_lo(xw[r][i].x); v[r][4 * i + 1] = bf_hi(xw[r][i].x); v[r][4 * i + 2] = bf_lo(xw[r][i].y); v[r][4 * i + 3] = bf_hi(xw[r][i].y); }
#pragma unroll
    for (int i = 0; i < 5; i++) s[r] += (v[r][4 * i] + v[r][4 * i + 1]) + (v[r][4 * i + 2] + v[r][4 * i + 3]);
  }
#pragma unroll
  for (int o = 16; o; o >>= 1)
#pragma unroll
    for (int r = 0; r < R; r++) s[r] += __shfl_xor_sync(0xffffffffu, s[r], o);
#pragma unroll
  for (int r = 0; r < R; r++) {
    s[r] *= 1.f / cfg::DM;
#pragma unroll
    for (int i = 0; i < 10; i++) { const float d = v[r][2 * i] - s[r], e = v[r][2 * i + 1] - s[r]; q[r] += d * d + e * e; }
  }
#pragma unroll
  for (int o = 16; o; o >>= 1)
#pragma unroll
    for (int r = 0; r < R; r++) q[r] += __shfl_xor_sync(0xffffffffu, q[r], o);
#pragma unroll
  for (int r = 0; r < R; r++) {
    const int row = row0 + r;
    const float mb = bf16r(s[r]), var = bf16r(q[r] * (1.f / cfg::DM));
    float sd; asm("sqrt.approx.f32 %0, %1;" : "=f"(sd) : "f"(bf16r(var + 1e-5f)));
    const float inv = rcpf(bf16r(sd));
#pragma unroll
    for (int i = 0; i < 5; i++) {
      float y[4];
#pragma unroll
      for (int e = 0; e < 4; e++) y[e] = v[r][4 * i + e] - mb;
      bf16r2(y[0], y[1]); bf16r2(y[2], y[3]);
      const uint32_t w0 = pack_bf16(y[0] * inv, y[1] * inv), w1 = pack_bf16(y[2] * inv, y[3] * inv);
      *(uint2*)(xn + (size_t)row * cfg::DM + i * 128 + lane * 4) = make_uint2(w0, w1);
      if (xh) xh[(((size_t)(row >> 5) * 10 + 2 * i + (lane >> 4)) * 32 + (row & 31)) * 16 + ((((lane >> 1) & 7) ^ (row & 7)) << 1) + (lane & 1)] =
          make_uint2(pack_f16(bf_lo(w0), bf_hi(w0)), pack_f16(bf_lo(w1), bf_hi(w1)));
    }
  }
}

__global__ void __cluster_dims__(3, 1, 1) __launch_bounds__(384, 1) chain_kernel(const ChainArgs a, const __grid_constant__ CUtensorMap tmWq,
    const __grid_constant__ CUtensorMap tmWk, const __grid_constant__ CUtensorMap tmWv, const __grid_constant__ CUtensorMap tmWo) {
  using namespace ch;
  extern __shared__ __align__(1024) unsigned char smem_raw[];
  const uint32_t sb = smem_u32(smem_raw);
  const int warp = __shfl_sync(0xffffffffu, (int)threadIdx.x >> 5, 0);
  const int cta = blockIdx.x, h = cta / 3, j = cta % 3;
  unsigned char* const arena = a.arena;
  if (sb & 1023u) __trap();
  asm volatile("griddepcontrol.launch_dependents;");
  TL_BEGIN(a.tl);
#ifdef TIMELINE
  const unsigned long long g_tl0 = gtime();
#define PT(i) TLW((a.tl >= 12) * 128 + 64 + (i))
#else
#define PT(i)
#endif
  const int col0 = j == 0 ? 0 : (j == 1 ? 224 : 432);
  auto stage_w = [&](const CUtensorMap* tm, uint32_t dst, uint32_t mb, int half) {
    mbar_expect_tx(mb + 8 * half, 40960);
    tma_load_2d(dst + half * 40960, tm, h * cfg::DH + j * 64, half * 320, mb + 8 * half);
    tma_load_2d(dst + half * 40960 + 20480, tm, h * cfg::DH + j * 64, half * 320 + 160, mb + 8 * half);
  };
  if (threadIdx.x == 256) {
    for (int i = 0; i < 9; i++) mbar_init(sb + MB_K + 8 * i, 1);
    mbar_init(sb + MB_S, 1); mbar_init(sb + MB_O, 1); mbar_init(sb + MB_X, 1);
    asm volatile("fence.mbarrier_init.release.cluster;" ::: "memory");
    for (int i = 0; i < 2; i++) { stage_w(&tmWk, sb + OFF_WQ, sb + MB_K, i); stage_w(&tmWv, sb + OFF_WO, sb + MB_V, i); }
    sts32(sb + SC_W, 0); sts32(sb + SC_W + 4, 0); sts32(sb + SC_W + 8, 0); sts32(sb + SC_IN + 12, 0); sts32(sb + SC_IN + 20, 0); sts32(sb + SC_TW + 4, 99);
    mbar_expect_tx(sb + MB_S, 1280); mbar_expect_tx(sb + MB_O, 2048);
  }
  __syncthreads();
  asm volatile("barrier.cluster.arrive.relaxed.aligned;" ::: "memory");
  const uint32_t d1 = mapa_u32(sb, (j + 1) % 3) - sb, d2 = mapa_u32(sb, (j + 2) % 3) - sb;

  if (warp >= 8) {
    asm volatile("setmaxnreg.dec.sync.aligned.u32 40;");
    const int lane = fresh(threadIdx.x & 31), hw = warp - 8, ht = hw * 32 + lane;
    const bool lead = ht == 0;
    auto stage_wo = [&](int i) {
      mbar_expect_tx(sb + MB_R + 8 * i, 64 * WOS);
      tma_load_2d(sb + OFF_WO + i * 64 * WOS, &tmWo, col0, h * cfg::DH + ((i + j) % 3) * 64, sb + MB_R + 8 * i);
    };
    const unsigned char* xg = (const unsigned char*)a.xh;
    auto issue_x = [&](int s) { mbar_expect_tx(sb + MB_X, 40960); bulk_g2s(sb + OFF_X, xg + (size_t)s * 40960, 40960, sb + MB_X); };
    uint4 v[5];
#pragma unroll
    for (int i = 0; i < 5; i++) { const int c = ht + 128 * i; v[i] = ld_relaxed_v4(a.mem0 + (c & 7) * cfg::DM + (c >> 3) * 8); }
    if (hw == 2) {
      asm volatile("griddepcontrol.wait;" ::: "memory");
      if (lane == 0) { if (cta == 0) st_relaxed_u32(a.go, 1); issue_x(0); }
      PT(0);
    }
    if (hw == 0) {
      bar_sync(B_QK, 160);
      if (lane == 0) {
        stage_w(&tmWq, sb + OFF_WQ, sb + MB_Q, 0);
        if (PF2) { prefetch_tma_2d(&tmWq, h * cfg::DH + j * 64, 320); prefetch_tma_2d(&tmWq, h * cfg::DH + j * 64, 480); }
      }
      bar_sync(B_SL, 160); if (lane == 0) stage_w(&tmWq, sb + OFF_WQ, sb + MB_Q, 1);
    }
    if (hw == 1) {
      bar_sync(B_V, 160);
      if (lane == 0) {
        stage_wo(0);
        if (PF2) { prefetch_tma_2d(&tmWo, col0, h * cfg::DH + ((1 + j) % 3) * 64); prefetch_tma_2d(&tmWo, col0, h * cfg::DH + ((2 + j) % 3) * 64); }
      }
      bar_sync(B_O, 160); if (lane == 0) { stage_wo(1); stage_wo(2); }
    }
    __syncwarp();
    {
      uint32_t m = 0;
#pragma unroll
      for (int i = 0; i < 5; i++) {
        m = amax_bf2(amax_bf2(m, amax_bf2(v[i].x, v[i].y)), amax_bf2(v[i].z, v[i].w));
      }
      m = amax_fold(m);
      if (lane == 0) sts32(sb + SC_MX + hw * 4, m);
      bar_sync(B_H, 128);
      const uint4 mm = lds128(sb + SC_MX);
      const int se = max(wscale_exp(max(max(mm.x, mm.y), max(mm.z, mm.w))), -100);
      const float sc = exp2i(se);
#pragma unroll
      for (int i = 0; i < 5; i++) {
        const int c = ht + 128 * i, t = c & 7, chn = c >> 3;
        sts128(sb + OFF_MEM + chn * 128 + ((t ^ (2 * (chn & 3))) << 4), bf2_to_h2(v[i].x, sc), bf2_to_h2(v[i].y, sc), bf2_to_h2(v[i].z, sc), bf2_to_h2(v[i].w, sc));
      }
      if (lead) { sts32(sb + SC_IN, __float_as_uint(exp2i(-se))); sts32(sb + SC_IN + 4, 0x7800u); }
    }
    if (hw == 0) PT(11);
    {
      const uint32_t p0 = sb + OFF_WQ + hw * 2048 + lane * 16;
      uint32_t m = 0;
#pragma unroll 1
      for (int i = 0; i < 10; i++) {
        if (i == 0 || i == 5) mbar_wait(sb + MB_Q + (i ? 8 : 0), 0);
        uint32_t r[4][4];
        static_for<0, 4>([&](auto K) { ldsm_x4_i<K.value * 512>(r[K.value], p0 + i * 8192); });
#pragma unroll
        for (int k = 0; k < 4; k++) m = amax_bf2(amax_bf2(m, amax_bf2(r[k][0], r[k][1])), amax_bf2(r[k][2], r[k][3]));
      }
      if (hw == 0) PT(9);
      m = amax_fold(m);
      if (lane == 0) asm volatile("red.shared.max.u32 [%0], %1;" :: "r"(sb + SC_W + 8), "r"(m) : "memory");
      bar_sync(B_H, 128);
      const uint32_t sc = (uint32_t)(wscale_exp(lds32_i<SC_W + 8>(sb)) + 127) * 0x00800080u;
      uint32_t r[4][4];
      static_for<0, 2>([&](auto K) { ldsm_x4_i<K.value * 512>(r[K.value], p0); });
      auto cvt = [&](uint32_t (&x)[4], uint32_t p) { bf2_to_h2_inplace(x[0], sc); bf2_to_h2_inplace(x[1], sc); bf2_to_h2_inplace(x[2], sc); bf2_to_h2_inplace(x[3], sc); stsm_x4(p, x[0], x[1], x[2], x[3]); };
#pragma unroll 1
      for (int i = 0; i < 10; i++) {
        const uint32_t p = p0 + i * 8192;
        ldsm_x4_i<1024>(r[2], p); ldsm_x4_i<1536>(r[3], p);
        cvt(r[0], p); cvt(r[1], p + 512);
        ldsm_x4_i<8192>(r[0], p); ldsm_x4_i<8192 + 512>(r[1], p);
        cvt(r[2], p + 1024); cvt(r[3], p + 1536);
      }
    }
    if (hw == 0) PT(10);
    bar_sync(0, 384);
    if (hw == 3) {
      const uint32_t eye = ((lane >> 3) == (lane & 3)) ? ((lane & 4) ? 0x3f800000u : 0x3f80u) : 0u;
      sts128(sb + OFF_LT + lane * 16, eye, eye, (lane & 2) * 64 + (lane >> 2) * 16 + (lane & 1) * 8, 0u);
      sts64(sb + OFF_S + 1280 + lane * 8, 0u, 0u);
    }
    if (lead) st_relaxed_u32(arena + AR_TAB + cta * 4, 0x80000000u | (lds32_i<SC_W>(sb) << 15) | lds32_i<SC_W + 4>(sb));
    asm volatile("barrier.cluster.wait.aligned;" ::: "memory");
    bar_sync(B_MEM0, 256); bar_sync(B_MEM1, 256);
    {
      uint32_t v0, v1, v2; int spin = 0;
      do {
        v0 = ld_relaxed_u32(arena + AR_TAB + lane * 4); v1 = ld_relaxed_u32(arena + AR_TAB + 128 + lane * 4); v2 = ld_relaxed_u32(arena + AR_TAB + 256 + lane * 4);
      } while (__any_sync(0xffffffffu, ((v0 & v1 & v2) >> 31) == 0) && ++spin < SPIN_LIMIT);
      const uint32_t mv = (max(max(v0, v1), v2) >> 15) & 0x7fffu, mo = max(max(v0 & 0x7fffu, v1 & 0x7fffu), v2 & 0x7fffu);
      sts32(sb + SC_IN + 8 + (lane & 1) * 16, 15 - ((__reduce_max_sync(0xffffffffu, mv) >> 7) + (__reduce_max_sync(0xffffffffu, mo) >> 7) - 252 + 22));
    }

    auto store_kv = [&](int s) {
      const size_t o = ((size_t)s * 96 + cta) * KVB; const uint32_t src = sb + OFF_KV + (s & 1) * (2 * KVB);
      fence_proxy_async(); bulk_s2g(a.kg + o, src, KVB); bulk_s2g(a.vg + o, src + KVB, KVB); bulk_commit();
    };
    const int cb28 = unit28(hw), du = (unit24(hw) - cb28) * 128;
    uint32_t n16 = lane * 16, hist = 0;
    const uint32_t us1 = sb + d1 + OFF_SR + 256 + (hw >> 1) * 512 + (hw & 1) * 128, us2 = sb + d2 + OFF_SR + (hw >> 1) * 512 + (hw & 1) * 128;
    const uint32_t uo1 = sb + d1 + OFF_O + 2048 + hw * 256, uo2 = sb + d2 + OFF_O + 1024 + hw * 256;
#ifdef STEPCLK
    if (lead) a.dbg[96 * 300 + cta * 2] = clk32();
#endif
#ifdef TIMELINE
    if (cta == 0 && lead) { g_tl2[(a.tl >= 12) * 128 + 0] = clock64(); g_tl2[(a.tl >= 12) * 128 + 1] = gtime(); }
#endif
#pragma unroll 1
    for (int s = 0; s < cfg::NSEG; s++) {
      TS_SETUP();
      const bool last = s == cfg::NSEG - 1;
      if (n16 == 0) {
        if (hw == 2 && !last) issue_x(s + 1);
        if (hw == 0 && (s & 3) == 1 && s > 1) st_relaxed_u32(arena + (prog_off(h, j) + lds32_i<SC_IN + 12>(sb)), s - 1);
        if (hw == 0 && s > 0) store_kv(s - 1);
        if (PFX && hw == 3 && cta < 80 && s + PFX < cfg::NSEG) prefetch_l2(xg + (size_t)(s + PFX) * 40960 + cta * 512, 512);
        if (PFACC && hw == 1 && s + PFACC < cfg::NSEG - 1)
          asm volatile("prefetch.global.L2 [%0];" :: "l"(arena + (AR_ACC + acc_step(s + PFACC) + acc_lane(cta / 24, (cta & 3) * 8) + acc_voff((cta % 24) >> 2))) : "memory");
      }
      __syncwarp();
      if (last) break;
      const uint32_t kv = (s & 1) * (2 * KVB);
      n16 = fresh(n16);
      uint32_t kb0[4], kb1[4];
      { const uint32_t ka = n16 + (n16 & 384) * 4 + (sb + kv + hw * 128); ldsm_x4_i<OFF_KV>(kb0, ka); ldsm_x4_i<OFF_KV + 2560>(kb1, ka); }
      TS(1);
      bar_sync(B_QK, 384);
      {
        uint32_t q0[4], q1[4], q2[4], q3[4];
        float sa[4] = {0, 0, 0, 0}, sc2[4] = {0, 0, 0, 0};
        ldsm_x4_i<OFF_Q>(q0, n16 + sb); ldsm_x4_i<OFF_Q + 1024>(q2, n16 + sb); ldsm_x4_i<OFF_Q + 512>(q1, n16 + sb);
        bar_arrive(B_A, 288);
        ldsm_x4_i<OFF_Q + 1536>(q3, n16 + sb);
        mma16816(sa, q0[0], q0[1], q0[2], q0[3], kb0[0], kb0[1]);
        mma16816(sc2, q2[0], q2[1], q2[2], q2[3], kb1[0], kb1[1]);
        mma16816(sa, q1[0], q1[1], q1[2], q1[3], kb0[2], kb0[3]);
        mma16816(sc2, q3[0], q3[1], q3[2], q3[3], kb1[2], kb1[3]);
        const float x0 = (sa[0] + sa[2]) + (sc2[0] + sc2[2]), x1 = (sa[1] + sa[3]) + (sc2[1] + sc2[3]);
        const uint32_t xp = pack_bf16(x0, x1);
        st_async_b32_i<0>((n16 >> 2) + us1, xp, sb + MB_S + d1);
        st_async_b32_i<0>((n16 >> 2) + us2, xp, sb + MB_S + d2);
        stsm_x2(n16 + (sb + OFF_S + hw * 256), __float_as_uint(x0), __float_as_uint(x1));
      }
      TS(3);
      uint32_t v0[4], v1[4], vm0, vm1;
      const uint32_t uv = sb + kv + hw * 1280;
      ldsm_x4_t_i<OFF_KV + KVB>(v0, n16 + uv); ldsm_x4_t_i<OFF_KV + KVB + 640>(v1, n16 + uv);
      bar_sync(B_SL, 256);
      float t0[4], t1[4], t2[4];
      { uint32_t x[4]; ldsm_x4_i<OFF_S>(x, n16 + sb); t0[0] = __uint_as_float(x[0]); t0[1] = __uint_as_float(x[1]); t0[2] = __uint_as_float(x[2]); t0[3] = __uint_as_float(x[3]); }
      { uint32_t x[4]; ldsm_x4_i<OFF_S + 512>(x, n16 + sb); t1[0] = __uint_as_float(x[0]); t1[1] = __uint_as_float(x[1]); t1[2] = __uint_as_float(x[2]); t1[3] = __uint_as_float(x[3]); }
      { uint32_t x[4]; ldsm_x4_i<OFF_S + 1024>(x, n16 + sb); t2[0] = __uint_as_float(x[0]); t2[1] = __uint_as_float(x[1]); t2[2] = __uint_as_float(x[2]); t2[3] = __uint_as_float(x[3]); }
      mbar_spin(sb + MB_S, s & 1);
      TS(4);
      uint2 xo;
      {
        uint32_t r0[4], r1[4], r2[2];
        ldsm_x4_i<OFF_SR>(r0, n16 + sb); ldsm_x4_i<OFF_SR + 512>(r1, n16 + sb); ldsm_x2_i<OFF_SR + 1024>(r2, n16 + sb);
        SFENCE(n16);
        const uint2 eye = lds64_i<OFF_LT>(n16 + sb);
        mma16816(t0, r0[0], r0[1], r0[2], r0[3], eye.x, eye.y);
        mma16816(t1, r1[0], r1[1], r1[2], r1[3], eye.x, eye.y);
        mma1688(t2, r2[0], r2[1], eye.x);
        bar_sync(B_V, 256);
        vm0 = ldsm_x1_t_i<OFF_KV + KVB + 512>(n16 + uv); vm1 = ldsm_x1_t_i<OFF_KV + KVB + 1152>(n16 + uv);
        SFENCE(n16);
        xo = lds64_i<OFF_LT + 8>(n16 + sb);
      }
      float sc[10] = {t0[0], t0[1], t0[2], t0[3], t1[0], t1[1], t1[2], t1[3], t2[0] + t2[2], t2[1] + t2[3]};
      const float cs = 0.07216878364870322f * 1.4426950408889634f;
      float mx = fmaxf(fmaxf(fmaxf(sc[0], sc[1]), fmaxf(sc[2], sc[3])), fmaxf(fmaxf(sc[4], sc[5]), fmaxf(sc[6], sc[7])));
      mx = fmaxf(mx, fmaxf(sc[8], sc[9]));
      {
        const float m1 = __shfl_xor_sync(0xffffffffu, mx, 1), m2 = __shfl_xor_sync(0xffffffffu, mx, 2), m3 = __shfl_xor_sync(0xffffffffu, mx, 3);
        mx = fmaxf(fmaxf(mx, m1), fmaxf(m2, m3));
      }
      const float mo = fmaf(mx, -cs, __uint_as_float(xo.x));
      auto ex = [&](int i) -> uint32_t { float x, y;
        asm volatile("ex2.approx.ftz.f32 %0, %1;" : "=f"(x) : "f"(fmaf(sc[i], cs, mo))); asm volatile("ex2.approx.ftz.f32 %0, %1;" : "=f"(y) : "f"(fmaf(sc[i + 1], cs, mo)));
        return pack_bf16(x, y); };
      float oa[4] = {0, 0, 0, 0}, ob[4] = {0, 0, 0, 0}, oc[4] = {0, 0, 0, 0}, od[4] = {0, 0, 0, 0}, rs[4] = {0, 0, 0, 0};
      const uint32_t ones = 0x3f803f80u;
      const uint32_t p4 = ex(8);
      if (MEMFIRST) { mma1688(rs, p4, 0u, ones); mma1688(oa, p4, 0u, vm0); mma1688(ob, p4, 0u, vm1); }
      const uint32_t p0 = ex(0), p1 = ex(2), p2 = ex(4), p3 = ex(6);
      TS(5);
      mma16816(rs, p0, p2, p1, p3, ones, ones);
      mma16816(oa, p0, p2, p1, p3, v0[0], v0[1]);
      mma16816(oc, p0, p2, p1, p3, v0[2], v0[3]);
      mma16816(ob, p0, p2, p1, p3, v1[0], v1[1]);
      mma16816(od, p0, p2, p1, p3, v1[2], v1[3]);
      if (!MEMFIRST) { mma1688(rs, p4, 0u, ones); mma1688(oa, p4, 0u, vm0); mma1688(ob, p4, 0u, vm1); }
      const float inv = rcpf(rs[0] + rs[2]) * __uint_as_float(xo.y);
      {
        const uint32_t y0 = pack_bf16((oa[0] + oc[2]) * inv, (oa[1] + oc[3]) * inv), y1 = pack_bf16((ob[0] + od[2]) * inv, (ob[1] + od[3]) * inv);
        st_async_v2_i<0>(xo.x + uo1, y0, y1, sb + MB_O + d1);
        st_async_v2_i<0>(xo.x + uo2, y0, y1, sb + MB_O + d2);
        sts64_i<OFF_O>(xo.x + (sb + hw * 256), y0, y1);
      }
      bar_arrive(B_O, 384);
      TS(6);
      if (hw == 0) bulk_wait<0>();
      mbar_expect_tx_if(n16 == 0 && hw == 3, sb + MB_S, 1280);
      n16 = fresh(n16);
      const int ln = n16 >> 4;
      auto mslot = [&](int c) -> uint32_t { return sb + OFF_MEM + c * 128 + (((ln >> 2) ^ (2 * (c & 3))) << 4); };
      const int lq = ln & 3;
      const uint32_t ma = mslot(cb28 + lq), mb_ = mslot(cb28 + (lq >> 1)) + (lq & 1) * 8;
      const unsigned char* gp = arena + (AR_ACC + acc_lane(hw, ln) + acc_step(s));
      const bool odd = ln & 1;
      const uint32_t delay = a.delay + ((hist & 2) ? a.margin : 0);
      SFENCE(ma);
      uint32_t tw;
      if (hw == 0 && (s & 3) == 0 && a.pubrel) {
        bar_arrive(B_RED, 384);
        asm volatile("fence.acq_rel.gpu;" ::: "memory");
        uint2 t; int sp = 0;
        do { asm volatile("ld.volatile.shared.v2.u32 {%0,%1}, [%2];" : "=r"(t.x), "=r"(t.y) : "r"(sb + SC_TW) : "memory"); } while (__any_sync(0xffffffffu, t.y != (uint32_t)s) && ++sp < SPIN_LIMIT);
        tw = t.x;
      } else {
        bar_sync(B_RED, 384);
        SFENCE(mb_);
        tw = clk_v();
        if (hw == 1) asm volatile("st.volatile.shared.v2.u32 [%0], {%1,%2};" :: "r"(sb + SC_TW), "r"(tw), "r"(s) : "memory");
      }
      TSV(7, tw);
      mbar_expect_tx_if(n16 == 0 && hw == 3, sb + MB_O, 2048);
      while (clk_v() - tw < delay) {}
      TS(8);
      uint4 v[6];
      int spin = 0;
      const uint32_t cm = odd ? 0x5000u : 0u;
      do {
        static_for<0, 6>([&](auto I) { v[I.value] = ld_relaxed_v4_i<acc_voff(I.value)>(gp); });
      } while (__any_sync(0xffffffffu, (~((v[0].w & v[1].w & v[2].w) & (v[3].w & v[4].w & v[5].w)) & cm) != 0) && ++spin < SPIN_LIMIT);
      v[0].w = odd ? v[3].x : v[0].w; v[1].w = odd ? v[3].y : v[1].w; v[2].w = odd ? v[3].z : v[2].w; v[3].w = odd ? 0u : v[3].w;
      sts128_i<0>(ma, v[0].x, v[0].y, v[0].z, v[0].w);
      sts128_i<512>(ma, v[1].x, v[1].y, v[1].z, v[1].w);
      sts128_i<1024>(ma, v[2].x, v[2].y, v[2].z, v[2].w);
      sts128_i<0>(ma + du, v[4].x, v[4].y, v[4].z, v[5].z);
      sts64_i<512>(mb_ + du, v[5].x, v[5].y);
      if (!odd) sts128_i<1536>(mb_, v[3].x, v[3].y, v[3].z, v[3].w);
      hist = (hist * 2 + (spin != 0)) & 0xffffu;
      TSV(11, spin);
#ifdef TIMELINE
      if (hw == 2 && ln == 0) { uint32_t gt; asm volatile("mov.u32 %0, %%globaltimer_lo;" : "=r"(gt)); *(uint4*)(g_step + (((a.tl >= 12) * 64 + s) * 96 + cta) * 4) = make_uint4(gt, spin, clk_v() - tw, tw); }
#endif
      TS(10);
      bar_sync(B_MEM0, 256); bar_sync(B_MEM1, 256);
      uint32_t m = lds32_i<SC_IN + 12>(sb);
      uint32_t m2 = m;
      static_for<0, 3>([&](auto I) { m = amax_h2(amax_h2(amax_h2(amax_h2(m, v[I.value].x), v[I.value].y), v[I.value].z), v[I.value].w); });
      static_for<3, 6>([&](auto I) { m2 = amax_h2(amax_h2(amax_h2(m2, v[I.value].x), v[I.value].y), v[I.value].z); });
      m = amax_fold(amax_h2(amax_h2(m2, v[3].w), m));
      if (n16 == 0) asm volatile("red.shared.max.u32 [%0], %1;" :: "r"(sb + SC_IN + 4 + 16 * ((s + 1) & 1)), "r"(m) : "memory");
    }
    bar_sync(B_RED, 384);
    if (hw == 0 && n16 == 0) {
      store_kv(cfg::NSEG - 1);
      bulk_wait<0>();
      st_release_u32(arena + (prog_off(h, j) + lds32_i<SC_IN + 12>(sb)), cfg::NSEG);
    }
    __syncwarp();
#ifdef STEPCLK
    if (hw == 0 && n16 == 0) a.dbg[96 * 300 + cta * 2 + 1 + (hist >> 20)] = clk32();
#endif
#ifdef TIMELINE
    if (cta == 0 && hw == 0 && n16 == 0) { g_tl2[(a.tl >= 12) * 128 + 2] = clock64(); g_tl2[(a.tl >= 12) * 128 + 3] = gtime(); }
#endif
    TL_END(a.tl);
    asm volatile("barrier.cluster.arrive.relaxed.aligned; barrier.cluster.wait.aligned;" ::: "memory");
  } else {
    asm volatile("setmaxnreg.inc.sync.aligned.u32 232;");
    const int wi = warp & 3, hf = warp >> 2;
    [[maybe_unused]] const int tid = threadIdx.x;
    int lane = fresh(threadIdx.x & 31);
    uint32_t w[40][4], wm = 0;
    uint32_t wqa;
    { const int r8 = lane & 7, mrow = r8 + ((lane >> 4) << 3), mch = 2 * wi + ((lane >> 3) & 1); wqa = sb + mrow * 128 + ((mch ^ r8) << 4); }
    float iw, iq;
#pragma unroll 1
    for (int live = a.dry ? 0 : 1; live < 2; live++) {
      const uint32_t wa = wqa + (hf ? OFF_WO : OFF_WQ);
      wm = 0;
      mbar_wait_if(live, sb + (hf ? MB_V : MB_K), 0);
      static_for<0, 20>([&](auto K) { ldsm_x4_t_i<K.value * 2048>(w[K.value], wa); });
#pragma unroll
      for (int k = 0; k < 20; k++) wm = amax_bf2(amax_bf2(wm, amax_bf2(w[k][0], w[k][1])), amax_bf2(w[k][2], w[k][3]));
      SFENCE2(wa, wm);
      if (warp == 0 && live) PT(1);
      if (live) bar_arrive(hf ? B_V : B_QK, 160);
      mbar_wait_if(live, sb + (hf ? MB_V : MB_K) + 8, 0);
      static_for<20, 40>([&](auto K) { ldsm_x4_t_i<K.value * 2048>(w[K.value], wa); });
#pragma unroll
      for (int k = 20; k < 40; k++) wm = amax_bf2(amax_bf2(wm, amax_bf2(w[k][0], w[k][1])), amax_bf2(w[k][2], w[k][3]));
      SFENCE2(wa, wm);
      if (warp == 4 && live) PT(2);
      if (live) bar_arrive(hf ? B_O : B_SL, 160);
      SFENCE(wa);
      const uint32_t m = amax_fold(wm);
      if (hf && live) asm volatile("red.shared.max.u32 [%0], %1;" :: "r"(sb + SC_W), "r"(m) : "memory");
      const int e = wscale_exp(m);
      const uint32_t sc = (uint32_t)(e + 127) * 0x00800080u; iw = exp2i(-e);
#pragma unroll
      for (int k = 0; k < 40; k++) { bf2_to_h2_inplace(w[k][0], sc); bf2_to_h2_inplace(w[k][1], sc); bf2_to_h2_inplace(w[k][2], sc); bf2_to_h2_inplace(w[k][3], sc); }
    }
    iw = uniform_f(iw);
    if (warp == 0) PT(3);
    uint32_t x0[8];
    {
      float xa[16];
      const uint32_t dlo = (((sb + OFF_X) & 0x3FFFF) >> 4) | (1u << 16);
      mbar_wait(sb + MB_X, 0);
      if (warp == 0) PT(4);
      wgmma_fence();
      static_for<0, 40>([&](auto K) { constexpr int k = K.value; wgmma_rs32h<((k >> 2) * 4096 + (k & 3) * 32) / 16, (k != 0)>(xa, w[k], dlo); });
      wgmma_commit();
      wgmma_wait<0>();
#pragma unroll
      for (int i = 0; i < 8; i++) x0[i] = pack_bf16(xa[2 * i] * iw, xa[2 * i + 1] * iw);
    }
    lane = fresh(threadIdx.x & 31);
    const int g = lane >> 2, q4 = lane & 3, r8 = lane & 7, m4 = lane >> 3;
    const bool t28 = j == 0 || warp < 4;
    const int bi = j == 0 ? hf : (warp < 4 ? j + 1 : 2 * (j - 1) + ((warp - 4) >> 1)), bv = t28 ? wi : 4 + (warp & 1);
    uint32_t wo1 = sb + OFF_WO + warp * 896 + lane * 16, wo2;
    {
      const int cb = (t28 ? unit28(bi) : unit24(bi)) - col0 / 8;
      uint32_t cp[4];
#pragma unroll
      for (int wd = 0; wd < 4; wd++) {
        int c, p;
        if (bv < 3) { c = 4 * bv + q4; p = wd; }
        else if (bv == 3) { if (q4 & 1) { c = 4 * (wd % 3) + q4; p = 3; } else { c = 12 + (q4 >> 1); p = wd; } }
        else if (bv == 4) { c = q4; p = wd; }
        else { if (wd < 2) { c = 4 + (q4 >> 1); p = 2 * (q4 & 1) + wd; } else { c = q4; p = 3; } }
        cp[wd] = sb + OFF_WO + ((g & 1) + (g & 2) * 4 + (g >> 2) * 2) * WOS + (cb + c) * 16 + p * 4;
      }
      const int cidx = (r8 & 1) + ((r8 >> 2) << 1);
      wo2 = sb + OFF_WO + warp * 896 + ((m4 & 1) ? 768 + (m4 >> 1) * 64 + cidx * 16 : 512 + (m4 >> 1) * 128 + r8 * 16);
      const bool dump = (m4 & 1) && (r8 & 2);
      uint32_t mo = 0;
      const bool regular = bv < 3 || bv == 4;
#pragma unroll 1
      for (int i = 0; i < 3; i++) {
        uint32_t x[4][4], y[4][4];
        const uint32_t o = i * 4 * WOK;
        mbar_wait(sb + MB_R + 8 * i, 0);
        if (warp == 0) PT(5 + i);
        if (regular) {
          static_for<0, 4>([&](auto K) {
            constexpr int kk = K.value;
            const uint4 u = lds128_i<kk * WOK>(cp[0] + o), v = lds128_i<kk * WOK + 4 * WOS>(cp[0] + o);
            x[kk][0] = u.x; x[kk][1] = u.y; x[kk][2] = u.z; x[kk][3] = u.w; y[kk][0] = v.x; y[kk][1] = v.y; y[kk][2] = v.z; y[kk][3] = v.w;
          });
        } else {
          static_for<0, 4>([&](auto K) {
            constexpr int kk = K.value;
#pragma unroll
            for (int wd = 0; wd < 4; wd++) { x[kk][wd] = lds32_i<kk * WOK>(cp[wd] + o); y[kk][wd] = lds32_i<kk * WOK + 4 * WOS>(cp[wd] + o); }
          });
        }
        bar_sync(B_C, 256);
        static_for<0, 4>([&](auto K) {
          constexpr int kk = K.value;
#pragma unroll
          for (int wd = 0; wd < 4; wd++) mo = amax_bf2(mo, amax_bf2(x[kk][wd], y[kk][wd]));
          stsm_x4_t_i<kk * WOK>(wo1 + o, x[kk][0], x[kk][1], y[kk][0], y[kk][1]);
          stsm_x4_t_i<0>(dump ? sb + OFF_S + 512 + lane * 16 : wo2 + o + kk * WOK, x[kk][2], x[kk][3], y[kk][2], y[kk][3]);
        });
      }
      if (warp == 0) PT(8);
      mo = amax_fold(mo);
      if (lane == 0) asm volatile("red.shared.max.u32 [%0], %1;" :: "r"(sb + SC_W + 4), "r"(mo) : "memory");
    }
    __syncwarp();
    auto run = [&](auto HF) {
    constexpr int hf = HF.value;
    uint32_t mema, sta, l16 = sb + lane * 16;
    uint32_t rq[hf ? NP1 : NQ0][4];
    auto step_addr = [&](uint32_t kv) {
      const int lr = (l16 >> 4) & 7, lm = (l16 >> 7) & 3;
      mema = l16 ^ (lm << 5);
      sta = sb + lr * 16 + (lm < 2 ? OFF_Q + wi * 512 + hf * 128 + lm * 256 : OFF_KV + kv + 512 + (2 * wi + lm - 2) * 640);
    };
    auto x_gemm = [&](uint32_t ph, [[maybe_unused]] uint32_t tsb) {
      float xa[16];
      const uint32_t dlo = (((sb + OFF_X) & 0x3FFFF) >> 4) | (1u << 16);
      constexpr int NP = hf ? NP1 : NP0;
      if constexpr (hf) {
        static_for<PQE, NP>([&](auto K) { ldsm_x4_t_i<OFF_WQ + K.value * 2048>(rq[K.value], wqa); });
        bar_sync(B_X, 256);
      }
      wgmma_fence();
      static_for<0, 40>([&](auto K) {
        constexpr int k = K.value;
        wgmma_rs32h<((k >> 2) * 4096 + (k & 3) * 32) / 16, (k != 0)>(xa, w[k], dlo);
        if constexpr (!hf && k == PFK && NP > PQE) { SFENCE(wqa); static_for<PQE, NP>([&](auto K) { ldsm_x4_t_i<OFF_WQ + K.value * 2048>(rq[K.value], wqa); }); SFENCE(wqa); }
        if constexpr (!hf && k == XT) bar_arrive(B_X, 256);
      });
      step_addr(ph * (2 * KVB));
      wgmma_commit();
      TS(9);
      wgmma_wait<0>();
      const uint32_t xs = l16 + (wi * 1280 + ph * (2 * KVB));
      stsm_x4_t_i<OFF_KV + hf * KVB>(xs, pack_bf16(xa[0] * iw, xa[1] * iw), pack_bf16(xa[4] * iw, xa[5] * iw), pack_bf16(xa[8] * iw, xa[9] * iw), pack_bf16(xa[12] * iw, xa[13] * iw));
      stsm_x4_t_i<OFF_KV + hf * KVB + 640>(xs, pack_bf16(xa[2] * iw, xa[3] * iw), pack_bf16(xa[6] * iw, xa[7] * iw), pack_bf16(xa[10] * iw, xa[11] * iw), pack_bf16(xa[14] * iw, xa[15] * iw));
      if constexpr (!hf) static_for<NP0, NP0 + NPL>([&](auto K) { ldsm_x4_t_i<OFF_WQ + K.value * 2048>(rq[K.value], wqa); });
    };
    auto wq_addr = [&](uint32_t l) -> uint32_t {
      const int lr = (l >> 4) & 7, lm = (l >> 7) & 3;
      return sb + hf * ((40 - NQ1) * 2048) + (lr + ((lm >> 1) << 3)) * 128 + (((2 * wi + (lm & 1)) ^ lr) << 4);
    };
    constexpr int NPM = hf ? NPM1 : NPM0;
    uint32_t u1[NPM][4], u2[NPM][4];
    static_for<0, NPM>([&](auto K) { ldsm_x4_i<(12 - NPM + K.value) * WOK>(u1[K.value], wo1); ldsm_x4_i<(12 - NPM + K.value) * WOK>(u2[K.value], wo2); });
    bar_sync(0, 384);
    iq = uniform_f(exp2i(-wscale_exp(lds32_i<SC_W + 8>(sb))));
    wqa = wq_addr(l16);
    static_for<0, (hf ? NP1 : NP0 + NPL)>([&](auto K) { ldsm_x4_t_i<OFF_WQ + K.value * 2048>(rq[K.value], wqa); });
    step_addr(0);
    stsm_x4_t_i<OFF_KV + hf * KVB>(l16 + wi * 1280, x0[0], x0[2], x0[4], x0[6]);
    stsm_x4_t_i<OFF_KV + hf * KVB + 640>(l16 + wi * 1280, x0[1], x0[3], x0[5], x0[7]);
    asm volatile("barrier.cluster.wait.aligned;" ::: "memory");
    TL_END(a.tl + 1);
#pragma unroll 1
    for (int s = 0; s < cfg::NSEG - 1; s++) {
      TS_SETUP();
#if CHAIN_TIMING
      if (tid == 0 && (s & 7) == 0) a.dbg[96 * 288 + cta * 8 + (s >> 3)] = clk32();
#endif
      bar_sync(hf ? B_MEM1 : B_MEM0, 256);
      const float sin_ = __uint_as_float(lds32_i<SC_IN>(sb + 16 * (s & 1)));
      constexpr int NPQ = (40 - NQ1) / 2;
      if constexpr (hf == 0) {
        float k0[4] = {0, 0, 0, 0}, k1[4] = {0, 0, 0, 0}, q0[4] = {0, 0, 0, 0}, q1[4] = {0, 0, 0, 0};
        constexpr auto pair_of = [](int t) { const int a = t * (20 - NPQ) / 20, b = (t + 1) * (20 - NPQ) / 20; return b > a ? NPQ + a : t - a; };
        uint32_t b[NB0][4];
        static_for<0, NB0>([&](auto T) { ldsm_x4_i<OFF_MEM + pair_of(T.value) * 512>(b[T.value], mema); });
        static_for<NP0 + NPL, NQ0>([&](auto K) { ldsm_x4_t_i<OFF_WQ + K.value * 2048>(rq[K.value], wqa); });
        if (BBS < 100) bbfence<0>(mema);
        static_for<0, 20>([&](auto T) {
          constexpr int t = T.value, p = pair_of(t);
          uint32_t (&bb)[4] = b[t % NB0];
          if constexpr (p < NPQ) {
            mma16816h(q0, rq[(2 * p) % NQ0], bb[0], bb[1]);
            if constexpr (2 * p + NQ0 < 2 * NPQ) ldsm_x4_t_i<OFF_WQ + (2 * p + NQ0) * 2048>(rq[(2 * p) % NQ0], wqa);
          }
          mma16816h(k0, w[2 * p], bb[0], bb[1]);
          if constexpr (p < NPQ) {
            mma16816h(q1, rq[(2 * p + 1) % NQ0], bb[2], bb[3]);
            if constexpr (2 * p + 1 + NQ0 < 2 * NPQ) ldsm_x4_t_i<OFF_WQ + (2 * p + 1 + NQ0) * 2048>(rq[(2 * p + 1) % NQ0], wqa);
          }
          mma16816h(k1, w[2 * p + 1], bb[2], bb[3]);
          if constexpr (NVE > 0 && t + NB0 == VET) bar_arrive(B_E, 256);
          if constexpr (t + NB0 < 20) ldsm_x4_i<OFF_MEM + pair_of(t + NB0) * 512>(bb, mema);
          if constexpr (t < 20 - NB0 && (t % BBS) == BBS - 1) bbfence<t + 1>(mema);
        });
        const float sq = sin_ * iq, sk = sin_ * iw;
        stsm_x4_t_i<0>(sta, pack_bf16((q0[0] + q1[0]) * sq, (q0[1] + q1[1]) * sq), pack_bf16((q0[2] + q1[2]) * sq, (q0[3] + q1[3]) * sq),
                       pack_bf16((k0[0] + k1[0]) * sk, (k0[1] + k1[1]) * sk), pack_bf16((k0[2] + k1[2]) * sk, (k0[3] + k1[3]) * sk));
        bar_sync(B_QK, 384);
        TS(2);
        {
          if (wi == 3) {
            const uint32_t xr = sb + ((l16 & 511) >> 2), ka = l16 + (l16 & 384) * 4 + (s & 1) * (2 * KVB);
            uint32_t a0[4], a1[4], a2[4], a3[4], kb0[4], kb1[4];
            ldsm_x4_i<OFF_Q>(a0, l16); ldsm_x4_i<OFF_KV + 512>(kb0, ka); ldsm_x4_i<OFF_Q + 1024>(a2, l16); ldsm_x4_i<OFF_KV + 512 + 2560>(kb1, ka);
            ldsm_x4_i<OFF_Q + 512>(a1, l16);
            bar_arrive(B_A, 288);
            ldsm_x4_i<OFF_Q + 1536>(a3, l16);
            float sa[4] = {0, 0, 0, 0}, sc2[4] = {0, 0, 0, 0};
            mma16816(sa, a0[0], a0[1], a0[2], a0[3], kb0[0], kb0[1]);
            mma16816(sc2, a2[0], a2[1], a2[2], a2[3], kb1[0], kb1[1]);
            mma16816(sa, a1[0], a1[1], a1[2], a1[3], kb0[2], kb0[3]);
            mma16816(sc2, a3[0], a3[1], a3[2], a3[3], kb1[2], kb1[3]);
            const float x0 = (sa[0] + sa[2]) + (sc2[0] + sc2[2]), x1 = (sa[1] + sa[3]) + (sc2[1] + sc2[3]);
            const uint32_t xp = pack_bf16(x0, x1);
            st_async_b32_i<OFF_SR + 1024 + 128>(xr + d1, xp, sb + MB_S + d1);
            st_async_b32_i<OFF_SR + 1024>(xr + d2, xp, sb + MB_S + d2);
            stsm_x2(l16 + OFF_S + 1024, __float_as_uint(x0), __float_as_uint(x1));
          } else if (wi == 0) {
            const uint4 si = lds128_i<SC_IN>(sb + 16 * (s & 1));
            const int em = (int)(si.y >> 10) - 14 + (int)(si.x >> 23) - 127;
            const uint32_t osc = __float_as_uint(exp2i(max(min((int)si.z - max(em, 1), 100), -100)));
            sts32(l16 + OFF_LT + 12, osc); sts64_i<SC_IN>(sb + 16 * ((s + 1) & 1), 0x7f000000u - osc, 0u);
          }
          bar_sync(B_SL, 256);
        }
      } else {
        float v0[4] = {0, 0, 0, 0}, v1[4] = {0, 0, 0, 0}, q0[4] = {0, 0, 0, 0}, q1[4] = {0, 0, 0, 0};
        constexpr int NB1 = NQ1 / 2 < 3 ? NQ1 / 2 : 3;
        uint32_t b[NB1][4];
        static_for<0, NB1>([&](auto T) { ldsm_x4_i<OFF_MEM + (NPQ + T.value) * 512>(b[T.value], mema); });
        static_for<0, NQ1 / 2>([&](auto T) {
          constexpr int t = T.value, p = NPQ + t;
          uint32_t (&bb)[4] = b[t % NB1];
          mma16816h(q0, rq[(2 * t) % NP1], bb[0], bb[1]);
          if constexpr (2 * t + NP1 < NQ1) ldsm_x4_t_i<OFF_WQ + (2 * t + NP1) * 2048>(rq[(2 * t) % NP1], wqa);
          mma16816h(q1, rq[(2 * t + 1) % NP1], bb[2], bb[3]);
          if constexpr (2 * t + 1 + NP1 < NQ1) ldsm_x4_t_i<OFF_WQ + (2 * t + 1 + NP1) * 2048>(rq[(2 * t + 1) % NP1], wqa);
          mma16816h(v0, w[2 * p], bb[0], bb[1]);
          mma16816h(v1, w[2 * p + 1], bb[2], bb[3]);
          if constexpr (t + NB1 < NQ1 / 2) ldsm_x4_i<OFF_MEM + (p + NB1) * 512>(bb, mema);
        });
        const float sq = sin_ * iq, sv = sin_ * iw;
        stsm_x2_t_i<0>(sta, pack_bf16((q0[0] + q1[0]) * sq, (q0[1] + q1[1]) * sq), pack_bf16((q0[2] + q1[2]) * sq, (q0[3] + q1[3]) * sq));
        TS(2);
        bar_arrive(B_QK, 384);
        float v2[4] = {0, 0, 0, 0}, v3[4] = {0, 0, 0, 0};
        auto vpair = [&](auto P, uint32_t (&bb)[4]) {
          constexpr int p = P.value;
          if constexpr (p & 1) { mma16816h(v0, w[2 * p], bb[0], bb[1]); mma16816h(v1, w[2 * p + 1], bb[2], bb[3]); }
          else { mma16816h(v2, w[2 * p], bb[0], bb[1]); mma16816h(v3, w[2 * p + 1], bb[2], bb[3]); }
        };
        if constexpr (NVE > 0) {
          uint32_t e[NVE ? NVE : 1][4];
          bar_sync(B_E, 256);
          static_for<0, NVE>([&](auto T) { ldsm_x4_i<OFF_MEM + T.value * 512>(e[T.value], mema); });
          static_for<0, NVE>([&](auto T) { vpair(T, e[T.value]); });
        }
        bar_sync(B_A, 288);
        uint32_t c[4][4];
        static_for<NVE, (NVE + 4 < NPQ ? NVE + 4 : NPQ)>([&](auto T) { ldsm_x4_i<OFF_MEM + T.value * 512>(c[T.value & 3], mema); });
        static_for<NVE, NPQ>([&](auto T) {
          constexpr int p = T.value;
          vpair(T, c[p & 3]);
          if constexpr (p + 4 < NPQ) ldsm_x4_i<OFF_MEM + (p + 4) * 512>(c[p & 3], mema);
        });
        stsm_x2_t_i<OFF_KV + KVB + 512>(l16 + (l16 & 128) * 4 + (wi * 1280 + (s & 1) * (2 * KVB)), pack_bf16(((v0[0] + v1[0]) + (v2[0] + v3[0])) * sv, ((v0[1] + v1[1]) + (v2[1] + v3[1])) * sv),
                            pack_bf16(((v0[2] + v1[2]) + (v2[2] + v3[2])) * sv, ((v0[3] + v1[3]) + (v2[3] + v3[3])) * sv));
        bar_arrive(B_V, 256);
      }
      TS(3);
      {
        uint32_t t1[12][4], t2[12][4];
        const uint32_t o16 = l16;
        wo1 = l16 + (OFF_WO + warp * 896);
        wo2 = sb + OFF_WO + warp * 896 + ((l16 & 128) ? 768 + ((l16 & 256) >> 2) + (l16 & 16) + ((l16 & 64) >> 1) : 512 + ((l16 & 256) >> 1) + (l16 & 112));
        constexpr int NR_ = NRT - NPM;
        auto ldw = [&](auto K) { if constexpr (K.value < 12 - NPM) { ldsm_x4_i<K.value * WOK>(t1[K.value], wo1); ldsm_x4_i<K.value * WOK>(t2[K.value], wo2); } };
        constexpr int PB = (hf ? PB1 : PB0) < NR_ ? (hf ? PB1 : PB0) : NR_, PA = (hf ? PA1 : PA0) < PB ? (hf ? PA1 : PA0) : PB;
        static_for<0, PA>(ldw);
        mbar_spin(sb + MB_X, (s + 1) & 1);
        if constexpr (PB > PA) {
          constexpr int PM = PA + PM1 < PB ? PA + PM1 : PB;
          mbar_spin(sb + MB_S, s & 1);
          const uint32_t t0 = clk_v();
          if constexpr (PM > PA) { while (clk_v() - t0 < GD1) {} static_for<PA, PM>(ldw); }
          if constexpr (PB > PM) { while (clk_v() - t0 < GD2) {} static_for<PM, PB>(ldw); }
        }
        float c0[4] = {0, 0, 0, 0}, c1[4] = {0, 0, 0, 0}, e0[4] = {0, 0, 0, 0}, e1[4] = {0, 0, 0, 0};
        uint32_t ob[6][4];
        auto kstep = [&](auto K) {
          constexpr int k = K.value;
          uint32_t (&bb)[4] = ob[k >> 1];
          uint32_t (&x)[4] = k < 12 - NPM ? t1[k] : u1[k < 12 - NPM ? 0 : k - (12 - NPM)];
          uint32_t (&y)[4] = k < 12 - NPM ? t2[k] : u2[k < 12 - NPM ? 0 : k - (12 - NPM)];
          if constexpr (k & 1) { mma16816(c1, x[0], x[1], x[2], x[3], bb[2], bb[3]); mma16816(e1, y[0], y[1], y[2], y[3], bb[2], bb[3]); }
          else { mma16816(c0, x[0], x[1], x[2], x[3], bb[0], bb[1]); mma16816(e0, y[0], y[1], y[2], y[3], bb[0], bb[1]); }
          if constexpr (k >= NRF) ldw(IC<k + NR_ - NRF>{});
        };
        auto ldo = [&](auto P) { ldsm_x4_i<OFF_O + P.value * 512>(ob[P.value], o16); };
        TS(4);
        bar_sync(B_O, 384);
        ldo(IC<0>{}); ldo(IC<1>{});
        SFENCE(o16);
        static_for<PB, NR_>(ldw);
        static_for<0, 4>(kstep);
        TS(5);
        mbar_spin(sb + MB_O, s & 1);
        TS(6);
        ldo(IC<2>{}); ldo(IC<NPM >= 2 ? 5 : 3>{});
        if (WOF) SFENCE(o16);
        kstep(IC<4>{});
        if constexpr (NPM < 2) { kstep(IC<5>{}); ldo(IC<4>{}); kstep(IC<6>{}); kstep(IC<7>{}); ldo(IC<5>{}); static_for<8, 12>(kstep); }
        else if constexpr (NPM >= 4) { kstep(IC<10>{}); kstep(IC<11>{}); ldo(IC<4>{}); kstep(IC<5>{}); ldo(IC<3>{}); kstep(IC<8>{}); kstep(IC<9>{}); kstep(IC<6>{}); kstep(IC<7>{}); }
        else { kstep(IC<5>{}); ldo(IC<3>{}); kstep(IC<11>{}); kstep(IC<10>{}); ldo(IC<4>{}); kstep(IC<6>{}); kstep(IC<7>{}); if constexpr (NPM == 3) { kstep(IC<9>{}); kstep(IC<8>{}); } else { kstep(IC<8>{}); kstep(IC<9>{}); } }
        l16 = fresh(l16);
        const int ln = (l16 >> 4) & 31;
        if constexpr (CEARLY && hf) { SFENCE2(o16, __float_as_uint(e1[0])); bar_arrive(B_G, 256); }
        unsigned char* gr = arena + (AR_ACC + acc_lane(bi, ln) + acc_voff(bv) + acc_step(s));
        const bool cnt = (ln & 1) || !t28;
        wqa = wq_addr(l16);
        SFENCE(o16);
        static_for<0, PQE>([&](auto K) { ldsm_x4_t_i<OFF_WQ + K.value * 2048>(rq[K.value], wqa); });
        const uint32_t y0 = movm_t(pack_f16(c0[0] + c1[0], c0[1] + c1[1])), y1 = movm_t(pack_f16(c0[2] + c1[2], c0[3] + c1[3]));
        const uint32_t y2 = movm_t(pack_f16(e0[0] + e1[0], e0[1] + e1[1])), y3 = movm_t(pack_f16(e0[2] + e1[2], e0[3] + e1[3]));
        asm volatile("red.relaxed.gpu.global.add.noftz.v4.f16x2 [%0], {%1,%2,%3,%4};" :: "l"(gr), "r"(y0), "r"(y1), "r"(y2), "r"(cnt ? 0x3c00u : y3) : "memory");
        bar_arrive(B_RED, 384);
        if constexpr (CEARLY && !hf) { bar_arrive(B_C, 256); bar_sync(B_G, 256); }
        else bar_sync(B_C, 256);
        TS(7);
      }
#if CHAIN_TIMING
      x_gemm((s + 1) & 1, tsb);
#else
      x_gemm((s + 1) & 1, 0);
#endif
      TS(8);
    }
    };
    if (hf == 0) run(IC<0>{}); else run(IC<1>{});
    {
      const uint32_t l16 = sb + (threadIdx.x & 31) * 16, mema = l16 ^ ((l16 >> 2) & 96);
      float c0[4] = {0, 0, 0, 0}, c1[4] = {0, 0, 0, 0}, c2[4] = {0, 0, 0, 0}, c3[4] = {0, 0, 0, 0};
      bar_sync(hf ? B_MEM1 : B_MEM0, 256);
      const float sc = __uint_as_float(lds32_i<SC_IN + 16>(sb)) * iw;
      static_for<0, 10>([&](auto T) {
        constexpr int p = 2 * T.value;
        uint32_t b0[4], b1[4];
        ldsm_x4_i<OFF_MEM + p * 512>(b0, mema); ldsm_x4_i<OFF_MEM + p * 512 + 512>(b1, mema);
        mma16816h(c0, w[2 * p], b0[0], b0[1]); mma16816h(c1, w[2 * p + 1], b0[2], b0[3]);
        mma16816h(c2, w[2 * p + 2], b1[0], b1[1]); mma16816h(c3, w[2 * p + 3], b1[2], b1[3]);
      });
      stsm_x2_t_i<OFF_KV + 2 * KVB + 512>(l16 + (l16 & 128) * 4 + wi * 1280 + hf * KVB, pack_bf16(((c0[0] + c1[0]) + (c2[0] + c3[0])) * sc, ((c0[1] + c1[1]) + (c2[1] + c3[1])) * sc),
                                          pack_bf16(((c0[2] + c1[2]) + (c2[2] + c3[2])) * sc, ((c0[3] + c1[3]) + (c2[3] + c3[3])) * sc));
      fence_proxy_async();
    }
    bar_arrive(B_RED, 384);
#if CHAIN_TIMING
    for (int i = tid; i < 288; i += 256) a.dbg[cta * 288 + i] = lds32_i<OFF_BAR + 128>(sb + i * 4);
#endif
    asm volatile("barrier.cluster.arrive.relaxed.aligned; barrier.cluster.wait.aligned;" ::: "memory");
  }
}
struct PrepArgs { const bf16 *wqkv, *wphi, *wo; unsigned char *wb, *wot; };
__device__ __forceinline__ void prep_body(const int cta, const PrepArgs& pa) {
  const int tid = threadIdx.x, lane = tid & 31, warp = tid >> 5, g = lane >> 2, q = lane & 3;
  const int pair = cta >> 1, which = cta & 1;
  uint32_t bfr[2][3][3];
#pragma unroll
  for (int hh = 0; hh < 2; hh++)
#pragma unroll
    for (int t = 0; t < 3; t++) {
      const unsigned short* ph = (const unsigned short*)pa.wphi + (2 * pair + hh) * 400 + (t < 2 ? 8 * t + g : 16 + (g >> 1)) + 2 * q * 20;
#pragma unroll
      for (int r = 0; r < 3; r++) {
        const int o = (r < 2 || q < 2) ? r * 160 : 0;
        const uint32_t v = (uint32_t)__ldg(ph + o) | ((uint32_t)__ldg(ph + o + 20) << 16);
        bfr[hh][t][r] = ((t < 2 || (g & 1) == hh) && (r < 2 || q < 2)) ? v : 0u;
      }
    }
  const int gt = cta * 256 + tid;
#pragma unroll 1
  for (int i = 0; i < 5; i++) {
    uint32_t af[2][6];
#pragma unroll
    for (int hh = 0; hh < 2; hh++) {
      const uint32_t* r0 = (const uint32_t*)(pa.wqkv + (size_t)((warp * 5 + i) * 16 + g) * 1920 + which * 640 + (2 * pair + hh) * 20) + q;
      af[hh][0] = __ldg(r0); af[hh][1] = __ldg(r0 + 7680); af[hh][2] = __ldg(r0 + 4); af[hh][3] = __ldg(r0 + 7684);
      af[hh][4] = __ldg(r0 + 8); af[hh][5] = __ldg(r0 + 7688);
    }
    const int iv = i * 4096 + (gt >> 1), k = (iv & 7) + (iv >> 8) * 8, h = (iv >> 3) & 31;
    const uint2* src = (const uint2*)(pa.wqkv + (size_t)k * 1920 + 1280 + h * 20) + (gt & 1) * 2;
    const uint2 a = __ldg(src), b = __ldg(src + 1), e = __ldg(src + 2);
    uint4 wv[2]; uint32_t wd[2];
#pragma unroll
    for (int n = 0; n < 2; n++) {
      const int iw = min((2 * i + n) * 5120 + gt, 640 * 80 - 1), r = iw & 7, c = (iw >> 3) % 80, kg = iw / 640, c5 = kg % 5;
      const int row = (kg / 5) * 40 + (c5 < 2 ? 8 * c5 + r : (c5 == 2 ? 16 + (r & 3) + (r >> 2) * 20 : 20 + 8 * (c5 - 3) + r));
      wv[n] = __ldg((const uint4*)(pa.wo + (size_t)row * cfg::DM + c * 8));
      wd[n] = (((c / 10) * 80 + kg) * 10 + c % 10) * 128 + r * 16;
    }
    uint4* dv = (uint4*)(pa.wb + ((size_t)((h >> 2) * 80 + (k >> 3)) * 32 + 20 + 3 * (h & 3)) * 128 + (k & 7) * 16);
    dv[(gt & 1) * 8] = make_uint4(a.x, a.y, b.x, b.y);
    if (gt & 1) dv[16] = (h & 1) ? make_uint4(0, 0, e.x, e.y) : make_uint4(e.x, e.y, 0, 0);
    if (gt < 5120) { *(uint4*)(pa.wot + wd[0]) = wv[0]; *(uint4*)(pa.wot + wd[1]) = wv[1]; }
    uint32_t* dst = (uint32_t*)(pa.wb + ((size_t)((pair >> 1) * 80 + (warp * 5 + i) * 2) * 32 + which * 10 + (pair & 1) * 5) * 128) + lane;
#pragma unroll
    for (int t = 0; t < 5; t++) {
      float d[4] = {0, 0, 0, 0};
#pragma unroll
      for (int hh = 0; hh < 2; hh++)
        if (t == 2 || (t > 2) == (hh == 1)) {
          const int tt = t < 3 ? t : t - 3;
          mma16816(d, af[hh][0], af[hh][1], af[hh][2], af[hh][3], bfr[hh][tt][0], bfr[hh][tt][1]);
          mma1688(d, q < 2 ? af[hh][4] : 0u, q < 2 ? af[hh][5] : 0u, bfr[hh][tt][2]);
        }
      dst[t * 32] = pack_bf16(d[0], d[1]); dst[1024 + t * 32] = pack_bf16(d[2], d[3]);
    }
  }
}

__global__ void __launch_bounds__(256, 4) ln_kernel(const bf16* __restrict__ xin, bf16* __restrict__ xn, uint2* __restrict__ xh, uint4* __restrict__ z0, int n0,
                                                    uint4* __restrict__ z1, int n1, const bf16* pfa, const bf16* pfb, int npf, int tl) {
  asm volatile("griddepcontrol.wait;" ::: "memory");
  asm volatile("griddepcontrol.launch_dependents;" ::: "memory");
  TL_BEGIN(tl);
  const int warp = threadIdx.x >> 5, lane = threadIdx.x & 31;
  const int row = blockIdx.x * 8 + warp;
  uint2 xw[1][5];
#pragma unroll
  for (int i = 0; i < 5; i++) xw[0][i] = *(const uint2*)(xin + (size_t)row * cfg::DM + i * 128 + lane * 4);
  for (int i = blockIdx.x * 256 + threadIdx.x; i < n0; i += 256 * 256) z0[i] = make_uint4(0, 0, 0, 0);
  for (int i = blockIdx.x * 256 + threadIdx.x; i < n1; i += 256 * 256) z1[i] = make_uint4(0, 0, 0, 0);
  if (npf && xw[0][4].y != 0x7fc17fc1u) {
    for (int i = 0; i < npf; i++) {
      const uint32_t l = (uint32_t)i * 32768u + (blockIdx.x * 256 + threadIdx.x) / 2;
      if (l < cfg::DM * cfg::HD / 64) asm volatile("prefetch.global.L2 [%0];" :: "l"(((threadIdx.x & 1) ? pfa : pfb) + (size_t)l * 64) : "memory");
    }
  }
  ln_rows<1>(xw, row, lane, xn, xh);
  TL_END(tl);
}
struct Pipe { uint32_t stage, phase; };
template <int NS> __device__ __forceinline__ void pipe_adv(Pipe& p) { if (++p.stage == NS) { p.stage = 0; p.phase ^= 1; } }
constexpr uint32_t SWZ128 = 1;
__device__ __forceinline__ uint64_t desc_kmajor(uint32_t a) { return make_desc(a, 16, 1024, SWZ128); }
__device__ __forceinline__ uint64_t desc_mnmajor(uint32_t a) { return make_desc(a, 8192, 1024, SWZ128); }
__device__ __forceinline__ void wait_ge(const void* p, uint32_t target, uint32_t ns = 32) {
  int spin = 0;
  while (ld_acquire_u32(p) < target) { __nanosleep(ns); if (++spin > (1 << 21)) break; }
}
__device__ __forceinline__ void bulk_g2s_hint(uint32_t dst, const void* src, uint32_t bytes, uint32_t mb, uint64_t pol) {
  asm volatile("cp.async.bulk.shared::cluster.global.mbarrier::complete_tx::bytes.L2::cache_hint [%0], [%1], %2, [%3], %4;"
               :: "r"(dst), "l"(src), "r"(bytes), "r"(mb), "l"(pol) : "memory");
}
#ifndef PF_WB
#define PF_WB 2
#endif
#ifndef PF_XN
#define PF_XN 1
#endif
#ifndef ZINIT
#define ZINIT 1
#endif
#ifndef STAG
#define STAG 1
#endif
#ifndef EF_KV
#define EF_KV 1
#endif
#ifndef EF_O
#define EF_O 1
#endif
__device__ __forceinline__ void fence_proxy_async_global() { asm volatile("fence.proxy.async.global;" ::: "memory"); }

namespace tr {
constexpr int NS = 4, STQ = 16384 + 24576, STO = 16384 + 40960;
constexpr int SEGB = 15360;
constexpr int OFF_K = NS * STQ;
constexpr int OFF_BAR = NS * STO;
constexpr int SMEM = OFF_BAR + 256;
static_assert(OFF_K + 4 * SEGB <= OFF_BAR && SMEM <= 232448, "smem");
enum { T_QA = 0, T_Q, T_A, T_OB, T_OS, T_L, T_END, T_P };
constexpr uint32_t C_QA = AR_CNT, C_O = AR_CNT + 64, C_Q = AR_CNT + 128, C_P = AR_CNT + 192;
constexpr int MAXITEMS = 1200;
struct Sched {
  uint8_t ks[16];
  uint8_t wide[16];
  uint8_t lrows[16];
  uint32_t n;
  uint16_t item[MAXITEMS];
};
struct Args {
  const unsigned char *kg, *vg;
  unsigned char* o;
  uint4* qs;
  unsigned char* part;
  const bf16 *xin, *xq;
  bf16 *xout, *xn;
  unsigned char* arena;
  const unsigned* go;
  int tl;
  uint32_t nap, nap2;
  int pfprep;
};
}

template <int N0, int N1>
__device__ __forceinline__ void tr_mainloop(float (&a0)[N0 / 2], float (&a1)[N1 ? N1 / 2 : 1], Pipe& p, uint32_t sb, uint32_t full, uint32_t empty, int nkb, int wg) {
  using namespace tr;
  constexpr uint32_t ST = N1 ? STO : STQ;
  uint32_t prev = 0;
#pragma unroll
  for (int i = 0; i < N0 / 2; i++) { if (ZINIT) a0[i] = 0.f; else asm volatile("" : "=f"(a0[i])); }
  if constexpr (N1 > 0) {
#pragma unroll
    for (int i = 0; i < N1 / 2; i++) a1[i] = 0.f;
  }
#pragma unroll 1
  for (int kb = 0; kb < nkb; kb++) {
    mbar_wait(full + 8 * p.stage, p.phase);
    const uint32_t st = ((sb & 0x3FFFF) >> 4) + p.stage * (ST / 16), sa = st + wg * 512;
    wgmma_fence();
#pragma unroll
    for (int kk = 0; kk < 4; kk++) {
      const uint64_t da = desc16<16, 1024, 1>(sa, kk * 32);
      if constexpr (N0 == 192) wgmma_n192<0, 1>(a0, da, desc16<8192, 1024, 1>(st, 16384 + kk * 2048), (kb | kk) != 0);
      else wgmma_n128<0, 1>(a0, da, desc16<8192, 1024, 1>(st, 16384 + kk * 2048), (kb | kk) != 0);
      if constexpr (N1 > 0) wgmma_n128<0, 1>(a1, da, desc16<8192, 1024, 1>(st, 16384 + 24576 + kk * 2048), (kb | kk) != 0);
    }
    wgmma_commit();
    if (kb > 0) { wgmma_wait<1>(); mbar_arrive_if((threadIdx.x & 127) == 0, empty + 8 * prev); }
    prev = p.stage;
    pipe_adv<NS>(p);
  }
  wgmma_wait<0>();
  mbar_arrive_if((threadIdx.x & 127) == 0, empty + 8 * prev);
}
template <int N> __device__ __forceinline__ void stage_tiles(const float (&o)[N / 2], uint32_t base, int wi, int lane) {
  const uint32_t ra = base + (wi * 16 + (lane & 7) + 8 * ((lane >> 3) & 1)) * 128;
#pragma unroll
  for (int v = 0; v < N / 8; v += 2)
    stsm_x4(ra + (v >> 3) * 8192 + ((((v & 7) + (lane >> 4)) ^ (lane & 7)) << 4), pack_bf16(o[4 * v], o[4 * v + 1]), pack_bf16(o[4 * v + 2], o[4 * v + 3]),
            pack_bf16(o[4 * v + 4], o[4 * v + 5]), pack_bf16(o[4 * v + 6], o[4 * v + 7]));
}
__global__ void __launch_bounds__(384, 1) trail_kernel(const __grid_constant__ CUtensorMap tmX, const __grid_constant__ CUtensorMap tmQ,
                                                       const __grid_constant__ CUtensorMap tmWo5, const __grid_constant__ CUtensorMap tmWo2,
                                                       const __grid_constant__ CUtensorMap tmP, const __grid_constant__ tr::Sched sc,
                                                       const __grid_constant__ tr::Args a, const __grid_constant__ PrepArgs pa) {
  using namespace tr;
  [[maybe_unused]] const int tl = a.tl;
  TL_BEGIN(tl);
  extern __shared__ __align__(1024) unsigned char smem_raw[];
  const uint32_t sb = smem_u32(smem_raw);
  const int warp = __shfl_sync(0xffffffffu, (int)threadIdx.x >> 5, 0), lane = threadIdx.x & 31;
  unsigned char* const arena = a.arena;
  const uint32_t full = sb + OFF_BAR, empty = full + 8 * NS, barK = empty + 8 * NS, barKfree = barK + 16, staged = barKfree + 16;
  const uint32_t kvrdy = staged + 32, mfull = kvrdy + 8, mempty = mfull + 16, mbox = mempty + 16;
  uint32_t go = 0;
  if (threadIdx.x == 256) go = ld_acquire_u32(a.go);
  if (threadIdx.x == 0) {
    for (int i = 0; i < NS; i++) { mbar_init(full + 8 * i, 1); mbar_init(empty + 8 * i, 2); }
    for (int i = 0; i < 2; i++) {
      mbar_init(barK + 8 * i, 1); mbar_init(barKfree + 8 * i, 1); mbar_init(staged + 16 * i, 4); mbar_init(staged + 16 * i + 8, 4);
      mbar_init(mfull + 8 * i, 1); mbar_init(mempty + 8 * i, 11);
    }
    mbar_init(kvrdy, 1);
    asm volatile("fence.mbarrier_init.release.cluster;" ::: "memory");
  }
  __syncthreads();
  Pipe mp{0, 0};
  auto next_item = [&]() -> uint32_t {
    uint32_t it;
    mbar_wait(mfull + 8 * mp.stage, mp.phase);
    asm volatile("ld.shared.u32 %0, [%1];" : "=r"(it) : "r"(mbox + 4 * mp.stage) : "memory");
    return it;
  };
  if (warp >= 8) {
    asm volatile("setmaxnreg.dec.sync.aligned.u32 40;");
    if (warp == 8) { go = __shfl_sync(0xffffffffu, go, 0); if (elect_one()) {
      Pipe p{0, 1};
      mp.phase = 1;
      uint32_t kph = 1, rph = 0, wide = 0, qdone = 0;
      prefetch_tmap(&tmX); prefetch_tmap(&tmQ); prefetch_tmap(&tmWo5); prefetch_tmap(&tmWo2); prefetch_tmap(&tmP);
      const uint64_t ef = policy_evict_first();
      auto ld_kv = [&](uint32_t d, const void* s, uint32_t n, uint32_t mb) { if (EF_KV) bulk_g2s_hint(d, s, n, mb, ef); else bulk_g2s(d, s, n, mb); };
      auto ld_o = [&](uint32_t d, const void* s, uint32_t n, uint32_t mb) { if (EF_O) bulk_g2s_hint(d, s, n, mb, ef); else bulk_g2s(d, s, n, mb); };
      auto stage = [&](uint32_t bytes) -> uint32_t {
        mbar_wait(empty + 8 * p.stage, p.phase);
        mbar_expect_tx(full + 8 * p.stage, bytes);
        return sb + p.stage * (wide ? STO : STQ);
      };
      auto fetch = [&]() -> uint32_t { uint32_t v; asm volatile("atom.relaxed.gpu.global.add.u32 %0, [%1], 1;" : "=r"(v) : "l"(arena + AR_QUEUE) : "memory"); return v; };
      if (!go) wait_ge(a.go, 1, 200);
      fence_proxy_async_global();
      uint32_t next = fetch();
      while (true) {
        const uint32_t item = next;
        const uint32_t code = sc.item[min(item, sc.n)];
        const int type = (code >> 11) & 7, m = (code >> 7) & 15, k = code & 127;
        const bool late = code >> 14;
        auto done_wait = [&]() { mbar_wait(mempty + 8 * (mp.stage ^ 1), mp.stage ? mp.phase ^ 1 : mp.phase); };
        if (type == T_A && !((qdone >> m) & 1)) { wait_ge(arena + C_Q + m * 4, 64); qdone |= 1u << m; }
        if (type == T_OB && !wide) for (uint32_t i = 0; i < NS; i++) mbar_wait(empty + 8 * i, i >= p.stage ? p.phase : p.phase ^ 1);
        wide = type == T_OB;
        mbar_wait(mempty + 8 * mp.stage, mp.phase);
        asm volatile("st.shared.u32 [%0], %1;" :: "r"(mbox + 4 * mp.stage), "r"((p.stage << 24) | (type << 16) | (m << 8) | (k & 255)) : "memory");
        mbar_arrive(mfull + 8 * mp.stage);
        pipe_adv<2>(mp);
        if (type == T_END) break;
        if (type == T_P) { done_wait(); next = fetch(); continue; }
        if (type == T_L) {
          const int nr = sc.lrows[m], np = sc.ks[m];
          prefetch_l2(a.xin + (size_t)(m * 128 + k * 8 * nr) * cfg::DM, nr * 10240);
          wait_ge(arena + C_O + m * 4, np * (sc.wide[m] ? 4 : 10), m < 13 ? a.nap : 32);
          fence_proxy_async_global();
#pragma unroll 1
          for (int r = 0; r < nr; r++) {
            const int rg = m * 16 + k * nr + r;
#pragma unroll 1
            for (int q0 = 0; q0 <= np; q0 += 4) {
              const int n = min(4, np + 1 - q0);
              const uint32_t st = stage(n * 10240), fb = full + 8 * p.stage;
#pragma unroll 1
              for (int q = q0; q < q0 + n; q++) {
                if (q == 0) bulk_g2s(st, a.xin + (size_t)rg * 8 * cfg::DM, 10240, fb);
                else tma_load_3d(st + (q - q0) * 10240, &tmP, 0, rg & 7, ((q - 1) * 32 + (rg >> 3)) * 10, fb);
              }
              pipe_adv<NS>(p);
            }
          }
          if (late) done_wait();
          next = fetch(); continue;
        }
        if (type <= T_A) {
          if (type != T_A)
#pragma unroll 1
            for (int kb = 0; kb < 10; kb++) {
              const uint32_t st = stage(STQ), fb = full + 8 * p.stage;
              tma_load_2d(st, &tmX, kb * 64, m * 128, fb);
              tma_load_3d(st + 16384, &tmQ, 0, kb * 64, k * 3, fb);
              pipe_adv<NS>(p);
              if (type == T_Q && kb == 8) next = fetch();
            }
          if (type != T_Q) {
            const size_t blk = ((size_t)m * 4 * 96 + k * 3) * 5120;
            kph ^= 1;
            mbar_wait(kvrdy, rph); rph ^= 1;
            if (!late) next = fetch();
            fence_proxy_async_global();
#pragma unroll 1
            for (int w = type == T_A ? 0 : 2; w < 4; w++) {
              const uint32_t st = stage(2 * SEGB), fb = full + 8 * p.stage;
              for (int sg = 0; sg < 2; sg++) ld_kv(st + sg * SEGB, (w < 2 ? a.kg : a.vg) + blk + (size_t)(2 * (w & 1) + sg) * (96 * 5120), SEGB, fb);
              pipe_adv<NS>(p);
            }
            if (late) { done_wait(); next = fetch(); }
          }
        } else {
          const int nn = wide ? 2 : 5, nb = wide ? 5 : 2, nt = k % nn, nkb = 96 / sc.ks[m], k0 = (k / nn) * nkb;
          const Pipe p0 = p;
          for (int kb = 0; kb < nkb; kb++) {
            if (wide && kb < NS && p.stage >= 2) { mbar_wait(barKfree, kph); mbar_wait(barKfree + 8, kph); }
            const uint32_t st = stage(16384 + nb * 8192), fb = full + 8 * p.stage;
            tma_load_3d(st + 16384, wide ? &tmWo5 : &tmWo2, 0, (k0 + kb) * 64, nt * nb, fb);
            if (kb >= NS) ld_o(st, a.o + ((size_t)m * 96 + k0 + kb) * 16384, 16384, fb);
            pipe_adv<NS>(p);
            if (kb == NS - 1 || (kb == nkb - 1 && nkb < NS)) {
              wait_ge(arena + C_QA + m * 4, 64, m < 14 ? a.nap : 32);
              fence_proxy_async_global();
              Pipe q = p0;
#pragma unroll 1
              for (int i = 0; i <= kb; i++) { ld_o(sb + q.stage * (wide ? STO : STQ), a.o + ((size_t)m * 96 + k0 + i) * 16384, 16384, full + 8 * q.stage); pipe_adv<NS>(q); }
            }
          }
          if (!late) next = fetch();
          for (int w = wide ? -(int)((2 - p.stage) & 3) : 0; w < 2; w++) { mbar_wait(empty + 8 * p.stage, p.phase); mbar_arrive(full + 8 * p.stage); pipe_adv<NS>(p); }
          kph ^= wide;
          if (late) { done_wait(); next = fetch(); }
        }
      }
    } } else if (warp < 11) { if (elect_one()) {
      const int w = warp - 9;
      uint32_t sph = 0;
      [[maybe_unused]] int nlog = 0;
#ifdef TIMELINE
      if (w == 0) { unsigned long long* lg = g_log + (((tl >= 12) * 132 + blockIdx.x) * 64 + nlog++) * 2; lg[0] = T_END << 16; lg[1] = gtime(); lg[2] = ~0ull; }
#endif
      while (true) {
        const uint32_t it = next_item();
        const int type = (it >> 16) & 255, m = (it >> 8) & 255, k = it & 255;
        const uint32_t slot = mp.stage;
        pipe_adv<2>(mp);
        if (type == T_END) break;
        mbar_wait(staged + 16 * w + 8 * slot, (sph >> slot) & 1); sph ^= 1u << slot;
        mbar_arrive(mempty + 8 * slot);
#ifdef TIMELINE
        if (w == 0 && nlog < 63) { unsigned long long* lg = g_log + (((tl >= 12) * 132 + blockIdx.x) * 64 + nlog++) * 2; lg[0] = (type << 16) | (m << 8) | k; lg[1] = gtime(); lg[2] = ~0ull; }
#endif
        if (type == T_L) continue;
        if (type == T_QA || type == T_A) {
          for (int jj = 0; jj < 3; jj++) bulk_s2g(a.o + ((size_t)m * 96 + k * 3 + jj) * 16384 + w * 8192, sb + OFF_K + w * 2 * SEGB + jj * 8192, 8192);
          bulk_commit();
          bulk_wait<0>();
          mbar_arrive(barKfree + 8 * w);
        } else if (type == T_OB || type == T_OS) {
          const bool wide = type == T_OB;
          const int nn = wide ? 2 : 5, nb = wide ? 5 : 2;
          const uint32_t own = wide ? 2 + w : ((it >> 24) + 96 / sc.ks[m] + w) % NS;
          bulk_s2g(a.part + ((size_t)((k / nn) * 32 + m * 2 + w) * 10 + (k % nn) * nb) * 8192, sb + own * (wide ? STO : STQ), nb * 8192);
          bulk_commit();
          bulk_wait<0>();
          mbar_arrive(empty + 8 * own);
          if (wide && w) { mbar_arrive(barKfree); mbar_arrive(barKfree + 8); }
        }
        red_release_inc(arena + (type == T_Q ? C_Q : (type <= T_A ? C_QA : (type == T_P ? C_P : C_O))) + m * 4);
      }
    } } else if (elect_one()) {
      const uint64_t ef = policy_evict_first();
      uint32_t kph = 1;
      if (PF_WB && blockIdx.x >= 52) { prefetch_l2(pa.wb + (blockIdx.x - 52) * 32768, 32768); prefetch_l2(pa.wot + (blockIdx.x - 52) * 10240, 10240); }
      if (PF_WB > 1 && blockIdx.x >= 52) { prefetch_l2(a.xn + (blockIdx.x - 52) * 8192, 16384); prefetch_l2(a.xout + (blockIdx.x - 52) * 8192, 16384); }
      while (true) {
        const uint32_t it = next_item();
        const int type = (it >> 16) & 255, m = (it >> 8) & 255, k = it & 255;
        const uint32_t slot = mp.stage;
        pipe_adv<2>(mp);
        if (type == T_END) break;
        if (a.pfprep && type == T_QA && m == 0) { prefetch_l2(pa.wqkv + k * 38400, 76800); prefetch_l2(pa.wo + k * 12800, 25600); }
        if (PF_XN && type == T_QA && m < 15) prefetch_l2(a.xq + ((m + 1) * 128 + k * 4) * cfg::DM, 5120);
        if (type == T_QA || type == T_A) {
          for (int spin = 0; spin < (1 << 21); spin++) {
            uint4 f;
            asm volatile("ld.acquire.gpu.global.v4.u32 {%0,%1,%2,%3}, [%4];" : "=r"(f.x), "=r"(f.y), "=r"(f.z), "=r"(f.w) : "l"(arena + prog_off(k, 0)) : "memory");
            if (min(min(f.x, f.y), f.z) >= (uint32_t)(4 * m + 4)) break;
            __nanosleep(m < 15 ? a.nap : a.nap2);
          }
          mbar_arrive(kvrdy);
          fence_proxy_async_global();
          const unsigned char* src = a.kg + ((size_t)m * 4 * 96 + k * 3) * 5120;
#pragma unroll 1
          for (int w = 0; w < 2; w++) {
            mbar_wait(barKfree + 8 * w, kph);
            if (type == T_A) { mbar_arrive(barK + 8 * w); continue; }
            mbar_expect_tx(barK + 8 * w, 2 * SEGB);
            for (int sg = 2 * w; sg < 2 * w + 2; sg++) { if (EF_KV) bulk_g2s_hint(sb + OFF_K + sg * SEGB, src + (size_t)sg * (96 * 5120), SEGB, barK + 8 * w, ef); else bulk_g2s(sb + OFF_K + sg * SEGB, src + (size_t)sg * (96 * 5120), SEGB, barK + 8 * w); }
          }
          kph ^= 1;
        } else if (type == T_OB) {
          mbar_wait(barKfree, kph); mbar_wait(barKfree + 8, kph);
          kph ^= 1;
        }
        mbar_arrive(mempty + 8 * slot);
      }
      if (blockIdx.x == gridDim.x - 1) asm volatile("griddepcontrol.wait;" ::: "memory");
    }
    return;
  }
  asm volatile("setmaxnreg.inc.sync.aligned.u32 232;");
  const int wg = warp >> 2, wi = warp & 3;
  const int g = lane >> 2, q4 = lane & 3;
  asm volatile("griddepcontrol.launch_dependents;" ::: "memory");
  Pipe p{0, 0};
  uint32_t kph = 0;
  auto own_slot = [&]() -> uint32_t {
    const uint32_t sA = p.stage, phA = p.phase; pipe_adv<NS>(p);
    const uint32_t sB = p.stage, phB = p.phase; pipe_adv<NS>(p);
    mbar_wait_if(wi == 0, full + 8 * (wg ? sA : sB), wg ? phA : phB);
    mbar_wait(full + 8 * (wg ? sB : sA), wg ? phB : phA);
    mbar_arrive_if((threadIdx.x & 127) == 0, empty + 8 * (wg ? sA : sB));
    return wg ? sB : sA;
  };
  while (true) {
    const uint32_t it = __shfl_sync(0xffffffffu, next_item(), 0);
    const int type = (it >> 16) & 255, m = (it >> 8) & 255, k = it & 255;
    mbar_arrive_if(lane == 0, mempty + 8 * mp.stage);
    const uint32_t done = staged + 16 * wg + 8 * mp.stage;
    pipe_adv<2>(mp);
    if (type == T_END) break;
    if (type == T_P) {
      prep_body(k, pa);
      bar_sync(3 + wg, 128);
      mbar_arrive_if(lane == 0, done);
      continue;
    }
    if (type == T_L) {
      const int nr = sc.lrows[m], np = sc.ks[m];
      const uint32_t po = (lane >> 4) * 1024 + warp * 128 + ((((lane >> 1) & 7) ^ warp) << 4) + (lane & 1) * 8;
#pragma unroll 1
      for (int r = 0; r < nr; r++) {
        uint2 xw[1][5]; float s[20];
#pragma unroll
        for (int i = 0; i < 20; i++) s[i] = 0.f;
#pragma unroll 1
        for (int q0 = 0; q0 <= np; q0 += 4) {
          const uint32_t st = sb + p.stage * STQ;
          mbar_wait(full + 8 * p.stage, p.phase);
          if (q0 == 0) static_for<0, 5>([&](auto I) { xw[0][I.value] = lds64_i<I.value * 256>(st + warp * 1280 + lane * 8); });
#pragma unroll 1
          for (int q = q0 ? 0 : 1; q < min(4, np + 1 - q0); q++)
            static_for<0, 5>([&](auto I) {
              constexpr int i = I.value;
              const uint2 t = lds64_i<i * 2048>(st + q * 10240 + po);
              s[4 * i] += bf_lo(t.x); s[4 * i + 1] += bf_hi(t.x); s[4 * i + 2] += bf_lo(t.y); s[4 * i + 3] += bf_hi(t.y);
            });
          bar_sync(3 + wg, 128);
          mbar_arrive_if((threadIdx.x & 127) == 0, empty + 8 * p.stage);
          pipe_adv<NS>(p);
        }
        const int row = (m * 16 + k * nr + r) * 8 + warp;
#pragma unroll
        for (int i = 0; i < 5; i++) {
          bf16r2(s[4 * i], s[4 * i + 1]); bf16r2(s[4 * i + 2], s[4 * i + 3]);
          xw[0][i] = make_uint2(pack_bf16(bf_lo(xw[0][i].x) + s[4 * i], bf_hi(xw[0][i].x) + s[4 * i + 1]), pack_bf16(bf_lo(xw[0][i].y) + s[4 * i + 2], bf_hi(xw[0][i].y) + s[4 * i + 3]));
          *(uint2*)(a.xout + (size_t)row * cfg::DM + i * 128 + lane * 4) = xw[0][i];
        }
        ln_rows<1>(xw, row, lane, a.xn, nullptr);
      }
      __syncwarp();
      mbar_arrive_if(lane == 0, done);
      continue;
    }
    if (type >= T_OB) {
      const int nkb = 96 / sc.ks[m];
      if (type == T_OB) {
        float a0[96], a1[64];
        tr_mainloop<192, 128>(a0, a1, p, sb, full, empty, nkb, wg);
        while (p.stage != 2) { mbar_wait_if(wi == 0, full + 8 * p.stage, p.phase); mbar_arrive_if((threadIdx.x & 127) == 0, empty + 8 * p.stage); pipe_adv<NS>(p); }
        const uint32_t st = sb + own_slot() * STO;
        stage_tiles<192>(a0, st, wi, lane); stage_tiles<128>(a1, st + 24576, wi, lane);
      } else {
        float a0[64], a1[1];
        tr_mainloop<128, 0>(a0, a1, p, sb, full, empty, nkb, wg);
        stage_tiles<128>(a0, sb + own_slot() * STQ, wi, lane);
      }
      fence_proxy_async();
      __syncwarp();
      mbar_arrive_if(lane == 0, done);
      continue;
    }
    uint32_t qf[12][4];
    uint4* qp = a.qs + ((size_t)((m & 7) * 32 + k) * 12) * 256 + threadIdx.x;
    if (type != T_A) {
      float acc[96], a1[1];
      tr_mainloop<192, 0>(acc, a1, p, sb, full, empty, 10, wg);
#pragma unroll
      for (int i = 0; i < 12; i++) {
        qf[i][0] = pack_bf16(acc[8 * i], acc[8 * i + 1]); qf[i][1] = pack_bf16(acc[8 * i + 2], acc[8 * i + 3]);
        qf[i][2] = pack_bf16(acc[8 * i + 4], acc[8 * i + 5]); qf[i][3] = pack_bf16(acc[8 * i + 6], acc[8 * i + 7]);
      }
      if (type == T_Q) {
#pragma unroll
        for (int i = 0; i < 12; i++) qp[i * 256] = make_uint4(qf[i][0], qf[i][1], qf[i][2], qf[i][3]);
        __syncwarp();
        mbar_arrive_if(lane == 0, done);
        continue;
      }
    } else {
#pragma unroll
      for (int i = 0; i < 12; i++) { const uint4 v = __ldcg(qp + i * 256); qf[i][0] = v.x; qf[i][1] = v.y; qf[i][2] = v.z; qf[i][3] = v.w; }
    }
    const uint32_t ost = sb + OFF_K + wg * 2 * SEGB;
    const bool second = wi >= 2;
    uint32_t pf[5][4];
    {
      float sa[20], sb2[20];
      uint32_t kbase = ost, kslot = 0;
      if (type == T_A) { kslot = own_slot(); kbase = sb + kslot * STQ; } else mbar_wait(barK + 8 * wg, kph);
      kbase = (kbase & 0x3FFFF) >> 4;
      if (STAG && wg) bar_sync(1, 256);
      wgmma_fence();
#pragma unroll
      for (int i = 0; i < 12; i++) {
        wgmma_rs_n40<0>(sa, qf[i][0], qf[i][1], qf[i][2], qf[i][3], desc16<640, 128, 0>(kbase, i * 1280), i != 0);
        wgmma_rs_n40<0>(sb2, qf[i][0], qf[i][1], qf[i][2], qf[i][3], desc16<640, 128, 0>(kbase, SEGB + i * 1280), i != 0);
      }
      wgmma_commit();
      if (STAG && !wg) bar_arrive(1, 256);
      wgmma_wait<0>();
      mbar_arrive_if(type == T_A && (threadIdx.x & 127) == 0, empty + 8 * kslot);
      const float cs = 0.07216878364870322f * 1.4426950408889634f;
      const int r0 = 16 * (wi & 1) + g, r1 = r0 + 8;
      float m0 = -INFINITY, m1 = -INFINITY;
#pragma unroll
      for (int n = 0; n < 5; n++) {
#pragma unroll
        for (int e = 0; e < 2; e++) {
          const int key = 8 * n + 2 * q4 + e;
          float x = second ? sb2[4 * n + e] : sa[4 * n + e], y = second ? sb2[4 * n + 2 + e] : sa[4 * n + 2 + e];
          if (n < 4) { if (key > r0) x = -INFINITY; if (key > r1) y = -INFINITY; }
          sa[4 * n + e] = x; sa[4 * n + 2 + e] = y;
          m0 = fmaxf(m0, x); m1 = fmaxf(m1, y);
        }
      }
      m0 = fmaxf(fmaxf(m0, __shfl_xor_sync(0xffffffffu, m0, 1)), fmaxf(__shfl_xor_sync(0xffffffffu, m0, 2), __shfl_xor_sync(0xffffffffu, m0, 3)));
      m1 = fmaxf(fmaxf(m1, __shfl_xor_sync(0xffffffffu, m1, 1)), fmaxf(__shfl_xor_sync(0xffffffffu, m1, 2), __shfl_xor_sync(0xffffffffu, m1, 3)));
      m0 *= -cs; m1 *= -cs;
      float s0 = 0.f, s1 = 0.f;
#pragma unroll
      for (int n = 0; n < 5; n++) {
#pragma unroll
        for (int e = 0; e < 2; e++) {
          sa[4 * n + e] = ex2f(fmaf(sa[4 * n + e], cs, m0)); sa[4 * n + 2 + e] = ex2f(fmaf(sa[4 * n + 2 + e], cs, m1));
          s0 += sa[4 * n + e]; s1 += sa[4 * n + 2 + e];
        }
      }
      s0 = (s0 + __shfl_xor_sync(0xffffffffu, s0, 1)) + (__shfl_xor_sync(0xffffffffu, s0, 2) + __shfl_xor_sync(0xffffffffu, s0, 3));
      s1 = (s1 + __shfl_xor_sync(0xffffffffu, s1, 1)) + (__shfl_xor_sync(0xffffffffu, s1, 2) + __shfl_xor_sync(0xffffffffu, s1, 3));
      const float i0 = rcpf(s0), i1 = rcpf(s1);
#pragma unroll
      for (int n = 0; n < 5; n++) {
        const uint32_t x = pack_bf16(sa[4 * n] * i0, sa[4 * n + 1] * i0), y = pack_bf16(sa[4 * n + 2] * i1, sa[4 * n + 3] * i1);
        if (n < 4) {
          pf[n >> 1][2 * (n & 1)] = second ? 0u : x; pf[n >> 1][2 * (n & 1) + 1] = second ? 0u : y;
          pf[2 + (n >> 1)][2 * (n & 1)] = second ? x : 0u; pf[2 + (n >> 1)][2 * (n & 1) + 1] = second ? y : 0u;
        } else {
          pf[4][0] = second ? 0u : x; pf[4][1] = second ? 0u : y; pf[4][2] = second ? x : 0u; pf[4][3] = second ? y : 0u;
        }
      }
    }
    {
      float o[96];
#pragma unroll
      for (int i = 0; i < 5; i++) { PIN(pf[i][0]); PIN(pf[i][1]); PIN(pf[i][2]); PIN(pf[i][3]); }
      const uint32_t own = own_slot(), vbase = ((sb & 0x3FFFF) >> 4) + own * (STQ / 16);
      wgmma_fence();
#pragma unroll
      for (int i = 0; i < 5; i++)
        wgmma_rs_n192<1>(o, pf[i][0], pf[i][1], pf[i][2], pf[i][3], i < 4 ? desc16<128, 640, 0>(vbase, (i >> 1) * SEGB + (i & 1) * 256) : desc16<SEGB, 640, 0>(vbase, 512), i != 0);
      wgmma_commit();
      if (type == T_A) mbar_wait(barK + 8 * wg, kph);
      kph ^= 1;
      wgmma_wait<0>();
      mbar_arrive_if((threadIdx.x & 127) == 0, empty + 8 * own);
      stage_tiles<192>(o, ost, wi, lane);
      fence_proxy_async();
      __syncwarp();
      mbar_arrive_if(lane == 0, done);
    }
  }
}
namespace bf {
constexpr int NS = 4, STAGE = 16384 + 32768;
constexpr int PIECE = 20480;
constexpr int OFF_PHI = 0, OFF_V = 40960, OFF_KV = 65536;
constexpr int OFF_OST = 5 * PIECE;
constexpr int OFF_WOT = 6 * PIECE;
constexpr int OFF_BAR = OFF_WOT + 102400;
constexpr int SMEM = OFF_BAR + 256;
static_assert(NS * STAGE <= OFF_BAR && SMEM <= 232448, "smem");
constexpr int KVACC = 32 * 5 * 1024;
struct Args {
  const unsigned char *wb, *wot;
  unsigned char *kvacc, *o2;
  const bf16* xin;
  bf16* xout;
  unsigned* go;
  const void* prep;
  const bf16 *pf0, *pf1;
  int pfn, pfns, pfwait;
  int tl;
};
}
__device__ __forceinline__ void hedgehog_features(float (&x)[2][5], uint32_t (&w)[2][5]) {
  const float L = 1.4426950408889634f;
  float mx[2], mn[2], sp[2], sn[2], pos[2][5], neg[2][5];
#pragma unroll
  for (int r = 0; r < 2; r++) {
    mx[r] = fmaxf(fmaxf(fmaxf(x[r][0], x[r][1]), fmaxf(x[r][2], x[r][3])), x[r][4]);
    mn[r] = fminf(fminf(fminf(x[r][0], x[r][1]), fminf(x[r][2], x[r][3])), x[r][4]);
  }
#pragma unroll
  for (int o = 1; o < 4; o <<= 1)
#pragma unroll
    for (int r = 0; r < 2; r++) {
      const uint32_t t = __shfl_xor_sync(0xffffffffu, __byte_perm(__float_as_uint(mn[r]), __float_as_uint(mx[r]), 0x7632), o);
      mx[r] = fmaxf(mx[r], bf_hi(t)); mn[r] = fminf(mn[r], bf_lo(t));
    }
#pragma unroll
  for (int r = 0; r < 2; r++) {
#pragma unroll
    for (int i = 0; i < 5; i++) { pos[r][i] = ex2f((x[r][i] - mx[r]) * L); neg[r][i] = ex2f((mn[r] - x[r][i]) * L); }
    sp[r] = ((pos[r][0] + pos[r][1]) + (pos[r][2] + pos[r][3])) + pos[r][4];
    sn[r] = ((neg[r][0] + neg[r][1]) + (neg[r][2] + neg[r][3])) + neg[r][4];
  }
#pragma unroll
  for (int o = 1; o < 4; o <<= 1)
#pragma unroll
    for (int r = 0; r < 2; r++) { sp[r] += __shfl_xor_sync(0xffffffffu, sp[r], o); sn[r] += __shfl_xor_sync(0xffffffffu, sn[r], o); }
#pragma unroll
  for (int r = 0; r < 2; r++) {
    const float ip = rcpf(sp[r]), in_ = rcpf(sn[r]);
    w[r][0] = pack_bf16(pos[r][0] * ip, pos[r][1] * ip); w[r][1] = pack_bf16(pos[r][2] * ip, pos[r][3] * ip);
    w[r][2] = pack_bf16(neg[r][0] * in_, neg[r][1] * in_); w[r][3] = pack_bf16(neg[r][2] * in_, neg[r][3] * in_);
    w[r][4] = pack_bf16(pos[r][4] * ip, neg[r][4] * in_);
  }
}
__device__ __forceinline__ void bulk_g2s_mc(uint32_t dst, const void* src, uint32_t bytes, uint32_t mb) {
  asm volatile("cp.async.bulk.shared::cluster.global.mbarrier::complete_tx::bytes.multicast::cluster [%0], [%1], %2, [%3], %4;"
               :: "r"(dst), "l"(src), "r"(bytes), "r"(mb), "h"((unsigned short)3) : "memory");
}
__device__ __forceinline__ void mbar_arrive_remote_if(bool c, uint32_t b) {
  asm volatile("{\n.reg .pred p;\nsetp.ne.u32 p, %1, 0;\n@p mbarrier.arrive.shared::cluster.b64 _, [%0];\n}" :: "r"(b), "r"((uint32_t)c) : "memory");
}

__global__ void __cluster_dims__(2, 1, 1) __launch_bounds__(384, 1) blayer_kernel(const __grid_constant__ CUtensorMap tmA, const __grid_constant__ bf::Args a) {
  using namespace bf;
  [[maybe_unused]] const int tl = a.tl;
  extern __shared__ __align__(1024) unsigned char smem_raw[];
  const uint32_t sb = smem_u32(smem_raw);
  const int warp = __shfl_sync(0xffffffffu, (int)threadIdx.x >> 5, 0), lane = threadIdx.x & 31;
  const uint32_t full = sb + OFF_BAR, empty = full + 8 * NS, full2 = empty + 8 * NS, empty2 = full2 + 64, barW = empty2 + 16, drained = barW + 8, staged = drained + 8, freeb = staged + 8;
  const int rank = blockIdx.x & 1, u = (blockIdx.x >> 1) & 7, mp = blockIdx.x >> 4;
  const int m = 2 * mp + rank;
  const int m2 = 2 * mp + (u & 1), ns = (u & ~1) + rank;
  const uint32_t dpeer = mapa_u32(sb, rank ^ 1) - sb;
  unsigned* cntO = (unsigned*)(a.kvacc + KVACC);
  if (threadIdx.x == 0) {
    for (int i = 0; i < NS; i++) { mbar_init(full + 8 * i, 1); mbar_init(empty + 8 * i, 4); }
    for (int i = 0; i < 8; i++) mbar_init(full2 + 8 * i, 1);
    mbar_init(empty2, 2); mbar_init(empty2 + 8, 2);
    mbar_init(barW, 1); mbar_init(drained, 1); mbar_init(staged, 8); mbar_init(freeb, 2);
    asm volatile("fence.mbarrier_init.release.cluster;" ::: "memory");
  }
  __syncthreads();
  asm volatile("barrier.cluster.arrive.relaxed.aligned; barrier.cluster.wait.aligned;" ::: "memory");
  if (warp >= 8) {
    asm volatile("setmaxnreg.dec.sync.aligned.u32 40;");
    if (warp == 8) { if (elect_one()) {
      const unsigned char* wsrc = a.wb + (size_t)u * 327680 + rank * 16384;
      if (a.prep) wait_ge(a.prep, 64);
      fence_proxy_async_global();
      for (int kb = 0; kb < NS; kb++) {
        mbar_expect_tx(full + 8 * kb, STAGE);
        bulk_g2s_mc(sb + kb * STAGE + 16384 + rank * 16384, wsrc + kb * 32768, 16384, full + 8 * kb);
      }
      asm volatile("griddepcontrol.wait;" ::: "memory");
      TL_BEGIN0(tl);
      if (blockIdx.x == 0) *a.go = 0;
      for (int kb = 0; kb < NS; kb++) tma_load_2d(sb + kb * STAGE, &tmA, kb * 64, m * 128, full + 8 * kb);
      if (m == 0) prefetch_l2(a.kvacc + u * (KVACC / 8), KVACC / 8);
#pragma unroll 1
      for (int kb = NS; kb < 10; kb++) {
        const uint32_t s = kb & 3, st = sb + s * STAGE, fb = full + 8 * s;
        mbar_wait(empty + 8 * s, ((kb >> 2) - 1) & 1);
        mbar_expect_tx(fb, STAGE);
        tma_load_2d(st, &tmA, kb * 64, m * 128, fb);
        bulk_g2s_mc(st + 16384 + rank * 16384, wsrc + kb * 32768, 16384, fb);
      }
      for (int i = 0; i < 6; i++) mbar_expect_tx(full2 + 8 * i, PIECE);
      mbar_wait(drained, 0);
      mbar_expect_tx(barW, 102400);
      bulk_g2s(sb + OFF_WOT, a.wot + (size_t)ns * 102400, 102400, barW);
      mbar_wait(staged, 0);
      bulk_s2g(a.o2 + (size_t)(m * 8 + u) * PIECE, sb + OFF_OST, PIECE);
      bulk_commit();
      bulk_wait<0>();
      mbar_arrive(freeb); mbar_arrive_remote_if(true, freeb + dpeer);
      red_release_inc(cntO + m);
      wait_ge(cntO + m2, 8, 20);
      mbar_wait(freeb, 0);
      fence_proxy_async_global();
      const unsigned char* osrc = a.o2 + (size_t)m2 * 8 * PIECE;
      for (int i = 0; i < 6; i++) bulk_g2s_mc(sb + i * PIECE + rank * (PIECE / 2), osrc + i * PIECE + rank * (PIECE / 2), PIECE / 2, full2 + 8 * i);
      for (int i = 0; i < 2; i++) {
        mbar_wait(empty2 + 8 * i, 0);
        mbar_expect_tx(full2 + 8 * (6 + i), PIECE);
        bulk_g2s(sb + i * PIECE, osrc + (6 + i) * PIECE, PIECE, full2 + 8 * (6 + i));
      }
    } } else if (warp == 9 && a.pf0) { if (elect_one()) {
      if (a.pfwait) asm volatile("griddepcontrol.wait;" ::: "memory");
      constexpr uint32_t CH = 2048;
      for (int i = 0; i < a.pfn; i++) {
        prefetch_l2((const unsigned char*)a.pf0 + (i * 128 + blockIdx.x) * CH, CH); prefetch_l2((const unsigned char*)a.pf1 + (i * 128 + blockIdx.x) * CH, CH);
        __nanosleep(a.pfns);
      }
    } }
    return;
  }
  asm volatile("setmaxnreg.inc.sync.aligned.u32 232;");
  const int wg = warp >> 2, wi = warp & 3;
  const int q4 = lane & 3;
  const bool lead = (threadIdx.x & 127) == 0;
  const uint32_t s16 = (sb & 0x3FFFF) >> 4;
  float acc[128];
  {
#pragma unroll 1
    for (int kb = 0; kb < 10; kb++) {
      const uint32_t s = kb & 3, st = s16 + s * (STAGE / 16);
      mbar_wait(full + 8 * s, (kb >> 2) & 1);
      wgmma_fence();
#pragma unroll
      for (int kk = 0; kk < 4; kk++) wgmma_n256<0, 1>(acc, desc16<16, 1024, 1>(st + wg * 512, kk * 32), desc16<4096, 128, 0>(st, 16384 + kk * 8192), (kb | kk) != 0);
      wgmma_commit();
      if (kb > 0 && kb < 7) { wgmma_wait<1>(); const uint32_t e = empty + 8 * ((kb - 1) & 3); mbar_arrive_if(lead, e); mbar_arrive_remote_if(lead, e + dpeer); }
    }
    wgmma_wait<0>();
    bar_sync(1, 256);
    mbar_arrive_if(threadIdx.x == 0, drained);
  }
  TL2((tl >= 12 ? 128 : 0) + 32 + 0);
  const uint32_t srow = (wg * 64 + wi * 16 + (lane & 15)) * 16 + (lane >> 4) * 2048;
  auto features = [&](auto T0, auto HH, uint32_t (&w)[2][5]) {
    constexpr int t = T0.value + 5 * (HH.value >> 1), o = (HH.value & 1) ? 3 : 0, e = HH.value & 1;
    float x[2][5];
#pragma unroll
    for (int r = 0; r < 2; r++) {
      x[r][0] = acc[4 * (t + o) + 2 * r]; x[r][1] = acc[4 * (t + o) + 2 * r + 1]; x[r][2] = acc[4 * (t + o + 1) + 2 * r]; x[r][3] = acc[4 * (t + o + 1) + 2 * r + 1];
      bf16r2(x[r][0], x[r][1]); bf16r2(x[r][2], x[r][3]);
    }
    x[0][4] = acc[4 * (t + 2) + e]; x[1][4] = acc[4 * (t + 2) + 2 + e];
    bf16r2(x[0][4], x[1][4]);
    hedgehog_features(x, w);
  };
  static_for<0, 4>([&](auto HH) {
    constexpr int hh = HH.value, t = 20 + 3 * hh;
    const uint32_t one = q4 == ((hh & 1) ? 0 : 2) ? 0x3f80u : 0u;
    const uint32_t va = sb + OFF_V + hh * 6144 + srow;
    stsm_x4(va, pack_bf16(acc[4 * t], acc[4 * t + 1]), pack_bf16(acc[4 * t + 2], acc[4 * t + 3]), pack_bf16(acc[4 * t + 4], acc[4 * t + 5]), pack_bf16(acc[4 * t + 6], acc[4 * t + 7]));
    const bool pad = (q4 >= 2) != (hh & 1);
    stsm_x2(va + 4096, pad ? one : pack_bf16(acc[4 * t + 8], acc[4 * t + 9]), pad ? one : pack_bf16(acc[4 * t + 10], acc[4 * t + 11]));
    uint32_t w[2][5];
    features(IC<10>{}, HH, w);
    const uint32_t pa = sb + OFF_PHI + hh * 10240 + srow;
    stsm_x4(pa, w[0][0], w[1][0], w[0][1], w[1][1]);
    stsm_x4(pa + 4096, w[0][2], w[1][2], w[0][3], w[1][3]);
    stsm_x2(pa + 8192, w[0][4], w[1][4]);
  });
  fence_proxy_async();
  bar_sync(1, 256);
  TL2((tl >= 12 ? 128 : 0) + 32 + 1);
  {
    float d0[12], d1[12];
    const uint32_t pa = s16 + wg * 1280, pv = s16 + wg * 768;
    wgmma_fence();
#pragma unroll
    for (int k = 0; k < 8; k++) {
      wgmma_n24<1, 1>(d0, desc16<128, 2048, 0>(pa, OFF_PHI + k * 256), desc16<128, 2048, 0>(pv, OFF_V + k * 256), k != 0);
      wgmma_n24<1, 1>(d1, desc16<128, 2048, 0>(pa, OFF_PHI + 10240 + k * 256), desc16<128, 2048, 0>(pv, OFF_V + 6144 + k * 256), k != 0);
    }
    wgmma_commit();
    wgmma_wait<0>();
    unsigned char* dst = a.kvacc + ((u * 4 + wg * 2) * 5 + 2 * wi) * 1024 + lane * 16;
    auto red4 = [&](bool on, unsigned char* p, float x, float y, float z) {
      asm volatile("{\n.reg .pred p;\nsetp.ne.u32 p, %4, 0;\n@p red.relaxed.gpu.global.add.v4.f32 [%0], {%1,%2,%3,%5};\n}" :: "l"(p), "f"(x), "f"(y), "f"(z), "r"((uint32_t)on), "f"(1.f) : "memory");
    };
    red4(wi < 3, dst, d0[0], d0[1], d0[4]); red4(wi < 3, dst + 512, d0[5], d0[8], d0[9]);
    red4(wi < 3, dst + 5120, d1[0], d1[1], d1[4]); red4(wi < 3, dst + 5632, d1[5], d1[8], d1[9]);
    red4(wi < 2, dst + 1024, d0[2], d0[3], d0[6]); red4(wi < 2, dst + 1536, d0[7], d0[10], d0[11]);
    red4(wi < 2, dst + 6144, d1[2], d1[3], d1[6]); red4(wi < 2, dst + 6656, d1[7], d1[10], d1[11]);
  }
  TL2((tl >= 12 ? 128 : 0) + 32 + 2);
  uint32_t qf[4][2][5];
  static_for<0, 4>([&](auto HH) { features(IC<0>{}, HH, qf[HH.value]); });
  uint4 xr[5];
#pragma unroll
  for (int i = 0; i < 5; i++) {
    const int c = lane + 32 * i;
    xr[i] = __ldcg((const uint4*)(a.xin + (size_t)(m2 * 128 + wg * 64 + wi * 16 + c / 10) * cfg::DM + ns * 80 + (c % 10) * 8));
  }
  {
    const unsigned char* src = a.kvacc + (u * 20 + warp) * 1024 + lane * 16;
    uint4 v[6];
    int spin = 0;
    while (true) {
      v[0] = ld_relaxed_v4_i<0>(src); v[1] = ld_relaxed_v4_i<512>(src); v[2] = ld_relaxed_v4_i<8192>(src); v[3] = ld_relaxed_v4_i<8704>(src);
      v[4] = ld_relaxed_v4_i<0>(src + (wg ? 0 : 16384)); v[5] = ld_relaxed_v4_i<512>(src + (wg ? 0 : 16384));
      const uint32_t c = (v[0].w & v[1].w & v[2].w) & (v[3].w & v[4].w & v[5].w);
      if (!__any_sync(0xffffffffu, (c & 0x41800000u) != 0x41800000u) || ++spin >= SPIN_LIMIT) break;
      __nanosleep(100);
    }
    const uint32_t kd = sb + OFF_KV + warp * 384 + lane * 4;
#pragma unroll
    for (int i = 0; i < 3; i++)
      if (i < 2 || wg == 0) {
        sts32(kd + i * 3072, pack_bf16(__uint_as_float(v[2 * i].x), __uint_as_float(v[2 * i].y)));
        sts32(kd + i * 3072 + 128, pack_bf16(__uint_as_float(v[2 * i].z), __uint_as_float(v[2 * i + 1].x)));
        sts32(kd + i * 3072 + 256, pack_bf16(__uint_as_float(v[2 * i + 1].y), __uint_as_float(v[2 * i + 1].z)));
      }
  }
  fence_proxy_async();
  bar_sync(1, 256);
  TL2((tl >= 12 ? 128 : 0) + 32 + 3);
  {
    float d[4][12];
    uint32_t zero = 0; PIN(zero);
#pragma unroll
    for (int hh = 0; hh < 4; hh++)
#pragma unroll
      for (int i = 0; i < 5; i++) { PIN(qf[hh][0][i]); PIN(qf[hh][1][i]); }
    wgmma_fence();
#pragma unroll
    for (int hh = 0; hh < 4; hh++) {
      const uint32_t kb = OFF_KV + hh * 1920;
      wgmma_rs_n24<1>(d[hh], qf[hh][0][0], qf[hh][1][0], qf[hh][0][1], qf[hh][1][1], desc16<384, 128, 0>(s16, kb), 0);
      wgmma_rs_n24<1>(d[hh], qf[hh][0][2], qf[hh][1][2], qf[hh][0][3], qf[hh][1][3], desc16<384, 128, 0>(s16, kb + 768), 1);
      wgmma_rs_n24<1>(d[hh], qf[hh][0][4], qf[hh][1][4], zero, zero, desc16<0, 128, 0>(s16, kb + 1536), 1);
    }
    wgmma_commit();
    wgmma_wait<0>();
    uint32_t ow[4][6];
#pragma unroll
    for (int hh = 0; hh < 4; hh++) {
      const int zl = (lane & ~3) | ((hh & 1) ? 0 : 2);
      const float da = bf16r(bf16r(__shfl_sync(0xffffffffu, d[hh][8], zl)) + 1e-6f), db = bf16r(bf16r(__shfl_sync(0xffffffffu, d[hh][10], zl)) + 1e-6f);
#pragma unroll
      for (int n = 0; n < 3; n++) {
        bf16r2(d[hh][4 * n], d[hh][4 * n + 1]); bf16r2(d[hh][4 * n + 2], d[hh][4 * n + 3]);
        ow[hh][2 * n] = pack_bf16(__fdividef(d[hh][4 * n], da), __fdividef(d[hh][4 * n + 1], da));
        ow[hh][2 * n + 1] = pack_bf16(__fdividef(d[hh][4 * n + 2], db), __fdividef(d[hh][4 * n + 3], db));
      }
    }
#pragma unroll
    for (int p = 0; p < 2; p++) {
      const uint32_t oa = sb + OFF_OST + p * 10240 + srow;
      stsm_x4(oa, ow[2 * p][0], ow[2 * p][1], ow[2 * p][2], ow[2 * p][3]);
      stsm_x2(oa + 4096, q4 < 2 ? ow[2 * p][4] : ow[2 * p + 1][4], q4 < 2 ? ow[2 * p][5] : ow[2 * p + 1][5]);
      stsm_x4(oa + 6144, ow[2 * p + 1][0], ow[2 * p + 1][1], ow[2 * p + 1][2], ow[2 * p + 1][3]);
    }
    fence_proxy_async();
    __syncwarp();
    mbar_arrive_if(lane == 0, staged);
  }
  TL2((tl >= 12 ? 128 : 0) + 32 + 4);
  float c2[40];
  mbar_wait(barW, 0);
#pragma unroll 1
  for (int i = 0; i < 8; i++) {
    mbar_wait(full2 + 8 * i, 0);
    const uint32_t st = s16 + (i < 6 ? i : i - 6) * (PIECE / 16) + wg * 64, wo = s16 + i * 800;
    wgmma_fence();
#pragma unroll
    for (int kk = 0; kk < 5; kk++) wgmma_n80<0, 1>(c2, desc16<2048, 128, 0>(st, kk * 4096), desc16<1280, 128, 0>(wo, OFF_WOT + kk * 2560), (i | kk) != 0);
    wgmma_commit();
    if (i == 1 || i == 2) { wgmma_wait<1>(); mbar_arrive_if(lead, empty2 + 8 * (i - 1)); }
  }
  wgmma_wait<0>();
  TL2((tl >= 12 ? 128 : 0) + 32 + 5);
  {
    bar_sync(1, 256);
    const uint32_t ost = sb + 2 * PIECE + warp * 3072;
#pragma unroll
    for (int v = 0; v < 10; v += 2)
      stsm_x4(ost + (lane & 15) * 176 + (v + (lane >> 4)) * 16, pack_bf16(c2[4 * v], c2[4 * v + 1]), pack_bf16(c2[4 * v + 2], c2[4 * v + 3]),
              pack_bf16(c2[4 * v + 4], c2[4 * v + 5]), pack_bf16(c2[4 * v + 6], c2[4 * v + 7]));
    __syncwarp();
#pragma unroll
    for (int i = 0; i < 5; i++) {
      const int c = lane + 32 * i, row = c / 10, chunk = c % 10;
      const uint4 y = lds128(ost + row * 176 + chunk * 16);
      const size_t off = (size_t)(m2 * 128 + wg * 64 + wi * 16 + row) * cfg::DM + ns * 80 + chunk * 8;
      const uint4 x = xr[i];
      *(uint4*)(a.xout + off) = make_uint4(pack_bf16(bf_lo(x.x) + bf_lo(y.x), bf_hi(x.x) + bf_hi(y.x)), pack_bf16(bf_lo(x.y) + bf_lo(y.y), bf_hi(x.y) + bf_hi(y.y)),
                                           pack_bf16(bf_lo(x.z) + bf_lo(y.z), bf_hi(x.z) + bf_hi(y.z)), pack_bf16(bf_lo(x.w) + bf_lo(y.w), bf_hi(x.w) + bf_hi(y.w)));
    }
  }
  TL_END(tl);
}
__device__ __align__(32768) unsigned char g_arena[AR_SIZE];
__device__ unsigned g_go[32];
__device__ __align__(1024) uint2 g_xh[2048 * 160];
__device__ __align__(1024) unsigned char g_k[64 * 96 * 5120], g_v[64 * 96 * 5120];
__device__ __align__(1024) bf16 g_o[2048 * 6144];
__device__ __align__(1024) uint4 g_qs[8 * 32 * 12 * 256];
__device__ __align__(1024) bf16 g_xn[2048 * 640], g_xn2[2048 * 640], g_xa[2048 * 640], g_xb[2048 * 640];
__device__ __align__(1024) bf16 g_part[24 * 2048 * 640];
__device__ __align__(1024) bf16 g_wb[2048 * 640], g_wot[640 * 640], g_pq[2048 * 640];
__device__ __align__(1024) float g_kvacc[bf::KVACC / 4 + 64];

typedef CUresult (*EncodeFn)(CUtensorMap*, CUtensorMapDataType, cuuint32_t, void*, const cuuint64_t*, const cuuint64_t*, const cuuint32_t*,
                             const cuuint32_t*, CUtensorMapInterleave, CUtensorMapSwizzle, CUtensorMapL2promotion, CUtensorMapFloatOOBfill);
static EncodeFn g_encode = nullptr;
static CUtensorMap make_map(const void* p, uint64_t cols, uint64_t rows, uint32_t bc, uint32_t br, bool swz = true) {
  CUtensorMap m;
  cuuint64_t dims[2] = {cols, rows}, strides[1] = {cols * 2};
  cuuint32_t box[2] = {bc, br}, es[2] = {1, 1};
  g_encode(&m, CU_TENSOR_MAP_DATA_TYPE_BFLOAT16, 2, const_cast<void*>(p), dims, strides, box, es, CU_TENSOR_MAP_INTERLEAVE_NONE,
           swz ? CU_TENSOR_MAP_SWIZZLE_128B : CU_TENSOR_MAP_SWIZZLE_NONE, CU_TENSOR_MAP_L2_PROMOTION_L2_256B, CU_TENSOR_MAP_FLOAT_OOB_FILL_NONE);
  return m;
}
static CUtensorMap make_map3(const void* p, uint64_t cols, uint64_t rows, uint32_t nb) {
  CUtensorMap m;
  cuuint64_t dims[3] = {64, rows, cols / 64}, strides[2] = {cols * 2, 128};
  cuuint32_t box[3] = {64, 64, nb}, es[3] = {1, 1, 1};
  g_encode(&m, CU_TENSOR_MAP_DATA_TYPE_BFLOAT16, 3, const_cast<void*>(p), dims, strides, box, es, CU_TENSOR_MAP_INTERLEAVE_NONE,
           CU_TENSOR_MAP_SWIZZLE_128B, CU_TENSOR_MAP_L2_PROMOTION_L2_256B, CU_TENSOR_MAP_FLOAT_OOB_FILL_NONE);
  return m;
}
template <class T> static T* sym(const T& s) { void* p = nullptr; cudaGetSymbolAddress(&p, s); return (T*)p; }

struct Ptrs {
  unsigned char *arena, *k, *v; bf16 *o, *xn, *xa, *xb, *wb, *wot, *pq; float *part, *kvacc; uint2* xh; uint4* qs; bf16* xn2; unsigned* go;
};

static tr::Sched make_sched(int layer, const char* str, const int* ks, const int* lr) {
  using namespace tr;
  Sched s = {};
  int n = 0;
  for (int b = 0; b < 16; b++) { s.ks[b] = (uint8_t)abs(ks[b]); s.wide[b] = ks[b] > 0; s.lrows[b] = (uint8_t)lr[b]; }
  for (const char* p = str; *p;) {
    if (*p == ' ') { p++; continue; }
    const bool late = *p < 'a';
    const char c = *p++ | 32;
    char* e;
    const int b = (int)strtol(p, &e, 10); p = e;
    int first = 0, cnt = c == 'o' ? s.ks[b] * (s.wide[b] ? 2 : 5) : (c == 'l' ? 16 / lr[b] : 32);
    if (*p == '.') { first = (int)strtol(p + 1, &e, 10); cnt = (int)strtol(e + 1, &e, 10); p = e; }
    const int type = c == 'a' ? T_QA : (c == 'q' ? T_Q : (c == 't' ? T_A : (c == 'l' ? T_L : (c == 'p' ? T_P : (s.wide[b] ? T_OB : T_OS)))));
    if (type == T_P && layer > 0) continue;
    for (int i = 0; i < cnt && n < MAXITEMS - 1; i++) s.item[n++] = (uint16_t)((late << 14) | (type << 11) | (b << 7) | (first + i));
  }
  s.n = n; s.item[n] = T_END << 11;
  return s;
}
static tr::Sched sched_of(int layer) {
  const char* str = "q12 q13 q14 a0 q15 a1 p0.0.16 o0 o1 a2 p0.16.16 o2 a3 a4 o3 a5 o4 a6 l0 o5 l1 a7 o6 l2 a8 o7 a9 o8 l3 l4 a10 O9 l5 a11 O10 t12 l6 l7 o11 O12 t13 t14 T15 O13 o15 O14 L10 L9 l15 l13 L8 l14 l12 l11";
  int ks[16] = {2, 2, 2, 2, 2, 2, 2, 2, 2, 3, 3, 3, 3, -4, -6, -8}, lr[16] = {4, 4, 4, 4, 4, 4, 4, 4, 1, 4, 1, 1, 1, 1, 1, 1};
#ifdef TUNE
  const bool mine = !getenv("ONLY") || atoi(getenv("ONLY")) == layer;
  if (mine && getenv("SCHED")) str = getenv("SCHED");
  if (const char* p = mine ? getenv("KS") : nullptr) for (int b = 0; b < 16; b++) { char* e; ks[b] = (int)strtol(p, &e, 10); p = e; }
  if (const char* p = mine ? getenv("LR") : nullptr) for (int b = 0; b < 16; b++) { char* e; lr[b] = (int)strtol(p, &e, 10); p = e; }
#endif
  return make_sched(layer, str, ks, lr);
}
#ifndef TRAIL_GRID
#define TRAIL_GRID 132
#endif
#ifndef PDL_LN
#define PDL_LN 0
#endif
#ifndef PDL_CH
#define PDL_CH 1
#endif
#ifndef PDL_B
#define PDL_B 1
#endif
#ifndef PF_A
#define PF_A 1
#endif
#ifndef PF_B
#define PF_B 1
#endif
extern "C" void kernel_launch(void* const* d_in, const int* in_sizes, int n_in, void* d_out, int out_size) {
  const bf16* x = (const bf16*)d_in[0];
  const bf16* mem0 = (const bf16*)d_in[1];
  const bf16 *Wq = (const bf16*)d_in[2], *Wk = (const bf16*)d_in[3], *Wv = (const bf16*)d_in[4], *Wo = (const bf16*)d_in[5];
  const bf16 *wqkv = (const bf16*)d_in[8], *wphi = (const bf16*)d_in[9], *wo = (const bf16*)d_in[10];
  bf16* out = (bf16*)d_out;
  static Ptrs P; static bool init = false;
  if (!init) {
    void* fn = nullptr; cudaDriverEntryPointQueryResult qr;
    cudaGetDriverEntryPoint("cuTensorMapEncodeTiled", &fn, cudaEnableDefault, &qr);
    g_encode = (EncodeFn)fn;
    void* p;
    cudaGetSymbolAddress(&p, g_arena); P.arena = (unsigned char*)p;
    cudaGetSymbolAddress(&p, g_k); P.k = (unsigned char*)p;   cudaGetSymbolAddress(&p, g_v); P.v = (unsigned char*)p;
    cudaGetSymbolAddress(&p, g_o); P.o = (bf16*)p;
    cudaGetSymbolAddress(&p, g_xn); P.xn = (bf16*)p;
    cudaGetSymbolAddress(&p, g_xa); P.xa = (bf16*)p;   cudaGetSymbolAddress(&p, g_xb); P.xb = (bf16*)p;
    cudaGetSymbolAddress(&p, g_wb); P.wb = (bf16*)p;   cudaGetSymbolAddress(&p, g_wot); P.wot = (bf16*)p;
    cudaGetSymbolAddress(&p, g_pq); P.pq = (bf16*)p;   cudaGetSymbolAddress(&p, g_part); P.part = (float*)p;
    cudaGetSymbolAddress(&p, g_kvacc); P.kvacc = (float*)p;
    cudaGetSymbolAddress(&p, g_xh); P.xh = (uint2*)p;
    cudaGetSymbolAddress(&p, g_go); P.go = (unsigned*)p;
    cudaGetSymbolAddress(&p, g_qs); P.qs = (uint4*)p;
    cudaGetSymbolAddress(&p, g_xn2); P.xn2 = (bf16*)p;
    cudaFuncSetAttribute(chain_kernel, cudaFuncAttributeMaxDynamicSharedMemorySize, ch::SMEM);
    cudaFuncSetAttribute(trail_kernel, cudaFuncAttributeMaxDynamicSharedMemorySize, tr::SMEM);
    cudaFuncSetAttribute(blayer_kernel, cudaFuncAttributeMaxDynamicSharedMemorySize, bf::SMEM);
    init = true;
  }
  const CUtensorMap tmXn = make_map(P.xn, 640, 2048, 64, 128), tmXn2 = make_map(P.xn2, 640, 2048, 64, 128);
  const CUtensorMap tmWq = make_map3(Wq, 6144, 640, 3);
  const CUtensorMap tmCq = make_map(Wq, 6144, 640, 64, 160), tmCk = make_map(Wk, 6144, 640, 64, 160), tmCv = make_map(Wv, 6144, 640, 64, 160), tmCo = make_map(Wo, 640, 6144, 224, 64, false);
  const CUtensorMap tmWo5 = make_map3(Wo, 640, 6144, 5), tmWo2 = make_map3(Wo, 640, 6144, 2);

  CUtensorMap tmP;
  {
    cuuint64_t dims[3] = {256, 8, 24 * 320}, strides[2] = {1024, 8192};
    cuuint32_t box[3] = {256, 1, 10}, es[3] = {1, 1, 1};
    g_encode(&tmP, CU_TENSOR_MAP_DATA_TYPE_UINT32, 3, P.part, dims, strides, box, es, CU_TENSOR_MAP_INTERLEAVE_NONE, CU_TENSOR_MAP_SWIZZLE_NONE,
             CU_TENSOR_MAP_L2_PROMOTION_NONE, CU_TENSOR_MAP_FLOAT_OOB_FILL_NONE);
  }
  ChainArgs ca;
  ca.xh = P.xh; ca.mem0 = mem0; ca.kg = P.k; ca.vg = P.v;
  ca.arena = P.arena; ca.dbg = nullptr; ca.go = P.go; ca.delay = POLL_DELAY; ca.margin = 150; ca.pubrel = 1;
#ifdef TUNE
  if (getenv("PR")) ca.pubrel = atoi(getenv("PR"));
  if (getenv("MG")) ca.margin = atoi(getenv("MG"));
  if (getenv("PD")) ca.delay = atoi(getenv("PD"));
#endif
  ca.tl = 0;
  uint4* zar = (uint4*)P.arena; const int nzar = AR_SIZE / 16;
  uint4* zkv = (uint4*)P.kvacc; const int nzkv = (bf::KVACC / 4 + 64) / 4;

  const PrepArgs pa{wqkv, wphi, wo, (unsigned char*)P.wb, (unsigned char*)P.wot};
  const bf16* xcur = x;
  cudaLaunchAttribute at[1];
  at[0].id = cudaLaunchAttributeProgrammaticStreamSerialization; at[0].val.programmaticStreamSerializationAllowed = 1;
  auto cfgof = [&](int grid, int block, int smem, bool pdl) {
    cudaLaunchConfig_t lc = {};
    lc.gridDim = dim3(grid); lc.blockDim = dim3(block); lc.dynamicSmemBytes = smem; lc.stream = cudaStreamPerThread;
    lc.attrs = at; lc.numAttrs = pdl ? 1 : 0;
    return lc;
  };
  int nlayers = 2;
#ifdef TUNE
  if (getenv("LAYERS")) nlayers = atoi(getenv("LAYERS"));
#endif
  for (int layer = 0; layer < nlayers; layer++) {
    const int tl = layer * 12;
    cudaLaunchConfig_t lc = cfgof(256, 256, 0, layer > 0 && PDL_LN);
    cudaLaunchKernelEx(&lc, ln_kernel, xcur, P.xn, P.xh, zar, nzar, zkv, nzkv, Wk, Wv, layer == 0 ? PF_A : 0, tl + 0);
    ca.tl = tl + 2; ca.dry = 1;
#ifdef TUNE
    if (getenv("DRY")) ca.dry = (atoi(getenv("DRY")) >> layer) & 1;
#endif
    lc = cfgof(96, 384, ch::SMEM, PDL_CH);
    cudaLaunchKernelEx(&lc, chain_kernel, ca, tmCq, tmCk, tmCv, tmCo);
    lc = cfgof(TRAIL_GRID, 384, tr::SMEM, true);
    tr::Args ta{P.k, P.v, (unsigned char*)P.o, P.qs, (unsigned char*)P.part, xcur, P.xn, P.xa, P.xn2, P.arena, P.go, tl + 4, 30, 20, layer == 0};
#ifdef TUNE
    if (getenv("NAP")) ta.nap = atoi(getenv("NAP"));
    if (getenv("NAP2")) ta.nap2 = atoi(getenv("NAP2"));
#endif
    cudaLaunchKernelEx(&lc, trail_kernel, tmXn, tmWq, tmWo5, tmWo2, tmP, sched_of(layer), ta, pa);
    lc = cfgof(128, 384, bf::SMEM, PDL_B);
    bf::Args ba{(const unsigned char*)P.wb, (const unsigned char*)P.wot, (unsigned char*)P.kvacc, (unsigned char*)P.pq, P.xa, layer == 0 ? P.xb : out, P.go, layer == 0 ? P.arena + tr::C_P : nullptr,
                      layer == 0 && PF_B ? Wk : nullptr, Wv, 30, 500, 0, tl + 7};
#ifdef TUNE
    if (getenv("PFN")) ba.pfn = atoi(getenv("PFN"));
    if (getenv("PFNS")) ba.pfns = atoi(getenv("PFNS"));
    if (getenv("PFWT")) ba.pfwait = atoi(getenv("PFWT"));
    if (getenv("PFB")) ba.pf0 = layer == 0 && atoi(getenv("PFB")) ? Wk : nullptr;
#endif
    cudaLaunchKernelEx(&lc, blayer_kernel, tmXn2, ba);
    xcur = P.xb;
  }
}
```

```cpp
#include <cuda_runtime.h>
#include <cuda.h>
#include <cuda_bf16.h>
#include <stdint.h>
#include <stdlib.h>
#include <type_traits>

typedef __nv_bfloat16 bf16;

namespace cfg {
constexpr int S = 2048, DM = 640, H = 32, DH = 192, NSEG = 64, SEG = 32, NM = 8;
constexpr int HD = H * DH;
}

__device__ __forceinline__ uint32_t smem_u32(const void* p) { return (uint32_t)__cvta_generic_to_shared(p); }
__device__ __forceinline__ uint32_t mapa_u32(uint32_t a, uint32_t r) {
  uint32_t o; asm("mapa.shared::cluster.u32 %0, %1, %2;" : "=r"(o) : "r"(a), "r"(r)); return o;
}
__device__ __forceinline__ void mbar_init(uint32_t b, uint32_t c) {
  asm volatile("mbarrier.init.shared::cta.b64 [%0], %1;" :: "r"(b), "r"(c) : "memory");
}
__device__ __forceinline__ void mbar_expect_tx(uint32_t b, uint32_t bytes) {
  asm volatile("mbarrier.arrive.expect_tx.shared::cta.b64 _, [%0], %1;" :: "r"(b), "r"(bytes) : "memory");
}
__device__ __forceinline__ void mbar_arrive(uint32_t b) {
  asm volatile("mbarrier.arrive.shared::cta.b64 _, [%0];" :: "r"(b) : "memory");
}
__device__ __forceinline__ void mbar_expect_tx_if(bool c, uint32_t b, uint32_t bytes) {
  asm volatile("{\n.reg .pred p;\nsetp.ne.u32 p, %2, 0;\n@p mbarrier.arrive.expect_tx.shared::cta.b64 _, [%0], %1;\n}" :: "r"(b), "r"(bytes), "r"((uint32_t)c) : "memory");
}
__device__ __forceinline__ void mbar_arrive_if(bool c, uint32_t b) {
  asm volatile("{\n.reg .pred p;\nsetp.ne.u32 p, %1, 0;\n@p mbarrier.arrive.shared::cta.b64 _, [%0];\n}" :: "r"(b), "r"((uint32_t)c) : "memory");
}
__device__ __forceinline__ bool mbar_try(uint32_t b, uint32_t ph) {
  uint32_t p;
  asm volatile("{.reg .pred p; mbarrier.try_wait.parity.shared::cta.b64 p, [%1], %2; selp.u32 %0, 1, 0, p;}"
               : "=r"(p) : "r"(b), "r"(ph) : "memory");
  return p;
}
__device__ __forceinline__ bool mbar_try_cluster(uint32_t b, uint32_t ph) {
  uint32_t p;
  asm volatile("{.reg .pred p; mbarrier.try_wait.parity.acquire.cluster.shared::cta.b64 p, [%1], %2; selp.u32 %0, 1, 0, p;}"
               : "=r"(p) : "r"(b), "r"(ph) : "memory");
  return p;
}
#ifndef SPIN_LIMIT
#define SPIN_LIMIT (1 << 20)
#endif
__device__ __forceinline__ void mbar_wait(uint32_t b, uint32_t ph) {
  asm volatile("{\n.reg .pred p, q;\n.reg .u32 c;\nmov.u32 c, 0;\n"
               "W_%=:\nmbarrier.try_wait.parity.shared::cta.b64 p, [%0], %1;\n@p bra.uni D_%=;\n"
               "add.u32 c, c, 1;\nsetp.lt.u32 q, c, %2;\n@q bra.uni W_%=;\nD_%=:\n}"
               :: "r"(b), "r"(ph), "n"(SPIN_LIMIT) : "memory");
}
__device__ __forceinline__ void mbar_wait_if(bool cnd, uint32_t b, uint32_t ph) {
  asm volatile("{\n.reg .pred p, q;\n.reg .u32 c;\nsetp.eq.u32 q, %3, 0;\n@q bra.uni D_%=;\nmov.u32 c, 0;\n"
               "W_%=:\nmbarrier.try_wait.parity.shared::cta.b64 p, [%0], %1;\n@p bra.uni D_%=;\n"
               "add.u32 c, c, 1;\nsetp.lt.u32 q, c, %2;\n@q bra.uni W_%=;\nD_%=:\n}"
               :: "r"(b), "r"(ph), "n"(SPIN_LIMIT), "r"((uint32_t)cnd) : "memory");
}
__device__ __forceinline__ void mbar_spin(uint32_t b, uint32_t ph) {
  asm volatile("{\n.reg .pred p, q;\n.reg .u32 c;\nmov.u32 c, 0;\n"
               "W_%=:\nmbarrier.test_wait.parity.shared::cta.b64 p, [%0], %1;\n@p bra D_%=;\n"
               "add.u32 c, c, 1;\nsetp.lt.u32 q, c, %2;\n@q bra W_%=;\nD_%=:\n}"
               :: "r"(b), "r"(ph), "n"(SPIN_LIMIT) : "memory");
}
#define PIN(x) asm volatile("" : "+r"(x))
__device__ __forceinline__ void mbar_wait_cluster(uint32_t b, uint32_t ph) {
  int s = 0;
  while (!mbar_try_cluster(b, ph)) { if (++s > SPIN_LIMIT) break; }
}
__device__ __forceinline__ void st_async_v2(uint32_t a, uint32_t x, uint32_t y, uint32_t mb) {
  asm volatile("st.async.weak.shared::cluster.mbarrier::complete_tx::bytes.v2.b32 [%0], {%1,%2}, [%3];"
               :: "r"(a), "r"(x), "r"(y), "r"(mb) : "memory");
}
__device__ __forceinline__ void st_async_v4(uint32_t a, uint32_t x, uint32_t y, uint32_t z, uint32_t w, uint32_t mb) {
  asm volatile("st.async.weak.shared::cluster.mbarrier::complete_tx::bytes.v4.b32 [%0], {%1,%2,%3,%4}, [%5];"
               :: "r"(a), "r"(x), "r"(y), "r"(z), "r"(w), "r"(mb) : "memory");
}
__device__ __forceinline__ void bulk_g2s(uint32_t dst, const void* src, uint32_t bytes, uint32_t mb) {
  asm volatile("cp.async.bulk.shared::cluster.global.mbarrier::complete_tx::bytes [%0], [%1], %2, [%3];"
               :: "r"(dst), "l"(src), "r"(bytes), "r"(mb) : "memory");
}
__device__ __forceinline__ void cp_async16(uint32_t dst, const void* src) {
  asm volatile("cp.async.cg.shared.global [%0], [%1], 16;" :: "r"(dst), "l"(src) : "memory");
}
__device__ __forceinline__ void cp_async_wait_all() { asm volatile("cp.async.wait_all;" ::: "memory"); }
__device__ __forceinline__ void fence_proxy_async() { asm volatile("fence.proxy.async.shared::cta;" ::: "memory"); }
__device__ __forceinline__ void bar_sync(int id, int n) { asm volatile("bar.sync %0, %1;" :: "r"(id), "r"(n) : "memory"); }
__device__ __forceinline__ void bar_arrive(int id, int n) { asm volatile("bar.arrive %0, %1;" :: "r"(id), "r"(n) : "memory"); }
__device__ __forceinline__ void cluster_sync_all() {
  asm volatile("barrier.cluster.arrive.release.aligned; barrier.cluster.wait.acquire.aligned;" ::: "memory");
}
__device__ __forceinline__ void ldsm_x4(uint32_t (&r)[4], uint32_t a) {
  asm volatile("ldmatrix.sync.aligned.m8n8.x4.shared.b16 {%0,%1,%2,%3}, [%4];"
               : "=r"(r[0]), "=r"(r[1]), "=r"(r[2]), "=r"(r[3]) : "r"(a) : "memory");
}
__device__ __forceinline__ void ldsm_x4_t(uint32_t (&r)[4], uint32_t a) {
  asm volatile("ldmatrix.sync.aligned.m8n8.x4.trans.shared.b16 {%0,%1,%2,%3}, [%4];"
               : "=r"(r[0]), "=r"(r[1]), "=r"(r[2]), "=r"(r[3]) : "r"(a) : "memory");
}
template <int IMM> __device__ __forceinline__ void ldsm_x4_i(uint32_t (&r)[4], uint32_t a) {
  asm volatile("ldmatrix.sync.aligned.m8n8.x4.shared.b16 {%0,%1,%2,%3}, [%4+%5];"
               : "=r"(r[0]), "=r"(r[1]), "=r"(r[2]), "=r"(r[3]) : "r"(a), "n"(IMM) : "memory");
}
template <int IMM> __device__ __forceinline__ void ldsm_x4_t_i(uint32_t (&r)[4], uint32_t a) {
  asm volatile("ldmatrix.sync.aligned.m8n8.x4.trans.shared.b16 {%0,%1,%2,%3}, [%4+%5];"
               : "=r"(r[0]), "=r"(r[1]), "=r"(r[2]), "=r"(r[3]) : "r"(a), "n"(IMM) : "memory");
}
template <int IMM> __device__ __forceinline__ uint4 lds128_i(uint32_t a) {
  uint4 v; asm volatile("ld.shared.v4.u32 {%0,%1,%2,%3}, [%4+%5];" : "=r"(v.x), "=r"(v.y), "=r"(v.z), "=r"(v.w) : "r"(a), "n"(IMM) : "memory"); return v;
}
template <int IMM> __device__ __forceinline__ uint2 lds64_i(uint32_t a) {
  uint2 v; asm volatile("ld.shared.v2.u32 {%0,%1}, [%2+%3];" : "=r"(v.x), "=r"(v.y) : "r"(a), "n"(IMM) : "memory"); return v;
}
template <int IMM> __device__ __forceinline__ void sts128_i(uint32_t a, uint32_t x, uint32_t y, uint32_t z, uint32_t w) {
  asm volatile("st.shared.v4.u32 [%0+%5], {%1,%2,%3,%4};" :: "r"(a), "r"(x), "r"(y), "r"(z), "r"(w), "n"(IMM) : "memory");
}
template <int IMM> __device__ __forceinline__ void sts64_i(uint32_t a, uint32_t x, uint32_t y) {
  asm volatile("st.shared.v2.u32 [%0+%3], {%1,%2};" :: "r"(a), "r"(x), "r"(y), "n"(IMM) : "memory");
}
template <int IMM> __device__ __forceinline__ void st_async_v2_i(uint32_t a, uint32_t x, uint32_t y, uint32_t mb) {
  asm volatile("st.async.weak.shared::cluster.mbarrier::complete_tx::bytes.v2.b32 [%0+%4], {%1,%2}, [%3];"
               :: "r"(a), "r"(x), "r"(y), "r"(mb), "n"(IMM) : "memory");
}
template <int IMM> __device__ __forceinline__ uint4 ld_relaxed_v4_i(const void* p) {
  uint4 v; asm volatile("ld.relaxed.gpu.global.v4.u32 {%0,%1,%2,%3}, [%4+%5];" : "=r"(v.x), "=r"(v.y), "=r"(v.z), "=r"(v.w) : "l"(p), "n"(IMM) : "memory"); return v;
}
template <int I, int N, class F> __device__ __forceinline__ void static_for(F&& f) {
  if constexpr (I < N) { f(std::integral_constant<int, I>{}); static_for<I + 1, N>(f); }
}
__device__ __forceinline__ uint32_t movm_t(uint32_t a) {
  uint32_t d; asm volatile("movmatrix.sync.aligned.m8n8.trans.b16 %0, %1;" : "=r"(d) : "r"(a)); return d;
}
__device__ __forceinline__ void mma16816(float (&d)[4], uint32_t a0, uint32_t a1, uint32_t a2, uint32_t a3, uint32_t b0, uint32_t b1) {
  asm volatile("mma.sync.aligned.m16n8k16.row.col.f32.bf16.bf16.f32 {%0,%1,%2,%3}, {%4,%5,%6,%7}, {%8,%9}, {%0,%1,%2,%3};"
               : "+f"(d[0]), "+f"(d[1]), "+f"(d[2]), "+f"(d[3]) : "r"(a0), "r"(a1), "r"(a2), "r"(a3), "r"(b0), "r"(b1));
}
__device__ __forceinline__ uint32_t pack_bf16(float lo, float hi) {
  uint32_t d; asm("cvt.rn.bf16x2.f32 %0, %1, %2;" : "=r"(d) : "f"(hi), "f"(lo)); return d;
}
__device__ __forceinline__ float bf_lo(uint32_t w) { return __uint_as_float(w << 16); }
__device__ __forceinline__ float bf_hi(uint32_t w) { return __uint_as_float(w & 0xffff0000u); }
__device__ __forceinline__ uint4 lds128(uint32_t a) {
  uint4 v; asm volatile("ld.shared.v4.u32 {%0,%1,%2,%3}, [%4];" : "=r"(v.x), "=r"(v.y), "=r"(v.z), "=r"(v.w) : "r"(a) : "memory"); return v;
}
__device__ __forceinline__ uint2 lds64(uint32_t a) {
  uint2 v; asm volatile("ld.shared.v2.u32 {%0,%1}, [%2];" : "=r"(v.x), "=r"(v.y) : "r"(a) : "memory"); return v;
}
__device__ __forceinline__ void sts128(uint32_t a, uint32_t x, uint32_t y, uint32_t z, uint32_t w) {
  asm volatile("st.shared.v4.u32 [%0], {%1,%2,%3,%4};" :: "r"(a), "r"(x), "r"(y), "r"(z), "r"(w) : "memory");
}
__device__ __forceinline__ void sts64(uint32_t a, uint32_t x, uint32_t y) {
  asm volatile("st.shared.v2.u32 [%0], {%1,%2};" :: "r"(a), "r"(x), "r"(y) : "memory");
}
__device__ __forceinline__ uint4 ld_relaxed_v4(const void* p) {
  uint4 v; asm volatile("ld.relaxed.gpu.global.v4.u32 {%0,%1,%2,%3}, [%4];" : "=r"(v.x), "=r"(v.y), "=r"(v.z), "=r"(v.w) : "l"(p) : "memory"); return v;
}
__device__ __forceinline__ uint32_t ld_relaxed_u32(const void* p) {
  uint32_t v; asm volatile("ld.relaxed.gpu.global.u32 %0, [%1];" : "=r"(v) : "l"(p) : "memory"); return v;
}
__device__ __forceinline__ void st_relaxed_v2(void* p, uint32_t a, uint32_t b) {
  asm volatile("st.relaxed.gpu.global.v2.u32 [%0], {%1,%2};" :: "l"(p), "r"(a), "r"(b) : "memory");
}
__device__ __forceinline__ void st_relaxed_u32(void* p, uint32_t v) {
  asm volatile("st.relaxed.gpu.global.u32 [%0], %1;" :: "l"(p), "r"(v) : "memory");
}
__device__ __forceinline__ void st_release_u32(void* p, uint32_t v) {
  asm volatile("st.release.gpu.global.u32 [%0], %1;" :: "l"(p), "r"(v) : "memory");
}
__device__ __forceinline__ void red_release_inc(void* p) { asm volatile("red.release.gpu.global.add.u32 [%0], 1;" :: "l"(p) : "memory"); }
__device__ __forceinline__ uint32_t clk32() { uint32_t c; asm volatile("mov.u32 %0, %%clock;" : "=r"(c) :: "memory"); return c; }
__device__ __forceinline__ uint32_t clkdep(uint32_t v) {
  uint32_t c; asm volatile("{.reg .pred p; setp.eq.u32 p, %1, 0xdeadbeef; @p trap; mov.u32 %0, %%clock;}" : "=r"(c) : "r"(v) : "memory"); return c;
}
__device__ __forceinline__ void wgmma_fence() { asm volatile("wgmma.fence.sync.aligned;" ::: "memory"); }
__device__ __forceinline__ void wgmma_commit() { asm volatile("wgmma.commit_group.sync.aligned;" ::: "memory"); }
template <int N> __device__ __forceinline__ void wgmma_wait() { asm volatile("wgmma.wait_group.sync.aligned %0;" :: "n"(N) : "memory"); }
__device__ __forceinline__ void wgmma_n8_ss_ta(float (&d)[4], uint64_t da, uint64_t db, int acc) {
  asm volatile("{\n.reg .pred p;\nsetp.ne.b32 p, %6, 0;\n"
               "wgmma.mma_async.sync.aligned.m64n8k16.f32.bf16.bf16 {%0,%1,%2,%3}, %4, %5, p, 1, 1, 1, 0;\n}\n"
               : "+f"(d[0]), "+f"(d[1]), "+f"(d[2]), "+f"(d[3]) : "l"(da), "l"(db), "r"(acc));
}
__device__ __forceinline__ uint64_t make_desc(uint32_t saddr, uint32_t lbo_bytes, uint32_t sbo_bytes, uint32_t swz) {
  return (uint64_t)((saddr & 0x3FFFF) >> 4) | ((uint64_t)(lbo_bytes >> 4) << 16) | ((uint64_t)(sbo_bytes >> 4) << 32) | ((uint64_t)swz << 62);
}


template <uint32_t LBO, uint32_t SBO, uint32_t SWZ> __device__ __forceinline__ uint64_t desc16(uint32_t a16, uint32_t off = 0) {
  return (uint64_t)(a16 + ((off >> 4) + ((LBO >> 4) << 16))) | ((uint64_t)((SBO >> 4) | (SWZ << 30)) << 32);
}

__device__ __forceinline__ bool elect_one() {
  uint32_t p; asm volatile("{\n.reg .pred p;\nelect.sync _|p, 0xffffffff;\nselp.u32 %0, 1, 0, p;\n}" : "=r"(p)); return p;
}
__device__ __forceinline__ void tma_load_3d(uint32_t dst, const CUtensorMap* tm, int c0, int c1, int c2, uint32_t mb) {
  asm volatile("cp.async.bulk.tensor.3d.shared::cluster.global.mbarrier::complete_tx::bytes [%0], [%1, {%3, %4, %5}], [%2];"
               :: "r"(dst), "l"(tm), "r"(mb), "r"(c0), "r"(c1), "r"(c2) : "memory");
}
__device__ __forceinline__ void tma_load_2d(uint32_t dst, const CUtensorMap* tm, int c0, int c1, uint32_t mb) {
  asm volatile("cp.async.bulk.tensor.2d.shared::cluster.global.mbarrier::complete_tx::bytes [%0], [%1, {%3, %4}], [%2];"
               :: "r"(dst), "l"(tm), "r"(mb), "r"(c0), "r"(c1) : "memory");
}
__device__ __forceinline__ void bulk_s2g(void* dst, uint32_t src, uint32_t bytes) {
  asm volatile("cp.async.bulk.global.shared::cta.bulk_group [%0], [%1], %2;" :: "l"(dst), "r"(src), "r"(bytes) : "memory");
}
__device__ __forceinline__ uint64_t policy_evict_first() {
  uint64_t p; asm volatile("createpolicy.fractional.L2::evict_first.b64 %0, 1.0;" : "=l"(p)); return p;
}
__device__ __forceinline__ void bulk_s2g_hint(void* dst, uint32_t src, uint32_t bytes, uint64_t pol) {
  asm volatile("cp.async.bulk.global.shared::cta.bulk_group.L2::cache_hint [%0], [%1], %2, %3;" :: "l"(dst), "r"(src), "r"(bytes), "l"(pol) : "memory");
}
__device__ __forceinline__ void bulk_commit() { asm volatile("cp.async.bulk.commit_group;" ::: "memory"); }
template <int N> __device__ __forceinline__ void bulk_wait_read() { asm volatile("cp.async.bulk.wait_group.read %0;" :: "n"(N) : "memory"); }
template <int N> __device__ __forceinline__ void bulk_wait() { asm volatile("cp.async.bulk.wait_group %0;" :: "n"(N) : "memory"); }
__device__ __forceinline__ void stsm_x4(uint32_t a, uint32_t r0, uint32_t r1, uint32_t r2, uint32_t r3) {
  asm volatile("stmatrix.sync.aligned.m8n8.x4.shared.b16 [%0], {%1,%2,%3,%4};" :: "r"(a), "r"(r0), "r"(r1), "r"(r2), "r"(r3) : "memory");
}
__device__ __forceinline__ void stsm_x2(uint32_t a, uint32_t r0, uint32_t r1) {
  asm volatile("stmatrix.sync.aligned.m8n8.x2.shared.b16 [%0], {%1,%2};" :: "r"(a), "r"(r0), "r"(r1) : "memory");
}
__device__ __forceinline__ void ldsm_x2(uint32_t (&r)[2], uint32_t a) {
  asm volatile("ldmatrix.sync.aligned.m8n8.x2.shared.b16 {%0,%1}, [%2];" : "=r"(r[0]), "=r"(r[1]) : "r"(a) : "memory");
}
__device__ __forceinline__ void ldsm_x2_t(uint32_t (&r)[2], uint32_t a) {
  asm volatile("ldmatrix.sync.aligned.m8n8.x2.trans.shared.b16 {%0,%1}, [%2];" : "=r"(r[0]), "=r"(r[1]) : "r"(a) : "memory");
}
__device__ __forceinline__ float bf16r(float x) { return __uint_as_float(pack_bf16(0.f, x) & 0xffff0000u); }
__device__ __forceinline__ void bf16r2(float& a, float& b) { const uint32_t w = pack_bf16(a, b); a = bf_lo(w); b = bf_hi(w); }
__device__ __forceinline__ float rcpf(float x) { float r; asm("rcp.approx.ftz.f32 %0, %1;" : "=f"(r) : "f"(x)); return r; }
__device__ __forceinline__ float ex2f(float x) { float e; asm("ex2.approx.ftz.f32 %0, %1;" : "=f"(e) : "f"(x)); return e; }
__device__ __forceinline__ void prefetch_tmap(const CUtensorMap* tm) { asm volatile("prefetch.tensormap [%0];" :: "l"(tm) : "memory"); }

#ifdef TLLITE
__device__ unsigned long long g_lite[8];
__device__ __forceinline__ void lite(int i) { unsigned long long t; asm volatile("mov.u64 %0, %%globaltimer;" : "=l"(t)); g_lite[i] = t; }
#define LITE(c, i) do { if (c) lite(i); } while (0)
#else
#define LITE(c, i)
#endif
#ifdef TIMELINE
__device__ unsigned long long g_tl[2 * 64];
__device__ unsigned g_step[2 * 64 * 96 * 4];
__device__ unsigned long long g_log[2 * 132 * 64 * 2 + 2];
__device__ unsigned long long g_tl2[4 * 64];
__device__ __forceinline__ unsigned long long gtime() { unsigned long long t; asm volatile("mov.u64 %0, %%globaltimer;" : "=l"(t)); return t; }
#define TL_BEGIN(id) do { if (threadIdx.x == 0) atomicMin(&g_tl[2 * (id)], gtime()); } while (0)
#define TL_END(id) do { if ((threadIdx.x & 31) == 0) atomicMax(&g_tl[2 * (id) + 1], gtime()); } while (0)
#define TL_ACC(idx, t0) do { if (threadIdx.x == 0 && m >= 4 && m < 11) { atomicAdd(&g_tl2[idx], gtime() - (t0)); atomicAdd(&g_tl2[(idx) + 1], 1ull); } } while (0)
#define TL_NOW() gtime()
#define TL2(idx) asm volatile("{\n.reg .pred p;\nsetp.eq.u32 p, %2, 0;\n@p red.relaxed.gpu.global.max.u64 [%0], %1;\n}" :: "l"(&g_tl2[idx]), "l"(gtime()), "r"(threadIdx.x) : "memory")
#define TLW(idx) asm volatile("{\n.reg .pred p;\nsetp.eq.u32 p, %2, 0;\n@p red.relaxed.gpu.global.max.u64 [%0], %1;\n@p red.relaxed.gpu.global.add.u64 [%0+128], %1;\n}" :: "l"(&g_tl2[idx]), "l"(gtime() - g_tl0), "r"(threadIdx.x & 31) : "memory")
#define TL_BEGIN0(id) atomicMin(&g_tl[2 * (id)], gtime())
#else
#define TL_ACC(idx, t0)
#define TL_NOW() 0ull
#define TL2(idx)
#define TL_BEGIN0(id)
#define TLW(idx)
#define TL_BEGIN(id)
#define TL_END(id)
#endif
template <int TA, int TB> __device__ __forceinline__ void wgmma_n24(float (&d)[12], uint64_t da, uint64_t db, int acc) {
  asm volatile("{\n.reg .pred p;\nsetp.ne.b32 p, %14, 0;\n"
    "wgmma.mma_async.sync.aligned.m64n24k16.f32.bf16.bf16 {%0, %1, %2, %3, %4, %5, %6, %7, %8, %9, %10, %11}, %12, %13, p, 1, 1, %15, %16;\n}\n"
    : "+f"(d[0]), "+f"(d[1]), "+f"(d[2]), "+f"(d[3]), "+f"(d[4]), "+f"(d[5]), "+f"(d[6]), "+f"(d[7]), "+f"(d[8]), "+f"(d[9]), "+f"(d[10]), "+f"(d[11])
    : "l"(da), "l"(db), "r"(acc), "n"(TA), "n"(TB));
}

template <int TA, int TB> __device__ __forceinline__ void wgmma_n80(float (&d)[40], uint64_t da, uint64_t db, int acc) {
  asm volatile("{\n.reg .pred p;\nsetp.ne.b32 p, %42, 0;\n"
    "wgmma.mma_async.sync.aligned.m64n80k16.f32.bf16.bf16 {%0, %1, %2, %3, %4, %5, %6, %7, %8, %9, %10, %11, %12, %13, %14, %15, %16, %17, %18, %19, %20, %21, %22, %23, %24, %25, %26, %27, %28, %29, %30, %31, %32, %33, %34, %35, %36, %37, %38, %39}, %40, %41, p, 1, 1, %43, %44;\n}\n"
    : "+f"(d[0]), "+f"(d[1]), "+f"(d[2]), "+f"(d[3]), "+f"(d[4]), "+f"(d[5]), "+f"(d[6]), "+f"(d[7]), "+f"(d[8]), "+f"(d[9]), "+f"(d[10]), "+f"(d[11]), "+f"(d[12]), "+f"(d[13]), "+f"(d[14]), "+f"(d[15]), "+f"(d[16]), "+f"(d[17]), "+f"(d[18]), "+f"(d[19]), "+f"(d[20]), "+f"(d[21]), "+f"(d[22]), "+f"(d[23]), "+f"(d[24]), "+f"(d[25]), "+f"(d[26]), "+f"(d[27]), "+f"(d[28]), "+f"(d[29]), "+f"(d[30]), "+f"(d[31]), "+f"(d[32]), "+f"(d[33]), "+f"(d[34]), "+f"(d[35]), "+f"(d[36]), "+f"(d[37]), "+f"(d[38]), "+f"(d[39])
    : "l"(da), "l"(db), "r"(acc), "n"(TA), "n"(TB));
}

template <int TA, int TB> __device__ __forceinline__ void wgmma_n128(float (&d)[64], uint64_t da, uint64_t db, int acc) {
  asm volatile("{\n.reg .pred p;\nsetp.ne.b32 p, %66, 0;\n"
    "wgmma.mma_async.sync.aligned.m64n128k16.f32.bf16.bf16 {%0, %1, %2, %3, %4, %5, %6, %7, %8, %9, %10, %11, %12, %13, %14, %15, %16, %17, %18, %19, %20, %21, %22, %23, %24, %25, %26, %27, %28, %29, %30, %31, %32, %33, %34, %35, %36, %37, %38, %39, %40, %41, %42, %43, %44, %45, %46, %47, %48, %49, %50, %51, %52, %53, %54, %55, %56, %57, %58, %59, %60, %61, %62, %63}, %64, %65, p, 1, 1, %67, %68;\n}\n"
    : "+f"(d[0]), "+f"(d[1]), "+f"(d[2]), "+f"(d[3]), "+f"(d[4]), "+f"(d[5]), "+f"(d[6]), "+f"(d[7]), "+f"(d[8]), "+f"(d[9]), "+f"(d[10]), "+f"(d[11]), "+f"(d[12]), "+f"(d[13]), "+f"(d[14]), "+f"(d[15]), "+f"(d[16]), "+f"(d[17]), "+f"(d[18]), "+f"(d[19]), "+f"(d[20]), "+f"(d[21]), "+f"(d[22]), "+f"(d[23]), "+f"(d[24]), "+f"(d[25]), "+f"(d[26]), "+f"(d[27]), "+f"(d[28]), "+f"(d[29]), "+f"(d[30]), "+f"(d[31]), "+f"(d[32]), "+f"(d[33]), "+f"(d[34]), "+f"(d[35]), "+f"(d[36]), "+f"(d[37]), "+f"(d[38]), "+f"(d[39]), "+f"(d[40]), "+f"(d[41]), "+f"(d[42]), "+f"(d[43]), "+f"(d[44]), "+f"(d[45]), "+f"(d[46]), "+f"(d[47]), "+f"(d[48]), "+f"(d[49]), "+f"(d[50]), "+f"(d[51]), "+f"(d[52]), "+f"(d[53]), "+f"(d[54]), "+f"(d[55]), "+f"(d[56]), "+f"(d[57]), "+f"(d[58]), "+f"(d[59]), "+f"(d[60]), "+f"(d[61]), "+f"(d[62]), "+f"(d[63])
    : "l"(da), "l"(db), "r"(acc), "n"(TA), "n"(TB));
}

template <int TA, int TB> __device__ __forceinline__ void wgmma_n192(float (&d)[96], uint64_t da, uint64_t db, int acc) {
  asm volatile("{\n.reg .pred p;\nsetp.ne.b32 p, %98, 0;\n"
    "wgmma.mma_async.sync.aligned.m64n192k16.f32.bf16.bf16 {%0, %1, %2, %3, %4, %5, %6, %7, %8, %9, %10, %11, %12, %13, %14, %15, %16, %17, %18, %19, %20, %21, %22, %23, %24, %25, %26, %27, %28, %29, %30, %31, %32, %33, %34, %35, %36, %37, %38, %39, %40, %41, %42, %43, %44, %45, %46, %47, %48, %49, %50, %51, %52, %53, %54, %55, %56, %57, %58, %59, %60, %61, %62, %63, %64, %65, %66, %67, %68, %69, %70, %71, %72, %73, %74, %75, %76, %77, %78, %79, %80, %81, %82, %83, %84, %85, %86, %87, %88, %89, %90, %91, %92, %93, %94, %95}, %96, %97, p, 1, 1, %99, %100;\n}\n"
    : "+f"(d[0]), "+f"(d[1]), "+f"(d[2]), "+f"(d[3]), "+f"(d[4]), "+f"(d[5]), "+f"(d[6]), "+f"(d[7]), "+f"(d[8]), "+f"(d[9]), "+f"(d[10]), "+f"(d[11]), "+f"(d[12]), "+f"(d[13]), "+f"(d[14]), "+f"(d[15]), "+f"(d[16]), "+f"(d[17]), "+f"(d[18]), "+f"(d[19]), "+f"(d[20]), "+f"(d[21]), "+f"(d[22]), "+f"(d[23]), "+f"(d[24]), "+f"(d[25]), "+f"(d[26]), "+f"(d[27]), "+f"(d[28]), "+f"(d[29]), "+f"(d[30]), "+f"(d[31]), "+f"(d[32]), "+f"(d[33]), "+f"(d[34]), "+f"(d[35]), "+f"(d[36]), "+f"(d[37]), "+f"(d[38]), "+f"(d[39]), "+f"(d[40]), "+f"(d[41]), "+f"(d[42]), "+f"(d[43]), "+f"(d[44]), "+f"(d[45]), "+f"(d[46]), "+f"(d[47]), "+f"(d[48]), "+f"(d[49]), "+f"(d[50]), "+f"(d[51]), "+f"(d[52]), "+f"(d[53]), "+f"(d[54]), "+f"(d[55]), "+f"(d[56]), "+f"(d[57]), "+f"(d[58]), "+f"(d[59]), "+f"(d[60]), "+f"(d[61]), "+f"(d[62]), "+f"(d[63]), "+f"(d[64]), "+f"(d[65]), "+f"(d[66]), "+f"(d[67]), "+f"(d[68]), "+f"(d[69]), "+f"(d[70]), "+f"(d[71]), "+f"(d[72]), "+f"(d[73]), "+f"(d[74]), "+f"(d[75]), "+f"(d[76]), "+f"(d[77]), "+f"(d[78]), "+f"(d[79]), "+f"(d[80]), "+f"(d[81]), "+f"(d[82]), "+f"(d[83]), "+f"(d[84]), "+f"(d[85]), "+f"(d[86]), "+f"(d[87]), "+f"(d[88]), "+f"(d[89]), "+f"(d[90]), "+f"(d[91]), "+f"(d[92]), "+f"(d[93]), "+f"(d[94]), "+f"(d[95])
    : "l"(da), "l"(db), "r"(acc), "n"(TA), "n"(TB));
}

template <int TA, int TB> __device__ __forceinline__ void wgmma_n256(float (&d)[128], uint64_t da, uint64_t db, int acc) {
  asm volatile("{\n.reg .pred p;\nsetp.ne.b32 p, %130, 0;\n"
    "wgmma.mma_async.sync.aligned.m64n256k16.f32.bf16.bf16 {%0, %1, %2, %3, %4, %5, %6, %7, %8, %9, %10, %11, %12, %13, %14, %15, %16, %17, %18, %19, %20, %21, %22, %23, %24, %25, %26, %27, %28, %29, %30, %31, %32, %33, %34, %35, %36, %37, %38, %39, %40, %41, %42, %43, %44, %45, %46, %47, %48, %49, %50, %51, %52, %53, %54, %55, %56, %57, %58, %59, %60, %61, %62, %63, %64, %65, %66, %67, %68, %69, %70, %71, %72, %73, %74, %75, %76, %77, %78, %79, %80, %81, %82, %83, %84, %85, %86, %87, %88, %89, %90, %91, %92, %93, %94, %95, %96, %97, %98, %99, %100, %101, %102, %103, %104, %105, %106, %107, %108, %109, %110, %111, %112, %113, %114, %115, %116, %117, %118, %119, %120, %121, %122, %123, %124, %125, %126, %127}, %128, %129, p, 1, 1, %131, %132;\n}\n"
    : "+f"(d[0]), "+f"(d[1]), "+f"(d[2]), "+f"(d[3]), "+f"(d[4]), "+f"(d[5]), "+f"(d[6]), "+f"(d[7]), "+f"(d[8]), "+f"(d[9]), "+f"(d[10]), "+f"(d[11]), "+f"(d[12]), "+f"(d[13]), "+f"(d[14]), "+f"(d[15]), "+f"(d[16]), "+f"(d[17]), "+f"(d[18]), "+f"(d[19]), "+f"(d[20]), "+f"(d[21]), "+f"(d[22]), "+f"(d[23]), "+f"(d[24]), "+f"(d[25]), "+f"(d[26]), "+f"(d[27]), "+f"(d[28]), "+f"(d[29]), "+f"(d[30]), "+f"(d[31]), "+f"(d[32]), "+f"(d[33]), "+f"(d[34]), "+f"(d[35]), "+f"(d[36]), "+f"(d[37]), "+f"(d[38]), "+f"(d[39]), "+f"(d[40]), "+f"(d[41]), "+f"(d[42]), "+f"(d[43]), "+f"(d[44]), "+f"(d[45]), "+f"(d[46]), "+f"(d[47]), "+f"(d[48]), "+f"(d[49]), "+f"(d[50]), "+f"(d[51]), "+f"(d[52]), "+f"(d[53]), "+f"(d[54]), "+f"(d[55]), "+f"(d[56]), "+f"(d[57]), "+f"(d[58]), "+f"(d[59]), "+f"(d[60]), "+f"(d[61]), "+f"(d[62]), "+f"(d[63]), "+f"(d[64]), "+f"(d[65]), "+f"(d[66]), "+f"(d[67]), "+f"(d[68]), "+f"(d[69]), "+f"(d[70]), "+f"(d[71]), "+f"(d[72]), "+f"(d[73]), "+f"(d[74]), "+f"(d[75]), "+f"(d[76]), "+f"(d[77]), "+f"(d[78]), "+f"(d[79]), "+f"(d[80]), "+f"(d[81]), "+f"(d[82]), "+f"(d[83]), "+f"(d[84]), "+f"(d[85]), "+f"(d[86]), "+f"(d[87]), "+f"(d[88]), "+f"(d[89]), "+f"(d[90]), "+f"(d[91]), "+f"(d[92]), "+f"(d[93]), "+f"(d[94]), "+f"(d[95]), "+f"(d[96]), "+f"(d[97]), "+f"(d[98]), "+f"(d[99]), "+f"(d[100]), "+f"(d[101]), "+f"(d[102]), "+f"(d[103]), "+f"(d[104]), "+f"(d[105]), "+f"(d[106]), "+f"(d[107]), "+f"(d[108]), "+f"(d[109]), "+f"(d[110]), "+f"(d[111]), "+f"(d[112]), "+f"(d[113]), "+f"(d[114]), "+f"(d[115]), "+f"(d[116]), "+f"(d[117]), "+f"(d[118]), "+f"(d[119]), "+f"(d[120]), "+f"(d[121]), "+f"(d[122]), "+f"(d[123]), "+f"(d[124]), "+f"(d[125]), "+f"(d[126]), "+f"(d[127])
    : "l"(da), "l"(db), "r"(acc), "n"(TA), "n"(TB));
}

template <int TB> __device__ __forceinline__ void wgmma_rs_n24(float (&d)[12], uint32_t a0, uint32_t a1, uint32_t a2, uint32_t a3, uint64_t db, int acc) {
  asm volatile("{\n.reg .pred p;\nsetp.ne.b32 p, %17, 0;\n"
    "wgmma.mma_async.sync.aligned.m64n24k16.f32.bf16.bf16 {%0, %1, %2, %3, %4, %5, %6, %7, %8, %9, %10, %11}, {%12, %13, %14, %15}, %16, p, 1, 1, %18;\n}\n"
    : "+f"(d[0]), "+f"(d[1]), "+f"(d[2]), "+f"(d[3]), "+f"(d[4]), "+f"(d[5]), "+f"(d[6]), "+f"(d[7]), "+f"(d[8]), "+f"(d[9]), "+f"(d[10]), "+f"(d[11])
    : "r"(a0), "r"(a1), "r"(a2), "r"(a3), "l"(db), "r"(acc), "n"(TB));
}

template <int TB> __device__ __forceinline__ void wgmma_rs_n40(float (&d)[20], uint32_t a0, uint32_t a1, uint32_t a2, uint32_t a3, uint64_t db, int acc) {
  asm volatile("{\n.reg .pred p;\nsetp.ne.b32 p, %25, 0;\n"
    "wgmma.mma_async.sync.aligned.m64n40k16.f32.bf16.bf16 {%0, %1, %2, %3, %4, %5, %6, %7, %8, %9, %10, %11, %12, %13, %14, %15, %16, %17, %18, %19}, {%20, %21, %22, %23}, %24, p, 1, 1, %26;\n}\n"
    : "+f"(d[0]), "+f"(d[1]), "+f"(d[2]), "+f"(d[3]), "+f"(d[4]), "+f"(d[5]), "+f"(d[6]), "+f"(d[7]), "+f"(d[8]), "+f"(d[9]), "+f"(d[10]), "+f"(d[11]), "+f"(d[12]), "+f"(d[13]), "+f"(d[14]), "+f"(d[15]), "+f"(d[16]), "+f"(d[17]), "+f"(d[18]), "+f"(d[19])
    : "r"(a0), "r"(a1), "r"(a2), "r"(a3), "l"(db), "r"(acc), "n"(TB));
}

template <int TB> __device__ __forceinline__ void wgmma_rs_n192(float (&d)[96], uint32_t a0, uint32_t a1, uint32_t a2, uint32_t a3, uint64_t db, int acc) {
  asm volatile("{\n.reg .pred p;\nsetp.ne.b32 p, %101, 0;\n"
    "wgmma.mma_async.sync.aligned.m64n192k16.f32.bf16.bf16 {%0, %1, %2, %3, %4, %5, %6, %7, %8, %9, %10, %11, %12, %13, %14, %15, %16, %17, %18, %19, %20, %21, %22, %23, %24, %25, %26, %27, %28, %29, %30, %31, %32, %33, %34, %35, %36, %37, %38, %39, %40, %41, %42, %43, %44, %45, %46, %47, %48, %49, %50, %51, %52, %53, %54, %55, %56, %57, %58, %59, %60, %61, %62, %63, %64, %65, %66, %67, %68, %69, %70, %71, %72, %73, %74, %75, %76, %77, %78, %79, %80, %81, %82, %83, %84, %85, %86, %87, %88, %89, %90, %91, %92, %93, %94, %95}, {%96, %97, %98, %99}, %100, p, 1, 1, %102;\n}\n"
    : "+f"(d[0]), "+f"(d[1]), "+f"(d[2]), "+f"(d[3]), "+f"(d[4]), "+f"(d[5]), "+f"(d[6]), "+f"(d[7]), "+f"(d[8]), "+f"(d[9]), "+f"(d[10]), "+f"(d[11]), "+f"(d[12]), "+f"(d[13]), "+f"(d[14]), "+f"(d[15]), "+f"(d[16]), "+f"(d[17]), "+f"(d[18]), "+f"(d[19]), "+f"(d[20]), "+f"(d[21]), "+f"(d[22]), "+f"(d[23]), "+f"(d[24]), "+f"(d[25]), "+f"(d[26]), "+f"(d[27]), "+f"(d[28]), "+f"(d[29]), "+f"(d[30]), "+f"(d[31]), "+f"(d[32]), "+f"(d[33]), "+f"(d[34]), "+f"(d[35]), "+f"(d[36]), "+f"(d[37]), "+f"(d[38]), "+f"(d[39]), "+f"(d[40]), "+f"(d[41]), "+f"(d[42]), "+f"(d[43]), "+f"(d[44]), "+f"(d[45]), "+f"(d[46]), "+f"(d[47]), "+f"(d[48]), "+f"(d[49]), "+f"(d[50]), "+f"(d[51]), "+f"(d[52]), "+f"(d[53]), "+f"(d[54]), "+f"(d[55]), "+f"(d[56]), "+f"(d[57]), "+f"(d[58]), "+f"(d[59]), "+f"(d[60]), "+f"(d[61]), "+f"(d[62]), "+f"(d[63]), "+f"(d[64]), "+f"(d[65]), "+f"(d[66]), "+f"(d[67]), "+f"(d[68]), "+f"(d[69]), "+f"(d[70]), "+f"(d[71]), "+f"(d[72]), "+f"(d[73]), "+f"(d[74]), "+f"(d[75]), "+f"(d[76]), "+f"(d[77]), "+f"(d[78]), "+f"(d[79]), "+f"(d[80]), "+f"(d[81]), "+f"(d[82]), "+f"(d[83]), "+f"(d[84]), "+f"(d[85]), "+f"(d[86]), "+f"(d[87]), "+f"(d[88]), "+f"(d[89]), "+f"(d[90]), "+f"(d[91]), "+f"(d[92]), "+f"(d[93]), "+f"(d[94]), "+f"(d[95])
    : "r"(a0), "r"(a1), "r"(a2), "r"(a3), "l"(db), "r"(acc), "n"(TB));
}
constexpr uint32_t AR_ACC = 0;
constexpr uint32_t AR_TAB = 0x100000;
constexpr uint32_t AR_PROG = 0x101000;
__host__ __device__ constexpr uint32_t prog_off(int h, int j) { return AR_PROG + h * 128 + j * 4; }
constexpr uint32_t AR_CNT = 0x108000;
constexpr uint32_t AR_QUEUE = 0x109000;
constexpr uint32_t AR_SIZE = 0x10a000;

struct ChainArgs {
  const bf16* mem0;
  const uint2* xh;
  unsigned char *kg, *vg;
  unsigned char* arena;
  unsigned* go;
  uint32_t* dbg;
  uint32_t delay;
  int margin, pubrel, dry;
  int tl;
};

namespace ch {
constexpr int OFF_WQ = 0;
constexpr int OFF_X = 81920;
constexpr int OFF_MEM = OFF_X + 40960;
constexpr int OFF_WO = OFF_MEM + 10240;
constexpr int WOK = 8 * 896;
constexpr int OFF_KV = OFF_WO + 10 * WOK;
constexpr int KVB = 5120;
constexpr int OFF_O = OFF_KV + 4 * KVB;
constexpr int OFF_Q = OFF_O + 1024;
constexpr int OFF_S = OFF_O + 3072;
constexpr int OFF_SR = OFF_S + 1536;
constexpr int OFF_LT = OFF_SR + 1280;
constexpr int OFF_BAR = OFF_LT + 512;
constexpr int SMEM = OFF_BAR + 256;
static_assert(SMEM <= 232448, "smem");
constexpr int MB_S = OFF_BAR, MB_O = OFF_BAR + 8, MB_X = OFF_BAR + 16;
constexpr int MB_K = OFF_BAR + 128, MB_V = MB_K + 16, MB_Q = MB_K + 32, MB_R = MB_K + 48;
constexpr int SC_IN = OFF_BAR + 64;
constexpr int SC_MX = OFF_S;
constexpr int SC_TW = OFF_BAR + 48;
constexpr int SC_W = OFF_BAR + 96;
constexpr int WOS = 448;
enum { B_MEM0 = 1, B_QK, B_SL, B_V, B_O, B_RED, B_X, B_C, B_H, B_MEM1, B_A, B_G, B_E };
#ifndef NQ1
#define NQ1 14
#endif
#ifndef NQ0
#define NQ0 8
#endif
#ifndef NP0
#define NP0 5
#endif
#ifndef NWO
#define NWO 5
#endif
#ifndef NWP
#define NWP 4
#endif
#ifndef NB0
#define NB0 2
#endif
#ifndef BBS
#define BBS 100
#endif
#ifndef VSYNC
#define VSYNC 0
#endif
#ifndef XPOS
#define XPOS 0
#endif
#ifndef XPD
#define XPD 300
#endif
#ifndef WOF
#define WOF 0
#endif
#ifndef XBYTES
#define XBYTES 36864
#endif
#ifndef NRT
#define NRT 7
#endif
#ifndef NRF
#define NRF 2
#endif
#ifndef NPM0
#define NPM0 2
#endif
#ifndef NPM1
#define NPM1 2
#endif
#ifndef RSYNC
#define RSYNC 1
#endif
#ifndef PFK
#define PFK 1
#endif
#ifndef PA0
#define PA0 3
#endif
#ifndef PA1
#define PA1 0
#endif
#ifndef PB0
#define PB0 7
#endif
#ifndef PB1
#define PB1 5
#endif
#ifndef PQE
#define PQE 1
#endif
#ifndef XT
#define XT 38
#endif
static_assert(NPM0 >= 2 && NPM1 >= 2, "the K / V blocks live in the last two k-steps of Wo");
}

#ifndef CHAIN_TIMING
#define CHAIN_TIMING 0
#endif
#if CHAIN_TIMING
#ifndef TR0
#define TR0 41
#endif
#ifndef TSMASK
#define TSMASK 0xffff
#endif
#define TSV(i, v) do { if ((TSMASK >> (i)) & 1) asm volatile("st.shared.u32 [%0+%1], %2;" :: "r"(tsb), "n"((i) * 4), "r"(v) : "memory"); } while (0)
#define TS(i) TSV(i, clk32())
#define TS_SETUP() const uint32_t tsb = sb + ((s == TR0 || s == TR0 + 1) ? OFF_BAR + 128 + ((s - TR0) * 12 + warp) * 48 : OFF_SR + 1152)
#else
#define TS(i)
#define TSV(i, v)
#define TS_SETUP()
#endif
#ifndef POLL_DELAY
#define POLL_DELAY 620
#endif
#ifndef XN
#define XN 40
#endif
#ifndef PF0
#define PF0 8
#endif
#ifndef PFS
#define PFS 3
#endif
#ifndef XDELAY
#define XDELAY 0
#endif
#ifndef NOKM
#define NOKM 0
#endif
#ifndef PFX
#define PFX 3
#endif
#ifndef NVE
#define NVE 8
#endif
#ifndef VET
#define VET 19
#endif
#ifndef MEMFIRST
#define MEMFIRST 0
#endif
#ifndef PM1
#define PM1 1
#endif
#ifndef GD1
#define GD1 30
#endif
#ifndef GD2
#define GD2 150
#endif
#ifndef CEARLY
#define CEARLY 0
#endif
#ifndef NPL
#define NPL 2
#endif
#ifndef NP1
#define NP1 (NQ1 < 6 ? NQ1 : 6)
#endif
#ifndef PF2
#define PF2 0
#endif
#ifndef PFACC
#define PFACC 1
#endif
template <int V> using IC = std::integral_constant<int, V>;
__device__ __forceinline__ uint32_t clk_v() { uint64_t c; asm volatile("mov.u64 %0, %%clock64;" : "=l"(c) :: "memory"); return (uint32_t)c; }
__device__ __forceinline__ int fresh(int x) { int y; asm volatile("shfl.sync.bfly.b32 %0, %1, 0, 0x1f, 0xffffffff;" : "=r"(y) : "r"(x)); return y; }
#define SFENCE2(x, d) asm volatile("{\n.reg .pred p;\nsetp.eq.u32 p, %0, 0x7fffffff;\n@p st.shared.u32 [%0], %1;\n}" :: "r"(x), "r"(d) : "memory")
#define SFENCE(x) asm volatile("{\n.reg .pred p;\nsetp.eq.u32 p, %0, 0x7fffffff;\n@p st.shared.u32 [%0], %0;\n}" :: "r"(x) : "memory")
template <int I> __device__ __forceinline__ void bbfence(uint32_t x) {
  asm volatile("{\n.reg .pred p;\nsetp.eq.u32 p, %0, %1;\nL_%=:\n@p st.volatile.shared.u32 [%0], %0;\n@p bra.uni L_%=;\n}" :: "r"(x), "n"(4 * I) : "memory");
}
__device__ __forceinline__ float uniform_f(float x) { return __uint_as_float(__reduce_max_sync(0xffffffffu, __float_as_uint(x))); }

__device__ __forceinline__ void mma16816h(float (&d)[4], const uint32_t (&a)[4], uint32_t b0, uint32_t b1) {
  asm volatile("mma.sync.aligned.m16n8k16.row.col.f32.f16.f16.f32 {%0,%1,%2,%3}, {%4,%5,%6,%7}, {%8,%9}, {%0,%1,%2,%3};"
               : "+f"(d[0]), "+f"(d[1]), "+f"(d[2]), "+f"(d[3]) : "r"(a[0]), "r"(a[1]), "r"(a[2]), "r"(a[3]), "r"(b0), "r"(b1));
}
__device__ __forceinline__ void mma1688(float (&d)[4], uint32_t a0, uint32_t a1, uint32_t b0) {
  asm volatile("mma.sync.aligned.m16n8k8.row.col.f32.bf16.bf16.f32 {%0,%1,%2,%3}, {%4,%5}, {%6}, {%0,%1,%2,%3};"
               : "+f"(d[0]), "+f"(d[1]), "+f"(d[2]), "+f"(d[3]) : "r"(a0), "r"(a1), "r"(b0));
}
template <int OFF16, int ACC> __device__ __forceinline__ void wgmma_rs32h(float (&d)[16], const uint32_t (&a)[4], uint32_t dlo) {
  asm volatile("{\n.reg .pred p;\n.reg .b32 t;\n.reg .b64 db;\nsetp.ne.b32 p, %22, 0;\nadd.u32 t, %20, %21;\nmov.b64 db, {t, 0x40000040};\n"
    "wgmma.mma_async.sync.aligned.m64n32k16.f32.f16.f16 {%0,%1,%2,%3,%4,%5,%6,%7,%8,%9,%10,%11,%12,%13,%14,%15}, {%16,%17,%18,%19}, db, p, 1, 1, 0;\n}\n"
    : "+f"(d[0]), "+f"(d[1]), "+f"(d[2]), "+f"(d[3]), "+f"(d[4]), "+f"(d[5]), "+f"(d[6]), "+f"(d[7]), "+f"(d[8]), "+f"(d[9]), "+f"(d[10]), "+f"(d[11]),
      "+f"(d[12]), "+f"(d[13]), "+f"(d[14]), "+f"(d[15])
    : "r"(a[0]), "r"(a[1]), "r"(a[2]), "r"(a[3]), "r"(dlo), "n"(OFF16), "n"(ACC));
}
template <int IMM> __device__ __forceinline__ void stsm_x4_t_i(uint32_t a, uint32_t r0, uint32_t r1, uint32_t r2, uint32_t r3) {
  asm volatile("stmatrix.sync.aligned.m8n8.x4.trans.shared.b16 [%0+%5], {%1,%2,%3,%4};" :: "r"(a), "r"(r0), "r"(r1), "r"(r2), "r"(r3), "n"(IMM) : "memory");
}
template <int IMM> __device__ __forceinline__ void stsm_x2_t_i(uint32_t a, uint32_t r0, uint32_t r1) {
  asm volatile("stmatrix.sync.aligned.m8n8.x2.trans.shared.b16 [%0+%3], {%1,%2};" :: "r"(a), "r"(r0), "r"(r1), "n"(IMM) : "memory");
}
template <int IMM> __device__ __forceinline__ void st_async_b32_i(uint32_t a, uint32_t x, uint32_t mb) {
  asm volatile("st.async.weak.shared::cluster.mbarrier::complete_tx::bytes.b32 [%0+%3], %1, [%2];" :: "r"(a), "r"(x), "r"(mb), "n"(IMM) : "memory");
}
template <int IMM> __device__ __forceinline__ void ld_relaxed_v4_if(uint4& v, const void* p, uint32_t c) {
  asm volatile("{\n.reg .pred p;\nsetp.ne.u32 p, %6, 0;\n@p ld.relaxed.gpu.global.v4.u32 {%0,%1,%2,%3}, [%4+%5];\n}"
               : "+r"(v.x), "+r"(v.y), "+r"(v.z), "+r"(v.w) : "l"(p), "n"(IMM), "r"(c) : "memory");
}
template <int IMM> __device__ __forceinline__ void ldsm_x2_i(uint32_t (&r)[2], uint32_t a) {
  asm volatile("ldmatrix.sync.aligned.m8n8.x2.shared.b16 {%0,%1}, [%2+%3];" : "=r"(r[0]), "=r"(r[1]) : "r"(a), "n"(IMM) : "memory");
}
template <int IMM> __device__ __forceinline__ uint32_t ldsm_x1_t_i(uint32_t a) {
  uint32_t r; asm volatile("ldmatrix.sync.aligned.m8n8.x1.trans.shared.b16 {%0}, [%1+%2];" : "=r"(r) : "r"(a), "n"(IMM) : "memory"); return r;
}
template <int IMM> __device__ __forceinline__ uint32_t lds32_i(uint32_t a) {
  uint32_t v; asm volatile("ld.shared.u32 %0, [%1+%2];" : "=r"(v) : "r"(a), "n"(IMM) : "memory"); return v;
}
__device__ __forceinline__ void sts32(uint32_t a, uint32_t v) { asm volatile("st.shared.u32 [%0], %1;" :: "r"(a), "r"(v) : "memory"); }
__device__ __forceinline__ uint32_t pack_f16(float lo, float hi) {
  uint32_t d; asm("cvt.rn.f16x2.f32 %0, %1, %2;" : "=r"(d) : "f"(hi), "f"(lo)); return d;
}
__device__ __forceinline__ uint32_t amax_bf2(uint32_t a, uint32_t b) { uint32_t d; asm("max.xorsign.abs.bf16x2 %0, %1, %2;" : "=r"(d) : "r"(a), "r"(b)); return d; }
__device__ __forceinline__ uint32_t amax_h2(uint32_t a, uint32_t b) { uint32_t d; asm("max.xorsign.abs.f16x2 %0, %1, %2;" : "=r"(d) : "r"(a), "r"(b)); return d; }
__device__ __forceinline__ uint32_t amax_fold(uint32_t m) { return __reduce_max_sync(0xffffffffu, max(m & 0x7fffu, (m >> 16) & 0x7fffu)); }
__device__ __forceinline__ int wscale_exp(uint32_t m) { return min(141 - (int)(m >> 7), 100); }
__device__ __forceinline__ float exp2i(int e) { return __uint_as_float((uint32_t)(e + 127) << 23); }
__device__ __forceinline__ uint32_t bf2_to_h2(uint32_t w, float sc) { return pack_f16(bf_lo(w) * sc, bf_hi(w) * sc); }
__device__ __forceinline__ void bf2_to_h2_inplace(uint32_t& w, uint32_t sc2) {
  asm volatile("{\n.reg .b32 t, lo, hi;\nmul.rn.bf16x2 t, %0, %1;\nshl.b32 lo, t, 16;\nand.b32 hi, t, 0xffff0000;\ncvt.rn.f16x2.f32 %0, hi, lo;\n}" : "+r"(w) : "r"(sc2));
}
__device__ __forceinline__ void prefetch_l2(const void* p, uint32_t bytes) { asm volatile("cp.async.bulk.prefetch.L2.global [%0], %1;" :: "l"(p), "r"(bytes) : "memory"); }
__device__ __forceinline__ void prefetch_tma_2d(const CUtensorMap* tm, int c0, int c1) {
  asm volatile("cp.async.bulk.prefetch.tensor.2d.L2.global [%0, {%1, %2}];" :: "l"(tm), "r"(c0), "r"(c1) : "memory");
}
__host__ __device__ constexpr uint32_t acc_voff(int v) { return v < 4 ? v * 1024u : (v == 4 ? 128u : 3072u + 128u); }
__device__ __forceinline__ int unit28(int i) { return i == 3 ? 54 : 14 * i; }
__device__ __forceinline__ int unit24(int i) { return i < 2 ? 48 - 6 * i : 56 + 6 * i; }
__device__ __forceinline__ uint32_t acc_step(int s) { return (s >> 1) * 32768 + (s & 1) * 512; }
__device__ __forceinline__ uint32_t acc_lane(int i, int lane) { return ((lane >> 3) & 1) * 256 + (lane >> 4) * 4096 + i * 8192 + (lane & 7) * 16; }

__device__ __forceinline__ uint32_t ld_acquire_u32(const void* p) {
  uint32_t v; asm volatile("ld.acquire.gpu.global.u32 %0, [%1];" : "=r"(v) : "l"(p) : "memory"); return v;
}
template <int R> __device__ __forceinline__ void ln_rows(const uint2 (&xw)[R][5], int row0, int lane, bf16* __restrict__ xn, uint2* __restrict__ xh) {
  float v[R][20], s[R], q[R];
#pragma unroll
  for (int r = 0; r < R; r++) {
    s[r] = 0.f; q[r] = 0.f;
#pragma unroll
    for (int i = 0; i < 5; i++) { v[r][4 * i] = bf_lo(xw[r][i].x); v[r][4 * i + 1] = bf_hi(xw[r][i].x); v[r][4 * i + 2] = bf_lo(xw[r][i].y); v[r][4 * i + 3] = bf_hi(xw[r][i].y); }
#pragma unroll
    for (int i = 0; i < 5; i++) s[r] += (v[r][4 * i] + v[r][4 * i + 1]) + (v[r][4 * i + 2] + v[r][4 * i + 3]);
  }
#pragma unroll
  for (int o = 16; o; o >>= 1)
#pragma unroll
    for (int r = 0; r < R; r++) s[r] += __shfl_xor_sync(0xffffffffu, s[r], o);
#pragma unroll
  for (int r = 0; r < R; r++) {
    s[r] *= 1.f / cfg::DM;
#pragma unroll
    for (int i = 0; i < 10; i++) { const float d = v[r][2 * i] - s[r], e = v[r][2 * i + 1] - s[r]; q[r] += d * d + e * e; }
  }
#pragma unroll
  for (int o = 16; o; o >>= 1)
#pragma unroll
    for (int r = 0; r < R; r++) q[r] += __shfl_xor_sync(0xffffffffu, q[r], o);
#pragma unroll
  for (int r = 0; r < R; r++) {
    const int row = row0 + r;
    const float mb = bf16r(s[r]), var = bf16r(q[r] * (1.f / cfg::DM));
    float sd; asm("sqrt.approx.f32 %0, %1;" : "=f"(sd) : "f"(bf16r(var + 1e-5f)));
    const float inv = rcpf(bf16r(sd));
#pragma unroll
    for (int i = 0; i < 5; i++) {
      float y[4];
#pragma unroll
      for (int e = 0; e < 4; e++) y[e] = v[r][4 * i + e] - mb;
      bf16r2(y[0], y[1]); bf16r2(y[2], y[3]);
      const uint32_t w0 = pack_bf16(y[0] * inv, y[1] * inv), w1 = pack_bf16(y[2] * inv, y[3] * inv);
      *(uint2*)(xn + (size_t)row * cfg::DM + i * 128 + lane * 4) = make_uint2(w0, w1);
      if (xh) xh[(((size_t)(row >> 5) * 10 + 2 * i + (lane >> 4)) * 32 + (row & 31)) * 16 + ((((lane >> 1) & 7) ^ (row & 7)) << 1) + (lane & 1)] =
          make_uint2(pack_f16(bf_lo(w0), bf_hi(w0)), pack_f16(bf_lo(w1), bf_hi(w1)));
    }
  }
}

__global__ void __cluster_dims__(3, 1, 1) __launch_bounds__(384, 1) chain_kernel(const ChainArgs a, const __grid_constant__ CUtensorMap tmWq,
    const __grid_constant__ CUtensorMap tmWk, const __grid_constant__ CUtensorMap tmWv, const __grid_constant__ CUtensorMap tmWo) {
  using namespace ch;
  extern __shared__ __align__(1024) unsigned char smem_raw[];
  const uint32_t sb = smem_u32(smem_raw);
  const int warp = __shfl_sync(0xffffffffu, (int)threadIdx.x >> 5, 0);
  const int cta = blockIdx.x, h = cta / 3, j = cta % 3;
  unsigned char* const arena = a.arena;
  if (sb & 1023u) __trap();
  asm volatile("griddepcontrol.launch_dependents;");
  TL_BEGIN(a.tl);
  LITE(cta == 0 && threadIdx.x == 0, (a.tl >= 12) * 4);
#ifdef TIMELINE
  const unsigned long long g_tl0 = gtime();
#define PT(i) TLW((a.tl >= 12) * 128 + 64 + (i))
#else
#define PT(i)
#endif
  const int col0 = j == 0 ? 0 : (j == 1 ? 224 : 432);
  auto stage_w = [&](const CUtensorMap* tm, uint32_t dst, uint32_t mb, int half) {
    mbar_expect_tx(mb + 8 * half, 40960);
    tma_load_2d(dst + half * 40960, tm, h * cfg::DH + j * 64, half * 320, mb + 8 * half);
    tma_load_2d(dst + half * 40960 + 20480, tm, h * cfg::DH + j * 64, half * 320 + 160, mb + 8 * half);
  };
  if (threadIdx.x == 256) {
    for (int i = 0; i < 9; i++) mbar_init(sb + MB_K + 8 * i, 1);
    mbar_init(sb + MB_S, 1); mbar_init(sb + MB_O, 1); mbar_init(sb + MB_X, 1);
    asm volatile("fence.mbarrier_init.release.cluster;" ::: "memory");
    for (int i = 0; i < 2; i++) { stage_w(&tmWk, sb + OFF_WQ, sb + MB_K, i); stage_w(&tmWv, sb + OFF_WO, sb + MB_V, i); }
    sts32(sb + SC_W, 0); sts32(sb + SC_W + 4, 0); sts32(sb + SC_W + 8, 0); sts32(sb + SC_IN + 12, 0); sts32(sb + SC_IN + 20, 0); sts32(sb + SC_TW + 4, 99);
    mbar_expect_tx(sb + MB_S, 1280); mbar_expect_tx(sb + MB_O, 2048);
  }
  __syncthreads();
  asm volatile("barrier.cluster.arrive.relaxed.aligned;" ::: "memory");
  const uint32_t d1 = mapa_u32(sb, (j + 1) % 3) - sb, d2 = mapa_u32(sb, (j + 2) % 3) - sb;

  if (warp >= 8) {
    asm volatile("setmaxnreg.dec.sync.aligned.u32 40;");
    const int lane = fresh(threadIdx.x & 31), hw = warp - 8, ht = hw * 32 + lane;
    const bool lead = ht == 0;
    auto stage_wo = [&](int i) {
      mbar_expect_tx(sb + MB_R + 8 * i, 64 * WOS);
      tma_load_2d(sb + OFF_WO + i * 64 * WOS, &tmWo, col0, h * cfg::DH + ((i + j) % 3) * 64, sb + MB_R + 8 * i);
    };
    const unsigned char* xg = (const unsigned char*)a.xh;
    auto issue_x = [&](int s) { mbar_expect_tx(sb + MB_X, 40960); bulk_g2s(sb + OFF_X, xg + (size_t)s * 40960, 40960, sb + MB_X); };
    uint4 v[5];
#pragma unroll
    for (int i = 0; i < 5; i++) { const int c = ht + 128 * i; v[i] = ld_relaxed_v4(a.mem0 + (c & 7) * cfg::DM + (c >> 3) * 8); }
    if (hw == 2) {
      asm volatile("griddepcontrol.wait;" ::: "memory");
      if (lane == 0) { if (cta == 0) st_relaxed_u32(a.go, 1); issue_x(0); }
      PT(0);
    }
    if (hw == 0) {
      bar_sync(B_QK, 160);
      if (lane == 0) {
        stage_w(&tmWq, sb + OFF_WQ, sb + MB_Q, 0);
        if (PF2) { prefetch_tma_2d(&tmWq, h * cfg::DH + j * 64, 320); prefetch_tma_2d(&tmWq, h * cfg::DH + j * 64, 480); }
      }
      bar_sync(B_SL, 160); if (lane == 0) stage_w(&tmWq, sb + OFF_WQ, sb + MB_Q, 1);
    }
    if (hw == 1) {
      bar_sync(B_V, 160);
      if (lane == 0) {
        stage_wo(0);
        if (PF2) { prefetch_tma_2d(&tmWo, col0, h * cfg::DH + ((1 + j) % 3) * 64); prefetch_tma_2d(&tmWo, col0, h * cfg::DH + ((2 + j) % 3) * 64); }
      }
      bar_sync(B_O, 160); if (lane == 0) { stage_wo(1); stage_wo(2); }
    }
    __syncwarp();
    {
      uint32_t m = 0;
#pragma unroll
      for (int i = 0; i < 5; i++) {
        m = amax_bf2(amax_bf2(m, amax_bf2(v[i].x, v[i].y)), amax_bf2(v[i].z, v[i].w));
      }
      m = amax_fold(m);
      if (lane == 0) sts32(sb + SC_MX + hw * 4, m);
      bar_sync(B_H, 128);
      const uint4 mm = lds128(sb + SC_MX);
      const int se = max(wscale_exp(max(max(mm.x, mm.y), max(mm.z, mm.w))), -100);
      const float sc = exp2i(se);
#pragma unroll
      for (int i = 0; i < 5; i++) {
        const int c = ht + 128 * i, t = c & 7, chn = c >> 3;
        sts128(sb + OFF_MEM + chn * 128 + ((t ^ (2 * (chn & 3))) << 4), bf2_to_h2(v[i].x, sc), bf2_to_h2(v[i].y, sc), bf2_to_h2(v[i].z, sc), bf2_to_h2(v[i].w, sc));
      }
      if (lead) { sts32(sb + SC_IN, __float_as_uint(exp2i(-se))); sts32(sb + SC_IN + 4, 0x7800u); }
    }
    if (hw == 0) PT(11);
    {
      const uint32_t p0 = sb + OFF_WQ + hw * 2048 + lane * 16;
      uint32_t m = 0;
#pragma unroll 1
      for (int i = 0; i < 10; i++) {
        if (i == 0 || i == 5) mbar_wait(sb + MB_Q + (i ? 8 : 0), 0);
        uint32_t r[4][4];
        static_for<0, 4>([&](auto K) { ldsm_x4_i<K.value * 512>(r[K.value], p0 + i * 8192); });
#pragma unroll
        for (int k = 0; k < 4; k++) m = amax_bf2(amax_bf2(m, amax_bf2(r[k][0], r[k][1])), amax_bf2(r[k][2], r[k][3]));
      }
      if (hw == 0) PT(9);
      m = amax_fold(m);
      if (lane == 0) asm volatile("red.shared.max.u32 [%0], %1;" :: "r"(sb + SC_W + 8), "r"(m) : "memory");
      bar_sync(B_H, 128);
      const uint32_t sc = (uint32_t)(wscale_exp(lds32_i<SC_W + 8>(sb)) + 127) * 0x00800080u;
      uint32_t r[4][4];
      static_for<0, 2>([&](auto K) { ldsm_x4_i<K.value * 512>(r[K.value], p0); });
      auto cvt = [&](uint32_t (&x)[4], uint32_t p) { bf2_to_h2_inplace(x[0], sc); bf2_to_h2_inplace(x[1], sc); bf2_to_h2_inplace(x[2], sc); bf2_to_h2_inplace(x[3], sc); stsm_x4(p, x[0], x[1], x[2], x[3]); };
#pragma unroll 1
      for (int i = 0; i < 10; i++) {
        const uint32_t p = p0 + i * 8192;
        ldsm_x4_i<1024>(r[2], p); ldsm_x4_i<1536>(r[3], p);
        cvt(r[0], p); cvt(r[1], p + 512);
        ldsm_x4_i<8192>(r[0], p); ldsm_x4_i<8192 + 512>(r[1], p);
        cvt(r[2], p + 1024); cvt(r[3], p + 1536);
      }
    }
    if (hw == 0) PT(10);
    bar_sync(0, 384);
    if (hw == 3) {
      const uint32_t eye = ((lane >> 3) == (lane & 3)) ? ((lane & 4) ? 0x3f800000u : 0x3f80u) : 0u;
      sts128(sb + OFF_LT + lane * 16, eye, eye, (lane & 2) * 64 + (lane >> 2) * 16 + (lane & 1) * 8, 0u);
      sts64(sb + OFF_S + 1280 + lane * 8, 0u, 0u);
    }
    if (lead) st_relaxed_u32(arena + AR_TAB + cta * 4, 0x80000000u | (lds32_i<SC_W>(sb) << 15) | lds32_i<SC_W + 4>(sb));
    asm volatile("barrier.cluster.wait.aligned;" ::: "memory");
    bar_sync(B_MEM0, 256); bar_sync(B_MEM1, 256);
    {
      uint32_t v0, v1, v2; int spin = 0;
      do {
        v0 = ld_relaxed_u32(arena + AR_TAB + lane * 4); v1 = ld_relaxed_u32(arena + AR_TAB + 128 + lane * 4); v2 = ld_relaxed_u32(arena + AR_TAB + 256 + lane * 4);
      } while (__any_sync(0xffffffffu, ((v0 & v1 & v2) >> 31) == 0) && ++spin < SPIN_LIMIT);
      const uint32_t mv = (max(max(v0, v1), v2) >> 15) & 0x7fffu, mo = max(max(v0 & 0x7fffu, v1 & 0x7fffu), v2 & 0x7fffu);
      sts32(sb + SC_IN + 8 + (lane & 1) * 16, 15 - ((__reduce_max_sync(0xffffffffu, mv) >> 7) + (__reduce_max_sync(0xffffffffu, mo) >> 7) - 252 + 22));
    }

    auto store_kv = [&](int s) {
      const size_t o = ((size_t)s * 96 + cta) * KVB; const uint32_t src = sb + OFF_KV + (s & 1) * (2 * KVB);
      fence_proxy_async(); bulk_s2g(a.kg + o, src, KVB); bulk_s2g(a.vg + o, src + KVB, KVB); bulk_commit();
    };
    const int cb28 = unit28(hw), du = (unit24(hw) - cb28) * 128;
    uint32_t n16 = lane * 16, hist = 0;
    const uint32_t us1 = sb + d1 + OFF_SR + 256 + (hw >> 1) * 512 + (hw & 1) * 128, us2 = sb + d2 + OFF_SR + (hw >> 1) * 512 + (hw & 1) * 128;
    const uint32_t uo1 = sb + d1 + OFF_O + 2048 + hw * 256, uo2 = sb + d2 + OFF_O + 1024 + hw * 256;
#ifdef STEPCLK
    if (lead) a.dbg[96 * 300 + cta * 2] = clk32();
#endif
#ifdef TIMELINE
    if (cta == 0 && lead) { g_tl2[(a.tl >= 12) * 128 + 0] = clock64(); g_tl2[(a.tl >= 12) * 128 + 1] = gtime(); }
#endif
#pragma unroll 1
    for (int s = 0; s < cfg::NSEG; s++) {
      TS_SETUP();
      const bool last = s == cfg::NSEG - 1;
      if (n16 == 0) {
        if (hw == 2 && !last) issue_x(s + 1);
        if (hw == 0 && (s & 3) == 1 && s > 1) st_relaxed_u32(arena + (prog_off(h, j) + lds32_i<SC_IN + 12>(sb)), s - 1);
        if (hw == 0 && s > 0) store_kv(s - 1);
        if (PFX && hw == 3 && cta < 80 && s + PFX < cfg::NSEG) prefetch_l2(xg + (size_t)(s + PFX) * 40960 + cta * 512, 512);
        if (PFACC && hw == 1 && s + PFACC < cfg::NSEG - 1)
          asm volatile("prefetch.global.L2 [%0];" :: "l"(arena + (AR_ACC + acc_step(s + PFACC) + acc_lane(cta / 24, (cta & 3) * 8) + acc_voff((cta % 24) >> 2))) : "memory");
      }
      __syncwarp();
      if (last) break;
      const uint32_t kv = (s & 1) * (2 * KVB);
      n16 = fresh(n16);
      uint32_t kb0[4], kb1[4];
      { const uint32_t ka = n16 + (n16 & 384) * 4 + (sb + kv + hw * 128); ldsm_x4_i<OFF_KV>(kb0, ka); ldsm_x4_i<OFF_KV + 2560>(kb1, ka); }
      TS(1);
      bar_sync(B_QK, 384);
      {
        uint32_t q0[4], q1[4], q2[4], q3[4];
        float sa[4] = {0, 0, 0, 0}, sc2[4] = {0, 0, 0, 0};
        ldsm_x4_i<OFF_Q>(q0, n16 + sb); ldsm_x4_i<OFF_Q + 1024>(q2, n16 + sb); ldsm_x4_i<OFF_Q + 512>(q1, n16 + sb);
        bar_arrive(B_A, 288);
        ldsm_x4_i<OFF_Q + 1536>(q3, n16 + sb);
        mma16816(sa, q0[0], q0[1], q0[2], q0[3], kb0[0], kb0[1]);
        mma16816(sc2, q2[0], q2[1], q2[2], q2[3], kb1[0], kb1[1]);
        mma16816(sa, q1[0], q1[1], q1[2], q1[3], kb0[2], kb0[3]);
        mma16816(sc2, q3[0], q3[1], q3[2], q3[3], kb1[2], kb1[3]);
        const float x0 = (sa[0] + sa[2]) + (sc2[0] + sc2[2]), x1 = (sa[1] + sa[3]) + (sc2[1] + sc2[3]);
        const uint32_t xp = pack_bf16(x0, x1);
        st_async_b32_i<0>((n16 >> 2) + us1, xp, sb + MB_S + d1);
        st_async_b32_i<0>((n16 >> 2) + us2, xp, sb + MB_S + d2);
        stsm_x2(n16 + (sb + OFF_S + hw * 256), __float_as_uint(x0), __float_as_uint(x1));
      }
      TS(3);
      uint32_t v0[4], v1[4], vm0, vm1;
      const uint32_t uv = sb + kv + hw * 1280;
      ldsm_x4_t_i<OFF_KV + KVB>(v0, n16 + uv); ldsm_x4_t_i<OFF_KV + KVB + 640>(v1, n16 + uv);
      bar_sync(B_SL, 256);
      float t0[4], t1[4], t2[4];
      { uint32_t x[4]; ldsm_x4_i<OFF_S>(x, n16 + sb); t0[0] = __uint_as_float(x[0]); t0[1] = __uint_as_float(x[1]); t0[2] = __uint_as_float(x[2]); t0[3] = __uint_as_float(x[3]); }
      { uint32_t x[4]; ldsm_x4_i<OFF_S + 512>(x, n16 + sb); t1[0] = __uint_as_float(x[0]); t1[1] = __uint_as_float(x[1]); t1[2] = __uint_as_float(x[2]); t1[3] = __uint_as_float(x[3]); }
      { uint32_t x[4]; ldsm_x4_i<OFF_S + 1024>(x, n16 + sb); t2[0] = __uint_as_float(x[0]); t2[1] = __uint_as_float(x[1]); t2[2] = __uint_as_float(x[2]); t2[3] = __uint_as_float(x[3]); }
      mbar_spin(sb + MB_S, s & 1);
      TS(4);
      uint2 xo;
      {
        uint32_t r0[4], r1[4], r2[2];
        ldsm_x4_i<OFF_SR>(r0, n16 + sb); ldsm_x4_i<OFF_SR + 512>(r1, n16 + sb); ldsm_x2_i<OFF_SR + 1024>(r2, n16 + sb);
        SFENCE(n16);
        const uint2 eye = lds64_i<OFF_LT>(n16 + sb);
        mma16816(t0, r0[0], r0[1], r0[2], r0[3], eye.x, eye.y);
        mma16816(t1, r1[0], r1[1], r1[2], r1[3], eye.x, eye.y);
        mma1688(t2, r2[0], r2[1], eye.x);
        bar_sync(B_V, 256);
        vm0 = ldsm_x1_t_i<OFF_KV + KVB + 512>(n16 + uv); vm1 = ldsm_x1_t_i<OFF_KV + KVB + 1152>(n16 + uv);
        SFENCE(n16);
        xo = lds64_i<OFF_LT + 8>(n16 + sb);
      }
      float sc[10] = {t0[0], t0[1], t0[2], t0[3], t1[0], t1[1], t1[2], t1[3], t2[0] + t2[2], t2[1] + t2[3]};
      const float cs = 0.07216878364870322f * 1.4426950408889634f;
      float mx = fmaxf(fmaxf(fmaxf(sc[0], sc[1]), fmaxf(sc[2], sc[3])), fmaxf(fmaxf(sc[4], sc[5]), fmaxf(sc[6], sc[7])));
      mx = fmaxf(mx, fmaxf(sc[8], sc[9]));
      {
        const float m1 = __shfl_xor_sync(0xffffffffu, mx, 1), m2 = __shfl_xor_sync(0xffffffffu, mx, 2), m3 = __shfl_xor_sync(0xffffffffu, mx, 3);
        mx = fmaxf(fmaxf(mx, m1), fmaxf(m2, m3));
      }
      const float mo = fmaf(mx, -cs, __uint_as_float(xo.x));
      auto ex = [&](int i) -> uint32_t { float x, y;
        asm volatile("ex2.approx.ftz.f32 %0, %1;" : "=f"(x) : "f"(fmaf(sc[i], cs, mo))); asm volatile("ex2.approx.ftz.f32 %0, %1;" : "=f"(y) : "f"(fmaf(sc[i + 1], cs, mo)));
        return pack_bf16(x, y); };
      float oa[4] = {0, 0, 0, 0}, ob[4] = {0, 0, 0, 0}, oc[4] = {0, 0, 0, 0}, od[4] = {0, 0, 0, 0}, rs[4] = {0, 0, 0, 0};
      const uint32_t ones = 0x3f803f80u;
      const uint32_t p4 = ex(8);
      if (MEMFIRST) { mma1688(rs, p4, 0u, ones); mma1688(oa, p4, 0u, vm0); mma1688(ob, p4, 0u, vm1); }
      const uint32_t p0 = ex(0), p1 = ex(2), p2 = ex(4), p3 = ex(6);
      TS(5);
      mma16816(rs, p0, p2, p1, p3, ones, ones);
      mma16816(oa, p0, p2, p1, p3, v0[0], v0[1]);
      mma16816(oc, p0, p2, p1, p3, v0[2], v0[3]);
      mma16816(ob, p0, p2, p1, p3, v1[0], v1[1]);
      mma16816(od, p0, p2, p1, p3, v1[2], v1[3]);
      if (!MEMFIRST) { mma1688(rs, p4, 0u, ones); mma1688(oa, p4, 0u, vm0); mma1688(ob, p4, 0u, vm1); }
      const float inv = rcpf(rs[0] + rs[2]) * __uint_as_float(xo.y);
      {
        const uint32_t y0 = pack_bf16((oa[0] + oc[2]) * inv, (oa[1] + oc[3]) * inv), y1 = pack_bf16((ob[0] + od[2]) * inv, (ob[1] + od[3]) * inv);
        st_async_v2_i<0>(xo.x + uo1, y0, y1, sb + MB_O + d1);
        st_async_v2_i<0>(xo.x + uo2, y0, y1, sb + MB_O + d2);
        sts64_i<OFF_O>(xo.x + (sb + hw * 256), y0, y1);
      }
      bar_arrive(B_O, 384);
      TS(6);
      if (hw == 0) bulk_wait<0>();
      mbar_expect_tx_if(n16 == 0 && hw == 3, sb + MB_S, 1280);
      n16 = fresh(n16);
      const int ln = n16 >> 4;
      auto mslot = [&](int c) -> uint32_t { return sb + OFF_MEM + c * 128 + (((ln >> 2) ^ (2 * (c & 3))) << 4); };
      const int lq = ln & 3;
      const uint32_t ma = mslot(cb28 + lq), mb_ = mslot(cb28 + (lq >> 1)) + (lq & 1) * 8;
      const unsigned char* gp = arena + (AR_ACC + acc_lane(hw, ln) + acc_step(s));
      const bool odd = ln & 1;
      const uint32_t delay = a.delay + ((hist & 2) ? a.margin : 0);
      SFENCE(ma);
      uint32_t tw;
      if (hw == 0 && (s & 3) == 0 && a.pubrel) {
        bar_arrive(B_RED, 384);
        asm volatile("fence.acq_rel.gpu;" ::: "memory");
        uint2 t; int sp = 0;
        do { asm volatile("ld.volatile.shared.v2.u32 {%0,%1}, [%2];" : "=r"(t.x), "=r"(t.y) : "r"(sb + SC_TW) : "memory"); } while (__any_sync(0xffffffffu, t.y != (uint32_t)s) && ++sp < SPIN_LIMIT);
        tw = t.x;
      } else {
        bar_sync(B_RED, 384);
        SFENCE(mb_);
        tw = clk_v();
        if (hw == 1) asm volatile("st.volatile.shared.v2.u32 [%0], {%1,%2};" :: "r"(sb + SC_TW), "r"(tw), "r"(s) : "memory");
      }
      TSV(7, tw);
      mbar_expect_tx_if(n16 == 0 && hw == 3, sb + MB_O, 2048);
      while (clk_v() - tw < delay) {}
      TS(8);
      uint4 v[6];
      int spin = 0;
      const uint32_t cm = odd ? 0x5000u : 0u;
      do {
        static_for<0, 6>([&](auto I) { v[I.value] = ld_relaxed_v4_i<acc_voff(I.value)>(gp); });
      } while (__any_sync(0xffffffffu, (~((v[0].w & v[1].w & v[2].w) & (v[3].w & v[4].w & v[5].w)) & cm) != 0) && ++spin < SPIN_LIMIT);
      v[0].w = odd ? v[3].x : v[0].w; v[1].w = odd ? v[3].y : v[1].w; v[2].w = odd ? v[3].z : v[2].w; v[3].w = odd ? 0u : v[3].w;
      sts128_i<0>(ma, v[0].x, v[0].y, v[0].z, v[0].w);
      sts128_i<512>(ma, v[1].x, v[1].y, v[1].z, v[1].w);
      sts128_i<1024>(ma, v[2].x, v[2].y, v[2].z, v[2].w);
      sts128_i<0>(ma + du, v[4].x, v[4].y, v[4].z, v[5].z);
      sts64_i<512>(mb_ + du, v[5].x, v[5].y);
      if (!odd) sts128_i<1536>(mb_, v[3].x, v[3].y, v[3].z, v[3].w);
      hist = (hist * 2 + (spin != 0)) & 0xffffu;
      TSV(11, spin);
#ifdef TIMELINE
      if (hw == 2 && ln == 0) { uint32_t gt; asm volatile("mov.u32 %0, %%globaltimer_lo;" : "=r"(gt)); *(uint4*)(g_step + (((a.tl >= 12) * 64 + s) * 96 + cta) * 4) = make_uint4(gt, spin, clk_v() - tw, tw); }
#endif
      TS(10);
      bar_sync(B_MEM0, 256); bar_sync(B_MEM1, 256);
      uint32_t m = lds32_i<SC_IN + 12>(sb);
      uint32_t m2 = m;
      static_for<0, 3>([&](auto I) { m = amax_h2(amax_h2(amax_h2(amax_h2(m, v[I.value].x), v[I.value].y), v[I.value].z), v[I.value].w); });
      static_for<3, 6>([&](auto I) { m2 = amax_h2(amax_h2(amax_h2(m2, v[I.value].x), v[I.value].y), v[I.value].z); });
      m = amax_fold(amax_h2(amax_h2(m2, v[3].w), m));
      if (n16 == 0) asm volatile("red.shared.max.u32 [%0], %1;" :: "r"(sb + SC_IN + 4 + 16 * ((s + 1) & 1)), "r"(m) : "memory");
    }
    bar_sync(B_RED, 384);
    if (hw == 0 && n16 == 0) {
      store_kv(cfg::NSEG - 1);
      bulk_wait<0>();
      st_release_u32(arena + (prog_off(h, j) + lds32_i<SC_IN + 12>(sb)), cfg::NSEG);
    }
    __syncwarp();
#ifdef STEPCLK
    if (hw == 0 && n16 == 0) a.dbg[96 * 300 + cta * 2 + 1 + (hist >> 20)] = clk32();
#endif
#ifdef TIMELINE
    if (cta == 0 && hw == 0 && n16 == 0) { g_tl2[(a.tl >= 12) * 128 + 2] = clock64(); g_tl2[(a.tl >= 12) * 128 + 3] = gtime(); }
#endif
    TL_END(a.tl);
    asm volatile("barrier.cluster.arrive.relaxed.aligned; barrier.cluster.wait.aligned;" ::: "memory");
  } else {
    asm volatile("setmaxnreg.inc.sync.aligned.u32 232;");
    const int wi = warp & 3, hf = warp >> 2;
    [[maybe_unused]] const int tid = threadIdx.x;
    int lane = fresh(threadIdx.x & 31);
    uint32_t w[40][4], wm = 0;
    uint32_t wqa;
    { const int r8 = lane & 7, mrow = r8 + ((lane >> 4) << 3), mch = 2 * wi + ((lane >> 3) & 1); wqa = sb + mrow * 128 + ((mch ^ r8) << 4); }
    float iw, iq;
#pragma unroll 1
    for (int live = a.dry ? 0 : 1; live < 2; live++) {
      const uint32_t wa = wqa + (hf ? OFF_WO : OFF_WQ);
      wm = 0;
      mbar_wait_if(live, sb + (hf ? MB_V : MB_K), 0);
      static_for<0, 20>([&](auto K) { ldsm_x4_t_i<K.value * 2048>(w[K.value], wa); });
#pragma unroll
      for (int k = 0; k < 20; k++) wm = amax_bf2(amax_bf2(wm, amax_bf2(w[k][0], w[k][1])), amax_bf2(w[k][2], w[k][3]));
      SFENCE2(wa, wm);
      if (warp == 0 && live) PT(1);
      if (live) bar_arrive(hf ? B_V : B_QK, 160);
      mbar_wait_if(live, sb + (hf ? MB_V : MB_K) + 8, 0);
      static_for<20, 40>([&](auto K) { ldsm_x4_t_i<K.value * 2048>(w[K.value], wa); });
#pragma unroll
      for (int k = 20; k < 40; k++) wm = amax_bf2(amax_bf2(wm, amax_bf2(w[k][0], w[k][1])), amax_bf2(w[k][2], w[k][3]));
      SFENCE2(wa, wm);
      if (warp == 4 && live) PT(2);
      if (live) bar_arrive(hf ? B_O : B_SL, 160);
      SFENCE(wa);
      const uint32_t m = amax_fold(wm);
      if (hf && live) asm volatile("red.shared.max.u32 [%0], %1;" :: "r"(sb + SC_W), "r"(m) : "memory");
      const int e = wscale_exp(m);
      const uint32_t sc = (uint32_t)(e + 127) * 0x00800080u; iw = exp2i(-e);
#pragma unroll
      for (int k = 0; k < 40; k++) { bf2_to_h2_inplace(w[k][0], sc); bf2_to_h2_inplace(w[k][1], sc); bf2_to_h2_inplace(w[k][2], sc); bf2_to_h2_inplace(w[k][3], sc); }
    }
    iw = uniform_f(iw);
    if (warp == 0) PT(3);
    uint32_t x0[8];
    {
      float xa[16];
      const uint32_t dlo = (((sb + OFF_X) & 0x3FFFF) >> 4) | (1u << 16);
      mbar_wait(sb + MB_X, 0);
      if (warp == 0) PT(4);
      wgmma_fence();
      static_for<0, 40>([&](auto K) { constexpr int k = K.value; wgmma_rs32h<((k >> 2) * 4096 + (k & 3) * 32) / 16, (k != 0)>(xa, w[k], dlo); });
      wgmma_commit();
      wgmma_wait<0>();
#pragma unroll
      for (int i = 0; i < 8; i++) x0[i] = pack_bf16(xa[2 * i] * iw, xa[2 * i + 1] * iw);
    }
    lane = fresh(threadIdx.x & 31);
    const int g = lane >> 2, q4 = lane & 3, r8 = lane & 7, m4 = lane >> 3;
    const bool t28 = j == 0 || warp < 4;
    const int bi = j == 0 ? hf : (warp < 4 ? j + 1 : 2 * (j - 1) + ((warp - 4) >> 1)), bv = t28 ? wi : 4 + (warp & 1);
    uint32_t wo1 = sb + OFF_WO + warp * 896 + lane * 16, wo2;
    {
      const int cb = (t28 ? unit28(bi) : unit24(bi)) - col0 / 8;
      uint32_t cp[4];
#pragma unroll
      for (int wd = 0; wd < 4; wd++) {
        int c, p;
        if (bv < 3) { c = 4 * bv + q4; p = wd; }
        else if (bv == 3) { if (q4 & 1) { c = 4 * (wd % 3) + q4; p = 3; } else { c = 12 + (q4 >> 1); p = wd; } }
        else if (bv == 4) { c = q4; p = wd; }
        else { if (wd < 2) { c = 4 + (q4 >> 1); p = 2 * (q4 & 1) + wd; } else { c = q4; p = 3; } }
        cp[wd] = sb + OFF_WO + ((g & 1) + (g & 2) * 4 + (g >> 2) * 2) * WOS + (cb + c) * 16 + p * 4;
      }
      const int cidx = (r8 & 1) + ((r8 >> 2) << 1);
      wo2 = sb + OFF_WO + warp * 896 + ((m4 & 1) ? 768 + (m4 >> 1) * 64 + cidx * 16 : 512 + (m4 >> 1) * 128 + r8 * 16);
      const bool dump = (m4 & 1) && (r8 & 2);
      uint32_t mo = 0;
      const bool regular = bv < 3 || bv == 4;
#pragma unroll 1
      for (int i = 0; i < 3; i++) {
        uint32_t x[4][4], y[4][4];
        const uint32_t o = i * 4 * WOK;
        mbar_wait(sb + MB_R + 8 * i, 0);
        if (warp == 0) PT(5 + i);
        if (regular) {
          static_for<0, 4>([&](auto K) {
            constexpr int kk = K.value;
            const uint4 u = lds128_i<kk * WOK>(cp[0] + o), v = lds128_i<kk * WOK + 4 * WOS>(cp[0] + o);
            x[kk][0] = u.x; x[kk][1] = u.y; x[kk][2] = u.z; x[kk][3] = u.w; y[kk][0] = v.x; y[kk][1] = v.y; y[kk][2] = v.z; y[kk][3] = v.w;
          });
        } else {
          static_for<0, 4>([&](auto K) {
            constexpr int kk = K.value;
#pragma unroll
            for (int wd = 0; wd < 4; wd++) { x[kk][wd] = lds32_i<kk * WOK>(cp[wd] + o); y[kk][wd] = lds32_i<kk * WOK + 4 * WOS>(cp[wd] + o); }
          });
        }
        bar_sync(B_C, 256);
        static_for<0, 4>([&](auto K) {
          constexpr int kk = K.value;
#pragma unroll
          for (int wd = 0; wd < 4; wd++) mo = amax_bf2(mo, amax_bf2(x[kk][wd], y[kk][wd]));
          stsm_x4_t_i<kk * WOK>(wo1 + o, x[kk][0], x[kk][1], y[kk][0], y[kk][1]);
          stsm_x4_t_i<0>(dump ? sb + OFF_S + 512 + lane * 16 : wo2 + o + kk * WOK, x[kk][2], x[kk][3], y[kk][2], y[kk][3]);
        });
      }
      if (warp == 0) PT(8);
      mo = amax_fold(mo);
      if (lane == 0) asm volatile("red.shared.max.u32 [%0], %1;" :: "r"(sb + SC_W + 4), "r"(mo) : "memory");
    }
    __syncwarp();
    auto run = [&](auto HF) {
    constexpr int hf = HF.value;
    uint32_t mema, sta, l16 = sb + lane * 16;
    uint32_t rq[hf ? NP1 : NQ0][4];
    auto step_addr = [&](uint32_t kv) {
      const int lr = (l16 >> 4) & 7, lm = (l16 >> 7) & 3;
      mema = l16 ^ (lm << 5);
      sta = sb + lr * 16 + (lm < 2 ? OFF_Q + wi * 512 + hf * 128 + lm * 256 : OFF_KV + kv + 512 + (2 * wi + lm - 2) * 640);
    };
    auto x_gemm = [&](uint32_t ph, [[maybe_unused]] uint32_t tsb) {
      float xa[16];
      const uint32_t dlo = (((sb + OFF_X) & 0x3FFFF) >> 4) | (1u << 16);
      constexpr int NP = hf ? NP1 : NP0;
      if constexpr (hf) {
        static_for<PQE, NP>([&](auto K) { ldsm_x4_t_i<OFF_WQ + K.value * 2048>(rq[K.value], wqa); });
        bar_sync(B_X, 256);
      }
      wgmma_fence();
      static_for<0, 40>([&](auto K) {
        constexpr int k = K.value;
        wgmma_rs32h<((k >> 2) * 4096 + (k & 3) * 32) / 16, (k != 0)>(xa, w[k], dlo);
        if constexpr (!hf && k == PFK && NP > PQE) { SFENCE(wqa); static_for<PQE, NP>([&](auto K) { ldsm_x4_t_i<OFF_WQ + K.value * 2048>(rq[K.value], wqa); }); SFENCE(wqa); }
        if constexpr (!hf && k == XT) bar_arrive(B_X, 256);
      });
      step_addr(ph * (2 * KVB));
      wgmma_commit();
      TS(9);
      wgmma_wait<0>();
      const uint32_t xs = l16 + (wi * 1280 + ph * (2 * KVB));
      stsm_x4_t_i<OFF_KV + hf * KVB>(xs, pack_bf16(xa[0] * iw, xa[1] * iw), pack_bf16(xa[4] * iw, xa[5] * iw), pack_bf16(xa[8] * iw, xa[9] * iw), pack_bf16(xa[12] * iw, xa[13] * iw));
      stsm_x4_t_i<OFF_KV + hf * KVB + 640>(xs, pack_bf16(xa[2] * iw, xa[3] * iw), pack_bf16(xa[6] * iw, xa[7] * iw), pack_bf16(xa[10] * iw, xa[11] * iw), pack_bf16(xa[14] * iw, xa[15] * iw));
      if constexpr (!hf) static_for<NP0, NP0 + NPL>([&](auto K) { ldsm_x4_t_i<OFF_WQ + K.value * 2048>(rq[K.value], wqa); });
    };
    auto wq_addr = [&](uint32_t l) -> uint32_t {
      const int lr = (l >> 4) & 7, lm = (l >> 7) & 3;
      return sb + hf * ((40 - NQ1) * 2048) + (lr + ((lm >> 1) << 3)) * 128 + (((2 * wi + (lm & 1)) ^ lr) << 4);
    };
    constexpr int NPM = hf ? NPM1 : NPM0;
    uint32_t u1[NPM][4], u2[NPM][4];
    static_for<0, NPM>([&](auto K) { ldsm_x4_i<(12 - NPM + K.value) * WOK>(u1[K.value], wo1); ldsm_x4_i<(12 - NPM + K.value) * WOK>(u2[K.value], wo2); });
    bar_sync(0, 384);
    iq = uniform_f(exp2i(-wscale_exp(lds32_i<SC_W + 8>(sb))));
    wqa = wq_addr(l16);
    static_for<0, (hf ? NP1 : NP0 + NPL)>([&](auto K) { ldsm_x4_t_i<OFF_WQ + K.value * 2048>(rq[K.value], wqa); });
    step_addr(0);
    stsm_x4_t_i<OFF_KV + hf * KVB>(l16 + wi * 1280, x0[0], x0[2], x0[4], x0[6]);
    stsm_x4_t_i<OFF_KV + hf * KVB + 640>(l16 + wi * 1280, x0[1], x0[3], x0[5], x0[7]);
    asm volatile("barrier.cluster.wait.aligned;" ::: "memory");
    TL_END(a.tl + 1);
#pragma unroll 1
    for (int s = 0; s < cfg::NSEG - 1; s++) {
      TS_SETUP();
#if CHAIN_TIMING
      if (tid == 0 && (s & 7) == 0) a.dbg[96 * 288 + cta * 8 + (s >> 3)] = clk32();
#endif
      bar_sync(hf ? B_MEM1 : B_MEM0, 256);
      const float sin_ = __uint_as_float(lds32_i<SC_IN>(sb + 16 * (s & 1)));
      constexpr int NPQ = (40 - NQ1) / 2;
      if constexpr (hf == 0) {
        float k0[4] = {0, 0, 0, 0}, k1[4] = {0, 0, 0, 0}, q0[4] = {0, 0, 0, 0}, q1[4] = {0, 0, 0, 0};
        constexpr auto pair_of = [](int t) { const int a = t * (20 - NPQ) / 20, b = (t + 1) * (20 - NPQ) / 20; return b > a ? NPQ + a : t - a; };
        uint32_t b[NB0][4];
        static_for<0, NB0>([&](auto T) { ldsm_x4_i<OFF_MEM + pair_of(T.value) * 512>(b[T.value], mema); });
        static_for<NP0 + NPL, NQ0>([&](auto K) { ldsm_x4_t_i<OFF_WQ + K.value * 2048>(rq[K.value], wqa); });
        if (BBS < 100) bbfence<0>(mema);
        static_for<0, 20>([&](auto T) {
          constexpr int t = T.value, p = pair_of(t);
          uint32_t (&bb)[4] = b[t % NB0];
          if constexpr (p < NPQ) {
            mma16816h(q0, rq[(2 * p) % NQ0], bb[0], bb[1]);
            if constexpr (2 * p + NQ0 < 2 * NPQ) ldsm_x4_t_i<OFF_WQ + (2 * p + NQ0) * 2048>(rq[(2 * p) % NQ0], wqa);
          }
          mma16816h(k0, w[2 * p], bb[0], bb[1]);
          if constexpr (p < NPQ) {
            mma16816h(q1, rq[(2 * p + 1) % NQ0], bb[2], bb[3]);
            if constexpr (2 * p + 1 + NQ0 < 2 * NPQ) ldsm_x4_t_i<OFF_WQ + (2 * p + 1 + NQ0) * 2048>(rq[(2 * p + 1) % NQ0], wqa);
          }
          mma16816h(k1, w[2 * p + 1], bb[2], bb[3]);
          if constexpr (NVE > 0 && t + NB0 == VET) bar_arrive(B_E, 256);
          if constexpr (t + NB0 < 20) ldsm_x4_i<OFF_MEM + pair_of(t + NB0) * 512>(bb, mema);
          if constexpr (t < 20 - NB0 && (t % BBS) == BBS - 1) bbfence<t + 1>(mema);
        });
        const float sq = sin_ * iq, sk = sin_ * iw;
        stsm_x4_t_i<0>(sta, pack_bf16((q0[0] + q1[0]) * sq, (q0[1] + q1[1]) * sq), pack_bf16((q0[2] + q1[2]) * sq, (q0[3] + q1[3]) * sq),
                       pack_bf16((k0[0] + k1[0]) * sk, (k0[1] + k1[1]) * sk), pack_bf16((k0[2] + k1[2]) * sk, (k0[3] + k1[3]) * sk));
        bar_sync(B_QK, 384);
        TS(2);
        {
          if (wi == 3) {
            const uint32_t xr = sb + ((l16 & 511) >> 2), ka = l16 + (l16 & 384) * 4 + (s & 1) * (2 * KVB);
            uint32_t a0[4], a1[4], a2[4], a3[4], kb0[4], kb1[4];
            ldsm_x4_i<OFF_Q>(a0, l16); ldsm_x4_i<OFF_KV + 512>(kb0, ka); ldsm_x4_i<OFF_Q + 1024>(a2, l16); ldsm_x4_i<OFF_KV + 512 + 2560>(kb1, ka);
            ldsm_x4_i<OFF_Q + 512>(a1, l16);
            bar_arrive(B_A, 288);
            ldsm_x4_i<OFF_Q + 1536>(a3, l16);
            float sa[4] = {0, 0, 0, 0}, sc2[4] = {0, 0, 0, 0};
            mma16816(sa, a0[0], a0[1], a0[2], a0[3], kb0[0], kb0[1]);
            mma16816(sc2, a2[0], a2[1], a2[2], a2[3], kb1[0], kb1[1]);
            mma16816(sa, a1[0], a1[1], a1[2], a1[3], kb0[2], kb0[3]);
            mma16816(sc2, a3[0], a3[1], a3[2], a3[3], kb1[2], kb1[3]);
            const float x0 = (sa[0] + sa[2]) + (sc2[0] + sc2[2]), x1 = (sa[1] + sa[3]) + (sc2[1] + sc2[3]);
            const uint32_t xp = pack_bf16(x0, x1);
            st_async_b32_i<OFF_SR + 1024 + 128>(xr + d1, xp, sb + MB_S + d1);
            st_async_b32_i<OFF_SR + 1024>(xr + d2, xp, sb + MB_S + d2);
            stsm_x2(l16 + OFF_S + 1024, __float_as_uint(x0), __float_as_uint(x1));
          } else if (wi == 0) {
            const uint4 si = lds128_i<SC_IN>(sb + 16 * (s & 1));
            const int em = (int)(si.y >> 10) - 14 + (int)(si.x >> 23) - 127;
            const uint32_t osc = __float_as_uint(exp2i(max(min((int)si.z - max(em, 1), 100), -100)));
            sts32(l16 + OFF_LT + 12, osc); sts64_i<SC_IN>(sb + 16 * ((s + 1) & 1), 0x7f000000u - osc, 0u);
          }
          bar_sync(B_SL, 256);
        }
      } else {
        float v0[4] = {0, 0, 0, 0}, v1[4] = {0, 0, 0, 0}, q0[4] = {0, 0, 0, 0}, q1[4] = {0, 0, 0, 0};
        constexpr int NB1 = NQ1 / 2 < 3 ? NQ1 / 2 : 3;
        uint32_t b[NB1][4];
        static_for<0, NB1>([&](auto T) { ldsm_x4_i<OFF_MEM + (NPQ + T.value) * 512>(b[T.value], mema); });
        static_for<0, NQ1 / 2>([&](auto T) {
          constexpr int t = T.value, p = NPQ + t;
          uint32_t (&bb)[4] = b[t % NB1];
          mma16816h(q0, rq[(2 * t) % NP1], bb[0], bb[1]);
          if constexpr (2 * t + NP1 < NQ1) ldsm_x4_t_i<OFF_WQ + (2 * t + NP1) * 2048>(rq[(2 * t) % NP1], wqa);
          mma16816h(q1, rq[(2 * t + 1) % NP1], bb[2], bb[3]);
          if constexpr (2 * t + 1 + NP1 < NQ1) ldsm_x4_t_i<OFF_WQ + (2 * t + 1 + NP1) * 2048>(rq[(2 * t + 1) % NP1], wqa);
          mma16816h(v0, w[2 * p], bb[0], bb[1]);
          mma16816h(v1, w[2 * p + 1], bb[2], bb[3]);
          if constexpr (t + NB1 < NQ1 / 2) ldsm_x4_i<OFF_MEM + (p + NB1) * 512>(bb, mema);
        });
        const float sq = sin_ * iq, sv = sin_ * iw;
        stsm_x2_t_i<0>(sta, pack_bf16((q0[0] + q1[0]) * sq, (q0[1] + q1[1]) * sq), pack_bf16((q0[2] + q1[2]) * sq, (q0[3] + q1[3]) * sq));
        TS(2);
        bar_arrive(B_QK, 384);
        float v2[4] = {0, 0, 0, 0}, v3[4] = {0, 0, 0, 0};
        auto vpair = [&](auto P, uint32_t (&bb)[4]) {
          constexpr int p = P.value;
          if constexpr (p & 1) { mma16816h(v0, w[2 * p], bb[0], bb[1]); mma16816h(v1, w[2 * p + 1], bb[2], bb[3]); }
          else { mma16816h(v2, w[2 * p], bb[0], bb[1]); mma16816h(v3, w[2 * p + 1], bb[2], bb[3]); }
        };
        if constexpr (NVE > 0) {
          uint32_t e[NVE ? NVE : 1][4];
          bar_sync(B_E, 256);
          static_for<0, NVE>([&](auto T) { ldsm_x4_i<OFF_MEM + T.value * 512>(e[T.value], mema); });
          static_for<0, NVE>([&](auto T) { vpair(T, e[T.value]); });
        }
        bar_sync(B_A, 288);
        uint32_t c[4][4];
        static_for<NVE, (NVE + 4 < NPQ ? NVE + 4 : NPQ)>([&](auto T) { ldsm_x4_i<OFF_MEM + T.value * 512>(c[T.value & 3], mema); });
        static_for<NVE, NPQ>([&](auto T) {
          constexpr int p = T.value;
          vpair(T, c[p & 3]);
          if constexpr (p + 4 < NPQ) ldsm_x4_i<OFF_MEM + (p + 4) * 512>(c[p & 3], mema);
        });
        stsm_x2_t_i<OFF_KV + KVB + 512>(l16 + (l16 & 128) * 4 + (wi * 1280 + (s & 1) * (2 * KVB)), pack_bf16(((v0[0] + v1[0]) + (v2[0] + v3[0])) * sv, ((v0[1] + v1[1]) + (v2[1] + v3[1])) * sv),
                            pack_bf16(((v0[2] + v1[2]) + (v2[2] + v3[2])) * sv, ((v0[3] + v1[3]) + (v2[3] + v3[3])) * sv));
        bar_arrive(B_V, 256);
      }
      TS(3);
      {
        uint32_t t1[12][4], t2[12][4];
        const uint32_t o16 = l16;
        wo1 = l16 + (OFF_WO + warp * 896);
        wo2 = sb + OFF_WO + warp * 896 + ((l16 & 128) ? 768 + ((l16 & 256) >> 2) + (l16 & 16) + ((l16 & 64) >> 1) : 512 + ((l16 & 256) >> 1) + (l16 & 112));
        constexpr int NR_ = NRT - NPM;
        auto ldw = [&](auto K) { if constexpr (K.value < 12 - NPM) { ldsm_x4_i<K.value * WOK>(t1[K.value], wo1); ldsm_x4_i<K.value * WOK>(t2[K.value], wo2); } };
        constexpr int PB = (hf ? PB1 : PB0) < NR_ ? (hf ? PB1 : PB0) : NR_, PA = (hf ? PA1 : PA0) < PB ? (hf ? PA1 : PA0) : PB;
        static_for<0, PA>(ldw);
        mbar_spin(sb + MB_X, (s + 1) & 1);
        if constexpr (PB > PA) {
          constexpr int PM = PA + PM1 < PB ? PA + PM1 : PB;
          mbar_spin(sb + MB_S, s & 1);
          const uint32_t t0 = clk_v();
          if constexpr (PM > PA) { while (clk_v() - t0 < GD1) {} static_for<PA, PM>(ldw); }
          if constexpr (PB > PM) { while (clk_v() - t0 < GD2) {} static_for<PM, PB>(ldw); }
        }
        float c0[4] = {0, 0, 0, 0}, c1[4] = {0, 0, 0, 0}, e0[4] = {0, 0, 0, 0}, e1[4] = {0, 0, 0, 0};
        uint32_t ob[6][4];
        auto kstep = [&](auto K) {
          constexpr int k = K.value;
          uint32_t (&bb)[4] = ob[k >> 1];
          uint32_t (&x)[4] = k < 12 - NPM ? t1[k] : u1[k < 12 - NPM ? 0 : k - (12 - NPM)];
          uint32_t (&y)[4] = k < 12 - NPM ? t2[k] : u2[k < 12 - NPM ? 0 : k - (12 - NPM)];
          if constexpr (k & 1) { mma16816(c1, x[0], x[1], x[2], x[3], bb[2], bb[3]); mma16816(e1, y[0], y[1], y[2], y[3], bb[2], bb[3]); }
          else { mma16816(c0, x[0], x[1], x[2], x[3], bb[0], bb[1]); mma16816(e0, y[0], y[1], y[2], y[3], bb[0], bb[1]); }
          if constexpr (k >= NRF) ldw(IC<k + NR_ - NRF>{});
        };
        auto ldo = [&](auto P) { ldsm_x4_i<OFF_O + P.value * 512>(ob[P.value], o16); };
        TS(4);
        bar_sync(B_O, 384);
        ldo(IC<0>{}); ldo(IC<1>{});
        SFENCE(o16);
        static_for<PB, NR_>(ldw);
        static_for<0, 4>(kstep);
        TS(5);
        mbar_spin(sb + MB_O, s & 1);
        TS(6);
        ldo(IC<2>{}); ldo(IC<NPM >= 2 ? 5 : 3>{});
        if (WOF) SFENCE(o16);
        kstep(IC<4>{});
        if constexpr (NPM < 2) { kstep(IC<5>{}); ldo(IC<4>{}); kstep(IC<6>{}); kstep(IC<7>{}); ldo(IC<5>{}); static_for<8, 12>(kstep); }
        else if constexpr (NPM >= 4) { kstep(IC<10>{}); kstep(IC<11>{}); ldo(IC<4>{}); kstep(IC<5>{}); ldo(IC<3>{}); kstep(IC<8>{}); kstep(IC<9>{}); kstep(IC<6>{}); kstep(IC<7>{}); }
        else { kstep(IC<5>{}); ldo(IC<3>{}); kstep(IC<11>{}); kstep(IC<10>{}); ldo(IC<4>{}); kstep(IC<6>{}); kstep(IC<7>{}); if constexpr (NPM == 3) { kstep(IC<9>{}); kstep(IC<8>{}); } else { kstep(IC<8>{}); kstep(IC<9>{}); } }
        l16 = fresh(l16);
        const int ln = (l16 >> 4) & 31;
        if constexpr (CEARLY && hf) { SFENCE2(o16, __float_as_uint(e1[0])); bar_arrive(B_G, 256); }
        unsigned char* gr = arena + (AR_ACC + acc_lane(bi, ln) + acc_voff(bv) + acc_step(s));
        const bool cnt = (ln & 1) || !t28;
        wqa = wq_addr(l16);
        SFENCE(o16);
        static_for<0, PQE>([&](auto K) { ldsm_x4_t_i<OFF_WQ + K.value * 2048>(rq[K.value], wqa); });
        const uint32_t y0 = movm_t(pack_f16(c0[0] + c1[0], c0[1] + c1[1])), y1 = movm_t(pack_f16(c0[2] + c1[2], c0[3] + c1[3]));
        const uint32_t y2 = movm_t(pack_f16(e0[0] + e1[0], e0[1] + e1[1])), y3 = movm_t(pack_f16(e0[2] + e1[2], e0[3] + e1[3]));
        asm volatile("red.relaxed.gpu.global.add.noftz.v4.f16x2 [%0], {%1,%2,%3,%4};" :: "l"(gr), "r"(y0), "r"(y1), "r"(y2), "r"(cnt ? 0x3c00u : y3) : "memory");
        bar_arrive(B_RED, 384);
        if constexpr (CEARLY && !hf) { bar_arrive(B_C, 256); bar_sync(B_G, 256); }
        else bar_sync(B_C, 256);
        TS(7);
      }
#if CHAIN_TIMING
      x_gemm((s + 1) & 1, tsb);
#else
      x_gemm((s + 1) & 1, 0);
#endif
      TS(8);
    }
    };
    if (hf == 0) run(IC<0>{}); else run(IC<1>{});
    {
      const uint32_t l16 = sb + (threadIdx.x & 31) * 16, mema = l16 ^ ((l16 >> 2) & 96);
      float c0[4] = {0, 0, 0, 0}, c1[4] = {0, 0, 0, 0}, c2[4] = {0, 0, 0, 0}, c3[4] = {0, 0, 0, 0};
      bar_sync(hf ? B_MEM1 : B_MEM0, 256);
      const float sc = __uint_as_float(lds32_i<SC_IN + 16>(sb)) * iw;
      static_for<0, 10>([&](auto T) {
        constexpr int p = 2 * T.value;
        uint32_t b0[4], b1[4];
        ldsm_x4_i<OFF_MEM + p * 512>(b0, mema); ldsm_x4_i<OFF_MEM + p * 512 + 512>(b1, mema);
        mma16816h(c0, w[2 * p], b0[0], b0[1]); mma16816h(c1, w[2 * p + 1], b0[2], b0[3]);
        mma16816h(c2, w[2 * p + 2], b1[0], b1[1]); mma16816h(c3, w[2 * p + 3], b1[2], b1[3]);
      });
      stsm_x2_t_i<OFF_KV + 2 * KVB + 512>(l16 + (l16 & 128) * 4 + wi * 1280 + hf * KVB, pack_bf16(((c0[0] + c1[0]) + (c2[0] + c3[0])) * sc, ((c0[1] + c1[1]) + (c2[1] + c3[1])) * sc),
                                          pack_bf16(((c0[2] + c1[2]) + (c2[2] + c3[2])) * sc, ((c0[3] + c1[3]) + (c2[3] + c3[3])) * sc));
      fence_proxy_async();
    }
    LITE(cta == 0 && threadIdx.x == 0, (a.tl >= 12) * 4 + 1);
    bar_arrive(B_RED, 384);
#if CHAIN_TIMING
    for (int i = tid; i < 288; i += 256) a.dbg[cta * 288 + i] = lds32_i<OFF_BAR + 128>(sb + i * 4);
#endif
    asm volatile("barrier.cluster.arrive.relaxed.aligned; barrier.cluster.wait.aligned;" ::: "memory");
  }
}
struct PrepArgs { const bf16 *wqkv, *wphi, *wo; unsigned char *wb, *wot; };
__device__ __forceinline__ void prep_body(const int cta, const PrepArgs& pa) {
  const int tid = threadIdx.x, lane = tid & 31, warp = tid >> 5, g = lane >> 2, q = lane & 3;
  const int pair = cta >> 1, which = cta & 1;
  uint32_t bfr[2][3][3];
#pragma unroll
  for (int hh = 0; hh < 2; hh++)
#pragma unroll
    for (int t = 0; t < 3; t++) {
      const unsigned short* ph = (const unsigned short*)pa.wphi + (2 * pair + hh) * 400 + (t < 2 ? 8 * t + g : 16 + (g >> 1)) + 2 * q * 20;
#pragma unroll
      for (int r = 0; r < 3; r++) {
        const int o = (r < 2 || q < 2) ? r * 160 : 0;
        const uint32_t v = (uint32_t)__ldg(ph + o) | ((uint32_t)__ldg(ph + o + 20) << 16);
        bfr[hh][t][r] = ((t < 2 || (g & 1) == hh) && (r < 2 || q < 2)) ? v : 0u;
      }
    }
  const int gt = cta * 256 + tid;
#pragma unroll 1
  for (int i = 0; i < 5; i++) {
    uint32_t af[2][6];
#pragma unroll
    for (int hh = 0; hh < 2; hh++) {
      const uint32_t* r0 = (const uint32_t*)(pa.wqkv + (size_t)((warp * 5 + i) * 16 + g) * 1920 + which * 640 + (2 * pair + hh) * 20) + q;
      af[hh][0] = __ldg(r0); af[hh][1] = __ldg(r0 + 7680); af[hh][2] = __ldg(r0 + 4); af[hh][3] = __ldg(r0 + 7684);
      af[hh][4] = __ldg(r0 + 8); af[hh][5] = __ldg(r0 + 7688);
    }
    const int iv = i * 4096 + (gt >> 1), k = (iv & 7) + (iv >> 8) * 8, h = (iv >> 3) & 31;
    const uint2* src = (const uint2*)(pa.wqkv + (size_t)k * 1920 + 1280 + h * 20) + (gt & 1) * 2;
    const uint2 a = __ldg(src), b = __ldg(src + 1), e = __ldg(src + 2);
    uint4 wv[2]; uint32_t wd[2];
#pragma unroll
    for (int n = 0; n < 2; n++) {
      const int iw = min((2 * i + n) * 5120 + gt, 640 * 80 - 1), r = iw & 7, c = (iw >> 3) % 80, kg = iw / 640, c5 = kg % 5;
      const int row = (kg / 5) * 40 + (c5 < 2 ? 8 * c5 + r : (c5 == 2 ? 16 + (r & 3) + (r >> 2) * 20 : 20 + 8 * (c5 - 3) + r));
      wv[n] = __ldg((const uint4*)(pa.wo + (size_t)row * cfg::DM + c * 8));
      wd[n] = (((c / 10) * 80 + kg) * 10 + c % 10) * 128 + r * 16;
    }
    uint4* dv = (uint4*)(pa.wb + ((size_t)((h >> 2) * 80 + (k >> 3)) * 32 + 20 + 3 * (h & 3)) * 128 + (k & 7) * 16);
    dv[(gt & 1) * 8] = make_uint4(a.x, a.y, b.x, b.y);
    if (gt & 1) dv[16] = (h & 1) ? make_uint4(0, 0, e.x, e.y) : make_uint4(e.x, e.y, 0, 0);
    if (gt < 5120) { *(uint4*)(pa.wot + wd[0]) = wv[0]; *(uint4*)(pa.wot + wd[1]) = wv[1]; }
    uint32_t* dst = (uint32_t*)(pa.wb + ((size_t)((pair >> 1) * 80 + (warp * 5 + i) * 2) * 32 + which * 10 + (pair & 1) * 5) * 128) + lane;
#pragma unroll
    for (int t = 0; t < 5; t++) {
      float d[4] = {0, 0, 0, 0};
#pragma unroll
      for (int hh = 0; hh < 2; hh++)
        if (t == 2 || (t > 2) == (hh == 1)) {
          const int tt = t < 3 ? t : t - 3;
          mma16816(d, af[hh][0], af[hh][1], af[hh][2], af[hh][3], bfr[hh][tt][0], bfr[hh][tt][1]);
          mma1688(d, q < 2 ? af[hh][4] : 0u, q < 2 ? af[hh][5] : 0u, bfr[hh][tt][2]);
        }
      dst[t * 32] = pack_bf16(d[0], d[1]); dst[1024 + t * 32] = pack_bf16(d[2], d[3]);
    }
  }
}

__global__ void __launch_bounds__(256, 4) ln_kernel(const bf16* __restrict__ xin, bf16* __restrict__ xn, uint2* __restrict__ xh, uint4* __restrict__ z0, int n0,
                                                    uint4* __restrict__ z1, int n1, const bf16* pfa, const bf16* pfb, int npf, int tl) {
  asm volatile("griddepcontrol.wait;" ::: "memory");
  asm volatile("griddepcontrol.launch_dependents;" ::: "memory");
  TL_BEGIN(tl);
  const int warp = threadIdx.x >> 5, lane = threadIdx.x & 31;
  const int row = blockIdx.x * 8 + warp;
  uint2 xw[1][5];
#pragma unroll
  for (int i = 0; i < 5; i++) xw[0][i] = *(const uint2*)(xin + (size_t)row * cfg::DM + i * 128 + lane * 4);
  for (int i = blockIdx.x * 256 + threadIdx.x; i < n0; i += 256 * 256) z0[i] = make_uint4(0, 0, 0, 0);
  for (int i = blockIdx.x * 256 + threadIdx.x; i < n1; i += 256 * 256) z1[i] = make_uint4(0, 0, 0, 0);
  if (npf && xw[0][4].y != 0x7fc17fc1u) {
    for (int i = 0; i < npf; i++) {
      const uint32_t l = (uint32_t)i * 32768u + (blockIdx.x * 256 + threadIdx.x) / 2;
      if (l < cfg::DM * cfg::HD / 64) asm volatile("prefetch.global.L2 [%0];" :: "l"(((threadIdx.x & 1) ? pfa : pfb) + (size_t)l * 64) : "memory");
    }
  }
  ln_rows<1>(xw, row, lane, xn, xh);
  TL_END(tl);
}
struct Pipe { uint32_t stage, phase; };
template <int NS> __device__ __forceinline__ void pipe_adv(Pipe& p) { if (++p.stage == NS) { p.stage = 0; p.phase ^= 1; } }
constexpr uint32_t SWZ128 = 1;
__device__ __forceinline__ uint64_t desc_kmajor(uint32_t a) { return make_desc(a, 16, 1024, SWZ128); }
__device__ __forceinline__ uint64_t desc_mnmajor(uint32_t a) { return make_desc(a, 8192, 1024, SWZ128); }
__device__ __forceinline__ void wait_ge(const void* p, uint32_t target, uint32_t ns = 32) {
  int spin = 0;
  while (ld_acquire_u32(p) < target) { __nanosleep(ns); if (++spin > (1 << 21)) break; }
}
__device__ __forceinline__ void bulk_g2s_hint(uint32_t dst, const void* src, uint32_t bytes, uint32_t mb, uint64_t pol) {
  asm volatile("cp.async.bulk.shared::cluster.global.mbarrier::complete_tx::bytes.L2::cache_hint [%0], [%1], %2, [%3], %4;"
               :: "r"(dst), "l"(src), "r"(bytes), "r"(mb), "l"(pol) : "memory");
}
#ifndef PF_WB
#define PF_WB 2
#endif
#ifndef PF_XN
#define PF_XN 1
#endif
#ifndef ZINIT
#define ZINIT 1
#endif
#ifndef STAG
#define STAG 1
#endif
#ifndef EF_KV
#define EF_KV 1
#endif
#ifndef EF_O
#define EF_O 1
#endif
__device__ __forceinline__ void fence_proxy_async_global() { asm volatile("fence.proxy.async.global;" ::: "memory"); }

namespace tr {
constexpr int NS = 4, STQ = 16384 + 24576, STO = 16384 + 40960;
constexpr int SEGB = 15360;
constexpr int OFF_K = NS * STQ;
constexpr int OFF_BAR = NS * STO;
constexpr int SMEM = OFF_BAR + 256;
static_assert(OFF_K + 4 * SEGB <= OFF_BAR && SMEM <= 232448, "smem");
enum { T_QA = 0, T_Q, T_A, T_OB, T_OS, T_L, T_END, T_P };
constexpr uint32_t C_QA = AR_CNT, C_O = AR_CNT + 64, C_Q = AR_CNT + 128, C_P = AR_CNT + 192;
constexpr int MAXITEMS = 1200;
struct Sched {
  uint8_t ks[16];
  uint8_t wide[16];
  uint8_t lrows[16];
  uint32_t n;
  uint16_t item[MAXITEMS];
};
struct Args {
  const unsigned char *kg, *vg;
  unsigned char* o;
  uint4* qs;
  unsigned char* part;
  const bf16 *xin, *xq;
  bf16 *xout, *xn;
  unsigned char* arena;
  const unsigned* go;
  int tl;
  uint32_t nap, nap2;
  int pfprep;
};
}

template <int N0, int N1>
__device__ __forceinline__ void tr_mainloop(float (&a0)[N0 / 2], float (&a1)[N1 ? N1 / 2 : 1], Pipe& p, uint32_t sb, uint32_t full, uint32_t empty, int nkb, int wg) {
  using namespace tr;
  constexpr uint32_t ST = N1 ? STO : STQ;
  uint32_t prev = 0;
#pragma unroll
  for (int i = 0; i < N0 / 2; i++) { if (ZINIT) a0[i] = 0.f; else asm volatile("" : "=f"(a0[i])); }
  if constexpr (N1 > 0) {
#pragma unroll
    for (int i = 0; i < N1 / 2; i++) a1[i] = 0.f;
  }
#pragma unroll 1
  for (int kb = 0; kb < nkb; kb++) {
    mbar_wait(full + 8 * p.stage, p.phase);
    const uint32_t st = ((sb & 0x3FFFF) >> 4) + p.stage * (ST / 16), sa = st + wg * 512;
    wgmma_fence();
#pragma unroll
    for (int kk = 0; kk < 4; kk++) {
      const uint64_t da = desc16<16, 1024, 1>(sa, kk * 32);
      if constexpr (N0 == 192) wgmma_n192<0, 1>(a0, da, desc16<8192, 1024, 1>(st, 16384 + kk * 2048), (kb | kk) != 0);
      else wgmma_n128<0, 1>(a0, da, desc16<8192, 1024, 1>(st, 16384 + kk * 2048), (kb | kk) != 0);
      if constexpr (N1 > 0) wgmma_n128<0, 1>(a1, da, desc16<8192, 1024, 1>(st, 16384 + 24576 + kk * 2048), (kb | kk) != 0);
    }
    wgmma_commit();
    if (kb > 0) { wgmma_wait<1>(); mbar_arrive_if((threadIdx.x & 127) == 0, empty + 8 * prev); }
    prev = p.stage;
    pipe_adv<NS>(p);
  }
  wgmma_wait<0>();
  mbar_arrive_if((threadIdx.x & 127) == 0, empty + 8 * prev);
}
template <int N> __device__ __forceinline__ void stage_tiles(const float (&o)[N / 2], uint32_t base, int wi, int lane) {
  const uint32_t ra = base + (wi * 16 + (lane & 7) + 8 * ((lane >> 3) & 1)) * 128;
#pragma unroll
  for (int v = 0; v < N / 8; v += 2)
    stsm_x4(ra + (v >> 3) * 8192 + ((((v & 7) + (lane >> 4)) ^ (lane & 7)) << 4), pack_bf16(o[4 * v], o[4 * v + 1]), pack_bf16(o[4 * v + 2], o[4 * v + 3]),
            pack_bf16(o[4 * v + 4], o[4 * v + 5]), pack_bf16(o[4 * v + 6], o[4 * v + 7]));
}
__global__ void __launch_bounds__(384, 1) trail_kernel(const __grid_constant__ CUtensorMap tmX, const __grid_constant__ CUtensorMap tmQ,
                                                       const __grid_constant__ CUtensorMap tmWo5, const __grid_constant__ CUtensorMap tmWo2,
                                                       const __grid_constant__ CUtensorMap tmP, const __grid_constant__ tr::Sched sc,
                                                       const __grid_constant__ tr::Args a, const __grid_constant__ PrepArgs pa) {
  using namespace tr;
  [[maybe_unused]] const int tl = a.tl;
  TL_BEGIN(tl);
  extern __shared__ __align__(1024) unsigned char smem_raw[];
  const uint32_t sb = smem_u32(smem_raw);
  const int warp = __shfl_sync(0xffffffffu, (int)threadIdx.x >> 5, 0), lane = threadIdx.x & 31;
  unsigned char* const arena = a.arena;
  const uint32_t full = sb + OFF_BAR, empty = full + 8 * NS, barK = empty + 8 * NS, barKfree = barK + 16, staged = barKfree + 16;
  const uint32_t kvrdy = staged + 32, mfull = kvrdy + 8, mempty = mfull + 16, mbox = mempty + 16;
  uint32_t go = 0;
  if (threadIdx.x == 256) go = ld_acquire_u32(a.go);
  if (threadIdx.x == 0) {
    for (int i = 0; i < NS; i++) { mbar_init(full + 8 * i, 1); mbar_init(empty + 8 * i, 2); }
    for (int i = 0; i < 2; i++) {
      mbar_init(barK + 8 * i, 1); mbar_init(barKfree + 8 * i, 1); mbar_init(staged + 16 * i, 4); mbar_init(staged + 16 * i + 8, 4);
      mbar_init(mfull + 8 * i, 1); mbar_init(mempty + 8 * i, 11);
    }
    mbar_init(kvrdy, 1);
    asm volatile("fence.mbarrier_init.release.cluster;" ::: "memory");
  }
  __syncthreads();
  Pipe mp{0, 0};
  auto next_item = [&]() -> uint32_t {
    uint32_t it;
    mbar_wait(mfull + 8 * mp.stage, mp.phase);
    asm volatile("ld.shared.u32 %0, [%1];" : "=r"(it) : "r"(mbox + 4 * mp.stage) : "memory");
    return it;
  };
  if (warp >= 8) {
    asm volatile("setmaxnreg.dec.sync.aligned.u32 40;");
    if (warp == 8) { go = __shfl_sync(0xffffffffu, go, 0); if (elect_one()) {
      Pipe p{0, 1};
      mp.phase = 1;
      uint32_t kph = 1, rph = 0, wide = 0, qdone = 0;
      prefetch_tmap(&tmX); prefetch_tmap(&tmQ); prefetch_tmap(&tmWo5); prefetch_tmap(&tmWo2); prefetch_tmap(&tmP);
      const uint64_t ef = policy_evict_first();
      auto ld_kv = [&](uint32_t d, const void* s, uint32_t n, uint32_t mb) { if (EF_KV) bulk_g2s_hint(d, s, n, mb, ef); else bulk_g2s(d, s, n, mb); };
      auto ld_o = [&](uint32_t d, const void* s, uint32_t n, uint32_t mb) { if (EF_O) bulk_g2s_hint(d, s, n, mb, ef); else bulk_g2s(d, s, n, mb); };
      auto stage = [&](uint32_t bytes) -> uint32_t {
        mbar_wait(empty + 8 * p.stage, p.phase);
        mbar_expect_tx(full + 8 * p.stage, bytes);
        return sb + p.stage * (wide ? STO : STQ);
      };
      auto fetch = [&]() -> uint32_t { uint32_t v; asm volatile("atom.relaxed.gpu.global.add.u32 %0, [%1], 1;" : "=r"(v) : "l"(arena + AR_QUEUE) : "memory"); return v; };
      if (!go) wait_ge(a.go, 1, 200);
      fence_proxy_async_global();
      uint32_t next = fetch();
      while (true) {
        const uint32_t item = next;
        const uint32_t code = sc.item[min(item, sc.n)];
        const int type = (code >> 11) & 7, m = (code >> 7) & 15, k = code & 127;
        const bool late = code >> 14;
        auto done_wait = [&]() { mbar_wait(mempty + 8 * (mp.stage ^ 1), mp.stage ? mp.phase ^ 1 : mp.phase); };
        if (type == T_A && !((qdone >> m) & 1)) { wait_ge(arena + C_Q + m * 4, 64); qdone |= 1u << m; }
        if (type == T_OB && !wide) for (uint32_t i = 0; i < NS; i++) mbar_wait(empty + 8 * i, i >= p.stage ? p.phase : p.phase ^ 1);
        wide = type == T_OB;
        mbar_wait(mempty + 8 * mp.stage, mp.phase);
        asm volatile("st.shared.u32 [%0], %1;" :: "r"(mbox + 4 * mp.stage), "r"((p.stage << 24) | (type << 16) | (m << 8) | (k & 255)) : "memory");
        mbar_arrive(mfull + 8 * mp.stage);
        pipe_adv<2>(mp);
        if (type == T_END) break;
        if (type == T_P) { done_wait(); next = fetch(); continue; }
        if (type == T_L) {
          const int nr = sc.lrows[m], np = sc.ks[m];
          prefetch_l2(a.xin + (size_t)(m * 128 + k * 8 * nr) * cfg::DM, nr * 10240);
          wait_ge(arena + C_O + m * 4, np * (sc.wide[m] ? 4 : 10), m < 13 ? a.nap : 32);
          fence_proxy_async_global();
#pragma unroll 1
          for (int r = 0; r < nr; r++) {
            const int rg = m * 16 + k * nr + r;
#pragma unroll 1
            for (int q0 = 0; q0 <= np; q0 += 4) {
              const int n = min(4, np + 1 - q0);
              const uint32_t st = stage(n * 10240), fb = full + 8 * p.stage;
#pragma unroll 1
              for (int q = q0; q < q0 + n; q++) {
                if (q == 0) bulk_g2s(st, a.xin + (size_t)rg * 8 * cfg::DM, 10240, fb);
                else tma_load_3d(st + (q - q0) * 10240, &tmP, 0, rg & 7, ((q - 1) * 32 + (rg >> 3)) * 10, fb);
              }
              pipe_adv<NS>(p);
            }
          }
          if (late) done_wait();
          next = fetch(); continue;
        }
        if (type <= T_A) {
          if (type != T_A)
#pragma unroll 1
            for (int kb = 0; kb < 10; kb++) {
              const uint32_t st = stage(STQ), fb = full + 8 * p.stage;
              tma_load_2d(st, &tmX, kb * 64, m * 128, fb);
              tma_load_3d(st + 16384, &tmQ, 0, kb * 64, k * 3, fb);
              pipe_adv<NS>(p);
              if (type == T_Q && kb == 8) next = fetch();
            }
          if (type != T_Q) {
            const size_t blk = ((size_t)m * 4 * 96 + k * 3) * 5120;
            kph ^= 1;
            mbar_wait(kvrdy, rph); rph ^= 1;
            if (!late) next = fetch();
            fence_proxy_async_global();
#pragma unroll 1
            for (int w = type == T_A ? 0 : 2; w < 4; w++) {
              const uint32_t st = stage(2 * SEGB), fb = full + 8 * p.stage;
              for (int sg = 0; sg < 2; sg++) ld_kv(st + sg * SEGB, (w < 2 ? a.kg : a.vg) + blk + (size_t)(2 * (w & 1) + sg) * (96 * 5120), SEGB, fb);
              pipe_adv<NS>(p);
            }
            if (late) { done_wait(); next = fetch(); }
          }
        } else {
          const int nn = wide ? 2 : 5, nb = wide ? 5 : 2, nt = k % nn, nkb = 96 / sc.ks[m], k0 = (k / nn) * nkb;
          const Pipe p0 = p;
          for (int kb = 0; kb < nkb; kb++) {
            if (wide && kb < NS && p.stage >= 2) { mbar_wait(barKfree, kph); mbar_wait(barKfree + 8, kph); }
            const uint32_t st = stage(16384 + nb * 8192), fb = full + 8 * p.stage;
            tma_load_3d(st + 16384, wide ? &tmWo5 : &tmWo2, 0, (k0 + kb) * 64, nt * nb, fb);
            if (kb >= NS) ld_o(st, a.o + ((size_t)m * 96 + k0 + kb) * 16384, 16384, fb);
            pipe_adv<NS>(p);
            if (kb == NS - 1 || (kb == nkb - 1 && nkb < NS)) {
              wait_ge(arena + C_QA + m * 4, 64, m < 14 ? a.nap : 32);
              fence_proxy_async_global();
              Pipe q = p0;
#pragma unroll 1
              for (int i = 0; i <= kb; i++) { ld_o(sb + q.stage * (wide ? STO : STQ), a.o + ((size_t)m * 96 + k0 + i) * 16384, 16384, full + 8 * q.stage); pipe_adv<NS>(q); }
            }
          }
          if (!late) next = fetch();
          for (int w = wide ? -(int)((2 - p.stage) & 3) : 0; w < 2; w++) { mbar_wait(empty + 8 * p.stage, p.phase); mbar_arrive(full + 8 * p.stage); pipe_adv<NS>(p); }
          kph ^= wide;
          if (late) { done_wait(); next = fetch(); }
        }
      }
    } } else if (warp < 11) { if (elect_one()) {
      const int w = warp - 9;
      uint32_t sph = 0;
      [[maybe_unused]] int nlog = 0;
#ifdef TIMELINE
      if (w == 0) { unsigned long long* lg = g_log + (((tl >= 12) * 132 + blockIdx.x) * 64 + nlog++) * 2; lg[0] = T_END << 16; lg[1] = gtime(); lg[2] = ~0ull; }
#endif
      while (true) {
        const uint32_t it = next_item();
        const int type = (it >> 16) & 255, m = (it >> 8) & 255, k = it & 255;
        const uint32_t slot = mp.stage;
        pipe_adv<2>(mp);
        if (type == T_END) break;
        mbar_wait(staged + 16 * w + 8 * slot, (sph >> slot) & 1); sph ^= 1u << slot;
        mbar_arrive(mempty + 8 * slot);
#ifdef TIMELINE
        if (w == 0 && nlog < 63) { unsigned long long* lg = g_log + (((tl >= 12) * 132 + blockIdx.x) * 64 + nlog++) * 2; lg[0] = (type << 16) | (m << 8) | k; lg[1] = gtime(); lg[2] = ~0ull; }
#endif
        if (type == T_L) continue;
        if (type == T_QA || type == T_A) {
          for (int jj = 0; jj < 3; jj++) bulk_s2g(a.o + ((size_t)m * 96 + k * 3 + jj) * 16384 + w * 8192, sb + OFF_K + w * 2 * SEGB + jj * 8192, 8192);
          bulk_commit();
          bulk_wait<0>();
          mbar_arrive(barKfree + 8 * w);
        } else if (type == T_OB || type == T_OS) {
          const bool wide = type == T_OB;
          const int nn = wide ? 2 : 5, nb = wide ? 5 : 2;
          const uint32_t own = wide ? 2 + w : ((it >> 24) + 96 / sc.ks[m] + w) % NS;
          bulk_s2g(a.part + ((size_t)((k / nn) * 32 + m * 2 + w) * 10 + (k % nn) * nb) * 8192, sb + own * (wide ? STO : STQ), nb * 8192);
          bulk_commit();
          bulk_wait<0>();
          mbar_arrive(empty + 8 * own);
          if (wide && w) { mbar_arrive(barKfree); mbar_arrive(barKfree + 8); }
        }
        red_release_inc(arena + (type == T_Q ? C_Q : (type <= T_A ? C_QA : (type == T_P ? C_P : C_O))) + m * 4);
      }
    } } else if (elect_one()) {
      const uint64_t ef = policy_evict_first();
      uint32_t kph = 1;
      if (PF_WB && blockIdx.x >= 52) { prefetch_l2(pa.wb + (blockIdx.x - 52) * 32768, 32768); prefetch_l2(pa.wot + (blockIdx.x - 52) * 10240, 10240); }
      if (PF_WB > 1 && blockIdx.x >= 52) { prefetch_l2(a.xn + (blockIdx.x - 52) * 8192, 16384); prefetch_l2(a.xout + (blockIdx.x - 52) * 8192, 16384); }
      while (true) {
        const uint32_t it = next_item();
        const int type = (it >> 16) & 255, m = (it >> 8) & 255, k = it & 255;
        const uint32_t slot = mp.stage;
        pipe_adv<2>(mp);
        if (type == T_END) break;
        if (a.pfprep && type == T_QA && m == 0) { prefetch_l2(pa.wqkv + k * 38400, 76800); prefetch_l2(pa.wo + k * 12800, 25600); }
        if (PF_XN && type == T_QA && m < 15) prefetch_l2(a.xq + ((m + 1) * 128 + k * 4) * cfg::DM, 5120);
        if (type == T_QA || type == T_A) {
          for (int spin = 0; spin < (1 << 21); spin++) {
            uint4 f;
            asm volatile("ld.acquire.gpu.global.v4.u32 {%0,%1,%2,%3}, [%4];" : "=r"(f.x), "=r"(f.y), "=r"(f.z), "=r"(f.w) : "l"(arena + prog_off(k, 0)) : "memory");
            if (min(min(f.x, f.y), f.z) >= (uint32_t)(4 * m + 4)) break;
            __nanosleep(m < 15 ? a.nap : a.nap2);
          }
          mbar_arrive(kvrdy);
          fence_proxy_async_global();
          const unsigned char* src = a.kg + ((size_t)m * 4 * 96 + k * 3) * 5120;
#pragma unroll 1
          for (int w = 0; w < 2; w++) {
            mbar_wait(barKfree + 8 * w, kph);
            if (type == T_A) { mbar_arrive(barK + 8 * w); continue; }
            mbar_expect_tx(barK + 8 * w, 2 * SEGB);
            for (int sg = 2 * w; sg < 2 * w + 2; sg++) { if (EF_KV) bulk_g2s_hint(sb + OFF_K + sg * SEGB, src + (size_t)sg * (96 * 5120), SEGB, barK + 8 * w, ef); else bulk_g2s(sb + OFF_K + sg * SEGB, src + (size_t)sg * (96 * 5120), SEGB, barK + 8 * w); }
          }
          kph ^= 1;
        } else if (type == T_OB) {
          mbar_wait(barKfree, kph); mbar_wait(barKfree + 8, kph);
          kph ^= 1;
        }
        mbar_arrive(mempty + 8 * slot);
      }
      if (blockIdx.x == gridDim.x - 1) asm volatile("griddepcontrol.wait;" ::: "memory");
    }
    return;
  }
  asm volatile("setmaxnreg.inc.sync.aligned.u32 232;");
  const int wg = warp >> 2, wi = warp & 3;
  const int g = lane >> 2, q4 = lane & 3;
  asm volatile("griddepcontrol.launch_dependents;" ::: "memory");
  Pipe p{0, 0};
  uint32_t kph = 0;
  auto own_slot = [&]() -> uint32_t {
    const uint32_t sA = p.stage, phA = p.phase; pipe_adv<NS>(p);
    const uint32_t sB = p.stage, phB = p.phase; pipe_adv<NS>(p);
    mbar_wait_if(wi == 0, full + 8 * (wg ? sA : sB), wg ? phA : phB);
    mbar_wait(full + 8 * (wg ? sB : sA), wg ? phB : phA);
    mbar_arrive_if((threadIdx.x & 127) == 0, empty + 8 * (wg ? sA : sB));
    return wg ? sB : sA;
  };
  while (true) {
    const uint32_t it = __shfl_sync(0xffffffffu, next_item(), 0);
    const int type = (it >> 16) & 255, m = (it >> 8) & 255, k = it & 255;
    mbar_arrive_if(lane == 0, mempty + 8 * mp.stage);
    const uint32_t done = staged + 16 * wg + 8 * mp.stage;
    pipe_adv<2>(mp);
    if (type == T_END) break;
    if (type == T_P) {
      prep_body(k, pa);
      bar_sync(3 + wg, 128);
      mbar_arrive_if(lane == 0, done);
      continue;
    }
    if (type == T_L) {
      const int nr = sc.lrows[m], np = sc.ks[m];
      const uint32_t po = (lane >> 4) * 1024 + warp * 128 + ((((lane >> 1) & 7) ^ warp) << 4) + (lane & 1) * 8;
#pragma unroll 1
      for (int r = 0; r < nr; r++) {
        uint2 xw[1][5]; float s[20];
#pragma unroll
        for (int i = 0; i < 20; i++) s[i] = 0.f;
#pragma unroll 1
        for (int q0 = 0; q0 <= np; q0 += 4) {
          const uint32_t st = sb + p.stage * STQ;
          mbar_wait(full + 8 * p.stage, p.phase);
          if (q0 == 0) static_for<0, 5>([&](auto I) { xw[0][I.value] = lds64_i<I.value * 256>(st + warp * 1280 + lane * 8); });
#pragma unroll 1
          for (int q = q0 ? 0 : 1; q < min(4, np + 1 - q0); q++)
            static_for<0, 5>([&](auto I) {
              constexpr int i = I.value;
              const uint2 t = lds64_i<i * 2048>(st + q * 10240 + po);
              s[4 * i] += bf_lo(t.x); s[4 * i + 1] += bf_hi(t.x); s[4 * i + 2] += bf_lo(t.y); s[4 * i + 3] += bf_hi(t.y);
            });
          bar_sync(3 + wg, 128);
          mbar_arrive_if((threadIdx.x & 127) == 0, empty + 8 * p.stage);
          pipe_adv<NS>(p);
        }
        const int row = (m * 16 + k * nr + r) * 8 + warp;
#pragma unroll
        for (int i = 0; i < 5; i++) {
          bf16r2(s[4 * i], s[4 * i + 1]); bf16r2(s[4 * i + 2], s[4 * i + 3]);
          xw[0][i] = make_uint2(pack_bf16(bf_lo(xw[0][i].x) + s[4 * i], bf_hi(xw[0][i].x) + s[4 * i + 1]), pack_bf16(bf_lo(xw[0][i].y) + s[4 * i + 2], bf_hi(xw[0][i].y) + s[4 * i + 3]));
          *(uint2*)(a.xout + (size_t)row * cfg::DM + i * 128 + lane * 4) = xw[0][i];
        }
        ln_rows<1>(xw, row, lane, a.xn, nullptr);
      }
      __syncwarp();
      mbar_arrive_if(lane == 0, done);
      continue;
    }
    if (type >= T_OB) {
      const int nkb = 96 / sc.ks[m];
      if (type == T_OB) {
        float a0[96], a1[64];
        tr_mainloop<192, 128>(a0, a1, p, sb, full, empty, nkb, wg);
        while (p.stage != 2) { mbar_wait_if(wi == 0, full + 8 * p.stage, p.phase); mbar_arrive_if((threadIdx.x & 127) == 0, empty + 8 * p.stage); pipe_adv<NS>(p); }
        const uint32_t st = sb + own_slot() * STO;
        stage_tiles<192>(a0, st, wi, lane); stage_tiles<128>(a1, st + 24576, wi, lane);
      } else {
        float a0[64], a1[1];
        tr_mainloop<128, 0>(a0, a1, p, sb, full, empty, nkb, wg);
        stage_tiles<128>(a0, sb + own_slot() * STQ, wi, lane);
      }
      fence_proxy_async();
      __syncwarp();
      mbar_arrive_if(lane == 0, done);
      continue;
    }
    uint32_t qf[12][4];
    uint4* qp = a.qs + ((size_t)((m & 7) * 32 + k) * 12) * 256 + threadIdx.x;
    if (type != T_A) {
      float acc[96], a1[1];
      tr_mainloop<192, 0>(acc, a1, p, sb, full, empty, 10, wg);
#pragma unroll
      for (int i = 0; i < 12; i++) {
        qf[i][0] = pack_bf16(acc[8 * i], acc[8 * i + 1]); qf[i][1] = pack_bf16(acc[8 * i + 2], acc[8 * i + 3]);
        qf[i][2] = pack_bf16(acc[8 * i + 4], acc[8 * i + 5]); qf[i][3] = pack_bf16(acc[8 * i + 6], acc[8 * i + 7]);
      }
      if (type == T_Q) {
#pragma unroll
        for (int i = 0; i < 12; i++) qp[i * 256] = make_uint4(qf[i][0], qf[i][1], qf[i][2], qf[i][3]);
        __syncwarp();
        mbar_arrive_if(lane == 0, done);
        continue;
      }
    } else {
#pragma unroll
      for (int i = 0; i < 12; i++) { const uint4 v = __ldcg(qp + i * 256); qf[i][0] = v.x; qf[i][1] = v.y; qf[i][2] = v.z; qf[i][3] = v.w; }
    }
    const uint32_t ost = sb + OFF_K + wg * 2 * SEGB;
    const bool second = wi >= 2;
    uint32_t pf[5][4];
    {
      float sa[20], sb2[20];
      uint32_t kbase = ost, kslot = 0;
      if (type == T_A) { kslot = own_slot(); kbase = sb + kslot * STQ; } else mbar_wait(barK + 8 * wg, kph);
      kbase = (kbase & 0x3FFFF) >> 4;
      if (STAG && wg) bar_sync(1, 256);
      wgmma_fence();
#pragma unroll
      for (int i = 0; i < 12; i++) {
        wgmma_rs_n40<0>(sa, qf[i][0], qf[i][1], qf[i][2], qf[i][3], desc16<640, 128, 0>(kbase, i * 1280), i != 0);
        wgmma_rs_n40<0>(sb2, qf[i][0], qf[i][1], qf[i][2], qf[i][3], desc16<640, 128, 0>(kbase, SEGB + i * 1280), i != 0);
      }
      wgmma_commit();
      if (STAG && !wg) bar_arrive(1, 256);
      wgmma_wait<0>();
      mbar_arrive_if(type == T_A && (threadIdx.x & 127) == 0, empty + 8 * kslot);
      const float cs = 0.07216878364870322f * 1.4426950408889634f;
      const int r0 = 16 * (wi & 1) + g, r1 = r0 + 8;
      float m0 = -INFINITY, m1 = -INFINITY;
#pragma unroll
      for (int n = 0; n < 5; n++) {
#pragma unroll
        for (int e = 0; e < 2; e++) {
          const int key = 8 * n + 2 * q4 + e;
          float x = second ? sb2[4 * n + e] : sa[4 * n + e], y = second ? sb2[4 * n + 2 + e] : sa[4 * n + 2 + e];
          if (n < 4) { if (key > r0) x = -INFINITY; if (key > r1) y = -INFINITY; }
          sa[4 * n + e] = x; sa[4 * n + 2 + e] = y;
          m0 = fmaxf(m0, x); m1 = fmaxf(m1, y);
        }
      }
      m0 = fmaxf(fmaxf(m0, __shfl_xor_sync(0xffffffffu, m0, 1)), fmaxf(__shfl_xor_sync(0xffffffffu, m0, 2), __shfl_xor_sync(0xffffffffu, m0, 3)));
      m1 = fmaxf(fmaxf(m1, __shfl_xor_sync(0xffffffffu, m1, 1)), fmaxf(__shfl_xor_sync(0xffffffffu, m1, 2), __shfl_xor_sync(0xffffffffu, m1, 3)));
      m0 *= -cs; m1 *= -cs;
      float s0 = 0.f, s1 = 0.f;
#pragma unroll
      for (int n = 0; n < 5; n++) {
#pragma unroll
        for (int e = 0; e < 2; e++) {
          sa[4 * n + e] = ex2f(fmaf(sa[4 * n + e], cs, m0)); sa[4 * n + 2 + e] = ex2f(fmaf(sa[4 * n + 2 + e], cs, m1));
          s0 += sa[4 * n + e]; s1 += sa[4 * n + 2 + e];
        }
      }
      s0 = (s0 + __shfl_xor_sync(0xffffffffu, s0, 1)) + (__shfl_xor_sync(0xffffffffu, s0, 2) + __shfl_xor_sync(0xffffffffu, s0, 3));
      s1 = (s1 + __shfl_xor_sync(0xffffffffu, s1, 1)) + (__shfl_xor_sync(0xffffffffu, s1, 2) + __shfl_xor_sync(0xffffffffu, s1, 3));
      const float i0 = rcpf(s0), i1 = rcpf(s1);
#pragma unroll
      for (int n = 0; n < 5; n++) {
        const uint32_t x = pack_bf16(sa[4 * n] * i0, sa[4 * n + 1] * i0), y = pack_bf16(sa[4 * n + 2] * i1, sa[4 * n + 3] * i1);
        if (n < 4) {
          pf[n >> 1][2 * (n & 1)] = second ? 0u : x; pf[n >> 1][2 * (n & 1) + 1] = second ? 0u : y;
          pf[2 + (n >> 1)][2 * (n & 1)] = second ? x : 0u; pf[2 + (n >> 1)][2 * (n & 1) + 1] = second ? y : 0u;
        } else {
          pf[4][0] = second ? 0u : x; pf[4][1] = second ? 0u : y; pf[4][2] = second ? x : 0u; pf[4][3] = second ? y : 0u;
        }
      }
    }
    {
      float o[96];
#pragma unroll
      for (int i = 0; i < 5; i++) { PIN(pf[i][0]); PIN(pf[i][1]); PIN(pf[i][2]); PIN(pf[i][3]); }
      const uint32_t own = own_slot(), vbase = ((sb & 0x3FFFF) >> 4) + own * (STQ / 16);
      wgmma_fence();
#pragma unroll
      for (int i = 0; i < 5; i++)
        wgmma_rs_n192<1>(o, pf[i][0], pf[i][1], pf[i][2], pf[i][3], i < 4 ? desc16<128, 640, 0>(vbase, (i >> 1) * SEGB + (i & 1) * 256) : desc16<SEGB, 640, 0>(vbase, 512), i != 0);
      wgmma_commit();
      if (type == T_A) mbar_wait(barK + 8 * wg, kph);
      kph ^= 1;
      wgmma_wait<0>();
      mbar_arrive_if((threadIdx.x & 127) == 0, empty + 8 * own);
      stage_tiles<192>(o, ost, wi, lane);
      fence_proxy_async();
      __syncwarp();
      mbar_arrive_if(lane == 0, done);
    }
  }
}
namespace bf {
constexpr int NS = 4, STAGE = 16384 + 32768;
constexpr int PIECE = 20480;
constexpr int OFF_PHI = 0, OFF_V = 40960, OFF_KV = 65536;
constexpr int OFF_OST = 5 * PIECE;
constexpr int OFF_WOT = 6 * PIECE;
constexpr int OFF_BAR = OFF_WOT + 102400;
constexpr int SMEM = OFF_BAR + 256;
static_assert(NS * STAGE <= OFF_BAR && SMEM <= 232448, "smem");
constexpr int KVACC = 32 * 5 * 1024;
struct Args {
  const unsigned char *wb, *wot;
  unsigned char *kvacc, *o2;
  const bf16* xin;
  bf16* xout;
  unsigned* go;
  const void* prep;
  const bf16 *pf0, *pf1;
  int pfn, pfns, pfwait;
  int tl;
};
}
__device__ __forceinline__ void hedgehog_features(float (&x)[2][5], uint32_t (&w)[2][5]) {
  const float L = 1.4426950408889634f;
  float mx[2], mn[2], sp[2], sn[2], pos[2][5], neg[2][5];
#pragma unroll
  for (int r = 0; r < 2; r++) {
    mx[r] = fmaxf(fmaxf(fmaxf(x[r][0], x[r][1]), fmaxf(x[r][2], x[r][3])), x[r][4]);
    mn[r] = fminf(fminf(fminf(x[r][0], x[r][1]), fminf(x[r][2], x[r][3])), x[r][4]);
  }
#pragma unroll
  for (int o = 1; o < 4; o <<= 1)
#pragma unroll
    for (int r = 0; r < 2; r++) {
      const uint32_t t = __shfl_xor_sync(0xffffffffu, __byte_perm(__float_as_uint(mn[r]), __float_as_uint(mx[r]), 0x7632), o);
      mx[r] = fmaxf(mx[r], bf_hi(t)); mn[r] = fminf(mn[r], bf_lo(t));
    }
#pragma unroll
  for (int r = 0; r < 2; r++) {
#pragma unroll
    for (int i = 0; i < 5; i++) { pos[r][i] = ex2f((x[r][i] - mx[r]) * L); neg[r][i] = ex2f((mn[r] - x[r][i]) * L); }
    sp[r] = ((pos[r][0] + pos[r][1]) + (pos[r][2] + pos[r][3])) + pos[r][4];
    sn[r] = ((neg[r][0] + neg[r][1]) + (neg[r][2] + neg[r][3])) + neg[r][4];
  }
#pragma unroll
  for (int o = 1; o < 4; o <<= 1)
#pragma unroll
    for (int r = 0; r < 2; r++) { sp[r] += __shfl_xor_sync(0xffffffffu, sp[r], o); sn[r] += __shfl_xor_sync(0xffffffffu, sn[r], o); }
#pragma unroll
  for (int r = 0; r < 2; r++) {
    const float ip = rcpf(sp[r]), in_ = rcpf(sn[r]);
    w[r][0] = pack_bf16(pos[r][0] * ip, pos[r][1] * ip); w[r][1] = pack_bf16(pos[r][2] * ip, pos[r][3] * ip);
    w[r][2] = pack_bf16(neg[r][0] * in_, neg[r][1] * in_); w[r][3] = pack_bf16(neg[r][2] * in_, neg[r][3] * in_);
    w[r][4] = pack_bf16(pos[r][4] * ip, neg[r][4] * in_);
  }
}
__device__ __forceinline__ void bulk_g2s_mc(uint32_t dst, const void* src, uint32_t bytes, uint32_t mb) {
  asm volatile("cp.async.bulk.shared::cluster.global.mbarrier::complete_tx::bytes.multicast::cluster [%0], [%1], %2, [%3], %4;"
               :: "r"(dst), "l"(src), "r"(bytes), "r"(mb), "h"((unsigned short)3) : "memory");
}
__device__ __forceinline__ void mbar_arrive_remote_if(bool c, uint32_t b) {
  asm volatile("{\n.reg .pred p;\nsetp.ne.u32 p, %1, 0;\n@p mbarrier.arrive.shared::cluster.b64 _, [%0];\n}" :: "r"(b), "r"((uint32_t)c) : "memory");
}

__global__ void __cluster_dims__(2, 1, 1) __launch_bounds__(384, 1) blayer_kernel(const __grid_constant__ CUtensorMap tmA, const __grid_constant__ bf::Args a) {
  using namespace bf;
  [[maybe_unused]] const int tl = a.tl;
  extern __shared__ __align__(1024) unsigned char smem_raw[];
  const uint32_t sb = smem_u32(smem_raw);
  const int warp = __shfl_sync(0xffffffffu, (int)threadIdx.x >> 5, 0), lane = threadIdx.x & 31;
  const uint32_t full = sb + OFF_BAR, empty = full + 8 * NS, full2 = empty + 8 * NS, empty2 = full2 + 64, barW = empty2 + 16, drained = barW + 8, staged = drained + 8, freeb = staged + 8;
  const int rank = blockIdx.x & 1, u = (blockIdx.x >> 1) & 7, mp = blockIdx.x >> 4;
  const int m = 2 * mp + rank;
  const int m2 = 2 * mp + (u & 1), ns = (u & ~1) + rank;
  const uint32_t dpeer = mapa_u32(sb, rank ^ 1) - sb;
  unsigned* cntO = (unsigned*)(a.kvacc + KVACC);
  if (threadIdx.x == 0) {
    for (int i = 0; i < NS; i++) { mbar_init(full + 8 * i, 1); mbar_init(empty + 8 * i, 4); }
    for (int i = 0; i < 8; i++) mbar_init(full2 + 8 * i, 1);
    mbar_init(empty2, 2); mbar_init(empty2 + 8, 2);
    mbar_init(barW, 1); mbar_init(drained, 1); mbar_init(staged, 8); mbar_init(freeb, 2);
    asm volatile("fence.mbarrier_init.release.cluster;" ::: "memory");
  }
  __syncthreads();
  asm volatile("barrier.cluster.arrive.relaxed.aligned; barrier.cluster.wait.aligned;" ::: "memory");
  if (warp >= 8) {
    asm volatile("setmaxnreg.dec.sync.aligned.u32 40;");
    if (warp == 8) { if (elect_one()) {
      const unsigned char* wsrc = a.wb + (size_t)u * 327680 + rank * 16384;
      if (a.prep) wait_ge(a.prep, 64);
      fence_proxy_async_global();
      for (int kb = 0; kb < NS; kb++) {
        mbar_expect_tx(full + 8 * kb, STAGE);
        bulk_g2s_mc(sb + kb * STAGE + 16384 + rank * 16384, wsrc + kb * 32768, 16384, full + 8 * kb);
      }
      asm volatile("griddepcontrol.wait;" ::: "memory");
      TL_BEGIN0(tl);
      LITE(blockIdx.x == 0, (tl >= 12) * 4 + 2);
      if (blockIdx.x == 0) *a.go = 0;
      for (int kb = 0; kb < NS; kb++) tma_load_2d(sb + kb * STAGE, &tmA, kb * 64, m * 128, full + 8 * kb);
      if (m == 0) prefetch_l2(a.kvacc + u * (KVACC / 8), KVACC / 8);
#pragma unroll 1
      for (int kb = NS; kb < 10; kb++) {
        const uint32_t s = kb & 3, st = sb + s * STAGE, fb = full + 8 * s;
        mbar_wait(empty + 8 * s, ((kb >> 2) - 1) & 1);
        mbar_expect_tx(fb, STAGE);
        tma_load_2d(st, &tmA, kb * 64, m * 128, fb);
        bulk_g2s_mc(st + 16384 + rank * 16384, wsrc + kb * 32768, 16384, fb);
      }
      for (int i = 0; i < 6; i++) mbar_expect_tx(full2 + 8 * i, PIECE);
      mbar_wait(drained, 0);
      mbar_expect_tx(barW, 102400);
      bulk_g2s(sb + OFF_WOT, a.wot + (size_t)ns * 102400, 102400, barW);
      mbar_wait(staged, 0);
      bulk_s2g(a.o2 + (size_t)(m * 8 + u) * PIECE, sb + OFF_OST, PIECE);
      bulk_commit();
      bulk_wait<0>();
      mbar_arrive(freeb); mbar_arrive_remote_if(true, freeb + dpeer);
      red_release_inc(cntO + m);
      wait_ge(cntO + m2, 8, 20);
      mbar_wait(freeb, 0);
      fence_proxy_async_global();
      const unsigned char* osrc = a.o2 + (size_t)m2 * 8 * PIECE;
      for (int i = 0; i < 6; i++) bulk_g2s_mc(sb + i * PIECE + rank * (PIECE / 2), osrc + i * PIECE + rank * (PIECE / 2), PIECE / 2, full2 + 8 * i);
      for (int i = 0; i < 2; i++) {
        mbar_wait(empty2 + 8 * i, 0);
        mbar_expect_tx(full2 + 8 * (6 + i), PIECE);
        bulk_g2s(sb + i * PIECE, osrc + (6 + i) * PIECE, PIECE, full2 + 8 * (6 + i));
      }
    } } else if (warp == 9 && a.pf0) { if (elect_one()) {
      if (a.pfwait) asm volatile("griddepcontrol.wait;" ::: "memory");
      constexpr uint32_t CH = 2048;
      for (int i = 0; i < a.pfn; i++) {
        prefetch_l2((const unsigned char*)a.pf0 + (i * 128 + blockIdx.x) * CH, CH); prefetch_l2((const unsigned char*)a.pf1 + (i * 128 + blockIdx.x) * CH, CH);
        __nanosleep(a.pfns);
      }
    } }
    return;
  }
  asm volatile("setmaxnreg.inc.sync.aligned.u32 232;");
  const int wg = warp >> 2, wi = warp & 3;
  const int q4 = lane & 3;
  const bool lead = (threadIdx.x & 127) == 0;
  const uint32_t s16 = (sb & 0x3FFFF) >> 4;
  float acc[128];
  {
#pragma unroll 1
    for (int kb = 0; kb < 10; kb++) {
      const uint32_t s = kb & 3, st = s16 + s * (STAGE / 16);
      mbar_wait(full + 8 * s, (kb >> 2) & 1);
      wgmma_fence();
#pragma unroll
      for (int kk = 0; kk < 4; kk++) wgmma_n256<0, 1>(acc, desc16<16, 1024, 1>(st + wg * 512, kk * 32), desc16<4096, 128, 0>(st, 16384 + kk * 8192), (kb | kk) != 0);
      wgmma_commit();
      if (kb > 0 && kb < 7) { wgmma_wait<1>(); const uint32_t e = empty + 8 * ((kb - 1) & 3); mbar_arrive_if(lead, e); mbar_arrive_remote_if(lead, e + dpeer); }
    }
    wgmma_wait<0>();
    bar_sync(1, 256);
    mbar_arrive_if(threadIdx.x == 0, drained);
  }
  TL2((tl >= 12 ? 128 : 0) + 32 + 0);
  const uint32_t srow = (wg * 64 + wi * 16 + (lane & 15)) * 16 + (lane >> 4) * 2048;
  auto features = [&](auto T0, auto HH, uint32_t (&w)[2][5]) {
    constexpr int t = T0.value + 5 * (HH.value >> 1), o = (HH.value & 1) ? 3 : 0, e = HH.value & 1;
    float x[2][5];
#pragma unroll
    for (int r = 0; r < 2; r++) {
      x[r][0] = acc[4 * (t + o) + 2 * r]; x[r][1] = acc[4 * (t + o) + 2 * r + 1]; x[r][2] = acc[4 * (t + o + 1) + 2 * r]; x[r][3] = acc[4 * (t + o + 1) + 2 * r + 1];
      bf16r2(x[r][0], x[r][1]); bf16r2(x[r][2], x[r][3]);
    }
    x[0][4] = acc[4 * (t + 2) + e]; x[1][4] = acc[4 * (t + 2) + 2 + e];
    bf16r2(x[0][4], x[1][4]);
    hedgehog_features(x, w);
  };
  static_for<0, 4>([&](auto HH) {
    constexpr int hh = HH.value, t = 20 + 3 * hh;
    const uint32_t one = q4 == ((hh & 1) ? 0 : 2) ? 0x3f80u : 0u;
    const uint32_t va = sb + OFF_V + hh * 6144 + srow;
    stsm_x4(va, pack_bf16(acc[4 * t], acc[4 * t + 1]), pack_bf16(acc[4 * t + 2], acc[4 * t + 3]), pack_bf16(acc[4 * t + 4], acc[4 * t + 5]), pack_bf16(acc[4 * t + 6], acc[4 * t + 7]));
    const bool pad = (q4 >= 2) != (hh & 1);
    stsm_x2(va + 4096, pad ? one : pack_bf16(acc[4 * t + 8], acc[4 * t + 9]), pad ? one : pack_bf16(acc[4 * t + 10], acc[4 * t + 11]));
    uint32_t w[2][5];
    features(IC<10>{}, HH, w);
    const uint32_t pa = sb + OFF_PHI + hh * 10240 + srow;
    stsm_x4(pa, w[0][0], w[1][0], w[0][1], w[1][1]);
    stsm_x4(pa + 4096, w[0][2], w[1][2], w[0][3], w[1][3]);
    stsm_x2(pa + 8192, w[0][4], w[1][4]);
  });
  fence_proxy_async();
  bar_sync(1, 256);
  TL2((tl >= 12 ? 128 : 0) + 32 + 1);
  {
    float d0[12], d1[12];
    const uint32_t pa = s16 + wg * 1280, pv = s16 + wg * 768;
    wgmma_fence();
#pragma unroll
    for (int k = 0; k < 8; k++) {
      wgmma_n24<1, 1>(d0, desc16<128, 2048, 0>(pa, OFF_PHI + k * 256), desc16<128, 2048, 0>(pv, OFF_V + k * 256), k != 0);
      wgmma_n24<1, 1>(d1, desc16<128, 2048, 0>(pa, OFF_PHI + 10240 + k * 256), desc16<128, 2048, 0>(pv, OFF_V + 6144 + k * 256), k != 0);
    }
    wgmma_commit();
    wgmma_wait<0>();
    unsigned char* dst = a.kvacc + ((u * 4 + wg * 2) * 5 + 2 * wi) * 1024 + lane * 16;
    auto red4 = [&](bool on, unsigned char* p, float x, float y, float z) {
      asm volatile("{\n.reg .pred p;\nsetp.ne.u32 p, %4, 0;\n@p red.relaxed.gpu.global.add.v4.f32 [%0], {%1,%2,%3,%5};\n}" :: "l"(p), "f"(x), "f"(y), "f"(z), "r"((uint32_t)on), "f"(1.f) : "memory");
    };
    red4(wi < 3, dst, d0[0], d0[1], d0[4]); red4(wi < 3, dst + 512, d0[5], d0[8], d0[9]);
    red4(wi < 3, dst + 5120, d1[0], d1[1], d1[4]); red4(wi < 3, dst + 5632, d1[5], d1[8], d1[9]);
    red4(wi < 2, dst + 1024, d0[2], d0[3], d0[6]); red4(wi < 2, dst + 1536, d0[7], d0[10], d0[11]);
    red4(wi < 2, dst + 6144, d1[2], d1[3], d1[6]); red4(wi < 2, dst + 6656, d1[7], d1[10], d1[11]);
  }
  TL2((tl >= 12 ? 128 : 0) + 32 + 2);
  uint32_t qf[4][2][5];
  static_for<0, 4>([&](auto HH) { features(IC<0>{}, HH, qf[HH.value]); });
  uint4 xr[5];
#pragma unroll
  for (int i = 0; i < 5; i++) {
    const int c = lane + 32 * i;
    xr[i] = __ldcg((const uint4*)(a.xin + (size_t)(m2 * 128 + wg * 64 + wi * 16 + c / 10) * cfg::DM + ns * 80 + (c % 10) * 8));
  }
  {
    const unsigned char* src = a.kvacc + (u * 20 + warp) * 1024 + lane * 16;
    uint4 v[6];
    int spin = 0;
    while (true) {
      v[0] = ld_relaxed_v4_i<0>(src); v[1] = ld_relaxed_v4_i<512>(src); v[2] = ld_relaxed_v4_i<8192>(src); v[3] = ld_relaxed_v4_i<8704>(src);
      v[4] = ld_relaxed_v4_i<0>(src + (wg ? 0 : 16384)); v[5] = ld_relaxed_v4_i<512>(src + (wg ? 0 : 16384));
      const uint32_t c = (v[0].w & v[1].w & v[2].w) & (v[3].w & v[4].w & v[5].w);
      if (!__any_sync(0xffffffffu, (c & 0x41800000u) != 0x41800000u) || ++spin >= SPIN_LIMIT) break;
      __nanosleep(100);
    }
    const uint32_t kd = sb + OFF_KV + warp * 384 + lane * 4;
#pragma unroll
    for (int i = 0; i < 3; i++)
      if (i < 2 || wg == 0) {
        sts32(kd + i * 3072, pack_bf16(__uint_as_float(v[2 * i].x), __uint_as_float(v[2 * i].y)));
        sts32(kd + i * 3072 + 128, pack_bf16(__uint_as_float(v[2 * i].z), __uint_as_float(v[2 * i + 1].x)));
        sts32(kd + i * 3072 + 256, pack_bf16(__uint_as_float(v[2 * i + 1].y), __uint_as_float(v[2 * i + 1].z)));
      }
  }
  fence_proxy_async();
  bar_sync(1, 256);
  TL2((tl >= 12 ? 128 : 0) + 32 + 3);
  {
    float d[4][12];
    uint32_t zero = 0; PIN(zero);
#pragma unroll
    for (int hh = 0; hh < 4; hh++)
#pragma unroll
      for (int i = 0; i < 5; i++) { PIN(qf[hh][0][i]); PIN(qf[hh][1][i]); }
    wgmma_fence();
#pragma unroll
    for (int hh = 0; hh < 4; hh++) {
      const uint32_t kb = OFF_KV + hh * 1920;
      wgmma_rs_n24<1>(d[hh], qf[hh][0][0], qf[hh][1][0], qf[hh][0][1], qf[hh][1][1], desc16<384, 128, 0>(s16, kb), 0);
      wgmma_rs_n24<1>(d[hh], qf[hh][0][2], qf[hh][1][2], qf[hh][0][3], qf[hh][1][3], desc16<384, 128, 0>(s16, kb + 768), 1);
      wgmma_rs_n24<1>(d[hh], qf[hh][0][4], qf[hh][1][4], zero, zero, desc16<0, 128, 0>(s16, kb + 1536), 1);
    }
    wgmma_commit();
    wgmma_wait<0>();
    uint32_t ow[4][6];
#pragma unroll
    for (int hh = 0; hh < 4; hh++) {
      const int zl = (lane & ~3) | ((hh & 1) ? 0 : 2);
      const float da = bf16r(bf16r(__shfl_sync(0xffffffffu, d[hh][8], zl)) + 1e-6f), db = bf16r(bf16r(__shfl_sync(0xffffffffu, d[hh][10], zl)) + 1e-6f);
#pragma unroll
      for (int n = 0; n < 3; n++) {
        bf16r2(d[hh][4 * n], d[hh][4 * n + 1]); bf16r2(d[hh][4 * n + 2], d[hh][4 * n + 3]);
        ow[hh][2 * n] = pack_bf16(__fdividef(d[hh][4 * n], da), __fdividef(d[hh][4 * n + 1], da));
        ow[hh][2 * n + 1] = pack_bf16(__fdividef(d[hh][4 * n + 2], db), __fdividef(d[hh][4 * n + 3], db));
      }
    }
#pragma unroll
    for (int p = 0; p < 2; p++) {
      const uint32_t oa = sb + OFF_OST + p * 10240 + srow;
      stsm_x4(oa, ow[2 * p][0], ow[2 * p][1], ow[2 * p][2], ow[2 * p][3]);
      stsm_x2(oa + 4096, q4 < 2 ? ow[2 * p][4] : ow[2 * p + 1][4], q4 < 2 ? ow[2 * p][5] : ow[2 * p + 1][5]);
      stsm_x4(oa + 6144, ow[2 * p + 1][0], ow[2 * p + 1][1], ow[2 * p + 1][2], ow[2 * p + 1][3]);
    }
    fence_proxy_async();
    __syncwarp();
    mbar_arrive_if(lane == 0, staged);
  }
  TL2((tl >= 12 ? 128 : 0) + 32 + 4);
  float c2[40];
  mbar_wait(barW, 0);
#pragma unroll 1
  for (int i = 0; i < 8; i++) {
    mbar_wait(full2 + 8 * i, 0);
    const uint32_t st = s16 + (i < 6 ? i : i - 6) * (PIECE / 16) + wg * 64, wo = s16 + i * 800;
    wgmma_fence();
#pragma unroll
    for (int kk = 0; kk < 5; kk++) wgmma_n80<0, 1>(c2, desc16<2048, 128, 0>(st, kk * 4096), desc16<1280, 128, 0>(wo, OFF_WOT + kk * 2560), (i | kk) != 0);
    wgmma_commit();
    if (i == 1 || i == 2) { wgmma_wait<1>(); mbar_arrive_if(lead, empty2 + 8 * (i - 1)); }
  }
  wgmma_wait<0>();
  TL2((tl >= 12 ? 128 : 0) + 32 + 5);
  {
    bar_sync(1, 256);
    const uint32_t ost = sb + 2 * PIECE + warp * 3072;
#pragma unroll
    for (int v = 0; v < 10; v += 2)
      stsm_x4(ost + (lane & 15) * 176 + (v + (lane >> 4)) * 16, pack_bf16(c2[4 * v], c2[4 * v + 1]), pack_bf16(c2[4 * v + 2], c2[4 * v + 3]),
              pack_bf16(c2[4 * v + 4], c2[4 * v + 5]), pack_bf16(c2[4 * v + 6], c2[4 * v + 7]));
    __syncwarp();
#pragma unroll
    for (int i = 0; i < 5; i++) {
      const int c = lane + 32 * i, row = c / 10, chunk = c % 10;
      const uint4 y = lds128(ost + row * 176 + chunk * 16);
      const size_t off = (size_t)(m2 * 128 + wg * 64 + wi * 16 + row) * cfg::DM + ns * 80 + chunk * 8;
      const uint4 x = xr[i];
      *(uint4*)(a.xout + off) = make_uint4(pack_bf16(bf_lo(x.x) + bf_lo(y.x), bf_hi(x.x) + bf_hi(y.x)), pack_bf16(bf_lo(x.y) + bf_lo(y.y), bf_hi(x.y) + bf_hi(y.y)),
                                           pack_bf16(bf_lo(x.z) + bf_lo(y.z), bf_hi(x.z) + bf_hi(y.z)), pack_bf16(bf_lo(x.w) + bf_lo(y.w), bf_hi(x.w) + bf_hi(y.w)));
    }
  }
  TL_END(tl);
}
__device__ __align__(32768) unsigned char g_arena[AR_SIZE];
__device__ unsigned g_go[32];
__device__ __align__(1024) uint2 g_xh[2048 * 160];
__device__ __align__(1024) unsigned char g_k[64 * 96 * 5120], g_v[64 * 96 * 5120];
__device__ __align__(1024) bf16 g_o[2048 * 6144];
__device__ __align__(1024) uint4 g_qs[8 * 32 * 12 * 256];
__device__ __align__(1024) bf16 g_xn[2048 * 640], g_xn2[2048 * 640], g_xa[2048 * 640], g_xb[2048 * 640];
__device__ __align__(1024) bf16 g_part[24 * 2048 * 640];
__device__ __align__(1024) bf16 g_wb[2048 * 640], g_wot[640 * 640], g_pq[2048 * 640];
__device__ __align__(1024) float g_kvacc[bf::KVACC / 4 + 64];

typedef CUresult (*EncodeFn)(CUtensorMap*, CUtensorMapDataType, cuuint32_t, void*, const cuuint64_t*, const cuuint64_t*, const cuuint32_t*,
                             const cuuint32_t*, CUtensorMapInterleave, CUtensorMapSwizzle, CUtensorMapL2promotion, CUtensorMapFloatOOBfill);
static EncodeFn g_encode = nullptr;
static CUtensorMap make_map(const void* p, uint64_t cols, uint64_t rows, uint32_t bc, uint32_t br, bool swz = true) {
  CUtensorMap m;
  cuuint64_t dims[2] = {cols, rows}, strides[1] = {cols * 2};
  cuuint32_t box[2] = {bc, br}, es[2] = {1, 1};
  g_encode(&m, CU_TENSOR_MAP_DATA_TYPE_BFLOAT16, 2, const_cast<void*>(p), dims, strides, box, es, CU_TENSOR_MAP_INTERLEAVE_NONE,
           swz ? CU_TENSOR_MAP_SWIZZLE_128B : CU_TENSOR_MAP_SWIZZLE_NONE, CU_TENSOR_MAP_L2_PROMOTION_L2_256B, CU_TENSOR_MAP_FLOAT_OOB_FILL_NONE);
  return m;
}
static CUtensorMap make_map3(const void* p, uint64_t cols, uint64_t rows, uint32_t nb) {
  CUtensorMap m;
  cuuint64_t dims[3] = {64, rows, cols / 64}, strides[2] = {cols * 2, 128};
  cuuint32_t box[3] = {64, 64, nb}, es[3] = {1, 1, 1};
  g_encode(&m, CU_TENSOR_MAP_DATA_TYPE_BFLOAT16, 3, const_cast<void*>(p), dims, strides, box, es, CU_TENSOR_MAP_INTERLEAVE_NONE,
           CU_TENSOR_MAP_SWIZZLE_128B, CU_TENSOR_MAP_L2_PROMOTION_L2_256B, CU_TENSOR_MAP_FLOAT_OOB_FILL_NONE);
  return m;
}
template <class T> static T* sym(const T& s) { void* p = nullptr; cudaGetSymbolAddress(&p, s); return (T*)p; }

struct Ptrs {
  unsigned char *arena, *k, *v; bf16 *o, *xn, *xa, *xb, *wb, *wot, *pq; float *part, *kvacc; uint2* xh; uint4* qs; bf16* xn2; unsigned* go;
};

static tr::Sched make_sched(int layer, const char* str, const int* ks, const int* lr) {
  using namespace tr;
  Sched s = {};
  int n = 0;
  for (int b = 0; b < 16; b++) { s.ks[b] = (uint8_t)abs(ks[b]); s.wide[b] = ks[b] > 0; s.lrows[b] = (uint8_t)lr[b]; }
  for (const char* p = str; *p;) {
    if (*p == ' ') { p++; continue; }
    const bool late = *p < 'a';
    const char c = *p++ | 32;
    char* e;
    const int b = (int)strtol(p, &e, 10); p = e;
    int first = 0, cnt = c == 'o' ? s.ks[b] * (s.wide[b] ? 2 : 5) : (c == 'l' ? 16 / lr[b] : 32);
    if (*p == '.') { first = (int)strtol(p + 1, &e, 10); cnt = (int)strtol(e + 1, &e, 10); p = e; }
    const int type = c == 'a' ? T_QA : (c == 'q' ? T_Q : (c == 't' ? T_A : (c == 'l' ? T_L : (c == 'p' ? T_P : (s.wide[b] ? T_OB : T_OS)))));
    if (type == T_P && layer > 0) continue;
    for (int i = 0; i < cnt && n < MAXITEMS - 1; i++) s.item[n++] = (uint16_t)((late << 14) | (type << 11) | (b << 7) | (first + i));
  }
  s.n = n; s.item[n] = T_END << 11;
  return s;
}
static tr::Sched sched_of(int layer) {
  const char* str = layer == 0
      ? "q13 q14 q12.0.8 a0.0.8 q12.8.24 q15 a0.8.24 a1 p0.0.16 a2 p0.16.16 o0 o1 a3.0.16 o2 a3.16.16 a4.0.16 o3 a4.16.16 a5.0.24 o4 a5.24.8 a6.0.20 l0 a6.20.12 o5 "
        "a7 o6 l2 a8.0.24 o7 l1 a8.24.8 a9 o8 l3 a10 l4 O9 a11 t12 l5 l6 l7 O10 O11 O12 t13 T14 t15 O13 O14 L8 O15 L10 L9 l11 l13 l12 l15 l14"
      : "q12 q13 q11 q14.0.20 a0 q14.20.12 q15 a1 o0 o1 a2 o2 a3 a4 o3 a5 o4 a6 o5 l0 l1 a7 o6 a8.0.20 l2 a8.20.12 o7 a9 o8 a10 l3 l4 O9 t11 O10 t12 l5 l7 L6 "
        "O11 O12 t13 t14 T15 O13 l10 O14 L8 o15 l13 l15 l9 L12 l14 L11";
  const int ks0[2][16] = {{2, 2, 2, 3, 2, 2, 2, 3, 2, 2, 3, 3, 3, -4, -8, -8}, {2, 2, 2, 2, 2, 2, 2, 2, 2, 3, 3, 3, 3, -4, -6, -12}};
  const int lr0[2][16] = {{4, 4, 4, 4, 4, 4, 4, 4, 2, 4, 1, 1, 1, 1, 1, 1}, {4, 4, 4, 4, 4, 4, 4, 1, 1, 4, 2, 1, 2, 1, 1, 1}};
  int ks[16], lr[16];
  for (int b = 0; b < 16; b++) { ks[b] = ks0[layer][b]; lr[b] = lr0[layer][b]; }
#ifdef TUNE
  const bool mine = !getenv("ONLY") || atoi(getenv("ONLY")) == layer;
  if (mine && getenv("SCHED")) str = getenv("SCHED");
  if (const char* p = getenv(layer ? "S1" : "S0")) {
    char* e;
    for (int b = 0; b < 16; b++) { ks[b] = (int)strtol(p, &e, 10); p = e; }
    for (int b = 0; b < 16; b++) { lr[b] = (int)strtol(p, &e, 10); p = e; }
    str = p;
  }
  if (const char* p = mine ? getenv("KS") : nullptr) for (int b = 0; b < 16; b++) { char* e; ks[b] = (int)strtol(p, &e, 10); p = e; }
  if (const char* p = mine ? getenv("LR") : nullptr) for (int b = 0; b < 16; b++) { char* e; lr[b] = (int)strtol(p, &e, 10); p = e; }
#endif
  return make_sched(layer, str, ks, lr);
}
#ifndef TRAIL_GRID
#define TRAIL_GRID 132
#endif
#ifndef PDL_LN
#define PDL_LN 0
#endif
#ifndef PDL_CH
#define PDL_CH 1
#endif
#ifndef PDL_B
#define PDL_B 1
#endif
#ifndef PF_A
#define PF_A 1
#endif
#ifndef PF_B
#define PF_B 1
#endif
extern "C" void kernel_launch(void* const* d_in, const int* in_sizes, int n_in, void* d_out, int out_size) {
  const bf16* x = (const bf16*)d_in[0];
  const bf16* mem0 = (const bf16*)d_in[1];
  const bf16 *Wq = (const bf16*)d_in[2], *Wk = (const bf16*)d_in[3], *Wv = (const bf16*)d_in[4], *Wo = (const bf16*)d_in[5];
  const bf16 *wqkv = (const bf16*)d_in[8], *wphi = (const bf16*)d_in[9], *wo = (const bf16*)d_in[10];
  bf16* out = (bf16*)d_out;
  static Ptrs P; static bool init = false;
  if (!init) {
    void* fn = nullptr; cudaDriverEntryPointQueryResult qr;
    cudaGetDriverEntryPoint("cuTensorMapEncodeTiled", &fn, cudaEnableDefault, &qr);
    g_encode = (EncodeFn)fn;
    void* p;
    cudaGetSymbolAddress(&p, g_arena); P.arena = (unsigned char*)p;
    cudaGetSymbolAddress(&p, g_k); P.k = (unsigned char*)p;   cudaGetSymbolAddress(&p, g_v); P.v = (unsigned char*)p;
    cudaGetSymbolAddress(&p, g_o); P.o = (bf16*)p;
    cudaGetSymbolAddress(&p, g_xn); P.xn = (bf16*)p;
    cudaGetSymbolAddress(&p, g_xa); P.xa = (bf16*)p;   cudaGetSymbolAddress(&p, g_xb); P.xb = (bf16*)p;
    cudaGetSymbolAddress(&p, g_wb); P.wb = (bf16*)p;   cudaGetSymbolAddress(&p, g_wot); P.wot = (bf16*)p;
    cudaGetSymbolAddress(&p, g_pq); P.pq = (bf16*)p;   cudaGetSymbolAddress(&p, g_part); P.part = (float*)p;
    cudaGetSymbolAddress(&p, g_kvacc); P.kvacc = (float*)p;
    cudaGetSymbolAddress(&p, g_xh); P.xh = (uint2*)p;
    cudaGetSymbolAddress(&p, g_go); P.go = (unsigned*)p;
    cudaGetSymbolAddress(&p, g_qs); P.qs = (uint4*)p;
    cudaGetSymbolAddress(&p, g_xn2); P.xn2 = (bf16*)p;
    cudaFuncSetAttribute(chain_kernel, cudaFuncAttributeMaxDynamicSharedMemorySize, ch::SMEM);
    cudaFuncSetAttribute(trail_kernel, cudaFuncAttributeMaxDynamicSharedMemorySize, tr::SMEM);
    cudaFuncSetAttribute(blayer_kernel, cudaFuncAttributeMaxDynamicSharedMemorySize, bf::SMEM);
    init = true;
  }
  const CUtensorMap tmXn = make_map(P.xn, 640, 2048, 64, 128), tmXn2 = make_map(P.xn2, 640, 2048, 64, 128);
  const CUtensorMap tmWq = make_map3(Wq, 6144, 640, 3);
  const CUtensorMap tmCq = make_map(Wq, 6144, 640, 64, 160), tmCk = make_map(Wk, 6144, 640, 64, 160), tmCv = make_map(Wv, 6144, 640, 64, 160), tmCo = make_map(Wo, 640, 6144, 224, 64, false);
  const CUtensorMap tmWo5 = make_map3(Wo, 640, 6144, 5), tmWo2 = make_map3(Wo, 640, 6144, 2);

  CUtensorMap tmP;
  {
    cuuint64_t dims[3] = {256, 8, 24 * 320}, strides[2] = {1024, 8192};
    cuuint32_t box[3] = {256, 1, 10}, es[3] = {1, 1, 1};
    g_encode(&tmP, CU_TENSOR_MAP_DATA_TYPE_UINT32, 3, P.part, dims, strides, box, es, CU_TENSOR_MAP_INTERLEAVE_NONE, CU_TENSOR_MAP_SWIZZLE_NONE,
             CU_TENSOR_MAP_L2_PROMOTION_NONE, CU_TENSOR_MAP_FLOAT_OOB_FILL_NONE);
  }
  ChainArgs ca;
  ca.xh = P.xh; ca.mem0 = mem0; ca.kg = P.k; ca.vg = P.v;
  ca.arena = P.arena; ca.dbg = nullptr; ca.go = P.go; ca.delay = POLL_DELAY; ca.margin = 150; ca.pubrel = 1;
#ifdef TUNE
  if (getenv("PR")) ca.pubrel = atoi(getenv("PR"));
  if (getenv("MG")) ca.margin = atoi(getenv("MG"));
  if (getenv("PD")) ca.delay = atoi(getenv("PD"));
#endif
  ca.tl = 0;
  uint4* zar = (uint4*)P.arena; const int nzar = AR_SIZE / 16;
  uint4* zkv = (uint4*)P.kvacc; const int nzkv = (bf::KVACC / 4 + 64) / 4;

  const PrepArgs pa{wqkv, wphi, wo, (unsigned char*)P.wb, (unsigned char*)P.wot};
  const bf16* xcur = x;
  cudaLaunchAttribute at[1];
  at[0].id = cudaLaunchAttributeProgrammaticStreamSerialization; at[0].val.programmaticStreamSerializationAllowed = 1;
  auto cfgof = [&](int grid, int block, int smem, bool pdl) {
    cudaLaunchConfig_t lc = {};
    lc.gridDim = dim3(grid); lc.blockDim = dim3(block); lc.dynamicSmemBytes = smem; lc.stream = cudaStreamPerThread;
    lc.attrs = at; lc.numAttrs = pdl ? 1 : 0;
    return lc;
  };
  int nlayers = 2;
#ifdef TUNE
  if (getenv("LAYERS")) nlayers = atoi(getenv("LAYERS"));
#endif
  for (int layer = 0; layer < nlayers; layer++) {
    const int tl = layer * 12;
    cudaLaunchConfig_t lc = cfgof(256, 256, 0, layer > 0 && PDL_LN);
    cudaLaunchKernelEx(&lc, ln_kernel, xcur, P.xn, P.xh, zar, nzar, zkv, nzkv, Wk, Wv, layer == 0 ? PF_A : 0, tl + 0);
    ca.tl = tl + 2; ca.dry = 1;
#ifdef TUNE
    if (getenv("DRY")) ca.dry = (atoi(getenv("DRY")) >> layer) & 1;
#endif
    lc = cfgof(96, 384, ch::SMEM, PDL_CH);
    cudaLaunchKernelEx(&lc, chain_kernel, ca, tmCq, tmCk, tmCv, tmCo);
    lc = cfgof(TRAIL_GRID, 384, tr::SMEM, true);
    tr::Args ta{P.k, P.v, (unsigned char*)P.o, P.qs, (unsigned char*)P.part, xcur, P.xn, P.xa, P.xn2, P.arena, P.go, tl + 4, 30, 20, layer == 0};
#ifdef TUNE
    if (getenv("NAP")) ta.nap = atoi(getenv("NAP"));
    if (getenv("NAP2")) ta.nap2 = atoi(getenv("NAP2"));
#endif
    cudaLaunchKernelEx(&lc, trail_kernel, tmXn, tmWq, tmWo5, tmWo2, tmP, sched_of(layer), ta, pa);
    lc = cfgof(128, 384, bf::SMEM, PDL_B);
    bf::Args ba{(const unsigned char*)P.wb, (const unsigned char*)P.wot, (unsigned char*)P.kvacc, (unsigned char*)P.pq, P.xa, layer == 0 ? P.xb : out, P.go, layer == 0 ? P.arena + tr::C_P : nullptr,
                      layer == 0 && PF_B ? Wk : nullptr, Wv, 30, 500, 0, tl + 7};
#ifdef TUNE
    if (getenv("PFN")) ba.pfn = atoi(getenv("PFN"));
    if (getenv("PFNS")) ba.pfns = atoi(getenv("PFNS"));
    if (getenv("PFWT")) ba.pfwait = atoi(getenv("PFWT"));
    if (getenv("PFB")) ba.pf0 = layer == 0 && atoi(getenv("PFB")) ? Wk : nullptr;
#endif
    cudaLaunchKernelEx(&lc, blayer_kernel, tmXn2, ba);
    xcur = P.xb;
  }
}
```

```cpp
#include <cuda_runtime.h>
#include <cuda.h>
#include <cuda_bf16.h>
#include <stdint.h>
#include <stdlib.h>
#include <type_traits>

typedef __nv_bfloat16 bf16;

namespace cfg {
constexpr int S = 2048, DM = 640, H = 32, DH = 192, NSEG = 64, SEG = 32, NM = 8;
constexpr int HD = H * DH;
}

__device__ __forceinline__ uint32_t smem_u32(const void* p) { return (uint32_t)__cvta_generic_to_shared(p); }
__device__ __forceinline__ uint32_t mapa_u32(uint32_t a, uint32_t r) {
  uint32_t o; asm("mapa.shared::cluster.u32 %0, %1, %2;" : "=r"(o) : "r"(a), "r"(r)); return o;
}
__device__ __forceinline__ void mbar_init(uint32_t b, uint32_t c) {
  asm volatile("mbarrier.init.shared::cta.b64 [%0], %1;" :: "r"(b), "r"(c) : "memory");
}
__device__ __forceinline__ void mbar_expect_tx(uint32_t b, uint32_t bytes) {
  asm volatile("mbarrier.arrive.expect_tx.shared::cta.b64 _, [%0], %1;" :: "r"(b), "r"(bytes) : "memory");
}
__device__ __forceinline__ void mbar_arrive(uint32_t b) {
  asm volatile("mbarrier.arrive.shared::cta.b64 _, [%0];" :: "r"(b) : "memory");
}
__device__ __forceinline__ void mbar_expect_tx_if(bool c, uint32_t b, uint32_t bytes) {
  asm volatile("{\n.reg .pred p;\nsetp.ne.u32 p, %2, 0;\n@p mbarrier.arrive.expect_tx.shared::cta.b64 _, [%0], %1;\n}" :: "r"(b), "r"(bytes), "r"((uint32_t)c) : "memory");
}
__device__ __forceinline__ void mbar_arrive_if(bool c, uint32_t b) {
  asm volatile("{\n.reg .pred p;\nsetp.ne.u32 p, %1, 0;\n@p mbarrier.arrive.shared::cta.b64 _, [%0];\n}" :: "r"(b), "r"((uint32_t)c) : "memory");
}
__device__ __forceinline__ bool mbar_try(uint32_t b, uint32_t ph) {
  uint32_t p;
  asm volatile("{.reg .pred p; mbarrier.try_wait.parity.shared::cta.b64 p, [%1], %2; selp.u32 %0, 1, 0, p;}"
               : "=r"(p) : "r"(b), "r"(ph) : "memory");
  return p;
}
__device__ __forceinline__ bool mbar_try_cluster(uint32_t b, uint32_t ph) {
  uint32_t p;
  asm volatile("{.reg .pred p; mbarrier.try_wait.parity.acquire.cluster.shared::cta.b64 p, [%1], %2; selp.u32 %0, 1, 0, p;}"
               : "=r"(p) : "r"(b), "r"(ph) : "memory");
  return p;
}
#ifndef SPIN_LIMIT
#define SPIN_LIMIT (1 << 20)
#endif
__device__ __forceinline__ void mbar_wait(uint32_t b, uint32_t ph) {
  asm volatile("{\n.reg .pred p, q;\n.reg .u32 c;\nmov.u32 c, 0;\n"
               "W_%=:\nmbarrier.try_wait.parity.shared::cta.b64 p, [%0], %1;\n@p bra.uni D_%=;\n"
               "add.u32 c, c, 1;\nsetp.lt.u32 q, c, %2;\n@q bra.uni W_%=;\nD_%=:\n}"
               :: "r"(b), "r"(ph), "n"(SPIN_LIMIT) : "memory");
}
__device__ __forceinline__ void mbar_wait_if(bool cnd, uint32_t b, uint32_t ph) {
  asm volatile("{\n.reg .pred p, q;\n.reg .u32 c;\nsetp.eq.u32 q, %3, 0;\n@q bra.uni D_%=;\nmov.u32 c, 0;\n"
               "W_%=:\nmbarrier.try_wait.parity.shared::cta.b64 p, [%0], %1;\n@p bra.uni D_%=;\n"
               "add.u32 c, c, 1;\nsetp.lt.u32 q, c, %2;\n@q bra.uni W_%=;\nD_%=:\n}"
               :: "r"(b), "r"(ph), "n"(SPIN_LIMIT), "r"((uint32_t)cnd) : "memory");
}
__device__ __forceinline__ void mbar_spin(uint32_t b, uint32_t ph) {
  asm volatile("{\n.reg .pred p, q;\n.reg .u32 c;\nmov.u32 c, 0;\n"
               "W_%=:\nmbarrier.test_wait.parity.shared::cta.b64 p, [%0], %1;\n@p bra D_%=;\n"
               "add.u32 c, c, 1;\nsetp.lt.u32 q, c, %2;\n@q bra W_%=;\nD_%=:\n}"
               :: "r"(b), "r"(ph), "n"(SPIN_LIMIT) : "memory");
}
#define PIN(x) asm volatile("" : "+r"(x))
__device__ __forceinline__ void mbar_wait_cluster(uint32_t b, uint32_t ph) {
  int s = 0;
  while (!mbar_try_cluster(b, ph)) { if (++s > SPIN_LIMIT) break; }
}
__device__ __forceinline__ void st_async_v2(uint32_t a, uint32_t x, uint32_t y, uint32_t mb) {
  asm volatile("st.async.weak.shared::cluster.mbarrier::complete_tx::bytes.v2.b32 [%0], {%1,%2}, [%3];"
               :: "r"(a), "r"(x), "r"(y), "r"(mb) : "memory");
}
__device__ __forceinline__ void st_async_v4(uint32_t a, uint32_t x, uint32_t y, uint32_t z, uint32_t w, uint32_t mb) {
  asm volatile("st.async.weak.shared::cluster.mbarrier::complete_tx::bytes.v4.b32 [%0], {%1,%2,%3,%4}, [%5];"
               :: "r"(a), "r"(x), "r"(y), "r"(z), "r"(w), "r"(mb) : "memory");
}
__device__ __forceinline__ void bulk_g2s(uint32_t dst, const void* src, uint32_t bytes, uint32_t mb) {
  asm volatile("cp.async.bulk.shared::cluster.global.mbarrier::complete_tx::bytes [%0], [%1], %2, [%3];"
               :: "r"(dst), "l"(src), "r"(bytes), "r"(mb) : "memory");
}
__device__ __forceinline__ void cp_async16(uint32_t dst, const void* src) {
  asm volatile("cp.async.cg.shared.global [%0], [%1], 16;" :: "r"(dst), "l"(src) : "memory");
}
__device__ __forceinline__ void cp_async_wait_all() { asm volatile("cp.async.wait_all;" ::: "memory"); }
__device__ __forceinline__ void fence_proxy_async() { asm volatile("fence.proxy.async.shared::cta;" ::: "memory"); }
__device__ __forceinline__ void bar_sync(int id, int n) { asm volatile("bar.sync %0, %1;" :: "r"(id), "r"(n) : "memory"); }
__device__ __forceinline__ void bar_arrive(int id, int n) { asm volatile("bar.arrive %0, %1;" :: "r"(id), "r"(n) : "memory"); }
__device__ __forceinline__ void cluster_sync_all() {
  asm volatile("barrier.cluster.arrive.release.aligned; barrier.cluster.wait.acquire.aligned;" ::: "memory");
}
__device__ __forceinline__ void ldsm_x4(uint32_t (&r)[4], uint32_t a) {
  asm volatile("ldmatrix.sync.aligned.m8n8.x4.shared.b16 {%0,%1,%2,%3}, [%4];"
               : "=r"(r[0]), "=r"(r[1]), "=r"(r[2]), "=r"(r[3]) : "r"(a) : "memory");
}
__device__ __forceinline__ void ldsm_x4_t(uint32_t (&r)[4], uint32_t a) {
  asm volatile("ldmatrix.sync.aligned.m8n8.x4.trans.shared.b16 {%0,%1,%2,%3}, [%4];"
               : "=r"(r[0]), "=r"(r[1]), "=r"(r[2]), "=r"(r[3]) : "r"(a) : "memory");
}
template <int IMM> __device__ __forceinline__ void ldsm_x4_i(uint32_t (&r)[4], uint32_t a) {
  asm volatile("ldmatrix.sync.aligned.m8n8.x4.shared.b16 {%0,%1,%2,%3}, [%4+%5];"
               : "=r"(r[0]), "=r"(r[1]), "=r"(r[2]), "=r"(r[3]) : "r"(a), "n"(IMM) : "memory");
}
template <int IMM> __device__ __forceinline__ void ldsm_x4_t_i(uint32_t (&r)[4], uint32_t a) {
  asm volatile("ldmatrix.sync.aligned.m8n8.x4.trans.shared.b16 {%0,%1,%2,%3}, [%4+%5];"
               : "=r"(r[0]), "=r"(r[1]), "=r"(r[2]), "=r"(r[3]) : "r"(a), "n"(IMM) : "memory");
}
template <int IMM> __device__ __forceinline__ uint4 lds128_i(uint32_t a) {
  uint4 v; asm volatile("ld.shared.v4.u32 {%0,%1,%2,%3}, [%4+%5];" : "=r"(v.x), "=r"(v.y), "=r"(v.z), "=r"(v.w) : "r"(a), "n"(IMM) : "memory"); return v;
}
template <int IMM> __device__ __forceinline__ uint2 lds64_i(uint32_t a) {
  uint2 v; asm volatile("ld.shared.v2.u32 {%0,%1}, [%2+%3];" : "=r"(v.x), "=r"(v.y) : "r"(a), "n"(IMM) : "memory"); return v;
}
template <int IMM> __device__ __forceinline__ void sts128_i(uint32_t a, uint32_t x, uint32_t y, uint32_t z, uint32_t w) {
  asm volatile("st.shared.v4.u32 [%0+%5], {%1,%2,%3,%4};" :: "r"(a), "r"(x), "r"(y), "r"(z), "r"(w), "n"(IMM) : "memory");
}
template <int IMM> __device__ __forceinline__ void sts64_i(uint32_t a, uint32_t x, uint32_t y) {
  asm volatile("st.shared.v2.u32 [%0+%3], {%1,%2};" :: "r"(a), "r"(x), "r"(y), "n"(IMM) : "memory");
}
template <int IMM> __device__ __forceinline__ void st_async_v2_i(uint32_t a, uint32_t x, uint32_t y, uint32_t mb) {
  asm volatile("st.async.weak.shared::cluster.mbarrier::complete_tx::bytes.v2.b32 [%0+%4], {%1,%2}, [%3];"
               :: "r"(a), "r"(x), "r"(y), "r"(mb), "n"(IMM) : "memory");
}
template <int IMM> __device__ __forceinline__ uint4 ld_relaxed_v4_i(const void* p) {
  uint4 v; asm volatile("ld.relaxed.gpu.global.v4.u32 {%0,%1,%2,%3}, [%4+%5];" : "=r"(v.x), "=r"(v.y), "=r"(v.z), "=r"(v.w) : "l"(p), "n"(IMM) : "memory"); return v;
}
template <int I, int N, class F> __device__ __forceinline__ void static_for(F&& f) {
  if constexpr (I < N) { f(std::integral_constant<int, I>{}); static_for<I + 1, N>(f); }
}
__device__ __forceinline__ uint32_t movm_t(uint32_t a) {
  uint32_t d; asm volatile("movmatrix.sync.aligned.m8n8.trans.b16 %0, %1;" : "=r"(d) : "r"(a)); return d;
}
__device__ __forceinline__ void mma16816(float (&d)[4], uint32_t a0, uint32_t a1, uint32_t a2, uint32_t a3, uint32_t b0, uint32_t b1) {
  asm volatile("mma.sync.aligned.m16n8k16.row.col.f32.bf16.bf16.f32 {%0,%1,%2,%3}, {%4,%5,%6,%7}, {%8,%9}, {%0,%1,%2,%3};"
               : "+f"(d[0]), "+f"(d[1]), "+f"(d[2]), "+f"(d[3]) : "r"(a0), "r"(a1), "r"(a2), "r"(a3), "r"(b0), "r"(b1));
}
__device__ __forceinline__ uint32_t pack_bf16(float lo, float hi) {
  uint32_t d; asm("cvt.rn.bf16x2.f32 %0, %1, %2;" : "=r"(d) : "f"(hi), "f"(lo)); return d;
}
__device__ __forceinline__ float bf_lo(uint32_t w) { return __uint_as_float(w << 16); }
__device__ __forceinline__ float bf_hi(uint32_t w) { return __uint_as_float(w & 0xffff0000u); }
__device__ __forceinline__ uint4 lds128(uint32_t a) {
  uint4 v; asm volatile("ld.shared.v4.u32 {%0,%1,%2,%3}, [%4];" : "=r"(v.x), "=r"(v.y), "=r"(v.z), "=r"(v.w) : "r"(a) : "memory"); return v;
}
__device__ __forceinline__ uint2 lds64(uint32_t a) {
  uint2 v; asm volatile("ld.shared.v2.u32 {%0,%1}, [%2];" : "=r"(v.x), "=r"(v.y) : "r"(a) : "memory"); return v;
}
__device__ __forceinline__ void sts128(uint32_t a, uint32_t x, uint32_t y, uint32_t z, uint32_t w) {
  asm volatile("st.shared.v4.u32 [%0], {%1,%2,%3,%4};" :: "r"(a), "r"(x), "r"(y), "r"(z), "r"(w) : "memory");
}
__device__ __forceinline__ void sts64(uint32_t a, uint32_t x, uint32_t y) {
  asm volatile("st.shared.v2.u32 [%0], {%1,%2};" :: "r"(a), "r"(x), "r"(y) : "memory");
}
__device__ __forceinline__ uint4 ld_relaxed_v4(const void* p) {
  uint4 v; asm volatile("ld.relaxed.gpu.global.v4.u32 {%0,%1,%2,%3}, [%4];" : "=r"(v.x), "=r"(v.y), "=r"(v.z), "=r"(v.w) : "l"(p) : "memory"); return v;
}
__device__ __forceinline__ uint32_t ld_relaxed_u32(const void* p) {
  uint32_t v; asm volatile("ld.relaxed.gpu.global.u32 %0, [%1];" : "=r"(v) : "l"(p) : "memory"); return v;
}
__device__ __forceinline__ void st_relaxed_v2(void* p, uint32_t a, uint32_t b) {
  asm volatile("st.relaxed.gpu.global.v2.u32 [%0], {%1,%2};" :: "l"(p), "r"(a), "r"(b) : "memory");
}
__device__ __forceinline__ void st_relaxed_u32(void* p, uint32_t v) {
  asm volatile("st.relaxed.gpu.global.u32 [%0], %1;" :: "l"(p), "r"(v) : "memory");
}
__device__ __forceinline__ void st_release_u32(void* p, uint32_t v) {
  asm volatile("st.release.gpu.global.u32 [%0], %1;" :: "l"(p), "r"(v) : "memory");
}
__device__ __forceinline__ void red_release_inc(void* p) { asm volatile("red.release.gpu.global.add.u32 [%0], 1;" :: "l"(p) : "memory"); }
__device__ __forceinline__ uint32_t clk32() { uint32_t c; asm volatile("mov.u32 %0, %%clock;" : "=r"(c) :: "memory"); return c; }
__device__ __forceinline__ uint32_t clkdep(uint32_t v) {
  uint32_t c; asm volatile("{.reg .pred p; setp.eq.u32 p, %1, 0xdeadbeef; @p trap; mov.u32 %0, %%clock;}" : "=r"(c) : "r"(v) : "memory"); return c;
}
__device__ __forceinline__ void wgmma_fence() { asm volatile("wgmma.fence.sync.aligned;" ::: "memory"); }
__device__ __forceinline__ void wgmma_commit() { asm volatile("wgmma.commit_group.sync.aligned;" ::: "memory"); }
template <int N> __device__ __forceinline__ void wgmma_wait() { asm volatile("wgmma.wait_group.sync.aligned %0;" :: "n"(N) : "memory"); }
__device__ __forceinline__ void wgmma_n8_ss_ta(float (&d)[4], uint64_t da, uint64_t db, int acc) {
  asm volatile("{\n.reg .pred p;\nsetp.ne.b32 p, %6, 0;\n"
               "wgmma.mma_async.sync.aligned.m64n8k16.f32.bf16.bf16 {%0,%1,%2,%3}, %4, %5, p, 1, 1, 1, 0;\n}\n"
               : "+f"(d[0]), "+f"(d[1]), "+f"(d[2]), "+f"(d[3]) : "l"(da), "l"(db), "r"(acc));
}
__device__ __forceinline__ uint64_t make_desc(uint32_t saddr, uint32_t lbo_bytes, uint32_t sbo_bytes, uint32_t swz) {
  return (uint64_t)((saddr & 0x3FFFF) >> 4) | ((uint64_t)(lbo_bytes >> 4) << 16) | ((uint64_t)(sbo_bytes >> 4) << 32) | ((uint64_t)swz << 62);
}


template <uint32_t LBO, uint32_t SBO, uint32_t SWZ> __device__ __forceinline__ uint64_t desc16(uint32_t a16, uint32_t off = 0) {
  return (uint64_t)(a16 + ((off >> 4) + ((LBO >> 4) << 16))) | ((uint64_t)((SBO >> 4) | (SWZ << 30)) << 32);
}

__device__ __forceinline__ bool elect_one() {
  uint32_t p; asm volatile("{\n.reg .pred p;\nelect.sync _|p, 0xffffffff;\nselp.u32 %0, 1, 0, p;\n}" : "=r"(p)); return p;
}
__device__ __forceinline__ void tma_load_3d(uint32_t dst, const CUtensorMap* tm, int c0, int c1, int c2, uint32_t mb) {
  asm volatile("cp.async.bulk.tensor.3d.shared::cluster.global.mbarrier::complete_tx::bytes [%0], [%1, {%3, %4, %5}], [%2];"
               :: "r"(dst), "l"(tm), "r"(mb), "r"(c0), "r"(c1), "r"(c2) : "memory");
}
__device__ __forceinline__ void tma_load_2d(uint32_t dst, const CUtensorMap* tm, int c0, int c1, uint32_t mb) {
  asm volatile("cp.async.bulk.tensor.2d.shared::cluster.global.mbarrier::complete_tx::bytes [%0], [%1, {%3, %4}], [%2];"
               :: "r"(dst), "l"(tm), "r"(mb), "r"(c0), "r"(c1) : "memory");
}
__device__ __forceinline__ void bulk_s2g(void* dst, uint32_t src, uint32_t bytes) {
  asm volatile("cp.async.bulk.global.shared::cta.bulk_group [%0], [%1], %2;" :: "l"(dst), "r"(src), "r"(bytes) : "memory");
}
__device__ __forceinline__ uint64_t policy_evict_first() {
  uint64_t p; asm volatile("createpolicy.fractional.L2::evict_first.b64 %0, 1.0;" : "=l"(p)); return p;
}
__device__ __forceinline__ void bulk_s2g_hint(void* dst, uint32_t src, uint32_t bytes, uint64_t pol) {
  asm volatile("cp.async.bulk.global.shared::cta.bulk_group.L2::cache_hint [%0], [%1], %2, %3;" :: "l"(dst), "r"(src), "r"(bytes), "l"(pol) : "memory");
}
__device__ __forceinline__ void bulk_commit() { asm volatile("cp.async.bulk.commit_group;" ::: "memory"); }
template <int N> __device__ __forceinline__ void bulk_wait_read() { asm volatile("cp.async.bulk.wait_group.read %0;" :: "n"(N) : "memory"); }
template <int N> __device__ __forceinline__ void bulk_wait() { asm volatile("cp.async.bulk.wait_group %0;" :: "n"(N) : "memory"); }
__device__ __forceinline__ void stsm_x4(uint32_t a, uint32_t r0, uint32_t r1, uint32_t r2, uint32_t r3) {
  asm volatile("stmatrix.sync.aligned.m8n8.x4.shared.b16 [%0], {%1,%2,%3,%4};" :: "r"(a), "r"(r0), "r"(r1), "r"(r2), "r"(r3) : "memory");
}
__device__ __forceinline__ void stsm_x2(uint32_t a, uint32_t r0, uint32_t r1) {
  asm volatile("stmatrix.sync.aligned.m8n8.x2.shared.b16 [%0], {%1,%2};" :: "r"(a), "r"(r0), "r"(r1) : "memory");
}
__device__ __forceinline__ void ldsm_x2(uint32_t (&r)[2], uint32_t a) {
  asm volatile("ldmatrix.sync.aligned.m8n8.x2.shared.b16 {%0,%1}, [%2];" : "=r"(r[0]), "=r"(r[1]) : "r"(a) : "memory");
}
__device__ __forceinline__ void ldsm_x2_t(uint32_t (&r)[2], uint32_t a) {
  asm volatile("ldmatrix.sync.aligned.m8n8.x2.trans.shared.b16 {%0,%1}, [%2];" : "=r"(r[0]), "=r"(r[1]) : "r"(a) : "memory");
}
__device__ __forceinline__ float bf16r(float x) { return __uint_as_float(pack_bf16(0.f, x) & 0xffff0000u); }
__device__ __forceinline__ void bf16r2(float& a, float& b) { const uint32_t w = pack_bf16(a, b); a = bf_lo(w); b = bf_hi(w); }
__device__ __forceinline__ float rcpf(float x) { float r; asm("rcp.approx.ftz.f32 %0, %1;" : "=f"(r) : "f"(x)); return r; }
__device__ __forceinline__ float ex2f(float x) { float e; asm("ex2.approx.ftz.f32 %0, %1;" : "=f"(e) : "f"(x)); return e; }
__device__ __forceinline__ void prefetch_tmap(const CUtensorMap* tm) { asm volatile("prefetch.tensormap [%0];" :: "l"(tm) : "memory"); }

#ifdef TLLITE
__device__ unsigned long long g_lite[8];
__device__ __forceinline__ void lite(int i) { unsigned long long t; asm volatile("mov.u64 %0, %%globaltimer;" : "=l"(t)); g_lite[i] = t; }
#define LITE(c, i) do { if (c) lite(i); } while (0)
#else
#define LITE(c, i)
#endif
#ifdef TIMELINE
__device__ unsigned long long g_tl[2 * 64];
__device__ unsigned g_step[2 * 64 * 96 * 4];
__device__ unsigned long long g_log[2 * 132 * 64 * 2 + 2];
__device__ unsigned long long g_tl2[4 * 64];
__device__ __forceinline__ unsigned long long gtime() { unsigned long long t; asm volatile("mov.u64 %0, %%globaltimer;" : "=l"(t)); return t; }
#define TL_BEGIN(id) do { if (threadIdx.x == 0) atomicMin(&g_tl[2 * (id)], gtime()); } while (0)
#define TL_END(id) do { if ((threadIdx.x & 31) == 0) atomicMax(&g_tl[2 * (id) + 1], gtime()); } while (0)
#define TL_ACC(idx, t0) do { if (threadIdx.x == 0 && m >= 4 && m < 11) { atomicAdd(&g_tl2[idx], gtime() - (t0)); atomicAdd(&g_tl2[(idx) + 1], 1ull); } } while (0)
#define TL_NOW() gtime()
#define TL2(idx) asm volatile("{\n.reg .pred p;\nsetp.eq.u32 p, %2, 0;\n@p red.relaxed.gpu.global.max.u64 [%0], %1;\n}" :: "l"(&g_tl2[idx]), "l"(gtime()), "r"(threadIdx.x) : "memory")
#define TLW(idx) asm volatile("{\n.reg .pred p;\nsetp.eq.u32 p, %2, 0;\n@p red.relaxed.gpu.global.max.u64 [%0], %1;\n@p red.relaxed.gpu.global.add.u64 [%0+128], %1;\n}" :: "l"(&g_tl2[idx]), "l"(gtime() - g_tl0), "r"(threadIdx.x & 31) : "memory")
#define TL_BEGIN0(id) atomicMin(&g_tl[2 * (id)], gtime())
#else
#define TL_ACC(idx, t0)
#define TL_NOW() 0ull
#define TL2(idx)
#define TL_BEGIN0(id)
#define TLW(idx)
#define TL_BEGIN(id)
#define TL_END(id)
#endif
template <int TA, int TB> __device__ __forceinline__ void wgmma_n24(float (&d)[12], uint64_t da, uint64_t db, int acc) {
  asm volatile("{\n.reg .pred p;\nsetp.ne.b32 p, %14, 0;\n"
    "wgmma.mma_async.sync.aligned.m64n24k16.f32.bf16.bf16 {%0, %1, %2, %3, %4, %5, %6, %7, %8, %9, %10, %11}, %12, %13, p, 1, 1, %15, %16;\n}\n"
    : "+f"(d[0]), "+f"(d[1]), "+f"(d[2]), "+f"(d[3]), "+f"(d[4]), "+f"(d[5]), "+f"(d[6]), "+f"(d[7]), "+f"(d[8]), "+f"(d[9]), "+f"(d[10]), "+f"(d[11])
    : "l"(da), "l"(db), "r"(acc), "n"(TA), "n"(TB));
}

template <int TA, int TB> __device__ __forceinline__ void wgmma_n80(float (&d)[40], uint64_t da, uint64_t db, int acc) {
  asm volatile("{\n.reg .pred p;\nsetp.ne.b32 p, %42, 0;\n"
    "wgmma.mma_async.sync.aligned.m64n80k16.f32.bf16.bf16 {%0, %1, %2, %3, %4, %5, %6, %7, %8, %9, %10, %11, %12, %13, %14, %15, %16, %17, %18, %19, %20, %21, %22, %23, %24, %25, %26, %27, %28, %29, %30, %31, %32, %33, %34, %35, %36, %37, %38, %39}, %40, %41, p, 1, 1, %43, %44;\n}\n"
    : "+f"(d[0]), "+f"(d[1]), "+f"(d[2]), "+f"(d[3]), "+f"(d[4]), "+f"(d[5]), "+f"(d[6]), "+f"(d[7]), "+f"(d[8]), "+f"(d[9]), "+f"(d[10]), "+f"(d[11]), "+f"(d[12]), "+f"(d[13]), "+f"(d[14]), "+f"(d[15]), "+f"(d[16]), "+f"(d[17]), "+f"(d[18]), "+f"(d[19]), "+f"(d[20]), "+f"(d[21]), "+f"(d[22]), "+f"(d[23]), "+f"(d[24]), "+f"(d[25]), "+f"(d[26]), "+f"(d[27]), "+f"(d[28]), "+f"(d[29]), "+f"(d[30]), "+f"(d[31]), "+f"(d[32]), "+f"(d[33]), "+f"(d[34]), "+f"(d[35]), "+f"(d[36]), "+f"(d[37]), "+f"(d[38]), "+f"(d[39])
    : "l"(da), "l"(db), "r"(acc), "n"(TA), "n"(TB));
}

template <int TA, int TB> __device__ __forceinline__ void wgmma_n128(float (&d)[64], uint64_t da, uint64_t db, int acc) {
  asm volatile("{\n.reg .pred p;\nsetp.ne.b32 p, %66, 0;\n"
    "wgmma.mma_async.sync.aligned.m64n128k16.f32.bf16.bf16 {%0, %1, %2, %3, %4, %5, %6, %7, %8, %9, %10, %11, %12, %13, %14, %15, %16, %17, %18, %19, %20, %21, %22, %23, %24, %25, %26, %27, %28, %29, %30, %31, %32, %33, %34, %35, %36, %37, %38, %39, %40, %41, %42, %43, %44, %45, %46, %47, %48, %49, %50, %51, %52, %53, %54, %55, %56, %57, %58, %59, %60, %61, %62, %63}, %64, %65, p, 1, 1, %67, %68;\n}\n"
    : "+f"(d[0]), "+f"(d[1]), "+f"(d[2]), "+f"(d[3]), "+f"(d[4]), "+f"(d[5]), "+f"(d[6]), "+f"(d[7]), "+f"(d[8]), "+f"(d[9]), "+f"(d[10]), "+f"(d[11]), "+f"(d[12]), "+f"(d[13]), "+f"(d[14]), "+f"(d[15]), "+f"(d[16]), "+f"(d[17]), "+f"(d[18]), "+f"(d[19]), "+f"(d[20]), "+f"(d[21]), "+f"(d[22]), "+f"(d[23]), "+f"(d[24]), "+f"(d[25]), "+f"(d[26]), "+f"(d[27]), "+f"(d[28]), "+f"(d[29]), "+f"(d[30]), "+f"(d[31]), "+f"(d[32]), "+f"(d[33]), "+f"(d[34]), "+f"(d[35]), "+f"(d[36]), "+f"(d[37]), "+f"(d[38]), "+f"(d[39]), "+f"(d[40]), "+f"(d[41]), "+f"(d[42]), "+f"(d[43]), "+f"(d[44]), "+f"(d[45]), "+f"(d[46]), "+f"(d[47]), "+f"(d[48]), "+f"(d[49]), "+f"(d[50]), "+f"(d[51]), "+f"(d[52]), "+f"(d[53]), "+f"(d[54]), "+f"(d[55]), "+f"(d[56]), "+f"(d[57]), "+f"(d[58]), "+f"(d[59]), "+f"(d[60]), "+f"(d[61]), "+f"(d[62]), "+f"(d[63])
    : "l"(da), "l"(db), "r"(acc), "n"(TA), "n"(TB));
}

template <int TA, int TB> __device__ __forceinline__ void wgmma_n192(float (&d)[96], uint64_t da, uint64_t db, int acc) {
  asm volatile("{\n.reg .pred p;\nsetp.ne.b32 p, %98, 0;\n"
    "wgmma.mma_async.sync.aligned.m64n192k16.f32.bf16.bf16 {%0, %1, %2, %3, %4, %5, %6, %7, %8, %9, %10, %11, %12, %13, %14, %15, %16, %17, %18, %19, %20, %21, %22, %23, %24, %25, %26, %27, %28, %29, %30, %31, %32, %33, %34, %35, %36, %37, %38, %39, %40, %41, %42, %43, %44, %45, %46, %47, %48, %49, %50, %51, %52, %53, %54, %55, %56, %57, %58, %59, %60, %61, %62, %63, %64, %65, %66, %67, %68, %69, %70, %71, %72, %73, %74, %75, %76, %77, %78, %79, %80, %81, %82, %83, %84, %85, %86, %87, %88, %89, %90, %91, %92, %93, %94, %95}, %96, %97, p, 1, 1, %99, %100;\n}\n"
    : "+f"(d[0]), "+f"(d[1]), "+f"(d[2]), "+f"(d[3]), "+f"(d[4]), "+f"(d[5]), "+f"(d[6]), "+f"(d[7]), "+f"(d[8]), "+f"(d[9]), "+f"(d[10]), "+f"(d[11]), "+f"(d[12]), "+f"(d[13]), "+f"(d[14]), "+f"(d[15]), "+f"(d[16]), "+f"(d[17]), "+f"(d[18]), "+f"(d[19]), "+f"(d[20]), "+f"(d[21]), "+f"(d[22]), "+f"(d[23]), "+f"(d[24]), "+f"(d[25]), "+f"(d[26]), "+f"(d[27]), "+f"(d[28]), "+f"(d[29]), "+f"(d[30]), "+f"(d[31]), "+f"(d[32]), "+f"(d[33]), "+f"(d[34]), "+f"(d[35]), "+f"(d[36]), "+f"(d[37]), "+f"(d[38]), "+f"(d[39]), "+f"(d[40]), "+f"(d[41]), "+f"(d[42]), "+f"(d[43]), "+f"(d[44]), "+f"(d[45]), "+f"(d[46]), "+f"(d[47]), "+f"(d[48]), "+f"(d[49]), "+f"(d[50]), "+f"(d[51]), "+f"(d[52]), "+f"(d[53]), "+f"(d[54]), "+f"(d[55]), "+f"(d[56]), "+f"(d[57]), "+f"(d[58]), "+f"(d[59]), "+f"(d[60]), "+f"(d[61]), "+f"(d[62]), "+f"(d[63]), "+f"(d[64]), "+f"(d[65]), "+f"(d[66]), "+f"(d[67]), "+f"(d[68]), "+f"(d[69]), "+f"(d[70]), "+f"(d[71]), "+f"(d[72]), "+f"(d[73]), "+f"(d[74]), "+f"(d[75]), "+f"(d[76]), "+f"(d[77]), "+f"(d[78]), "+f"(d[79]), "+f"(d[80]), "+f"(d[81]), "+f"(d[82]), "+f"(d[83]), "+f"(d[84]), "+f"(d[85]), "+f"(d[86]), "+f"(d[87]), "+f"(d[88]), "+f"(d[89]), "+f"(d[90]), "+f"(d[91]), "+f"(d[92]), "+f"(d[93]), "+f"(d[94]), "+f"(d[95])
    : "l"(da), "l"(db), "r"(acc), "n"(TA), "n"(TB));
}

template <int TA, int TB> __device__ __forceinline__ void wgmma_n256(float (&d)[128], uint64_t da, uint64_t db, int acc) {
  asm volatile("{\n.reg .pred p;\nsetp.ne.b32 p, %130, 0;\n"
    "wgmma.mma_async.sync.aligned.m64n256k16.f32.bf16.bf16 {%0, %1, %2, %3, %4, %5, %6, %7, %8, %9, %10, %11, %12, %13, %14, %15, %16, %17, %18, %19, %20, %21, %22, %23, %24, %25, %26, %27, %28, %29, %30, %31, %32, %33, %34, %35, %36, %37, %38, %39, %40, %41, %42, %43, %44, %45, %46, %47, %48, %49, %50, %51, %52, %53, %54, %55, %56, %57, %58, %59, %60, %61, %62, %63, %64, %65, %66, %67, %68, %69, %70, %71, %72, %73, %74, %75, %76, %77, %78, %79, %80, %81, %82, %83, %84, %85, %86, %87, %88, %89, %90, %91, %92, %93, %94, %95, %96, %97, %98, %99, %100, %101, %102, %103, %104, %105, %106, %107, %108, %109, %110, %111, %112, %113, %114, %115, %116, %117, %118, %119, %120, %121, %122, %123, %124, %125, %126, %127}, %128, %129, p, 1, 1, %131, %132;\n}\n"
    : "+f"(d[0]), "+f"(d[1]), "+f"(d[2]), "+f"(d[3]), "+f"(d[4]), "+f"(d[5]), "+f"(d[6]), "+f"(d[7]), "+f"(d[8]), "+f"(d[9]), "+f"(d[10]), "+f"(d[11]), "+f"(d[12]), "+f"(d[13]), "+f"(d[14]), "+f"(d[15]), "+f"(d[16]), "+f"(d[17]), "+f"(d[18]), "+f"(d[19]), "+f"(d[20]), "+f"(d[21]), "+f"(d[22]), "+f"(d[23]), "+f"(d[24]), "+f"(d[25]), "+f"(d[26]), "+f"(d[27]), "+f"(d[28]), "+f"(d[29]), "+f"(d[30]), "+f"(d[31]), "+f"(d[32]), "+f"(d[33]), "+f"(d[34]), "+f"(d[35]), "+f"(d[36]), "+f"(d[37]), "+f"(d[38]), "+f"(d[39]), "+f"(d[40]), "+f"(d[41]), "+f"(d[42]), "+f"(d[43]), "+f"(d[44]), "+f"(d[45]), "+f"(d[46]), "+f"(d[47]), "+f"(d[48]), "+f"(d[49]), "+f"(d[50]), "+f"(d[51]), "+f"(d[52]), "+f"(d[53]), "+f"(d[54]), "+f"(d[55]), "+f"(d[56]), "+f"(d[57]), "+f"(d[58]), "+f"(d[59]), "+f"(d[60]), "+f"(d[61]), "+f"(d[62]), "+f"(d[63]), "+f"(d[64]), "+f"(d[65]), "+f"(d[66]), "+f"(d[67]), "+f"(d[68]), "+f"(d[69]), "+f"(d[70]), "+f"(d[71]), "+f"(d[72]), "+f"(d[73]), "+f"(d[74]), "+f"(d[75]), "+f"(d[76]), "+f"(d[77]), "+f"(d[78]), "+f"(d[79]), "+f"(d[80]), "+f"(d[81]), "+f"(d[82]), "+f"(d[83]), "+f"(d[84]), "+f"(d[85]), "+f"(d[86]), "+f"(d[87]), "+f"(d[88]), "+f"(d[89]), "+f"(d[90]), "+f"(d[91]), "+f"(d[92]), "+f"(d[93]), "+f"(d[94]), "+f"(d[95]), "+f"(d[96]), "+f"(d[97]), "+f"(d[98]), "+f"(d[99]), "+f"(d[100]), "+f"(d[101]), "+f"(d[102]), "+f"(d[103]), "+f"(d[104]), "+f"(d[105]), "+f"(d[106]), "+f"(d[107]), "+f"(d[108]), "+f"(d[109]), "+f"(d[110]), "+f"(d[111]), "+f"(d[112]), "+f"(d[113]), "+f"(d[114]), "+f"(d[115]), "+f"(d[116]), "+f"(d[117]), "+f"(d[118]), "+f"(d[119]), "+f"(d[120]), "+f"(d[121]), "+f"(d[122]), "+f"(d[123]), "+f"(d[124]), "+f"(d[125]), "+f"(d[126]), "+f"(d[127])
    : "l"(da), "l"(db), "r"(acc), "n"(TA), "n"(TB));
}

template <int TB> __device__ __forceinline__ void wgmma_rs_n24(float (&d)[12], uint32_t a0, uint32_t a1, uint32_t a2, uint32_t a3, uint64_t db, int acc) {
  asm volatile("{\n.reg .pred p;\nsetp.ne.b32 p, %17, 0;\n"
    "wgmma.mma_async.sync.aligned.m64n24k16.f32.bf16.bf16 {%0, %1, %2, %3, %4, %5, %6, %7, %8, %9, %10, %11}, {%12, %13, %14, %15}, %16, p, 1, 1, %18;\n}\n"
    : "+f"(d[0]), "+f"(d[1]), "+f"(d[2]), "+f"(d[3]), "+f"(d[4]), "+f"(d[5]), "+f"(d[6]), "+f"(d[7]), "+f"(d[8]), "+f"(d[9]), "+f"(d[10]), "+f"(d[11])
    : "r"(a0), "r"(a1), "r"(a2), "r"(a3), "l"(db), "r"(acc), "n"(TB));
}

template <int TB> __device__ __forceinline__ void wgmma_rs_n40(float (&d)[20], uint32_t a0, uint32_t a1, uint32_t a2, uint32_t a3, uint64_t db, int acc) {
  asm volatile("{\n.reg .pred p;\nsetp.ne.b32 p, %25, 0;\n"
    "wgmma.mma_async.sync.aligned.m64n40k16.f32.bf16.bf16 {%0, %1, %2, %3, %4, %5, %6, %7, %8, %9, %10, %11, %12, %13, %14, %15, %16, %17, %18, %19}, {%20, %21, %22, %23}, %24, p, 1, 1, %26;\n}\n"
    : "+f"(d[0]), "+f"(d[1]), "+f"(d[2]), "+f"(d[3]), "+f"(d[4]), "+f"(d[5]), "+f"(d[6]), "+f"(d[7]), "+f"(d[8]), "+f"(d[9]), "+f"(d[10]), "+f"(d[11]), "+f"(d[12]), "+f"(d[13]), "+f"(d[14]), "+f"(d[15]), "+f"(d[16]), "+f"(d[17]), "+f"(d[18]), "+f"(d[19])
    : "r"(a0), "r"(a1), "r"(a2), "r"(a3), "l"(db), "r"(acc), "n"(TB));
}

template <int TB> __device__ __forceinline__ void wgmma_rs_n192(float (&d)[96], uint32_t a0, uint32_t a1, uint32_t a2, uint32_t a3, uint64_t db, int acc) {
  asm volatile("{\n.reg .pred p;\nsetp.ne.b32 p, %101, 0;\n"
    "wgmma.mma_async.sync.aligned.m64n192k16.f32.bf16.bf16 {%0, %1, %2, %3, %4, %5, %6, %7, %8, %9, %10, %11, %12, %13, %14, %15, %16, %17, %18, %19, %20, %21, %22, %23, %24, %25, %26, %27, %28, %29, %30, %31, %32, %33, %34, %35, %36, %37, %38, %39, %40, %41, %42, %43, %44, %45, %46, %47, %48, %49, %50, %51, %52, %53, %54, %55, %56, %57, %58, %59, %60, %61, %62, %63, %64, %65, %66, %67, %68, %69, %70, %71, %72, %73, %74, %75, %76, %77, %78, %79, %80, %81, %82, %83, %84, %85, %86, %87, %88, %89, %90, %91, %92, %93, %94, %95}, {%96, %97, %98, %99}, %100, p, 1, 1, %102;\n}\n"
    : "+f"(d[0]), "+f"(d[1]), "+f"(d[2]), "+f"(d[3]), "+f"(d[4]), "+f"(d[5]), "+f"(d[6]), "+f"(d[7]), "+f"(d[8]), "+f"(d[9]), "+f"(d[10]), "+f"(d[11]), "+f"(d[12]), "+f"(d[13]), "+f"(d[14]), "+f"(d[15]), "+f"(d[16]), "+f"(d[17]), "+f"(d[18]), "+f"(d[19]), "+f"(d[20]), "+f"(d[21]), "+f"(d[22]), "+f"(d[23]), "+f"(d[24]), "+f"(d[25]), "+f"(d[26]), "+f"(d[27]), "+f"(d[28]), "+f"(d[29]), "+f"(d[30]), "+f"(d[31]), "+f"(d[32]), "+f"(d[33]), "+f"(d[34]), "+f"(d[35]), "+f"(d[36]), "+f"(d[37]), "+f"(d[38]), "+f"(d[39]), "+f"(d[40]), "+f"(d[41]), "+f"(d[42]), "+f"(d[43]), "+f"(d[44]), "+f"(d[45]), "+f"(d[46]), "+f"(d[47]), "+f"(d[48]), "+f"(d[49]), "+f"(d[50]), "+f"(d[51]), "+f"(d[52]), "+f"(d[53]), "+f"(d[54]), "+f"(d[55]), "+f"(d[56]), "+f"(d[57]), "+f"(d[58]), "+f"(d[59]), "+f"(d[60]), "+f"(d[61]), "+f"(d[62]), "+f"(d[63]), "+f"(d[64]), "+f"(d[65]), "+f"(d[66]), "+f"(d[67]), "+f"(d[68]), "+f"(d[69]), "+f"(d[70]), "+f"(d[71]), "+f"(d[72]), "+f"(d[73]), "+f"(d[74]), "+f"(d[75]), "+f"(d[76]), "+f"(d[77]), "+f"(d[78]), "+f"(d[79]), "+f"(d[80]), "+f"(d[81]), "+f"(d[82]), "+f"(d[83]), "+f"(d[84]), "+f"(d[85]), "+f"(d[86]), "+f"(d[87]), "+f"(d[88]), "+f"(d[89]), "+f"(d[90]), "+f"(d[91]), "+f"(d[92]), "+f"(d[93]), "+f"(d[94]), "+f"(d[95])
    : "r"(a0), "r"(a1), "r"(a2), "r"(a3), "l"(db), "r"(acc), "n"(TB));
}
constexpr uint32_t AR_ACC = 0;
constexpr uint32_t AR_TAB = 0x100000;
constexpr uint32_t AR_PROG = 0x101000;
__host__ __device__ constexpr uint32_t prog_off(int h, int j) { return AR_PROG + h * 128 + j * 4; }
constexpr uint32_t AR_CNT = 0x108000;
constexpr uint32_t AR_QUEUE = 0x109000;
constexpr uint32_t AR_SIZE = 0x10a000;

struct ChainArgs {
  const bf16* mem0;
  const uint2* xh;
  unsigned char *kg, *vg;
  unsigned char* arena;
  unsigned* go;
  uint32_t* dbg;
  uint32_t delay;
  int margin, pubrel, dry;
  int tl;
};

namespace ch {
constexpr int OFF_WQ = 0;
constexpr int OFF_X = 81920;
constexpr int OFF_MEM = OFF_X + 40960;
constexpr int OFF_WO = OFF_MEM + 10240;
constexpr int WOK = 8 * 896;
constexpr int OFF_KV = OFF_WO + 10 * WOK;
constexpr int KVB = 5120;
constexpr int OFF_O = OFF_KV + 4 * KVB;
constexpr int OFF_Q = OFF_O + 1024;
constexpr int OFF_S = OFF_O + 3072;
constexpr int OFF_SR = OFF_S + 1536;
constexpr int OFF_LT = OFF_SR + 1280;
constexpr int OFF_BAR = OFF_LT + 512;
constexpr int SMEM = OFF_BAR + 256;
static_assert(SMEM <= 232448, "smem");
constexpr int MB_S = OFF_BAR, MB_O = OFF_BAR + 8, MB_X = OFF_BAR + 16;
constexpr int MB_K = OFF_BAR + 128, MB_V = MB_K + 16, MB_Q = MB_K + 32, MB_R = MB_K + 48;
constexpr int SC_IN = OFF_BAR + 64;
constexpr int SC_MX = OFF_S;
constexpr int SC_TW = OFF_BAR + 48;
constexpr int SC_W = OFF_BAR + 96;
constexpr int WOS = 448;
enum { B_MEM0 = 1, B_QK, B_SL, B_V, B_O, B_RED, B_X, B_C, B_H, B_MEM1, B_A, B_G, B_E };
#ifndef NQ1
#define NQ1 14
#endif
#ifndef NQ0
#define NQ0 8
#endif
#ifndef NP0
#define NP0 5
#endif
#ifndef NWO
#define NWO 5
#endif
#ifndef NWP
#define NWP 4
#endif
#ifndef NB0
#define NB0 2
#endif
#ifndef BBS
#define BBS 100
#endif
#ifndef VSYNC
#define VSYNC 0
#endif
#ifndef XPOS
#define XPOS 0
#endif
#ifndef XPD
#define XPD 300
#endif
#ifndef WOF
#define WOF 0
#endif
#ifndef XBYTES
#define XBYTES 36864
#endif
#ifndef NRT
#define NRT 7
#endif
#ifndef NRF
#define NRF 2
#endif
#ifndef NPM0
#define NPM0 2
#endif
#ifndef NPM1
#define NPM1 2
#endif
#ifndef RSYNC
#define RSYNC 1
#endif
#ifndef PFK
#define PFK 1
#endif
#ifndef PA0
#define PA0 3
#endif
#ifndef PA1
#define PA1 0
#endif
#ifndef PB0
#define PB0 7
#endif
#ifndef PB1
#define PB1 5
#endif
#ifndef PQE
#define PQE 1
#endif
#ifndef XT
#define XT 38
#endif
static_assert(NPM0 >= 2 && NPM1 >= 2, "the K / V blocks live in the last two k-steps of Wo");
}

#ifndef CHAIN_TIMING
#define CHAIN_TIMING 0
#endif
#if CHAIN_TIMING
#ifndef TR0
#define TR0 41
#endif
#ifndef TSMASK
#define TSMASK 0xffff
#endif
#define TSV(i, v) do { if ((TSMASK >> (i)) & 1) asm volatile("st.shared.u32 [%0+%1], %2;" :: "r"(tsb), "n"((i) * 4), "r"(v) : "memory"); } while (0)
#define TS(i) TSV(i, clk32())
#define TS_SETUP() const uint32_t tsb = sb + ((s == TR0 || s == TR0 + 1) ? OFF_BAR + 128 + ((s - TR0) * 12 + warp) * 48 : OFF_SR + 1152)
#else
#define TS(i)
#define TSV(i, v)
#define TS_SETUP()
#endif
#ifndef POLL_DELAY
#define POLL_DELAY 620
#endif
#ifndef XN
#define XN 40
#endif
#ifndef PF0
#define PF0 8
#endif
#ifndef PFS
#define PFS 3
#endif
#ifndef XDELAY
#define XDELAY 0
#endif
#ifndef NOKM
#define NOKM 0
#endif
#ifndef PFX
#define PFX 3
#endif
#ifndef NVE
#define NVE 8
#endif
#ifndef VET
#define VET 19
#endif
#ifndef MEMFIRST
#define MEMFIRST 0
#endif
#ifndef PM1
#define PM1 1
#endif
#ifndef GD1
#define GD1 30
#endif
#ifndef GD2
#define GD2 150
#endif
#ifndef CEARLY
#define CEARLY 0
#endif
#ifndef NPL
#define NPL 2
#endif
#ifndef NP1
#define NP1 (NQ1 < 6 ? NQ1 : 6)
#endif
#ifndef PF2
#define PF2 0
#endif
#ifndef PFACC
#define PFACC 1
#endif
template <int V> using IC = std::integral_constant<int, V>;
__device__ __forceinline__ uint32_t clk_v() { uint64_t c; asm volatile("mov.u64 %0, %%clock64;" : "=l"(c) :: "memory"); return (uint32_t)c; }
__device__ __forceinline__ int fresh(int x) { int y; asm volatile("shfl.sync.bfly.b32 %0, %1, 0, 0x1f, 0xffffffff;" : "=r"(y) : "r"(x)); return y; }
#define SFENCE2(x, d) asm volatile("{\n.reg .pred p;\nsetp.eq.u32 p, %0, 0x7fffffff;\n@p st.shared.u32 [%0], %1;\n}" :: "r"(x), "r"(d) : "memory")
#define SFENCE(x) asm volatile("{\n.reg .pred p;\nsetp.eq.u32 p, %0, 0x7fffffff;\n@p st.shared.u32 [%0], %0;\n}" :: "r"(x) : "memory")
template <int I> __device__ __forceinline__ void bbfence(uint32_t x) {
  asm volatile("{\n.reg .pred p;\nsetp.eq.u32 p, %0, %1;\nL_%=:\n@p st.volatile.shared.u32 [%0], %0;\n@p bra.uni L_%=;\n}" :: "r"(x), "n"(4 * I) : "memory");
}
__device__ __forceinline__ float uniform_f(float x) { return __uint_as_float(__reduce_max_sync(0xffffffffu, __float_as_uint(x))); }

__device__ __forceinline__ void mma16816h(float (&d)[4], const uint32_t (&a)[4], uint32_t b0, uint32_t b1) {
  asm volatile("mma.sync.aligned.m16n8k16.row.col.f32.f16.f16.f32 {%0,%1,%2,%3}, {%4,%5,%6,%7}, {%8,%9}, {%0,%1,%2,%3};"
               : "+f"(d[0]), "+f"(d[1]), "+f"(d[2]), "+f"(d[3]) : "r"(a[0]), "r"(a[1]), "r"(a[2]), "r"(a[3]), "r"(b0), "r"(b1));
}
__device__ __forceinline__ void mma1688(float (&d)[4], uint32_t a0, uint32_t a1, uint32_t b0) {
  asm volatile("mma.sync.aligned.m16n8k8.row.col.f32.bf16.bf16.f32 {%0,%1,%2,%3}, {%4,%5}, {%6}, {%0,%1,%2,%3};"
               : "+f"(d[0]), "+f"(d[1]), "+f"(d[2]), "+f"(d[3]) : "r"(a0), "r"(a1), "r"(b0));
}
template <int OFF16, int ACC> __device__ __forceinline__ void wgmma_rs32h(float (&d)[16], const uint32_t (&a)[4], uint32_t dlo) {
  asm volatile("{\n.reg .pred p;\n.reg .b32 t;\n.reg .b64 db;\nsetp.ne.b32 p, %22, 0;\nadd.u32 t, %20, %21;\nmov.b64 db, {t, 0x40000040};\n"
    "wgmma.mma_async.sync.aligned.m64n32k16.f32.f16.f16 {%0,%1,%2,%3,%4,%5,%6,%7,%8,%9,%10,%11,%12,%13,%14,%15}, {%16,%17,%18,%19}, db, p, 1, 1, 0;\n}\n"
    : "+f"(d[0]), "+f"(d[1]), "+f"(d[2]), "+f"(d[3]), "+f"(d[4]), "+f"(d[5]), "+f"(d[6]), "+f"(d[7]), "+f"(d[8]), "+f"(d[9]), "+f"(d[10]), "+f"(d[11]),
      "+f"(d[12]), "+f"(d[13]), "+f"(d[14]), "+f"(d[15])
    : "r"(a[0]), "r"(a[1]), "r"(a[2]), "r"(a[3]), "r"(dlo), "n"(OFF16), "n"(ACC));
}
template <int IMM> __device__ __forceinline__ void stsm_x4_t_i(uint32_t a, uint32_t r0, uint32_t r1, uint32_t r2, uint32_t r3) {
  asm volatile("stmatrix.sync.aligned.m8n8.x4.trans.shared.b16 [%0+%5], {%1,%2,%3,%4};" :: "r"(a), "r"(r0), "r"(r1), "r"(r2), "r"(r3), "n"(IMM) : "memory");
}
template <int IMM> __device__ __forceinline__ void stsm_x2_t_i(uint32_t a, uint32_t r0, uint32_t r1) {
  asm volatile("stmatrix.sync.aligned.m8n8.x2.trans.shared.b16 [%0+%3], {%1,%2};" :: "r"(a), "r"(r0), "r"(r1), "n"(IMM) : "memory");
}
template <int IMM> __device__ __forceinline__ void st_async_b32_i(uint32_t a, uint32_t x, uint32_t mb) {
  asm volatile("st.async.weak.shared::cluster.mbarrier::complete_tx::bytes.b32 [%0+%3], %1, [%2];" :: "r"(a), "r"(x), "r"(mb), "n"(IMM) : "memory");
}
template <int IMM> __device__ __forceinline__ void ld_relaxed_v4_if(uint4& v, const void* p, uint32_t c) {
  asm volatile("{\n.reg .pred p;\nsetp.ne.u32 p, %6, 0;\n@p ld.relaxed.gpu.global.v4.u32 {%0,%1,%2,%3}, [%4+%5];\n}"
               : "+r"(v.x), "+r"(v.y), "+r"(v.z), "+r"(v.w) : "l"(p), "n"(IMM), "r"(c) : "memory");
}
template <int IMM> __device__ __forceinline__ void ldsm_x2_i(uint32_t (&r)[2], uint32_t a) {
  asm volatile("ldmatrix.sync.aligned.m8n8.x2.shared.b16 {%0,%1}, [%2+%3];" : "=r"(r[0]), "=r"(r[1]) : "r"(a), "n"(IMM) : "memory");
}
template <int IMM> __device__ __forceinline__ uint32_t ldsm_x1_t_i(uint32_t a) {
  uint32_t r; asm volatile("ldmatrix.sync.aligned.m8n8.x1.trans.shared.b16 {%0}, [%1+%2];" : "=r"(r) : "r"(a), "n"(IMM) : "memory"); return r;
}
template <int IMM> __device__ __forceinline__ uint32_t lds32_i(uint32_t a) {
  uint32_t v; asm volatile("ld.shared.u32 %0, [%1+%2];" : "=r"(v) : "r"(a), "n"(IMM) : "memory"); return v;
}
__device__ __forceinline__ void sts32(uint32_t a, uint32_t v) { asm volatile("st.shared.u32 [%0], %1;" :: "r"(a), "r"(v) : "memory"); }
__device__ __forceinline__ uint32_t pack_f16(float lo, float hi) {
  uint32_t d; asm("cvt.rn.f16x2.f32 %0, %1, %2;" : "=r"(d) : "f"(hi), "f"(lo)); return d;
}
__device__ __forceinline__ uint32_t amax_bf2(uint32_t a, uint32_t b) { uint32_t d; asm("max.xorsign.abs.bf16x2 %0, %1, %2;" : "=r"(d) : "r"(a), "r"(b)); return d; }
__device__ __forceinline__ uint32_t amax_h2(uint32_t a, uint32_t b) { uint32_t d; asm("max.xorsign.abs.f16x2 %0, %1, %2;" : "=r"(d) : "r"(a), "r"(b)); return d; }
__device__ __forceinline__ uint32_t amax_fold(uint32_t m) { return __reduce_max_sync(0xffffffffu, max(m & 0x7fffu, (m >> 16) & 0x7fffu)); }
__device__ __forceinline__ int wscale_exp(uint32_t m) { return min(141 - (int)(m >> 7), 100); }
__device__ __forceinline__ float exp2i(int e) { return __uint_as_float((uint32_t)(e + 127) << 23); }
__device__ __forceinline__ uint32_t bf2_to_h2(uint32_t w, float sc) { return pack_f16(bf_lo(w) * sc, bf_hi(w) * sc); }
__device__ __forceinline__ void bf2_to_h2_inplace(uint32_t& w, uint32_t sc2) {
  asm volatile("{\n.reg .b32 t, lo, hi;\nmul.rn.bf16x2 t, %0, %1;\nshl.b32 lo, t, 16;\nand.b32 hi, t, 0xffff0000;\ncvt.rn.f16x2.f32 %0, hi, lo;\n}" : "+r"(w) : "r"(sc2));
}
__device__ __forceinline__ void prefetch_l2(const void* p, uint32_t bytes) { asm volatile("cp.async.bulk.prefetch.L2.global [%0], %1;" :: "l"(p), "r"(bytes) : "memory"); }
__device__ __forceinline__ void prefetch_tma_2d(const CUtensorMap* tm, int c0, int c1) {
  asm volatile("cp.async.bulk.prefetch.tensor.2d.L2.global [%0, {%1, %2}];" :: "l"(tm), "r"(c0), "r"(c1) : "memory");
}
__host__ __device__ constexpr uint32_t acc_voff(int v) { return v < 4 ? v * 1024u : (v == 4 ? 128u : 3072u + 128u); }
__device__ __forceinline__ int unit28(int i) { return i == 3 ? 54 : 14 * i; }
__device__ __forceinline__ int unit24(int i) { return i < 2 ? 48 - 6 * i : 56 + 6 * i; }
__device__ __forceinline__ uint32_t acc_step(int s) { return (s >> 1) * 32768 + (s & 1) * 512; }
__device__ __forceinline__ uint32_t acc_lane(int i, int lane) { return ((lane >> 3) & 1) * 256 + (lane >> 4) * 4096 + i * 8192 + (lane & 7) * 16; }

__device__ __forceinline__ uint32_t ld_acquire_u32(const void* p) {
  uint32_t v; asm volatile("ld.acquire.gpu.global.u32 %0, [%1];" : "=r"(v) : "l"(p) : "memory"); return v;
}
template <int R> __device__ __forceinline__ void ln_rows(const uint2 (&xw)[R][5], int row0, int lane, bf16* __restrict__ xn, uint2* __restrict__ xh) {
  float v[R][20], s[R], q[R];
#pragma unroll
  for (int r = 0; r < R; r++) {
    s[r] = 0.f; q[r] = 0.f;
#pragma unroll
    for (int i = 0; i < 5; i++) { v[r][4 * i] = bf_lo(xw[r][i].x); v[r][4 * i + 1] = bf_hi(xw[r][i].x); v[r][4 * i + 2] = bf_lo(xw[r][i].y); v[r][4 * i + 3] = bf_hi(xw[r][i].y); }
#pragma unroll
    for (int i = 0; i < 5; i++) s[r] += (v[r][4 * i] + v[r][4 * i + 1]) + (v[r][4 * i + 2] + v[r][4 * i + 3]);
  }
#pragma unroll
  for (int o = 16; o; o >>= 1)
#pragma unroll
    for (int r = 0; r < R; r++) s[r] += __shfl_xor_sync(0xffffffffu, s[r], o);
#pragma unroll
  for (int r = 0; r < R; r++) {
    s[r] *= 1.f / cfg::DM;
#pragma unroll
    for (int i = 0; i < 10; i++) { const float d = v[r][2 * i] - s[r], e = v[r][2 * i + 1] - s[r]; q[r] += d * d + e * e; }
  }
#pragma unroll
  for (int o = 16; o; o >>= 1)
#pragma unroll
    for (int r = 0; r < R; r++) q[r] += __shfl_xor_sync(0xffffffffu, q[r], o);
#pragma unroll
  for (int r = 0; r < R; r++) {
    const int row = row0 + r;
    const float mb = bf16r(s[r]), var = bf16r(q[r] * (1.f / cfg::DM));
    float sd; asm("sqrt.approx.f32 %0, %1;" : "=f"(sd) : "f"(bf16r(var + 1e-5f)));
    const float inv = rcpf(bf16r(sd));
#pragma unroll
    for (int i = 0; i < 5; i++) {
      float y[4];
#pragma unroll
      for (int e = 0; e < 4; e++) y[e] = v[r][4 * i + e] - mb;
      bf16r2(y[0], y[1]); bf16r2(y[2], y[3]);
      const uint32_t w0 = pack_bf16(y[0] * inv, y[1] * inv), w1 = pack_bf16(y[2] * inv, y[3] * inv);
      *(uint2*)(xn + (size_t)row * cfg::DM + i * 128 + lane * 4) = make_uint2(w0, w1);
      if (xh) xh[(((size_t)(row >> 5) * 10 + 2 * i + (lane >> 4)) * 32 + (row & 31)) * 16 + ((((lane >> 1) & 7) ^ (row & 7)) << 1) + (lane & 1)] =
          make_uint2(pack_f16(bf_lo(w0), bf_hi(w0)), pack_f16(bf_lo(w1), bf_hi(w1)));
    }
  }
}

__global__ void __cluster_dims__(3, 1, 1) __launch_bounds__(384, 1) chain_kernel(const ChainArgs a, const __grid_constant__ CUtensorMap tmWq,
    const __grid_constant__ CUtensorMap tmWk, const __grid_constant__ CUtensorMap tmWv, const __grid_constant__ CUtensorMap tmWo) {
  using namespace ch;
  extern __shared__ __align__(1024) unsigned char smem_raw[];
  const uint32_t sb = smem_u32(smem_raw);
  const int warp = __shfl_sync(0xffffffffu, (int)threadIdx.x >> 5, 0);
  const int cta = blockIdx.x, h = cta / 3, j = cta % 3;
  unsigned char* const arena = a.arena;
  if (sb & 1023u) __trap();
  asm volatile("griddepcontrol.launch_dependents;");
  TL_BEGIN(a.tl);
  LITE(cta == 0 && threadIdx.x == 0, (a.tl >= 12) * 4);
#ifdef TIMELINE
  const unsigned long long g_tl0 = gtime();
#define PT(i) TLW((a.tl >= 12) * 128 + 64 + (i))
#else
#define PT(i)
#endif
  const int col0 = j == 0 ? 0 : (j == 1 ? 224 : 432);
  auto stage_w = [&](const CUtensorMap* tm, uint32_t dst, uint32_t mb, int half) {
    mbar_expect_tx(mb + 8 * half, 40960);
    tma_load_2d(dst + half * 40960, tm, h * cfg::DH + j * 64, half * 320, mb + 8 * half);
    tma_load_2d(dst + half * 40960 + 20480, tm, h * cfg::DH + j * 64, half * 320 + 160, mb + 8 * half);
  };
  if (threadIdx.x == 256) {
    for (int i = 0; i < 9; i++) mbar_init(sb + MB_K + 8 * i, 1);
    mbar_init(sb + MB_S, 1); mbar_init(sb + MB_O, 1); mbar_init(sb + MB_X, 1);
    asm volatile("fence.mbarrier_init.release.cluster;" ::: "memory");
    for (int i = 0; i < 2; i++) { stage_w(&tmWk, sb + OFF_WQ, sb + MB_K, i); stage_w(&tmWv, sb + OFF_WO, sb + MB_V, i); }
    sts32(sb + SC_W, 0); sts32(sb + SC_W + 4, 0); sts32(sb + SC_W + 8, 0); sts32(sb + SC_IN + 12, 0); sts32(sb + SC_IN + 20, 0); sts32(sb + SC_TW + 4, 99);
    mbar_expect_tx(sb + MB_S, 1280); mbar_expect_tx(sb + MB_O, 2048);
  }
  __syncthreads();
  asm volatile("barrier.cluster.arrive.relaxed.aligned;" ::: "memory");
  const uint32_t d1 = mapa_u32(sb, (j + 1) % 3) - sb, d2 = mapa_u32(sb, (j + 2) % 3) - sb;

  if (warp >= 8) {
    asm volatile("setmaxnreg.dec.sync.aligned.u32 40;");
    const int lane = fresh(threadIdx.x & 31), hw = warp - 8, ht = hw * 32 + lane;
    const bool lead = ht == 0;
    auto stage_wo = [&](int i) {
      mbar_expect_tx(sb + MB_R + 8 * i, 64 * WOS);
      tma_load_2d(sb + OFF_WO + i * 64 * WOS, &tmWo, col0, h * cfg::DH + ((i + j) % 3) * 64, sb + MB_R + 8 * i);
    };
    const unsigned char* xg = (const unsigned char*)a.xh;
    auto issue_x = [&](int s) { mbar_expect_tx(sb + MB_X, 40960); bulk_g2s(sb + OFF_X, xg + (size_t)s * 40960, 40960, sb + MB_X); };
    uint4 v[5];
#pragma unroll
    for (int i = 0; i < 5; i++) { const int c = ht + 128 * i; v[i] = ld_relaxed_v4(a.mem0 + (c & 7) * cfg::DM + (c >> 3) * 8); }
    if (hw == 2) {
      asm volatile("griddepcontrol.wait;" ::: "memory");
      if (lane == 0) { if (cta == 0) st_relaxed_u32(a.go, 1); issue_x(0); }
      PT(0);
    }
    if (hw == 0) {
      bar_sync(B_QK, 160);
      if (lane == 0) {
        stage_w(&tmWq, sb + OFF_WQ, sb + MB_Q, 0);
        if (PF2) { prefetch_tma_2d(&tmWq, h * cfg::DH + j * 64, 320); prefetch_tma_2d(&tmWq, h * cfg::DH + j * 64, 480); }
      }
      bar_sync(B_SL, 160); if (lane == 0) stage_w(&tmWq, sb + OFF_WQ, sb + MB_Q, 1);
    }
    if (hw == 1) {
      bar_sync(B_V, 160);
      if (lane == 0) {
        stage_wo(0);
        if (PF2) { prefetch_tma_2d(&tmWo, col0, h * cfg::DH + ((1 + j) % 3) * 64); prefetch_tma_2d(&tmWo, col0, h * cfg::DH + ((2 + j) % 3) * 64); }
      }
      bar_sync(B_O, 160); if (lane == 0) { stage_wo(1); stage_wo(2); }
    }
    __syncwarp();
    {
      uint32_t m = 0;
#pragma unroll
      for (int i = 0; i < 5; i++) {
        m = amax_bf2(amax_bf2(m, amax_bf2(v[i].x, v[i].y)), amax_bf2(v[i].z, v[i].w));
      }
      m = amax_fold(m);
      if (lane == 0) sts32(sb + SC_MX + hw * 4, m);
      bar_sync(B_H, 128);
      const uint4 mm = lds128(sb + SC_MX);
      const int se = max(wscale_exp(max(max(mm.x, mm.y), max(mm.z, mm.w))), -100);
      const float sc = exp2i(se);
#pragma unroll
      for (int i = 0; i < 5; i++) {
        const int c = ht + 128 * i, t = c & 7, chn = c >> 3;
        sts128(sb + OFF_MEM + chn * 128 + ((t ^ (2 * (chn & 3))) << 4), bf2_to_h2(v[i].x, sc), bf2_to_h2(v[i].y, sc), bf2_to_h2(v[i].z, sc), bf2_to_h2(v[i].w, sc));
      }
      if (lead) { sts32(sb + SC_IN, __float_as_uint(exp2i(-se))); sts32(sb + SC_IN + 4, 0x7800u); }
    }
    if (hw == 0) PT(11);
    {
      const uint32_t p0 = sb + OFF_WQ + hw * 2048 + lane * 16;
      uint32_t m = 0;
#pragma unroll 1
      for (int i = 0; i < 10; i++) {
        if (i == 0 || i == 5) mbar_wait(sb + MB_Q + (i ? 8 : 0), 0);
        uint32_t r[4][4];
        static_for<0, 4>([&](auto K) { ldsm_x4_i<K.value * 512>(r[K.value], p0 + i * 8192); });
#pragma unroll
        for (int k = 0; k < 4; k++) m = amax_bf2(amax_bf2(m, amax_bf2(r[k][0], r[k][1])), amax_bf2(r[k][2], r[k][3]));
      }
      if (hw == 0) PT(9);
      m = amax_fold(m);
      if (lane == 0) asm volatile("red.shared.max.u32 [%0], %1;" :: "r"(sb + SC_W + 8), "r"(m) : "memory");
      bar_sync(B_H, 128);
      const uint32_t sc = (uint32_t)(wscale_exp(lds32_i<SC_W + 8>(sb)) + 127) * 0x00800080u;
      uint32_t r[4][4];
      static_for<0, 2>([&](auto K) { ldsm_x4_i<K.value * 512>(r[K.value], p0); });
      auto cvt = [&](uint32_t (&x)[4], uint32_t p) { bf2_to_h2_inplace(x[0], sc); bf2_to_h2_inplace(x[1], sc); bf2_to_h2_inplace(x[2], sc); bf2_to_h2_inplace(x[3], sc); stsm_x4(p, x[0], x[1], x[2], x[3]); };
#pragma unroll 1
      for (int i = 0; i < 10; i++) {
        const uint32_t p = p0 + i * 8192;
        ldsm_x4_i<1024>(r[2], p); ldsm_x4_i<1536>(r[3], p);
        cvt(r[0], p); cvt(r[1], p + 512);
        ldsm_x4_i<8192>(r[0], p); ldsm_x4_i<8192 + 512>(r[1], p);
        cvt(r[2], p + 1024); cvt(r[3], p + 1536);
      }
    }
    if (hw == 0) PT(10);
    bar_sync(0, 384);
    if (hw == 3) {
      const uint32_t eye = ((lane >> 3) == (lane & 3)) ? ((lane & 4) ? 0x3f800000u : 0x3f80u) : 0u;
      sts128(sb + OFF_LT + lane * 16, eye, eye, (lane & 2) * 64 + (lane >> 2) * 16 + (lane & 1) * 8, 0u);
      sts64(sb + OFF_S + 1280 + lane * 8, 0u, 0u);
    }
    if (lead) st_relaxed_u32(arena + AR_TAB + cta * 4, 0x80000000u | (lds32_i<SC_W>(sb) << 15) | lds32_i<SC_W + 4>(sb));
    asm volatile("barrier.cluster.wait.aligned;" ::: "memory");
    bar_sync(B_MEM0, 256); bar_sync(B_MEM1, 256);
    {
      uint32_t v0, v1, v2; int spin = 0;
      do {
        v0 = ld_relaxed_u32(arena + AR_TAB + lane * 4); v1 = ld_relaxed_u32(arena + AR_TAB + 128 + lane * 4); v2 = ld_relaxed_u32(arena + AR_TAB + 256 + lane * 4);
      } while (__any_sync(0xffffffffu, ((v0 & v1 & v2) >> 31) == 0) && ++spin < SPIN_LIMIT);
      const uint32_t mv = (max(max(v0, v1), v2) >> 15) & 0x7fffu, mo = max(max(v0 & 0x7fffu, v1 & 0x7fffu), v2 & 0x7fffu);
      sts32(sb + SC_IN + 8 + (lane & 1) * 16, 15 - ((__reduce_max_sync(0xffffffffu, mv) >> 7) + (__reduce_max_sync(0xffffffffu, mo) >> 7) - 252 + 22));
    }

    auto store_kv = [&](int s) {
      const size_t o = ((size_t)s * 96 + cta) * KVB; const uint32_t src = sb + OFF_KV + (s & 1) * (2 * KVB);
      fence_proxy_async(); bulk_s2g(a.kg + o, src, KVB); bulk_s2g(a.vg + o, src + KVB, KVB); bulk_commit();
    };
    const int cb28 = unit28(hw), du = (unit24(hw) - cb28) * 128;
    uint32_t n16 = lane * 16, hist = 0;
    const uint32_t us1 = sb + d1 + OFF_SR + 256 + (hw >> 1) * 512 + (hw & 1) * 128, us2 = sb + d2 + OFF_SR + (hw >> 1) * 512 + (hw & 1) * 128;
    const uint32_t uo1 = sb + d1 + OFF_O + 2048 + hw * 256, uo2 = sb + d2 + OFF_O + 1024 + hw * 256;
#ifdef STEPCLK
    if (lead) a.dbg[96 * 300 + cta * 2] = clk32();
#endif
#ifdef TIMELINE
    if (cta == 0 && lead) { g_tl2[(a.tl >= 12) * 128 + 0] = clock64(); g_tl2[(a.tl >= 12) * 128 + 1] = gtime(); }
#endif
#pragma unroll 1
    for (int s = 0; s < cfg::NSEG; s++) {
      TS_SETUP();
      const bool last = s == cfg::NSEG - 1;
      if (n16 == 0) {
        if (hw == 2 && !last) issue_x(s + 1);
        if (hw == 0 && (s & 3) == 1 && s > 1) st_relaxed_u32(arena + (prog_off(h, j) + lds32_i<SC_IN + 12>(sb)), s - 1);
        if (hw == 0 && s > 0) store_kv(s - 1);
        if (PFX && hw == 3 && cta < 80 && s + PFX < cfg::NSEG) prefetch_l2(xg + (size_t)(s + PFX) * 40960 + cta * 512, 512);
        if (PFACC && hw == 1 && s + PFACC < cfg::NSEG - 1)
          asm volatile("prefetch.global.L2 [%0];" :: "l"(arena + (AR_ACC + acc_step(s + PFACC) + acc_lane(cta / 24, (cta & 3) * 8) + acc_voff((cta % 24) >> 2))) : "memory");
      }
      __syncwarp();
      if (last) break;
      const uint32_t kv = (s & 1) * (2 * KVB);
      n16 = fresh(n16);
      uint32_t kb0[4], kb1[4];
      { const uint32_t ka = n16 + (n16 & 384) * 4 + (sb + kv + hw * 128); ldsm_x4_i<OFF_KV>(kb0, ka); ldsm_x4_i<OFF_KV + 2560>(kb1, ka); }
      TS(1);
      bar_sync(B_QK, 384);
      {
        uint32_t q0[4], q1[4], q2[4], q3[4];
        float sa[4] = {0, 0, 0, 0}, sc2[4] = {0, 0, 0, 0};
        ldsm_x4_i<OFF_Q>(q0, n16 + sb); ldsm_x4_i<OFF_Q + 1024>(q2, n16 + sb); ldsm_x4_i<OFF_Q + 512>(q1, n16 + sb);
        bar_arrive(B_A, 288);
        ldsm_x4_i<OFF_Q + 1536>(q3, n16 + sb);
        mma16816(sa, q0[0], q0[1], q0[2], q0[3], kb0[0], kb0[1]);
        mma16816(sc2, q2[0], q2[1], q2[2], q2[3], kb1[0], kb1[1]);
        mma16816(sa, q1[0], q1[1], q1[2], q1[3], kb0[2], kb0[3]);
        mma16816(sc2, q3[0], q3[1], q3[2], q3[3], kb1[2], kb1[3]);
        const float x0 = (sa[0] + sa[2]) + (sc2[0] + sc2[2]), x1 = (sa[1] + sa[3]) + (sc2[1] + sc2[3]);
        const uint32_t xp = pack_bf16(x0, x1);
        st_async_b32_i<0>((n16 >> 2) + us1, xp, sb + MB_S + d1);
        st_async_b32_i<0>((n16 >> 2) + us2, xp, sb + MB_S + d2);
        stsm_x2(n16 + (sb + OFF_S + hw * 256), __float_as_uint(x0), __float_as_uint(x1));
      }
      TS(3);
      uint32_t v0[4], v1[4], vm0, vm1;
      const uint32_t uv = sb + kv + hw * 1280;
      ldsm_x4_t_i<OFF_KV + KVB>(v0, n16 + uv); ldsm_x4_t_i<OFF_KV + KVB + 640>(v1, n16 + uv);
      bar_sync(B_SL, 256);
      float t0[4], t1[4], t2[4];
      { uint32_t x[4]; ldsm_x4_i<OFF_S>(x, n16 + sb); t0[0] = __uint_as_float(x[0]); t0[1] = __uint_as_float(x[1]); t0[2] = __uint_as_float(x[2]); t0[3] = __uint_as_float(x[3]); }
      { uint32_t x[4]; ldsm_x4_i<OFF_S + 512>(x, n16 + sb); t1[0] = __uint_as_float(x[0]); t1[1] = __uint_as_float(x[1]); t1[2] = __uint_as_float(x[2]); t1[3] = __uint_as_float(x[3]); }
      { uint32_t x[4]; ldsm_x4_i<OFF_S + 1024>(x, n16 + sb); t2[0] = __uint_as_float(x[0]); t2[1] = __uint_as_float(x[1]); t2[2] = __uint_as_float(x[2]); t2[3] = __uint_as_float(x[3]); }
      mbar_spin(sb + MB_S, s & 1);
      TS(4);
      uint2 xo;
      {
        uint32_t r0[4], r1[4], r2[2];
        ldsm_x4_i<OFF_SR>(r0, n16 + sb); ldsm_x4_i<OFF_SR + 512>(r1, n16 + sb); ldsm_x2_i<OFF_SR + 1024>(r2, n16 + sb);
        SFENCE(n16);
        const uint2 eye = lds64_i<OFF_LT>(n16 + sb);
        mma16816(t0, r0[0], r0[1], r0[2], r0[3], eye.x, eye.y);
        mma16816(t1, r1[0], r1[1], r1[2], r1[3], eye.x, eye.y);
        mma1688(t2, r2[0], r2[1], eye.x);
        bar_sync(B_V, 256);
        vm0 = ldsm_x1_t_i<OFF_KV + KVB + 512>(n16 + uv); vm1 = ldsm_x1_t_i<OFF_KV + KVB + 1152>(n16 + uv);
        SFENCE(n16);
        xo = lds64_i<OFF_LT + 8>(n16 + sb);
      }
      float sc[10] = {t0[0], t0[1], t0[2], t0[3], t1[0], t1[1], t1[2], t1[3], t2[0] + t2[2], t2[1] + t2[3]};
      const float cs = 0.07216878364870322f * 1.4426950408889634f;
      float mx = fmaxf(fmaxf(fmaxf(sc[0], sc[1]), fmaxf(sc[2], sc[3])), fmaxf(fmaxf(sc[4], sc[5]), fmaxf(sc[6], sc[7])));
      mx = fmaxf(mx, fmaxf(sc[8], sc[9]));
      {
        const float m1 = __shfl_xor_sync(0xffffffffu, mx, 1), m2 = __shfl_xor_sync(0xffffffffu, mx, 2), m3 = __shfl_xor_sync(0xffffffffu, mx, 3);
        mx = fmaxf(fmaxf(mx, m1), fmaxf(m2, m3));
      }
      const float mo = fmaf(mx, -cs, __uint_as_float(xo.x));
      auto ex = [&](int i) -> uint32_t { float x, y;
        asm volatile("ex2.approx.ftz.f32 %0, %1;" : "=f"(x) : "f"(fmaf(sc[i], cs, mo))); asm volatile("ex2.approx.ftz.f32 %0, %1;" : "=f"(y) : "f"(fmaf(sc[i + 1], cs, mo)));
        return pack_bf16(x, y); };
      float oa[4] = {0, 0, 0, 0}, ob[4] = {0, 0, 0, 0}, oc[4] = {0, 0, 0, 0}, od[4] = {0, 0, 0, 0}, rs[4] = {0, 0, 0, 0};
      const uint32_t ones = 0x3f803f80u;
      const uint32_t p4 = ex(8);
      if (MEMFIRST) { mma1688(rs, p4, 0u, ones); mma1688(oa, p4, 0u, vm0); mma1688(ob, p4, 0u, vm1); }
      const uint32_t p0 = ex(0), p1 = ex(2), p2 = ex(4), p3 = ex(6);
      TS(5);
      mma16816(rs, p0, p2, p1, p3, ones, ones);
      mma16816(oa, p0, p2, p1, p3, v0[0], v0[1]);
      mma16816(oc, p0, p2, p1, p3, v0[2], v0[3]);
      mma16816(ob, p0, p2, p1, p3, v1[0], v1[1]);
      mma16816(od, p0, p2, p1, p3, v1[2], v1[3]);
      if (!MEMFIRST) { mma1688(rs, p4, 0u, ones); mma1688(oa, p4, 0u, vm0); mma1688(ob, p4, 0u, vm1); }
      const float inv = rcpf(rs[0] + rs[2]) * __uint_as_float(xo.y);
      {
        const uint32_t y0 = pack_bf16((oa[0] + oc[2]) * inv, (oa[1] + oc[3]) * inv), y1 = pack_bf16((ob[0] + od[2]) * inv, (ob[1] + od[3]) * inv);
        st_async_v2_i<0>(xo.x + uo1, y0, y1, sb + MB_O + d1);
        st_async_v2_i<0>(xo.x + uo2, y0, y1, sb + MB_O + d2);
        sts64_i<OFF_O>(xo.x + (sb + hw * 256), y0, y1);
      }
      bar_arrive(B_O, 384);
      TS(6);
      if (hw == 0) bulk_wait<0>();
      mbar_expect_tx_if(n16 == 0 && hw == 3, sb + MB_S, 1280);
      n16 = fresh(n16);
      const int ln = n16 >> 4;
      auto mslot = [&](int c) -> uint32_t { return sb + OFF_MEM + c * 128 + (((ln >> 2) ^ (2 * (c & 3))) << 4); };
      const int lq = ln & 3;
      const uint32_t ma = mslot(cb28 + lq), mb_ = mslot(cb28 + (lq >> 1)) + (lq & 1) * 8;
      const unsigned char* gp = arena + (AR_ACC + acc_lane(hw, ln) + acc_step(s));
      const bool odd = ln & 1;
      const uint32_t delay = a.delay + ((hist & 2) ? a.margin : 0);
      SFENCE(ma);
      uint32_t tw;
      if (hw == 0 && (s & 3) == 0 && a.pubrel) {
        bar_arrive(B_RED, 384);
        asm volatile("fence.acq_rel.gpu;" ::: "memory");
        uint2 t; int sp = 0;
        do { asm volatile("ld.volatile.shared.v2.u32 {%0,%1}, [%2];" : "=r"(t.x), "=r"(t.y) : "r"(sb + SC_TW) : "memory"); } while (__any_sync(0xffffffffu, t.y != (uint32_t)s) && ++sp < SPIN_LIMIT);
        tw = t.x;
      } else {
        bar_sync(B_RED, 384);
        SFENCE(mb_);
        tw = clk_v();
        if (hw == 1) asm volatile("st.volatile.shared.v2.u32 [%0], {%1,%2};" :: "r"(sb + SC_TW), "r"(tw), "r"(s) : "memory");
      }
      TSV(7, tw);
      mbar_expect_tx_if(n16 == 0 && hw == 3, sb + MB_O, 2048);
      while (clk_v() - tw < delay) {}
      TS(8);
      uint4 v[6];
      int spin = 0;
      const uint32_t cm = odd ? 0x5000u : 0u;
      do {
        static_for<0, 6>([&](auto I) { v[I.value] = ld_relaxed_v4_i<acc_voff(I.value)>(gp); });
      } while (__any_sync(0xffffffffu, (~((v[0].w & v[1].w & v[2].w) & (v[3].w & v[4].w & v[5].w)) & cm) != 0) && ++spin < SPIN_LIMIT);
      v[0].w = odd ? v[3].x : v[0].w; v[1].w = odd ? v[3].y : v[1].w; v[2].w = odd ? v[3].z : v[2].w; v[3].w = odd ? 0u : v[3].w;
      sts128_i<0>(ma, v[0].x, v[0].y, v[0].z, v[0].w);
      sts128_i<512>(ma, v[1].x, v[1].y, v[1].z, v[1].w);
      sts128_i<1024>(ma, v[2].x, v[2].y, v[2].z, v[2].w);
      sts128_i<0>(ma + du, v[4].x, v[4].y, v[4].z, v[5].z);
      sts64_i<512>(mb_ + du, v[5].x, v[5].y);
      if (!odd) sts128_i<1536>(mb_, v[3].x, v[3].y, v[3].z, v[3].w);
      hist = (hist * 2 + (spin != 0)) & 0xffffu;
      TSV(11, spin);
#ifdef TIMELINE
      if (hw == 2 && ln == 0) { uint32_t gt; asm volatile("mov.u32 %0, %%globaltimer_lo;" : "=r"(gt)); *(uint4*)(g_step + (((a.tl >= 12) * 64 + s) * 96 + cta) * 4) = make_uint4(gt, spin, clk_v() - tw, tw); }
#endif
      TS(10);
      bar_sync(B_MEM0, 256); bar_sync(B_MEM1, 256);
      uint32_t m = lds32_i<SC_IN + 12>(sb);
      uint32_t m2 = m;
      static_for<0, 3>([&](auto I) { m = amax_h2(amax_h2(amax_h2(amax_h2(m, v[I.value].x), v[I.value].y), v[I.value].z), v[I.value].w); });
      static_for<3, 6>([&](auto I) { m2 = amax_h2(amax_h2(amax_h2(m2, v[I.value].x), v[I.value].y), v[I.value].z); });
      m = amax_fold(amax_h2(amax_h2(m2, v[3].w), m));
      if (n16 == 0) asm volatile("red.shared.max.u32 [%0], %1;" :: "r"(sb + SC_IN + 4 + 16 * ((s + 1) & 1)), "r"(m) : "memory");
    }
    bar_sync(B_RED, 384);
    if (hw == 0 && n16 == 0) {
      store_kv(cfg::NSEG - 1);
      bulk_wait<0>();
      st_release_u32(arena + (prog_off(h, j) + lds32_i<SC_IN + 12>(sb)), cfg::NSEG);
    }
    __syncwarp();
#ifdef STEPCLK
    if (hw == 0 && n16 == 0) a.dbg[96 * 300 + cta * 2 + 1 + (hist >> 20)] = clk32();
#endif
#ifdef TIMELINE
    if (cta == 0 && hw == 0 && n16 == 0) { g_tl2[(a.tl >= 12) * 128 + 2] = clock64(); g_tl2[(a.tl >= 12) * 128 + 3] = gtime(); }
#endif
    TL_END(a.tl);
    asm volatile("barrier.cluster.arrive.relaxed.aligned; barrier.cluster.wait.aligned;" ::: "memory");
  } else {
    asm volatile("setmaxnreg.inc.sync.aligned.u32 232;");
    const int wi = warp & 3, hf = warp >> 2;
    [[maybe_unused]] const int tid = threadIdx.x;
    int lane = fresh(threadIdx.x & 31);
    uint32_t w[40][4], wm = 0;
    uint32_t wqa;
    { const int r8 = lane & 7, mrow = r8 + ((lane >> 4) << 3), mch = 2 * wi + ((lane >> 3) & 1); wqa = sb + mrow * 128 + ((mch ^ r8) << 4); }
    float iw, iq;
#pragma unroll 1
    for (int live = a.dry ? 0 : 1; live < 2; live++) {
      const uint32_t wa = wqa + (hf ? OFF_WO : OFF_WQ);
      wm = 0;
      mbar_wait_if(live, sb + (hf ? MB_V : MB_K), 0);
      static_for<0, 20>([&](auto K) { ldsm_x4_t_i<K.value * 2048>(w[K.value], wa); });
#pragma unroll
      for (int k = 0; k < 20; k++) wm = amax_bf2(amax_bf2(wm, amax_bf2(w[k][0], w[k][1])), amax_bf2(w[k][2], w[k][3]));
      SFENCE2(wa, wm);
      if (warp == 0 && live) PT(1);
      if (live) bar_arrive(hf ? B_V : B_QK, 160);
      mbar_wait_if(live, sb + (hf ? MB_V : MB_K) + 8, 0);
      static_for<20, 40>([&](auto K) { ldsm_x4_t_i<K.value * 2048>(w[K.value], wa); });
#pragma unroll
      for (int k = 20; k < 40; k++) wm = amax_bf2(amax_bf2(wm, amax_bf2(w[k][0], w[k][1])), amax_bf2(w[k][2], w[k][3]));
      SFENCE2(wa, wm);
      if (warp == 4 && live) PT(2);
      if (live) bar_arrive(hf ? B_O : B_SL, 160);
      SFENCE(wa);
      const uint32_t m = amax_fold(wm);
      if (hf && live) asm volatile("red.shared.max.u32 [%0], %1;" :: "r"(sb + SC_W), "r"(m) : "memory");
      const int e = wscale_exp(m);
      const uint32_t sc = (uint32_t)(e + 127) * 0x00800080u; iw = exp2i(-e);
#pragma unroll
      for (int k = 0; k < 40; k++) { bf2_to_h2_inplace(w[k][0], sc); bf2_to_h2_inplace(w[k][1], sc); bf2_to_h2_inplace(w[k][2], sc); bf2_to_h2_inplace(w[k][3], sc); }
    }
    iw = uniform_f(iw);
    if (warp == 0) PT(3);
    uint32_t x0[8];
    {
      float xa[16];
      const uint32_t dlo = (((sb + OFF_X) & 0x3FFFF) >> 4) | (1u << 16);
      mbar_wait(sb + MB_X, 0);
      if (warp == 0) PT(4);
      wgmma_fence();
      static_for<0, 40>([&](auto K) { constexpr int k = K.value; wgmma_rs32h<((k >> 2) * 4096 + (k & 3) * 32) / 16, (k != 0)>(xa, w[k], dlo); });
      wgmma_commit();
      wgmma_wait<0>();
#pragma unroll
      for (int i = 0; i < 8; i++) x0[i] = pack_bf16(xa[2 * i] * iw, xa[2 * i + 1] * iw);
    }
    lane = fresh(threadIdx.x & 31);
    const int g = lane >> 2, q4 = lane & 3, r8 = lane & 7, m4 = lane >> 3;
    const bool t28 = j == 0 || warp < 4;
    const int bi = j == 0 ? hf : (warp < 4 ? j + 1 : 2 * (j - 1) + ((warp - 4) >> 1)), bv = t28 ? wi : 4 + (warp & 1);
    uint32_t wo1 = sb + OFF_WO + warp * 896 + lane * 16, wo2;
    {
      const int cb = (t28 ? unit28(bi) : unit24(bi)) - col0 / 8;
      uint32_t cp[4];
#pragma unroll
      for (int wd = 0; wd < 4; wd++) {
        int c, p;
        if (bv < 3) { c = 4 * bv + q4; p = wd; }
        else if (bv == 3) { if (q4 & 1) { c = 4 * (wd % 3) + q4; p = 3; } else { c = 12 + (q4 >> 1); p = wd; } }
        else if (bv == 4) { c = q4; p = wd; }
        else { if (wd < 2) { c = 4 + (q4 >> 1); p = 2 * (q4 & 1) + wd; } else { c = q4; p = 3; } }
        cp[wd] = sb + OFF_WO + ((g & 1) + (g & 2) * 4 + (g >> 2) * 2) * WOS + (cb + c) * 16 + p * 4;
      }
      const int cidx = (r8 & 1) + ((r8 >> 2) << 1);
      wo2 = sb + OFF_WO + warp * 896 + ((m4 & 1) ? 768 + (m4 >> 1) * 64 + cidx * 16 : 512 + (m4 >> 1) * 128 + r8 * 16);
      const bool dump = (m4 & 1) && (r8 & 2);
      uint32_t mo = 0;
      const bool regular = bv < 3 || bv == 4;
#pragma unroll 1
      for (int i = 0; i < 3; i++) {
        uint32_t x[4][4], y[4][4];
        const uint32_t o = i * 4 * WOK;
        mbar_wait(sb + MB_R + 8 * i, 0);
        if (warp == 0) PT(5 + i);
        if (regular) {
          static_for<0, 4>([&](auto K) {
            constexpr int kk = K.value;
            const uint4 u = lds128_i<kk * WOK>(cp[0] + o), v = lds128_i<kk * WOK + 4 * WOS>(cp[0] + o);
            x[kk][0] = u.x; x[kk][1] = u.y; x[kk][2] = u.z; x[kk][3] = u.w; y[kk][0] = v.x; y[kk][1] = v.y; y[kk][2] = v.z; y[kk][3] = v.w;
          });
        } else {
          static_for<0, 4>([&](auto K) {
            constexpr int kk = K.value;
#pragma unroll
            for (int wd = 0; wd < 4; wd++) { x[kk][wd] = lds32_i<kk * WOK>(cp[wd] + o); y[kk][wd] = lds32_i<kk * WOK + 4 * WOS>(cp[wd] + o); }
          });
        }
        bar_sync(B_C, 256);
        static_for<0, 4>([&](auto K) {
          constexpr int kk = K.value;
#pragma unroll
          for (int wd = 0; wd < 4; wd++) mo = amax_bf2(mo, amax_bf2(x[kk][wd], y[kk][wd]));
          stsm_x4_t_i<kk * WOK>(wo1 + o, x[kk][0], x[kk][1], y[kk][0], y[kk][1]);
          stsm_x4_t_i<0>(dump ? sb + OFF_S + 512 + lane * 16 : wo2 + o + kk * WOK, x[kk][2], x[kk][3], y[kk][2], y[kk][3]);
        });
      }
      if (warp == 0) PT(8);
      mo = amax_fold(mo);
      if (lane == 0) asm volatile("red.shared.max.u32 [%0], %1;" :: "r"(sb + SC_W + 4), "r"(mo) : "memory");
    }
    __syncwarp();
    auto run = [&](auto HF) {
    constexpr int hf = HF.value;
    uint32_t mema, sta, l16 = sb + lane * 16;
    uint32_t rq[hf ? NP1 : NQ0][4];
    auto step_addr = [&](uint32_t kv) {
      const int lr = (l16 >> 4) & 7, lm = (l16 >> 7) & 3;
      mema = l16 ^ (lm << 5);
      sta = sb + lr * 16 + (lm < 2 ? OFF_Q + wi * 512 + hf * 128 + lm * 256 : OFF_KV + kv + 512 + (2 * wi + lm - 2) * 640);
    };
    auto x_gemm = [&](uint32_t ph, [[maybe_unused]] uint32_t tsb) {
      float xa[16];
      const uint32_t dlo = (((sb + OFF_X) & 0x3FFFF) >> 4) | (1u << 16);
      constexpr int NP = hf ? NP1 : NP0;
      if constexpr (hf) {
        static_for<PQE, NP>([&](auto K) { ldsm_x4_t_i<OFF_WQ + K.value * 2048>(rq[K.value], wqa); });
        bar_sync(B_X, 256);
      }
      wgmma_fence();
      static_for<0, 40>([&](auto K) {
        constexpr int k = K.value;
        wgmma_rs32h<((k >> 2) * 4096 + (k & 3) * 32) / 16, (k != 0)>(xa, w[k], dlo);
        if constexpr (!hf && k == PFK && NP > PQE) { SFENCE(wqa); static_for<PQE, NP>([&](auto K) { ldsm_x4_t_i<OFF_WQ + K.value * 2048>(rq[K.value], wqa); }); SFENCE(wqa); }
        if constexpr (!hf && k == XT) bar_arrive(B_X, 256);
      });
      step_addr(ph * (2 * KVB));
      wgmma_commit();
      TS(9);
      wgmma_wait<0>();
      const uint32_t xs = l16 + (wi * 1280 + ph * (2 * KVB));
      stsm_x4_t_i<OFF_KV + hf * KVB>(xs, pack_bf16(xa[0] * iw, xa[1] * iw), pack_bf16(xa[4] * iw, xa[5] * iw), pack_bf16(xa[8] * iw, xa[9] * iw), pack_bf16(xa[12] * iw, xa[13] * iw));
      stsm_x4_t_i<OFF_KV + hf * KVB + 640>(xs, pack_bf16(xa[2] * iw, xa[3] * iw), pack_bf16(xa[6] * iw, xa[7] * iw), pack_bf16(xa[10] * iw, xa[11] * iw), pack_bf16(xa[14] * iw, xa[15] * iw));
      if constexpr (!hf) static_for<NP0, NP0 + NPL>([&](auto K) { ldsm_x4_t_i<OFF_WQ + K.value * 2048>(rq[K.value], wqa); });
    };
    auto wq_addr = [&](uint32_t l) -> uint32_t {
      const int lr = (l >> 4) & 7, lm = (l >> 7) & 3;
      return sb + hf * ((40 - NQ1) * 2048) + (lr + ((lm >> 1) << 3)) * 128 + (((2 * wi + (lm & 1)) ^ lr) << 4);
    };
    constexpr int NPM = hf ? NPM1 : NPM0;
    uint32_t u1[NPM][4], u2[NPM][4];
    static_for<0, NPM>([&](auto K) { ldsm_x4_i<(12 - NPM + K.value) * WOK>(u1[K.value], wo1); ldsm_x4_i<(12 - NPM + K.value) * WOK>(u2[K.value], wo2); });
    bar_sync(0, 384);
    iq = uniform_f(exp2i(-wscale_exp(lds32_i<SC_W + 8>(sb))));
    wqa = wq_addr(l16);
    static_for<0, (hf ? NP1 : NP0 + NPL)>([&](auto K) { ldsm_x4_t_i<OFF_WQ + K.value * 2048>(rq[K.value], wqa); });
    step_addr(0);
    stsm_x4_t_i<OFF_KV + hf * KVB>(l16 + wi * 1280, x0[0], x0[2], x0[4], x0[6]);
    stsm_x4_t_i<OFF_KV + hf * KVB + 640>(l16 + wi * 1280, x0[1], x0[3], x0[5], x0[7]);
    asm volatile("barrier.cluster.wait.aligned;" ::: "memory");
    TL_END(a.tl + 1);
#pragma unroll 1
    for (int s = 0; s < cfg::NSEG - 1; s++) {
      TS_SETUP();
#if CHAIN_TIMING
      if (tid == 0 && (s & 7) == 0) a.dbg[96 * 288 + cta * 8 + (s >> 3)] = clk32();
#endif
      bar_sync(hf ? B_MEM1 : B_MEM0, 256);
      const float sin_ = __uint_as_float(lds32_i<SC_IN>(sb + 16 * (s & 1)));
      constexpr int NPQ = (40 - NQ1) / 2;
      if constexpr (hf == 0) {
        float k0[4] = {0, 0, 0, 0}, k1[4] = {0, 0, 0, 0}, q0[4] = {0, 0, 0, 0}, q1[4] = {0, 0, 0, 0};
        constexpr auto pair_of = [](int t) { const int a = t * (20 - NPQ) / 20, b = (t + 1) * (20 - NPQ) / 20; return b > a ? NPQ + a : t - a; };
        uint32_t b[NB0][4];
        static_for<0, NB0>([&](auto T) { ldsm_x4_i<OFF_MEM + pair_of(T.value) * 512>(b[T.value], mema); });
        static_for<NP0 + NPL, NQ0>([&](auto K) { ldsm_x4_t_i<OFF_WQ + K.value * 2048>(rq[K.value], wqa); });
        if (BBS < 100) bbfence<0>(mema);
        static_for<0, 20>([&](auto T) {
          constexpr int t = T.value, p = pair_of(t);
          uint32_t (&bb)[4] = b[t % NB0];
          if constexpr (p < NPQ) {
            mma16816h(q0, rq[(2 * p) % NQ0], bb[0], bb[1]);
            if constexpr (2 * p + NQ0 < 2 * NPQ) ldsm_x4_t_i<OFF_WQ + (2 * p + NQ0) * 2048>(rq[(2 * p) % NQ0], wqa);
          }
          mma16816h(k0, w[2 * p], bb[0], bb[1]);
          if constexpr (p < NPQ) {
            mma16816h(q1, rq[(2 * p + 1) % NQ0], bb[2], bb[3]);
            if constexpr (2 * p + 1 + NQ0 < 2 * NPQ) ldsm_x4_t_i<OFF_WQ + (2 * p + 1 + NQ0) * 2048>(rq[(2 * p + 1) % NQ0], wqa);
          }
          mma16816h(k1, w[2 * p + 1], bb[2], bb[3]);
          if constexpr (NVE > 0 && t + NB0 == VET) bar_arrive(B_E, 256);
          if constexpr (t + NB0 < 20) ldsm_x4_i<OFF_MEM + pair_of(t + NB0) * 512>(bb, mema);
          if constexpr (t < 20 - NB0 && (t % BBS) == BBS - 1) bbfence<t + 1>(mema);
        });
        const float sq = sin_ * iq, sk = sin_ * iw;
        stsm_x4_t_i<0>(sta, pack_bf16((q0[0] + q1[0]) * sq, (q0[1] + q1[1]) * sq), pack_bf16((q0[2] + q1[2]) * sq, (q0[3] + q1[3]) * sq),
                       pack_bf16((k0[0] + k1[0]) * sk, (k0[1] + k1[1]) * sk), pack_bf16((k0[2] + k1[2]) * sk, (k0[3] + k1[3]) * sk));
        bar_sync(B_QK, 384);
        TS(2);
        {
          if (wi == 3) {
            const uint32_t xr = sb + ((l16 & 511) >> 2), ka = l16 + (l16 & 384) * 4 + (s & 1) * (2 * KVB);
            uint32_t a0[4], a1[4], a2[4], a3[4], kb0[4], kb1[4];
            ldsm_x4_i<OFF_Q>(a0, l16); ldsm_x4_i<OFF_KV + 512>(kb0, ka); ldsm_x4_i<OFF_Q + 1024>(a2, l16); ldsm_x4_i<OFF_KV + 512 + 2560>(kb1, ka);
            ldsm_x4_i<OFF_Q + 512>(a1, l16);
            bar_arrive(B_A, 288);
            ldsm_x4_i<OFF_Q + 1536>(a3, l16);
            float sa[4] = {0, 0, 0, 0}, sc2[4] = {0, 0, 0, 0};
            mma16816(sa, a0[0], a0[1], a0[2], a0[3], kb0[0], kb0[1]);
            mma16816(sc2, a2[0], a2[1], a2[2], a2[3], kb1[0], kb1[1]);
            mma16816(sa, a1[0], a1[1], a1[2], a1[3], kb0[2], kb0[3]);
            mma16816(sc2, a3[0], a3[1], a3[2], a3[3], kb1[2], kb1[3]);
            const float x0 = (sa[0] + sa[2]) + (sc2[0] + sc2[2]), x1 = (sa[1] + sa[3]) + (sc2[1] + sc2[3]);
            const uint32_t xp = pack_bf16(x0, x1);
            st_async_b32_i<OFF_SR + 1024 + 128>(xr + d1, xp, sb + MB_S + d1);
            st_async_b32_i<OFF_SR + 1024>(xr + d2, xp, sb + MB_S + d2);
            stsm_x2(l16 + OFF_S + 1024, __float_as_uint(x0), __float_as_uint(x1));
          } else if (wi == 0) {
            const uint4 si = lds128_i<SC_IN>(sb + 16 * (s & 1));
            const int em = (int)(si.y >> 10) - 14 + (int)(si.x >> 23) - 127;
            const uint32_t osc = __float_as_uint(exp2i(max(min((int)si.z - max(em, 1), 100), -100)));
            sts32(l16 + OFF_LT + 12, osc); sts64_i<SC_IN>(sb + 16 * ((s + 1) & 1), 0x7f000000u - osc, 0u);
          }
          bar_sync(B_SL, 256);
        }
      } else {
        float v0[4] = {0, 0, 0, 0}, v1[4] = {0, 0, 0, 0}, q0[4] = {0, 0, 0, 0}, q1[4] = {0, 0, 0, 0};
        constexpr int NB1 = NQ1 / 2 < 3 ? NQ1 / 2 : 3;
        uint32_t b[NB1][4];
        static_for<0, NB1>([&](auto T) { ldsm_x4_i<OFF_MEM + (NPQ + T.value) * 512>(b[T.value], mema); });
        static_for<0, NQ1 / 2>([&](auto T) {
          constexpr int t = T.value, p = NPQ + t;
          uint32_t (&bb)[4] = b[t % NB1];
          mma16816h(q0, rq[(2 * t) % NP1], bb[0], bb[1]);
          if constexpr (2 * t + NP1 < NQ1) ldsm_x4_t_i<OFF_WQ + (2 * t + NP1) * 2048>(rq[(2 * t) % NP1], wqa);
          mma16816h(q1, rq[(2 * t + 1) % NP1], bb[2], bb[3]);
          if constexpr (2 * t + 1 + NP1 < NQ1) ldsm_x4_t_i<OFF_WQ + (2 * t + 1 + NP1) * 2048>(rq[(2 * t + 1) % NP1], wqa);
          mma16816h(v0, w[2 * p], bb[0], bb[1]);
          mma16816h(v1, w[2 * p + 1], bb[2], bb[3]);
          if constexpr (t + NB1 < NQ1 / 2) ldsm_x4_i<OFF_MEM + (p + NB1) * 512>(bb, mema);
        });
        const float sq = sin_ * iq, sv = sin_ * iw;
        stsm_x2_t_i<0>(sta, pack_bf16((q0[0] + q1[0]) * sq, (q0[1] + q1[1]) * sq), pack_bf16((q0[2] + q1[2]) * sq, (q0[3] + q1[3]) * sq));
        TS(2);
        bar_arrive(B_QK, 384);
        float v2[4] = {0, 0, 0, 0}, v3[4] = {0, 0, 0, 0};
        auto vpair = [&](auto P, uint32_t (&bb)[4]) {
          constexpr int p = P.value;
          if constexpr (p & 1) { mma16816h(v0, w[2 * p], bb[0], bb[1]); mma16816h(v1, w[2 * p + 1], bb[2], bb[3]); }
          else { mma16816h(v2, w[2 * p], bb[0], bb[1]); mma16816h(v3, w[2 * p + 1], bb[2], bb[3]); }
        };
        if constexpr (NVE > 0) {
          uint32_t e[NVE ? NVE : 1][4];
          bar_sync(B_E, 256);
          static_for<0, NVE>([&](auto T) { ldsm_x4_i<OFF_MEM + T.value * 512>(e[T.value], mema); });
          static_for<0, NVE>([&](auto T) { vpair(T, e[T.value]); });
        }
        bar_sync(B_A, 288);
        uint32_t c[4][4];
        static_for<NVE, (NVE + 4 < NPQ ? NVE + 4 : NPQ)>([&](auto T) { ldsm_x4_i<OFF_MEM + T.value * 512>(c[T.value & 3], mema); });
        static_for<NVE, NPQ>([&](auto T) {
          constexpr int p = T.value;
          vpair(T, c[p & 3]);
          if constexpr (p + 4 < NPQ) ldsm_x4_i<OFF_MEM + (p + 4) * 512>(c[p & 3], mema);
        });
        stsm_x2_t_i<OFF_KV + KVB + 512>(l16 + (l16 & 128) * 4 + (wi * 1280 + (s & 1) * (2 * KVB)), pack_bf16(((v0[0] + v1[0]) + (v2[0] + v3[0])) * sv, ((v0[1] + v1[1]) + (v2[1] + v3[1])) * sv),
                            pack_bf16(((v0[2] + v1[2]) + (v2[2] + v3[2])) * sv, ((v0[3] + v1[3]) + (v2[3] + v3[3])) * sv));
        bar_arrive(B_V, 256);
      }
      TS(3);
      {
        uint32_t t1[12][4], t2[12][4];
        const uint32_t o16 = l16;
        wo1 = l16 + (OFF_WO + warp * 896);
        wo2 = sb + OFF_WO + warp * 896 + ((l16 & 128) ? 768 + ((l16 & 256) >> 2) + (l16 & 16) + ((l16 & 64) >> 1) : 512 + ((l16 & 256) >> 1) + (l16 & 112));
        constexpr int NR_ = NRT - NPM;
        auto ldw = [&](auto K) { if constexpr (K.value < 12 - NPM) { ldsm_x4_i<K.value * WOK>(t1[K.value], wo1); ldsm_x4_i<K.value * WOK>(t2[K.value], wo2); } };
        constexpr int PB = (hf ? PB1 : PB0) < NR_ ? (hf ? PB1 : PB0) : NR_, PA = (hf ? PA1 : PA0) < PB ? (hf ? PA1 : PA0) : PB;
        static_for<0, PA>(ldw);
        mbar_spin(sb + MB_X, (s + 1) & 1);
        if constexpr (PB > PA) {
          constexpr int PM = PA + PM1 < PB ? PA + PM1 : PB;
          mbar_spin(sb + MB_S, s & 1);
          const uint32_t t0 = clk_v();
          if constexpr (PM > PA) { while (clk_v() - t0 < GD1) {} static_for<PA, PM>(ldw); }
          if constexpr (PB > PM) { while (clk_v() - t0 < GD2) {} static_for<PM, PB>(ldw); }
        }
        float c0[4] = {0, 0, 0, 0}, c1[4] = {0, 0, 0, 0}, e0[4] = {0, 0, 0, 0}, e1[4] = {0, 0, 0, 0};
        uint32_t ob[6][4];
        auto kstep = [&](auto K) {
          constexpr int k = K.value;
          uint32_t (&bb)[4] = ob[k >> 1];
          uint32_t (&x)[4] = k < 12 - NPM ? t1[k] : u1[k < 12 - NPM ? 0 : k - (12 - NPM)];
          uint32_t (&y)[4] = k < 12 - NPM ? t2[k] : u2[k < 12 - NPM ? 0 : k - (12 - NPM)];
          if constexpr (k & 1) { mma16816(c1, x[0], x[1], x[2], x[3], bb[2], bb[3]); mma16816(e1, y[0], y[1], y[2], y[3], bb[2], bb[3]); }
          else { mma16816(c0, x[0], x[1], x[2], x[3], bb[0], bb[1]); mma16816(e0, y[0], y[1], y[2], y[3], bb[0], bb[1]); }
          if constexpr (k >= NRF) ldw(IC<k + NR_ - NRF>{});
        };
        auto ldo = [&](auto P) { ldsm_x4_i<OFF_O + P.value * 512>(ob[P.value], o16); };
        TS(4);
        bar_sync(B_O, 384);
        ldo(IC<0>{}); ldo(IC<1>{});
        SFENCE(o16);
        static_for<PB, NR_>(ldw);
        static_for<0, 4>(kstep);
        TS(5);
        mbar_spin(sb + MB_O, s & 1);
        TS(6);
        ldo(IC<2>{}); ldo(IC<NPM >= 2 ? 5 : 3>{});
        if (WOF) SFENCE(o16);
        kstep(IC<4>{});
        if constexpr (NPM < 2) { kstep(IC<5>{}); ldo(IC<4>{}); kstep(IC<6>{}); kstep(IC<7>{}); ldo(IC<5>{}); static_for<8, 12>(kstep); }
        else if constexpr (NPM >= 4) { kstep(IC<10>{}); kstep(IC<11>{}); ldo(IC<4>{}); kstep(IC<5>{}); ldo(IC<3>{}); kstep(IC<8>{}); kstep(IC<9>{}); kstep(IC<6>{}); kstep(IC<7>{}); }
        else { kstep(IC<5>{}); ldo(IC<3>{}); kstep(IC<11>{}); kstep(IC<10>{}); ldo(IC<4>{}); kstep(IC<6>{}); kstep(IC<7>{}); if constexpr (NPM == 3) { kstep(IC<9>{}); kstep(IC<8>{}); } else { kstep(IC<8>{}); kstep(IC<9>{}); } }
        l16 = fresh(l16);
        const int ln = (l16 >> 4) & 31;
        if constexpr (CEARLY && hf) { SFENCE2(o16, __float_as_uint(e1[0])); bar_arrive(B_G, 256); }
        unsigned char* gr = arena + (AR_ACC + acc_lane(bi, ln) + acc_voff(bv) + acc_step(s));
        const bool cnt = (ln & 1) || !t28;
        wqa = wq_addr(l16);
        SFENCE(o16);
        static_for<0, PQE>([&](auto K) { ldsm_x4_t_i<OFF_WQ + K.value * 2048>(rq[K.value], wqa); });
        const uint32_t y0 = movm_t(pack_f16(c0[0] + c1[0], c0[1] + c1[1])), y1 = movm_t(pack_f16(c0[2] + c1[2], c0[3] + c1[3]));
        const uint32_t y2 = movm_t(pack_f16(e0[0] + e1[0], e0[1] + e1[1])), y3 = movm_t(pack_f16(e0[2] + e1[2], e0[3] + e1[3]));
        asm volatile("red.relaxed.gpu.global.add.noftz.v4.f16x2 [%0], {%1,%2,%3,%4};" :: "l"(gr), "r"(y0), "r"(y1), "r"(y2), "r"(cnt ? 0x3c00u : y3) : "memory");
        bar_arrive(B_RED, 384);
        if constexpr (CEARLY && !hf) { bar_arrive(B_C, 256); bar_sync(B_G, 256); }
        else bar_sync(B_C, 256);
        TS(7);
      }
#if CHAIN_TIMING
      x_gemm((s + 1) & 1, tsb);
#else
      x_gemm((s + 1) & 1, 0);
#endif
      TS(8);
    }
    };
    if (hf == 0) run(IC<0>{}); else run(IC<1>{});
    {
      const uint32_t l16 = sb + (threadIdx.x & 31) * 16, mema = l16 ^ ((l16 >> 2) & 96);
      float c0[4] = {0, 0, 0, 0}, c1[4] = {0, 0, 0, 0}, c2[4] = {0, 0, 0, 0}, c3[4] = {0, 0, 0, 0};
      bar_sync(hf ? B_MEM1 : B_MEM0, 256);
      const float sc = __uint_as_float(lds32_i<SC_IN + 16>(sb)) * iw;
      static_for<0, 10>([&](auto T) {
        constexpr int p = 2 * T.value;
        uint32_t b0[4], b1[4];
        ldsm_x4_i<OFF_MEM + p * 512>(b0, mema); ldsm_x4_i<OFF_MEM + p * 512 + 512>(b1, mema);
        mma16816h(c0, w[2 * p], b0[0], b0[1]); mma16816h(c1, w[2 * p + 1], b0[2], b0[3]);
        mma16816h(c2, w[2 * p + 2], b1[0], b1[1]); mma16816h(c3, w[2 * p + 3], b1[2], b1[3]);
      });
      stsm_x2_t_i<OFF_KV + 2 * KVB + 512>(l16 + (l16 & 128) * 4 + wi * 1280 + hf * KVB, pack_bf16(((c0[0] + c1[0]) + (c2[0] + c3[0])) * sc, ((c0[1] + c1[1]) + (c2[1] + c3[1])) * sc),
                                          pack_bf16(((c0[2] + c1[2]) + (c2[2] + c3[2])) * sc, ((c0[3] + c1[3]) + (c2[3] + c3[3])) * sc));
      fence_proxy_async();
    }
    LITE(cta == 0 && threadIdx.x == 0, (a.tl >= 12) * 4 + 1);
    bar_arrive(B_RED, 384);
#if CHAIN_TIMING
    for (int i = tid; i < 288; i += 256) a.dbg[cta * 288 + i] = lds32_i<OFF_BAR + 128>(sb + i * 4);
#endif
    asm volatile("barrier.cluster.arrive.relaxed.aligned; barrier.cluster.wait.aligned;" ::: "memory");
  }
}
struct PrepArgs { const bf16 *wqkv, *wphi, *wo; unsigned char *wb, *wot; };
__device__ __forceinline__ void prep_body(const int cta, const PrepArgs& pa) {
  const int tid = threadIdx.x, lane = tid & 31, warp = tid >> 5, g = lane >> 2, q = lane & 3;
  const int pair = cta >> 1, which = cta & 1;
  uint32_t bfr[2][3][3];
#pragma unroll
  for (int hh = 0; hh < 2; hh++)
#pragma unroll
    for (int t = 0; t < 3; t++) {
      const unsigned short* ph = (const unsigned short*)pa.wphi + (2 * pair + hh) * 400 + (t < 2 ? 8 * t + g : 16 + (g >> 1)) + 2 * q * 20;
#pragma unroll
      for (int r = 0; r < 3; r++) {
        const int o = (r < 2 || q < 2) ? r * 160 : 0;
        const uint32_t v = (uint32_t)__ldg(ph + o) | ((uint32_t)__ldg(ph + o + 20) << 16);
        bfr[hh][t][r] = ((t < 2 || (g & 1) == hh) && (r < 2 || q < 2)) ? v : 0u;
      }
    }
  const int gt = cta * 256 + tid;
#pragma unroll 1
  for (int i = 0; i < 5; i++) {
    uint32_t af[2][6];
#pragma unroll
    for (int hh = 0; hh < 2; hh++) {
      const uint32_t* r0 = (const uint32_t*)(pa.wqkv + (size_t)((warp * 5 + i) * 16 + g) * 1920 + which * 640 + (2 * pair + hh) * 20) + q;
      af[hh][0] = __ldg(r0); af[hh][1] = __ldg(r0 + 7680); af[hh][2] = __ldg(r0 + 4); af[hh][3] = __ldg(r0 + 7684);
      af[hh][4] = __ldg(r0 + 8); af[hh][5] = __ldg(r0 + 7688);
    }
    const int iv = i * 4096 + (gt >> 1), k = (iv & 7) + (iv >> 8) * 8, h = (iv >> 3) & 31;
    const uint2* src = (const uint2*)(pa.wqkv + (size_t)k * 1920 + 1280 + h * 20) + (gt & 1) * 2;
    const uint2 a = __ldg(src), b = __ldg(src + 1), e = __ldg(src + 2);
    uint4 wv[2]; uint32_t wd[2];
#pragma unroll
    for (int n = 0; n < 2; n++) {
      const int iw = min((2 * i + n) * 5120 + gt, 640 * 80 - 1), r = iw & 7, c = (iw >> 3) % 80, kg = iw / 640, c5 = kg % 5;
      const int row = (kg / 5) * 40 + (c5 < 2 ? 8 * c5 + r : (c5 == 2 ? 16 + (r & 3) + (r >> 2) * 20 : 20 + 8 * (c5 - 3) + r));
      wv[n] = __ldg((const uint4*)(pa.wo + (size_t)row * cfg::DM + c * 8));
      wd[n] = (((c / 10) * 80 + kg) * 10 + c % 10) * 128 + r * 16;
    }
    uint4* dv = (uint4*)(pa.wb + ((size_t)((h >> 2) * 80 + (k >> 3)) * 32 + 20 + 3 * (h & 3)) * 128 + (k & 7) * 16);
    dv[(gt & 1) * 8] = make_uint4(a.x, a.y, b.x, b.y);
    if (gt & 1) dv[16] = (h & 1) ? make_uint4(0, 0, e.x, e.y) : make_uint4(e.x, e.y, 0, 0);
    if (gt < 5120) { *(uint4*)(pa.wot + wd[0]) = wv[0]; *(uint4*)(pa.wot + wd[1]) = wv[1]; }
    uint32_t* dst = (uint32_t*)(pa.wb + ((size_t)((pair >> 1) * 80 + (warp * 5 + i) * 2) * 32 + which * 10 + (pair & 1) * 5) * 128) + lane;
#pragma unroll
    for (int t = 0; t < 5; t++) {
      float d[4] = {0, 0, 0, 0};
#pragma unroll
      for (int hh = 0; hh < 2; hh++)
        if (t == 2 || (t > 2) == (hh == 1)) {
          const int tt = t < 3 ? t : t - 3;
          mma16816(d, af[hh][0], af[hh][1], af[hh][2], af[hh][3], bfr[hh][tt][0], bfr[hh][tt][1]);
          mma1688(d, q < 2 ? af[hh][4] : 0u, q < 2 ? af[hh][5] : 0u, bfr[hh][tt][2]);
        }
      dst[t * 32] = pack_bf16(d[0], d[1]); dst[1024 + t * 32] = pack_bf16(d[2], d[3]);
    }
  }
}

__global__ void __launch_bounds__(256, 4) ln_kernel(const bf16* __restrict__ xin, bf16* __restrict__ xn, uint2* __restrict__ xh, uint4* __restrict__ z0, int n0,
                                                    uint4* __restrict__ z1, int n1, const bf16* pfa, const bf16* pfb, int npf, int tl) {
  asm volatile("griddepcontrol.wait;" ::: "memory");
  asm volatile("griddepcontrol.launch_dependents;" ::: "memory");
  TL_BEGIN(tl);
  const int warp = threadIdx.x >> 5, lane = threadIdx.x & 31;
  const int row = blockIdx.x * 8 + warp;
  uint2 xw[1][5];
#pragma unroll
  for (int i = 0; i < 5; i++) xw[0][i] = *(const uint2*)(xin + (size_t)row * cfg::DM + i * 128 + lane * 4);
  for (int i = blockIdx.x * 256 + threadIdx.x; i < n0; i += 256 * 256) z0[i] = make_uint4(0, 0, 0, 0);
  for (int i = blockIdx.x * 256 + threadIdx.x; i < n1; i += 256 * 256) z1[i] = make_uint4(0, 0, 0, 0);
  if (npf && xw[0][4].y != 0x7fc17fc1u) {
    for (int i = 0; i < npf; i++) {
      const uint32_t l = (uint32_t)i * 32768u + (blockIdx.x * 256 + threadIdx.x) / 2;
      if (l < cfg::DM * cfg::HD / 64) asm volatile("prefetch.global.L2 [%0];" :: "l"(((threadIdx.x & 1) ? pfa : pfb) + (size_t)l * 64) : "memory");
    }
  }
  ln_rows<1>(xw, row, lane, xn, xh);
  TL_END(tl);
}
struct Pipe { uint32_t stage, phase; };
template <int NS> __device__ __forceinline__ void pipe_adv(Pipe& p) { if (++p.stage == NS) { p.stage = 0; p.phase ^= 1; } }
constexpr uint32_t SWZ128 = 1;
__device__ __forceinline__ uint64_t desc_kmajor(uint32_t a) { return make_desc(a, 16, 1024, SWZ128); }
__device__ __forceinline__ uint64_t desc_mnmajor(uint32_t a) { return make_desc(a, 8192, 1024, SWZ128); }
__device__ __forceinline__ void wait_ge(const void* p, uint32_t target, uint32_t ns = 32) {
  int spin = 0;
  while (ld_acquire_u32(p) < target) { __nanosleep(ns); if (++spin > (1 << 21)) break; }
}
__device__ __forceinline__ void bulk_g2s_hint(uint32_t dst, const void* src, uint32_t bytes, uint32_t mb, uint64_t pol) {
  asm volatile("cp.async.bulk.shared::cluster.global.mbarrier::complete_tx::bytes.L2::cache_hint [%0], [%1], %2, [%3], %4;"
               :: "r"(dst), "l"(src), "r"(bytes), "r"(mb), "l"(pol) : "memory");
}
#ifndef PF_WB
#define PF_WB 2
#endif
#ifndef ZINIT
#define ZINIT 1
#endif
#ifndef STAG
#define STAG 1
#endif
#ifndef EF_KV
#define EF_KV 1
#endif
#ifndef EF_O
#define EF_O 1
#endif
__device__ __forceinline__ void fence_proxy_async_global() { asm volatile("fence.proxy.async.global;" ::: "memory"); }

namespace tr {
constexpr int NS = 4, STQ = 16384 + 24576, STO = 16384 + 40960;
constexpr int SEGB = 15360;
constexpr int OFF_K = NS * STQ;
constexpr int OFF_BAR = NS * STO;
constexpr int SMEM = OFF_BAR + 256;
static_assert(OFF_K + 4 * SEGB <= OFF_BAR && SMEM <= 232448, "smem");
enum { T_QA = 0, T_Q, T_A, T_OB, T_OS, T_L, T_END, T_P };
constexpr uint32_t C_QA = AR_CNT, C_O = AR_CNT + 64, C_Q = AR_CNT + 128, C_P = AR_CNT + 192;
constexpr int MAXITEMS = 1200;
struct Sched {
  uint8_t ks[16];
  uint8_t wide[16];
  uint8_t lrows[16];
  uint32_t n;
  int nqa;
  uint16_t item[MAXITEMS];
};
struct Args {
  const unsigned char *kg, *vg;
  unsigned char* o;
  uint4* qs;
  unsigned char* part;
  const bf16 *xin, *xq;
  bf16 *xout, *xn;
  unsigned char* arena;
  const unsigned* go;
  int tl;
  uint32_t nap, nap2;
  int pfprep, pfq;
};
}

template <int N0, int N1>
__device__ __forceinline__ void tr_mainloop(float (&a0)[N0 / 2], float (&a1)[N1 ? N1 / 2 : 1], Pipe& p, uint32_t sb, uint32_t full, uint32_t empty, int nkb, int wg) {
  using namespace tr;
  constexpr uint32_t ST = N1 ? STO : STQ;
  uint32_t prev = 0;
#pragma unroll
  for (int i = 0; i < N0 / 2; i++) { if (ZINIT) a0[i] = 0.f; else asm volatile("" : "=f"(a0[i])); }
  if constexpr (N1 > 0) {
#pragma unroll
    for (int i = 0; i < N1 / 2; i++) a1[i] = 0.f;
  }
#pragma unroll 1
  for (int kb = 0; kb < nkb; kb++) {
    mbar_wait(full + 8 * p.stage, p.phase);
    const uint32_t st = ((sb & 0x3FFFF) >> 4) + p.stage * (ST / 16), sa = st + wg * 512;
    wgmma_fence();
#pragma unroll
    for (int kk = 0; kk < 4; kk++) {
      const uint64_t da = desc16<16, 1024, 1>(sa, kk * 32);
      if constexpr (N0 == 192) wgmma_n192<0, 1>(a0, da, desc16<8192, 1024, 1>(st, 16384 + kk * 2048), (kb | kk) != 0);
      else wgmma_n128<0, 1>(a0, da, desc16<8192, 1024, 1>(st, 16384 + kk * 2048), (kb | kk) != 0);
      if constexpr (N1 > 0) wgmma_n128<0, 1>(a1, da, desc16<8192, 1024, 1>(st, 16384 + 24576 + kk * 2048), (kb | kk) != 0);
    }
    wgmma_commit();
    if (kb > 0) { wgmma_wait<1>(); mbar_arrive_if((threadIdx.x & 127) == 0, empty + 8 * prev); }
    prev = p.stage;
    pipe_adv<NS>(p);
  }
  wgmma_wait<0>();
  mbar_arrive_if((threadIdx.x & 127) == 0, empty + 8 * prev);
}
template <int N> __device__ __forceinline__ void stage_tiles(const float (&o)[N / 2], uint32_t base, int wi, int lane) {
  const uint32_t ra = base + (wi * 16 + (lane & 7) + 8 * ((lane >> 3) & 1)) * 128;
#pragma unroll
  for (int v = 0; v < N / 8; v += 2)
    stsm_x4(ra + (v >> 3) * 8192 + ((((v & 7) + (lane >> 4)) ^ (lane & 7)) << 4), pack_bf16(o[4 * v], o[4 * v + 1]), pack_bf16(o[4 * v + 2], o[4 * v + 3]),
            pack_bf16(o[4 * v + 4], o[4 * v + 5]), pack_bf16(o[4 * v + 6], o[4 * v + 7]));
}
__global__ void __launch_bounds__(384, 1) trail_kernel(const __grid_constant__ CUtensorMap tmX, const __grid_constant__ CUtensorMap tmQ,
                                                       const __grid_constant__ CUtensorMap tmWo5, const __grid_constant__ CUtensorMap tmWo2,
                                                       const __grid_constant__ CUtensorMap tmP, const __grid_constant__ tr::Sched sc,
                                                       const __grid_constant__ tr::Args a, const __grid_constant__ PrepArgs pa) {
  using namespace tr;
  [[maybe_unused]] const int tl = a.tl;
  TL_BEGIN(tl);
  extern __shared__ __align__(1024) unsigned char smem_raw[];
  const uint32_t sb = smem_u32(smem_raw);
  const int warp = __shfl_sync(0xffffffffu, (int)threadIdx.x >> 5, 0), lane = threadIdx.x & 31;
  unsigned char* const arena = a.arena;
  const uint32_t full = sb + OFF_BAR, empty = full + 8 * NS, barK = empty + 8 * NS, barKfree = barK + 16, staged = barKfree + 16;
  const uint32_t kvrdy = staged + 32, mfull = kvrdy + 8, mempty = mfull + 16, mbox = mempty + 16;
  uint32_t go = 0;
  if (threadIdx.x == 256) go = ld_acquire_u32(a.go);
  if (threadIdx.x == 0) {
    for (int i = 0; i < NS; i++) { mbar_init(full + 8 * i, 1); mbar_init(empty + 8 * i, 2); }
    for (int i = 0; i < 2; i++) {
      mbar_init(barK + 8 * i, 1); mbar_init(barKfree + 8 * i, 1); mbar_init(staged + 16 * i, 4); mbar_init(staged + 16 * i + 8, 4);
      mbar_init(mfull + 8 * i, 1); mbar_init(mempty + 8 * i, 11);
    }
    mbar_init(kvrdy, 1);
    asm volatile("fence.mbarrier_init.release.cluster;" ::: "memory");
  }
  __syncthreads();
  Pipe mp{0, 0};
  auto next_item = [&]() -> uint32_t {
    uint32_t it;
    mbar_wait(mfull + 8 * mp.stage, mp.phase);
    asm volatile("ld.shared.u32 %0, [%1];" : "=r"(it) : "r"(mbox + 4 * mp.stage) : "memory");
    return it;
  };
  if (warp >= 8) {
    asm volatile("setmaxnreg.dec.sync.aligned.u32 40;");
    if (warp == 8) { go = __shfl_sync(0xffffffffu, go, 0); if (elect_one()) {
      Pipe p{0, 1};
      mp.phase = 1;
      uint32_t kph = 1, rph = 0, wide = 0, qdone = 0;
      prefetch_tmap(&tmX); prefetch_tmap(&tmQ); prefetch_tmap(&tmWo5); prefetch_tmap(&tmWo2); prefetch_tmap(&tmP);
      const uint64_t ef = policy_evict_first();
      auto ld_kv = [&](uint32_t d, const void* s, uint32_t n, uint32_t mb) { if (EF_KV) bulk_g2s_hint(d, s, n, mb, ef); else bulk_g2s(d, s, n, mb); };
      auto ld_o = [&](uint32_t d, const void* s, uint32_t n, uint32_t mb) { if (EF_O) bulk_g2s_hint(d, s, n, mb, ef); else bulk_g2s(d, s, n, mb); };
      auto stage = [&](uint32_t bytes) -> uint32_t {
        mbar_wait(empty + 8 * p.stage, p.phase);
        mbar_expect_tx(full + 8 * p.stage, bytes);
        return sb + p.stage * (wide ? STO : STQ);
      };
      auto fetch = [&]() -> uint32_t { uint32_t v; asm volatile("atom.relaxed.gpu.global.add.u32 %0, [%1], 1;" : "=r"(v) : "l"(arena + AR_QUEUE) : "memory"); return v; };
      if (!go) wait_ge(a.go, 1, 200);
      fence_proxy_async_global();
      uint32_t next = fetch();
      while (true) {
        const uint32_t item = next;
        const uint32_t code = sc.item[min(item, sc.n)];
        const int type = (code >> 11) & 7, m = (code >> 7) & 15, k = code & 127;
        const bool late = code >> 14;
        auto done_wait = [&]() { mbar_wait(mempty + 8 * (mp.stage ^ 1), mp.stage ? mp.phase ^ 1 : mp.phase); };
        if (type == T_A && !((qdone >> m) & 1)) { wait_ge(arena + C_Q + m * 4, 64); qdone |= 1u << m; }
        if (type == T_OB && !wide) for (uint32_t i = 0; i < NS; i++) mbar_wait(empty + 8 * i, i >= p.stage ? p.phase : p.phase ^ 1);
        wide = type == T_OB;
        mbar_wait(mempty + 8 * mp.stage, mp.phase);
        asm volatile("st.shared.u32 [%0], %1;" :: "r"(mbox + 4 * mp.stage), "r"((p.stage << 24) | (type << 16) | (m << 8) | (k & 255)) : "memory");
        mbar_arrive(mfull + 8 * mp.stage);
        pipe_adv<2>(mp);
        if (type == T_END) break;
        if (type == T_P) { done_wait(); next = fetch(); continue; }
        if (type == T_L) {
          const int nr = sc.lrows[m], np = sc.ks[m];
          prefetch_l2(a.xin + (size_t)(m * 128 + k * 8 * nr) * cfg::DM, nr * 10240);
          wait_ge(arena + C_O + m * 4, np * (sc.wide[m] ? 4 : 10), m < 13 ? a.nap : 32);
          fence_proxy_async_global();
#pragma unroll 1
          for (int r = 0; r < nr; r++) {
            const int rg = m * 16 + k * nr + r;
#pragma unroll 1
            for (int q0 = 0; q0 <= np; q0 += 4) {
              const int n = min(4, np + 1 - q0);
              const uint32_t st = stage(n * 10240), fb = full + 8 * p.stage;
#pragma unroll 1
              for (int q = q0; q < q0 + n; q++) {
                if (q == 0) bulk_g2s(st, a.xin + (size_t)rg * 8 * cfg::DM, 10240, fb);
                else tma_load_3d(st + (q - q0) * 10240, &tmP, 0, rg & 7, ((q - 1) * 32 + (rg >> 3)) * 10, fb);
              }
              pipe_adv<NS>(p);
            }
          }
          if (late) done_wait();
          next = fetch(); continue;
        }
        if (type <= T_A) {
          if (type != T_A)
#pragma unroll 1
            for (int kb = 0; kb < 10; kb++) {
              const uint32_t st = stage(STQ), fb = full + 8 * p.stage;
              tma_load_2d(st, &tmX, kb * 64, m * 128, fb);
              tma_load_3d(st + 16384, &tmQ, 0, kb * 64, k * 3, fb);
              pipe_adv<NS>(p);
              if (type == T_Q && kb == 8) next = fetch();
            }
          if (type != T_Q) {
            const size_t blk = ((size_t)m * 4 * 96 + k * 3) * 5120;
            kph ^= 1;
            mbar_wait(kvrdy, rph); rph ^= 1;
            if (!late) next = fetch();
            fence_proxy_async_global();
#pragma unroll 1
            for (int w = type == T_A ? 0 : 2; w < 4; w++) {
              const uint32_t st = stage(2 * SEGB), fb = full + 8 * p.stage;
              for (int sg = 0; sg < 2; sg++) ld_kv(st + sg * SEGB, (w < 2 ? a.kg : a.vg) + blk + (size_t)(2 * (w & 1) + sg) * (96 * 5120), SEGB, fb);
              pipe_adv<NS>(p);
            }
            if (late) { done_wait(); next = fetch(); }
          }
        } else {
          const int nn = wide ? 2 : 5, nb = wide ? 5 : 2, nt = k % nn, nkb = 96 / sc.ks[m], k0 = (k / nn) * nkb;
          const Pipe p0 = p;
          for (int kb = 0; kb < nkb; kb++) {
            if (wide && kb < NS && p.stage >= 2) { mbar_wait(barKfree, kph); mbar_wait(barKfree + 8, kph); }
            const uint32_t st = stage(16384 + nb * 8192), fb = full + 8 * p.stage;
            tma_load_3d(st + 16384, wide ? &tmWo5 : &tmWo2, 0, (k0 + kb) * 64, nt * nb, fb);
            if (kb >= NS) ld_o(st, a.o + ((size_t)m * 96 + k0 + kb) * 16384, 16384, fb);
            pipe_adv<NS>(p);
            if (kb == NS - 1 || (kb == nkb - 1 && nkb < NS)) {
              wait_ge(arena + C_QA + m * 4, 64, m < 14 ? a.nap : 32);
              fence_proxy_async_global();
              Pipe q = p0;
#pragma unroll 1
              for (int i = 0; i <= kb; i++) { ld_o(sb + q.stage * (wide ? STO : STQ), a.o + ((size_t)m * 96 + k0 + i) * 16384, 16384, full + 8 * q.stage); pipe_adv<NS>(q); }
            }
          }
          if (!late) next = fetch();
          for (int w = wide ? -(int)((2 - p.stage) & 3) : 0; w < 2; w++) { mbar_wait(empty + 8 * p.stage, p.phase); mbar_arrive(full + 8 * p.stage); pipe_adv<NS>(p); }
          kph ^= wide;
          if (late) { done_wait(); next = fetch(); }
        }
      }
    } } else if (warp < 11) { if (elect_one()) {
      const int w = warp - 9;
      uint32_t sph = 0;
      [[maybe_unused]] int nlog = 0;
#ifdef TIMELINE
      if (w == 0) { unsigned long long* lg = g_log + (((tl >= 12) * 132 + blockIdx.x) * 64 + nlog++) * 2; lg[0] = T_END << 16; lg[1] = gtime(); lg[2] = ~0ull; }
#endif
      while (true) {
        const uint32_t it = next_item();
        const int type = (it >> 16) & 255, m = (it >> 8) & 255, k = it & 255;
        const uint32_t slot = mp.stage;
        pipe_adv<2>(mp);
        if (type == T_END) break;
        mbar_wait(staged + 16 * w + 8 * slot, (sph >> slot) & 1); sph ^= 1u << slot;
        mbar_arrive(mempty + 8 * slot);
#ifdef TIMELINE
        if (w == 0 && nlog < 63) { unsigned long long* lg = g_log + (((tl >= 12) * 132 + blockIdx.x) * 64 + nlog++) * 2; lg[0] = (type << 16) | (m << 8) | k; lg[1] = gtime(); lg[2] = ~0ull; }
#endif
        if (type == T_L) continue;
        if (type == T_QA || type == T_A) {
          for (int jj = 0; jj < 3; jj++) bulk_s2g(a.o + ((size_t)m * 96 + k * 3 + jj) * 16384 + w * 8192, sb + OFF_K + w * 2 * SEGB + jj * 8192, 8192);
          bulk_commit();
          bulk_wait<0>();
          mbar_arrive(barKfree + 8 * w);
        } else if (type == T_OB || type == T_OS) {
          const bool wide = type == T_OB;
          const int nn = wide ? 2 : 5, nb = wide ? 5 : 2;
          const uint32_t own = wide ? 2 + w : ((it >> 24) + 96 / sc.ks[m] + w) % NS;
          bulk_s2g(a.part + ((size_t)((k / nn) * 32 + m * 2 + w) * 10 + (k % nn) * nb) * 8192, sb + own * (wide ? STO : STQ), nb * 8192);
          bulk_commit();
          bulk_wait<0>();
          mbar_arrive(empty + 8 * own);
          if (wide && w) { mbar_arrive(barKfree); mbar_arrive(barKfree + 8); }
        }
        red_release_inc(arena + (type == T_Q ? C_Q : (type <= T_A ? C_QA : (type == T_P ? C_P : C_O))) + m * 4);
      }
    } } else if (elect_one()) {
      const uint64_t ef = policy_evict_first();
      uint32_t kph = 1;
      if (PF_WB && blockIdx.x >= 52) { prefetch_l2(pa.wb + (blockIdx.x - 52) * 32768, 32768); prefetch_l2(pa.wot + (blockIdx.x - 52) * 10240, 10240); }
      if (PF_WB > 1 && blockIdx.x >= 52) { prefetch_l2(a.xn + (blockIdx.x - 52) * 8192, 16384); prefetch_l2(a.xout + (blockIdx.x - 52) * 8192, 16384); }
      while (true) {
        const uint32_t it = next_item();
        const int type = (it >> 16) & 255, m = (it >> 8) & 255, k = it & 255;
        const uint32_t slot = mp.stage;
        pipe_adv<2>(mp);
        if (type == T_END) break;
        if (a.pfprep && type == T_QA && m == 0) { prefetch_l2(pa.wqkv + k * 38400, 76800); prefetch_l2(pa.wo + k * 12800, 25600); }
        if ((type == T_QA || type == T_A) && m < 15) {
          if (m + 1 < sc.nqa) prefetch_l2(a.xq + ((m + 1) * 128 + k * 4) * cfg::DM, 5120);
          else if (a.pfq) prefetch_l2(a.qs + ((size_t)(((m + 1) & 7) * 32 + k) * 12) * 256, 49152);
        }
        if (type == T_QA || type == T_A) {
          for (int spin = 0; spin < (1 << 21); spin++) {
            uint4 f;
            asm volatile("ld.acquire.gpu.global.v4.u32 {%0,%1,%2,%3}, [%4];" : "=r"(f.x), "=r"(f.y), "=r"(f.z), "=r"(f.w) : "l"(arena + prog_off(k, 0)) : "memory");
            if (min(min(f.x, f.y), f.z) >= (uint32_t)(4 * m + 4)) break;
            __nanosleep(m < 15 ? a.nap : a.nap2);
          }
          mbar_arrive(kvrdy);
          fence_proxy_async_global();
          const unsigned char* src = a.kg + ((size_t)m * 4 * 96 + k * 3) * 5120;
#pragma unroll 1
          for (int w = 0; w < 2; w++) {
            mbar_wait(barKfree + 8 * w, kph);
            if (type == T_A) { mbar_arrive(barK + 8 * w); continue; }
            mbar_expect_tx(barK + 8 * w, 2 * SEGB);
            for (int sg = 2 * w; sg < 2 * w + 2; sg++) { if (EF_KV) bulk_g2s_hint(sb + OFF_K + sg * SEGB, src + (size_t)sg * (96 * 5120), SEGB, barK + 8 * w, ef); else bulk_g2s(sb + OFF_K + sg * SEGB, src + (size_t)sg * (96 * 5120), SEGB, barK + 8 * w); }
          }
          kph ^= 1;
        } else if (type == T_OB) {
          mbar_wait(barKfree, kph); mbar_wait(barKfree + 8, kph);
          kph ^= 1;
        }
        mbar_arrive(mempty + 8 * slot);
      }
      if (blockIdx.x == gridDim.x - 1) asm volatile("griddepcontrol.wait;" ::: "memory");
    }
    return;
  }
  asm volatile("setmaxnreg.inc.sync.aligned.u32 232;");
  const int wg = warp >> 2, wi = warp & 3;
  const int g = lane >> 2, q4 = lane & 3;
  asm volatile("griddepcontrol.launch_dependents;" ::: "memory");
  Pipe p{0, 0};
  uint32_t kph = 0;
  auto own_slot = [&]() -> uint32_t {
    const uint32_t sA = p.stage, phA = p.phase; pipe_adv<NS>(p);
    const uint32_t sB = p.stage, phB = p.phase; pipe_adv<NS>(p);
    mbar_wait_if(wi == 0, full + 8 * (wg ? sA : sB), wg ? phA : phB);
    mbar_wait(full + 8 * (wg ? sB : sA), wg ? phB : phA);
    mbar_arrive_if((threadIdx.x & 127) == 0, empty + 8 * (wg ? sA : sB));
    return wg ? sB : sA;
  };
  while (true) {
    const uint32_t it = __shfl_sync(0xffffffffu, next_item(), 0);
    const int type = (it >> 16) & 255, m = (it >> 8) & 255, k = it & 255;
    mbar_arrive_if(lane == 0, mempty + 8 * mp.stage);
    const uint32_t done = staged + 16 * wg + 8 * mp.stage;
    pipe_adv<2>(mp);
    if (type == T_END) break;
    if (type == T_P) {
      prep_body(k, pa);
      bar_sync(3 + wg, 128);
      mbar_arrive_if(lane == 0, done);
      continue;
    }
    if (type == T_L) {
      const int nr = sc.lrows[m], np = sc.ks[m];
      const uint32_t po = (lane >> 4) * 1024 + warp * 128 + ((((lane >> 1) & 7) ^ warp) << 4) + (lane & 1) * 8;
#pragma unroll 1
      for (int r = 0; r < nr; r++) {
        uint2 xw[1][5]; float s[20];
#pragma unroll
        for (int i = 0; i < 20; i++) s[i] = 0.f;
#pragma unroll 1
        for (int q0 = 0; q0 <= np; q0 += 4) {
          const uint32_t st = sb + p.stage * STQ;
          mbar_wait(full + 8 * p.stage, p.phase);
          if (q0 == 0) static_for<0, 5>([&](auto I) { xw[0][I.value] = lds64_i<I.value * 256>(st + warp * 1280 + lane * 8); });
#pragma unroll 1
          for (int q = q0 ? 0 : 1; q < min(4, np + 1 - q0); q++)
            static_for<0, 5>([&](auto I) {
              constexpr int i = I.value;
              const uint2 t = lds64_i<i * 2048>(st + q * 10240 + po);
              s[4 * i] += bf_lo(t.x); s[4 * i + 1] += bf_hi(t.x); s[4 * i + 2] += bf_lo(t.y); s[4 * i + 3] += bf_hi(t.y);
            });
          bar_sync(3 + wg, 128);
          mbar_arrive_if((threadIdx.x & 127) == 0, empty + 8 * p.stage);
          pipe_adv<NS>(p);
        }
        const int row = (m * 16 + k * nr + r) * 8 + warp;
#pragma unroll
        for (int i = 0; i < 5; i++) {
          bf16r2(s[4 * i], s[4 * i + 1]); bf16r2(s[4 * i + 2], s[4 * i + 3]);
          xw[0][i] = make_uint2(pack_bf16(bf_lo(xw[0][i].x) + s[4 * i], bf_hi(xw[0][i].x) + s[4 * i + 1]), pack_bf16(bf_lo(xw[0][i].y) + s[4 * i + 2], bf_hi(xw[0][i].y) + s[4 * i + 3]));
          *(uint2*)(a.xout + (size_t)row * cfg::DM + i * 128 + lane * 4) = xw[0][i];
        }
        ln_rows<1>(xw, row, lane, a.xn, nullptr);
      }
      __syncwarp();
      mbar_arrive_if(lane == 0, done);
      continue;
    }
    if (type >= T_OB) {
      const int nkb = 96 / sc.ks[m];
      if (type == T_OB) {
        float a0[96], a1[64];
        tr_mainloop<192, 128>(a0, a1, p, sb, full, empty, nkb, wg);
        while (p.stage != 2) { mbar_wait_if(wi == 0, full + 8 * p.stage, p.phase); mbar_arrive_if((threadIdx.x & 127) == 0, empty + 8 * p.stage); pipe_adv<NS>(p); }
        const uint32_t st = sb + own_slot() * STO;
        stage_tiles<192>(a0, st, wi, lane); stage_tiles<128>(a1, st + 24576, wi, lane);
      } else {
        float a0[64], a1[1];
        tr_mainloop<128, 0>(a0, a1, p, sb, full, empty, nkb, wg);
        stage_tiles<128>(a0, sb + own_slot() * STQ, wi, lane);
      }
      fence_proxy_async();
      __syncwarp();
      mbar_arrive_if(lane == 0, done);
      continue;
    }
    uint32_t qf[12][4];
    uint4* qp = a.qs + ((size_t)((m & 7) * 32 + k) * 12) * 256 + threadIdx.x;
    if (type != T_A) {
      float acc[96], a1[1];
      tr_mainloop<192, 0>(acc, a1, p, sb, full, empty, 10, wg);
#pragma unroll
      for (int i = 0; i < 12; i++) {
        qf[i][0] = pack_bf16(acc[8 * i], acc[8 * i + 1]); qf[i][1] = pack_bf16(acc[8 * i + 2], acc[8 * i + 3]);
        qf[i][2] = pack_bf16(acc[8 * i + 4], acc[8 * i + 5]); qf[i][3] = pack_bf16(acc[8 * i + 6], acc[8 * i + 7]);
      }
      if (type == T_Q) {
#pragma unroll
        for (int i = 0; i < 12; i++) qp[i * 256] = make_uint4(qf[i][0], qf[i][1], qf[i][2], qf[i][3]);
        __syncwarp();
        mbar_arrive_if(lane == 0, done);
        continue;
      }
    } else {
#pragma unroll
      for (int i = 0; i < 12; i++) { const uint4 v = __ldcg(qp + i * 256); qf[i][0] = v.x; qf[i][1] = v.y; qf[i][2] = v.z; qf[i][3] = v.w; }
    }
    const uint32_t ost = sb + OFF_K + wg * 2 * SEGB;
    const bool second = wi >= 2;
    uint32_t pf[5][4];
    {
      float sa[20], sb2[20];
      uint32_t kbase = ost, kslot = 0;
      if (type == T_A) { kslot = own_slot(); kbase = sb + kslot * STQ; } else mbar_wait(barK + 8 * wg, kph);
      kbase = (kbase & 0x3FFFF) >> 4;
      if (STAG && wg) bar_sync(1, 256);
      wgmma_fence();
#pragma unroll
      for (int i = 0; i < 12; i++) {
        wgmma_rs_n40<0>(sa, qf[i][0], qf[i][1], qf[i][2], qf[i][3], desc16<640, 128, 0>(kbase, i * 1280), i != 0);
        wgmma_rs_n40<0>(sb2, qf[i][0], qf[i][1], qf[i][2], qf[i][3], desc16<640, 128, 0>(kbase, SEGB + i * 1280), i != 0);
      }
      wgmma_commit();
      if (STAG && !wg) bar_arrive(1, 256);
      wgmma_wait<0>();
      mbar_arrive_if(type == T_A && (threadIdx.x & 127) == 0, empty + 8 * kslot);
      const float cs = 0.07216878364870322f * 1.4426950408889634f;
      const int r0 = 16 * (wi & 1) + g, r1 = r0 + 8;
      float m0 = -INFINITY, m1 = -INFINITY;
#pragma unroll
      for (int n = 0; n < 5; n++) {
#pragma unroll
        for (int e = 0; e < 2; e++) {
          const int key = 8 * n + 2 * q4 + e;
          float x = second ? sb2[4 * n + e] : sa[4 * n + e], y = second ? sb2[4 * n + 2 + e] : sa[4 * n + 2 + e];
          if (n < 4) { if (key > r0) x = -INFINITY; if (key > r1) y = -INFINITY; }
          sa[4 * n + e] = x; sa[4 * n + 2 + e] = y;
          m0 = fmaxf(m0, x); m1 = fmaxf(m1, y);
        }
      }
      m0 = fmaxf(fmaxf(m0, __shfl_xor_sync(0xffffffffu, m0, 1)), fmaxf(__shfl_xor_sync(0xffffffffu, m0, 2), __shfl_xor_sync(0xffffffffu, m0, 3)));
      m1 = fmaxf(fmaxf(m1, __shfl_xor_sync(0xffffffffu, m1, 1)), fmaxf(__shfl_xor_sync(0xffffffffu, m1, 2), __shfl_xor_sync(0xffffffffu, m1, 3)));
      m0 *= -cs; m1 *= -cs;
      float s0 = 0.f, s1 = 0.f;
#pragma unroll
      for (int n = 0; n < 5; n++) {
#pragma unroll
        for (int e = 0; e < 2; e++) {
          sa[4 * n + e] = ex2f(fmaf(sa[4 * n + e], cs, m0)); sa[4 * n + 2 + e] = ex2f(fmaf(sa[4 * n + 2 + e], cs, m1));
          s0 += sa[4 * n + e]; s1 += sa[4 * n + 2 + e];
        }
      }
      s0 = (s0 + __shfl_xor_sync(0xffffffffu, s0, 1)) + (__shfl_xor_sync(0xffffffffu, s0, 2) + __shfl_xor_sync(0xffffffffu, s0, 3));
      s1 = (s1 + __shfl_xor_sync(0xffffffffu, s1, 1)) + (__shfl_xor_sync(0xffffffffu, s1, 2) + __shfl_xor_sync(0xffffffffu, s1, 3));
      const float i0 = rcpf(s0), i1 = rcpf(s1);
#pragma unroll
      for (int n = 0; n < 5; n++) {
        const uint32_t x = pack_bf16(sa[4 * n] * i0, sa[4 * n + 1] * i0), y = pack_bf16(sa[4 * n + 2] * i1, sa[4 * n + 3] * i1);
        if (n < 4) {
          pf[n >> 1][2 * (n & 1)] = second ? 0u : x; pf[n >> 1][2 * (n & 1) + 1] = second ? 0u : y;
          pf[2 + (n >> 1)][2 * (n & 1)] = second ? x : 0u; pf[2 + (n >> 1)][2 * (n & 1) + 1] = second ? y : 0u;
        } else {
          pf[4][0] = second ? 0u : x; pf[4][1] = second ? 0u : y; pf[4][2] = second ? x : 0u; pf[4][3] = second ? y : 0u;
        }
      }
    }
    {
      float o[96];
#pragma unroll
      for (int i = 0; i < 5; i++) { PIN(pf[i][0]); PIN(pf[i][1]); PIN(pf[i][2]); PIN(pf[i][3]); }
      const uint32_t own = own_slot(), vbase = ((sb & 0x3FFFF) >> 4) + own * (STQ / 16);
      wgmma_fence();
#pragma unroll
      for (int i = 0; i < 5; i++)
        wgmma_rs_n192<1>(o, pf[i][0], pf[i][1], pf[i][2], pf[i][3], i < 4 ? desc16<128, 640, 0>(vbase, (i >> 1) * SEGB + (i & 1) * 256) : desc16<SEGB, 640, 0>(vbase, 512), i != 0);
      wgmma_commit();
      if (type == T_A) mbar_wait(barK + 8 * wg, kph);
      kph ^= 1;
      wgmma_wait<0>();
      mbar_arrive_if((threadIdx.x & 127) == 0, empty + 8 * own);
      stage_tiles<192>(o, ost, wi, lane);
      fence_proxy_async();
      __syncwarp();
      mbar_arrive_if(lane == 0, done);
    }
  }
}
namespace bf {
constexpr int NS = 4, STAGE = 16384 + 32768;
constexpr int PIECE = 20480;
constexpr int OFF_PHI = 0, OFF_V = 40960, OFF_KV = 65536;
constexpr int OFF_OST = 5 * PIECE;
constexpr int OFF_WOT = 6 * PIECE;
constexpr int OFF_BAR = OFF_WOT + 102400;
constexpr int SMEM = OFF_BAR + 256;
static_assert(NS * STAGE <= OFF_BAR && SMEM <= 232448, "smem");
constexpr int KVACC = 32 * 5 * 1024;
struct Args {
  const unsigned char *wb, *wot;
  unsigned char *kvacc, *o2;
  const bf16* xin;
  bf16* xout;
  unsigned* go;
  const void* prep;
  const bf16 *pf0, *pf1;
  int pfn, pfns, pfwait;
  int tl;
};
}
__device__ __forceinline__ void hedgehog_features(float (&x)[2][5], uint32_t (&w)[2][5]) {
  const float L = 1.4426950408889634f;
  float mx[2], mn[2], sp[2], sn[2], pos[2][5], neg[2][5];
#pragma unroll
  for (int r = 0; r < 2; r++) {
    mx[r] = fmaxf(fmaxf(fmaxf(x[r][0], x[r][1]), fmaxf(x[r][2], x[r][3])), x[r][4]);
    mn[r] = fminf(fminf(fminf(x[r][0], x[r][1]), fminf(x[r][2], x[r][3])), x[r][4]);
  }
#pragma unroll
  for (int o = 1; o < 4; o <<= 1)
#pragma unroll
    for (int r = 0; r < 2; r++) {
      const uint32_t t = __shfl_xor_sync(0xffffffffu, __byte_perm(__float_as_uint(mn[r]), __float_as_uint(mx[r]), 0x7632), o);
      mx[r] = fmaxf(mx[r], bf_hi(t)); mn[r] = fminf(mn[r], bf_lo(t));
    }
#pragma unroll
  for (int r = 0; r < 2; r++) {
#pragma unroll
    for (int i = 0; i < 5; i++) { pos[r][i] = ex2f((x[r][i] - mx[r]) * L); neg[r][i] = ex2f((mn[r] - x[r][i]) * L); }
    sp[r] = ((pos[r][0] + pos[r][1]) + (pos[r][2] + pos[r][3])) + pos[r][4];
    sn[r] = ((neg[r][0] + neg[r][1]) + (neg[r][2] + neg[r][3])) + neg[r][4];
  }
#pragma unroll
  for (int o = 1; o < 4; o <<= 1)
#pragma unroll
    for (int r = 0; r < 2; r++) { sp[r] += __shfl_xor_sync(0xffffffffu, sp[r], o); sn[r] += __shfl_xor_sync(0xffffffffu, sn[r], o); }
#pragma unroll
  for (int r = 0; r < 2; r++) {
    const float ip = rcpf(sp[r]), in_ = rcpf(sn[r]);
    w[r][0] = pack_bf16(pos[r][0] * ip, pos[r][1] * ip); w[r][1] = pack_bf16(pos[r][2] * ip, pos[r][3] * ip);
    w[r][2] = pack_bf16(neg[r][0] * in_, neg[r][1] * in_); w[r][3] = pack_bf16(neg[r][2] * in_, neg[r][3] * in_);
    w[r][4] = pack_bf16(pos[r][4] * ip, neg[r][4] * in_);
  }
}
__device__ __forceinline__ void bulk_g2s_mc(uint32_t dst, const void* src, uint32_t bytes, uint32_t mb) {
  asm volatile("cp.async.bulk.shared::cluster.global.mbarrier::complete_tx::bytes.multicast::cluster [%0], [%1], %2, [%3], %4;"
               :: "r"(dst), "l"(src), "r"(bytes), "r"(mb), "h"((unsigned short)3) : "memory");
}
__device__ __forceinline__ void mbar_arrive_remote_if(bool c, uint32_t b) {
  asm volatile("{\n.reg .pred p;\nsetp.ne.u32 p, %1, 0;\n@p mbarrier.arrive.shared::cluster.b64 _, [%0];\n}" :: "r"(b), "r"((uint32_t)c) : "memory");
}

__global__ void __cluster_dims__(2, 1, 1) __launch_bounds__(384, 1) blayer_kernel(const __grid_constant__ CUtensorMap tmA, const __grid_constant__ bf::Args a) {
  using namespace bf;
  [[maybe_unused]] const int tl = a.tl;
  extern __shared__ __align__(1024) unsigned char smem_raw[];
  const uint32_t sb = smem_u32(smem_raw);
  const int warp = __shfl_sync(0xffffffffu, (int)threadIdx.x >> 5, 0), lane = threadIdx.x & 31;
  const uint32_t full = sb + OFF_BAR, empty = full + 8 * NS, full2 = empty + 8 * NS, empty2 = full2 + 64, barW = empty2 + 16, drained = barW + 8, staged = drained + 8, freeb = staged + 8;
  const int rank = blockIdx.x & 1, u = (blockIdx.x >> 1) & 7, mp = blockIdx.x >> 4;
  const int m = 2 * mp + rank;
  const int m2 = 2 * mp + (u & 1), ns = (u & ~1) + rank;
  const uint32_t dpeer = mapa_u32(sb, rank ^ 1) - sb;
  unsigned* cntO = (unsigned*)(a.kvacc + KVACC);
  if (threadIdx.x == 0) {
    for (int i = 0; i < NS; i++) { mbar_init(full + 8 * i, 1); mbar_init(empty + 8 * i, 4); }
    for (int i = 0; i < 8; i++) mbar_init(full2 + 8 * i, 1);
    mbar_init(empty2, 2); mbar_init(empty2 + 8, 2);
    mbar_init(barW, 1); mbar_init(drained, 1); mbar_init(staged, 8); mbar_init(freeb, 2);
    asm volatile("fence.mbarrier_init.release.cluster;" ::: "memory");
  }
  __syncthreads();
  asm volatile("barrier.cluster.arrive.relaxed.aligned; barrier.cluster.wait.aligned;" ::: "memory");
  if (warp >= 8) {
    asm volatile("setmaxnreg.dec.sync.aligned.u32 40;");
    if (warp == 8) { if (elect_one()) {
      const unsigned char* wsrc = a.wb + (size_t)u * 327680 + rank * 16384;
      if (a.prep) wait_ge(a.prep, 64);
      fence_proxy_async_global();
      for (int kb = 0; kb < NS; kb++) {
        mbar_expect_tx(full + 8 * kb, STAGE);
        bulk_g2s_mc(sb + kb * STAGE + 16384 + rank * 16384, wsrc + kb * 32768, 16384, full + 8 * kb);
      }
      asm volatile("griddepcontrol.wait;" ::: "memory");
      TL_BEGIN0(tl);
      LITE(blockIdx.x == 0, (tl >= 12) * 4 + 2);
      if (blockIdx.x == 0) *a.go = 0;
      for (int kb = 0; kb < NS; kb++) tma_load_2d(sb + kb * STAGE, &tmA, kb * 64, m * 128, full + 8 * kb);
      if (m == 0) prefetch_l2(a.kvacc + u * (KVACC / 8), KVACC / 8);
#pragma unroll 1
      for (int kb = NS; kb < 10; kb++) {
        const uint32_t s = kb & 3, st = sb + s * STAGE, fb = full + 8 * s;
        mbar_wait(empty + 8 * s, ((kb >> 2) - 1) & 1);
        mbar_expect_tx(fb, STAGE);
        tma_load_2d(st, &tmA, kb * 64, m * 128, fb);
        bulk_g2s_mc(st + 16384 + rank * 16384, wsrc + kb * 32768, 16384, fb);
      }
      for (int i = 0; i < 6; i++) mbar_expect_tx(full2 + 8 * i, PIECE);
      mbar_wait(drained, 0);
      mbar_expect_tx(barW, 102400);
      bulk_g2s(sb + OFF_WOT, a.wot + (size_t)ns * 102400, 102400, barW);
      mbar_wait(staged, 0);
      bulk_s2g(a.o2 + (size_t)(m * 8 + u) * PIECE, sb + OFF_OST, PIECE);
      bulk_commit();
      bulk_wait<0>();
      mbar_arrive(freeb); mbar_arrive_remote_if(true, freeb + dpeer);
      red_release_inc(cntO + m);
      wait_ge(cntO + m2, 8, 20);
      mbar_wait(freeb, 0);
      fence_proxy_async_global();
      const unsigned char* osrc = a.o2 + (size_t)m2 * 8 * PIECE;
      for (int i = 0; i < 6; i++) bulk_g2s_mc(sb + i * PIECE + rank * (PIECE / 2), osrc + i * PIECE + rank * (PIECE / 2), PIECE / 2, full2 + 8 * i);
      for (int i = 0; i < 2; i++) {
        mbar_wait(empty2 + 8 * i, 0);
        mbar_expect_tx(full2 + 8 * (6 + i), PIECE);
        bulk_g2s(sb + i * PIECE, osrc + (6 + i) * PIECE, PIECE, full2 + 8 * (6 + i));
      }
    } } else if (warp == 9 && a.pf0) { if (elect_one()) {
      if (a.pfwait) asm volatile("griddepcontrol.wait;" ::: "memory");
      constexpr uint32_t CH = 2048;
      for (int i = 0; i < a.pfn; i++) {
        prefetch_l2((const unsigned char*)a.pf0 + (i * 128 + blockIdx.x) * CH, CH); prefetch_l2((const unsigned char*)a.pf1 + (i * 128 + blockIdx.x) * CH, CH);
        __nanosleep(a.pfns);
      }
    } }
    return;
  }
  asm volatile("setmaxnreg.inc.sync.aligned.u32 232;");
  const int wg = warp >> 2, wi = warp & 3;
  const int q4 = lane & 3;
  const bool lead = (threadIdx.x & 127) == 0;
  const uint32_t s16 = (sb & 0x3FFFF) >> 4;
  float acc[128];
  {
#pragma unroll 1
    for (int kb = 0; kb < 10; kb++) {
      const uint32_t s = kb & 3, st = s16 + s * (STAGE / 16);
      mbar_wait(full + 8 * s, (kb >> 2) & 1);
      wgmma_fence();
#pragma unroll
      for (int kk = 0; kk < 4; kk++) wgmma_n256<0, 1>(acc, desc16<16, 1024, 1>(st + wg * 512, kk * 32), desc16<4096, 128, 0>(st, 16384 + kk * 8192), (kb | kk) != 0);
      wgmma_commit();
      if (kb > 0 && kb < 7) { wgmma_wait<1>(); const uint32_t e = empty + 8 * ((kb - 1) & 3); mbar_arrive_if(lead, e); mbar_arrive_remote_if(lead, e + dpeer); }
    }
    wgmma_wait<0>();
    bar_sync(1, 256);
    mbar_arrive_if(threadIdx.x == 0, drained);
  }
  TL2((tl >= 12 ? 128 : 0) + 32 + 0);
  const uint32_t srow = (wg * 64 + wi * 16 + (lane & 15)) * 16 + (lane >> 4) * 2048;
  auto features = [&](auto T0, auto HH, uint32_t (&w)[2][5]) {
    constexpr int t = T0.value + 5 * (HH.value >> 1), o = (HH.value & 1) ? 3 : 0, e = HH.value & 1;
    float x[2][5];
#pragma unroll
    for (int r = 0; r < 2; r++) {
      x[r][0] = acc[4 * (t + o) + 2 * r]; x[r][1] = acc[4 * (t + o) + 2 * r + 1]; x[r][2] = acc[4 * (t + o + 1) + 2 * r]; x[r][3] = acc[4 * (t + o + 1) + 2 * r + 1];
      bf16r2(x[r][0], x[r][1]); bf16r2(x[r][2], x[r][3]);
    }
    x[0][4] = acc[4 * (t + 2) + e]; x[1][4] = acc[4 * (t + 2) + 2 + e];
    bf16r2(x[0][4], x[1][4]);
    hedgehog_features(x, w);
  };
  static_for<0, 4>([&](auto HH) {
    constexpr int hh = HH.value, t = 20 + 3 * hh;
    const uint32_t one = q4 == ((hh & 1) ? 0 : 2) ? 0x3f80u : 0u;
    const uint32_t va = sb + OFF_V + hh * 6144 + srow;
    stsm_x4(va, pack_bf16(acc[4 * t], acc[4 * t + 1]), pack_bf16(acc[4 * t + 2], acc[4 * t + 3]), pack_bf16(acc[4 * t + 4], acc[4 * t + 5]), pack_bf16(acc[4 * t + 6], acc[4 * t + 7]));
    const bool pad = (q4 >= 2) != (hh & 1);
    stsm_x2(va + 4096, pad ? one : pack_bf16(acc[4 * t + 8], acc[4 * t + 9]), pad ? one : pack_bf16(acc[4 * t + 10], acc[4 * t + 11]));
    uint32_t w[2][5];
    features(IC<10>{}, HH, w);
    const uint32_t pa = sb + OFF_PHI + hh * 10240 + srow;
    stsm_x4(pa, w[0][0], w[1][0], w[0][1], w[1][1]);
    stsm_x4(pa + 4096, w[0][2], w[1][2], w[0][3], w[1][3]);
    stsm_x2(pa + 8192, w[0][4], w[1][4]);
  });
  fence_proxy_async();
  bar_sync(1, 256);
  TL2((tl >= 12 ? 128 : 0) + 32 + 1);
  {
    float d0[12], d1[12];
    const uint32_t pa = s16 + wg * 1280, pv = s16 + wg * 768;
    wgmma_fence();
#pragma unroll
    for (int k = 0; k < 8; k++) {
      wgmma_n24<1, 1>(d0, desc16<128, 2048, 0>(pa, OFF_PHI + k * 256), desc16<128, 2048, 0>(pv, OFF_V + k * 256), k != 0);
      wgmma_n24<1, 1>(d1, desc16<128, 2048, 0>(pa, OFF_PHI + 10240 + k * 256), desc16<128, 2048, 0>(pv, OFF_V + 6144 + k * 256), k != 0);
    }
    wgmma_commit();
    wgmma_wait<0>();
    unsigned char* dst = a.kvacc + ((u * 4 + wg * 2) * 5 + 2 * wi) * 1024 + lane * 16;
    auto red4 = [&](bool on, unsigned char* p, float x, float y, float z) {
      asm volatile("{\n.reg .pred p;\nsetp.ne.u32 p, %4, 0;\n@p red.relaxed.gpu.global.add.v4.f32 [%0], {%1,%2,%3,%5};\n}" :: "l"(p), "f"(x), "f"(y), "f"(z), "r"((uint32_t)on), "f"(1.f) : "memory");
    };
    red4(wi < 3, dst, d0[0], d0[1], d0[4]); red4(wi < 3, dst + 512, d0[5], d0[8], d0[9]);
    red4(wi < 3, dst + 5120, d1[0], d1[1], d1[4]); red4(wi < 3, dst + 5632, d1[5], d1[8], d1[9]);
    red4(wi < 2, dst + 1024, d0[2], d0[3], d0[6]); red4(wi < 2, dst + 1536, d0[7], d0[10], d0[11]);
    red4(wi < 2, dst + 6144, d1[2], d1[3], d1[6]); red4(wi < 2, dst + 6656, d1[7], d1[10], d1[11]);
  }
  TL2((tl >= 12 ? 128 : 0) + 32 + 2);
  uint32_t qf[4][2][5];
  static_for<0, 4>([&](auto HH) { features(IC<0>{}, HH, qf[HH.value]); });
  uint4 xr[5];
#pragma unroll
  for (int i = 0; i < 5; i++) {
    const int c = lane + 32 * i;
    xr[i] = __ldcg((const uint4*)(a.xin + (size_t)(m2 * 128 + wg * 64 + wi * 16 + c / 10) * cfg::DM + ns * 80 + (c % 10) * 8));
  }
  {
    const unsigned char* src = a.kvacc + (u * 20 + warp) * 1024 + lane * 16;
    uint4 v[6];
    int spin = 0;
    while (true) {
      v[0] = ld_relaxed_v4_i<0>(src); v[1] = ld_relaxed_v4_i<512>(src); v[2] = ld_relaxed_v4_i<8192>(src); v[3] = ld_relaxed_v4_i<8704>(src);
      v[4] = ld_relaxed_v4_i<0>(src + (wg ? 0 : 16384)); v[5] = ld_relaxed_v4_i<512>(src + (wg ? 0 : 16384));
      const uint32_t c = (v[0].w & v[1].w & v[2].w) & (v[3].w & v[4].w & v[5].w);
      if (!__any_sync(0xffffffffu, (c & 0x41800000u) != 0x41800000u) || ++spin >= SPIN_LIMIT) break;
      __nanosleep(100);
    }
    const uint32_t kd = sb + OFF_KV + warp * 384 + lane * 4;
#pragma unroll
    for (int i = 0; i < 3; i++)
      if (i < 2 || wg == 0) {
        sts32(kd + i * 3072, pack_bf16(__uint_as_float(v[2 * i].x), __uint_as_float(v[2 * i].y)));
        sts32(kd + i * 3072 + 128, pack_bf16(__uint_as_float(v[2 * i].z), __uint_as_float(v[2 * i + 1].x)));
        sts32(kd + i * 3072 + 256, pack_bf16(__uint_as_float(v[2 * i + 1].y), __uint_as_float(v[2 * i + 1].z)));
      }
  }
  fence_proxy_async();
  bar_sync(1, 256);
  TL2((tl >= 12 ? 128 : 0) + 32 + 3);
  {
    float d[4][12];
    uint32_t zero = 0; PIN(zero);
#pragma unroll
    for (int hh = 0; hh < 4; hh++)
#pragma unroll
      for (int i = 0; i < 5; i++) { PIN(qf[hh][0][i]); PIN(qf[hh][1][i]); }
    wgmma_fence();
#pragma unroll
    for (int hh = 0; hh < 4; hh++) {
      const uint32_t kb = OFF_KV + hh * 1920;
      wgmma_rs_n24<1>(d[hh], qf[hh][0][0], qf[hh][1][0], qf[hh][0][1], qf[hh][1][1], desc16<384, 128, 0>(s16, kb), 0);
      wgmma_rs_n24<1>(d[hh], qf[hh][0][2], qf[hh][1][2], qf[hh][0][3], qf[hh][1][3], desc16<384, 128, 0>(s16, kb + 768), 1);
      wgmma_rs_n24<1>(d[hh], qf[hh][0][4], qf[hh][1][4], zero, zero, desc16<0, 128, 0>(s16, kb + 1536), 1);
    }
    wgmma_commit();
    wgmma_wait<0>();
    uint32_t ow[4][6];
#pragma unroll
    for (int hh = 0; hh < 4; hh++) {
      const int zl = (lane & ~3) | ((hh & 1) ? 0 : 2);
      const float da = bf16r(bf16r(__shfl_sync(0xffffffffu, d[hh][8], zl)) + 1e-6f), db = bf16r(bf16r(__shfl_sync(0xffffffffu, d[hh][10], zl)) + 1e-6f);
#pragma unroll
      for (int n = 0; n < 3; n++) {
        bf16r2(d[hh][4 * n], d[hh][4 * n + 1]); bf16r2(d[hh][4 * n + 2], d[hh][4 * n + 3]);
        ow[hh][2 * n] = pack_bf16(__fdividef(d[hh][4 * n], da), __fdividef(d[hh][4 * n + 1], da));
        ow[hh][2 * n + 1] = pack_bf16(__fdividef(d[hh][4 * n + 2], db), __fdividef(d[hh][4 * n + 3], db));
      }
    }
#pragma unroll
    for (int p = 0; p < 2; p++) {
      const uint32_t oa = sb + OFF_OST + p * 10240 + srow;
      stsm_x4(oa, ow[2 * p][0], ow[2 * p][1], ow[2 * p][2], ow[2 * p][3]);
      stsm_x2(oa + 4096, q4 < 2 ? ow[2 * p][4] : ow[2 * p + 1][4], q4 < 2 ? ow[2 * p][5] : ow[2 * p + 1][5]);
      stsm_x4(oa + 6144, ow[2 * p + 1][0], ow[2 * p + 1][1], ow[2 * p + 1][2], ow[2 * p + 1][3]);
    }
    fence_proxy_async();
    __syncwarp();
    mbar_arrive_if(lane == 0, staged);
  }
  TL2((tl >= 12 ? 128 : 0) + 32 + 4);
  float c2[40];
  mbar_wait(barW, 0);
#pragma unroll 1
  for (int i = 0; i < 8; i++) {
    mbar_wait(full2 + 8 * i, 0);
    const uint32_t st = s16 + (i < 6 ? i : i - 6) * (PIECE / 16) + wg * 64, wo = s16 + i * 800;
    wgmma_fence();
#pragma unroll
    for (int kk = 0; kk < 5; kk++) wgmma_n80<0, 1>(c2, desc16<2048, 128, 0>(st, kk * 4096), desc16<1280, 128, 0>(wo, OFF_WOT + kk * 2560), (i | kk) != 0);
    wgmma_commit();
    if (i == 1 || i == 2) { wgmma_wait<1>(); mbar_arrive_if(lead, empty2 + 8 * (i - 1)); }
  }
  wgmma_wait<0>();
  TL2((tl >= 12 ? 128 : 0) + 32 + 5);
  {
    bar_sync(1, 256);
    const uint32_t ost = sb + 2 * PIECE + warp * 3072;
#pragma unroll
    for (int v = 0; v < 10; v += 2)
      stsm_x4(ost + (lane & 15) * 176 + (v + (lane >> 4)) * 16, pack_bf16(c2[4 * v], c2[4 * v + 1]), pack_bf16(c2[4 * v + 2], c2[4 * v + 3]),
              pack_bf16(c2[4 * v + 4], c2[4 * v + 5]), pack_bf16(c2[4 * v + 6], c2[4 * v + 7]));
    __syncwarp();
#pragma unroll
    for (int i = 0; i < 5; i++) {
      const int c = lane + 32 * i, row = c / 10, chunk = c % 10;
      const uint4 y = lds128(ost + row * 176 + chunk * 16);
      const size_t off = (size_t)(m2 * 128 + wg * 64 + wi * 16 + row) * cfg::DM + ns * 80 + chunk * 8;
      const uint4 x = xr[i];
      *(uint4*)(a.xout + off) = make_uint4(pack_bf16(bf_lo(x.x) + bf_lo(y.x), bf_hi(x.x) + bf_hi(y.x)), pack_bf16(bf_lo(x.y) + bf_lo(y.y), bf_hi(x.y) + bf_hi(y.y)),
                                           pack_bf16(bf_lo(x.z) + bf_lo(y.z), bf_hi(x.z) + bf_hi(y.z)), pack_bf16(bf_lo(x.w) + bf_lo(y.w), bf_hi(x.w) + bf_hi(y.w)));
    }
  }
  TL_END(tl);
}
__device__ __align__(32768) unsigned char g_arena[AR_SIZE];
__device__ unsigned g_go[32];
__device__ __align__(1024) uint2 g_xh[2048 * 160];
__device__ __align__(1024) unsigned char g_k[64 * 96 * 5120], g_v[64 * 96 * 5120];
__device__ __align__(1024) bf16 g_o[2048 * 6144];
__device__ __align__(1024) uint4 g_qs[8 * 32 * 12 * 256];
__device__ __align__(1024) bf16 g_xn[2048 * 640], g_xn2[2048 * 640], g_xa[2048 * 640], g_xb[2048 * 640];
__device__ __align__(1024) bf16 g_part[24 * 2048 * 640];
__device__ __align__(1024) bf16 g_wb[2048 * 640], g_wot[640 * 640], g_pq[2048 * 640];
__device__ __align__(1024) float g_kvacc[bf::KVACC / 4 + 64];

typedef CUresult (*EncodeFn)(CUtensorMap*, CUtensorMapDataType, cuuint32_t, void*, const cuuint64_t*, const cuuint64_t*, const cuuint32_t*,
                             const cuuint32_t*, CUtensorMapInterleave, CUtensorMapSwizzle, CUtensorMapL2promotion, CUtensorMapFloatOOBfill);
static EncodeFn g_encode = nullptr;
static CUtensorMap make_map(const void* p, uint64_t cols, uint64_t rows, uint32_t bc, uint32_t br, bool swz = true) {
  CUtensorMap m;
  cuuint64_t dims[2] = {cols, rows}, strides[1] = {cols * 2};
  cuuint32_t box[2] = {bc, br}, es[2] = {1, 1};
  g_encode(&m, CU_TENSOR_MAP_DATA_TYPE_BFLOAT16, 2, const_cast<void*>(p), dims, strides, box, es, CU_TENSOR_MAP_INTERLEAVE_NONE,
           swz ? CU_TENSOR_MAP_SWIZZLE_128B : CU_TENSOR_MAP_SWIZZLE_NONE, CU_TENSOR_MAP_L2_PROMOTION_L2_256B, CU_TENSOR_MAP_FLOAT_OOB_FILL_NONE);
  return m;
}
static CUtensorMap make_map3(const void* p, uint64_t cols, uint64_t rows, uint32_t nb) {
  CUtensorMap m;
  cuuint64_t dims[3] = {64, rows, cols / 64}, strides[2] = {cols * 2, 128};
  cuuint32_t box[3] = {64, 64, nb}, es[3] = {1, 1, 1};
  g_encode(&m, CU_TENSOR_MAP_DATA_TYPE_BFLOAT16, 3, const_cast<void*>(p), dims, strides, box, es, CU_TENSOR_MAP_INTERLEAVE_NONE,
           CU_TENSOR_MAP_SWIZZLE_128B, CU_TENSOR_MAP_L2_PROMOTION_L2_256B, CU_TENSOR_MAP_FLOAT_OOB_FILL_NONE);
  return m;
}
template <class T> static T* sym(const T& s) { void* p = nullptr; cudaGetSymbolAddress(&p, s); return (T*)p; }

struct Ptrs {
  unsigned char *arena, *k, *v; bf16 *o, *xn, *xa, *xb, *wb, *wot, *pq; float *part, *kvacc; uint2* xh; uint4* qs; bf16* xn2; unsigned* go;
};

static tr::Sched make_sched(int layer, const char* str, const int* ks, const int* lr) {
  using namespace tr;
  Sched s = {};
  int n = 0;
  s.nqa = 16;
  for (int b = 0; b < 16; b++) { s.ks[b] = (uint8_t)abs(ks[b]); s.wide[b] = ks[b] > 0; s.lrows[b] = (uint8_t)lr[b]; }
  for (const char* p = str; *p;) {
    if (*p == ' ') { p++; continue; }
    const bool late = *p < 'a';
    const char c = *p++ | 32;
    char* e;
    const int b = (int)strtol(p, &e, 10); p = e;
    int first = 0, cnt = c == 'o' ? s.ks[b] * (s.wide[b] ? 2 : 5) : (c == 'l' ? 16 / lr[b] : 32);
    if (*p == '.') { first = (int)strtol(p + 1, &e, 10); cnt = (int)strtol(e + 1, &e, 10); p = e; }
    const int type = c == 'a' ? T_QA : (c == 'q' ? T_Q : (c == 't' ? T_A : (c == 'l' ? T_L : (c == 'p' ? T_P : (s.wide[b] ? T_OB : T_OS)))));
    if (type == T_P && layer > 0) continue;
    if (type == T_A && b < s.nqa) s.nqa = b;
    for (int i = 0; i < cnt && n < MAXITEMS - 1; i++) s.item[n++] = (uint16_t)((late << 14) | (type << 11) | (b << 7) | (first + i));
  }
  s.n = n; s.item[n] = T_END << 11;
  return s;
}
static tr::Sched sched_of(int layer) {
  const char* str = layer == 0
      ? "q13 q14 q12.0.8 a0.0.8 q12.8.24 q15 a0.8.24 a1 p0.0.16 a2 p0.16.16 o0 o1 a3.0.16 o2 a3.16.16 a4.0.16 o3 a4.16.16 a5.0.24 o4 a5.24.8 a6.0.20 l0 a6.20.12 o5 "
        "a7 o6 l2 a8.0.24 o7 l1 a8.24.8 a9 o8 l3 a10 l4 O9 a11 t12 l5 l6 l7 O10 O11 O12 t13 T14 t15 O13 O14 L8 O15 L10 L9 l11 l13 l12 l15 l14"
      : "q12 q13 q11 q14.0.20 a0 q14.20.12 q15 a1 o0 o1 a2 o2 a3 a4 o3 a5 o4 a6 o5 l0 l1 a7 o6 a8.0.20 l2 a8.20.12 o7 a9 o8 a10 l3 l4 O9 t11 O10 t12 l5 l7 L6 "
        "O11 O12 t13 t14 T15 O13 l10 O14 L8 o15 l13 l15 l9 L12 l14 L11";
  const int ks0[2][16] = {{2, 2, 2, 3, 2, 2, 2, 3, 2, 2, 3, 3, 3, -4, -8, -8}, {2, 2, 2, 2, 2, 2, 2, 2, 2, 3, 3, 3, 3, -4, -6, -12}};
  const int lr0[2][16] = {{4, 4, 4, 4, 4, 4, 4, 4, 2, 4, 1, 1, 1, 1, 1, 1}, {4, 4, 4, 4, 4, 4, 4, 1, 1, 4, 2, 1, 2, 1, 1, 1}};
  int ks[16], lr[16];
  for (int b = 0; b < 16; b++) { ks[b] = ks0[layer][b]; lr[b] = lr0[layer][b]; }
#ifdef TUNE
  const bool mine = !getenv("ONLY") || atoi(getenv("ONLY")) == layer;
  if (mine && getenv("SCHED")) str = getenv("SCHED");
  if (const char* p = getenv(layer ? "S1" : "S0")) {
    char* e;
    for (int b = 0; b < 16; b++) { ks[b] = (int)strtol(p, &e, 10); p = e; }
    for (int b = 0; b < 16; b++) { lr[b] = (int)strtol(p, &e, 10); p = e; }
    str = p;
  }
  if (const char* p = mine ? getenv("KS") : nullptr) for (int b = 0; b < 16; b++) { char* e; ks[b] = (int)strtol(p, &e, 10); p = e; }
  if (const char* p = mine ? getenv("LR") : nullptr) for (int b = 0; b < 16; b++) { char* e; lr[b] = (int)strtol(p, &e, 10); p = e; }
#endif
  return make_sched(layer, str, ks, lr);
}
#ifndef TRAIL_GRID
#define TRAIL_GRID 132
#endif
#ifndef PDL_LN
#define PDL_LN 0
#endif
#ifndef PDL_CH
#define PDL_CH 1
#endif
#ifndef PDL_B
#define PDL_B 1
#endif
#ifndef PF_A
#define PF_A 1
#endif
#ifndef PF_B
#define PF_B 1
#endif
extern "C" void kernel_launch(void* const* d_in, const int* in_sizes, int n_in, void* d_out, int out_size) {
  const bf16* x = (const bf16*)d_in[0];
  const bf16* mem0 = (const bf16*)d_in[1];
  const bf16 *Wq = (const bf16*)d_in[2], *Wk = (const bf16*)d_in[3], *Wv = (const bf16*)d_in[4], *Wo = (const bf16*)d_in[5];
  const bf16 *wqkv = (const bf16*)d_in[8], *wphi = (const bf16*)d_in[9], *wo = (const bf16*)d_in[10];
  bf16* out = (bf16*)d_out;
  static Ptrs P; static bool init = false;
  if (!init) {
    void* fn = nullptr; cudaDriverEntryPointQueryResult qr;
    cudaGetDriverEntryPoint("cuTensorMapEncodeTiled", &fn, cudaEnableDefault, &qr);
    g_encode = (EncodeFn)fn;
    void* p;
    cudaGetSymbolAddress(&p, g_arena); P.arena = (unsigned char*)p;
    cudaGetSymbolAddress(&p, g_k); P.k = (unsigned char*)p;   cudaGetSymbolAddress(&p, g_v); P.v = (unsigned char*)p;
    cudaGetSymbolAddress(&p, g_o); P.o = (bf16*)p;
    cudaGetSymbolAddress(&p, g_xn); P.xn = (bf16*)p;
    cudaGetSymbolAddress(&p, g_xa); P.xa = (bf16*)p;   cudaGetSymbolAddress(&p, g_xb); P.xb = (bf16*)p;
    cudaGetSymbolAddress(&p, g_wb); P.wb = (bf16*)p;   cudaGetSymbolAddress(&p, g_wot); P.wot = (bf16*)p;
    cudaGetSymbolAddress(&p, g_pq); P.pq = (bf16*)p;   cudaGetSymbolAddress(&p, g_part); P.part = (float*)p;
    cudaGetSymbolAddress(&p, g_kvacc); P.kvacc = (float*)p;
    cudaGetSymbolAddress(&p, g_xh); P.xh = (uint2*)p;
    cudaGetSymbolAddress(&p, g_go); P.go = (unsigned*)p;
    cudaGetSymbolAddress(&p, g_qs); P.qs = (uint4*)p;
    cudaGetSymbolAddress(&p, g_xn2); P.xn2 = (bf16*)p;
    cudaFuncSetAttribute(chain_kernel, cudaFuncAttributeMaxDynamicSharedMemorySize, ch::SMEM);
    cudaFuncSetAttribute(trail_kernel, cudaFuncAttributeMaxDynamicSharedMemorySize, tr::SMEM);
    cudaFuncSetAttribute(blayer_kernel, cudaFuncAttributeMaxDynamicSharedMemorySize, bf::SMEM);
    init = true;
  }
  const CUtensorMap tmXn = make_map(P.xn, 640, 2048, 64, 128), tmXn2 = make_map(P.xn2, 640, 2048, 64, 128);
  const CUtensorMap tmWq = make_map3(Wq, 6144, 640, 3);
  const CUtensorMap tmCq = make_map(Wq, 6144, 640, 64, 160), tmCk = make_map(Wk, 6144, 640, 64, 160), tmCv = make_map(Wv, 6144, 640, 64, 160), tmCo = make_map(Wo, 640, 6144, 224, 64, false);
  const CUtensorMap tmWo5 = make_map3(Wo, 640, 6144, 5), tmWo2 = make_map3(Wo, 640, 6144, 2);

  CUtensorMap tmP;
  {
    cuuint64_t dims[3] = {256, 8, 24 * 320}, strides[2] = {1024, 8192};
    cuuint32_t box[3] = {256, 1, 10}, es[3] = {1, 1, 1};
    g_encode(&tmP, CU_TENSOR_MAP_DATA_TYPE_UINT32, 3, P.part, dims, strides, box, es, CU_TENSOR_MAP_INTERLEAVE_NONE, CU_TENSOR_MAP_SWIZZLE_NONE,
             CU_TENSOR_MAP_L2_PROMOTION_NONE, CU_TENSOR_MAP_FLOAT_OOB_FILL_NONE);
  }
  ChainArgs ca;
  ca.xh = P.xh; ca.mem0 = mem0; ca.kg = P.k; ca.vg = P.v;
  ca.arena = P.arena; ca.dbg = nullptr; ca.go = P.go; ca.delay = POLL_DELAY; ca.margin = 150; ca.pubrel = 1;
#ifdef TUNE
  if (getenv("PR")) ca.pubrel = atoi(getenv("PR"));
  if (getenv("MG")) ca.margin = atoi(getenv("MG"));
  if (getenv("PD")) ca.delay = atoi(getenv("PD"));
#endif
  ca.tl = 0;
  uint4* zar = (uint4*)P.arena; const int nzar = AR_SIZE / 16;
  uint4* zkv = (uint4*)P.kvacc; const int nzkv = (bf::KVACC / 4 + 64) / 4;

  const PrepArgs pa{wqkv, wphi, wo, (unsigned char*)P.wb, (unsigned char*)P.wot};
  const bf16* xcur = x;
  cudaLaunchAttribute at[1];
  at[0].id = cudaLaunchAttributeProgrammaticStreamSerialization; at[0].val.programmaticStreamSerializationAllowed = 1;
  auto cfgof = [&](int grid, int block, int smem, bool pdl) {
    cudaLaunchConfig_t lc = {};
    lc.gridDim = dim3(grid); lc.blockDim = dim3(block); lc.dynamicSmemBytes = smem; lc.stream = cudaStreamPerThread;
    lc.attrs = at; lc.numAttrs = pdl ? 1 : 0;
    return lc;
  };
  int nlayers = 2;
#ifdef TUNE
  if (getenv("LAYERS")) nlayers = atoi(getenv("LAYERS"));
#endif
  for (int layer = 0; layer < nlayers; layer++) {
    const int tl = layer * 12;
    cudaLaunchConfig_t lc = cfgof(256, 256, 0, layer > 0 && PDL_LN);
    cudaLaunchKernelEx(&lc, ln_kernel, xcur, P.xn, P.xh, zar, nzar, zkv, nzkv, Wk, Wv, layer == 0 ? PF_A : 0, tl + 0);
    ca.tl = tl + 2; ca.dry = 1;
#ifdef TUNE
    if (getenv("DRY")) ca.dry = (atoi(getenv("DRY")) >> layer) & 1;
#endif
    lc = cfgof(96, 384, ch::SMEM, PDL_CH);
    cudaLaunchKernelEx(&lc, chain_kernel, ca, tmCq, tmCk, tmCv, tmCo);
    lc = cfgof(TRAIL_GRID, 384, tr::SMEM, true);
    tr::Args ta{P.k, P.v, (unsigned char*)P.o, P.qs, (unsigned char*)P.part, xcur, P.xn, P.xa, P.xn2, P.arena, P.go, tl + 4, 30, 20, layer == 0, 1};
#ifdef TUNE
    if (getenv("NAP")) ta.nap = atoi(getenv("NAP"));
    if (getenv("PFQ")) ta.pfq = atoi(getenv("PFQ"));
    if (getenv("NAP2")) ta.nap2 = atoi(getenv("NAP2"));
#endif
    cudaLaunchKernelEx(&lc, trail_kernel, tmXn, tmWq, tmWo5, tmWo2, tmP, sched_of(layer), ta, pa);
    lc = cfgof(128, 384, bf::SMEM, PDL_B);
    bf::Args ba{(const unsigned char*)P.wb, (const unsigned char*)P.wot, (unsigned char*)P.kvacc, (unsigned char*)P.pq, P.xa, layer == 0 ? P.xb : out, P.go, layer == 0 ? P.arena + tr::C_P : nullptr,
                      layer == 0 && PF_B ? Wk : nullptr, Wv, 30, 500, 0, tl + 7};
#ifdef TUNE
    if (getenv("PFN")) ba.pfn = atoi(getenv("PFN"));
    if (getenv("PFNS")) ba.pfns = atoi(getenv("PFNS"));
    if (getenv("PFWT")) ba.pfwait = atoi(getenv("PFWT"));
    if (getenv("PFB")) ba.pf0 = layer == 0 && atoi(getenv("PFB")) ? Wk : nullptr;
#endif
    cudaLaunchKernelEx(&lc, blayer_kernel, tmXn2, ba);
    xcur = P.xb;
  }
}
```

```cpp
#include <cuda_runtime.h>
#include <cuda.h>
#include <cuda_bf16.h>
#include <stdint.h>
#include <stdlib.h>
#include <type_traits>

typedef __nv_bfloat16 bf16;

namespace cfg {
constexpr int S = 2048, DM = 640, H = 32, DH = 192, NSEG = 64, SEG = 32, NM = 8;
constexpr int HD = H * DH;
}

__device__ __forceinline__ uint32_t smem_u32(const void* p) { return (uint32_t)__cvta_generic_to_shared(p); }
__device__ __forceinline__ uint32_t mapa_u32(uint32_t a, uint32_t r) {
  uint32_t o; asm("mapa.shared::cluster.u32 %0, %1, %2;" : "=r"(o) : "r"(a), "r"(r)); return o;
}
__device__ __forceinline__ void mbar_init(uint32_t b, uint32_t c) {
  asm volatile("mbarrier.init.shared::cta.b64 [%0], %1;" :: "r"(b), "r"(c) : "memory");
}
__device__ __forceinline__ void mbar_expect_tx(uint32_t b, uint32_t bytes) {
  asm volatile("mbarrier.arrive.expect_tx.shared::cta.b64 _, [%0], %1;" :: "r"(b), "r"(bytes) : "memory");
}
__device__ __forceinline__ void mbar_arrive(uint32_t b) {
  asm volatile("mbarrier.arrive.shared::cta.b64 _, [%0];" :: "r"(b) : "memory");
}
__device__ __forceinline__ void mbar_expect_tx_if(bool c, uint32_t b, uint32_t bytes) {
  asm volatile("{\n.reg .pred p;\nsetp.ne.u32 p, %2, 0;\n@p mbarrier.arrive.expect_tx.shared::cta.b64 _, [%0], %1;\n}" :: "r"(b), "r"(bytes), "r"((uint32_t)c) : "memory");
}
__device__ __forceinline__ void mbar_arrive_if(bool c, uint32_t b) {
  asm volatile("{\n.reg .pred p;\nsetp.ne.u32 p, %1, 0;\n@p mbarrier.arrive.shared::cta.b64 _, [%0];\n}" :: "r"(b), "r"((uint32_t)c) : "memory");
}
__device__ __forceinline__ bool mbar_try(uint32_t b, uint32_t ph) {
  uint32_t p;
  asm volatile("{.reg .pred p; mbarrier.try_wait.parity.shared::cta.b64 p, [%1], %2; selp.u32 %0, 1, 0, p;}"
               : "=r"(p) : "r"(b), "r"(ph) : "memory");
  return p;
}
__device__ __forceinline__ bool mbar_try_cluster(uint32_t b, uint32_t ph) {
  uint32_t p;
  asm volatile("{.reg .pred p; mbarrier.try_wait.parity.acquire.cluster.shared::cta.b64 p, [%1], %2; selp.u32 %0, 1, 0, p;}"
               : "=r"(p) : "r"(b), "r"(ph) : "memory");
  return p;
}
#ifndef SPIN_LIMIT
#define SPIN_LIMIT (1 << 20)
#endif
__device__ __forceinline__ void mbar_wait(uint32_t b, uint32_t ph) {
  asm volatile("{\n.reg .pred p, q;\n.reg .u32 c;\nmov.u32 c, 0;\n"
               "W_%=:\nmbarrier.try_wait.parity.shared::cta.b64 p, [%0], %1;\n@p bra.uni D_%=;\n"
               "add.u32 c, c, 1;\nsetp.lt.u32 q, c, %2;\n@q bra.uni W_%=;\nD_%=:\n}"
               :: "r"(b), "r"(ph), "n"(SPIN_LIMIT) : "memory");
}
__device__ __forceinline__ void mbar_wait_if(bool cnd, uint32_t b, uint32_t ph) {
  asm volatile("{\n.reg .pred p, q;\n.reg .u32 c;\nsetp.eq.u32 q, %3, 0;\n@q bra.uni D_%=;\nmov.u32 c, 0;\n"
               "W_%=:\nmbarrier.try_wait.parity.shared::cta.b64 p, [%0], %1;\n@p bra.uni D_%=;\n"
               "add.u32 c, c, 1;\nsetp.lt.u32 q, c, %2;\n@q bra.uni W_%=;\nD_%=:\n}"
               :: "r"(b), "r"(ph), "n"(SPIN_LIMIT), "r"((uint32_t)cnd) : "memory");
}
__device__ __forceinline__ void mbar_spin(uint32_t b, uint32_t ph) {
  asm volatile("{\n.reg .pred p, q;\n.reg .u32 c;\nmov.u32 c, 0;\n"
               "W_%=:\nmbarrier.test_wait.parity.shared::cta.b64 p, [%0], %1;\n@p bra D_%=;\n"
               "add.u32 c, c, 1;\nsetp.lt.u32 q, c, %2;\n@q bra W_%=;\nD_%=:\n}"
               :: "r"(b), "r"(ph), "n"(SPIN_LIMIT) : "memory");
}
#define PIN(x) asm volatile("" : "+r"(x))
__device__ __forceinline__ void mbar_wait_cluster(uint32_t b, uint32_t ph) {
  int s = 0;
  while (!mbar_try_cluster(b, ph)) { if (++s > SPIN_LIMIT) break; }
}
__device__ __forceinline__ void st_async_v2(uint32_t a, uint32_t x, uint32_t y, uint32_t mb) {
  asm volatile("st.async.weak.shared::cluster.mbarrier::complete_tx::bytes.v2.b32 [%0], {%1,%2}, [%3];"
               :: "r"(a), "r"(x), "r"(y), "r"(mb) : "memory");
}
__device__ __forceinline__ void st_async_v4(uint32_t a, uint32_t x, uint32_t y, uint32_t z, uint32_t w, uint32_t mb) {
  asm volatile("st.async.weak.shared::cluster.mbarrier::complete_tx::bytes.v4.b32 [%0], {%1,%2,%3,%4}, [%5];"
               :: "r"(a), "r"(x), "r"(y), "r"(z), "r"(w), "r"(mb) : "memory");
}
__device__ __forceinline__ void bulk_g2s(uint32_t dst, const void* src, uint32_t bytes, uint32_t mb) {
  asm volatile("cp.async.bulk.shared::cluster.global.mbarrier::complete_tx::bytes [%0], [%1], %2, [%3];"
               :: "r"(dst), "l"(src), "r"(bytes), "r"(mb) : "memory");
}
__device__ __forceinline__ void cp_async16(uint32_t dst, const void* src) {
  asm volatile("cp.async.cg.shared.global [%0], [%1], 16;" :: "r"(dst), "l"(src) : "memory");
}
__device__ __forceinline__ void cp_async_wait_all() { asm volatile("cp.async.wait_all;" ::: "memory"); }
__device__ __forceinline__ void fence_proxy_async() { asm volatile("fence.proxy.async.shared::cta;" ::: "memory"); }
__device__ __forceinline__ void bar_sync(int id, int n) { asm volatile("bar.sync %0, %1;" :: "r"(id), "r"(n) : "memory"); }
__device__ __forceinline__ void bar_arrive(int id, int n) { asm volatile("bar.arrive %0, %1;" :: "r"(id), "r"(n) : "memory"); }
__device__ __forceinline__ void cluster_sync_all() {
  asm volatile("barrier.cluster.arrive.release.aligned; barrier.cluster.wait.acquire.aligned;" ::: "memory");
}
__device__ __forceinline__ void ldsm_x4(uint32_t (&r)[4], uint32_t a) {
  asm volatile("ldmatrix.sync.aligned.m8n8.x4.shared.b16 {%0,%1,%2,%3}, [%4];"
               : "=r"(r[0]), "=r"(r[1]), "=r"(r[2]), "=r"(r[3]) : "r"(a) : "memory");
}
__device__ __forceinline__ void ldsm_x4_t(uint32_t (&r)[4], uint32_t a) {
  asm volatile("ldmatrix.sync.aligned.m8n8.x4.trans.shared.b16 {%0,%1,%2,%3}, [%4];"
               : "=r"(r[0]), "=r"(r[1]), "=r"(r[2]), "=r"(r[3]) : "r"(a) : "memory");
}
template <int IMM> __device__ __forceinline__ void ldsm_x4_i(uint32_t (&r)[4], uint32_t a) {
  asm volatile("ldmatrix.sync.aligned.m8n8.x4.shared.b16 {%0,%1,%2,%3}, [%4+%5];"
               : "=r"(r[0]), "=r"(r[1]), "=r"(r[2]), "=r"(r[3]) : "r"(a), "n"(IMM) : "memory");
}
template <int IMM> __device__ __forceinline__ void ldsm_x4_t_i(uint32_t (&r)[4], uint32_t a) {
  asm volatile("ldmatrix.sync.aligned.m8n8.x4.trans.shared.b16 {%0,%1,%2,%3}, [%4+%5];"
               : "=r"(r[0]), "=r"(r[1]), "=r"(r[2]), "=r"(r[3]) : "r"(a), "n"(IMM) : "memory");
}
template <int IMM> __device__ __forceinline__ uint4 lds128_i(uint32_t a) {
  uint4 v; asm volatile("ld.shared.v4.u32 {%0,%1,%2,%3}, [%4+%5];" : "=r"(v.x), "=r"(v.y), "=r"(v.z), "=r"(v.w) : "r"(a), "n"(IMM) : "memory"); return v;
}
template <int IMM> __device__ __forceinline__ uint2 lds64_i(uint32_t a) {
  uint2 v; asm volatile("ld.shared.v2.u32 {%0,%1}, [%2+%3];" : "=r"(v.x), "=r"(v.y) : "r"(a), "n"(IMM) : "memory"); return v;
}
template <int IMM> __device__ __forceinline__ void sts128_i(uint32_t a, uint32_t x, uint32_t y, uint32_t z, uint32_t w) {
  asm volatile("st.shared.v4.u32 [%0+%5], {%1,%2,%3,%4};" :: "r"(a), "r"(x), "r"(y), "r"(z), "r"(w), "n"(IMM) : "memory");
}
template <int IMM> __device__ __forceinline__ void sts64_i(uint32_t a, uint32_t x, uint32_t y) {
  asm volatile("st.shared.v2.u32 [%0+%3], {%1,%2};" :: "r"(a), "r"(x), "r"(y), "n"(IMM) : "memory");
}
template <int IMM> __device__ __forceinline__ void st_async_v2_i(uint32_t a, uint32_t x, uint32_t y, uint32_t mb) {
  asm volatile("st.async.weak.shared::cluster.mbarrier::complete_tx::bytes.v2.b32 [%0+%4], {%1,%2}, [%3];"
               :: "r"(a), "r"(x), "r"(y), "r"(mb), "n"(IMM) : "memory");
}
template <int IMM> __device__ __forceinline__ uint4 ld_relaxed_v4_i(const void* p) {
  uint4 v; asm volatile("ld.relaxed.gpu.global.v4.u32 {%0,%1,%2,%3}, [%4+%5];" : "=r"(v.x), "=r"(v.y), "=r"(v.z), "=r"(v.w) : "l"(p), "n"(IMM) : "memory"); return v;
}
template <int I, int N, class F> __device__ __forceinline__ void static_for(F&& f) {
  if constexpr (I < N) { f(std::integral_constant<int, I>{}); static_for<I + 1, N>(f); }
}
__device__ __forceinline__ uint32_t movm_t(uint32_t a) {
  uint32_t d; asm volatile("movmatrix.sync.aligned.m8n8.trans.b16 %0, %1;" : "=r"(d) : "r"(a)); return d;
}
__device__ __forceinline__ void mma16816(float (&d)[4], uint32_t a0, uint32_t a1, uint32_t a2, uint32_t a3, uint32_t b0, uint32_t b1) {
  asm volatile("mma.sync.aligned.m16n8k16.row.col.f32.bf16.bf16.f32 {%0,%1,%2,%3}, {%4,%5,%6,%7}, {%8,%9}, {%0,%1,%2,%3};"
               : "+f"(d[0]), "+f"(d[1]), "+f"(d[2]), "+f"(d[3]) : "r"(a0), "r"(a1), "r"(a2), "r"(a3), "r"(b0), "r"(b1));
}
__device__ __forceinline__ uint32_t pack_bf16(float lo, float hi) {
  uint32_t d; asm("cvt.rn.bf16x2.f32 %0, %1, %2;" : "=r"(d) : "f"(hi), "f"(lo)); return d;
}
__device__ __forceinline__ float bf_lo(uint32_t w) { return __uint_as_float(w << 16); }
__device__ __forceinline__ float bf_hi(uint32_t w) { return __uint_as_float(w & 0xffff0000u); }
__device__ __forceinline__ uint4 lds128(uint32_t a) {
  uint4 v; asm volatile("ld.shared.v4.u32 {%0,%1,%2,%3}, [%4];" : "=r"(v.x), "=r"(v.y), "=r"(v.z), "=r"(v.w) : "r"(a) : "memory"); return v;
}
__device__ __forceinline__ uint2 lds64(uint32_t a) {
  uint2 v; asm volatile("ld.shared.v2.u32 {%0,%1}, [%2];" : "=r"(v.x), "=r"(v.y) : "r"(a) : "memory"); return v;
}
__device__ __forceinline__ void sts128(uint32_t a, uint32_t x, uint32_t y, uint32_t z, uint32_t w) {
  asm volatile("st.shared.v4.u32 [%0], {%1,%2,%3,%4};" :: "r"(a), "r"(x), "r"(y), "r"(z), "r"(w) : "memory");
}
__device__ __forceinline__ void sts64(uint32_t a, uint32_t x, uint32_t y) {
  asm volatile("st.shared.v2.u32 [%0], {%1,%2};" :: "r"(a), "r"(x), "r"(y) : "memory");
}
__device__ __forceinline__ uint4 ld_relaxed_v4(const void* p) {
  uint4 v; asm volatile("ld.relaxed.gpu.global.v4.u32 {%0,%1,%2,%3}, [%4];" : "=r"(v.x), "=r"(v.y), "=r"(v.z), "=r"(v.w) : "l"(p) : "memory"); return v;
}
__device__ __forceinline__ uint32_t ld_relaxed_u32(const void* p) {
  uint32_t v; asm volatile("ld.relaxed.gpu.global.u32 %0, [%1];" : "=r"(v) : "l"(p) : "memory"); return v;
}
__device__ __forceinline__ void st_relaxed_v2(void* p, uint32_t a, uint32_t b) {
  asm volatile("st.relaxed.gpu.global.v2.u32 [%0], {%1,%2};" :: "l"(p), "r"(a), "r"(b) : "memory");
}
__device__ __forceinline__ void st_relaxed_u32(void* p, uint32_t v) {
  asm volatile("st.relaxed.gpu.global.u32 [%0], %1;" :: "l"(p), "r"(v) : "memory");
}
__device__ __forceinline__ void st_release_u32(void* p, uint32_t v) {
  asm volatile("st.release.gpu.global.u32 [%0], %1;" :: "l"(p), "r"(v) : "memory");
}
__device__ __forceinline__ void red_release_inc(void* p) { asm volatile("red.release.gpu.global.add.u32 [%0], 1;" :: "l"(p) : "memory"); }
__device__ __forceinline__ uint32_t clk32() { uint32_t c; asm volatile("mov.u32 %0, %%clock;" : "=r"(c) :: "memory"); return c; }
__device__ __forceinline__ uint32_t clkdep(uint32_t v) {
  uint32_t c; asm volatile("{.reg .pred p; setp.eq.u32 p, %1, 0xdeadbeef; @p trap; mov.u32 %0, %%clock;}" : "=r"(c) : "r"(v) : "memory"); return c;
}
__device__ __forceinline__ void wgmma_fence() { asm volatile("wgmma.fence.sync.aligned;" ::: "memory"); }
__device__ __forceinline__ void wgmma_commit() { asm volatile("wgmma.commit_group.sync.aligned;" ::: "memory"); }
template <int N> __device__ __forceinline__ void wgmma_wait() { asm volatile("wgmma.wait_group.sync.aligned %0;" :: "n"(N) : "memory"); }
__device__ __forceinline__ void wgmma_n8_ss_ta(float (&d)[4], uint64_t da, uint64_t db, int acc) {
  asm volatile("{\n.reg .pred p;\nsetp.ne.b32 p, %6, 0;\n"
               "wgmma.mma_async.sync.aligned.m64n8k16.f32.bf16.bf16 {%0,%1,%2,%3}, %4, %5, p, 1, 1, 1, 0;\n}\n"
               : "+f"(d[0]), "+f"(d[1]), "+f"(d[2]), "+f"(d[3]) : "l"(da), "l"(db), "r"(acc));
}
__device__ __forceinline__ uint64_t make_desc(uint32_t saddr, uint32_t lbo_bytes, uint32_t sbo_bytes, uint32_t swz) {
  return (uint64_t)((saddr & 0x3FFFF) >> 4) | ((uint64_t)(lbo_bytes >> 4) << 16) | ((uint64_t)(sbo_bytes >> 4) << 32) | ((uint64_t)swz << 62);
}


template <uint32_t LBO, uint32_t SBO, uint32_t SWZ> __device__ __forceinline__ uint64_t desc16(uint32_t a16, uint32_t off = 0) {
  return (uint64_t)(a16 + ((off >> 4) + ((LBO >> 4) << 16))) | ((uint64_t)((SBO >> 4) | (SWZ << 30)) << 32);
}

__device__ __forceinline__ bool elect_one() {
  uint32_t p; asm volatile("{\n.reg .pred p;\nelect.sync _|p, 0xffffffff;\nselp.u32 %0, 1, 0, p;\n}" : "=r"(p)); return p;
}
__device__ __forceinline__ void tma_load_4d(uint32_t dst, const CUtensorMap* tm, int c0, int c1, int c2, int c3, uint32_t mb) {
  asm volatile("cp.async.bulk.tensor.4d.shared::cluster.global.mbarrier::complete_tx::bytes [%0], [%1, {%3, %4, %5, %6}], [%2];"
               :: "r"(dst), "l"(tm), "r"(mb), "r"(c0), "r"(c1), "r"(c2), "r"(c3) : "memory");
}
__device__ __forceinline__ void tma_load_3d(uint32_t dst, const CUtensorMap* tm, int c0, int c1, int c2, uint32_t mb) {
  asm volatile("cp.async.bulk.tensor.3d.shared::cluster.global.mbarrier::complete_tx::bytes [%0], [%1, {%3, %4, %5}], [%2];"
               :: "r"(dst), "l"(tm), "r"(mb), "r"(c0), "r"(c1), "r"(c2) : "memory");
}
__device__ __forceinline__ void tma_load_2d(uint32_t dst, const CUtensorMap* tm, int c0, int c1, uint32_t mb) {
  asm volatile("cp.async.bulk.tensor.2d.shared::cluster.global.mbarrier::complete_tx::bytes [%0], [%1, {%3, %4}], [%2];"
               :: "r"(dst), "l"(tm), "r"(mb), "r"(c0), "r"(c1) : "memory");
}
__device__ __forceinline__ void bulk_s2g(void* dst, uint32_t src, uint32_t bytes) {
  asm volatile("cp.async.bulk.global.shared::cta.bulk_group [%0], [%1], %2;" :: "l"(dst), "r"(src), "r"(bytes) : "memory");
}
__device__ __forceinline__ uint64_t policy_evict_first() {
  uint64_t p; asm volatile("createpolicy.fractional.L2::evict_first.b64 %0, 1.0;" : "=l"(p)); return p;
}
__device__ __forceinline__ void bulk_s2g_hint(void* dst, uint32_t src, uint32_t bytes, uint64_t pol) {
  asm volatile("cp.async.bulk.global.shared::cta.bulk_group.L2::cache_hint [%0], [%1], %2, %3;" :: "l"(dst), "r"(src), "r"(bytes), "l"(pol) : "memory");
}
__device__ __forceinline__ void bulk_commit() { asm volatile("cp.async.bulk.commit_group;" ::: "memory"); }
template <int N> __device__ __forceinline__ void bulk_wait_read() { asm volatile("cp.async.bulk.wait_group.read %0;" :: "n"(N) : "memory"); }
template <int N> __device__ __forceinline__ void bulk_wait() { asm volatile("cp.async.bulk.wait_group %0;" :: "n"(N) : "memory"); }
__device__ __forceinline__ void stsm_x4(uint32_t a, uint32_t r0, uint32_t r1, uint32_t r2, uint32_t r3) {
  asm volatile("stmatrix.sync.aligned.m8n8.x4.shared.b16 [%0], {%1,%2,%3,%4};" :: "r"(a), "r"(r0), "r"(r1), "r"(r2), "r"(r3) : "memory");
}
__device__ __forceinline__ void stsm_x2(uint32_t a, uint32_t r0, uint32_t r1) {
  asm volatile("stmatrix.sync.aligned.m8n8.x2.shared.b16 [%0], {%1,%2};" :: "r"(a), "r"(r0), "r"(r1) : "memory");
}
__device__ __forceinline__ void ldsm_x2(uint32_t (&r)[2], uint32_t a) {
  asm volatile("ldmatrix.sync.aligned.m8n8.x2.shared.b16 {%0,%1}, [%2];" : "=r"(r[0]), "=r"(r[1]) : "r"(a) : "memory");
}
__device__ __forceinline__ void ldsm_x2_t(uint32_t (&r)[2], uint32_t a) {
  asm volatile("ldmatrix.sync.aligned.m8n8.x2.trans.shared.b16 {%0,%1}, [%2];" : "=r"(r[0]), "=r"(r[1]) : "r"(a) : "memory");
}
__device__ __forceinline__ float bf16r(float x) { return __uint_as_float(pack_bf16(0.f, x) & 0xffff0000u); }
__device__ __forceinline__ void bf16r2(float& a, float& b) { const uint32_t w = pack_bf16(a, b); a = bf_lo(w); b = bf_hi(w); }
__device__ __forceinline__ float rcpf(float x) { float r; asm("rcp.approx.ftz.f32 %0, %1;" : "=f"(r) : "f"(x)); return r; }
__device__ __forceinline__ float ex2f(float x) { float e; asm("ex2.approx.ftz.f32 %0, %1;" : "=f"(e) : "f"(x)); return e; }
__device__ __forceinline__ void prefetch_tmap(const CUtensorMap* tm) { asm volatile("prefetch.tensormap [%0];" :: "l"(tm) : "memory"); }

#ifdef TLLITE
__device__ unsigned long long g_lite[8];
__device__ __forceinline__ void lite(int i) { unsigned long long t; asm volatile("mov.u64 %0, %%globaltimer;" : "=l"(t)); g_lite[i] = t; }
#define LITE(c, i) do { if (c) lite(i); } while (0)
#else
#define LITE(c, i)
#endif
#ifdef TIMELINE
__device__ unsigned long long g_tl[2 * 64];
__device__ unsigned g_step[2 * 64 * 96 * 4];
__device__ unsigned long long g_log[2 * 132 * 64 * 2 + 2];
__device__ unsigned long long g_tl2[4 * 64];
__device__ __forceinline__ unsigned long long gtime() { unsigned long long t; asm volatile("mov.u64 %0, %%globaltimer;" : "=l"(t)); return t; }
#define TL_BEGIN(id) do { if (threadIdx.x == 0) atomicMin(&g_tl[2 * (id)], gtime()); } while (0)
#define TL_END(id) do { if ((threadIdx.x & 31) == 0) atomicMax(&g_tl[2 * (id) + 1], gtime()); } while (0)
#define TL_ACC(idx, t0) do { if (threadIdx.x == 0 && m >= 4 && m < 11) { atomicAdd(&g_tl2[idx], gtime() - (t0)); atomicAdd(&g_tl2[(idx) + 1], 1ull); } } while (0)
#define TL_NOW() gtime()
#define TL2(idx) asm volatile("{\n.reg .pred p;\nsetp.eq.u32 p, %2, 0;\n@p red.relaxed.gpu.global.max.u64 [%0], %1;\n}" :: "l"(&g_tl2[idx]), "l"(gtime()), "r"(threadIdx.x) : "memory")
#define TLW(idx) asm volatile("{\n.reg .pred p;\nsetp.eq.u32 p, %2, 0;\n@p red.relaxed.gpu.global.max.u64 [%0], %1;\n@p red.relaxed.gpu.global.add.u64 [%0+128], %1;\n}" :: "l"(&g_tl2[idx]), "l"(gtime() - g_tl0), "r"(threadIdx.x & 31) : "memory")
#define TL_BEGIN0(id) atomicMin(&g_tl[2 * (id)], gtime())
#else
#define TL_ACC(idx, t0)
#define TL_NOW() 0ull
#define TL2(idx)
#define TL_BEGIN0(id)
#define TLW(idx)
#define TL_BEGIN(id)
#define TL_END(id)
#endif
template <int TA, int TB> __device__ __forceinline__ void wgmma_n24(float (&d)[12], uint64_t da, uint64_t db, int acc) {
  asm volatile("{\n.reg .pred p;\nsetp.ne.b32 p, %14, 0;\n"
    "wgmma.mma_async.sync.aligned.m64n24k16.f32.bf16.bf16 {%0, %1, %2, %3, %4, %5, %6, %7, %8, %9, %10, %11}, %12, %13, p, 1, 1, %15, %16;\n}\n"
    : "+f"(d[0]), "+f"(d[1]), "+f"(d[2]), "+f"(d[3]), "+f"(d[4]), "+f"(d[5]), "+f"(d[6]), "+f"(d[7]), "+f"(d[8]), "+f"(d[9]), "+f"(d[10]), "+f"(d[11])
    : "l"(da), "l"(db), "r"(acc), "n"(TA), "n"(TB));
}

template <int TA, int TB> __device__ __forceinline__ void wgmma_n80(float (&d)[40], uint64_t da, uint64_t db, int acc) {
  asm volatile("{\n.reg .pred p;\nsetp.ne.b32 p, %42, 0;\n"
    "wgmma.mma_async.sync.aligned.m64n80k16.f32.bf16.bf16 {%0, %1, %2, %3, %4, %5, %6, %7, %8, %9, %10, %11, %12, %13, %14, %15, %16, %17, %18, %19, %20, %21, %22, %23, %24, %25, %26, %27, %28, %29, %30, %31, %32, %33, %34, %35, %36, %37, %38, %39}, %40, %41, p, 1, 1, %43, %44;\n}\n"
    : "+f"(d[0]), "+f"(d[1]), "+f"(d[2]), "+f"(d[3]), "+f"(d[4]), "+f"(d[5]), "+f"(d[6]), "+f"(d[7]), "+f"(d[8]), "+f"(d[9]), "+f"(d[10]), "+f"(d[11]), "+f"(d[12]), "+f"(d[13]), "+f"(d[14]), "+f"(d[15]), "+f"(d[16]), "+f"(d[17]), "+f"(d[18]), "+f"(d[19]), "+f"(d[20]), "+f"(d[21]), "+f"(d[22]), "+f"(d[23]), "+f"(d[24]), "+f"(d[25]), "+f"(d[26]), "+f"(d[27]), "+f"(d[28]), "+f"(d[29]), "+f"(d[30]), "+f"(d[31]), "+f"(d[32]), "+f"(d[33]), "+f"(d[34]), "+f"(d[35]), "+f"(d[36]), "+f"(d[37]), "+f"(d[38]), "+f"(d[39])
    : "l"(da), "l"(db), "r"(acc), "n"(TA), "n"(TB));
}

template <int TA, int TB> __device__ __forceinline__ void wgmma_n128(float (&d)[64], uint64_t da, uint64_t db, int acc) {
  asm volatile("{\n.reg .pred p;\nsetp.ne.b32 p, %66, 0;\n"
    "wgmma.mma_async.sync.aligned.m64n128k16.f32.bf16.bf16 {%0, %1, %2, %3, %4, %5, %6, %7, %8, %9, %10, %11, %12, %13, %14, %15, %16, %17, %18, %19, %20, %21, %22, %23, %24, %25, %26, %27, %28, %29, %30, %31, %32, %33, %34, %35, %36, %37, %38, %39, %40, %41, %42, %43, %44, %45, %46, %47, %48, %49, %50, %51, %52, %53, %54, %55, %56, %57, %58, %59, %60, %61, %62, %63}, %64, %65, p, 1, 1, %67, %68;\n}\n"
    : "+f"(d[0]), "+f"(d[1]), "+f"(d[2]), "+f"(d[3]), "+f"(d[4]), "+f"(d[5]), "+f"(d[6]), "+f"(d[7]), "+f"(d[8]), "+f"(d[9]), "+f"(d[10]), "+f"(d[11]), "+f"(d[12]), "+f"(d[13]), "+f"(d[14]), "+f"(d[15]), "+f"(d[16]), "+f"(d[17]), "+f"(d[18]), "+f"(d[19]), "+f"(d[20]), "+f"(d[21]), "+f"(d[22]), "+f"(d[23]), "+f"(d[24]), "+f"(d[25]), "+f"(d[26]), "+f"(d[27]), "+f"(d[28]), "+f"(d[29]), "+f"(d[30]), "+f"(d[31]), "+f"(d[32]), "+f"(d[33]), "+f"(d[34]), "+f"(d[35]), "+f"(d[36]), "+f"(d[37]), "+f"(d[38]), "+f"(d[39]), "+f"(d[40]), "+f"(d[41]), "+f"(d[42]), "+f"(d[43]), "+f"(d[44]), "+f"(d[45]), "+f"(d[46]), "+f"(d[47]), "+f"(d[48]), "+f"(d[49]), "+f"(d[50]), "+f"(d[51]), "+f"(d[52]), "+f"(d[53]), "+f"(d[54]), "+f"(d[55]), "+f"(d[56]), "+f"(d[57]), "+f"(d[58]), "+f"(d[59]), "+f"(d[60]), "+f"(d[61]), "+f"(d[62]), "+f"(d[63])
    : "l"(da), "l"(db), "r"(acc), "n"(TA), "n"(TB));
}

template <int TA, int TB> __device__ __forceinline__ void wgmma_n192(float (&d)[96], uint64_t da, uint64_t db, int acc) {
  asm volatile("{\n.reg .pred p;\nsetp.ne.b32 p, %98, 0;\n"
    "wgmma.mma_async.sync.aligned.m64n192k16.f32.bf16.bf16 {%0, %1, %2, %3, %4, %5, %6, %7, %8, %9, %10, %11, %12, %13, %14, %15, %16, %17, %18, %19, %20, %21, %22, %23, %24, %25, %26, %27, %28, %29, %30, %31, %32, %33, %34, %35, %36, %37, %38, %39, %40, %41, %42, %43, %44, %45, %46, %47, %48, %49, %50, %51, %52, %53, %54, %55, %56, %57, %58, %59, %60, %61, %62, %63, %64, %65, %66, %67, %68, %69, %70, %71, %72, %73, %74, %75, %76, %77, %78, %79, %80, %81, %82, %83, %84, %85, %86, %87, %88, %89, %90, %91, %92, %93, %94, %95}, %96, %97, p, 1, 1, %99, %100;\n}\n"
    : "+f"(d[0]), "+f"(d[1]), "+f"(d[2]), "+f"(d[3]), "+f"(d[4]), "+f"(d[5]), "+f"(d[6]), "+f"(d[7]), "+f"(d[8]), "+f"(d[9]), "+f"(d[10]), "+f"(d[11]), "+f"(d[12]), "+f"(d[13]), "+f"(d[14]), "+f"(d[15]), "+f"(d[16]), "+f"(d[17]), "+f"(d[18]), "+f"(d[19]), "+f"(d[20]), "+f"(d[21]), "+f"(d[22]), "+f"(d[23]), "+f"(d[24]), "+f"(d[25]), "+f"(d[26]), "+f"(d[27]), "+f"(d[28]), "+f"(d[29]), "+f"(d[30]), "+f"(d[31]), "+f"(d[32]), "+f"(d[33]), "+f"(d[34]), "+f"(d[35]), "+f"(d[36]), "+f"(d[37]), "+f"(d[38]), "+f"(d[39]), "+f"(d[40]), "+f"(d[41]), "+f"(d[42]), "+f"(d[43]), "+f"(d[44]), "+f"(d[45]), "+f"(d[46]), "+f"(d[47]), "+f"(d[48]), "+f"(d[49]), "+f"(d[50]), "+f"(d[51]), "+f"(d[52]), "+f"(d[53]), "+f"(d[54]), "+f"(d[55]), "+f"(d[56]), "+f"(d[57]), "+f"(d[58]), "+f"(d[59]), "+f"(d[60]), "+f"(d[61]), "+f"(d[62]), "+f"(d[63]), "+f"(d[64]), "+f"(d[65]), "+f"(d[66]), "+f"(d[67]), "+f"(d[68]), "+f"(d[69]), "+f"(d[70]), "+f"(d[71]), "+f"(d[72]), "+f"(d[73]), "+f"(d[74]), "+f"(d[75]), "+f"(d[76]), "+f"(d[77]), "+f"(d[78]), "+f"(d[79]), "+f"(d[80]), "+f"(d[81]), "+f"(d[82]), "+f"(d[83]), "+f"(d[84]), "+f"(d[85]), "+f"(d[86]), "+f"(d[87]), "+f"(d[88]), "+f"(d[89]), "+f"(d[90]), "+f"(d[91]), "+f"(d[92]), "+f"(d[93]), "+f"(d[94]), "+f"(d[95])
    : "l"(da), "l"(db), "r"(acc), "n"(TA), "n"(TB));
}

template <int TA, int TB> __device__ __forceinline__ void wgmma_n256(float (&d)[128], uint64_t da, uint64_t db, int acc) {
  asm volatile("{\n.reg .pred p;\nsetp.ne.b32 p, %130, 0;\n"
    "wgmma.mma_async.sync.aligned.m64n256k16.f32.bf16.bf16 {%0, %1, %2, %3, %4, %5, %6, %7, %8, %9, %10, %11, %12, %13, %14, %15, %16, %17, %18, %19, %20, %21, %22, %23, %24, %25, %26, %27, %28, %29, %30, %31, %32, %33, %34, %35, %36, %37, %38, %39, %40, %41, %42, %43, %44, %45, %46, %47, %48, %49, %50, %51, %52, %53, %54, %55, %56, %57, %58, %59, %60, %61, %62, %63, %64, %65, %66, %67, %68, %69, %70, %71, %72, %73, %74, %75, %76, %77, %78, %79, %80, %81, %82, %83, %84, %85, %86, %87, %88, %89, %90, %91, %92, %93, %94, %95, %96, %97, %98, %99, %100, %101, %102, %103, %104, %105, %106, %107, %108, %109, %110, %111, %112, %113, %114, %115, %116, %117, %118, %119, %120, %121, %122, %123, %124, %125, %126, %127}, %128, %129, p, 1, 1, %131, %132;\n}\n"
    : "+f"(d[0]), "+f"(d[1]), "+f"(d[2]), "+f"(d[3]), "+f"(d[4]), "+f"(d[5]), "+f"(d[6]), "+f"(d[7]), "+f"(d[8]), "+f"(d[9]), "+f"(d[10]), "+f"(d[11]), "+f"(d[12]), "+f"(d[13]), "+f"(d[14]), "+f"(d[15]), "+f"(d[16]), "+f"(d[17]), "+f"(d[18]), "+f"(d[19]), "+f"(d[20]), "+f"(d[21]), "+f"(d[22]), "+f"(d[23]), "+f"(d[24]), "+f"(d[25]), "+f"(d[26]), "+f"(d[27]), "+f"(d[28]), "+f"(d[29]), "+f"(d[30]), "+f"(d[31]), "+f"(d[32]), "+f"(d[33]), "+f"(d[34]), "+f"(d[35]), "+f"(d[36]), "+f"(d[37]), "+f"(d[38]), "+f"(d[39]), "+f"(d[40]), "+f"(d[41]), "+f"(d[42]), "+f"(d[43]), "+f"(d[44]), "+f"(d[45]), "+f"(d[46]), "+f"(d[47]), "+f"(d[48]), "+f"(d[49]), "+f"(d[50]), "+f"(d[51]), "+f"(d[52]), "+f"(d[53]), "+f"(d[54]), "+f"(d[55]), "+f"(d[56]), "+f"(d[57]), "+f"(d[58]), "+f"(d[59]), "+f"(d[60]), "+f"(d[61]), "+f"(d[62]), "+f"(d[63]), "+f"(d[64]), "+f"(d[65]), "+f"(d[66]), "+f"(d[67]), "+f"(d[68]), "+f"(d[69]), "+f"(d[70]), "+f"(d[71]), "+f"(d[72]), "+f"(d[73]), "+f"(d[74]), "+f"(d[75]), "+f"(d[76]), "+f"(d[77]), "+f"(d[78]), "+f"(d[79]), "+f"(d[80]), "+f"(d[81]), "+f"(d[82]), "+f"(d[83]), "+f"(d[84]), "+f"(d[85]), "+f"(d[86]), "+f"(d[87]), "+f"(d[88]), "+f"(d[89]), "+f"(d[90]), "+f"(d[91]), "+f"(d[92]), "+f"(d[93]), "+f"(d[94]), "+f"(d[95]), "+f"(d[96]), "+f"(d[97]), "+f"(d[98]), "+f"(d[99]), "+f"(d[100]), "+f"(d[101]), "+f"(d[102]), "+f"(d[103]), "+f"(d[104]), "+f"(d[105]), "+f"(d[106]), "+f"(d[107]), "+f"(d[108]), "+f"(d[109]), "+f"(d[110]), "+f"(d[111]), "+f"(d[112]), "+f"(d[113]), "+f"(d[114]), "+f"(d[115]), "+f"(d[116]), "+f"(d[117]), "+f"(d[118]), "+f"(d[119]), "+f"(d[120]), "+f"(d[121]), "+f"(d[122]), "+f"(d[123]), "+f"(d[124]), "+f"(d[125]), "+f"(d[126]), "+f"(d[127])
    : "l"(da), "l"(db), "r"(acc), "n"(TA), "n"(TB));
}

template <int TB> __device__ __forceinline__ void wgmma_rs_n24(float (&d)[12], uint32_t a0, uint32_t a1, uint32_t a2, uint32_t a3, uint64_t db, int acc) {
  asm volatile("{\n.reg .pred p;\nsetp.ne.b32 p, %17, 0;\n"
    "wgmma.mma_async.sync.aligned.m64n24k16.f32.bf16.bf16 {%0, %1, %2, %3, %4, %5, %6, %7, %8, %9, %10, %11}, {%12, %13, %14, %15}, %16, p, 1, 1, %18;\n}\n"
    : "+f"(d[0]), "+f"(d[1]), "+f"(d[2]), "+f"(d[3]), "+f"(d[4]), "+f"(d[5]), "+f"(d[6]), "+f"(d[7]), "+f"(d[8]), "+f"(d[9]), "+f"(d[10]), "+f"(d[11])
    : "r"(a0), "r"(a1), "r"(a2), "r"(a3), "l"(db), "r"(acc), "n"(TB));
}

template <int TB> __device__ __forceinline__ void wgmma_rs_n40(float (&d)[20], uint32_t a0, uint32_t a1, uint32_t a2, uint32_t a3, uint64_t db, int acc) {
  asm volatile("{\n.reg .pred p;\nsetp.ne.b32 p, %25, 0;\n"
    "wgmma.mma_async.sync.aligned.m64n40k16.f32.bf16.bf16 {%0, %1, %2, %3, %4, %5, %6, %7, %8, %9, %10, %11, %12, %13, %14, %15, %16, %17, %18, %19}, {%20, %21, %22, %23}, %24, p, 1, 1, %26;\n}\n"
    : "+f"(d[0]), "+f"(d[1]), "+f"(d[2]), "+f"(d[3]), "+f"(d[4]), "+f"(d[5]), "+f"(d[6]), "+f"(d[7]), "+f"(d[8]), "+f"(d[9]), "+f"(d[10]), "+f"(d[11]), "+f"(d[12]), "+f"(d[13]), "+f"(d[14]), "+f"(d[15]), "+f"(d[16]), "+f"(d[17]), "+f"(d[18]), "+f"(d[19])
    : "r"(a0), "r"(a1), "r"(a2), "r"(a3), "l"(db), "r"(acc), "n"(TB));
}

template <int TB> __device__ __forceinline__ void wgmma_rs_n192(float (&d)[96], uint32_t a0, uint32_t a1, uint32_t a2, uint32_t a3, uint64_t db, int acc) {
  asm volatile("{\n.reg .pred p;\nsetp.ne.b32 p, %101, 0;\n"
    "wgmma.mma_async.sync.aligned.m64n192k16.f32.bf16.bf16 {%0, %1, %2, %3, %4, %5, %6, %7, %8, %9, %10, %11, %12, %13, %14, %15, %16, %17, %18, %19, %20, %21, %22, %23, %24, %25, %26, %27, %28, %29, %30, %31, %32, %33, %34, %35, %36, %37, %38, %39, %40, %41, %42, %43, %44, %45, %46, %47, %48, %49, %50, %51, %52, %53, %54, %55, %56, %57, %58, %59, %60, %61, %62, %63, %64, %65, %66, %67, %68, %69, %70, %71, %72, %73, %74, %75, %76, %77, %78, %79, %80, %81, %82, %83, %84, %85, %86, %87, %88, %89, %90, %91, %92, %93, %94, %95}, {%96, %97, %98, %99}, %100, p, 1, 1, %102;\n}\n"
    : "+f"(d[0]), "+f"(d[1]), "+f"(d[2]), "+f"(d[3]), "+f"(d[4]), "+f"(d[5]), "+f"(d[6]), "+f"(d[7]), "+f"(d[8]), "+f"(d[9]), "+f"(d[10]), "+f"(d[11]), "+f"(d[12]), "+f"(d[13]), "+f"(d[14]), "+f"(d[15]), "+f"(d[16]), "+f"(d[17]), "+f"(d[18]), "+f"(d[19]), "+f"(d[20]), "+f"(d[21]), "+f"(d[22]), "+f"(d[23]), "+f"(d[24]), "+f"(d[25]), "+f"(d[26]), "+f"(d[27]), "+f"(d[28]), "+f"(d[29]), "+f"(d[30]), "+f"(d[31]), "+f"(d[32]), "+f"(d[33]), "+f"(d[34]), "+f"(d[35]), "+f"(d[36]), "+f"(d[37]), "+f"(d[38]), "+f"(d[39]), "+f"(d[40]), "+f"(d[41]), "+f"(d[42]), "+f"(d[43]), "+f"(d[44]), "+f"(d[45]), "+f"(d[46]), "+f"(d[47]), "+f"(d[48]), "+f"(d[49]), "+f"(d[50]), "+f"(d[51]), "+f"(d[52]), "+f"(d[53]), "+f"(d[54]), "+f"(d[55]), "+f"(d[56]), "+f"(d[57]), "+f"(d[58]), "+f"(d[59]), "+f"(d[60]), "+f"(d[61]), "+f"(d[62]), "+f"(d[63]), "+f"(d[64]), "+f"(d[65]), "+f"(d[66]), "+f"(d[67]), "+f"(d[68]), "+f"(d[69]), "+f"(d[70]), "+f"(d[71]), "+f"(d[72]), "+f"(d[73]), "+f"(d[74]), "+f"(d[75]), "+f"(d[76]), "+f"(d[77]), "+f"(d[78]), "+f"(d[79]), "+f"(d[80]), "+f"(d[81]), "+f"(d[82]), "+f"(d[83]), "+f"(d[84]), "+f"(d[85]), "+f"(d[86]), "+f"(d[87]), "+f"(d[88]), "+f"(d[89]), "+f"(d[90]), "+f"(d[91]), "+f"(d[92]), "+f"(d[93]), "+f"(d[94]), "+f"(d[95])
    : "r"(a0), "r"(a1), "r"(a2), "r"(a3), "l"(db), "r"(acc), "n"(TB));
}
constexpr uint32_t AR_ACC = 0;
constexpr uint32_t AR_TAB = 0x100000;
constexpr uint32_t AR_PROG = 0x101000;
__host__ __device__ constexpr uint32_t prog_off(int h, int j) { return AR_PROG + h * 128 + j * 4; }
constexpr uint32_t AR_CNT = 0x108000;
constexpr uint32_t AR_QUEUE = 0x109000;
constexpr uint32_t AR_SIZE = 0x10a000;

struct ChainArgs {
  const bf16* mem0;
  const uint2* xh;
  unsigned char *kg, *vg;
  unsigned char* arena;
  unsigned* go;
  uint32_t* dbg;
  uint32_t delay;
  int margin, pubrel, dry;
  int tl;
};

namespace ch {
constexpr int OFF_WQ = 0;
constexpr int OFF_X = 81920;
constexpr int OFF_MEM = OFF_X + 40960;
constexpr int OFF_WO = OFF_MEM + 10240;
constexpr int WOK = 8 * 896;
constexpr int OFF_KV = OFF_WO + 10 * WOK;
constexpr int KVB = 5120;
constexpr int OFF_O = OFF_KV + 4 * KVB;
constexpr int OFF_Q = OFF_O + 1024;
constexpr int OFF_S = OFF_O + 3072;
constexpr int OFF_SR = OFF_S + 1536;
constexpr int OFF_LT = OFF_SR + 1280;
constexpr int OFF_BAR = OFF_LT + 512;
constexpr int SMEM = OFF_BAR + 256;
static_assert(SMEM <= 232448, "smem");
constexpr int MB_S = OFF_BAR, MB_O = OFF_BAR + 8, MB_X = OFF_BAR + 16;
constexpr int MB_K = OFF_BAR + 128, MB_V = MB_K + 16, MB_Q = MB_K + 32, MB_R = MB_K + 48;
constexpr int SC_IN = OFF_BAR + 64;
constexpr int SC_MX = OFF_S;
constexpr int SC_TW = OFF_BAR + 48;
constexpr int SC_W = OFF_BAR + 96;
constexpr int WOS = 448;
enum { B_MEM0 = 1, B_QK, B_SL, B_V, B_O, B_RED, B_X, B_C, B_H, B_MEM1, B_A, B_G, B_E };
#ifndef NQ1
#define NQ1 14
#endif
#ifndef NQ0
#define NQ0 8
#endif
#ifndef NP0
#define NP0 5
#endif
#ifndef NWO
#define NWO 5
#endif
#ifndef NWP
#define NWP 4
#endif
#ifndef NB0
#define NB0 2
#endif
#ifndef BBS
#define BBS 100
#endif
#ifndef VSYNC
#define VSYNC 0
#endif
#ifndef XPOS
#define XPOS 0
#endif
#ifndef XPD
#define XPD 300
#endif
#ifndef WOF
#define WOF 0
#endif
#ifndef XBYTES
#define XBYTES 36864
#endif
#ifndef NRT
#define NRT 7
#endif
#ifndef NRF
#define NRF 2
#endif
#ifndef NPM0
#define NPM0 2
#endif
#ifndef NPM1
#define NPM1 2
#endif
#ifndef RSYNC
#define RSYNC 1
#endif
#ifndef PFK
#define PFK 1
#endif
#ifndef PA0
#define PA0 3
#endif
#ifndef PA1
#define PA1 0
#endif
#ifndef PB0
#define PB0 7
#endif
#ifndef PB1
#define PB1 5
#endif
#ifndef PQE
#define PQE 1
#endif
#ifndef XT
#define XT 38
#endif
static_assert(NPM0 >= 2 && NPM1 >= 2, "the K / V blocks live in the last two k-steps of Wo");
}

#ifndef CHAIN_TIMING
#define CHAIN_TIMING 0
#endif
#if CHAIN_TIMING
#ifndef TR0
#define TR0 41
#endif
#ifndef TSMASK
#define TSMASK 0xffff
#endif
#define TSV(i, v) do { if ((TSMASK >> (i)) & 1) asm volatile("st.shared.u32 [%0+%1], %2;" :: "r"(tsb), "n"((i) * 4), "r"(v) : "memory"); } while (0)
#define TS(i) TSV(i, clk32())
#define TS_SETUP() const uint32_t tsb = sb + ((s == TR0 || s == TR0 + 1) ? OFF_BAR + 128 + ((s - TR0) * 12 + warp) * 48 : OFF_SR + 1152)
#else
#define TS(i)
#define TSV(i, v)
#define TS_SETUP()
#endif
#ifndef POLL_DELAY
#define POLL_DELAY 620
#endif
#ifndef XN
#define XN 40
#endif
#ifndef PF0
#define PF0 8
#endif
#ifndef PFS
#define PFS 3
#endif
#ifndef XDELAY
#define XDELAY 0
#endif
#ifndef NOKM
#define NOKM 0
#endif
#ifndef PFX
#define PFX 3
#endif
#ifndef NVE
#define NVE 8
#endif
#ifndef VET
#define VET 19
#endif
#ifndef MEMFIRST
#define MEMFIRST 0
#endif
#ifndef PM1
#define PM1 1
#endif
#ifndef GD1
#define GD1 30
#endif
#ifndef GD2
#define GD2 150
#endif
#ifndef CEARLY
#define CEARLY 0
#endif
#ifndef NPL
#define NPL 2
#endif
#ifndef NP1
#define NP1 (NQ1 < 6 ? NQ1 : 6)
#endif
#ifndef PF2
#define PF2 0
#endif
#ifndef PFACC
#define PFACC 1
#endif
template <int V> using IC = std::integral_constant<int, V>;
__device__ __forceinline__ uint32_t clk_v() { uint64_t c; asm volatile("mov.u64 %0, %%clock64;" : "=l"(c) :: "memory"); return (uint32_t)c; }
__device__ __forceinline__ int fresh(int x) { int y; asm volatile("shfl.sync.bfly.b32 %0, %1, 0, 0x1f, 0xffffffff;" : "=r"(y) : "r"(x)); return y; }
#define SFENCE2(x, d) asm volatile("{\n.reg .pred p;\nsetp.eq.u32 p, %0, 0x7fffffff;\n@p st.shared.u32 [%0], %1;\n}" :: "r"(x), "r"(d) : "memory")
#define SFENCE(x) asm volatile("{\n.reg .pred p;\nsetp.eq.u32 p, %0, 0x7fffffff;\n@p st.shared.u32 [%0], %0;\n}" :: "r"(x) : "memory")
template <int I> __device__ __forceinline__ void bbfence(uint32_t x) {
  asm volatile("{\n.reg .pred p;\nsetp.eq.u32 p, %0, %1;\nL_%=:\n@p st.volatile.shared.u32 [%0], %0;\n@p bra.uni L_%=;\n}" :: "r"(x), "n"(4 * I) : "memory");
}
__device__ __forceinline__ float uniform_f(float x) { return __uint_as_float(__reduce_max_sync(0xffffffffu, __float_as_uint(x))); }

__device__ __forceinline__ void mma16816h(float (&d)[4], const uint32_t (&a)[4], uint32_t b0, uint32_t b1) {
  asm volatile("mma.sync.aligned.m16n8k16.row.col.f32.f16.f16.f32 {%0,%1,%2,%3}, {%4,%5,%6,%7}, {%8,%9}, {%0,%1,%2,%3};"
               : "+f"(d[0]), "+f"(d[1]), "+f"(d[2]), "+f"(d[3]) : "r"(a[0]), "r"(a[1]), "r"(a[2]), "r"(a[3]), "r"(b0), "r"(b1));
}
__device__ __forceinline__ void mma1688(float (&d)[4], uint32_t a0, uint32_t a1, uint32_t b0) {
  asm volatile("mma.sync.aligned.m16n8k8.row.col.f32.bf16.bf16.f32 {%0,%1,%2,%3}, {%4,%5}, {%6}, {%0,%1,%2,%3};"
               : "+f"(d[0]), "+f"(d[1]), "+f"(d[2]), "+f"(d[3]) : "r"(a0), "r"(a1), "r"(b0));
}
template <int OFF16, int ACC> __device__ __forceinline__ void wgmma_rs32h(float (&d)[16], const uint32_t (&a)[4], uint32_t dlo) {
  asm volatile("{\n.reg .pred p;\n.reg .b32 t;\n.reg .b64 db;\nsetp.ne.b32 p, %22, 0;\nadd.u32 t, %20, %21;\nmov.b64 db, {t, 0x40000040};\n"
    "wgmma.mma_async.sync.aligned.m64n32k16.f32.f16.f16 {%0,%1,%2,%3,%4,%5,%6,%7,%8,%9,%10,%11,%12,%13,%14,%15}, {%16,%17,%18,%19}, db, p, 1, 1, 0;\n}\n"
    : "+f"(d[0]), "+f"(d[1]), "+f"(d[2]), "+f"(d[3]), "+f"(d[4]), "+f"(d[5]), "+f"(d[6]), "+f"(d[7]), "+f"(d[8]), "+f"(d[9]), "+f"(d[10]), "+f"(d[11]),
      "+f"(d[12]), "+f"(d[13]), "+f"(d[14]), "+f"(d[15])
    : "r"(a[0]), "r"(a[1]), "r"(a[2]), "r"(a[3]), "r"(dlo), "n"(OFF16), "n"(ACC));
}
template <int IMM> __device__ __forceinline__ void stsm_x4_t_i(uint32_t a, uint32_t r0, uint32_t r1, uint32_t r2, uint32_t r3) {
  asm volatile("stmatrix.sync.aligned.m8n8.x4.trans.shared.b16 [%0+%5], {%1,%2,%3,%4};" :: "r"(a), "r"(r0), "r"(r1), "r"(r2), "r"(r3), "n"(IMM) : "memory");
}
template <int IMM> __device__ __forceinline__ void stsm_x2_t_i(uint32_t a, uint32_t r0, uint32_t r1) {
  asm volatile("stmatrix.sync.aligned.m8n8.x2.trans.shared.b16 [%0+%3], {%1,%2};" :: "r"(a), "r"(r0), "r"(r1), "n"(IMM) : "memory");
}
template <int IMM> __device__ __forceinline__ void st_async_b32_i(uint32_t a, uint32_t x, uint32_t mb) {
  asm volatile("st.async.weak.shared::cluster.mbarrier::complete_tx::bytes.b32 [%0+%3], %1, [%2];" :: "r"(a), "r"(x), "r"(mb), "n"(IMM) : "memory");
}
template <int IMM> __device__ __forceinline__ void ld_relaxed_v4_if(uint4& v, const void* p, uint32_t c) {
  asm volatile("{\n.reg .pred p;\nsetp.ne.u32 p, %6, 0;\n@p ld.relaxed.gpu.global.v4.u32 {%0,%1,%2,%3}, [%4+%5];\n}"
               : "+r"(v.x), "+r"(v.y), "+r"(v.z), "+r"(v.w) : "l"(p), "n"(IMM), "r"(c) : "memory");
}
template <int IMM> __device__ __forceinline__ void ldsm_x2_i(uint32_t (&r)[2], uint32_t a) {
  asm volatile("ldmatrix.sync.aligned.m8n8.x2.shared.b16 {%0,%1}, [%2+%3];" : "=r"(r[0]), "=r"(r[1]) : "r"(a), "n"(IMM) : "memory");
}
template <int IMM> __device__ __forceinline__ uint32_t ldsm_x1_t_i(uint32_t a) {
  uint32_t r; asm volatile("ldmatrix.sync.aligned.m8n8.x1.trans.shared.b16 {%0}, [%1+%2];" : "=r"(r) : "r"(a), "n"(IMM) : "memory"); return r;
}
template <int IMM> __device__ __forceinline__ uint32_t lds32_i(uint32_t a) {
  uint32_t v; asm volatile("ld.shared.u32 %0, [%1+%2];" : "=r"(v) : "r"(a), "n"(IMM) : "memory"); return v;
}
__device__ __forceinline__ void sts32(uint32_t a, uint32_t v) { asm volatile("st.shared.u32 [%0], %1;" :: "r"(a), "r"(v) : "memory"); }
__device__ __forceinline__ uint32_t pack_f16(float lo, float hi) {
  uint32_t d; asm("cvt.rn.f16x2.f32 %0, %1, %2;" : "=r"(d) : "f"(hi), "f"(lo)); return d;
}
__device__ __forceinline__ uint32_t amax_bf2(uint32_t a, uint32_t b) { uint32_t d; asm("max.xorsign.abs.bf16x2 %0, %1, %2;" : "=r"(d) : "r"(a), "r"(b)); return d; }
__device__ __forceinline__ uint32_t amax_h2(uint32_t a, uint32_t b) { uint32_t d; asm("max.xorsign.abs.f16x2 %0, %1, %2;" : "=r"(d) : "r"(a), "r"(b)); return d; }
__device__ __forceinline__ uint32_t amax_fold(uint32_t m) { return __reduce_max_sync(0xffffffffu, max(m & 0x7fffu, (m >> 16) & 0x7fffu)); }
__device__ __forceinline__ int wscale_exp(uint32_t m) { return min(141 - (int)(m >> 7), 100); }
__device__ __forceinline__ float exp2i(int e) { return __uint_as_float((uint32_t)(e + 127) << 23); }
__device__ __forceinline__ uint32_t bf2_to_h2(uint32_t w, float sc) { return pack_f16(bf_lo(w) * sc, bf_hi(w) * sc); }
__device__ __forceinline__ void bf2_to_h2_inplace(uint32_t& w, uint32_t sc2) {
  asm volatile("{\n.reg .b32 t, lo, hi;\nmul.rn.bf16x2 t, %0, %1;\nshl.b32 lo, t, 16;\nand.b32 hi, t, 0xffff0000;\ncvt.rn.f16x2.f32 %0, hi, lo;\n}" : "+r"(w) : "r"(sc2));
}
__device__ __forceinline__ void prefetch_l2(const void* p, uint32_t bytes) { asm volatile("cp.async.bulk.prefetch.L2.global [%0], %1;" :: "l"(p), "r"(bytes) : "memory"); }
__device__ __forceinline__ void prefetch_tma_2d(const CUtensorMap* tm, int c0, int c1) {
  asm volatile("cp.async.bulk.prefetch.tensor.2d.L2.global [%0, {%1, %2}];" :: "l"(tm), "r"(c0), "r"(c1) : "memory");
}
__host__ __device__ constexpr uint32_t acc_voff(int v) { return v < 4 ? v * 1024u : (v == 4 ? 128u : 3072u + 128u); }
__device__ __forceinline__ int unit28(int i) { return i == 3 ? 54 : 14 * i; }
__device__ __forceinline__ int unit24(int i) { return i < 2 ? 48 - 6 * i : 56 + 6 * i; }
__device__ __forceinline__ uint32_t acc_step(int s) { return (s >> 1) * 32768 + (s & 1) * 512; }
__device__ __forceinline__ uint32_t acc_lane(int i, int lane) { return ((lane >> 3) & 1) * 256 + (lane >> 4) * 4096 + i * 8192 + (lane & 7) * 16; }

__device__ __forceinline__ uint32_t ld_acquire_u32(const void* p) {
  uint32_t v; asm volatile("ld.acquire.gpu.global.u32 %0, [%1];" : "=r"(v) : "l"(p) : "memory"); return v;
}
template <int R> __device__ __forceinline__ void ln_rows(const uint2 (&xw)[R][5], int row0, int lane, bf16* __restrict__ xn, uint2* __restrict__ xh) {
  float v[R][20], s[R], q[R];
#pragma unroll
  for (int r = 0; r < R; r++) {
    s[r] = 0.f; q[r] = 0.f;
#pragma unroll
    for (int i = 0; i < 5; i++) { v[r][4 * i] = bf_lo(xw[r][i].x); v[r][4 * i + 1] = bf_hi(xw[r][i].x); v[r][4 * i + 2] = bf_lo(xw[r][i].y); v[r][4 * i + 3] = bf_hi(xw[r][i].y); }
#pragma unroll
    for (int i = 0; i < 5; i++) s[r] += (v[r][4 * i] + v[r][4 * i + 1]) + (v[r][4 * i + 2] + v[r][4 * i + 3]);
  }
#pragma unroll
  for (int o = 16; o; o >>= 1)
#pragma unroll
    for (int r = 0; r < R; r++) s[r] += __shfl_xor_sync(0xffffffffu, s[r], o);
#pragma unroll
  for (int r = 0; r < R; r++) {
    s[r] *= 1.f / cfg::DM;
#pragma unroll
    for (int i = 0; i < 10; i++) { const float d = v[r][2 * i] - s[r], e = v[r][2 * i + 1] - s[r]; q[r] += d * d + e * e; }
  }
#pragma unroll
  for (int o = 16; o; o >>= 1)
#pragma unroll
    for (int r = 0; r < R; r++) q[r] += __shfl_xor_sync(0xffffffffu, q[r], o);
#pragma unroll
  for (int r = 0; r < R; r++) {
    const int row = row0 + r;
    const float mb = bf16r(s[r]), var = bf16r(q[r] * (1.f / cfg::DM));
    float sd; asm("sqrt.approx.f32 %0, %1;" : "=f"(sd) : "f"(bf16r(var + 1e-5f)));
    const float inv = rcpf(bf16r(sd));
#pragma unroll
    for (int i = 0; i < 5; i++) {
      float y[4];
#pragma unroll
      for (int e = 0; e < 4; e++) y[e] = v[r][4 * i + e] - mb;
      bf16r2(y[0], y[1]); bf16r2(y[2], y[3]);
      const uint32_t w0 = pack_bf16(y[0] * inv, y[1] * inv), w1 = pack_bf16(y[2] * inv, y[3] * inv);
      *(uint2*)(xn + (size_t)row * cfg::DM + i * 128 + lane * 4) = make_uint2(w0, w1);
      if (xh) xh[(((size_t)(row >> 5) * 10 + 2 * i + (lane >> 4)) * 32 + (row & 31)) * 16 + ((((lane >> 1) & 7) ^ (row & 7)) << 1) + (lane & 1)] =
          make_uint2(pack_f16(bf_lo(w0), bf_hi(w0)), pack_f16(bf_lo(w1), bf_hi(w1)));
    }
  }
}

__global__ void __cluster_dims__(3, 1, 1) __launch_bounds__(384, 1) chain_kernel(const ChainArgs a, const __grid_constant__ CUtensorMap tmWq,
    const __grid_constant__ CUtensorMap tmWk, const __grid_constant__ CUtensorMap tmWv, const __grid_constant__ CUtensorMap tmWo) {
  using namespace ch;
  extern __shared__ __align__(1024) unsigned char smem_raw[];
  const uint32_t sb = smem_u32(smem_raw);
  const int warp = __shfl_sync(0xffffffffu, (int)threadIdx.x >> 5, 0);
  const int cta = blockIdx.x, h = cta / 3, j = cta % 3;
  unsigned char* const arena = a.arena;
  if (sb & 1023u) __trap();
  asm volatile("griddepcontrol.launch_dependents;");
  TL_BEGIN(a.tl);
  LITE(cta == 0 && threadIdx.x == 0, (a.tl >= 12) * 4);
#ifdef TIMELINE
  const unsigned long long g_tl0 = gtime();
#define PT(i) TLW((a.tl >= 12) * 128 + 64 + (i))
#else
#define PT(i)
#endif
  const int col0 = j == 0 ? 0 : (j == 1 ? 224 : 432);
  auto stage_w = [&](const CUtensorMap* tm, uint32_t dst, uint32_t mb, int half) {
    mbar_expect_tx(mb + 8 * half, 40960);
    tma_load_2d(dst + half * 40960, tm, h * cfg::DH + j * 64, half * 320, mb + 8 * half);
    tma_load_2d(dst + half * 40960 + 20480, tm, h * cfg::DH + j * 64, half * 320 + 160, mb + 8 * half);
  };
  if (threadIdx.x == 256) {
    for (int i = 0; i < 9; i++) mbar_init(sb + MB_K + 8 * i, 1);
    mbar_init(sb + MB_S, 1); mbar_init(sb + MB_O, 1); mbar_init(sb + MB_X, 1);
    asm volatile("fence.mbarrier_init.release.cluster;" ::: "memory");
    for (int i = 0; i < 2; i++) { stage_w(&tmWk, sb + OFF_WQ, sb + MB_K, i); stage_w(&tmWv, sb + OFF_WO, sb + MB_V, i); }
    sts32(sb + SC_W, 0); sts32(sb + SC_W + 4, 0); sts32(sb + SC_W + 8, 0); sts32(sb + SC_IN + 12, 0); sts32(sb + SC_IN + 20, 0); sts32(sb + SC_TW + 4, 99);
    mbar_expect_tx(sb + MB_S, 1280); mbar_expect_tx(sb + MB_O, 2048);
  }
  __syncthreads();
  asm volatile("barrier.cluster.arrive.relaxed.aligned;" ::: "memory");
  const uint32_t d1 = mapa_u32(sb, (j + 1) % 3) - sb, d2 = mapa_u32(sb, (j + 2) % 3) - sb;

  if (warp >= 8) {
    asm volatile("setmaxnreg.dec.sync.aligned.u32 40;");
    const int lane = fresh(threadIdx.x & 31), hw = warp - 8, ht = hw * 32 + lane;
    const bool lead = ht == 0;
    auto stage_wo = [&](int i) {
      mbar_expect_tx(sb + MB_R + 8 * i, 64 * WOS);
      tma_load_2d(sb + OFF_WO + i * 64 * WOS, &tmWo, col0, h * cfg::DH + ((i + j) % 3) * 64, sb + MB_R + 8 * i);
    };
    const unsigned char* xg = (const unsigned char*)a.xh;
    auto issue_x = [&](int s) { mbar_expect_tx(sb + MB_X, 40960); bulk_g2s(sb + OFF_X, xg + (size_t)s * 40960, 40960, sb + MB_X); };
    uint4 v[5];
#pragma unroll
    for (int i = 0; i < 5; i++) { const int c = ht + 128 * i; v[i] = ld_relaxed_v4(a.mem0 + (c & 7) * cfg::DM + (c >> 3) * 8); }
    if (hw == 2) {
      asm volatile("griddepcontrol.wait;" ::: "memory");
      if (lane == 0) { if (cta == 0) st_relaxed_u32(a.go, 1); issue_x(0); }
      PT(0);
    }
    if (hw == 0) {
      bar_sync(B_QK, 160);
      if (lane == 0) {
        stage_w(&tmWq, sb + OFF_WQ, sb + MB_Q, 0);
        if (PF2) { prefetch_tma_2d(&tmWq, h * cfg::DH + j * 64, 320); prefetch_tma_2d(&tmWq, h * cfg::DH + j * 64, 480); }
      }
      bar_sync(B_SL, 160); if (lane == 0) stage_w(&tmWq, sb + OFF_WQ, sb + MB_Q, 1);
    }
    if (hw == 1) {
      bar_sync(B_V, 160);
      if (lane == 0) {
        stage_wo(0);
        if (PF2) { prefetch_tma_2d(&tmWo, col0, h * cfg::DH + ((1 + j) % 3) * 64); prefetch_tma_2d(&tmWo, col0, h * cfg::DH + ((2 + j) % 3) * 64); }
      }
      bar_sync(B_O, 160); if (lane == 0) { stage_wo(1); stage_wo(2); }
    }
    __syncwarp();
    {
      uint32_t m = 0;
#pragma unroll
      for (int i = 0; i < 5; i++) {
        m = amax_bf2(amax_bf2(m, amax_bf2(v[i].x, v[i].y)), amax_bf2(v[i].z, v[i].w));
      }
      m = amax_fold(m);
      if (lane == 0) sts32(sb + SC_MX + hw * 4, m);
      bar_sync(B_H, 128);
      const uint4 mm = lds128(sb + SC_MX);
      const int se = max(wscale_exp(max(max(mm.x, mm.y), max(mm.z, mm.w))), -100);
      const float sc = exp2i(se);
#pragma unroll
      for (int i = 0; i < 5; i++) {
        const int c = ht + 128 * i, t = c & 7, chn = c >> 3;
        sts128(sb + OFF_MEM + chn * 128 + ((t ^ (2 * (chn & 3))) << 4), bf2_to_h2(v[i].x, sc), bf2_to_h2(v[i].y, sc), bf2_to_h2(v[i].z, sc), bf2_to_h2(v[i].w, sc));
      }
      if (lead) { sts32(sb + SC_IN, __float_as_uint(exp2i(-se))); sts32(sb + SC_IN + 4, 0x7800u); }
    }
    if (hw == 0) PT(11);
    {
      const uint32_t p0 = sb + OFF_WQ + hw * 2048 + lane * 16;
      uint32_t m = 0;
#pragma unroll 1
      for (int i = 0; i < 10; i++) {
        if (i == 0 || i == 5) mbar_wait(sb + MB_Q + (i ? 8 : 0), 0);
        uint32_t r[4][4];
        static_for<0, 4>([&](auto K) { ldsm_x4_i<K.value * 512>(r[K.value], p0 + i * 8192); });
#pragma unroll
        for (int k = 0; k < 4; k++) m = amax_bf2(amax_bf2(m, amax_bf2(r[k][0], r[k][1])), amax_bf2(r[k][2], r[k][3]));
      }
      if (hw == 0) PT(9);
      m = amax_fold(m);
      if (lane == 0) asm volatile("red.shared.max.u32 [%0], %1;" :: "r"(sb + SC_W + 8), "r"(m) : "memory");
      bar_sync(B_H, 128);
      const uint32_t sc = (uint32_t)(wscale_exp(lds32_i<SC_W + 8>(sb)) + 127) * 0x00800080u;
      uint32_t r[4][4];
      static_for<0, 2>([&](auto K) { ldsm_x4_i<K.value * 512>(r[K.value], p0); });
      auto cvt = [&](uint32_t (&x)[4], uint32_t p) { bf2_to_h2_inplace(x[0], sc); bf2_to_h2_inplace(x[1], sc); bf2_to_h2_inplace(x[2], sc); bf2_to_h2_inplace(x[3], sc); stsm_x4(p, x[0], x[1], x[2], x[3]); };
#pragma unroll 1
      for (int i = 0; i < 10; i++) {
        const uint32_t p = p0 + i * 8192;
        ldsm_x4_i<1024>(r[2], p); ldsm_x4_i<1536>(r[3], p);
        cvt(r[0], p); cvt(r[1], p + 512);
        ldsm_x4_i<8192>(r[0], p); ldsm_x4_i<8192 + 512>(r[1], p);
        cvt(r[2], p + 1024); cvt(r[3], p + 1536);
      }
    }
    if (hw == 0) PT(10);
    bar_sync(0, 384);
    if (hw == 3) {
      const uint32_t eye = ((lane >> 3) == (lane & 3)) ? ((lane & 4) ? 0x3f800000u : 0x3f80u) : 0u;
      sts128(sb + OFF_LT + lane * 16, eye, eye, (lane & 2) * 64 + (lane >> 2) * 16 + (lane & 1) * 8, 0u);
      sts64(sb + OFF_S + 1280 + lane * 8, 0u, 0u);
    }
    if (lead) st_relaxed_u32(arena + AR_TAB + cta * 4, 0x80000000u | (lds32_i<SC_W>(sb) << 15) | lds32_i<SC_W + 4>(sb));
    asm volatile("barrier.cluster.wait.aligned;" ::: "memory");
    bar_sync(B_MEM0, 256); bar_sync(B_MEM1, 256);
    {
      uint32_t v0, v1, v2; int spin = 0;
      do {
        v0 = ld_relaxed_u32(arena + AR_TAB + lane * 4); v1 = ld_relaxed_u32(arena + AR_TAB + 128 + lane * 4); v2 = ld_relaxed_u32(arena + AR_TAB + 256 + lane * 4);
      } while (__any_sync(0xffffffffu, ((v0 & v1 & v2) >> 31) == 0) && ++spin < SPIN_LIMIT);
      const uint32_t mv = (max(max(v0, v1), v2) >> 15) & 0x7fffu, mo = max(max(v0 & 0x7fffu, v1 & 0x7fffu), v2 & 0x7fffu);
      sts32(sb + SC_IN + 8 + (lane & 1) * 16, 15 - ((__reduce_max_sync(0xffffffffu, mv) >> 7) + (__reduce_max_sync(0xffffffffu, mo) >> 7) - 252 + 22));
    }

    auto store_kv = [&](int s) {
      const size_t o = ((size_t)s * 96 + cta) * KVB; const uint32_t src = sb + OFF_KV + (s & 1) * (2 * KVB);
      fence_proxy_async(); bulk_s2g(a.kg + o, src, KVB); bulk_s2g(a.vg + o, src + KVB, KVB); bulk_commit();
    };
    const int cb28 = unit28(hw), du = (unit24(hw) - cb28) * 128;
    uint32_t n16 = lane * 16, hist = 0;
    const uint32_t us1 = sb + d1 + OFF_SR + 256 + (hw >> 1) * 512 + (hw & 1) * 128, us2 = sb + d2 + OFF_SR + (hw >> 1) * 512 + (hw & 1) * 128;
    const uint32_t uo1 = sb + d1 + OFF_O + 2048 + hw * 256, uo2 = sb + d2 + OFF_O + 1024 + hw * 256;
#ifdef STEPCLK
    if (lead) a.dbg[96 * 300 + cta * 2] = clk32();
#endif
#ifdef TIMELINE
    if (cta == 0 && lead) { g_tl2[(a.tl >= 12) * 128 + 0] = clock64(); g_tl2[(a.tl >= 12) * 128 + 1] = gtime(); }
#endif
#pragma unroll 1
    for (int s = 0; s < cfg::NSEG; s++) {
      TS_SETUP();
      const bool last = s == cfg::NSEG - 1;
      if (n16 == 0) {
        if (hw == 2 && !last) issue_x(s + 1);
        if (hw == 0 && (s & 3) == 1 && s > 1) st_relaxed_u32(arena + (prog_off(h, j) + lds32_i<SC_IN + 12>(sb)), s - 1);
        if (hw == 0 && s > 0) store_kv(s - 1);
        if (PFX && hw == 3 && cta < 80 && s + PFX < cfg::NSEG) prefetch_l2(xg + (size_t)(s + PFX) * 40960 + cta * 512, 512);
        if (PFACC && hw == 1 && s + PFACC < cfg::NSEG - 1)
          asm volatile("prefetch.global.L2 [%0];" :: "l"(arena + (AR_ACC + acc_step(s + PFACC) + acc_lane(cta / 24, (cta & 3) * 8) + acc_voff((cta % 24) >> 2))) : "memory");
      }
      __syncwarp();
      if (last) break;
      const uint32_t kv = (s & 1) * (2 * KVB);
      n16 = fresh(n16);
      uint32_t kb0[4], kb1[4];
      { const uint32_t ka = n16 + (n16 & 384) * 4 + (sb + kv + hw * 128); ldsm_x4_i<OFF_KV>(kb0, ka); ldsm_x4_i<OFF_KV + 2560>(kb1, ka); }
      TS(1);
      bar_sync(B_QK, 384);
      {
        uint32_t q0[4], q1[4], q2[4], q3[4];
        float sa[4] = {0, 0, 0, 0}, sc2[4] = {0, 0, 0, 0};
        ldsm_x4_i<OFF_Q>(q0, n16 + sb); ldsm_x4_i<OFF_Q + 1024>(q2, n16 + sb); ldsm_x4_i<OFF_Q + 512>(q1, n16 + sb);
        bar_arrive(B_A, 288);
        ldsm_x4_i<OFF_Q + 1536>(q3, n16 + sb);
        mma16816(sa, q0[0], q0[1], q0[2], q0[3], kb0[0], kb0[1]);
        mma16816(sc2, q2[0], q2[1], q2[2], q2[3], kb1[0], kb1[1]);
        mma16816(sa, q1[0], q1[1], q1[2], q1[3], kb0[2], kb0[3]);
        mma16816(sc2, q3[0], q3[1], q3[2], q3[3], kb1[2], kb1[3]);
        const float x0 = (sa[0] + sa[2]) + (sc2[0] + sc2[2]), x1 = (sa[1] + sa[3]) + (sc2[1] + sc2[3]);
        const uint32_t xp = pack_bf16(x0, x1);
        st_async_b32_i<0>((n16 >> 2) + us1, xp, sb + MB_S + d1);
        st_async_b32_i<0>((n16 >> 2) + us2, xp, sb + MB_S + d2);
        stsm_x2(n16 + (sb + OFF_S + hw * 256), __float_as_uint(x0), __float_as_uint(x1));
      }
      TS(3);
      uint32_t v0[4], v1[4], vm0, vm1;
      const uint32_t uv = sb + kv + hw * 1280;
      ldsm_x4_t_i<OFF_KV + KVB>(v0, n16 + uv); ldsm_x4_t_i<OFF_KV + KVB + 640>(v1, n16 + uv);
      bar_sync(B_SL, 256);
      float t0[4], t1[4], t2[4];
      { uint32_t x[4]; ldsm_x4_i<OFF_S>(x, n16 + sb); t0[0] = __uint_as_float(x[0]); t0[1] = __uint_as_float(x[1]); t0[2] = __uint_as_float(x[2]); t0[3] = __uint_as_float(x[3]); }
      { uint32_t x[4]; ldsm_x4_i<OFF_S + 512>(x, n16 + sb); t1[0] = __uint_as_float(x[0]); t1[1] = __uint_as_float(x[1]); t1[2] = __uint_as_float(x[2]); t1[3] = __uint_as_float(x[3]); }
      { uint32_t x[4]; ldsm_x4_i<OFF_S + 1024>(x, n16 + sb); t2[0] = __uint_as_float(x[0]); t2[1] = __uint_as_float(x[1]); t2[2] = __uint_as_float(x[2]); t2[3] = __uint_as_float(x[3]); }
      mbar_spin(sb + MB_S, s & 1);
      TS(4);
      uint2 xo;
      {
        uint32_t r0[4], r1[4], r2[2];
        ldsm_x4_i<OFF_SR>(r0, n16 + sb); ldsm_x4_i<OFF_SR + 512>(r1, n16 + sb); ldsm_x2_i<OFF_SR + 1024>(r2, n16 + sb);
        SFENCE(n16);
        const uint2 eye = lds64_i<OFF_LT>(n16 + sb);
        mma16816(t0, r0[0], r0[1], r0[2], r0[3], eye.x, eye.y);
        mma16816(t1, r1[0], r1[1], r1[2], r1[3], eye.x, eye.y);
        mma1688(t2, r2[0], r2[1], eye.x);
        bar_sync(B_V, 256);
        vm0 = ldsm_x1_t_i<OFF_KV + KVB + 512>(n16 + uv); vm1 = ldsm_x1_t_i<OFF_KV + KVB + 1152>(n16 + uv);
        SFENCE(n16);
        xo = lds64_i<OFF_LT + 8>(n16 + sb);
      }
      float sc[10] = {t0[0], t0[1], t0[2], t0[3], t1[0], t1[1], t1[2], t1[3], t2[0] + t2[2], t2[1] + t2[3]};
      const float cs = 0.07216878364870322f * 1.4426950408889634f;
      float mx = fmaxf(fmaxf(fmaxf(sc[0], sc[1]), fmaxf(sc[2], sc[3])), fmaxf(fmaxf(sc[4], sc[5]), fmaxf(sc[6], sc[7])));
      mx = fmaxf(mx, fmaxf(sc[8], sc[9]));
      {
        const float m1 = __shfl_xor_sync(0xffffffffu, mx, 1), m2 = __shfl_xor_sync(0xffffffffu, mx, 2), m3 = __shfl_xor_sync(0xffffffffu, mx, 3);
        mx = fmaxf(fmaxf(mx, m1), fmaxf(m2, m3));
      }
      const float mo = fmaf(mx, -cs, __uint_as_float(xo.x));
      auto ex = [&](int i) -> uint32_t { float x, y;
        asm volatile("ex2.approx.ftz.f32 %0, %1;" : "=f"(x) : "f"(fmaf(sc[i], cs, mo))); asm volatile("ex2.approx.ftz.f32 %0, %1;" : "=f"(y) : "f"(fmaf(sc[i + 1], cs, mo)));
        return pack_bf16(x, y); };
      float oa[4] = {0, 0, 0, 0}, ob[4] = {0, 0, 0, 0}, oc[4] = {0, 0, 0, 0}, od[4] = {0, 0, 0, 0}, rs[4] = {0, 0, 0, 0};
      const uint32_t ones = 0x3f803f80u;
      const uint32_t p4 = ex(8);
      if (MEMFIRST) { mma1688(rs, p4, 0u, ones); mma1688(oa, p4, 0u, vm0); mma1688(ob, p4, 0u, vm1); }
      const uint32_t p0 = ex(0), p1 = ex(2), p2 = ex(4), p3 = ex(6);
      TS(5);
      mma16816(rs, p0, p2, p1, p3, ones, ones);
      mma16816(oa, p0, p2, p1, p3, v0[0], v0[1]);
      mma16816(oc, p0, p2, p1, p3, v0[2], v0[3]);
      mma16816(ob, p0, p2, p1, p3, v1[0], v1[1]);
      mma16816(od, p0, p2, p1, p3, v1[2], v1[3]);
      if (!MEMFIRST) { mma1688(rs, p4, 0u, ones); mma1688(oa, p4, 0u, vm0); mma1688(ob, p4, 0u, vm1); }
      const float inv = rcpf(rs[0] + rs[2]) * __uint_as_float(xo.y);
      {
        const uint32_t y0 = pack_bf16((oa[0] + oc[2]) * inv, (oa[1] + oc[3]) * inv), y1 = pack_bf16((ob[0] + od[2]) * inv, (ob[1] + od[3]) * inv);
        st_async_v2_i<0>(xo.x + uo1, y0, y1, sb + MB_O + d1);
        st_async_v2_i<0>(xo.x + uo2, y0, y1, sb + MB_O + d2);
        sts64_i<OFF_O>(xo.x + (sb + hw * 256), y0, y1);
      }
      bar_arrive(B_O, 384);
      TS(6);
      if (hw == 0) bulk_wait<0>();
      mbar_expect_tx_if(n16 == 0 && hw == 3, sb + MB_S, 1280);
      n16 = fresh(n16);
      const int ln = n16 >> 4;
      auto mslot = [&](int c) -> uint32_t { return sb + OFF_MEM + c * 128 + (((ln >> 2) ^ (2 * (c & 3))) << 4); };
      const int lq = ln & 3;
      const uint32_t ma = mslot(cb28 + lq), mb_ = mslot(cb28 + (lq >> 1)) + (lq & 1) * 8;
      const unsigned char* gp = arena + (AR_ACC + acc_lane(hw, ln) + acc_step(s));
      const bool odd = ln & 1;
      const uint32_t delay = a.delay + ((hist & 2) ? a.margin : 0);
      SFENCE(ma);
      uint32_t tw;
      if (hw == 0 && (s & 3) == 0 && a.pubrel) {
        bar_arrive(B_RED, 384);
        asm volatile("fence.acq_rel.gpu;" ::: "memory");
        uint2 t; int sp = 0;
        do { asm volatile("ld.volatile.shared.v2.u32 {%0,%1}, [%2];" : "=r"(t.x), "=r"(t.y) : "r"(sb + SC_TW) : "memory"); } while (__any_sync(0xffffffffu, t.y != (uint32_t)s) && ++sp < SPIN_LIMIT);
        tw = t.x;
      } else {
        bar_sync(B_RED, 384);
        SFENCE(mb_);
        tw = clk_v();
        if (hw == 1) asm volatile("st.volatile.shared.v2.u32 [%0], {%1,%2};" :: "r"(sb + SC_TW), "r"(tw), "r"(s) : "memory");
      }
      TSV(7, tw);
      mbar_expect_tx_if(n16 == 0 && hw == 3, sb + MB_O, 2048);
      while (clk_v() - tw < delay) {}
      TS(8);
      uint4 v[6];
      int spin = 0;
      const uint32_t cm = odd ? 0x5000u : 0u;
      do {
        static_for<0, 6>([&](auto I) { v[I.value] = ld_relaxed_v4_i<acc_voff(I.value)>(gp); });
      } while (__any_sync(0xffffffffu, (~((v[0].w & v[1].w & v[2].w) & (v[3].w & v[4].w & v[5].w)) & cm) != 0) && ++spin < SPIN_LIMIT);
      v[0].w = odd ? v[3].x : v[0].w; v[1].w = odd ? v[3].y : v[1].w; v[2].w = odd ? v[3].z : v[2].w; v[3].w = odd ? 0u : v[3].w;
      sts128_i<0>(ma, v[0].x, v[0].y, v[0].z, v[0].w);
      sts128_i<512>(ma, v[1].x, v[1].y, v[1].z, v[1].w);
      sts128_i<1024>(ma, v[2].x, v[2].y, v[2].z, v[2].w);
      sts128_i<0>(ma + du, v[4].x, v[4].y, v[4].z, v[5].z);
      sts64_i<512>(mb_ + du, v[5].x, v[5].y);
      if (!odd) sts128_i<1536>(mb_, v[3].x, v[3].y, v[3].z, v[3].w);
      hist = (hist * 2 + (spin != 0)) & 0xffffu;
      TSV(11, spin);
#ifdef TIMELINE
      if (hw == 2 && ln == 0) { uint32_t gt; asm volatile("mov.u32 %0, %%globaltimer_lo;" : "=r"(gt)); *(uint4*)(g_step + (((a.tl >= 12) * 64 + s) * 96 + cta) * 4) = make_uint4(gt, spin, clk_v() - tw, tw); }
#endif
      TS(10);
      bar_sync(B_MEM0, 256); bar_sync(B_MEM1, 256);
      uint32_t m = lds32_i<SC_IN + 12>(sb);
      uint32_t m2 = m;
      static_for<0, 3>([&](auto I) { m = amax_h2(amax_h2(amax_h2(amax_h2(m, v[I.value].x), v[I.value].y), v[I.value].z), v[I.value].w); });
      static_for<3, 6>([&](auto I) { m2 = amax_h2(amax_h2(amax_h2(m2, v[I.value].x), v[I.value].y), v[I.value].z); });
      m = amax_fold(amax_h2(amax_h2(m2, v[3].w), m));
      if (n16 == 0) asm volatile("red.shared.max.u32 [%0], %1;" :: "r"(sb + SC_IN + 4 + 16 * ((s + 1) & 1)), "r"(m) : "memory");
    }
    bar_sync(B_RED, 384);
    if (hw == 0 && n16 == 0) {
      store_kv(cfg::NSEG - 1);
      bulk_wait<0>();
      st_release_u32(arena + (prog_off(h, j) + lds32_i<SC_IN + 12>(sb)), cfg::NSEG);
    }
    __syncwarp();
#ifdef STEPCLK
    if (hw == 0 && n16 == 0) a.dbg[96 * 300 + cta * 2 + 1 + (hist >> 20)] = clk32();
#endif
#ifdef TIMELINE
    if (cta == 0 && hw == 0 && n16 == 0) { g_tl2[(a.tl >= 12) * 128 + 2] = clock64(); g_tl2[(a.tl >= 12) * 128 + 3] = gtime(); }
#endif
    TL_END(a.tl);
    asm volatile("barrier.cluster.arrive.relaxed.aligned; barrier.cluster.wait.aligned;" ::: "memory");
  } else {
    asm volatile("setmaxnreg.inc.sync.aligned.u32 232;");
    const int wi = warp & 3, hf = warp >> 2;
    [[maybe_unused]] const int tid = threadIdx.x;
    int lane = fresh(threadIdx.x & 31);
    uint32_t w[40][4], wm = 0;
    uint32_t wqa;
    { const int r8 = lane & 7, mrow = r8 + ((lane >> 4) << 3), mch = 2 * wi + ((lane >> 3) & 1); wqa = sb + mrow * 128 + ((mch ^ r8) << 4); }
    float iw, iq;
#pragma unroll 1
    for (int live = a.dry ? 0 : 1; live < 2; live++) {
      const uint32_t wa = wqa + (hf ? OFF_WO : OFF_WQ);
      wm = 0;
      mbar_wait_if(live, sb + (hf ? MB_V : MB_K), 0);
      static_for<0, 20>([&](auto K) { ldsm_x4_t_i<K.value * 2048>(w[K.value], wa); });
#pragma unroll
      for (int k = 0; k < 20; k++) wm = amax_bf2(amax_bf2(wm, amax_bf2(w[k][0], w[k][1])), amax_bf2(w[k][2], w[k][3]));
      SFENCE2(wa, wm);
      if (warp == 0 && live) PT(1);
      if (live) bar_arrive(hf ? B_V : B_QK, 160);
      mbar_wait_if(live, sb + (hf ? MB_V : MB_K) + 8, 0);
      static_for<20, 40>([&](auto K) { ldsm_x4_t_i<K.value * 2048>(w[K.value], wa); });
#pragma unroll
      for (int k = 20; k < 40; k++) wm = amax_bf2(amax_bf2(wm, amax_bf2(w[k][0], w[k][1])), amax_bf2(w[k][2], w[k][3]));
      SFENCE2(wa, wm);
      if (warp == 4 && live) PT(2);
      if (live) bar_arrive(hf ? B_O : B_SL, 160);
      SFENCE(wa);
      const uint32_t m = amax_fold(wm);
      if (hf && live) asm volatile("red.shared.max.u32 [%0], %1;" :: "r"(sb + SC_W), "r"(m) : "memory");
      const int e = wscale_exp(m);
      const uint32_t sc = (uint32_t)(e + 127) * 0x00800080u; iw = exp2i(-e);
#pragma unroll
      for (int k = 0; k < 40; k++) { bf2_to_h2_inplace(w[k][0], sc); bf2_to_h2_inplace(w[k][1], sc); bf2_to_h2_inplace(w[k][2], sc); bf2_to_h2_inplace(w[k][3], sc); }
    }
    iw = uniform_f(iw);
    if (warp == 0) PT(3);
    uint32_t x0[8];
    {
      float xa[16];
      const uint32_t dlo = (((sb + OFF_X) & 0x3FFFF) >> 4) | (1u << 16);
      mbar_wait(sb + MB_X, 0);
      if (warp == 0) PT(4);
      wgmma_fence();
      static_for<0, 40>([&](auto K) { constexpr int k = K.value; wgmma_rs32h<((k >> 2) * 4096 + (k & 3) * 32) / 16, (k != 0)>(xa, w[k], dlo); });
      wgmma_commit();
      wgmma_wait<0>();
#pragma unroll
      for (int i = 0; i < 8; i++) x0[i] = pack_bf16(xa[2 * i] * iw, xa[2 * i + 1] * iw);
    }
    lane = fresh(threadIdx.x & 31);
    const int g = lane >> 2, q4 = lane & 3, r8 = lane & 7, m4 = lane >> 3;
    const bool t28 = j == 0 || warp < 4;
    const int bi = j == 0 ? hf : (warp < 4 ? j + 1 : 2 * (j - 1) + ((warp - 4) >> 1)), bv = t28 ? wi : 4 + (warp & 1);
    uint32_t wo1 = sb + OFF_WO + warp * 896 + lane * 16, wo2;
    {
      const int cb = (t28 ? unit28(bi) : unit24(bi)) - col0 / 8;
      uint32_t cp[4];
#pragma unroll
      for (int wd = 0; wd < 4; wd++) {
        int c, p;
        if (bv < 3) { c = 4 * bv + q4; p = wd; }
        else if (bv == 3) { if (q4 & 1) { c = 4 * (wd % 3) + q4; p = 3; } else { c = 12 + (q4 >> 1); p = wd; } }
        else if (bv == 4) { c = q4; p = wd; }
        else { if (wd < 2) { c = 4 + (q4 >> 1); p = 2 * (q4 & 1) + wd; } else { c = q4; p = 3; } }
        cp[wd] = sb + OFF_WO + ((g & 1) + (g & 2) * 4 + (g >> 2) * 2) * WOS + (cb + c) * 16 + p * 4;
      }
      const int cidx = (r8 & 1) + ((r8 >> 2) << 1);
      wo2 = sb + OFF_WO + warp * 896 + ((m4 & 1) ? 768 + (m4 >> 1) * 64 + cidx * 16 : 512 + (m4 >> 1) * 128 + r8 * 16);
      const bool dump = (m4 & 1) && (r8 & 2);
      uint32_t mo = 0;
      const bool regular = bv < 3 || bv == 4;
#pragma unroll 1
      for (int i = 0; i < 3; i++) {
        uint32_t x[4][4], y[4][4];
        const uint32_t o = i * 4 * WOK;
        mbar_wait(sb + MB_R + 8 * i, 0);
        if (warp == 0) PT(5 + i);
        if (regular) {
          static_for<0, 4>([&](auto K) {
            constexpr int kk = K.value;
            const uint4 u = lds128_i<kk * WOK>(cp[0] + o), v = lds128_i<kk * WOK + 4 * WOS>(cp[0] + o);
            x[kk][0] = u.x; x[kk][1] = u.y; x[kk][2] = u.z; x[kk][3] = u.w; y[kk][0] = v.x; y[kk][1] = v.y; y[kk][2] = v.z; y[kk][3] = v.w;
          });
        } else {
          static_for<0, 4>([&](auto K) {
            constexpr int kk = K.value;
#pragma unroll
            for (int wd = 0; wd < 4; wd++) { x[kk][wd] = lds32_i<kk * WOK>(cp[wd] + o); y[kk][wd] = lds32_i<kk * WOK + 4 * WOS>(cp[wd] + o); }
          });
        }
        bar_sync(B_C, 256);
        static_for<0, 4>([&](auto K) {
          constexpr int kk = K.value;
#pragma unroll
          for (int wd = 0; wd < 4; wd++) mo = amax_bf2(mo, amax_bf2(x[kk][wd], y[kk][wd]));
          stsm_x4_t_i<kk * WOK>(wo1 + o, x[kk][0], x[kk][1], y[kk][0], y[kk][1]);
          stsm_x4_t_i<0>(dump ? sb + OFF_S + 512 + lane * 16 : wo2 + o + kk * WOK, x[kk][2], x[kk][3], y[kk][2], y[kk][3]);
        });
      }
      if (warp == 0) PT(8);
      mo = amax_fold(mo);
      if (lane == 0) asm volatile("red.shared.max.u32 [%0], %1;" :: "r"(sb + SC_W + 4), "r"(mo) : "memory");
    }
    __syncwarp();
    auto run = [&](auto HF) {
    constexpr int hf = HF.value;
    uint32_t mema, sta, l16 = sb + lane * 16;
    uint32_t rq[hf ? NP1 : NQ0][4];
    auto step_addr = [&](uint32_t kv) {
      const int lr = (l16 >> 4) & 7, lm = (l16 >> 7) & 3;
      mema = l16 ^ (lm << 5);
      sta = sb + lr * 16 + (lm < 2 ? OFF_Q + wi * 512 + hf * 128 + lm * 256 : OFF_KV + kv + 512 + (2 * wi + lm - 2) * 640);
    };
    auto x_gemm = [&](uint32_t ph, [[maybe_unused]] uint32_t tsb) {
      float xa[16];
      const uint32_t dlo = (((sb + OFF_X) & 0x3FFFF) >> 4) | (1u << 16);
      constexpr int NP = hf ? NP1 : NP0;
      if constexpr (hf) {
        static_for<PQE, NP>([&](auto K) { ldsm_x4_t_i<OFF_WQ + K.value * 2048>(rq[K.value], wqa); });
        bar_sync(B_X, 256);
      }
      wgmma_fence();
      static_for<0, 40>([&](auto K) {
        constexpr int k = K.value;
        wgmma_rs32h<((k >> 2) * 4096 + (k & 3) * 32) / 16, (k != 0)>(xa, w[k], dlo);
        if constexpr (!hf && k == PFK && NP > PQE) { SFENCE(wqa); static_for<PQE, NP>([&](auto K) { ldsm_x4_t_i<OFF_WQ + K.value * 2048>(rq[K.value], wqa); }); SFENCE(wqa); }
        if constexpr (!hf && k == XT) bar_arrive(B_X, 256);
      });
      step_addr(ph * (2 * KVB));
      wgmma_commit();
      TS(9);
      wgmma_wait<0>();
      const uint32_t xs = l16 + (wi * 1280 + ph * (2 * KVB));
      stsm_x4_t_i<OFF_KV + hf * KVB>(xs, pack_bf16(xa[0] * iw, xa[1] * iw), pack_bf16(xa[4] * iw, xa[5] * iw), pack_bf16(xa[8] * iw, xa[9] * iw), pack_bf16(xa[12] * iw, xa[13] * iw));
      stsm_x4_t_i<OFF_KV + hf * KVB + 640>(xs, pack_bf16(xa[2] * iw, xa[3] * iw), pack_bf16(xa[6] * iw, xa[7] * iw), pack_bf16(xa[10] * iw, xa[11] * iw), pack_bf16(xa[14] * iw, xa[15] * iw));
      if constexpr (!hf) static_for<NP0, NP0 + NPL>([&](auto K) { ldsm_x4_t_i<OFF_WQ + K.value * 2048>(rq[K.value], wqa); });
    };
    auto wq_addr = [&](uint32_t l) -> uint32_t {
      const int lr = (l >> 4) & 7, lm = (l >> 7) & 3;
      return sb + hf * ((40 - NQ1) * 2048) + (lr + ((lm >> 1) << 3)) * 128 + (((2 * wi + (lm & 1)) ^ lr) << 4);
    };
    constexpr int NPM = hf ? NPM1 : NPM0;
    uint32_t u1[NPM][4], u2[NPM][4];
    static_for<0, NPM>([&](auto K) { ldsm_x4_i<(12 - NPM + K.value) * WOK>(u1[K.value], wo1); ldsm_x4_i<(12 - NPM + K.value) * WOK>(u2[K.value], wo2); });
    bar_sync(0, 384);
    iq = uniform_f(exp2i(-wscale_exp(lds32_i<SC_W + 8>(sb))));
    wqa = wq_addr(l16);
    static_for<0, (hf ? NP1 : NP0 + NPL)>([&](auto K) { ldsm_x4_t_i<OFF_WQ + K.value * 2048>(rq[K.value], wqa); });
    step_addr(0);
    stsm_x4_t_i<OFF_KV + hf * KVB>(l16 + wi * 1280, x0[0], x0[2], x0[4], x0[6]);
    stsm_x4_t_i<OFF_KV + hf * KVB + 640>(l16 + wi * 1280, x0[1], x0[3], x0[5], x0[7]);
    asm volatile("barrier.cluster.wait.aligned;" ::: "memory");
    TL_END(a.tl + 1);
#pragma unroll 1
    for (int s = 0; s < cfg::NSEG - 1; s++) {
      TS_SETUP();
#if CHAIN_TIMING
      if (tid == 0 && (s & 7) == 0) a.dbg[96 * 288 + cta * 8 + (s >> 3)] = clk32();
#endif
      bar_sync(hf ? B_MEM1 : B_MEM0, 256);
      const float sin_ = __uint_as_float(lds32_i<SC_IN>(sb + 16 * (s & 1)));
      constexpr int NPQ = (40 - NQ1) / 2;
      if constexpr (hf == 0) {
        float k0[4] = {0, 0, 0, 0}, k1[4] = {0, 0, 0, 0}, q0[4] = {0, 0, 0, 0}, q1[4] = {0, 0, 0, 0};
        constexpr auto pair_of = [](int t) { const int a = t * (20 - NPQ) / 20, b = (t + 1) * (20 - NPQ) / 20; return b > a ? NPQ + a : t - a; };
        uint32_t b[NB0][4];
        static_for<0, NB0>([&](auto T) { ldsm_x4_i<OFF_MEM + pair_of(T.value) * 512>(b[T.value], mema); });
        static_for<NP0 + NPL, NQ0>([&](auto K) { ldsm_x4_t_i<OFF_WQ + K.value * 2048>(rq[K.value], wqa); });
        if (BBS < 100) bbfence<0>(mema);
        static_for<0, 20>([&](auto T) {
          constexpr int t = T.value, p = pair_of(t);
          uint32_t (&bb)[4] = b[t % NB0];
          if constexpr (p < NPQ) {
            mma16816h(q0, rq[(2 * p) % NQ0], bb[0], bb[1]);
            if constexpr (2 * p + NQ0 < 2 * NPQ) ldsm_x4_t_i<OFF_WQ + (2 * p + NQ0) * 2048>(rq[(2 * p) % NQ0], wqa);
          }
          mma16816h(k0, w[2 * p], bb[0], bb[1]);
          if constexpr (p < NPQ) {
            mma16816h(q1, rq[(2 * p + 1) % NQ0], bb[2], bb[3]);
            if constexpr (2 * p + 1 + NQ0 < 2 * NPQ) ldsm_x4_t_i<OFF_WQ + (2 * p + 1 + NQ0) * 2048>(rq[(2 * p + 1) % NQ0], wqa);
          }
          mma16816h(k1, w[2 * p + 1], bb[2], bb[3]);
          if constexpr (NVE > 0 && t + NB0 == VET) bar_arrive(B_E, 256);
          if constexpr (t + NB0 < 20) ldsm_x4_i<OFF_MEM + pair_of(t + NB0) * 512>(bb, mema);
          if constexpr (t < 20 - NB0 && (t % BBS) == BBS - 1) bbfence<t + 1>(mema);
        });
        const float sq = sin_ * iq, sk = sin_ * iw;
        stsm_x4_t_i<0>(sta, pack_bf16((q0[0] + q1[0]) * sq, (q0[1] + q1[1]) * sq), pack_bf16((q0[2] + q1[2]) * sq, (q0[3] + q1[3]) * sq),
                       pack_bf16((k0[0] + k1[0]) * sk, (k0[1] + k1[1]) * sk), pack_bf16((k0[2] + k1[2]) * sk, (k0[3] + k1[3]) * sk));
        bar_sync(B_QK, 384);
        TS(2);
        {
          if (wi == 3) {
            const uint32_t xr = sb + ((l16 & 511) >> 2), ka = l16 + (l16 & 384) * 4 + (s & 1) * (2 * KVB);
            uint32_t a0[4], a1[4], a2[4], a3[4], kb0[4], kb1[4];
            ldsm_x4_i<OFF_Q>(a0, l16); ldsm_x4_i<OFF_KV + 512>(kb0, ka); ldsm_x4_i<OFF_Q + 1024>(a2, l16); ldsm_x4_i<OFF_KV + 512 + 2560>(kb1, ka);
            ldsm_x4_i<OFF_Q + 512>(a1, l16);
            bar_arrive(B_A, 288);
            ldsm_x4_i<OFF_Q + 1536>(a3, l16);
            float sa[4] = {0, 0, 0, 0}, sc2[4] = {0, 0, 0, 0};
            mma16816(sa, a0[0], a0[1], a0[2], a0[3], kb0[0], kb0[1]);
            mma16816(sc2, a2[0], a2[1], a2[2], a2[3], kb1[0], kb1[1]);
            mma16816(sa, a1[0], a1[1], a1[2], a1[3], kb0[2], kb0[3]);
            mma16816(sc2, a3[0], a3[1], a3[2], a3[3], kb1[2], kb1[3]);
            const float x0 = (sa[0] + sa[2]) + (sc2[0] + sc2[2]), x1 = (sa[1] + sa[3]) + (sc2[1] + sc2[3]);
            const uint32_t xp = pack_bf16(x0, x1);
            st_async_b32_i<OFF_SR + 1024 + 128>(xr + d1, xp, sb + MB_S + d1);
            st_async_b32_i<OFF_SR + 1024>(xr + d2, xp, sb + MB_S + d2);
            stsm_x2(l16 + OFF_S + 1024, __float_as_uint(x0), __float_as_uint(x1));
          } else if (wi == 0) {
            const uint4 si = lds128_i<SC_IN>(sb + 16 * (s & 1));
            const int em = (int)(si.y >> 10) - 14 + (int)(si.x >> 23) - 127;
            const uint32_t osc = __float_as_uint(exp2i(max(min((int)si.z - max(em, 1), 100), -100)));
            sts32(l16 + OFF_LT + 12, osc); sts64_i<SC_IN>(sb + 16 * ((s + 1) & 1), 0x7f000000u - osc, 0u);
          }
          bar_sync(B_SL, 256);
        }
      } else {
        float v0[4] = {0, 0, 0, 0}, v1[4] = {0, 0, 0, 0}, q0[4] = {0, 0, 0, 0}, q1[4] = {0, 0, 0, 0};
        constexpr int NB1 = NQ1 / 2 < 3 ? NQ1 / 2 : 3;
        uint32_t b[NB1][4];
        static_for<0, NB1>([&](auto T) { ldsm_x4_i<OFF_MEM + (NPQ + T.value) * 512>(b[T.value], mema); });
        static_for<0, NQ1 / 2>([&](auto T) {
          constexpr int t = T.value, p = NPQ + t;
          uint32_t (&bb)[4] = b[t % NB1];
          mma16816h(q0, rq[(2 * t) % NP1], bb[0], bb[1]);
          if constexpr (2 * t + NP1 < NQ1) ldsm_x4_t_i<OFF_WQ + (2 * t + NP1) * 2048>(rq[(2 * t) % NP1], wqa);
          mma16816h(q1, rq[(2 * t + 1) % NP1], bb[2], bb[3]);
          if constexpr (2 * t + 1 + NP1 < NQ1) ldsm_x4_t_i<OFF_WQ + (2 * t + 1 + NP1) * 2048>(rq[(2 * t + 1) % NP1], wqa);
          mma16816h(v0, w[2 * p], bb[0], bb[1]);
          mma16816h(v1, w[2 * p + 1], bb[2], bb[3]);
          if constexpr (t + NB1 < NQ1 / 2) ldsm_x4_i<OFF_MEM + (p + NB1) * 512>(bb, mema);
        });
        const float sq = sin_ * iq, sv = sin_ * iw;
        stsm_x2_t_i<0>(sta, pack_bf16((q0[0] + q1[0]) * sq, (q0[1] + q1[1]) * sq), pack_bf16((q0[2] + q1[2]) * sq, (q0[3] + q1[3]) * sq));
        TS(2);
        bar_arrive(B_QK, 384);
        float v2[4] = {0, 0, 0, 0}, v3[4] = {0, 0, 0, 0};
        auto vpair = [&](auto P, uint32_t (&bb)[4]) {
          constexpr int p = P.value;
          if constexpr (p & 1) { mma16816h(v0, w[2 * p], bb[0], bb[1]); mma16816h(v1, w[2 * p + 1], bb[2], bb[3]); }
          else { mma16816h(v2, w[2 * p], bb[0], bb[1]); mma16816h(v3, w[2 * p + 1], bb[2], bb[3]); }
        };
        if constexpr (NVE > 0) {
          uint32_t e[NVE ? NVE : 1][4];
          bar_sync(B_E, 256);
          static_for<0, NVE>([&](auto T) { ldsm_x4_i<OFF_MEM + T.value * 512>(e[T.value], mema); });
          static_for<0, NVE>([&](auto T) { vpair(T, e[T.value]); });
        }
        bar_sync(B_A, 288);
        uint32_t c[4][4];
        static_for<NVE, (NVE + 4 < NPQ ? NVE + 4 : NPQ)>([&](auto T) { ldsm_x4_i<OFF_MEM + T.value * 512>(c[T.value & 3], mema); });
        static_for<NVE, NPQ>([&](auto T) {
          constexpr int p = T.value;
          vpair(T, c[p & 3]);
          if constexpr (p + 4 < NPQ) ldsm_x4_i<OFF_MEM + (p + 4) * 512>(c[p & 3], mema);
        });
        stsm_x2_t_i<OFF_KV + KVB + 512>(l16 + (l16 & 128) * 4 + (wi * 1280 + (s & 1) * (2 * KVB)), pack_bf16(((v0[0] + v1[0]) + (v2[0] + v3[0])) * sv, ((v0[1] + v1[1]) + (v2[1] + v3[1])) * sv),
                            pack_bf16(((v0[2] + v1[2]) + (v2[2] + v3[2])) * sv, ((v0[3] + v1[3]) + (v2[3] + v3[3])) * sv));
        bar_arrive(B_V, 256);
      }
      TS(3);
      {
        uint32_t t1[12][4], t2[12][4];
        const uint32_t o16 = l16;
        wo1 = l16 + (OFF_WO + warp * 896);
        wo2 = sb + OFF_WO + warp * 896 + ((l16 & 128) ? 768 + ((l16 & 256) >> 2) + (l16 & 16) + ((l16 & 64) >> 1) : 512 + ((l16 & 256) >> 1) + (l16 & 112));
        constexpr int NR_ = NRT - NPM;
        auto ldw = [&](auto K) { if constexpr (K.value < 12 - NPM) { ldsm_x4_i<K.value * WOK>(t1[K.value], wo1); ldsm_x4_i<K.value * WOK>(t2[K.value], wo2); } };
        constexpr int PB = (hf ? PB1 : PB0) < NR_ ? (hf ? PB1 : PB0) : NR_, PA = (hf ? PA1 : PA0) < PB ? (hf ? PA1 : PA0) : PB;
        static_for<0, PA>(ldw);
        mbar_spin(sb + MB_X, (s + 1) & 1);
        if constexpr (PB > PA) {
          constexpr int PM = PA + PM1 < PB ? PA + PM1 : PB;
          mbar_spin(sb + MB_S, s & 1);
          const uint32_t t0 = clk_v();
          if constexpr (PM > PA) { while (clk_v() - t0 < GD1) {} static_for<PA, PM>(ldw); }
          if constexpr (PB > PM) { while (clk_v() - t0 < GD2) {} static_for<PM, PB>(ldw); }
        }
        float c0[4] = {0, 0, 0, 0}, c1[4] = {0, 0, 0, 0}, e0[4] = {0, 0, 0, 0}, e1[4] = {0, 0, 0, 0};
        uint32_t ob[6][4];
        auto kstep = [&](auto K) {
          constexpr int k = K.value;
          uint32_t (&bb)[4] = ob[k >> 1];
          uint32_t (&x)[4] = k < 12 - NPM ? t1[k] : u1[k < 12 - NPM ? 0 : k - (12 - NPM)];
          uint32_t (&y)[4] = k < 12 - NPM ? t2[k] : u2[k < 12 - NPM ? 0 : k - (12 - NPM)];
          if constexpr (k & 1) { mma16816(c1, x[0], x[1], x[2], x[3], bb[2], bb[3]); mma16816(e1, y[0], y[1], y[2], y[3], bb[2], bb[3]); }
          else { mma16816(c0, x[0], x[1], x[2], x[3], bb[0], bb[1]); mma16816(e0, y[0], y[1], y[2], y[3], bb[0], bb[1]); }
          if constexpr (k >= NRF) ldw(IC<k + NR_ - NRF>{});
        };
        auto ldo = [&](auto P) { ldsm_x4_i<OFF_O + P.value * 512>(ob[P.value], o16); };
        TS(4);
        bar_sync(B_O, 384);
        ldo(IC<0>{}); ldo(IC<1>{});
        SFENCE(o16);
        static_for<PB, NR_>(ldw);
        static_for<0, 4>(kstep);
        TS(5);
        mbar_spin(sb + MB_O, s & 1);
        TS(6);
        ldo(IC<2>{}); ldo(IC<NPM >= 2 ? 5 : 3>{});
        if (WOF) SFENCE(o16);
        kstep(IC<4>{});
        if constexpr (NPM < 2) { kstep(IC<5>{}); ldo(IC<4>{}); kstep(IC<6>{}); kstep(IC<7>{}); ldo(IC<5>{}); static_for<8, 12>(kstep); }
        else if constexpr (NPM >= 4) { kstep(IC<10>{}); kstep(IC<11>{}); ldo(IC<4>{}); kstep(IC<5>{}); ldo(IC<3>{}); kstep(IC<8>{}); kstep(IC<9>{}); kstep(IC<6>{}); kstep(IC<7>{}); }
        else { kstep(IC<5>{}); ldo(IC<3>{}); kstep(IC<11>{}); kstep(IC<10>{}); ldo(IC<4>{}); kstep(IC<6>{}); kstep(IC<7>{}); if constexpr (NPM == 3) { kstep(IC<9>{}); kstep(IC<8>{}); } else { kstep(IC<8>{}); kstep(IC<9>{}); } }
        l16 = fresh(l16);
        const int ln = (l16 >> 4) & 31;
        if constexpr (CEARLY && hf) { SFENCE2(o16, __float_as_uint(e1[0])); bar_arrive(B_G, 256); }
        unsigned char* gr = arena + (AR_ACC + acc_lane(bi, ln) + acc_voff(bv) + acc_step(s));
        const bool cnt = (ln & 1) || !t28;
        wqa = wq_addr(l16);
        SFENCE(o16);
        static_for<0, PQE>([&](auto K) { ldsm_x4_t_i<OFF_WQ + K.value * 2048>(rq[K.value], wqa); });
        const uint32_t y0 = movm_t(pack_f16(c0[0] + c1[0], c0[1] + c1[1])), y1 = movm_t(pack_f16(c0[2] + c1[2], c0[3] + c1[3]));
        const uint32_t y2 = movm_t(pack_f16(e0[0] + e1[0], e0[1] + e1[1])), y3 = movm_t(pack_f16(e0[2] + e1[2], e0[3] + e1[3]));
        asm volatile("red.relaxed.gpu.global.add.noftz.v4.f16x2 [%0], {%1,%2,%3,%4};" :: "l"(gr), "r"(y0), "r"(y1), "r"(y2), "r"(cnt ? 0x3c00u : y3) : "memory");
        bar_arrive(B_RED, 384);
        if constexpr (CEARLY && !hf) { bar_arrive(B_C, 256); bar_sync(B_G, 256); }
        else bar_sync(B_C, 256);
        TS(7);
      }
#if CHAIN_TIMING
      x_gemm((s + 1) & 1, tsb);
#else
      x_gemm((s + 1) & 1, 0);
#endif
      TS(8);
    }
    };
    if (hf == 0) run(IC<0>{}); else run(IC<1>{});
    {
      const uint32_t l16 = sb + (threadIdx.x & 31) * 16, mema = l16 ^ ((l16 >> 2) & 96);
      float c0[4] = {0, 0, 0, 0}, c1[4] = {0, 0, 0, 0}, c2[4] = {0, 0, 0, 0}, c3[4] = {0, 0, 0, 0};
      bar_sync(hf ? B_MEM1 : B_MEM0, 256);
      const float sc = __uint_as_float(lds32_i<SC_IN + 16>(sb)) * iw;
      static_for<0, 10>([&](auto T) {
        constexpr int p = 2 * T.value;
        uint32_t b0[4], b1[4];
        ldsm_x4_i<OFF_MEM + p * 512>(b0, mema); ldsm_x4_i<OFF_MEM + p * 512 + 512>(b1, mema);
        mma16816h(c0, w[2 * p], b0[0], b0[1]); mma16816h(c1, w[2 * p + 1], b0[2], b0[3]);
        mma16816h(c2, w[2 * p + 2], b1[0], b1[1]); mma16816h(c3, w[2 * p + 3], b1[2], b1[3]);
      });
      stsm_x2_t_i<OFF_KV + 2 * KVB + 512>(l16 + (l16 & 128) * 4 + wi * 1280 + hf * KVB, pack_bf16(((c0[0] + c1[0]) + (c2[0] + c3[0])) * sc, ((c0[1] + c1[1]) + (c2[1] + c3[1])) * sc),
                                          pack_bf16(((c0[2] + c1[2]) + (c2[2] + c3[2])) * sc, ((c0[3] + c1[3]) + (c2[3] + c3[3])) * sc));
      fence_proxy_async();
    }
    LITE(cta == 0 && threadIdx.x == 0, (a.tl >= 12) * 4 + 1);
    bar_arrive(B_RED, 384);
#if CHAIN_TIMING
    for (int i = tid; i < 288; i += 256) a.dbg[cta * 288 + i] = lds32_i<OFF_BAR + 128>(sb + i * 4);
#endif
    asm volatile("barrier.cluster.arrive.relaxed.aligned; barrier.cluster.wait.aligned;" ::: "memory");
  }
}
struct PrepArgs { const bf16 *wqkv, *wphi, *wo; unsigned char *wb, *wot; };
__device__ __forceinline__ void prep_body(const int cta, const PrepArgs& pa) {
  const int tid = threadIdx.x, lane = tid & 31, warp = tid >> 5, g = lane >> 2, q = lane & 3;
  const int pair = cta >> 1, which = cta & 1;
  uint32_t bfr[2][3][3];
#pragma unroll
  for (int hh = 0; hh < 2; hh++)
#pragma unroll
    for (int t = 0; t < 3; t++) {
      const unsigned short* ph = (const unsigned short*)pa.wphi + (2 * pair + hh) * 400 + (t < 2 ? 8 * t + g : 16 + (g >> 1)) + 2 * q * 20;
#pragma unroll
      for (int r = 0; r < 3; r++) {
        const int o = (r < 2 || q < 2) ? r * 160 : 0;
        const uint32_t v = (uint32_t)__ldg(ph + o) | ((uint32_t)__ldg(ph + o + 20) << 16);
        bfr[hh][t][r] = ((t < 2 || (g & 1) == hh) && (r < 2 || q < 2)) ? v : 0u;
      }
    }
  const int gt = cta * 256 + tid;
#pragma unroll 1
  for (int i = 0; i < 5; i++) {
    uint32_t af[2][6];
#pragma unroll
    for (int hh = 0; hh < 2; hh++) {
      const uint32_t* r0 = (const uint32_t*)(pa.wqkv + (size_t)((warp * 5 + i) * 16 + g) * 1920 + which * 640 + (2 * pair + hh) * 20) + q;
      af[hh][0] = __ldg(r0); af[hh][1] = __ldg(r0 + 7680); af[hh][2] = __ldg(r0 + 4); af[hh][3] = __ldg(r0 + 7684);
      af[hh][4] = __ldg(r0 + 8); af[hh][5] = __ldg(r0 + 7688);
    }
    const int iv = i * 4096 + (gt >> 1), k = (iv & 7) + (iv >> 8) * 8, h = (iv >> 3) & 31;
    const uint2* src = (const uint2*)(pa.wqkv + (size_t)k * 1920 + 1280 + h * 20) + (gt & 1) * 2;
    const uint2 a = __ldg(src), b = __ldg(src + 1), e = __ldg(src + 2);
    uint4 wv[2]; uint32_t wd[2];
#pragma unroll
    for (int n = 0; n < 2; n++) {
      const int iw = min((2 * i + n) * 5120 + gt, 640 * 80 - 1), r = iw & 7, c = (iw >> 3) % 80, kg = iw / 640, c5 = kg % 5;
      const int row = (kg / 5) * 40 + (c5 < 2 ? 8 * c5 + r : (c5 == 2 ? 16 + (r & 3) + (r >> 2) * 20 : 20 + 8 * (c5 - 3) + r));
      wv[n] = __ldg((const uint4*)(pa.wo + (size_t)row * cfg::DM + c * 8));
      wd[n] = (((c / 10) * 80 + kg) * 10 + c % 10) * 128 + r * 16;
    }
    uint4* dv = (uint4*)(pa.wb + ((size_t)((h >> 2) * 80 + (k >> 3)) * 32 + 20 + 3 * (h & 3)) * 128 + (k & 7) * 16);
    dv[(gt & 1) * 8] = make_uint4(a.x, a.y, b.x, b.y);
    if (gt & 1) dv[16] = (h & 1) ? make_uint4(0, 0, e.x, e.y) : make_uint4(e.x, e.y, 0, 0);
    if (gt < 5120) { *(uint4*)(pa.wot + wd[0]) = wv[0]; *(uint4*)(pa.wot + wd[1]) = wv[1]; }
    uint32_t* dst = (uint32_t*)(pa.wb + ((size_t)((pair >> 1) * 80 + (warp * 5 + i) * 2) * 32 + which * 10 + (pair & 1) * 5) * 128) + lane;
#pragma unroll
    for (int t = 0; t < 5; t++) {
      float d[4] = {0, 0, 0, 0};
#pragma unroll
      for (int hh = 0; hh < 2; hh++)
        if (t == 2 || (t > 2) == (hh == 1)) {
          const int tt = t < 3 ? t : t - 3;
          mma16816(d, af[hh][0], af[hh][1], af[hh][2], af[hh][3], bfr[hh][tt][0], bfr[hh][tt][1]);
          mma1688(d, q < 2 ? af[hh][4] : 0u, q < 2 ? af[hh][5] : 0u, bfr[hh][tt][2]);
        }
      dst[t * 32] = pack_bf16(d[0], d[1]); dst[1024 + t * 32] = pack_bf16(d[2], d[3]);
    }
  }
}

__global__ void __launch_bounds__(256, 4) ln_kernel(const bf16* __restrict__ xin, bf16* __restrict__ xn, uint2* __restrict__ xh, uint4* __restrict__ z0, int n0,
                                                    uint4* __restrict__ z1, int n1, const bf16* pfa, const bf16* pfb, int npf, int tl) {
  asm volatile("griddepcontrol.wait;" ::: "memory");
  asm volatile("griddepcontrol.launch_dependents;" ::: "memory");
  TL_BEGIN(tl);
  const int warp = threadIdx.x >> 5, lane = threadIdx.x & 31;
  const int row = blockIdx.x * 8 + warp;
  uint2 xw[1][5];
#pragma unroll
  for (int i = 0; i < 5; i++) xw[0][i] = *(const uint2*)(xin + (size_t)row * cfg::DM + i * 128 + lane * 4);
  for (int i = blockIdx.x * 256 + threadIdx.x; i < n0; i += 256 * 256) z0[i] = make_uint4(0, 0, 0, 0);
  for (int i = blockIdx.x * 256 + threadIdx.x; i < n1; i += 256 * 256) z1[i] = make_uint4(0, 0, 0, 0);
  if (npf && xw[0][4].y != 0x7fc17fc1u) {
    for (int i = 0; i < npf; i++) {
      const uint32_t l = (uint32_t)i * 32768u + (blockIdx.x * 256 + threadIdx.x) / 2;
      if (l < cfg::DM * cfg::HD / 64) asm volatile("prefetch.global.L2 [%0];" :: "l"(((threadIdx.x & 1) ? pfa : pfb) + (size_t)l * 64) : "memory");
    }
  }
  ln_rows<1>(xw, row, lane, xn, xh);
  TL_END(tl);
}
struct Pipe { uint32_t stage, phase; };
template <int NS> __device__ __forceinline__ void pipe_adv(Pipe& p) { if (++p.stage == NS) { p.stage = 0; p.phase ^= 1; } }
constexpr uint32_t SWZ128 = 1;
__device__ __forceinline__ uint64_t desc_kmajor(uint32_t a) { return make_desc(a, 16, 1024, SWZ128); }
__device__ __forceinline__ uint64_t desc_mnmajor(uint32_t a) { return make_desc(a, 8192, 1024, SWZ128); }
__device__ __forceinline__ void wait_ge(const void* p, uint32_t target, uint32_t ns = 32) {
  int spin = 0;
  while (ld_acquire_u32(p) < target) { __nanosleep(ns); if (++spin > (1 << 21)) break; }
}
__device__ __forceinline__ void bulk_g2s_hint(uint32_t dst, const void* src, uint32_t bytes, uint32_t mb, uint64_t pol) {
  asm volatile("cp.async.bulk.shared::cluster.global.mbarrier::complete_tx::bytes.L2::cache_hint [%0], [%1], %2, [%3], %4;"
               :: "r"(dst), "l"(src), "r"(bytes), "r"(mb), "l"(pol) : "memory");
}
#ifndef ZINIT
#define ZINIT 1
#endif
#ifndef STAG
#define STAG 1
#endif
#ifndef EF_KV
#define EF_KV 1
#endif
#ifndef EF_O
#define EF_O 1
#endif
__device__ __forceinline__ void fence_proxy_async_global() { asm volatile("fence.proxy.async.global;" ::: "memory"); }

namespace tr {
constexpr int NS = 4, STQ = 16384 + 24576, STO = 16384 + 40960;
constexpr int SEGB = 15360;
constexpr int OFF_K = NS * STQ;
constexpr int OFF_BAR = NS * STO;
constexpr int SMEM = OFF_BAR + 256;
static_assert(OFF_K + 4 * SEGB <= OFF_BAR && SMEM <= 232448, "smem");
enum { T_QA = 0, T_Q, T_A, T_OB, T_OS, T_L, T_END, T_P };
constexpr uint32_t C_QA = AR_CNT, C_O = AR_CNT + 64, C_Q = AR_CNT + 128, C_P = AR_CNT + 192;
constexpr int MAXITEMS = 1200;
struct Sched {
  uint8_t ks[16];
  uint8_t wide[16];
  uint8_t lrows[16];
  uint32_t n;
  int nqa;
  uint16_t item[MAXITEMS];
};
struct Args {
  const unsigned char *kg, *vg;
  unsigned char* o;
  uint4* qs;
  unsigned char* part;
  const bf16 *xin, *xq;
  bf16 *xout, *xn;
  unsigned char* arena;
  const unsigned* go;
  int tl;
  uint32_t nap, nap2;
  int pfprep, pfq, pfb;
};
}

template <int N0, int N1>
__device__ __forceinline__ void tr_mainloop(float (&a0)[N0 / 2], float (&a1)[N1 ? N1 / 2 : 1], Pipe& p, uint32_t sb, uint32_t full, uint32_t empty, int nkb, int wg) {
  using namespace tr;
  constexpr uint32_t ST = N1 ? STO : STQ;
  uint32_t prev = 0;
#pragma unroll
  for (int i = 0; i < N0 / 2; i++) { if (ZINIT) a0[i] = 0.f; else asm volatile("" : "=f"(a0[i])); }
  if constexpr (N1 > 0) {
#pragma unroll
    for (int i = 0; i < N1 / 2; i++) a1[i] = 0.f;
  }
#pragma unroll 1
  for (int kb = 0; kb < nkb; kb++) {
    mbar_wait(full + 8 * p.stage, p.phase);
    const uint32_t st = ((sb & 0x3FFFF) >> 4) + p.stage * (ST / 16), sa = st + wg * 512;
    wgmma_fence();
#pragma unroll
    for (int kk = 0; kk < 4; kk++) {
      const uint64_t da = desc16<16, 1024, 1>(sa, kk * 32);
      if constexpr (N0 == 192) wgmma_n192<0, 1>(a0, da, desc16<8192, 1024, 1>(st, 16384 + kk * 2048), (kb | kk) != 0);
      else wgmma_n128<0, 1>(a0, da, desc16<8192, 1024, 1>(st, 16384 + kk * 2048), (kb | kk) != 0);
      if constexpr (N1 > 0) wgmma_n128<0, 1>(a1, da, desc16<8192, 1024, 1>(st, 16384 + 24576 + kk * 2048), (kb | kk) != 0);
    }
    wgmma_commit();
    if (kb > 0) { wgmma_wait<1>(); mbar_arrive_if((threadIdx.x & 127) == 0, empty + 8 * prev); }
    prev = p.stage;
    pipe_adv<NS>(p);
  }
  wgmma_wait<0>();
  mbar_arrive_if((threadIdx.x & 127) == 0, empty + 8 * prev);
}
template <int N> __device__ __forceinline__ void stage_tiles(const float (&o)[N / 2], uint32_t base, int wi, int lane) {
  const uint32_t ra = base + (wi * 16 + (lane & 7) + 8 * ((lane >> 3) & 1)) * 128;
#pragma unroll
  for (int v = 0; v < N / 8; v += 2)
    stsm_x4(ra + (v >> 3) * 8192 + ((((v & 7) + (lane >> 4)) ^ (lane & 7)) << 4), pack_bf16(o[4 * v], o[4 * v + 1]), pack_bf16(o[4 * v + 2], o[4 * v + 3]),
            pack_bf16(o[4 * v + 4], o[4 * v + 5]), pack_bf16(o[4 * v + 6], o[4 * v + 7]));
}
__global__ void __launch_bounds__(384, 1) trail_kernel(const __grid_constant__ CUtensorMap tmX, const __grid_constant__ CUtensorMap tmQ,
                                                       const __grid_constant__ CUtensorMap tmWo5, const __grid_constant__ CUtensorMap tmWo2,
                                                       const __grid_constant__ CUtensorMap tmP, const __grid_constant__ CUtensorMap tmP4, const __grid_constant__ tr::Sched sc,
                                                       const __grid_constant__ tr::Args a, const __grid_constant__ PrepArgs pa) {
  using namespace tr;
  [[maybe_unused]] const int tl = a.tl;
  TL_BEGIN(tl);
  extern __shared__ __align__(1024) unsigned char smem_raw[];
  const uint32_t sb = smem_u32(smem_raw);
  const int warp = __shfl_sync(0xffffffffu, (int)threadIdx.x >> 5, 0), lane = threadIdx.x & 31;
  unsigned char* const arena = a.arena;
  const uint32_t full = sb + OFF_BAR, empty = full + 8 * NS, barK = empty + 8 * NS, barKfree = barK + 16, staged = barKfree + 16;
  const uint32_t kvrdy = staged + 32, mfull = kvrdy + 8, mempty = mfull + 16, mbox = mempty + 16;
  uint32_t go = 0;
  if (threadIdx.x == 256) go = ld_acquire_u32(a.go);
  if (threadIdx.x == 0) {
    for (int i = 0; i < NS; i++) { mbar_init(full + 8 * i, 1); mbar_init(empty + 8 * i, 2); }
    for (int i = 0; i < 2; i++) {
      mbar_init(barK + 8 * i, 1); mbar_init(barKfree + 8 * i, 1); mbar_init(staged + 16 * i, 4); mbar_init(staged + 16 * i + 8, 4);
      mbar_init(mfull + 8 * i, 1); mbar_init(mempty + 8 * i, 11);
    }
    mbar_init(kvrdy, 1);
    asm volatile("fence.mbarrier_init.release.cluster;" ::: "memory");
  }
  __syncthreads();
  Pipe mp{0, 0};
  auto next_item = [&]() -> uint32_t {
    uint32_t it;
    mbar_wait(mfull + 8 * mp.stage, mp.phase);
    asm volatile("ld.shared.u32 %0, [%1];" : "=r"(it) : "r"(mbox + 4 * mp.stage) : "memory");
    return it;
  };
  if (warp >= 8) {
    asm volatile("setmaxnreg.dec.sync.aligned.u32 40;");
    if (warp == 8) { go = __shfl_sync(0xffffffffu, go, 0); if (elect_one()) {
      Pipe p{0, 1};
      mp.phase = 1;
      uint32_t kph = 1, rph = 0, wide = 0, qdone = 0;
      prefetch_tmap(&tmX); prefetch_tmap(&tmQ); prefetch_tmap(&tmWo5); prefetch_tmap(&tmWo2); prefetch_tmap(&tmP); prefetch_tmap(&tmP4);
      const uint64_t ef = policy_evict_first();
      auto ld_kv = [&](uint32_t d, const void* s, uint32_t n, uint32_t mb) { if (EF_KV) bulk_g2s_hint(d, s, n, mb, ef); else bulk_g2s(d, s, n, mb); };
      auto ld_o = [&](uint32_t d, const void* s, uint32_t n, uint32_t mb) { if (EF_O) bulk_g2s_hint(d, s, n, mb, ef); else bulk_g2s(d, s, n, mb); };
      auto stage = [&](uint32_t bytes) -> uint32_t {
        mbar_wait(empty + 8 * p.stage, p.phase);
        mbar_expect_tx(full + 8 * p.stage, bytes);
        return sb + p.stage * (wide ? STO : STQ);
      };
      auto fetch = [&]() -> uint32_t { uint32_t v; asm volatile("atom.relaxed.gpu.global.add.u32 %0, [%1], 1;" : "=r"(v) : "l"(arena + AR_QUEUE) : "memory"); return v; };
      if (!go) wait_ge(a.go, 1, 200);
      fence_proxy_async_global();
      uint32_t next = fetch();
      while (true) {
        const uint32_t item = next;
        const uint32_t code = sc.item[min(item, sc.n)];
        const int type = (code >> 11) & 7, m = (code >> 7) & 15, k = code & 127;
        const bool late = code >> 14;
        auto done_wait = [&]() { mbar_wait(mempty + 8 * (mp.stage ^ 1), mp.stage ? mp.phase ^ 1 : mp.phase); };
        if (type == T_A && !((qdone >> m) & 1)) { wait_ge(arena + C_Q + m * 4, 64); qdone |= 1u << m; }
        if (type == T_OB && !wide) for (uint32_t i = 0; i < NS; i++) mbar_wait(empty + 8 * i, i >= p.stage ? p.phase : p.phase ^ 1);
        wide = type == T_OB;
        mbar_wait(mempty + 8 * mp.stage, mp.phase);
        asm volatile("st.shared.u32 [%0], %1;" :: "r"(mbox + 4 * mp.stage), "r"((p.stage << 24) | (type << 16) | (m << 8) | (k & 255)) : "memory");
        mbar_arrive(mfull + 8 * mp.stage);
        pipe_adv<2>(mp);
        if (type == T_END) break;
        if (type == T_P) { done_wait(); next = fetch(); continue; }
        if (type == T_L) {
          const int nr = sc.lrows[m], np = sc.ks[m];
          prefetch_l2(a.xin + (size_t)(m * 128 + k * 8 * nr) * cfg::DM, nr * 10240);
          wait_ge(arena + C_O + m * 4, np * (sc.wide[m] ? 4 : 10), m < 13 ? a.nap : 20);
          fence_proxy_async_global();
#pragma unroll 1
          for (int r = 0; r < nr; r++) {
            const int rg = m * 16 + k * nr + r;
#pragma unroll 1
            for (int q0 = 0; q0 <= np; q0 += 4) {
              const int n = min(4, np + 1 - q0);
              const uint32_t st = stage(n * 10240), fb = full + 8 * p.stage;
              if (q0 + 4 <= np) tma_load_4d(st, &tmP4, 0, rg & 7, (rg >> 3) * 10, q0, fb);
              else {
                bulk_g2s(st + (n - 1) * 10240, a.xin + (size_t)rg * 8 * cfg::DM, 10240, fb);
#pragma unroll 1
                for (int q = q0; q < np; q++) tma_load_4d(st + (q - q0) * 10240, &tmP, 0, rg & 7, (rg >> 3) * 10, q, fb);
              }
              pipe_adv<NS>(p);
            }
          }
          if (late) done_wait();
          next = fetch(); continue;
        }
        if (type <= T_A) {
          if (type != T_A)
#pragma unroll 1
            for (int kb = 0; kb < 10; kb++) {
              const uint32_t st = stage(STQ), fb = full + 8 * p.stage;
              tma_load_2d(st, &tmX, kb * 64, m * 128, fb);
              tma_load_3d(st + 16384, &tmQ, 0, kb * 64, k * 3, fb);
              pipe_adv<NS>(p);
              if (type == T_Q && kb == 8) next = fetch();
            }
          if (type != T_Q) {
            const size_t blk = ((size_t)m * 4 * 96 + k * 3) * 5120;
            kph ^= 1;
            mbar_wait(kvrdy, rph); rph ^= 1;
            if (!late) next = fetch();
            fence_proxy_async_global();
#pragma unroll 1
            for (int w = type == T_A ? 0 : 2; w < 4; w++) {
              const uint32_t st = stage(2 * SEGB), fb = full + 8 * p.stage;
              for (int sg = 0; sg < 2; sg++) ld_kv(st + sg * SEGB, (w < 2 ? a.kg : a.vg) + blk + (size_t)(2 * (w & 1) + sg) * (96 * 5120), SEGB, fb);
              pipe_adv<NS>(p);
            }
            if (late) { done_wait(); next = fetch(); }
          }
        } else {
          const int nn = wide ? 2 : 5, nb = wide ? 5 : 2, nt = k % nn, nkb = 96 / sc.ks[m], k0 = (k / nn) * nkb;
          const Pipe p0 = p;
          for (int kb = 0; kb < nkb; kb++) {
            if (wide && kb < NS && p.stage >= 2) { mbar_wait(barKfree, kph); mbar_wait(barKfree + 8, kph); }
            const uint32_t st = stage(16384 + nb * 8192), fb = full + 8 * p.stage;
            tma_load_3d(st + 16384, wide ? &tmWo5 : &tmWo2, 0, (k0 + kb) * 64, nt * nb, fb);
            if (kb >= NS) ld_o(st, a.o + ((size_t)m * 96 + k0 + kb) * 16384, 16384, fb);
            pipe_adv<NS>(p);
            if (kb == NS - 1 || (kb == nkb - 1 && nkb < NS)) {
              wait_ge(arena + C_QA + m * 4, 64, m < 14 ? a.nap : 32);
              fence_proxy_async_global();
              Pipe q = p0;
#pragma unroll 1
              for (int i = 0; i <= kb; i++) { ld_o(sb + q.stage * (wide ? STO : STQ), a.o + ((size_t)m * 96 + k0 + i) * 16384, 16384, full + 8 * q.stage); pipe_adv<NS>(q); }
            }
          }
          if (!late) next = fetch();
          for (int w = wide ? -(int)((2 - p.stage) & 3) : 0; w < 2; w++) { mbar_wait(empty + 8 * p.stage, p.phase); mbar_arrive(full + 8 * p.stage); pipe_adv<NS>(p); }
          kph ^= wide;
          if (late) { done_wait(); next = fetch(); }
        }
      }
    } } else if (warp < 11) { if (elect_one()) {
      const int w = warp - 9;
      uint32_t sph = 0;
      [[maybe_unused]] int nlog = 0;
#ifdef TIMELINE
      if (w == 0) { unsigned long long* lg = g_log + (((tl >= 12) * 132 + blockIdx.x) * 64 + nlog++) * 2; lg[0] = T_END << 16; lg[1] = gtime(); lg[2] = ~0ull; }
#endif
      while (true) {
        const uint32_t it = next_item();
        const int type = (it >> 16) & 255, m = (it >> 8) & 255, k = it & 255;
        const uint32_t slot = mp.stage;
        pipe_adv<2>(mp);
        if (type == T_END) break;
        mbar_wait(staged + 16 * w + 8 * slot, (sph >> slot) & 1); sph ^= 1u << slot;
        mbar_arrive(mempty + 8 * slot);
#ifdef TIMELINE
        if (w == 0 && nlog < 63) { unsigned long long* lg = g_log + (((tl >= 12) * 132 + blockIdx.x) * 64 + nlog++) * 2; lg[0] = (type << 16) | (m << 8) | k; lg[1] = gtime(); lg[2] = ~0ull; }
#endif
        if (type == T_L) continue;
        if (type == T_QA || type == T_A) {
          for (int jj = 0; jj < 3; jj++) bulk_s2g(a.o + ((size_t)m * 96 + k * 3 + jj) * 16384 + w * 8192, sb + OFF_K + w * 2 * SEGB + jj * 8192, 8192);
          bulk_commit();
          bulk_wait<0>();
          mbar_arrive(barKfree + 8 * w);
        } else if (type == T_OB || type == T_OS) {
          const bool wide = type == T_OB;
          const int nn = wide ? 2 : 5, nb = wide ? 5 : 2;
          const uint32_t own = wide ? 2 + w : ((it >> 24) + 96 / sc.ks[m] + w) % NS;
          bulk_s2g(a.part + ((size_t)((k / nn) * 32 + m * 2 + w) * 10 + (k % nn) * nb) * 8192, sb + own * (wide ? STO : STQ), nb * 8192);
          bulk_commit();
          bulk_wait<0>();
          mbar_arrive(empty + 8 * own);
          if (wide && w) { mbar_arrive(barKfree); mbar_arrive(barKfree + 8); }
        }
        red_release_inc(arena + (type == T_Q ? C_Q : (type <= T_A ? C_QA : (type == T_P ? C_P : C_O))) + m * 4);
      }
    } } else if (elect_one()) {
      const uint64_t ef = policy_evict_first();
      uint32_t kph = 1;
      while (true) {
        const uint32_t it = next_item();
        const int type = (it >> 16) & 255, m = (it >> 8) & 255, k = it & 255;
        const uint32_t slot = mp.stage;
        pipe_adv<2>(mp);
        if (type == T_END) break;
        if ((type == T_QA || type == T_A) && m == a.pfprep) { prefetch_l2(pa.wqkv + k * 38400, 76800); prefetch_l2(pa.wo + k * 12800, 25600); }
        if ((type == T_QA || type == T_A) && m == a.pfb) { prefetch_l2(pa.wb + k * 81920, 81920); prefetch_l2(pa.wot + k * 25600, 25600); }
        if ((type == T_QA || type == T_A) && m == a.pfb + 1) { prefetch_l2(a.xn + k * 20480, 40960); prefetch_l2(a.xout + k * 20480, 40960); }
        if ((type == T_QA || type == T_A) && m < 15) {
          if (m + 1 < sc.nqa) prefetch_l2(a.xq + ((m + 1) * 128 + k * 4) * cfg::DM, 5120);
          else if (a.pfq) prefetch_l2(a.qs + ((size_t)(((m + 1) & 7) * 32 + k) * 12) * 256, 49152);
        }
        if (type == T_QA || type == T_A) {
          for (int spin = 0; spin < (1 << 21); spin++) {
            uint4 f;
            asm volatile("ld.acquire.gpu.global.v4.u32 {%0,%1,%2,%3}, [%4];" : "=r"(f.x), "=r"(f.y), "=r"(f.z), "=r"(f.w) : "l"(arena + prog_off(k, 0)) : "memory");
            if (min(min(f.x, f.y), f.z) >= (uint32_t)(4 * m + 4)) break;
            __nanosleep(m < 15 ? a.nap : a.nap2);
          }
          mbar_arrive(kvrdy);
          fence_proxy_async_global();
          const unsigned char* src = a.kg + ((size_t)m * 4 * 96 + k * 3) * 5120;
#pragma unroll 1
          for (int w = 0; w < 2; w++) {
            mbar_wait(barKfree + 8 * w, kph);
            if (type == T_A) { mbar_arrive(barK + 8 * w); continue; }
            mbar_expect_tx(barK + 8 * w, 2 * SEGB);
            for (int sg = 2 * w; sg < 2 * w + 2; sg++) { if (EF_KV) bulk_g2s_hint(sb + OFF_K + sg * SEGB, src + (size_t)sg * (96 * 5120), SEGB, barK + 8 * w, ef); else bulk_g2s(sb + OFF_K + sg * SEGB, src + (size_t)sg * (96 * 5120), SEGB, barK + 8 * w); }
          }
          kph ^= 1;
        } else if (type == T_OB) {
          mbar_wait(barKfree, kph); mbar_wait(barKfree + 8, kph);
          kph ^= 1;
        }
        mbar_arrive(mempty + 8 * slot);
      }
      if (blockIdx.x == gridDim.x - 1) asm volatile("griddepcontrol.wait;" ::: "memory");
    }
    return;
  }
  asm volatile("setmaxnreg.inc.sync.aligned.u32 232;");
  const int wg = warp >> 2, wi = warp & 3;
  const int g = lane >> 2, q4 = lane & 3;
  asm volatile("griddepcontrol.launch_dependents;" ::: "memory");
  Pipe p{0, 0};
  uint32_t kph = 0;
  auto own_slot = [&]() -> uint32_t {
    const uint32_t sA = p.stage, phA = p.phase; pipe_adv<NS>(p);
    const uint32_t sB = p.stage, phB = p.phase; pipe_adv<NS>(p);
    mbar_wait_if(wi == 0, full + 8 * (wg ? sA : sB), wg ? phA : phB);
    mbar_wait(full + 8 * (wg ? sB : sA), wg ? phB : phA);
    mbar_arrive_if((threadIdx.x & 127) == 0, empty + 8 * (wg ? sA : sB));
    return wg ? sB : sA;
  };
  while (true) {
    const uint32_t it = __shfl_sync(0xffffffffu, next_item(), 0);
    const int type = (it >> 16) & 255, m = (it >> 8) & 255, k = it & 255;
    mbar_arrive_if(lane == 0, mempty + 8 * mp.stage);
    const uint32_t done = staged + 16 * wg + 8 * mp.stage;
    pipe_adv<2>(mp);
    if (type == T_END) break;
    if (type == T_P) {
      prep_body(k, pa);
      bar_sync(3 + wg, 128);
      mbar_arrive_if(lane == 0, done);
      continue;
    }
    if (type == T_L) {
      const int nr = sc.lrows[m], np = sc.ks[m];
      const uint32_t po = (lane >> 4) * 1024 + warp * 128 + ((((lane >> 1) & 7) ^ warp) << 4) + (lane & 1) * 8;
#pragma unroll 1
      for (int r = 0; r < nr; r++) {
        uint2 xw[1][5]; float s[20];
#pragma unroll
        for (int i = 0; i < 20; i++) s[i] = 0.f;
#pragma unroll 1
        for (int q0 = 0; q0 <= np; q0 += 4) {
          const uint32_t st = sb + p.stage * STQ;
          mbar_wait(full + 8 * p.stage, p.phase);
          const int n = min(4, np - q0);
#pragma unroll 1
          for (int q = 0; q < n; q += 2) {
            uint2 t[5], u[5];
            const uint32_t pa_ = st + q * 10240 + po, keep = q + 1 < n ? ~0u : 0u;
            static_for<0, 5>([&](auto I) { t[I.value] = lds64_i<I.value * 2048>(pa_); u[I.value] = lds64_i<I.value * 2048 + 10240>(pa_); });
#pragma unroll
            for (int i = 0; i < 5; i++) {
              u[i].x &= keep; u[i].y &= keep;
              s[4 * i] += bf_lo(t[i].x) + bf_lo(u[i].x); s[4 * i + 1] += bf_hi(t[i].x) + bf_hi(u[i].x); s[4 * i + 2] += bf_lo(t[i].y) + bf_lo(u[i].y); s[4 * i + 3] += bf_hi(t[i].y) + bf_hi(u[i].y);
            }
          }
          if (n < 4) {
            static_for<0, 5>([&](auto I) { xw[0][I.value] = lds64_i<I.value * 256>(st + n * 10240 + warp * 1280 + lane * 8); });
            SFENCE2(st, xw[0][0].x ^ xw[0][1].x ^ xw[0][2].x ^ xw[0][3].x ^ xw[0][4].x);
          }
          bar_sync(3 + wg, 128);
          mbar_arrive_if((threadIdx.x & 127) == 0, empty + 8 * p.stage);
          pipe_adv<NS>(p);
        }
        const int row = (m * 16 + k * nr + r) * 8 + warp;
#pragma unroll
        for (int i = 0; i < 5; i++) {
          bf16r2(s[4 * i], s[4 * i + 1]); bf16r2(s[4 * i + 2], s[4 * i + 3]);
          xw[0][i] = make_uint2(pack_bf16(bf_lo(xw[0][i].x) + s[4 * i], bf_hi(xw[0][i].x) + s[4 * i + 1]), pack_bf16(bf_lo(xw[0][i].y) + s[4 * i + 2], bf_hi(xw[0][i].y) + s[4 * i + 3]));
          *(uint2*)(a.xout + (size_t)row * cfg::DM + i * 128 + lane * 4) = xw[0][i];
        }
        ln_rows<1>(xw, row, lane, a.xn, nullptr);
      }
      __syncwarp();
      mbar_arrive_if(lane == 0, done);
      continue;
    }
    if (type >= T_OB) {
      const int nkb = 96 / sc.ks[m];
      if (type == T_OB) {
        float a0[96], a1[64];
        tr_mainloop<192, 128>(a0, a1, p, sb, full, empty, nkb, wg);
        while (p.stage != 2) { mbar_wait_if(wi == 0, full + 8 * p.stage, p.phase); mbar_arrive_if((threadIdx.x & 127) == 0, empty + 8 * p.stage); pipe_adv<NS>(p); }
        const uint32_t st = sb + own_slot() * STO;
        stage_tiles<192>(a0, st, wi, lane); stage_tiles<128>(a1, st + 24576, wi, lane);
      } else {
        float a0[64], a1[1];
        tr_mainloop<128, 0>(a0, a1, p, sb, full, empty, nkb, wg);
        stage_tiles<128>(a0, sb + own_slot() * STQ, wi, lane);
      }
      fence_proxy_async();
      __syncwarp();
      mbar_arrive_if(lane == 0, done);
      continue;
    }
    uint32_t qf[12][4];
    uint4* qp = a.qs + ((size_t)((m & 7) * 32 + k) * 12) * 256 + threadIdx.x;
    if (type != T_A) {
      float acc[96], a1[1];
      tr_mainloop<192, 0>(acc, a1, p, sb, full, empty, 10, wg);
#pragma unroll
      for (int i = 0; i < 12; i++) {
        qf[i][0] = pack_bf16(acc[8 * i], acc[8 * i + 1]); qf[i][1] = pack_bf16(acc[8 * i + 2], acc[8 * i + 3]);
        qf[i][2] = pack_bf16(acc[8 * i + 4], acc[8 * i + 5]); qf[i][3] = pack_bf16(acc[8 * i + 6], acc[8 * i + 7]);
      }
      if (type == T_Q) {
#pragma unroll
        for (int i = 0; i < 12; i++) qp[i * 256] = make_uint4(qf[i][0], qf[i][1], qf[i][2], qf[i][3]);
        __syncwarp();
        mbar_arrive_if(lane == 0, done);
        continue;
      }
    } else {
#pragma unroll
      for (int i = 0; i < 12; i++) { const uint4 v = __ldcg(qp + i * 256); qf[i][0] = v.x; qf[i][1] = v.y; qf[i][2] = v.z; qf[i][3] = v.w; }
    }
    const uint32_t ost = sb + OFF_K + wg * 2 * SEGB;
    const bool second = wi >= 2;
    uint32_t pf[5][4];
    {
      float sa[20], sb2[20];
      uint32_t kbase = ost, kslot = 0;
      if (type == T_A) { kslot = own_slot(); kbase = sb + kslot * STQ; } else mbar_wait(barK + 8 * wg, kph);
      kbase = (kbase & 0x3FFFF) >> 4;
      if (STAG && wg) bar_sync(1, 256);
      wgmma_fence();
#pragma unroll
      for (int i = 0; i < 12; i++) {
        wgmma_rs_n40<0>(sa, qf[i][0], qf[i][1], qf[i][2], qf[i][3], desc16<640, 128, 0>(kbase, i * 1280), i != 0);
        wgmma_rs_n40<0>(sb2, qf[i][0], qf[i][1], qf[i][2], qf[i][3], desc16<640, 128, 0>(kbase, SEGB + i * 1280), i != 0);
      }
      wgmma_commit();
      if (STAG && !wg) bar_arrive(1, 256);
      wgmma_wait<0>();
      mbar_arrive_if(type == T_A && (threadIdx.x & 127) == 0, empty + 8 * kslot);
      const float cs = 0.07216878364870322f * 1.4426950408889634f;
      const int r0 = 16 * (wi & 1) + g, r1 = r0 + 8;
      float m0 = -INFINITY, m1 = -INFINITY;
#pragma unroll
      for (int n = 0; n < 5; n++) {
#pragma unroll
        for (int e = 0; e < 2; e++) {
          const int key = 8 * n + 2 * q4 + e;
          float x = second ? sb2[4 * n + e] : sa[4 * n + e], y = second ? sb2[4 * n + 2 + e] : sa[4 * n + 2 + e];
          if (n < 4) { if (key > r0) x = -INFINITY; if (key > r1) y = -INFINITY; }
          sa[4 * n + e] = x; sa[4 * n + 2 + e] = y;
          m0 = fmaxf(m0, x); m1 = fmaxf(m1, y);
        }
      }
      m0 = fmaxf(fmaxf(m0, __shfl_xor_sync(0xffffffffu, m0, 1)), fmaxf(__shfl_xor_sync(0xffffffffu, m0, 2), __shfl_xor_sync(0xffffffffu, m0, 3)));
      m1 = fmaxf(fmaxf(m1, __shfl_xor_sync(0xffffffffu, m1, 1)), fmaxf(__shfl_xor_sync(0xffffffffu, m1, 2), __shfl_xor_sync(0xffffffffu, m1, 3)));
      m0 *= -cs; m1 *= -cs;
      float s0 = 0.f, s1 = 0.f;
#pragma unroll
      for (int n = 0; n < 5; n++) {
#pragma unroll
        for (int e = 0; e < 2; e++) {
          sa[4 * n + e] = ex2f(fmaf(sa[4 * n + e], cs, m0)); sa[4 * n + 2 + e] = ex2f(fmaf(sa[4 * n + 2 + e], cs, m1));
          s0 += sa[4 * n + e]; s1 += sa[4 * n + 2 + e];
        }
      }
      s0 = (s0 + __shfl_xor_sync(0xffffffffu, s0, 1)) + (__shfl_xor_sync(0xffffffffu, s0, 2) + __shfl_xor_sync(0xffffffffu, s0, 3));
      s1 = (s1 + __shfl_xor_sync(0xffffffffu, s1, 1)) + (__shfl_xor_sync(0xffffffffu, s1, 2) + __shfl_xor_sync(0xffffffffu, s1, 3));
      const float i0 = rcpf(s0), i1 = rcpf(s1);
#pragma unroll
      for (int n = 0; n < 5; n++) {
        const uint32_t x = pack_bf16(sa[4 * n] * i0, sa[4 * n + 1] * i0), y = pack_bf16(sa[4 * n + 2] * i1, sa[4 * n + 3] * i1);
        if (n < 4) {
          pf[n >> 1][2 * (n & 1)] = second ? 0u : x; pf[n >> 1][2 * (n & 1) + 1] = second ? 0u : y;
          pf[2 + (n >> 1)][2 * (n & 1)] = second ? x : 0u; pf[2 + (n >> 1)][2 * (n & 1) + 1] = second ? y : 0u;
        } else {
          pf[4][0] = second ? 0u : x; pf[4][1] = second ? 0u : y; pf[4][2] = second ? x : 0u; pf[4][3] = second ? y : 0u;
        }
      }
    }
    {
      float o[96];
#pragma unroll
      for (int i = 0; i < 5; i++) { PIN(pf[i][0]); PIN(pf[i][1]); PIN(pf[i][2]); PIN(pf[i][3]); }
      const uint32_t own = own_slot(), vbase = ((sb & 0x3FFFF) >> 4) + own * (STQ / 16);
      wgmma_fence();
#pragma unroll
      for (int i = 0; i < 5; i++)
        wgmma_rs_n192<1>(o, pf[i][0], pf[i][1], pf[i][2], pf[i][3], i < 4 ? desc16<128, 640, 0>(vbase, (i >> 1) * SEGB + (i & 1) * 256) : desc16<SEGB, 640, 0>(vbase, 512), i != 0);
      wgmma_commit();
      if (type == T_A) mbar_wait(barK + 8 * wg, kph);
      kph ^= 1;
      wgmma_wait<0>();
      mbar_arrive_if((threadIdx.x & 127) == 0, empty + 8 * own);
      stage_tiles<192>(o, ost, wi, lane);
      fence_proxy_async();
      __syncwarp();
      mbar_arrive_if(lane == 0, done);
    }
  }
}
namespace bf {
constexpr int NS = 4, STAGE = 16384 + 32768;
constexpr int PIECE = 20480;
constexpr int OFF_PHI = 0, OFF_V = 40960, OFF_KV = 65536;
constexpr int OFF_OST = 5 * PIECE;
constexpr int OFF_WOT = 6 * PIECE;
constexpr int OFF_BAR = OFF_WOT + 102400;
constexpr int SMEM = OFF_BAR + 256;
static_assert(NS * STAGE <= OFF_BAR && SMEM <= 232448, "smem");
constexpr int KVACC = 32 * 5 * 1024;
struct Args {
  const unsigned char *wb, *wot;
  unsigned char *kvacc, *o2;
  const bf16* xin;
  bf16* xout;
  unsigned* go;
  const void* prep;
  const bf16 *pf0, *pf1;
  int pfn, pfns, pfwait;
  int tl;
};
}
__device__ __forceinline__ void hedgehog_features(float (&x)[2][5], uint32_t (&w)[2][5]) {
  const float L = 1.4426950408889634f;
  float mx[2], mn[2], sp[2], sn[2], pos[2][5], neg[2][5];
#pragma unroll
  for (int r = 0; r < 2; r++) {
    mx[r] = fmaxf(fmaxf(fmaxf(x[r][0], x[r][1]), fmaxf(x[r][2], x[r][3])), x[r][4]);
    mn[r] = fminf(fminf(fminf(x[r][0], x[r][1]), fminf(x[r][2], x[r][3])), x[r][4]);
  }
#pragma unroll
  for (int o = 1; o < 4; o <<= 1)
#pragma unroll
    for (int r = 0; r < 2; r++) {
      const uint32_t t = __shfl_xor_sync(0xffffffffu, __byte_perm(__float_as_uint(mn[r]), __float_as_uint(mx[r]), 0x7632), o);
      mx[r] = fmaxf(mx[r], bf_hi(t)); mn[r] = fminf(mn[r], bf_lo(t));
    }
#pragma unroll
  for (int r = 0; r < 2; r++) {
#pragma unroll
    for (int i = 0; i < 5; i++) { pos[r][i] = ex2f((x[r][i] - mx[r]) * L); neg[r][i] = ex2f((mn[r] - x[r][i]) * L); }
    sp[r] = ((pos[r][0] + pos[r][1]) + (pos[r][2] + pos[r][3])) + pos[r][4];
    sn[r] = ((neg[r][0] + neg[r][1]) + (neg[r][2] + neg[r][3])) + neg[r][4];
  }
#pragma unroll
  for (int o = 1; o < 4; o <<= 1)
#pragma unroll
    for (int r = 0; r < 2; r++) { sp[r] += __shfl_xor_sync(0xffffffffu, sp[r], o); sn[r] += __shfl_xor_sync(0xffffffffu, sn[r], o); }
#pragma unroll
  for (int r = 0; r < 2; r++) {
    const float ip = rcpf(sp[r]), in_ = rcpf(sn[r]);
    w[r][0] = pack_bf16(pos[r][0] * ip, pos[r][1] * ip); w[r][1] = pack_bf16(pos[r][2] * ip, pos[r][3] * ip);
    w[r][2] = pack_bf16(neg[r][0] * in_, neg[r][1] * in_); w[r][3] = pack_bf16(neg[r][2] * in_, neg[r][3] * in_);
    w[r][4] = pack_bf16(pos[r][4] * ip, neg[r][4] * in_);
  }
}
__device__ __forceinline__ void bulk_g2s_mc(uint32_t dst, const void* src, uint32_t bytes, uint32_t mb) {
  asm volatile("cp.async.bulk.shared::cluster.global.mbarrier::complete_tx::bytes.multicast::cluster [%0], [%1], %2, [%3], %4;"
               :: "r"(dst), "l"(src), "r"(bytes), "r"(mb), "h"((unsigned short)3) : "memory");
}
__device__ __forceinline__ void mbar_arrive_remote_if(bool c, uint32_t b) {
  asm volatile("{\n.reg .pred p;\nsetp.ne.u32 p, %1, 0;\n@p mbarrier.arrive.shared::cluster.b64 _, [%0];\n}" :: "r"(b), "r"((uint32_t)c) : "memory");
}

__global__ void __cluster_dims__(2, 1, 1) __launch_bounds__(384, 1) blayer_kernel(const __grid_constant__ CUtensorMap tmA, const __grid_constant__ bf::Args a) {
  using namespace bf;
  [[maybe_unused]] const int tl = a.tl;
  extern __shared__ __align__(1024) unsigned char smem_raw[];
  const uint32_t sb = smem_u32(smem_raw);
  const int warp = __shfl_sync(0xffffffffu, (int)threadIdx.x >> 5, 0), lane = threadIdx.x & 31;
  const uint32_t full = sb + OFF_BAR, empty = full + 8 * NS, full2 = empty + 8 * NS, empty2 = full2 + 64, barW = empty2 + 16, drained = barW + 8, staged = drained + 8, freeb = staged + 8;
  const int rank = blockIdx.x & 1, u = (blockIdx.x >> 1) & 7, mp = blockIdx.x >> 4;
  const int m = 2 * mp + rank;
  const int m2 = 2 * mp + (u & 1), ns = (u & ~1) + rank;
  const uint32_t dpeer = mapa_u32(sb, rank ^ 1) - sb;
  unsigned* cntO = (unsigned*)(a.kvacc + KVACC);
  if (threadIdx.x == 0) {
    for (int i = 0; i < NS; i++) { mbar_init(full + 8 * i, 1); mbar_init(empty + 8 * i, 4); }
    for (int i = 0; i < 8; i++) mbar_init(full2 + 8 * i, 1);
    mbar_init(empty2, 2); mbar_init(empty2 + 8, 2);
    mbar_init(barW, 1); mbar_init(drained, 1); mbar_init(staged, 8); mbar_init(freeb, 2);
    asm volatile("fence.mbarrier_init.release.cluster;" ::: "memory");
  }
  __syncthreads();
  asm volatile("barrier.cluster.arrive.relaxed.aligned; barrier.cluster.wait.aligned;" ::: "memory");
  if (warp >= 8) {
    asm volatile("setmaxnreg.dec.sync.aligned.u32 40;");
    if (warp == 8) { if (elect_one()) {
      const unsigned char* wsrc = a.wb + (size_t)u * 327680 + rank * 16384;
      if (a.prep) wait_ge(a.prep, 64);
      fence_proxy_async_global();
      for (int kb = 0; kb < NS; kb++) {
        mbar_expect_tx(full + 8 * kb, STAGE);
        bulk_g2s_mc(sb + kb * STAGE + 16384 + rank * 16384, wsrc + kb * 32768, 16384, full + 8 * kb);
      }
      asm volatile("griddepcontrol.wait;" ::: "memory");
      TL_BEGIN0(tl);
      LITE(blockIdx.x == 0, (tl >= 12) * 4 + 2);
      if (blockIdx.x == 0) *a.go = 0;
      for (int kb = 0; kb < NS; kb++) tma_load_2d(sb + kb * STAGE, &tmA, kb * 64, m * 128, full + 8 * kb);
      if (m == 0) prefetch_l2(a.kvacc + u * (KVACC / 8), KVACC / 8);
#pragma unroll 1
      for (int kb = NS; kb < 10; kb++) {
        const uint32_t s = kb & 3, st = sb + s * STAGE, fb = full + 8 * s;
        mbar_wait(empty + 8 * s, ((kb >> 2) - 1) & 1);
        mbar_expect_tx(fb, STAGE);
        tma_load_2d(st, &tmA, kb * 64, m * 128, fb);
        bulk_g2s_mc(st + 16384 + rank * 16384, wsrc + kb * 32768, 16384, fb);
      }
      for (int i = 0; i < 6; i++) mbar_expect_tx(full2 + 8 * i, PIECE);
      mbar_wait(drained, 0);
      mbar_expect_tx(barW, 102400);
      bulk_g2s(sb + OFF_WOT, a.wot + (size_t)ns * 102400, 102400, barW);
      mbar_wait(staged, 0);
      bulk_s2g(a.o2 + (size_t)(m * 8 + u) * PIECE, sb + OFF_OST, PIECE);
      bulk_commit();
      bulk_wait<0>();
      mbar_arrive(freeb); mbar_arrive_remote_if(true, freeb + dpeer);
      red_release_inc(cntO + m);
      wait_ge(cntO + m2, 8, 20);
      mbar_wait(freeb, 0);
      fence_proxy_async_global();
      const unsigned char* osrc = a.o2 + (size_t)m2 * 8 * PIECE;
      for (int i = 0; i < 6; i++) bulk_g2s_mc(sb + i * PIECE + rank * (PIECE / 2), osrc + i * PIECE + rank * (PIECE / 2), PIECE / 2, full2 + 8 * i);
      for (int i = 0; i < 2; i++) {
        mbar_wait(empty2 + 8 * i, 0);
        mbar_expect_tx(full2 + 8 * (6 + i), PIECE);
        bulk_g2s(sb + i * PIECE, osrc + (6 + i) * PIECE, PIECE, full2 + 8 * (6 + i));
      }
    } } else if (warp == 9 && a.pf0) { if (elect_one()) {
      if (a.pfwait) asm volatile("griddepcontrol.wait;" ::: "memory");
      constexpr uint32_t CH = 2048;
      for (int i = 0; i < a.pfn; i++) {
        prefetch_l2((const unsigned char*)a.pf0 + (i * 128 + blockIdx.x) * CH, CH); prefetch_l2((const unsigned char*)a.pf1 + (i * 128 + blockIdx.x) * CH, CH);
        __nanosleep(a.pfns);
      }
    } }
    return;
  }
  asm volatile("setmaxnreg.inc.sync.aligned.u32 232;");
  const int wg = warp >> 2, wi = warp & 3;
  const int q4 = lane & 3;
  const bool lead = (threadIdx.x & 127) == 0;
  const uint32_t s16 = (sb & 0x3FFFF) >> 4;
  float acc[128];
  {
#pragma unroll 1
    for (int kb = 0; kb < 10; kb++) {
      const uint32_t s = kb & 3, st = s16 + s * (STAGE / 16);
      mbar_wait(full + 8 * s, (kb >> 2) & 1);
      wgmma_fence();
#pragma unroll
      for (int kk = 0; kk < 4; kk++) wgmma_n256<0, 1>(acc, desc16<16, 1024, 1>(st + wg * 512, kk * 32), desc16<4096, 128, 0>(st, 16384 + kk * 8192), (kb | kk) != 0);
      wgmma_commit();
      if (kb > 0 && kb < 7) { wgmma_wait<1>(); const uint32_t e = empty + 8 * ((kb - 1) & 3); mbar_arrive_if(lead, e); mbar_arrive_remote_if(lead, e + dpeer); }
    }
    wgmma_wait<0>();
    bar_sync(1, 256);
    mbar_arrive_if(threadIdx.x == 0, drained);
  }
  TL2((tl >= 12 ? 128 : 0) + 32 + 0);
  const uint32_t srow = (wg * 64 + wi * 16 + (lane & 15)) * 16 + (lane >> 4) * 2048;
  auto features = [&](auto T0, auto HH, uint32_t (&w)[2][5]) {
    constexpr int t = T0.value + 5 * (HH.value >> 1), o = (HH.value & 1) ? 3 : 0, e = HH.value & 1;
    float x[2][5];
#pragma unroll
    for (int r = 0; r < 2; r++) {
      x[r][0] = acc[4 * (t + o) + 2 * r]; x[r][1] = acc[4 * (t + o) + 2 * r + 1]; x[r][2] = acc[4 * (t + o + 1) + 2 * r]; x[r][3] = acc[4 * (t + o + 1) + 2 * r + 1];
      bf16r2(x[r][0], x[r][1]); bf16r2(x[r][2], x[r][3]);
    }
    x[0][4] = acc[4 * (t + 2) + e]; x[1][4] = acc[4 * (t + 2) + 2 + e];
    bf16r2(x[0][4], x[1][4]);
    hedgehog_features(x, w);
  };
  static_for<0, 4>([&](auto HH) {
    constexpr int hh = HH.value, t = 20 + 3 * hh;
    const uint32_t one = q4 == ((hh & 1) ? 0 : 2) ? 0x3f80u : 0u;
    const uint32_t va = sb + OFF_V + hh * 6144 + srow;
    stsm_x4(va, pack_bf16(acc[4 * t], acc[4 * t + 1]), pack_bf16(acc[4 * t + 2], acc[4 * t + 3]), pack_bf16(acc[4 * t + 4], acc[4 * t + 5]), pack_bf16(acc[4 * t + 6], acc[4 * t + 7]));
    const bool pad = (q4 >= 2) != (hh & 1);
    stsm_x2(va + 4096, pad ? one : pack_bf16(acc[4 * t + 8], acc[4 * t + 9]), pad ? one : pack_bf16(acc[4 * t + 10], acc[4 * t + 11]));
    uint32_t w[2][5];
    features(IC<10>{}, HH, w);
    const uint32_t pa = sb + OFF_PHI + hh * 10240 + srow;
    stsm_x4(pa, w[0][0], w[1][0], w[0][1], w[1][1]);
    stsm_x4(pa + 4096, w[0][2], w[1][2], w[0][3], w[1][3]);
    stsm_x2(pa + 8192, w[0][4], w[1][4]);
  });
  fence_proxy_async();
  bar_sync(1, 256);
  TL2((tl >= 12 ? 128 : 0) + 32 + 1);
  {
    float d0[12], d1[12];
    const uint32_t pa = s16 + wg * 1280, pv = s16 + wg * 768;
    wgmma_fence();
#pragma unroll
    for (int k = 0; k < 8; k++) {
      wgmma_n24<1, 1>(d0, desc16<128, 2048, 0>(pa, OFF_PHI + k * 256), desc16<128, 2048, 0>(pv, OFF_V + k * 256), k != 0);
      wgmma_n24<1, 1>(d1, desc16<128, 2048, 0>(pa, OFF_PHI + 10240 + k * 256), desc16<128, 2048, 0>(pv, OFF_V + 6144 + k * 256), k != 0);
    }
    wgmma_commit();
    wgmma_wait<0>();
    unsigned char* dst = a.kvacc + ((u * 4 + wg * 2) * 5 + 2 * wi) * 1024 + lane * 16;
    auto red4 = [&](bool on, unsigned char* p, float x, float y, float z) {
      asm volatile("{\n.reg .pred p;\nsetp.ne.u32 p, %4, 0;\n@p red.relaxed.gpu.global.add.v4.f32 [%0], {%1,%2,%3,%5};\n}" :: "l"(p), "f"(x), "f"(y), "f"(z), "r"((uint32_t)on), "f"(1.f) : "memory");
    };
    red4(wi < 3, dst, d0[0], d0[1], d0[4]); red4(wi < 3, dst + 512, d0[5], d0[8], d0[9]);
    red4(wi < 3, dst + 5120, d1[0], d1[1], d1[4]); red4(wi < 3, dst + 5632, d1[5], d1[8], d1[9]);
    red4(wi < 2, dst + 1024, d0[2], d0[3], d0[6]); red4(wi < 2, dst + 1536, d0[7], d0[10], d0[11]);
    red4(wi < 2, dst + 6144, d1[2], d1[3], d1[6]); red4(wi < 2, dst + 6656, d1[7], d1[10], d1[11]);
  }
  TL2((tl >= 12 ? 128 : 0) + 32 + 2);
  uint32_t qf[4][2][5];
  static_for<0, 4>([&](auto HH) { features(IC<0>{}, HH, qf[HH.value]); });
  uint4 xr[5];
#pragma unroll
  for (int i = 0; i < 5; i++) {
    const int c = lane + 32 * i;
    xr[i] = __ldcg((const uint4*)(a.xin + (size_t)(m2 * 128 + wg * 64 + wi * 16 + c / 10) * cfg::DM + ns * 80 + (c % 10) * 8));
  }
  {
    const unsigned char* src = a.kvacc + (u * 20 + warp) * 1024 + lane * 16;
    uint4 v[6];
    int spin = 0;
    while (true) {
      v[0] = ld_relaxed_v4_i<0>(src); v[1] = ld_relaxed_v4_i<512>(src); v[2] = ld_relaxed_v4_i<8192>(src); v[3] = ld_relaxed_v4_i<8704>(src);
      v[4] = ld_relaxed_v4_i<0>(src + (wg ? 0 : 16384)); v[5] = ld_relaxed_v4_i<512>(src + (wg ? 0 : 16384));
      const uint32_t c = (v[0].w & v[1].w & v[2].w) & (v[3].w & v[4].w & v[5].w);
      if (!__any_sync(0xffffffffu, (c & 0x41800000u) != 0x41800000u) || ++spin >= SPIN_LIMIT) break;
      __nanosleep(100);
    }
    const uint32_t kd = sb + OFF_KV + warp * 384 + lane * 4;
#pragma unroll
    for (int i = 0; i < 3; i++)
      if (i < 2 || wg == 0) {
        sts32(kd + i * 3072, pack_bf16(__uint_as_float(v[2 * i].x), __uint_as_float(v[2 * i].y)));
        sts32(kd + i * 3072 + 128, pack_bf16(__uint_as_float(v[2 * i].z), __uint_as_float(v[2 * i + 1].x)));
        sts32(kd + i * 3072 + 256, pack_bf16(__uint_as_float(v[2 * i + 1].y), __uint_as_float(v[2 * i + 1].z)));
      }
  }
  fence_proxy_async();
  bar_sync(1, 256);
  TL2((tl >= 12 ? 128 : 0) + 32 + 3);
  {
    float d[4][12];
    uint32_t zero = 0; PIN(zero);
#pragma unroll
    for (int hh = 0; hh < 4; hh++)
#pragma unroll
      for (int i = 0; i < 5; i++) { PIN(qf[hh][0][i]); PIN(qf[hh][1][i]); }
    wgmma_fence();
#pragma unroll
    for (int hh = 0; hh < 4; hh++) {
      const uint32_t kb = OFF_KV + hh * 1920;
      wgmma_rs_n24<1>(d[hh], qf[hh][0][0], qf[hh][1][0], qf[hh][0][1], qf[hh][1][1], desc16<384, 128, 0>(s16, kb), 0);
      wgmma_rs_n24<1>(d[hh], qf[hh][0][2], qf[hh][1][2], qf[hh][0][3], qf[hh][1][3], desc16<384, 128, 0>(s16, kb + 768), 1);
      wgmma_rs_n24<1>(d[hh], qf[hh][0][4], qf[hh][1][4], zero, zero, desc16<0, 128, 0>(s16, kb + 1536), 1);
    }
    wgmma_commit();
    wgmma_wait<0>();
    uint32_t ow[4][6];
#pragma unroll
    for (int hh = 0; hh < 4; hh++) {
      const int zl = (lane & ~3) | ((hh & 1) ? 0 : 2);
      const float da = bf16r(bf16r(__shfl_sync(0xffffffffu, d[hh][8], zl)) + 1e-6f), db = bf16r(bf16r(__shfl_sync(0xffffffffu, d[hh][10], zl)) + 1e-6f);
#pragma unroll
      for (int n = 0; n < 3; n++) {
        bf16r2(d[hh][4 * n], d[hh][4 * n + 1]); bf16r2(d[hh][4 * n + 2], d[hh][4 * n + 3]);
        ow[hh][2 * n] = pack_bf16(__fdividef(d[hh][4 * n], da), __fdividef(d[hh][4 * n + 1], da));
        ow[hh][2 * n + 1] = pack_bf16(__fdividef(d[hh][4 * n + 2], db), __fdividef(d[hh][4 * n + 3], db));
      }
    }
#pragma unroll
    for (int p = 0; p < 2; p++) {
      const uint32_t oa = sb + OFF_OST + p * 10240 + srow;
      stsm_x4(oa, ow[2 * p][0], ow[2 * p][1], ow[2 * p][2], ow[2 * p][3]);
      stsm_x2(oa + 4096, q4 < 2 ? ow[2 * p][4] : ow[2 * p + 1][4], q4 < 2 ? ow[2 * p][5] : ow[2 * p + 1][5]);
      stsm_x4(oa + 6144, ow[2 * p + 1][0], ow[2 * p + 1][1], ow[2 * p + 1][2], ow[2 * p + 1][3]);
    }
    fence_proxy_async();
    __syncwarp();
    mbar_arrive_if(lane == 0, staged);
  }
  TL2((tl >= 12 ? 128 : 0) + 32 + 4);
  float c2[40];
  mbar_wait(barW, 0);
#pragma unroll 1
  for (int i = 0; i < 8; i++) {
    mbar_wait(full2 + 8 * i, 0);
    const uint32_t st = s16 + (i < 6 ? i : i - 6) * (PIECE / 16) + wg * 64, wo = s16 + i * 800;
    wgmma_fence();
#pragma unroll
    for (int kk = 0; kk < 5; kk++) wgmma_n80<0, 1>(c2, desc16<2048, 128, 0>(st, kk * 4096), desc16<1280, 128, 0>(wo, OFF_WOT + kk * 2560), (i | kk) != 0);
    wgmma_commit();
    if (i == 1 || i == 2) { wgmma_wait<1>(); mbar_arrive_if(lead, empty2 + 8 * (i - 1)); }
  }
  wgmma_wait<0>();
  TL2((tl >= 12 ? 128 : 0) + 32 + 5);
  {
    bar_sync(1, 256);
    const uint32_t ost = sb + 2 * PIECE + warp * 3072;
#pragma unroll
    for (int v = 0; v < 10; v += 2)
      stsm_x4(ost + (lane & 15) * 176 + (v + (lane >> 4)) * 16, pack_bf16(c2[4 * v], c2[4 * v + 1]), pack_bf16(c2[4 * v + 2], c2[4 * v + 3]),
              pack_bf16(c2[4 * v + 4], c2[4 * v + 5]), pack_bf16(c2[4 * v + 6], c2[4 * v + 7]));
    __syncwarp();
#pragma unroll
    for (int i = 0; i < 5; i++) {
      const int c = lane + 32 * i, row = c / 10, chunk = c % 10;
      const uint4 y = lds128(ost + row * 176 + chunk * 16);
      const size_t off = (size_t)(m2 * 128 + wg * 64 + wi * 16 + row) * cfg::DM + ns * 80 + chunk * 8;
      const uint4 x = xr[i];
      *(uint4*)(a.xout + off) = make_uint4(pack_bf16(bf_lo(x.x) + bf_lo(y.x), bf_hi(x.x) + bf_hi(y.x)), pack_bf16(bf_lo(x.y) + bf_lo(y.y), bf_hi(x.y) + bf_hi(y.y)),
                                           pack_bf16(bf_lo(x.z) + bf_lo(y.z), bf_hi(x.z) + bf_hi(y.z)), pack_bf16(bf_lo(x.w) + bf_lo(y.w), bf_hi(x.w) + bf_hi(y.w)));
    }
  }
  TL_END(tl);
}
__device__ __align__(32768) unsigned char g_arena[AR_SIZE];
__device__ unsigned g_go[32];
__device__ __align__(1024) uint2 g_xh[2048 * 160];
__device__ __align__(1024) unsigned char g_k[64 * 96 * 5120], g_v[64 * 96 * 5120];
__device__ __align__(1024) bf16 g_o[2048 * 6144];
__device__ __align__(1024) uint4 g_qs[8 * 32 * 12 * 256];
__device__ __align__(1024) bf16 g_xn[2048 * 640], g_xn2[2048 * 640], g_xa[2048 * 640], g_xb[2048 * 640];
__device__ __align__(1024) bf16 g_part[24 * 2048 * 640];
__device__ __align__(1024) bf16 g_wb[2048 * 640], g_wot[640 * 640], g_pq[2048 * 640];
__device__ __align__(1024) float g_kvacc[bf::KVACC / 4 + 64];

typedef CUresult (*EncodeFn)(CUtensorMap*, CUtensorMapDataType, cuuint32_t, void*, const cuuint64_t*, const cuuint64_t*, const cuuint32_t*,
                             const cuuint32_t*, CUtensorMapInterleave, CUtensorMapSwizzle, CUtensorMapL2promotion, CUtensorMapFloatOOBfill);
static EncodeFn g_encode = nullptr;
static CUtensorMap make_map(const void* p, uint64_t cols, uint64_t rows, uint32_t bc, uint32_t br, bool swz = true) {
  CUtensorMap m;
  cuuint64_t dims[2] = {cols, rows}, strides[1] = {cols * 2};
  cuuint32_t box[2] = {bc, br}, es[2] = {1, 1};
  g_encode(&m, CU_TENSOR_MAP_DATA_TYPE_BFLOAT16, 2, const_cast<void*>(p), dims, strides, box, es, CU_TENSOR_MAP_INTERLEAVE_NONE,
           swz ? CU_TENSOR_MAP_SWIZZLE_128B : CU_TENSOR_MAP_SWIZZLE_NONE, CU_TENSOR_MAP_L2_PROMOTION_L2_256B, CU_TENSOR_MAP_FLOAT_OOB_FILL_NONE);
  return m;
}
static CUtensorMap make_map3(const void* p, uint64_t cols, uint64_t rows, uint32_t nb) {
  CUtensorMap m;
  cuuint64_t dims[3] = {64, rows, cols / 64}, strides[2] = {cols * 2, 128};
  cuuint32_t box[3] = {64, 64, nb}, es[3] = {1, 1, 1};
  g_encode(&m, CU_TENSOR_MAP_DATA_TYPE_BFLOAT16, 3, const_cast<void*>(p), dims, strides, box, es, CU_TENSOR_MAP_INTERLEAVE_NONE,
           CU_TENSOR_MAP_SWIZZLE_128B, CU_TENSOR_MAP_L2_PROMOTION_L2_256B, CU_TENSOR_MAP_FLOAT_OOB_FILL_NONE);
  return m;
}
template <class T> static T* sym(const T& s) { void* p = nullptr; cudaGetSymbolAddress(&p, s); return (T*)p; }

struct Ptrs {
  unsigned char *arena, *k, *v; bf16 *o, *xn, *xa, *xb, *wb, *wot, *pq; float *part, *kvacc; uint2* xh; uint4* qs; bf16* xn2; unsigned* go;
};

static tr::Sched make_sched(int layer, const char* str, const int* ks, const int* lr) {
  using namespace tr;
  Sched s = {};
  int n = 0;
  s.nqa = 16;
  for (int b = 0; b < 16; b++) { s.ks[b] = (uint8_t)abs(ks[b]); s.wide[b] = ks[b] > 0; s.lrows[b] = (uint8_t)lr[b]; }
  for (const char* p = str; *p;) {
    if (*p == ' ') { p++; continue; }
    const bool late = *p < 'a';
    const char c = *p++ | 32;
    char* e;
    const int b = (int)strtol(p, &e, 10); p = e;
    int first = 0, cnt = c == 'o' ? s.ks[b] * (s.wide[b] ? 2 : 5) : (c == 'l' ? 16 / lr[b] : 32);
    if (*p == '.') { first = (int)strtol(p + 1, &e, 10); cnt = (int)strtol(e + 1, &e, 10); p = e; }
    const int type = c == 'a' ? T_QA : (c == 'q' ? T_Q : (c == 't' ? T_A : (c == 'l' ? T_L : (c == 'p' ? T_P : (s.wide[b] ? T_OB : T_OS)))));
    if (type == T_P && layer > 0) continue;
    if (type == T_A && b < s.nqa) s.nqa = b;
    for (int i = 0; i < cnt && n < MAXITEMS - 1; i++) s.item[n++] = (uint16_t)((late << 14) | (type << 11) | (b << 7) | (first + i));
  }
  s.n = n; s.item[n] = T_END << 11;
  return s;
}
static tr::Sched sched_of(int layer) {
  const char* str = layer == 0
      ? "q13 q14 q12.0.8 a0.0.8 q12.8.24 q15 a0.8.24 a1 p0.0.16 a2 p0.16.16 o0 o1 a3.0.16 o2 a3.16.16 a4.0.16 o3 a4.16.16 a5.0.24 o4 a5.24.8 a6.0.20 l0 a6.20.12 o5 "
        "a7 o6 l2 a8.0.24 o7 l1 a8.24.8 a9 o8 l3 a10 l4 O9 a11 t12 l5 l7 l6 O10 O11 O12 t13 t14 T15.0.20 O13 T15.20.12 l8 o14 L9 O15 L10 L12 l11 l15 l13 l14"
      : "q12 q14.0.8 q13 q15.0.16 q11.0.24 a0 q11.24.8 q14.8.24 o0 a1 a2 q15.16.16 o1 o2 a3 a4 o3 o4 a5 a6 o5 l1 a7 o6 l2 l0 a8.0.24 o7 a8.24.8 a9 o8 a10 "
        "O9 t11 l4 l3 O10 l5 o11 t12 l6 l7 O12 t13 t14 T15 o13 L9 o14 o15 L13 l10 L8 l12 l15 l11 l14";
  const int ks0[2][16] = {{2, 2, 2, 2, 2, 2, 2, 3, 2, 2, 3, 3, 3, -4, -8, -8}, {2, 2, 3, 2, 2, 2, 2, 2, 3, 3, 2, 4, 6, -6, -6, -12}};
  const int lr0[2][16] = {{4, 4, 4, 4, 4, 4, 4, 4, 2, 4, 1, 1, 1, 1, 1, 1}, {4, 4, 4, 4, 4, 4, 1, 2, 1, 4, 2, 1, 1, 1, 1, 1}};
  int ks[16], lr[16];
  for (int b = 0; b < 16; b++) { ks[b] = ks0[layer][b]; lr[b] = lr0[layer][b]; }
#ifdef TUNE
  const bool mine = !getenv("ONLY") || atoi(getenv("ONLY")) == layer;
  if (mine && getenv("SCHED")) str = getenv("SCHED");
  if (const char* p = getenv(layer ? "S1" : "S0")) {
    char* e;
    for (int b = 0; b < 16; b++) { ks[b] = (int)strtol(p, &e, 10); p = e; }
    for (int b = 0; b < 16; b++) { lr[b] = (int)strtol(p, &e, 10); p = e; }
    str = p;
  }
  if (const char* p = mine ? getenv("KS") : nullptr) for (int b = 0; b < 16; b++) { char* e; ks[b] = (int)strtol(p, &e, 10); p = e; }
  if (const char* p = mine ? getenv("LR") : nullptr) for (int b = 0; b < 16; b++) { char* e; lr[b] = (int)strtol(p, &e, 10); p = e; }
#endif
  return make_sched(layer, str, ks, lr);
}
#ifndef TRAIL_GRID
#define TRAIL_GRID 132
#endif
#ifndef PDL_LN
#define PDL_LN 0
#endif
#ifndef PDL_CH
#define PDL_CH 1
#endif
#ifndef PDL_B
#define PDL_B 1
#endif
#ifndef PF_A
#define PF_A 1
#endif
#ifndef PF_B
#define PF_B 1
#endif
extern "C" void kernel_launch(void* const* d_in, const int* in_sizes, int n_in, void* d_out, int out_size) {
  const bf16* x = (const bf16*)d_in[0];
  const bf16* mem0 = (const bf16*)d_in[1];
  const bf16 *Wq = (const bf16*)d_in[2], *Wk = (const bf16*)d_in[3], *Wv = (const bf16*)d_in[4], *Wo = (const bf16*)d_in[5];
  const bf16 *wqkv = (const bf16*)d_in[8], *wphi = (const bf16*)d_in[9], *wo = (const bf16*)d_in[10];
  bf16* out = (bf16*)d_out;
  static Ptrs P; static bool init = false;
  if (!init) {
    void* fn = nullptr; cudaDriverEntryPointQueryResult qr;
    cudaGetDriverEntryPoint("cuTensorMapEncodeTiled", &fn, cudaEnableDefault, &qr);
    g_encode = (EncodeFn)fn;
    void* p;
    cudaGetSymbolAddress(&p, g_arena); P.arena = (unsigned char*)p;
    cudaGetSymbolAddress(&p, g_k); P.k = (unsigned char*)p;   cudaGetSymbolAddress(&p, g_v); P.v = (unsigned char*)p;
    cudaGetSymbolAddress(&p, g_o); P.o = (bf16*)p;
    cudaGetSymbolAddress(&p, g_xn); P.xn = (bf16*)p;
    cudaGetSymbolAddress(&p, g_xa); P.xa = (bf16*)p;   cudaGetSymbolAddress(&p, g_xb); P.xb = (bf16*)p;
    cudaGetSymbolAddress(&p, g_wb); P.wb = (bf16*)p;   cudaGetSymbolAddress(&p, g_wot); P.wot = (bf16*)p;
    cudaGetSymbolAddress(&p, g_pq); P.pq = (bf16*)p;   cudaGetSymbolAddress(&p, g_part); P.part = (float*)p;
    cudaGetSymbolAddress(&p, g_kvacc); P.kvacc = (float*)p;
    cudaGetSymbolAddress(&p, g_xh); P.xh = (uint2*)p;
    cudaGetSymbolAddress(&p, g_go); P.go = (unsigned*)p;
    cudaGetSymbolAddress(&p, g_qs); P.qs = (uint4*)p;
    cudaGetSymbolAddress(&p, g_xn2); P.xn2 = (bf16*)p;
    cudaFuncSetAttribute(chain_kernel, cudaFuncAttributeMaxDynamicSharedMemorySize, ch::SMEM);
    cudaFuncSetAttribute(trail_kernel, cudaFuncAttributeMaxDynamicSharedMemorySize, tr::SMEM);
    cudaFuncSetAttribute(blayer_kernel, cudaFuncAttributeMaxDynamicSharedMemorySize, bf::SMEM);
    init = true;
  }
  const CUtensorMap tmXn = make_map(P.xn, 640, 2048, 64, 128), tmXn2 = make_map(P.xn2, 640, 2048, 64, 128);
  const CUtensorMap tmWq = make_map3(Wq, 6144, 640, 3);
  const CUtensorMap tmCq = make_map(Wq, 6144, 640, 64, 160), tmCk = make_map(Wk, 6144, 640, 64, 160), tmCv = make_map(Wv, 6144, 640, 64, 160), tmCo = make_map(Wo, 640, 6144, 224, 64, false);
  const CUtensorMap tmWo5 = make_map3(Wo, 640, 6144, 5), tmWo2 = make_map3(Wo, 640, 6144, 2);

  CUtensorMap tmP, tmP4;
  for (int i = 0; i < 2; i++) {
    cuuint64_t dims[4] = {256, 8, 320, 24}, strides[3] = {1024, 8192, 320 * 8192};
    cuuint32_t box[4] = {256, 1, 10, i ? 4u : 1u}, es[4] = {1, 1, 1, 1};
    g_encode(i ? &tmP4 : &tmP, CU_TENSOR_MAP_DATA_TYPE_UINT32, 4, P.part, dims, strides, box, es, CU_TENSOR_MAP_INTERLEAVE_NONE, CU_TENSOR_MAP_SWIZZLE_NONE,
             CU_TENSOR_MAP_L2_PROMOTION_NONE, CU_TENSOR_MAP_FLOAT_OOB_FILL_NONE);
  }
  ChainArgs ca;
  ca.xh = P.xh; ca.mem0 = mem0; ca.kg = P.k; ca.vg = P.v;
  ca.arena = P.arena; ca.dbg = nullptr; ca.go = P.go; ca.delay = POLL_DELAY; ca.margin = 150; ca.pubrel = 1;
#ifdef TUNE
  if (getenv("PR")) ca.pubrel = atoi(getenv("PR"));
  if (getenv("MG")) ca.margin = atoi(getenv("MG"));
  if (getenv("PD")) ca.delay = atoi(getenv("PD"));
#endif
  ca.tl = 0;
  uint4* zar = (uint4*)P.arena; const int nzar = AR_SIZE / 16;
  uint4* zkv = (uint4*)P.kvacc; const int nzkv = (bf::KVACC / 4 + 64) / 4;

  const PrepArgs pa{wqkv, wphi, wo, (unsigned char*)P.wb, (unsigned char*)P.wot};
  const bf16* xcur = x;
  cudaLaunchAttribute at[1];
  at[0].id = cudaLaunchAttributeProgrammaticStreamSerialization; at[0].val.programmaticStreamSerializationAllowed = 1;
  auto cfgof = [&](int grid, int block, int smem, bool pdl) {
    cudaLaunchConfig_t lc = {};
    lc.gridDim = dim3(grid); lc.blockDim = dim3(block); lc.dynamicSmemBytes = smem; lc.stream = cudaStreamPerThread;
    lc.attrs = at; lc.numAttrs = pdl ? 1 : 0;
    return lc;
  };
  int nlayers = 2;
#ifdef TUNE
  if (getenv("LAYERS")) nlayers = atoi(getenv("LAYERS"));
#endif
  for (int layer = 0; layer < nlayers; layer++) {
    const int tl = layer * 12;
    cudaLaunchConfig_t lc = cfgof(256, 256, 0, layer > 0 && PDL_LN);
    cudaLaunchKernelEx(&lc, ln_kernel, xcur, P.xn, P.xh, zar, nzar, zkv, nzkv, Wk, Wv, layer == 0 ? PF_A : 0, tl + 0);
    ca.tl = tl + 2; ca.dry = 1;
#ifdef TUNE
    if (getenv("DRY")) ca.dry = (atoi(getenv("DRY")) >> layer) & 1;
#endif
    lc = cfgof(96, 384, ch::SMEM, PDL_CH);
    cudaLaunchKernelEx(&lc, chain_kernel, ca, tmCq, tmCk, tmCv, tmCo);
    lc = cfgof(TRAIL_GRID, 384, tr::SMEM, true);
    tr::Args ta{P.k, P.v, (unsigned char*)P.o, P.qs, (unsigned char*)P.part, xcur, P.xn, P.xa, P.xn2, P.arena, P.go, tl + 4, 30, 20, layer == 0 ? 0 : 99, 1, 13};
#ifdef TUNE
    if (getenv("NAP")) ta.nap = atoi(getenv("NAP"));
    if (getenv("PFBB")) ta.pfb = atoi(getenv("PFBB"));
    if (getenv("PFP") && layer == 0) ta.pfprep = atoi(getenv("PFP"));
    if (getenv("PFQ")) ta.pfq = atoi(getenv("PFQ"));
    if (getenv("NAP2")) ta.nap2 = atoi(getenv("NAP2"));
#endif
    cudaLaunchKernelEx(&lc, trail_kernel, tmXn, tmWq, tmWo5, tmWo2, tmP, tmP4, sched_of(layer), ta, pa);
    lc = cfgof(128, 384, bf::SMEM, PDL_B);
    bf::Args ba{(const unsigned char*)P.wb, (const unsigned char*)P.wot, (unsigned char*)P.kvacc, (unsigned char*)P.pq, P.xa, layer == 0 ? P.xb : out, P.go, layer == 0 ? P.arena + tr::C_P : nullptr,
                      layer == 0 && PF_B ? Wk : nullptr, Wv, 30, 500, 0, tl + 7};
#ifdef TUNE
    if (getenv("PFN")) ba.pfn = atoi(getenv("PFN"));
    if (getenv("PFNS")) ba.pfns = atoi(getenv("PFNS"));
    if (getenv("PFWT")) ba.pfwait = atoi(getenv("PFWT"));
    if (getenv("PFB")) ba.pf0 = layer == 0 && atoi(getenv("PFB")) ? Wk : nullptr;
#endif
    cudaLaunchKernelEx(&lc, blayer_kernel, tmXn2, ba);
    xcur = P.xb;
  }
}
```

```cpp
#include <cuda_runtime.h>
#include <cuda.h>
#include <cuda_bf16.h>
#include <stdint.h>
#include <stdlib.h>
#include <type_traits>

typedef __nv_bfloat16 bf16;

namespace cfg {
constexpr int S = 2048, DM = 640, H = 32, DH = 192, NSEG = 64, SEG = 32, NM = 8;
constexpr int HD = H * DH;
}

__device__ __forceinline__ uint32_t smem_u32(const void* p) { return (uint32_t)__cvta_generic_to_shared(p); }
__device__ __forceinline__ uint32_t mapa_u32(uint32_t a, uint32_t r) {
  uint32_t o; asm("mapa.shared::cluster.u32 %0, %1, %2;" : "=r"(o) : "r"(a), "r"(r)); return o;
}
__device__ __forceinline__ void mbar_init(uint32_t b, uint32_t c) {
  asm volatile("mbarrier.init.shared::cta.b64 [%0], %1;" :: "r"(b), "r"(c) : "memory");
}
__device__ __forceinline__ void mbar_expect_tx(uint32_t b, uint32_t bytes) {
  asm volatile("mbarrier.arrive.expect_tx.shared::cta.b64 _, [%0], %1;" :: "r"(b), "r"(bytes) : "memory");
}
__device__ __forceinline__ void mbar_arrive(uint32_t b) {
  asm volatile("mbarrier.arrive.shared::cta.b64 _, [%0];" :: "r"(b) : "memory");
}
__device__ __forceinline__ void mbar_expect_tx_if(bool c, uint32_t b, uint32_t bytes) {
  asm volatile("{\n.reg .pred p;\nsetp.ne.u32 p, %2, 0;\n@p mbarrier.arrive.expect_tx.shared::cta.b64 _, [%0], %1;\n}" :: "r"(b), "r"(bytes), "r"((uint32_t)c) : "memory");
}
__device__ __forceinline__ void mbar_arrive_if(bool c, uint32_t b) {
  asm volatile("{\n.reg .pred p;\nsetp.ne.u32 p, %1, 0;\n@p mbarrier.arrive.shared::cta.b64 _, [%0];\n}" :: "r"(b), "r"((uint32_t)c) : "memory");
}
#define SPIN_LIMIT (1 << 20)
__device__ __forceinline__ void mbar_wait(uint32_t b, uint32_t ph) {
  asm volatile("{\n.reg .pred p, q;\n.reg .u32 c;\nmov.u32 c, 0;\n"
               "W_%=:\nmbarrier.try_wait.parity.shared::cta.b64 p, [%0], %1;\n@p bra.uni D_%=;\n"
               "add.u32 c, c, 1;\nsetp.lt.u32 q, c, %2;\n@q bra.uni W_%=;\nD_%=:\n}"
               :: "r"(b), "r"(ph), "n"(SPIN_LIMIT) : "memory");
}
__device__ __forceinline__ void mbar_wait_if(bool cnd, uint32_t b, uint32_t ph) {
  asm volatile("{\n.reg .pred p, q;\n.reg .u32 c;\nsetp.eq.u32 q, %3, 0;\n@q bra.uni D_%=;\nmov.u32 c, 0;\n"
               "W_%=:\nmbarrier.try_wait.parity.shared::cta.b64 p, [%0], %1;\n@p bra.uni D_%=;\n"
               "add.u32 c, c, 1;\nsetp.lt.u32 q, c, %2;\n@q bra.uni W_%=;\nD_%=:\n}"
               :: "r"(b), "r"(ph), "n"(SPIN_LIMIT), "r"((uint32_t)cnd) : "memory");
}
__device__ __forceinline__ void mbar_spin(uint32_t b, uint32_t ph) {
  asm volatile("{\n.reg .pred p, q;\n.reg .u32 c;\nmov.u32 c, 0;\n"
               "W_%=:\nmbarrier.test_wait.parity.shared::cta.b64 p, [%0], %1;\n@p bra D_%=;\n"
               "add.u32 c, c, 1;\nsetp.lt.u32 q, c, %2;\n@q bra W_%=;\nD_%=:\n}"
               :: "r"(b), "r"(ph), "n"(SPIN_LIMIT) : "memory");
}
#define PIN(x) asm volatile("" : "+r"(x))
__device__ __forceinline__ void bulk_g2s(uint32_t dst, const void* src, uint32_t bytes, uint32_t mb) {
  asm volatile("cp.async.bulk.shared::cluster.global.mbarrier::complete_tx::bytes [%0], [%1], %2, [%3];"
               :: "r"(dst), "l"(src), "r"(bytes), "r"(mb) : "memory");
}
__device__ __forceinline__ void fence_proxy_async() { asm volatile("fence.proxy.async.shared::cta;" ::: "memory"); }
__device__ __forceinline__ void bar_sync(int id, int n) { asm volatile("bar.sync %0, %1;" :: "r"(id), "r"(n) : "memory"); }
__device__ __forceinline__ void bar_arrive(int id, int n) { asm volatile("bar.arrive %0, %1;" :: "r"(id), "r"(n) : "memory"); }
template <int IMM> __device__ __forceinline__ void ldsm_x4_i(uint32_t (&r)[4], uint32_t a) {
  asm volatile("ldmatrix.sync.aligned.m8n8.x4.shared.b16 {%0,%1,%2,%3}, [%4+%5];"
               : "=r"(r[0]), "=r"(r[1]), "=r"(r[2]), "=r"(r[3]) : "r"(a), "n"(IMM) : "memory");
}
template <int IMM> __device__ __forceinline__ void ldsm_x4_t_i(uint32_t (&r)[4], uint32_t a) {
  asm volatile("ldmatrix.sync.aligned.m8n8.x4.trans.shared.b16 {%0,%1,%2,%3}, [%4+%5];"
               : "=r"(r[0]), "=r"(r[1]), "=r"(r[2]), "=r"(r[3]) : "r"(a), "n"(IMM) : "memory");
}
template <int IMM> __device__ __forceinline__ uint4 lds128_i(uint32_t a) {
  uint4 v; asm volatile("ld.shared.v4.u32 {%0,%1,%2,%3}, [%4+%5];" : "=r"(v.x), "=r"(v.y), "=r"(v.z), "=r"(v.w) : "r"(a), "n"(IMM) : "memory"); return v;
}
template <int IMM> __device__ __forceinline__ uint2 lds64_i(uint32_t a) {
  uint2 v; asm volatile("ld.shared.v2.u32 {%0,%1}, [%2+%3];" : "=r"(v.x), "=r"(v.y) : "r"(a), "n"(IMM) : "memory"); return v;
}
template <int IMM> __device__ __forceinline__ void sts128_i(uint32_t a, uint32_t x, uint32_t y, uint32_t z, uint32_t w) {
  asm volatile("st.shared.v4.u32 [%0+%5], {%1,%2,%3,%4};" :: "r"(a), "r"(x), "r"(y), "r"(z), "r"(w), "n"(IMM) : "memory");
}
template <int IMM> __device__ __forceinline__ void sts64_i(uint32_t a, uint32_t x, uint32_t y) {
  asm volatile("st.shared.v2.u32 [%0+%3], {%1,%2};" :: "r"(a), "r"(x), "r"(y), "n"(IMM) : "memory");
}
template <int IMM> __device__ __forceinline__ void st_async_v2_i(uint32_t a, uint32_t x, uint32_t y, uint32_t mb) {
  asm volatile("st.async.weak.shared::cluster.mbarrier::complete_tx::bytes.v2.b32 [%0+%4], {%1,%2}, [%3];"
               :: "r"(a), "r"(x), "r"(y), "r"(mb), "n"(IMM) : "memory");
}
template <int IMM> __device__ __forceinline__ uint4 ld_relaxed_v4_i(const void* p) {
  uint4 v; asm volatile("ld.relaxed.gpu.global.v4.u32 {%0,%1,%2,%3}, [%4+%5];" : "=r"(v.x), "=r"(v.y), "=r"(v.z), "=r"(v.w) : "l"(p), "n"(IMM) : "memory"); return v;
}
template <int I, int N, class F> __device__ __forceinline__ void static_for(F&& f) {
  if constexpr (I < N) { f(std::integral_constant<int, I>{}); static_for<I + 1, N>(f); }
}
__device__ __forceinline__ uint32_t movm_t(uint32_t a) {
  uint32_t d; asm volatile("movmatrix.sync.aligned.m8n8.trans.b16 %0, %1;" : "=r"(d) : "r"(a)); return d;
}
__device__ __forceinline__ void mma16816(float (&d)[4], uint32_t a0, uint32_t a1, uint32_t a2, uint32_t a3, uint32_t b0, uint32_t b1) {
  asm volatile("mma.sync.aligned.m16n8k16.row.col.f32.bf16.bf16.f32 {%0,%1,%2,%3}, {%4,%5,%6,%7}, {%8,%9}, {%0,%1,%2,%3};"
               : "+f"(d[0]), "+f"(d[1]), "+f"(d[2]), "+f"(d[3]) : "r"(a0), "r"(a1), "r"(a2), "r"(a3), "r"(b0), "r"(b1));
}
__device__ __forceinline__ uint32_t pack_bf16(float lo, float hi) {
  uint32_t d; asm("cvt.rn.bf16x2.f32 %0, %1, %2;" : "=r"(d) : "f"(hi), "f"(lo)); return d;
}
__device__ __forceinline__ float bf_lo(uint32_t w) { return __uint_as_float(w << 16); }
__device__ __forceinline__ float bf_hi(uint32_t w) { return __uint_as_float(w & 0xffff0000u); }
__device__ __forceinline__ uint4 lds128(uint32_t a) {
  uint4 v; asm volatile("ld.shared.v4.u32 {%0,%1,%2,%3}, [%4];" : "=r"(v.x), "=r"(v.y), "=r"(v.z), "=r"(v.w) : "r"(a) : "memory"); return v;
}
__device__ __forceinline__ void sts128(uint32_t a, uint32_t x, uint32_t y, uint32_t z, uint32_t w) {
  asm volatile("st.shared.v4.u32 [%0], {%1,%2,%3,%4};" :: "r"(a), "r"(x), "r"(y), "r"(z), "r"(w) : "memory");
}
__device__ __forceinline__ void sts64(uint32_t a, uint32_t x, uint32_t y) {
  asm volatile("st.shared.v2.u32 [%0], {%1,%2};" :: "r"(a), "r"(x), "r"(y) : "memory");
}
__device__ __forceinline__ uint4 ld_relaxed_v4(const void* p) {
  uint4 v; asm volatile("ld.relaxed.gpu.global.v4.u32 {%0,%1,%2,%3}, [%4];" : "=r"(v.x), "=r"(v.y), "=r"(v.z), "=r"(v.w) : "l"(p) : "memory"); return v;
}
__device__ __forceinline__ uint32_t ld_relaxed_u32(const void* p) {
  uint32_t v; asm volatile("ld.relaxed.gpu.global.u32 %0, [%1];" : "=r"(v) : "l"(p) : "memory"); return v;
}
__device__ __forceinline__ void st_relaxed_u32(void* p, uint32_t v) {
  asm volatile("st.relaxed.gpu.global.u32 [%0], %1;" :: "l"(p), "r"(v) : "memory");
}
__device__ __forceinline__ void st_release_u32(void* p, uint32_t v) {
  asm volatile("st.release.gpu.global.u32 [%0], %1;" :: "l"(p), "r"(v) : "memory");
}
__device__ __forceinline__ void red_release_inc(void* p) { asm volatile("red.release.gpu.global.add.u32 [%0], 1;" :: "l"(p) : "memory"); }
__device__ __forceinline__ void wgmma_fence() { asm volatile("wgmma.fence.sync.aligned;" ::: "memory"); }
__device__ __forceinline__ void wgmma_commit() { asm volatile("wgmma.commit_group.sync.aligned;" ::: "memory"); }
template <int N> __device__ __forceinline__ void wgmma_wait() { asm volatile("wgmma.wait_group.sync.aligned %0;" :: "n"(N) : "memory"); }
__device__ __forceinline__ uint64_t make_desc(uint32_t saddr, uint32_t lbo_bytes, uint32_t sbo_bytes, uint32_t swz) {
  return (uint64_t)((saddr & 0x3FFFF) >> 4) | ((uint64_t)(lbo_bytes >> 4) << 16) | ((uint64_t)(sbo_bytes >> 4) << 32) | ((uint64_t)swz << 62);
}

template <uint32_t LBO, uint32_t SBO, uint32_t SWZ> __device__ __forceinline__ uint64_t desc16(uint32_t a16, uint32_t off = 0) {
  return (uint64_t)(a16 + ((off >> 4) + ((LBO >> 4) << 16))) | ((uint64_t)((SBO >> 4) | (SWZ << 30)) << 32);
}

__device__ __forceinline__ bool elect_one() {
  uint32_t p; asm volatile("{\n.reg .pred p;\nelect.sync _|p, 0xffffffff;\nselp.u32 %0, 1, 0, p;\n}" : "=r"(p)); return p;
}
__device__ __forceinline__ void tma_load_4d(uint32_t dst, const CUtensorMap* tm, int c0, int c1, int c2, int c3, uint32_t mb) {
  asm volatile("cp.async.bulk.tensor.4d.shared::cluster.global.mbarrier::complete_tx::bytes [%0], [%1, {%3, %4, %5, %6}], [%2];"
               :: "r"(dst), "l"(tm), "r"(mb), "r"(c0), "r"(c1), "r"(c2), "r"(c3) : "memory");
}
__device__ __forceinline__ void tma_load_3d(uint32_t dst, const CUtensorMap* tm, int c0, int c1, int c2, uint32_t mb) {
  asm volatile("cp.async.bulk.tensor.3d.shared::cluster.global.mbarrier::complete_tx::bytes [%0], [%1, {%3, %4, %5}], [%2];"
               :: "r"(dst), "l"(tm), "r"(mb), "r"(c0), "r"(c1), "r"(c2) : "memory");
}
__device__ __forceinline__ void tma_load_2d(uint32_t dst, const CUtensorMap* tm, int c0, int c1, uint32_t mb) {
  asm volatile("cp.async.bulk.tensor.2d.shared::cluster.global.mbarrier::complete_tx::bytes [%0], [%1, {%3, %4}], [%2];"
               :: "r"(dst), "l"(tm), "r"(mb), "r"(c0), "r"(c1) : "memory");
}
__device__ __forceinline__ void bulk_s2g(void* dst, uint32_t src, uint32_t bytes) {
  asm volatile("cp.async.bulk.global.shared::cta.bulk_group [%0], [%1], %2;" :: "l"(dst), "r"(src), "r"(bytes) : "memory");
}
__device__ __forceinline__ uint64_t policy_evict_first() {
  uint64_t p; asm volatile("createpolicy.fractional.L2::evict_first.b64 %0, 1.0;" : "=l"(p)); return p;
}
__device__ __forceinline__ void bulk_commit() { asm volatile("cp.async.bulk.commit_group;" ::: "memory"); }
template <int N> __device__ __forceinline__ void bulk_wait() { asm volatile("cp.async.bulk.wait_group %0;" :: "n"(N) : "memory"); }
__device__ __forceinline__ void stsm_x4(uint32_t a, uint32_t r0, uint32_t r1, uint32_t r2, uint32_t r3) {
  asm volatile("stmatrix.sync.aligned.m8n8.x4.shared.b16 [%0], {%1,%2,%3,%4};" :: "r"(a), "r"(r0), "r"(r1), "r"(r2), "r"(r3) : "memory");
}
__device__ __forceinline__ void stsm_x2(uint32_t a, uint32_t r0, uint32_t r1) {
  asm volatile("stmatrix.sync.aligned.m8n8.x2.shared.b16 [%0], {%1,%2};" :: "r"(a), "r"(r0), "r"(r1) : "memory");
}
__device__ __forceinline__ float bf16r(float x) { return __uint_as_float(pack_bf16(0.f, x) & 0xffff0000u); }
__device__ __forceinline__ void bf16r2(float& a, float& b) { const uint32_t w = pack_bf16(a, b); a = bf_lo(w); b = bf_hi(w); }
__device__ __forceinline__ float rcpf(float x) { float r; asm("rcp.approx.ftz.f32 %0, %1;" : "=f"(r) : "f"(x)); return r; }
__device__ __forceinline__ float ex2f(float x) { float e; asm("ex2.approx.ftz.f32 %0, %1;" : "=f"(e) : "f"(x)); return e; }
__device__ __forceinline__ void prefetch_tmap(const CUtensorMap* tm) { asm volatile("prefetch.tensormap [%0];" :: "l"(tm) : "memory"); }

template <int TA, int TB> __device__ __forceinline__ void wgmma_n24(float (&d)[12], uint64_t da, uint64_t db, int acc) {
  asm volatile("{\n.reg .pred p;\nsetp.ne.b32 p, %14, 0;\n"
    "wgmma.mma_async.sync.aligned.m64n24k16.f32.bf16.bf16 {%0, %1, %2, %3, %4, %5, %6, %7, %8, %9, %10, %11}, %12, %13, p, 1, 1, %15, %16;\n}\n"
    : "+f"(d[0]), "+f"(d[1]), "+f"(d[2]), "+f"(d[3]), "+f"(d[4]), "+f"(d[5]), "+f"(d[6]), "+f"(d[7]), "+f"(d[8]), "+f"(d[9]), "+f"(d[10]), "+f"(d[11])
    : "l"(da), "l"(db), "r"(acc), "n"(TA), "n"(TB));
}

template <int TA, int TB> __device__ __forceinline__ void wgmma_n80(float (&d)[40], uint64_t da, uint64_t db, int acc) {
  asm volatile("{\n.reg .pred p;\nsetp.ne.b32 p, %42, 0;\n"
    "wgmma.mma_async.sync.aligned.m64n80k16.f32.bf16.bf16 {%0, %1, %2, %3, %4, %5, %6, %7, %8, %9, %10, %11, %12, %13, %14, %15, %16, %17, %18, %19, %20, %21, %22, %23, %24, %25, %26, %27, %28, %29, %30, %31, %32, %33, %34, %35, %36, %37, %38, %39}, %40, %41, p, 1, 1, %43, %44;\n}\n"
    : "+f"(d[0]), "+f"(d[1]), "+f"(d[2]), "+f"(d[3]), "+f"(d[4]), "+f"(d[5]), "+f"(d[6]), "+f"(d[7]), "+f"(d[8]), "+f"(d[9]), "+f"(d[10]), "+f"(d[11]), "+f"(d[12]), "+f"(d[13]), "+f"(d[14]), "+f"(d[15]), "+f"(d[16]), "+f"(d[17]), "+f"(d[18]), "+f"(d[19]), "+f"(d[20]), "+f"(d[21]), "+f"(d[22]), "+f"(d[23]), "+f"(d[24]), "+f"(d[25]), "+f"(d[26]), "+f"(d[27]), "+f"(d[28]), "+f"(d[29]), "+f"(d[30]), "+f"(d[31]), "+f"(d[32]), "+f"(d[33]), "+f"(d[34]), "+f"(d[35]), "+f"(d[36]), "+f"(d[37]), "+f"(d[38]), "+f"(d[39])
    : "l"(da), "l"(db), "r"(acc), "n"(TA), "n"(TB));
}

template <int TA, int TB> __device__ __forceinline__ void wgmma_n128(float (&d)[64], uint64_t da, uint64_t db, int acc) {
  asm volatile("{\n.reg .pred p;\nsetp.ne.b32 p, %66, 0;\n"
    "wgmma.mma_async.sync.aligned.m64n128k16.f32.bf16.bf16 {%0, %1, %2, %3, %4, %5, %6, %7, %8, %9, %10, %11, %12, %13, %14, %15, %16, %17, %18, %19, %20, %21, %22, %23, %24, %25, %26, %27, %28, %29, %30, %31, %32, %33, %34, %35, %36, %37, %38, %39, %40, %41, %42, %43, %44, %45, %46, %47, %48, %49, %50, %51, %52, %53, %54, %55, %56, %57, %58, %59, %60, %61, %62, %63}, %64, %65, p, 1, 1, %67, %68;\n}\n"
    : "+f"(d[0]), "+f"(d[1]), "+f"(d[2]), "+f"(d[3]), "+f"(d[4]), "+f"(d[5]), "+f"(d[6]), "+f"(d[7]), "+f"(d[8]), "+f"(d[9]), "+f"(d[10]), "+f"(d[11]), "+f"(d[12]), "+f"(d[13]), "+f"(d[14]), "+f"(d[15]), "+f"(d[16]), "+f"(d[17]), "+f"(d[18]), "+f"(d[19]), "+f"(d[20]), "+f"(d[21]), "+f"(d[22]), "+f"(d[23]), "+f"(d[24]), "+f"(d[25]), "+f"(d[26]), "+f"(d[27]), "+f"(d[28]), "+f"(d[29]), "+f"(d[30]), "+f"(d[31]), "+f"(d[32]), "+f"(d[33]), "+f"(d[34]), "+f"(d[35]), "+f"(d[36]), "+f"(d[37]), "+f"(d[38]), "+f"(d[39]), "+f"(d[40]), "+f"(d[41]), "+f"(d[42]), "+f"(d[43]), "+f"(d[44]), "+f"(d[45]), "+f"(d[46]), "+f"(d[47]), "+f"(d[48]), "+f"(d[49]), "+f"(d[50]), "+f"(d[51]), "+f"(d[52]), "+f"(d[53]), "+f"(d[54]), "+f"(d[55]), "+f"(d[56]), "+f"(d[57]), "+f"(d[58]), "+f"(d[59]), "+f"(d[60]), "+f"(d[61]), "+f"(d[62]), "+f"(d[63])
    : "l"(da), "l"(db), "r"(acc), "n"(TA), "n"(TB));
}

template <int TA, int TB> __device__ __forceinline__ void wgmma_n192(float (&d)[96], uint64_t da, uint64_t db, int acc) {
  asm volatile("{\n.reg .pred p;\nsetp.ne.b32 p, %98, 0;\n"
    "wgmma.mma_async.sync.aligned.m64n192k16.f32.bf16.bf16 {%0, %1, %2, %3, %4, %5, %6, %7, %8, %9, %10, %11, %12, %13, %14, %15, %16, %17, %18, %19, %20, %21, %22, %23, %24, %25, %26, %27, %28, %29, %30, %31, %32, %33, %34, %35, %36, %37, %38, %39, %40, %41, %42, %43, %44, %45, %46, %47, %48, %49, %50, %51, %52, %53, %54, %55, %56, %57, %58, %59, %60, %61, %62, %63, %64, %65, %66, %67, %68, %69, %70, %71, %72, %73, %74, %75, %76, %77, %78, %79, %80, %81, %82, %83, %84, %85, %86, %87, %88, %89, %90, %91, %92, %93, %94, %95}, %96, %97, p, 1, 1, %99, %100;\n}\n"
    : "+f"(d[0]), "+f"(d[1]), "+f"(d[2]), "+f"(d[3]), "+f"(d[4]), "+f"(d[5]), "+f"(d[6]), "+f"(d[7]), "+f"(d[8]), "+f"(d[9]), "+f"(d[10]), "+f"(d[11]), "+f"(d[12]), "+f"(d[13]), "+f"(d[14]), "+f"(d[15]), "+f"(d[16]), "+f"(d[17]), "+f"(d[18]), "+f"(d[19]), "+f"(d[20]), "+f"(d[21]), "+f"(d[22]), "+f"(d[23]), "+f"(d[24]), "+f"(d[25]), "+f"(d[26]), "+f"(d[27]), "+f"(d[28]), "+f"(d[29]), "+f"(d[30]), "+f"(d[31]), "+f"(d[32]), "+f"(d[33]), "+f"(d[34]), "+f"(d[35]), "+f"(d[36]), "+f"(d[37]), "+f"(d[38]), "+f"(d[39]), "+f"(d[40]), "+f"(d[41]), "+f"(d[42]), "+f"(d[43]), "+f"(d[44]), "+f"(d[45]), "+f"(d[46]), "+f"(d[47]), "+f"(d[48]), "+f"(d[49]), "+f"(d[50]), "+f"(d[51]), "+f"(d[52]), "+f"(d[53]), "+f"(d[54]), "+f"(d[55]), "+f"(d[56]), "+f"(d[57]), "+f"(d[58]), "+f"(d[59]), "+f"(d[60]), "+f"(d[61]), "+f"(d[62]), "+f"(d[63]), "+f"(d[64]), "+f"(d[65]), "+f"(d[66]), "+f"(d[67]), "+f"(d[68]), "+f"(d[69]), "+f"(d[70]), "+f"(d[71]), "+f"(d[72]), "+f"(d[73]), "+f"(d[74]), "+f"(d[75]), "+f"(d[76]), "+f"(d[77]), "+f"(d[78]), "+f"(d[79]), "+f"(d[80]), "+f"(d[81]), "+f"(d[82]), "+f"(d[83]), "+f"(d[84]), "+f"(d[85]), "+f"(d[86]), "+f"(d[87]), "+f"(d[88]), "+f"(d[89]), "+f"(d[90]), "+f"(d[91]), "+f"(d[92]), "+f"(d[93]), "+f"(d[94]), "+f"(d[95])
    : "l"(da), "l"(db), "r"(acc), "n"(TA), "n"(TB));
}

template <int TA, int TB> __device__ __forceinline__ void wgmma_n256(float (&d)[128], uint64_t da, uint64_t db, int acc) {
  asm volatile("{\n.reg .pred p;\nsetp.ne.b32 p, %130, 0;\n"
    "wgmma.mma_async.sync.aligned.m64n256k16.f32.bf16.bf16 {%0, %1, %2, %3, %4, %5, %6, %7, %8, %9, %10, %11, %12, %13, %14, %15, %16, %17, %18, %19, %20, %21, %22, %23, %24, %25, %26, %27, %28, %29, %30, %31, %32, %33, %34, %35, %36, %37, %38, %39, %40, %41, %42, %43, %44, %45, %46, %47, %48, %49, %50, %51, %52, %53, %54, %55, %56, %57, %58, %59, %60, %61, %62, %63, %64, %65, %66, %67, %68, %69, %70, %71, %72, %73, %74, %75, %76, %77, %78, %79, %80, %81, %82, %83, %84, %85, %86, %87, %88, %89, %90, %91, %92, %93, %94, %95, %96, %97, %98, %99, %100, %101, %102, %103, %104, %105, %106, %107, %108, %109, %110, %111, %112, %113, %114, %115, %116, %117, %118, %119, %120, %121, %122, %123, %124, %125, %126, %127}, %128, %129, p, 1, 1, %131, %132;\n}\n"
    : "+f"(d[0]), "+f"(d[1]), "+f"(d[2]), "+f"(d[3]), "+f"(d[4]), "+f"(d[5]), "+f"(d[6]), "+f"(d[7]), "+f"(d[8]), "+f"(d[9]), "+f"(d[10]), "+f"(d[11]), "+f"(d[12]), "+f"(d[13]), "+f"(d[14]), "+f"(d[15]), "+f"(d[16]), "+f"(d[17]), "+f"(d[18]), "+f"(d[19]), "+f"(d[20]), "+f"(d[21]), "+f"(d[22]), "+f"(d[23]), "+f"(d[24]), "+f"(d[25]), "+f"(d[26]), "+f"(d[27]), "+f"(d[28]), "+f"(d[29]), "+f"(d[30]), "+f"(d[31]), "+f"(d[32]), "+f"(d[33]), "+f"(d[34]), "+f"(d[35]), "+f"(d[36]), "+f"(d[37]), "+f"(d[38]), "+f"(d[39]), "+f"(d[40]), "+f"(d[41]), "+f"(d[42]), "+f"(d[43]), "+f"(d[44]), "+f"(d[45]), "+f"(d[46]), "+f"(d[47]), "+f"(d[48]), "+f"(d[49]), "+f"(d[50]), "+f"(d[51]), "+f"(d[52]), "+f"(d[53]), "+f"(d[54]), "+f"(d[55]), "+f"(d[56]), "+f"(d[57]), "+f"(d[58]), "+f"(d[59]), "+f"(d[60]), "+f"(d[61]), "+f"(d[62]), "+f"(d[63]), "+f"(d[64]), "+f"(d[65]), "+f"(d[66]), "+f"(d[67]), "+f"(d[68]), "+f"(d[69]), "+f"(d[70]), "+f"(d[71]), "+f"(d[72]), "+f"(d[73]), "+f"(d[74]), "+f"(d[75]), "+f"(d[76]), "+f"(d[77]), "+f"(d[78]), "+f"(d[79]), "+f"(d[80]), "+f"(d[81]), "+f"(d[82]), "+f"(d[83]), "+f"(d[84]), "+f"(d[85]), "+f"(d[86]), "+f"(d[87]), "+f"(d[88]), "+f"(d[89]), "+f"(d[90]), "+f"(d[91]), "+f"(d[92]), "+f"(d[93]), "+f"(d[94]), "+f"(d[95]), "+f"(d[96]), "+f"(d[97]), "+f"(d[98]), "+f"(d[99]), "+f"(d[100]), "+f"(d[101]), "+f"(d[102]), "+f"(d[103]), "+f"(d[104]), "+f"(d[105]), "+f"(d[106]), "+f"(d[107]), "+f"(d[108]), "+f"(d[109]), "+f"(d[110]), "+f"(d[111]), "+f"(d[112]), "+f"(d[113]), "+f"(d[114]), "+f"(d[115]), "+f"(d[116]), "+f"(d[117]), "+f"(d[118]), "+f"(d[119]), "+f"(d[120]), "+f"(d[121]), "+f"(d[122]), "+f"(d[123]), "+f"(d[124]), "+f"(d[125]), "+f"(d[126]), "+f"(d[127])
    : "l"(da), "l"(db), "r"(acc), "n"(TA), "n"(TB));
}

template <int TB> __device__ __forceinline__ void wgmma_rs_n24(float (&d)[12], uint32_t a0, uint32_t a1, uint32_t a2, uint32_t a3, uint64_t db, int acc) {
  asm volatile("{\n.reg .pred p;\nsetp.ne.b32 p, %17, 0;\n"
    "wgmma.mma_async.sync.aligned.m64n24k16.f32.bf16.bf16 {%0, %1, %2, %3, %4, %5, %6, %7, %8, %9, %10, %11}, {%12, %13, %14, %15}, %16, p, 1, 1, %18;\n}\n"
    : "+f"(d[0]), "+f"(d[1]), "+f"(d[2]), "+f"(d[3]), "+f"(d[4]), "+f"(d[5]), "+f"(d[6]), "+f"(d[7]), "+f"(d[8]), "+f"(d[9]), "+f"(d[10]), "+f"(d[11])
    : "r"(a0), "r"(a1), "r"(a2), "r"(a3), "l"(db), "r"(acc), "n"(TB));
}

template <int TB> __device__ __forceinline__ void wgmma_rs_n40(float (&d)[20], uint32_t a0, uint32_t a1, uint32_t a2, uint32_t a3, uint64_t db, int acc) {
  asm volatile("{\n.reg .pred p;\nsetp.ne.b32 p, %25, 0;\n"
    "wgmma.mma_async.sync.aligned.m64n40k16.f32.bf16.bf16 {%0, %1, %2, %3, %4, %5, %6, %7, %8, %9, %10, %11, %12, %13, %14, %15, %16, %17, %18, %19}, {%20, %21, %22, %23}, %24, p, 1, 1, %26;\n}\n"
    : "+f"(d[0]), "+f"(d[1]), "+f"(d[2]), "+f"(d[3]), "+f"(d[4]), "+f"(d[5]), "+f"(d[6]), "+f"(d[7]), "+f"(d[8]), "+f"(d[9]), "+f"(d[10]), "+f"(d[11]), "+f"(d[12]), "+f"(d[13]), "+f"(d[14]), "+f"(d[15]), "+f"(d[16]), "+f"(d[17]), "+f"(d[18]), "+f"(d[19])
    : "r"(a0), "r"(a1), "r"(a2), "r"(a3), "l"(db), "r"(acc), "n"(TB));
}

template <int TB> __device__ __forceinline__ void wgmma_rs_n192(float (&d)[96], uint32_t a0, uint32_t a1, uint32_t a2, uint32_t a3, uint64_t db, int acc) {
  asm volatile("{\n.reg .pred p;\nsetp.ne.b32 p, %101, 0;\n"
    "wgmma.mma_async.sync.aligned.m64n192k16.f32.bf16.bf16 {%0, %1, %2, %3, %4, %5, %6, %7, %8, %9, %10, %11, %12, %13, %14, %15, %16, %17, %18, %19, %20, %21, %22, %23, %24, %25, %26, %27, %28, %29, %30, %31, %32, %33, %34, %35, %36, %37, %38, %39, %40, %41, %42, %43, %44, %45, %46, %47, %48, %49, %50, %51, %52, %53, %54, %55, %56, %57, %58, %59, %60, %61, %62, %63, %64, %65, %66, %67, %68, %69, %70, %71, %72, %73, %74, %75, %76, %77, %78, %79, %80, %81, %82, %83, %84, %85, %86, %87, %88, %89, %90, %91, %92, %93, %94, %95}, {%96, %97, %98, %99}, %100, p, 1, 1, %102;\n}\n"
    : "+f"(d[0]), "+f"(d[1]), "+f"(d[2]), "+f"(d[3]), "+f"(d[4]), "+f"(d[5]), "+f"(d[6]), "+f"(d[7]), "+f"(d[8]), "+f"(d[9]), "+f"(d[10]), "+f"(d[11]), "+f"(d[12]), "+f"(d[13]), "+f"(d[14]), "+f"(d[15]), "+f"(d[16]), "+f"(d[17]), "+f"(d[18]), "+f"(d[19]), "+f"(d[20]), "+f"(d[21]), "+f"(d[22]), "+f"(d[23]), "+f"(d[24]), "+f"(d[25]), "+f"(d[26]), "+f"(d[27]), "+f"(d[28]), "+f"(d[29]), "+f"(d[30]), "+f"(d[31]), "+f"(d[32]), "+f"(d[33]), "+f"(d[34]), "+f"(d[35]), "+f"(d[36]), "+f"(d[37]), "+f"(d[38]), "+f"(d[39]), "+f"(d[40]), "+f"(d[41]), "+f"(d[42]), "+f"(d[43]), "+f"(d[44]), "+f"(d[45]), "+f"(d[46]), "+f"(d[47]), "+f"(d[48]), "+f"(d[49]), "+f"(d[50]), "+f"(d[51]), "+f"(d[52]), "+f"(d[53]), "+f"(d[54]), "+f"(d[55]), "+f"(d[56]), "+f"(d[57]), "+f"(d[58]), "+f"(d[59]), "+f"(d[60]), "+f"(d[61]), "+f"(d[62]), "+f"(d[63]), "+f"(d[64]), "+f"(d[65]), "+f"(d[66]), "+f"(d[67]), "+f"(d[68]), "+f"(d[69]), "+f"(d[70]), "+f"(d[71]), "+f"(d[72]), "+f"(d[73]), "+f"(d[74]), "+f"(d[75]), "+f"(d[76]), "+f"(d[77]), "+f"(d[78]), "+f"(d[79]), "+f"(d[80]), "+f"(d[81]), "+f"(d[82]), "+f"(d[83]), "+f"(d[84]), "+f"(d[85]), "+f"(d[86]), "+f"(d[87]), "+f"(d[88]), "+f"(d[89]), "+f"(d[90]), "+f"(d[91]), "+f"(d[92]), "+f"(d[93]), "+f"(d[94]), "+f"(d[95])
    : "r"(a0), "r"(a1), "r"(a2), "r"(a3), "l"(db), "r"(acc), "n"(TB));
}
constexpr uint32_t AR_ACC = 0;
constexpr uint32_t AR_TAB = 0x100000;
constexpr uint32_t AR_PROG = 0x101000;
__host__ __device__ constexpr uint32_t prog_off(int h, int j) { return AR_PROG + h * 128 + j * 4; }
constexpr uint32_t AR_CNT = 0x108000;
constexpr uint32_t AR_QUEUE = 0x109000;
constexpr uint32_t AR_SIZE = 0x10a000;

struct ChainArgs {
  const bf16* mem0;
  const uint2* xh;
  unsigned char *kg, *vg;
  unsigned char* arena;
  unsigned* go;
  uint32_t delay;
  int margin, pubrel, dry;
  int tl;
};

namespace ch {
constexpr int OFF_WQ = 0;
constexpr int OFF_X = 81920;
constexpr int OFF_MEM = OFF_X + 40960;
constexpr int OFF_WO = OFF_MEM + 10240;
constexpr int WOK = 8 * 896;
constexpr int OFF_KV = OFF_WO + 10 * WOK;
constexpr int KVB = 5120;
constexpr int OFF_O = OFF_KV + 4 * KVB;
constexpr int OFF_Q = OFF_O + 1024;
constexpr int OFF_S = OFF_O + 3072;
constexpr int OFF_SR = OFF_S + 1536;
constexpr int OFF_LT = OFF_SR + 1280;
constexpr int OFF_BAR = OFF_LT + 512;
constexpr int SMEM = OFF_BAR + 256;
static_assert(SMEM <= 232448, "smem");
constexpr int MB_S = OFF_BAR, MB_O = OFF_BAR + 8, MB_X = OFF_BAR + 16;
constexpr int MB_K = OFF_BAR + 128, MB_V = MB_K + 16, MB_Q = MB_K + 32, MB_R = MB_K + 48;
constexpr int SC_IN = OFF_BAR + 64;
constexpr int SC_MX = OFF_S;
constexpr int SC_TW = OFF_BAR + 48;
constexpr int SC_W = OFF_BAR + 96;
constexpr int WOS = 448;
enum { B_MEM0 = 1, B_QK, B_SL, B_V, B_O, B_RED, B_X, B_C, B_H, B_MEM1, B_A, B_G, B_E };
#define NQ1 14
#define NP1 (NQ1 < 6 ? NQ1 : 6)
#define NQ0 8
#define NP0 5
#define NPL 2
#define PQE 1
#define PFK 1
#define NB0 2
#ifndef NVE
#define NVE 8
#endif
#define VET 19
#define NPM0 2
#define NPM1 2
#define NRT 7
#define NRF 2
#define PA0 3
#define PA1 0
#define PB0 7
#define PB1 5
#define PM1 1
#define GD1 30
#define GD2 150
#define XT 38
#define WOF 0
#define MEMFIRST 0
#define CEARLY 0
#define POLL_DELAY 620
#define PFX 3
#define PFACC 1
static_assert(NPM0 >= 2 && NPM1 >= 2, "the K / V blocks live in the last two k-steps of Wo");
}

template <int V> using IC = std::integral_constant<int, V>;
__device__ __forceinline__ uint32_t clk_v() { uint64_t c; asm volatile("mov.u64 %0, %%clock64;" : "=l"(c) :: "memory"); return (uint32_t)c; }
__device__ __forceinline__ int fresh(int x) { int y; asm volatile("shfl.sync.bfly.b32 %0, %1, 0, 0x1f, 0xffffffff;" : "=r"(y) : "r"(x)); return y; }
#define SFENCE2(x, d) asm volatile("{\n.reg .pred p;\nsetp.eq.u32 p, %0, 0x7fffffff;\n@p st.shared.u32 [%0], %1;\n}" :: "r"(x), "r"(d) : "memory")
#define SFENCE(x) asm volatile("{\n.reg .pred p;\nsetp.eq.u32 p, %0, 0x7fffffff;\n@p st.shared.u32 [%0], %0;\n}" :: "r"(x) : "memory")
__device__ __forceinline__ float uniform_f(float x) { return __uint_as_float(__reduce_max_sync(0xffffffffu, __float_as_uint(x))); }

__device__ __forceinline__ void mma16816h(float (&d)[4], const uint32_t (&a)[4], uint32_t b0, uint32_t b1) {
  asm volatile("mma.sync.aligned.m16n8k16.row.col.f32.f16.f16.f32 {%0,%1,%2,%3}, {%4,%5,%6,%7}, {%8,%9}, {%0,%1,%2,%3};"
               : "+f"(d[0]), "+f"(d[1]), "+f"(d[2]), "+f"(d[3]) : "r"(a[0]), "r"(a[1]), "r"(a[2]), "r"(a[3]), "r"(b0), "r"(b1));
}
__device__ __forceinline__ void mma1688(float (&d)[4], uint32_t a0, uint32_t a1, uint32_t b0) {
  asm volatile("mma.sync.aligned.m16n8k8.row.col.f32.bf16.bf16.f32 {%0,%1,%2,%3}, {%4,%5}, {%6}, {%0,%1,%2,%3};"
               : "+f"(d[0]), "+f"(d[1]), "+f"(d[2]), "+f"(d[3]) : "r"(a0), "r"(a1), "r"(b0));
}
template <int OFF16, int ACC> __device__ __forceinline__ void wgmma_rs32h(float (&d)[16], const uint32_t (&a)[4], uint32_t dlo) {
  asm volatile("{\n.reg .pred p;\n.reg .b32 t;\n.reg .b64 db;\nsetp.ne.b32 p, %22, 0;\nadd.u32 t, %20, %21;\nmov.b64 db, {t, 0x40000040};\n"
    "wgmma.mma_async.sync.aligned.m64n32k16.f32.f16.f16 {%0,%1,%2,%3,%4,%5,%6,%7,%8,%9,%10,%11,%12,%13,%14,%15}, {%16,%17,%18,%19}, db, p, 1, 1, 0;\n}\n"
    : "+f"(d[0]), "+f"(d[1]), "+f"(d[2]), "+f"(d[3]), "+f"(d[4]), "+f"(d[5]), "+f"(d[6]), "+f"(d[7]), "+f"(d[8]), "+f"(d[9]), "+f"(d[10]), "+f"(d[11]),
      "+f"(d[12]), "+f"(d[13]), "+f"(d[14]), "+f"(d[15])
    : "r"(a[0]), "r"(a[1]), "r"(a[2]), "r"(a[3]), "r"(dlo), "n"(OFF16), "n"(ACC));
}
template <int IMM> __device__ __forceinline__ void stsm_x4_t_i(uint32_t a, uint32_t r0, uint32_t r1, uint32_t r2, uint32_t r3) {
  asm volatile("stmatrix.sync.aligned.m8n8.x4.trans.shared.b16 [%0+%5], {%1,%2,%3,%4};" :: "r"(a), "r"(r0), "r"(r1), "r"(r2), "r"(r3), "n"(IMM) : "memory");
}
template <int IMM> __device__ __forceinline__ void stsm_x2_t_i(uint32_t a, uint32_t r0, uint32_t r1) {
  asm volatile("stmatrix.sync.aligned.m8n8.x2.trans.shared.b16 [%0+%3], {%1,%2};" :: "r"(a), "r"(r0), "r"(r1), "n"(IMM) : "memory");
}
template <int IMM> __device__ __forceinline__ void st_async_b32_i(uint32_t a, uint32_t x, uint32_t mb) {
  asm volatile("st.async.weak.shared::cluster.mbarrier::complete_tx::bytes.b32 [%0+%3], %1, [%2];" :: "r"(a), "r"(x), "r"(mb), "n"(IMM) : "memory");
}
template <int IMM> __device__ __forceinline__ void ldsm_x2_i(uint32_t (&r)[2], uint32_t a) {
  asm volatile("ldmatrix.sync.aligned.m8n8.x2.shared.b16 {%0,%1}, [%2+%3];" : "=r"(r[0]), "=r"(r[1]) : "r"(a), "n"(IMM) : "memory");
}
template <int IMM> __device__ __forceinline__ uint32_t ldsm_x1_t_i(uint32_t a) {
  uint32_t r; asm volatile("ldmatrix.sync.aligned.m8n8.x1.trans.shared.b16 {%0}, [%1+%2];" : "=r"(r) : "r"(a), "n"(IMM) : "memory"); return r;
}
template <int IMM> __device__ __forceinline__ uint32_t lds32_i(uint32_t a) {
  uint32_t v; asm volatile("ld.shared.u32 %0, [%1+%2];" : "=r"(v) : "r"(a), "n"(IMM) : "memory"); return v;
}
__device__ __forceinline__ void sts32(uint32_t a, uint32_t v) { asm volatile("st.shared.u32 [%0], %1;" :: "r"(a), "r"(v) : "memory"); }
__device__ __forceinline__ uint32_t pack_f16(float lo, float hi) {
  uint32_t d; asm("cvt.rn.f16x2.f32 %0, %1, %2;" : "=r"(d) : "f"(hi), "f"(lo)); return d;
}
__device__ __forceinline__ uint32_t amax_bf2(uint32_t a, uint32_t b) { uint32_t d; asm("max.xorsign.abs.bf16x2 %0, %1, %2;" : "=r"(d) : "r"(a), "r"(b)); return d; }
__device__ __forceinline__ uint32_t amax_h2(uint32_t a, uint32_t b) { uint32_t d; asm("max.xorsign.abs.f16x2 %0, %1, %2;" : "=r"(d) : "r"(a), "r"(b)); return d; }
__device__ __forceinline__ uint32_t amax_fold(uint32_t m) { return __reduce_max_sync(0xffffffffu, max(m & 0x7fffu, (m >> 16) & 0x7fffu)); }
__device__ __forceinline__ int wscale_exp(uint32_t m) { return min(141 - (int)(m >> 7), 100); }
__device__ __forceinline__ float exp2i(int e) { return __uint_as_float((uint32_t)(e + 127) << 23); }
__device__ __forceinline__ uint32_t bf2_to_h2(uint32_t w, float sc) { return pack_f16(bf_lo(w) * sc, bf_hi(w) * sc); }
__device__ __forceinline__ void bf2_to_h2_inplace(uint32_t& w, uint32_t sc2) {
  asm volatile("{\n.reg .b32 t, lo, hi;\nmul.rn.bf16x2 t, %0, %1;\nshl.b32 lo, t, 16;\nand.b32 hi, t, 0xffff0000;\ncvt.rn.f16x2.f32 %0, hi, lo;\n}" : "+r"(w) : "r"(sc2));
}
__device__ __forceinline__ void prefetch_l2(const void* p, uint32_t bytes) { asm volatile("cp.async.bulk.prefetch.L2.global [%0], %1;" :: "l"(p), "r"(bytes) : "memory"); }
__host__ __device__ constexpr uint32_t acc_voff(int v) { return v < 4 ? v * 1024u : (v == 4 ? 128u : 3072u + 128u); }
__device__ __forceinline__ int unit28(int i) { return i == 3 ? 54 : 14 * i; }
__device__ __forceinline__ int unit24(int i) { return i < 2 ? 48 - 6 * i : 56 + 6 * i; }
__device__ __forceinline__ uint32_t acc_step(int s) { return (s >> 1) * 32768 + (s & 1) * 512; }
__device__ __forceinline__ uint32_t acc_lane(int i, int lane) { return ((lane >> 3) & 1) * 256 + (lane >> 4) * 4096 + i * 8192 + (lane & 7) * 16; }

__device__ __forceinline__ uint32_t ld_acquire_u32(const void* p) {
  uint32_t v; asm volatile("ld.acquire.gpu.global.u32 %0, [%1];" : "=r"(v) : "l"(p) : "memory"); return v;
}
template <int R> __device__ __forceinline__ void ln_rows(const uint2 (&xw)[R][5], int row0, int lane, bf16* __restrict__ xn, uint2* __restrict__ xh) {
  float v[R][20], s[R], q[R];
#pragma unroll
  for (int r = 0; r < R; r++) {
    s[r] = 0.f; q[r] = 0.f;
#pragma unroll
    for (int i = 0; i < 5; i++) { v[r][4 * i] = bf_lo(xw[r][i].x); v[r][4 * i + 1] = bf_hi(xw[r][i].x); v[r][4 * i + 2] = bf_lo(xw[r][i].y); v[r][4 * i + 3] = bf_hi(xw[r][i].y); }
#pragma unroll
    for (int i = 0; i < 5; i++) s[r] += (v[r][4 * i] + v[r][4 * i + 1]) + (v[r][4 * i + 2] + v[r][4 * i + 3]);
  }
#pragma unroll
  for (int o = 16; o; o >>= 1)
#pragma unroll
    for (int r = 0; r < R; r++) s[r] += __shfl_xor_sync(0xffffffffu, s[r], o);
#pragma unroll
  for (int r = 0; r < R; r++) {
    s[r] *= 1.f / cfg::DM;
#pragma unroll
    for (int i = 0; i < 10; i++) { const float d = v[r][2 * i] - s[r], e = v[r][2 * i + 1] - s[r]; q[r] += d * d + e * e; }
  }
#pragma unroll
  for (int o = 16; o; o >>= 1)
#pragma unroll
    for (int r = 0; r < R; r++) q[r] += __shfl_xor_sync(0xffffffffu, q[r], o);
#pragma unroll
  for (int r = 0; r < R; r++) {
    const int row = row0 + r;
    const float mb = bf16r(s[r]), var = bf16r(q[r] * (1.f / cfg::DM));
    float sd; asm("sqrt.approx.f32 %0, %1;" : "=f"(sd) : "f"(bf16r(var + 1e-5f)));
    const float inv = rcpf(bf16r(sd));
#pragma unroll
    for (int i = 0; i < 5; i++) {
      float y[4];
#pragma unroll
      for (int e = 0; e < 4; e++) y[e] = v[r][4 * i + e] - mb;
      bf16r2(y[0], y[1]); bf16r2(y[2], y[3]);
      const uint32_t w0 = pack_bf16(y[0] * inv, y[1] * inv), w1 = pack_bf16(y[2] * inv, y[3] * inv);
      *(uint2*)(xn + (size_t)row * cfg::DM + i * 128 + lane * 4) = make_uint2(w0, w1);
      if (xh) xh[(((size_t)(row >> 5) * 10 + 2 * i + (lane >> 4)) * 32 + (row & 31)) * 16 + ((((lane >> 1) & 7) ^ (row & 7)) << 1) + (lane & 1)] =
          make_uint2(pack_f16(bf_lo(w0), bf_hi(w0)), pack_f16(bf_lo(w1), bf_hi(w1)));
    }
  }
}

__global__ void __cluster_dims__(3, 1, 1) __launch_bounds__(384, 1) chain_kernel(const ChainArgs a, const __grid_constant__ CUtensorMap tmWq,
    const __grid_constant__ CUtensorMap tmWk, const __grid_constant__ CUtensorMap tmWv, const __grid_constant__ CUtensorMap tmWo) {
  using namespace ch;
  extern __shared__ __align__(1024) unsigned char smem_raw[];
  const uint32_t sb = smem_u32(smem_raw);
  const int warp = __shfl_sync(0xffffffffu, (int)threadIdx.x >> 5, 0);
  const int cta = blockIdx.x, h = cta / 3, j = cta % 3;
  unsigned char* const arena = a.arena;
  if (sb & 1023u) __trap();
  asm volatile("griddepcontrol.launch_dependents;");
  const int col0 = j == 0 ? 0 : (j == 1 ? 224 : 432);
  auto stage_w = [&](const CUtensorMap* tm, uint32_t dst, uint32_t mb, int half) {
    mbar_expect_tx(mb + 8 * half, 40960);
    tma_load_2d(dst + half * 40960, tm, h * cfg::DH + j * 64, half * 320, mb + 8 * half);
    tma_load_2d(dst + half * 40960 + 20480, tm, h * cfg::DH + j * 64, half * 320 + 160, mb + 8 * half);
  };
  if (threadIdx.x == 256) {
    for (int i = 0; i < 9; i++) mbar_init(sb + MB_K + 8 * i, 1);
    mbar_init(sb + MB_S, 1); mbar_init(sb + MB_O, 1); mbar_init(sb + MB_X, 1);
    asm volatile("fence.mbarrier_init.release.cluster;" ::: "memory");
    for (int i = 0; i < 2; i++) { stage_w(&tmWk, sb + OFF_WQ, sb + MB_K, i); stage_w(&tmWv, sb + OFF_WO, sb + MB_V, i); }
    sts32(sb + SC_W, 0); sts32(sb + SC_W + 4, 0); sts32(sb + SC_W + 8, 0); sts32(sb + SC_IN + 12, 0); sts32(sb + SC_IN + 20, 0); sts32(sb + SC_TW + 4, 99);
    mbar_expect_tx(sb + MB_S, 1280); mbar_expect_tx(sb + MB_O, 2048);
  }
  __syncthreads();
  asm volatile("barrier.cluster.arrive.relaxed.aligned;" ::: "memory");
  const uint32_t d1 = mapa_u32(sb, (j + 1) % 3) - sb, d2 = mapa_u32(sb, (j + 2) % 3) - sb;

  if (warp >= 8) {
    asm volatile("setmaxnreg.dec.sync.aligned.u32 40;");
    const int lane = fresh(threadIdx.x & 31), hw = warp - 8, ht = hw * 32 + lane;
    const bool lead = ht == 0;
    auto stage_wo = [&](int i) {
      mbar_expect_tx(sb + MB_R + 8 * i, 64 * WOS);
      tma_load_2d(sb + OFF_WO + i * 64 * WOS, &tmWo, col0, h * cfg::DH + ((i + j) % 3) * 64, sb + MB_R + 8 * i);
    };
    const unsigned char* xg = (const unsigned char*)a.xh;
    auto issue_x = [&](int s) { mbar_expect_tx(sb + MB_X, 40960); bulk_g2s(sb + OFF_X, xg + (size_t)s * 40960, 40960, sb + MB_X); };
    uint4 v[5];
#pragma unroll
    for (int i = 0; i < 5; i++) { const int c = ht + 128 * i; v[i] = ld_relaxed_v4(a.mem0 + (c & 7) * cfg::DM + (c >> 3) * 8); }
    if (hw == 2) {
      asm volatile("griddepcontrol.wait;" ::: "memory");
      if (lane == 0) { if (cta == 0) st_relaxed_u32(a.go, 1); issue_x(0); }
    }
    if (hw == 0) {
      bar_sync(B_QK, 160);
      if (lane == 0) {
        stage_w(&tmWq, sb + OFF_WQ, sb + MB_Q, 0);
      }
      bar_sync(B_SL, 160); if (lane == 0) stage_w(&tmWq, sb + OFF_WQ, sb + MB_Q, 1);
    }
    if (hw == 1) {
      bar_sync(B_V, 160);
      if (lane == 0) {
        stage_wo(0);
      }
      bar_sync(B_O, 160); if (lane == 0) { stage_wo(1); stage_wo(2); }
    }
    __syncwarp();
    {
      uint32_t m = 0;
#pragma unroll
      for (int i = 0; i < 5; i++) {
        m = amax_bf2(amax_bf2(m, amax_bf2(v[i].x, v[i].y)), amax_bf2(v[i].z, v[i].w));
      }
      m = amax_fold(m);
      if (lane == 0) sts32(sb + SC_MX + hw * 4, m);
      bar_sync(B_H, 128);
      const uint4 mm = lds128(sb + SC_MX);
      const int se = max(wscale_exp(max(max(mm.x, mm.y), max(mm.z, mm.w))), -100);
      const float sc = exp2i(se);
#pragma unroll
      for (int i = 0; i < 5; i++) {
        const int c = ht + 128 * i, t = c & 7, chn = c >> 3;
        sts128(sb + OFF_MEM + chn * 128 + ((t ^ (2 * (chn & 3))) << 4), bf2_to_h2(v[i].x, sc), bf2_to_h2(v[i].y, sc), bf2_to_h2(v[i].z, sc), bf2_to_h2(v[i].w, sc));
      }
      if (lead) { sts32(sb + SC_IN, __float_as_uint(exp2i(-se))); sts32(sb + SC_IN + 4, 0x7800u); }
    }
    {
      const uint32_t p0 = sb + OFF_WQ + hw * 2048 + lane * 16;
      uint32_t m = 0;
#pragma unroll 1
      for (int i = 0; i < 10; i++) {
        if (i == 0 || i == 5) mbar_wait(sb + MB_Q + (i ? 8 : 0), 0);
        uint32_t r[4][4];
        static_for<0, 4>([&](auto K) { ldsm_x4_i<K.value * 512>(r[K.value], p0 + i * 8192); });
#pragma unroll
        for (int k = 0; k < 4; k++) m = amax_bf2(amax_bf2(m, amax_bf2(r[k][0], r[k][1])), amax_bf2(r[k][2], r[k][3]));
      }
      m = amax_fold(m);
      if (lane == 0) asm volatile("red.shared.max.u32 [%0], %1;" :: "r"(sb + SC_W + 8), "r"(m) : "memory");
      bar_sync(B_H, 128);
      const uint32_t sc = (uint32_t)(wscale_exp(lds32_i<SC_W + 8>(sb)) + 127) * 0x00800080u;
      uint32_t r[4][4];
      static_for<0, 2>([&](auto K) { ldsm_x4_i<K.value * 512>(r[K.value], p0); });
      auto cvt = [&](uint32_t (&x)[4], uint32_t p) { bf2_to_h2_inplace(x[0], sc); bf2_to_h2_inplace(x[1], sc); bf2_to_h2_inplace(x[2], sc); bf2_to_h2_inplace(x[3], sc); stsm_x4(p, x[0], x[1], x[2], x[3]); };
#pragma unroll 1
      for (int i = 0; i < 10; i++) {
        const uint32_t p = p0 + i * 8192;
        ldsm_x4_i<1024>(r[2], p); ldsm_x4_i<1536>(r[3], p);
        cvt(r[0], p); cvt(r[1], p + 512);
        ldsm_x4_i<8192>(r[0], p); ldsm_x4_i<8192 + 512>(r[1], p);
        cvt(r[2], p + 1024); cvt(r[3], p + 1536);
      }
    }
    bar_sync(0, 384);
    if (hw == 3) {
      const uint32_t eye = ((lane >> 3) == (lane & 3)) ? ((lane & 4) ? 0x3f800000u : 0x3f80u) : 0u;
      sts128(sb + OFF_LT + lane * 16, eye, eye, (lane & 2) * 64 + (lane >> 2) * 16 + (lane & 1) * 8, 0u);
      sts64(sb + OFF_S + 1280 + lane * 8, 0u, 0u);
    }
    if (lead) st_relaxed_u32(arena + AR_TAB + cta * 4, 0x80000000u | (lds32_i<SC_W>(sb) << 15) | lds32_i<SC_W + 4>(sb));
    asm volatile("barrier.cluster.wait.aligned;" ::: "memory");
    bar_sync(B_MEM0, 256); bar_sync(B_MEM1, 256);
    {
      uint32_t v0, v1, v2; int spin = 0;
      do {
        v0 = ld_relaxed_u32(arena + AR_TAB + lane * 4); v1 = ld_relaxed_u32(arena + AR_TAB + 128 + lane * 4); v2 = ld_relaxed_u32(arena + AR_TAB + 256 + lane * 4);
      } while (__any_sync(0xffffffffu, ((v0 & v1 & v2) >> 31) == 0) && ++spin < SPIN_LIMIT);
      const uint32_t mv = (max(max(v0, v1), v2) >> 15) & 0x7fffu, mo = max(max(v0 & 0x7fffu, v1 & 0x7fffu), v2 & 0x7fffu);
      sts32(sb + SC_IN + 8 + (lane & 1) * 16, 15 - ((__reduce_max_sync(0xffffffffu, mv) >> 7) + (__reduce_max_sync(0xffffffffu, mo) >> 7) - 252 + 22));
    }

    auto store_kv = [&](int s) {
      const size_t o = ((size_t)s * 96 + cta) * KVB; const uint32_t src = sb + OFF_KV + (s & 1) * (2 * KVB);
      fence_proxy_async(); bulk_s2g(a.kg + o, src, KVB); bulk_s2g(a.vg + o, src + KVB, KVB); bulk_commit();
    };
    const int cb28 = unit28(hw), du = (unit24(hw) - cb28) * 128;
    uint32_t n16 = lane * 16, hist = 0;
    const uint32_t us1 = sb + d1 + OFF_SR + 256 + (hw >> 1) * 512 + (hw & 1) * 128, us2 = sb + d2 + OFF_SR + (hw >> 1) * 512 + (hw & 1) * 128;
    const uint32_t uo1 = sb + d1 + OFF_O + 2048 + hw * 256, uo2 = sb + d2 + OFF_O + 1024 + hw * 256;
#pragma unroll 1
    for (int s = 0; s < cfg::NSEG; s++) {
      const bool last = s == cfg::NSEG - 1;
      if (n16 == 0) {
        if (hw == 2 && !last) issue_x(s + 1);
        if (hw == 0 && (s & 3) == 1 && s > 1) st_relaxed_u32(arena + (prog_off(h, j) + lds32_i<SC_IN + 12>(sb)), s - 1);
        if (hw == 0 && s > 0) store_kv(s - 1);
        if (PFX && hw == 3 && cta < 80 && s + PFX < cfg::NSEG) prefetch_l2(xg + (size_t)(s + PFX) * 40960 + cta * 512, 512);
        if (PFACC && hw == 1 && s + PFACC < cfg::NSEG - 1)
          asm volatile("prefetch.global.L2 [%0];" :: "l"(arena + (AR_ACC + acc_step(s + PFACC) + acc_lane(cta / 24, (cta & 3) * 8) + acc_voff((cta % 24) >> 2))) : "memory");
      }
      __syncwarp();
      if (last) break;
      const uint32_t kv = (s & 1) * (2 * KVB);
      n16 = fresh(n16);
      uint32_t kb0[4], kb1[4];
      { const uint32_t ka = n16 + (n16 & 384) * 4 + (sb + kv + hw * 128); ldsm_x4_i<OFF_KV>(kb0, ka); ldsm_x4_i<OFF_KV + 2560>(kb1, ka); }
      bar_sync(B_QK, 384);
      {
        uint32_t q0[4], q1[4], q2[4], q3[4];
        float sa[4] = {0, 0, 0, 0}, sc2[4] = {0, 0, 0, 0};
        ldsm_x4_i<OFF_Q>(q0, n16 + sb); ldsm_x4_i<OFF_Q + 1024>(q2, n16 + sb); ldsm_x4_i<OFF_Q + 512>(q1, n16 + sb);
        bar_arrive(B_A, 288);
        ldsm_x4_i<OFF_Q + 1536>(q3, n16 + sb);
        mma16816(sa, q0[0], q0[1], q0[2], q0[3], kb0[0], kb0[1]);
        mma16816(sc2, q2[0], q2[1], q2[2], q2[3], kb1[0], kb1[1]);
        mma16816(sa, q1[0], q1[1], q1[2], q1[3], kb0[2], kb0[3]);
        mma16816(sc2, q3[0], q3[1], q3[2], q3[3], kb1[2], kb1[3]);
        const float x0 = (sa[0] + sa[2]) + (sc2[0] + sc2[2]), x1 = (sa[1] + sa[3]) + (sc2[1] + sc2[3]);
        const uint32_t xp = pack_bf16(x0, x1);
        st_async_b32_i<0>((n16 >> 2) + us1, xp, sb + MB_S + d1);
        st_async_b32_i<0>((n16 >> 2) + us2, xp, sb + MB_S + d2);
        stsm_x2(n16 + (sb + OFF_S + hw * 256), __float_as_uint(x0), __float_as_uint(x1));
      }
      uint32_t v0[4], v1[4], vm0, vm1;
      const uint32_t uv = sb + kv + hw * 1280;
      ldsm_x4_t_i<OFF_KV + KVB>(v0, n16 + uv); ldsm_x4_t_i<OFF_KV + KVB + 640>(v1, n16 + uv);
      bar_sync(B_SL, 256);
      float t0[4], t1[4], t2[4];
      { uint32_t x[4]; ldsm_x4_i<OFF_S>(x, n16 + sb); t0[0] = __uint_as_float(x[0]); t0[1] = __uint_as_float(x[1]); t0[2] = __uint_as_float(x[2]); t0[3] = __uint_as_float(x[3]); }
      { uint32_t x[4]; ldsm_x4_i<OFF_S + 512>(x, n16 + sb); t1[0] = __uint_as_float(x[0]); t1[1] = __uint_as_float(x[1]); t1[2] = __uint_as_float(x[2]); t1[3] = __uint_as_float(x[3]); }
      { uint32_t x[4]; ldsm_x4_i<OFF_S + 1024>(x, n16 + sb); t2[0] = __uint_as_float(x[0]); t2[1] = __uint_as_float(x[1]); t2[2] = __uint_as_float(x[2]); t2[3] = __uint_as_float(x[3]); }
      mbar_spin(sb + MB_S, s & 1);
      uint2 xo;
      {
        uint32_t r0[4], r1[4], r2[2];
        ldsm_x4_i<OFF_SR>(r0, n16 + sb); ldsm_x4_i<OFF_SR + 512>(r1, n16 + sb); ldsm_x2_i<OFF_SR + 1024>(r2, n16 + sb);
        SFENCE(n16);
        const uint2 eye = lds64_i<OFF_LT>(n16 + sb);
        mma16816(t0, r0[0], r0[1], r0[2], r0[3], eye.x, eye.y);
        mma16816(t1, r1[0], r1[1], r1[2], r1[3], eye.x, eye.y);
        mma1688(t2, r2[0], r2[1], eye.x);
        bar_sync(B_V, 256);
        vm0 = ldsm_x1_t_i<OFF_KV + KVB + 512>(n16 + uv); vm1 = ldsm_x1_t_i<OFF_KV + KVB + 1152>(n16 + uv);
        SFENCE(n16);
        xo = lds64_i<OFF_LT + 8>(n16 + sb);
      }
      float sc[10] = {t0[0], t0[1], t0[2], t0[3], t1[0], t1[1], t1[2], t1[3], t2[0] + t2[2], t2[1] + t2[3]};
      const float cs = 0.07216878364870322f * 1.4426950408889634f;
      float mx = fmaxf(fmaxf(fmaxf(sc[0], sc[1]), fmaxf(sc[2], sc[3])), fmaxf(fmaxf(sc[4], sc[5]), fmaxf(sc[6], sc[7])));
      mx = fmaxf(mx, fmaxf(sc[8], sc[9]));
      {
        const float m1 = __shfl_xor_sync(0xffffffffu, mx, 1), m2 = __shfl_xor_sync(0xffffffffu, mx, 2), m3 = __shfl_xor_sync(0xffffffffu, mx, 3);
        mx = fmaxf(fmaxf(mx, m1), fmaxf(m2, m3));
      }
      const float mo = fmaf(mx, -cs, __uint_as_float(xo.x));
      auto ex = [&](int i) -> uint32_t { float x, y;
        asm volatile("ex2.approx.ftz.f32 %0, %1;" : "=f"(x) : "f"(fmaf(sc[i], cs, mo))); asm volatile("ex2.approx.ftz.f32 %0, %1;" : "=f"(y) : "f"(fmaf(sc[i + 1], cs, mo)));
        return pack_bf16(x, y); };
      float oa[4] = {0, 0, 0, 0}, ob[4] = {0, 0, 0, 0}, oc[4] = {0, 0, 0, 0}, od[4] = {0, 0, 0, 0}, rs[4] = {0, 0, 0, 0};
      const uint32_t ones = 0x3f803f80u;
      const uint32_t p4 = ex(8);
      if (MEMFIRST) { mma1688(rs, p4, 0u, ones); mma1688(oa, p4, 0u, vm0); mma1688(ob, p4, 0u, vm1); }
      const uint32_t p0 = ex(0), p1 = ex(2), p2 = ex(4), p3 = ex(6);
      mma16816(rs, p0, p2, p1, p3, ones, ones);
      mma16816(oa, p0, p2, p1, p3, v0[0], v0[1]);
      mma16816(oc, p0, p2, p1, p3, v0[2], v0[3]);
      mma16816(ob, p0, p2, p1, p3, v1[0], v1[1]);
      mma16816(od, p0, p2, p1, p3, v1[2], v1[3]);
      if (!MEMFIRST) { mma1688(rs, p4, 0u, ones); mma1688(oa, p4, 0u, vm0); mma1688(ob, p4, 0u, vm1); }
      const float inv = rcpf(rs[0] + rs[2]) * __uint_as_float(xo.y);
      {
        const uint32_t y0 = pack_bf16((oa[0] + oc[2]) * inv, (oa[1] + oc[3]) * inv), y1 = pack_bf16((ob[0] + od[2]) * inv, (ob[1] + od[3]) * inv);
        st_async_v2_i<0>(xo.x + uo1, y0, y1, sb + MB_O + d1);
        st_async_v2_i<0>(xo.x + uo2, y0, y1, sb + MB_O + d2);
        sts64_i<OFF_O>(xo.x + (sb + hw * 256), y0, y1);
      }
      bar_arrive(B_O, 384);
      if (hw == 0) bulk_wait<0>();
      mbar_expect_tx_if(n16 == 0 && hw == 3, sb + MB_S, 1280);
      n16 = fresh(n16);
      const int ln = n16 >> 4;
      auto mslot = [&](int c) -> uint32_t { return sb + OFF_MEM + c * 128 + (((ln >> 2) ^ (2 * (c & 3))) << 4); };
      const int lq = ln & 3;
      const uint32_t ma = mslot(cb28 + lq), mb_ = mslot(cb28 + (lq >> 1)) + (lq & 1) * 8;
      const unsigned char* gp = arena + (AR_ACC + acc_lane(hw, ln) + acc_step(s));
      const bool odd = ln & 1;
      const uint32_t delay = a.delay + ((hist & 2) ? a.margin : 0);
      SFENCE(ma);
      uint32_t tw;
      if (hw == 0 && (s & 3) == 0 && a.pubrel) {
        bar_arrive(B_RED, 384);
        asm volatile("fence.acq_rel.gpu;" ::: "memory");
        uint2 t; int sp = 0;
        do { asm volatile("ld.volatile.shared.v2.u32 {%0,%1}, [%2];" : "=r"(t.x), "=r"(t.y) : "r"(sb + SC_TW) : "memory"); } while (__any_sync(0xffffffffu, t.y != (uint32_t)s) && ++sp < SPIN_LIMIT);
        tw = t.x;
      } else {
        bar_sync(B_RED, 384);
        SFENCE(mb_);
        tw = clk_v();
        if (hw == 1) asm volatile("st.volatile.shared.v2.u32 [%0], {%1,%2};" :: "r"(sb + SC_TW), "r"(tw), "r"(s) : "memory");
      }
      mbar_expect_tx_if(n16 == 0 && hw == 3, sb + MB_O, 2048);
      while (clk_v() - tw < delay) {}
      uint4 v[6];
      int spin = 0;
      const uint32_t cm = odd ? 0x5000u : 0u;
      do {
        static_for<0, 6>([&](auto I) { v[I.value] = ld_relaxed_v4_i<acc_voff(I.value)>(gp); });
      } while (__any_sync(0xffffffffu, (~((v[0].w & v[1].w & v[2].w) & (v[3].w & v[4].w & v[5].w)) & cm) != 0) && ++spin < SPIN_LIMIT);
      v[0].w = odd ? v[3].x : v[0].w; v[1].w = odd ? v[3].y : v[1].w; v[2].w = odd ? v[3].z : v[2].w; v[3].w = odd ? 0u : v[3].w;
      sts128_i<0>(ma, v[0].x, v[0].y, v[0].z, v[0].w);
      sts128_i<512>(ma, v[1].x, v[1].y, v[1].z, v[1].w);
      sts128_i<1024>(ma, v[2].x, v[2].y, v[2].z, v[2].w);
      sts128_i<0>(ma + du, v[4].x, v[4].y, v[4].z, v[5].z);
      sts64_i<512>(mb_ + du, v[5].x, v[5].y);
      if (!odd) sts128_i<1536>(mb_, v[3].x, v[3].y, v[3].z, v[3].w);
      hist = (hist * 2 + (spin != 0)) & 0xffffu;
      bar_sync(B_MEM0, 256); bar_sync(B_MEM1, 256);
      uint32_t m = lds32_i<SC_IN + 12>(sb);
      uint32_t m2 = m;
      static_for<0, 3>([&](auto I) { m = amax_h2(amax_h2(amax_h2(amax_h2(m, v[I.value].x), v[I.value].y), v[I.value].z), v[I.value].w); });
      static_for<3, 6>([&](auto I) { m2 = amax_h2(amax_h2(amax_h2(m2, v[I.value].x), v[I.value].y), v[I.value].z); });
      m = amax_fold(amax_h2(amax_h2(m2, v[3].w), m));
      if (n16 == 0) asm volatile("red.shared.max.u32 [%0], %1;" :: "r"(sb + SC_IN + 4 + 16 * ((s + 1) & 1)), "r"(m) : "memory");
    }
    bar_sync(B_RED, 384);
    if (hw == 0 && n16 == 0) {
      store_kv(cfg::NSEG - 1);
      bulk_wait<0>();
      st_release_u32(arena + (prog_off(h, j) + lds32_i<SC_IN + 12>(sb)), cfg::NSEG);
    }
    __syncwarp();
    asm volatile("barrier.cluster.arrive.relaxed.aligned; barrier.cluster.wait.aligned;" ::: "memory");
  } else {
    asm volatile("setmaxnreg.inc.sync.aligned.u32 232;");
    const int wi = warp & 3, hf = warp >> 2;
    int lane = fresh(threadIdx.x & 31);
    uint32_t w[40][4], wm = 0;
    uint32_t wqa;
    { const int r8 = lane & 7, mrow = r8 + ((lane >> 4) << 3), mch = 2 * wi + ((lane >> 3) & 1); wqa = sb + mrow * 128 + ((mch ^ r8) << 4); }
    float iw, iq;
#pragma unroll 1
    for (int live = a.dry ? 0 : 1; live < 2; live++) {
      const uint32_t wa = wqa + (hf ? OFF_WO : OFF_WQ);
      wm = 0;
      mbar_wait_if(live, sb + (hf ? MB_V : MB_K), 0);
      static_for<0, 20>([&](auto K) { ldsm_x4_t_i<K.value * 2048>(w[K.value], wa); });
#pragma unroll
      for (int k = 0; k < 20; k++) wm = amax_bf2(amax_bf2(wm, amax_bf2(w[k][0], w[k][1])), amax_bf2(w[k][2], w[k][3]));
      SFENCE2(wa, wm);
      if (live) bar_arrive(hf ? B_V : B_QK, 160);
      mbar_wait_if(live, sb + (hf ? MB_V : MB_K) + 8, 0);
      static_for<20, 40>([&](auto K) { ldsm_x4_t_i<K.value * 2048>(w[K.value], wa); });
#pragma unroll
      for (int k = 20; k < 40; k++) wm = amax_bf2(amax_bf2(wm, amax_bf2(w[k][0], w[k][1])), amax_bf2(w[k][2], w[k][3]));
      SFENCE2(wa, wm);
      if (live) bar_arrive(hf ? B_O : B_SL, 160);
      SFENCE(wa);
      const uint32_t m = amax_fold(wm);
      if (hf && live) asm volatile("red.shared.max.u32 [%0], %1;" :: "r"(sb + SC_W), "r"(m) : "memory");
      const int e = wscale_exp(m);
      const uint32_t sc = (uint32_t)(e + 127) * 0x00800080u; iw = exp2i(-e);
#pragma unroll
      for (int k = 0; k < 40; k++) { bf2_to_h2_inplace(w[k][0], sc); bf2_to_h2_inplace(w[k][1], sc); bf2_to_h2_inplace(w[k][2], sc); bf2_to_h2_inplace(w[k][3], sc); }
    }
    iw = uniform_f(iw);
    uint32_t x0[8];
    {
      float xa[16];
      const uint32_t dlo = (((sb + OFF_X) & 0x3FFFF) >> 4) | (1u << 16);
      mbar_wait(sb + MB_X, 0);
      wgmma_fence();
      static_for<0, 40>([&](auto K) { constexpr int k = K.value; wgmma_rs32h<((k >> 2) * 4096 + (k & 3) * 32) / 16, (k != 0)>(xa, w[k], dlo); });
      wgmma_commit();
      wgmma_wait<0>();
#pragma unroll
      for (int i = 0; i < 8; i++) x0[i] = pack_bf16(xa[2 * i] * iw, xa[2 * i + 1] * iw);
    }
    lane = fresh(threadIdx.x & 31);
    const int g = lane >> 2, q4 = lane & 3, r8 = lane & 7, m4 = lane >> 3;
    const bool t28 = j == 0 || warp < 4;
    const int bi = j == 0 ? hf : (warp < 4 ? j + 1 : 2 * (j - 1) + ((warp - 4) >> 1)), bv = t28 ? wi : 4 + (warp & 1);
    uint32_t wo1 = sb + OFF_WO + warp * 896 + lane * 16, wo2;
    {
      const int cb = (t28 ? unit28(bi) : unit24(bi)) - col0 / 8;
      uint32_t cp[4];
#pragma unroll
      for (int wd = 0; wd < 4; wd++) {
        int c, p;
        if (bv < 3) { c = 4 * bv + q4; p = wd; }
        else if (bv == 3) { if (q4 & 1) { c = 4 * (wd % 3) + q4; p = 3; } else { c = 12 + (q4 >> 1); p = wd; } }
        else if (bv == 4) { c = q4; p = wd; }
        else { if (wd < 2) { c = 4 + (q4 >> 1); p = 2 * (q4 & 1) + wd; } else { c = q4; p = 3; } }
        cp[wd] = sb + OFF_WO + ((g & 1) + (g & 2) * 4 + (g >> 2) * 2) * WOS + (cb + c) * 16 + p * 4;
      }
      const int cidx = (r8 & 1) + ((r8 >> 2) << 1);
      wo2 = sb + OFF_WO + warp * 896 + ((m4 & 1) ? 768 + (m4 >> 1) * 64 + cidx * 16 : 512 + (m4 >> 1) * 128 + r8 * 16);
      const bool dump = (m4 & 1) && (r8 & 2);
      uint32_t mo = 0;
      const bool regular = bv < 3 || bv == 4;
#pragma unroll 1
      for (int i = 0; i < 3; i++) {
        uint32_t x[4][4], y[4][4];
        const uint32_t o = i * 4 * WOK;
        mbar_wait(sb + MB_R + 8 * i, 0);
        if (regular) {
          static_for<0, 4>([&](auto K) {
            constexpr int kk = K.value;
            const uint4 u = lds128_i<kk * WOK>(cp[0] + o), v = lds128_i<kk * WOK + 4 * WOS>(cp[0] + o);
            x[kk][0] = u.x; x[kk][1] = u.y; x[kk][2] = u.z; x[kk][3] = u.w; y[kk][0] = v.x; y[kk][1] = v.y; y[kk][2] = v.z; y[kk][3] = v.w;
          });
        } else {
          static_for<0, 4>([&](auto K) {
            constexpr int kk = K.value;
#pragma unroll
            for (int wd = 0; wd < 4; wd++) { x[kk][wd] = lds32_i<kk * WOK>(cp[wd] + o); y[kk][wd] = lds32_i<kk * WOK + 4 * WOS>(cp[wd] + o); }
          });
        }
        bar_sync(B_C, 256);
        static_for<0, 4>([&](auto K) {
          constexpr int kk = K.value;
#pragma unroll
          for (int wd = 0; wd < 4; wd++) mo = amax_bf2(mo, amax_bf2(x[kk][wd], y[kk][wd]));
          stsm_x4_t_i<kk * WOK>(wo1 + o, x[kk][0], x[kk][1], y[kk][0], y[kk][1]);
          stsm_x4_t_i<0>(dump ? sb + OFF_S + 512 + lane * 16 : wo2 + o + kk * WOK, x[kk][2], x[kk][3], y[kk][2], y[kk][3]);
        });
      }
      mo = amax_fold(mo);
      if (lane == 0) asm volatile("red.shared.max.u32 [%0], %1;" :: "r"(sb + SC_W + 4), "r"(mo) : "memory");
    }
    __syncwarp();
    auto run = [&](auto HF) {
    constexpr int hf = HF.value;
    uint32_t mema, sta, l16 = sb + lane * 16;
    uint32_t rq[hf ? NP1 : NQ0][4];
    auto step_addr = [&](uint32_t kv) {
      const int lr = (l16 >> 4) & 7, lm = (l16 >> 7) & 3;
      mema = l16 ^ (lm << 5);
      sta = sb + lr * 16 + (lm < 2 ? OFF_Q + wi * 512 + hf * 128 + lm * 256 : OFF_KV + kv + 512 + (2 * wi + lm - 2) * 640);
    };
    auto x_gemm = [&](uint32_t ph) {
      float xa[16];
      const uint32_t dlo = (((sb + OFF_X) & 0x3FFFF) >> 4) | (1u << 16);
      constexpr int NP = hf ? NP1 : NP0;
      if constexpr (hf) {
        static_for<PQE, NP>([&](auto K) { ldsm_x4_t_i<OFF_WQ + K.value * 2048>(rq[K.value], wqa); });
        bar_sync(B_X, 256);
      }
      wgmma_fence();
      static_for<0, 40>([&](auto K) {
        constexpr int k = K.value;
        wgmma_rs32h<((k >> 2) * 4096 + (k & 3) * 32) / 16, (k != 0)>(xa, w[k], dlo);
        if constexpr (!hf && k == PFK && NP > PQE) { SFENCE(wqa); static_for<PQE, NP>([&](auto K) { ldsm_x4_t_i<OFF_WQ + K.value * 2048>(rq[K.value], wqa); }); SFENCE(wqa); }
        if constexpr (!hf && k == XT) bar_arrive(B_X, 256);
      });
      step_addr(ph * (2 * KVB));
      wgmma_commit();
      wgmma_wait<0>();
      const uint32_t xs = l16 + (wi * 1280 + ph * (2 * KVB));
      stsm_x4_t_i<OFF_KV + hf * KVB>(xs, pack_bf16(xa[0] * iw, xa[1] * iw), pack_bf16(xa[4] * iw, xa[5] * iw), pack_bf16(xa[8] * iw, xa[9] * iw), pack_bf16(xa[12] * iw, xa[13] * iw));
      stsm_x4_t_i<OFF_KV + hf * KVB + 640>(xs, pack_bf16(xa[2] * iw, xa[3] * iw), pack_bf16(xa[6] * iw, xa[7] * iw), pack_bf16(xa[10] * iw, xa[11] * iw), pack_bf16(xa[14] * iw, xa[15] * iw));
      if constexpr (!hf) static_for<NP0, NP0 + NPL>([&](auto K) { ldsm_x4_t_i<OFF_WQ + K.value * 2048>(rq[K.value], wqa); });
    };
    auto wq_addr = [&](uint32_t l) -> uint32_t {
      const int lr = (l >> 4) & 7, lm = (l >> 7) & 3;
      return sb + hf * ((40 - NQ1) * 2048) + (lr + ((lm >> 1) << 3)) * 128 + (((2 * wi + (lm & 1)) ^ lr) << 4);
    };
    constexpr int NPM = hf ? NPM1 : NPM0;
    uint32_t u1[NPM][4], u2[NPM][4];
    static_for<0, NPM>([&](auto K) { ldsm_x4_i<(12 - NPM + K.value) * WOK>(u1[K.value], wo1); ldsm_x4_i<(12 - NPM + K.value) * WOK>(u2[K.value], wo2); });
    bar_sync(0, 384);
    iq = uniform_f(exp2i(-wscale_exp(lds32_i<SC_W + 8>(sb))));
    wqa = wq_addr(l16);
    static_for<0, (hf ? NP1 : NP0 + NPL)>([&](auto K) { ldsm_x4_t_i<OFF_WQ + K.value * 2048>(rq[K.value], wqa); });
    step_addr(0);
    stsm_x4_t_i<OFF_KV + hf * KVB>(l16 + wi * 1280, x0[0], x0[2], x0[4], x0[6]);
    stsm_x4_t_i<OFF_KV + hf * KVB + 640>(l16 + wi * 1280, x0[1], x0[3], x0[5], x0[7]);
    asm volatile("barrier.cluster.wait.aligned;" ::: "memory");
#pragma unroll 1
    for (int s = 0; s < cfg::NSEG - 1; s++) {
      bar_sync(hf ? B_MEM1 : B_MEM0, 256);
      const float sin_ = __uint_as_float(lds32_i<SC_IN>(sb + 16 * (s & 1)));
      constexpr int NPQ = (40 - NQ1) / 2;
      if constexpr (hf == 0) {
        float k0[4] = {0, 0, 0, 0}, k1[4] = {0, 0, 0, 0}, q0[4] = {0, 0, 0, 0}, q1[4] = {0, 0, 0, 0};
        constexpr auto pair_of = [](int t) { const int a = t * (20 - NPQ) / 20, b = (t + 1) * (20 - NPQ) / 20; return b > a ? NPQ + a : t - a; };
        uint32_t b[NB0][4];
        static_for<0, NB0>([&](auto T) { ldsm_x4_i<OFF_MEM + pair_of(T.value) * 512>(b[T.value], mema); });
        static_for<NP0 + NPL, NQ0>([&](auto K) { ldsm_x4_t_i<OFF_WQ + K.value * 2048>(rq[K.value], wqa); });
        static_for<0, 20>([&](auto T) {
          constexpr int t = T.value, p = pair_of(t);
          uint32_t (&bb)[4] = b[t % NB0];
          if constexpr (p < NPQ) {
            mma16816h(q0, rq[(2 * p) % NQ0], bb[0], bb[1]);
            if constexpr (2 * p + NQ0 < 2 * NPQ) ldsm_x4_t_i<OFF_WQ + (2 * p + NQ0) * 2048>(rq[(2 * p) % NQ0], wqa);
          }
          mma16816h(k0, w[2 * p], bb[0], bb[1]);
          if constexpr (p < NPQ) {
            mma16816h(q1, rq[(2 * p + 1) % NQ0], bb[2], bb[3]);
            if constexpr (2 * p + 1 + NQ0 < 2 * NPQ) ldsm_x4_t_i<OFF_WQ + (2 * p + 1 + NQ0) * 2048>(rq[(2 * p + 1) % NQ0], wqa);
          }
          mma16816h(k1, w[2 * p + 1], bb[2], bb[3]);
          if constexpr (NVE > 0 && t + NB0 == VET) bar_arrive(B_E, 256);
          if constexpr (t + NB0 < 20) ldsm_x4_i<OFF_MEM + pair_of(t + NB0) * 512>(bb, mema);
        });
        const float sq = sin_ * iq, sk = sin_ * iw;
        stsm_x4_t_i<0>(sta, pack_bf16((q0[0] + q1[0]) * sq, (q0[1] + q1[1]) * sq), pack_bf16((q0[2] + q1[2]) * sq, (q0[3] + q1[3]) * sq),
                       pack_bf16((k0[0] + k1[0]) * sk, (k0[1] + k1[1]) * sk), pack_bf16((k0[2] + k1[2]) * sk, (k0[3] + k1[3]) * sk));
        bar_sync(B_QK, 384);
        {
          if (wi == 3) {
            const uint32_t xr = sb + ((l16 & 511) >> 2), ka = l16 + (l16 & 384) * 4 + (s & 1) * (2 * KVB);
            uint32_t a0[4], a1[4], a2[4], a3[4], kb0[4], kb1[4];
            ldsm_x4_i<OFF_Q>(a0, l16); ldsm_x4_i<OFF_KV + 512>(kb0, ka); ldsm_x4_i<OFF_Q + 1024>(a2, l16); ldsm_x4_i<OFF_KV + 512 + 2560>(kb1, ka);
            ldsm_x4_i<OFF_Q + 512>(a1, l16);
            bar_arrive(B_A, 288);
            ldsm_x4_i<OFF_Q + 1536>(a3, l16);
            float sa[4] = {0, 0, 0, 0}, sc2[4] = {0, 0, 0, 0};
            mma16816(sa, a0[0], a0[1], a0[2], a0[3], kb0[0], kb0[1]);
            mma16816(sc2, a2[0], a2[1], a2[2], a2[3], kb1[0], kb1[1]);
            mma16816(sa, a1[0], a1[1], a1[2], a1[3], kb0[2], kb0[3]);
            mma16816(sc2, a3[0], a3[1], a3[2], a3[3], kb1[2], kb1[3]);
            const float x0 = (sa[0] + sa[2]) + (sc2[0] + sc2[2]), x1 = (sa[1] + sa[3]) + (sc2[1] + sc2[3]);
            const uint32_t xp = pack_bf16(x0, x1);
            st_async_b32_i<OFF_SR + 1024 + 128>(xr + d1, xp, sb + MB_S + d1);
            st_async_b32_i<OFF_SR + 1024>(xr + d2, xp, sb + MB_S + d2);
            stsm_x2(l16 + OFF_S + 1024, __float_as_uint(x0), __float_as_uint(x1));
          } else if (wi == 0) {
            const uint4 si = lds128_i<SC_IN>(sb + 16 * (s & 1));
            const int em = (int)(si.y >> 10) - 14 + (int)(si.x >> 23) - 127;
            const uint32_t osc = __float_as_uint(exp2i(max(min((int)si.z - max(em, 1), 100), -100)));
            sts32(l16 + OFF_LT + 12, osc); sts64_i<SC_IN>(sb + 16 * ((s + 1) & 1), 0x7f000000u - osc, 0u);
          }
          bar_sync(B_SL, 256);
        }
      } else {
        float v0[4] = {0, 0, 0, 0}, v1[4] = {0, 0, 0, 0}, q0[4] = {0, 0, 0, 0}, q1[4] = {0, 0, 0, 0};
        constexpr int NB1 = NQ1 / 2 < 3 ? NQ1 / 2 : 3;
        uint32_t b[NB1][4];
        static_for<0, NB1>([&](auto T) { ldsm_x4_i<OFF_MEM + (NPQ + T.value) * 512>(b[T.value], mema); });
        static_for<0, NQ1 / 2>([&](auto T) {
          constexpr int t = T.value, p = NPQ + t;
          uint32_t (&bb)[4] = b[t % NB1];
          mma16816h(q0, rq[(2 * t) % NP1], bb[0], bb[1]);
          if constexpr (2 * t + NP1 < NQ1) ldsm_x4_t_i<OFF_WQ + (2 * t + NP1) * 2048>(rq[(2 * t) % NP1], wqa);
          mma16816h(q1, rq[(2 * t + 1) % NP1], bb[2], bb[3]);
          if constexpr (2 * t + 1 + NP1 < NQ1) ldsm_x4_t_i<OFF_WQ + (2 * t + 1 + NP1) * 2048>(rq[(2 * t + 1) % NP1], wqa);
          mma16816h(v0, w[2 * p], bb[0], bb[1]);
          mma16816h(v1, w[2 * p + 1], bb[2], bb[3]);
          if constexpr (t + NB1 < NQ1 / 2) ldsm_x4_i<OFF_MEM + (p + NB1) * 512>(bb, mema);
        });
        const float sq = sin_ * iq, sv = sin_ * iw;
        stsm_x2_t_i<0>(sta, pack_bf16((q0[0] + q1[0]) * sq, (q0[1] + q1[1]) * sq), pack_bf16((q0[2] + q1[2]) * sq, (q0[3] + q1[3]) * sq));
        bar_arrive(B_QK, 384);
        float v2[4] = {0, 0, 0, 0}, v3[4] = {0, 0, 0, 0};
        auto vpair = [&](auto P, uint32_t (&bb)[4]) {
          constexpr int p = P.value;
          if constexpr (p & 1) { mma16816h(v0, w[2 * p], bb[0], bb[1]); mma16816h(v1, w[2 * p + 1], bb[2], bb[3]); }
          else { mma16816h(v2, w[2 * p], bb[0], bb[1]); mma16816h(v3, w[2 * p + 1], bb[2], bb[3]); }
        };
        if constexpr (NVE > 0) {
          uint32_t e[NVE ? NVE : 1][4];
          bar_sync(B_E, 256);
          static_for<0, NVE>([&](auto T) { ldsm_x4_i<OFF_MEM + T.value * 512>(e[T.value], mema); });
          static_for<0, NVE>([&](auto T) { vpair(T, e[T.value]); });
        }
        bar_sync(B_A, 288);
        uint32_t c[4][4];
        static_for<NVE, (NVE + 4 < NPQ ? NVE + 4 : NPQ)>([&](auto T) { ldsm_x4_i<OFF_MEM + T.value * 512>(c[T.value & 3], mema); });
        static_for<NVE, NPQ>([&](auto T) {
          constexpr int p = T.value;
          vpair(T, c[p & 3]);
          if constexpr (p + 4 < NPQ) ldsm_x4_i<OFF_MEM + (p + 4) * 512>(c[p & 3], mema);
        });
        stsm_x2_t_i<OFF_KV + KVB + 512>(l16 + (l16 & 128) * 4 + (wi * 1280 + (s & 1) * (2 * KVB)), pack_bf16(((v0[0] + v1[0]) + (v2[0] + v3[0])) * sv, ((v0[1] + v1[1]) + (v2[1] + v3[1])) * sv),
                            pack_bf16(((v0[2] + v1[2]) + (v2[2] + v3[2])) * sv, ((v0[3] + v1[3]) + (v2[3] + v3[3])) * sv));
        bar_arrive(B_V, 256);
      }
      {
        uint32_t t1[12][4], t2[12][4];
        const uint32_t o16 = l16;
        wo1 = l16 + (OFF_WO + warp * 896);
        wo2 = sb + OFF_WO + warp * 896 + ((l16 & 128) ? 768 + ((l16 & 256) >> 2) + (l16 & 16) + ((l16 & 64) >> 1) : 512 + ((l16 & 256) >> 1) + (l16 & 112));
        constexpr int NR_ = NRT - NPM;
        auto ldw = [&](auto K) { if constexpr (K.value < 12 - NPM) { ldsm_x4_i<K.value * WOK>(t1[K.value], wo1); ldsm_x4_i<K.value * WOK>(t2[K.value], wo2); } };
        constexpr int PB = (hf ? PB1 : PB0) < NR_ ? (hf ? PB1 : PB0) : NR_, PA = (hf ? PA1 : PA0) < PB ? (hf ? PA1 : PA0) : PB;
        static_for<0, PA>(ldw);
        mbar_spin(sb + MB_X, (s + 1) & 1);
        if constexpr (PB > PA) {
          constexpr int PM = PA + PM1 < PB ? PA + PM1 : PB;
          mbar_spin(sb + MB_S, s & 1);
          const uint32_t t0 = clk_v();
          if constexpr (PM > PA) { while (clk_v() - t0 < GD1) {} static_for<PA, PM>(ldw); }
          if constexpr (PB > PM) { while (clk_v() - t0 < GD2) {} static_for<PM, PB>(ldw); }
        }
        float c0[4] = {0, 0, 0, 0}, c1[4] = {0, 0, 0, 0}, e0[4] = {0, 0, 0, 0}, e1[4] = {0, 0, 0, 0};
        uint32_t ob[6][4];
        auto kstep = [&](auto K) {
          constexpr int k = K.value;
          uint32_t (&bb)[4] = ob[k >> 1];
          uint32_t (&x)[4] = k < 12 - NPM ? t1[k] : u1[k < 12 - NPM ? 0 : k - (12 - NPM)];
          uint32_t (&y)[4] = k < 12 - NPM ? t2[k] : u2[k < 12 - NPM ? 0 : k - (12 - NPM)];
          if constexpr (k & 1) { mma16816(c1, x[0], x[1], x[2], x[3], bb[2], bb[3]); mma16816(e1, y[0], y[1], y[2], y[3], bb[2], bb[3]); }
          else { mma16816(c0, x[0], x[1], x[2], x[3], bb[0], bb[1]); mma16816(e0, y[0], y[1], y[2], y[3], bb[0], bb[1]); }
          if constexpr (k >= NRF) ldw(IC<k + NR_ - NRF>{});
        };
        auto ldo = [&](auto P) { ldsm_x4_i<OFF_O + P.value * 512>(ob[P.value], o16); };
        bar_sync(B_O, 384);
        ldo(IC<0>{}); ldo(IC<1>{});
        SFENCE(o16);
        static_for<PB, NR_>(ldw);
        static_for<0, 4>(kstep);
        mbar_spin(sb + MB_O, s & 1);
        ldo(IC<2>{}); ldo(IC<NPM >= 2 ? 5 : 3>{});
        if (WOF) SFENCE(o16);
        kstep(IC<4>{});
        if constexpr (NPM < 2) { kstep(IC<5>{}); ldo(IC<4>{}); kstep(IC<6>{}); kstep(IC<7>{}); ldo(IC<5>{}); static_for<8, 12>(kstep); }
        else if constexpr (NPM >= 4) { kstep(IC<10>{}); kstep(IC<11>{}); ldo(IC<4>{}); kstep(IC<5>{}); ldo(IC<3>{}); kstep(IC<8>{}); kstep(IC<9>{}); kstep(IC<6>{}); kstep(IC<7>{}); }
        else { kstep(IC<5>{}); ldo(IC<3>{}); kstep(IC<11>{}); kstep(IC<10>{}); ldo(IC<4>{}); kstep(IC<6>{}); kstep(IC<7>{}); if constexpr (NPM == 3) { kstep(IC<9>{}); kstep(IC<8>{}); } else { kstep(IC<8>{}); kstep(IC<9>{}); } }
        l16 = fresh(l16);
        const int ln = (l16 >> 4) & 31;
        if constexpr (CEARLY && hf) { SFENCE2(o16, __float_as_uint(e1[0])); bar_arrive(B_G, 256); }
        unsigned char* gr = arena + (AR_ACC + acc_lane(bi, ln) + acc_voff(bv) + acc_step(s));
        const bool cnt = (ln & 1) || !t28;
        wqa = wq_addr(l16);
        SFENCE(o16);
        static_for<0, PQE>([&](auto K) { ldsm_x4_t_i<OFF_WQ + K.value * 2048>(rq[K.value], wqa); });
        const uint32_t y0 = movm_t(pack_f16(c0[0] + c1[0], c0[1] + c1[1])), y1 = movm_t(pack_f16(c0[2] + c1[2], c0[3] + c1[3]));
        const uint32_t y2 = movm_t(pack_f16(e0[0] + e1[0], e0[1] + e1[1])), y3 = movm_t(pack_f16(e0[2] + e1[2], e0[3] + e1[3]));
        asm volatile("red.relaxed.gpu.global.add.noftz.v4.f16x2 [%0], {%1,%2,%3,%4};" :: "l"(gr), "r"(y0), "r"(y1), "r"(y2), "r"(cnt ? 0x3c00u : y3) : "memory");
        bar_arrive(B_RED, 384);
        if constexpr (CEARLY && !hf) { bar_arrive(B_C, 256); bar_sync(B_G, 256); }
        else bar_sync(B_C, 256);
      }
      x_gemm((s + 1) & 1);
    }
    };
    if (hf == 0) run(IC<0>{}); else run(IC<1>{});
    {
      const uint32_t l16 = sb + (threadIdx.x & 31) * 16, mema = l16 ^ ((l16 >> 2) & 96);
      float c0[4] = {0, 0, 0, 0}, c1[4] = {0, 0, 0, 0}, c2[4] = {0, 0, 0, 0}, c3[4] = {0, 0, 0, 0};
      bar_sync(hf ? B_MEM1 : B_MEM0, 256);
      const float sc = __uint_as_float(lds32_i<SC_IN + 16>(sb)) * iw;
      static_for<0, 10>([&](auto T) {
        constexpr int p = 2 * T.value;
        uint32_t b0[4], b1[4];
        ldsm_x4_i<OFF_MEM + p * 512>(b0, mema); ldsm_x4_i<OFF_MEM + p * 512 + 512>(b1, mema);
        mma16816h(c0, w[2 * p], b0[0], b0[1]); mma16816h(c1, w[2 * p + 1], b0[2], b0[3]);
        mma16816h(c2, w[2 * p + 2], b1[0], b1[1]); mma16816h(c3, w[2 * p + 3], b1[2], b1[3]);
      });
      stsm_x2_t_i<OFF_KV + 2 * KVB + 512>(l16 + (l16 & 128) * 4 + wi * 1280 + hf * KVB, pack_bf16(((c0[0] + c1[0]) + (c2[0] + c3[0])) * sc, ((c0[1] + c1[1]) + (c2[1] + c3[1])) * sc),
                                          pack_bf16(((c0[2] + c1[2]) + (c2[2] + c3[2])) * sc, ((c0[3] + c1[3]) + (c2[3] + c3[3])) * sc));
      fence_proxy_async();
    }
    bar_arrive(B_RED, 384);
    asm volatile("barrier.cluster.arrive.relaxed.aligned; barrier.cluster.wait.aligned;" ::: "memory");
  }
}
struct PrepArgs { const bf16 *wqkv, *wphi, *wo; unsigned char *wb, *wot; };
__device__ __forceinline__ void prep_body(const int cta, const PrepArgs& pa) {
  const int tid = threadIdx.x, lane = tid & 31, warp = tid >> 5, g = lane >> 2, q = lane & 3;
  const int pair = cta >> 1, which = cta & 1;
  uint32_t bfr[2][3][3];
#pragma unroll
  for (int hh = 0; hh < 2; hh++)
#pragma unroll
    for (int t = 0; t < 3; t++) {
      const unsigned short* ph = (const unsigned short*)pa.wphi + (2 * pair + hh) * 400 + (t < 2 ? 8 * t + g : 16 + (g >> 1)) + 2 * q * 20;
#pragma unroll
      for (int r = 0; r < 3; r++) {
        const int o = (r < 2 || q < 2) ? r * 160 : 0;
        const uint32_t v = (uint32_t)__ldg(ph + o) | ((uint32_t)__ldg(ph + o + 20) << 16);
        bfr[hh][t][r] = ((t < 2 || (g & 1) == hh) && (r < 2 || q < 2)) ? v : 0u;
      }
    }
  const int gt = cta * 256 + tid;
#pragma unroll 1
  for (int i = 0; i < 5; i++) {
    uint32_t af[2][6];
#pragma unroll
    for (int hh = 0; hh < 2; hh++) {
      const uint32_t* r0 = (const uint32_t*)(pa.wqkv + (size_t)((warp * 5 + i) * 16 + g) * 1920 + which * 640 + (2 * pair + hh) * 20) + q;
      af[hh][0] = __ldg(r0); af[hh][1] = __ldg(r0 + 7680); af[hh][2] = __ldg(r0 + 4); af[hh][3] = __ldg(r0 + 7684);
      af[hh][4] = __ldg(r0 + 8); af[hh][5] = __ldg(r0 + 7688);
    }
    const int iv = i * 4096 + (gt >> 1), k = (iv & 7) + (iv >> 8) * 8, h = (iv >> 3) & 31;
    const uint2* src = (const uint2*)(pa.wqkv + (size_t)k * 1920 + 1280 + h * 20) + (gt & 1) * 2;
    const uint2 a = __ldg(src), b = __ldg(src + 1), e = __ldg(src + 2);
    uint4 wv[2]; uint32_t wd[2];
#pragma unroll
    for (int n = 0; n < 2; n++) {
      const int iw = min((2 * i + n) * 5120 + gt, 640 * 80 - 1), r = iw & 7, c = (iw >> 3) % 80, kg = iw / 640, c5 = kg % 5;
      const int row = (kg / 5) * 40 + (c5 < 2 ? 8 * c5 + r : (c5 == 2 ? 16 + (r & 3) + (r >> 2) * 20 : 20 + 8 * (c5 - 3) + r));
      wv[n] = __ldg((const uint4*)(pa.wo + (size_t)row * cfg::DM + c * 8));
      wd[n] = (((c / 10) * 80 + kg) * 10 + c % 10) * 128 + r * 16;
    }
    uint4* dv = (uint4*)(pa.wb + ((size_t)((h >> 2) * 80 + (k >> 3)) * 32 + 20 + 3 * (h & 3)) * 128 + (k & 7) * 16);
    dv[(gt & 1) * 8] = make_uint4(a.x, a.y, b.x, b.y);
    if (gt & 1) dv[16] = (h & 1) ? make_uint4(0, 0, e.x, e.y) : make_uint4(e.x, e.y, 0, 0);
    if (gt < 5120) { *(uint4*)(pa.wot + wd[0]) = wv[0]; *(uint4*)(pa.wot + wd[1]) = wv[1]; }
    uint32_t* dst = (uint32_t*)(pa.wb + ((size_t)((pair >> 1) * 80 + (warp * 5 + i) * 2) * 32 + which * 10 + (pair & 1) * 5) * 128) + lane;
#pragma unroll
    for (int t = 0; t < 5; t++) {
      float d[4] = {0, 0, 0, 0};
#pragma unroll
      for (int hh = 0; hh < 2; hh++)
        if (t == 2 || (t > 2) == (hh == 1)) {
          const int tt = t < 3 ? t : t - 3;
          mma16816(d, af[hh][0], af[hh][1], af[hh][2], af[hh][3], bfr[hh][tt][0], bfr[hh][tt][1]);
          mma1688(d, q < 2 ? af[hh][4] : 0u, q < 2 ? af[hh][5] : 0u, bfr[hh][tt][2]);
        }
      dst[t * 32] = pack_bf16(d[0], d[1]); dst[1024 + t * 32] = pack_bf16(d[2], d[3]);
    }
  }
}

__global__ void __launch_bounds__(256, 4) ln_kernel(const bf16* __restrict__ xin, bf16* __restrict__ xn, uint2* __restrict__ xh, uint4* __restrict__ z0, int n0,
                                                    uint4* __restrict__ z1, int n1, const bf16* pfa, const bf16* pfb, int npf, int tl) {
  asm volatile("griddepcontrol.wait;" ::: "memory");
  asm volatile("griddepcontrol.launch_dependents;" ::: "memory");
  const int warp = threadIdx.x >> 5, lane = threadIdx.x & 31;
  const int row = blockIdx.x * 8 + warp;
  uint2 xw[1][5];
#pragma unroll
  for (int i = 0; i < 5; i++) xw[0][i] = *(const uint2*)(xin + (size_t)row * cfg::DM + i * 128 + lane * 4);
  for (int i = blockIdx.x * 256 + threadIdx.x; i < n0; i += 256 * 256) z0[i] = make_uint4(0, 0, 0, 0);
  for (int i = blockIdx.x * 256 + threadIdx.x; i < n1; i += 256 * 256) z1[i] = make_uint4(0, 0, 0, 0);
  if (npf && xw[0][4].y != 0x7fc17fc1u) {
    for (int i = 0; i < npf; i++) {
      const uint32_t l = (uint32_t)i * 32768u + (blockIdx.x * 256 + threadIdx.x) / 2;
      if (l < cfg::DM * cfg::HD / 64) asm volatile("prefetch.global.L2 [%0];" :: "l"(((threadIdx.x & 1) ? pfa : pfb) + (size_t)l * 64) : "memory");
    }
  }
  ln_rows<1>(xw, row, lane, xn, xh);
}
struct Pipe { uint32_t stage, phase; };
template <int NS> __device__ __forceinline__ void pipe_adv(Pipe& p) { if (++p.stage == NS) { p.stage = 0; p.phase ^= 1; } }
__device__ __forceinline__ void wait_ge(const void* p, uint32_t target, uint32_t ns = 32) {
  int spin = 0;
  while (ld_acquire_u32(p) < target) { __nanosleep(ns); if (++spin > (1 << 21)) break; }
}
__device__ __forceinline__ void bulk_g2s_hint(uint32_t dst, const void* src, uint32_t bytes, uint32_t mb, uint64_t pol) {
  asm volatile("cp.async.bulk.shared::cluster.global.mbarrier::complete_tx::bytes.L2::cache_hint [%0], [%1], %2, [%3], %4;"
               :: "r"(dst), "l"(src), "r"(bytes), "r"(mb), "l"(pol) : "memory");
}
#define STAG 1
#define EF_KV 1
#define EF_O 1
__device__ __forceinline__ void fence_proxy_async_global() { asm volatile("fence.proxy.async.global;" ::: "memory"); }

namespace tr {
constexpr int NS = 4, STQ = 16384 + 24576, STO = 16384 + 40960;
constexpr int SEGB = 15360;
constexpr int OFF_K = NS * STQ;
constexpr int OFF_BAR = NS * STO;
constexpr int SMEM = OFF_BAR + 256;
static_assert(OFF_K + 4 * SEGB <= OFF_BAR && SMEM <= 232448, "smem");
enum { T_QA = 0, T_Q, T_A, T_OB, T_OS, T_L, T_END, T_P };
constexpr uint32_t C_QA = AR_CNT, C_O = AR_CNT + 64, C_Q = AR_CNT + 128, C_P = AR_CNT + 192;
constexpr int MAXITEMS = 1200;
struct Sched {
  uint8_t ks[16];
  uint8_t wide[16];
  uint8_t lrows[16];
  uint32_t n;
  int nqa;
  uint16_t item[MAXITEMS];
};
struct Args {
  const unsigned char *kg, *vg;
  unsigned char* o;
  uint4* qs;
  unsigned char* part;
  const bf16 *xin, *xq;
  bf16 *xout, *xn;
  unsigned char* arena;
  const unsigned* go;
  int tl;
  uint32_t nap, nap2;
  int pfprep, pfq, pfb;
};
}

template <int N0, int N1>
__device__ __forceinline__ void tr_mainloop(float (&a0)[N0 / 2], float (&a1)[N1 ? N1 / 2 : 1], Pipe& p, uint32_t sb, uint32_t full, uint32_t empty, int nkb, int wg) {
  using namespace tr;
  constexpr uint32_t ST = N1 ? STO : STQ;
  uint32_t prev = 0;
#pragma unroll
  for (int i = 0; i < N0 / 2; i++) a0[i] = 0.f;
  if constexpr (N1 > 0) {
#pragma unroll
    for (int i = 0; i < N1 / 2; i++) a1[i] = 0.f;
  }
#pragma unroll 1
  for (int kb = 0; kb < nkb; kb++) {
    mbar_wait(full + 8 * p.stage, p.phase);
    const uint32_t st = ((sb & 0x3FFFF) >> 4) + p.stage * (ST / 16), sa = st + wg * 512;
    wgmma_fence();
#pragma unroll
    for (int kk = 0; kk < 4; kk++) {
      const uint64_t da = desc16<16, 1024, 1>(sa, kk * 32);
      if constexpr (N0 == 192) wgmma_n192<0, 1>(a0, da, desc16<8192, 1024, 1>(st, 16384 + kk * 2048), (kb | kk) != 0);
      else wgmma_n128<0, 1>(a0, da, desc16<8192, 1024, 1>(st, 16384 + kk * 2048), (kb | kk) != 0);
      if constexpr (N1 > 0) wgmma_n128<0, 1>(a1, da, desc16<8192, 1024, 1>(st, 16384 + 24576 + kk * 2048), (kb | kk) != 0);
    }
    wgmma_commit();
    if (kb > 0) { wgmma_wait<1>(); mbar_arrive_if((threadIdx.x & 127) == 0, empty + 8 * prev); }
    prev = p.stage;
    pipe_adv<NS>(p);
  }
  wgmma_wait<0>();
  mbar_arrive_if((threadIdx.x & 127) == 0, empty + 8 * prev);
}
template <int N> __device__ __forceinline__ void stage_tiles(const float (&o)[N / 2], uint32_t base, int wi, int lane) {
  const uint32_t ra = base + (wi * 16 + (lane & 7) + 8 * ((lane >> 3) & 1)) * 128;
#pragma unroll
  for (int v = 0; v < N / 8; v += 2)
    stsm_x4(ra + (v >> 3) * 8192 + ((((v & 7) + (lane >> 4)) ^ (lane & 7)) << 4), pack_bf16(o[4 * v], o[4 * v + 1]), pack_bf16(o[4 * v + 2], o[4 * v + 3]),
            pack_bf16(o[4 * v + 4], o[4 * v + 5]), pack_bf16(o[4 * v + 6], o[4 * v + 7]));
}
__global__ void __launch_bounds__(384, 1) trail_kernel(const __grid_constant__ CUtensorMap tmX, const __grid_constant__ CUtensorMap tmQ,
                                                       const __grid_constant__ CUtensorMap tmWo5, const __grid_constant__ CUtensorMap tmWo2,
                                                       const __grid_constant__ CUtensorMap tmP, const __grid_constant__ CUtensorMap tmP4, const __grid_constant__ tr::Sched sc,
                                                       const __grid_constant__ tr::Args a, const __grid_constant__ PrepArgs pa) {
  using namespace tr;
  [[maybe_unused]] const int tl = a.tl;
  extern __shared__ __align__(1024) unsigned char smem_raw[];
  const uint32_t sb = smem_u32(smem_raw);
  const int warp = __shfl_sync(0xffffffffu, (int)threadIdx.x >> 5, 0), lane = threadIdx.x & 31;
  unsigned char* const arena = a.arena;
  const uint32_t full = sb + OFF_BAR, empty = full + 8 * NS, barK = empty + 8 * NS, barKfree = barK + 16, staged = barKfree + 16;
  const uint32_t kvrdy = staged + 32, mfull = kvrdy + 8, mempty = mfull + 16, mbox = mempty + 16;
  uint32_t go = 0;
  if (threadIdx.x == 256) go = ld_acquire_u32(a.go);
  if (threadIdx.x == 0) {
    for (int i = 0; i < NS; i++) { mbar_init(full + 8 * i, 1); mbar_init(empty + 8 * i, 2); }
    for (int i = 0; i < 2; i++) {
      mbar_init(barK + 8 * i, 1); mbar_init(barKfree + 8 * i, 1); mbar_init(staged + 16 * i, 4); mbar_init(staged + 16 * i + 8, 4);
      mbar_init(mfull + 8 * i, 1); mbar_init(mempty + 8 * i, 11);
    }
    mbar_init(kvrdy, 1);
    asm volatile("fence.mbarrier_init.release.cluster;" ::: "memory");
  }
  __syncthreads();
  Pipe mp{0, 0};
  auto next_item = [&]() -> uint32_t {
    uint32_t it;
    mbar_wait(mfull + 8 * mp.stage, mp.phase);
    asm volatile("ld.shared.u32 %0, [%1];" : "=r"(it) : "r"(mbox + 4 * mp.stage) : "memory");
    return it;
  };
  if (warp >= 8) {
    asm volatile("setmaxnreg.dec.sync.aligned.u32 40;");
    if (warp == 8) { go = __shfl_sync(0xffffffffu, go, 0); if (elect_one()) {
      Pipe p{0, 1};
      mp.phase = 1;
      uint32_t kph = 1, rph = 0, wide = 0, qdone = 0;
      prefetch_tmap(&tmX); prefetch_tmap(&tmQ); prefetch_tmap(&tmWo5); prefetch_tmap(&tmWo2); prefetch_tmap(&tmP); prefetch_tmap(&tmP4);
      const uint64_t ef = policy_evict_first();
      auto ld_kv = [&](uint32_t d, const void* s, uint32_t n, uint32_t mb) { if (EF_KV) bulk_g2s_hint(d, s, n, mb, ef); else bulk_g2s(d, s, n, mb); };
      auto ld_o = [&](uint32_t d, const void* s, uint32_t n, uint32_t mb) { if (EF_O) bulk_g2s_hint(d, s, n, mb, ef); else bulk_g2s(d, s, n, mb); };
      auto stage = [&](uint32_t bytes) -> uint32_t {
        mbar_wait(empty + 8 * p.stage, p.phase);
        mbar_expect_tx(full + 8 * p.stage, bytes);
        return sb + p.stage * (wide ? STO : STQ);
      };
      auto fetch = [&]() -> uint32_t { uint32_t v; asm volatile("atom.relaxed.gpu.global.add.u32 %0, [%1], 1;" : "=r"(v) : "l"(arena + AR_QUEUE) : "memory"); return v; };
      if (!go) wait_ge(a.go, 1, 200);
      fence_proxy_async_global();
      uint32_t next = fetch();
      while (true) {
        const uint32_t item = next;
        const uint32_t code = sc.item[min(item, sc.n)];
        const int type = (code >> 11) & 7, m = (code >> 7) & 15, k = code & 127;
        const bool late = code >> 14;
        auto done_wait = [&]() { mbar_wait(mempty + 8 * (mp.stage ^ 1), mp.stage ? mp.phase ^ 1 : mp.phase); };
        if (type == T_A && !((qdone >> m) & 1)) { wait_ge(arena + C_Q + m * 4, 64); qdone |= 1u << m; }
        if (type == T_OB && !wide) for (uint32_t i = 0; i < NS; i++) mbar_wait(empty + 8 * i, i >= p.stage ? p.phase : p.phase ^ 1);
        wide = type == T_OB;
        mbar_wait(mempty + 8 * mp.stage, mp.phase);
        asm volatile("st.shared.u32 [%0], %1;" :: "r"(mbox + 4 * mp.stage), "r"((p.stage << 24) | (type << 16) | (m << 8) | (k & 255)) : "memory");
        mbar_arrive(mfull + 8 * mp.stage);
        pipe_adv<2>(mp);
        if (type == T_END) break;
        if (type == T_P) { done_wait(); next = fetch(); continue; }
        if (type == T_L) {
          const int nr = sc.lrows[m], np = sc.ks[m];
          prefetch_l2(a.xin + (size_t)(m * 128 + k * 8 * nr) * cfg::DM, nr * 10240);
          wait_ge(arena + C_O + m * 4, np * (sc.wide[m] ? 4 : 10), m < 13 ? a.nap : 20);
          fence_proxy_async_global();
#pragma unroll 1
          for (int r = 0; r < nr; r++) {
            const int rg = m * 16 + k * nr + r;
#pragma unroll 1
            for (int q0 = 0; q0 <= np; q0 += 4) {
              const int n = min(4, np + 1 - q0);
              const uint32_t st = stage(n * 10240), fb = full + 8 * p.stage;
              if (q0 + 4 <= np) tma_load_4d(st, &tmP4, 0, rg & 7, (rg >> 3) * 10, q0, fb);
              else {
                bulk_g2s(st + (n - 1) * 10240, a.xin + (size_t)rg * 8 * cfg::DM, 10240, fb);
#pragma unroll 1
                for (int q = q0; q < np; q++) tma_load_4d(st + (q - q0) * 10240, &tmP, 0, rg & 7, (rg >> 3) * 10, q, fb);
              }
              pipe_adv<NS>(p);
            }
          }
          if (late) done_wait();
          next = fetch(); continue;
        }
        if (type <= T_A) {
          if (type != T_A)
#pragma unroll 1
            for (int kb = 0; kb < 10; kb++) {
              const uint32_t st = stage(STQ), fb = full + 8 * p.stage;
              tma_load_2d(st, &tmX, kb * 64, m * 128, fb);
              tma_load_3d(st + 16384, &tmQ, 0, kb * 64, k * 3, fb);
              pipe_adv<NS>(p);
              if (type == T_Q && kb == 8) next = fetch();
            }
          if (type != T_Q) {
            const size_t blk = ((size_t)m * 4 * 96 + k * 3) * 5120;
            kph ^= 1;
            mbar_wait(kvrdy, rph); rph ^= 1;
            if (!late) next = fetch();
            fence_proxy_async_global();
#pragma unroll 1
            for (int w = type == T_A ? 0 : 2; w < 4; w++) {
              const uint32_t st = stage(2 * SEGB), fb = full + 8 * p.stage;
              for (int sg = 0; sg < 2; sg++) ld_kv(st + sg * SEGB, (w < 2 ? a.kg : a.vg) + blk + (size_t)(2 * (w & 1) + sg) * (96 * 5120), SEGB, fb);
              pipe_adv<NS>(p);
            }
            if (late) { done_wait(); next = fetch(); }
          }
        } else {
          const int nn = wide ? 2 : 5, nb = wide ? 5 : 2, nt = k % nn, nkb = 96 / sc.ks[m], k0 = (k / nn) * nkb;
          const Pipe p0 = p;
          for (int kb = 0; kb < nkb; kb++) {
            if (wide && kb < NS && p.stage >= 2) { mbar_wait(barKfree, kph); mbar_wait(barKfree + 8, kph); }
            const uint32_t st = stage(16384 + nb * 8192), fb = full + 8 * p.stage;
            tma_load_3d(st + 16384, wide ? &tmWo5 : &tmWo2, 0, (k0 + kb) * 64, nt * nb, fb);
            if (kb >= NS) ld_o(st, a.o + ((size_t)m * 96 + k0 + kb) * 16384, 16384, fb);
            pipe_adv<NS>(p);
            if (kb == NS - 1 || (kb == nkb - 1 && nkb < NS)) {
              wait_ge(arena + C_QA + m * 4, 64, m < 14 ? a.nap : 32);
              fence_proxy_async_global();
              Pipe q = p0;
#pragma unroll 1
              for (int i = 0; i <= kb; i++) { ld_o(sb + q.stage * (wide ? STO : STQ), a.o + ((size_t)m * 96 + k0 + i) * 16384, 16384, full + 8 * q.stage); pipe_adv<NS>(q); }
            }
          }
          if (!late) next = fetch();
          for (int w = wide ? -(int)((2 - p.stage) & 3) : 0; w < 2; w++) { mbar_wait(empty + 8 * p.stage, p.phase); mbar_arrive(full + 8 * p.stage); pipe_adv<NS>(p); }
          kph ^= wide;
          if (late) { done_wait(); next = fetch(); }
        }
      }
    } } else if (warp < 11) { if (elect_one()) {
      const int w = warp - 9;
      uint32_t sph = 0;
      [[maybe_unused]] int nlog = 0;
      while (true) {
        const uint32_t it = next_item();
        const int type = (it >> 16) & 255, m = (it >> 8) & 255, k = it & 255;
        const uint32_t slot = mp.stage;
        pipe_adv<2>(mp);
        if (type == T_END) break;
        mbar_wait(staged + 16 * w + 8 * slot, (sph >> slot) & 1); sph ^= 1u << slot;
        mbar_arrive(mempty + 8 * slot);
        if (type == T_L) continue;
        if (type == T_QA || type == T_A) {
          for (int jj = 0; jj < 3; jj++) bulk_s2g(a.o + ((size_t)m * 96 + k * 3 + jj) * 16384 + w * 8192, sb + OFF_K + w * 2 * SEGB + jj * 8192, 8192);
          bulk_commit();
          bulk_wait<0>();
          mbar_arrive(barKfree + 8 * w);
        } else if (type == T_OB || type == T_OS) {
          const bool wide = type == T_OB;
          const int nn = wide ? 2 : 5, nb = wide ? 5 : 2;
          const uint32_t own = wide ? 2 + w : ((it >> 24) + 96 / sc.ks[m] + w) % NS;
          bulk_s2g(a.part + ((size_t)((k / nn) * 32 + m * 2 + w) * 10 + (k % nn) * nb) * 8192, sb + own * (wide ? STO : STQ), nb * 8192);
          bulk_commit();
          bulk_wait<0>();
          mbar_arrive(empty + 8 * own);
          if (wide && w) { mbar_arrive(barKfree); mbar_arrive(barKfree + 8); }
        }
        red_release_inc(arena + (type == T_Q ? C_Q : (type <= T_A ? C_QA : (type == T_P ? C_P : C_O))) + m * 4);
      }
    } } else if (elect_one()) {
      const uint64_t ef = policy_evict_first();
      uint32_t kph = 1;
      while (true) {
        const uint32_t it = next_item();
        const int type = (it >> 16) & 255, m = (it >> 8) & 255, k = it & 255;
        const uint32_t slot = mp.stage;
        pipe_adv<2>(mp);
        if (type == T_END) break;
        if ((type == T_QA || type == T_A) && m == a.pfprep) { prefetch_l2(pa.wqkv + k * 38400, 76800); prefetch_l2(pa.wo + k * 12800, 25600); }
        if ((type == T_QA || type == T_A) && m == a.pfb) { prefetch_l2(pa.wb + k * 81920, 81920); prefetch_l2(pa.wot + k * 25600, 25600); }
        if ((type == T_QA || type == T_A) && m == a.pfb + 1) { prefetch_l2(a.xn + k * 20480, 40960); prefetch_l2(a.xout + k * 20480, 40960); }
        if ((type == T_QA || type == T_A) && m < 15) {
          if (m + 1 < sc.nqa) prefetch_l2(a.xq + ((m + 1) * 128 + k * 4) * cfg::DM, 5120);
          else if (a.pfq) prefetch_l2(a.qs + ((size_t)(((m + 1) & 7) * 32 + k) * 12) * 256, 49152);
        }
        if (type == T_QA || type == T_A) {
          for (int spin = 0; spin < (1 << 21); spin++) {
            uint4 f;
            asm volatile("ld.acquire.gpu.global.v4.u32 {%0,%1,%2,%3}, [%4];" : "=r"(f.x), "=r"(f.y), "=r"(f.z), "=r"(f.w) : "l"(arena + prog_off(k, 0)) : "memory");
            if (min(min(f.x, f.y), f.z) >= (uint32_t)(4 * m + 4)) break;
            __nanosleep(m < 15 ? a.nap : a.nap2);
          }
          mbar_arrive(kvrdy);
          fence_proxy_async_global();
          const unsigned char* src = a.kg + ((size_t)m * 4 * 96 + k * 3) * 5120;
#pragma unroll 1
          for (int w = 0; w < 2; w++) {
            mbar_wait(barKfree + 8 * w, kph);
            if (type == T_A) { mbar_arrive(barK + 8 * w); continue; }
            mbar_expect_tx(barK + 8 * w, 2 * SEGB);
            for (int sg = 2 * w; sg < 2 * w + 2; sg++) { if (EF_KV) bulk_g2s_hint(sb + OFF_K + sg * SEGB, src + (size_t)sg * (96 * 5120), SEGB, barK + 8 * w, ef); else bulk_g2s(sb + OFF_K + sg * SEGB, src + (size_t)sg * (96 * 5120), SEGB, barK + 8 * w); }
          }
          kph ^= 1;
        } else if (type == T_OB) {
          mbar_wait(barKfree, kph); mbar_wait(barKfree + 8, kph);
          kph ^= 1;
        }
        mbar_arrive(mempty + 8 * slot);
      }
      if (blockIdx.x == gridDim.x - 1) asm volatile("griddepcontrol.wait;" ::: "memory");
    }
    return;
  }
  asm volatile("setmaxnreg.inc.sync.aligned.u32 232;");
  const int wg = warp >> 2, wi = warp & 3;
  const int g = lane >> 2, q4 = lane & 3;
  asm volatile("griddepcontrol.launch_dependents;" ::: "memory");
  Pipe p{0, 0};
  uint32_t kph = 0;
  auto own_slot = [&]() -> uint32_t {
    const uint32_t sA = p.stage, phA = p.phase; pipe_adv<NS>(p);
    const uint32_t sB = p.stage, phB = p.phase; pipe_adv<NS>(p);
    mbar_wait_if(wi == 0, full + 8 * (wg ? sA : sB), wg ? phA : phB);
    mbar_wait(full + 8 * (wg ? sB : sA), wg ? phB : phA);
    mbar_arrive_if((threadIdx.x & 127) == 0, empty + 8 * (wg ? sA : sB));
    return wg ? sB : sA;
  };
  while (true) {
    const uint32_t it = __shfl_sync(0xffffffffu, next_item(), 0);
    const int type = (it >> 16) & 255, m = (it >> 8) & 255, k = it & 255;
    mbar_arrive_if(lane == 0, mempty + 8 * mp.stage);
    const uint32_t done = staged + 16 * wg + 8 * mp.stage;
    pipe_adv<2>(mp);
    if (type == T_END) break;
    if (type == T_P) {
      prep_body(k, pa);
      bar_sync(3 + wg, 128);
      mbar_arrive_if(lane == 0, done);
      continue;
    }
    if (type == T_L) {
      const int nr = sc.lrows[m], np = sc.ks[m];
      const uint32_t po = (lane >> 4) * 1024 + warp * 128 + ((((lane >> 1) & 7) ^ warp) << 4) + (lane & 1) * 8;
#pragma unroll 1
      for (int r = 0; r < nr; r++) {
        uint2 xw[1][5]; float s[20];
#pragma unroll
        for (int i = 0; i < 20; i++) s[i] = 0.f;
#pragma unroll 1
        for (int q0 = 0; q0 <= np; q0 += 4) {
          const uint32_t st = sb + p.stage * STQ;
          mbar_wait(full + 8 * p.stage, p.phase);
          const int n = min(4, np - q0);
#pragma unroll 1
          for (int q = 0; q < n; q += 2) {
            uint2 t[5], u[5];
            const uint32_t pa_ = st + q * 10240 + po, keep = q + 1 < n ? ~0u : 0u;
            static_for<0, 5>([&](auto I) { t[I.value] = lds64_i<I.value * 2048>(pa_); u[I.value] = lds64_i<I.value * 2048 + 10240>(pa_); });
#pragma unroll
            for (int i = 0; i < 5; i++) {
              u[i].x &= keep; u[i].y &= keep;
              s[4 * i] += bf_lo(t[i].x) + bf_lo(u[i].x); s[4 * i + 1] += bf_hi(t[i].x) + bf_hi(u[i].x); s[4 * i + 2] += bf_lo(t[i].y) + bf_lo(u[i].y); s[4 * i + 3] += bf_hi(t[i].y) + bf_hi(u[i].y);
            }
          }
          if (n < 4) {
            static_for<0, 5>([&](auto I) { xw[0][I.value] = lds64_i<I.value * 256>(st + n * 10240 + warp * 1280 + lane * 8); });
            SFENCE2(st, xw[0][0].x ^ xw[0][1].x ^ xw[0][2].x ^ xw[0][3].x ^ xw[0][4].x);
          }
          bar_sync(3 + wg, 128);
          mbar_arrive_if((threadIdx.x & 127) == 0, empty + 8 * p.stage);
          pipe_adv<NS>(p);
        }
        const int row = (m * 16 + k * nr + r) * 8 + warp;
#pragma unroll
        for (int i = 0; i < 5; i++) {
          bf16r2(s[4 * i], s[4 * i + 1]); bf16r2(s[4 * i + 2], s[4 * i + 3]);
          xw[0][i] = make_uint2(pack_bf16(bf_lo(xw[0][i].x) + s[4 * i], bf_hi(xw[0][i].x) + s[4 * i + 1]), pack_bf16(bf_lo(xw[0][i].y) + s[4 * i + 2], bf_hi(xw[0][i].y) + s[4 * i + 3]));
          *(uint2*)(a.xout + (size_t)row * cfg::DM + i * 128 + lane * 4) = xw[0][i];
        }
        ln_rows<1>(xw, row, lane, a.xn, nullptr);
      }
      __syncwarp();
      mbar_arrive_if(lane == 0, done);
      continue;
    }
    if (type >= T_OB) {
      const int nkb = 96 / sc.ks[m];
      if (type == T_OB) {
        float a0[96], a1[64];
        tr_mainloop<192, 128>(a0, a1, p, sb, full, empty, nkb, wg);
        while (p.stage != 2) { mbar_wait_if(wi == 0, full + 8 * p.stage, p.phase); mbar_arrive_if((threadIdx.x & 127) == 0, empty + 8 * p.stage); pipe_adv<NS>(p); }
        const uint32_t st = sb + own_slot() * STO;
        stage_tiles<192>(a0, st, wi, lane); stage_tiles<128>(a1, st + 24576, wi, lane);
      } else {
        float a0[64], a1[1];
        tr_mainloop<128, 0>(a0, a1, p, sb, full, empty, nkb, wg);
        stage_tiles<128>(a0, sb + own_slot() * STQ, wi, lane);
      }
      fence_proxy_async();
      __syncwarp();
      mbar_arrive_if(lane == 0, done);
      continue;
    }
    uint32_t qf[12][4];
    uint4* qp = a.qs + ((size_t)((m & 7) * 32 + k) * 12) * 256 + threadIdx.x;
    if (type != T_A) {
      float acc[96], a1[1];
      tr_mainloop<192, 0>(acc, a1, p, sb, full, empty, 10, wg);
#pragma unroll
      for (int i = 0; i < 12; i++) {
        qf[i][0] = pack_bf16(acc[8 * i], acc[8 * i + 1]); qf[i][1] = pack_bf16(acc[8 * i + 2], acc[8 * i + 3]);
        qf[i][2] = pack_bf16(acc[8 * i + 4], acc[8 * i + 5]); qf[i][3] = pack_bf16(acc[8 * i + 6], acc[8 * i + 7]);
      }
      if (type == T_Q) {
#pragma unroll
        for (int i = 0; i < 12; i++) qp[i * 256] = make_uint4(qf[i][0], qf[i][1], qf[i][2], qf[i][3]);
        __syncwarp();
        mbar_arrive_if(lane == 0, done);
        continue;
      }
    } else {
#pragma unroll
      for (int i = 0; i < 12; i++) { const uint4 v = __ldcg(qp + i * 256); qf[i][0] = v.x; qf[i][1] = v.y; qf[i][2] = v.z; qf[i][3] = v.w; }
    }
    const uint32_t ost = sb + OFF_K + wg * 2 * SEGB;
    const bool second = wi >= 2;
    uint32_t pf[5][4];
    {
      float sa[20], sb2[20];
      uint32_t kbase = ost, kslot = 0;
      if (type == T_A) { kslot = own_slot(); kbase = sb + kslot * STQ; } else mbar_wait(barK + 8 * wg, kph);
      kbase = (kbase & 0x3FFFF) >> 4;
      if (STAG && wg) bar_sync(1, 256);
      wgmma_fence();
#pragma unroll
      for (int i = 0; i < 12; i++) {
        wgmma_rs_n40<0>(sa, qf[i][0], qf[i][1], qf[i][2], qf[i][3], desc16<640, 128, 0>(kbase, i * 1280), i != 0);
        wgmma_rs_n40<0>(sb2, qf[i][0], qf[i][1], qf[i][2], qf[i][3], desc16<640, 128, 0>(kbase, SEGB + i * 1280), i != 0);
      }
      wgmma_commit();
      if (STAG && !wg) bar_arrive(1, 256);
      wgmma_wait<0>();
      mbar_arrive_if(type == T_A && (threadIdx.x & 127) == 0, empty + 8 * kslot);
      const float cs = 0.07216878364870322f * 1.4426950408889634f;
      const int r0 = 16 * (wi & 1) + g, r1 = r0 + 8;
      float m0 = -INFINITY, m1 = -INFINITY;
#pragma unroll
      for (int n = 0; n < 5; n++) {
#pragma unroll
        for (int e = 0; e < 2; e++) {
          const int key = 8 * n + 2 * q4 + e;
          float x = second ? sb2[4 * n + e] : sa[4 * n + e], y = second ? sb2[4 * n + 2 + e] : sa[4 * n + 2 + e];
          if (n < 4) { if (key > r0) x = -INFINITY; if (key > r1) y = -INFINITY; }
          sa[4 * n + e] = x; sa[4 * n + 2 + e] = y;
          m0 = fmaxf(m0, x); m1 = fmaxf(m1, y);
        }
      }
      m0 = fmaxf(fmaxf(m0, __shfl_xor_sync(0xffffffffu, m0, 1)), fmaxf(__shfl_xor_sync(0xffffffffu, m0, 2), __shfl_xor_sync(0xffffffffu, m0, 3)));
      m1 = fmaxf(fmaxf(m1, __shfl_xor_sync(0xffffffffu, m1, 1)), fmaxf(__shfl_xor_sync(0xffffffffu, m1, 2), __shfl_xor_sync(0xffffffffu, m1, 3)));
      m0 *= -cs; m1 *= -cs;
      float s0 = 0.f, s1 = 0.f;
#pragma unroll
      for (int n = 0; n < 5; n++) {
#pragma unroll
        for (int e = 0; e < 2; e++) {
          sa[4 * n + e] = ex2f(fmaf(sa[4 * n + e], cs, m0)); sa[4 * n + 2 + e] = ex2f(fmaf(sa[4 * n + 2 + e], cs, m1));
          s0 += sa[4 * n + e]; s1 += sa[4 * n + 2 + e];
        }
      }
      s0 = (s0 + __shfl_xor_sync(0xffffffffu, s0, 1)) + (__shfl_xor_sync(0xffffffffu, s0, 2) + __shfl_xor_sync(0xffffffffu, s0, 3));
      s1 = (s1 + __shfl_xor_sync(0xffffffffu, s1, 1)) + (__shfl_xor_sync(0xffffffffu, s1, 2) + __shfl_xor_sync(0xffffffffu, s1, 3));
      const float i0 = rcpf(s0), i1 = rcpf(s1);
#pragma unroll
      for (int n = 0; n < 5; n++) {
        const uint32_t x = pack_bf16(sa[4 * n] * i0, sa[4 * n + 1] * i0), y = pack_bf16(sa[4 * n + 2] * i1, sa[4 * n + 3] * i1);
        if (n < 4) {
          pf[n >> 1][2 * (n & 1)] = second ? 0u : x; pf[n >> 1][2 * (n & 1) + 1] = second ? 0u : y;
          pf[2 + (n >> 1)][2 * (n & 1)] = second ? x : 0u; pf[2 + (n >> 1)][2 * (n & 1) + 1] = second ? y : 0u;
        } else {
          pf[4][0] = second ? 0u : x; pf[4][1] = second ? 0u : y; pf[4][2] = second ? x : 0u; pf[4][3] = second ? y : 0u;
        }
      }
    }
    {
      float o[96];
#pragma unroll
      for (int i = 0; i < 5; i++) { PIN(pf[i][0]); PIN(pf[i][1]); PIN(pf[i][2]); PIN(pf[i][3]); }
      const uint32_t own = own_slot(), vbase = ((sb & 0x3FFFF) >> 4) + own * (STQ / 16);
      wgmma_fence();
#pragma unroll
      for (int i = 0; i < 5; i++)
        wgmma_rs_n192<1>(o, pf[i][0], pf[i][1], pf[i][2], pf[i][3], i < 4 ? desc16<128, 640, 0>(vbase, (i >> 1) * SEGB + (i & 1) * 256) : desc16<SEGB, 640, 0>(vbase, 512), i != 0);
      wgmma_commit();
      if (type == T_A) mbar_wait(barK + 8 * wg, kph);
      kph ^= 1;
      wgmma_wait<0>();
      mbar_arrive_if((threadIdx.x & 127) == 0, empty + 8 * own);
      stage_tiles<192>(o, ost, wi, lane);
      fence_proxy_async();
      __syncwarp();
      mbar_arrive_if(lane == 0, done);
    }
  }
}
namespace bf {
constexpr int NS = 4, STAGE = 16384 + 32768;
constexpr int PIECE = 20480;
constexpr int OFF_PHI = 0, OFF_V = 40960, OFF_KV = 65536;
constexpr int OFF_OST = 5 * PIECE;
constexpr int OFF_WOT = 6 * PIECE;
constexpr int OFF_BAR = OFF_WOT + 102400;
constexpr int SMEM = OFF_BAR + 256;
static_assert(NS * STAGE <= OFF_BAR && SMEM <= 232448, "smem");
constexpr int KVACC = 32 * 5 * 1024;
struct Args {
  const unsigned char *wb, *wot;
  unsigned char *kvacc, *o2;
  const bf16* xin;
  bf16* xout;
  unsigned* go;
  const void* prep;
  const bf16 *pf0, *pf1;
  int pfn, pfns, pfwait;
  int tl;
};
}
__device__ __forceinline__ void hedgehog_features(float (&x)[2][5], uint32_t (&w)[2][5]) {
  const float L = 1.4426950408889634f;
  float mx[2], mn[2], sp[2], sn[2], pos[2][5], neg[2][5];
#pragma unroll
  for (int r = 0; r < 2; r++) {
    mx[r] = fmaxf(fmaxf(fmaxf(x[r][0], x[r][1]), fmaxf(x[r][2], x[r][3])), x[r][4]);
    mn[r] = fminf(fminf(fminf(x[r][0], x[r][1]), fminf(x[r][2], x[r][3])), x[r][4]);
  }
#pragma unroll
  for (int o = 1; o < 4; o <<= 1)
#pragma unroll
    for (int r = 0; r < 2; r++) {
      const uint32_t t = __shfl_xor_sync(0xffffffffu, __byte_perm(__float_as_uint(mn[r]), __float_as_uint(mx[r]), 0x7632), o);
      mx[r] = fmaxf(mx[r], bf_hi(t)); mn[r] = fminf(mn[r], bf_lo(t));
    }
#pragma unroll
  for (int r = 0; r < 2; r++) {
#pragma unroll
    for (int i = 0; i < 5; i++) { pos[r][i] = ex2f((x[r][i] - mx[r]) * L); neg[r][i] = ex2f((mn[r] - x[r][i]) * L); }
    sp[r] = ((pos[r][0] + pos[r][1]) + (pos[r][2] + pos[r][3])) + pos[r][4];
    sn[r] = ((neg[r][0] + neg[r][1]) + (neg[r][2] + neg[r][3])) + neg[r][4];
  }
#pragma unroll
  for (int o = 1; o < 4; o <<= 1)
#pragma unroll
    for (int r = 0; r < 2; r++) { sp[r] += __shfl_xor_sync(0xffffffffu, sp[r], o); sn[r] += __shfl_xor_sync(0xffffffffu, sn[r], o); }
#pragma unroll
  for (int r = 0; r < 2; r++) {
    const float ip = rcpf(sp[r]), in_ = rcpf(sn[r]);
    w[r][0] = pack_bf16(pos[r][0] * ip, pos[r][1] * ip); w[r][1] = pack_bf16(pos[r][2] * ip, pos[r][3] * ip);
    w[r][2] = pack_bf16(neg[r][0] * in_, neg[r][1] * in_); w[r][3] = pack_bf16(neg[r][2] * in_, neg[r][3] * in_);
    w[r][4] = pack_bf16(pos[r][4] * ip, neg[r][4] * in_);
  }
}
__device__ __forceinline__ void bulk_g2s_mc(uint32_t dst, const void* src, uint32_t bytes, uint32_t mb) {
  asm volatile("cp.async.bulk.shared::cluster.global.mbarrier::complete_tx::bytes.multicast::cluster [%0], [%1], %2, [%3], %4;"
               :: "r"(dst), "l"(src), "r"(bytes), "r"(mb), "h"((unsigned short)3) : "memory");
}
__device__ __forceinline__ void mbar_arrive_remote_if(bool c, uint32_t b) {
  asm volatile("{\n.reg .pred p;\nsetp.ne.u32 p, %1, 0;\n@p mbarrier.arrive.shared::cluster.b64 _, [%0];\n}" :: "r"(b), "r"((uint32_t)c) : "memory");
}

__global__ void __cluster_dims__(2, 1, 1) __launch_bounds__(384, 1) blayer_kernel(const __grid_constant__ CUtensorMap tmA, const __grid_constant__ bf::Args a) {
  using namespace bf;
  [[maybe_unused]] const int tl = a.tl;
  extern __shared__ __align__(1024) unsigned char smem_raw[];
  const uint32_t sb = smem_u32(smem_raw);
  const int warp = __shfl_sync(0xffffffffu, (int)threadIdx.x >> 5, 0), lane = threadIdx.x & 31;
  const uint32_t full = sb + OFF_BAR, empty = full + 8 * NS, full2 = empty + 8 * NS, empty2 = full2 + 64, barW = empty2 + 16, drained = barW + 8, staged = drained + 8, freeb = staged + 8;
  const int rank = blockIdx.x & 1, u = (blockIdx.x >> 1) & 7, mp = blockIdx.x >> 4;
  const int m = 2 * mp + rank;
  const int m2 = 2 * mp + (u & 1), ns = (u & ~1) + rank;
  const uint32_t dpeer = mapa_u32(sb, rank ^ 1) - sb;
  unsigned* cntO = (unsigned*)(a.kvacc + KVACC);
  if (threadIdx.x == 0) {
    for (int i = 0; i < NS; i++) { mbar_init(full + 8 * i, 1); mbar_init(empty + 8 * i, 4); }
    for (int i = 0; i < 8; i++) mbar_init(full2 + 8 * i, 1);
    mbar_init(empty2, 2); mbar_init(empty2 + 8, 2);
    mbar_init(barW, 1); mbar_init(drained, 1); mbar_init(staged, 8); mbar_init(freeb, 2);
    asm volatile("fence.mbarrier_init.release.cluster;" ::: "memory");
  }
  __syncthreads();
  asm volatile("barrier.cluster.arrive.relaxed.aligned; barrier.cluster.wait.aligned;" ::: "memory");
  if (warp >= 8) {
    asm volatile("setmaxnreg.dec.sync.aligned.u32 40;");
    if (warp == 8) { if (elect_one()) {
      const unsigned char* wsrc = a.wb + (size_t)u * 327680 + rank * 16384;
      if (a.prep) wait_ge(a.prep, 64);
      fence_proxy_async_global();
      for (int kb = 0; kb < NS; kb++) {
        mbar_expect_tx(full + 8 * kb, STAGE);
        bulk_g2s_mc(sb + kb * STAGE + 16384 + rank * 16384, wsrc + kb * 32768, 16384, full + 8 * kb);
      }
      asm volatile("griddepcontrol.wait;" ::: "memory");
      if (blockIdx.x == 0) *a.go = 0;
      for (int kb = 0; kb < NS; kb++) tma_load_2d(sb + kb * STAGE, &tmA, kb * 64, m * 128, full + 8 * kb);
      if (m == 0) prefetch_l2(a.kvacc + u * (KVACC / 8), KVACC / 8);
#pragma unroll 1
      for (int kb = NS; kb < 10; kb++) {
        const uint32_t s = kb & 3, st = sb + s * STAGE, fb = full + 8 * s;
        mbar_wait(empty + 8 * s, ((kb >> 2) - 1) & 1);
        mbar_expect_tx(fb, STAGE);
        tma_load_2d(st, &tmA, kb * 64, m * 128, fb);
        bulk_g2s_mc(st + 16384 + rank * 16384, wsrc + kb * 32768, 16384, fb);
      }
      for (int i = 0; i < 6; i++) mbar_expect_tx(full2 + 8 * i, PIECE);
      mbar_wait(drained, 0);
      mbar_expect_tx(barW, 102400);
      bulk_g2s(sb + OFF_WOT, a.wot + (size_t)ns * 102400, 102400, barW);
      mbar_wait(staged, 0);
      bulk_s2g(a.o2 + (size_t)(m * 8 + u) * PIECE, sb + OFF_OST, PIECE);
      bulk_commit();
      bulk_wait<0>();
      mbar_arrive(freeb); mbar_arrive_remote_if(true, freeb + dpeer);
      red_release_inc(cntO + m);
      wait_ge(cntO + m2, 8, 20);
      mbar_wait(freeb, 0);
      fence_proxy_async_global();
      const unsigned char* osrc = a.o2 + (size_t)m2 * 8 * PIECE;
      for (int i = 0; i < 6; i++) bulk_g2s_mc(sb + i * PIECE + rank * (PIECE / 2), osrc + i * PIECE + rank * (PIECE / 2), PIECE / 2, full2 + 8 * i);
      for (int i = 0; i < 2; i++) {
        mbar_wait(empty2 + 8 * i, 0);
        mbar_expect_tx(full2 + 8 * (6 + i), PIECE);
        bulk_g2s(sb + i * PIECE, osrc + (6 + i) * PIECE, PIECE, full2 + 8 * (6 + i));
      }
    } } else if (warp == 9 && a.pf0) { if (elect_one()) {
      if (a.pfwait) asm volatile("griddepcontrol.wait;" ::: "memory");
      constexpr uint32_t CH = 2048;
      for (int i = 0; i < a.pfn; i++) {
        prefetch_l2((const unsigned char*)a.pf0 + (i * 128 + blockIdx.x) * CH, CH); prefetch_l2((const unsigned char*)a.pf1 + (i * 128 + blockIdx.x) * CH, CH);
        __nanosleep(a.pfns);
      }
    } }
    return;
  }
  asm volatile("setmaxnreg.inc.sync.aligned.u32 232;");
  const int wg = warp >> 2, wi = warp & 3;
  const int q4 = lane & 3;
  const bool lead = (threadIdx.x & 127) == 0;
  const uint32_t s16 = (sb & 0x3FFFF) >> 4;
  float acc[128];
  {
#pragma unroll 1
    for (int kb = 0; kb < 10; kb++) {
      const uint32_t s = kb & 3, st = s16 + s * (STAGE / 16);
      mbar_wait(full + 8 * s, (kb >> 2) & 1);
      wgmma_fence();
#pragma unroll
      for (int kk = 0; kk < 4; kk++) wgmma_n256<0, 1>(acc, desc16<16, 1024, 1>(st + wg * 512, kk * 32), desc16<4096, 128, 0>(st, 16384 + kk * 8192), (kb | kk) != 0);
      wgmma_commit();
      if (kb > 0 && kb < 7) { wgmma_wait<1>(); const uint32_t e = empty + 8 * ((kb - 1) & 3); mbar_arrive_if(lead, e); mbar_arrive_remote_if(lead, e + dpeer); }
    }
    wgmma_wait<0>();
    bar_sync(1, 256);
    mbar_arrive_if(threadIdx.x == 0, drained);
  }
  const uint32_t srow = (wg * 64 + wi * 16 + (lane & 15)) * 16 + (lane >> 4) * 2048;
  auto features = [&](auto T0, auto HH, uint32_t (&w)[2][5]) {
    constexpr int t = T0.value + 5 * (HH.value >> 1), o = (HH.value & 1) ? 3 : 0, e = HH.value & 1;
    float x[2][5];
#pragma unroll
    for (int r = 0; r < 2; r++) {
      x[r][0] = acc[4 * (t + o) + 2 * r]; x[r][1] = acc[4 * (t + o) + 2 * r + 1]; x[r][2] = acc[4 * (t + o + 1) + 2 * r]; x[r][3] = acc[4 * (t + o + 1) + 2 * r + 1];
      bf16r2(x[r][0], x[r][1]); bf16r2(x[r][2], x[r][3]);
    }
    x[0][4] = acc[4 * (t + 2) + e]; x[1][4] = acc[4 * (t + 2) + 2 + e];
    bf16r2(x[0][4], x[1][4]);
    hedgehog_features(x, w);
  };
  static_for<0, 4>([&](auto HH) {
    constexpr int hh = HH.value, t = 20 + 3 * hh;
    const uint32_t one = q4 == ((hh & 1) ? 0 : 2) ? 0x3f80u : 0u;
    const uint32_t va = sb + OFF_V + hh * 6144 + srow;
    stsm_x4(va, pack_bf16(acc[4 * t], acc[4 * t + 1]), pack_bf16(acc[4 * t + 2], acc[4 * t + 3]), pack_bf16(acc[4 * t + 4], acc[4 * t + 5]), pack_bf16(acc[4 * t + 6], acc[4 * t + 7]));
    const bool pad = (q4 >= 2) != (hh & 1);
    stsm_x2(va + 4096, pad ? one : pack_bf16(acc[4 * t + 8], acc[4 * t + 9]), pad ? one : pack_bf16(acc[4 * t + 10], acc[4 * t + 11]));
    uint32_t w[2][5];
    features(IC<10>{}, HH, w);
    const uint32_t pa = sb + OFF_PHI + hh * 10240 + srow;
    stsm_x4(pa, w[0][0], w[1][0], w[0][1], w[1][1]);
    stsm_x4(pa + 4096, w[0][2], w[1][2], w[0][3], w[1][3]);
    stsm_x2(pa + 8192, w[0][4], w[1][4]);
  });
  fence_proxy_async();
  bar_sync(1, 256);
  {
    float d0[12], d1[12];
    const uint32_t pa = s16 + wg * 1280, pv = s16 + wg * 768;
    wgmma_fence();
#pragma unroll
    for (int k = 0; k < 8; k++) {
      wgmma_n24<1, 1>(d0, desc16<128, 2048, 0>(pa, OFF_PHI + k * 256), desc16<128, 2048, 0>(pv, OFF_V + k * 256), k != 0);
      wgmma_n24<1, 1>(d1, desc16<128, 2048, 0>(pa, OFF_PHI + 10240 + k * 256), desc16<128, 2048, 0>(pv, OFF_V + 6144 + k * 256), k != 0);
    }
    wgmma_commit();
    wgmma_wait<0>();
    unsigned char* dst = a.kvacc + ((u * 4 + wg * 2) * 5 + 2 * wi) * 1024 + lane * 16;
    auto red4 = [&](bool on, unsigned char* p, float x, float y, float z) {
      asm volatile("{\n.reg .pred p;\nsetp.ne.u32 p, %4, 0;\n@p red.relaxed.gpu.global.add.v4.f32 [%0], {%1,%2,%3,%5};\n}" :: "l"(p), "f"(x), "f"(y), "f"(z), "r"((uint32_t)on), "f"(1.f) : "memory");
    };
    red4(wi < 3, dst, d0[0], d0[1], d0[4]); red4(wi < 3, dst + 512, d0[5], d0[8], d0[9]);
    red4(wi < 3, dst + 5120, d1[0], d1[1], d1[4]); red4(wi < 3, dst + 5632, d1[5], d1[8], d1[9]);
    red4(wi < 2, dst + 1024, d0[2], d0[3], d0[6]); red4(wi < 2, dst + 1536, d0[7], d0[10], d0[11]);
    red4(wi < 2, dst + 6144, d1[2], d1[3], d1[6]); red4(wi < 2, dst + 6656, d1[7], d1[10], d1[11]);
  }
  uint32_t qf[4][2][5];
  static_for<0, 4>([&](auto HH) { features(IC<0>{}, HH, qf[HH.value]); });
  uint4 xr[5];
#pragma unroll
  for (int i = 0; i < 5; i++) {
    const int c = lane + 32 * i;
    xr[i] = __ldcg((const uint4*)(a.xin + (size_t)(m2 * 128 + wg * 64 + wi * 16 + c / 10) * cfg::DM + ns * 80 + (c % 10) * 8));
  }
  {
    const unsigned char* src = a.kvacc + (u * 20 + warp) * 1024 + lane * 16;
    uint4 v[6];
    int spin = 0;
    while (true) {
      v[0] = ld_relaxed_v4_i<0>(src); v[1] = ld_relaxed_v4_i<512>(src); v[2] = ld_relaxed_v4_i<8192>(src); v[3] = ld_relaxed_v4_i<8704>(src);
      v[4] = ld_relaxed_v4_i<0>(src + (wg ? 0 : 16384)); v[5] = ld_relaxed_v4_i<512>(src + (wg ? 0 : 16384));
      const uint32_t c = (v[0].w & v[1].w & v[2].w) & (v[3].w & v[4].w & v[5].w);
      if (!__any_sync(0xffffffffu, (c & 0x41800000u) != 0x41800000u) || ++spin >= SPIN_LIMIT) break;
      __nanosleep(100);
    }
    const uint32_t kd = sb + OFF_KV + warp * 384 + lane * 4;
#pragma unroll
    for (int i = 0; i < 3; i++)
      if (i < 2 || wg == 0) {
        sts32(kd + i * 3072, pack_bf16(__uint_as_float(v[2 * i].x), __uint_as_float(v[2 * i].y)));
        sts32(kd + i * 3072 + 128, pack_bf16(__uint_as_float(v[2 * i].z), __uint_as_float(v[2 * i + 1].x)));
        sts32(kd + i * 3072 + 256, pack_bf16(__uint_as_float(v[2 * i + 1].y), __uint_as_float(v[2 * i + 1].z)));
      }
  }
  fence_proxy_async();
  bar_sync(1, 256);
  {
    float d[4][12];
    uint32_t zero = 0; PIN(zero);
#pragma unroll
    for (int hh = 0; hh < 4; hh++)
#pragma unroll
      for (int i = 0; i < 5; i++) { PIN(qf[hh][0][i]); PIN(qf[hh][1][i]); }
    wgmma_fence();
#pragma unroll
    for (int hh = 0; hh < 4; hh++) {
      const uint32_t kb = OFF_KV + hh * 1920;
      wgmma_rs_n24<1>(d[hh], qf[hh][0][0], qf[hh][1][0], qf[hh][0][1], qf[hh][1][1], desc16<384, 128, 0>(s16, kb), 0);
      wgmma_rs_n24<1>(d[hh], qf[hh][0][2], qf[hh][1][2], qf[hh][0][3], qf[hh][1][3], desc16<384, 128, 0>(s16, kb + 768), 1);
      wgmma_rs_n24<1>(d[hh], qf[hh][0][4], qf[hh][1][4], zero, zero, desc16<0, 128, 0>(s16, kb + 1536), 1);
    }
    wgmma_commit();
    wgmma_wait<0>();
    uint32_t ow[4][6];
#pragma unroll
    for (int hh = 0; hh < 4; hh++) {
      const int zl = (lane & ~3) | ((hh & 1) ? 0 : 2);
      const float da = bf16r(bf16r(__shfl_sync(0xffffffffu, d[hh][8], zl)) + 1e-6f), db = bf16r(bf16r(__shfl_sync(0xffffffffu, d[hh][10], zl)) + 1e-6f);
#pragma unroll
      for (int n = 0; n < 3; n++) {
        bf16r2(d[hh][4 * n], d[hh][4 * n + 1]); bf16r2(d[hh][4 * n + 2], d[hh][4 * n + 3]);
        ow[hh][2 * n] = pack_bf16(__fdividef(d[hh][4 * n], da), __fdividef(d[hh][4 * n + 1], da));
        ow[hh][2 * n + 1] = pack_bf16(__fdividef(d[hh][4 * n + 2], db), __fdividef(d[hh][4 * n + 3], db));
      }
    }
#pragma unroll
    for (int p = 0; p < 2; p++) {
      const uint32_t oa = sb + OFF_OST + p * 10240 + srow;
      stsm_x4(oa, ow[2 * p][0], ow[2 * p][1], ow[2 * p][2], ow[2 * p][3]);
      stsm_x2(oa + 4096, q4 < 2 ? ow[2 * p][4] : ow[2 * p + 1][4], q4 < 2 ? ow[2 * p][5] : ow[2 * p + 1][5]);
      stsm_x4(oa + 6144, ow[2 * p + 1][0], ow[2 * p + 1][1], ow[2 * p + 1][2], ow[2 * p + 1][3]);
    }
    fence_proxy_async();
    __syncwarp();
    mbar_arrive_if(lane == 0, staged);
  }
  float c2[40];
  mbar_wait(barW, 0);
#pragma unroll 1
  for (int i = 0; i < 8; i++) {
    mbar_wait(full2 + 8 * i, 0);
    const uint32_t st = s16 + (i < 6 ? i : i - 6) * (PIECE / 16) + wg * 64, wo = s16 + i * 800;
    wgmma_fence();
#pragma unroll
    for (int kk = 0; kk < 5; kk++) wgmma_n80<0, 1>(c2, desc16<2048, 128, 0>(st, kk * 4096), desc16<1280, 128, 0>(wo, OFF_WOT + kk * 2560), (i | kk) != 0);
    wgmma_commit();
    if (i == 1 || i == 2) { wgmma_wait<1>(); mbar_arrive_if(lead, empty2 + 8 * (i - 1)); }
  }
  wgmma_wait<0>();
  {
    bar_sync(1, 256);
    const uint32_t ost = sb + 2 * PIECE + warp * 3072;
#pragma unroll
    for (int v = 0; v < 10; v += 2)
      stsm_x4(ost + (lane & 15) * 176 + (v + (lane >> 4)) * 16, pack_bf16(c2[4 * v], c2[4 * v + 1]), pack_bf16(c2[4 * v + 2], c2[4 * v + 3]),
              pack_bf16(c2[4 * v + 4], c2[4 * v + 5]), pack_bf16(c2[4 * v + 6], c2[4 * v + 7]));
    __syncwarp();
#pragma unroll
    for (int i = 0; i < 5; i++) {
      const int c = lane + 32 * i, row = c / 10, chunk = c % 10;
      const uint4 y = lds128(ost + row * 176 + chunk * 16);
      const size_t off = (size_t)(m2 * 128 + wg * 64 + wi * 16 + row) * cfg::DM + ns * 80 + chunk * 8;
      const uint4 x = xr[i];
      *(uint4*)(a.xout + off) = make_uint4(pack_bf16(bf_lo(x.x) + bf_lo(y.x), bf_hi(x.x) + bf_hi(y.x)), pack_bf16(bf_lo(x.y) + bf_lo(y.y), bf_hi(x.y) + bf_hi(y.y)),
                                           pack_bf16(bf_lo(x.z) + bf_lo(y.z), bf_hi(x.z) + bf_hi(y.z)), pack_bf16(bf_lo(x.w) + bf_lo(y.w), bf_hi(x.w) + bf_hi(y.w)));
    }
  }
}
__device__ __align__(32768) unsigned char g_arena[AR_SIZE];
__device__ unsigned g_go[32];
__device__ __align__(1024) uint2 g_xh[2048 * 160];
__device__ __align__(1024) unsigned char g_k[64 * 96 * 5120], g_v[64 * 96 * 5120];
__device__ __align__(1024) bf16 g_o[2048 * 6144];
__device__ __align__(1024) uint4 g_qs[8 * 32 * 12 * 256];
__device__ __align__(1024) bf16 g_xn[2048 * 640], g_xn2[2048 * 640], g_xa[2048 * 640], g_xb[2048 * 640];
__device__ __align__(1024) bf16 g_part[24 * 2048 * 640];
__device__ __align__(1024) bf16 g_wb[2048 * 640], g_wot[640 * 640], g_pq[2048 * 640];
__device__ __align__(1024) float g_kvacc[bf::KVACC / 4 + 64];

typedef CUresult (*EncodeFn)(CUtensorMap*, CUtensorMapDataType, cuuint32_t, void*, const cuuint64_t*, const cuuint64_t*, const cuuint32_t*,
                             const cuuint32_t*, CUtensorMapInterleave, CUtensorMapSwizzle, CUtensorMapL2promotion, CUtensorMapFloatOOBfill);
static EncodeFn g_encode = nullptr;
static CUtensorMap make_map(const void* p, uint64_t cols, uint64_t rows, uint32_t bc, uint32_t br, bool swz = true) {
  CUtensorMap m;
  cuuint64_t dims[2] = {cols, rows}, strides[1] = {cols * 2};
  cuuint32_t box[2] = {bc, br}, es[2] = {1, 1};
  g_encode(&m, CU_TENSOR_MAP_DATA_TYPE_BFLOAT16, 2, const_cast<void*>(p), dims, strides, box, es, CU_TENSOR_MAP_INTERLEAVE_NONE,
           swz ? CU_TENSOR_MAP_SWIZZLE_128B : CU_TENSOR_MAP_SWIZZLE_NONE, CU_TENSOR_MAP_L2_PROMOTION_L2_256B, CU_TENSOR_MAP_FLOAT_OOB_FILL_NONE);
  return m;
}
static CUtensorMap make_map3(const void* p, uint64_t cols, uint64_t rows, uint32_t nb) {
  CUtensorMap m;
  cuuint64_t dims[3] = {64, rows, cols / 64}, strides[2] = {cols * 2, 128};
  cuuint32_t box[3] = {64, 64, nb}, es[3] = {1, 1, 1};
  g_encode(&m, CU_TENSOR_MAP_DATA_TYPE_BFLOAT16, 3, const_cast<void*>(p), dims, strides, box, es, CU_TENSOR_MAP_INTERLEAVE_NONE,
           CU_TENSOR_MAP_SWIZZLE_128B, CU_TENSOR_MAP_L2_PROMOTION_L2_256B, CU_TENSOR_MAP_FLOAT_OOB_FILL_NONE);
  return m;
}

struct Ptrs {
  unsigned char *arena, *k, *v; bf16 *o, *xn, *xa, *xb, *wb, *wot, *pq; float *part, *kvacc; uint2* xh; uint4* qs; bf16* xn2; unsigned* go;
};

static tr::Sched make_sched(int layer, const char* str, const int* ks, const int* lr) {
  using namespace tr;
  Sched s = {};
  int n = 0;
  s.nqa = 16;
  for (int b = 0; b < 16; b++) { s.ks[b] = (uint8_t)abs(ks[b]); s.wide[b] = ks[b] > 0; s.lrows[b] = (uint8_t)lr[b]; }
  for (const char* p = str; *p;) {
    if (*p == ' ') { p++; continue; }
    const bool late = *p < 'a';
    const char c = *p++ | 32;
    char* e;
    const int b = (int)strtol(p, &e, 10); p = e;
    int first = 0, cnt = c == 'o' ? s.ks[b] * (s.wide[b] ? 2 : 5) : (c == 'l' ? 16 / lr[b] : 32);
    if (*p == '.') { first = (int)strtol(p + 1, &e, 10); cnt = (int)strtol(e + 1, &e, 10); p = e; }
    const int type = c == 'a' ? T_QA : (c == 'q' ? T_Q : (c == 't' ? T_A : (c == 'l' ? T_L : (c == 'p' ? T_P : (s.wide[b] ? T_OB : T_OS)))));
    if (type == T_P && layer > 0) continue;
    if (type == T_A && b < s.nqa) s.nqa = b;
    for (int i = 0; i < cnt && n < MAXITEMS - 1; i++) s.item[n++] = (uint16_t)((late << 14) | (type << 11) | (b << 7) | (first + i));
  }
  s.n = n; s.item[n] = T_END << 11;
  return s;
}
static tr::Sched sched_of(int layer) {
  const char* str = layer == 0
      ? "q13 q14 q12.0.8 a0.0.8 q12.8.24 q15 a0.8.24 a1 p0.0.16 a2 p0.16.16 o0 o1 a3.0.16 o2 a3.16.16 a4.0.16 o3 a4.16.16 a5.0.24 o4 a5.24.8 a6.0.20 l0 a6.20.12 o5 "
        "a7 o6 l2 a8.0.24 o7 l1 a8.24.8 a9 o8 l3 a10 l4 O9 a11 t12 l5 l7 l6 O10 O11 O12 t13 t14 T15.0.20 O13 T15.20.12 l8 o14 L9 O15 L10 L12 l11 l15 l13 l14"
      : "q12 q14.0.8 q13 q15.0.16 q11.0.24 a0 q11.24.8 q14.8.24 o0 a1 a2 q15.16.16 o1 o2 a3 a4 o3 o4 a5 a6 o5 l1 a7 o6 l2 l0 a8.0.24 o7 a8.24.8 a9 o8 a10 "
        "O9 t11 l4 l3 O10 l5 o11 t12 l6 l7 O12 t13 t14 T15 o13 L9 o14 o15 L13 l10 L8 l12 l15 l11 l14";
  const int ks0[2][16] = {{2, 2, 2, 2, 2, 2, 2, 3, 2, 2, 3, 3, 3, -4, -8, -8}, {2, 2, 3, 2, 2, 2, 2, 2, 3, 3, 2, 4, 6, -6, -6, -12}};
  const int lr0[2][16] = {{4, 4, 4, 4, 4, 4, 4, 4, 2, 4, 1, 1, 1, 1, 1, 1}, {4, 4, 4, 4, 4, 4, 1, 2, 1, 4, 2, 1, 1, 1, 1, 1}};
  int ks[16], lr[16];
  for (int b = 0; b < 16; b++) { ks[b] = ks0[layer][b]; lr[b] = lr0[layer][b]; }
  return make_sched(layer, str, ks, lr);
}
#define TRAIL_GRID 132
#define PDL_LN 0
#define PDL_CH 1
#define PDL_B 1
#define PF_A 1
#define PF_B 1
extern "C" void kernel_launch(void* const* d_in, const int* in_sizes, int n_in, void* d_out, int out_size) {
  const bf16* x = (const bf16*)d_in[0];
  const bf16* mem0 = (const bf16*)d_in[1];
  const bf16 *Wq = (const bf16*)d_in[2], *Wk = (const bf16*)d_in[3], *Wv = (const bf16*)d_in[4], *Wo = (const bf16*)d_in[5];
  const bf16 *wqkv = (const bf16*)d_in[8], *wphi = (const bf16*)d_in[9], *wo = (const bf16*)d_in[10];
  bf16* out = (bf16*)d_out;
  static Ptrs P; static bool init = false;
  if (!init) {
    void* fn = nullptr; cudaDriverEntryPointQueryResult qr;
    cudaGetDriverEntryPoint("cuTensorMapEncodeTiled", &fn, cudaEnableDefault, &qr);
    g_encode = (EncodeFn)fn;
    void* p;
    cudaGetSymbolAddress(&p, g_arena); P.arena = (unsigned char*)p;
    cudaGetSymbolAddress(&p, g_k); P.k = (unsigned char*)p;   cudaGetSymbolAddress(&p, g_v); P.v = (unsigned char*)p;
    cudaGetSymbolAddress(&p, g_o); P.o = (bf16*)p;
    cudaGetSymbolAddress(&p, g_xn); P.xn = (bf16*)p;
    cudaGetSymbolAddress(&p, g_xa); P.xa = (bf16*)p;   cudaGetSymbolAddress(&p, g_xb); P.xb = (bf16*)p;
    cudaGetSymbolAddress(&p, g_wb); P.wb = (bf16*)p;   cudaGetSymbolAddress(&p, g_wot); P.wot = (bf16*)p;
    cudaGetSymbolAddress(&p, g_pq); P.pq = (bf16*)p;   cudaGetSymbolAddress(&p, g_part); P.part = (float*)p;
    cudaGetSymbolAddress(&p, g_kvacc); P.kvacc = (float*)p;
    cudaGetSymbolAddress(&p, g_xh); P.xh = (uint2*)p;
    cudaGetSymbolAddress(&p, g_go); P.go = (unsigned*)p;
    cudaGetSymbolAddress(&p, g_qs); P.qs = (uint4*)p;
    cudaGetSymbolAddress(&p, g_xn2); P.xn2 = (bf16*)p;
    cudaFuncSetAttribute(chain_kernel, cudaFuncAttributeMaxDynamicSharedMemorySize, ch::SMEM);
    cudaFuncSetAttribute(trail_kernel, cudaFuncAttributeMaxDynamicSharedMemorySize, tr::SMEM);
    cudaFuncSetAttribute(blayer_kernel, cudaFuncAttributeMaxDynamicSharedMemorySize, bf::SMEM);
    init = true;
  }
  const CUtensorMap tmXn = make_map(P.xn, 640, 2048, 64, 128), tmXn2 = make_map(P.xn2, 640, 2048, 64, 128);
  const CUtensorMap tmWq = make_map3(Wq, 6144, 640, 3);
  const CUtensorMap tmCq = make_map(Wq, 6144, 640, 64, 160), tmCk = make_map(Wk, 6144, 640, 64, 160), tmCv = make_map(Wv, 6144, 640, 64, 160), tmCo = make_map(Wo, 640, 6144, 224, 64, false);
  const CUtensorMap tmWo5 = make_map3(Wo, 640, 6144, 5), tmWo2 = make_map3(Wo, 640, 6144, 2);

  CUtensorMap tmP, tmP4;
  for (int i = 0; i < 2; i++) {
    cuuint64_t dims[4] = {256, 8, 320, 24}, strides[3] = {1024, 8192, 320 * 8192};
    cuuint32_t box[4] = {256, 1, 10, i ? 4u : 1u}, es[4] = {1, 1, 1, 1};
    g_encode(i ? &tmP4 : &tmP, CU_TENSOR_MAP_DATA_TYPE_UINT32, 4, P.part, dims, strides, box, es, CU_TENSOR_MAP_INTERLEAVE_NONE, CU_TENSOR_MAP_SWIZZLE_NONE,
             CU_TENSOR_MAP_L2_PROMOTION_NONE, CU_TENSOR_MAP_FLOAT_OOB_FILL_NONE);
  }
  ChainArgs ca;
  ca.xh = P.xh; ca.mem0 = mem0; ca.kg = P.k; ca.vg = P.v;
  ca.arena = P.arena; ca.go = P.go; ca.delay = POLL_DELAY; ca.margin = 150; ca.pubrel = 1;
  ca.tl = 0;
  uint4* zar = (uint4*)P.arena; const int nzar = AR_SIZE / 16;
  uint4* zkv = (uint4*)P.kvacc; const int nzkv = (bf::KVACC / 4 + 64) / 4;

  const PrepArgs pa{wqkv, wphi, wo, (unsigned char*)P.wb, (unsigned char*)P.wot};
  const bf16* xcur = x;
  cudaLaunchAttribute at[1];
  at[0].id = cudaLaunchAttributeProgrammaticStreamSerialization; at[0].val.programmaticStreamSerializationAllowed = 1;
  auto cfgof = [&](int grid, int block, int smem, bool pdl) {
    cudaLaunchConfig_t lc = {};
    lc.gridDim = dim3(grid); lc.blockDim = dim3(block); lc.dynamicSmemBytes = smem; lc.stream = cudaStreamPerThread;
    lc.attrs = at; lc.numAttrs = pdl ? 1 : 0;
    return lc;
  };
  int nlayers = 2;
  for (int layer = 0; layer < nlayers; layer++) {
    const int tl = layer * 12;
    cudaLaunchConfig_t lc = cfgof(256, 256, 0, layer > 0 && PDL_LN);
    cudaLaunchKernelEx(&lc, ln_kernel, xcur, P.xn, P.xh, zar, nzar, zkv, nzkv, Wk, Wv, layer == 0 ? PF_A : 0, tl + 0);
    ca.tl = tl + 2; ca.dry = 1;
    lc = cfgof(96, 384, ch::SMEM, PDL_CH);
    cudaLaunchKernelEx(&lc, chain_kernel, ca, tmCq, tmCk, tmCv, tmCo);
    lc = cfgof(TRAIL_GRID, 384, tr::SMEM, true);
    tr::Args ta{P.k, P.v, (unsigned char*)P.o, P.qs, (unsigned char*)P.part, xcur, P.xn, P.xa, P.xn2, P.arena, P.go, tl + 4, 30, 20, layer == 0 ? 0 : 99, 1, 13};
    cudaLaunchKernelEx(&lc, trail_kernel, tmXn, tmWq, tmWo5, tmWo2, tmP, tmP4, sched_of(layer), ta, pa);
    lc = cfgof(128, 384, bf::SMEM, PDL_B);
    bf::Args ba{(const unsigned char*)P.wb, (const unsigned char*)P.wot, (unsigned char*)P.kvacc, (unsigned char*)P.pq, P.xa, layer == 0 ? P.xb : out, P.go, layer == 0 ? P.arena + tr::C_P : nullptr,
                      layer == 0 && PF_B ? Wk : nullptr, Wv, 30, 500, 0, tl + 7};
    cudaLaunchKernelEx(&lc, blayer_kernel, tmXn2, ba);
    xcur = P.xb;
  }
}
```

```cpp
#include <cuda_runtime.h>
#include <cuda.h>
#include <cuda_bf16.h>
#include <stdint.h>
#include <stdlib.h>
#include <type_traits>

typedef __nv_bfloat16 bf16;

namespace cfg {
constexpr int S = 2048, DM = 640, H = 32, DH = 192, NSEG = 64, SEG = 32, NM = 8;
constexpr int HD = H * DH;
}

__device__ __forceinline__ uint32_t smem_u32(const void* p) { return (uint32_t)__cvta_generic_to_shared(p); }
__device__ __forceinline__ uint32_t mapa_u32(uint32_t a, uint32_t r) {
  uint32_t o; asm("mapa.shared::cluster.u32 %0, %1, %2;" : "=r"(o) : "r"(a), "r"(r)); return o;
}
__device__ __forceinline__ void mbar_init(uint32_t b, uint32_t c) {
  asm volatile("mbarrier.init.shared::cta.b64 [%0], %1;" :: "r"(b), "r"(c) : "memory");
}
__device__ __forceinline__ void mbar_expect_tx(uint32_t b, uint32_t bytes) {
  asm volatile("mbarrier.arrive.expect_tx.shared::cta.b64 _, [%0], %1;" :: "r"(b), "r"(bytes) : "memory");
}
__device__ __forceinline__ void mbar_arrive(uint32_t b) {
  asm volatile("mbarrier.arrive.shared::cta.b64 _, [%0];" :: "r"(b) : "memory");
}
__device__ __forceinline__ void mbar_expect_tx_if(bool c, uint32_t b, uint32_t bytes) {
  asm volatile("{\n.reg .pred p;\nsetp.ne.u32 p, %2, 0;\n@p mbarrier.arrive.expect_tx.shared::cta.b64 _, [%0], %1;\n}" :: "r"(b), "r"(bytes), "r"((uint32_t)c) : "memory");
}
__device__ __forceinline__ void mbar_arrive_if(bool c, uint32_t b) {
  asm volatile("{\n.reg .pred p;\nsetp.ne.u32 p, %1, 0;\n@p mbarrier.arrive.shared::cta.b64 _, [%0];\n}" :: "r"(b), "r"((uint32_t)c) : "memory");
}
#define SPIN_LIMIT (1 << 20)
__device__ __forceinline__ void mbar_wait(uint32_t b, uint32_t ph) {
  asm volatile("{\n.reg .pred p, q;\n.reg .u32 c;\nmov.u32 c, 0;\n"
               "W_%=:\nmbarrier.try_wait.parity.shared::cta.b64 p, [%0], %1;\n@p bra.uni D_%=;\n"
               "add.u32 c, c, 1;\nsetp.lt.u32 q, c, %2;\n@q bra.uni W_%=;\nD_%=:\n}"
               :: "r"(b), "r"(ph), "n"(SPIN_LIMIT) : "memory");
}
__device__ __forceinline__ void mbar_wait_if(bool cnd, uint32_t b, uint32_t ph) {
  asm volatile("{\n.reg .pred p, q;\n.reg .u32 c;\nsetp.eq.u32 q, %3, 0;\n@q bra.uni D_%=;\nmov.u32 c, 0;\n"
               "W_%=:\nmbarrier.try_wait.parity.shared::cta.b64 p, [%0], %1;\n@p bra.uni D_%=;\n"
               "add.u32 c, c, 1;\nsetp.lt.u32 q, c, %2;\n@q bra.uni W_%=;\nD_%=:\n}"
               :: "r"(b), "r"(ph), "n"(SPIN_LIMIT), "r"((uint32_t)cnd) : "memory");
}
__device__ __forceinline__ void mbar_spin(uint32_t b, uint32_t ph) {
  asm volatile("{\n.reg .pred p, q;\n.reg .u32 c;\nmov.u32 c, 0;\n"
               "W_%=:\nmbarrier.test_wait.parity.shared::cta.b64 p, [%0], %1;\n@p bra D_%=;\n"
               "add.u32 c, c, 1;\nsetp.lt.u32 q, c, %2;\n@q bra W_%=;\nD_%=:\n}"
               :: "r"(b), "r"(ph), "n"(SPIN_LIMIT) : "memory");
}
#define PIN(x) asm volatile("" : "+r"(x))
__device__ __forceinline__ void bulk_g2s(uint32_t dst, const void* src, uint32_t bytes, uint32_t mb) {
  asm volatile("cp.async.bulk.shared::cluster.global.mbarrier::complete_tx::bytes [%0], [%1], %2, [%3];"
               :: "r"(dst), "l"(src), "r"(bytes), "r"(mb) : "memory");
}
__device__ __forceinline__ void fence_proxy_async() { asm volatile("fence.proxy.async.shared::cta;" ::: "memory"); }
__device__ __forceinline__ void bar_sync(int id, int n) { asm volatile("bar.sync %0, %1;" :: "r"(id), "r"(n) : "memory"); }
__device__ __forceinline__ void bar_arrive(int id, int n) { asm volatile("bar.arrive %0, %1;" :: "r"(id), "r"(n) : "memory"); }
template <int IMM> __device__ __forceinline__ void ldsm_x4_i(uint32_t (&r)[4], uint32_t a) {
  asm volatile("ldmatrix.sync.aligned.m8n8.x4.shared.b16 {%0,%1,%2,%3}, [%4+%5];"
               : "=r"(r[0]), "=r"(r[1]), "=r"(r[2]), "=r"(r[3]) : "r"(a), "n"(IMM) : "memory");
}
template <int IMM> __device__ __forceinline__ void ldsm_x4_t_i(uint32_t (&r)[4], uint32_t a) {
  asm volatile("ldmatrix.sync.aligned.m8n8.x4.trans.shared.b16 {%0,%1,%2,%3}, [%4+%5];"
               : "=r"(r[0]), "=r"(r[1]), "=r"(r[2]), "=r"(r[3]) : "r"(a), "n"(IMM) : "memory");
}
template <int IMM> __device__ __forceinline__ uint4 lds128_i(uint32_t a) {
  uint4 v; asm volatile("ld.shared.v4.u32 {%0,%1,%2,%3}, [%4+%5];" : "=r"(v.x), "=r"(v.y), "=r"(v.z), "=r"(v.w) : "r"(a), "n"(IMM) : "memory"); return v;
}
template <int IMM> __device__ __forceinline__ uint2 lds64_i(uint32_t a) {
  uint2 v; asm volatile("ld.shared.v2.u32 {%0,%1}, [%2+%3];" : "=r"(v.x), "=r"(v.y) : "r"(a), "n"(IMM) : "memory"); return v;
}
template <int IMM> __device__ __forceinline__ void sts128_i(uint32_t a, uint32_t x, uint32_t y, uint32_t z, uint32_t w) {
  asm volatile("st.shared.v4.u32 [%0+%5], {%1,%2,%3,%4};" :: "r"(a), "r"(x), "r"(y), "r"(z), "r"(w), "n"(IMM) : "memory");
}
template <int IMM> __device__ __forceinline__ void sts64_i(uint32_t a, uint32_t x, uint32_t y) {
  asm volatile("st.shared.v2.u32 [%0+%3], {%1,%2};" :: "r"(a), "r"(x), "r"(y), "n"(IMM) : "memory");
}
template <int IMM> __device__ __forceinline__ void st_async_v2_i(uint32_t a, uint32_t x, uint32_t y, uint32_t mb) {
  asm volatile("st.async.weak.shared::cluster.mbarrier::complete_tx::bytes.v2.b32 [%0+%4], {%1,%2}, [%3];"
               :: "r"(a), "r"(x), "r"(y), "r"(mb), "n"(IMM) : "memory");
}
template <int IMM> __device__ __forceinline__ uint4 ld_relaxed_v4_i(const void* p) {
  uint4 v; asm volatile("ld.relaxed.gpu.global.v4.u32 {%0,%1,%2,%3}, [%4+%5];" : "=r"(v.x), "=r"(v.y), "=r"(v.z), "=r"(v.w) : "l"(p), "n"(IMM) : "memory"); return v;
}
template <int I, int N, class F> __device__ __forceinline__ void static_for(F&& f) {
  if constexpr (I < N) { f(std::integral_constant<int, I>{}); static_for<I + 1, N>(f); }
}
__device__ __forceinline__ uint32_t movm_t(uint32_t a) {
  uint32_t d; asm volatile("movmatrix.sync.aligned.m8n8.trans.b16 %0, %1;" : "=r"(d) : "r"(a)); return d;
}
__device__ __forceinline__ void mma16816(float (&d)[4], uint32_t a0, uint32_t a1, uint32_t a2, uint32_t a3, uint32_t b0, uint32_t b1) {
  asm volatile("mma.sync.aligned.m16n8k16.row.col.f32.bf16.bf16.f32 {%0,%1,%2,%3}, {%4,%5,%6,%7}, {%8,%9}, {%0,%1,%2,%3};"
               : "+f"(d[0]), "+f"(d[1]), "+f"(d[2]), "+f"(d[3]) : "r"(a0), "r"(a1), "r"(a2), "r"(a3), "r"(b0), "r"(b1));
}
__device__ __forceinline__ uint32_t pack_bf16(float lo, float hi) {
  uint32_t d; asm("cvt.rn.bf16x2.f32 %0, %1, %2;" : "=r"(d) : "f"(hi), "f"(lo)); return d;
}
__device__ __forceinline__ float bf_lo(uint32_t w) { return __uint_as_float(w << 16); }
__device__ __forceinline__ float bf_hi(uint32_t w) { return __uint_as_float(w & 0xffff0000u); }
__device__ __forceinline__ uint4 lds128(uint32_t a) {
  uint4 v; asm volatile("ld.shared.v4.u32 {%0,%1,%2,%3}, [%4];" : "=r"(v.x), "=r"(v.y), "=r"(v.z), "=r"(v.w) : "r"(a) : "memory"); return v;
}
__device__ __forceinline__ void sts128(uint32_t a, uint32_t x, uint32_t y, uint32_t z, uint32_t w) {
  asm volatile("st.shared.v4.u32 [%0], {%1,%2,%3,%4};" :: "r"(a), "r"(x), "r"(y), "r"(z), "r"(w) : "memory");
}
__device__ __forceinline__ void sts64(uint32_t a, uint32_t x, uint32_t y) {
  asm volatile("st.shared.v2.u32 [%0], {%1,%2};" :: "r"(a), "r"(x), "r"(y) : "memory");
}
__device__ __forceinline__ uint4 ld_relaxed_v4(const void* p) {
  uint4 v; asm volatile("ld.relaxed.gpu.global.v4.u32 {%0,%1,%2,%3}, [%4];" : "=r"(v.x), "=r"(v.y), "=r"(v.z), "=r"(v.w) : "l"(p) : "memory"); return v;
}
__device__ __forceinline__ uint32_t ld_relaxed_u32(const void* p) {
  uint32_t v; asm volatile("ld.relaxed.gpu.global.u32 %0, [%1];" : "=r"(v) : "l"(p) : "memory"); return v;
}
__device__ __forceinline__ void st_relaxed_u32(void* p, uint32_t v) {
  asm volatile("st.relaxed.gpu.global.u32 [%0], %1;" :: "l"(p), "r"(v) : "memory");
}
__device__ __forceinline__ void st_release_u32(void* p, uint32_t v) {
  asm volatile("st.release.gpu.global.u32 [%0], %1;" :: "l"(p), "r"(v) : "memory");
}
__device__ __forceinline__ void red_release_inc(void* p) { asm volatile("red.release.gpu.global.add.u32 [%0], 1;" :: "l"(p) : "memory"); }
__device__ __forceinline__ void wgmma_fence() { asm volatile("wgmma.fence.sync.aligned;" ::: "memory"); }
__device__ __forceinline__ void wgmma_commit() { asm volatile("wgmma.commit_group.sync.aligned;" ::: "memory"); }
template <int N> __device__ __forceinline__ void wgmma_wait() { asm volatile("wgmma.wait_group.sync.aligned %0;" :: "n"(N) : "memory"); }
__device__ __forceinline__ uint64_t make_desc(uint32_t saddr, uint32_t lbo_bytes, uint32_t sbo_bytes, uint32_t swz) {
  return (uint64_t)((saddr & 0x3FFFF) >> 4) | ((uint64_t)(lbo_bytes >> 4) << 16) | ((uint64_t)(sbo_bytes >> 4) << 32) | ((uint64_t)swz << 62);
}

template <uint32_t LBO, uint32_t SBO, uint32_t SWZ> __device__ __forceinline__ uint64_t desc16(uint32_t a16, uint32_t off = 0) {
  return (uint64_t)(a16 + ((off >> 4) + ((LBO >> 4) << 16))) | ((uint64_t)((SBO >> 4) | (SWZ << 30)) << 32);
}

__device__ __forceinline__ bool elect_one() {
  uint32_t p; asm volatile("{\n.reg .pred p;\nelect.sync _|p, 0xffffffff;\nselp.u32 %0, 1, 0, p;\n}" : "=r"(p)); return p;
}
__device__ __forceinline__ void tma_load_4d(uint32_t dst, const CUtensorMap* tm, int c0, int c1, int c2, int c3, uint32_t mb) {
  asm volatile("cp.async.bulk.tensor.4d.shared::cluster.global.mbarrier::complete_tx::bytes [%0], [%1, {%3, %4, %5, %6}], [%2];"
               :: "r"(dst), "l"(tm), "r"(mb), "r"(c0), "r"(c1), "r"(c2), "r"(c3) : "memory");
}
__device__ __forceinline__ void tma_load_3d(uint32_t dst, const CUtensorMap* tm, int c0, int c1, int c2, uint32_t mb) {
  asm volatile("cp.async.bulk.tensor.3d.shared::cluster.global.mbarrier::complete_tx::bytes [%0], [%1, {%3, %4, %5}], [%2];"
               :: "r"(dst), "l"(tm), "r"(mb), "r"(c0), "r"(c1), "r"(c2) : "memory");
}
__device__ __forceinline__ void tma_load_2d(uint32_t dst, const CUtensorMap* tm, int c0, int c1, uint32_t mb) {
  asm volatile("cp.async.bulk.tensor.2d.shared::cluster.global.mbarrier::complete_tx::bytes [%0], [%1, {%3, %4}], [%2];"
               :: "r"(dst), "l"(tm), "r"(mb), "r"(c0), "r"(c1) : "memory");
}
__device__ __forceinline__ void bulk_s2g(void* dst, uint32_t src, uint32_t bytes) {
  asm volatile("cp.async.bulk.global.shared::cta.bulk_group [%0], [%1], %2;" :: "l"(dst), "r"(src), "r"(bytes) : "memory");
}
__device__ __forceinline__ uint64_t policy_evict_first() {
  uint64_t p; asm volatile("createpolicy.fractional.L2::evict_first.b64 %0, 1.0;" : "=l"(p)); return p;
}
__device__ __forceinline__ void bulk_commit() { asm volatile("cp.async.bulk.commit_group;" ::: "memory"); }
template <int N> __device__ __forceinline__ void bulk_wait() { asm volatile("cp.async.bulk.wait_group %0;" :: "n"(N) : "memory"); }
__device__ __forceinline__ void stsm_x4(uint32_t a, uint32_t r0, uint32_t r1, uint32_t r2, uint32_t r3) {
  asm volatile("stmatrix.sync.aligned.m8n8.x4.shared.b16 [%0], {%1,%2,%3,%4};" :: "r"(a), "r"(r0), "r"(r1), "r"(r2), "r"(r3) : "memory");
}
__device__ __forceinline__ void stsm_x2(uint32_t a, uint32_t r0, uint32_t r1) {
  asm volatile("stmatrix.sync.aligned.m8n8.x2.shared.b16 [%0], {%1,%2};" :: "r"(a), "r"(r0), "r"(r1) : "memory");
}
__device__ __forceinline__ float bf16r(float x) { return __uint_as_float(pack_bf16(0.f, x) & 0xffff0000u); }
__device__ __forceinline__ void bf16r2(float& a, float& b) { const uint32_t w = pack_bf16(a, b); a = bf_lo(w); b = bf_hi(w); }
__device__ __forceinline__ float rcpf(float x) { float r; asm("rcp.approx.ftz.f32 %0, %1;" : "=f"(r) : "f"(x)); return r; }
__device__ __forceinline__ float ex2f(float x) { float e; asm("ex2.approx.ftz.f32 %0, %1;" : "=f"(e) : "f"(x)); return e; }
__device__ __forceinline__ void prefetch_tmap(const CUtensorMap* tm) { asm volatile("prefetch.tensormap [%0];" :: "l"(tm) : "memory"); }

template <int TA, int TB> __device__ __forceinline__ void wgmma_n24(float (&d)[12], uint64_t da, uint64_t db, int acc) {
  asm volatile("{\n.reg .pred p;\nsetp.ne.b32 p, %14, 0;\n"
    "wgmma.mma_async.sync.aligned.m64n24k16.f32.bf16.bf16 {%0, %1, %2, %3, %4, %5, %6, %7, %8, %9, %10, %11}, %12, %13, p, 1, 1, %15, %16;\n}\n"
    : "+f"(d[0]), "+f"(d[1]), "+f"(d[2]), "+f"(d[3]), "+f"(d[4]), "+f"(d[5]), "+f"(d[6]), "+f"(d[7]), "+f"(d[8]), "+f"(d[9]), "+f"(d[10]), "+f"(d[11])
    : "l"(da), "l"(db), "r"(acc), "n"(TA), "n"(TB));
}

template <int TA, int TB> __device__ __forceinline__ void wgmma_n80(float (&d)[40], uint64_t da, uint64_t db, int acc) {
  asm volatile("{\n.reg .pred p;\nsetp.ne.b32 p, %42, 0;\n"
    "wgmma.mma_async.sync.aligned.m64n80k16.f32.bf16.bf16 {%0, %1, %2, %3, %4, %5, %6, %7, %8, %9, %10, %11, %12, %13, %14, %15, %16, %17, %18, %19, %20, %21, %22, %23, %24, %25, %26, %27, %28, %29, %30, %31, %32, %33, %34, %35, %36, %37, %38, %39}, %40, %41, p, 1, 1, %43, %44;\n}\n"
    : "+f"(d[0]), "+f"(d[1]), "+f"(d[2]), "+f"(d[3]), "+f"(d[4]), "+f"(d[5]), "+f"(d[6]), "+f"(d[7]), "+f"(d[8]), "+f"(d[9]), "+f"(d[10]), "+f"(d[11]), "+f"(d[12]), "+f"(d[13]), "+f"(d[14]), "+f"(d[15]), "+f"(d[16]), "+f"(d[17]), "+f"(d[18]), "+f"(d[19]), "+f"(d[20]), "+f"(d[21]), "+f"(d[22]), "+f"(d[23]), "+f"(d[24]), "+f"(d[25]), "+f"(d[26]), "+f"(d[27]), "+f"(d[28]), "+f"(d[29]), "+f"(d[30]), "+f"(d[31]), "+f"(d[32]), "+f"(d[33]), "+f"(d[34]), "+f"(d[35]), "+f"(d[36]), "+f"(d[37]), "+f"(d[38]), "+f"(d[39])
    : "l"(da), "l"(db), "r"(acc), "n"(TA), "n"(TB));
}

template <int TA, int TB> __device__ __forceinline__ void wgmma_n128(float (&d)[64], uint64_t da, uint64_t db, int acc) {
  asm volatile("{\n.reg .pred p;\nsetp.ne.b32 p, %66, 0;\n"
    "wgmma.mma_async.sync.aligned.m64n128k16.f32.bf16.bf16 {%0, %1, %2, %3, %4, %5, %6, %7, %8, %9, %10, %11, %12, %13, %14, %15, %16, %17, %18, %19, %20, %21, %22, %23, %24, %25, %26, %27, %28, %29, %30, %31, %32, %33, %34, %35, %36, %37, %38, %39, %40, %41, %42, %43, %44, %45, %46, %47, %48, %49, %50, %51, %52, %53, %54, %55, %56, %57, %58, %59, %60, %61, %62, %63}, %64, %65, p, 1, 1, %67, %68;\n}\n"
    : "+f"(d[0]), "+f"(d[1]), "+f"(d[2]), "+f"(d[3]), "+f"(d[4]), "+f"(d[5]), "+f"(d[6]), "+f"(d[7]), "+f"(d[8]), "+f"(d[9]), "+f"(d[10]), "+f"(d[11]), "+f"(d[12]), "+f"(d[13]), "+f"(d[14]), "+f"(d[15]), "+f"(d[16]), "+f"(d[17]), "+f"(d[18]), "+f"(d[19]), "+f"(d[20]), "+f"(d[21]), "+f"(d[22]), "+f"(d[23]), "+f"(d[24]), "+f"(d[25]), "+f"(d[26]), "+f"(d[27]), "+f"(d[28]), "+f"(d[29]), "+f"(d[30]), "+f"(d[31]), "+f"(d[32]), "+f"(d[33]), "+f"(d[34]), "+f"(d[35]), "+f"(d[36]), "+f"(d[37]), "+f"(d[38]), "+f"(d[39]), "+f"(d[40]), "+f"(d[41]), "+f"(d[42]), "+f"(d[43]), "+f"(d[44]), "+f"(d[45]), "+f"(d[46]), "+f"(d[47]), "+f"(d[48]), "+f"(d[49]), "+f"(d[50]), "+f"(d[51]), "+f"(d[52]), "+f"(d[53]), "+f"(d[54]), "+f"(d[55]), "+f"(d[56]), "+f"(d[57]), "+f"(d[58]), "+f"(d[59]), "+f"(d[60]), "+f"(d[61]), "+f"(d[62]), "+f"(d[63])
    : "l"(da), "l"(db), "r"(acc), "n"(TA), "n"(TB));
}

template <int TA, int TB> __device__ __forceinline__ void wgmma_n192(float (&d)[96], uint64_t da, uint64_t db, int acc) {
  asm volatile("{\n.reg .pred p;\nsetp.ne.b32 p, %98, 0;\n"
    "wgmma.mma_async.sync.aligned.m64n192k16.f32.bf16.bf16 {%0, %1, %2, %3, %4, %5, %6, %7, %8, %9, %10, %11, %12, %13, %14, %15, %16, %17, %18, %19, %20, %21, %22, %23, %24, %25, %26, %27, %28, %29, %30, %31, %32, %33, %34, %35, %36, %37, %38, %39, %40, %41, %42, %43, %44, %45, %46, %47, %48, %49, %50, %51, %52, %53, %54, %55, %56, %57, %58, %59, %60, %61, %62, %63, %64, %65, %66, %67, %68, %69, %70, %71, %72, %73, %74, %75, %76, %77, %78, %79, %80, %81, %82, %83, %84, %85, %86, %87, %88, %89, %90, %91, %92, %93, %94, %95}, %96, %97, p, 1, 1, %99, %100;\n}\n"
    : "+f"(d[0]), "+f"(d[1]), "+f"(d[2]), "+f"(d[3]), "+f"(d[4]), "+f"(d[5]), "+f"(d[6]), "+f"(d[7]), "+f"(d[8]), "+f"(d[9]), "+f"(d[10]), "+f"(d[11]), "+f"(d[12]), "+f"(d[13]), "+f"(d[14]), "+f"(d[15]), "+f"(d[16]), "+f"(d[17]), "+f"(d[18]), "+f"(d[19]), "+f"(d[20]), "+f"(d[21]), "+f"(d[22]), "+f"(d[23]), "+f"(d[24]), "+f"(d[25]), "+f"(d[26]), "+f"(d[27]), "+f"(d[28]), "+f"(d[29]), "+f"(d[30]), "+f"(d[31]), "+f"(d[32]), "+f"(d[33]), "+f"(d[34]), "+f"(d[35]), "+f"(d[36]), "+f"(d[37]), "+f"(d[38]), "+f"(d[39]), "+f"(d[40]), "+f"(d[41]), "+f"(d[42]), "+f"(d[43]), "+f"(d[44]), "+f"(d[45]), "+f"(d[46]), "+f"(d[47]), "+f"(d[48]), "+f"(d[49]), "+f"(d[50]), "+f"(d[51]), "+f"(d[52]), "+f"(d[53]), "+f"(d[54]), "+f"(d[55]), "+f"(d[56]), "+f"(d[57]), "+f"(d[58]), "+f"(d[59]), "+f"(d[60]), "+f"(d[61]), "+f"(d[62]), "+f"(d[63]), "+f"(d[64]), "+f"(d[65]), "+f"(d[66]), "+f"(d[67]), "+f"(d[68]), "+f"(d[69]), "+f"(d[70]), "+f"(d[71]), "+f"(d[72]), "+f"(d[73]), "+f"(d[74]), "+f"(d[75]), "+f"(d[76]), "+f"(d[77]), "+f"(d[78]), "+f"(d[79]), "+f"(d[80]), "+f"(d[81]), "+f"(d[82]), "+f"(d[83]), "+f"(d[84]), "+f"(d[85]), "+f"(d[86]), "+f"(d[87]), "+f"(d[88]), "+f"(d[89]), "+f"(d[90]), "+f"(d[91]), "+f"(d[92]), "+f"(d[93]), "+f"(d[94]), "+f"(d[95])
    : "l"(da), "l"(db), "r"(acc), "n"(TA), "n"(TB));
}

template <int TA, int TB> __device__ __forceinline__ void wgmma_n256(float (&d)[128], uint64_t da, uint64_t db, int acc) {
  asm volatile("{\n.reg .pred p;\nsetp.ne.b32 p, %130, 0;\n"
    "wgmma.mma_async.sync.aligned.m64n256k16.f32.bf16.bf16 {%0, %1, %2, %3, %4, %5, %6, %7, %8, %9, %10, %11, %12, %13, %14, %15, %16, %17, %18, %19, %20, %21, %22, %23, %24, %25, %26, %27, %28, %29, %30, %31, %32, %33, %34, %35, %36, %37, %38, %39, %40, %41, %42, %43, %44, %45, %46, %47, %48, %49, %50, %51, %52, %53, %54, %55, %56, %57, %58, %59, %60, %61, %62, %63, %64, %65, %66, %67, %68, %69, %70, %71, %72, %73, %74, %75, %76, %77, %78, %79, %80, %81, %82, %83, %84, %85, %86, %87, %88, %89, %90, %91, %92, %93, %94, %95, %96, %97, %98, %99, %100, %101, %102, %103, %104, %105, %106, %107, %108, %109, %110, %111, %112, %113, %114, %115, %116, %117, %118, %119, %120, %121, %122, %123, %124, %125, %126, %127}, %128, %129, p, 1, 1, %131, %132;\n}\n"
    : "+f"(d[0]), "+f"(d[1]), "+f"(d[2]), "+f"(d[3]), "+f"(d[4]), "+f"(d[5]), "+f"(d[6]), "+f"(d[7]), "+f"(d[8]), "+f"(d[9]), "+f"(d[10]), "+f"(d[11]), "+f"(d[12]), "+f"(d[13]), "+f"(d[14]), "+f"(d[15]), "+f"(d[16]), "+f"(d[17]), "+f"(d[18]), "+f"(d[19]), "+f"(d[20]), "+f"(d[21]), "+f"(d[22]), "+f"(d[23]), "+f"(d[24]), "+f"(d[25]), "+f"(d[26]), "+f"(d[27]), "+f"(d[28]), "+f"(d[29]), "+f"(d[30]), "+f"(d[31]), "+f"(d[32]), "+f"(d[33]), "+f"(d[34]), "+f"(d[35]), "+f"(d[36]), "+f"(d[37]), "+f"(d[38]), "+f"(d[39]), "+f"(d[40]), "+f"(d[41]), "+f"(d[42]), "+f"(d[43]), "+f"(d[44]), "+f"(d[45]), "+f"(d[46]), "+f"(d[47]), "+f"(d[48]), "+f"(d[49]), "+f"(d[50]), "+f"(d[51]), "+f"(d[52]), "+f"(d[53]), "+f"(d[54]), "+f"(d[55]), "+f"(d[56]), "+f"(d[57]), "+f"(d[58]), "+f"(d[59]), "+f"(d[60]), "+f"(d[61]), "+f"(d[62]), "+f"(d[63]), "+f"(d[64]), "+f"(d[65]), "+f"(d[66]), "+f"(d[67]), "+f"(d[68]), "+f"(d[69]), "+f"(d[70]), "+f"(d[71]), "+f"(d[72]), "+f"(d[73]), "+f"(d[74]), "+f"(d[75]), "+f"(d[76]), "+f"(d[77]), "+f"(d[78]), "+f"(d[79]), "+f"(d[80]), "+f"(d[81]), "+f"(d[82]), "+f"(d[83]), "+f"(d[84]), "+f"(d[85]), "+f"(d[86]), "+f"(d[87]), "+f"(d[88]), "+f"(d[89]), "+f"(d[90]), "+f"(d[91]), "+f"(d[92]), "+f"(d[93]), "+f"(d[94]), "+f"(d[95]), "+f"(d[96]), "+f"(d[97]), "+f"(d[98]), "+f"(d[99]), "+f"(d[100]), "+f"(d[101]), "+f"(d[102]), "+f"(d[103]), "+f"(d[104]), "+f"(d[105]), "+f"(d[106]), "+f"(d[107]), "+f"(d[108]), "+f"(d[109]), "+f"(d[110]), "+f"(d[111]), "+f"(d[112]), "+f"(d[113]), "+f"(d[114]), "+f"(d[115]), "+f"(d[116]), "+f"(d[117]), "+f"(d[118]), "+f"(d[119]), "+f"(d[120]), "+f"(d[121]), "+f"(d[122]), "+f"(d[123]), "+f"(d[124]), "+f"(d[125]), "+f"(d[126]), "+f"(d[127])
    : "l"(da), "l"(db), "r"(acc), "n"(TA), "n"(TB));
}

template <int TB> __device__ __forceinline__ void wgmma_rs_n24(float (&d)[12], uint32_t a0, uint32_t a1, uint32_t a2, uint32_t a3, uint64_t db, int acc) {
  asm volatile("{\n.reg .pred p;\nsetp.ne.b32 p, %17, 0;\n"
    "wgmma.mma_async.sync.aligned.m64n24k16.f32.bf16.bf16 {%0, %1, %2, %3, %4, %5, %6, %7, %8, %9, %10, %11}, {%12, %13, %14, %15}, %16, p, 1, 1, %18;\n}\n"
    : "+f"(d[0]), "+f"(d[1]), "+f"(d[2]), "+f"(d[3]), "+f"(d[4]), "+f"(d[5]), "+f"(d[6]), "+f"(d[7]), "+f"(d[8]), "+f"(d[9]), "+f"(d[10]), "+f"(d[11])
    : "r"(a0), "r"(a1), "r"(a2), "r"(a3), "l"(db), "r"(acc), "n"(TB));
}

template <int TB> __device__ __forceinline__ void wgmma_rs_n40(float (&d)[20], uint32_t a0, uint32_t a1, uint32_t a2, uint32_t a3, uint64_t db, int acc) {
  asm volatile("{\n.reg .pred p;\nsetp.ne.b32 p, %25, 0;\n"
    "wgmma.mma_async.sync.aligned.m64n40k16.f32.bf16.bf16 {%0, %1, %2, %3, %4, %5, %6, %7, %8, %9, %10, %11, %12, %13, %14, %15, %16, %17, %18, %19}, {%20, %21, %22, %23}, %24, p, 1, 1, %26;\n}\n"
    : "+f"(d[0]), "+f"(d[1]), "+f"(d[2]), "+f"(d[3]), "+f"(d[4]), "+f"(d[5]), "+f"(d[6]), "+f"(d[7]), "+f"(d[8]), "+f"(d[9]), "+f"(d[10]), "+f"(d[11]), "+f"(d[12]), "+f"(d[13]), "+f"(d[14]), "+f"(d[15]), "+f"(d[16]), "+f"(d[17]), "+f"(d[18]), "+f"(d[19])
    : "r"(a0), "r"(a1), "r"(a2), "r"(a3), "l"(db), "r"(acc), "n"(TB));
}

template <int TB> __device__ __forceinline__ void wgmma_rs_n192(float (&d)[96], uint32_t a0, uint32_t a1, uint32_t a2, uint32_t a3, uint64_t db, int acc) {
  asm volatile("{\n.reg .pred p;\nsetp.ne.b32 p, %101, 0;\n"
    "wgmma.mma_async.sync.aligned.m64n192k16.f32.bf16.bf16 {%0, %1, %2, %3, %4, %5, %6, %7, %8, %9, %10, %11, %12, %13, %14, %15, %16, %17, %18, %19, %20, %21, %22, %23, %24, %25, %26, %27, %28, %29, %30, %31, %32, %33, %34, %35, %36, %37, %38, %39, %40, %41, %42, %43, %44, %45, %46, %47, %48, %49, %50, %51, %52, %53, %54, %55, %56, %57, %58, %59, %60, %61, %62, %63, %64, %65, %66, %67, %68, %69, %70, %71, %72, %73, %74, %75, %76, %77, %78, %79, %80, %81, %82, %83, %84, %85, %86, %87, %88, %89, %90, %91, %92, %93, %94, %95}, {%96, %97, %98, %99}, %100, p, 1, 1, %102;\n}\n"
    : "+f"(d[0]), "+f"(d[1]), "+f"(d[2]), "+f"(d[3]), "+f"(d[4]), "+f"(d[5]), "+f"(d[6]), "+f"(d[7]), "+f"(d[8]), "+f"(d[9]), "+f"(d[10]), "+f"(d[11]), "+f"(d[12]), "+f"(d[13]), "+f"(d[14]), "+f"(d[15]), "+f"(d[16]), "+f"(d[17]), "+f"(d[18]), "+f"(d[19]), "+f"(d[20]), "+f"(d[21]), "+f"(d[22]), "+f"(d[23]), "+f"(d[24]), "+f"(d[25]), "+f"(d[26]), "+f"(d[27]), "+f"(d[28]), "+f"(d[29]), "+f"(d[30]), "+f"(d[31]), "+f"(d[32]), "+f"(d[33]), "+f"(d[34]), "+f"(d[35]), "+f"(d[36]), "+f"(d[37]), "+f"(d[38]), "+f"(d[39]), "+f"(d[40]), "+f"(d[41]), "+f"(d[42]), "+f"(d[43]), "+f"(d[44]), "+f"(d[45]), "+f"(d[46]), "+f"(d[47]), "+f"(d[48]), "+f"(d[49]), "+f"(d[50]), "+f"(d[51]), "+f"(d[52]), "+f"(d[53]), "+f"(d[54]), "+f"(d[55]), "+f"(d[56]), "+f"(d[57]), "+f"(d[58]), "+f"(d[59]), "+f"(d[60]), "+f"(d[61]), "+f"(d[62]), "+f"(d[63]), "+f"(d[64]), "+f"(d[65]), "+f"(d[66]), "+f"(d[67]), "+f"(d[68]), "+f"(d[69]), "+f"(d[70]), "+f"(d[71]), "+f"(d[72]), "+f"(d[73]), "+f"(d[74]), "+f"(d[75]), "+f"(d[76]), "+f"(d[77]), "+f"(d[78]), "+f"(d[79]), "+f"(d[80]), "+f"(d[81]), "+f"(d[82]), "+f"(d[83]), "+f"(d[84]), "+f"(d[85]), "+f"(d[86]), "+f"(d[87]), "+f"(d[88]), "+f"(d[89]), "+f"(d[90]), "+f"(d[91]), "+f"(d[92]), "+f"(d[93]), "+f"(d[94]), "+f"(d[95])
    : "r"(a0), "r"(a1), "r"(a2), "r"(a3), "l"(db), "r"(acc), "n"(TB));
}
constexpr uint32_t AR_ACC = 0;
constexpr uint32_t AR_TAB = 0x100000;
constexpr uint32_t AR_PROG = 0x101000;
__host__ __device__ constexpr uint32_t prog_off(int h, int j) { return AR_PROG + h * 128 + j * 4; }
constexpr uint32_t AR_CNT = 0x108000;
constexpr uint32_t AR_QUEUE = 0x109000;
constexpr uint32_t AR_SIZE = 0x10a000;

struct ChainArgs {
  const bf16* mem0;
  const uint2* xh;
  unsigned char *kg, *vg;
  unsigned char* arena;
  unsigned* go;
  uint32_t delay;
  int margin, pubrel, dry;
  int tl;
};

namespace ch {
constexpr int OFF_WQ = 0;
constexpr int OFF_X = 81920;
constexpr int OFF_MEM = OFF_X + 40960;
constexpr int OFF_WO = OFF_MEM + 10240;
constexpr int WOK = 8 * 896;
constexpr int OFF_KV = OFF_WO + 10 * WOK;
constexpr int KVB = 5120;
constexpr int OFF_O = OFF_KV + 4 * KVB;
constexpr int OFF_Q = OFF_O + 1024;
constexpr int OFF_S = OFF_O + 3072;
constexpr int OFF_SR = OFF_S + 1536;
constexpr int OFF_LT = OFF_SR + 1280;
constexpr int OFF_BAR = OFF_LT + 512;
constexpr int SMEM = OFF_BAR + 256;
static_assert(SMEM <= 232448, "smem");
constexpr int MB_S = OFF_BAR, MB_O = OFF_BAR + 8, MB_X = OFF_BAR + 16;
constexpr int MB_K = OFF_BAR + 128, MB_V = MB_K + 16, MB_Q = MB_K + 32, MB_R = MB_K + 48;
constexpr int SC_IN = OFF_BAR + 64;
constexpr int SC_MX = OFF_S;
constexpr int SC_TW = OFF_BAR + 48;
constexpr int SC_W = OFF_BAR + 96;
constexpr int WOS = 448;
enum { B_MEM0 = 1, B_QK, B_SL, B_V, B_O, B_RED, B_X, B_C, B_H, B_MEM1, B_A, B_G, B_E };
#define NQ1 14
#define NP1 (NQ1 < 6 ? NQ1 : 6)
#define NQ0 8
#define NP0 5
#define NPL 2
#define PQE 1
#define PFK 1
#define NB0 2
#ifndef NVE
#define NVE 8
#endif
#define VET 19
#define NPM0 2
#define NPM1 2
#define NRT 7
#define NRF 2
#define PA0 3
#define PA1 0
#define PB0 7
#define PB1 5
#define PM1 1
#define GD1 30
#define GD2 150
#define XT 38
#define WOF 0
#define MEMFIRST 0
#define CEARLY 0
#define POLL_DELAY 620
#define PFX 3
#define PFACC 1
static_assert(NPM0 >= 2 && NPM1 >= 2, "the K / V blocks live in the last two k-steps of Wo");
}

template <int V> using IC = std::integral_constant<int, V>;
__device__ __forceinline__ uint32_t clk_v() { uint64_t c; asm volatile("mov.u64 %0, %%clock64;" : "=l"(c) :: "memory"); return (uint32_t)c; }
__device__ __forceinline__ int fresh(int x) { int y; asm volatile("shfl.sync.bfly.b32 %0, %1, 0, 0x1f, 0xffffffff;" : "=r"(y) : "r"(x)); return y; }
#define SFENCE2(x, d) asm volatile("{\n.reg .pred p;\nsetp.eq.u32 p, %0, 0x7fffffff;\n@p st.shared.u32 [%0], %1;\n}" :: "r"(x), "r"(d) : "memory")
#define SFENCE(x) asm volatile("{\n.reg .pred p;\nsetp.eq.u32 p, %0, 0x7fffffff;\n@p st.shared.u32 [%0], %0;\n}" :: "r"(x) : "memory")
__device__ __forceinline__ float uniform_f(float x) { return __uint_as_float(__reduce_max_sync(0xffffffffu, __float_as_uint(x))); }

__device__ __forceinline__ void mma16816h(float (&d)[4], const uint32_t (&a)[4], uint32_t b0, uint32_t b1) {
  asm volatile("mma.sync.aligned.m16n8k16.row.col.f32.f16.f16.f32 {%0,%1,%2,%3}, {%4,%5,%6,%7}, {%8,%9}, {%0,%1,%2,%3};"
               : "+f"(d[0]), "+f"(d[1]), "+f"(d[2]), "+f"(d[3]) : "r"(a[0]), "r"(a[1]), "r"(a[2]), "r"(a[3]), "r"(b0), "r"(b1));
}
__device__ __forceinline__ void mma1688(float (&d)[4], uint32_t a0, uint32_t a1, uint32_t b0) {
  asm volatile("mma.sync.aligned.m16n8k8.row.col.f32.bf16.bf16.f32 {%0,%1,%2,%3}, {%4,%5}, {%6}, {%0,%1,%2,%3};"
               : "+f"(d[0]), "+f"(d[1]), "+f"(d[2]), "+f"(d[3]) : "r"(a0), "r"(a1), "r"(b0));
}
template <int OFF16, int ACC> __device__ __forceinline__ void wgmma_rs32h(float (&d)[16], const uint32_t (&a)[4], uint32_t dlo) {
  asm volatile("{\n.reg .pred p;\n.reg .b32 t;\n.reg .b64 db;\nsetp.ne.b32 p, %22, 0;\nadd.u32 t, %20, %21;\nmov.b64 db, {t, 0x40000040};\n"
    "wgmma.mma_async.sync.aligned.m64n32k16.f32.f16.f16 {%0,%1,%2,%3,%4,%5,%6,%7,%8,%9,%10,%11,%12,%13,%14,%15}, {%16,%17,%18,%19}, db, p, 1, 1, 0;\n}\n"
    : "+f"(d[0]), "+f"(d[1]), "+f"(d[2]), "+f"(d[3]), "+f"(d[4]), "+f"(d[5]), "+f"(d[6]), "+f"(d[7]), "+f"(d[8]), "+f"(d[9]), "+f"(d[10]), "+f"(d[11]),
      "+f"(d[12]), "+f"(d[13]), "+f"(d[14]), "+f"(d[15])
    : "r"(a[0]), "r"(a[1]), "r"(a[2]), "r"(a[3]), "r"(dlo), "n"(OFF16), "n"(ACC));
}
template <int IMM> __device__ __forceinline__ void stsm_x4_t_i(uint32_t a, uint32_t r0, uint32_t r1, uint32_t r2, uint32_t r3) {
  asm volatile("stmatrix.sync.aligned.m8n8.x4.trans.shared.b16 [%0+%5], {%1,%2,%3,%4};" :: "r"(a), "r"(r0), "r"(r1), "r"(r2), "r"(r3), "n"(IMM) : "memory");
}
template <int IMM> __device__ __forceinline__ void stsm_x2_t_i(uint32_t a, uint32_t r0, uint32_t r1) {
  asm volatile("stmatrix.sync.aligned.m8n8.x2.trans.shared.b16 [%0+%3], {%1,%2};" :: "r"(a), "r"(r0), "r"(r1), "n"(IMM) : "memory");
}
template <int IMM> __device__ __forceinline__ void st_async_b32_i(uint32_t a, uint32_t x, uint32_t mb) {
  asm volatile("st.async.weak.shared::cluster.mbarrier::complete_tx::bytes.b32 [%0+%3], %1, [%2];" :: "r"(a), "r"(x), "r"(mb), "n"(IMM) : "memory");
}
template <int IMM> __device__ __forceinline__ void ldsm_x2_i(uint32_t (&r)[2], uint32_t a) {
  asm volatile("ldmatrix.sync.aligned.m8n8.x2.shared.b16 {%0,%1}, [%2+%3];" : "=r"(r[0]), "=r"(r[1]) : "r"(a), "n"(IMM) : "memory");
}
template <int IMM> __device__ __forceinline__ uint32_t ldsm_x1_t_i(uint32_t a) {
  uint32_t r; asm volatile("ldmatrix.sync.aligned.m8n8.x1.trans.shared.b16 {%0}, [%1+%2];" : "=r"(r) : "r"(a), "n"(IMM) : "memory"); return r;
}
template <int IMM> __device__ __forceinline__ uint32_t lds32_i(uint32_t a) {
  uint32_t v; asm volatile("ld.shared.u32 %0, [%1+%2];" : "=r"(v) : "r"(a), "n"(IMM) : "memory"); return v;
}
__device__ __forceinline__ void sts32(uint32_t a, uint32_t v) { asm volatile("st.shared.u32 [%0], %1;" :: "r"(a), "r"(v) : "memory"); }
__device__ __forceinline__ uint32_t pack_f16(float lo, float hi) {
  uint32_t d; asm("cvt.rn.f16x2.f32 %0, %1, %2;" : "=r"(d) : "f"(hi), "f"(lo)); return d;
}
__device__ __forceinline__ uint32_t amax_bf2(uint32_t a, uint32_t b) { uint32_t d; asm("max.xorsign.abs.bf16x2 %0, %1, %2;" : "=r"(d) : "r"(a), "r"(b)); return d; }
__device__ __forceinline__ uint32_t amax_h2(uint32_t a, uint32_t b) { uint32_t d; asm("max.xorsign.abs.f16x2 %0, %1, %2;" : "=r"(d) : "r"(a), "r"(b)); return d; }
__device__ __forceinline__ uint32_t amax_fold(uint32_t m) { return __reduce_max_sync(0xffffffffu, max(m & 0x7fffu, (m >> 16) & 0x7fffu)); }
__device__ __forceinline__ int wscale_exp(uint32_t m) { return min(141 - (int)(m >> 7), 100); }
__device__ __forceinline__ float exp2i(int e) { return __uint_as_float((uint32_t)(e + 127) << 23); }
__device__ __forceinline__ uint32_t bf2_to_h2(uint32_t w, float sc) { return pack_f16(bf_lo(w) * sc, bf_hi(w) * sc); }
__device__ __forceinline__ void bf2_to_h2_inplace(uint32_t& w, uint32_t sc2) {
  asm volatile("{\n.reg .b32 t, lo, hi;\nmul.rn.bf16x2 t, %0, %1;\nshl.b32 lo, t, 16;\nand.b32 hi, t, 0xffff0000;\ncvt.rn.f16x2.f32 %0, hi, lo;\n}" : "+r"(w) : "r"(sc2));
}
__device__ __forceinline__ void prefetch_l2(const void* p, uint32_t bytes) { asm volatile("cp.async.bulk.prefetch.L2.global [%0], %1;" :: "l"(p), "r"(bytes) : "memory"); }
__host__ __device__ constexpr uint32_t acc_voff(int v) { return v < 4 ? v * 1024u : (v == 4 ? 128u : 3072u + 128u); }
__device__ __forceinline__ int unit28(int i) { return i == 3 ? 54 : 14 * i; }
__device__ __forceinline__ int unit24(int i) { return i < 2 ? 48 - 6 * i : 56 + 6 * i; }
__device__ __forceinline__ uint32_t acc_step(int s) { return (s >> 1) * 32768 + (s & 1) * 512; }
__device__ __forceinline__ uint32_t acc_lane(int i, int lane) { return ((lane >> 3) & 1) * 256 + (lane >> 4) * 4096 + i * 8192 + (lane & 7) * 16; }

__device__ __forceinline__ uint32_t ld_acquire_u32(const void* p) {
  uint32_t v; asm volatile("ld.acquire.gpu.global.u32 %0, [%1];" : "=r"(v) : "l"(p) : "memory"); return v;
}
template <int R> __device__ __forceinline__ void ln_rows(const uint2 (&xw)[R][5], int row0, int lane, bf16* __restrict__ xn, uint2* __restrict__ xh) {
  float v[R][20], s[R], q[R];
#pragma unroll
  for (int r = 0; r < R; r++) {
    s[r] = 0.f; q[r] = 0.f;
#pragma unroll
    for (int i = 0; i < 5; i++) { v[r][4 * i] = bf_lo(xw[r][i].x); v[r][4 * i + 1] = bf_hi(xw[r][i].x); v[r][4 * i + 2] = bf_lo(xw[r][i].y); v[r][4 * i + 3] = bf_hi(xw[r][i].y); }
#pragma unroll
    for (int i = 0; i < 5; i++) s[r] += (v[r][4 * i] + v[r][4 * i + 1]) + (v[r][4 * i + 2] + v[r][4 * i + 3]);
  }
#pragma unroll
  for (int o = 16; o; o >>= 1)
#pragma unroll
    for (int r = 0; r < R; r++) s[r] += __shfl_xor_sync(0xffffffffu, s[r], o);
#pragma unroll
  for (int r = 0; r < R; r++) {
    s[r] *= 1.f / cfg::DM;
#pragma unroll
    for (int i = 0; i < 10; i++) { const float d = v[r][2 * i] - s[r], e = v[r][2 * i + 1] - s[r]; q[r] += d * d + e * e; }
  }
#pragma unroll
  for (int o = 16; o; o >>= 1)
#pragma unroll
    for (int r = 0; r < R; r++) q[r] += __shfl_xor_sync(0xffffffffu, q[r], o);
#pragma unroll
  for (int r = 0; r < R; r++) {
    const int row = row0 + r;
    const float mb = bf16r(s[r]), var = bf16r(q[r] * (1.f / cfg::DM));
    float sd; asm("sqrt.approx.f32 %0, %1;" : "=f"(sd) : "f"(bf16r(var + 1e-5f)));
    const float inv = rcpf(bf16r(sd));
#pragma unroll
    for (int i = 0; i < 5; i++) {
      float y[4];
#pragma unroll
      for (int e = 0; e < 4; e++) y[e] = v[r][4 * i + e] - mb;
      bf16r2(y[0], y[1]); bf16r2(y[2], y[3]);
      const uint32_t w0 = pack_bf16(y[0] * inv, y[1] * inv), w1 = pack_bf16(y[2] * inv, y[3] * inv);
      *(uint2*)(xn + (size_t)row * cfg::DM + i * 128 + lane * 4) = make_uint2(w0, w1);
      if (xh) xh[(((size_t)(row >> 5) * 10 + 2 * i + (lane >> 4)) * 32 + (row & 31)) * 16 + ((((lane >> 1) & 7) ^ (row & 7)) << 1) + (lane & 1)] =
          make_uint2(pack_f16(bf_lo(w0), bf_hi(w0)), pack_f16(bf_lo(w1), bf_hi(w1)));
    }
  }
}

__global__ void __cluster_dims__(3, 1, 1) __launch_bounds__(384, 1) chain_kernel(const ChainArgs a, const __grid_constant__ CUtensorMap tmWq,
    const __grid_constant__ CUtensorMap tmWk, const __grid_constant__ CUtensorMap tmWv, const __grid_constant__ CUtensorMap tmWo) {
  using namespace ch;
  extern __shared__ __align__(1024) unsigned char smem_raw[];
  const uint32_t sb = smem_u32(smem_raw);
  const int warp = __shfl_sync(0xffffffffu, (int)threadIdx.x >> 5, 0);
  const int cta = blockIdx.x, h = cta / 3, j = cta % 3;
  unsigned char* const arena = a.arena;
  if (sb & 1023u) __trap();
  asm volatile("griddepcontrol.launch_dependents;");
  const int col0 = j == 0 ? 0 : (j == 1 ? 224 : 432);
  auto stage_w = [&](const CUtensorMap* tm, uint32_t dst, uint32_t mb, int half) {
    mbar_expect_tx(mb + 8 * half, 40960);
    tma_load_2d(dst + half * 40960, tm, h * cfg::DH + j * 64, half * 320, mb + 8 * half);
    tma_load_2d(dst + half * 40960 + 20480, tm, h * cfg::DH + j * 64, half * 320 + 160, mb + 8 * half);
  };
  if (threadIdx.x == 256) {
    for (int i = 0; i < 9; i++) mbar_init(sb + MB_K + 8 * i, 1);
    mbar_init(sb + MB_S, 1); mbar_init(sb + MB_O, 1); mbar_init(sb + MB_X, 1);
    asm volatile("fence.mbarrier_init.release.cluster;" ::: "memory");
    for (int i = 0; i < 2; i++) { stage_w(&tmWk, sb + OFF_WQ, sb + MB_K, i); stage_w(&tmWv, sb + OFF_WO, sb + MB_V, i); }
    sts32(sb + SC_W, 0); sts32(sb + SC_W + 4, 0); sts32(sb + SC_W + 8, 0); sts32(sb + SC_IN + 12, 0); sts32(sb + SC_IN + 20, 0); sts32(sb + SC_TW + 4, 99);
    mbar_expect_tx(sb + MB_S, 1280); mbar_expect_tx(sb + MB_O, 2048);
  }
  __syncthreads();
  asm volatile("barrier.cluster.arrive.relaxed.aligned;" ::: "memory");
  const uint32_t d1 = mapa_u32(sb, (j + 1) % 3) - sb, d2 = mapa_u32(sb, (j + 2) % 3) - sb;

  if (warp >= 8) {
    asm volatile("setmaxnreg.dec.sync.aligned.u32 40;");
    const int lane = fresh(threadIdx.x & 31), hw = warp - 8, ht = hw * 32 + lane;
    const bool lead = ht == 0;
    auto stage_wo = [&](int i) {
      mbar_expect_tx(sb + MB_R + 8 * i, 64 * WOS);
      tma_load_2d(sb + OFF_WO + i * 64 * WOS, &tmWo, col0, h * cfg::DH + ((i + j) % 3) * 64, sb + MB_R + 8 * i);
    };
    const unsigned char* xg = (const unsigned char*)a.xh;
    auto issue_x = [&](int s) { mbar_expect_tx(sb + MB_X, 40960); bulk_g2s(sb + OFF_X, xg + (size_t)s * 40960, 40960, sb + MB_X); };
    uint4 v[5];
#pragma unroll
    for (int i = 0; i < 5; i++) { const int c = ht + 128 * i; v[i] = ld_relaxed_v4(a.mem0 + (c & 7) * cfg::DM + (c >> 3) * 8); }
    if (hw == 2) {
      asm volatile("griddepcontrol.wait;" ::: "memory");
      if (lane == 0) { if (cta == 0) st_relaxed_u32(a.go, 1); issue_x(0); }
    }
    if (hw == 0) {
      bar_sync(B_QK, 160);
      if (lane == 0) {
        stage_w(&tmWq, sb + OFF_WQ, sb + MB_Q, 0);
      }
      bar_sync(B_SL, 160); if (lane == 0) stage_w(&tmWq, sb + OFF_WQ, sb + MB_Q, 1);
    }
    if (hw == 1) {
      bar_sync(B_V, 160);
      if (lane == 0) {
        stage_wo(0);
      }
      bar_sync(B_O, 160); if (lane == 0) { stage_wo(1); stage_wo(2); }
    }
    __syncwarp();
    {
      uint32_t m = 0;
#pragma unroll
      for (int i = 0; i < 5; i++) {
        m = amax_bf2(amax_bf2(m, amax_bf2(v[i].x, v[i].y)), amax_bf2(v[i].z, v[i].w));
      }
      m = amax_fold(m);
      if (lane == 0) sts32(sb + SC_MX + hw * 4, m);
      bar_sync(B_H, 128);
      const uint4 mm = lds128(sb + SC_MX);
      const int se = max(wscale_exp(max(max(mm.x, mm.y), max(mm.z, mm.w))), -100);
      const float sc = exp2i(se);
#pragma unroll
      for (int i = 0; i < 5; i++) {
        const int c = ht + 128 * i, t = c & 7, chn = c >> 3;
        sts128(sb + OFF_MEM + chn * 128 + ((t ^ (2 * (chn & 3))) << 4), bf2_to_h2(v[i].x, sc), bf2_to_h2(v[i].y, sc), bf2_to_h2(v[i].z, sc), bf2_to_h2(v[i].w, sc));
      }
      if (lead) { sts32(sb + SC_IN, __float_as_uint(exp2i(-se))); sts32(sb + SC_IN + 4, 0x7800u); }
    }
    {
      const uint32_t p0 = sb + OFF_WQ + hw * 2048 + lane * 16;
      uint32_t m = 0;
#pragma unroll 1
      for (int i = 0; i < 10; i++) {
        if (i == 0 || i == 5) mbar_wait(sb + MB_Q + (i ? 8 : 0), 0);
        uint32_t r[4][4];
        static_for<0, 4>([&](auto K) { ldsm_x4_i<K.value * 512>(r[K.value], p0 + i * 8192); });
#pragma unroll
        for (int k = 0; k < 4; k++) m = amax_bf2(amax_bf2(m, amax_bf2(r[k][0], r[k][1])), amax_bf2(r[k][2], r[k][3]));
      }
      m = amax_fold(m);
      if (lane == 0) asm volatile("red.shared.max.u32 [%0], %1;" :: "r"(sb + SC_W + 8), "r"(m) : "memory");
      bar_sync(B_H, 128);
      const uint32_t sc = (uint32_t)(wscale_exp(lds32_i<SC_W + 8>(sb)) + 127) * 0x00800080u;
      uint32_t r[4][4];
      static_for<0, 2>([&](auto K) { ldsm_x4_i<K.value * 512>(r[K.value], p0); });
      auto cvt = [&](uint32_t (&x)[4], uint32_t p) { bf2_to_h2_inplace(x[0], sc); bf2_to_h2_inplace(x[1], sc); bf2_to_h2_inplace(x[2], sc); bf2_to_h2_inplace(x[3], sc); stsm_x4(p, x[0], x[1], x[2], x[3]); };
#pragma unroll 1
      for (int i = 0; i < 10; i++) {
        const uint32_t p = p0 + i * 8192;
        ldsm_x4_i<1024>(r[2], p); ldsm_x4_i<1536>(r[3], p);
        cvt(r[0], p); cvt(r[1], p + 512);
        ldsm_x4_i<8192>(r[0], p); ldsm_x4_i<8192 + 512>(r[1], p);
        cvt(r[2], p + 1024); cvt(r[3], p + 1536);
      }
    }
    bar_sync(0, 384);
    if (hw == 3) {
      const uint32_t eye = ((lane >> 3) == (lane & 3)) ? ((lane & 4) ? 0x3f800000u : 0x3f80u) : 0u;
      sts128(sb + OFF_LT + lane * 16, eye, eye, (lane & 2) * 64 + (lane >> 2) * 16 + (lane & 1) * 8, 0u);
      sts64(sb + OFF_S + 1280 + lane * 8, 0u, 0u);
    }
    if (lead) st_relaxed_u32(arena + AR_TAB + cta * 4, 0x80000000u | (lds32_i<SC_W>(sb) << 15) | lds32_i<SC_W + 4>(sb));
    asm volatile("barrier.cluster.wait.aligned;" ::: "memory");
    bar_sync(B_MEM0, 256); bar_sync(B_MEM1, 256);
    {
      uint32_t v0, v1, v2; int spin = 0;
      do {
        v0 = ld_relaxed_u32(arena + AR_TAB + lane * 4); v1 = ld_relaxed_u32(arena + AR_TAB + 128 + lane * 4); v2 = ld_relaxed_u32(arena + AR_TAB + 256 + lane * 4);
      } while (__any_sync(0xffffffffu, ((v0 & v1 & v2) >> 31) == 0) && ++spin < SPIN_LIMIT);
      const uint32_t mv = (max(max(v0, v1), v2) >> 15) & 0x7fffu, mo = max(max(v0 & 0x7fffu, v1 & 0x7fffu), v2 & 0x7fffu);
      sts32(sb + SC_IN + 8 + (lane & 1) * 16, 15 - ((__reduce_max_sync(0xffffffffu, mv) >> 7) + (__reduce_max_sync(0xffffffffu, mo) >> 7) - 252 + 22));
    }

    auto store_kv = [&](int s) {
      const size_t o = ((size_t)s * 96 + cta) * KVB; const uint32_t src = sb + OFF_KV + (s & 1) * (2 * KVB);
      fence_proxy_async(); bulk_s2g(a.kg + o, src, KVB); bulk_s2g(a.vg + o, src + KVB, KVB); bulk_commit();
    };
    const int cb28 = unit28(hw), du = (unit24(hw) - cb28) * 128;
    uint32_t n16 = lane * 16, hist = 0;
    const uint32_t us1 = sb + d1 + OFF_SR + 256 + (hw >> 1) * 512 + (hw & 1) * 128, us2 = sb + d2 + OFF_SR + (hw >> 1) * 512 + (hw & 1) * 128;
    const uint32_t uo1 = sb + d1 + OFF_O + 2048 + hw * 256, uo2 = sb + d2 + OFF_O + 1024 + hw * 256;
#pragma unroll 1
    for (int s = 0; s < cfg::NSEG; s++) {
      const bool last = s == cfg::NSEG - 1;
      if (n16 == 0) {
        if (hw == 2 && !last) issue_x(s + 1);
        if (hw == 0 && (s & 3) == 1 && s > 1) st_relaxed_u32(arena + (prog_off(h, j) + lds32_i<SC_IN + 12>(sb)), s - 1);
        if (hw == 0 && s > 0) store_kv(s - 1);
        if (PFX && hw == 3 && cta < 80 && s + PFX < cfg::NSEG) prefetch_l2(xg + (size_t)(s + PFX) * 40960 + cta * 512, 512);
        if (PFACC && hw == 1 && s + PFACC < cfg::NSEG - 1)
          asm volatile("prefetch.global.L2 [%0];" :: "l"(arena + (AR_ACC + acc_step(s + PFACC) + acc_lane(cta / 24, (cta & 3) * 8) + acc_voff((cta % 24) >> 2))) : "memory");
      }
      __syncwarp();
      if (last) break;
      const uint32_t kv = (s & 1) * (2 * KVB);
      n16 = fresh(n16);
      uint32_t kb0[4], kb1[4];
      { const uint32_t ka = n16 + (n16 & 384) * 4 + (sb + kv + hw * 128); ldsm_x4_i<OFF_KV>(kb0, ka); ldsm_x4_i<OFF_KV + 2560>(kb1, ka); }
      bar_sync(B_QK, 384);
      {
        uint32_t q0[4], q1[4], q2[4], q3[4];
        float sa[4] = {0, 0, 0, 0}, sc2[4] = {0, 0, 0, 0};
        ldsm_x4_i<OFF_Q>(q0, n16 + sb); ldsm_x4_i<OFF_Q + 1024>(q2, n16 + sb); ldsm_x4_i<OFF_Q + 512>(q1, n16 + sb);
        bar_arrive(B_A, 288);
        ldsm_x4_i<OFF_Q + 1536>(q3, n16 + sb);
        mma16816(sa, q0[0], q0[1], q0[2], q0[3], kb0[0], kb0[1]);
        mma16816(sc2, q2[0], q2[1], q2[2], q2[3], kb1[0], kb1[1]);
        mma16816(sa, q1[0], q1[1], q1[2], q1[3], kb0[2], kb0[3]);
        mma16816(sc2, q3[0], q3[1], q3[2], q3[3], kb1[2], kb1[3]);
        const float x0 = (sa[0] + sa[2]) + (sc2[0] + sc2[2]), x1 = (sa[1] + sa[3]) + (sc2[1] + sc2[3]);
        const uint32_t xp = pack_bf16(x0, x1);
        st_async_b32_i<0>((n16 >> 2) + us1, xp, sb + MB_S + d1);
        st_async_b32_i<0>((n16 >> 2) + us2, xp, sb + MB_S + d2);
        stsm_x2(n16 + (sb + OFF_S + hw * 256), __float_as_uint(x0), __float_as_uint(x1));
      }
      uint32_t v0[4], v1[4], vm0, vm1;
      const uint32_t uv = sb + kv + hw * 1280;
      ldsm_x4_t_i<OFF_KV + KVB>(v0, n16 + uv); ldsm_x4_t_i<OFF_KV + KVB + 640>(v1, n16 + uv);
      bar_sync(B_SL, 256);
      float t0[4], t1[4], t2[4];
      { uint32_t x[4]; ldsm_x4_i<OFF_S>(x, n16 + sb); t0[0] = __uint_as_float(x[0]); t0[1] = __uint_as_float(x[1]); t0[2] = __uint_as_float(x[2]); t0[3] = __uint_as_float(x[3]); }
      { uint32_t x[4]; ldsm_x4_i<OFF_S + 512>(x, n16 + sb); t1[0] = __uint_as_float(x[0]); t1[1] = __uint_as_float(x[1]); t1[2] = __uint_as_float(x[2]); t1[3] = __uint_as_float(x[3]); }
      { uint32_t x[4]; ldsm_x4_i<OFF_S + 1024>(x, n16 + sb); t2[0] = __uint_as_float(x[0]); t2[1] = __uint_as_float(x[1]); t2[2] = __uint_as_float(x[2]); t2[3] = __uint_as_float(x[3]); }
      mbar_spin(sb + MB_S, s & 1);
      uint2 xo;
      {
        uint32_t r0[4], r1[4], r2[2];
        ldsm_x4_i<OFF_SR>(r0, n16 + sb); ldsm_x4_i<OFF_SR + 512>(r1, n16 + sb); ldsm_x2_i<OFF_SR + 1024>(r2, n16 + sb);
        SFENCE(n16);
        const uint2 eye = lds64_i<OFF_LT>(n16 + sb);
        mma16816(t0, r0[0], r0[1], r0[2], r0[3], eye.x, eye.y);
        mma16816(t1, r1[0], r1[1], r1[2], r1[3], eye.x, eye.y);
        mma1688(t2, r2[0], r2[1], eye.x);
        bar_sync(B_V, 256);
        vm0 = ldsm_x1_t_i<OFF_KV + KVB + 512>(n16 + uv); vm1 = ldsm_x1_t_i<OFF_KV + KVB + 1152>(n16 + uv);
        SFENCE(n16);
        xo = lds64_i<OFF_LT + 8>(n16 + sb);
      }
      float sc[10] = {t0[0], t0[1], t0[2], t0[3], t1[0], t1[1], t1[2], t1[3], t2[0] + t2[2], t2[1] + t2[3]};
      float mx = fmaxf(fmaxf(fmaxf(sc[0], sc[1]), fmaxf(sc[2], sc[3])), fmaxf(fmaxf(sc[4], sc[5]), fmaxf(sc[6], sc[7])));
      mx = fmaxf(mx, fmaxf(sc[8], sc[9]));
      {
        const float m1 = __shfl_xor_sync(0xffffffffu, mx, 1), m2 = __shfl_xor_sync(0xffffffffu, mx, 2), m3 = __shfl_xor_sync(0xffffffffu, mx, 3);
        mx = fmaxf(fmaxf(mx, m1), fmaxf(m2, m3));
      }
      const float mo = __fadd_rn(mx, __uint_as_float(xo.x));
      auto ex = [&](int i) -> uint32_t { float x, y;
        asm volatile("ex2.approx.ftz.f32 %0, %1;" : "=f"(x) : "f"(__fsub_rn(sc[i], mo))); asm volatile("ex2.approx.ftz.f32 %0, %1;" : "=f"(y) : "f"(__fsub_rn(sc[i + 1], mo)));
        return pack_bf16(x, y); };
      float oa[4] = {0, 0, 0, 0}, ob[4] = {0, 0, 0, 0}, oc[4] = {0, 0, 0, 0}, od[4] = {0, 0, 0, 0}, rs[4] = {0, 0, 0, 0};
      const uint32_t ones = 0x3f803f80u;
      const uint32_t p4 = ex(8);
      if (MEMFIRST) { mma1688(rs, p4, 0u, ones); mma1688(oa, p4, 0u, vm0); mma1688(ob, p4, 0u, vm1); }
      const uint32_t p0 = ex(0), p1 = ex(2), p2 = ex(4), p3 = ex(6);
      mma16816(rs, p0, p2, p1, p3, ones, ones);
      mma16816(oa, p0, p2, p1, p3, v0[0], v0[1]);
      mma16816(oc, p0, p2, p1, p3, v0[2], v0[3]);
      mma16816(ob, p0, p2, p1, p3, v1[0], v1[1]);
      mma16816(od, p0, p2, p1, p3, v1[2], v1[3]);
      if (!MEMFIRST) { mma1688(rs, p4, 0u, ones); mma1688(oa, p4, 0u, vm0); mma1688(ob, p4, 0u, vm1); }
      const float inv = rcpf(rs[0] + rs[2]) * __uint_as_float(xo.y);
      {
        const uint32_t y0 = pack_bf16((oa[0] + oc[2]) * inv, (oa[1] + oc[3]) * inv), y1 = pack_bf16((ob[0] + od[2]) * inv, (ob[1] + od[3]) * inv);
        st_async_v2_i<0>(xo.x + uo1, y0, y1, sb + MB_O + d1);
        st_async_v2_i<0>(xo.x + uo2, y0, y1, sb + MB_O + d2);
        sts64_i<OFF_O>(xo.x + (sb + hw * 256), y0, y1);
      }
      bar_arrive(B_O, 384);
      if (hw == 0) bulk_wait<0>();
      mbar_expect_tx_if(n16 == 0 && hw == 3, sb + MB_S, 1280);
      n16 = fresh(n16);
      const int ln = n16 >> 4;
      auto mslot = [&](int c) -> uint32_t { return sb + OFF_MEM + c * 128 + (((ln >> 2) ^ (2 * (c & 3))) << 4); };
      const int lq = ln & 3;
      const uint32_t ma = mslot(cb28 + lq), mb_ = mslot(cb28 + (lq >> 1)) + (lq & 1) * 8;
      const unsigned char* gp = arena + (AR_ACC + acc_lane(hw, ln) + acc_step(s));
      const bool odd = ln & 1;
      const uint32_t delay = a.delay + ((hist & 2) ? a.margin : 0);
      SFENCE(ma);
      uint32_t tw;
      if (hw == 0 && (s & 3) == 0 && a.pubrel) {
        bar_arrive(B_RED, 384);
        asm volatile("fence.acq_rel.gpu;" ::: "memory");
        uint2 t; int sp = 0;
        do { asm volatile("ld.volatile.shared.v2.u32 {%0,%1}, [%2];" : "=r"(t.x), "=r"(t.y) : "r"(sb + SC_TW) : "memory"); } while (__any_sync(0xffffffffu, t.y != (uint32_t)s) && ++sp < SPIN_LIMIT);
        tw = t.x;
      } else {
        bar_sync(B_RED, 384);
        SFENCE(mb_);
        tw = clk_v();
        if (hw == 1) asm volatile("st.volatile.shared.v2.u32 [%0], {%1,%2};" :: "r"(sb + SC_TW), "r"(tw), "r"(s) : "memory");
      }
      mbar_expect_tx_if(n16 == 0 && hw == 3, sb + MB_O, 2048);
      while (clk_v() - tw < delay) {}
      uint4 v[6];
      int spin = 0;
      const uint32_t cm = odd ? 0x5000u : 0u;
      do {
        static_for<0, 6>([&](auto I) { v[I.value] = ld_relaxed_v4_i<acc_voff(I.value)>(gp); });
      } while (__any_sync(0xffffffffu, (~((v[0].w & v[1].w & v[2].w) & (v[3].w & v[4].w & v[5].w)) & cm) != 0) && ++spin < SPIN_LIMIT);
      v[0].w = odd ? v[3].x : v[0].w; v[1].w = odd ? v[3].y : v[1].w; v[2].w = odd ? v[3].z : v[2].w; v[3].w = odd ? 0u : v[3].w;
      sts128_i<0>(ma, v[0].x, v[0].y, v[0].z, v[0].w);
      sts128_i<512>(ma, v[1].x, v[1].y, v[1].z, v[1].w);
      sts128_i<1024>(ma, v[2].x, v[2].y, v[2].z, v[2].w);
      sts128_i<0>(ma + du, v[4].x, v[4].y, v[4].z, v[5].z);
      sts64_i<512>(mb_ + du, v[5].x, v[5].y);
      if (!odd) sts128_i<1536>(mb_, v[3].x, v[3].y, v[3].z, v[3].w);
      hist = (hist * 2 + (spin != 0)) & 0xffffu;
      bar_sync(B_MEM0, 256); bar_sync(B_MEM1, 256);
      uint32_t m = lds32_i<SC_IN + 12>(sb);
      uint32_t m2 = m;
      static_for<0, 3>([&](auto I) { m = amax_h2(amax_h2(amax_h2(amax_h2(m, v[I.value].x), v[I.value].y), v[I.value].z), v[I.value].w); });
      static_for<3, 6>([&](auto I) { m2 = amax_h2(amax_h2(amax_h2(m2, v[I.value].x), v[I.value].y), v[I.value].z); });
      m = amax_fold(amax_h2(amax_h2(m2, v[3].w), m));
      if (n16 == 0) asm volatile("red.shared.max.u32 [%0], %1;" :: "r"(sb + SC_IN + 4 + 16 * ((s + 1) & 1)), "r"(m) : "memory");
    }
    bar_sync(B_RED, 384);
    if (hw == 0 && n16 == 0) {
      store_kv(cfg::NSEG - 1);
      bulk_wait<0>();
      st_release_u32(arena + (prog_off(h, j) + lds32_i<SC_IN + 12>(sb)), cfg::NSEG);
    }
    __syncwarp();
    asm volatile("barrier.cluster.arrive.relaxed.aligned; barrier.cluster.wait.aligned;" ::: "memory");
  } else {
    asm volatile("setmaxnreg.inc.sync.aligned.u32 232;");
    const int wi = warp & 3, hf = warp >> 2;
    int lane = fresh(threadIdx.x & 31);
    uint32_t w[40][4], wm = 0;
    uint32_t wqa;
    { const int r8 = lane & 7, mrow = r8 + ((lane >> 4) << 3), mch = 2 * wi + ((lane >> 3) & 1); wqa = sb + mrow * 128 + ((mch ^ r8) << 4); }
    float iw, iq;
#pragma unroll 1
    for (int live = a.dry ? 0 : 1; live < 2; live++) {
      const uint32_t wa = wqa + (hf ? OFF_WO : OFF_WQ);
      wm = 0;
      mbar_wait_if(live, sb + (hf ? MB_V : MB_K), 0);
      static_for<0, 20>([&](auto K) { ldsm_x4_t_i<K.value * 2048>(w[K.value], wa); });
#pragma unroll
      for (int k = 0; k < 20; k++) wm = amax_bf2(amax_bf2(wm, amax_bf2(w[k][0], w[k][1])), amax_bf2(w[k][2], w[k][3]));
      SFENCE2(wa, wm);
      if (live) bar_arrive(hf ? B_V : B_QK, 160);
      mbar_wait_if(live, sb + (hf ? MB_V : MB_K) + 8, 0);
      static_for<20, 40>([&](auto K) { ldsm_x4_t_i<K.value * 2048>(w[K.value], wa); });
#pragma unroll
      for (int k = 20; k < 40; k++) wm = amax_bf2(amax_bf2(wm, amax_bf2(w[k][0], w[k][1])), amax_bf2(w[k][2], w[k][3]));
      SFENCE2(wa, wm);
      if (live) bar_arrive(hf ? B_O : B_SL, 160);
      SFENCE(wa);
      const uint32_t m = amax_fold(wm);
      if (hf && live) asm volatile("red.shared.max.u32 [%0], %1;" :: "r"(sb + SC_W), "r"(m) : "memory");
      const int e = wscale_exp(m);
      const uint32_t sc = (uint32_t)(e + 127) * 0x00800080u; iw = exp2i(-e);
#pragma unroll
      for (int k = 0; k < 40; k++) { bf2_to_h2_inplace(w[k][0], sc); bf2_to_h2_inplace(w[k][1], sc); bf2_to_h2_inplace(w[k][2], sc); bf2_to_h2_inplace(w[k][3], sc); }
    }
    iw = uniform_f(iw);
    uint32_t x0[8];
    {
      float xa[16];
      const uint32_t dlo = (((sb + OFF_X) & 0x3FFFF) >> 4) | (1u << 16);
      mbar_wait(sb + MB_X, 0);
      wgmma_fence();
      static_for<0, 40>([&](auto K) { constexpr int k = K.value; wgmma_rs32h<((k >> 2) * 4096 + (k & 3) * 32) / 16, (k != 0)>(xa, w[k], dlo); });
      wgmma_commit();
      wgmma_wait<0>();
#pragma unroll
      for (int i = 0; i < 8; i++) x0[i] = pack_bf16(xa[2 * i] * iw, xa[2 * i + 1] * iw);
    }
    lane = fresh(threadIdx.x & 31);
    const int g = lane >> 2, q4 = lane & 3, r8 = lane & 7, m4 = lane >> 3;
    const bool t28 = j == 0 || warp < 4;
    const int bi = j == 0 ? hf : (warp < 4 ? j + 1 : 2 * (j - 1) + ((warp - 4) >> 1)), bv = t28 ? wi : 4 + (warp & 1);
    uint32_t wo1 = sb + OFF_WO + warp * 896 + lane * 16, wo2;
    {
      const int cb = (t28 ? unit28(bi) : unit24(bi)) - col0 / 8;
      uint32_t cp[4];
#pragma unroll
      for (int wd = 0; wd < 4; wd++) {
        int c, p;
        if (bv < 3) { c = 4 * bv + q4; p = wd; }
        else if (bv == 3) { if (q4 & 1) { c = 4 * (wd % 3) + q4; p = 3; } else { c = 12 + (q4 >> 1); p = wd; } }
        else if (bv == 4) { c = q4; p = wd; }
        else { if (wd < 2) { c = 4 + (q4 >> 1); p = 2 * (q4 & 1) + wd; } else { c = q4; p = 3; } }
        cp[wd] = sb + OFF_WO + ((g & 1) + (g & 2) * 4 + (g >> 2) * 2) * WOS + (cb + c) * 16 + p * 4;
      }
      const int cidx = (r8 & 1) + ((r8 >> 2) << 1);
      wo2 = sb + OFF_WO + warp * 896 + ((m4 & 1) ? 768 + (m4 >> 1) * 64 + cidx * 16 : 512 + (m4 >> 1) * 128 + r8 * 16);
      const bool dump = (m4 & 1) && (r8 & 2);
      uint32_t mo = 0;
      const bool regular = bv < 3 || bv == 4;
#pragma unroll 1
      for (int i = 0; i < 3; i++) {
        uint32_t x[4][4], y[4][4];
        const uint32_t o = i * 4 * WOK;
        mbar_wait(sb + MB_R + 8 * i, 0);
        if (regular) {
          static_for<0, 4>([&](auto K) {
            constexpr int kk = K.value;
            const uint4 u = lds128_i<kk * WOK>(cp[0] + o), v = lds128_i<kk * WOK + 4 * WOS>(cp[0] + o);
            x[kk][0] = u.x; x[kk][1] = u.y; x[kk][2] = u.z; x[kk][3] = u.w; y[kk][0] = v.x; y[kk][1] = v.y; y[kk][2] = v.z; y[kk][3] = v.w;
          });
        } else {
          static_for<0, 4>([&](auto K) {
            constexpr int kk = K.value;
#pragma unroll
            for (int wd = 0; wd < 4; wd++) { x[kk][wd] = lds32_i<kk * WOK>(cp[wd] + o); y[kk][wd] = lds32_i<kk * WOK + 4 * WOS>(cp[wd] + o); }
          });
        }
        bar_sync(B_C, 256);
        static_for<0, 4>([&](auto K) {
          constexpr int kk = K.value;
#pragma unroll
          for (int wd = 0; wd < 4; wd++) mo = amax_bf2(mo, amax_bf2(x[kk][wd], y[kk][wd]));
          stsm_x4_t_i<kk * WOK>(wo1 + o, x[kk][0], x[kk][1], y[kk][0], y[kk][1]);
          stsm_x4_t_i<0>(dump ? sb + OFF_S + 512 + lane * 16 : wo2 + o + kk * WOK, x[kk][2], x[kk][3], y[kk][2], y[kk][3]);
        });
      }
      mo = amax_fold(mo);
      if (lane == 0) asm volatile("red.shared.max.u32 [%0], %1;" :: "r"(sb + SC_W + 4), "r"(mo) : "memory");
    }
    __syncwarp();
    auto run = [&](auto HF) {
    constexpr int hf = HF.value;
    uint32_t mema, sta, l16 = sb + lane * 16;
    uint32_t rq[hf ? NP1 : NQ0][4];
    auto step_addr = [&](uint32_t kv) {
      const int lr = (l16 >> 4) & 7, lm = (l16 >> 7) & 3;
      mema = l16 ^ (lm << 5);
      sta = sb + lr * 16 + (lm < 2 ? OFF_Q + wi * 512 + hf * 128 + lm * 256 : OFF_KV + kv + 512 + (2 * wi + lm - 2) * 640);
    };
    auto x_gemm = [&](uint32_t ph) {
      float xa[16];
      const uint32_t dlo = (((sb + OFF_X) & 0x3FFFF) >> 4) | (1u << 16);
      constexpr int NP = hf ? NP1 : NP0;
      if constexpr (hf) {
        static_for<PQE, NP>([&](auto K) { ldsm_x4_t_i<OFF_WQ + K.value * 2048>(rq[K.value], wqa); });
        bar_sync(B_X, 256);
      }
      wgmma_fence();
      static_for<0, 40>([&](auto K) {
        constexpr int k = K.value;
        wgmma_rs32h<((k >> 2) * 4096 + (k & 3) * 32) / 16, (k != 0)>(xa, w[k], dlo);
        if constexpr (!hf && k == PFK && NP > PQE) { SFENCE(wqa); static_for<PQE, NP>([&](auto K) { ldsm_x4_t_i<OFF_WQ + K.value * 2048>(rq[K.value], wqa); }); SFENCE(wqa); }
        if constexpr (!hf && k == XT) bar_arrive(B_X, 256);
      });
      step_addr(ph * (2 * KVB));
      wgmma_commit();
      wgmma_wait<0>();
      const uint32_t xs = l16 + (wi * 1280 + ph * (2 * KVB));
      stsm_x4_t_i<OFF_KV + hf * KVB>(xs, pack_bf16(xa[0] * iw, xa[1] * iw), pack_bf16(xa[4] * iw, xa[5] * iw), pack_bf16(xa[8] * iw, xa[9] * iw), pack_bf16(xa[12] * iw, xa[13] * iw));
      stsm_x4_t_i<OFF_KV + hf * KVB + 640>(xs, pack_bf16(xa[2] * iw, xa[3] * iw), pack_bf16(xa[6] * iw, xa[7] * iw), pack_bf16(xa[10] * iw, xa[11] * iw), pack_bf16(xa[14] * iw, xa[15] * iw));
      if constexpr (!hf) static_for<NP0, NP0 + NPL>([&](auto K) { ldsm_x4_t_i<OFF_WQ + K.value * 2048>(rq[K.value], wqa); });
    };
    auto wq_addr = [&](uint32_t l) -> uint32_t {
      const int lr = (l >> 4) & 7, lm = (l >> 7) & 3;
      return sb + hf * ((40 - NQ1) * 2048) + (lr + ((lm >> 1) << 3)) * 128 + (((2 * wi + (lm & 1)) ^ lr) << 4);
    };
    constexpr int NPM = hf ? NPM1 : NPM0;
    uint32_t u1[NPM][4], u2[NPM][4];
    static_for<0, NPM>([&](auto K) { ldsm_x4_i<(12 - NPM + K.value) * WOK>(u1[K.value], wo1); ldsm_x4_i<(12 - NPM + K.value) * WOK>(u2[K.value], wo2); });
    bar_sync(0, 384);
    iq = uniform_f(exp2i(-wscale_exp(lds32_i<SC_W + 8>(sb))) * (0.07216878364870322f * 1.4426950408889634f));
    wqa = wq_addr(l16);
    static_for<0, (hf ? NP1 : NP0 + NPL)>([&](auto K) { ldsm_x4_t_i<OFF_WQ + K.value * 2048>(rq[K.value], wqa); });
    step_addr(0);
    stsm_x4_t_i<OFF_KV + hf * KVB>(l16 + wi * 1280, x0[0], x0[2], x0[4], x0[6]);
    stsm_x4_t_i<OFF_KV + hf * KVB + 640>(l16 + wi * 1280, x0[1], x0[3], x0[5], x0[7]);
    asm volatile("barrier.cluster.wait.aligned;" ::: "memory");
#pragma unroll 1
    for (int s = 0; s < cfg::NSEG - 1; s++) {
      bar_sync(hf ? B_MEM1 : B_MEM0, 256);
      const float sin_ = __uint_as_float(lds32_i<SC_IN>(sb + 16 * (s & 1)));
      constexpr int NPQ = (40 - NQ1) / 2;
      if constexpr (hf == 0) {
        float k0[4] = {0, 0, 0, 0}, k1[4] = {0, 0, 0, 0}, q0[4] = {0, 0, 0, 0}, q1[4] = {0, 0, 0, 0};
        constexpr auto pair_of = [](int t) { const int a = t * (20 - NPQ) / 20, b = (t + 1) * (20 - NPQ) / 20; return b > a ? NPQ + a : t - a; };
        uint32_t b[NB0][4];
        static_for<0, NB0>([&](auto T) { ldsm_x4_i<OFF_MEM + pair_of(T.value) * 512>(b[T.value], mema); });
        static_for<NP0 + NPL, NQ0>([&](auto K) { ldsm_x4_t_i<OFF_WQ + K.value * 2048>(rq[K.value], wqa); });
        static_for<0, 20>([&](auto T) {
          constexpr int t = T.value, p = pair_of(t);
          uint32_t (&bb)[4] = b[t % NB0];
          if constexpr (p < NPQ) {
            mma16816h(q0, rq[(2 * p) % NQ0], bb[0], bb[1]);
            if constexpr (2 * p + NQ0 < 2 * NPQ) ldsm_x4_t_i<OFF_WQ + (2 * p + NQ0) * 2048>(rq[(2 * p) % NQ0], wqa);
          }
          mma16816h(k0, w[2 * p], bb[0], bb[1]);
          if constexpr (p < NPQ) {
            mma16816h(q1, rq[(2 * p + 1) % NQ0], bb[2], bb[3]);
            if constexpr (2 * p + 1 + NQ0 < 2 * NPQ) ldsm_x4_t_i<OFF_WQ + (2 * p + 1 + NQ0) * 2048>(rq[(2 * p + 1) % NQ0], wqa);
          }
          mma16816h(k1, w[2 * p + 1], bb[2], bb[3]);
          if constexpr (NVE > 0 && t + NB0 == VET) bar_arrive(B_E, 256);
          if constexpr (t + NB0 < 20) ldsm_x4_i<OFF_MEM + pair_of(t + NB0) * 512>(bb, mema);
        });
        const float sq = sin_ * iq, sk = sin_ * iw;
        stsm_x4_t_i<0>(sta, pack_bf16((q0[0] + q1[0]) * sq, (q0[1] + q1[1]) * sq), pack_bf16((q0[2] + q1[2]) * sq, (q0[3] + q1[3]) * sq),
                       pack_bf16((k0[0] + k1[0]) * sk, (k0[1] + k1[1]) * sk), pack_bf16((k0[2] + k1[2]) * sk, (k0[3] + k1[3]) * sk));
        bar_sync(B_QK, 384);
        {
          if (wi == 3) {
            const uint32_t xr = sb + ((l16 & 511) >> 2), ka = l16 + (l16 & 384) * 4 + (s & 1) * (2 * KVB);
            uint32_t a0[4], a1[4], a2[4], a3[4], kb0[4], kb1[4];
            ldsm_x4_i<OFF_Q>(a0, l16); ldsm_x4_i<OFF_KV + 512>(kb0, ka); ldsm_x4_i<OFF_Q + 1024>(a2, l16); ldsm_x4_i<OFF_KV + 512 + 2560>(kb1, ka);
            ldsm_x4_i<OFF_Q + 512>(a1, l16);
            bar_arrive(B_A, 288);
            ldsm_x4_i<OFF_Q + 1536>(a3, l16);
            float sa[4] = {0, 0, 0, 0}, sc2[4] = {0, 0, 0, 0};
            mma16816(sa, a0[0], a0[1], a0[2], a0[3], kb0[0], kb0[1]);
            mma16816(sc2, a2[0], a2[1], a2[2], a2[3], kb1[0], kb1[1]);
            mma16816(sa, a1[0], a1[1], a1[2], a1[3], kb0[2], kb0[3]);
            mma16816(sc2, a3[0], a3[1], a3[2], a3[3], kb1[2], kb1[3]);
            const float x0 = (sa[0] + sa[2]) + (sc2[0] + sc2[2]), x1 = (sa[1] + sa[3]) + (sc2[1] + sc2[3]);
            const uint32_t xp = pack_bf16(x0, x1);
            st_async_b32_i<OFF_SR + 1024 + 128>(xr + d1, xp, sb + MB_S + d1);
            st_async_b32_i<OFF_SR + 1024>(xr + d2, xp, sb + MB_S + d2);
            stsm_x2(l16 + OFF_S + 1024, __float_as_uint(x0), __float_as_uint(x1));
          } else if (wi == 0) {
            const uint4 si = lds128_i<SC_IN>(sb + 16 * (s & 1));
            const int em = (int)(si.y >> 10) - 14 + (int)(si.x >> 23) - 127;
            const uint32_t osc = __float_as_uint(exp2i(max(min((int)si.z - max(em, 1), 100), -100)));
            sts32(l16 + OFF_LT + 12, osc); sts64_i<SC_IN>(sb + 16 * ((s + 1) & 1), 0x7f000000u - osc, 0u);
          }
          bar_sync(B_SL, 256);
        }
      } else {
        float v0[4] = {0, 0, 0, 0}, v1[4] = {0, 0, 0, 0}, q0[4] = {0, 0, 0, 0}, q1[4] = {0, 0, 0, 0};
        constexpr int NB1 = NQ1 / 2 < 3 ? NQ1 / 2 : 3;
        uint32_t b[NB1][4];
        static_for<0, NB1>([&](auto T) { ldsm_x4_i<OFF_MEM + (NPQ + T.value) * 512>(b[T.value], mema); });
        static_for<0, NQ1 / 2>([&](auto T) {
          constexpr int t = T.value, p = NPQ + t;
          uint32_t (&bb)[4] = b[t % NB1];
          mma16816h(q0, rq[(2 * t) % NP1], bb[0], bb[1]);
          if constexpr (2 * t + NP1 < NQ1) ldsm_x4_t_i<OFF_WQ + (2 * t + NP1) * 2048>(rq[(2 * t) % NP1], wqa);
          mma16816h(q1, rq[(2 * t + 1) % NP1], bb[2], bb[3]);
          if constexpr (2 * t + 1 + NP1 < NQ1) ldsm_x4_t_i<OFF_WQ + (2 * t + 1 + NP1) * 2048>(rq[(2 * t + 1) % NP1], wqa);
          mma16816h(v0, w[2 * p], bb[0], bb[1]);
          mma16816h(v1, w[2 * p + 1], bb[2], bb[3]);
          if constexpr (t + NB1 < NQ1 / 2) ldsm_x4_i<OFF_MEM + (p + NB1) * 512>(bb, mema);
        });
        const float sq = sin_ * iq, sv = sin_ * iw;
        stsm_x2_t_i<0>(sta, pack_bf16((q0[0] + q1[0]) * sq, (q0[1] + q1[1]) * sq), pack_bf16((q0[2] + q1[2]) * sq, (q0[3] + q1[3]) * sq));
        bar_arrive(B_QK, 384);
        float v2[4] = {0, 0, 0, 0}, v3[4] = {0, 0, 0, 0};
        auto vpair = [&](auto P, uint32_t (&bb)[4]) {
          constexpr int p = P.value;
          if constexpr (p & 1) { mma16816h(v0, w[2 * p], bb[0], bb[1]); mma16816h(v1, w[2 * p + 1], bb[2], bb[3]); }
          else { mma16816h(v2, w[2 * p], bb[0], bb[1]); mma16816h(v3, w[2 * p + 1], bb[2], bb[3]); }
        };
        if constexpr (NVE > 0) {
          uint32_t e[NVE ? NVE : 1][4];
          bar_sync(B_E, 256);
          static_for<0, NVE>([&](auto T) { ldsm_x4_i<OFF_MEM + T.value * 512>(e[T.value], mema); });
          static_for<0, NVE>([&](auto T) { vpair(T, e[T.value]); });
        }
        bar_sync(B_A, 288);
        uint32_t c[4][4];
        static_for<NVE, (NVE + 4 < NPQ ? NVE + 4 : NPQ)>([&](auto T) { ldsm_x4_i<OFF_MEM + T.value * 512>(c[T.value & 3], mema); });
        static_for<NVE, NPQ>([&](auto T) {
          constexpr int p = T.value;
          vpair(T, c[p & 3]);
          if constexpr (p + 4 < NPQ) ldsm_x4_i<OFF_MEM + (p + 4) * 512>(c[p & 3], mema);
        });
        stsm_x2_t_i<OFF_KV + KVB + 512>(l16 + (l16 & 128) * 4 + (wi * 1280 + (s & 1) * (2 * KVB)), pack_bf16(((v0[0] + v1[0]) + (v2[0] + v3[0])) * sv, ((v0[1] + v1[1]) + (v2[1] + v3[1])) * sv),
                            pack_bf16(((v0[2] + v1[2]) + (v2[2] + v3[2])) * sv, ((v0[3] + v1[3]) + (v2[3] + v3[3])) * sv));
        bar_arrive(B_V, 256);
      }
      {
        uint32_t t1[12][4], t2[12][4];
        const uint32_t o16 = l16;
        wo1 = l16 + (OFF_WO + warp * 896);
        wo2 = sb + OFF_WO + warp * 896 + ((l16 & 128) ? 768 + ((l16 & 256) >> 2) + (l16 & 16) + ((l16 & 64) >> 1) : 512 + ((l16 & 256) >> 1) + (l16 & 112));
        constexpr int NR_ = NRT - NPM;
        auto ldw = [&](auto K) { if constexpr (K.value < 12 - NPM) { ldsm_x4_i<K.value * WOK>(t1[K.value], wo1); ldsm_x4_i<K.value * WOK>(t2[K.value], wo2); } };
        constexpr int PB = (hf ? PB1 : PB0) < NR_ ? (hf ? PB1 : PB0) : NR_, PA = (hf ? PA1 : PA0) < PB ? (hf ? PA1 : PA0) : PB;
        static_for<0, PA>(ldw);
        mbar_spin(sb + MB_X, (s + 1) & 1);
        if constexpr (PB > PA) {
          constexpr int PM = PA + PM1 < PB ? PA + PM1 : PB;
          mbar_spin(sb + MB_S, s & 1);
          const uint32_t t0 = clk_v();
          if constexpr (PM > PA) { while (clk_v() - t0 < GD1) {} static_for<PA, PM>(ldw); }
          if constexpr (PB > PM) { while (clk_v() - t0 < GD2) {} static_for<PM, PB>(ldw); }
        }
        float c0[4] = {0, 0, 0, 0}, c1[4] = {0, 0, 0, 0}, e0[4] = {0, 0, 0, 0}, e1[4] = {0, 0, 0, 0};
        uint32_t ob[6][4];
        auto kstep = [&](auto K) {
          constexpr int k = K.value;
          uint32_t (&bb)[4] = ob[k >> 1];
          uint32_t (&x)[4] = k < 12 - NPM ? t1[k] : u1[k < 12 - NPM ? 0 : k - (12 - NPM)];
          uint32_t (&y)[4] = k < 12 - NPM ? t2[k] : u2[k < 12 - NPM ? 0 : k - (12 - NPM)];
          if constexpr (k & 1) { mma16816(c1, x[0], x[1], x[2], x[3], bb[2], bb[3]); mma16816(e1, y[0], y[1], y[2], y[3], bb[2], bb[3]); }
          else { mma16816(c0, x[0], x[1], x[2], x[3], bb[0], bb[1]); mma16816(e0, y[0], y[1], y[2], y[3], bb[0], bb[1]); }
          if constexpr (k >= NRF) ldw(IC<k + NR_ - NRF>{});
        };
        auto ldo = [&](auto P) { ldsm_x4_i<OFF_O + P.value * 512>(ob[P.value], o16); };
        bar_sync(B_O, 384);
        ldo(IC<0>{}); ldo(IC<1>{});
        SFENCE(o16);
        static_for<PB, NR_>(ldw);
        static_for<0, 4>(kstep);
        mbar_spin(sb + MB_O, s & 1);
        ldo(IC<2>{}); ldo(IC<NPM >= 2 ? 5 : 3>{});
        if (WOF) SFENCE(o16);
        kstep(IC<4>{});
        if constexpr (NPM < 2) { kstep(IC<5>{}); ldo(IC<4>{}); kstep(IC<6>{}); kstep(IC<7>{}); ldo(IC<5>{}); static_for<8, 12>(kstep); }
        else if constexpr (NPM >= 4) { kstep(IC<10>{}); kstep(IC<11>{}); ldo(IC<4>{}); kstep(IC<5>{}); ldo(IC<3>{}); kstep(IC<8>{}); kstep(IC<9>{}); kstep(IC<6>{}); kstep(IC<7>{}); }
        else { kstep(IC<5>{}); ldo(IC<3>{}); kstep(IC<11>{}); kstep(IC<10>{}); ldo(IC<4>{}); kstep(IC<6>{}); kstep(IC<7>{}); if constexpr (NPM == 3) { kstep(IC<9>{}); kstep(IC<8>{}); } else { kstep(IC<8>{}); kstep(IC<9>{}); } }
        l16 = fresh(l16);
        const int ln = (l16 >> 4) & 31;
        if constexpr (CEARLY && hf) { SFENCE2(o16, __float_as_uint(e1[0])); bar_arrive(B_G, 256); }
        unsigned char* gr = arena + (AR_ACC + acc_lane(bi, ln) + acc_voff(bv) + acc_step(s));
        const bool cnt = (ln & 1) || !t28;
        wqa = wq_addr(l16);
        SFENCE(o16);
        static_for<0, PQE>([&](auto K) { ldsm_x4_t_i<OFF_WQ + K.value * 2048>(rq[K.value], wqa); });
        const uint32_t y0 = movm_t(pack_f16(c0[0] + c1[0], c0[1] + c1[1])), y1 = movm_t(pack_f16(c0[2] + c1[2], c0[3] + c1[3]));
        const uint32_t y2 = movm_t(pack_f16(e0[0] + e1[0], e0[1] + e1[1])), y3 = movm_t(pack_f16(e0[2] + e1[2], e0[3] + e1[3]));
        asm volatile("red.relaxed.gpu.global.add.noftz.v4.f16x2 [%0], {%1,%2,%3,%4};" :: "l"(gr), "r"(y0), "r"(y1), "r"(y2), "r"(cnt ? 0x3c00u : y3) : "memory");
        bar_arrive(B_RED, 384);
        if constexpr (CEARLY && !hf) { bar_arrive(B_C, 256); bar_sync(B_G, 256); }
        else bar_sync(B_C, 256);
      }
      x_gemm((s + 1) & 1);
    }
    };
    if (hf == 0) run(IC<0>{}); else run(IC<1>{});
    {
      const uint32_t l16 = sb + (threadIdx.x & 31) * 16, mema = l16 ^ ((l16 >> 2) & 96);
      float c0[4] = {0, 0, 0, 0}, c1[4] = {0, 0, 0, 0}, c2[4] = {0, 0, 0, 0}, c3[4] = {0, 0, 0, 0};
      bar_sync(hf ? B_MEM1 : B_MEM0, 256);
      const float sc = __uint_as_float(lds32_i<SC_IN + 16>(sb)) * iw;
      static_for<0, 10>([&](auto T) {
        constexpr int p = 2 * T.value;
        uint32_t b0[4], b1[4];
        ldsm_x4_i<OFF_MEM + p * 512>(b0, mema); ldsm_x4_i<OFF_MEM + p * 512 + 512>(b1, mema);
        mma16816h(c0, w[2 * p], b0[0], b0[1]); mma16816h(c1, w[2 * p + 1], b0[2], b0[3]);
        mma16816h(c2, w[2 * p + 2], b1[0], b1[1]); mma16816h(c3, w[2 * p + 3], b1[2], b1[3]);
      });
      stsm_x2_t_i<OFF_KV + 2 * KVB + 512>(l16 + (l16 & 128) * 4 + wi * 1280 + hf * KVB, pack_bf16(((c0[0] + c1[0]) + (c2[0] + c3[0])) * sc, ((c0[1] + c1[1]) + (c2[1] + c3[1])) * sc),
                                          pack_bf16(((c0[2] + c1[2]) + (c2[2] + c3[2])) * sc, ((c0[3] + c1[3]) + (c2[3] + c3[3])) * sc));
      fence_proxy_async();
    }
    bar_arrive(B_RED, 384);
    asm volatile("barrier.cluster.arrive.relaxed.aligned; barrier.cluster.wait.aligned;" ::: "memory");
  }
}
struct PrepArgs { const bf16 *wqkv, *wphi, *wo; unsigned char *wb, *wot; };
__device__ __forceinline__ void prep_body(const int cta, const PrepArgs& pa) {
  const int tid = threadIdx.x, lane = tid & 31, warp = tid >> 5, g = lane >> 2, q = lane & 3;
  const int pair = cta >> 1, which = cta & 1;
  uint32_t bfr[2][3][3];
#pragma unroll
  for (int hh = 0; hh < 2; hh++)
#pragma unroll
    for (int t = 0; t < 3; t++) {
      const unsigned short* ph = (const unsigned short*)pa.wphi + (2 * pair + hh) * 400 + (t < 2 ? 8 * t + g : 16 + (g >> 1)) + 2 * q * 20;
#pragma unroll
      for (int r = 0; r < 3; r++) {
        const int o = (r < 2 || q < 2) ? r * 160 : 0;
        const uint32_t v = (uint32_t)__ldg(ph + o) | ((uint32_t)__ldg(ph + o + 20) << 16);
        bfr[hh][t][r] = ((t < 2 || (g & 1) == hh) && (r < 2 || q < 2)) ? v : 0u;
      }
    }
  const int gt = cta * 256 + tid;
#pragma unroll 1
  for (int i = 0; i < 5; i++) {
    uint32_t af[2][6];
#pragma unroll
    for (int hh = 0; hh < 2; hh++) {
      const uint32_t* r0 = (const uint32_t*)(pa.wqkv + (size_t)((warp * 5 + i) * 16 + g) * 1920 + which * 640 + (2 * pair + hh) * 20) + q;
      af[hh][0] = __ldg(r0); af[hh][1] = __ldg(r0 + 7680); af[hh][2] = __ldg(r0 + 4); af[hh][3] = __ldg(r0 + 7684);
      af[hh][4] = __ldg(r0 + 8); af[hh][5] = __ldg(r0 + 7688);
    }
    const int iv = i * 4096 + (gt >> 1), k = (iv & 7) + (iv >> 8) * 8, h = (iv >> 3) & 31;
    const uint2* src = (const uint2*)(pa.wqkv + (size_t)k * 1920 + 1280 + h * 20) + (gt & 1) * 2;
    const uint2 a = __ldg(src), b = __ldg(src + 1), e = __ldg(src + 2);
    uint4 wv[2]; uint32_t wd[2];
#pragma unroll
    for (int n = 0; n < 2; n++) {
      const int iw = min((2 * i + n) * 5120 + gt, 640 * 80 - 1), r = iw & 7, c = (iw >> 3) % 80, kg = iw / 640, c5 = kg % 5;
      const int row = (kg / 5) * 40 + (c5 < 2 ? 8 * c5 + r : (c5 == 2 ? 16 + (r & 3) + (r >> 2) * 20 : 20 + 8 * (c5 - 3) + r));
      wv[n] = __ldg((const uint4*)(pa.wo + (size_t)row * cfg::DM + c * 8));
      wd[n] = (((c / 10) * 80 + kg) * 10 + c % 10) * 128 + r * 16;
    }
    uint4* dv = (uint4*)(pa.wb + ((size_t)((h >> 2) * 80 + (k >> 3)) * 32 + 20 + 3 * (h & 3)) * 128 + (k & 7) * 16);
    dv[(gt & 1) * 8] = make_uint4(a.x, a.y, b.x, b.y);
    if (gt & 1) dv[16] = (h & 1) ? make_uint4(0, 0, e.x, e.y) : make_uint4(e.x, e.y, 0, 0);
    if (gt < 5120) { *(uint4*)(pa.wot + wd[0]) = wv[0]; *(uint4*)(pa.wot + wd[1]) = wv[1]; }
    uint32_t* dst = (uint32_t*)(pa.wb + ((size_t)((pair >> 1) * 80 + (warp * 5 + i) * 2) * 32 + which * 10 + (pair & 1) * 5) * 128) + lane;
#pragma unroll
    for (int t = 0; t < 5; t++) {
      float d[4] = {0, 0, 0, 0};
#pragma unroll
      for (int hh = 0; hh < 2; hh++)
        if (t == 2 || (t > 2) == (hh == 1)) {
          const int tt = t < 3 ? t : t - 3;
          mma16816(d, af[hh][0], af[hh][1], af[hh][2], af[hh][3], bfr[hh][tt][0], bfr[hh][tt][1]);
          mma1688(d, q < 2 ? af[hh][4] : 0u, q < 2 ? af[hh][5] : 0u, bfr[hh][tt][2]);
        }
      dst[t * 32] = pack_bf16(d[0], d[1]); dst[1024 + t * 32] = pack_bf16(d[2], d[3]);
    }
  }
}

__global__ void __launch_bounds__(256, 4) ln_kernel(const bf16* __restrict__ xin, bf16* __restrict__ xn, uint2* __restrict__ xh, uint4* __restrict__ z0, int n0,
                                                    uint4* __restrict__ z1, int n1, const bf16* pfa, const bf16* pfb, int npf, int tl) {
  asm volatile("griddepcontrol.wait;" ::: "memory");
  asm volatile("griddepcontrol.launch_dependents;" ::: "memory");
  const int warp = threadIdx.x >> 5, lane = threadIdx.x & 31;
  const int row = blockIdx.x * 8 + warp;
  uint2 xw[1][5];
#pragma unroll
  for (int i = 0; i < 5; i++) xw[0][i] = *(const uint2*)(xin + (size_t)row * cfg::DM + i * 128 + lane * 4);
  for (int i = blockIdx.x * 256 + threadIdx.x; i < n0; i += 256 * 256) z0[i] = make_uint4(0, 0, 0, 0);
  for (int i = blockIdx.x * 256 + threadIdx.x; i < n1; i += 256 * 256) z1[i] = make_uint4(0, 0, 0, 0);
  if (npf && xw[0][4].y != 0x7fc17fc1u) {
    for (int i = 0; i < npf; i++) {
      const uint32_t l = (uint32_t)i * 32768u + (blockIdx.x * 256 + threadIdx.x) / 2;
      if (l < cfg::DM * cfg::HD / 64) asm volatile("prefetch.global.L2 [%0];" :: "l"(((threadIdx.x & 1) ? pfa : pfb) + (size_t)l * 64) : "memory");
    }
  }
  ln_rows<1>(xw, row, lane, xn, xh);
}
struct Pipe { uint32_t stage, phase; };
template <int NS> __device__ __forceinline__ void pipe_adv(Pipe& p) { if (++p.stage == NS) { p.stage = 0; p.phase ^= 1; } }
__device__ __forceinline__ void wait_ge(const void* p, uint32_t target, uint32_t ns = 32) {
  int spin = 0;
  while (ld_acquire_u32(p) < target) { __nanosleep(ns); if (++spin > (1 << 21)) break; }
}
__device__ __forceinline__ void bulk_g2s_hint(uint32_t dst, const void* src, uint32_t bytes, uint32_t mb, uint64_t pol) {
  asm volatile("cp.async.bulk.shared::cluster.global.mbarrier::complete_tx::bytes.L2::cache_hint [%0], [%1], %2, [%3], %4;"
               :: "r"(dst), "l"(src), "r"(bytes), "r"(mb), "l"(pol) : "memory");
}
#define STAG 1
#define EF_KV 1
#define EF_O 1
__device__ __forceinline__ void fence_proxy_async_global() { asm volatile("fence.proxy.async.global;" ::: "memory"); }

namespace tr {
constexpr int NS = 4, STQ = 16384 + 24576, STO = 16384 + 40960;
constexpr int SEGB = 15360;
constexpr int OFF_K = NS * STQ;
constexpr int OFF_BAR = NS * STO;
constexpr int SMEM = OFF_BAR + 256;
static_assert(OFF_K + 4 * SEGB <= OFF_BAR && SMEM <= 232448, "smem");
enum { T_QA = 0, T_Q, T_A, T_OB, T_OS, T_L, T_END, T_P };
constexpr uint32_t C_QA = AR_CNT, C_O = AR_CNT + 64, C_Q = AR_CNT + 128, C_P = AR_CNT + 192;
constexpr int MAXITEMS = 1200;
struct Sched {
  uint8_t ks[16];
  uint8_t wide[16];
  uint8_t lrows[16];
  uint32_t n;
  int nqa;
  uint16_t item[MAXITEMS];
};
struct Args {
  const unsigned char *kg, *vg;
  unsigned char* o;
  uint4* qs;
  unsigned char* part;
  const bf16 *xin, *xq;
  bf16 *xout, *xn;
  unsigned char* arena;
  const unsigned* go;
  int tl;
  uint32_t nap, nap2;
  int pfprep, pfq, pfb;
};
}

template <int N0, int N1>
__device__ __forceinline__ void tr_mainloop(float (&a0)[N0 / 2], float (&a1)[N1 ? N1 / 2 : 1], Pipe& p, uint32_t sb, uint32_t full, uint32_t empty, int nkb, int wg) {
  using namespace tr;
  constexpr uint32_t ST = N1 ? STO : STQ;
  uint32_t prev = 0;
#pragma unroll
  for (int i = 0; i < N0 / 2; i++) a0[i] = 0.f;
  if constexpr (N1 > 0) {
#pragma unroll
    for (int i = 0; i < N1 / 2; i++) a1[i] = 0.f;
  }
#pragma unroll 1
  for (int kb = 0; kb < nkb; kb++) {
    mbar_wait(full + 8 * p.stage, p.phase);
    const uint32_t st = ((sb & 0x3FFFF) >> 4) + p.stage * (ST / 16), sa = st + wg * 512;
    wgmma_fence();
#pragma unroll
    for (int kk = 0; kk < 4; kk++) {
      const uint64_t da = desc16<16, 1024, 1>(sa, kk * 32);
      if constexpr (N0 == 192) wgmma_n192<0, 1>(a0, da, desc16<8192, 1024, 1>(st, 16384 + kk * 2048), (kb | kk) != 0);
      else wgmma_n128<0, 1>(a0, da, desc16<8192, 1024, 1>(st, 16384 + kk * 2048), (kb | kk) != 0);
      if constexpr (N1 > 0) wgmma_n128<0, 1>(a1, da, desc16<8192, 1024, 1>(st, 16384 + 24576 + kk * 2048), (kb | kk) != 0);
    }
    wgmma_commit();
    if (kb > 0) { wgmma_wait<1>(); mbar_arrive_if((threadIdx.x & 127) == 0, empty + 8 * prev); }
    prev = p.stage;
    pipe_adv<NS>(p);
  }
  wgmma_wait<0>();
  mbar_arrive_if((threadIdx.x & 127) == 0, empty + 8 * prev);
}
template <int N> __device__ __forceinline__ void stage_tiles(const float (&o)[N / 2], uint32_t base, int wi, int lane) {
  const uint32_t ra = base + (wi * 16 + (lane & 7) + 8 * ((lane >> 3) & 1)) * 128;
#pragma unroll
  for (int v = 0; v < N / 8; v += 2)
    stsm_x4(ra + (v >> 3) * 8192 + ((((v & 7) + (lane >> 4)) ^ (lane & 7)) << 4), pack_bf16(o[4 * v], o[4 * v + 1]), pack_bf16(o[4 * v + 2], o[4 * v + 3]),
            pack_bf16(o[4 * v + 4], o[4 * v + 5]), pack_bf16(o[4 * v + 6], o[4 * v + 7]));
}
__global__ void __launch_bounds__(384, 1) trail_kernel(const __grid_constant__ CUtensorMap tmX, const __grid_constant__ CUtensorMap tmQ,
                                                       const __grid_constant__ CUtensorMap tmWo5, const __grid_constant__ CUtensorMap tmWo2,
                                                       const __grid_constant__ CUtensorMap tmP, const __grid_constant__ CUtensorMap tmP4, const __grid_constant__ tr::Sched sc,
                                                       const __grid_constant__ tr::Args a, const __grid_constant__ PrepArgs pa) {
  using namespace tr;
  [[maybe_unused]] const int tl = a.tl;
  extern __shared__ __align__(1024) unsigned char smem_raw[];
  const uint32_t sb = smem_u32(smem_raw);
  const int warp = __shfl_sync(0xffffffffu, (int)threadIdx.x >> 5, 0), lane = threadIdx.x & 31;
  unsigned char* const arena = a.arena;
  const uint32_t full = sb + OFF_BAR, empty = full + 8 * NS, barK = empty + 8 * NS, barKfree = barK + 16, staged = barKfree + 16;
  const uint32_t kvrdy = staged + 32, mfull = kvrdy + 8, mempty = mfull + 16, mbox = mempty + 16;
  uint32_t go = 0;
  if (threadIdx.x == 256) go = ld_acquire_u32(a.go);
  if (threadIdx.x == 0) {
    for (int i = 0; i < NS; i++) { mbar_init(full + 8 * i, 1); mbar_init(empty + 8 * i, 2); }
    for (int i = 0; i < 2; i++) {
      mbar_init(barK + 8 * i, 1); mbar_init(barKfree + 8 * i, 1); mbar_init(staged + 16 * i, 4); mbar_init(staged + 16 * i + 8, 4);
      mbar_init(mfull + 8 * i, 1); mbar_init(mempty + 8 * i, 11);
    }
    mbar_init(kvrdy, 1);
    asm volatile("fence.mbarrier_init.release.cluster;" ::: "memory");
  }
  __syncthreads();
  Pipe mp{0, 0};
  auto next_item = [&]() -> uint32_t {
    uint32_t it;
    mbar_wait(mfull + 8 * mp.stage, mp.phase);
    asm volatile("ld.shared.u32 %0, [%1];" : "=r"(it) : "r"(mbox + 4 * mp.stage) : "memory");
    return it;
  };
  if (warp >= 8) {
    asm volatile("setmaxnreg.dec.sync.aligned.u32 40;");
    if (warp == 8) { go = __shfl_sync(0xffffffffu, go, 0); if (elect_one()) {
      Pipe p{0, 1};
      mp.phase = 1;
      uint32_t kph = 1, rph = 0, wide = 0, qdone = 0;
      prefetch_tmap(&tmX); prefetch_tmap(&tmQ); prefetch_tmap(&tmWo5); prefetch_tmap(&tmWo2); prefetch_tmap(&tmP); prefetch_tmap(&tmP4);
      const uint64_t ef = policy_evict_first();
      auto ld_kv = [&](uint32_t d, const void* s, uint32_t n, uint32_t mb) { if (EF_KV) bulk_g2s_hint(d, s, n, mb, ef); else bulk_g2s(d, s, n, mb); };
      auto ld_o = [&](uint32_t d, const void* s, uint32_t n, uint32_t mb) { if (EF_O) bulk_g2s_hint(d, s, n, mb, ef); else bulk_g2s(d, s, n, mb); };
      auto stage = [&](uint32_t bytes) -> uint32_t {
        mbar_wait(empty + 8 * p.stage, p.phase);
        mbar_expect_tx(full + 8 * p.stage, bytes);
        return sb + p.stage * (wide ? STO : STQ);
      };
      auto fetch = [&]() -> uint32_t { uint32_t v; asm volatile("atom.relaxed.gpu.global.add.u32 %0, [%1], 1;" : "=r"(v) : "l"(arena + AR_QUEUE) : "memory"); return v; };
      if (!go) wait_ge(a.go, 1, 200);
      fence_proxy_async_global();
      uint32_t next = fetch();
      while (true) {
        const uint32_t item = next;
        const uint32_t code = sc.item[min(item, sc.n)];
        const int type = (code >> 11) & 7, m = (code >> 7) & 15, k = code & 127;
        const bool late = code >> 14;
        auto done_wait = [&]() { mbar_wait(mempty + 8 * (mp.stage ^ 1), mp.stage ? mp.phase ^ 1 : mp.phase); };
        if (type == T_A && !((qdone >> m) & 1)) { wait_ge(arena + C_Q + m * 4, 64); qdone |= 1u << m; }
        if (type == T_OB && !wide) for (uint32_t i = 0; i < NS; i++) mbar_wait(empty + 8 * i, i >= p.stage ? p.phase : p.phase ^ 1);
        wide = type == T_OB;
        mbar_wait(mempty + 8 * mp.stage, mp.phase);
        asm volatile("st.shared.u32 [%0], %1;" :: "r"(mbox + 4 * mp.stage), "r"((p.stage << 24) | (type << 16) | (m << 8) | (k & 255)) : "memory");
        mbar_arrive(mfull + 8 * mp.stage);
        pipe_adv<2>(mp);
        if (type == T_END) break;
        if (type == T_P) { done_wait(); next = fetch(); continue; }
        if (type == T_L) {
          const int nr = sc.lrows[m], np = sc.ks[m];
          prefetch_l2(a.xin + (size_t)(m * 128 + k * 8 * nr) * cfg::DM, nr * 10240);
          wait_ge(arena + C_O + m * 4, np * (sc.wide[m] ? 4 : 10), m < 13 ? a.nap : 20);
          fence_proxy_async_global();
#pragma unroll 1
          for (int r = 0; r < nr; r++) {
            const int rg = m * 16 + k * nr + r;
#pragma unroll 1
            for (int q0 = 0; q0 <= np; q0 += 4) {
              const int n = min(4, np + 1 - q0);
              const uint32_t st = stage(n * 10240), fb = full + 8 * p.stage;
              if (q0 + 4 <= np) tma_load_4d(st, &tmP4, 0, rg & 7, (rg >> 3) * 10, q0, fb);
              else {
                bulk_g2s(st + (n - 1) * 10240, a.xin + (size_t)rg * 8 * cfg::DM, 10240, fb);
#pragma unroll 1
                for (int q = q0; q < np; q++) tma_load_4d(st + (q - q0) * 10240, &tmP, 0, rg & 7, (rg >> 3) * 10, q, fb);
              }
              pipe_adv<NS>(p);
            }
          }
          if (late) done_wait();
          next = fetch(); continue;
        }
        if (type <= T_A) {
          if (type != T_A)
#pragma unroll 1
            for (int kb = 0; kb < 10; kb++) {
              const uint32_t st = stage(STQ), fb = full + 8 * p.stage;
              tma_load_2d(st, &tmX, kb * 64, m * 128, fb);
              tma_load_3d(st + 16384, &tmQ, 0, kb * 64, k * 3, fb);
              pipe_adv<NS>(p);
              if (type == T_Q && kb == 8) next = fetch();
            }
          if (type != T_Q) {
            const size_t blk = ((size_t)m * 4 * 96 + k * 3) * 5120;
            kph ^= 1;
            mbar_wait(kvrdy, rph); rph ^= 1;
            if (!late) next = fetch();
            fence_proxy_async_global();
#pragma unroll 1
            for (int w = type == T_A ? 0 : 2; w < 4; w++) {
              const uint32_t st = stage(2 * SEGB), fb = full + 8 * p.stage;
              for (int sg = 0; sg < 2; sg++) ld_kv(st + sg * SEGB, (w < 2 ? a.kg : a.vg) + blk + (size_t)(2 * (w & 1) + sg) * (96 * 5120), SEGB, fb);
              pipe_adv<NS>(p);
            }
            if (late) { done_wait(); next = fetch(); }
          }
        } else {
          const int nn = wide ? 2 : 5, nb = wide ? 5 : 2, nt = k % nn, nkb = 96 / sc.ks[m], k0 = (k / nn) * nkb;
          const Pipe p0 = p;
          for (int kb = 0; kb < nkb; kb++) {
            if (wide && kb < NS && p.stage >= 2) { mbar_wait(barKfree, kph); mbar_wait(barKfree + 8, kph); }
            const uint32_t st = stage(16384 + nb * 8192), fb = full + 8 * p.stage;
            tma_load_3d(st + 16384, wide ? &tmWo5 : &tmWo2, 0, (k0 + kb) * 64, nt * nb, fb);
            if (kb >= NS) ld_o(st, a.o + ((size_t)m * 96 + k0 + kb) * 16384, 16384, fb);
            pipe_adv<NS>(p);
            if (kb == NS - 1 || (kb == nkb - 1 && nkb < NS)) {
              wait_ge(arena + C_QA + m * 4, 64, m < 14 ? a.nap : 32);
              fence_proxy_async_global();
              Pipe q = p0;
#pragma unroll 1
              for (int i = 0; i <= kb; i++) { ld_o(sb + q.stage * (wide ? STO : STQ), a.o + ((size_t)m * 96 + k0 + i) * 16384, 16384, full + 8 * q.stage); pipe_adv<NS>(q); }
            }
          }
          if (!late) next = fetch();
          for (int w = wide ? -(int)((2 - p.stage) & 3) : 0; w < 2; w++) { mbar_wait(empty + 8 * p.stage, p.phase); mbar_arrive(full + 8 * p.stage); pipe_adv<NS>(p); }
          kph ^= wide;
          if (late) { done_wait(); next = fetch(); }
        }
      }
    } } else if (warp < 11) { if (elect_one()) {
      const int w = warp - 9;
      uint32_t sph = 0;
      [[maybe_unused]] int nlog = 0;
      while (true) {
        const uint32_t it = next_item();
        const int type = (it >> 16) & 255, m = (it >> 8) & 255, k = it & 255;
        const uint32_t slot = mp.stage;
        pipe_adv<2>(mp);
        if (type == T_END) break;
        mbar_wait(staged + 16 * w + 8 * slot, (sph >> slot) & 1); sph ^= 1u << slot;
        mbar_arrive(mempty + 8 * slot);
        if (type == T_L) continue;
        if (type == T_QA || type == T_A) {
          for (int jj = 0; jj < 3; jj++) bulk_s2g(a.o + ((size_t)m * 96 + k * 3 + jj) * 16384 + w * 8192, sb + OFF_K + w * 2 * SEGB + jj * 8192, 8192);
          bulk_commit();
          bulk_wait<0>();
          mbar_arrive(barKfree + 8 * w);
        } else if (type == T_OB || type == T_OS) {
          const bool wide = type == T_OB;
          const int nn = wide ? 2 : 5, nb = wide ? 5 : 2;
          const uint32_t own = wide ? 2 + w : ((it >> 24) + 96 / sc.ks[m] + w) % NS;
          bulk_s2g(a.part + ((size_t)((k / nn) * 32 + m * 2 + w) * 10 + (k % nn) * nb) * 8192, sb + own * (wide ? STO : STQ), nb * 8192);
          bulk_commit();
          bulk_wait<0>();
          mbar_arrive(empty + 8 * own);
          if (wide && w) { mbar_arrive(barKfree); mbar_arrive(barKfree + 8); }
        }
        red_release_inc(arena + (type == T_Q ? C_Q : (type <= T_A ? C_QA : (type == T_P ? C_P : C_O))) + m * 4);
      }
    } } else if (elect_one()) {
      const uint64_t ef = policy_evict_first();
      uint32_t kph = 1;
      while (true) {
        const uint32_t it = next_item();
        const int type = (it >> 16) & 255, m = (it >> 8) & 255, k = it & 255;
        const uint32_t slot = mp.stage;
        pipe_adv<2>(mp);
        if (type == T_END) break;
        if ((type == T_QA || type == T_A) && m == a.pfprep) { prefetch_l2(pa.wqkv + k * 38400, 76800); prefetch_l2(pa.wo + k * 12800, 25600); }
        if ((type == T_QA || type == T_A) && m == a.pfb) { prefetch_l2(pa.wb + k * 81920, 81920); prefetch_l2(pa.wot + k * 25600, 25600); }
        if ((type == T_QA || type == T_A) && m == a.pfb + 1) { prefetch_l2(a.xn + k * 20480, 40960); prefetch_l2(a.xout + k * 20480, 40960); }
        if ((type == T_QA || type == T_A) && m < 15) {
          if (m + 1 < sc.nqa) prefetch_l2(a.xq + ((m + 1) * 128 + k * 4) * cfg::DM, 5120);
          else if (a.pfq) prefetch_l2(a.qs + ((size_t)(((m + 1) & 7) * 32 + k) * 12) * 256, 49152);
        }
        if (type == T_QA || type == T_A) {
          for (int spin = 0; spin < (1 << 21); spin++) {
            uint4 f;
            asm volatile("ld.acquire.gpu.global.v4.u32 {%0,%1,%2,%3}, [%4];" : "=r"(f.x), "=r"(f.y), "=r"(f.z), "=r"(f.w) : "l"(arena + prog_off(k, 0)) : "memory");
            if (min(min(f.x, f.y), f.z) >= (uint32_t)(4 * m + 4)) break;
            __nanosleep(m < 15 ? a.nap : a.nap2);
          }
          mbar_arrive(kvrdy);
          fence_proxy_async_global();
          const unsigned char* src = a.kg + ((size_t)m * 4 * 96 + k * 3) * 5120;
#pragma unroll 1
          for (int w = 0; w < 2; w++) {
            mbar_wait(barKfree + 8 * w, kph);
            if (type == T_A) { mbar_arrive(barK + 8 * w); continue; }
            mbar_expect_tx(barK + 8 * w, 2 * SEGB);
            for (int sg = 2 * w; sg < 2 * w + 2; sg++) { if (EF_KV) bulk_g2s_hint(sb + OFF_K + sg * SEGB, src + (size_t)sg * (96 * 5120), SEGB, barK + 8 * w, ef); else bulk_g2s(sb + OFF_K + sg * SEGB, src + (size_t)sg * (96 * 5120), SEGB, barK + 8 * w); }
          }
          kph ^= 1;
        } else if (type == T_OB) {
          mbar_wait(barKfree, kph); mbar_wait(barKfree + 8, kph);
          kph ^= 1;
        }
        mbar_arrive(mempty + 8 * slot);
      }
      if (blockIdx.x == gridDim.x - 1) asm volatile("griddepcontrol.wait;" ::: "memory");
    }
    return;
  }
  asm volatile("setmaxnreg.inc.sync.aligned.u32 232;");
  const int wg = warp >> 2, wi = warp & 3;
  const int g = lane >> 2, q4 = lane & 3;
  asm volatile("griddepcontrol.launch_dependents;" ::: "memory");
  Pipe p{0, 0};
  uint32_t kph = 0;
  auto own_slot = [&]() -> uint32_t {
    const uint32_t sA = p.stage, phA = p.phase; pipe_adv<NS>(p);
    const uint32_t sB = p.stage, phB = p.phase; pipe_adv<NS>(p);
    mbar_wait_if(wi == 0, full + 8 * (wg ? sA : sB), wg ? phA : phB);
    mbar_wait(full + 8 * (wg ? sB : sA), wg ? phB : phA);
    mbar_arrive_if((threadIdx.x & 127) == 0, empty + 8 * (wg ? sA : sB));
    return wg ? sB : sA;
  };
  while (true) {
    const uint32_t it = __shfl_sync(0xffffffffu, next_item(), 0);
    const int type = (it >> 16) & 255, m = (it >> 8) & 255, k = it & 255;
    mbar_arrive_if(lane == 0, mempty + 8 * mp.stage);
    const uint32_t done = staged + 16 * wg + 8 * mp.stage;
    pipe_adv<2>(mp);
    if (type == T_END) break;
    if (type == T_P) {
      prep_body(k, pa);
      bar_sync(3 + wg, 128);
      mbar_arrive_if(lane == 0, done);
      continue;
    }
    if (type == T_L) {
      const int nr = sc.lrows[m], np = sc.ks[m];
      const uint32_t po = (lane >> 4) * 1024 + warp * 128 + ((((lane >> 1) & 7) ^ warp) << 4) + (lane & 1) * 8;
#pragma unroll 1
      for (int r = 0; r < nr; r++) {
        uint2 xw[1][5]; float s[20];
#pragma unroll
        for (int i = 0; i < 20; i++) s[i] = 0.f;
#pragma unroll 1
        for (int q0 = 0; q0 <= np; q0 += 4) {
          const uint32_t st = sb + p.stage * STQ;
          mbar_wait(full + 8 * p.stage, p.phase);
          const int n = min(4, np - q0);
#pragma unroll 1
          for (int q = 0; q < n; q += 2) {
            uint2 t[5], u[5];
            const uint32_t pa_ = st + q * 10240 + po, keep = q + 1 < n ? ~0u : 0u;
            static_for<0, 5>([&](auto I) { t[I.value] = lds64_i<I.value * 2048>(pa_); u[I.value] = lds64_i<I.value * 2048 + 10240>(pa_); });
#pragma unroll
            for (int i = 0; i < 5; i++) {
              u[i].x &= keep; u[i].y &= keep;
              s[4 * i] += bf_lo(t[i].x) + bf_lo(u[i].x); s[4 * i + 1] += bf_hi(t[i].x) + bf_hi(u[i].x); s[4 * i + 2] += bf_lo(t[i].y) + bf_lo(u[i].y); s[4 * i + 3] += bf_hi(t[i].y) + bf_hi(u[i].y);
            }
          }
          if (n < 4) {
            static_for<0, 5>([&](auto I) { xw[0][I.value] = lds64_i<I.value * 256>(st + n * 10240 + warp * 1280 + lane * 8); });
            SFENCE2(st, xw[0][0].x ^ xw[0][1].x ^ xw[0][2].x ^ xw[0][3].x ^ xw[0][4].x);
          }
          bar_sync(3 + wg, 128);
          mbar_arrive_if((threadIdx.x & 127) == 0, empty + 8 * p.stage);
          pipe_adv<NS>(p);
        }
        const int row = (m * 16 + k * nr + r) * 8 + warp;
#pragma unroll
        for (int i = 0; i < 5; i++) {
          bf16r2(s[4 * i], s[4 * i + 1]); bf16r2(s[4 * i + 2], s[4 * i + 3]);
          xw[0][i] = make_uint2(pack_bf16(bf_lo(xw[0][i].x) + s[4 * i], bf_hi(xw[0][i].x) + s[4 * i + 1]), pack_bf16(bf_lo(xw[0][i].y) + s[4 * i + 2], bf_hi(xw[0][i].y) + s[4 * i + 3]));
          *(uint2*)(a.xout + (size_t)row * cfg::DM + i * 128 + lane * 4) = xw[0][i];
        }
        ln_rows<1>(xw, row, lane, a.xn, nullptr);
      }
      __syncwarp();
      mbar_arrive_if(lane == 0, done);
      continue;
    }
    if (type >= T_OB) {
      const int nkb = 96 / sc.ks[m];
      if (type == T_OB) {
        float a0[96], a1[64];
        tr_mainloop<192, 128>(a0, a1, p, sb, full, empty, nkb, wg);
        while (p.stage != 2) { mbar_wait_if(wi == 0, full + 8 * p.stage, p.phase); mbar_arrive_if((threadIdx.x & 127) == 0, empty + 8 * p.stage); pipe_adv<NS>(p); }
        const uint32_t st = sb + own_slot() * STO;
        stage_tiles<192>(a0, st, wi, lane); stage_tiles<128>(a1, st + 24576, wi, lane);
      } else {
        float a0[64], a1[1];
        tr_mainloop<128, 0>(a0, a1, p, sb, full, empty, nkb, wg);
        stage_tiles<128>(a0, sb + own_slot() * STQ, wi, lane);
      }
      fence_proxy_async();
      __syncwarp();
      mbar_arrive_if(lane == 0, done);
      continue;
    }
    uint32_t qf[12][4];
    uint4* qp = a.qs + ((size_t)((m & 7) * 32 + k) * 12) * 256 + threadIdx.x;
    if (type != T_A) {
      float acc[96], a1[1];
      tr_mainloop<192, 0>(acc, a1, p, sb, full, empty, 10, wg);
#pragma unroll
      for (int i = 0; i < 12; i++) {
        qf[i][0] = pack_bf16(acc[8 * i], acc[8 * i + 1]); qf[i][1] = pack_bf16(acc[8 * i + 2], acc[8 * i + 3]);
        qf[i][2] = pack_bf16(acc[8 * i + 4], acc[8 * i + 5]); qf[i][3] = pack_bf16(acc[8 * i + 6], acc[8 * i + 7]);
      }
      if (type == T_Q) {
#pragma unroll
        for (int i = 0; i < 12; i++) qp[i * 256] = make_uint4(qf[i][0], qf[i][1], qf[i][2], qf[i][3]);
        __syncwarp();
        mbar_arrive_if(lane == 0, done);
        continue;
      }
    } else {
#pragma unroll
      for (int i = 0; i < 12; i++) { const uint4 v = __ldcg(qp + i * 256); qf[i][0] = v.x; qf[i][1] = v.y; qf[i][2] = v.z; qf[i][3] = v.w; }
    }
    const uint32_t ost = sb + OFF_K + wg * 2 * SEGB;
    const bool second = wi >= 2;
    uint32_t pf[5][4];
    {
      float sa[20], sb2[20];
      uint32_t kbase = ost, kslot = 0;
      if (type == T_A) { kslot = own_slot(); kbase = sb + kslot * STQ; } else mbar_wait(barK + 8 * wg, kph);
      kbase = (kbase & 0x3FFFF) >> 4;
      if (STAG && wg) bar_sync(1, 256);
      wgmma_fence();
#pragma unroll
      for (int i = 0; i < 12; i++) {
        wgmma_rs_n40<0>(sa, qf[i][0], qf[i][1], qf[i][2], qf[i][3], desc16<640, 128, 0>(kbase, i * 1280), i != 0);
        wgmma_rs_n40<0>(sb2, qf[i][0], qf[i][1], qf[i][2], qf[i][3], desc16<640, 128, 0>(kbase, SEGB + i * 1280), i != 0);
      }
      wgmma_commit();
      if (STAG && !wg) bar_arrive(1, 256);
      wgmma_wait<0>();
      mbar_arrive_if(type == T_A && (threadIdx.x & 127) == 0, empty + 8 * kslot);
      const float cs = 0.07216878364870322f * 1.4426950408889634f;
      const int r0 = 16 * (wi & 1) + g, r1 = r0 + 8;
      float m0 = -INFINITY, m1 = -INFINITY;
#pragma unroll
      for (int n = 0; n < 5; n++) {
#pragma unroll
        for (int e = 0; e < 2; e++) {
          const int key = 8 * n + 2 * q4 + e;
          float x = second ? sb2[4 * n + e] : sa[4 * n + e], y = second ? sb2[4 * n + 2 + e] : sa[4 * n + 2 + e];
          if (n < 4) { if (key > r0) x = -INFINITY; if (key > r1) y = -INFINITY; }
          sa[4 * n + e] = x; sa[4 * n + 2 + e] = y;
          m0 = fmaxf(m0, x); m1 = fmaxf(m1, y);
        }
      }
      m0 = fmaxf(fmaxf(m0, __shfl_xor_sync(0xffffffffu, m0, 1)), fmaxf(__shfl_xor_sync(0xffffffffu, m0, 2), __shfl_xor_sync(0xffffffffu, m0, 3)));
      m1 = fmaxf(fmaxf(m1, __shfl_xor_sync(0xffffffffu, m1, 1)), fmaxf(__shfl_xor_sync(0xffffffffu, m1, 2), __shfl_xor_sync(0xffffffffu, m1, 3)));
      m0 = __fmul_rn(m0, cs); m1 = __fmul_rn(m1, cs);
      float s0 = 0.f, s1 = 0.f;
#pragma unroll
      for (int n = 0; n < 5; n++) {
#pragma unroll
        for (int e = 0; e < 2; e++) {
          sa[4 * n + e] = ex2f(__fsub_rn(__fmul_rn(sa[4 * n + e], cs), m0)); sa[4 * n + 2 + e] = ex2f(__fsub_rn(__fmul_rn(sa[4 * n + 2 + e], cs), m1));
          s0 += sa[4 * n + e]; s1 += sa[4 * n + 2 + e];
        }
      }
      s0 = (s0 + __shfl_xor_sync(0xffffffffu, s0, 1)) + (__shfl_xor_sync(0xffffffffu, s0, 2) + __shfl_xor_sync(0xffffffffu, s0, 3));
      s1 = (s1 + __shfl_xor_sync(0xffffffffu, s1, 1)) + (__shfl_xor_sync(0xffffffffu, s1, 2) + __shfl_xor_sync(0xffffffffu, s1, 3));
      const float i0 = rcpf(s0), i1 = rcpf(s1);
#pragma unroll
      for (int n = 0; n < 5; n++) {
        const uint32_t x = pack_bf16(sa[4 * n] * i0, sa[4 * n + 1] * i0), y = pack_bf16(sa[4 * n + 2] * i1, sa[4 * n + 3] * i1);
        if (n < 4) {
          pf[n >> 1][2 * (n & 1)] = second ? 0u : x; pf[n >> 1][2 * (n & 1) + 1] = second ? 0u : y;
          pf[2 + (n >> 1)][2 * (n & 1)] = second ? x : 0u; pf[2 + (n >> 1)][2 * (n & 1) + 1] = second ? y : 0u;
        } else {
          pf[4][0] = second ? 0u : x; pf[4][1] = second ? 0u : y; pf[4][2] = second ? x : 0u; pf[4][3] = second ? y : 0u;
        }
      }
    }
    {
      float o[96];
#pragma unroll
      for (int i = 0; i < 5; i++) { PIN(pf[i][0]); PIN(pf[i][1]); PIN(pf[i][2]); PIN(pf[i][3]); }
      const uint32_t own = own_slot(), vbase = ((sb & 0x3FFFF) >> 4) + own * (STQ / 16);
      wgmma_fence();
#pragma unroll
      for (int i = 0; i < 5; i++)
        wgmma_rs_n192<1>(o, pf[i][0], pf[i][1], pf[i][2], pf[i][3], i < 4 ? desc16<128, 640, 0>(vbase, (i >> 1) * SEGB + (i & 1) * 256) : desc16<SEGB, 640, 0>(vbase, 512), i != 0);
      wgmma_commit();
      if (type == T_A) mbar_wait(barK + 8 * wg, kph);
      kph ^= 1;
      wgmma_wait<0>();
      mbar_arrive_if((threadIdx.x & 127) == 0, empty + 8 * own);
      stage_tiles<192>(o, ost, wi, lane);
      fence_proxy_async();
      __syncwarp();
      mbar_arrive_if(lane == 0, done);
    }
  }
}
namespace bf {
constexpr int NS = 4, STAGE = 16384 + 32768;
constexpr int PIECE = 20480;
constexpr int OFF_PHI = 0, OFF_V = 40960, OFF_KV = 65536;
constexpr int OFF_OST = 5 * PIECE;
constexpr int OFF_WOT = 6 * PIECE;
constexpr int OFF_BAR = OFF_WOT + 102400;
constexpr int SMEM = OFF_BAR + 256;
static_assert(NS * STAGE <= OFF_BAR && SMEM <= 232448, "smem");
constexpr int KVACC = 32 * 5 * 1024;
struct Args {
  const unsigned char *wb, *wot;
  unsigned char *kvacc, *o2;
  const bf16* xin;
  bf16* xout;
  unsigned* go;
  const void* prep;
  const bf16 *pf0, *pf1;
  int pfn, pfns, pfwait;
  int tl;
};
}
__device__ __forceinline__ void hedgehog_features(float (&x)[2][5], uint32_t (&w)[2][5]) {
  const float L = 1.4426950408889634f;
  float mx[2], mn[2], sp[2], sn[2], pos[2][5], neg[2][5];
#pragma unroll
  for (int r = 0; r < 2; r++) {
    mx[r] = fmaxf(fmaxf(fmaxf(x[r][0], x[r][1]), fmaxf(x[r][2], x[r][3])), x[r][4]);
    mn[r] = fminf(fminf(fminf(x[r][0], x[r][1]), fminf(x[r][2], x[r][3])), x[r][4]);
  }
#pragma unroll
  for (int o = 1; o < 4; o <<= 1)
#pragma unroll
    for (int r = 0; r < 2; r++) {
      const uint32_t t = __shfl_xor_sync(0xffffffffu, __byte_perm(__float_as_uint(mn[r]), __float_as_uint(mx[r]), 0x7632), o);
      mx[r] = fmaxf(mx[r], bf_hi(t)); mn[r] = fminf(mn[r], bf_lo(t));
    }
#pragma unroll
  for (int r = 0; r < 2; r++) {
#pragma unroll
    for (int i = 0; i < 5; i++) { pos[r][i] = ex2f((x[r][i] - mx[r]) * L); neg[r][i] = ex2f((mn[r] - x[r][i]) * L); }
    sp[r] = ((pos[r][0] + pos[r][1]) + (pos[r][2] + pos[r][3])) + pos[r][4];
    sn[r] = ((neg[r][0] + neg[r][1]) + (neg[r][2] + neg[r][3])) + neg[r][4];
  }
#pragma unroll
  for (int o = 1; o < 4; o <<= 1)
#pragma unroll
    for (int r = 0; r < 2; r++) { sp[r] += __shfl_xor_sync(0xffffffffu, sp[r], o); sn[r] += __shfl_xor_sync(0xffffffffu, sn[r], o); }
#pragma unroll
  for (int r = 0; r < 2; r++) {
    const float ip = rcpf(sp[r]), in_ = rcpf(sn[r]);
    w[r][0] = pack_bf16(pos[r][0] * ip, pos[r][1] * ip); w[r][1] = pack_bf16(pos[r][2] * ip, pos[r][3] * ip);
    w[r][2] = pack_bf16(neg[r][0] * in_, neg[r][1] * in_); w[r][3] = pack_bf16(neg[r][2] * in_, neg[r][3] * in_);
    w[r][4] = pack_bf16(pos[r][4] * ip, neg[r][4] * in_);
  }
}
__device__ __forceinline__ void bulk_g2s_mc(uint32_t dst, const void* src, uint32_t bytes, uint32_t mb) {
  asm volatile("cp.async.bulk.shared::cluster.global.mbarrier::complete_tx::bytes.multicast::cluster [%0], [%1], %2, [%3], %4;"
               :: "r"(dst), "l"(src), "r"(bytes), "r"(mb), "h"((unsigned short)3) : "memory");
}
__device__ __forceinline__ void mbar_arrive_remote_if(bool c, uint32_t b) {
  asm volatile("{\n.reg .pred p;\nsetp.ne.u32 p, %1, 0;\n@p mbarrier.arrive.shared::cluster.b64 _, [%0];\n}" :: "r"(b), "r"((uint32_t)c) : "memory");
}

__global__ void __cluster_dims__(2, 1, 1) __launch_bounds__(384, 1) blayer_kernel(const __grid_constant__ CUtensorMap tmA, const __grid_constant__ bf::Args a) {
  using namespace bf;
  [[maybe_unused]] const int tl = a.tl;
  extern __shared__ __align__(1024) unsigned char smem_raw[];
  const uint32_t sb = smem_u32(smem_raw);
  const int warp = __shfl_sync(0xffffffffu, (int)threadIdx.x >> 5, 0), lane = threadIdx.x & 31;
  const uint32_t full = sb + OFF_BAR, empty = full + 8 * NS, full2 = empty + 8 * NS, empty2 = full2 + 64, barW = empty2 + 16, drained = barW + 8, staged = drained + 8, freeb = staged + 8;
  const int rank = blockIdx.x & 1, u = (blockIdx.x >> 1) & 7, mp = blockIdx.x >> 4;
  const int m = 2 * mp + rank;
  const int m2 = 2 * mp + (u & 1), ns = (u & ~1) + rank;
  const uint32_t dpeer = mapa_u32(sb, rank ^ 1) - sb;
  unsigned* cntO = (unsigned*)(a.kvacc + KVACC);
  if (threadIdx.x == 0) {
    for (int i = 0; i < NS; i++) { mbar_init(full + 8 * i, 1); mbar_init(empty + 8 * i, 4); }
    for (int i = 0; i < 8; i++) mbar_init(full2 + 8 * i, 1);
    mbar_init(empty2, 2); mbar_init(empty2 + 8, 2);
    mbar_init(barW, 1); mbar_init(drained, 1); mbar_init(staged, 8); mbar_init(freeb, 2);
    asm volatile("fence.mbarrier_init.release.cluster;" ::: "memory");
  }
  __syncthreads();
  asm volatile("barrier.cluster.arrive.relaxed.aligned; barrier.cluster.wait.aligned;" ::: "memory");
  if (warp >= 8) {
    asm volatile("setmaxnreg.dec.sync.aligned.u32 40;");
    if (warp == 8) { if (elect_one()) {
      const unsigned char* wsrc = a.wb + (size_t)u * 327680 + rank * 16384;
      if (a.prep) wait_ge(a.prep, 64);
      fence_proxy_async_global();
      for (int kb = 0; kb < NS; kb++) {
        mbar_expect_tx(full + 8 * kb, STAGE);
        bulk_g2s_mc(sb + kb * STAGE + 16384 + rank * 16384, wsrc + kb * 32768, 16384, full + 8 * kb);
      }
      asm volatile("griddepcontrol.wait;" ::: "memory");
      if (blockIdx.x == 0) *a.go = 0;
      for (int kb = 0; kb < NS; kb++) tma_load_2d(sb + kb * STAGE, &tmA, kb * 64, m * 128, full + 8 * kb);
      if (m == 0) prefetch_l2(a.kvacc + u * (KVACC / 8), KVACC / 8);
#pragma unroll 1
      for (int kb = NS; kb < 10; kb++) {
        const uint32_t s = kb & 3, st = sb + s * STAGE, fb = full + 8 * s;
        mbar_wait(empty + 8 * s, ((kb >> 2) - 1) & 1);
        mbar_expect_tx(fb, STAGE);
        tma_load_2d(st, &tmA, kb * 64, m * 128, fb);
        bulk_g2s_mc(st + 16384 + rank * 16384, wsrc + kb * 32768, 16384, fb);
      }
      for (int i = 0; i < 6; i++) mbar_expect_tx(full2 + 8 * i, PIECE);
      mbar_wait(drained, 0);
      mbar_expect_tx(barW, 102400);
      bulk_g2s(sb + OFF_WOT, a.wot + (size_t)ns * 102400, 102400, barW);
      mbar_wait(staged, 0);
      bulk_s2g(a.o2 + (size_t)(m * 8 + u) * PIECE, sb + OFF_OST, PIECE);
      bulk_commit();
      bulk_wait<0>();
      mbar_arrive(freeb); mbar_arrive_remote_if(true, freeb + dpeer);
      red_release_inc(cntO + m);
      wait_ge(cntO + m2, 8, 20);
      mbar_wait(freeb, 0);
      fence_proxy_async_global();
      const unsigned char* osrc = a.o2 + (size_t)m2 * 8 * PIECE;
      for (int i = 0; i < 6; i++) bulk_g2s_mc(sb + i * PIECE + rank * (PIECE / 2), osrc + i * PIECE + rank * (PIECE / 2), PIECE / 2, full2 + 8 * i);
      for (int i = 0; i < 2; i++) {
        mbar_wait(empty2 + 8 * i, 0);
        mbar_expect_tx(full2 + 8 * (6 + i), PIECE);
        bulk_g2s(sb + i * PIECE, osrc + (6 + i) * PIECE, PIECE, full2 + 8 * (6 + i));
      }
    } } else if (warp == 9 && a.pf0) { if (elect_one()) {
      if (a.pfwait) asm volatile("griddepcontrol.wait;" ::: "memory");
      constexpr uint32_t CH = 2048;
      for (int i = 0; i < a.pfn; i++) {
        prefetch_l2((const unsigned char*)a.pf0 + (i * 128 + blockIdx.x) * CH, CH); prefetch_l2((const unsigned char*)a.pf1 + (i * 128 + blockIdx.x) * CH, CH);
        __nanosleep(a.pfns);
      }
    } }
    return;
  }
  asm volatile("setmaxnreg.inc.sync.aligned.u32 232;");
  const int wg = warp >> 2, wi = warp & 3;
  const int q4 = lane & 3;
  const bool lead = (threadIdx.x & 127) == 0;
  const uint32_t s16 = (sb & 0x3FFFF) >> 4;
  float acc[128];
  {
#pragma unroll 1
    for (int kb = 0; kb < 10; kb++) {
      const uint32_t s = kb & 3, st = s16 + s * (STAGE / 16);
      mbar_wait(full + 8 * s, (kb >> 2) & 1);
      wgmma_fence();
#pragma unroll
      for (int kk = 0; kk < 4; kk++) wgmma_n256<0, 1>(acc, desc16<16, 1024, 1>(st + wg * 512, kk * 32), desc16<4096, 128, 0>(st, 16384 + kk * 8192), (kb | kk) != 0);
      wgmma_commit();
      if (kb > 0 && kb < 7) { wgmma_wait<1>(); const uint32_t e = empty + 8 * ((kb - 1) & 3); mbar_arrive_if(lead, e); mbar_arrive_remote_if(lead, e + dpeer); }
    }
    wgmma_wait<0>();
    bar_sync(1, 256);
    mbar_arrive_if(threadIdx.x == 0, drained);
  }
  const uint32_t srow = (wg * 64 + wi * 16 + (lane & 15)) * 16 + (lane >> 4) * 2048;
  auto features = [&](auto T0, auto HH, uint32_t (&w)[2][5]) {
    constexpr int t = T0.value + 5 * (HH.value >> 1), o = (HH.value & 1) ? 3 : 0, e = HH.value & 1;
    float x[2][5];
#pragma unroll
    for (int r = 0; r < 2; r++) {
      x[r][0] = acc[4 * (t + o) + 2 * r]; x[r][1] = acc[4 * (t + o) + 2 * r + 1]; x[r][2] = acc[4 * (t + o + 1) + 2 * r]; x[r][3] = acc[4 * (t + o + 1) + 2 * r + 1];
      bf16r2(x[r][0], x[r][1]); bf16r2(x[r][2], x[r][3]);
    }
    x[0][4] = acc[4 * (t + 2) + e]; x[1][4] = acc[4 * (t + 2) + 2 + e];
    bf16r2(x[0][4], x[1][4]);
    hedgehog_features(x, w);
  };
  static_for<0, 4>([&](auto HH) {
    constexpr int hh = HH.value, t = 20 + 3 * hh;
    const uint32_t one = q4 == ((hh & 1) ? 0 : 2) ? 0x3f80u : 0u;
    const uint32_t va = sb + OFF_V + hh * 6144 + srow;
    stsm_x4(va, pack_bf16(acc[4 * t], acc[4 * t + 1]), pack_bf16(acc[4 * t + 2], acc[4 * t + 3]), pack_bf16(acc[4 * t + 4], acc[4 * t + 5]), pack_bf16(acc[4 * t + 6], acc[4 * t + 7]));
    const bool pad = (q4 >= 2) != (hh & 1);
    stsm_x2(va + 4096, pad ? one : pack_bf16(acc[4 * t + 8], acc[4 * t + 9]), pad ? one : pack_bf16(acc[4 * t + 10], acc[4 * t + 11]));
    uint32_t w[2][5];
    features(IC<10>{}, HH, w);
    const uint32_t pa = sb + OFF_PHI + hh * 10240 + srow;
    stsm_x4(pa, w[0][0], w[1][0], w[0][1], w[1][1]);
    stsm_x4(pa + 4096, w[0][2], w[1][2], w[0][3], w[1][3]);
    stsm_x2(pa + 8192, w[0][4], w[1][4]);
  });
  fence_proxy_async();
  bar_sync(1, 256);
  {
    float d0[12], d1[12];
    const uint32_t pa = s16 + wg * 1280, pv = s16 + wg * 768;
    wgmma_fence();
#pragma unroll
    for (int k = 0; k < 8; k++) {
      wgmma_n24<1, 1>(d0, desc16<128, 2048, 0>(pa, OFF_PHI + k * 256), desc16<128, 2048, 0>(pv, OFF_V + k * 256), k != 0);
      wgmma_n24<1, 1>(d1, desc16<128, 2048, 0>(pa, OFF_PHI + 10240 + k * 256), desc16<128, 2048, 0>(pv, OFF_V + 6144 + k * 256), k != 0);
    }
    wgmma_commit();
    wgmma_wait<0>();
    unsigned char* dst = a.kvacc + ((u * 4 + wg * 2) * 5 + 2 * wi) * 1024 + lane * 16;
    auto red4 = [&](bool on, unsigned char* p, float x, float y, float z) {
      asm volatile("{\n.reg .pred p;\nsetp.ne.u32 p, %4, 0;\n@p red.relaxed.gpu.global.add.v4.f32 [%0], {%1,%2,%3,%5};\n}" :: "l"(p), "f"(x), "f"(y), "f"(z), "r"((uint32_t)on), "f"(1.f) : "memory");
    };
    red4(wi < 3, dst, d0[0], d0[1], d0[4]); red4(wi < 3, dst + 512, d0[5], d0[8], d0[9]);
    red4(wi < 3, dst + 5120, d1[0], d1[1], d1[4]); red4(wi < 3, dst + 5632, d1[5], d1[8], d1[9]);
    red4(wi < 2, dst + 1024, d0[2], d0[3], d0[6]); red4(wi < 2, dst + 1536, d0[7], d0[10], d0[11]);
    red4(wi < 2, dst + 6144, d1[2], d1[3], d1[6]); red4(wi < 2, dst + 6656, d1[7], d1[10], d1[11]);
  }
  uint32_t qf[4][2][5];
  static_for<0, 4>([&](auto HH) { features(IC<0>{}, HH, qf[HH.value]); });
  uint4 xr[5];
#pragma unroll
  for (int i = 0; i < 5; i++) {
    const int c = lane + 32 * i;
    xr[i] = __ldcg((const uint4*)(a.xin + (size_t)(m2 * 128 + wg * 64 + wi * 16 + c / 10) * cfg::DM + ns * 80 + (c % 10) * 8));
  }
  {
    const unsigned char* src = a.kvacc + (u * 20 + warp) * 1024 + lane * 16;
    uint4 v[6];
    int spin = 0;
    while (true) {
      v[0] = ld_relaxed_v4_i<0>(src); v[1] = ld_relaxed_v4_i<512>(src); v[2] = ld_relaxed_v4_i<8192>(src); v[3] = ld_relaxed_v4_i<8704>(src);
      v[4] = ld_relaxed_v4_i<0>(src + (wg ? 0 : 16384)); v[5] = ld_relaxed_v4_i<512>(src + (wg ? 0 : 16384));
      const uint32_t c = (v[0].w & v[1].w & v[2].w) & (v[3].w & v[4].w & v[5].w);
      if (!__any_sync(0xffffffffu, (c & 0x41800000u) != 0x41800000u) || ++spin >= SPIN_LIMIT) break;
      __nanosleep(100);
    }
    const uint32_t kd = sb + OFF_KV + warp * 384 + lane * 4;
#pragma unroll
    for (int i = 0; i < 3; i++)
      if (i < 2 || wg == 0) {
        sts32(kd + i * 3072, pack_bf16(__uint_as_float(v[2 * i].x), __uint_as_float(v[2 * i].y)));
        sts32(kd + i * 3072 + 128, pack_bf16(__uint_as_float(v[2 * i].z), __uint_as_float(v[2 * i + 1].x)));
        sts32(kd + i * 3072 + 256, pack_bf16(__uint_as_float(v[2 * i + 1].y), __uint_as_float(v[2 * i + 1].z)));
      }
  }
  fence_proxy_async();
  bar_sync(1, 256);
  {
    float d[4][12];
    uint32_t zero = 0; PIN(zero);
#pragma unroll
    for (int hh = 0; hh < 4; hh++)
#pragma unroll
      for (int i = 0; i < 5; i++) { PIN(qf[hh][0][i]); PIN(qf[hh][1][i]); }
    wgmma_fence();
#pragma unroll
    for (int hh = 0; hh < 4; hh++) {
      const uint32_t kb = OFF_KV + hh * 1920;
      wgmma_rs_n24<1>(d[hh], qf[hh][0][0], qf[hh][1][0], qf[hh][0][1], qf[hh][1][1], desc16<384, 128, 0>(s16, kb), 0);
      wgmma_rs_n24<1>(d[hh], qf[hh][0][2], qf[hh][1][2], qf[hh][0][3], qf[hh][1][3], desc16<384, 128, 0>(s16, kb + 768), 1);
      wgmma_rs_n24<1>(d[hh], qf[hh][0][4], qf[hh][1][4], zero, zero, desc16<0, 128, 0>(s16, kb + 1536), 1);
    }
    wgmma_commit();
    wgmma_wait<0>();
    uint32_t ow[4][6];
#pragma unroll
    for (int hh = 0; hh < 4; hh++) {
      const int zl = (lane & ~3) | ((hh & 1) ? 0 : 2);
      const float da = bf16r(bf16r(__shfl_sync(0xffffffffu, d[hh][8], zl)) + 1e-6f), db = bf16r(bf16r(__shfl_sync(0xffffffffu, d[hh][10], zl)) + 1e-6f);
#pragma unroll
      for (int n = 0; n < 3; n++) {
        bf16r2(d[hh][4 * n], d[hh][4 * n + 1]); bf16r2(d[hh][4 * n + 2], d[hh][4 * n + 3]);
        ow[hh][2 * n] = pack_bf16(__fdividef(d[hh][4 * n], da), __fdividef(d[hh][4 * n + 1], da));
        ow[hh][2 * n + 1] = pack_bf16(__fdividef(d[hh][4 * n + 2], db), __fdividef(d[hh][4 * n + 3], db));
      }
    }
#pragma unroll
    for (int p = 0; p < 2; p++) {
      const uint32_t oa = sb + OFF_OST + p * 10240 + srow;
      stsm_x4(oa, ow[2 * p][0], ow[2 * p][1], ow[2 * p][2], ow[2 * p][3]);
      stsm_x2(oa + 4096, q4 < 2 ? ow[2 * p][4] : ow[2 * p + 1][4], q4 < 2 ? ow[2 * p][5] : ow[2 * p + 1][5]);
      stsm_x4(oa + 6144, ow[2 * p + 1][0], ow[2 * p + 1][1], ow[2 * p + 1][2], ow[2 * p + 1][3]);
    }
    fence_proxy_async();
    __syncwarp();
    mbar_arrive_if(lane == 0, staged);
  }
  float c2[40];
  mbar_wait(barW, 0);
#pragma unroll 1
  for (int i = 0; i < 8; i++) {
    mbar_wait(full2 + 8 * i, 0);
    const uint32_t st = s16 + (i < 6 ? i : i - 6) * (PIECE / 16) + wg * 64, wo = s16 + i * 800;
    wgmma_fence();
#pragma unroll
    for (int kk = 0; kk < 5; kk++) wgmma_n80<0, 1>(c2, desc16<2048, 128, 0>(st, kk * 4096), desc16<1280, 128, 0>(wo, OFF_WOT + kk * 2560), (i | kk) != 0);
    wgmma_commit();
    if (i == 1 || i == 2) { wgmma_wait<1>(); mbar_arrive_if(lead, empty2 + 8 * (i - 1)); }
  }
  wgmma_wait<0>();
  {
    bar_sync(1, 256);
    const uint32_t ost = sb + 2 * PIECE + warp * 3072;
#pragma unroll
    for (int v = 0; v < 10; v += 2)
      stsm_x4(ost + (lane & 15) * 176 + (v + (lane >> 4)) * 16, pack_bf16(c2[4 * v], c2[4 * v + 1]), pack_bf16(c2[4 * v + 2], c2[4 * v + 3]),
              pack_bf16(c2[4 * v + 4], c2[4 * v + 5]), pack_bf16(c2[4 * v + 6], c2[4 * v + 7]));
    __syncwarp();
#pragma unroll
    for (int i = 0; i < 5; i++) {
      const int c = lane + 32 * i, row = c / 10, chunk = c % 10;
      const uint4 y = lds128(ost + row * 176 + chunk * 16);
      const size_t off = (size_t)(m2 * 128 + wg * 64 + wi * 16 + row) * cfg::DM + ns * 80 + chunk * 8;
      const uint4 x = xr[i];
      *(uint4*)(a.xout + off) = make_uint4(pack_bf16(bf_lo(x.x) + bf_lo(y.x), bf_hi(x.x) + bf_hi(y.x)), pack_bf16(bf_lo(x.y) + bf_lo(y.y), bf_hi(x.y) + bf_hi(y.y)),
                                           pack_bf16(bf_lo(x.z) + bf_lo(y.z), bf_hi(x.z) + bf_hi(y.z)), pack_bf16(bf_lo(x.w) + bf_lo(y.w), bf_hi(x.w) + bf_hi(y.w)));
    }
  }
}
__device__ __align__(32768) unsigned char g_arena[AR_SIZE];
__device__ unsigned g_go[32];
__device__ __align__(1024) uint2 g_xh[2048 * 160];
__device__ __align__(1024) unsigned char g_k[64 * 96 * 5120], g_v[64 * 96 * 5120];
__device__ __align__(1024) bf16 g_o[2048 * 6144];
__device__ __align__(1024) uint4 g_qs[8 * 32 * 12 * 256];
__device__ __align__(1024) bf16 g_xn[2048 * 640], g_xn2[2048 * 640], g_xa[2048 * 640], g_xb[2048 * 640];
__device__ __align__(1024) bf16 g_part[24 * 2048 * 640];
__device__ __align__(1024) bf16 g_wb[2048 * 640], g_wot[640 * 640], g_pq[2048 * 640];
__device__ __align__(1024) float g_kvacc[bf::KVACC / 4 + 64];

typedef CUresult (*EncodeFn)(CUtensorMap*, CUtensorMapDataType, cuuint32_t, void*, const cuuint64_t*, const cuuint64_t*, const cuuint32_t*,
                             const cuuint32_t*, CUtensorMapInterleave, CUtensorMapSwizzle, CUtensorMapL2promotion, CUtensorMapFloatOOBfill);
static EncodeFn g_encode = nullptr;
static CUtensorMap make_map(const void* p, uint64_t cols, uint64_t rows, uint32_t bc, uint32_t br, bool swz = true) {
  CUtensorMap m;
  cuuint64_t dims[2] = {cols, rows}, strides[1] = {cols * 2};
  cuuint32_t box[2] = {bc, br}, es[2] = {1, 1};
  g_encode(&m, CU_TENSOR_MAP_DATA_TYPE_BFLOAT16, 2, const_cast<void*>(p), dims, strides, box, es, CU_TENSOR_MAP_INTERLEAVE_NONE,
           swz ? CU_TENSOR_MAP_SWIZZLE_128B : CU_TENSOR_MAP_SWIZZLE_NONE, CU_TENSOR_MAP_L2_PROMOTION_L2_256B, CU_TENSOR_MAP_FLOAT_OOB_FILL_NONE);
  return m;
}
static CUtensorMap make_map3(const void* p, uint64_t cols, uint64_t rows, uint32_t nb) {
  CUtensorMap m;
  cuuint64_t dims[3] = {64, rows, cols / 64}, strides[2] = {cols * 2, 128};
  cuuint32_t box[3] = {64, 64, nb}, es[3] = {1, 1, 1};
  g_encode(&m, CU_TENSOR_MAP_DATA_TYPE_BFLOAT16, 3, const_cast<void*>(p), dims, strides, box, es, CU_TENSOR_MAP_INTERLEAVE_NONE,
           CU_TENSOR_MAP_SWIZZLE_128B, CU_TENSOR_MAP_L2_PROMOTION_L2_256B, CU_TENSOR_MAP_FLOAT_OOB_FILL_NONE);
  return m;
}

struct Ptrs {
  unsigned char *arena, *k, *v; bf16 *o, *xn, *xa, *xb, *wb, *wot, *pq; float *part, *kvacc; uint2* xh; uint4* qs; bf16* xn2; unsigned* go;
};

static tr::Sched make_sched(int layer, const char* str, const int* ks, const int* lr) {
  using namespace tr;
  Sched s = {};
  int n = 0;
  s.nqa = 16;
  for (int b = 0; b < 16; b++) { s.ks[b] = (uint8_t)abs(ks[b]); s.wide[b] = ks[b] > 0; s.lrows[b] = (uint8_t)lr[b]; }
  for (const char* p = str; *p;) {
    if (*p == ' ') { p++; continue; }
    const bool late = *p < 'a';
    const char c = *p++ | 32;
    char* e;
    const int b = (int)strtol(p, &e, 10); p = e;
    int first = 0, cnt = c == 'o' ? s.ks[b] * (s.wide[b] ? 2 : 5) : (c == 'l' ? 16 / lr[b] : 32);
    if (*p == '.') { first = (int)strtol(p + 1, &e, 10); cnt = (int)strtol(e + 1, &e, 10); p = e; }
    const int type = c == 'a' ? T_QA : (c == 'q' ? T_Q : (c == 't' ? T_A : (c == 'l' ? T_L : (c == 'p' ? T_P : (s.wide[b] ? T_OB : T_OS)))));
    if (type == T_P && layer > 0) continue;
    if (type == T_A && b < s.nqa) s.nqa = b;
    for (int i = 0; i < cnt && n < MAXITEMS - 1; i++) s.item[n++] = (uint16_t)((late << 14) | (type << 11) | (b << 7) | (first + i));
  }
  s.n = n; s.item[n] = T_END << 11;
  return s;
}
static tr::Sched sched_of(int layer) {
  const char* str = layer == 0
      ? "q13 q14 q12.0.8 a0.0.8 q12.8.24 q15 a0.8.24 a1 p0.0.16 a2 p0.16.16 o0 o1 a3.0.16 o2 a3.16.16 a4.0.16 o3 a4.16.16 a5.0.24 o4 a5.24.8 a6.0.20 l0 a6.20.12 o5 "
        "a7 o6 l2 a8.0.24 o7 l1 a8.24.8 a9 o8 l3 a10 l4 O9 a11 t12 l5 l7 l6 O10 O11 O12 t13 t14 T15.0.20 O13 T15.20.12 l8 o14 L9 O15 L10 L12 l11 l15 l13 l14"
      : "q12 q14.0.8 q13 q15.0.16 q11.0.24 a0 q11.24.8 q14.8.24 o0 a1 a2 q15.16.16 o1 o2 a3 a4 o3 o4 a5 a6 o5 l1 a7 o6 l2 l0 a8.0.24 o7 a8.24.8 a9 o8 a10 "
        "O9 t11 l4 l3 O10 l5 o11 t12 l6 l7 O12 t13 t14 T15 o13 L9 o14 o15 L13 l10 L8 l12 l15 l11 l14";
  const int ks0[2][16] = {{2, 2, 2, 2, 2, 2, 2, 3, 2, 2, 3, 3, 3, -4, -8, -8}, {2, 2, 3, 2, 2, 2, 2, 2, 3, 3, 2, 4, 6, -6, -6, -12}};
  const int lr0[2][16] = {{4, 4, 4, 4, 4, 4, 4, 4, 2, 4, 1, 1, 1, 1, 1, 1}, {4, 4, 4, 4, 4, 4, 1, 2, 1, 4, 2, 1, 1, 1, 1, 1}};
  int ks[16], lr[16];
  for (int b = 0; b < 16; b++) { ks[b] = ks0[layer][b]; lr[b] = lr0[layer][b]; }
  return make_sched(layer, str, ks, lr);
}
#define TRAIL_GRID 132
#define PDL_LN 0
#define PDL_CH 1
#define PDL_B 1
#define PF_A 1
#define PF_B 1
extern "C" void kernel_launch(void* const* d_in, const int* in_sizes, int n_in, void* d_out, int out_size) {
  const bf16* x = (const bf16*)d_in[0];
  const bf16* mem0 = (const bf16*)d_in[1];
  const bf16 *Wq = (const bf16*)d_in[2], *Wk = (const bf16*)d_in[3], *Wv = (const bf16*)d_in[4], *Wo = (const bf16*)d_in[5];
  const bf16 *wqkv = (const bf16*)d_in[8], *wphi = (const bf16*)d_in[9], *wo = (const bf16*)d_in[10];
  bf16* out = (bf16*)d_out;
  static Ptrs P; static bool init = false;
  if (!init) {
    void* fn = nullptr; cudaDriverEntryPointQueryResult qr;
    cudaGetDriverEntryPoint("cuTensorMapEncodeTiled", &fn, cudaEnableDefault, &qr);
    g_encode = (EncodeFn)fn;
    void* p;
    cudaGetSymbolAddress(&p, g_arena); P.arena = (unsigned char*)p;
    cudaGetSymbolAddress(&p, g_k); P.k = (unsigned char*)p;   cudaGetSymbolAddress(&p, g_v); P.v = (unsigned char*)p;
    cudaGetSymbolAddress(&p, g_o); P.o = (bf16*)p;
    cudaGetSymbolAddress(&p, g_xn); P.xn = (bf16*)p;
    cudaGetSymbolAddress(&p, g_xa); P.xa = (bf16*)p;   cudaGetSymbolAddress(&p, g_xb); P.xb = (bf16*)p;
    cudaGetSymbolAddress(&p, g_wb); P.wb = (bf16*)p;   cudaGetSymbolAddress(&p, g_wot); P.wot = (bf16*)p;
    cudaGetSymbolAddress(&p, g_pq); P.pq = (bf16*)p;   cudaGetSymbolAddress(&p, g_part); P.part = (float*)p;
    cudaGetSymbolAddress(&p, g_kvacc); P.kvacc = (float*)p;
    cudaGetSymbolAddress(&p, g_xh); P.xh = (uint2*)p;
    cudaGetSymbolAddress(&p, g_go); P.go = (unsigned*)p;
    cudaGetSymbolAddress(&p, g_qs); P.qs = (uint4*)p;
    cudaGetSymbolAddress(&p, g_xn2); P.xn2 = (bf16*)p;
    cudaFuncSetAttribute(chain_kernel, cudaFuncAttributeMaxDynamicSharedMemorySize, ch::SMEM);
    cudaFuncSetAttribute(trail_kernel, cudaFuncAttributeMaxDynamicSharedMemorySize, tr::SMEM);
    cudaFuncSetAttribute(blayer_kernel, cudaFuncAttributeMaxDynamicSharedMemorySize, bf::SMEM);
    init = true;
  }
  const CUtensorMap tmXn = make_map(P.xn, 640, 2048, 64, 128), tmXn2 = make_map(P.xn2, 640, 2048, 64, 128);
  const CUtensorMap tmWq = make_map3(Wq, 6144, 640, 3);
  const CUtensorMap tmCq = make_map(Wq, 6144, 640, 64, 160), tmCk = make_map(Wk, 6144, 640, 64, 160), tmCv = make_map(Wv, 6144, 640, 64, 160), tmCo = make_map(Wo, 640, 6144, 224, 64, false);
  const CUtensorMap tmWo5 = make_map3(Wo, 640, 6144, 5), tmWo2 = make_map3(Wo, 640, 6144, 2);

  CUtensorMap tmP, tmP4;
  for (int i = 0; i < 2; i++) {
    cuuint64_t dims[4] = {256, 8, 320, 24}, strides[3] = {1024, 8192, 320 * 8192};
    cuuint32_t box[4] = {256, 1, 10, i ? 4u : 1u}, es[4] = {1, 1, 1, 1};
    g_encode(i ? &tmP4 : &tmP, CU_TENSOR_MAP_DATA_TYPE_UINT32, 4, P.part, dims, strides, box, es, CU_TENSOR_MAP_INTERLEAVE_NONE, CU_TENSOR_MAP_SWIZZLE_NONE,
             CU_TENSOR_MAP_L2_PROMOTION_NONE, CU_TENSOR_MAP_FLOAT_OOB_FILL_NONE);
  }
  ChainArgs ca;
  ca.xh = P.xh; ca.mem0 = mem0; ca.kg = P.k; ca.vg = P.v;
  ca.arena = P.arena; ca.go = P.go; ca.delay = POLL_DELAY; ca.margin = 150; ca.pubrel = 1;
  ca.tl = 0;
  uint4* zar = (uint4*)P.arena; const int nzar = AR_SIZE / 16;
  uint4* zkv = (uint4*)P.kvacc; const int nzkv = (bf::KVACC / 4 + 64) / 4;

  const PrepArgs pa{wqkv, wphi, wo, (unsigned char*)P.wb, (unsigned char*)P.wot};
  const bf16* xcur = x;
  cudaLaunchAttribute at[1];
  at[0].id = cudaLaunchAttributeProgrammaticStreamSerialization; at[0].val.programmaticStreamSerializationAllowed = 1;
  auto cfgof = [&](int grid, int block, int smem, bool pdl) {
    cudaLaunchConfig_t lc = {};
    lc.gridDim = dim3(grid); lc.blockDim = dim3(block); lc.dynamicSmemBytes = smem; lc.stream = cudaStreamPerThread;
    lc.attrs = at; lc.numAttrs = pdl ? 1 : 0;
    return lc;
  };
  int nlayers = 2;
  for (int layer = 0; layer < nlayers; layer++) {
    const int tl = layer * 12;
    cudaLaunchConfig_t lc = cfgof(256, 256, 0, layer > 0 && PDL_LN);
    cudaLaunchKernelEx(&lc, ln_kernel, xcur, P.xn, P.xh, zar, nzar, zkv, nzkv, Wk, Wv, layer == 0 ? PF_A : 0, tl + 0);
    ca.tl = tl + 2; ca.dry = 1;
    lc = cfgof(96, 384, ch::SMEM, PDL_CH);
    cudaLaunchKernelEx(&lc, chain_kernel, ca, tmCq, tmCk, tmCv, tmCo);
    lc = cfgof(TRAIL_GRID, 384, tr::SMEM, true);
    tr::Args ta{P.k, P.v, (unsigned char*)P.o, P.qs, (unsigned char*)P.part, xcur, P.xn, P.xa, P.xn2, P.arena, P.go, tl + 4, 30, 20, layer == 0 ? 0 : 99, 1, 13};
    cudaLaunchKernelEx(&lc, trail_kernel, tmXn, tmWq, tmWo5, tmWo2, tmP, tmP4, sched_of(layer), ta, pa);
    lc = cfgof(128, 384, bf::SMEM, PDL_B);
    bf::Args ba{(const unsigned char*)P.wb, (const unsigned char*)P.wot, (unsigned char*)P.kvacc, (unsigned char*)P.pq, P.xa, layer == 0 ? P.xb : out, P.go, layer == 0 ? P.arena + tr::C_P : nullptr,
                      layer == 0 && PF_B ? Wk : nullptr, Wv, 30, 500, 0, tl + 7};
    cudaLaunchKernelEx(&lc, blayer_kernel, tmXn2, ba);
    xcur = P.xb;
  }
}
```
